```python
import torch

def _softmax(x, axis=-1):
    return torch.softmax(x, dim=axis)
def _gelu(x):
    return torch.nn.functional.gelu(x, approximate="tanh")
def _silu(x):
    return torch.nn.functional.silu(x)
def _sigmoid(x):
    return torch.sigmoid(x)
def _layernorm(x, axis=-1, eps=1e-5):
    m = x.mean(dim=axis, keepdim=True)
    v = x.var(dim=axis, keepdim=True, unbiased=False)
    return (x - m) / torch.sqrt(v + eps)
def _scatter_add(tgt, idx, src, axis=0):
    return tgt.clone().index_add_(axis, idx, src)
def _segment_sum(src, seg, n):
    out = torch.zeros((n,) + src.shape[1:], dtype=src.dtype)
    return out.index_add_(0, seg, src)
def _pad(x, pw):
    flat = tuple(v for pair in reversed(pw) for v in pair)
    return torch.nn.functional.pad(x, flat)

kernel_name = 'gated_mix__ssm_conv_h3__compressed_kv_cla__prompt'

def setup_inputs():

    _w = (lambda a: (lambda t: t.to(torch.bfloat16) if t.is_floating_point() else t)(torch.as_tensor(a)))
    def _A_setup():
        B, S, D = 1, 2048, 1024
        ks = 4
        return {
            "q": _w((lambda *s: torch.randn(*s, dtype=torch.bfloat16) * 0.05)(B, S, D)),
            "k": _w((lambda *s: torch.randn(*s, dtype=torch.bfloat16) * 0.4)(B, S, D)),
            "v": _w((lambda *s: torch.randn(*s, dtype=torch.bfloat16) * 0.4)(B, S, D)),
            "shift_k": _w((lambda *s: torch.randn(*s, dtype=torch.bfloat16) * 0.4)(D, ks) * 0.5),
            "ssm_k": _w((lambda *s: torch.randn(*s, dtype=torch.bfloat16) * 0.8)(D, S) * (1.0 / S ** 0.5)),
            "ssm_D": _w((lambda *s: torch.randn(*s, dtype=torch.bfloat16) * 0.4)(D)),
        }
    _A_in = _A_setup()

    def _B_setup():
        B, H, Sq, Sk, D, M = 1, 32, 2048, 2048, 128, 1024
        Dc = 4 * D
        return {
            "x": _w((lambda *s: torch.randn(*s, dtype=torch.bfloat16) * 0.05)(B, Sq, M)),
            "c_kv": _w((lambda *s: torch.randn(*s, dtype=torch.bfloat16) * 0.4)(B, Sk, Dc)),
            "w_q": _w((lambda *s: torch.randn(*s, dtype=torch.bfloat16) * 6.4)(M, H, D) * (M ** -0.5)),
            "w_uk": _w((lambda *s: torch.randn(*s, dtype=torch.bfloat16) * 6.4)(Dc, H, D) * (Dc ** -0.5)),
            "w_uv": _w((lambda *s: torch.randn(*s, dtype=torch.bfloat16) * 0.4)(Dc, H, D) * (Dc ** -0.5)),
            "w_o": _w((lambda *s: torch.randn(*s, dtype=torch.bfloat16) * 0.4)(H, D, M) * ((H * D) ** -0.5)),
        }
    _B_in = _B_setup()

    return {
        "A_q": _A_in["q"],
        "A_k": _A_in["k"],
        "A_v": _A_in["v"],
        "A_shift_k": _A_in["shift_k"],
        "A_ssm_k": _A_in["ssm_k"],
        "A_ssm_D": _A_in["ssm_D"],
        "B_x": _B_in["x"],
        "B_c_kv": _B_in["c_kv"],
        "B_w_q": _B_in["w_q"],
        "B_w_uk": _B_in["w_uk"],
        "B_w_uv": _B_in["w_uv"],
        "B_w_o": _B_in["w_o"],
        "gate_w": _w((lambda *s: torch.randn(*s, dtype=torch.bfloat16) * 0.05)(1024) * 16.0),
    }

def reference(A_q, A_k, A_v, A_shift_k, A_ssm_k, A_ssm_D, B_x, B_c_kv, B_w_q, B_w_uk, B_w_uv, B_w_o, gate_w):
    def _A_ref(q, k, v, shift_k, ssm_k, ssm_D):
        B, S, D = q.shape
        ks = shift_k.shape[-1]
        k_pad = _pad(k, ((0, 0), (ks - 1, 0), (0, 0)))
        k_shift = torch.zeros_like(k)
        for t in range(ks):
            k_shift = k_shift + k_pad[:, t:t + S, :] * shift_k[:, ks - 1 - t][None, None, :]
        kv = k_shift * v
        L = 2 * S
        kv_pad = _pad(kv, ((0, 0), (0, S), (0, 0)))
        kf_pad = _pad(ssm_k, ((0, 0), (0, S)))
        kv_f = (lambda x, axes=(-2,-1): torch.fft.rfft2(x.float(), dim=axes))(kv_pad[:, None, :, :], axes=(1, 2))
        kf_f = (lambda x, axes=(-2,-1): torch.fft.rfft2(x.float(), dim=axes))(kf_pad[:, None, :], axes=(1, 2))
        kf_f = (lambda x, *d: x.permute(*d))(kf_f, 1, 2, 0)
        y_f = kv_f * kf_f[None, :, :, :]
        y = (lambda x, s, axes=(-2,-1): torch.fft.irfft2(x, s=s, dim=axes).to(torch.bfloat16))(y_f, (1, L), axes=(1, 2))[:, 0, :S, :]
        y = y + kv * ssm_D[None, None, :]
        return q * y

    def _B_ref(x, c_kv, w_q, w_uk, w_uv, w_o):
        B, Sq, M = x.shape[0], x.shape[1], x.shape[2]
        Sk = c_kv.shape[1]
        H, D = w_q.shape[1], w_q.shape[2]
        q = torch.einsum("bqm,mhd->bhqd", x, w_q)
        k = torch.einsum("bkc,chd->bhkd", c_kv, w_uk)
        v = torch.einsum("bkc,chd->bhkd", c_kv, w_uv)
        scores = torch.einsum("bhqd,bhkd->bhqk", q, k) * (D ** -0.5)
        off = Sk - Sq
        qi = torch.arange(Sq)[:, None]
        kj = torch.arange(Sk)[None, :]
        cmask = kj <= (qi + off)
        scores = torch.where(cmask[None, None], scores, -1e9)
        p = _softmax(scores, axis=-1)
        ctx = torch.einsum("bhqk,bhkd->bhqd", p, v)
        return torch.einsum("bhqd,hdm->bqm", ctx, w_o)

    x = A_q
    g = _sigmoid((x * gate_w).sum(-1, keepdims=True))
    a = _A_ref(x, A_k, A_v, A_shift_k, A_ssm_k, A_ssm_D)
    b = _B_ref(x, B_c_kv, B_w_q, B_w_uk, B_w_uv, B_w_o)
    return g * a + (1 - g) * b
```

```cpp
#include <cuda_runtime.h>
#include <cuda.h>
#include <cuda_bf16.h>
#include <stdint.h>

template<int TB> __device__ __forceinline__ void wgmma_ss_n256(float (&d)[128], uint64_t da, uint64_t db, int scale_d) {
  asm volatile("{\n.reg .pred p;\nsetp.ne.b32 p, %130, 0;\n"
    "wgmma.mma_async.sync.aligned.m64n256k16.f32.bf16.bf16 {%0, %1, %2, %3, %4, %5, %6, %7, %8, %9, %10, %11, %12, %13, %14, %15, %16, %17, %18, %19, %20, %21, %22, %23, %24, %25, %26, %27, %28, %29, %30, %31, %32, %33, %34, %35, %36, %37, %38, %39, %40, %41, %42, %43, %44, %45, %46, %47, %48, %49, %50, %51, %52, %53, %54, %55, %56, %57, %58, %59, %60, %61, %62, %63, %64, %65, %66, %67, %68, %69, %70, %71, %72, %73, %74, %75, %76, %77, %78, %79, %80, %81, %82, %83, %84, %85, %86, %87, %88, %89, %90, %91, %92, %93, %94, %95, %96, %97, %98, %99, %100, %101, %102, %103, %104, %105, %106, %107, %108, %109, %110, %111, %112, %113, %114, %115, %116, %117, %118, %119, %120, %121, %122, %123, %124, %125, %126, %127}, %128, %129, p, 1, 1, 0, %131;\n}\n"
    : "+f"(d[0]), "+f"(d[1]), "+f"(d[2]), "+f"(d[3]), "+f"(d[4]), "+f"(d[5]), "+f"(d[6]), "+f"(d[7]), "+f"(d[8]), "+f"(d[9]), "+f"(d[10]), "+f"(d[11]), "+f"(d[12]), "+f"(d[13]), "+f"(d[14]), "+f"(d[15]), "+f"(d[16]), "+f"(d[17]), "+f"(d[18]), "+f"(d[19]), "+f"(d[20]), "+f"(d[21]), "+f"(d[22]), "+f"(d[23]), "+f"(d[24]), "+f"(d[25]), "+f"(d[26]), "+f"(d[27]), "+f"(d[28]), "+f"(d[29]), "+f"(d[30]), "+f"(d[31]), "+f"(d[32]), "+f"(d[33]), "+f"(d[34]), "+f"(d[35]), "+f"(d[36]), "+f"(d[37]), "+f"(d[38]), "+f"(d[39]), "+f"(d[40]), "+f"(d[41]), "+f"(d[42]), "+f"(d[43]), "+f"(d[44]), "+f"(d[45]), "+f"(d[46]), "+f"(d[47]), "+f"(d[48]), "+f"(d[49]), "+f"(d[50]), "+f"(d[51]), "+f"(d[52]), "+f"(d[53]), "+f"(d[54]), "+f"(d[55]), "+f"(d[56]), "+f"(d[57]), "+f"(d[58]), "+f"(d[59]), "+f"(d[60]), "+f"(d[61]), "+f"(d[62]), "+f"(d[63]), "+f"(d[64]), "+f"(d[65]), "+f"(d[66]), "+f"(d[67]), "+f"(d[68]), "+f"(d[69]), "+f"(d[70]), "+f"(d[71]), "+f"(d[72]), "+f"(d[73]), "+f"(d[74]), "+f"(d[75]), "+f"(d[76]), "+f"(d[77]), "+f"(d[78]), "+f"(d[79]), "+f"(d[80]), "+f"(d[81]), "+f"(d[82]), "+f"(d[83]), "+f"(d[84]), "+f"(d[85]), "+f"(d[86]), "+f"(d[87]), "+f"(d[88]), "+f"(d[89]), "+f"(d[90]), "+f"(d[91]), "+f"(d[92]), "+f"(d[93]), "+f"(d[94]), "+f"(d[95]), "+f"(d[96]), "+f"(d[97]), "+f"(d[98]), "+f"(d[99]), "+f"(d[100]), "+f"(d[101]), "+f"(d[102]), "+f"(d[103]), "+f"(d[104]), "+f"(d[105]), "+f"(d[106]), "+f"(d[107]), "+f"(d[108]), "+f"(d[109]), "+f"(d[110]), "+f"(d[111]), "+f"(d[112]), "+f"(d[113]), "+f"(d[114]), "+f"(d[115]), "+f"(d[116]), "+f"(d[117]), "+f"(d[118]), "+f"(d[119]), "+f"(d[120]), "+f"(d[121]), "+f"(d[122]), "+f"(d[123]), "+f"(d[124]), "+f"(d[125]), "+f"(d[126]), "+f"(d[127])
    : "l"(da), "l"(db), "r"(scale_d), "n"(TB));
}
template<int TB> __device__ __forceinline__ void wgmma_ss_n128(float (&d)[64], uint64_t da, uint64_t db, int scale_d) {
  asm volatile("{\n.reg .pred p;\nsetp.ne.b32 p, %66, 0;\n"
    "wgmma.mma_async.sync.aligned.m64n128k16.f32.bf16.bf16 {%0, %1, %2, %3, %4, %5, %6, %7, %8, %9, %10, %11, %12, %13, %14, %15, %16, %17, %18, %19, %20, %21, %22, %23, %24, %25, %26, %27, %28, %29, %30, %31, %32, %33, %34, %35, %36, %37, %38, %39, %40, %41, %42, %43, %44, %45, %46, %47, %48, %49, %50, %51, %52, %53, %54, %55, %56, %57, %58, %59, %60, %61, %62, %63}, %64, %65, p, 1, 1, 0, %67;\n}\n"
    : "+f"(d[0]), "+f"(d[1]), "+f"(d[2]), "+f"(d[3]), "+f"(d[4]), "+f"(d[5]), "+f"(d[6]), "+f"(d[7]), "+f"(d[8]), "+f"(d[9]), "+f"(d[10]), "+f"(d[11]), "+f"(d[12]), "+f"(d[13]), "+f"(d[14]), "+f"(d[15]), "+f"(d[16]), "+f"(d[17]), "+f"(d[18]), "+f"(d[19]), "+f"(d[20]), "+f"(d[21]), "+f"(d[22]), "+f"(d[23]), "+f"(d[24]), "+f"(d[25]), "+f"(d[26]), "+f"(d[27]), "+f"(d[28]), "+f"(d[29]), "+f"(d[30]), "+f"(d[31]), "+f"(d[32]), "+f"(d[33]), "+f"(d[34]), "+f"(d[35]), "+f"(d[36]), "+f"(d[37]), "+f"(d[38]), "+f"(d[39]), "+f"(d[40]), "+f"(d[41]), "+f"(d[42]), "+f"(d[43]), "+f"(d[44]), "+f"(d[45]), "+f"(d[46]), "+f"(d[47]), "+f"(d[48]), "+f"(d[49]), "+f"(d[50]), "+f"(d[51]), "+f"(d[52]), "+f"(d[53]), "+f"(d[54]), "+f"(d[55]), "+f"(d[56]), "+f"(d[57]), "+f"(d[58]), "+f"(d[59]), "+f"(d[60]), "+f"(d[61]), "+f"(d[62]), "+f"(d[63])
    : "l"(da), "l"(db), "r"(scale_d), "n"(TB));
}
template<int TB> __device__ __forceinline__ void wgmma_rs_n128(float (&d)[64], uint32_t a0, uint32_t a1, uint32_t a2, uint32_t a3, uint64_t db, int scale_d) {
  asm volatile("{\n.reg .pred p;\nsetp.ne.b32 p, %69, 0;\n"
    "wgmma.mma_async.sync.aligned.m64n128k16.f32.bf16.bf16 {%0, %1, %2, %3, %4, %5, %6, %7, %8, %9, %10, %11, %12, %13, %14, %15, %16, %17, %18, %19, %20, %21, %22, %23, %24, %25, %26, %27, %28, %29, %30, %31, %32, %33, %34, %35, %36, %37, %38, %39, %40, %41, %42, %43, %44, %45, %46, %47, %48, %49, %50, %51, %52, %53, %54, %55, %56, %57, %58, %59, %60, %61, %62, %63}, {%64, %65, %66, %67}, %68, p, 1, 1, %70;\n}\n"
    : "+f"(d[0]), "+f"(d[1]), "+f"(d[2]), "+f"(d[3]), "+f"(d[4]), "+f"(d[5]), "+f"(d[6]), "+f"(d[7]), "+f"(d[8]), "+f"(d[9]), "+f"(d[10]), "+f"(d[11]), "+f"(d[12]), "+f"(d[13]), "+f"(d[14]), "+f"(d[15]), "+f"(d[16]), "+f"(d[17]), "+f"(d[18]), "+f"(d[19]), "+f"(d[20]), "+f"(d[21]), "+f"(d[22]), "+f"(d[23]), "+f"(d[24]), "+f"(d[25]), "+f"(d[26]), "+f"(d[27]), "+f"(d[28]), "+f"(d[29]), "+f"(d[30]), "+f"(d[31]), "+f"(d[32]), "+f"(d[33]), "+f"(d[34]), "+f"(d[35]), "+f"(d[36]), "+f"(d[37]), "+f"(d[38]), "+f"(d[39]), "+f"(d[40]), "+f"(d[41]), "+f"(d[42]), "+f"(d[43]), "+f"(d[44]), "+f"(d[45]), "+f"(d[46]), "+f"(d[47]), "+f"(d[48]), "+f"(d[49]), "+f"(d[50]), "+f"(d[51]), "+f"(d[52]), "+f"(d[53]), "+f"(d[54]), "+f"(d[55]), "+f"(d[56]), "+f"(d[57]), "+f"(d[58]), "+f"(d[59]), "+f"(d[60]), "+f"(d[61]), "+f"(d[62]), "+f"(d[63])
    : "r"(a0), "r"(a1), "r"(a2), "r"(a3), "l"(db), "r"(scale_d), "n"(TB));
}
template<int TB> __device__ __forceinline__ void wgmma_rs_n64(float (&d)[32], uint32_t a0, uint32_t a1, uint32_t a2, uint32_t a3, uint64_t db, int scale_d) {
  asm volatile("{\n.reg .pred p;\nsetp.ne.b32 p, %37, 0;\n"
    "wgmma.mma_async.sync.aligned.m64n64k16.f32.bf16.bf16 {%0, %1, %2, %3, %4, %5, %6, %7, %8, %9, %10, %11, %12, %13, %14, %15, %16, %17, %18, %19, %20, %21, %22, %23, %24, %25, %26, %27, %28, %29, %30, %31}, {%32, %33, %34, %35}, %36, p, 1, 1, %38;\n}\n"
    : "+f"(d[0]), "+f"(d[1]), "+f"(d[2]), "+f"(d[3]), "+f"(d[4]), "+f"(d[5]), "+f"(d[6]), "+f"(d[7]), "+f"(d[8]), "+f"(d[9]), "+f"(d[10]), "+f"(d[11]), "+f"(d[12]), "+f"(d[13]), "+f"(d[14]), "+f"(d[15]), "+f"(d[16]), "+f"(d[17]), "+f"(d[18]), "+f"(d[19]), "+f"(d[20]), "+f"(d[21]), "+f"(d[22]), "+f"(d[23]), "+f"(d[24]), "+f"(d[25]), "+f"(d[26]), "+f"(d[27]), "+f"(d[28]), "+f"(d[29]), "+f"(d[30]), "+f"(d[31])
    : "r"(a0), "r"(a1), "r"(a2), "r"(a3), "l"(db), "r"(scale_d), "n"(TB));
}

constexpr int NCTA = 132, NREG = 128;
constexpr int UNIT = 16384, NUNIT = 14;
constexpr int SM_BAR = NUNIT * UNIT;
constexpr int SMEM_BYTES = SM_BAR + 1024;
constexpr int UPITCH = 4160, UCH = 2 * UPITCH;
constexpr float QSCALE = 0.08838834764831845f * 1.4426950408889634f;
constexpr float BOUND2 = 48.f * 48.f / 1.15f;
#define CONV_REG 4
constexpr int CONV_EXTRA = (1024 - NREG * CONV_REG) / (NCTA - NREG);
constexpr int CH_EXTRA_TOTAL = CONV_EXTRA * (NCTA - NREG);
constexpr int C_KV = 0;
constexpr int C_CTX = 32;
constexpr int C_U = 48;
constexpr int C_Z = 80;
constexpr int C_GATE = 88;
constexpr int C_EXIT = 89;
constexpr int C_NUM = 96;
constexpr int CSTRIDE = 32;
enum { PH_PRE = 1, PH_KV = 2, PH_ATT = 4, PH_CONV = 8, PH_OUT = 16, PH_ALL = 31 };

__device__ __align__(1024) uint8_t g_K[32 * 16 * 32768];
__device__ __align__(1024) uint8_t g_V[32 * 16 * 32768];
__device__ __align__(1024) uint8_t g_ctx[16 * 64 * 16384];
__device__ __align__(1024) uint8_t g_u[1024 * UCH];
__device__ __align__(1024) __nv_bfloat16 g_z[1024 * 2048];
__device__ __align__(1024) float g_gate[2048];
__device__ __align__(1024) float g_kn2[32 * 128];
__device__ __align__(1024) unsigned g_cnt[C_NUM * CSTRIDE];

struct __align__(64) Maps { CUtensorMap x, c, wq, wk, wv, wo, h, z, out; };
struct Params {
  const __nv_bfloat16 *x, *k, *v, *shift, *D, *gw;
  int mask;
};

__device__ __forceinline__ void wg_fence() { asm volatile("wgmma.fence.sync.aligned;" ::: "memory"); }
__device__ __forceinline__ void wg_commit() { asm volatile("wgmma.commit_group.sync.aligned;" ::: "memory"); }
template<int N> __device__ __forceinline__ void wg_wait() { asm volatile("wgmma.wait_group.sync.aligned %0;" :: "n"(N) : "memory"); }
__device__ __forceinline__ uint64_t mkdesc(uint32_t addr, uint32_t lbo, uint32_t sbo, uint32_t swz) {
  return (uint64_t)((addr & 0x3FFFF) >> 4) | ((uint64_t)(lbo >> 4) << 16) | ((uint64_t)(sbo >> 4) << 32) | ((uint64_t)swz << 62);
}
__device__ __forceinline__ void mbar_init(uint32_t bar, int cnt) { asm volatile("mbarrier.init.shared::cta.b64 [%0], %1;" :: "r"(bar), "r"(cnt)); }
__device__ __forceinline__ void mbar_expect(uint32_t bar, uint32_t bytes) { asm volatile("mbarrier.arrive.expect_tx.shared::cta.b64 _, [%0], %1;" :: "r"(bar), "r"(bytes) : "memory"); }
__device__ __forceinline__ void mbar_arrive(uint32_t bar) { asm volatile("mbarrier.arrive.shared::cta.b64 _, [%0];" :: "r"(bar) : "memory"); }
__device__ __forceinline__ void mbar_arrive_n(uint32_t bar, int n) { asm volatile("mbarrier.arrive.shared::cta.b64 _, [%0], %1;" :: "r"(bar), "r"(n) : "memory"); }
__device__ __forceinline__ void mbar_wait(uint32_t bar, uint32_t parity) {
  asm volatile("{\n.reg .pred p;\n.reg .u32 n;\nmov.u32 n, 0;\n"
    "LW:\nmbarrier.try_wait.parity.shared::cta.b64 p, [%0], %1;\n@p bra LD;\n"
    "add.u32 n, n, 1;\nsetp.lt.u32 p, n, 2097152;\n@p bra LW;\ntrap;\nLD:\n}\n" :: "r"(bar), "r"(parity) : "memory");
}
__device__ __forceinline__ void cnt_wait(const unsigned* p, unsigned target) {
  asm volatile("{\n.reg .pred p;\n.reg .u32 n, v;\nmov.u32 n, 0;\n"
    "LW:\nld.acquire.gpu.global.u32 v, [%0];\nsetp.ge.u32 p, v, %1;\n@p bra LD;\n"
    "add.u32 n, n, 1;\nsetp.lt.u32 p, n, 4194304;\n@p bra LW;\ntrap;\nLD:\nfence.proxy.async;\n}\n" :: "l"(p), "r"(target) : "memory");
}
__device__ __forceinline__ void cnt_signal(unsigned* p, int lane) {
  __syncwarp();
  if (lane == 0) asm volatile("red.release.gpu.global.add.u32 [%0], 1;" :: "l"(p) : "memory");
}
__device__ __forceinline__ void bulk_g2s(uint32_t dst, const void* src, uint32_t bytes, uint32_t bar) {
  asm volatile("cp.async.bulk.shared::cluster.global.mbarrier::complete_tx::bytes [%0], [%1], %2, [%3];" :: "r"(dst), "l"(src), "r"(bytes), "r"(bar) : "memory");
}
__device__ __forceinline__ void tma2d(uint32_t dst, const CUtensorMap* m, int x, int y, uint32_t bar) {
  asm volatile("cp.async.bulk.tensor.2d.shared::cluster.global.mbarrier::complete_tx::bytes [%0], [%1, {%3, %4}], [%2];" :: "r"(dst), "l"(m), "r"(bar), "r"(x), "r"(y) : "memory");
}
__device__ __forceinline__ void tma3d(uint32_t dst, const CUtensorMap* m, int x, int y, int z, uint32_t bar) {
  asm volatile("cp.async.bulk.tensor.3d.shared::cluster.global.mbarrier::complete_tx::bytes [%0], [%1, {%3, %4, %5}], [%2];" :: "r"(dst), "l"(m), "r"(bar), "r"(x), "r"(y), "r"(z) : "memory");
}
__device__ __forceinline__ void tma2d_store(const CUtensorMap* m, uint32_t src, int x, int y) {
  asm volatile("cp.async.bulk.tensor.2d.global.shared::cta.bulk_group [%0, {%2, %3}], [%1];" :: "l"(m), "r"(src), "r"(x), "r"(y) : "memory");
}
__device__ __forceinline__ void bar_sync(int id, int n) { asm volatile("bar.sync %0, %1;" :: "r"(id), "r"(n) : "memory"); }
__device__ __forceinline__ void bar_arrive(int id, int n) { asm volatile("bar.arrive %0, %1;" :: "r"(id), "r"(n) : "memory"); }
__device__ __forceinline__ int bar_and(int id, int n, int pred) {
  int r; asm volatile("{\n.reg .pred p, q;\nsetp.ne.b32 p, %3, 0;\nbar.red.and.pred q, %1, %2, p;\nselp.b32 %0, 1, 0, q;\n}\n" : "=r"(r) : "r"(id), "r"(n), "r"(pred) : "memory");
  return r;
}
__device__ __forceinline__ void fence_async_smem() { asm volatile("fence.proxy.async.shared::cta;" ::: "memory"); }
__device__ __forceinline__ float ex2(float x) { float y; asm("ex2.approx.ftz.f32 %0, %1;" : "=f"(y) : "f"(x)); return y; }
__device__ __forceinline__ uint32_t pack_bf16(float lo, float hi) { uint32_t r; asm("cvt.rn.bf16x2.f32 %0, %1, %2;" : "=r"(r) : "f"(hi), "f"(lo)); return r; }
__device__ __forceinline__ uint32_t hmul2(uint32_t a, uint32_t b) { uint32_t r; asm("mul.rn.bf16x2 %0, %1, %2;" : "=r"(r) : "r"(a), "r"(b)); return r; }
__device__ __forceinline__ uint32_t hadd2(uint32_t a, uint32_t b) { uint32_t r; asm("add.rn.bf16x2 %0, %1, %2;" : "=r"(r) : "r"(a), "r"(b)); return r; }
__device__ __forceinline__ uint32_t hfma2(uint32_t a, uint32_t b, uint32_t c) { uint32_t r; asm("fma.rn.bf16x2 %0, %1, %2, %3;" : "=r"(r) : "r"(a), "r"(b), "r"(c)); return r; }
__device__ __forceinline__ float bf_lo(uint32_t a) { return __uint_as_float(a << 16); }
__device__ __forceinline__ float bf_hi(uint32_t a) { return __uint_as_float(a & 0xffff0000u); }
__device__ __forceinline__ uint32_t lds32(uint32_t a) { uint32_t v; asm volatile("ld.shared.u32 %0, [%1];" : "=r"(v) : "r"(a) : "memory"); return v; }
__device__ __forceinline__ float2 lds64f(uint32_t a) { float2 v; asm volatile("ld.shared.v2.f32 {%0,%1}, [%2];" : "=f"(v.x), "=f"(v.y) : "r"(a) : "memory"); return v; }
__device__ __forceinline__ uint4 lds128(uint32_t a) { uint4 v; asm volatile("ld.shared.v4.u32 {%0,%1,%2,%3}, [%4];" : "=r"(v.x), "=r"(v.y), "=r"(v.z), "=r"(v.w) : "r"(a) : "memory"); return v; }
__device__ __forceinline__ void sts64f(uint32_t a, float x, float y) { asm volatile("st.shared.v2.f32 [%0], {%1,%2};" :: "r"(a), "f"(x), "f"(y) : "memory"); }
__device__ __forceinline__ void sts128(uint32_t a, uint4 v) { asm volatile("st.shared.v4.u32 [%0], {%1,%2,%3,%4};" :: "r"(a), "r"(v.x), "r"(v.y), "r"(v.z), "r"(v.w) : "memory"); }
__device__ __forceinline__ void ldsm4(uint32_t a, uint32_t& r0, uint32_t& r1, uint32_t& r2, uint32_t& r3) {
  asm volatile("ldmatrix.sync.aligned.m8n8.x4.shared.b16 {%0,%1,%2,%3}, [%4];" : "=r"(r0), "=r"(r1), "=r"(r2), "=r"(r3) : "r"(a) : "memory");
}
__device__ __forceinline__ void ldsm4t(uint32_t a, uint32_t& r0, uint32_t& r1, uint32_t& r2, uint32_t& r3) {
  asm volatile("ldmatrix.sync.aligned.m8n8.x4.trans.shared.b16 {%0,%1,%2,%3}, [%4];" : "=r"(r0), "=r"(r1), "=r"(r2), "=r"(r3) : "r"(a) : "memory");
}
__device__ __forceinline__ void stsm4(uint32_t a, uint32_t r0, uint32_t r1, uint32_t r2, uint32_t r3) {
  asm volatile("stmatrix.sync.aligned.m8n8.x4.shared.b16 [%0], {%1,%2,%3,%4};" :: "r"(a), "r"(r0), "r"(r1), "r"(r2), "r"(r3) : "memory");
}
template<int N> __device__ __forceinline__ void fence_regs(float (&d)[N]) {
#pragma unroll
  for (int i = 0; i < N; i++) asm volatile("" : "+f"(d[i]) :: "memory");
}
template<int N> __device__ __forceinline__ void fence_regs(uint32_t (&d)[N]) {
#pragma unroll
  for (int i = 0; i < N; i++) asm volatile("" : "+r"(d[i]) :: "memory");
}
__device__ __forceinline__ void sched_fence(float x, uint32_t dummy) {
  asm volatile("{\n.reg .pred p;\nsetp.eq.u32 p, %0, 0x7fc12345;\n@p st.shared.u32 [%1], %0;\n}\n" :: "r"(__float_as_uint(x)), "r"(dummy) : "memory");
}
#define TS(role, i)

struct Prod {
  uint32_t base, mask;
  __device__ __forceinline__ uint32_t full(int u) const { return base + SM_BAR + 8 * u; }
  __device__ __forceinline__ uint32_t addr(int u) const { return base + u * UNIT; }
  __device__ __forceinline__ void acquire(int u, int n) {
    for (int i = 0; i < n; i++) mbar_wait(base + SM_BAR + 128 + 8 * (u + i), (mask >> (u + i)) & 1);
    mask ^= ((1u << n) - 1) << u;
  }
};
struct Cons {
  uint32_t base, mask; int lane, warp, wg;
  __device__ __forceinline__ uint32_t addr(int u) const { return base + u * UNIT; }
  __device__ __forceinline__ void wait(int u) { mbar_wait(base + SM_BAR + 8 * u, (mask >> u) & 1); mask ^= 1u << u; }
  __device__ __forceinline__ void skip(int u) { mask ^= 1u << u; }
  __device__ __forceinline__ void release(int u, int n) { if (lane < n) mbar_arrive(base + SM_BAR + 128 + 8 * (u + lane)); }
  __device__ __forceinline__ void release2(int u, int n) { if (lane < n) mbar_arrive_n(base + SM_BAR + 128 + 8 * (u + lane), 2); }
  __device__ __forceinline__ void turn() { bar_sync(1 + wg, 256); }
  __device__ __forceinline__ void pass() { bar_arrive(2 - wg, 256); }
};
__device__ __forceinline__ int att_slot(int i) { return i == 0 ? 12 : 2 + 2 * i; }
__device__ __forceinline__ int conv_channel(int cta, int i) {
  return cta < NREG ? CH_EXTRA_TOTAL + cta * CONV_REG + i : (i >> 1) * 8 + (cta - NREG) * 2 + (i & 1);
}

template<int OFF, int N> __device__ __forceinline__ void pack_chunk(const float (&a)[N], float sc0, float sc1, uint4& v0, uint4& v1) {
  v0.x = pack_bf16(a[OFF + 0] * sc0, a[OFF + 1] * sc0); v0.y = pack_bf16(a[OFF + 4] * sc0, a[OFF + 5] * sc0);
  v0.z = pack_bf16(a[OFF + 8] * sc0, a[OFF + 9] * sc0); v0.w = pack_bf16(a[OFF + 12] * sc0, a[OFF + 13] * sc0);
  v1.x = pack_bf16(a[OFF + 2] * sc1, a[OFF + 3] * sc1); v1.y = pack_bf16(a[OFF + 6] * sc1, a[OFF + 7] * sc1);
  v1.z = pack_bf16(a[OFF + 10] * sc1, a[OFF + 11] * sc1); v1.w = pack_bf16(a[OFF + 14] * sc1, a[OFF + 15] * sc1);
}
template<int OFF, int N> __device__ __forceinline__ void pack_chunk(const float (&a)[N], uint4& v0, uint4& v1) {
  v0.x = pack_bf16(a[OFF + 0], a[OFF + 1]); v0.y = pack_bf16(a[OFF + 4], a[OFF + 5]);
  v0.z = pack_bf16(a[OFF + 8], a[OFF + 9]); v0.w = pack_bf16(a[OFF + 12], a[OFF + 13]);
  v1.x = pack_bf16(a[OFF + 2], a[OFF + 3]); v1.y = pack_bf16(a[OFF + 6], a[OFF + 7]);
  v1.z = pack_bf16(a[OFF + 10], a[OFF + 11]); v1.w = pack_bf16(a[OFF + 14], a[OFF + 15]);
}
__device__ __forceinline__ void sq_acc(const uint4& v, uint32_t& a, uint32_t& b) {
  a = hfma2(v.x, v.x, a); b = hfma2(v.y, v.y, b); a = hfma2(v.z, v.z, a); b = hfma2(v.w, v.w, b);
}
__device__ __forceinline__ float norm2_max(uint32_t a0, uint32_t b0, uint32_t a1, uint32_t b1) {
  float n0 = (bf_lo(a0) + bf_hi(a0)) + (bf_lo(b0) + bf_hi(b0)), n1 = (bf_lo(a1) + bf_hi(a1)) + (bf_lo(b1) + bf_hi(b1));
  n0 += __shfl_xor_sync(~0u, n0, 1); n1 += __shfl_xor_sync(~0u, n1, 1);
  n0 += __shfl_xor_sync(~0u, n0, 2); n1 += __shfl_xor_sync(~0u, n1, 2);
  uint32_t m = max(__float_as_uint(n0) & 0x7fffffffu, __float_as_uint(n1) & 0x7fffffffu);
  return __uint_as_float(__reduce_max_sync(~0u, m));
}

__device__ __forceinline__ void cons_kv(Cons& c, int h, int g, unsigned* pend) {
  const uint32_t toff = (c.wg * 8 + c.warp * 2) * 2048 + (c.lane & 3) * 128 + (c.lane >> 2) * 16;
  for (int tile = 0; tile < 2; tile++) {
    float acc[128];
#define KV_STEP(FIRST) { \
      const int u = 3 * (ks & 3); \
      c.wait(u); \
      const uint64_t da = mkdesc(c.addr(u) + c.wg * 8192, 16, 1024, 1), db = mkdesc(c.addr(u + 1), 8192, 1024, 1); \
      c.turn(); \
      wg_fence(); \
      _Pragma("unroll") for (int kk = 0; kk < 4; kk++) wgmma_ss_n256<1>(acc, da + kk * 2, db + kk * 128, !(FIRST && kk == 0)); \
      wg_commit(); \
      c.pass(); }
    { const int ks = 0; KV_STEP(true) }
    for (int ks = 1; ks < 8; ks++) {
      KV_STEP(false)
      wg_wait<1>();
      c.release(3 * ((ks - 1) & 3), 3);
      if (ks == 2 && pend) { cnt_signal(pend, c.lane); pend = nullptr; }
    }
#undef KV_STEP
    wg_wait<0>(); fence_regs(acc);
    c.release(9, 3);
    const int blk = 2 * g + tile;
    uint8_t* dk = g_K + (size_t)(h * 16 + blk) * 32768 + toff;
    uint8_t* dv = g_V + (size_t)(h * 16 + blk) * 32768 + toff;
    uint32_t a0 = 0, b0 = 0, a1 = 0, b1 = 0, e0 = 0, f0 = 0, e1 = 0, f1 = 0;
    uint4 v0, v1;
#define KV_CHUNK(J) pack_chunk<16 * J>(acc, v0, v1); *(uint4*)(dk + J * 512) = v0; *(uint4*)(dk + J * 512 + 2048) = v1; sq_acc(v0, a0, b0); sq_acc(v1, a1, b1); \
    pack_chunk<64 + 16 * J>(acc, v0, v1); *(uint4*)(dv + J * 512) = v0; *(uint4*)(dv + J * 512 + 2048) = v1; sq_acc(v0, e0, f0); sq_acc(v1, e1, f1);
    KV_CHUNK(0) KV_CHUNK(1) KV_CHUNK(2) KV_CHUNK(3)
#undef KV_CHUNK
    float kn = norm2_max(a0, b0, a1, b1);
    const float vn = norm2_max(e0, f0, e1, f1);
    if (!(vn <= 1.0e30f && vn >= 1.0e-30f)) kn = __uint_as_float(0x7f800000u);
    if (c.lane == 0) g_kn2[h * 128 + blk * 8 + c.wg * 4 + c.warp] = kn;
  }
}

__device__ __forceinline__ int cons_q(Cons& c, unsigned* pend) {
  float a[64], b[64];
#define Q_STEP(FIRST) { \
    const int u = 3 * (ks & 3); \
    c.wait(u); \
    const uint64_t da = mkdesc(c.addr(u) + c.wg * 8192, 16, 1024, 1), db = mkdesc(c.addr(u + 2), 8192, 1024, 1); \
    c.turn(); \
    wg_fence(); \
    _Pragma("unroll") for (int kk = 0; kk < 4; kk++) wgmma_ss_n128<1>(a, da + kk * 2, db + kk * 128, !(FIRST && kk == 0)); \
    _Pragma("unroll") for (int kk = 0; kk < 4; kk++) wgmma_ss_n128<1>(b, da + 1024 + kk * 2, db + kk * 128, !(FIRST && kk == 0)); \
    wg_commit(); \
    c.pass(); }
  { const int ks = 0; Q_STEP(true) }
  for (int ks = 1; ks < 16; ks++) {
    Q_STEP(false)
    wg_wait<1>();
    c.release(3 * ((ks - 1) & 3), 3);
    if (ks == 2 && pend) { cnt_signal(pend, c.lane); pend = nullptr; }
  }
#undef Q_STEP
  wg_wait<0>(); fence_regs(a); fence_regs(b);
  c.release(9, 3);
  c.wait(0);
  const uint32_t q0 = c.addr(0) + (c.wg * 8 + c.warp * 2) * 2048 + (c.lane & 3) * 128 + (c.lane >> 2) * 16;
  uint32_t a0 = 0, b0 = 0, a1 = 0, b1 = 0, e0 = 0, f0 = 0, e1 = 0, f1 = 0;
  uint4 v0, v1;
#define Q_CHUNK(J) pack_chunk<16 * J>(a, QSCALE, QSCALE, v0, v1); sts128(q0 + J * 512, v0); sts128(q0 + J * 512 + 2048, v1); sq_acc(v0, a0, b0); sq_acc(v1, a1, b1); \
  pack_chunk<16 * J>(b, QSCALE, QSCALE, v0, v1); sts128(q0 + 32768 + J * 512, v0); sts128(q0 + 32768 + J * 512 + 2048, v1); sq_acc(v0, e0, f0); sq_acc(v1, e1, f1);
  Q_CHUNK(0) Q_CHUNK(1) Q_CHUNK(2) Q_CHUNK(3)
#undef Q_CHUNK
  fence_async_smem();
  const float qa = norm2_max(a0, b0, a1, b1), qb = norm2_max(e0, f0, e1, f1);
  const float kn = __uint_as_float(lds32(c.base + SM_BAR + 256));
  return bar_and(3 + c.wg, 128, (qa * kn <= BOUND2) && (qb * kn <= BOUND2));
}

__device__ __forceinline__ void issue_qk(float (&s)[64], uint32_t qaddr, uint32_t kaddr) {
  const uint64_t da = mkdesc(qaddr, 128, 2048, 0), db = mkdesc(kaddr, 128, 2048, 0);
#pragma unroll
  for (int kk = 0; kk < 8; kk++) wgmma_ss_n128<0>(s, da + kk * 16, db + kk * 16, kk > 0);
  wg_commit();
}
__device__ __forceinline__ void issue_pv(float (&o)[64], uint32_t (&p)[32], uint32_t vaddr, int acc) {
  const uint64_t db = mkdesc(vaddr, 2048, 128, 0);
#pragma unroll
  for (int kk = 0; kk < 8; kk++) wgmma_rs_n128<1>(o, p[4 * kk], p[4 * kk + 1], p[4 * kk + 2], p[4 * kk + 3], db + kk * 256, kk > 0 ? 1 : acc);
  wg_commit();
}
template<int A, int B> __device__ __forceinline__ void exp_rng(float (&s)[64]) {
#pragma unroll
  for (int i = 4 * A; i < 4 * B; i++) s[i] = ex2(s[i]);
}
template<int A, int B> __device__ __forceinline__ void sum_rng(const float (&s)[64], float (&l)[4]) {
#pragma unroll
  for (int i = A; i < B; i++) { l[0] += s[4 * i]; l[1] += s[4 * i + 1]; l[2] += s[4 * i + 2]; l[3] += s[4 * i + 3]; }
}
__device__ __forceinline__ void cvt_p(const float (&s)[64], uint32_t (&p)[32]) {
#pragma unroll
  for (int i = 0; i < 32; i++) p[i] = pack_bf16(s[2 * i], s[2 * i + 1]);
}
__device__ __forceinline__ void mask_diag(float (&s)[64], int lim) {
#pragma unroll
  for (int i = 0; i < 16; i++) {
    if (8 * i > lim) s[4 * i] = -INFINITY;
    if (8 * i + 1 > lim) s[4 * i + 1] = -INFINITY;
    if (8 * i - 8 > lim) s[4 * i + 2] = -INFINITY;
    if (8 * i - 7 > lim) s[4 * i + 3] = -INFINITY;
  }
}
__device__ __forceinline__ void store_o(const float (&o)[64], float l0, float l1, uint8_t* dst) {
  l0 += __shfl_xor_sync(~0u, l0, 1); l1 += __shfl_xor_sync(~0u, l1, 1);
  l0 += __shfl_xor_sync(~0u, l0, 2); l1 += __shfl_xor_sync(~0u, l1, 2);
  const float i0 = __fdividef(1.f, l0), i1 = __fdividef(1.f, l1);
  uint4 v0, v1;
  pack_chunk<0>(o, i0, i1, v0, v1);  *(uint4*)(dst) = v0;               *(uint4*)(dst + 1024) = v1;
  pack_chunk<16>(o, i0, i1, v0, v1); *(uint4*)(dst + 512) = v0;         *(uint4*)(dst + 512 + 1024) = v1;
  pack_chunk<32>(o, i0, i1, v0, v1); *(uint4*)(dst + 16384) = v0;       *(uint4*)(dst + 16384 + 1024) = v1;
  pack_chunk<48>(o, i0, i1, v0, v1); *(uint4*)(dst + 16384 + 512) = v0; *(uint4*)(dst + 16384 + 512 + 1024) = v1;
}
__device__ __forceinline__ void softmax_safe(float (&s)[64], float& m0, float& m1, float& sc0, float& sc1) {
  float a0 = m0, a1 = m1;
#pragma unroll
  for (int i = 0; i < 16; i++) { a0 = fmaxf(a0, fmaxf(s[4 * i], s[4 * i + 1])); a1 = fmaxf(a1, fmaxf(s[4 * i + 2], s[4 * i + 3])); }
  a0 = fmaxf(a0, __shfl_xor_sync(~0u, a0, 1)); a1 = fmaxf(a1, __shfl_xor_sync(~0u, a1, 1));
  a0 = fmaxf(a0, __shfl_xor_sync(~0u, a0, 2)); a1 = fmaxf(a1, __shfl_xor_sync(~0u, a1, 2));
  sc0 = ex2(m0 - a0); sc1 = ex2(m1 - a1);
  m0 = a0; m1 = a1;
#pragma unroll
  for (int i = 0; i < 16; i++) { s[4 * i] -= a0; s[4 * i + 1] -= a0; s[4 * i + 2] -= a1; s[4 * i + 3] -= a1; }
}
template<bool FAST> __device__ __forceinline__ void cons_att(Cons& c, int h, int g) {
  const int lim = c.wg * 64 + c.warp * 16 + (c.lane >> 2) - 2 * (c.lane & 3);
  const uint32_t dummy = c.base + SM_BAR + 260;
  uint8_t* const ctx0 = g_ctx + (size_t)(2 * h) * 16384 + (c.wg * 8 + c.warp * 2) * 1024 + (c.lane & 3) * 128 + (c.lane >> 2) * 16;
  float s[64], o[64]; uint32_t p[32];
  float l[4] = {0.f, 0.f, 0.f, 0.f};
  float m0 = -INFINITY, m1 = -INFINITY, sc0, sc1;
  int si = 0;
  uint32_t qaddr = c.addr(0) + c.wg * 16384;
  {
    const int uk = att_slot(si); si++;
    c.wait(uk);
    c.turn();
    wg_fence();
    issue_qk(s, qaddr, c.addr(uk));
    c.pass();
    wg_wait<0>(); fence_regs(s);
    c.release(uk, 2);
    if (!FAST) softmax_safe(s, m0, m1, sc0, sc1);
    exp_rng<0, 16>(s); sum_rng<0, 16>(s, l); cvt_p(s, p);
#pragma unroll
    for (int i = 0; i < 64; i++) o[i] = 0.f;
  }
  int acc = 0;
#define ATT_STEP(MODE, LASTQ) { \
    const int uk = att_slot(si); si = si == 4 ? 0 : si + 1; \
    const int uv = att_slot(si); si = si == 4 ? 0 : si + 1; \
    c.wait(uk); c.wait(uv); \
    c.turn(); \
    fence_regs(o); fence_regs(p); \
    wg_fence(); \
    issue_qk(s, qaddr, c.addr(uk)); \
    issue_pv(o, p, c.addr(uv), acc); \
    c.pass(); \
    acc = 1; \
    wg_wait<1>(); fence_regs(s); \
    c.release(uk, 2); \
    if (LASTQ) c.release(MODE == 1 ? 0 : 2, 2); \
    float lo0, lo1; \
    if (MODE == 2) { lo0 = l[0] + l[1]; lo1 = l[2] + l[3]; l[0] = l[1] = l[2] = l[3] = 0.f; m0 = m1 = -INFINITY; } \
    if (MODE != 0) mask_diag(s, lim); \
    if (!FAST) { softmax_safe(s, m0, m1, sc0, sc1); l[0] *= sc0; l[1] *= sc0; l[2] *= sc1; l[3] *= sc1; } \
    exp_rng<0, 10>(s); sum_rng<0, 10>(s, l); \
    sched_fence((l[0] + l[1]) + (l[2] + l[3]), dummy); \
    wg_wait<0>(); fence_regs(o); fence_regs(p); \
    c.release(uv, 2); \
    exp_rng<10, 16>(s); sum_rng<10, 16>(s, l); cvt_p(s, p); \
    if (MODE == 2) { store_o(o, lo0, lo1, ctx0 + (size_t)(15 - g) * 64 * 16384); acc = 0; } \
    else if (!FAST) { _Pragma("unroll") for (int i = 0; i < 16; i++) { o[4 * i] *= sc0; o[4 * i + 1] *= sc0; o[4 * i + 2] *= sc1; o[4 * i + 3] *= sc1; } } \
  }
  for (int t = 0; t < 2; t++) {
    const int n = t == 0 ? 14 - g : g;
    for (int j = n; j > 0; j--) ATT_STEP(0, (t == 1 && j == 1))
    if (t == 0) {
      ATT_STEP(1, true)
      qaddr += 32768;
      ATT_STEP(2, (g == 0))
    }
  }
#undef ATT_STEP
  {
    const int uv = att_slot(si);
    c.wait(uv);
    c.turn();
    fence_regs(o); fence_regs(p);
    wg_fence();
    issue_pv(o, p, c.addr(uv), acc);
    c.pass();
    wg_wait<0>(); fence_regs(o); fence_regs(p);
    c.release(uv, 2);
    store_o(o, l[0] + l[1], l[2] + l[3], ctx0 + (size_t)g * 64 * 16384);
  }
}

constexpr int CV_H = 1024, CV_U = 5120;
__device__ __forceinline__ void cons_conv(Cons& c, const Params& P, int cta, int nch, unsigned* pend) {
  const int r = c.lane >> 2, q = c.lane & 3, tid = c.warp * 32 + c.lane;
  const uint32_t part = c.addr(4 + 2 * c.wg);
  c.wait(4);
  const uint32_t aoff = CV_U + ((r & 1) ? 0 : UPITCH) + 4 * (((2039 - r) >> 1) + q - 8 * c.warp);
  const uint32_t woff = part + c.warp * 8192 + r * 1024;
  for (int i = 0; i < nch / 2; i++) {
    const int ch = conv_channel(cta, 2 * i + c.wg);
    const int u = 2 * c.wg + (i & 1);
    c.wait(u); c.skip(u ^ 2);
    const uint32_t ub = c.addr(u);
    uint32_t a[64];
#pragma unroll
    for (int G = 0; G < 16; G++) {
      a[4 * G + 0] = lds32(ub + aoff - 256 * G);
      a[4 * G + 1] = lds32(ub + aoff - 256 * G - 128);
      a[4 * G + 2] = lds32(ub + aoff - 256 * G + 16);
      a[4 * G + 3] = lds32(ub + aoff - 256 * G - 128 + 16);
    }
    float d0[32], d1[32], d2[32], d3[32];
    const uint64_t db = mkdesc(ub + CV_H - 16, 16, 128, 0);
    c.turn();
    wg_fence();
#pragma unroll
    for (int G = 0; G < 4; G++) wgmma_rs_n64<0>(d0, a[4 * G], a[4 * G + 1], a[4 * G + 2], a[4 * G + 3], db - 16 * G, G > 0);
#pragma unroll
    for (int G = 0; G < 8; G++) wgmma_rs_n64<0>(d1, a[4 * G], a[4 * G + 1], a[4 * G + 2], a[4 * G + 3], db + 64 - 16 * G, G > 0);
#pragma unroll
    for (int G = 0; G < 12; G++) wgmma_rs_n64<0>(d2, a[4 * G], a[4 * G + 1], a[4 * G + 2], a[4 * G + 3], db + 128 - 16 * G, G > 0);
#pragma unroll
    for (int G = 0; G < 16; G++) wgmma_rs_n64<0>(d3, a[4 * G], a[4 * G + 1], a[4 * G + 2], a[4 * G + 3], db + 192 - 16 * G, G > 0);
    wg_commit();
    c.pass();
    if (pend) { cnt_signal(pend, c.lane); pend = nullptr; }
    const uint32_t D2 = (uint32_t)__bfloat16_as_ushort(P.D[ch]) * 0x10001u;
    wg_wait<0>(); fence_regs(d0); fence_regs(d1); fence_regs(d2); fence_regs(d3); fence_regs(a);
    const uint32_t sw = (r & 3) * 32, wq = woff + q * 8;
    float c0 = 0.f, c1 = 0.f;
#define CV_ST(DD, R) _Pragma("unroll") for (int n = 0; n < 8; n++) { sts64f((wq + (R * 64 + n * 8) * 4) ^ sw, DD[4 * n] + c0, DD[4 * n + 1] + c1); c0 = DD[4 * n + 2]; c1 = DD[4 * n + 3]; }
    CV_ST(d0, 0) CV_ST(d1, 1) CV_ST(d2, 2) CV_ST(d3, 3)
#undef CV_ST
    bar_sync(3 + c.wg, 128);
    float y0[8], y1[8];
#pragma unroll
    for (int rr = 0; rr < 8; rr++) { const float2 v = lds64f((part + rr * 1024 + tid * 8) ^ ((rr & 3) * 32)); y0[rr] = v.x; y1[rr] = v.y; }
#pragma unroll
    for (int w = 1; w < 4; w++) {
      if (tid >= w) {
#pragma unroll
        for (int rr = 0; rr < 8; rr++) { const float2 v = lds64f((part + w * 8192 + rr * 1024 + (tid - w) * 8) ^ ((rr & 3) * 32)); y0[rr] += v.x; y1[rr] += v.y; }
      }
    }
    const uint4 ua = lds128(ub + CV_U + 4064 - 32 * tid + 16), uc = lds128(ub + CV_U + 4064 - 32 * tid);
    uint4 z0, z1;
    z0.x = hadd2(pack_bf16(y0[0], y0[1]), hmul2(__byte_perm(ua.w, 0, 0x1032), D2));
    z0.y = hadd2(pack_bf16(y0[2], y0[3]), hmul2(__byte_perm(ua.z, 0, 0x1032), D2));
    z0.z = hadd2(pack_bf16(y0[4], y0[5]), hmul2(__byte_perm(ua.y, 0, 0x1032), D2));
    z0.w = hadd2(pack_bf16(y0[6], y0[7]), hmul2(__byte_perm(ua.x, 0, 0x1032), D2));
    z1.x = hadd2(pack_bf16(y1[0], y1[1]), hmul2(__byte_perm(uc.w, 0, 0x1032), D2));
    z1.y = hadd2(pack_bf16(y1[2], y1[3]), hmul2(__byte_perm(uc.z, 0, 0x1032), D2));
    z1.z = hadd2(pack_bf16(y1[4], y1[5]), hmul2(__byte_perm(uc.y, 0, 0x1032), D2));
    z1.w = hadd2(pack_bf16(y1[6], y1[7]), hmul2(__byte_perm(uc.x, 0, 0x1032), D2));
    uint4* zp = (uint4*)(g_z + (size_t)ch * 2048 + tid * 16);
    zp[0] = z0; zp[1] = z1;
    __syncwarp();
    c.release2(u, 1);
    bar_sync(3 + c.wg, 128);
    pend = g_cnt + (C_Z + (ch >> 7)) * CSTRIDE;
  }
  c.release(4, 4);
  cnt_signal(pend, c.lane);
}

constexpr int OUT_XZ_AT = 58;
__device__ __forceinline__ int out_slot(int i) { return i < 3 ? 8 + 2 * i : 2 * (i - 3); }
__device__ __forceinline__ void cons_out(Cons& c, const Maps& M, int mb, int nb) {
  float acc[64];
  uint32_t ga[32];
  int si = 0, pu, u;
#define OUT_STEP(FIRST) { \
    u = out_slot(si); si = si == 6 ? 0 : si + 1; \
    c.wait(u); \
    const uint64_t da = mkdesc(c.addr(u) + c.wg * 8192, 128, 1024, 0), db = mkdesc(c.addr(u + 1), 8192, 1024, 1); \
    wg_fence(); \
    _Pragma("unroll") for (int kk = 0; kk < 4; kk++) wgmma_ss_n128<1>(acc, da + kk * 16, db + kk * 128, !(FIRST && kk == 0)); \
    wg_commit(); }
  OUT_STEP(true)
  pu = u;
  for (int ks = 1; ks <= OUT_XZ_AT; ks++) { OUT_STEP(false) wg_wait<1>(); c.release(pu, 2); pu = u; }
  const int ux = out_slot(si); si = si == 6 ? 0 : si + 1;
  const int uz = out_slot(si); si = si == 6 ? 0 : si + 1;
  OUT_STEP(false)
  c.wait(ux); c.wait(uz);
  const int row = mb * 128 + c.wg * 64 + c.warp * 16 + (c.lane >> 2);
  const float g0 = __ldcg(g_gate + row), g1 = __ldcg(g_gate + row + 8);
  const uint32_t gg0 = pack_bf16(g0, g0), gg1 = pack_bf16(g1, g1);
  const uint32_t og0 = pack_bf16(1.f - g0, 1.f - g0), og1 = pack_bf16(1.f - g1, 1.f - g1);
  const int xr = c.wg * 64 + c.warp * 16 + (c.lane & 15);
  const uint32_t xa = c.addr(ux) + xr * 128, xs = xr & 7, xh = c.lane >> 4;
  const int zr = (c.lane & 7) + ((c.lane >> 4) << 3);
  const uint32_t za = c.addr(uz) + c.wg * 16384 + zr * 128 + (((c.warp * 2 + ((c.lane >> 3) & 1)) ^ (zr & 7)) << 4);
#pragma unroll
  for (int i = 0; i < 8; i++) {
    uint32_t x0, x1, x2, x3, z0, z1, z2, z3;
    ldsm4(xa + (i >> 2) * 16384 + ((((i & 3) * 2 + xh) ^ xs) << 4), x0, x1, x2, x3);
    ldsm4t(za + i * 2048, z0, z1, z2, z3);
    ga[4 * i + 0] = hmul2(gg0, hmul2(x0, z0)); ga[4 * i + 1] = hmul2(gg1, hmul2(x1, z1));
    ga[4 * i + 2] = hmul2(gg0, hmul2(x2, z2)); ga[4 * i + 3] = hmul2(gg1, hmul2(x3, z3));
  }
  wg_wait<1>(); c.release(pu, 2); pu = u;
  for (int ks = OUT_XZ_AT + 2; ks < 64; ks++) { OUT_STEP(false) wg_wait<1>(); c.release(pu, 2); pu = u; }
#undef OUT_STEP
  wg_wait<0>(); fence_regs(acc);
#pragma unroll
  for (int i = 0; i < 8; i++) {
    const uint32_t r0 = hadd2(ga[4 * i + 0], hmul2(og0, pack_bf16(acc[8 * i + 0], acc[8 * i + 1])));
    const uint32_t r1 = hadd2(ga[4 * i + 1], hmul2(og1, pack_bf16(acc[8 * i + 2], acc[8 * i + 3])));
    const uint32_t r2 = hadd2(ga[4 * i + 2], hmul2(og0, pack_bf16(acc[8 * i + 4], acc[8 * i + 5])));
    const uint32_t r3 = hadd2(ga[4 * i + 3], hmul2(og1, pack_bf16(acc[8 * i + 6], acc[8 * i + 7])));
    stsm4(xa + (i >> 2) * 16384 + ((((i & 3) * 2 + xh) ^ xs) << 4), r0, r1, r2, r3);
  }
  fence_async_smem();
  __syncwarp();
  if (c.lane < 2) {
    const int r0 = c.wg * 64 + c.warp * 16;
    tma2d_store(&M.out, c.addr(ux) + c.lane * 16384 + r0 * 128, nb * 128 + c.lane * 64, mb * 128 + r0);
    asm volatile("cp.async.bulk.commit_group;\ncp.async.bulk.wait_group.read 0;" ::: "memory");
  }
}

__device__ __forceinline__ void prod_conv(Prod& p, const Maps& M, int cta, int nch, int lane) {
  p.acquire(4, 4);
  if (lane == 0) mbar_arrive(p.full(4));
  int ready = -1;
  for (int i = 0; i < nch; i++) {
    const int ch = conv_channel(cta, i);
    const int u = 2 * (i & 1) + ((i >> 1) & 1);
    if ((ch >> 5) != ready) { ready = ch >> 5; cnt_wait(g_cnt + (C_U + ready) * CSTRIDE, 128); }
    p.acquire(u, 1);
    if (lane == 0) {
      mbar_expect(p.full(u), 5120 + UCH);
      tma3d(p.addr(u), &M.h, 0, -8, ch, p.full(u));
      bulk_g2s(p.addr(u) + CV_U, g_u + (size_t)ch * UCH, UCH, p.full(u));
    }
  }
}
__device__ __forceinline__ void producer(const Maps& M, const Params& P, uint32_t base, int cta, int lane) {
  Prod p{base, 0xffffffffu};
  if (cta >= NREG) { if (P.mask & PH_CONV) prod_conv(p, M, cta, CONV_EXTRA, lane); return; }
  const int g = cta & 7, j = cta >> 3;
  for (int half = 0; half < 2; half++) {
    const int h = 2 * j + half;
    if (P.mask & PH_KV) {
      for (int it = 0; it < 16; it++) {
        const int u = 3 * (it & 3), ks = it & 7;
        p.acquire(u, 3);
        if (lane == 0) {
          mbar_expect(p.full(u), 3 * UNIT);
          tma2d(p.addr(u), &M.c, ks * 64, (2 * g + (it >> 3)) * 128, p.full(u));
          tma3d(p.addr(u + 1), &M.wk, 0, ks * 64, 2 * h, p.full(u));
          tma3d(p.addr(u + 2), &M.wv, 0, ks * 64, 2 * h, p.full(u));
        }
      }
    }
    if (P.mask & PH_ATT) {
      for (int ks = 0; ks < 16; ks++) {
        const int u = 3 * (ks & 3);
        p.acquire(u, 3);
        if (lane == 0) {
          mbar_expect(p.full(u), 3 * UNIT);
          tma2d(p.addr(u), &M.x, ks * 64, (15 - g) * 128, p.full(u));
          tma2d(p.addr(u + 1), &M.x, ks * 64, g * 128, p.full(u));
          tma3d(p.addr(u + 2), &M.wq, 0, ks * 64, 2 * h, p.full(u));
        }
      }
      TS(2, 8 * half + 0);
      cnt_wait(g_cnt + (C_KV + h) * CSTRIDE, 64);
      TS(2, 8 * half + 1);
      const uint8_t* Kh = g_K + (size_t)h * 16 * 32768;
      const uint8_t* Vh = g_V + (size_t)h * 16 * 32768;
      int si = 0, pv = 0;
      for (int s = 0; s <= 17; s++) {
        const int blk = s <= 15 - g ? s : 16 - s;
        if (s < 17) {
          const int u = att_slot(si); si = si == 4 ? 0 : si + 1;
          p.acquire(u, 2);
          if (lane == 0) { mbar_expect(p.full(u), 32768); bulk_g2s(p.addr(u), Kh + (size_t)blk * 32768, 32768, p.full(u)); }
        }
        if (s == 0) {
          const float4 kn = __ldcg((const float4*)(g_kn2 + h * 128) + lane);
          const uint32_t m = __reduce_max_sync(~0u, max(max(__float_as_uint(kn.x), __float_as_uint(kn.y)), max(__float_as_uint(kn.z), __float_as_uint(kn.w))));
          p.acquire(0, 4);
          if (lane == 0) { asm volatile("st.shared.u32 [%0], %1;" :: "r"(base + SM_BAR + 256), "r"(m) : "memory"); mbar_arrive(p.full(0)); }
        } else {
          const int u = att_slot(si); si = si == 4 ? 0 : si + 1;
          p.acquire(u, 2);
          if (lane == 0) { mbar_expect(p.full(u), 32768); bulk_g2s(p.addr(u), Vh + (size_t)pv * 32768, 32768, p.full(u)); }
        }
        pv = blk;
      }
    }
  }
  if (P.mask & PH_CONV) prod_conv(p, M, cta, CONV_REG, lane);
  if (P.mask & PH_OUT) {
    const int mb = j < 8 ? g : 15 - g, nb = j & 7;
    int si = 0;
    for (int ks = 0; ks < 64; ks++) {
      if ((ks & 31) == 0) { TS(2, 16 + (ks >> 4)); cnt_wait(g_cnt + (C_CTX + (ks >> 5) * 8 + g) * CSTRIDE, 128); TS(2, 17 + (ks >> 4)); }
      const int kb = ((ks & 31) >> 1) * 4 + (ks >> 5) * 2 + (ks & 1);
      const int u = out_slot(si); si = si == 6 ? 0 : si + 1;
      p.acquire(u, 2);
      if (lane == 0) {
        mbar_expect(p.full(u), 2 * UNIT);
        bulk_g2s(p.addr(u), g_ctx + (size_t)(mb * 64 + kb) * 16384, UNIT, p.full(u));
        tma3d(p.addr(u + 1), &M.wo, 0, kb * 64, 2 * nb, p.full(u));
      }
      if (ks == OUT_XZ_AT) {
        const int ux = out_slot(si); si = si == 6 ? 0 : si + 1;
        const int uz = out_slot(si); si = si == 6 ? 0 : si + 1;
        p.acquire(ux, 2);
        if (lane == 0) {
          mbar_expect(p.full(ux), 2 * UNIT);
          tma2d(p.addr(ux), &M.x, nb * 128, mb * 128, p.full(ux));
          tma2d(p.addr(ux + 1), &M.x, nb * 128 + 64, mb * 128, p.full(ux));
        }
        TS(2, 20);
        cnt_wait(g_cnt + C_GATE * CSTRIDE, 2048);
        cnt_wait(g_cnt + (C_Z + nb) * CSTRIDE, 512);
        TS(2, 21);
        p.acquire(uz, 2);
        if (lane == 0) {
          mbar_expect(p.full(uz), 2 * UNIT);
          tma2d(p.addr(uz), &M.z, mb * 128, nb * 128, p.full(uz));
          tma2d(p.addr(uz + 1), &M.z, mb * 128 + 64, nb * 128, p.full(uz));
        }
      }
    }
  }
}

__device__ __forceinline__ void aux_pre(const Params& P, int aw, int lane) {
  const int cp = lane & 15, tb = lane >> 4;
  for (int unit = aw; unit < 4096; unit += NCTA * 3) {
    const int grp = unit >> 7, t0 = (unit & 127) * 16 + tb * 8;
    const int ch = grp * 32 + cp * 2;
    const uint32_t* kp = (const uint32_t*)(P.k + ch), * vp = (const uint32_t*)(P.v + ch);
    uint32_t kk[12], vv[9];
#pragma unroll
    for (int i = 0; i < 12; i++) { const int t = t0 - 4 + i; kk[i] = t >= 0 ? __ldg(kp + (size_t)t * 512) : 0u; }
#pragma unroll
    for (int i = 0; i < 9; i++) { const int t = t0 - 1 + i; vv[i] = t >= 0 ? __ldg(vp + (size_t)t * 512) : 0u; }
    const uint4 sw = __ldg((const uint4*)(P.shift + ch * 4));
    const uint32_t w0 = __byte_perm(sw.x, sw.z, 0x5410), w1 = __byte_perm(sw.x, sw.z, 0x7632), w2 = __byte_perm(sw.y, sw.w, 0x5410), w3 = __byte_perm(sw.y, sw.w, 0x7632);
#pragma unroll
    for (int i = 0; i < 9; i++)
      vv[i] = hmul2(hadd2(hadd2(hadd2(hmul2(kk[i], w3), hmul2(kk[i + 1], w2)), hmul2(kk[i + 2], w1)), hmul2(kk[i + 3], w0)), vv[i]);
    if (t0 == 0) vv[0] = 0;
    uint8_t* e0 = g_u + (size_t)ch * UCH + (2040 - t0) * 2;
    *(uint4*)(e0)                = make_uint4(__byte_perm(vv[8], vv[7], 0x5410), __byte_perm(vv[6], vv[5], 0x5410), __byte_perm(vv[4], vv[3], 0x5410), __byte_perm(vv[2], vv[1], 0x5410));
    *(uint4*)(e0 + UPITCH)       = make_uint4(__byte_perm(vv[7], vv[6], 0x5410), __byte_perm(vv[5], vv[4], 0x5410), __byte_perm(vv[3], vv[2], 0x5410), __byte_perm(vv[1], vv[0], 0x5410));
    *(uint4*)(e0 + UCH)          = make_uint4(__byte_perm(vv[8], vv[7], 0x7632), __byte_perm(vv[6], vv[5], 0x7632), __byte_perm(vv[4], vv[3], 0x7632), __byte_perm(vv[2], vv[1], 0x7632));
    *(uint4*)(e0 + UCH + UPITCH) = make_uint4(__byte_perm(vv[7], vv[6], 0x7632), __byte_perm(vv[5], vv[4], 0x7632), __byte_perm(vv[3], vv[2], 0x7632), __byte_perm(vv[1], vv[0], 0x7632));
    if (t0 == 0) {
      const uint4 zz = make_uint4(0, 0, 0, 0);
      *(uint4*)(e0 + 16) = zz; *(uint4*)(e0 + UPITCH + 16) = zz; *(uint4*)(e0 + UCH + 16) = zz; *(uint4*)(e0 + UCH + UPITCH + 16) = zz;
    }
    cnt_signal(g_cnt + (C_U + grp) * CSTRIDE, lane);
  }
  for (int row = aw; row < 2048; row += NCTA * 3) {
    float a = 0.f;
#pragma unroll
    for (int i = 0; i < 4; i++) {
      const uint4 xv = __ldg((const uint4*)(P.x + (size_t)row * 1024) + i * 32 + lane), gv = __ldg((const uint4*)P.gw + i * 32 + lane);
      uint32_t m;
      m = hmul2(xv.x, gv.x); a += bf_lo(m) + bf_hi(m); m = hmul2(xv.y, gv.y); a += bf_lo(m) + bf_hi(m);
      m = hmul2(xv.z, gv.z); a += bf_lo(m) + bf_hi(m); m = hmul2(xv.w, gv.w); a += bf_lo(m) + bf_hi(m);
    }
#pragma unroll
    for (int o = 16; o > 0; o >>= 1) a += __shfl_xor_sync(~0u, a, o);
    a = bf_lo(pack_bf16(a, 0.f));
    const float gt = bf_lo(pack_bf16(__fdividef(1.f, 1.f + ex2(-a * 1.4426950408889634f)), 0.f));
    if (lane == 0) g_gate[row] = gt;
    cnt_signal(g_cnt + C_GATE * CSTRIDE, lane);
  }
}

__global__ void __launch_bounds__(384, 1) gated_mix_kernel(const __grid_constant__ Maps M, const __grid_constant__ Params P) {
  extern __shared__ __align__(1024) uint8_t smem[];
  const uint32_t base = (uint32_t)__cvta_generic_to_shared(smem);
  if (threadIdx.x == 0) {
    for (int i = 0; i < NUNIT; i++) { mbar_init(base + SM_BAR + 8 * i, 1); mbar_init(base + SM_BAR + 128 + 8 * i, 8); }
    mbar_init(base + SM_BAR + 272, 12);
    asm volatile("fence.mbarrier_init.release.cluster;" ::: "memory");
  }
  __syncthreads();
  const int wg = __shfl_sync(~0u, threadIdx.x >> 7, 0);
  const int warp = __shfl_sync(~0u, (threadIdx.x >> 5) & 3, 0);
  const int lane = threadIdx.x & 31;
  const int cta = blockIdx.x;
  if (wg == 2) {
    asm volatile("setmaxnreg.dec.sync.aligned.u32 56;");
    TS(2, 62);
    if (warp == 0) producer(M, P, base, cta, lane);
    else if (P.mask & PH_PRE) aux_pre(P, cta + (warp - 1) * NCTA, lane);
    __syncwarp();
    if (lane == 0) mbar_arrive(base + SM_BAR + 272);
    if (warp == 0 && (P.mask & PH_OUT)) {
      mbar_wait(base + SM_BAR + 272, 0);
      unsigned old = 0;
      if (lane == 0) asm volatile("atom.acq_rel.gpu.global.add.u32 %0, [%1], 1;" : "=r"(old) : "l"(g_cnt + C_EXIT * CSTRIDE) : "memory");
      old = __shfl_sync(~0u, old, 0);
      if (old == NCTA - 1) for (int i = lane; i < C_NUM; i += 32) g_cnt[i * CSTRIDE] = 0;
    }
  } else {
    asm volatile("setmaxnreg.inc.sync.aligned.u32 224;");
    Cons c{base, 0u, lane, warp, wg};
    if (wg == 1) bar_arrive(1, 256);
    unsigned* pend = nullptr;
    TS(wg, 0);
    if (cta < NREG) {
      const int g = cta & 7, j = cta >> 3;
      for (int half = 0; half < 2; half++) {
        const int h = 2 * j + half;
        if (P.mask & PH_KV) { cons_kv(c, h, g, pend); pend = g_cnt + (C_KV + h) * CSTRIDE; }
        TS(wg, 1 + 4 * half);
        if (P.mask & PH_ATT) {
          const int fast = cons_q(c, pend);
          TS(wg, 2 + 4 * half);
          if (fast) cons_att<true>(c, h, g); else cons_att<false>(c, h, g);
          pend = g_cnt + (C_CTX + half * 8 + g) * CSTRIDE;
          TS(wg, 3 + 4 * half);
        }
      }
    }
    if (P.mask & PH_CONV) { cons_conv(c, P, cta, cta < NREG ? CONV_REG : CONV_EXTRA, pend); pend = nullptr; }
    TS(wg, 9);
    if (pend) cnt_signal(pend, lane);
    if (cta < NREG && (P.mask & PH_OUT)) cons_out(c, M, (cta >> 3) < 8 ? (cta & 7) : 15 - (cta & 7), (cta >> 3) & 7);
    TS(wg, 10);
    __syncwarp();
    if (lane == 0) mbar_arrive(base + SM_BAR + 272);
  }
}

typedef CUresult (*EncFn)(CUtensorMap*, CUtensorMapDataType, cuuint32_t, void*, const cuuint64_t*, const cuuint64_t*, const cuuint32_t*, const cuuint32_t*,
                          CUtensorMapInterleave, CUtensorMapSwizzle, CUtensorMapL2promotion, CUtensorMapFloatOOBfill);
static void enc(EncFn f, CUtensorMap* m, const void* ptr, int rank, const cuuint64_t* dims, const cuuint64_t* strides, const cuuint32_t* box, CUtensorMapSwizzle sw) {
  const cuuint32_t es[3] = {1, 1, 1};
  f(m, CU_TENSOR_MAP_DATA_TYPE_BFLOAT16, rank, (void*)ptr, dims, strides, box, es, CU_TENSOR_MAP_INTERLEAVE_NONE, sw, CU_TENSOR_MAP_L2_PROMOTION_L2_256B, CU_TENSOR_MAP_FLOAT_OOB_FILL_NONE);
}
static void enc2(EncFn f, CUtensorMap* m, const void* ptr, int cols, int rows, int brows) {
  const cuuint64_t d[2] = {(cuuint64_t)cols, (cuuint64_t)rows}, s[1] = {(cuuint64_t)cols * 2}; const cuuint32_t b[2] = {64, (cuuint32_t)brows};
  enc(f, m, ptr, 2, d, s, b, CU_TENSOR_MAP_SWIZZLE_128B);
}
static void encw(EncFn f, CUtensorMap* m, const void* ptr, int cols, int rows) {
  const cuuint64_t d[3] = {64, (cuuint64_t)rows, (cuuint64_t)cols / 64}, s[2] = {(cuuint64_t)cols * 2, 128}; const cuuint32_t b[3] = {64, 64, 2};
  enc(f, m, ptr, 3, d, s, b, CU_TENSOR_MAP_SWIZZLE_128B);
}
extern "C" void kernel_launch(void* const* d_in, const int* in_sizes, int n_in, void* d_out, int out_size) {
  static EncFn fn = nullptr;
  static int nsm = 0;
  static void* zptr = nullptr;
  if (!fn) {
    void* p = nullptr; cudaDriverEntryPointQueryResult qr;
    cudaGetDriverEntryPoint("cuTensorMapEncodeTiled", &p, cudaEnableDefault, &qr);
    fn = (EncFn)p;
    cudaFuncSetAttribute(gated_mix_kernel, cudaFuncAttributeMaxDynamicSharedMemorySize, SMEM_BYTES);
    int dev = 0; cudaGetDevice(&dev);
    cudaDeviceGetAttribute(&nsm, cudaDevAttrMultiProcessorCount, dev);
    cudaGetSymbolAddress(&zptr, g_z);
  }
  Maps M;
  enc2(fn, &M.x, d_in[0], 1024, 2048, 128);
  enc2(fn, &M.c, d_in[7], 512, 2048, 128);
  encw(fn, &M.wq, d_in[8], 4096, 1024);
  encw(fn, &M.wk, d_in[9], 4096, 512);
  encw(fn, &M.wv, d_in[10], 4096, 512);
  encw(fn, &M.wo, d_in[11], 1024, 4096);
  { const cuuint64_t d[3] = {64, 32, 1024}, s[2] = {128, 4096}; const cuuint32_t b[3] = {64, 40, 1}; enc(fn, &M.h, d_in[4], 3, d, s, b, CU_TENSOR_MAP_SWIZZLE_NONE); }
  enc2(fn, &M.z, zptr, 2048, 1024, 128);
  enc2(fn, &M.out, d_out, 1024, 2048, 16);
  Params P{(const __nv_bfloat16*)d_in[0], (const __nv_bfloat16*)d_in[1], (const __nv_bfloat16*)d_in[2], (const __nv_bfloat16*)d_in[3],
           (const __nv_bfloat16*)d_in[5], (const __nv_bfloat16*)d_in[12], PH_ALL};
  bool split = nsm < NCTA;
  if (!split) {
    gated_mix_kernel<<<NCTA, 384, SMEM_BYTES>>>(M, P);
  } else {
    P.mask = PH_PRE | PH_KV;   gated_mix_kernel<<<NCTA, 384, SMEM_BYTES>>>(M, P);
    P.mask = PH_ATT | PH_CONV; gated_mix_kernel<<<NCTA, 384, SMEM_BYTES>>>(M, P);
    P.mask = PH_OUT;           gated_mix_kernel<<<NCTA, 384, SMEM_BYTES>>>(M, P);
  }
}
```

```cpp
#include <cuda_runtime.h>
#include <cuda.h>
#include <cuda_bf16.h>
#include <stdint.h>

template<int TB> __device__ __forceinline__ void wgmma_ss_n256(float (&d)[128], uint64_t da, uint64_t db, int scale_d) {
  asm volatile("{\n.reg .pred p;\nsetp.ne.b32 p, %130, 0;\n"
    "wgmma.mma_async.sync.aligned.m64n256k16.f32.bf16.bf16 {%0, %1, %2, %3, %4, %5, %6, %7, %8, %9, %10, %11, %12, %13, %14, %15, %16, %17, %18, %19, %20, %21, %22, %23, %24, %25, %26, %27, %28, %29, %30, %31, %32, %33, %34, %35, %36, %37, %38, %39, %40, %41, %42, %43, %44, %45, %46, %47, %48, %49, %50, %51, %52, %53, %54, %55, %56, %57, %58, %59, %60, %61, %62, %63, %64, %65, %66, %67, %68, %69, %70, %71, %72, %73, %74, %75, %76, %77, %78, %79, %80, %81, %82, %83, %84, %85, %86, %87, %88, %89, %90, %91, %92, %93, %94, %95, %96, %97, %98, %99, %100, %101, %102, %103, %104, %105, %106, %107, %108, %109, %110, %111, %112, %113, %114, %115, %116, %117, %118, %119, %120, %121, %122, %123, %124, %125, %126, %127}, %128, %129, p, 1, 1, 0, %131;\n}\n"
    : "+f"(d[0]), "+f"(d[1]), "+f"(d[2]), "+f"(d[3]), "+f"(d[4]), "+f"(d[5]), "+f"(d[6]), "+f"(d[7]), "+f"(d[8]), "+f"(d[9]), "+f"(d[10]), "+f"(d[11]), "+f"(d[12]), "+f"(d[13]), "+f"(d[14]), "+f"(d[15]), "+f"(d[16]), "+f"(d[17]), "+f"(d[18]), "+f"(d[19]), "+f"(d[20]), "+f"(d[21]), "+f"(d[22]), "+f"(d[23]), "+f"(d[24]), "+f"(d[25]), "+f"(d[26]), "+f"(d[27]), "+f"(d[28]), "+f"(d[29]), "+f"(d[30]), "+f"(d[31]), "+f"(d[32]), "+f"(d[33]), "+f"(d[34]), "+f"(d[35]), "+f"(d[36]), "+f"(d[37]), "+f"(d[38]), "+f"(d[39]), "+f"(d[40]), "+f"(d[41]), "+f"(d[42]), "+f"(d[43]), "+f"(d[44]), "+f"(d[45]), "+f"(d[46]), "+f"(d[47]), "+f"(d[48]), "+f"(d[49]), "+f"(d[50]), "+f"(d[51]), "+f"(d[52]), "+f"(d[53]), "+f"(d[54]), "+f"(d[55]), "+f"(d[56]), "+f"(d[57]), "+f"(d[58]), "+f"(d[59]), "+f"(d[60]), "+f"(d[61]), "+f"(d[62]), "+f"(d[63]), "+f"(d[64]), "+f"(d[65]), "+f"(d[66]), "+f"(d[67]), "+f"(d[68]), "+f"(d[69]), "+f"(d[70]), "+f"(d[71]), "+f"(d[72]), "+f"(d[73]), "+f"(d[74]), "+f"(d[75]), "+f"(d[76]), "+f"(d[77]), "+f"(d[78]), "+f"(d[79]), "+f"(d[80]), "+f"(d[81]), "+f"(d[82]), "+f"(d[83]), "+f"(d[84]), "+f"(d[85]), "+f"(d[86]), "+f"(d[87]), "+f"(d[88]), "+f"(d[89]), "+f"(d[90]), "+f"(d[91]), "+f"(d[92]), "+f"(d[93]), "+f"(d[94]), "+f"(d[95]), "+f"(d[96]), "+f"(d[97]), "+f"(d[98]), "+f"(d[99]), "+f"(d[100]), "+f"(d[101]), "+f"(d[102]), "+f"(d[103]), "+f"(d[104]), "+f"(d[105]), "+f"(d[106]), "+f"(d[107]), "+f"(d[108]), "+f"(d[109]), "+f"(d[110]), "+f"(d[111]), "+f"(d[112]), "+f"(d[113]), "+f"(d[114]), "+f"(d[115]), "+f"(d[116]), "+f"(d[117]), "+f"(d[118]), "+f"(d[119]), "+f"(d[120]), "+f"(d[121]), "+f"(d[122]), "+f"(d[123]), "+f"(d[124]), "+f"(d[125]), "+f"(d[126]), "+f"(d[127])
    : "l"(da), "l"(db), "r"(scale_d), "n"(TB));
}
template<int TB> __device__ __forceinline__ void wgmma_ss_n128(float (&d)[64], uint64_t da, uint64_t db, int scale_d) {
  asm volatile("{\n.reg .pred p;\nsetp.ne.b32 p, %66, 0;\n"
    "wgmma.mma_async.sync.aligned.m64n128k16.f32.bf16.bf16 {%0, %1, %2, %3, %4, %5, %6, %7, %8, %9, %10, %11, %12, %13, %14, %15, %16, %17, %18, %19, %20, %21, %22, %23, %24, %25, %26, %27, %28, %29, %30, %31, %32, %33, %34, %35, %36, %37, %38, %39, %40, %41, %42, %43, %44, %45, %46, %47, %48, %49, %50, %51, %52, %53, %54, %55, %56, %57, %58, %59, %60, %61, %62, %63}, %64, %65, p, 1, 1, 0, %67;\n}\n"
    : "+f"(d[0]), "+f"(d[1]), "+f"(d[2]), "+f"(d[3]), "+f"(d[4]), "+f"(d[5]), "+f"(d[6]), "+f"(d[7]), "+f"(d[8]), "+f"(d[9]), "+f"(d[10]), "+f"(d[11]), "+f"(d[12]), "+f"(d[13]), "+f"(d[14]), "+f"(d[15]), "+f"(d[16]), "+f"(d[17]), "+f"(d[18]), "+f"(d[19]), "+f"(d[20]), "+f"(d[21]), "+f"(d[22]), "+f"(d[23]), "+f"(d[24]), "+f"(d[25]), "+f"(d[26]), "+f"(d[27]), "+f"(d[28]), "+f"(d[29]), "+f"(d[30]), "+f"(d[31]), "+f"(d[32]), "+f"(d[33]), "+f"(d[34]), "+f"(d[35]), "+f"(d[36]), "+f"(d[37]), "+f"(d[38]), "+f"(d[39]), "+f"(d[40]), "+f"(d[41]), "+f"(d[42]), "+f"(d[43]), "+f"(d[44]), "+f"(d[45]), "+f"(d[46]), "+f"(d[47]), "+f"(d[48]), "+f"(d[49]), "+f"(d[50]), "+f"(d[51]), "+f"(d[52]), "+f"(d[53]), "+f"(d[54]), "+f"(d[55]), "+f"(d[56]), "+f"(d[57]), "+f"(d[58]), "+f"(d[59]), "+f"(d[60]), "+f"(d[61]), "+f"(d[62]), "+f"(d[63])
    : "l"(da), "l"(db), "r"(scale_d), "n"(TB));
}
template<int TB> __device__ __forceinline__ void wgmma_ss_n64(float (&d)[32], uint64_t da, uint64_t db, int scale_d) {
  asm volatile("{\n.reg .pred p;\nsetp.ne.b32 p, %34, 0;\n"
    "wgmma.mma_async.sync.aligned.m64n64k16.f32.bf16.bf16 {%0, %1, %2, %3, %4, %5, %6, %7, %8, %9, %10, %11, %12, %13, %14, %15, %16, %17, %18, %19, %20, %21, %22, %23, %24, %25, %26, %27, %28, %29, %30, %31}, %32, %33, p, 1, 1, 0, %35;\n}\n"
    : "+f"(d[0]), "+f"(d[1]), "+f"(d[2]), "+f"(d[3]), "+f"(d[4]), "+f"(d[5]), "+f"(d[6]), "+f"(d[7]), "+f"(d[8]), "+f"(d[9]), "+f"(d[10]), "+f"(d[11]), "+f"(d[12]), "+f"(d[13]), "+f"(d[14]), "+f"(d[15]), "+f"(d[16]), "+f"(d[17]), "+f"(d[18]), "+f"(d[19]), "+f"(d[20]), "+f"(d[21]), "+f"(d[22]), "+f"(d[23]), "+f"(d[24]), "+f"(d[25]), "+f"(d[26]), "+f"(d[27]), "+f"(d[28]), "+f"(d[29]), "+f"(d[30]), "+f"(d[31])
    : "l"(da), "l"(db), "r"(scale_d), "n"(TB));
}
template<int TB> __device__ __forceinline__ void wgmma_rs_n128(float (&d)[64], uint32_t a0, uint32_t a1, uint32_t a2, uint32_t a3, uint64_t db, int scale_d) {
  asm volatile("{\n.reg .pred p;\nsetp.ne.b32 p, %69, 0;\n"
    "wgmma.mma_async.sync.aligned.m64n128k16.f32.bf16.bf16 {%0, %1, %2, %3, %4, %5, %6, %7, %8, %9, %10, %11, %12, %13, %14, %15, %16, %17, %18, %19, %20, %21, %22, %23, %24, %25, %26, %27, %28, %29, %30, %31, %32, %33, %34, %35, %36, %37, %38, %39, %40, %41, %42, %43, %44, %45, %46, %47, %48, %49, %50, %51, %52, %53, %54, %55, %56, %57, %58, %59, %60, %61, %62, %63}, {%64, %65, %66, %67}, %68, p, 1, 1, %70;\n}\n"
    : "+f"(d[0]), "+f"(d[1]), "+f"(d[2]), "+f"(d[3]), "+f"(d[4]), "+f"(d[5]), "+f"(d[6]), "+f"(d[7]), "+f"(d[8]), "+f"(d[9]), "+f"(d[10]), "+f"(d[11]), "+f"(d[12]), "+f"(d[13]), "+f"(d[14]), "+f"(d[15]), "+f"(d[16]), "+f"(d[17]), "+f"(d[18]), "+f"(d[19]), "+f"(d[20]), "+f"(d[21]), "+f"(d[22]), "+f"(d[23]), "+f"(d[24]), "+f"(d[25]), "+f"(d[26]), "+f"(d[27]), "+f"(d[28]), "+f"(d[29]), "+f"(d[30]), "+f"(d[31]), "+f"(d[32]), "+f"(d[33]), "+f"(d[34]), "+f"(d[35]), "+f"(d[36]), "+f"(d[37]), "+f"(d[38]), "+f"(d[39]), "+f"(d[40]), "+f"(d[41]), "+f"(d[42]), "+f"(d[43]), "+f"(d[44]), "+f"(d[45]), "+f"(d[46]), "+f"(d[47]), "+f"(d[48]), "+f"(d[49]), "+f"(d[50]), "+f"(d[51]), "+f"(d[52]), "+f"(d[53]), "+f"(d[54]), "+f"(d[55]), "+f"(d[56]), "+f"(d[57]), "+f"(d[58]), "+f"(d[59]), "+f"(d[60]), "+f"(d[61]), "+f"(d[62]), "+f"(d[63])
    : "r"(a0), "r"(a1), "r"(a2), "r"(a3), "l"(db), "r"(scale_d), "n"(TB));
}
template<int TB> __device__ __forceinline__ void wgmma_rs_n64(float (&d)[32], uint32_t a0, uint32_t a1, uint32_t a2, uint32_t a3, uint64_t db, int scale_d) {
  asm volatile("{\n.reg .pred p;\nsetp.ne.b32 p, %37, 0;\n"
    "wgmma.mma_async.sync.aligned.m64n64k16.f32.bf16.bf16 {%0, %1, %2, %3, %4, %5, %6, %7, %8, %9, %10, %11, %12, %13, %14, %15, %16, %17, %18, %19, %20, %21, %22, %23, %24, %25, %26, %27, %28, %29, %30, %31}, {%32, %33, %34, %35}, %36, p, 1, 1, %38;\n}\n"
    : "+f"(d[0]), "+f"(d[1]), "+f"(d[2]), "+f"(d[3]), "+f"(d[4]), "+f"(d[5]), "+f"(d[6]), "+f"(d[7]), "+f"(d[8]), "+f"(d[9]), "+f"(d[10]), "+f"(d[11]), "+f"(d[12]), "+f"(d[13]), "+f"(d[14]), "+f"(d[15]), "+f"(d[16]), "+f"(d[17]), "+f"(d[18]), "+f"(d[19]), "+f"(d[20]), "+f"(d[21]), "+f"(d[22]), "+f"(d[23]), "+f"(d[24]), "+f"(d[25]), "+f"(d[26]), "+f"(d[27]), "+f"(d[28]), "+f"(d[29]), "+f"(d[30]), "+f"(d[31])
    : "r"(a0), "r"(a1), "r"(a2), "r"(a3), "l"(db), "r"(scale_d), "n"(TB));
}

constexpr int NCTA = 132, NREG = 128;
constexpr int UNIT = 16384, NUNIT = 14;
constexpr uint32_t SMEM_BASE = 1024;
constexpr int SM_BAR = NUNIT * UNIT;
constexpr int SMEM_BYTES = SM_BAR + 1024;
constexpr int UPITCH = 4160, UCH = 2 * UPITCH;
constexpr float QSCALE = 0.08838834764831845f * 1.4426950408889634f;
constexpr float BOUND2 = 48.f * 48.f / 1.15f;
#define CONV_REG 4
constexpr int CONV_EXTRA = (1024 - NREG * CONV_REG) / (NCTA - NREG);
constexpr int CH_EXTRA_TOTAL = CONV_EXTRA * (NCTA - NREG);
constexpr int C_KV = 0;
constexpr int C_CTX = 32;
constexpr int C_U = 48;
constexpr int C_Z = 80;
constexpr int C_GATE = 88;
constexpr int C_EXIT = 89;
constexpr int C_NUM = 96;
constexpr int CSTRIDE = 32;
constexpr int SM_KMAX = SM_BAR + 256, SM_DUMMY = SM_BAR + 264, SM_EXIT = SM_BAR + 272, SM_SIG = SM_BAR + 320, SM_RDY = SM_BAR + 384;
enum { SIG_KV = 0, SIG_CTX = 2, SIG_Z = 4 };
enum { RDY_KV = 0, RDY_CTX = 2, RDY_U = 4, RDY_Z = 5 };
enum { PH_PRE = 1, PH_KV = 2, PH_ATT = 4, PH_CONV = 8, PH_OUT = 16, PH_ALL = 31 };

__device__ __align__(1024) uint8_t g_KV[32 * 16 * 65536];
__device__ __align__(1024) uint8_t g_ctx[16 * 64 * 16384];
__device__ __align__(1024) uint8_t g_u[1024 * UCH];
__device__ __align__(1024) __nv_bfloat16 g_z[1024 * 2048];
__device__ __align__(1024) float g_gate[2048];
__device__ __align__(1024) float g_kn2[32 * 128];
__device__ __align__(1024) unsigned g_cnt[C_NUM * CSTRIDE];

struct __align__(64) Maps { CUtensorMap x, c, wq, wk, wv, wo, h, z, out; };
struct Params {
  const __nv_bfloat16 *x, *k, *v, *shift, *D, *gw;
};

__device__ __forceinline__ void wg_fence() { asm volatile("wgmma.fence.sync.aligned;" ::: "memory"); }
__device__ __forceinline__ void wg_commit() { asm volatile("wgmma.commit_group.sync.aligned;" ::: "memory"); }
template<int N> __device__ __forceinline__ void wg_wait() { asm volatile("wgmma.wait_group.sync.aligned %0;" :: "n"(N) : "memory"); }
__device__ __forceinline__ uint64_t mkdesc(uint32_t addr, uint32_t lbo, uint32_t sbo, uint32_t swz) {
  return (uint64_t)((addr & 0x3FFFF) >> 4) | ((uint64_t)(lbo >> 4) << 16) | ((uint64_t)(sbo >> 4) << 32) | ((uint64_t)swz << 62);
}
__device__ __forceinline__ void mbar_init(uint32_t bar, int cnt) { asm volatile("mbarrier.init.shared::cta.b64 [%0], %1;" :: "r"(bar), "r"(cnt)); }
__device__ __forceinline__ void mbar_expect(uint32_t bar, uint32_t bytes) { asm volatile("mbarrier.arrive.expect_tx.shared::cta.b64 _, [%0], %1;" :: "r"(bar), "r"(bytes) : "memory"); }
__device__ __forceinline__ void mbar_arrive(uint32_t bar) { asm volatile("mbarrier.arrive.shared::cta.b64 _, [%0];" :: "r"(bar) : "memory"); }
__device__ __forceinline__ void mbar_arrive_n(uint32_t bar, int n) { asm volatile("mbarrier.arrive.shared::cta.b64 _, [%0], %1;" :: "r"(bar), "r"(n) : "memory"); }
__device__ __forceinline__ void mbar_wait(uint32_t bar, uint32_t parity) {
  asm volatile("{\n.reg .pred p;\n.reg .u32 n;\nmov.u32 n, 0;\n"
    "LW:\nmbarrier.try_wait.parity.shared::cta.b64 p, [%0], %1;\n@p bra LD;\n"
    "add.u32 n, n, 1;\nsetp.lt.u32 p, n, 2097152;\n@p bra LW;\ntrap;\nLD:\n}\n" :: "r"(bar), "r"(parity) : "memory");
}
__device__ __forceinline__ void mbar_wait_slow(uint32_t bar, uint32_t parity) {
  asm volatile("{\n.reg .pred p;\n.reg .u32 n;\nmov.u32 n, 0;\n"
    "LW:\nmbarrier.test_wait.parity.shared::cta.b64 p, [%0], %1;\n@p bra LD;\n"
    "nanosleep.u32 128;\nadd.u32 n, n, 1;\nsetp.lt.u32 p, n, 4194304;\n@p bra LW;\ntrap;\nLD:\n}\n" :: "r"(bar), "r"(parity) : "memory");
}
__device__ __forceinline__ void mbar_wait_all(uint32_t bar, uint32_t parity) {
  asm volatile("{\n.reg .pred p, q;\n.reg .u32 n;\nmov.u32 n, 0;\n"
    "LW:\nmbarrier.try_wait.parity.shared::cta.b64 p, [%0], %1;\nvote.sync.all.pred q, p, 0xffffffff;\n@q bra.uni LD;\n"
    "add.u32 n, n, 1;\nsetp.lt.u32 q, n, 2097152;\n@q bra.uni LW;\ntrap;\nLD:\n}\n" :: "r"(bar), "r"(parity) : "memory");
}
__device__ __forceinline__ void cnt_wait(const unsigned* p, unsigned target) {
  asm volatile("{\n.reg .pred p;\n.reg .u32 n, v;\nmov.u32 n, 0;\n"
    "LW:\nld.relaxed.gpu.global.u32 v, [%0];\nsetp.ge.u32 p, v, %1;\n@p bra LD;\n"
    "nanosleep.u32 64;\nadd.u32 n, n, 1;\nsetp.lt.u32 p, n, 4194304;\n@p bra LW;\ntrap;\nLD:\nfence.acq_rel.gpu;\nfence.proxy.async;\n}\n" :: "l"(p), "r"(target) : "memory");
}
__device__ __forceinline__ void cnt_signal(unsigned* p, int lane) {
  __syncwarp();
  if (lane == 0) asm volatile("red.release.gpu.global.add.u32 [%0], 1;" :: "l"(p) : "memory");
}
__device__ __forceinline__ void cnt_publish(unsigned* p, unsigned n) {
  asm volatile("fence.acq_rel.gpu;\nred.relaxed.gpu.global.add.u32 [%0], %1;" :: "l"(p), "r"(n) : "memory");
}
__device__ __forceinline__ void bulk_g2s(uint32_t dst, const void* src, uint32_t bytes, uint32_t bar) {
  asm volatile("cp.async.bulk.shared::cluster.global.mbarrier::complete_tx::bytes [%0], [%1], %2, [%3];" :: "r"(dst), "l"(src), "r"(bytes), "r"(bar) : "memory");
}
__device__ __forceinline__ void tma2d(uint32_t dst, const CUtensorMap* m, int x, int y, uint32_t bar) {
  asm volatile("cp.async.bulk.tensor.2d.shared::cluster.global.mbarrier::complete_tx::bytes [%0], [%1, {%3, %4}], [%2];" :: "r"(dst), "l"(m), "r"(bar), "r"(x), "r"(y) : "memory");
}
__device__ __forceinline__ void tma3d(uint32_t dst, const CUtensorMap* m, int x, int y, int z, uint32_t bar) {
  asm volatile("cp.async.bulk.tensor.3d.shared::cluster.global.mbarrier::complete_tx::bytes [%0], [%1, {%3, %4, %5}], [%2];" :: "r"(dst), "l"(m), "r"(bar), "r"(x), "r"(y), "r"(z) : "memory");
}
__device__ __forceinline__ void tma2d_store(const CUtensorMap* m, uint32_t src, int x, int y) {
  asm volatile("cp.async.bulk.tensor.2d.global.shared::cta.bulk_group [%0, {%2, %3}], [%1];" :: "l"(m), "r"(src), "r"(x), "r"(y) : "memory");
}
__device__ __forceinline__ bool elect() {
  uint32_t r; asm volatile("{\n.reg .pred p;\nelect.sync _|p, 0xffffffff;\nselp.u32 %0, 1, 0, p;\n}\n" : "=r"(r)); return r != 0;
}
__device__ __forceinline__ void bar_sync(int id, int n) { asm volatile("bar.sync %0, %1;" :: "r"(id), "r"(n) : "memory"); }
__device__ __forceinline__ void bar_arrive(int id, int n) { asm volatile("bar.arrive %0, %1;" :: "r"(id), "r"(n) : "memory"); }
__device__ __forceinline__ int bar_and(int id, int n, int pred) {
  int r; asm volatile("{\n.reg .pred p, q;\nsetp.ne.b32 p, %3, 0;\nbar.red.and.pred q, %1, %2, p;\nselp.b32 %0, 1, 0, q;\n}\n" : "=r"(r) : "r"(id), "r"(n), "r"(pred) : "memory");
  return r;
}
__device__ __forceinline__ void fence_async_smem() { asm volatile("fence.proxy.async.shared::cta;" ::: "memory"); }
__device__ __forceinline__ float ex2(float x) { float y; asm("ex2.approx.ftz.f32 %0, %1;" : "=f"(y) : "f"(x)); return y; }
__device__ __forceinline__ uint32_t pack_bf16(float lo, float hi) { uint32_t r; asm("cvt.rn.bf16x2.f32 %0, %1, %2;" : "=r"(r) : "f"(hi), "f"(lo)); return r; }
__device__ __forceinline__ uint32_t hmul2(uint32_t a, uint32_t b) { uint32_t r; asm("mul.rn.bf16x2 %0, %1, %2;" : "=r"(r) : "r"(a), "r"(b)); return r; }
__device__ __forceinline__ uint32_t hadd2(uint32_t a, uint32_t b) { uint32_t r; asm("add.rn.bf16x2 %0, %1, %2;" : "=r"(r) : "r"(a), "r"(b)); return r; }
__device__ __forceinline__ uint32_t hfma2(uint32_t a, uint32_t b, uint32_t c) { uint32_t r; asm("fma.rn.bf16x2 %0, %1, %2, %3;" : "=r"(r) : "r"(a), "r"(b), "r"(c)); return r; }
__device__ __forceinline__ float bf_lo(uint32_t a) { return __uint_as_float(a << 16); }
__device__ __forceinline__ float bf_hi(uint32_t a) { return __uint_as_float(a & 0xffff0000u); }
__device__ __forceinline__ uint32_t lds32(uint32_t a) { uint32_t v; asm volatile("ld.shared.u32 %0, [%1];" : "=r"(v) : "r"(a) : "memory"); return v; }
__device__ __forceinline__ float2 lds64f(uint32_t a) { float2 v; asm volatile("ld.shared.v2.f32 {%0,%1}, [%2];" : "=f"(v.x), "=f"(v.y) : "r"(a) : "memory"); return v; }
__device__ __forceinline__ uint4 lds128(uint32_t a) { uint4 v; asm volatile("ld.shared.v4.u32 {%0,%1,%2,%3}, [%4];" : "=r"(v.x), "=r"(v.y), "=r"(v.z), "=r"(v.w) : "r"(a) : "memory"); return v; }
__device__ __forceinline__ void sts64f(uint32_t a, float x, float y) { asm volatile("st.shared.v2.f32 [%0], {%1,%2};" :: "r"(a), "f"(x), "f"(y) : "memory"); }
__device__ __forceinline__ void sts128(uint32_t a, uint4 v) { asm volatile("st.shared.v4.u32 [%0], {%1,%2,%3,%4};" :: "r"(a), "r"(v.x), "r"(v.y), "r"(v.z), "r"(v.w) : "memory"); }
__device__ __forceinline__ void ldsm4(uint32_t a, uint32_t& r0, uint32_t& r1, uint32_t& r2, uint32_t& r3) {
  asm volatile("ldmatrix.sync.aligned.m8n8.x4.shared.b16 {%0,%1,%2,%3}, [%4];" : "=r"(r0), "=r"(r1), "=r"(r2), "=r"(r3) : "r"(a) : "memory");
}
__device__ __forceinline__ void ldsm4t(uint32_t a, uint32_t& r0, uint32_t& r1, uint32_t& r2, uint32_t& r3) {
  asm volatile("ldmatrix.sync.aligned.m8n8.x4.trans.shared.b16 {%0,%1,%2,%3}, [%4];" : "=r"(r0), "=r"(r1), "=r"(r2), "=r"(r3) : "r"(a) : "memory");
}
__device__ __forceinline__ void stsm4(uint32_t a, uint32_t r0, uint32_t r1, uint32_t r2, uint32_t r3) {
  asm volatile("stmatrix.sync.aligned.m8n8.x4.shared.b16 [%0], {%1,%2,%3,%4};" :: "r"(a), "r"(r0), "r"(r1), "r"(r2), "r"(r3) : "memory");
}
template<int N> __device__ __forceinline__ void fence_regs(float (&d)[N]) {
#pragma unroll
  for (int i = 0; i < N; i++) asm volatile("" : "+f"(d[i]) :: "memory");
}
template<int N> __device__ __forceinline__ void fence_regs(uint32_t (&d)[N]) {
#pragma unroll
  for (int i = 0; i < N; i++) asm volatile("" : "+r"(d[i]) :: "memory");
}
__device__ __forceinline__ void sched_fence(float x, uint32_t dummy) {
  asm volatile("{\n.reg .pred p;\nsetp.eq.u32 p, %0, 0x7fc12345;\n@p st.shared.u32 [%1], %0;\n}\n" :: "r"(__float_as_uint(x)), "r"(dummy) : "memory");
}
#define TS(role, i)
#define TR(obj, role, tag)

struct Prod {
  uint32_t base, mask; int lane, nt;
  __device__ __forceinline__ uint32_t full(int u) const { return base + SM_BAR + 8 * u; }
  __device__ __forceinline__ uint32_t addr(int u) const { return base + u * UNIT; }
  __device__ __forceinline__ void acquire(int u, int n) {
    const int v = u + min(lane, n - 1);
    mbar_wait_all(base + SM_BAR + 128 + 8 * v, (mask >> v) & 1);
    mask ^= ((1u << n) - 1) << u;
    TR(*this, 2, 16 + u);
  }
};
struct Cons {
  uint32_t base, mask; int lane, warp, wg, nt;
  __device__ __forceinline__ uint32_t addr(int u) const { return base + u * UNIT; }
  __device__ __forceinline__ void wait(int u) { TR(*this, wg, 1); mbar_wait(base + SM_BAR + 8 * u, (mask >> u) & 1); mask ^= 1u << u; TR(*this, wg, 2); }
  __device__ __forceinline__ void wait2(int u0, int u1) {
    TR(*this, wg, 1);
    const int v = (lane & 1) ? u1 : u0;
    mbar_wait_all(base + SM_BAR + 8 * v, (mask >> v) & 1); mask ^= (1u << u0) | (1u << u1);
    TR(*this, wg, 2);
  }
  __device__ __forceinline__ void skip(int u) { mask ^= 1u << u; }
  __device__ __forceinline__ void release(int u, int n) { TR(*this, wg, 5); if (lane < n) mbar_arrive(base + SM_BAR + 128 + 8 * (u + lane)); }
  __device__ __forceinline__ void release2(int u, int n) { if (lane < n) mbar_arrive_n(base + SM_BAR + 128 + 8 * (u + lane), 2); }
  __device__ __forceinline__ void signal(int i) { __syncwarp(); if (lane == 0) mbar_arrive(base + SM_SIG + 8 * i); }
  __device__ __forceinline__ void turn() { bar_sync(1 + wg, 256); TR(*this, wg, 3); }
  __device__ __forceinline__ void pass() { bar_arrive(2 - wg, 256); TR(*this, wg, 4); }
};
__device__ __forceinline__ int att_slot(int i) { return i == 0 ? 12 : 2 + 2 * i; }
__device__ __forceinline__ int conv_channel(int cta, int i) {
  return cta < NREG ? CH_EXTRA_TOTAL + cta * CONV_REG + i : (i >> 1) * 8 + (cta - NREG) * 2 + (i & 1);
}

template<int OFF, int N> __device__ __forceinline__ void pack_chunk(const float (&a)[N], float sc0, float sc1, uint4& v0, uint4& v1) {
  v0.x = pack_bf16(a[OFF + 0] * sc0, a[OFF + 1] * sc0); v0.y = pack_bf16(a[OFF + 4] * sc0, a[OFF + 5] * sc0);
  v0.z = pack_bf16(a[OFF + 8] * sc0, a[OFF + 9] * sc0); v0.w = pack_bf16(a[OFF + 12] * sc0, a[OFF + 13] * sc0);
  v1.x = pack_bf16(a[OFF + 2] * sc1, a[OFF + 3] * sc1); v1.y = pack_bf16(a[OFF + 6] * sc1, a[OFF + 7] * sc1);
  v1.z = pack_bf16(a[OFF + 10] * sc1, a[OFF + 11] * sc1); v1.w = pack_bf16(a[OFF + 14] * sc1, a[OFF + 15] * sc1);
}
template<int OFF, int N> __device__ __forceinline__ void pack_chunk(const float (&a)[N], uint4& v0, uint4& v1) {
  v0.x = pack_bf16(a[OFF + 0], a[OFF + 1]); v0.y = pack_bf16(a[OFF + 4], a[OFF + 5]);
  v0.z = pack_bf16(a[OFF + 8], a[OFF + 9]); v0.w = pack_bf16(a[OFF + 12], a[OFF + 13]);
  v1.x = pack_bf16(a[OFF + 2], a[OFF + 3]); v1.y = pack_bf16(a[OFF + 6], a[OFF + 7]);
  v1.z = pack_bf16(a[OFF + 10], a[OFF + 11]); v1.w = pack_bf16(a[OFF + 14], a[OFF + 15]);
}
__device__ __forceinline__ void sq_acc(const uint4& v, uint32_t& a) { a = hfma2(v.x, v.x, a); a = hfma2(v.y, v.y, a); a = hfma2(v.z, v.z, a); a = hfma2(v.w, v.w, a); }
__device__ __forceinline__ float norm2_max(uint32_t a0, uint32_t a1) {
  float n0 = bf_lo(a0) + bf_hi(a0), n1 = bf_lo(a1) + bf_hi(a1);
  n0 += __shfl_xor_sync(~0u, n0, 1); n1 += __shfl_xor_sync(~0u, n1, 1);
  n0 += __shfl_xor_sync(~0u, n0, 2); n1 += __shfl_xor_sync(~0u, n1, 2);
  return __uint_as_float(__reduce_max_sync(~0u, max(__float_as_uint(n0) & 0x7fffffffu, __float_as_uint(n1) & 0x7fffffffu)));
}

struct Pend { uint4 v[16]; uint8_t* d0; uint32_t n0, n1; float kn; };
template<int N> __device__ __forceinline__ void pin(Pend& w) {
#pragma unroll
  for (int i = 0; i < N; i++) asm volatile("" : "+r"(w.v[i].x), "+r"(w.v[i].y), "+r"(w.v[i].z), "+r"(w.v[i].w) :: "memory");
}
template<int J> __device__ __forceinline__ void flush_o(const Pend& w) {
  uint8_t* d = w.d0 + (J >> 1) * 16384 + (J & 1) * 512;
  *(uint4*)d = w.v[2 * J]; *(uint4*)(d + 1024) = w.v[2 * J + 1];
}
template<int J> __device__ __forceinline__ void flush_kv(Pend& w) {
  uint8_t* d = w.d0 + (J >> 2) * 32768 + (J & 3) * 512;
  *(uint4*)d = w.v[2 * J]; *(uint4*)(d + 2048) = w.v[2 * J + 1];
  if ((J & 3) == 0) w.n0 = w.n1 = 0;
  sq_acc(w.v[2 * J], w.n0); sq_acc(w.v[2 * J + 1], w.n1);
  if (J == 3) w.kn = norm2_max(w.n0, w.n1);
}
__device__ __forceinline__ void finish_kv(const Pend& w, float* slot, int lane) {
  const float vn = norm2_max(w.n0, w.n1);
  if (lane == 0) *slot = (vn <= 1.0e30f && vn >= 1.0e-30f) ? w.kn : __uint_as_float(0x7f800000u);
}
template<int KS> __device__ __forceinline__ void kv_step(Cons& c, float (&acc)[128]) {
  constexpr int u = 3 * (KS & 3);
  c.wait(u);
  const uint64_t da = mkdesc(c.addr(u) + c.wg * 8192, 16, 1024, 1), db = mkdesc(c.addr(u + 1), 8192, 1024, 1);
  if (KS > 0) { wg_wait<0>(); c.release(3 * ((KS - 1) & 3), 3); }
  c.turn();
  wg_fence();
#pragma unroll
  for (int kk = 0; kk < 4; kk++) wgmma_ss_n256<1>(acc, da + kk * 2, db + kk * 128, !(KS == 0 && kk == 0));
  wg_commit();
  c.pass();
}
__device__ __forceinline__ void pack_kv(Cons& c, float (&acc)[128], Pend& w, int h, int blk) {
  wg_wait<0>(); fence_regs(acc);
  c.release(9, 3);
  pack_chunk<0>(acc, w.v[0], w.v[1]);    pack_chunk<16>(acc, w.v[2], w.v[3]);    pack_chunk<32>(acc, w.v[4], w.v[5]);    pack_chunk<48>(acc, w.v[6], w.v[7]);
  pack_chunk<64>(acc, w.v[8], w.v[9]);   pack_chunk<80>(acc, w.v[10], w.v[11]);  pack_chunk<96>(acc, w.v[12], w.v[13]);  pack_chunk<112>(acc, w.v[14], w.v[15]);
  w.d0 = g_KV + (uint32_t)((h * 16 + blk) * 65536 + (c.wg * 8 + c.warp * 2) * 2048 + (c.lane & 3) * 128 + (c.lane >> 2) * 16);
  pin<16>(w);
}
__device__ __forceinline__ void cons_kv(Cons& c, int h, int g, Pend& w, bool pend_o) {
  float acc[128];
  kv_step<0>(c, acc); if (pend_o) flush_o<0>(w);
  kv_step<1>(c, acc); if (pend_o) flush_o<1>(w);
  kv_step<2>(c, acc); if (pend_o) flush_o<2>(w);
  kv_step<3>(c, acc); if (pend_o) { flush_o<3>(w); c.signal(SIG_CTX); }
  kv_step<4>(c, acc); kv_step<5>(c, acc); kv_step<6>(c, acc); kv_step<7>(c, acc);
  pack_kv(c, acc, w, h, 2 * g);
  kv_step<0>(c, acc); flush_kv<0>(w); kv_step<1>(c, acc); flush_kv<1>(w); kv_step<2>(c, acc); flush_kv<2>(w); flush_kv<3>(w);
  kv_step<3>(c, acc); flush_kv<4>(w); kv_step<4>(c, acc); flush_kv<5>(w); kv_step<5>(c, acc); flush_kv<6>(w); kv_step<6>(c, acc); flush_kv<7>(w);
  finish_kv(w, g_kn2 + h * 128 + 2 * g * 8 + c.wg * 4 + c.warp, c.lane);
  kv_step<7>(c, acc);
  pack_kv(c, acc, w, h, 2 * g + 1);
}
template<bool FIRST> __device__ __forceinline__ void q_step(Cons& c, float (&a)[64], float (&b)[64], int ks) {
  const int u = 3 * (ks & 3);
  c.wait(u);
  const uint64_t da = mkdesc(c.addr(u) + c.wg * 8192, 16, 1024, 1), db = mkdesc(c.addr(u + 2), 8192, 1024, 1);
  const uint64_t da2 = mkdesc(c.addr(u + 1) + (1 - c.wg) * 8192, 16, 1024, 1);
  if (!FIRST) { wg_wait<0>(); c.release(3 * ((ks - 1) & 3), 3); }
  c.turn();
  wg_fence();
#pragma unroll
  for (int kk = 0; kk < 4; kk++) wgmma_ss_n128<1>(a, da + kk * 2, db + kk * 128, !(FIRST && kk == 0));
#pragma unroll
  for (int kk = 0; kk < 4; kk++) wgmma_ss_n128<1>(b, da2 + kk * 2, db + kk * 128, !(FIRST && kk == 0));
  wg_commit();
  c.pass();
}
__device__ __forceinline__ void flush_kv_all(Cons& c, Pend& w, int h, int g) {
  flush_kv<0>(w); flush_kv<1>(w); flush_kv<2>(w); flush_kv<3>(w); flush_kv<4>(w); flush_kv<5>(w); flush_kv<6>(w); flush_kv<7>(w);
  finish_kv(w, g_kn2 + h * 128 + (2 * g + 1) * 8 + c.wg * 4 + c.warp, c.lane);
  c.signal(SIG_KV + (h & 1));
}
__device__ __forceinline__ int cons_q(Cons& c, int h, int g, Pend& w, bool pend_kv) {
  float a[64], b[64];
  q_step<true>(c, a, b, 0);  if (pend_kv) flush_kv<0>(w);
  q_step<false>(c, a, b, 1); if (pend_kv) { flush_kv<1>(w); flush_kv<2>(w); }
  q_step<false>(c, a, b, 2); if (pend_kv) flush_kv<3>(w);
  q_step<false>(c, a, b, 3); if (pend_kv) { flush_kv<4>(w); flush_kv<5>(w); }
  q_step<false>(c, a, b, 4); if (pend_kv) flush_kv<6>(w);
  q_step<false>(c, a, b, 5);
  if (pend_kv) { flush_kv<7>(w); finish_kv(w, g_kn2 + h * 128 + (2 * g + 1) * 8 + c.wg * 4 + c.warp, c.lane); c.signal(SIG_KV + (h & 1)); }
  TS(c.wg, 20);
#pragma unroll 1
  for (int ks = 6; ks < 16; ks++) q_step<false>(c, a, b, ks);
  TS(c.wg, 21);
  c.wait(0);
  wg_wait<0>(); fence_regs(a); fence_regs(b);
  c.release(9, 3);
  const uint32_t q0 = c.addr(0) + (c.wg * 8 + c.warp * 2) * 2048 + (c.lane & 3) * 128 + (c.lane >> 2) * 16;
  uint32_t a0 = 0, a1 = 0, e0 = 0, e1 = 0;
  uint4 v0, v1;
#define Q_CHUNK(J) pack_chunk<16 * J>(a, QSCALE, QSCALE, v0, v1); sts128(q0 + J * 512, v0); sts128(q0 + J * 512 + 2048, v1); sq_acc(v0, a0); sq_acc(v1, a1); \
  pack_chunk<16 * J>(b, QSCALE, QSCALE, v0, v1); sts128(q0 + 32768 + J * 512, v0); sts128(q0 + 32768 + J * 512 + 2048, v1); sq_acc(v0, e0); sq_acc(v1, e1);
  Q_CHUNK(0) Q_CHUNK(1) Q_CHUNK(2) Q_CHUNK(3)
#undef Q_CHUNK
  TR(c, c.wg, 40);
  fence_async_smem();
  TR(c, c.wg, 41);
  const float qa = norm2_max(a0, a1), qb = norm2_max(e0, e1);
  const float kn = __uint_as_float(lds32(c.base + SM_KMAX + 4 * (h & 1)));
  TR(c, c.wg, 42);
  return __shfl_sync(~0u, bar_and(3 + c.wg, 128, (qa * kn <= BOUND2) && (qb * kn <= BOUND2)), 0);
}

template<bool HALF> __device__ __forceinline__ void issue_qk(float (&s)[64], uint32_t qaddr, uint32_t kaddr) {
  const uint64_t da = mkdesc(qaddr, 128, 2048, 0), db = mkdesc(kaddr, 128, 2048, 0);
#pragma unroll
  for (int kk = 0; kk < 8; kk++) {
    if (HALF) wgmma_ss_n64<0>(reinterpret_cast<float (&)[32]>(s), da + kk * 16, db + kk * 16, kk > 0);
    else wgmma_ss_n128<0>(s, da + kk * 16, db + kk * 16, kk > 0);
  }
  wg_commit();
}
template<bool HALF> __device__ __forceinline__ void issue_pv(float (&o)[64], uint32_t (&p)[32], uint32_t vaddr, int acc) {
  const uint64_t db = mkdesc(vaddr, 2048, 128, 0);
#pragma unroll
  for (int kk = 0; kk < (HALF ? 4 : 8); kk++) wgmma_rs_n128<1>(o, p[4 * kk], p[4 * kk + 1], p[4 * kk + 2], p[4 * kk + 3], db + kk * 256, kk > 0 ? 1 : acc);
  wg_commit();
}
template<int A, int B> __device__ __forceinline__ void exp_rng(float (&s)[64]) {
#pragma unroll
  for (int i = 4 * A; i < 4 * B; i++) s[i] = ex2(s[i]);
}
template<int A, int B> __device__ __forceinline__ void sum_rng(const float (&s)[64], float (&l)[4]) {
#pragma unroll
  for (int i = A; i < B; i++) { l[0] += s[4 * i]; l[1] += s[4 * i + 1]; l[2] += s[4 * i + 2]; l[3] += s[4 * i + 3]; }
}
template<int N> __device__ __forceinline__ void cvt_p(const float (&s)[64], uint32_t (&p)[32]) {
#pragma unroll
  for (int i = 0; i < N; i++) p[i] = pack_bf16(s[2 * i], s[2 * i + 1]);
}
template<int K0> __device__ __forceinline__ void mask_half(float (&s)[64], int warp, int lane) {
  const int l0 = warp + (2 * (lane & 3) <= (lane >> 2)), l1 = warp + (2 * (lane & 3) < (lane >> 2));
#pragma unroll
  for (int k = 0; k < 4; k++) {
    float* t = s + 8 * (K0 + k);
    if (k >= l0) { t[0] = -INFINITY; t[6] = -INFINITY; }
    if (k >= l1) { t[1] = -INFINITY; t[7] = -INFINITY; }
    if (k > warp) { t[2] = -INFINITY; t[3] = -INFINITY; }
    if (k >= warp) { t[4] = -INFINITY; t[5] = -INFINITY; }
  }
}
__device__ __forceinline__ void mask_diag(float (&s)[64], int lim) {
#pragma unroll
  for (int i = 0; i < 16; i++) {
    if (8 * i > lim) s[4 * i] = -INFINITY;
    if (8 * i + 1 > lim) s[4 * i + 1] = -INFINITY;
    if (8 * i - 8 > lim) s[4 * i + 2] = -INFINITY;
    if (8 * i - 7 > lim) s[4 * i + 3] = -INFINITY;
  }
}
__device__ __forceinline__ void pack_o(const float (&o)[64], float l0, float l1, Pend& w, uint8_t* dst) {
  l0 += __shfl_xor_sync(~0u, l0, 1); l1 += __shfl_xor_sync(~0u, l1, 1);
  l0 += __shfl_xor_sync(~0u, l0, 2); l1 += __shfl_xor_sync(~0u, l1, 2);
  const float i0 = __fdividef(1.f, l0), i1 = __fdividef(1.f, l1);
  pack_chunk<0>(o, i0, i1, w.v[0], w.v[1]); pack_chunk<16>(o, i0, i1, w.v[2], w.v[3]);
  pack_chunk<32>(o, i0, i1, w.v[4], w.v[5]); pack_chunk<48>(o, i0, i1, w.v[6], w.v[7]);
  w.d0 = dst;
  pin<8>(w);
}
__device__ __forceinline__ void flush_o_all(const Pend& w) { flush_o<0>(w); flush_o<1>(w); flush_o<2>(w); flush_o<3>(w); }
__device__ __forceinline__ void softmax_safe(float (&s)[64], float& m0, float& m1, float& sc0, float& sc1) {
  float a0 = m0, a1 = m1;
#pragma unroll
  for (int i = 0; i < 16; i++) { a0 = fmaxf(a0, fmaxf(s[4 * i], s[4 * i + 1])); a1 = fmaxf(a1, fmaxf(s[4 * i + 2], s[4 * i + 3])); }
  a0 = fmaxf(a0, __shfl_xor_sync(~0u, a0, 1)); a1 = fmaxf(a1, __shfl_xor_sync(~0u, a1, 1));
  a0 = fmaxf(a0, __shfl_xor_sync(~0u, a0, 2)); a1 = fmaxf(a1, __shfl_xor_sync(~0u, a1, 2));
  sc0 = ex2(m0 - a0); sc1 = ex2(m1 - a1);
  m0 = a0; m1 = a1;
#pragma unroll
  for (int i = 0; i < 16; i++) { s[4 * i] -= a0; s[4 * i + 1] -= a0; s[4 * i + 2] -= a1; s[4 * i + 3] -= a1; }
}
struct Att {
  float s[64], o[64], l[4]; uint32_t p[32];
  int si, acc; uint32_t qaddr;
};
enum { QK_FULL = 0, QK_DIAG_LO = 1, QK_DIAG_HI = 2 };
template<int QK, bool PVHALF, bool SWITCH, bool FLUSH>
__device__ __forceinline__ void att_step(Cons& c, Att& a, Pend& w, int relq, uint8_t* dst) {
  const int uk = att_slot(a.si); a.si = a.si == 4 ? 0 : a.si + 1;
  const int uv = att_slot(a.si); a.si = a.si == 4 ? 0 : a.si + 1;
  c.wait2(uk, uv);
  c.turn();
  fence_regs(a.o); fence_regs(a.p);
  wg_fence();
  issue_qk<QK == QK_DIAG_LO>(a.s, a.qaddr, c.addr(uk));
  issue_pv<PVHALF>(a.o, a.p, c.addr(uv), a.acc);
  c.pass();
  if (FLUSH) flush_o_all(w);
  a.acc = 1;
  wg_wait<1>();
  if (QK == QK_DIAG_LO) fence_regs(reinterpret_cast<float (&)[32]>(a.s)); else fence_regs(a.s);
  c.release(uk, 2);
  if (relq >= 0) c.release(relq, 2);
  float lo0, lo1;
  if (SWITCH) { lo0 = a.l[0] + a.l[1]; lo1 = a.l[2] + a.l[3]; a.l[0] = a.l[1] = a.l[2] = a.l[3] = 0.f; }
  constexpr int SPLIT = QK == QK_DIAG_LO ? 8 : (PVHALF ? 6 : 10);
  if (QK == QK_DIAG_LO) mask_half<0>(a.s, c.warp, c.lane);
  if (QK == QK_DIAG_HI) mask_half<4>(a.s, c.warp, c.lane);
  exp_rng<0, SPLIT>(a.s); sum_rng<0, SPLIT>(a.s, a.l);
  sched_fence((a.l[0] + a.l[1]) + (a.l[2] + a.l[3]), c.base + SM_DUMMY);
  wg_wait<0>(); fence_regs(a.o); fence_regs(a.p);
  c.release(uv, 2);
  if (QK == QK_DIAG_LO) cvt_p<16>(a.s, a.p);
  else { exp_rng<SPLIT, 16>(a.s); sum_rng<SPLIT, 16>(a.s, a.l); cvt_p<32>(a.s, a.p); }
  if (SWITCH) { pack_o(a.o, lo0, lo1, w, dst); a.acc = 0; }
}
template<bool PVHALF> __device__ __forceinline__ void att_last(Cons& c, Att& a, Pend& w, uint8_t* dst) {
  const int uv = att_slot(a.si);
  c.wait(uv);
  c.turn();
  fence_regs(a.o); fence_regs(a.p);
  wg_fence();
  issue_pv<PVHALF>(a.o, a.p, c.addr(uv), a.acc);
  c.pass();
  wg_wait<0>(); fence_regs(a.o); fence_regs(a.p);
  c.release(uv, 2);
  pack_o(a.o, a.l[0] + a.l[1], a.l[2] + a.l[3], w, dst);
}
__device__ __forceinline__ uint8_t* ctx_ptr(const Cons& c, int h, int qb, int rowhalf) {
  return g_ctx + (uint32_t)((qb * 64 + 2 * h) * 16384 + (rowhalf * 8 + c.warp * 2) * 1024 + (c.lane & 3) * 128 + (c.lane >> 2) * 16);
}
__device__ __forceinline__ void att_first(Cons& c, Att& a) {
  a.si = 1; a.acc = 0; a.qaddr = c.addr(0) + c.wg * 16384;
  c.wait(12);
  c.turn();
  wg_fence();
  issue_qk<false>(a.s, a.qaddr, c.addr(12));
  c.pass();
#pragma unroll
  for (int i = 0; i < 64; i++) a.o[i] = 0.f;
  a.l[0] = a.l[1] = a.l[2] = a.l[3] = 0.f;
  wg_wait<0>(); fence_regs(a.s);
  c.release(12, 2);
}
__device__ __forceinline__ void cons_att_fast(Cons& c, int h, int g, Pend& w) {
  Att a;
  att_first(c, a);
  exp_rng<0, 16>(a.s); sum_rng<0, 16>(a.s, a.l); cvt_p<32>(a.s, a.p);
  for (int t = 0; t < 2; t++) {
    for (int j = t == 0 ? 14 - g : g - 1; j > 0; j--) att_step<QK_FULL, false, false, false>(c, a, w, (t == 1 && j == 1) ? 2 : -1, nullptr);
    if (t == 0) {
      if (c.wg == 0) {
        att_step<QK_DIAG_LO, false, false, false>(c, a, w, 0, nullptr);
        a.qaddr += 32768;
        if (h < 64) att_step<QK_DIAG_HI, true, true, false>(c, a, w, g == 0 ? 2 : -1, ctx_ptr(c, h, 15 - g, 0));
        if (g > 0) att_step<QK_FULL, false, false, true>(c, a, w, g == 1 ? 2 : -1, nullptr); else flush_o_all(w);
      } else {
        att_step<QK_DIAG_HI, false, false, false>(c, a, w, 0, nullptr);
        a.qaddr += 32768;
        att_step<QK_DIAG_LO, false, true, false>(c, a, w, g == 0 ? 2 : -1, ctx_ptr(c, h, 15 - g, 1));
        if (g > 0) att_step<QK_FULL, true, false, true>(c, a, w, g == 1 ? 2 : -1, nullptr);
        else {
          flush_o_all(w);
#pragma unroll
          for (int i = 16; i < 32; i++) a.p[i] = 0;
        }
      }
    }
  }
  att_last<false>(c, a, w, ctx_ptr(c, h, g, 1 - c.wg));
}
__device__ __forceinline__ void cons_att_safe(Cons& c, int h, int g, Pend& w) {
  Att a;
  float m0 = -INFINITY, m1 = -INFINITY, sc0, sc1;
  att_first(c, a);
  softmax_safe(a.s, m0, m1, sc0, sc1);
  exp_rng<0, 16>(a.s); sum_rng<0, 16>(a.s, a.l); cvt_p<32>(a.s, a.p);
  for (int st = 1; st <= 16; st++) {
    const bool sw = st == 16 - g;
    if (sw) a.qaddr += 32768;
    const int uk = att_slot(a.si); a.si = a.si == 4 ? 0 : a.si + 1;
    const int uv = att_slot(a.si); a.si = a.si == 4 ? 0 : a.si + 1;
    c.wait2(uk, uv);
    c.turn();
    fence_regs(a.o); fence_regs(a.p);
    wg_fence();
    issue_qk<false>(a.s, a.qaddr, c.addr(uk));
    issue_pv<false>(a.o, a.p, c.addr(uv), a.acc);
    c.pass();
    a.acc = 1;
    wg_wait<0>(); fence_regs(a.s); fence_regs(a.o); fence_regs(a.p);
    c.release(uk, 2); c.release(uv, 2);
    if (st == 15 - g) c.release(0, 2);
    if (st == 16) c.release(2, 2);
    if (sw) {
      pack_o(a.o, a.l[0] + a.l[1], a.l[2] + a.l[3], w, ctx_ptr(c, h, 15 - g, c.wg)); flush_o_all(w);
      a.acc = 0; m0 = m1 = -INFINITY; a.l[0] = a.l[1] = a.l[2] = a.l[3] = 0.f;
    }
    if (sw || st == 15 - g) mask_diag(a.s, (sw ? 1 - c.wg : c.wg) * 64 + c.warp * 16 + (c.lane >> 2) - 2 * (c.lane & 3));
    softmax_safe(a.s, m0, m1, sc0, sc1);
    a.l[0] *= sc0; a.l[1] *= sc0; a.l[2] *= sc1; a.l[3] *= sc1;
    exp_rng<0, 16>(a.s); sum_rng<0, 16>(a.s, a.l); cvt_p<32>(a.s, a.p);
    if (!sw) {
#pragma unroll
      for (int i = 0; i < 16; i++) { a.o[4 * i] *= sc0; a.o[4 * i + 1] *= sc0; a.o[4 * i + 2] *= sc1; a.o[4 * i + 3] *= sc1; }
    }
  }
  att_last<false>(c, a, w, ctx_ptr(c, h, g, 1 - c.wg));
}

constexpr int CV_H = 1024, CV_U = 5120, CV_ROW = 1056;
__device__ __forceinline__ void cons_conv(Cons& c, const Params& P, int cta, int nch) {
  const int r = c.lane >> 2, q = c.lane & 3, tid = c.warp * 32 + c.lane;
  const uint32_t part = c.addr(4) + c.wg * (32 * CV_ROW) + 32;
  c.wait(4);
  sts64f(part + (tid >> 2) * CV_ROW - 32 + q * 8, 0.f, 0.f);
  const uint32_t aoff = CV_U + ((r & 1) ? 0 : UPITCH) + 4 * (((2039 - r) >> 1) + q - 8 * c.warp);
  const uint32_t wq = part + (c.warp * 8 + r) * CV_ROW + q * 8, rq = part + tid * 8;
  for (int i = 0; i < nch / 2; i++) {
    const int ch = conv_channel(cta, 2 * i + c.wg);
    const int u = 2 * c.wg + (i & 1);
    c.wait(u); c.skip(u ^ 2);
    const uint32_t ub = c.addr(u);
    uint32_t a[64];
#pragma unroll
    for (int G = 0; G < 16; G++) {
      a[4 * G + 0] = lds32(ub + aoff - 256 * G);
      a[4 * G + 1] = lds32(ub + aoff - 256 * G - 128);
      a[4 * G + 2] = lds32(ub + aoff - 256 * G + 16);
      a[4 * G + 3] = lds32(ub + aoff - 256 * G - 128 + 16);
    }
    float d0[32], d1[32], d2[32], d3[32];
    const uint64_t db = mkdesc(ub + CV_H - 16, 16, 128, 0);
    c.turn();
    wg_fence();
#pragma unroll
    for (int G = 0; G < 4; G++) wgmma_rs_n64<0>(d0, a[4 * G], a[4 * G + 1], a[4 * G + 2], a[4 * G + 3], db - 16 * G, G > 0);
#pragma unroll
    for (int G = 0; G < 8; G++) wgmma_rs_n64<0>(d1, a[4 * G], a[4 * G + 1], a[4 * G + 2], a[4 * G + 3], db + 64 - 16 * G, G > 0);
#pragma unroll
    for (int G = 0; G < 12; G++) wgmma_rs_n64<0>(d2, a[4 * G], a[4 * G + 1], a[4 * G + 2], a[4 * G + 3], db + 128 - 16 * G, G > 0);
#pragma unroll
    for (int G = 0; G < 16; G++) wgmma_rs_n64<0>(d3, a[4 * G], a[4 * G + 1], a[4 * G + 2], a[4 * G + 3], db + 192 - 16 * G, G > 0);
    wg_commit();
    c.pass();
    const uint32_t D2 = (uint32_t)__bfloat16_as_ushort(P.D[ch]) * 0x10001u;
    wg_wait<0>(); fence_regs(d0); fence_regs(d1); fence_regs(d2); fence_regs(d3); fence_regs(a);
    float c0 = 0.f, c1 = 0.f;
#define CV_ST(DD, R) _Pragma("unroll") for (int n = 0; n < 8; n++) { sts64f(wq + (R * 64 + n * 8) * 4, DD[4 * n] + c0, DD[4 * n + 1] + c1); c0 = DD[4 * n + 2]; c1 = DD[4 * n + 3]; }
    CV_ST(d0, 0) CV_ST(d1, 1) CV_ST(d2, 2) CV_ST(d3, 3)
#undef CV_ST
    bar_sync(3 + c.wg, 128);
    float y0[8], y1[8];
#pragma unroll
    for (int rr = 0; rr < 8; rr++) { const float2 v = lds64f(rq + rr * CV_ROW); y0[rr] = v.x; y1[rr] = v.y; }
#pragma unroll
    for (int w = 1; w < 4; w++) {
#pragma unroll
      for (int rr = 0; rr < 8; rr++) { const float2 v = lds64f(rq + (w * 8 + rr) * CV_ROW - w * 8); y0[rr] += v.x; y1[rr] += v.y; }
    }
    const uint4 ua = lds128(ub + CV_U + 4064 - 32 * tid + 16), uc = lds128(ub + CV_U + 4064 - 32 * tid);
    uint4 z0, z1;
    z0.x = hadd2(pack_bf16(y0[0], y0[1]), hmul2(__byte_perm(ua.w, 0, 0x1032), D2));
    z0.y = hadd2(pack_bf16(y0[2], y0[3]), hmul2(__byte_perm(ua.z, 0, 0x1032), D2));
    z0.z = hadd2(pack_bf16(y0[4], y0[5]), hmul2(__byte_perm(ua.y, 0, 0x1032), D2));
    z0.w = hadd2(pack_bf16(y0[6], y0[7]), hmul2(__byte_perm(ua.x, 0, 0x1032), D2));
    z1.x = hadd2(pack_bf16(y1[0], y1[1]), hmul2(__byte_perm(uc.w, 0, 0x1032), D2));
    z1.y = hadd2(pack_bf16(y1[2], y1[3]), hmul2(__byte_perm(uc.z, 0, 0x1032), D2));
    z1.z = hadd2(pack_bf16(y1[4], y1[5]), hmul2(__byte_perm(uc.y, 0, 0x1032), D2));
    z1.w = hadd2(pack_bf16(y1[6], y1[7]), hmul2(__byte_perm(uc.x, 0, 0x1032), D2));
    uint4* zp = (uint4*)(g_z + (size_t)ch * 2048 + tid * 16);
    zp[0] = z0; zp[1] = z1;
    __syncwarp();
    c.release2(u, 1);
    bar_sync(3 + c.wg, 128);
    if ((i & 15) == 15 || i == nch / 2 - 1) c.signal(SIG_Z + (i >> 4));
  }
  c.release(4, 5);
}

constexpr int OUT_XZ_AT = 58;
__device__ __forceinline__ int out_slot(int i) { return i < 2 ? 10 + 2 * i : 2 * (i - 2); }
__device__ __forceinline__ void cons_out(Cons& c, const Maps& M, int mb, int nb) {
  float acc[64];
  uint32_t ga[32];
  int si = 0, pu, u;
#define OUT_STEP(FIRST) { \
    u = out_slot(si); si = si == 6 ? 0 : si + 1; \
    c.wait(u); \
    const uint64_t da = mkdesc(c.addr(u) + c.wg * 8192, 128, 1024, 0), db = mkdesc(c.addr(u + 1), 8192, 1024, 1); \
    wg_fence(); \
    _Pragma("unroll") for (int kk = 0; kk < 4; kk++) wgmma_ss_n128<1>(acc, da + kk * 16, db + kk * 128, !(FIRST && kk == 0)); \
    wg_commit(); }
  OUT_STEP(true)
  pu = u;
#pragma unroll 1
  for (int ks = 1; ks <= OUT_XZ_AT; ks++) { OUT_STEP(false) wg_wait<1>(); c.release(pu, 2); pu = u; }
  const int ux = out_slot(si); si = si == 6 ? 0 : si + 1;
  const int uz = out_slot(si); si = si == 6 ? 0 : si + 1;
  OUT_STEP(false)
  c.wait2(ux, uz);
  const int row = mb * 128 + c.wg * 64 + c.warp * 16 + (c.lane >> 2);
  const float g0 = __ldcg(g_gate + row), g1 = __ldcg(g_gate + row + 8);
  const uint32_t gg0 = pack_bf16(g0, g0), gg1 = pack_bf16(g1, g1);
  const uint32_t og0 = pack_bf16(1.f - g0, 1.f - g0), og1 = pack_bf16(1.f - g1, 1.f - g1);
  const int xr = c.wg * 64 + c.warp * 16 + (c.lane & 15);
  const uint32_t xa = c.addr(ux) + xr * 128, xs = xr & 7, xh = c.lane >> 4;
  const int zr = (c.lane & 7) + ((c.lane >> 4) << 3);
  const uint32_t za = c.addr(uz) + c.wg * 16384 + zr * 128 + (((c.warp * 2 + ((c.lane >> 3) & 1)) ^ (zr & 7)) << 4);
#pragma unroll
  for (int i = 0; i < 8; i++) {
    uint32_t x0, x1, x2, x3, z0, z1, z2, z3;
    ldsm4(xa + (i >> 2) * 16384 + ((((i & 3) * 2 + xh) ^ xs) << 4), x0, x1, x2, x3);
    ldsm4t(za + i * 2048, z0, z1, z2, z3);
    ga[4 * i + 0] = hmul2(gg0, hmul2(x0, z0)); ga[4 * i + 1] = hmul2(gg1, hmul2(x1, z1));
    ga[4 * i + 2] = hmul2(gg0, hmul2(x2, z2)); ga[4 * i + 3] = hmul2(gg1, hmul2(x3, z3));
  }
  wg_wait<1>(); c.release(pu, 2); pu = u;
#pragma unroll 1
  for (int ks = OUT_XZ_AT + 2; ks < 64; ks++) { OUT_STEP(false) wg_wait<1>(); c.release(pu, 2); pu = u; }
#undef OUT_STEP
  wg_wait<0>(); fence_regs(acc);
#pragma unroll
  for (int i = 0; i < 8; i++) {
    const uint32_t r0 = hadd2(ga[4 * i + 0], hmul2(og0, pack_bf16(acc[8 * i + 0], acc[8 * i + 1])));
    const uint32_t r1 = hadd2(ga[4 * i + 1], hmul2(og1, pack_bf16(acc[8 * i + 2], acc[8 * i + 3])));
    const uint32_t r2 = hadd2(ga[4 * i + 2], hmul2(og0, pack_bf16(acc[8 * i + 4], acc[8 * i + 5])));
    const uint32_t r3 = hadd2(ga[4 * i + 3], hmul2(og1, pack_bf16(acc[8 * i + 6], acc[8 * i + 7])));
    stsm4(xa + (i >> 2) * 16384 + ((((i & 3) * 2 + xh) ^ xs) << 4), r0, r1, r2, r3);
  }
  fence_async_smem();
  __syncwarp();
  if (c.lane < 2) {
    const int r0 = c.wg * 64 + c.warp * 16;
    tma2d_store(&M.out, c.addr(ux) + c.lane * 16384 + r0 * 128, nb * 128 + c.lane * 64, mb * 128 + r0);
    asm volatile("cp.async.bulk.commit_group;\ncp.async.bulk.wait_group.read 0;" ::: "memory");
  }
}

__device__ __forceinline__ void prod_conv(Prod& p, const Maps& M, int cta, int nch) {
  p.acquire(4, 5);
  if (elect()) mbar_arrive(p.full(4));
  int ready = -1;
#pragma unroll 1
  for (int i = 0; i < nch; i++) {
    const int ch = conv_channel(cta, i);
    const int u = 2 * (i & 1) + ((i >> 1) & 1);
    if ((ch >> 5) != ready) { ready = ch >> 5; if (cta < NREG) mbar_wait(p.base + SM_RDY + 8 * RDY_U, 0); else cnt_wait(g_cnt + (C_U + ready) * CSTRIDE, 128); }
    p.acquire(u, 1);
    if (elect()) {
      mbar_expect(p.full(u), 5120 + UCH);
      tma3d(p.addr(u), &M.h, 0, -8, ch, p.full(u));
      bulk_g2s(p.addr(u) + CV_U, g_u + (size_t)ch * UCH, UCH, p.full(u));
    }
  }
}
template<int MASK> __device__ __forceinline__ void producer(const Maps& M, const Params& P, uint32_t base, int cta, int lane) {
  Prod p{base, 0xffffffffu, lane, (cta * 3 + 2) * 2048};
  if (cta >= NREG) { if (MASK & PH_CONV) prod_conv(p, M, cta, CONV_EXTRA); return; }
  const int g = cta & 7, j = cta >> 3;
#pragma unroll 1
  for (int half = 0; half < 2; half++) {
    const int h = 2 * j + half;
    if (MASK & PH_KV) {
#pragma unroll 1
      for (int it = 0; it < 16; it++) {
        const int u = 3 * (it & 3), ks = it & 7;
        p.acquire(u, 3);
        if (elect()) {
          mbar_expect(p.full(u), 3 * UNIT);
          tma2d(p.addr(u), &M.c, ks * 64, (2 * g + (it >> 3)) * 128, p.full(u));
          tma3d(p.addr(u + 1), &M.wk, 0, ks * 64, 2 * h, p.full(u));
          tma3d(p.addr(u + 2), &M.wv, 0, ks * 64, 2 * h, p.full(u));
        }
      }
    }
    if (MASK & PH_ATT) {
#pragma unroll 1
      for (int ks = 0; ks < 16; ks++) {
        const int u = 3 * (ks & 3);
        p.acquire(u, 3);
        if (elect()) {
          mbar_expect(p.full(u), 3 * UNIT);
          tma2d(p.addr(u), &M.x, ks * 64, (15 - g) * 128, p.full(u));
          tma2d(p.addr(u + 1), &M.x, ks * 64, g * 128, p.full(u));
          tma3d(p.addr(u + 2), &M.wq, 0, ks * 64, 2 * h, p.full(u));
        }
      }
      TS(2, 8 * half + 0);
      mbar_wait(base + SM_RDY + 8 * (RDY_KV + half), 0);
      TS(2, 8 * half + 1);
      const uint8_t* Kh = g_KV + (size_t)h * 16 * 65536;
      const uint8_t* Vh = Kh + 32768;
      int si = 0, pv = 0;
#pragma unroll 1
      for (int s = 0; s <= 17; s++) {
        const int blk = s <= 15 - g ? s : 16 - s;
        if (s < 17) {
          const int u = att_slot(si); si = si == 4 ? 0 : si + 1;
          p.acquire(u, 2);
          if (elect()) { mbar_expect(p.full(u), 32768); bulk_g2s(p.addr(u), Kh + (size_t)blk * 65536, 32768, p.full(u)); }
        }
        if (s == 0) {
          p.acquire(0, 4);
          if (elect()) mbar_arrive(p.full(0));
        } else {
          const int u = att_slot(si); si = si == 4 ? 0 : si + 1;
          p.acquire(u, 2);
          if (elect()) { mbar_expect(p.full(u), 32768); bulk_g2s(p.addr(u), Vh + (size_t)pv * 65536, 32768, p.full(u)); }
        }
        pv = blk;
      }
    }
  }
  if (MASK & PH_CONV) prod_conv(p, M, cta, CONV_REG);
  if (MASK & PH_OUT) {
    const int mb = j < 8 ? g : 15 - g, nb = j & 7;
    int si = 0;
#pragma unroll 1
    for (int ks = 0; ks < 64; ks++) {
      if ((ks & 31) == 0) { TS(2, 16 + (ks >> 4)); mbar_wait(base + SM_RDY + 8 * (RDY_CTX + (ks >> 5)), 0); TS(2, 17 + (ks >> 4)); }
      const int kb = ((ks & 31) >> 1) * 4 + (ks >> 5) * 2 + (ks & 1);
      const int u = out_slot(si); si = si == 6 ? 0 : si + 1;
      p.acquire(u, 2);
      if (elect()) {
        mbar_expect(p.full(u), 2 * UNIT);
        bulk_g2s(p.addr(u), g_ctx + (size_t)(mb * 64 + kb) * 16384, UNIT, p.full(u));
        tma3d(p.addr(u + 1), &M.wo, 0, kb * 64, 2 * nb, p.full(u));
      }
      if (ks == OUT_XZ_AT) {
        const int ux = out_slot(si); si = si == 6 ? 0 : si + 1;
        const int uz = out_slot(si); si = si == 6 ? 0 : si + 1;
        p.acquire(ux, 2);
        if (elect()) {
          mbar_expect(p.full(ux), 2 * UNIT);
          tma2d(p.addr(ux), &M.x, nb * 128, mb * 128, p.full(ux));
          tma2d(p.addr(ux + 1), &M.x, nb * 128 + 64, mb * 128, p.full(ux));
        }
        TS(2, 20);
        mbar_wait(base + SM_RDY + 8 * RDY_Z, 0);
        TS(2, 21);
        p.acquire(uz, 2);
        if (elect()) {
          mbar_expect(p.full(uz), 2 * UNIT);
          tma2d(p.addr(uz), &M.z, mb * 128, nb * 128, p.full(uz));
          tma2d(p.addr(uz + 1), &M.z, mb * 128 + 64, nb * 128, p.full(uz));
        }
      }
    }
  }
}

template<int MASK> __device__ __forceinline__ void sync_agent(const Params& P, uint32_t base, int cta, int lane) {
#define PUBLISH(SIG, CNT, N) { mbar_wait_slow(base + SM_SIG + 8 * (SIG), 0); if (lane == 0) cnt_publish(g_cnt + (CNT) * CSTRIDE, N); __syncwarp(); }
#define READY(RDY) { __syncwarp(); if (lane == 0) mbar_arrive(base + SM_RDY + 8 * (RDY)); }
  if (cta >= NREG) {
    if (MASK & PH_CONV) for (int b = 0; b * 32 < CONV_EXTRA; b++) PUBLISH(SIG_Z + b, C_Z + b, min(32, CONV_EXTRA - b * 32))
    return;
  }
  const int g = cta & 7, j = cta >> 3;
#pragma unroll 1
  for (int half = 0; half < 2; half++) {
    const int h = 2 * j + half;
    if (half == 1 && (MASK & PH_ATT)) PUBLISH(SIG_CTX, C_CTX + g, 1)
    if (MASK & PH_KV) PUBLISH(SIG_KV + half, C_KV + h, 1)
    if (MASK & PH_ATT) {
      cnt_wait(g_cnt + (C_KV + h) * CSTRIDE, 8);
      const float4 kn = __ldcg((const float4*)(g_kn2 + h * 128) + lane);
      const uint32_t m = __reduce_max_sync(~0u, max(max(__float_as_uint(kn.x), __float_as_uint(kn.y)), max(__float_as_uint(kn.z), __float_as_uint(kn.w))));
      if (lane == 0) asm volatile("st.shared.u32 [%0], %1;" :: "r"(base + SM_KMAX + 4 * half), "r"(m) : "memory");
      READY(RDY_KV + half)
    }
  }
  if (MASK & PH_CONV) {
    cnt_wait(g_cnt + (C_U + (conv_channel(cta, 0) >> 5)) * CSTRIDE, 128);
    cnt_wait(g_cnt + (C_U + (conv_channel(cta, CONV_REG - 1) >> 5)) * CSTRIDE, 128);
    READY(RDY_U)
  }
  if (MASK & PH_OUT) { cnt_wait(g_cnt + (C_CTX + g) * CSTRIDE, 16); READY(RDY_CTX) }
  if (MASK & PH_ATT) PUBLISH(SIG_CTX + 1, C_CTX + 8 + g, 1)
  if (MASK & PH_CONV) {
    const int c0 = conv_channel(cta, 0), c1 = c0 + CONV_REG - 1;
    if ((c0 >> 7) == (c1 >> 7)) PUBLISH(SIG_Z, C_Z + (c0 >> 7), CONV_REG)
    else { PUBLISH(SIG_Z, C_Z + (c0 >> 7), 128 - (c0 & 127)) PUBLISH(SIG_Z, C_Z + (c1 >> 7), (c1 & 127) + 1) }
  }
  if (MASK & PH_OUT) {
    cnt_wait(g_cnt + (C_CTX + 8 + g) * CSTRIDE, 16); READY(RDY_CTX + 1)
    cnt_wait(g_cnt + C_GATE * CSTRIDE, 2048);
    cnt_wait(g_cnt + (C_Z + (j & 7)) * CSTRIDE, 128); READY(RDY_Z)
  }
#undef PUBLISH
#undef READY
}

__device__ __forceinline__ void aux_pre(const Params& P, int aw, int lane) {
  const int cp = lane & 15, tb = lane >> 4;
#pragma unroll 1
  for (int unit = aw; unit < 4096; unit += NCTA * 2) {
    const int grp = unit >> 7, t0 = (unit & 127) * 16 + tb * 8;
    const int ch = grp * 32 + cp * 2;
    const uint32_t* kp = (const uint32_t*)(P.k + ch), * vp = (const uint32_t*)(P.v + ch);
    uint32_t kk[12], vv[9];
#pragma unroll
    for (int i = 0; i < 12; i++) { const int t = t0 - 4 + i; kk[i] = t >= 0 ? __ldg(kp + (size_t)t * 512) : 0u; }
#pragma unroll
    for (int i = 0; i < 9; i++) { const int t = t0 - 1 + i; vv[i] = t >= 0 ? __ldg(vp + (size_t)t * 512) : 0u; }
    const uint4 sw = __ldg((const uint4*)(P.shift + ch * 4));
    const uint32_t w0 = __byte_perm(sw.x, sw.z, 0x5410), w1 = __byte_perm(sw.x, sw.z, 0x7632), w2 = __byte_perm(sw.y, sw.w, 0x5410), w3 = __byte_perm(sw.y, sw.w, 0x7632);
#pragma unroll
    for (int i = 0; i < 9; i++)
      vv[i] = hmul2(hadd2(hadd2(hadd2(hmul2(kk[i], w3), hmul2(kk[i + 1], w2)), hmul2(kk[i + 2], w1)), hmul2(kk[i + 3], w0)), vv[i]);
    if (t0 == 0) vv[0] = 0;
    uint8_t* e0 = g_u + (size_t)ch * UCH + (2040 - t0) * 2;
    *(uint4*)(e0)                = make_uint4(__byte_perm(vv[8], vv[7], 0x5410), __byte_perm(vv[6], vv[5], 0x5410), __byte_perm(vv[4], vv[3], 0x5410), __byte_perm(vv[2], vv[1], 0x5410));
    *(uint4*)(e0 + UPITCH)       = make_uint4(__byte_perm(vv[7], vv[6], 0x5410), __byte_perm(vv[5], vv[4], 0x5410), __byte_perm(vv[3], vv[2], 0x5410), __byte_perm(vv[1], vv[0], 0x5410));
    *(uint4*)(e0 + UCH)          = make_uint4(__byte_perm(vv[8], vv[7], 0x7632), __byte_perm(vv[6], vv[5], 0x7632), __byte_perm(vv[4], vv[3], 0x7632), __byte_perm(vv[2], vv[1], 0x7632));
    *(uint4*)(e0 + UCH + UPITCH) = make_uint4(__byte_perm(vv[7], vv[6], 0x7632), __byte_perm(vv[5], vv[4], 0x7632), __byte_perm(vv[3], vv[2], 0x7632), __byte_perm(vv[1], vv[0], 0x7632));
    if (t0 == 0) {
      const uint4 zz = make_uint4(0, 0, 0, 0);
      *(uint4*)(e0 + 16) = zz; *(uint4*)(e0 + UPITCH + 16) = zz; *(uint4*)(e0 + UCH + 16) = zz; *(uint4*)(e0 + UCH + UPITCH + 16) = zz;
    }
    cnt_signal(g_cnt + (C_U + grp) * CSTRIDE, lane);
  }
#pragma unroll 1
  for (int row = aw; row < 2048; row += NCTA * 2) {
    float a = 0.f;
#pragma unroll
    for (int i = 0; i < 4; i++) {
      const uint4 xv = __ldg((const uint4*)(P.x + (size_t)row * 1024) + i * 32 + lane), gv = __ldg((const uint4*)P.gw + i * 32 + lane);
      uint32_t m;
      m = hmul2(xv.x, gv.x); a += bf_lo(m) + bf_hi(m); m = hmul2(xv.y, gv.y); a += bf_lo(m) + bf_hi(m);
      m = hmul2(xv.z, gv.z); a += bf_lo(m) + bf_hi(m); m = hmul2(xv.w, gv.w); a += bf_lo(m) + bf_hi(m);
    }
#pragma unroll
    for (int o = 16; o > 0; o >>= 1) a += __shfl_xor_sync(~0u, a, o);
    a = bf_lo(pack_bf16(a, 0.f));
    const float gt = bf_lo(pack_bf16(__fdividef(1.f, 1.f + ex2(-a * 1.4426950408889634f)), 0.f));
    if (lane == 0) g_gate[row] = gt;
    cnt_signal(g_cnt + C_GATE * CSTRIDE, lane);
  }
}

template<int MASK> __global__ void __launch_bounds__(384, 1) gated_mix_kernel(const __grid_constant__ Maps M, const __grid_constant__ Params P) {
  extern __shared__ __align__(1024) uint8_t smem[];
  constexpr uint32_t base = SMEM_BASE;
  if (threadIdx.x == 0) {
    if ((uint32_t)__cvta_generic_to_shared(smem) != SMEM_BASE) asm volatile("trap;");
    for (int i = 0; i < NUNIT; i++) { mbar_init(base + SM_BAR + 8 * i, 1); mbar_init(base + SM_BAR + 128 + 8 * i, 8); }
    mbar_init(base + SM_EXIT, 12);
    for (int i = 0; i < 8; i++) { mbar_init(base + SM_SIG + 8 * i, 8); mbar_init(base + SM_RDY + 8 * i, 1); }
    asm volatile("fence.mbarrier_init.release.cluster;" ::: "memory");
  }
  __syncthreads();
  const int wg = __shfl_sync(~0u, threadIdx.x >> 7, 0);
  const int warp = __shfl_sync(~0u, (threadIdx.x >> 5) & 3, 0);
  const int lane = threadIdx.x & 31;
  const int cta = blockIdx.x;
  if (wg == 2) {
    asm volatile("setmaxnreg.dec.sync.aligned.u32 56;");
    TS(2, 62);
    if (warp == 0) producer<MASK>(M, P, base, cta, lane);
    else if (warp == 1) sync_agent<MASK>(P, base, cta, lane);
    else if (MASK & PH_PRE) aux_pre(P, cta + (warp - 2) * NCTA, lane);
    __syncwarp();
    if (lane == 0) mbar_arrive(base + SM_EXIT);
    if (warp == 0 && (MASK & PH_OUT)) {
      mbar_wait_slow(base + SM_EXIT, 0);
      unsigned old = 0;
      if (lane == 0) asm volatile("atom.acq_rel.gpu.global.add.u32 %0, [%1], 1;" : "=r"(old) : "l"(g_cnt + C_EXIT * CSTRIDE) : "memory");
      old = __shfl_sync(~0u, old, 0);
      if (old == NCTA - 1) for (int i = lane; i < C_NUM; i += 32) g_cnt[i * CSTRIDE] = 0;
    }
  } else {
    asm volatile("setmaxnreg.inc.sync.aligned.u32 224;");
    Cons c{base, 0u, lane, warp, wg, (cta * 3 + wg) * 2048};
    if (wg == 1) bar_arrive(1, 256);
    TS(wg, 0);
    if (cta < NREG) {
      const int g = cta & 7, j = cta >> 3;
      Pend w = {};
      for (int half = 0; half < 2; half++) {
        const int h = 2 * j + half;
        const bool pend_o = half == 1 && (MASK & PH_ATT);
        if (MASK & PH_KV) cons_kv(c, h, g, w, pend_o);
        else if (pend_o) { flush_o_all(w); c.signal(SIG_CTX); }
        TS(wg, 1 + 4 * half);
        if (MASK & PH_ATT) {
          const int fast = cons_q(c, h, g, w, MASK & PH_KV);
          TS(wg, 2 + 4 * half);
          if (fast) cons_att_fast(c, h, g, w); else cons_att_safe(c, h, g, w);
          TS(wg, 3 + 4 * half);
        } else if (MASK & PH_KV) flush_kv_all(c, w, h, g);
      }
      if (MASK & PH_ATT) { flush_o_all(w); c.signal(SIG_CTX + 1); }
    }
    if (MASK & PH_CONV) cons_conv(c, P, cta, cta < NREG ? CONV_REG : CONV_EXTRA);
    TS(wg, 9);
    if (cta < NREG && (MASK & PH_OUT)) cons_out(c, M, (cta >> 3) < 8 ? (cta & 7) : 15 - (cta & 7), (cta >> 3) & 7);
    TS(wg, 10);
    __syncwarp();
    if (lane == 0) mbar_arrive(base + SM_EXIT);
  }
}

typedef CUresult (*EncFn)(CUtensorMap*, CUtensorMapDataType, cuuint32_t, void*, const cuuint64_t*, const cuuint64_t*, const cuuint32_t*, const cuuint32_t*,
                          CUtensorMapInterleave, CUtensorMapSwizzle, CUtensorMapL2promotion, CUtensorMapFloatOOBfill);
static void enc(EncFn f, CUtensorMap* m, const void* ptr, int rank, const cuuint64_t* dims, const cuuint64_t* strides, const cuuint32_t* box, CUtensorMapSwizzle sw) {
  const cuuint32_t es[3] = {1, 1, 1};
  f(m, CU_TENSOR_MAP_DATA_TYPE_BFLOAT16, rank, (void*)ptr, dims, strides, box, es, CU_TENSOR_MAP_INTERLEAVE_NONE, sw, CU_TENSOR_MAP_L2_PROMOTION_L2_256B, CU_TENSOR_MAP_FLOAT_OOB_FILL_NONE);
}
static void enc2(EncFn f, CUtensorMap* m, const void* ptr, int cols, int rows, int brows) {
  const cuuint64_t d[2] = {(cuuint64_t)cols, (cuuint64_t)rows}, s[1] = {(cuuint64_t)cols * 2}; const cuuint32_t b[2] = {64, (cuuint32_t)brows};
  enc(f, m, ptr, 2, d, s, b, CU_TENSOR_MAP_SWIZZLE_128B);
}
static void encw(EncFn f, CUtensorMap* m, const void* ptr, int cols, int rows) {
  const cuuint64_t d[3] = {64, (cuuint64_t)rows, (cuuint64_t)cols / 64}, s[2] = {(cuuint64_t)cols * 2, 128}; const cuuint32_t b[3] = {64, 64, 2};
  enc(f, m, ptr, 3, d, s, b, CU_TENSOR_MAP_SWIZZLE_128B);
}
extern "C" void kernel_launch(void* const* d_in, const int* in_sizes, int n_in, void* d_out, int out_size) {
  static EncFn fn = nullptr;
  static int nsm = 0;
  static void* zptr = nullptr;
  if (!fn) {
    void* p = nullptr; cudaDriverEntryPointQueryResult qr;
    cudaGetDriverEntryPoint("cuTensorMapEncodeTiled", &p, cudaEnableDefault, &qr);
    fn = (EncFn)p;
    cudaFuncSetAttribute(gated_mix_kernel<PH_ALL>, cudaFuncAttributeMaxDynamicSharedMemorySize, SMEM_BYTES);
    cudaFuncSetAttribute(gated_mix_kernel<PH_PRE | PH_KV>, cudaFuncAttributeMaxDynamicSharedMemorySize, SMEM_BYTES);
    cudaFuncSetAttribute(gated_mix_kernel<PH_ATT | PH_CONV>, cudaFuncAttributeMaxDynamicSharedMemorySize, SMEM_BYTES);
    cudaFuncSetAttribute(gated_mix_kernel<PH_OUT>, cudaFuncAttributeMaxDynamicSharedMemorySize, SMEM_BYTES);
    int dev = 0; cudaGetDevice(&dev);
    cudaDeviceGetAttribute(&nsm, cudaDevAttrMultiProcessorCount, dev);
    cudaGetSymbolAddress(&zptr, g_z);
  }
  Maps M;
  enc2(fn, &M.x, d_in[0], 1024, 2048, 128);
  enc2(fn, &M.c, d_in[7], 512, 2048, 128);
  encw(fn, &M.wq, d_in[8], 4096, 1024);
  encw(fn, &M.wk, d_in[9], 4096, 512);
  encw(fn, &M.wv, d_in[10], 4096, 512);
  encw(fn, &M.wo, d_in[11], 1024, 4096);
  { const cuuint64_t d[3] = {64, 32, 1024}, s[2] = {128, 4096}; const cuuint32_t b[3] = {64, 40, 1}; enc(fn, &M.h, d_in[4], 3, d, s, b, CU_TENSOR_MAP_SWIZZLE_NONE); }
  enc2(fn, &M.z, zptr, 2048, 1024, 128);
  enc2(fn, &M.out, d_out, 1024, 2048, 16);
  Params P{(const __nv_bfloat16*)d_in[0], (const __nv_bfloat16*)d_in[1], (const __nv_bfloat16*)d_in[2], (const __nv_bfloat16*)d_in[3],
           (const __nv_bfloat16*)d_in[5], (const __nv_bfloat16*)d_in[12]};
  bool split = nsm < NCTA;
  if (!split) {
    gated_mix_kernel<PH_ALL><<<NCTA, 384, SMEM_BYTES>>>(M, P);
  } else {
    gated_mix_kernel<PH_PRE | PH_KV><<<NCTA, 384, SMEM_BYTES>>>(M, P);
    gated_mix_kernel<PH_ATT | PH_CONV><<<NCTA, 384, SMEM_BYTES>>>(M, P);
    gated_mix_kernel<PH_OUT><<<NCTA, 384, SMEM_BYTES>>>(M, P);
  }
}
```

```cpp
#include <cuda_runtime.h>
#include <cuda.h>
#include <cuda_bf16.h>
#include <stdint.h>

template<int TB> __device__ __forceinline__ void wgmma_ss_n256(float (&d)[128], uint64_t da, uint64_t db, int scale_d) {
  asm volatile("{\n.reg .pred p;\nsetp.ne.b32 p, %130, 0;\n"
    "wgmma.mma_async.sync.aligned.m64n256k16.f32.bf16.bf16 {%0, %1, %2, %3, %4, %5, %6, %7, %8, %9, %10, %11, %12, %13, %14, %15, %16, %17, %18, %19, %20, %21, %22, %23, %24, %25, %26, %27, %28, %29, %30, %31, %32, %33, %34, %35, %36, %37, %38, %39, %40, %41, %42, %43, %44, %45, %46, %47, %48, %49, %50, %51, %52, %53, %54, %55, %56, %57, %58, %59, %60, %61, %62, %63, %64, %65, %66, %67, %68, %69, %70, %71, %72, %73, %74, %75, %76, %77, %78, %79, %80, %81, %82, %83, %84, %85, %86, %87, %88, %89, %90, %91, %92, %93, %94, %95, %96, %97, %98, %99, %100, %101, %102, %103, %104, %105, %106, %107, %108, %109, %110, %111, %112, %113, %114, %115, %116, %117, %118, %119, %120, %121, %122, %123, %124, %125, %126, %127}, %128, %129, p, 1, 1, 0, %131;\n}\n"
    : "+f"(d[0]), "+f"(d[1]), "+f"(d[2]), "+f"(d[3]), "+f"(d[4]), "+f"(d[5]), "+f"(d[6]), "+f"(d[7]), "+f"(d[8]), "+f"(d[9]), "+f"(d[10]), "+f"(d[11]), "+f"(d[12]), "+f"(d[13]), "+f"(d[14]), "+f"(d[15]), "+f"(d[16]), "+f"(d[17]), "+f"(d[18]), "+f"(d[19]), "+f"(d[20]), "+f"(d[21]), "+f"(d[22]), "+f"(d[23]), "+f"(d[24]), "+f"(d[25]), "+f"(d[26]), "+f"(d[27]), "+f"(d[28]), "+f"(d[29]), "+f"(d[30]), "+f"(d[31]), "+f"(d[32]), "+f"(d[33]), "+f"(d[34]), "+f"(d[35]), "+f"(d[36]), "+f"(d[37]), "+f"(d[38]), "+f"(d[39]), "+f"(d[40]), "+f"(d[41]), "+f"(d[42]), "+f"(d[43]), "+f"(d[44]), "+f"(d[45]), "+f"(d[46]), "+f"(d[47]), "+f"(d[48]), "+f"(d[49]), "+f"(d[50]), "+f"(d[51]), "+f"(d[52]), "+f"(d[53]), "+f"(d[54]), "+f"(d[55]), "+f"(d[56]), "+f"(d[57]), "+f"(d[58]), "+f"(d[59]), "+f"(d[60]), "+f"(d[61]), "+f"(d[62]), "+f"(d[63]), "+f"(d[64]), "+f"(d[65]), "+f"(d[66]), "+f"(d[67]), "+f"(d[68]), "+f"(d[69]), "+f"(d[70]), "+f"(d[71]), "+f"(d[72]), "+f"(d[73]), "+f"(d[74]), "+f"(d[75]), "+f"(d[76]), "+f"(d[77]), "+f"(d[78]), "+f"(d[79]), "+f"(d[80]), "+f"(d[81]), "+f"(d[82]), "+f"(d[83]), "+f"(d[84]), "+f"(d[85]), "+f"(d[86]), "+f"(d[87]), "+f"(d[88]), "+f"(d[89]), "+f"(d[90]), "+f"(d[91]), "+f"(d[92]), "+f"(d[93]), "+f"(d[94]), "+f"(d[95]), "+f"(d[96]), "+f"(d[97]), "+f"(d[98]), "+f"(d[99]), "+f"(d[100]), "+f"(d[101]), "+f"(d[102]), "+f"(d[103]), "+f"(d[104]), "+f"(d[105]), "+f"(d[106]), "+f"(d[107]), "+f"(d[108]), "+f"(d[109]), "+f"(d[110]), "+f"(d[111]), "+f"(d[112]), "+f"(d[113]), "+f"(d[114]), "+f"(d[115]), "+f"(d[116]), "+f"(d[117]), "+f"(d[118]), "+f"(d[119]), "+f"(d[120]), "+f"(d[121]), "+f"(d[122]), "+f"(d[123]), "+f"(d[124]), "+f"(d[125]), "+f"(d[126]), "+f"(d[127])
    : "l"(da), "l"(db), "r"(scale_d), "n"(TB));
}
template<int TB> __device__ __forceinline__ void wgmma_ss_n128(float (&d)[64], uint64_t da, uint64_t db, int scale_d) {
  asm volatile("{\n.reg .pred p;\nsetp.ne.b32 p, %66, 0;\n"
    "wgmma.mma_async.sync.aligned.m64n128k16.f32.bf16.bf16 {%0, %1, %2, %3, %4, %5, %6, %7, %8, %9, %10, %11, %12, %13, %14, %15, %16, %17, %18, %19, %20, %21, %22, %23, %24, %25, %26, %27, %28, %29, %30, %31, %32, %33, %34, %35, %36, %37, %38, %39, %40, %41, %42, %43, %44, %45, %46, %47, %48, %49, %50, %51, %52, %53, %54, %55, %56, %57, %58, %59, %60, %61, %62, %63}, %64, %65, p, 1, 1, 0, %67;\n}\n"
    : "+f"(d[0]), "+f"(d[1]), "+f"(d[2]), "+f"(d[3]), "+f"(d[4]), "+f"(d[5]), "+f"(d[6]), "+f"(d[7]), "+f"(d[8]), "+f"(d[9]), "+f"(d[10]), "+f"(d[11]), "+f"(d[12]), "+f"(d[13]), "+f"(d[14]), "+f"(d[15]), "+f"(d[16]), "+f"(d[17]), "+f"(d[18]), "+f"(d[19]), "+f"(d[20]), "+f"(d[21]), "+f"(d[22]), "+f"(d[23]), "+f"(d[24]), "+f"(d[25]), "+f"(d[26]), "+f"(d[27]), "+f"(d[28]), "+f"(d[29]), "+f"(d[30]), "+f"(d[31]), "+f"(d[32]), "+f"(d[33]), "+f"(d[34]), "+f"(d[35]), "+f"(d[36]), "+f"(d[37]), "+f"(d[38]), "+f"(d[39]), "+f"(d[40]), "+f"(d[41]), "+f"(d[42]), "+f"(d[43]), "+f"(d[44]), "+f"(d[45]), "+f"(d[46]), "+f"(d[47]), "+f"(d[48]), "+f"(d[49]), "+f"(d[50]), "+f"(d[51]), "+f"(d[52]), "+f"(d[53]), "+f"(d[54]), "+f"(d[55]), "+f"(d[56]), "+f"(d[57]), "+f"(d[58]), "+f"(d[59]), "+f"(d[60]), "+f"(d[61]), "+f"(d[62]), "+f"(d[63])
    : "l"(da), "l"(db), "r"(scale_d), "n"(TB));
}
template<int TB> __device__ __forceinline__ void wgmma_rs_n128(float (&d)[64], uint32_t a0, uint32_t a1, uint32_t a2, uint32_t a3, uint64_t db, int scale_d) {
  asm volatile("{\n.reg .pred p;\nsetp.ne.b32 p, %69, 0;\n"
    "wgmma.mma_async.sync.aligned.m64n128k16.f32.bf16.bf16 {%0, %1, %2, %3, %4, %5, %6, %7, %8, %9, %10, %11, %12, %13, %14, %15, %16, %17, %18, %19, %20, %21, %22, %23, %24, %25, %26, %27, %28, %29, %30, %31, %32, %33, %34, %35, %36, %37, %38, %39, %40, %41, %42, %43, %44, %45, %46, %47, %48, %49, %50, %51, %52, %53, %54, %55, %56, %57, %58, %59, %60, %61, %62, %63}, {%64, %65, %66, %67}, %68, p, 1, 1, %70;\n}\n"
    : "+f"(d[0]), "+f"(d[1]), "+f"(d[2]), "+f"(d[3]), "+f"(d[4]), "+f"(d[5]), "+f"(d[6]), "+f"(d[7]), "+f"(d[8]), "+f"(d[9]), "+f"(d[10]), "+f"(d[11]), "+f"(d[12]), "+f"(d[13]), "+f"(d[14]), "+f"(d[15]), "+f"(d[16]), "+f"(d[17]), "+f"(d[18]), "+f"(d[19]), "+f"(d[20]), "+f"(d[21]), "+f"(d[22]), "+f"(d[23]), "+f"(d[24]), "+f"(d[25]), "+f"(d[26]), "+f"(d[27]), "+f"(d[28]), "+f"(d[29]), "+f"(d[30]), "+f"(d[31]), "+f"(d[32]), "+f"(d[33]), "+f"(d[34]), "+f"(d[35]), "+f"(d[36]), "+f"(d[37]), "+f"(d[38]), "+f"(d[39]), "+f"(d[40]), "+f"(d[41]), "+f"(d[42]), "+f"(d[43]), "+f"(d[44]), "+f"(d[45]), "+f"(d[46]), "+f"(d[47]), "+f"(d[48]), "+f"(d[49]), "+f"(d[50]), "+f"(d[51]), "+f"(d[52]), "+f"(d[53]), "+f"(d[54]), "+f"(d[55]), "+f"(d[56]), "+f"(d[57]), "+f"(d[58]), "+f"(d[59]), "+f"(d[60]), "+f"(d[61]), "+f"(d[62]), "+f"(d[63])
    : "r"(a0), "r"(a1), "r"(a2), "r"(a3), "l"(db), "r"(scale_d), "n"(TB));
}
template<int TB> __device__ __forceinline__ void wgmma_rs_n64(float (&d)[32], uint32_t a0, uint32_t a1, uint32_t a2, uint32_t a3, uint64_t db, int scale_d) {
  asm volatile("{\n.reg .pred p;\nsetp.ne.b32 p, %37, 0;\n"
    "wgmma.mma_async.sync.aligned.m64n64k16.f32.bf16.bf16 {%0, %1, %2, %3, %4, %5, %6, %7, %8, %9, %10, %11, %12, %13, %14, %15, %16, %17, %18, %19, %20, %21, %22, %23, %24, %25, %26, %27, %28, %29, %30, %31}, {%32, %33, %34, %35}, %36, p, 1, 1, %38;\n}\n"
    : "+f"(d[0]), "+f"(d[1]), "+f"(d[2]), "+f"(d[3]), "+f"(d[4]), "+f"(d[5]), "+f"(d[6]), "+f"(d[7]), "+f"(d[8]), "+f"(d[9]), "+f"(d[10]), "+f"(d[11]), "+f"(d[12]), "+f"(d[13]), "+f"(d[14]), "+f"(d[15]), "+f"(d[16]), "+f"(d[17]), "+f"(d[18]), "+f"(d[19]), "+f"(d[20]), "+f"(d[21]), "+f"(d[22]), "+f"(d[23]), "+f"(d[24]), "+f"(d[25]), "+f"(d[26]), "+f"(d[27]), "+f"(d[28]), "+f"(d[29]), "+f"(d[30]), "+f"(d[31])
    : "r"(a0), "r"(a1), "r"(a2), "r"(a3), "l"(db), "r"(scale_d), "n"(TB));
}
__device__ __forceinline__ void wgmma_pv_sel(float (&d)[64], const uint32_t (&p)[32], uint64_t db, int full, int acc) {
  asm volatile("{\n.reg .pred q, s;\n.reg .b64 t;\nsetp.ne.b32 s, %98, 0;\nsetp.eq.b32 q, %97, 0;\n@q bra.uni LH;\n"
    "wgmma.fence.sync.aligned;\n"
    "add.s64 t, %96, 0;\nwgmma.mma_async.sync.aligned.m64n128k16.f32.bf16.bf16 {%0, %1, %2, %3, %4, %5, %6, %7, %8, %9, %10, %11, %12, %13, %14, %15, %16, %17, %18, %19, %20, %21, %22, %23, %24, %25, %26, %27, %28, %29, %30, %31, %32, %33, %34, %35, %36, %37, %38, %39, %40, %41, %42, %43, %44, %45, %46, %47, %48, %49, %50, %51, %52, %53, %54, %55, %56, %57, %58, %59, %60, %61, %62, %63}, {%64, %65, %66, %67}, t, s, 1, 1, 1;\n"
    "add.s64 t, %96, 256;\nwgmma.mma_async.sync.aligned.m64n128k16.f32.bf16.bf16 {%0, %1, %2, %3, %4, %5, %6, %7, %8, %9, %10, %11, %12, %13, %14, %15, %16, %17, %18, %19, %20, %21, %22, %23, %24, %25, %26, %27, %28, %29, %30, %31, %32, %33, %34, %35, %36, %37, %38, %39, %40, %41, %42, %43, %44, %45, %46, %47, %48, %49, %50, %51, %52, %53, %54, %55, %56, %57, %58, %59, %60, %61, %62, %63}, {%68, %69, %70, %71}, t, 1, 1, 1, 1;\n"
    "add.s64 t, %96, 512;\nwgmma.mma_async.sync.aligned.m64n128k16.f32.bf16.bf16 {%0, %1, %2, %3, %4, %5, %6, %7, %8, %9, %10, %11, %12, %13, %14, %15, %16, %17, %18, %19, %20, %21, %22, %23, %24, %25, %26, %27, %28, %29, %30, %31, %32, %33, %34, %35, %36, %37, %38, %39, %40, %41, %42, %43, %44, %45, %46, %47, %48, %49, %50, %51, %52, %53, %54, %55, %56, %57, %58, %59, %60, %61, %62, %63}, {%72, %73, %74, %75}, t, 1, 1, 1, 1;\n"
    "add.s64 t, %96, 768;\nwgmma.mma_async.sync.aligned.m64n128k16.f32.bf16.bf16 {%0, %1, %2, %3, %4, %5, %6, %7, %8, %9, %10, %11, %12, %13, %14, %15, %16, %17, %18, %19, %20, %21, %22, %23, %24, %25, %26, %27, %28, %29, %30, %31, %32, %33, %34, %35, %36, %37, %38, %39, %40, %41, %42, %43, %44, %45, %46, %47, %48, %49, %50, %51, %52, %53, %54, %55, %56, %57, %58, %59, %60, %61, %62, %63}, {%76, %77, %78, %79}, t, 1, 1, 1, 1;\n"
    "add.s64 t, %96, 1024;\nwgmma.mma_async.sync.aligned.m64n128k16.f32.bf16.bf16 {%0, %1, %2, %3, %4, %5, %6, %7, %8, %9, %10, %11, %12, %13, %14, %15, %16, %17, %18, %19, %20, %21, %22, %23, %24, %25, %26, %27, %28, %29, %30, %31, %32, %33, %34, %35, %36, %37, %38, %39, %40, %41, %42, %43, %44, %45, %46, %47, %48, %49, %50, %51, %52, %53, %54, %55, %56, %57, %58, %59, %60, %61, %62, %63}, {%80, %81, %82, %83}, t, 1, 1, 1, 1;\n"
    "add.s64 t, %96, 1280;\nwgmma.mma_async.sync.aligned.m64n128k16.f32.bf16.bf16 {%0, %1, %2, %3, %4, %5, %6, %7, %8, %9, %10, %11, %12, %13, %14, %15, %16, %17, %18, %19, %20, %21, %22, %23, %24, %25, %26, %27, %28, %29, %30, %31, %32, %33, %34, %35, %36, %37, %38, %39, %40, %41, %42, %43, %44, %45, %46, %47, %48, %49, %50, %51, %52, %53, %54, %55, %56, %57, %58, %59, %60, %61, %62, %63}, {%84, %85, %86, %87}, t, 1, 1, 1, 1;\n"
    "add.s64 t, %96, 1536;\nwgmma.mma_async.sync.aligned.m64n128k16.f32.bf16.bf16 {%0, %1, %2, %3, %4, %5, %6, %7, %8, %9, %10, %11, %12, %13, %14, %15, %16, %17, %18, %19, %20, %21, %22, %23, %24, %25, %26, %27, %28, %29, %30, %31, %32, %33, %34, %35, %36, %37, %38, %39, %40, %41, %42, %43, %44, %45, %46, %47, %48, %49, %50, %51, %52, %53, %54, %55, %56, %57, %58, %59, %60, %61, %62, %63}, {%88, %89, %90, %91}, t, 1, 1, 1, 1;\n"
    "add.s64 t, %96, 1792;\nwgmma.mma_async.sync.aligned.m64n128k16.f32.bf16.bf16 {%0, %1, %2, %3, %4, %5, %6, %7, %8, %9, %10, %11, %12, %13, %14, %15, %16, %17, %18, %19, %20, %21, %22, %23, %24, %25, %26, %27, %28, %29, %30, %31, %32, %33, %34, %35, %36, %37, %38, %39, %40, %41, %42, %43, %44, %45, %46, %47, %48, %49, %50, %51, %52, %53, %54, %55, %56, %57, %58, %59, %60, %61, %62, %63}, {%92, %93, %94, %95}, t, 1, 1, 1, 1;\n"
    "wgmma.commit_group.sync.aligned;\n"
    "bra.uni LE;\nLH:\n"
    "wgmma.fence.sync.aligned;\n"
    "add.s64 t, %96, 0;\nwgmma.mma_async.sync.aligned.m64n128k16.f32.bf16.bf16 {%0, %1, %2, %3, %4, %5, %6, %7, %8, %9, %10, %11, %12, %13, %14, %15, %16, %17, %18, %19, %20, %21, %22, %23, %24, %25, %26, %27, %28, %29, %30, %31, %32, %33, %34, %35, %36, %37, %38, %39, %40, %41, %42, %43, %44, %45, %46, %47, %48, %49, %50, %51, %52, %53, %54, %55, %56, %57, %58, %59, %60, %61, %62, %63}, {%80, %81, %82, %83}, t, s, 1, 1, 1;\n"
    "add.s64 t, %96, 256;\nwgmma.mma_async.sync.aligned.m64n128k16.f32.bf16.bf16 {%0, %1, %2, %3, %4, %5, %6, %7, %8, %9, %10, %11, %12, %13, %14, %15, %16, %17, %18, %19, %20, %21, %22, %23, %24, %25, %26, %27, %28, %29, %30, %31, %32, %33, %34, %35, %36, %37, %38, %39, %40, %41, %42, %43, %44, %45, %46, %47, %48, %49, %50, %51, %52, %53, %54, %55, %56, %57, %58, %59, %60, %61, %62, %63}, {%84, %85, %86, %87}, t, 1, 1, 1, 1;\n"
    "add.s64 t, %96, 512;\nwgmma.mma_async.sync.aligned.m64n128k16.f32.bf16.bf16 {%0, %1, %2, %3, %4, %5, %6, %7, %8, %9, %10, %11, %12, %13, %14, %15, %16, %17, %18, %19, %20, %21, %22, %23, %24, %25, %26, %27, %28, %29, %30, %31, %32, %33, %34, %35, %36, %37, %38, %39, %40, %41, %42, %43, %44, %45, %46, %47, %48, %49, %50, %51, %52, %53, %54, %55, %56, %57, %58, %59, %60, %61, %62, %63}, {%88, %89, %90, %91}, t, 1, 1, 1, 1;\n"
    "add.s64 t, %96, 768;\nwgmma.mma_async.sync.aligned.m64n128k16.f32.bf16.bf16 {%0, %1, %2, %3, %4, %5, %6, %7, %8, %9, %10, %11, %12, %13, %14, %15, %16, %17, %18, %19, %20, %21, %22, %23, %24, %25, %26, %27, %28, %29, %30, %31, %32, %33, %34, %35, %36, %37, %38, %39, %40, %41, %42, %43, %44, %45, %46, %47, %48, %49, %50, %51, %52, %53, %54, %55, %56, %57, %58, %59, %60, %61, %62, %63}, {%92, %93, %94, %95}, t, 1, 1, 1, 1;\n"
    "wgmma.commit_group.sync.aligned;\n"
    "LE:\n}\n"
    : "+f"(d[0]), "+f"(d[1]), "+f"(d[2]), "+f"(d[3]), "+f"(d[4]), "+f"(d[5]), "+f"(d[6]), "+f"(d[7]), "+f"(d[8]), "+f"(d[9]), "+f"(d[10]), "+f"(d[11]), "+f"(d[12]), "+f"(d[13]), "+f"(d[14]), "+f"(d[15]), "+f"(d[16]), "+f"(d[17]), "+f"(d[18]), "+f"(d[19]), "+f"(d[20]), "+f"(d[21]), "+f"(d[22]), "+f"(d[23]), "+f"(d[24]), "+f"(d[25]), "+f"(d[26]), "+f"(d[27]), "+f"(d[28]), "+f"(d[29]), "+f"(d[30]), "+f"(d[31]), "+f"(d[32]), "+f"(d[33]), "+f"(d[34]), "+f"(d[35]), "+f"(d[36]), "+f"(d[37]), "+f"(d[38]), "+f"(d[39]), "+f"(d[40]), "+f"(d[41]), "+f"(d[42]), "+f"(d[43]), "+f"(d[44]), "+f"(d[45]), "+f"(d[46]), "+f"(d[47]), "+f"(d[48]), "+f"(d[49]), "+f"(d[50]), "+f"(d[51]), "+f"(d[52]), "+f"(d[53]), "+f"(d[54]), "+f"(d[55]), "+f"(d[56]), "+f"(d[57]), "+f"(d[58]), "+f"(d[59]), "+f"(d[60]), "+f"(d[61]), "+f"(d[62]), "+f"(d[63])
    : "r"(p[0]), "r"(p[1]), "r"(p[2]), "r"(p[3]), "r"(p[4]), "r"(p[5]), "r"(p[6]), "r"(p[7]), "r"(p[8]), "r"(p[9]), "r"(p[10]), "r"(p[11]), "r"(p[12]), "r"(p[13]), "r"(p[14]), "r"(p[15]), "r"(p[16]), "r"(p[17]), "r"(p[18]), "r"(p[19]), "r"(p[20]), "r"(p[21]), "r"(p[22]), "r"(p[23]), "r"(p[24]), "r"(p[25]), "r"(p[26]), "r"(p[27]), "r"(p[28]), "r"(p[29]), "r"(p[30]), "r"(p[31]), "l"(db), "r"(full), "r"(acc) : "memory");
}

constexpr int NCTA = 132, NREG = 128;
constexpr int UNIT = 16384, NUNIT = 14;
constexpr uint32_t SMEM_BASE = 1024;
constexpr int SM_BAR = NUNIT * UNIT;
constexpr int SMEM_BYTES = SM_BAR + 1024;
constexpr int UPITCH = 4160, UCH = 2 * UPITCH;
constexpr float QSCALE = 0.08838834764831845f * 1.4426950408889634f;
constexpr float BOUND2 = 48.f * 48.f / 1.15f;
#define CONV_REG 4
constexpr int CONV_EXTRA = (1024 - NREG * CONV_REG) / (NCTA - NREG);
constexpr int CH_EXTRA_TOTAL = CONV_EXTRA * (NCTA - NREG);
constexpr int C_KV = 0;
constexpr int C_CTX = 32;
constexpr int C_U = 48;
constexpr int C_Z = 80;
constexpr int C_GATE = 88;
constexpr int C_EXIT = 89;
constexpr int C_NUM = 96;
constexpr int CSTRIDE = 32;
constexpr int SM_KMAX = SM_BAR + 256, SM_DUMMY = SM_BAR + 264, SM_EXIT = SM_BAR + 272, SM_SIG = SM_BAR + 320, SM_RDY = SM_BAR + 384;
enum { SIG_KV = 0, SIG_CTX = 2, SIG_Z = 4 };
enum { RDY_KV = 0, RDY_CTX = 2, RDY_U = 4, RDY_Z = 5 };
enum { PH_PRE = 1, PH_KV = 2, PH_ATT = 4, PH_CONV = 8, PH_OUT = 16, PH_ALL = 31 };

constexpr uint32_t T_CTX = 0, T_KV = 16 * 32 * 32768, T_BYTES = T_KV + 32 * 16 * 65536;
__device__ __align__(1024) uint8_t g_T[T_BYTES];
__device__ __align__(1024) uint8_t g_u[1024 * UCH];
__device__ __align__(1024) __nv_bfloat16 g_z[1024 * 2048];
__device__ __align__(1024) float g_gate[2048];
__device__ __align__(1024) float g_kn2[32 * 128];
__device__ __align__(1024) unsigned g_cnt[C_NUM * CSTRIDE];

struct __align__(64) Maps { CUtensorMap x, c, wq, wk, wv, wo, h, z, out, ctx; };
struct Params {
  const __nv_bfloat16 *x, *k, *v, *shift, *D, *gw;
};

__device__ __forceinline__ void wg_fence() { asm volatile("wgmma.fence.sync.aligned;" ::: "memory"); }
__device__ __forceinline__ void wg_commit() { asm volatile("wgmma.commit_group.sync.aligned;" ::: "memory"); }
template<int N> __device__ __forceinline__ void wg_wait() { asm volatile("wgmma.wait_group.sync.aligned %0;" :: "n"(N) : "memory"); }
__device__ __forceinline__ uint64_t mkdesc(uint32_t addr, uint32_t lbo, uint32_t sbo, uint32_t swz) {
  return (uint64_t)((addr & 0x3FFFF) >> 4) | ((uint64_t)(lbo >> 4) << 16) | ((uint64_t)(sbo >> 4) << 32) | ((uint64_t)swz << 62);
}
__device__ __forceinline__ void mbar_init(uint32_t bar, int cnt) { asm volatile("mbarrier.init.shared::cta.b64 [%0], %1;" :: "r"(bar), "r"(cnt)); }
__device__ __forceinline__ void mbar_expect(uint32_t bar, uint32_t bytes) { asm volatile("mbarrier.arrive.expect_tx.shared::cta.b64 _, [%0], %1;" :: "r"(bar), "r"(bytes) : "memory"); }
__device__ __forceinline__ void mbar_arrive(uint32_t bar) { asm volatile("mbarrier.arrive.shared::cta.b64 _, [%0];" :: "r"(bar) : "memory"); }
__device__ __forceinline__ void mbar_arrive_n(uint32_t bar, int n) { asm volatile("mbarrier.arrive.shared::cta.b64 _, [%0], %1;" :: "r"(bar), "r"(n) : "memory"); }
__device__ __forceinline__ void mbar_wait(uint32_t bar, uint32_t parity) {
  asm volatile("{\n.reg .pred p;\n.reg .u32 n;\nmov.u32 n, 0;\n"
    "LW:\nmbarrier.try_wait.parity.shared::cta.b64 p, [%0], %1;\n@p bra LD;\n"
    "add.u32 n, n, 1;\nsetp.lt.u32 p, n, 2097152;\n@p bra LW;\ntrap;\nLD:\n}\n" :: "r"(bar), "r"(parity) : "memory");
}
__device__ __forceinline__ void mbar_wait_slow(uint32_t bar, uint32_t parity) {
  asm volatile("{\n.reg .pred p;\n.reg .u32 n;\nmov.u32 n, 0;\n"
    "LW:\nmbarrier.test_wait.parity.shared::cta.b64 p, [%0], %1;\n@p bra LD;\n"
    "nanosleep.u32 128;\nadd.u32 n, n, 1;\nsetp.lt.u32 p, n, 4194304;\n@p bra LW;\ntrap;\nLD:\n}\n" :: "r"(bar), "r"(parity) : "memory");
}
__device__ __forceinline__ void mbar_wait_all(uint32_t bar, uint32_t parity) {
  asm volatile("{\n.reg .pred p, q;\n.reg .u32 n;\nmov.u32 n, 0;\n"
    "LW:\nmbarrier.try_wait.parity.shared::cta.b64 p, [%0], %1;\nvote.sync.all.pred q, p, 0xffffffff;\n@q bra.uni LD;\n"
    "add.u32 n, n, 1;\nsetp.lt.u32 q, n, 2097152;\n@q bra.uni LW;\ntrap;\nLD:\n}\n" :: "r"(bar), "r"(parity) : "memory");
}
__device__ __forceinline__ void cnt_wait(const unsigned* p, unsigned target) {
  asm volatile("{\n.reg .pred p;\n.reg .u32 n, v;\nmov.u32 n, 0;\n"
    "LW:\nld.relaxed.gpu.global.u32 v, [%0];\nsetp.ge.u32 p, v, %1;\n@p bra LD;\n"
    "nanosleep.u32 64;\nadd.u32 n, n, 1;\nsetp.lt.u32 p, n, 4194304;\n@p bra LW;\ntrap;\nLD:\nfence.acq_rel.gpu;\nfence.proxy.async;\n}\n" :: "l"(p), "r"(target) : "memory");
}
__device__ __forceinline__ void cnt_signal(unsigned* p, int lane) {
  __syncwarp();
  if (lane == 0) asm volatile("red.release.gpu.global.add.u32 [%0], 1;" :: "l"(p) : "memory");
}
__device__ __forceinline__ void cnt_publish(unsigned* p, unsigned n) {
  asm volatile("fence.acq_rel.gpu;\nred.relaxed.gpu.global.add.u32 [%0], %1;" :: "l"(p), "r"(n) : "memory");
}
__device__ __forceinline__ void bulk_g2s(uint32_t dst, const void* src, uint32_t bytes, uint32_t bar) {
  asm volatile("cp.async.bulk.shared::cluster.global.mbarrier::complete_tx::bytes [%0], [%1], %2, [%3];" :: "r"(dst), "l"(src), "r"(bytes), "r"(bar) : "memory");
}
__device__ __forceinline__ void tma2d(uint32_t dst, const CUtensorMap* m, int x, int y, uint32_t bar) {
  asm volatile("cp.async.bulk.tensor.2d.shared::cluster.global.mbarrier::complete_tx::bytes [%0], [%1, {%3, %4}], [%2];" :: "r"(dst), "l"(m), "r"(bar), "r"(x), "r"(y) : "memory");
}
__device__ __forceinline__ void tma3d(uint32_t dst, const CUtensorMap* m, int x, int y, int z, uint32_t bar) {
  asm volatile("cp.async.bulk.tensor.3d.shared::cluster.global.mbarrier::complete_tx::bytes [%0], [%1, {%3, %4, %5}], [%2];" :: "r"(dst), "l"(m), "r"(bar), "r"(x), "r"(y), "r"(z) : "memory");
}
__device__ __forceinline__ void bulk_g2s_mc(uint32_t dst, const void* src, uint32_t bytes, uint32_t bar) {
  asm volatile("cp.async.bulk.shared::cluster.global.mbarrier::complete_tx::bytes.multicast::cluster [%0], [%1], %2, [%3], %4;" :: "r"(dst), "l"(src), "r"(bytes), "r"(bar), "h"((uint16_t)3) : "memory");
}
__device__ __forceinline__ void tma2d_mc(uint32_t dst, const CUtensorMap* m, int x, int y, uint32_t bar) {
  asm volatile("cp.async.bulk.tensor.2d.shared::cluster.global.mbarrier::complete_tx::bytes.multicast::cluster [%0], [%1, {%3, %4}], [%2], %5;" :: "r"(dst), "l"(m), "r"(bar), "r"(x), "r"(y), "h"((uint16_t)3) : "memory");
}
__device__ __forceinline__ void tma3d_mc(uint32_t dst, const CUtensorMap* m, int x, int y, int z, uint32_t bar) {
  asm volatile("cp.async.bulk.tensor.3d.shared::cluster.global.mbarrier::complete_tx::bytes.multicast::cluster [%0], [%1, {%3, %4, %5}], [%2], %6;" :: "r"(dst), "l"(m), "r"(bar), "r"(x), "r"(y), "r"(z), "h"((uint16_t)3) : "memory");
}
__device__ __forceinline__ void tma2d_store(const CUtensorMap* m, uint32_t src, int x, int y) {
  asm volatile("cp.async.bulk.tensor.2d.global.shared::cta.bulk_group [%0, {%2, %3}], [%1];" :: "l"(m), "r"(src), "r"(x), "r"(y) : "memory");
}
__device__ __forceinline__ bool elect() {
  uint32_t r; asm volatile("{\n.reg .pred p;\nelect.sync _|p, 0xffffffff;\nselp.u32 %0, 1, 0, p;\n}\n" : "=r"(r)); return r != 0;
}
__device__ __forceinline__ void cluster_arrive() { asm volatile("barrier.cluster.arrive;" ::: "memory"); }
__device__ __forceinline__ void cluster_wait() { asm volatile("barrier.cluster.wait;" ::: "memory"); }
__device__ __forceinline__ void bar_sync(int id, int n) { asm volatile("bar.sync %0, %1;" :: "r"(id), "r"(n) : "memory"); }
__device__ __forceinline__ void bar_arrive(int id, int n) { asm volatile("bar.arrive %0, %1;" :: "r"(id), "r"(n) : "memory"); }
__device__ __forceinline__ int bar_and(int id, int n, int pred) {
  int r; asm volatile("{\n.reg .pred p, q;\nsetp.ne.b32 p, %3, 0;\nbar.red.and.pred q, %1, %2, p;\nselp.b32 %0, 1, 0, q;\n}\n" : "=r"(r) : "r"(id), "r"(n), "r"(pred) : "memory");
  return r;
}
__device__ __forceinline__ void fence_async_smem() { asm volatile("fence.proxy.async.shared::cta;" ::: "memory"); }
__device__ __forceinline__ float ex2(float x) { float y; asm("ex2.approx.ftz.f32 %0, %1;" : "=f"(y) : "f"(x)); return y; }
__device__ __forceinline__ uint32_t pack_bf16(float lo, float hi) { uint32_t r; asm("cvt.rn.bf16x2.f32 %0, %1, %2;" : "=r"(r) : "f"(hi), "f"(lo)); return r; }
__device__ __forceinline__ uint32_t hmul2(uint32_t a, uint32_t b) { uint32_t r; asm("mul.rn.bf16x2 %0, %1, %2;" : "=r"(r) : "r"(a), "r"(b)); return r; }
__device__ __forceinline__ uint32_t hadd2(uint32_t a, uint32_t b) { uint32_t r; asm("add.rn.bf16x2 %0, %1, %2;" : "=r"(r) : "r"(a), "r"(b)); return r; }
__device__ __forceinline__ uint32_t hfma2(uint32_t a, uint32_t b, uint32_t c) { uint32_t r; asm("fma.rn.bf16x2 %0, %1, %2, %3;" : "=r"(r) : "r"(a), "r"(b), "r"(c)); return r; }
__device__ __forceinline__ float bf_lo(uint32_t a) { return __uint_as_float(a << 16); }
__device__ __forceinline__ float bf_hi(uint32_t a) { return __uint_as_float(a & 0xffff0000u); }
__device__ __forceinline__ uint32_t lds32(uint32_t a) { uint32_t v; asm volatile("ld.shared.u32 %0, [%1];" : "=r"(v) : "r"(a) : "memory"); return v; }
__device__ __forceinline__ float2 lds64f(uint32_t a) { float2 v; asm volatile("ld.shared.v2.f32 {%0,%1}, [%2];" : "=f"(v.x), "=f"(v.y) : "r"(a) : "memory"); return v; }
__device__ __forceinline__ uint4 lds128(uint32_t a) { uint4 v; asm volatile("ld.shared.v4.u32 {%0,%1,%2,%3}, [%4];" : "=r"(v.x), "=r"(v.y), "=r"(v.z), "=r"(v.w) : "r"(a) : "memory"); return v; }
__device__ __forceinline__ void sts64f(uint32_t a, float x, float y) { asm volatile("st.shared.v2.f32 [%0], {%1,%2};" :: "r"(a), "f"(x), "f"(y) : "memory"); }
__device__ __forceinline__ void sts128(uint32_t a, uint4 v) { asm volatile("st.shared.v4.u32 [%0], {%1,%2,%3,%4};" :: "r"(a), "r"(v.x), "r"(v.y), "r"(v.z), "r"(v.w) : "memory"); }
template<int OFF> __device__ __forceinline__ void sts128o(uint32_t a, uint4 v) { asm volatile("st.shared.v4.u32 [%0+%5], {%1,%2,%3,%4};" :: "r"(a), "r"(v.x), "r"(v.y), "r"(v.z), "r"(v.w), "n"(OFF) : "memory"); }
__device__ __forceinline__ void ldsm4(uint32_t a, uint32_t& r0, uint32_t& r1, uint32_t& r2, uint32_t& r3) {
  asm volatile("ldmatrix.sync.aligned.m8n8.x4.shared.b16 {%0,%1,%2,%3}, [%4];" : "=r"(r0), "=r"(r1), "=r"(r2), "=r"(r3) : "r"(a) : "memory");
}
__device__ __forceinline__ void ldsm4t(uint32_t a, uint32_t& r0, uint32_t& r1, uint32_t& r2, uint32_t& r3) {
  asm volatile("ldmatrix.sync.aligned.m8n8.x4.trans.shared.b16 {%0,%1,%2,%3}, [%4];" : "=r"(r0), "=r"(r1), "=r"(r2), "=r"(r3) : "r"(a) : "memory");
}
__device__ __forceinline__ void stsm4(uint32_t a, uint32_t r0, uint32_t r1, uint32_t r2, uint32_t r3) {
  asm volatile("stmatrix.sync.aligned.m8n8.x4.shared.b16 [%0], {%1,%2,%3,%4};" :: "r"(a), "r"(r0), "r"(r1), "r"(r2), "r"(r3) : "memory");
}
template<int N> __device__ __forceinline__ void fence_regs(float (&d)[N]) {
#pragma unroll
  for (int i = 0; i < N; i++) asm volatile("" : "+f"(d[i]) :: "memory");
}
template<int N> __device__ __forceinline__ void fence_regs(uint32_t (&d)[N]) {
#pragma unroll
  for (int i = 0; i < N; i++) asm volatile("" : "+r"(d[i]) :: "memory");
}
__device__ __forceinline__ void sched_fence(float x, uint32_t dummy) {
  asm volatile("{\n.reg .pred p;\nsetp.eq.u32 p, %0, 0x7fc12345;\n@p st.shared.u32 [%1], %0;\n}\n" :: "r"(__float_as_uint(x)), "r"(dummy) : "memory");
}
#define TS(role, i)
#define TR(obj, role, tag)

struct Prod {
  uint32_t base, mask; int lane, nt;
  __device__ __forceinline__ uint32_t full(int u) const { return base + SM_BAR + 8 * u; }
  __device__ __forceinline__ uint32_t addr(int u) const { return base + u * UNIT; }
  __device__ __forceinline__ void acquire(int u, int n) {
    const int v = u + min(lane, n - 1);
    mbar_wait_all(base + SM_BAR + 128 + 8 * v, (mask >> v) & 1);
    mask ^= ((1u << n) - 1) << u;
    TR(*this, 2, 16 + u);
  }
};
struct Cons {
  uint32_t base, rel, mask; int lane, warp, wg, nt;
  __device__ __forceinline__ uint32_t addr(int u) const { return base + u * UNIT; }
  __device__ __forceinline__ static uint32_t daddr(int u) { return SMEM_BASE + u * UNIT; }
  __device__ __forceinline__ void wait(int u) { TR(*this, wg, 1); mbar_wait(base + SM_BAR + 8 * u, (mask >> u) & 1); mask ^= 1u << u; TR(*this, wg, 2); }
  __device__ __forceinline__ void wait2(int u0, int u1) {
    TR(*this, wg, 1);
    const int v = (lane & 1) ? u1 : u0;
    mbar_wait_all(base + SM_BAR + 8 * v, (mask >> v) & 1); mask ^= (1u << u0) | (1u << u1);
    TR(*this, wg, 2);
  }
  __device__ __forceinline__ void skip(int u) { mask ^= 1u << u; }
  __device__ __forceinline__ void release(int u, int n) { TR(*this, wg, 5); if ((lane & 15) < n) asm volatile("mbarrier.arrive.shared::cluster.b64 _, [%0];" :: "r"(rel + 8 * u) : "memory"); }
  __device__ __forceinline__ void release2(int u) { if ((lane & 15) == 0) asm volatile("mbarrier.arrive.shared::cluster.b64 _, [%0], 2;" :: "r"(rel + 8 * u) : "memory"); }
  __device__ __forceinline__ void signal(int i) { __syncwarp(); if (lane == 0) mbar_arrive(base + SM_SIG + 8 * i); }
  __device__ __forceinline__ void turn() { bar_sync(1 + wg, 256); TR(*this, wg, 3); }
  __device__ __forceinline__ void pass() { bar_arrive(2 - wg, 256); TR(*this, wg, 4); }
};
__device__ __forceinline__ int gemm_unit(int ks) { return 3 * ((ks & 3) ^ ((~ks >> 1) & 1)); }
__device__ __forceinline__ int att_slot(int i) { return i == 0 ? 12 : 2 + 2 * i; }
__device__ __forceinline__ int out_mb(int cta) { return (cta >> 1) & 15; }
__device__ __forceinline__ int out_nb(int cta) { return (cta >> 5) * 2 + (cta & 1); }
__device__ __forceinline__ int conv_channel(int cta, int i) {
  return cta < NREG ? CH_EXTRA_TOTAL + cta * CONV_REG + i : (i >> 1) * 8 + (cta - NREG) * 2 + (i & 1);
}

template<int OFF, int N> __device__ __forceinline__ void pack_chunk(const float (&a)[N], float sc0, float sc1, uint4& v0, uint4& v1) {
  v0.x = pack_bf16(a[OFF + 0] * sc0, a[OFF + 1] * sc0); v0.y = pack_bf16(a[OFF + 4] * sc0, a[OFF + 5] * sc0);
  v0.z = pack_bf16(a[OFF + 8] * sc0, a[OFF + 9] * sc0); v0.w = pack_bf16(a[OFF + 12] * sc0, a[OFF + 13] * sc0);
  v1.x = pack_bf16(a[OFF + 2] * sc1, a[OFF + 3] * sc1); v1.y = pack_bf16(a[OFF + 6] * sc1, a[OFF + 7] * sc1);
  v1.z = pack_bf16(a[OFF + 10] * sc1, a[OFF + 11] * sc1); v1.w = pack_bf16(a[OFF + 14] * sc1, a[OFF + 15] * sc1);
}
template<int OFF, int N> __device__ __forceinline__ void pack_chunk(const float (&a)[N], uint4& v0, uint4& v1) {
  v0.x = pack_bf16(a[OFF + 0], a[OFF + 1]); v0.y = pack_bf16(a[OFF + 4], a[OFF + 5]);
  v0.z = pack_bf16(a[OFF + 8], a[OFF + 9]); v0.w = pack_bf16(a[OFF + 12], a[OFF + 13]);
  v1.x = pack_bf16(a[OFF + 2], a[OFF + 3]); v1.y = pack_bf16(a[OFF + 6], a[OFF + 7]);
  v1.z = pack_bf16(a[OFF + 10], a[OFF + 11]); v1.w = pack_bf16(a[OFF + 14], a[OFF + 15]);
}
__device__ __forceinline__ void sq_acc(const uint4& v, uint32_t& a) { a = hfma2(v.x, v.x, a); a = hfma2(v.y, v.y, a); a = hfma2(v.z, v.z, a); a = hfma2(v.w, v.w, a); }
__device__ __forceinline__ float norm2_max(uint32_t a0, uint32_t a1) {
  float n0 = bf_lo(a0) + bf_hi(a0), n1 = bf_lo(a1) + bf_hi(a1);
  n0 += __shfl_xor_sync(~0u, n0, 1); n1 += __shfl_xor_sync(~0u, n1, 1);
  n0 += __shfl_xor_sync(~0u, n0, 2); n1 += __shfl_xor_sync(~0u, n1, 2);
  return __uint_as_float(__reduce_max_sync(~0u, max(__float_as_uint(n0) & 0x7fffffffu, __float_as_uint(n1) & 0x7fffffffu)));
}

struct Pend { uint4 lo[8], hi[8]; uint32_t dst; float kn; };
__device__ __forceinline__ void pin(uint4 (&v)[8]) {
#pragma unroll
  for (int i = 0; i < 8; i++) asm volatile("" : "+r"(v[i].x), "+r"(v[i].y), "+r"(v[i].z), "+r"(v[i].w) :: "memory");
}
__device__ __forceinline__ uint32_t atom_off(int lane) { return (lane >> 2) * 64 + (((lane ^ (lane >> 3)) & 3) << 4); }
template<int J0, int J1> __device__ __forceinline__ void tile_store(const uint4 (&v)[8], uint32_t dst, int lane) {
  uint8_t* d = g_T + (dst + atom_off(lane));
#pragma unroll
  for (int j = J0; j < J1; j++) { *(uint4*)(d + j * 512) = v[2 * j]; *(uint4*)(d + j * 512 + 2048) = v[2 * j + 1]; }
}
__device__ __forceinline__ float tile_norm2(const uint4 (&v)[8]) {
  uint32_t n0 = 0, n1 = 0;
#pragma unroll
  for (int j = 0; j < 4; j++) { sq_acc(v[2 * j], n0); sq_acc(v[2 * j + 1], n1); }
  return norm2_max(n0, n1);
}
template<int PART> __device__ __forceinline__ void out_part(Cons& c, Pend& w) {
  if (PART == 0) { w.kn = tile_norm2(w.lo); tile_store<0, 2>(w.lo, w.dst, c.lane); }
  if (PART == 1) tile_store<2, 4>(w.lo, w.dst, c.lane);
  if (PART == 2) {
    const float vn = tile_norm2(w.hi);
    if (c.lane == 0) g_kn2[((w.dst - T_KV) >> 16) * 8 + c.wg * 4 + c.warp] = (vn <= 1.0e30f && vn >= 1.0e-30f) ? w.kn : __uint_as_float(0x7f800000u);
    tile_store<0, 2>(w.hi, w.dst + 32768, c.lane);
  }
  if (PART == 3) tile_store<2, 4>(w.hi, w.dst + 32768, c.lane);
}
template<bool FIRST> __device__ __forceinline__ void kv_issue(Cons& c, float (&acc)[128], int u) {
  const uint64_t da = mkdesc(c.daddr(u) + c.wg * 8192, 16, 1024, 1), db = mkdesc(c.daddr(u + 1), 8192, 1024, 1);
  c.turn();
  wg_fence();
#pragma unroll
  for (int kk = 0; kk < 4; kk++) wgmma_ss_n256<1>(acc, da + kk * 2, db + kk * 128, !(FIRST && kk == 0));
  wg_commit();
  c.pass();
}
__device__ __forceinline__ void cons_kv(Cons& c, int h, int g, Pend& w, bool pend_o) {
#pragma unroll 1
  for (int tile = 0; tile < 2; tile++) {
    float acc[128];
    c.wait(3);
    kv_issue<true>(c, acc, 3);
    if (tile == 1 || pend_o) out_part<0>(c, w);
#pragma unroll 1
    for (int ks = 1; ks < 8; ks++) {
      if (ks == 3 && (tile == 1 || pend_o)) { out_part<1>(c, w); if (tile == 0) c.signal(SIG_CTX); }
      if (ks == 5 && tile == 1) out_part<2>(c, w);
      if (ks == 7 && tile == 1) out_part<3>(c, w);
      const int u = gemm_unit(ks);
      c.wait(u);
      wg_wait<0>();
      c.release(gemm_unit(ks - 1), 3);
      kv_issue<false>(c, acc, u);
    }
    wg_wait<0>(); fence_regs(acc);
    c.release(9, 3);
    pack_chunk<0>(acc, w.lo[0], w.lo[1]);  pack_chunk<16>(acc, w.lo[2], w.lo[3]); pack_chunk<32>(acc, w.lo[4], w.lo[5]); pack_chunk<48>(acc, w.lo[6], w.lo[7]);
    pack_chunk<64>(acc, w.hi[0], w.hi[1]); pack_chunk<80>(acc, w.hi[2], w.hi[3]); pack_chunk<96>(acc, w.hi[4], w.hi[5]); pack_chunk<112>(acc, w.hi[6], w.hi[7]);
    pin(w.lo); pin(w.hi);
    w.dst = T_KV + (h * 16 + 2 * g + tile) * 65536 + (c.wg * 4 + c.warp) * 4096;
  }
}
template<bool FIRST> __device__ __forceinline__ void q_issue(Cons& c, float (&a)[64], float (&b)[64], int u) {
  const uint64_t da = mkdesc(c.daddr(u) + c.wg * 8192, 16, 1024, 1), db = mkdesc(c.daddr(u + 2), 8192, 1024, 1);
  const uint64_t da2 = mkdesc(c.daddr(u + 1) + (1 - c.wg) * 8192, 16, 1024, 1);
  c.turn();
  wg_fence();
#pragma unroll
  for (int kk = 0; kk < 4; kk++) wgmma_ss_n128<1>(a, da + kk * 2, db + kk * 128, !(FIRST && kk == 0));
#pragma unroll
  for (int kk = 0; kk < 4; kk++) wgmma_ss_n128<1>(b, da2 + kk * 2, db + kk * 128, !(FIRST && kk == 0));
  wg_commit();
  c.pass();
}
template<bool PEND_KV> __device__ __forceinline__ int cons_q(Cons& c, int h, Pend& w) {
  float a[64], b[64];
  c.wait(3);
  q_issue<true>(c, a, b, 3);
  if (PEND_KV) out_part<0>(c, w);
#pragma unroll 1
  for (int ks = 1; ks < 16; ks++) {
    if (PEND_KV) {
      if (ks == 2) out_part<1>(c, w);
      if (ks == 4) out_part<2>(c, w);
      if (ks == 5) { out_part<3>(c, w); c.signal(SIG_KV + (h & 1)); }
    }
    const int u = gemm_unit(ks);
    c.wait(u);
    wg_wait<0>();
    c.release(gemm_unit(ks - 1), 3);
    q_issue<false>(c, a, b, u);
  }
  c.wait(0);
  wg_wait<0>(); fence_regs(a); fence_regs(b);
  c.release(9, 3);
  const uint32_t q0 = c.addr(0) + (c.wg * 4 + c.warp) * 4096 + atom_off(c.lane);
  uint32_t a0 = 0, a1 = 0, e0 = 0, e1 = 0;
  uint4 v0, v1;
#define Q_CHUNK(J) pack_chunk<16 * J>(a, QSCALE, QSCALE, v0, v1); sts128o<J * 512>(q0, v0); sts128o<J * 512 + 2048>(q0, v1); sq_acc(v0, a0); sq_acc(v1, a1); \
  pack_chunk<16 * J>(b, QSCALE, QSCALE, v0, v1); sts128o<32768 + J * 512>(q0, v0); sts128o<32768 + J * 512 + 2048>(q0, v1); sq_acc(v0, e0); sq_acc(v1, e1);
  Q_CHUNK(0) Q_CHUNK(1) Q_CHUNK(2) Q_CHUNK(3)
#undef Q_CHUNK
  TR(c, c.wg, 40);
  fence_async_smem();
  const float qa = norm2_max(a0, a1), qb = norm2_max(e0, e1);
  const float kn = __uint_as_float(lds32(c.base + SM_KMAX + 4 * (h & 1)));
  TR(c, c.wg, 42);
  return __shfl_sync(~0u, bar_and(3 + c.wg, 128, (qa * kn <= BOUND2) && (qb * kn <= BOUND2)), 0);
}

__device__ __forceinline__ void issue_qk(float (&s)[64], uint32_t qaddr, uint32_t kaddr) {
  const uint64_t da = mkdesc(qaddr, 16, 2048, 2), db = mkdesc(kaddr, 16, 2048, 2);
#pragma unroll
  for (int kk = 0; kk < 8; kk++) wgmma_ss_n128<0>(s, da + (kk >> 1) * 32 + (kk & 1) * 2, db + (kk >> 1) * 32 + (kk & 1) * 2, kk > 0);
  wg_commit();
}
template<bool FRESH, int NK> __device__ __forceinline__ void issue_pv_n(float (&o)[64], uint32_t (&p)[32], uint32_t vaddr) {
  const uint64_t db = mkdesc(vaddr, 512, 2048, 2);
#pragma unroll
  for (int kk = 0; kk < NK; kk++) wgmma_rs_n128<1>(o, p[4 * kk], p[4 * kk + 1], p[4 * kk + 2], p[4 * kk + 3], db + kk * 256, !(FRESH && kk == 0));
  wg_commit();
}
template<bool FRESH> __device__ __forceinline__ void issue_pv(float (&o)[64], uint32_t (&p)[32], uint32_t vaddr, bool full) {
  wgmma_pv_sel(o, p, mkdesc(vaddr, 512, 2048, 2), full, FRESH ? gridDim.y - 1 : 1);
}
template<int A, int B> __device__ __forceinline__ void exp_rng(float (&s)[64]) {
#pragma unroll
  for (int i = 4 * A; i < 4 * B; i++) s[i] = ex2(s[i]);
}
template<int A, int B> __device__ __forceinline__ void sum_rng(const float (&s)[64], float (&l)[4]) {
#pragma unroll
  for (int i = A; i < B; i++) { l[0] += s[4 * i]; l[1] += s[4 * i + 1]; l[2] += s[4 * i + 2]; l[3] += s[4 * i + 3]; }
}
template<int A, int B> __device__ __forceinline__ void cvt_p(const float (&s)[64], uint32_t (&p)[32]) {
#pragma unroll
  for (int i = 2 * A; i < 2 * B; i++) p[i] = pack_bf16(s[2 * i], s[2 * i + 1]);
}
template<int K0> __device__ __forceinline__ void mask_half(float (&s)[64], int warp, int lane) {
  const int l0 = warp + (2 * (lane & 3) <= (lane >> 2)), l1 = warp + (2 * (lane & 3) < (lane >> 2));
#pragma unroll
  for (int k = 0; k < 4; k++) {
    float* t = s + 8 * (K0 + k);
    if (k >= l0) { t[0] = -INFINITY; t[6] = -INFINITY; }
    if (k >= l1) { t[1] = -INFINITY; t[7] = -INFINITY; }
    if (k > warp) { t[2] = -INFINITY; t[3] = -INFINITY; }
    if (k >= warp) { t[4] = -INFINITY; t[5] = -INFINITY; }
  }
}
__device__ __forceinline__ void mask_diag(float (&s)[64], int lim) {
#pragma unroll
  for (int i = 0; i < 16; i++) {
    if (8 * i > lim) s[4 * i] = -INFINITY;
    if (8 * i + 1 > lim) s[4 * i + 1] = -INFINITY;
    if (8 * i - 8 > lim) s[4 * i + 2] = -INFINITY;
    if (8 * i - 7 > lim) s[4 * i + 3] = -INFINITY;
  }
}
__device__ __forceinline__ void row_inv(float& l0, float& l1) {
  l0 += __shfl_xor_sync(~0u, l0, 1); l1 += __shfl_xor_sync(~0u, l1, 1);
  l0 += __shfl_xor_sync(~0u, l0, 2); l1 += __shfl_xor_sync(~0u, l1, 2);
  l0 = __fdividef(1.f, l0); l1 = __fdividef(1.f, l1);
}
__device__ __forceinline__ void pack_o(const float (&o)[64], float i0, float i1, uint4 (&v)[8]) {
  pack_chunk<0>(o, i0, i1, v[0], v[1]); pack_chunk<16>(o, i0, i1, v[2], v[3]);
  pack_chunk<32>(o, i0, i1, v[4], v[5]); pack_chunk<48>(o, i0, i1, v[6], v[7]);
  pin(v);
}
__device__ __forceinline__ void softmax_safe(float (&s)[64], float& m0, float& m1, float& sc0, float& sc1) {
  float a0 = m0, a1 = m1;
#pragma unroll
  for (int i = 0; i < 16; i++) { a0 = fmaxf(a0, fmaxf(s[4 * i], s[4 * i + 1])); a1 = fmaxf(a1, fmaxf(s[4 * i + 2], s[4 * i + 3])); }
  a0 = fmaxf(a0, __shfl_xor_sync(~0u, a0, 1)); a1 = fmaxf(a1, __shfl_xor_sync(~0u, a1, 1));
  a0 = fmaxf(a0, __shfl_xor_sync(~0u, a0, 2)); a1 = fmaxf(a1, __shfl_xor_sync(~0u, a1, 2));
  sc0 = ex2(m0 - a0); sc1 = ex2(m1 - a1);
  m0 = a0; m1 = a1;
#pragma unroll
  for (int i = 0; i < 16; i++) { s[4 * i] -= a0; s[4 * i + 1] -= a0; s[4 * i + 2] -= a1; s[4 * i + 3] -= a1; }
}
struct Att {
  float s[64], o[64], l[4], i0, i1; uint32_t p[32];
  int si; uint32_t qaddr;
};
__device__ __forceinline__ uint32_t ctx_off(const Cons& c, int h, int qb, int rowhalf) { return T_CTX + (qb * 32 + h) * 32768 + (rowhalf * 4 + c.warp) * 4096; }
template<bool DIAG, bool DRAIN>
__device__ __forceinline__ void att_step(Cons& c, Att& a, bool qkfull, bool pvfull, int relq, uint32_t dst) {
  const int uk = att_slot(a.si); a.si = a.si == 4 ? 0 : a.si + 1;
  const int uv = att_slot(a.si); a.si = a.si == 4 ? 0 : a.si + 1;
  if (DRAIN) c.wait(uk); else c.wait2(uk, uv);
  c.turn();
  fence_regs(a.o); fence_regs(a.p);
  if (DIAG) { wg_fence(); issue_qk(a.s, a.qaddr, c.daddr(uk) - (qkfull ? 0 : 16384)); }
  else { wg_fence(); issue_qk(a.s, a.qaddr, c.daddr(uk)); }
  if (DRAIN) {
    c.wait(uv);
    fence_regs(a.o);
    uint4 v[8];
    pack_o(a.o, a.i0, a.i1, v); tile_store<0, 4>(v, dst, c.lane);
  }
  if (DRAIN || DIAG) issue_pv<DRAIN>(a.o, a.p, c.daddr(uv), pvfull); else issue_pv_n<false, 8>(a.o, a.p, c.daddr(uv));
  c.pass();
  wg_wait<1>(); fence_regs(a.s);
  c.release(uk, 2);
  if (relq >= 0) c.release(relq, 2);
  constexpr int SPLIT = DIAG ? 8 : 6;
  if (DIAG) mask_half<4>(a.s, c.warp, c.lane);
  exp_rng<SPLIT, 16>(a.s); sum_rng<SPLIT, 16>(a.s, a.l);
  sched_fence((a.l[0] + a.l[1]) + (a.l[2] + a.l[3]), c.base + SM_DUMMY);
  wg_wait<0>(); fence_regs(a.o); fence_regs(a.p);
  c.release(uv, 2);
  cvt_p<SPLIT, 16>(a.s, a.p);
  if (!DIAG || qkfull) { exp_rng<0, SPLIT>(a.s); sum_rng<0, SPLIT>(a.s, a.l); cvt_p<0, SPLIT>(a.s, a.p); }
}
__device__ __forceinline__ void att_first(Cons& c, Att& a) {
  a.si = 1; a.qaddr = c.daddr(0) + c.wg * 16384;
  c.wait(12);
  c.turn();
  wg_fence();
  issue_qk(a.s, a.qaddr, c.daddr(12));
  c.pass();
#pragma unroll
  for (int i = 0; i < 64; i++) a.o[i] = 0.f;
  a.l[0] = a.l[1] = a.l[2] = a.l[3] = 0.f; a.i0 = a.i1 = 0.f;
  wg_wait<0>(); fence_regs(a.s);
  c.release(12, 2);
}
__device__ __forceinline__ void att_switch(Att& a) {
  a.i0 = a.l[0] + a.l[1]; a.i1 = a.l[2] + a.l[3]; row_inv(a.i0, a.i1);
  a.l[0] = a.l[1] = a.l[2] = a.l[3] = 0.f;
  a.qaddr += 32768;
}
__device__ __forceinline__ void att_drain_now(Cons& c, Att& a, uint32_t dst) {
  uint4 v[8];
  pack_o(a.o, a.i0, a.i1, v); tile_store<0, 4>(v, dst, c.lane);
#pragma unroll
  for (int i = 0; i < 64; i++) a.o[i] = 0.f;
}
__device__ __forceinline__ void att_last(Cons& c, Att& a, Pend& w, bool pvfull, uint32_t dst) {
  const int uv = att_slot(a.si);
  c.wait(uv);
  c.turn();
  fence_regs(a.o); fence_regs(a.p);
  issue_pv<false>(a.o, a.p, c.daddr(uv), pvfull);
  c.pass();
  a.i0 = a.l[0] + a.l[1]; a.i1 = a.l[2] + a.l[3]; row_inv(a.i0, a.i1);
  wg_wait<0>(); fence_regs(a.o); fence_regs(a.p);
  c.release(uv, 2);
  pack_o(a.o, a.i0, a.i1, w.lo);
  w.dst = dst;
}
__device__ __forceinline__ void cons_att_fast(Cons& c, Att& a, int h, int g) {
  exp_rng<0, 16>(a.s); sum_rng<0, 16>(a.s, a.l); cvt_p<0, 16>(a.s, a.p);
#pragma unroll 1
  for (int t = 0; t < 2; t++) {
#pragma unroll 1
    for (int j = t == 0 ? 14 - g : g - 1; j > 0; j--) att_step<false, false>(c, a, true, true, (t == 1 && j == 1) ? 2 : -1, 0);
    if (t == 0) {
#pragma unroll 1
      for (int d = 0; d < 2; d++) {
        att_step<true, false>(c, a, d != c.wg, !(d == 1 && c.wg == 0), d == 0 ? 0 : (g == 0 ? 2 : -1), 0);
        if (d == 0) att_switch(a);
      }
      if (g > 0) att_step<false, true>(c, a, true, c.wg == 0, g == 1 ? 2 : -1, ctx_off(c, h, 15 - g, c.wg));
      else att_drain_now(c, a, ctx_off(c, h, 15, c.wg));
    }
  }
}
__device__ __forceinline__ void cons_att_safe(Cons& c, Att& a, int h, int g) {
  float m0 = -INFINITY, m1 = -INFINITY, sc0, sc1;
#pragma unroll 1
  for (int st = 0; st <= 16; st++) {
    const bool sw = st == 16 - g;
    if (st > 0) {
      if (sw) att_switch(a);
      const int uk = att_slot(a.si); a.si = a.si == 4 ? 0 : a.si + 1;
      const int uv = att_slot(a.si); a.si = a.si == 4 ? 0 : a.si + 1;
      c.wait2(uk, uv);
      c.turn();
      fence_regs(a.o); fence_regs(a.p);
      wg_fence();
      issue_qk(a.s, a.qaddr, c.daddr(uk));
      issue_pv_n<false, 8>(a.o, a.p, c.daddr(uv));
      c.pass();
      wg_wait<0>(); fence_regs(a.s); fence_regs(a.o); fence_regs(a.p);
      c.release(uk, 2); c.release(uv, 2);
      if (st == 15 - g) c.release(0, 2);
      if (st == 16) c.release(2, 2);
      if (sw) { att_drain_now(c, a, ctx_off(c, h, 15 - g, c.wg)); m0 = m1 = -INFINITY; }
      if (sw || st == 15 - g) mask_diag(a.s, (sw ? 1 - c.wg : c.wg) * 64 + c.warp * 16 + (c.lane >> 2) - 2 * (c.lane & 3));
    }
    softmax_safe(a.s, m0, m1, sc0, sc1);
    a.l[0] *= sc0; a.l[1] *= sc0; a.l[2] *= sc1; a.l[3] *= sc1;
    exp_rng<0, 16>(a.s); sum_rng<0, 16>(a.s, a.l); cvt_p<0, 16>(a.s, a.p);
#pragma unroll
    for (int i = 0; i < 16; i++) { a.o[4 * i] *= sc0; a.o[4 * i + 1] *= sc0; a.o[4 * i + 2] *= sc1; a.o[4 * i + 3] *= sc1; }
  }
}
__device__ __forceinline__ void cons_att(Cons& c, int h, int g, int fast, Pend& w) {
  Att a;
  att_first(c, a);
  if (fast) cons_att_fast(c, a, h, g);
  else {
#pragma unroll
    for (int i = 0; i < 32; i++) a.p[i] = 0;
    cons_att_safe(c, a, h, g);
  }
  att_last(c, a, w, !(fast && g == 0 && c.wg == 1), ctx_off(c, h, g, 1 - c.wg));
}

constexpr int CV_H = 1024, CV_U = 5120, CV_ROW = 1056;
__device__ __forceinline__ void cons_conv(Cons& c, const Params& P, int cta, int nch) {
  const int r = c.lane >> 2, q = c.lane & 3, tid = c.warp * 32 + c.lane;
  const uint32_t part = c.addr(4) + c.wg * (32 * CV_ROW) + 32;
  c.wait(4);
  sts64f(part + (tid >> 2) * CV_ROW - 32 + q * 8, 0.f, 0.f);
  const uint32_t aoff = CV_U + ((r & 1) ? 0 : UPITCH) + 4 * (((2039 - r) >> 1) + q - 8 * c.warp);
  const uint32_t wq = part + (c.warp * 8 + r) * CV_ROW + q * 8, rq = part + tid * 8;
#pragma unroll 1
  for (int i = 0; i < nch / 2; i++) {
    const int ch = conv_channel(cta, 2 * i + c.wg);
    const int u = 2 * c.wg + (i & 1);
    c.wait(u); c.skip(u ^ 2);
    const uint32_t ub = c.addr(u);
    uint32_t a[64];
#pragma unroll
    for (int G = 0; G < 16; G++) {
      a[4 * G + 0] = lds32(ub + aoff - 256 * G);
      a[4 * G + 1] = lds32(ub + aoff - 256 * G - 128);
      a[4 * G + 2] = lds32(ub + aoff - 256 * G + 16);
      a[4 * G + 3] = lds32(ub + aoff - 256 * G - 128 + 16);
    }
    float d0[32], d1[32], d2[32], d3[32];
    const uint64_t db = mkdesc(c.daddr(u) + CV_H - 16, 16, 128, 0);
    c.turn();
    wg_fence();
#pragma unroll
    for (int G = 0; G < 4; G++) wgmma_rs_n64<0>(d0, a[4 * G], a[4 * G + 1], a[4 * G + 2], a[4 * G + 3], db - 16 * G, G > 0);
#pragma unroll
    for (int G = 0; G < 8; G++) wgmma_rs_n64<0>(d1, a[4 * G], a[4 * G + 1], a[4 * G + 2], a[4 * G + 3], db + 64 - 16 * G, G > 0);
#pragma unroll
    for (int G = 0; G < 12; G++) wgmma_rs_n64<0>(d2, a[4 * G], a[4 * G + 1], a[4 * G + 2], a[4 * G + 3], db + 128 - 16 * G, G > 0);
#pragma unroll
    for (int G = 0; G < 16; G++) wgmma_rs_n64<0>(d3, a[4 * G], a[4 * G + 1], a[4 * G + 2], a[4 * G + 3], db + 192 - 16 * G, G > 0);
    wg_commit();
    c.pass();
    const uint32_t D2 = (uint32_t)__bfloat16_as_ushort(P.D[ch]) * 0x10001u;
    wg_wait<0>(); fence_regs(d0); fence_regs(d1); fence_regs(d2); fence_regs(d3); fence_regs(a);
    float c0 = 0.f, c1 = 0.f;
#define CV_ST(DD, R) _Pragma("unroll") for (int n = 0; n < 8; n++) { sts64f(wq + (R * 64 + n * 8) * 4, DD[4 * n] + c0, DD[4 * n + 1] + c1); c0 = DD[4 * n + 2]; c1 = DD[4 * n + 3]; }
    CV_ST(d0, 0) CV_ST(d1, 1) CV_ST(d2, 2) CV_ST(d3, 3)
#undef CV_ST
    bar_sync(3 + c.wg, 128);
    float y0[8], y1[8];
#pragma unroll
    for (int rr = 0; rr < 8; rr++) { const float2 v = lds64f(rq + rr * CV_ROW); y0[rr] = v.x; y1[rr] = v.y; }
#pragma unroll
    for (int w = 1; w < 4; w++) {
#pragma unroll
      for (int rr = 0; rr < 8; rr++) { const float2 v = lds64f(rq + (w * 8 + rr) * CV_ROW - w * 8); y0[rr] += v.x; y1[rr] += v.y; }
    }
    const uint4 ua = lds128(ub + CV_U + 4064 - 32 * tid + 16), uc = lds128(ub + CV_U + 4064 - 32 * tid);
    uint4 z0, z1;
    z0.x = hadd2(pack_bf16(y0[0], y0[1]), hmul2(__byte_perm(ua.w, 0, 0x1032), D2));
    z0.y = hadd2(pack_bf16(y0[2], y0[3]), hmul2(__byte_perm(ua.z, 0, 0x1032), D2));
    z0.z = hadd2(pack_bf16(y0[4], y0[5]), hmul2(__byte_perm(ua.y, 0, 0x1032), D2));
    z0.w = hadd2(pack_bf16(y0[6], y0[7]), hmul2(__byte_perm(ua.x, 0, 0x1032), D2));
    z1.x = hadd2(pack_bf16(y1[0], y1[1]), hmul2(__byte_perm(uc.w, 0, 0x1032), D2));
    z1.y = hadd2(pack_bf16(y1[2], y1[3]), hmul2(__byte_perm(uc.z, 0, 0x1032), D2));
    z1.z = hadd2(pack_bf16(y1[4], y1[5]), hmul2(__byte_perm(uc.y, 0, 0x1032), D2));
    z1.w = hadd2(pack_bf16(y1[6], y1[7]), hmul2(__byte_perm(uc.x, 0, 0x1032), D2));
    uint4* zp = (uint4*)(g_z + (size_t)ch * 2048 + tid * 16);
    zp[0] = z0; zp[1] = z1;
    __syncwarp();
    c.release2(u);
    bar_sync(3 + c.wg, 128);
    if ((i & 15) == 15 || i == nch / 2 - 1) c.signal(SIG_Z + (i >> 4));
  }
  c.release(4, 5);
}

constexpr int OUT_XZ_AT = 58;
__device__ __forceinline__ int out_slot(int i) { return i < 2 ? 10 + 2 * i : 2 * (i - 2); }
__device__ __forceinline__ void cons_out(Cons& c, const Maps& M, int mb, int nb) {
  float acc[64];
  uint32_t ga[32];
  int si = 0, pu, u;
#define OUT_STEP(FIRST) { \
    u = out_slot(si); si = si == 6 ? 0 : si + 1; \
    c.wait(u); \
    const uint64_t da = mkdesc(c.daddr(u) + c.wg * 8192, 16, 1024, 2), db = mkdesc(c.daddr(u + 1), 8192, 1024, 1); \
    wg_fence(); \
    _Pragma("unroll") for (int kk = 0; kk < 4; kk++) wgmma_ss_n128<1>(acc, da + (kk >> 1) * 32 + (kk & 1) * 2, db + kk * 128, !(FIRST && kk == 0)); \
    wg_commit(); }
  OUT_STEP(true)
  pu = u;
#pragma unroll 1
  for (int ks = 1; ks <= OUT_XZ_AT; ks++) { OUT_STEP(false) wg_wait<1>(); c.release(pu, 2); pu = u; }
  const int ux = out_slot(si); si = si == 6 ? 0 : si + 1;
  const int uz = out_slot(si); si = si == 6 ? 0 : si + 1;
  OUT_STEP(false)
  c.wait2(ux, uz);
  const int row = mb * 128 + c.wg * 64 + c.warp * 16 + (c.lane >> 2);
  const float g0 = __ldcg(g_gate + row), g1 = __ldcg(g_gate + row + 8);
  const uint32_t gg0 = pack_bf16(g0, g0), gg1 = pack_bf16(g1, g1);
  const uint32_t og0 = pack_bf16(1.f - g0, 1.f - g0), og1 = pack_bf16(1.f - g1, 1.f - g1);
  const int xr = c.wg * 64 + c.warp * 16 + (c.lane & 15);
  const uint32_t xa = c.addr(ux) + xr * 128, xs = xr & 7, xh = c.lane >> 4;
  const int zr = (c.lane & 7) + ((c.lane >> 4) << 3);
  const uint32_t za = c.addr(uz) + c.wg * 16384 + zr * 128 + (((c.warp * 2 + ((c.lane >> 3) & 1)) ^ (zr & 7)) << 4);
#pragma unroll
  for (int i = 0; i < 8; i++) {
    uint32_t x0, x1, x2, x3, z0, z1, z2, z3;
    ldsm4(xa + (i >> 2) * 16384 + ((((i & 3) * 2 + xh) ^ xs) << 4), x0, x1, x2, x3);
    ldsm4t(za + i * 2048, z0, z1, z2, z3);
    ga[4 * i + 0] = hmul2(gg0, hmul2(x0, z0)); ga[4 * i + 1] = hmul2(gg1, hmul2(x1, z1));
    ga[4 * i + 2] = hmul2(gg0, hmul2(x2, z2)); ga[4 * i + 3] = hmul2(gg1, hmul2(x3, z3));
  }
  wg_wait<1>(); c.release(pu, 2);
#pragma unroll 1
  for (int ks = OUT_XZ_AT + 2; ks < 64; ks++) OUT_STEP(false)
#undef OUT_STEP
  asm volatile("barrier.cluster.arrive.relaxed;" ::: "memory");
  wg_wait<0>(); fence_regs(acc);
#pragma unroll
  for (int i = 0; i < 8; i++) {
    const uint32_t r0 = hadd2(ga[4 * i + 0], hmul2(og0, pack_bf16(acc[8 * i + 0], acc[8 * i + 1])));
    const uint32_t r1 = hadd2(ga[4 * i + 1], hmul2(og1, pack_bf16(acc[8 * i + 2], acc[8 * i + 3])));
    const uint32_t r2 = hadd2(ga[4 * i + 2], hmul2(og0, pack_bf16(acc[8 * i + 4], acc[8 * i + 5])));
    const uint32_t r3 = hadd2(ga[4 * i + 3], hmul2(og1, pack_bf16(acc[8 * i + 6], acc[8 * i + 7])));
    stsm4(xa + (i >> 2) * 16384 + ((((i & 3) * 2 + xh) ^ xs) << 4), r0, r1, r2, r3);
  }
  fence_async_smem();
  __syncwarp();
  if (c.lane < 2) {
    const int r0 = c.wg * 64 + c.warp * 16;
    tma2d_store(&M.out, c.addr(ux) + c.lane * 16384 + r0 * 128, nb * 128 + c.lane * 64, mb * 128 + r0);
    asm volatile("cp.async.bulk.commit_group;\ncp.async.bulk.wait_group.read 0;" ::: "memory");
  }
}

__device__ __forceinline__ void prod_conv(Prod& p, const Maps& M, int cta, int nch) {
  p.acquire(4, 5);
  if (elect()) mbar_arrive(p.full(4));
  int ready = -1;
#pragma unroll 1
  for (int i = 0; i < nch; i++) {
    const int ch = conv_channel(cta, i);
    const int u = 2 * (i & 1) + ((i >> 1) & 1);
    if ((ch >> 5) != ready) { ready = ch >> 5; if (cta < NREG) mbar_wait(p.base + SM_RDY + 8 * RDY_U, 0); else cnt_wait(g_cnt + (C_U + ready) * CSTRIDE, 128); }
    p.acquire(u, 1);
    if (elect()) {
      mbar_expect(p.full(u), 5120 + UCH);
      tma3d(p.addr(u), &M.h, 0, -8, ch, p.full(u));
      bulk_g2s(p.addr(u) + CV_U, g_u + (size_t)ch * UCH, UCH, p.full(u));
    }
  }
}
template<int MASK> __device__ __forceinline__ void producer(const Maps& M, const Params& P, uint32_t base, int cta, int lane) {
  Prod p{base, 0xffffffffu, lane, (cta * 3 + 2) * 2048};
  if (cta >= NREG) { if (MASK & PH_CONV) prod_conv(p, M, cta, CONV_EXTRA); return; }
  const int g = cta & 7, j = cta >> 3, rank = cta & 1;
#pragma unroll 1
  for (int half = 0; half < 2; half++) {
    const int h = 2 * j + half;
    if (MASK & PH_KV) {
#pragma unroll 1
      for (int it = 0; it < 16; it++) {
        const int u = gemm_unit(it), ks = it & 7;
        p.acquire(u, 3);
        if (elect()) {
          mbar_expect(p.full(u), 3 * UNIT);
          tma2d(p.addr(u), &M.c, ks * 64, (2 * g + (it >> 3)) * 128, p.full(u));
          tma3d_mc(p.addr(u + 1 + rank), rank ? &M.wv : &M.wk, 0, ks * 64, 2 * h, p.full(u));
        }
      }
    }
    if (MASK & PH_ATT) {
#pragma unroll 1
      for (int ks = 0; ks < 16; ks++) {
        const int u = gemm_unit(ks);
        p.acquire(u, 3);
        if (elect()) {
          mbar_expect(p.full(u), 3 * UNIT);
          tma2d(p.addr(u), &M.x, ks * 64, (15 - g) * 128, p.full(u));
          tma2d(p.addr(u + 1), &M.x, ks * 64, g * 128, p.full(u));
          tma2d_mc(p.addr(u + 2) + rank * 8192, &M.wq, h * 128 + rank * 64, ks * 64, p.full(u));
        }
      }
      TS(2, 8 * half + 0);
      mbar_wait(base + SM_RDY + 8 * (RDY_KV + half), 0);
      TS(2, 8 * half + 1);
      const uint8_t* KVh = g_T + T_KV + (size_t)h * 16 * 65536;
      int si = 0;
#pragma unroll 1
      for (int i = 0; i < 34; i++) {
        const int isv = (i > 0 && !(i & 1)) || i == 33;
        const int st = i == 33 ? 16 : (isv ? (i >> 1) - 1 : (i + 1) >> 1);
        const uint8_t* src = KVh + (st <= 15 - g ? st : 16 - st) * 65536 + isv * 32768;
        const int u = att_slot(si); si = si == 4 ? 0 : si + 1;
        p.acquire(u, 2);
        if (elect()) {
          mbar_expect(p.full(u), 32768);
          if (st == 15 - (g & 6)) bulk_g2s(p.addr(u), src, 32768, p.full(u));
          else bulk_g2s_mc(p.addr(u + rank), src + rank * UNIT, UNIT, p.full(u));
        }
        if (i == 0) { p.acquire(0, 4); if (elect()) mbar_arrive(p.full(0)); }
      }
    }
  }
  if (MASK & PH_CONV) prod_conv(p, M, cta, CONV_REG);
  if (MASK & PH_OUT) {
    const int mb = out_mb(cta), nb = out_nb(cta);
    int si = 0;
#pragma unroll 1
    for (int ks = 0; ks < 64; ks++) {
      if ((ks & 31) == 0) { TS(2, 16 + (ks >> 4)); mbar_wait(base + SM_RDY + 8 * (RDY_CTX + (ks >> 5)), 0); TS(2, 17 + (ks >> 4)); }
      const int kb = ((ks & 31) >> 1) * 4 + (ks >> 5) * 2 + (ks & 1);
      const int u = out_slot(si); si = si == 6 ? 0 : si + 1;
      p.acquire(u, 2);
      if (elect()) {
        mbar_expect(p.full(u), 2 * UNIT);
        tma2d_mc(p.addr(u) + rank * 8192, &M.ctx, (kb & 1) * 256, (mb * 32 + (kb >> 1)) * 16 + rank * 8, p.full(u));
        tma3d(p.addr(u + 1), &M.wo, 0, kb * 64, 2 * nb, p.full(u));
      }
      if (ks == OUT_XZ_AT) {
        const int ux = out_slot(si); si = si == 6 ? 0 : si + 1;
        const int uz = out_slot(si); si = si == 6 ? 0 : si + 1;
        p.acquire(ux, 2);
        if (elect()) {
          mbar_expect(p.full(ux), 2 * UNIT);
          tma2d(p.addr(ux), &M.x, nb * 128, mb * 128, p.full(ux));
          tma2d(p.addr(ux + 1), &M.x, nb * 128 + 64, mb * 128, p.full(ux));
        }
        TS(2, 20);
        mbar_wait(base + SM_RDY + 8 * RDY_Z, 0);
        TS(2, 21);
        p.acquire(uz, 2);
        if (elect()) {
          mbar_expect(p.full(uz), 2 * UNIT);
          tma2d(p.addr(uz), &M.z, mb * 128, nb * 128, p.full(uz));
          tma2d(p.addr(uz + 1), &M.z, mb * 128 + 64, nb * 128, p.full(uz));
        }
      }
    }
  }
}

template<int MASK> __device__ __forceinline__ void sync_agent(const Params& P, uint32_t base, int cta, int lane) {
#define PUBLISH(SIG, CNT, N) { mbar_wait_slow(base + SM_SIG + 8 * (SIG), 0); if (lane == 0) cnt_publish(g_cnt + (CNT) * CSTRIDE, N); __syncwarp(); }
#define READY(RDY) { __syncwarp(); if (lane == 0) mbar_arrive(base + SM_RDY + 8 * (RDY)); }
  if (cta >= NREG) {
    if (MASK & PH_CONV) for (int b = 0; b * 32 < CONV_EXTRA; b++) PUBLISH(SIG_Z + b, C_Z + b, min(32, CONV_EXTRA - b * 32))
    return;
  }
  const int g = cta & 7, j = cta >> 3;
#pragma unroll 1
  for (int half = 0; half < 2; half++) {
    const int h = 2 * j + half;
    if (half == 1 && (MASK & PH_ATT)) PUBLISH(SIG_CTX, C_CTX + g, 1)
    if (MASK & PH_KV) PUBLISH(SIG_KV + half, C_KV + h, 1)
    if (MASK & PH_ATT) {
      cnt_wait(g_cnt + (C_KV + h) * CSTRIDE, 8);
      const float4 kn = __ldcg((const float4*)(g_kn2 + h * 128) + lane);
      const uint32_t m = __reduce_max_sync(~0u, max(max(__float_as_uint(kn.x), __float_as_uint(kn.y)), max(__float_as_uint(kn.z), __float_as_uint(kn.w))));
      if (lane == 0) asm volatile("st.shared.u32 [%0], %1;" :: "r"(base + SM_KMAX + 4 * half), "r"(m) : "memory");
      READY(RDY_KV + half)
    }
  }
  if (MASK & PH_CONV) {
    cnt_wait(g_cnt + (C_U + (conv_channel(cta, 0) >> 5)) * CSTRIDE, 128);
    cnt_wait(g_cnt + (C_U + (conv_channel(cta, CONV_REG - 1) >> 5)) * CSTRIDE, 128);
    READY(RDY_U)
  }
  const int go = min(out_mb(cta), 15 - out_mb(cta));
  if (MASK & PH_OUT) { cnt_wait(g_cnt + (C_CTX + go) * CSTRIDE, 16); READY(RDY_CTX) }
  if (MASK & PH_ATT) PUBLISH(SIG_CTX + 1, C_CTX + 8 + g, 1)
  if (MASK & PH_CONV) {
    const int c0 = conv_channel(cta, 0), c1 = c0 + CONV_REG - 1;
    if ((c0 >> 7) == (c1 >> 7)) PUBLISH(SIG_Z, C_Z + (c0 >> 7), CONV_REG)
    else { PUBLISH(SIG_Z, C_Z + (c0 >> 7), 128 - (c0 & 127)) PUBLISH(SIG_Z, C_Z + (c1 >> 7), (c1 & 127) + 1) }
  }
  if (MASK & PH_OUT) {
    cnt_wait(g_cnt + (C_CTX + 8 + go) * CSTRIDE, 16); READY(RDY_CTX + 1)
    cnt_wait(g_cnt + C_GATE * CSTRIDE, 2048);
    cnt_wait(g_cnt + (C_Z + out_nb(cta)) * CSTRIDE, 128); READY(RDY_Z)
  }
#undef PUBLISH
#undef READY
}

__device__ __forceinline__ void aux_pre(const Params& P, int aw, int lane) {
  const int cp = lane & 15, tb = lane >> 4;
#pragma unroll 1
  for (int unit = aw; unit < 4096; unit += NCTA * 2) {
    const int grp = unit >> 7, t0 = (unit & 127) * 16 + tb * 8;
    const int ch = grp * 32 + cp * 2;
    const uint32_t* kp = (const uint32_t*)(P.k + ch), * vp = (const uint32_t*)(P.v + ch);
    uint32_t kk[12], vv[9];
#pragma unroll
    for (int i = 0; i < 12; i++) { const int t = t0 - 4 + i; kk[i] = t >= 0 ? __ldg(kp + (size_t)t * 512) : 0u; }
#pragma unroll
    for (int i = 0; i < 9; i++) { const int t = t0 - 1 + i; vv[i] = t >= 0 ? __ldg(vp + (size_t)t * 512) : 0u; }
    const uint4 sw = __ldg((const uint4*)(P.shift + ch * 4));
    const uint32_t w0 = __byte_perm(sw.x, sw.z, 0x5410), w1 = __byte_perm(sw.x, sw.z, 0x7632), w2 = __byte_perm(sw.y, sw.w, 0x5410), w3 = __byte_perm(sw.y, sw.w, 0x7632);
#pragma unroll
    for (int i = 0; i < 9; i++)
      vv[i] = hmul2(hadd2(hadd2(hadd2(hmul2(kk[i], w3), hmul2(kk[i + 1], w2)), hmul2(kk[i + 2], w1)), hmul2(kk[i + 3], w0)), vv[i]);
    if (t0 == 0) vv[0] = 0;
    uint8_t* e0 = g_u + (size_t)ch * UCH + (2040 - t0) * 2;
    *(uint4*)(e0)                = make_uint4(__byte_perm(vv[8], vv[7], 0x5410), __byte_perm(vv[6], vv[5], 0x5410), __byte_perm(vv[4], vv[3], 0x5410), __byte_perm(vv[2], vv[1], 0x5410));
    *(uint4*)(e0 + UPITCH)       = make_uint4(__byte_perm(vv[7], vv[6], 0x5410), __byte_perm(vv[5], vv[4], 0x5410), __byte_perm(vv[3], vv[2], 0x5410), __byte_perm(vv[1], vv[0], 0x5410));
    *(uint4*)(e0 + UCH)          = make_uint4(__byte_perm(vv[8], vv[7], 0x7632), __byte_perm(vv[6], vv[5], 0x7632), __byte_perm(vv[4], vv[3], 0x7632), __byte_perm(vv[2], vv[1], 0x7632));
    *(uint4*)(e0 + UCH + UPITCH) = make_uint4(__byte_perm(vv[7], vv[6], 0x7632), __byte_perm(vv[5], vv[4], 0x7632), __byte_perm(vv[3], vv[2], 0x7632), __byte_perm(vv[1], vv[0], 0x7632));
    if (t0 == 0) {
      const uint4 zz = make_uint4(0, 0, 0, 0);
      *(uint4*)(e0 + 16) = zz; *(uint4*)(e0 + UPITCH + 16) = zz; *(uint4*)(e0 + UCH + 16) = zz; *(uint4*)(e0 + UCH + UPITCH + 16) = zz;
    }
    cnt_signal(g_cnt + (C_U + grp) * CSTRIDE, lane);
  }
#pragma unroll 1
  for (int row = aw; row < 2048; row += NCTA * 2) {
    float a = 0.f;
#pragma unroll
    for (int i = 0; i < 4; i++) {
      const uint4 xv = __ldg((const uint4*)(P.x + (size_t)row * 1024) + i * 32 + lane), gv = __ldg((const uint4*)P.gw + i * 32 + lane);
      uint32_t m;
      m = hmul2(xv.x, gv.x); a += bf_lo(m) + bf_hi(m); m = hmul2(xv.y, gv.y); a += bf_lo(m) + bf_hi(m);
      m = hmul2(xv.z, gv.z); a += bf_lo(m) + bf_hi(m); m = hmul2(xv.w, gv.w); a += bf_lo(m) + bf_hi(m);
    }
#pragma unroll
    for (int o = 16; o > 0; o >>= 1) a += __shfl_xor_sync(~0u, a, o);
    a = bf_lo(pack_bf16(a, 0.f));
    const float gt = bf_lo(pack_bf16(__fdividef(1.f, 1.f + ex2(-a * 1.4426950408889634f)), 0.f));
    if (lane == 0) g_gate[row] = gt;
    cnt_signal(g_cnt + C_GATE * CSTRIDE, lane);
  }
}

template<int MASK> __global__ void __cluster_dims__(2, 1, 1) __launch_bounds__(384, 1) gated_mix_kernel(const __grid_constant__ Maps M, const __grid_constant__ Params P) {
  extern __shared__ __align__(1024) uint8_t smem[];
  const uint32_t base = (uint32_t)__cvta_generic_to_shared(smem);
  if (threadIdx.x == 0) {
    if ((base & 0x3FFFF) != SMEM_BASE) asm volatile("trap;");
    for (int i = 0; i < NUNIT; i++) { mbar_init(base + SM_BAR + 8 * i, 1); mbar_init(base + SM_BAR + 128 + 8 * i, 16); }
    mbar_init(base + SM_EXIT, 4);
    for (int i = 0; i < 8; i++) { mbar_init(base + SM_SIG + 8 * i, 8); mbar_init(base + SM_RDY + 8 * i, 1); }
    asm volatile("fence.mbarrier_init.release.cluster;" ::: "memory");
  }
  __syncthreads();
  asm volatile("barrier.cluster.arrive.relaxed.aligned;\nbarrier.cluster.wait.aligned;" ::: "memory");
  const int wg = __shfl_sync(~0u, threadIdx.x >> 7, 0);
  const int warp = __shfl_sync(~0u, (threadIdx.x >> 5) & 3, 0);
  const int lane = threadIdx.x & 31;
  const int cta = blockIdx.x;
  if (wg == 2) {
    asm volatile("setmaxnreg.dec.sync.aligned.u32 56;");
    TS(2, 62);
    if (warp == 0) producer<MASK>(M, P, base, cta, lane);
    else if (warp == 1) sync_agent<MASK>(P, base, cta, lane);
    else if (MASK & PH_PRE) aux_pre(P, cta + (warp - 2) * NCTA, lane);
    __syncwarp();
    if (lane == 0) mbar_arrive(base + SM_EXIT);
    if (warp == 0 && (MASK & PH_OUT)) {
      mbar_wait_slow(base + SM_EXIT, 0);
      unsigned old = 0;
      if (lane == 0) asm volatile("atom.acq_rel.gpu.global.add.u32 %0, [%1], 1;" : "=r"(old) : "l"(g_cnt + C_EXIT * CSTRIDE) : "memory");
      old = __shfl_sync(~0u, old, 0);
      if (old == NCTA - 1) for (int i = lane; i < C_NUM; i += 32) g_cnt[i * CSTRIDE] = 0;
    }
    if (warp == 0) { cluster_arrive(); cluster_wait(); }
  } else {
    asm volatile("setmaxnreg.inc.sync.aligned.u32 224;");
    uint32_t rel;
    asm volatile("mapa.shared::cluster.u32 %0, %1, %2;" : "=r"(rel) : "r"(base + SM_BAR + 128 + 8 * (lane & 15)), "r"(lane >> 4));
    Cons c{base, rel, 0u, lane, warp, wg, (cta * 3 + wg) * 2048};
    if (wg == 1) bar_arrive(1, 256);
    TS(wg, 0);
    if (cta < NREG) {
      const int g = cta & 7, j = cta >> 3;
      Pend w = {};
#pragma unroll 1
      for (int half = 0; half < 2; half++) {
        const int h = 2 * j + half;
        if (MASK & PH_KV) cons_kv(c, h, g, w, half == 1 && (MASK & PH_ATT));
        TS(wg, 1 + 4 * half);
        if (MASK & PH_ATT) {
          const int fast = cons_q<(MASK & PH_KV) != 0>(c, h, w);
          TS(wg, 2 + 4 * half);
          cons_att(c, h, g, fast, w);
#pragma unroll
          for (int i = 0; i < 8; i++) w.hi[i] = make_uint4(0, 0, 0, 0);
          TS(wg, 3 + 4 * half);
          if (half == 1 || !(MASK & PH_KV)) { tile_store<0, 4>(w.lo, w.dst, lane); c.signal(SIG_CTX + half); }
        } else if (MASK & PH_KV) { out_part<0>(c, w); out_part<1>(c, w); out_part<2>(c, w); out_part<3>(c, w); c.signal(SIG_KV + half); }
      }
    }
    if (MASK & PH_CONV) cons_conv(c, P, cta, cta < NREG ? CONV_REG : CONV_EXTRA);
    TS(wg, 9);
    if (cta < NREG && (MASK & PH_OUT)) cons_out(c, M, out_mb(cta), out_nb(cta)); else cluster_arrive();
    TS(wg, 10);
  }
}

typedef CUresult (*EncFn)(CUtensorMap*, CUtensorMapDataType, cuuint32_t, void*, const cuuint64_t*, const cuuint64_t*, const cuuint32_t*, const cuuint32_t*,
                          CUtensorMapInterleave, CUtensorMapSwizzle, CUtensorMapL2promotion, CUtensorMapFloatOOBfill);
static void enc(EncFn f, CUtensorMap* m, const void* ptr, int rank, const cuuint64_t* dims, const cuuint64_t* strides, const cuuint32_t* box, CUtensorMapSwizzle sw,
                CUtensorMapDataType dt = CU_TENSOR_MAP_DATA_TYPE_BFLOAT16) {
  const cuuint32_t es[3] = {1, 1, 1};
  f(m, dt, rank, (void*)ptr, dims, strides, box, es, CU_TENSOR_MAP_INTERLEAVE_NONE, sw, CU_TENSOR_MAP_L2_PROMOTION_L2_256B, CU_TENSOR_MAP_FLOAT_OOB_FILL_NONE);
}
static void enc2(EncFn f, CUtensorMap* m, const void* ptr, int cols, int rows, int brows) {
  const cuuint64_t d[2] = {(cuuint64_t)cols, (cuuint64_t)rows}, s[1] = {(cuuint64_t)cols * 2}; const cuuint32_t b[2] = {64, (cuuint32_t)brows};
  enc(f, m, ptr, 2, d, s, b, CU_TENSOR_MAP_SWIZZLE_128B);
}
static void encw(EncFn f, CUtensorMap* m, const void* ptr, int cols, int rows) {
  const cuuint64_t d[3] = {64, (cuuint64_t)rows, (cuuint64_t)cols / 64}, s[2] = {(cuuint64_t)cols * 2, 128}; const cuuint32_t b[3] = {64, 64, 2};
  enc(f, m, ptr, 3, d, s, b, CU_TENSOR_MAP_SWIZZLE_128B);
}
extern "C" void kernel_launch(void* const* d_in, const int* in_sizes, int n_in, void* d_out, int out_size) {
  static EncFn fn = nullptr;
  static int ncl = 0;
  static void* zptr = nullptr;
  static void* tptr = nullptr;
  if (!fn) {
    void* p = nullptr; cudaDriverEntryPointQueryResult qr;
    cudaGetDriverEntryPoint("cuTensorMapEncodeTiled", &p, cudaEnableDefault, &qr);
    fn = (EncFn)p;
    cudaFuncSetAttribute(gated_mix_kernel<PH_ALL>, cudaFuncAttributeMaxDynamicSharedMemorySize, SMEM_BYTES);
    cudaFuncSetAttribute(gated_mix_kernel<PH_PRE | PH_KV>, cudaFuncAttributeMaxDynamicSharedMemorySize, SMEM_BYTES);
    cudaFuncSetAttribute(gated_mix_kernel<PH_ATT | PH_CONV>, cudaFuncAttributeMaxDynamicSharedMemorySize, SMEM_BYTES);
    cudaFuncSetAttribute(gated_mix_kernel<PH_OUT>, cudaFuncAttributeMaxDynamicSharedMemorySize, SMEM_BYTES);
    cudaLaunchConfig_t cfg = {}; cfg.gridDim = NCTA; cfg.blockDim = 384; cfg.dynamicSmemBytes = SMEM_BYTES;
    cudaLaunchAttribute at; at.id = cudaLaunchAttributeClusterDimension; at.val.clusterDim.x = 2; at.val.clusterDim.y = 1; at.val.clusterDim.z = 1;
    cfg.attrs = &at; cfg.numAttrs = 1;
    cudaOccupancyMaxActiveClusters(&ncl, gated_mix_kernel<PH_ALL>, &cfg);
    cudaGetSymbolAddress(&zptr, g_z);
    cudaGetSymbolAddress(&tptr, g_T);
  }
  Maps M;
  enc2(fn, &M.x, d_in[0], 1024, 2048, 128);
  enc2(fn, &M.c, d_in[7], 512, 2048, 128);
  enc2(fn, &M.wq, d_in[8], 4096, 1024, 64);
  encw(fn, &M.wk, d_in[9], 4096, 512);
  encw(fn, &M.wv, d_in[10], 4096, 512);
  encw(fn, &M.wo, d_in[11], 1024, 4096);
  { const cuuint64_t d[3] = {64, 32, 1024}, s[2] = {128, 4096}; const cuuint32_t b[3] = {64, 40, 1}; enc(fn, &M.h, d_in[4], 3, d, s, b, CU_TENSOR_MAP_SWIZZLE_NONE); }
  enc2(fn, &M.z, zptr, 2048, 1024, 128);
  enc2(fn, &M.out, d_out, 1024, 2048, 16);
  { const cuuint64_t d[2] = {512, 512 * 16}, s[1] = {2048}; const cuuint32_t b[2] = {256, 8};
    enc(fn, &M.ctx, tptr, 2, d, s, b, CU_TENSOR_MAP_SWIZZLE_NONE, CU_TENSOR_MAP_DATA_TYPE_UINT32); }
  Params P{(const __nv_bfloat16*)d_in[0], (const __nv_bfloat16*)d_in[1], (const __nv_bfloat16*)d_in[2], (const __nv_bfloat16*)d_in[3],
           (const __nv_bfloat16*)d_in[5], (const __nv_bfloat16*)d_in[12]};
  bool split = 2 * ncl < NCTA;
  if (!split) {
    gated_mix_kernel<PH_ALL><<<NCTA, 384, SMEM_BYTES>>>(M, P);
  } else {
    gated_mix_kernel<PH_PRE | PH_KV><<<NCTA, 384, SMEM_BYTES>>>(M, P);
    gated_mix_kernel<PH_ATT | PH_CONV><<<NCTA, 384, SMEM_BYTES>>>(M, P);
    gated_mix_kernel<PH_OUT><<<NCTA, 384, SMEM_BYTES>>>(M, P);
  }
}
```

```cpp
#include <cuda_runtime.h>
#include <cuda.h>
#include <cuda_bf16.h>
#include <stdint.h>

template<int TB> __device__ __forceinline__ void wgmma_ss_n256(float (&d)[128], uint64_t da, uint64_t db, int scale_d) {
  asm volatile("{\n.reg .pred p;\nsetp.ne.b32 p, %130, 0;\n"
    "wgmma.mma_async.sync.aligned.m64n256k16.f32.bf16.bf16 {%0, %1, %2, %3, %4, %5, %6, %7, %8, %9, %10, %11, %12, %13, %14, %15, %16, %17, %18, %19, %20, %21, %22, %23, %24, %25, %26, %27, %28, %29, %30, %31, %32, %33, %34, %35, %36, %37, %38, %39, %40, %41, %42, %43, %44, %45, %46, %47, %48, %49, %50, %51, %52, %53, %54, %55, %56, %57, %58, %59, %60, %61, %62, %63, %64, %65, %66, %67, %68, %69, %70, %71, %72, %73, %74, %75, %76, %77, %78, %79, %80, %81, %82, %83, %84, %85, %86, %87, %88, %89, %90, %91, %92, %93, %94, %95, %96, %97, %98, %99, %100, %101, %102, %103, %104, %105, %106, %107, %108, %109, %110, %111, %112, %113, %114, %115, %116, %117, %118, %119, %120, %121, %122, %123, %124, %125, %126, %127}, %128, %129, p, 1, 1, 0, %131;\n}\n"
    : "+f"(d[0]), "+f"(d[1]), "+f"(d[2]), "+f"(d[3]), "+f"(d[4]), "+f"(d[5]), "+f"(d[6]), "+f"(d[7]), "+f"(d[8]), "+f"(d[9]), "+f"(d[10]), "+f"(d[11]), "+f"(d[12]), "+f"(d[13]), "+f"(d[14]), "+f"(d[15]), "+f"(d[16]), "+f"(d[17]), "+f"(d[18]), "+f"(d[19]), "+f"(d[20]), "+f"(d[21]), "+f"(d[22]), "+f"(d[23]), "+f"(d[24]), "+f"(d[25]), "+f"(d[26]), "+f"(d[27]), "+f"(d[28]), "+f"(d[29]), "+f"(d[30]), "+f"(d[31]), "+f"(d[32]), "+f"(d[33]), "+f"(d[34]), "+f"(d[35]), "+f"(d[36]), "+f"(d[37]), "+f"(d[38]), "+f"(d[39]), "+f"(d[40]), "+f"(d[41]), "+f"(d[42]), "+f"(d[43]), "+f"(d[44]), "+f"(d[45]), "+f"(d[46]), "+f"(d[47]), "+f"(d[48]), "+f"(d[49]), "+f"(d[50]), "+f"(d[51]), "+f"(d[52]), "+f"(d[53]), "+f"(d[54]), "+f"(d[55]), "+f"(d[56]), "+f"(d[57]), "+f"(d[58]), "+f"(d[59]), "+f"(d[60]), "+f"(d[61]), "+f"(d[62]), "+f"(d[63]), "+f"(d[64]), "+f"(d[65]), "+f"(d[66]), "+f"(d[67]), "+f"(d[68]), "+f"(d[69]), "+f"(d[70]), "+f"(d[71]), "+f"(d[72]), "+f"(d[73]), "+f"(d[74]), "+f"(d[75]), "+f"(d[76]), "+f"(d[77]), "+f"(d[78]), "+f"(d[79]), "+f"(d[80]), "+f"(d[81]), "+f"(d[82]), "+f"(d[83]), "+f"(d[84]), "+f"(d[85]), "+f"(d[86]), "+f"(d[87]), "+f"(d[88]), "+f"(d[89]), "+f"(d[90]), "+f"(d[91]), "+f"(d[92]), "+f"(d[93]), "+f"(d[94]), "+f"(d[95]), "+f"(d[96]), "+f"(d[97]), "+f"(d[98]), "+f"(d[99]), "+f"(d[100]), "+f"(d[101]), "+f"(d[102]), "+f"(d[103]), "+f"(d[104]), "+f"(d[105]), "+f"(d[106]), "+f"(d[107]), "+f"(d[108]), "+f"(d[109]), "+f"(d[110]), "+f"(d[111]), "+f"(d[112]), "+f"(d[113]), "+f"(d[114]), "+f"(d[115]), "+f"(d[116]), "+f"(d[117]), "+f"(d[118]), "+f"(d[119]), "+f"(d[120]), "+f"(d[121]), "+f"(d[122]), "+f"(d[123]), "+f"(d[124]), "+f"(d[125]), "+f"(d[126]), "+f"(d[127])
    : "l"(da), "l"(db), "r"(scale_d), "n"(TB));
}
template<int TB> __device__ __forceinline__ void wgmma_ss_n128(float (&d)[64], uint64_t da, uint64_t db, int scale_d) {
  asm volatile("{\n.reg .pred p;\nsetp.ne.b32 p, %66, 0;\n"
    "wgmma.mma_async.sync.aligned.m64n128k16.f32.bf16.bf16 {%0, %1, %2, %3, %4, %5, %6, %7, %8, %9, %10, %11, %12, %13, %14, %15, %16, %17, %18, %19, %20, %21, %22, %23, %24, %25, %26, %27, %28, %29, %30, %31, %32, %33, %34, %35, %36, %37, %38, %39, %40, %41, %42, %43, %44, %45, %46, %47, %48, %49, %50, %51, %52, %53, %54, %55, %56, %57, %58, %59, %60, %61, %62, %63}, %64, %65, p, 1, 1, 0, %67;\n}\n"
    : "+f"(d[0]), "+f"(d[1]), "+f"(d[2]), "+f"(d[3]), "+f"(d[4]), "+f"(d[5]), "+f"(d[6]), "+f"(d[7]), "+f"(d[8]), "+f"(d[9]), "+f"(d[10]), "+f"(d[11]), "+f"(d[12]), "+f"(d[13]), "+f"(d[14]), "+f"(d[15]), "+f"(d[16]), "+f"(d[17]), "+f"(d[18]), "+f"(d[19]), "+f"(d[20]), "+f"(d[21]), "+f"(d[22]), "+f"(d[23]), "+f"(d[24]), "+f"(d[25]), "+f"(d[26]), "+f"(d[27]), "+f"(d[28]), "+f"(d[29]), "+f"(d[30]), "+f"(d[31]), "+f"(d[32]), "+f"(d[33]), "+f"(d[34]), "+f"(d[35]), "+f"(d[36]), "+f"(d[37]), "+f"(d[38]), "+f"(d[39]), "+f"(d[40]), "+f"(d[41]), "+f"(d[42]), "+f"(d[43]), "+f"(d[44]), "+f"(d[45]), "+f"(d[46]), "+f"(d[47]), "+f"(d[48]), "+f"(d[49]), "+f"(d[50]), "+f"(d[51]), "+f"(d[52]), "+f"(d[53]), "+f"(d[54]), "+f"(d[55]), "+f"(d[56]), "+f"(d[57]), "+f"(d[58]), "+f"(d[59]), "+f"(d[60]), "+f"(d[61]), "+f"(d[62]), "+f"(d[63])
    : "l"(da), "l"(db), "r"(scale_d), "n"(TB));
}
template<int TB> __device__ __forceinline__ void wgmma_rs_n128(float (&d)[64], uint32_t a0, uint32_t a1, uint32_t a2, uint32_t a3, uint64_t db, int scale_d) {
  asm volatile("{\n.reg .pred p;\nsetp.ne.b32 p, %69, 0;\n"
    "wgmma.mma_async.sync.aligned.m64n128k16.f32.bf16.bf16 {%0, %1, %2, %3, %4, %5, %6, %7, %8, %9, %10, %11, %12, %13, %14, %15, %16, %17, %18, %19, %20, %21, %22, %23, %24, %25, %26, %27, %28, %29, %30, %31, %32, %33, %34, %35, %36, %37, %38, %39, %40, %41, %42, %43, %44, %45, %46, %47, %48, %49, %50, %51, %52, %53, %54, %55, %56, %57, %58, %59, %60, %61, %62, %63}, {%64, %65, %66, %67}, %68, p, 1, 1, %70;\n}\n"
    : "+f"(d[0]), "+f"(d[1]), "+f"(d[2]), "+f"(d[3]), "+f"(d[4]), "+f"(d[5]), "+f"(d[6]), "+f"(d[7]), "+f"(d[8]), "+f"(d[9]), "+f"(d[10]), "+f"(d[11]), "+f"(d[12]), "+f"(d[13]), "+f"(d[14]), "+f"(d[15]), "+f"(d[16]), "+f"(d[17]), "+f"(d[18]), "+f"(d[19]), "+f"(d[20]), "+f"(d[21]), "+f"(d[22]), "+f"(d[23]), "+f"(d[24]), "+f"(d[25]), "+f"(d[26]), "+f"(d[27]), "+f"(d[28]), "+f"(d[29]), "+f"(d[30]), "+f"(d[31]), "+f"(d[32]), "+f"(d[33]), "+f"(d[34]), "+f"(d[35]), "+f"(d[36]), "+f"(d[37]), "+f"(d[38]), "+f"(d[39]), "+f"(d[40]), "+f"(d[41]), "+f"(d[42]), "+f"(d[43]), "+f"(d[44]), "+f"(d[45]), "+f"(d[46]), "+f"(d[47]), "+f"(d[48]), "+f"(d[49]), "+f"(d[50]), "+f"(d[51]), "+f"(d[52]), "+f"(d[53]), "+f"(d[54]), "+f"(d[55]), "+f"(d[56]), "+f"(d[57]), "+f"(d[58]), "+f"(d[59]), "+f"(d[60]), "+f"(d[61]), "+f"(d[62]), "+f"(d[63])
    : "r"(a0), "r"(a1), "r"(a2), "r"(a3), "l"(db), "r"(scale_d), "n"(TB));
}
template<int TB> __device__ __forceinline__ void wgmma_rs_n64(float (&d)[32], uint32_t a0, uint32_t a1, uint32_t a2, uint32_t a3, uint64_t db, int scale_d) {
  asm volatile("{\n.reg .pred p;\nsetp.ne.b32 p, %37, 0;\n"
    "wgmma.mma_async.sync.aligned.m64n64k16.f32.bf16.bf16 {%0, %1, %2, %3, %4, %5, %6, %7, %8, %9, %10, %11, %12, %13, %14, %15, %16, %17, %18, %19, %20, %21, %22, %23, %24, %25, %26, %27, %28, %29, %30, %31}, {%32, %33, %34, %35}, %36, p, 1, 1, %38;\n}\n"
    : "+f"(d[0]), "+f"(d[1]), "+f"(d[2]), "+f"(d[3]), "+f"(d[4]), "+f"(d[5]), "+f"(d[6]), "+f"(d[7]), "+f"(d[8]), "+f"(d[9]), "+f"(d[10]), "+f"(d[11]), "+f"(d[12]), "+f"(d[13]), "+f"(d[14]), "+f"(d[15]), "+f"(d[16]), "+f"(d[17]), "+f"(d[18]), "+f"(d[19]), "+f"(d[20]), "+f"(d[21]), "+f"(d[22]), "+f"(d[23]), "+f"(d[24]), "+f"(d[25]), "+f"(d[26]), "+f"(d[27]), "+f"(d[28]), "+f"(d[29]), "+f"(d[30]), "+f"(d[31])
    : "r"(a0), "r"(a1), "r"(a2), "r"(a3), "l"(db), "r"(scale_d), "n"(TB));
}
__device__ __forceinline__ void wgmma_pv_sel(float (&d)[64], const uint32_t (&p)[32], uint64_t db, int full, int acc) {
  asm volatile("{\n.reg .pred q, s;\n.reg .b64 t;\nsetp.ne.b32 s, %98, 0;\nsetp.eq.b32 q, %97, 0;\n@q bra.uni LH;\n"
    "wgmma.fence.sync.aligned;\n"
    "add.s64 t, %96, 0;\nwgmma.mma_async.sync.aligned.m64n128k16.f32.bf16.bf16 {%0, %1, %2, %3, %4, %5, %6, %7, %8, %9, %10, %11, %12, %13, %14, %15, %16, %17, %18, %19, %20, %21, %22, %23, %24, %25, %26, %27, %28, %29, %30, %31, %32, %33, %34, %35, %36, %37, %38, %39, %40, %41, %42, %43, %44, %45, %46, %47, %48, %49, %50, %51, %52, %53, %54, %55, %56, %57, %58, %59, %60, %61, %62, %63}, {%64, %65, %66, %67}, t, s, 1, 1, 1;\n"
    "add.s64 t, %96, 256;\nwgmma.mma_async.sync.aligned.m64n128k16.f32.bf16.bf16 {%0, %1, %2, %3, %4, %5, %6, %7, %8, %9, %10, %11, %12, %13, %14, %15, %16, %17, %18, %19, %20, %21, %22, %23, %24, %25, %26, %27, %28, %29, %30, %31, %32, %33, %34, %35, %36, %37, %38, %39, %40, %41, %42, %43, %44, %45, %46, %47, %48, %49, %50, %51, %52, %53, %54, %55, %56, %57, %58, %59, %60, %61, %62, %63}, {%68, %69, %70, %71}, t, 1, 1, 1, 1;\n"
    "add.s64 t, %96, 512;\nwgmma.mma_async.sync.aligned.m64n128k16.f32.bf16.bf16 {%0, %1, %2, %3, %4, %5, %6, %7, %8, %9, %10, %11, %12, %13, %14, %15, %16, %17, %18, %19, %20, %21, %22, %23, %24, %25, %26, %27, %28, %29, %30, %31, %32, %33, %34, %35, %36, %37, %38, %39, %40, %41, %42, %43, %44, %45, %46, %47, %48, %49, %50, %51, %52, %53, %54, %55, %56, %57, %58, %59, %60, %61, %62, %63}, {%72, %73, %74, %75}, t, 1, 1, 1, 1;\n"
    "add.s64 t, %96, 768;\nwgmma.mma_async.sync.aligned.m64n128k16.f32.bf16.bf16 {%0, %1, %2, %3, %4, %5, %6, %7, %8, %9, %10, %11, %12, %13, %14, %15, %16, %17, %18, %19, %20, %21, %22, %23, %24, %25, %26, %27, %28, %29, %30, %31, %32, %33, %34, %35, %36, %37, %38, %39, %40, %41, %42, %43, %44, %45, %46, %47, %48, %49, %50, %51, %52, %53, %54, %55, %56, %57, %58, %59, %60, %61, %62, %63}, {%76, %77, %78, %79}, t, 1, 1, 1, 1;\n"
    "add.s64 t, %96, 1024;\nwgmma.mma_async.sync.aligned.m64n128k16.f32.bf16.bf16 {%0, %1, %2, %3, %4, %5, %6, %7, %8, %9, %10, %11, %12, %13, %14, %15, %16, %17, %18, %19, %20, %21, %22, %23, %24, %25, %26, %27, %28, %29, %30, %31, %32, %33, %34, %35, %36, %37, %38, %39, %40, %41, %42, %43, %44, %45, %46, %47, %48, %49, %50, %51, %52, %53, %54, %55, %56, %57, %58, %59, %60, %61, %62, %63}, {%80, %81, %82, %83}, t, 1, 1, 1, 1;\n"
    "add.s64 t, %96, 1280;\nwgmma.mma_async.sync.aligned.m64n128k16.f32.bf16.bf16 {%0, %1, %2, %3, %4, %5, %6, %7, %8, %9, %10, %11, %12, %13, %14, %15, %16, %17, %18, %19, %20, %21, %22, %23, %24, %25, %26, %27, %28, %29, %30, %31, %32, %33, %34, %35, %36, %37, %38, %39, %40, %41, %42, %43, %44, %45, %46, %47, %48, %49, %50, %51, %52, %53, %54, %55, %56, %57, %58, %59, %60, %61, %62, %63}, {%84, %85, %86, %87}, t, 1, 1, 1, 1;\n"
    "add.s64 t, %96, 1536;\nwgmma.mma_async.sync.aligned.m64n128k16.f32.bf16.bf16 {%0, %1, %2, %3, %4, %5, %6, %7, %8, %9, %10, %11, %12, %13, %14, %15, %16, %17, %18, %19, %20, %21, %22, %23, %24, %25, %26, %27, %28, %29, %30, %31, %32, %33, %34, %35, %36, %37, %38, %39, %40, %41, %42, %43, %44, %45, %46, %47, %48, %49, %50, %51, %52, %53, %54, %55, %56, %57, %58, %59, %60, %61, %62, %63}, {%88, %89, %90, %91}, t, 1, 1, 1, 1;\n"
    "add.s64 t, %96, 1792;\nwgmma.mma_async.sync.aligned.m64n128k16.f32.bf16.bf16 {%0, %1, %2, %3, %4, %5, %6, %7, %8, %9, %10, %11, %12, %13, %14, %15, %16, %17, %18, %19, %20, %21, %22, %23, %24, %25, %26, %27, %28, %29, %30, %31, %32, %33, %34, %35, %36, %37, %38, %39, %40, %41, %42, %43, %44, %45, %46, %47, %48, %49, %50, %51, %52, %53, %54, %55, %56, %57, %58, %59, %60, %61, %62, %63}, {%92, %93, %94, %95}, t, 1, 1, 1, 1;\n"
    "wgmma.commit_group.sync.aligned;\n"
    "bra.uni LE;\nLH:\n"
    "wgmma.fence.sync.aligned;\n"
    "add.s64 t, %96, 0;\nwgmma.mma_async.sync.aligned.m64n128k16.f32.bf16.bf16 {%0, %1, %2, %3, %4, %5, %6, %7, %8, %9, %10, %11, %12, %13, %14, %15, %16, %17, %18, %19, %20, %21, %22, %23, %24, %25, %26, %27, %28, %29, %30, %31, %32, %33, %34, %35, %36, %37, %38, %39, %40, %41, %42, %43, %44, %45, %46, %47, %48, %49, %50, %51, %52, %53, %54, %55, %56, %57, %58, %59, %60, %61, %62, %63}, {%80, %81, %82, %83}, t, s, 1, 1, 1;\n"
    "add.s64 t, %96, 256;\nwgmma.mma_async.sync.aligned.m64n128k16.f32.bf16.bf16 {%0, %1, %2, %3, %4, %5, %6, %7, %8, %9, %10, %11, %12, %13, %14, %15, %16, %17, %18, %19, %20, %21, %22, %23, %24, %25, %26, %27, %28, %29, %30, %31, %32, %33, %34, %35, %36, %37, %38, %39, %40, %41, %42, %43, %44, %45, %46, %47, %48, %49, %50, %51, %52, %53, %54, %55, %56, %57, %58, %59, %60, %61, %62, %63}, {%84, %85, %86, %87}, t, 1, 1, 1, 1;\n"
    "add.s64 t, %96, 512;\nwgmma.mma_async.sync.aligned.m64n128k16.f32.bf16.bf16 {%0, %1, %2, %3, %4, %5, %6, %7, %8, %9, %10, %11, %12, %13, %14, %15, %16, %17, %18, %19, %20, %21, %22, %23, %24, %25, %26, %27, %28, %29, %30, %31, %32, %33, %34, %35, %36, %37, %38, %39, %40, %41, %42, %43, %44, %45, %46, %47, %48, %49, %50, %51, %52, %53, %54, %55, %56, %57, %58, %59, %60, %61, %62, %63}, {%88, %89, %90, %91}, t, 1, 1, 1, 1;\n"
    "add.s64 t, %96, 768;\nwgmma.mma_async.sync.aligned.m64n128k16.f32.bf16.bf16 {%0, %1, %2, %3, %4, %5, %6, %7, %8, %9, %10, %11, %12, %13, %14, %15, %16, %17, %18, %19, %20, %21, %22, %23, %24, %25, %26, %27, %28, %29, %30, %31, %32, %33, %34, %35, %36, %37, %38, %39, %40, %41, %42, %43, %44, %45, %46, %47, %48, %49, %50, %51, %52, %53, %54, %55, %56, %57, %58, %59, %60, %61, %62, %63}, {%92, %93, %94, %95}, t, 1, 1, 1, 1;\n"
    "wgmma.commit_group.sync.aligned;\n"
    "LE:\n}\n"
    : "+f"(d[0]), "+f"(d[1]), "+f"(d[2]), "+f"(d[3]), "+f"(d[4]), "+f"(d[5]), "+f"(d[6]), "+f"(d[7]), "+f"(d[8]), "+f"(d[9]), "+f"(d[10]), "+f"(d[11]), "+f"(d[12]), "+f"(d[13]), "+f"(d[14]), "+f"(d[15]), "+f"(d[16]), "+f"(d[17]), "+f"(d[18]), "+f"(d[19]), "+f"(d[20]), "+f"(d[21]), "+f"(d[22]), "+f"(d[23]), "+f"(d[24]), "+f"(d[25]), "+f"(d[26]), "+f"(d[27]), "+f"(d[28]), "+f"(d[29]), "+f"(d[30]), "+f"(d[31]), "+f"(d[32]), "+f"(d[33]), "+f"(d[34]), "+f"(d[35]), "+f"(d[36]), "+f"(d[37]), "+f"(d[38]), "+f"(d[39]), "+f"(d[40]), "+f"(d[41]), "+f"(d[42]), "+f"(d[43]), "+f"(d[44]), "+f"(d[45]), "+f"(d[46]), "+f"(d[47]), "+f"(d[48]), "+f"(d[49]), "+f"(d[50]), "+f"(d[51]), "+f"(d[52]), "+f"(d[53]), "+f"(d[54]), "+f"(d[55]), "+f"(d[56]), "+f"(d[57]), "+f"(d[58]), "+f"(d[59]), "+f"(d[60]), "+f"(d[61]), "+f"(d[62]), "+f"(d[63])
    : "r"(p[0]), "r"(p[1]), "r"(p[2]), "r"(p[3]), "r"(p[4]), "r"(p[5]), "r"(p[6]), "r"(p[7]), "r"(p[8]), "r"(p[9]), "r"(p[10]), "r"(p[11]), "r"(p[12]), "r"(p[13]), "r"(p[14]), "r"(p[15]), "r"(p[16]), "r"(p[17]), "r"(p[18]), "r"(p[19]), "r"(p[20]), "r"(p[21]), "r"(p[22]), "r"(p[23]), "r"(p[24]), "r"(p[25]), "r"(p[26]), "r"(p[27]), "r"(p[28]), "r"(p[29]), "r"(p[30]), "r"(p[31]), "l"(db), "r"(full), "r"(acc) : "memory");
}

constexpr int NCTA = 132, NREG = 128;
constexpr int UNIT = 16384, NUNIT = 14;
constexpr uint32_t SMEM_BASE = 1024;
constexpr int SM_BAR = NUNIT * UNIT;
constexpr int SMEM_BYTES = SM_BAR + 1024;
constexpr int UPITCH = 4160, UCH = 2 * UPITCH;
constexpr float QSCALE = 0.08838834764831845f * 1.4426950408889634f;
constexpr float BOUND2 = 48.f * 48.f / 1.15f;
#define CONV_REG 4
constexpr int CONV_EXTRA = (1024 - NREG * CONV_REG) / (NCTA - NREG);
constexpr int CH_EXTRA_TOTAL = CONV_EXTRA * (NCTA - NREG);
constexpr int C_KV = 0;
constexpr int C_CTX = 32;
constexpr int C_U = 48;
constexpr int C_Z = 80;
constexpr int C_GATE = 88;
constexpr int C_EXIT = 89;
constexpr int C_GO = 90;
#define GO_ARRIVALS 4
constexpr int C_NUM = 96;
constexpr int CSTRIDE = 32;
constexpr int SM_KMAX = SM_BAR + 256, SM_DUMMY = SM_BAR + 264, SM_EXIT = SM_BAR + 272, SM_SIG = SM_BAR + 320, SM_RDY = SM_BAR + 448;
enum { SIG_KV = 0, SIG_CTX = 2, SIG_Z = 4, SIG_GO = 8 };
enum { RDY_KV = 0, RDY_CTX = 2, RDY_U = 4, RDY_Z = 5 };
enum { PH_PRE = 1, PH_KV = 2, PH_ATT = 4, PH_CONV = 8, PH_OUT = 16, PH_ALL = 31 };

constexpr uint32_t T_CTX = 0, T_KV = 16 * 32 * 32768, T_BYTES = T_KV + 32 * 16 * 65536;
__device__ __align__(1024) uint8_t g_T[T_BYTES];
__device__ __align__(1024) uint8_t g_u[1024 * UCH];
__device__ __align__(1024) __nv_bfloat16 g_z[1024 * 2048];
__device__ __align__(1024) float g_gate[2048];
__device__ __align__(1024) float g_kn2[32 * 128];
__device__ __align__(1024) unsigned g_cnt[C_NUM * CSTRIDE];

struct __align__(64) Maps { CUtensorMap x, c, wq, wk, wv, wo, h, z, out, ctx; };
struct Params {
  const __nv_bfloat16 *x, *k, *v, *shift, *D, *gw;
};

__device__ __forceinline__ void wg_fence() { asm volatile("wgmma.fence.sync.aligned;" ::: "memory"); }
__device__ __forceinline__ void wg_commit() { asm volatile("wgmma.commit_group.sync.aligned;" ::: "memory"); }
template<int N> __device__ __forceinline__ void wg_wait() { asm volatile("wgmma.wait_group.sync.aligned %0;" :: "n"(N) : "memory"); }
__device__ __forceinline__ uint64_t mkdesc(uint32_t addr, uint32_t lbo, uint32_t sbo, uint32_t swz) {
  return (uint64_t)((addr & 0x3FFFF) >> 4) | ((uint64_t)(lbo >> 4) << 16) | ((uint64_t)(sbo >> 4) << 32) | ((uint64_t)swz << 62);
}
__device__ __forceinline__ void mbar_init(uint32_t bar, int cnt) { asm volatile("mbarrier.init.shared::cta.b64 [%0], %1;" :: "r"(bar), "r"(cnt)); }
__device__ __forceinline__ void mbar_expect(uint32_t bar, uint32_t bytes) { asm volatile("mbarrier.arrive.expect_tx.shared::cta.b64 _, [%0], %1;" :: "r"(bar), "r"(bytes) : "memory"); }
__device__ __forceinline__ void mbar_arrive(uint32_t bar) { asm volatile("mbarrier.arrive.shared::cta.b64 _, [%0];" :: "r"(bar) : "memory"); }
__device__ __forceinline__ void mbar_arrive_n(uint32_t bar, int n) { asm volatile("mbarrier.arrive.shared::cta.b64 _, [%0], %1;" :: "r"(bar), "r"(n) : "memory"); }
__device__ __forceinline__ void mbar_wait(uint32_t bar, uint32_t parity) {
  asm volatile("{\n.reg .pred p;\n.reg .u32 n;\nmov.u32 n, 0;\n"
    "LW:\nmbarrier.try_wait.parity.shared::cta.b64 p, [%0], %1;\n@p bra LD;\n"
    "add.u32 n, n, 1;\nsetp.lt.u32 p, n, 2097152;\n@p bra LW;\ntrap;\nLD:\n}\n" :: "r"(bar), "r"(parity) : "memory");
}
__device__ __forceinline__ void mbar_wait_slow(uint32_t bar, uint32_t parity) {
  asm volatile("{\n.reg .pred p;\n.reg .u32 n;\nmov.u32 n, 0;\n"
    "LW:\nmbarrier.test_wait.parity.shared::cta.b64 p, [%0], %1;\n@p bra LD;\n"
    "nanosleep.u32 128;\nadd.u32 n, n, 1;\nsetp.lt.u32 p, n, 4194304;\n@p bra LW;\ntrap;\nLD:\n}\n" :: "r"(bar), "r"(parity) : "memory");
}
__device__ __forceinline__ void mbar_wait_all(uint32_t bar, uint32_t parity) {
  asm volatile("{\n.reg .pred p, q;\n.reg .u32 n;\nmov.u32 n, 0;\n"
    "LW:\nmbarrier.try_wait.parity.shared::cta.b64 p, [%0], %1;\nvote.sync.all.pred q, p, 0xffffffff;\n@q bra.uni LD;\n"
    "add.u32 n, n, 1;\nsetp.lt.u32 q, n, 2097152;\n@q bra.uni LW;\ntrap;\nLD:\n}\n" :: "r"(bar), "r"(parity) : "memory");
}
__device__ __forceinline__ void cnt_wait(const unsigned* p, unsigned target) {
  asm volatile("{\n.reg .pred p;\n.reg .u32 n, v;\nmov.u32 n, 0;\n"
    "LW:\nld.relaxed.gpu.global.u32 v, [%0];\nsetp.ge.u32 p, v, %1;\n@p bra LD;\n"
    "nanosleep.u32 64;\nadd.u32 n, n, 1;\nsetp.lt.u32 p, n, 4194304;\n@p bra LW;\ntrap;\nLD:\nfence.acq_rel.gpu;\nfence.proxy.async;\n}\n" :: "l"(p), "r"(target) : "memory");
}
__device__ __forceinline__ void cnt_poll(const unsigned* p, unsigned target) {
  asm volatile("{\n.reg .pred p;\n.reg .u32 n, v;\nmov.u32 n, 0;\n"
    "LW:\nld.relaxed.gpu.global.u32 v, [%0];\nsetp.ge.u32 p, v, %1;\n@p bra LD;\n"
    "add.u32 n, n, 1;\nsetp.lt.u32 p, n, 4194304;\n@p bra LW;\ntrap;\nLD:\n}\n" :: "l"(p), "r"(target) : "memory");
}
__device__ __forceinline__ void cnt_signal(unsigned* p, int lane) {
  __syncwarp();
  if (lane == 0) asm volatile("red.release.gpu.global.add.u32 [%0], 1;" :: "l"(p) : "memory");
}
__device__ __forceinline__ void cnt_publish(unsigned* p, unsigned n) {
  asm volatile("fence.acq_rel.gpu;\nred.relaxed.gpu.global.add.u32 [%0], %1;" :: "l"(p), "r"(n) : "memory");
}
__device__ __forceinline__ void bulk_g2s(uint32_t dst, const void* src, uint32_t bytes, uint32_t bar) {
  asm volatile("cp.async.bulk.shared::cluster.global.mbarrier::complete_tx::bytes [%0], [%1], %2, [%3];" :: "r"(dst), "l"(src), "r"(bytes), "r"(bar) : "memory");
}
__device__ __forceinline__ void tma2d(uint32_t dst, const CUtensorMap* m, int x, int y, uint32_t bar) {
  asm volatile("cp.async.bulk.tensor.2d.shared::cluster.global.mbarrier::complete_tx::bytes [%0], [%1, {%3, %4}], [%2];" :: "r"(dst), "l"(m), "r"(bar), "r"(x), "r"(y) : "memory");
}
__device__ __forceinline__ void tma3d(uint32_t dst, const CUtensorMap* m, int x, int y, int z, uint32_t bar) {
  asm volatile("cp.async.bulk.tensor.3d.shared::cluster.global.mbarrier::complete_tx::bytes [%0], [%1, {%3, %4, %5}], [%2];" :: "r"(dst), "l"(m), "r"(bar), "r"(x), "r"(y), "r"(z) : "memory");
}
__device__ __forceinline__ void bulk_g2s_mc(uint32_t dst, const void* src, uint32_t bytes, uint32_t bar) {
  asm volatile("cp.async.bulk.shared::cluster.global.mbarrier::complete_tx::bytes.multicast::cluster [%0], [%1], %2, [%3], %4;" :: "r"(dst), "l"(src), "r"(bytes), "r"(bar), "h"((uint16_t)3) : "memory");
}
__device__ __forceinline__ void tma2d_mc(uint32_t dst, const CUtensorMap* m, int x, int y, uint32_t bar) {
  asm volatile("cp.async.bulk.tensor.2d.shared::cluster.global.mbarrier::complete_tx::bytes.multicast::cluster [%0], [%1, {%3, %4}], [%2], %5;" :: "r"(dst), "l"(m), "r"(bar), "r"(x), "r"(y), "h"((uint16_t)3) : "memory");
}
__device__ __forceinline__ void tma3d_mc(uint32_t dst, const CUtensorMap* m, int x, int y, int z, uint32_t bar) {
  asm volatile("cp.async.bulk.tensor.3d.shared::cluster.global.mbarrier::complete_tx::bytes.multicast::cluster [%0], [%1, {%3, %4, %5}], [%2], %6;" :: "r"(dst), "l"(m), "r"(bar), "r"(x), "r"(y), "r"(z), "h"((uint16_t)3) : "memory");
}
__device__ __forceinline__ void tma2d_store(const CUtensorMap* m, uint32_t src, int x, int y) {
  asm volatile("cp.async.bulk.tensor.2d.global.shared::cta.bulk_group [%0, {%2, %3}], [%1];" :: "l"(m), "r"(src), "r"(x), "r"(y) : "memory");
}
__device__ __forceinline__ bool elect() {
  uint32_t r; asm volatile("{\n.reg .pred p;\nelect.sync _|p, 0xffffffff;\nselp.u32 %0, 1, 0, p;\n}\n" : "=r"(r)); return r != 0;
}
__device__ __forceinline__ void cluster_arrive() { asm volatile("barrier.cluster.arrive;" ::: "memory"); }
__device__ __forceinline__ void cluster_wait() { asm volatile("barrier.cluster.wait;" ::: "memory"); }
__device__ __forceinline__ void bar_sync(int id, int n) { asm volatile("bar.sync %0, %1;" :: "r"(id), "r"(n) : "memory"); }
__device__ __forceinline__ void bar_arrive(int id, int n) { asm volatile("bar.arrive %0, %1;" :: "r"(id), "r"(n) : "memory"); }
__device__ __forceinline__ int bar_and(int id, int n, int pred) {
  int r; asm volatile("{\n.reg .pred p, q;\nsetp.ne.b32 p, %3, 0;\nbar.red.and.pred q, %1, %2, p;\nselp.b32 %0, 1, 0, q;\n}\n" : "=r"(r) : "r"(id), "r"(n), "r"(pred) : "memory");
  return r;
}
__device__ __forceinline__ void fence_async_smem() { asm volatile("fence.proxy.async.shared::cta;" ::: "memory"); }
__device__ __forceinline__ float ex2(float x) { float y; asm("ex2.approx.ftz.f32 %0, %1;" : "=f"(y) : "f"(x)); return y; }
__device__ __forceinline__ uint32_t pack_bf16(float lo, float hi) { uint32_t r; asm("cvt.rn.bf16x2.f32 %0, %1, %2;" : "=r"(r) : "f"(hi), "f"(lo)); return r; }
__device__ __forceinline__ uint32_t hmul2(uint32_t a, uint32_t b) { uint32_t r; asm("mul.rn.bf16x2 %0, %1, %2;" : "=r"(r) : "r"(a), "r"(b)); return r; }
__device__ __forceinline__ uint32_t hadd2(uint32_t a, uint32_t b) { uint32_t r; asm("add.rn.bf16x2 %0, %1, %2;" : "=r"(r) : "r"(a), "r"(b)); return r; }
__device__ __forceinline__ uint32_t hfma2(uint32_t a, uint32_t b, uint32_t c) { uint32_t r; asm("fma.rn.bf16x2 %0, %1, %2, %3;" : "=r"(r) : "r"(a), "r"(b), "r"(c)); return r; }
__device__ __forceinline__ float bf_lo(uint32_t a) { return __uint_as_float(a << 16); }
__device__ __forceinline__ float bf_hi(uint32_t a) { return __uint_as_float(a & 0xffff0000u); }
__device__ __forceinline__ uint32_t lds32(uint32_t a) { uint32_t v; asm volatile("ld.shared.u32 %0, [%1];" : "=r"(v) : "r"(a) : "memory"); return v; }
__device__ __forceinline__ float2 lds64f(uint32_t a) { float2 v; asm volatile("ld.shared.v2.f32 {%0,%1}, [%2];" : "=f"(v.x), "=f"(v.y) : "r"(a) : "memory"); return v; }
__device__ __forceinline__ uint4 lds128(uint32_t a) { uint4 v; asm volatile("ld.shared.v4.u32 {%0,%1,%2,%3}, [%4];" : "=r"(v.x), "=r"(v.y), "=r"(v.z), "=r"(v.w) : "r"(a) : "memory"); return v; }
__device__ __forceinline__ void sts64f(uint32_t a, float x, float y) { asm volatile("st.shared.v2.f32 [%0], {%1,%2};" :: "r"(a), "f"(x), "f"(y) : "memory"); }
__device__ __forceinline__ void sts128(uint32_t a, uint4 v) { asm volatile("st.shared.v4.u32 [%0], {%1,%2,%3,%4};" :: "r"(a), "r"(v.x), "r"(v.y), "r"(v.z), "r"(v.w) : "memory"); }
template<int OFF> __device__ __forceinline__ void sts128o(uint32_t a, uint4 v) { asm volatile("st.shared.v4.u32 [%0+%5], {%1,%2,%3,%4};" :: "r"(a), "r"(v.x), "r"(v.y), "r"(v.z), "r"(v.w), "n"(OFF) : "memory"); }
__device__ __forceinline__ void ldsm4(uint32_t a, uint32_t& r0, uint32_t& r1, uint32_t& r2, uint32_t& r3) {
  asm volatile("ldmatrix.sync.aligned.m8n8.x4.shared.b16 {%0,%1,%2,%3}, [%4];" : "=r"(r0), "=r"(r1), "=r"(r2), "=r"(r3) : "r"(a) : "memory");
}
__device__ __forceinline__ void ldsm4t(uint32_t a, uint32_t& r0, uint32_t& r1, uint32_t& r2, uint32_t& r3) {
  asm volatile("ldmatrix.sync.aligned.m8n8.x4.trans.shared.b16 {%0,%1,%2,%3}, [%4];" : "=r"(r0), "=r"(r1), "=r"(r2), "=r"(r3) : "r"(a) : "memory");
}
__device__ __forceinline__ void stsm4(uint32_t a, uint32_t r0, uint32_t r1, uint32_t r2, uint32_t r3) {
  asm volatile("stmatrix.sync.aligned.m8n8.x4.shared.b16 [%0], {%1,%2,%3,%4};" :: "r"(a), "r"(r0), "r"(r1), "r"(r2), "r"(r3) : "memory");
}
template<int N> __device__ __forceinline__ void fence_regs(float (&d)[N]) {
#pragma unroll
  for (int i = 0; i < N; i++) asm volatile("" : "+f"(d[i]) :: "memory");
}
template<int N> __device__ __forceinline__ void fence_regs(uint32_t (&d)[N]) {
#pragma unroll
  for (int i = 0; i < N; i++) asm volatile("" : "+r"(d[i]) :: "memory");
}
__device__ __forceinline__ void sched_fence(float x, uint32_t dummy) {
  asm volatile("{\n.reg .pred p;\nsetp.eq.u32 p, %0, 0x7fc12345;\n@p st.shared.u32 [%1], %0;\n}\n" :: "r"(__float_as_uint(x)), "r"(dummy) : "memory");
}
#define TS(role, i)
#define TR(obj, role, tag)

struct Prod {
  uint32_t base, mask; int lane, nt;
  __device__ __forceinline__ uint32_t full(int u) const { return base + SM_BAR + 8 * u; }
  __device__ __forceinline__ uint32_t addr(int u) const { return base + u * UNIT; }
  __device__ __forceinline__ void acquire(int u, int n) {
    const int v = u + min(lane, n - 1);
    mbar_wait_all(base + SM_BAR + 128 + 8 * v, (mask >> v) & 1);
    mask ^= ((1u << n) - 1) << u;
    TR(*this, 2, 16 + u);
  }
};
struct Cons {
  uint32_t base, rel, mask; int lane, warp, wg, nt;
  __device__ __forceinline__ uint32_t addr(int u) const { return base + u * UNIT; }
  __device__ __forceinline__ static uint32_t daddr(int u) { return SMEM_BASE + u * UNIT; }
  __device__ __forceinline__ void wait(int u) { TR(*this, wg, 1); mbar_wait(base + SM_BAR + 8 * u, (mask >> u) & 1); mask ^= 1u << u; TR(*this, wg, 2); }
  __device__ __forceinline__ void wait2(int u0, int u1) {
    TR(*this, wg, 1);
    const int v = (lane & 1) ? u1 : u0;
    mbar_wait_all(base + SM_BAR + 8 * v, (mask >> v) & 1); mask ^= (1u << u0) | (1u << u1);
    TR(*this, wg, 2);
  }
  __device__ __forceinline__ void skip(int u) { mask ^= 1u << u; }
  __device__ __forceinline__ void release(int u, int n) { TR(*this, wg, 5); if ((lane & 15) < n) asm volatile("mbarrier.arrive.shared::cluster.b64 _, [%0];" :: "r"(rel + 8 * u) : "memory"); }
  __device__ __forceinline__ void release2(int u) { if ((lane & 15) == 0) asm volatile("mbarrier.arrive.shared::cluster.b64 _, [%0], 2;" :: "r"(rel + 8 * u) : "memory"); }
  __device__ __forceinline__ void signal(int i) { __syncwarp(); if (lane == 0) mbar_arrive(base + SM_SIG + 8 * i); }
  __device__ __forceinline__ void turn() { bar_sync(1 + wg, 256); TR(*this, wg, 3); }
  __device__ __forceinline__ void pass() { bar_arrive(2 - wg, 256); TR(*this, wg, 4); }
};
__device__ __forceinline__ int gemm_unit(int ks) { return 3 * ((ks & 3) ^ ((~ks >> 1) & 1)); }
__device__ __forceinline__ int att_slot(int i) { return i == 0 ? 12 : 2 + 2 * i; }
__device__ __forceinline__ int out_mb(int cta) { return cta >> 3; }
__device__ __forceinline__ int out_nb(int cta) { return cta & 7; }
__device__ __forceinline__ int conv_channel(int cta, int i) {
  return cta < NREG ? CH_EXTRA_TOTAL + cta * CONV_REG + i : (i >> 1) * 8 + (cta - NREG) * 2 + (i & 1);
}

template<int OFF, int N> __device__ __forceinline__ void pack_chunk(const float (&a)[N], float sc0, float sc1, uint4& v0, uint4& v1) {
  v0.x = pack_bf16(a[OFF + 0] * sc0, a[OFF + 1] * sc0); v0.y = pack_bf16(a[OFF + 4] * sc0, a[OFF + 5] * sc0);
  v0.z = pack_bf16(a[OFF + 8] * sc0, a[OFF + 9] * sc0); v0.w = pack_bf16(a[OFF + 12] * sc0, a[OFF + 13] * sc0);
  v1.x = pack_bf16(a[OFF + 2] * sc1, a[OFF + 3] * sc1); v1.y = pack_bf16(a[OFF + 6] * sc1, a[OFF + 7] * sc1);
  v1.z = pack_bf16(a[OFF + 10] * sc1, a[OFF + 11] * sc1); v1.w = pack_bf16(a[OFF + 14] * sc1, a[OFF + 15] * sc1);
}
template<int OFF, int N> __device__ __forceinline__ void pack_chunk(const float (&a)[N], uint4& v0, uint4& v1) {
  v0.x = pack_bf16(a[OFF + 0], a[OFF + 1]); v0.y = pack_bf16(a[OFF + 4], a[OFF + 5]);
  v0.z = pack_bf16(a[OFF + 8], a[OFF + 9]); v0.w = pack_bf16(a[OFF + 12], a[OFF + 13]);
  v1.x = pack_bf16(a[OFF + 2], a[OFF + 3]); v1.y = pack_bf16(a[OFF + 6], a[OFF + 7]);
  v1.z = pack_bf16(a[OFF + 10], a[OFF + 11]); v1.w = pack_bf16(a[OFF + 14], a[OFF + 15]);
}
__device__ __forceinline__ void sq_acc(const uint4& v, uint32_t& a) { a = hfma2(v.x, v.x, a); a = hfma2(v.y, v.y, a); a = hfma2(v.z, v.z, a); a = hfma2(v.w, v.w, a); }
__device__ __forceinline__ float norm2_max(uint32_t a0, uint32_t a1) {
  float n0 = bf_lo(a0) + bf_hi(a0), n1 = bf_lo(a1) + bf_hi(a1);
  n0 += __shfl_xor_sync(~0u, n0, 1); n1 += __shfl_xor_sync(~0u, n1, 1);
  n0 += __shfl_xor_sync(~0u, n0, 2); n1 += __shfl_xor_sync(~0u, n1, 2);
  return __uint_as_float(__reduce_max_sync(~0u, max(__float_as_uint(n0) & 0x7fffffffu, __float_as_uint(n1) & 0x7fffffffu)));
}

struct Pend { uint4 lo[8], hi[8]; uint32_t dst; float kn; };
__device__ __forceinline__ void pin(uint4 (&v)[8]) {
#pragma unroll
  for (int i = 0; i < 8; i++) asm volatile("" : "+r"(v[i].x), "+r"(v[i].y), "+r"(v[i].z), "+r"(v[i].w) :: "memory");
}
__device__ __forceinline__ uint32_t atom_off(int lane) { return (lane >> 2) * 64 + (((lane ^ (lane >> 3)) & 3) << 4); }
template<int J0, int J1> __device__ __forceinline__ void tile_store(const uint4 (&v)[8], uint32_t dst, int lane) {
  uint8_t* d = g_T + (dst + atom_off(lane));
#pragma unroll
  for (int j = J0; j < J1; j++) { *(uint4*)(d + j * 512) = v[2 * j]; *(uint4*)(d + j * 512 + 2048) = v[2 * j + 1]; }
}
__device__ __forceinline__ float tile_norm2(const uint4 (&v)[8]) {
  uint32_t n0 = 0, n1 = 0;
#pragma unroll
  for (int j = 0; j < 4; j++) { sq_acc(v[2 * j], n0); sq_acc(v[2 * j + 1], n1); }
  return norm2_max(n0, n1);
}
template<int PART> __device__ __forceinline__ void out_part(Cons& c, Pend& w) {
  if (PART == 0) { w.kn = tile_norm2(w.lo); tile_store<0, 2>(w.lo, w.dst, c.lane); }
  if (PART == 1) tile_store<2, 4>(w.lo, w.dst, c.lane);
  if (PART == 2) {
    const float vn = tile_norm2(w.hi);
    if (c.lane == 0) g_kn2[((w.dst - T_KV) >> 16) * 8 + c.wg * 4 + c.warp] = (vn <= 1.0e30f && vn >= 1.0e-30f) ? w.kn : __uint_as_float(0x7f800000u);
    tile_store<0, 2>(w.hi, w.dst + 32768, c.lane);
  }
  if (PART == 3) tile_store<2, 4>(w.hi, w.dst + 32768, c.lane);
}
template<bool FIRST> __device__ __forceinline__ void kv_issue(Cons& c, float (&acc)[128], int u) {
  const uint64_t da = mkdesc(c.daddr(u) + c.wg * 8192, 16, 1024, 1), db = mkdesc(c.daddr(u + 1), 8192, 1024, 1);
  c.turn();
  wg_fence();
#pragma unroll
  for (int kk = 0; kk < 4; kk++) wgmma_ss_n256<1>(acc, da + kk * 2, db + kk * 128, !(FIRST && kk == 0));
  wg_commit();
  c.pass();
}
__device__ __forceinline__ void cons_kv(Cons& c, int h, int g, Pend& w, bool pend_o) {
#pragma unroll 1
  for (int tile = 0; tile < 2; tile++) {
    float acc[128];
    c.wait(3);
    kv_issue<true>(c, acc, 3);
    if (tile == 1 || pend_o) out_part<0>(c, w);
#pragma unroll 1
    for (int ks = 1; ks < 8; ks++) {
      if (ks == 3 && (tile == 1 || pend_o)) { out_part<1>(c, w); if (tile == 0) c.signal(SIG_CTX); }
      if (ks == 5 && tile == 1) out_part<2>(c, w);
      if (ks == 7 && tile == 1) out_part<3>(c, w);
      const int u = gemm_unit(ks);
      c.wait(u);
      wg_wait<0>();
      c.release(gemm_unit(ks - 1), 3);
      kv_issue<false>(c, acc, u);
    }
    wg_wait<0>(); fence_regs(acc);
    c.release(9, 3);
    pack_chunk<0>(acc, w.lo[0], w.lo[1]);  pack_chunk<16>(acc, w.lo[2], w.lo[3]); pack_chunk<32>(acc, w.lo[4], w.lo[5]); pack_chunk<48>(acc, w.lo[6], w.lo[7]);
    pack_chunk<64>(acc, w.hi[0], w.hi[1]); pack_chunk<80>(acc, w.hi[2], w.hi[3]); pack_chunk<96>(acc, w.hi[4], w.hi[5]); pack_chunk<112>(acc, w.hi[6], w.hi[7]);
    pin(w.lo); pin(w.hi);
    w.dst = T_KV + (h * 16 + 2 * g + tile) * 65536 + (c.wg * 4 + c.warp) * 4096;
  }
}
template<bool FIRST> __device__ __forceinline__ void q_issue(Cons& c, float (&a)[64], float (&b)[64], int u) {
  const uint64_t da = mkdesc(c.daddr(u) + c.wg * 8192, 16, 1024, 1), db = mkdesc(c.daddr(u + 2), 8192, 1024, 1);
  const uint64_t da2 = mkdesc(c.daddr(u + 1) + (1 - c.wg) * 8192, 16, 1024, 1);
  c.turn();
  wg_fence();
#pragma unroll
  for (int kk = 0; kk < 4; kk++) wgmma_ss_n128<1>(a, da + kk * 2, db + kk * 128, !(FIRST && kk == 0));
#pragma unroll
  for (int kk = 0; kk < 4; kk++) wgmma_ss_n128<1>(b, da2 + kk * 2, db + kk * 128, !(FIRST && kk == 0));
  wg_commit();
  c.pass();
}
template<bool PEND_KV> __device__ __forceinline__ int cons_q(Cons& c, int h, Pend& w) {
  float a[64], b[64];
  c.wait(3);
  q_issue<true>(c, a, b, 3);
  if (PEND_KV) out_part<0>(c, w);
#pragma unroll 1
  for (int ks = 1; ks < 16; ks++) {
    if (PEND_KV) {
      if (ks == 2) out_part<1>(c, w);
      if (ks == 4) out_part<2>(c, w);
      if (ks == 5) { out_part<3>(c, w); c.signal(SIG_KV + (h & 1)); }
    }
    const int u = gemm_unit(ks);
    c.wait(u);
    wg_wait<0>();
    c.release(gemm_unit(ks - 1), 3);
    q_issue<false>(c, a, b, u);
  }
  c.wait(0);
  wg_wait<0>(); fence_regs(a); fence_regs(b);
  c.release(9, 3);
  const uint32_t q0 = c.addr(0) + (c.wg * 4 + c.warp) * 4096 + atom_off(c.lane);
  uint32_t a0 = 0, a1 = 0, e0 = 0, e1 = 0;
  uint4 v0, v1;
#define Q_CHUNK(J) pack_chunk<16 * J>(a, QSCALE, QSCALE, v0, v1); sts128o<J * 512>(q0, v0); sts128o<J * 512 + 2048>(q0, v1); sq_acc(v0, a0); sq_acc(v1, a1); \
  pack_chunk<16 * J>(b, QSCALE, QSCALE, v0, v1); sts128o<32768 + J * 512>(q0, v0); sts128o<32768 + J * 512 + 2048>(q0, v1); sq_acc(v0, e0); sq_acc(v1, e1);
  Q_CHUNK(0) Q_CHUNK(1) Q_CHUNK(2) Q_CHUNK(3)
#undef Q_CHUNK
  TR(c, c.wg, 40);
  fence_async_smem();
  const float qa = norm2_max(a0, a1), qb = norm2_max(e0, e1);
  const float kn = __uint_as_float(lds32(c.base + SM_KMAX + 4 * (h & 1)));
  TR(c, c.wg, 42);
  return __shfl_sync(~0u, bar_and(3 + c.wg, 128, (qa * kn <= BOUND2) && (qb * kn <= BOUND2)), 0);
}

__device__ __forceinline__ void issue_qk(float (&s)[64], uint32_t qaddr, uint32_t kaddr) {
  const uint64_t da = mkdesc(qaddr, 16, 2048, 2), db = mkdesc(kaddr, 16, 2048, 2);
#pragma unroll
  for (int kk = 0; kk < 8; kk++) wgmma_ss_n128<0>(s, da + (kk >> 1) * 32 + (kk & 1) * 2, db + (kk >> 1) * 32 + (kk & 1) * 2, kk > 0);
  wg_commit();
}
template<bool FRESH, int NK> __device__ __forceinline__ void issue_pv_n(float (&o)[64], uint32_t (&p)[32], uint32_t vaddr) {
  const uint64_t db = mkdesc(vaddr, 512, 2048, 2);
#pragma unroll
  for (int kk = 0; kk < NK; kk++) wgmma_rs_n128<1>(o, p[4 * kk], p[4 * kk + 1], p[4 * kk + 2], p[4 * kk + 3], db + kk * 256, !(FRESH && kk == 0));
  wg_commit();
}
template<bool FRESH> __device__ __forceinline__ void issue_pv(float (&o)[64], uint32_t (&p)[32], uint32_t vaddr, bool full) {
  wgmma_pv_sel(o, p, mkdesc(vaddr, 512, 2048, 2), full, FRESH ? gridDim.y - 1 : 1);
}
template<int A, int B> __device__ __forceinline__ void exp_rng(float (&s)[64]) {
#pragma unroll
  for (int i = 4 * A; i < 4 * B; i++) s[i] = ex2(s[i]);
}
template<int A, int B> __device__ __forceinline__ void sum_rng(const float (&s)[64], float (&l)[4]) {
#pragma unroll
  for (int i = A; i < B; i++) { l[0] += s[4 * i]; l[1] += s[4 * i + 1]; l[2] += s[4 * i + 2]; l[3] += s[4 * i + 3]; }
}
template<int A, int B> __device__ __forceinline__ void cvt_p(const float (&s)[64], uint32_t (&p)[32]) {
#pragma unroll
  for (int i = 2 * A; i < 2 * B; i++) p[i] = pack_bf16(s[2 * i], s[2 * i + 1]);
}
template<int K0> __device__ __forceinline__ void mask_half(float (&s)[64], int warp, int lane) {
  const int l0 = warp + (2 * (lane & 3) <= (lane >> 2)), l1 = warp + (2 * (lane & 3) < (lane >> 2));
#pragma unroll
  for (int k = 0; k < 4; k++) {
    float* t = s + 8 * (K0 + k);
    if (k >= l0) { t[0] = -INFINITY; t[6] = -INFINITY; }
    if (k >= l1) { t[1] = -INFINITY; t[7] = -INFINITY; }
    if (k > warp) { t[2] = -INFINITY; t[3] = -INFINITY; }
    if (k >= warp) { t[4] = -INFINITY; t[5] = -INFINITY; }
  }
}
__device__ __forceinline__ void mask_diag(float (&s)[64], int lim) {
#pragma unroll
  for (int i = 0; i < 16; i++) {
    if (8 * i > lim) s[4 * i] = -INFINITY;
    if (8 * i + 1 > lim) s[4 * i + 1] = -INFINITY;
    if (8 * i - 8 > lim) s[4 * i + 2] = -INFINITY;
    if (8 * i - 7 > lim) s[4 * i + 3] = -INFINITY;
  }
}
__device__ __forceinline__ void row_inv(float& l0, float& l1) {
  l0 += __shfl_xor_sync(~0u, l0, 1); l1 += __shfl_xor_sync(~0u, l1, 1);
  l0 += __shfl_xor_sync(~0u, l0, 2); l1 += __shfl_xor_sync(~0u, l1, 2);
  l0 = __fdividef(1.f, l0); l1 = __fdividef(1.f, l1);
}
__device__ __forceinline__ void pack_o(const float (&o)[64], float i0, float i1, uint4 (&v)[8]) {
  pack_chunk<0>(o, i0, i1, v[0], v[1]); pack_chunk<16>(o, i0, i1, v[2], v[3]);
  pack_chunk<32>(o, i0, i1, v[4], v[5]); pack_chunk<48>(o, i0, i1, v[6], v[7]);
  pin(v);
}
__device__ __forceinline__ void softmax_safe(float (&s)[64], float& m0, float& m1, float& sc0, float& sc1) {
  float a0 = m0, a1 = m1;
#pragma unroll
  for (int i = 0; i < 16; i++) { a0 = fmaxf(a0, fmaxf(s[4 * i], s[4 * i + 1])); a1 = fmaxf(a1, fmaxf(s[4 * i + 2], s[4 * i + 3])); }
  a0 = fmaxf(a0, __shfl_xor_sync(~0u, a0, 1)); a1 = fmaxf(a1, __shfl_xor_sync(~0u, a1, 1));
  a0 = fmaxf(a0, __shfl_xor_sync(~0u, a0, 2)); a1 = fmaxf(a1, __shfl_xor_sync(~0u, a1, 2));
  sc0 = ex2(m0 - a0); sc1 = ex2(m1 - a1);
  m0 = a0; m1 = a1;
#pragma unroll
  for (int i = 0; i < 16; i++) { s[4 * i] -= a0; s[4 * i + 1] -= a0; s[4 * i + 2] -= a1; s[4 * i + 3] -= a1; }
}
struct Att {
  float s[64], o[64], l[4], i0, i1; uint32_t p[32];
  int si; uint32_t qaddr;
};
__device__ __forceinline__ uint32_t ctx_off(const Cons& c, int h, int qb, int rowhalf) { return T_CTX + (qb * 32 + h) * 32768 + (rowhalf * 4 + c.warp) * 4096; }
template<bool DIAG, bool DRAIN>
__device__ __forceinline__ void att_step(Cons& c, Att& a, bool qkfull, bool pvfull, int relq, uint32_t dst) {
  const int uk = att_slot(a.si); a.si = a.si == 4 ? 0 : a.si + 1;
  const int uv = att_slot(a.si); a.si = a.si == 4 ? 0 : a.si + 1;
  if (DRAIN) c.wait(uk); else c.wait2(uk, uv);
  c.turn();
  fence_regs(a.o); fence_regs(a.p);
  if (DIAG) { wg_fence(); issue_qk(a.s, a.qaddr, c.daddr(uk) - (qkfull ? 0 : 16384)); }
  else { wg_fence(); issue_qk(a.s, a.qaddr, c.daddr(uk)); }
  if (DRAIN) {
    c.wait(uv);
    fence_regs(a.o);
    uint4 v[8];
    pack_o(a.o, a.i0, a.i1, v); tile_store<0, 4>(v, dst, c.lane);
  }
  if (DRAIN || DIAG) issue_pv<DRAIN>(a.o, a.p, c.daddr(uv), pvfull); else issue_pv_n<false, 8>(a.o, a.p, c.daddr(uv));
  c.pass();
  wg_wait<1>(); fence_regs(a.s);
  c.release(uk, 2);
  if (relq >= 0) c.release(relq, 2);
  constexpr int SPLIT = DIAG ? 8 : 6;
  if (DIAG) mask_half<4>(a.s, c.warp, c.lane);
  exp_rng<SPLIT, 16>(a.s); sum_rng<SPLIT, 16>(a.s, a.l);
  sched_fence((a.l[0] + a.l[1]) + (a.l[2] + a.l[3]), c.base + SM_DUMMY);
  wg_wait<0>(); fence_regs(a.o); fence_regs(a.p);
  c.release(uv, 2);
  cvt_p<SPLIT, 16>(a.s, a.p);
  if (!DIAG || qkfull) { exp_rng<0, SPLIT>(a.s); sum_rng<0, SPLIT>(a.s, a.l); cvt_p<0, SPLIT>(a.s, a.p); }
}
__device__ __forceinline__ void att_first(Cons& c, Att& a) {
  a.si = 1; a.qaddr = c.daddr(0) + c.wg * 16384;
  c.wait(12);
  c.turn();
  wg_fence();
  issue_qk(a.s, a.qaddr, c.daddr(12));
  c.pass();
#pragma unroll
  for (int i = 0; i < 64; i++) a.o[i] = 0.f;
  a.l[0] = a.l[1] = a.l[2] = a.l[3] = 0.f; a.i0 = a.i1 = 0.f;
  wg_wait<0>(); fence_regs(a.s);
  c.release(12, 2);
}
__device__ __forceinline__ void att_switch(Att& a) {
  a.i0 = a.l[0] + a.l[1]; a.i1 = a.l[2] + a.l[3]; row_inv(a.i0, a.i1);
  a.l[0] = a.l[1] = a.l[2] = a.l[3] = 0.f;
  a.qaddr += 32768;
}
__device__ __forceinline__ void att_drain_now(Cons& c, Att& a, uint32_t dst) {
  uint4 v[8];
  pack_o(a.o, a.i0, a.i1, v); tile_store<0, 4>(v, dst, c.lane);
#pragma unroll
  for (int i = 0; i < 64; i++) a.o[i] = 0.f;
}
__device__ __forceinline__ void att_last(Cons& c, Att& a, Pend& w, bool pvfull, uint32_t dst) {
  const int uv = att_slot(a.si);
  c.wait(uv);
  c.turn();
  fence_regs(a.o); fence_regs(a.p);
  issue_pv<false>(a.o, a.p, c.daddr(uv), pvfull);
  c.pass();
  a.i0 = a.l[0] + a.l[1]; a.i1 = a.l[2] + a.l[3]; row_inv(a.i0, a.i1);
  wg_wait<0>(); fence_regs(a.o); fence_regs(a.p);
  c.release(uv, 2);
  pack_o(a.o, a.i0, a.i1, w.lo);
  w.dst = dst;
}
__device__ __forceinline__ void cons_att_fast(Cons& c, Att& a, int h, int g) {
  exp_rng<0, 16>(a.s); sum_rng<0, 16>(a.s, a.l); cvt_p<0, 16>(a.s, a.p);
#pragma unroll 1
  for (int t = 0; t < 2; t++) {
#pragma unroll 1
    for (int j = t == 0 ? 14 - g : g - 1; j > 0; j--) att_step<false, false>(c, a, true, true, (t == 1 && j == 1) ? 2 : -1, 0);
    if (t == 0) {
#pragma unroll 1
      for (int d = 0; d < 2; d++) {
        att_step<true, false>(c, a, d != c.wg, !(d == 1 && c.wg == 0), d == 0 ? 0 : (g == 0 ? 2 : -1), 0);
        if (d == 0) att_switch(a);
      }
      if (g > 0) att_step<false, true>(c, a, true, c.wg == 0, g == 1 ? 2 : -1, ctx_off(c, h, 15 - g, c.wg));
      else att_drain_now(c, a, ctx_off(c, h, 15, c.wg));
    }
  }
}
__device__ __forceinline__ void cons_att_safe(Cons& c, Att& a, int h, int g) {
  float m0 = -INFINITY, m1 = -INFINITY, sc0, sc1;
#pragma unroll 1
  for (int st = 0; st <= 16; st++) {
    const bool sw = st == 16 - g;
    if (st > 0) {
      if (sw) att_switch(a);
      const int uk = att_slot(a.si); a.si = a.si == 4 ? 0 : a.si + 1;
      const int uv = att_slot(a.si); a.si = a.si == 4 ? 0 : a.si + 1;
      c.wait2(uk, uv);
      c.turn();
      fence_regs(a.o); fence_regs(a.p);
      wg_fence();
      issue_qk(a.s, a.qaddr, c.daddr(uk));
      issue_pv_n<false, 8>(a.o, a.p, c.daddr(uv));
      c.pass();
      wg_wait<0>(); fence_regs(a.s); fence_regs(a.o); fence_regs(a.p);
      c.release(uk, 2); c.release(uv, 2);
      if (st == 15 - g) c.release(0, 2);
      if (st == 16) c.release(2, 2);
      if (sw) { att_drain_now(c, a, ctx_off(c, h, 15 - g, c.wg)); m0 = m1 = -INFINITY; }
      if (sw || st == 15 - g) mask_diag(a.s, (sw ? 1 - c.wg : c.wg) * 64 + c.warp * 16 + (c.lane >> 2) - 2 * (c.lane & 3));
    }
    softmax_safe(a.s, m0, m1, sc0, sc1);
    a.l[0] *= sc0; a.l[1] *= sc0; a.l[2] *= sc1; a.l[3] *= sc1;
    exp_rng<0, 16>(a.s); sum_rng<0, 16>(a.s, a.l); cvt_p<0, 16>(a.s, a.p);
#pragma unroll
    for (int i = 0; i < 16; i++) { a.o[4 * i] *= sc0; a.o[4 * i + 1] *= sc0; a.o[4 * i + 2] *= sc1; a.o[4 * i + 3] *= sc1; }
  }
}
__device__ __forceinline__ void cons_att(Cons& c, int h, int g, int fast, Pend& w) {
  Att a;
  att_first(c, a);
  if (fast) cons_att_fast(c, a, h, g);
  else {
#pragma unroll
    for (int i = 0; i < 32; i++) a.p[i] = 0;
    cons_att_safe(c, a, h, g);
  }
  att_last(c, a, w, !(fast && g == 0 && c.wg == 1), ctx_off(c, h, g, 1 - c.wg));
}

constexpr int CV_H = 1024, CV_U = 5120, CV_D = CV_U + 4128, CV_ROW = 1056;
template<int OFF> __device__ __forceinline__ uint32_t lds32o(uint32_t a) { uint32_t v; asm volatile("ld.shared.u32 %0, [%1+%2];" : "=r"(v) : "r"(a), "n"(OFF) : "memory"); return v; }
template<int G> __device__ __forceinline__ void conv_lda(uint32_t (&a)[64], uint32_t p) {
  a[4 * G + 0] = lds32o<-256 * G>(p);
  a[4 * G + 1] = lds32o<-256 * G - 128>(p);
  a[4 * G + 2] = lds32o<-256 * G + 16>(p);
  a[4 * G + 3] = lds32o<-256 * G - 112>(p);
  if constexpr (G < 15) conv_lda<G + 1>(a, p);
}
template<int R, int G0, int G1> __device__ __forceinline__ void conv_mma(float (&d)[32], const uint32_t (&a)[64], uint64_t db) {
#pragma unroll
  for (int G = G0; G < G1; G++) wgmma_rs_n64<0>(d, a[4 * G], a[4 * G + 1], a[4 * G + 2], a[4 * G + 3], db + 64 * R - 16 * G, G > 0);
}
template<int R> __device__ __forceinline__ void conv_st(const float (&d)[32], uint32_t wq, float& c0, float& c1) {
#pragma unroll
  for (int n = 0; n < 8; n++) { sts64f(wq + (R * 64 + n * 8) * 4, d[4 * n] + c0, d[4 * n + 1] + c1); c0 = d[4 * n + 2]; c1 = d[4 * n + 3]; }
}
__device__ __forceinline__ void cons_conv(Cons& c, int cta, int nch) {
  const int r = c.lane >> 2, q = c.lane & 3, tid = c.warp * 32 + c.lane;
  const uint32_t part = c.addr(4) - 2048 + (1 - c.wg) * (32 * CV_ROW) + 32;
  const uint32_t aoff = CV_U + ((r & 1) ? 0 : UPITCH) + 4 * (((2039 - r) >> 1) + q - 8 * c.warp);
  const uint32_t wq = part + (c.warp * 8 + r) * CV_ROW + q * 8, rq = part + tid * 8;
  uint32_t a[64];
  c.wait(c.wg); c.skip(c.wg ^ 1);
  conv_lda<0>(a, c.addr(c.wg) + aoff);
  c.wait(4);
  sts64f(part + (tid >> 2) * CV_ROW - 32 + q * 8, 0.f, 0.f);
#pragma unroll 1
  for (int i = 0; i < nch / 2; i++) {
    const int u = 2 * (i & 1) + c.wg;
    float d0[32], d1[32], d2[32], d3[32];
    float c0 = 0.f, c1 = 0.f;
    const uint64_t db = mkdesc(c.daddr(u) + CV_H - 16, 16, 128, 0);
    c.turn();
    fence_regs(a);
    wg_fence();
    conv_mma<0, 0, 4>(d0, a, db); conv_mma<1, 0, 8>(d1, a, db); wg_commit();
    conv_mma<2, 0, 12>(d2, a, db); wg_commit();
    wg_wait<1>(); fence_regs(d0); fence_regs(d1);
    conv_st<0>(d0, wq, c0, c1);
    wg_fence();
    conv_mma<3, 0, 8>(d3, a, db);
    conv_st<1>(d1, wq, c0, c1);
    conv_mma<3, 8, 16>(d3, a, db); wg_commit();
    c.pass();
    if (i == nch / 2 - 1 && (GO_ARRIVALS == 8 || c.wg == 0)) c.signal(SIG_GO);
    wg_wait<1>(); fence_regs(d2);
    conv_st<2>(d2, wq, c0, c1);
    wg_wait<0>(); fence_regs(d3); fence_regs(a);
    conv_st<3>(d3, wq, c0, c1);
    TR(c, c.wg, 50);
    const uint32_t ub = c.addr(u);
    const uint4 ua = lds128(ub + CV_U + 4064 - 32 * tid + 16), uc = lds128(ub + CV_U + 4064 - 32 * tid);
    const uint32_t D2 = lds32(ub + CV_D);
    bar_sync(3 + c.wg, 128);
    c.release2(u);
    TR(c, c.wg, 51);
    float y0[8], y1[8];
#pragma unroll
    for (int rr = 0; rr < 8; rr++) { const float2 v = lds64f(rq + rr * CV_ROW); y0[rr] = v.x; y1[rr] = v.y; }
#pragma unroll
    for (int w = 1; w < 4; w++) {
#pragma unroll
      for (int rr = 0; rr < 8; rr++) { const float2 v = lds64f(rq + (w * 8 + rr) * CV_ROW - w * 8); y0[rr] += v.x; y1[rr] += v.y; }
    }
    if (i + 1 < nch / 2) { c.wait(u ^ 2); c.skip(u ^ 3); conv_lda<0>(a, c.addr(u ^ 2) + aoff); }
    uint4 z0, z1;
    z0.x = hadd2(pack_bf16(y0[0], y0[1]), hmul2(__byte_perm(ua.w, 0, 0x1032), D2));
    z0.y = hadd2(pack_bf16(y0[2], y0[3]), hmul2(__byte_perm(ua.z, 0, 0x1032), D2));
    z0.z = hadd2(pack_bf16(y0[4], y0[5]), hmul2(__byte_perm(ua.y, 0, 0x1032), D2));
    z0.w = hadd2(pack_bf16(y0[6], y0[7]), hmul2(__byte_perm(ua.x, 0, 0x1032), D2));
    z1.x = hadd2(pack_bf16(y1[0], y1[1]), hmul2(__byte_perm(uc.w, 0, 0x1032), D2));
    z1.y = hadd2(pack_bf16(y1[2], y1[3]), hmul2(__byte_perm(uc.z, 0, 0x1032), D2));
    z1.z = hadd2(pack_bf16(y1[4], y1[5]), hmul2(__byte_perm(uc.y, 0, 0x1032), D2));
    z1.w = hadd2(pack_bf16(y1[6], y1[7]), hmul2(__byte_perm(uc.x, 0, 0x1032), D2));
    uint4* zp = (uint4*)(g_z + (size_t)conv_channel(cta, 2 * i + c.wg) * 2048 + tid * 16);
    zp[0] = z0; zp[1] = z1;
    TR(c, c.wg, 52);
    if ((i & 15) == 15 || i == nch / 2 - 1) c.signal(SIG_Z + (i >> 4));
  }
  c.release(4, 4);
}

constexpr int OUT_XZ_AT = 58;
__device__ __forceinline__ int out_slot(int i) { return (0x26408CA >> (4 * i)) & 15; }
__device__ __forceinline__ void cons_out(Cons& c, const Maps& M, int mb, int nb) {
  float acc[64];
  uint32_t ga[32];
  int si = 0, pu, u;
#define OUT_STEP(FIRST) { \
    u = out_slot(si); si = si == 6 ? 0 : si + 1; \
    c.wait(u); \
    const uint64_t da = mkdesc(c.daddr(u) + c.wg * 8192, 16, 1024, 2), db = mkdesc(c.daddr(u + 1), 8192, 1024, 1); \
    wg_fence(); \
    _Pragma("unroll") for (int kk = 0; kk < 4; kk++) wgmma_ss_n128<1>(acc, da + (kk >> 1) * 32 + (kk & 1) * 2, db + kk * 128, !(FIRST && kk == 0)); \
    wg_commit(); }
  OUT_STEP(true)
  pu = u;
#pragma unroll 1
  for (int ks = 1; ks <= OUT_XZ_AT; ks++) { OUT_STEP(false) wg_wait<1>(); c.release(pu, 2); pu = u; }
  const int ux = out_slot(si); si = si == 6 ? 0 : si + 1;
  const int uz = out_slot(si); si = si == 6 ? 0 : si + 1;
  OUT_STEP(false)
  c.wait2(ux, uz);
  const int row = mb * 128 + c.wg * 64 + c.warp * 16 + (c.lane >> 2);
  const float g0 = __ldcg(g_gate + row), g1 = __ldcg(g_gate + row + 8);
  const uint32_t gg0 = pack_bf16(g0, g0), gg1 = pack_bf16(g1, g1);
  const uint32_t og0 = pack_bf16(1.f - g0, 1.f - g0), og1 = pack_bf16(1.f - g1, 1.f - g1);
  const int xr = c.wg * 64 + c.warp * 16 + (c.lane & 15);
  const uint32_t xa = c.addr(ux) + xr * 128, xs = xr & 7, xh = c.lane >> 4;
  const int zr = (c.lane & 7) + ((c.lane >> 4) << 3);
  const uint32_t za = c.addr(uz) + c.wg * 16384 + zr * 128 + (((c.warp * 2 + ((c.lane >> 3) & 1)) ^ (zr & 7)) << 4);
#pragma unroll
  for (int i = 0; i < 8; i++) {
    uint32_t x0, x1, x2, x3, z0, z1, z2, z3;
    ldsm4(xa + (i >> 2) * 16384 + ((((i & 3) * 2 + xh) ^ xs) << 4), x0, x1, x2, x3);
    ldsm4t(za + i * 2048, z0, z1, z2, z3);
    ga[4 * i + 0] = hmul2(gg0, hmul2(x0, z0)); ga[4 * i + 1] = hmul2(gg1, hmul2(x1, z1));
    ga[4 * i + 2] = hmul2(gg0, hmul2(x2, z2)); ga[4 * i + 3] = hmul2(gg1, hmul2(x3, z3));
  }
  wg_wait<1>(); c.release(pu, 2);
#pragma unroll 1
  for (int ks = OUT_XZ_AT + 2; ks < 64; ks++) OUT_STEP(false)
#undef OUT_STEP
  asm volatile("barrier.cluster.arrive.relaxed;" ::: "memory");
  wg_wait<0>(); fence_regs(acc);
#pragma unroll
  for (int i = 0; i < 8; i++) {
    const uint32_t r0 = hadd2(ga[4 * i + 0], hmul2(og0, pack_bf16(acc[8 * i + 0], acc[8 * i + 1])));
    const uint32_t r1 = hadd2(ga[4 * i + 1], hmul2(og1, pack_bf16(acc[8 * i + 2], acc[8 * i + 3])));
    const uint32_t r2 = hadd2(ga[4 * i + 2], hmul2(og0, pack_bf16(acc[8 * i + 4], acc[8 * i + 5])));
    const uint32_t r3 = hadd2(ga[4 * i + 3], hmul2(og1, pack_bf16(acc[8 * i + 6], acc[8 * i + 7])));
    stsm4(xa + (i >> 2) * 16384 + ((((i & 3) * 2 + xh) ^ xs) << 4), r0, r1, r2, r3);
  }
  fence_async_smem();
  __syncwarp();
  if (c.lane < 2) {
    const int r0 = c.wg * 64 + c.warp * 16;
    tma2d_store(&M.out, c.addr(ux) + c.lane * 16384 + r0 * 128, nb * 128 + c.lane * 64, mb * 128 + r0);
    asm volatile("cp.async.bulk.commit_group;\ncp.async.bulk.wait_group.read 0;" ::: "memory");
  }
}

__device__ __forceinline__ void prod_conv(Prod& p, const Maps& M, int cta, int nch) {
  int ready = -1;
#pragma unroll 1
  for (int i = 0; i < nch; i++) {
    const int ch = conv_channel(cta, i);
    const int u = i & 3;
    if ((ch >> 5) != ready) { ready = ch >> 5; if (cta < NREG) mbar_wait(p.base + SM_RDY + 8 * RDY_U, 0); else cnt_wait(g_cnt + (C_U + ready) * CSTRIDE, 128); }
    p.acquire(u, 1);
    if (elect()) {
      mbar_expect(p.full(u), 5120 + UCH);
      tma3d(p.addr(u), &M.h, 0, -8, ch, p.full(u));
      bulk_g2s(p.addr(u) + CV_U, g_u + (size_t)ch * UCH, UCH, p.full(u));
    }
    if (i == 3) { p.acquire(4, 4); if (elect()) mbar_arrive(p.full(4)); }
  }
}
template<int MASK> __device__ __forceinline__ void producer(const Maps& M, const Params& P, uint32_t base, int cta, int lane) {
  Prod p{base, 0xffffffffu, lane, (cta * 3 + 2) * 2048};
  if (cta >= NREG) { if (MASK & PH_CONV) prod_conv(p, M, cta, CONV_EXTRA); return; }
  const int g = cta & 7, j = cta >> 3, rank = cta & 1;
#pragma unroll 1
  for (int half = 0; half < 2; half++) {
    const int h = 2 * j + half;
    if (MASK & PH_KV) {
#pragma unroll 1
      for (int it = 0; it < 16; it++) {
        const int u = gemm_unit(it), ks = it & 7;
        p.acquire(u, 3);
        if (elect()) {
          mbar_expect(p.full(u), 3 * UNIT);
          tma2d(p.addr(u), &M.c, ks * 64, (2 * g + (it >> 3)) * 128, p.full(u));
          tma3d_mc(p.addr(u + 1 + rank), rank ? &M.wv : &M.wk, 0, ks * 64, 2 * h, p.full(u));
        }
      }
    }
    if (MASK & PH_ATT) {
#pragma unroll 1
      for (int ks = 0; ks < 16; ks++) {
        const int u = gemm_unit(ks);
        p.acquire(u, 3);
        if (elect()) {
          mbar_expect(p.full(u), 3 * UNIT);
          tma2d(p.addr(u), &M.x, ks * 64, (15 - g) * 128, p.full(u));
          tma2d(p.addr(u + 1), &M.x, ks * 64, g * 128, p.full(u));
          tma2d_mc(p.addr(u + 2) + rank * 8192, &M.wq, h * 128 + rank * 64, ks * 64, p.full(u));
        }
      }
      TS(2, 8 * half + 0);
      mbar_wait(base + SM_RDY + 8 * (RDY_KV + half), 0);
      TS(2, 8 * half + 1);
      const uint8_t* KVh = g_T + T_KV + (size_t)h * 16 * 65536;
      int si = 0;
#pragma unroll 1
      for (int i = 0; i < 34; i++) {
        const int isv = (i > 0 && !(i & 1)) || i == 33;
        const int st = i == 33 ? 16 : (isv ? (i >> 1) - 1 : (i + 1) >> 1);
        const uint8_t* src = KVh + (st <= 15 - g ? st : 16 - st) * 65536 + isv * 32768;
        const int u = att_slot(si); si = si == 4 ? 0 : si + 1;
        p.acquire(u, 2);
        if (elect()) {
          mbar_expect(p.full(u), 32768);
          if (st == 15 - (g & 6)) bulk_g2s(p.addr(u), src, 32768, p.full(u));
          else bulk_g2s_mc(p.addr(u + rank), src + rank * UNIT, UNIT, p.full(u));
        }
        if (i == 0) { p.acquire(0, 4); if (elect()) mbar_arrive(p.full(0)); }
      }
    }
  }
  if (MASK & PH_CONV) prod_conv(p, M, cta, CONV_REG);
  if (MASK & PH_OUT) {
    const int mb = out_mb(cta), nb = out_nb(cta);
    int si = 0;
#pragma unroll 1
    for (int ks = 0; ks < 64; ks++) {
      if ((ks & 31) == 0) { TS(2, 16 + (ks >> 4)); mbar_wait(base + SM_RDY + 8 * (RDY_CTX + (ks >> 5)), 0); TS(2, 17 + (ks >> 4)); }
      const int kb = ((ks & 31) >> 1) * 4 + (ks >> 5) * 2 + (ks & 1);
      const int u = out_slot(si); si = si == 6 ? 0 : si + 1;
      p.acquire(u, 2);
      if (elect()) {
        mbar_expect(p.full(u), 2 * UNIT);
        tma2d_mc(p.addr(u) + rank * 8192, &M.ctx, (kb & 1) * 256, (mb * 32 + (kb >> 1)) * 16 + rank * 8, p.full(u));
        tma3d(p.addr(u + 1), &M.wo, 0, kb * 64, 2 * nb, p.full(u));
      }
      if (ks == OUT_XZ_AT) {
        const int ux = out_slot(si); si = si == 6 ? 0 : si + 1;
        const int uz = out_slot(si); si = si == 6 ? 0 : si + 1;
        p.acquire(ux, 2);
        if (elect()) {
          mbar_expect(p.full(ux), 2 * UNIT);
          tma2d(p.addr(ux), &M.x, nb * 128, mb * 128, p.full(ux));
          tma2d(p.addr(ux + 1), &M.x, nb * 128 + 64, mb * 128, p.full(ux));
        }
        TS(2, 20);
        mbar_wait(base + SM_RDY + 8 * RDY_Z, 0);
        TS(2, 21);
        p.acquire(uz, 2);
        if (elect()) {
          mbar_expect(p.full(uz), 2 * UNIT);
          tma2d(p.addr(uz), &M.z, mb * 128, nb * 128, p.full(uz));
          tma2d(p.addr(uz + 1), &M.z, mb * 128 + 64, nb * 128, p.full(uz));
        }
      }
    }
  }
}

template<int MASK> __device__ __forceinline__ void sync_agent(const Params& P, uint32_t base, int cta, int lane) {
#define PUBLISH(SIG, CNT, N) { mbar_wait_slow(base + SM_SIG + 8 * (SIG), 0); if (lane == 0) cnt_publish(g_cnt + (CNT) * CSTRIDE, N); __syncwarp(); }
#define READY(RDY) { __syncwarp(); if (lane == 0) mbar_arrive(base + SM_RDY + 8 * (RDY)); }
  if (cta >= NREG) {
    if (MASK & PH_CONV) for (int b = 0; b * 32 < CONV_EXTRA; b++) PUBLISH(SIG_Z + b, C_Z + b, min(32, CONV_EXTRA - b * 32))
    return;
  }
  const int g = cta & 7, j = cta >> 3;
#pragma unroll 1
  for (int half = 0; half < 2; half++) {
    const int h = 2 * j + half;
    if (half == 1 && (MASK & PH_ATT)) PUBLISH(SIG_CTX, C_CTX + g, 1)
    if (MASK & PH_KV) PUBLISH(SIG_KV + half, C_KV + h, 1)
    if (MASK & PH_ATT) {
      cnt_wait(g_cnt + (C_KV + h) * CSTRIDE, 8);
      const float4 kn = __ldcg((const float4*)(g_kn2 + h * 128) + lane);
      const uint32_t m = __reduce_max_sync(~0u, max(max(__float_as_uint(kn.x), __float_as_uint(kn.y)), max(__float_as_uint(kn.z), __float_as_uint(kn.w))));
      if (lane == 0) asm volatile("st.shared.u32 [%0], %1;" :: "r"(base + SM_KMAX + 4 * half), "r"(m) : "memory");
      READY(RDY_KV + half)
    }
  }
  if (MASK & PH_CONV) {
    cnt_wait(g_cnt + (C_U + (conv_channel(cta, 0) >> 5)) * CSTRIDE, 128);
    cnt_wait(g_cnt + (C_U + (conv_channel(cta, CONV_REG - 1) >> 5)) * CSTRIDE, 128);
    READY(RDY_U)
  }
  const int go = min(out_mb(cta), 15 - out_mb(cta));
  if (MASK & PH_OUT) cnt_wait(g_cnt + (C_CTX + go) * CSTRIDE, 16);
  if (MASK & PH_ATT) PUBLISH(SIG_CTX + 1, C_CTX + 8 + g, 1)
  if (MASK == PH_ALL) {
    mbar_wait(base + SM_SIG + 8 * SIG_GO, 0);
    if (lane == 0) asm volatile("red.relaxed.gpu.global.add.u32 [%0], 1;" :: "l"(g_cnt + C_GO * CSTRIDE) : "memory");
    cnt_poll(g_cnt + C_GO * CSTRIDE, NREG);
  }
  if (MASK & PH_OUT) READY(RDY_CTX)
  if (MASK & PH_CONV) {
    const int c0 = conv_channel(cta, 0), c1 = c0 + CONV_REG - 1;
    if ((c0 >> 7) == (c1 >> 7)) PUBLISH(SIG_Z, C_Z + (c0 >> 7), CONV_REG)
    else { PUBLISH(SIG_Z, C_Z + (c0 >> 7), 128 - (c0 & 127)) PUBLISH(SIG_Z, C_Z + (c1 >> 7), (c1 & 127) + 1) }
  }
  if (MASK & PH_OUT) {
    cnt_wait(g_cnt + (C_CTX + 8 + go) * CSTRIDE, 16); READY(RDY_CTX + 1)
    cnt_wait(g_cnt + C_GATE * CSTRIDE, 2048);
    cnt_wait(g_cnt + (C_Z + out_nb(cta)) * CSTRIDE, 128); READY(RDY_Z)
  }
#undef PUBLISH
#undef READY
}

__device__ __forceinline__ void aux_pre(const Params& P, int aw, int lane) {
  const int cp = lane & 15, tb = lane >> 4;
#pragma unroll 1
  for (int unit = aw; unit < 4096; unit += NCTA * 2) {
    const int grp = unit >> 7, t0 = (unit & 127) * 16 + tb * 8;
    const int ch = grp * 32 + cp * 2;
    const uint32_t* kp = (const uint32_t*)(P.k + ch), * vp = (const uint32_t*)(P.v + ch);
    uint32_t kk[12], vv[9];
#pragma unroll
    for (int i = 0; i < 12; i++) { const int t = t0 - 4 + i; kk[i] = t >= 0 ? __ldg(kp + (size_t)t * 512) : 0u; }
#pragma unroll
    for (int i = 0; i < 9; i++) { const int t = t0 - 1 + i; vv[i] = t >= 0 ? __ldg(vp + (size_t)t * 512) : 0u; }
    const uint4 sw = __ldg((const uint4*)(P.shift + ch * 4));
    const uint32_t w0 = __byte_perm(sw.x, sw.z, 0x5410), w1 = __byte_perm(sw.x, sw.z, 0x7632), w2 = __byte_perm(sw.y, sw.w, 0x5410), w3 = __byte_perm(sw.y, sw.w, 0x7632);
#pragma unroll
    for (int i = 0; i < 9; i++)
      vv[i] = hmul2(hadd2(hadd2(hadd2(hmul2(kk[i], w3), hmul2(kk[i + 1], w2)), hmul2(kk[i + 2], w1)), hmul2(kk[i + 3], w0)), vv[i]);
    if (t0 == 0) vv[0] = 0;
    uint8_t* e0 = g_u + (size_t)ch * UCH + (2040 - t0) * 2;
    *(uint4*)(e0)                = make_uint4(__byte_perm(vv[8], vv[7], 0x5410), __byte_perm(vv[6], vv[5], 0x5410), __byte_perm(vv[4], vv[3], 0x5410), __byte_perm(vv[2], vv[1], 0x5410));
    *(uint4*)(e0 + UPITCH)       = make_uint4(__byte_perm(vv[7], vv[6], 0x5410), __byte_perm(vv[5], vv[4], 0x5410), __byte_perm(vv[3], vv[2], 0x5410), __byte_perm(vv[1], vv[0], 0x5410));
    *(uint4*)(e0 + UCH)          = make_uint4(__byte_perm(vv[8], vv[7], 0x7632), __byte_perm(vv[6], vv[5], 0x7632), __byte_perm(vv[4], vv[3], 0x7632), __byte_perm(vv[2], vv[1], 0x7632));
    *(uint4*)(e0 + UCH + UPITCH) = make_uint4(__byte_perm(vv[7], vv[6], 0x7632), __byte_perm(vv[5], vv[4], 0x7632), __byte_perm(vv[3], vv[2], 0x7632), __byte_perm(vv[1], vv[0], 0x7632));
    if (t0 == 0) {
      const uint4 zz = make_uint4(0, 0, 0, 0);
      *(uint4*)(e0 + 16) = zz; *(uint4*)(e0 + UPITCH + 16) = zz; *(uint4*)(e0 + UCH + 16) = zz; *(uint4*)(e0 + UCH + UPITCH + 16) = zz;
      const uint32_t dd = __ldg((const uint32_t*)(P.D + ch));
      *(uint32_t*)(e0 + 48) = __byte_perm(dd, 0, 0x1010); *(uint32_t*)(e0 + UCH + 48) = __byte_perm(dd, 0, 0x3232);
    }
    cnt_signal(g_cnt + (C_U + grp) * CSTRIDE, lane);
  }
#pragma unroll 1
  for (int row = aw; row < 2048; row += NCTA * 2) {
    float a = 0.f;
#pragma unroll
    for (int i = 0; i < 4; i++) {
      const uint4 xv = __ldg((const uint4*)(P.x + (size_t)row * 1024) + i * 32 + lane), gv = __ldg((const uint4*)P.gw + i * 32 + lane);
      uint32_t m;
      m = hmul2(xv.x, gv.x); a += bf_lo(m) + bf_hi(m); m = hmul2(xv.y, gv.y); a += bf_lo(m) + bf_hi(m);
      m = hmul2(xv.z, gv.z); a += bf_lo(m) + bf_hi(m); m = hmul2(xv.w, gv.w); a += bf_lo(m) + bf_hi(m);
    }
#pragma unroll
    for (int o = 16; o > 0; o >>= 1) a += __shfl_xor_sync(~0u, a, o);
    a = bf_lo(pack_bf16(a, 0.f));
    const float gt = bf_lo(pack_bf16(__fdividef(1.f, 1.f + ex2(-a * 1.4426950408889634f)), 0.f));
    if (lane == 0) g_gate[row] = gt;
    cnt_signal(g_cnt + C_GATE * CSTRIDE, lane);
  }
}

template<int MASK> __global__ void __cluster_dims__(2, 1, 1) __launch_bounds__(384, 1) gated_mix_kernel(const __grid_constant__ Maps M, const __grid_constant__ Params P) {
  extern __shared__ __align__(1024) uint8_t smem[];
  const uint32_t base = (uint32_t)__cvta_generic_to_shared(smem);
  if (threadIdx.x == 0) {
    if ((base & 0x3FFFF) != SMEM_BASE) asm volatile("trap;");
    for (int i = 0; i < NUNIT; i++) { mbar_init(base + SM_BAR + 8 * i, 1); mbar_init(base + SM_BAR + 128 + 8 * i, 16); }
    mbar_init(base + SM_EXIT, 4);
    for (int i = 0; i < 9; i++) { mbar_init(base + SM_SIG + 8 * i, i == SIG_GO ? GO_ARRIVALS : 8); mbar_init(base + SM_RDY + 8 * i, 1); }
    asm volatile("fence.mbarrier_init.release.cluster;" ::: "memory");
  }
  __syncthreads();
  asm volatile("barrier.cluster.arrive.relaxed.aligned;\nbarrier.cluster.wait.aligned;" ::: "memory");
  const int wg = __shfl_sync(~0u, threadIdx.x >> 7, 0);
  const int warp = __shfl_sync(~0u, (threadIdx.x >> 5) & 3, 0);
  const int lane = threadIdx.x & 31;
  const int cta = blockIdx.x;
  if (wg == 2) {
    asm volatile("setmaxnreg.dec.sync.aligned.u32 56;");
    TS(2, 62);
    if (warp == 0) producer<MASK>(M, P, base, cta, lane);
    else if (warp == 1) sync_agent<MASK>(P, base, cta, lane);
    else if (MASK & PH_PRE) aux_pre(P, cta + (warp - 2) * NCTA, lane);
    __syncwarp();
    if (lane == 0) mbar_arrive(base + SM_EXIT);
    if (warp == 0 && (MASK & PH_OUT)) {
      mbar_wait_slow(base + SM_EXIT, 0);
      unsigned old = 0;
      if (lane == 0) asm volatile("atom.acq_rel.gpu.global.add.u32 %0, [%1], 1;" : "=r"(old) : "l"(g_cnt + C_EXIT * CSTRIDE) : "memory");
      old = __shfl_sync(~0u, old, 0);
      if (old == NCTA - 1) for (int i = lane; i < C_NUM; i += 32) g_cnt[i * CSTRIDE] = 0;
    }
    if (warp == 0) { cluster_arrive(); cluster_wait(); }
  } else {
    asm volatile("setmaxnreg.inc.sync.aligned.u32 224;");
    uint32_t rel;
    asm volatile("mapa.shared::cluster.u32 %0, %1, %2;" : "=r"(rel) : "r"(base + SM_BAR + 128 + 8 * (lane & 15)), "r"(lane >> 4));
    Cons c{base, rel, 0u, lane, warp, wg, (cta * 3 + wg) * 2048};
    if (wg == 1) bar_arrive(1, 256);
    TS(wg, 0);
    if (cta < NREG) {
      const int g = cta & 7, j = cta >> 3;
      Pend w = {};
#pragma unroll 1
      for (int half = 0; half < 2; half++) {
        const int h = 2 * j + half;
        if (MASK & PH_KV) cons_kv(c, h, g, w, half == 1 && (MASK & PH_ATT));
        TS(wg, 1 + 4 * half);
        if (MASK & PH_ATT) {
          const int fast = cons_q<(MASK & PH_KV) != 0>(c, h, w);
          TS(wg, 2 + 4 * half);
          cons_att(c, h, g, fast, w);
#pragma unroll
          for (int i = 0; i < 8; i++) w.hi[i] = make_uint4(0, 0, 0, 0);
          TS(wg, 3 + 4 * half);
          if (half == 1 || !(MASK & PH_KV)) { tile_store<0, 4>(w.lo, w.dst, lane); c.signal(SIG_CTX + half); }
        } else if (MASK & PH_KV) { out_part<0>(c, w); out_part<1>(c, w); out_part<2>(c, w); out_part<3>(c, w); c.signal(SIG_KV + half); }
      }
    }
    if (MASK & PH_CONV) cons_conv(c, cta, cta < NREG ? CONV_REG : CONV_EXTRA);
    TS(wg, 9);
    if (cta < NREG && (MASK & PH_OUT)) cons_out(c, M, out_mb(cta), out_nb(cta)); else cluster_arrive();
    TS(wg, 10);
  }
}

typedef CUresult (*EncFn)(CUtensorMap*, CUtensorMapDataType, cuuint32_t, void*, const cuuint64_t*, const cuuint64_t*, const cuuint32_t*, const cuuint32_t*,
                          CUtensorMapInterleave, CUtensorMapSwizzle, CUtensorMapL2promotion, CUtensorMapFloatOOBfill);
static void enc(EncFn f, CUtensorMap* m, const void* ptr, int rank, const cuuint64_t* dims, const cuuint64_t* strides, const cuuint32_t* box, CUtensorMapSwizzle sw,
                CUtensorMapDataType dt = CU_TENSOR_MAP_DATA_TYPE_BFLOAT16) {
  const cuuint32_t es[3] = {1, 1, 1};
  f(m, dt, rank, (void*)ptr, dims, strides, box, es, CU_TENSOR_MAP_INTERLEAVE_NONE, sw, CU_TENSOR_MAP_L2_PROMOTION_L2_256B, CU_TENSOR_MAP_FLOAT_OOB_FILL_NONE);
}
static void enc2(EncFn f, CUtensorMap* m, const void* ptr, int cols, int rows, int brows) {
  const cuuint64_t d[2] = {(cuuint64_t)cols, (cuuint64_t)rows}, s[1] = {(cuuint64_t)cols * 2}; const cuuint32_t b[2] = {64, (cuuint32_t)brows};
  enc(f, m, ptr, 2, d, s, b, CU_TENSOR_MAP_SWIZZLE_128B);
}
static void encw(EncFn f, CUtensorMap* m, const void* ptr, int cols, int rows) {
  const cuuint64_t d[3] = {64, (cuuint64_t)rows, (cuuint64_t)cols / 64}, s[2] = {(cuuint64_t)cols * 2, 128}; const cuuint32_t b[3] = {64, 64, 2};
  enc(f, m, ptr, 3, d, s, b, CU_TENSOR_MAP_SWIZZLE_128B);
}
extern "C" void kernel_launch(void* const* d_in, const int* in_sizes, int n_in, void* d_out, int out_size) {
  static EncFn fn = nullptr;
  static int ncl = 0;
  static void* zptr = nullptr;
  static void* tptr = nullptr;
  if (!fn) {
    void* p = nullptr; cudaDriverEntryPointQueryResult qr;
    cudaGetDriverEntryPoint("cuTensorMapEncodeTiled", &p, cudaEnableDefault, &qr);
    fn = (EncFn)p;
    cudaFuncSetAttribute(gated_mix_kernel<PH_ALL>, cudaFuncAttributeMaxDynamicSharedMemorySize, SMEM_BYTES);
    cudaFuncSetAttribute(gated_mix_kernel<PH_PRE | PH_KV>, cudaFuncAttributeMaxDynamicSharedMemorySize, SMEM_BYTES);
    cudaFuncSetAttribute(gated_mix_kernel<PH_ATT | PH_CONV>, cudaFuncAttributeMaxDynamicSharedMemorySize, SMEM_BYTES);
    cudaFuncSetAttribute(gated_mix_kernel<PH_OUT>, cudaFuncAttributeMaxDynamicSharedMemorySize, SMEM_BYTES);
    cudaLaunchConfig_t cfg = {}; cfg.gridDim = NCTA; cfg.blockDim = 384; cfg.dynamicSmemBytes = SMEM_BYTES;
    cudaLaunchAttribute at; at.id = cudaLaunchAttributeClusterDimension; at.val.clusterDim.x = 2; at.val.clusterDim.y = 1; at.val.clusterDim.z = 1;
    cfg.attrs = &at; cfg.numAttrs = 1;
    cudaOccupancyMaxActiveClusters(&ncl, gated_mix_kernel<PH_ALL>, &cfg);
    cudaGetSymbolAddress(&zptr, g_z);
    cudaGetSymbolAddress(&tptr, g_T);
  }
  Maps M;
  enc2(fn, &M.x, d_in[0], 1024, 2048, 128);
  enc2(fn, &M.c, d_in[7], 512, 2048, 128);
  enc2(fn, &M.wq, d_in[8], 4096, 1024, 64);
  encw(fn, &M.wk, d_in[9], 4096, 512);
  encw(fn, &M.wv, d_in[10], 4096, 512);
  encw(fn, &M.wo, d_in[11], 1024, 4096);
  { const cuuint64_t d[3] = {64, 32, 1024}, s[2] = {128, 4096}; const cuuint32_t b[3] = {64, 40, 1}; enc(fn, &M.h, d_in[4], 3, d, s, b, CU_TENSOR_MAP_SWIZZLE_NONE); }
  enc2(fn, &M.z, zptr, 2048, 1024, 128);
  enc2(fn, &M.out, d_out, 1024, 2048, 16);
  { const cuuint64_t d[2] = {512, 512 * 16}, s[1] = {2048}; const cuuint32_t b[2] = {256, 8};
    enc(fn, &M.ctx, tptr, 2, d, s, b, CU_TENSOR_MAP_SWIZZLE_NONE, CU_TENSOR_MAP_DATA_TYPE_UINT32); }
  Params P{(const __nv_bfloat16*)d_in[0], (const __nv_bfloat16*)d_in[1], (const __nv_bfloat16*)d_in[2], (const __nv_bfloat16*)d_in[3],
           (const __nv_bfloat16*)d_in[5], (const __nv_bfloat16*)d_in[12]};
  bool split = 2 * ncl < NCTA;
  if (!split) {
    gated_mix_kernel<PH_ALL><<<NCTA, 384, SMEM_BYTES>>>(M, P);
  } else {
    gated_mix_kernel<PH_PRE | PH_KV><<<NCTA, 384, SMEM_BYTES>>>(M, P);
    gated_mix_kernel<PH_ATT | PH_CONV><<<NCTA, 384, SMEM_BYTES>>>(M, P);
    gated_mix_kernel<PH_OUT><<<NCTA, 384, SMEM_BYTES>>>(M, P);
  }
}
```

```cpp
#include <cuda_runtime.h>
#include <cuda.h>
#include <cuda_bf16.h>
#include <stdint.h>

template<int TB> __device__ __forceinline__ void wgmma_ss_n256(float (&d)[128], uint64_t da, uint64_t db, int scale_d) {
  asm volatile("{\n.reg .pred p;\nsetp.ne.b32 p, %130, 0;\n"
    "wgmma.mma_async.sync.aligned.m64n256k16.f32.bf16.bf16 {%0, %1, %2, %3, %4, %5, %6, %7, %8, %9, %10, %11, %12, %13, %14, %15, %16, %17, %18, %19, %20, %21, %22, %23, %24, %25, %26, %27, %28, %29, %30, %31, %32, %33, %34, %35, %36, %37, %38, %39, %40, %41, %42, %43, %44, %45, %46, %47, %48, %49, %50, %51, %52, %53, %54, %55, %56, %57, %58, %59, %60, %61, %62, %63, %64, %65, %66, %67, %68, %69, %70, %71, %72, %73, %74, %75, %76, %77, %78, %79, %80, %81, %82, %83, %84, %85, %86, %87, %88, %89, %90, %91, %92, %93, %94, %95, %96, %97, %98, %99, %100, %101, %102, %103, %104, %105, %106, %107, %108, %109, %110, %111, %112, %113, %114, %115, %116, %117, %118, %119, %120, %121, %122, %123, %124, %125, %126, %127}, %128, %129, p, 1, 1, 0, %131;\n}\n"
    : "+f"(d[0]), "+f"(d[1]), "+f"(d[2]), "+f"(d[3]), "+f"(d[4]), "+f"(d[5]), "+f"(d[6]), "+f"(d[7]), "+f"(d[8]), "+f"(d[9]), "+f"(d[10]), "+f"(d[11]), "+f"(d[12]), "+f"(d[13]), "+f"(d[14]), "+f"(d[15]), "+f"(d[16]), "+f"(d[17]), "+f"(d[18]), "+f"(d[19]), "+f"(d[20]), "+f"(d[21]), "+f"(d[22]), "+f"(d[23]), "+f"(d[24]), "+f"(d[25]), "+f"(d[26]), "+f"(d[27]), "+f"(d[28]), "+f"(d[29]), "+f"(d[30]), "+f"(d[31]), "+f"(d[32]), "+f"(d[33]), "+f"(d[34]), "+f"(d[35]), "+f"(d[36]), "+f"(d[37]), "+f"(d[38]), "+f"(d[39]), "+f"(d[40]), "+f"(d[41]), "+f"(d[42]), "+f"(d[43]), "+f"(d[44]), "+f"(d[45]), "+f"(d[46]), "+f"(d[47]), "+f"(d[48]), "+f"(d[49]), "+f"(d[50]), "+f"(d[51]), "+f"(d[52]), "+f"(d[53]), "+f"(d[54]), "+f"(d[55]), "+f"(d[56]), "+f"(d[57]), "+f"(d[58]), "+f"(d[59]), "+f"(d[60]), "+f"(d[61]), "+f"(d[62]), "+f"(d[63]), "+f"(d[64]), "+f"(d[65]), "+f"(d[66]), "+f"(d[67]), "+f"(d[68]), "+f"(d[69]), "+f"(d[70]), "+f"(d[71]), "+f"(d[72]), "+f"(d[73]), "+f"(d[74]), "+f"(d[75]), "+f"(d[76]), "+f"(d[77]), "+f"(d[78]), "+f"(d[79]), "+f"(d[80]), "+f"(d[81]), "+f"(d[82]), "+f"(d[83]), "+f"(d[84]), "+f"(d[85]), "+f"(d[86]), "+f"(d[87]), "+f"(d[88]), "+f"(d[89]), "+f"(d[90]), "+f"(d[91]), "+f"(d[92]), "+f"(d[93]), "+f"(d[94]), "+f"(d[95]), "+f"(d[96]), "+f"(d[97]), "+f"(d[98]), "+f"(d[99]), "+f"(d[100]), "+f"(d[101]), "+f"(d[102]), "+f"(d[103]), "+f"(d[104]), "+f"(d[105]), "+f"(d[106]), "+f"(d[107]), "+f"(d[108]), "+f"(d[109]), "+f"(d[110]), "+f"(d[111]), "+f"(d[112]), "+f"(d[113]), "+f"(d[114]), "+f"(d[115]), "+f"(d[116]), "+f"(d[117]), "+f"(d[118]), "+f"(d[119]), "+f"(d[120]), "+f"(d[121]), "+f"(d[122]), "+f"(d[123]), "+f"(d[124]), "+f"(d[125]), "+f"(d[126]), "+f"(d[127])
    : "l"(da), "l"(db), "r"(scale_d), "n"(TB));
}
template<int TB> __device__ __forceinline__ void wgmma_ss_n128(float (&d)[64], uint64_t da, uint64_t db, int scale_d) {
  asm volatile("{\n.reg .pred p;\nsetp.ne.b32 p, %66, 0;\n"
    "wgmma.mma_async.sync.aligned.m64n128k16.f32.bf16.bf16 {%0, %1, %2, %3, %4, %5, %6, %7, %8, %9, %10, %11, %12, %13, %14, %15, %16, %17, %18, %19, %20, %21, %22, %23, %24, %25, %26, %27, %28, %29, %30, %31, %32, %33, %34, %35, %36, %37, %38, %39, %40, %41, %42, %43, %44, %45, %46, %47, %48, %49, %50, %51, %52, %53, %54, %55, %56, %57, %58, %59, %60, %61, %62, %63}, %64, %65, p, 1, 1, 0, %67;\n}\n"
    : "+f"(d[0]), "+f"(d[1]), "+f"(d[2]), "+f"(d[3]), "+f"(d[4]), "+f"(d[5]), "+f"(d[6]), "+f"(d[7]), "+f"(d[8]), "+f"(d[9]), "+f"(d[10]), "+f"(d[11]), "+f"(d[12]), "+f"(d[13]), "+f"(d[14]), "+f"(d[15]), "+f"(d[16]), "+f"(d[17]), "+f"(d[18]), "+f"(d[19]), "+f"(d[20]), "+f"(d[21]), "+f"(d[22]), "+f"(d[23]), "+f"(d[24]), "+f"(d[25]), "+f"(d[26]), "+f"(d[27]), "+f"(d[28]), "+f"(d[29]), "+f"(d[30]), "+f"(d[31]), "+f"(d[32]), "+f"(d[33]), "+f"(d[34]), "+f"(d[35]), "+f"(d[36]), "+f"(d[37]), "+f"(d[38]), "+f"(d[39]), "+f"(d[40]), "+f"(d[41]), "+f"(d[42]), "+f"(d[43]), "+f"(d[44]), "+f"(d[45]), "+f"(d[46]), "+f"(d[47]), "+f"(d[48]), "+f"(d[49]), "+f"(d[50]), "+f"(d[51]), "+f"(d[52]), "+f"(d[53]), "+f"(d[54]), "+f"(d[55]), "+f"(d[56]), "+f"(d[57]), "+f"(d[58]), "+f"(d[59]), "+f"(d[60]), "+f"(d[61]), "+f"(d[62]), "+f"(d[63])
    : "l"(da), "l"(db), "r"(scale_d), "n"(TB));
}
template<int TB> __device__ __forceinline__ void wgmma_rs_n128(float (&d)[64], uint32_t a0, uint32_t a1, uint32_t a2, uint32_t a3, uint64_t db, int scale_d) {
  asm volatile("{\n.reg .pred p;\nsetp.ne.b32 p, %69, 0;\n"
    "wgmma.mma_async.sync.aligned.m64n128k16.f32.bf16.bf16 {%0, %1, %2, %3, %4, %5, %6, %7, %8, %9, %10, %11, %12, %13, %14, %15, %16, %17, %18, %19, %20, %21, %22, %23, %24, %25, %26, %27, %28, %29, %30, %31, %32, %33, %34, %35, %36, %37, %38, %39, %40, %41, %42, %43, %44, %45, %46, %47, %48, %49, %50, %51, %52, %53, %54, %55, %56, %57, %58, %59, %60, %61, %62, %63}, {%64, %65, %66, %67}, %68, p, 1, 1, %70;\n}\n"
    : "+f"(d[0]), "+f"(d[1]), "+f"(d[2]), "+f"(d[3]), "+f"(d[4]), "+f"(d[5]), "+f"(d[6]), "+f"(d[7]), "+f"(d[8]), "+f"(d[9]), "+f"(d[10]), "+f"(d[11]), "+f"(d[12]), "+f"(d[13]), "+f"(d[14]), "+f"(d[15]), "+f"(d[16]), "+f"(d[17]), "+f"(d[18]), "+f"(d[19]), "+f"(d[20]), "+f"(d[21]), "+f"(d[22]), "+f"(d[23]), "+f"(d[24]), "+f"(d[25]), "+f"(d[26]), "+f"(d[27]), "+f"(d[28]), "+f"(d[29]), "+f"(d[30]), "+f"(d[31]), "+f"(d[32]), "+f"(d[33]), "+f"(d[34]), "+f"(d[35]), "+f"(d[36]), "+f"(d[37]), "+f"(d[38]), "+f"(d[39]), "+f"(d[40]), "+f"(d[41]), "+f"(d[42]), "+f"(d[43]), "+f"(d[44]), "+f"(d[45]), "+f"(d[46]), "+f"(d[47]), "+f"(d[48]), "+f"(d[49]), "+f"(d[50]), "+f"(d[51]), "+f"(d[52]), "+f"(d[53]), "+f"(d[54]), "+f"(d[55]), "+f"(d[56]), "+f"(d[57]), "+f"(d[58]), "+f"(d[59]), "+f"(d[60]), "+f"(d[61]), "+f"(d[62]), "+f"(d[63])
    : "r"(a0), "r"(a1), "r"(a2), "r"(a3), "l"(db), "r"(scale_d), "n"(TB));
}
template<int TB> __device__ __forceinline__ void wgmma_rs_n64(float (&d)[32], uint32_t a0, uint32_t a1, uint32_t a2, uint32_t a3, uint64_t db, int scale_d) {
  asm volatile("{\n.reg .pred p;\nsetp.ne.b32 p, %37, 0;\n"
    "wgmma.mma_async.sync.aligned.m64n64k16.f32.bf16.bf16 {%0, %1, %2, %3, %4, %5, %6, %7, %8, %9, %10, %11, %12, %13, %14, %15, %16, %17, %18, %19, %20, %21, %22, %23, %24, %25, %26, %27, %28, %29, %30, %31}, {%32, %33, %34, %35}, %36, p, 1, 1, %38;\n}\n"
    : "+f"(d[0]), "+f"(d[1]), "+f"(d[2]), "+f"(d[3]), "+f"(d[4]), "+f"(d[5]), "+f"(d[6]), "+f"(d[7]), "+f"(d[8]), "+f"(d[9]), "+f"(d[10]), "+f"(d[11]), "+f"(d[12]), "+f"(d[13]), "+f"(d[14]), "+f"(d[15]), "+f"(d[16]), "+f"(d[17]), "+f"(d[18]), "+f"(d[19]), "+f"(d[20]), "+f"(d[21]), "+f"(d[22]), "+f"(d[23]), "+f"(d[24]), "+f"(d[25]), "+f"(d[26]), "+f"(d[27]), "+f"(d[28]), "+f"(d[29]), "+f"(d[30]), "+f"(d[31])
    : "r"(a0), "r"(a1), "r"(a2), "r"(a3), "l"(db), "r"(scale_d), "n"(TB));
}
__device__ __forceinline__ void wgmma_pv_sel(float (&d)[64], const uint32_t (&p)[32], uint64_t db, int full, int acc) {
  asm volatile("{\n.reg .pred q, s;\n.reg .b64 t;\nsetp.ne.b32 s, %98, 0;\nsetp.eq.b32 q, %97, 0;\n@q bra.uni LH;\n"
    "wgmma.fence.sync.aligned;\n"
    "add.s64 t, %96, 0;\nwgmma.mma_async.sync.aligned.m64n128k16.f32.bf16.bf16 {%0, %1, %2, %3, %4, %5, %6, %7, %8, %9, %10, %11, %12, %13, %14, %15, %16, %17, %18, %19, %20, %21, %22, %23, %24, %25, %26, %27, %28, %29, %30, %31, %32, %33, %34, %35, %36, %37, %38, %39, %40, %41, %42, %43, %44, %45, %46, %47, %48, %49, %50, %51, %52, %53, %54, %55, %56, %57, %58, %59, %60, %61, %62, %63}, {%64, %65, %66, %67}, t, s, 1, 1, 1;\n"
    "add.s64 t, %96, 256;\nwgmma.mma_async.sync.aligned.m64n128k16.f32.bf16.bf16 {%0, %1, %2, %3, %4, %5, %6, %7, %8, %9, %10, %11, %12, %13, %14, %15, %16, %17, %18, %19, %20, %21, %22, %23, %24, %25, %26, %27, %28, %29, %30, %31, %32, %33, %34, %35, %36, %37, %38, %39, %40, %41, %42, %43, %44, %45, %46, %47, %48, %49, %50, %51, %52, %53, %54, %55, %56, %57, %58, %59, %60, %61, %62, %63}, {%68, %69, %70, %71}, t, 1, 1, 1, 1;\n"
    "add.s64 t, %96, 512;\nwgmma.mma_async.sync.aligned.m64n128k16.f32.bf16.bf16 {%0, %1, %2, %3, %4, %5, %6, %7, %8, %9, %10, %11, %12, %13, %14, %15, %16, %17, %18, %19, %20, %21, %22, %23, %24, %25, %26, %27, %28, %29, %30, %31, %32, %33, %34, %35, %36, %37, %38, %39, %40, %41, %42, %43, %44, %45, %46, %47, %48, %49, %50, %51, %52, %53, %54, %55, %56, %57, %58, %59, %60, %61, %62, %63}, {%72, %73, %74, %75}, t, 1, 1, 1, 1;\n"
    "add.s64 t, %96, 768;\nwgmma.mma_async.sync.aligned.m64n128k16.f32.bf16.bf16 {%0, %1, %2, %3, %4, %5, %6, %7, %8, %9, %10, %11, %12, %13, %14, %15, %16, %17, %18, %19, %20, %21, %22, %23, %24, %25, %26, %27, %28, %29, %30, %31, %32, %33, %34, %35, %36, %37, %38, %39, %40, %41, %42, %43, %44, %45, %46, %47, %48, %49, %50, %51, %52, %53, %54, %55, %56, %57, %58, %59, %60, %61, %62, %63}, {%76, %77, %78, %79}, t, 1, 1, 1, 1;\n"
    "add.s64 t, %96, 1024;\nwgmma.mma_async.sync.aligned.m64n128k16.f32.bf16.bf16 {%0, %1, %2, %3, %4, %5, %6, %7, %8, %9, %10, %11, %12, %13, %14, %15, %16, %17, %18, %19, %20, %21, %22, %23, %24, %25, %26, %27, %28, %29, %30, %31, %32, %33, %34, %35, %36, %37, %38, %39, %40, %41, %42, %43, %44, %45, %46, %47, %48, %49, %50, %51, %52, %53, %54, %55, %56, %57, %58, %59, %60, %61, %62, %63}, {%80, %81, %82, %83}, t, 1, 1, 1, 1;\n"
    "add.s64 t, %96, 1280;\nwgmma.mma_async.sync.aligned.m64n128k16.f32.bf16.bf16 {%0, %1, %2, %3, %4, %5, %6, %7, %8, %9, %10, %11, %12, %13, %14, %15, %16, %17, %18, %19, %20, %21, %22, %23, %24, %25, %26, %27, %28, %29, %30, %31, %32, %33, %34, %35, %36, %37, %38, %39, %40, %41, %42, %43, %44, %45, %46, %47, %48, %49, %50, %51, %52, %53, %54, %55, %56, %57, %58, %59, %60, %61, %62, %63}, {%84, %85, %86, %87}, t, 1, 1, 1, 1;\n"
    "add.s64 t, %96, 1536;\nwgmma.mma_async.sync.aligned.m64n128k16.f32.bf16.bf16 {%0, %1, %2, %3, %4, %5, %6, %7, %8, %9, %10, %11, %12, %13, %14, %15, %16, %17, %18, %19, %20, %21, %22, %23, %24, %25, %26, %27, %28, %29, %30, %31, %32, %33, %34, %35, %36, %37, %38, %39, %40, %41, %42, %43, %44, %45, %46, %47, %48, %49, %50, %51, %52, %53, %54, %55, %56, %57, %58, %59, %60, %61, %62, %63}, {%88, %89, %90, %91}, t, 1, 1, 1, 1;\n"
    "add.s64 t, %96, 1792;\nwgmma.mma_async.sync.aligned.m64n128k16.f32.bf16.bf16 {%0, %1, %2, %3, %4, %5, %6, %7, %8, %9, %10, %11, %12, %13, %14, %15, %16, %17, %18, %19, %20, %21, %22, %23, %24, %25, %26, %27, %28, %29, %30, %31, %32, %33, %34, %35, %36, %37, %38, %39, %40, %41, %42, %43, %44, %45, %46, %47, %48, %49, %50, %51, %52, %53, %54, %55, %56, %57, %58, %59, %60, %61, %62, %63}, {%92, %93, %94, %95}, t, 1, 1, 1, 1;\n"
    "wgmma.commit_group.sync.aligned;\n"
    "bra.uni LE;\nLH:\n"
    "wgmma.fence.sync.aligned;\n"
    "add.s64 t, %96, 0;\nwgmma.mma_async.sync.aligned.m64n128k16.f32.bf16.bf16 {%0, %1, %2, %3, %4, %5, %6, %7, %8, %9, %10, %11, %12, %13, %14, %15, %16, %17, %18, %19, %20, %21, %22, %23, %24, %25, %26, %27, %28, %29, %30, %31, %32, %33, %34, %35, %36, %37, %38, %39, %40, %41, %42, %43, %44, %45, %46, %47, %48, %49, %50, %51, %52, %53, %54, %55, %56, %57, %58, %59, %60, %61, %62, %63}, {%80, %81, %82, %83}, t, s, 1, 1, 1;\n"
    "add.s64 t, %96, 256;\nwgmma.mma_async.sync.aligned.m64n128k16.f32.bf16.bf16 {%0, %1, %2, %3, %4, %5, %6, %7, %8, %9, %10, %11, %12, %13, %14, %15, %16, %17, %18, %19, %20, %21, %22, %23, %24, %25, %26, %27, %28, %29, %30, %31, %32, %33, %34, %35, %36, %37, %38, %39, %40, %41, %42, %43, %44, %45, %46, %47, %48, %49, %50, %51, %52, %53, %54, %55, %56, %57, %58, %59, %60, %61, %62, %63}, {%84, %85, %86, %87}, t, 1, 1, 1, 1;\n"
    "add.s64 t, %96, 512;\nwgmma.mma_async.sync.aligned.m64n128k16.f32.bf16.bf16 {%0, %1, %2, %3, %4, %5, %6, %7, %8, %9, %10, %11, %12, %13, %14, %15, %16, %17, %18, %19, %20, %21, %22, %23, %24, %25, %26, %27, %28, %29, %30, %31, %32, %33, %34, %35, %36, %37, %38, %39, %40, %41, %42, %43, %44, %45, %46, %47, %48, %49, %50, %51, %52, %53, %54, %55, %56, %57, %58, %59, %60, %61, %62, %63}, {%88, %89, %90, %91}, t, 1, 1, 1, 1;\n"
    "add.s64 t, %96, 768;\nwgmma.mma_async.sync.aligned.m64n128k16.f32.bf16.bf16 {%0, %1, %2, %3, %4, %5, %6, %7, %8, %9, %10, %11, %12, %13, %14, %15, %16, %17, %18, %19, %20, %21, %22, %23, %24, %25, %26, %27, %28, %29, %30, %31, %32, %33, %34, %35, %36, %37, %38, %39, %40, %41, %42, %43, %44, %45, %46, %47, %48, %49, %50, %51, %52, %53, %54, %55, %56, %57, %58, %59, %60, %61, %62, %63}, {%92, %93, %94, %95}, t, 1, 1, 1, 1;\n"
    "wgmma.commit_group.sync.aligned;\n"
    "LE:\n}\n"
    : "+f"(d[0]), "+f"(d[1]), "+f"(d[2]), "+f"(d[3]), "+f"(d[4]), "+f"(d[5]), "+f"(d[6]), "+f"(d[7]), "+f"(d[8]), "+f"(d[9]), "+f"(d[10]), "+f"(d[11]), "+f"(d[12]), "+f"(d[13]), "+f"(d[14]), "+f"(d[15]), "+f"(d[16]), "+f"(d[17]), "+f"(d[18]), "+f"(d[19]), "+f"(d[20]), "+f"(d[21]), "+f"(d[22]), "+f"(d[23]), "+f"(d[24]), "+f"(d[25]), "+f"(d[26]), "+f"(d[27]), "+f"(d[28]), "+f"(d[29]), "+f"(d[30]), "+f"(d[31]), "+f"(d[32]), "+f"(d[33]), "+f"(d[34]), "+f"(d[35]), "+f"(d[36]), "+f"(d[37]), "+f"(d[38]), "+f"(d[39]), "+f"(d[40]), "+f"(d[41]), "+f"(d[42]), "+f"(d[43]), "+f"(d[44]), "+f"(d[45]), "+f"(d[46]), "+f"(d[47]), "+f"(d[48]), "+f"(d[49]), "+f"(d[50]), "+f"(d[51]), "+f"(d[52]), "+f"(d[53]), "+f"(d[54]), "+f"(d[55]), "+f"(d[56]), "+f"(d[57]), "+f"(d[58]), "+f"(d[59]), "+f"(d[60]), "+f"(d[61]), "+f"(d[62]), "+f"(d[63])
    : "r"(p[0]), "r"(p[1]), "r"(p[2]), "r"(p[3]), "r"(p[4]), "r"(p[5]), "r"(p[6]), "r"(p[7]), "r"(p[8]), "r"(p[9]), "r"(p[10]), "r"(p[11]), "r"(p[12]), "r"(p[13]), "r"(p[14]), "r"(p[15]), "r"(p[16]), "r"(p[17]), "r"(p[18]), "r"(p[19]), "r"(p[20]), "r"(p[21]), "r"(p[22]), "r"(p[23]), "r"(p[24]), "r"(p[25]), "r"(p[26]), "r"(p[27]), "r"(p[28]), "r"(p[29]), "r"(p[30]), "r"(p[31]), "l"(db), "r"(full), "r"(acc) : "memory");
}

constexpr int NCTA = 132, NREG = 128;
constexpr int UNIT = 16384, NUNIT = 14;
constexpr uint32_t SMEM_BASE = 1024;
constexpr int SM_BAR = NUNIT * UNIT;
constexpr int SMEM_BYTES = SM_BAR + 1024;
constexpr int UPITCH = 4160, UCH = 2 * UPITCH;
constexpr float QSCALE = 0.08838834764831845f * 1.4426950408889634f;
constexpr float BOUND2 = 48.f * 48.f / 1.15f;
#define CONV_REG 4
constexpr int CONV_EXTRA = (1024 - NREG * CONV_REG) / (NCTA - NREG);
constexpr int CH_EXTRA_TOTAL = CONV_EXTRA * (NCTA - NREG);
constexpr int C_KV = 0;
constexpr int C_CTX = 32;
constexpr int C_U = 48;
constexpr int C_Z = 80;
constexpr int C_GATE = 88;
constexpr int C_EXIT = 89;
constexpr int C_GO = 90;
#define HEAD(j, half) ((j) + 16 * (half))
#define HALF(h) ((h) >> 4)
#define JOF(h) ((h) & 15)
#define PRE_EARLY 1
#define PRE_HALF 0
#define EF 0
#define POL(bit) (((EF >> (bit)) & 1) != 0)
#define GO_ARRIVALS 4
constexpr int C_WAR = 96;
constexpr int C_NUM = 112;
constexpr int CSTRIDE = 32;
constexpr int SM_KMAX = SM_BAR + 256, SM_DUMMY = SM_BAR + 264, SM_EXIT = SM_BAR + 272, SM_PRE = SM_BAR + 280, SM_SIG = SM_BAR + 320, SM_RDY = SM_BAR + 448;
enum { SIG_KV = 0, SIG_CTX = 2, SIG_Z = 4, SIG_GO = 8, SIG_WAR = 9, SIG_ATT = 10 };
enum { RDY_KV = 0, RDY_CTX = 2, RDY_U = 4, RDY_Z = 5, RDY_WAR = 6 };
enum { PH_PRE = 1, PH_KV = 2, PH_ATT = 4, PH_CONV = 8, PH_OUT = 16, PH_ALL = 31 };

constexpr uint32_t T_CTX = 0, T_KV = 16 * 32 * 32768, T_BYTES = T_KV + 32 * 16 * 65536;
__device__ __align__(1024) uint8_t g_T[T_BYTES];
__device__ __align__(1024) uint8_t g_u[1024 * UCH];
__device__ __align__(1024) __nv_bfloat16 g_z[1024 * 2048];
__device__ __align__(1024) float g_gate[2048];
__device__ __align__(1024) float g_kn2[32 * 128];
__device__ __align__(1024) unsigned g_cnt[C_NUM * CSTRIDE];

struct __align__(64) Maps { CUtensorMap x, c, wq, wk, wv, wo, h, z, out, ctx, k, v; };
struct Params {
  const __nv_bfloat16 *x, *shift, *D, *gw;
};

__device__ __forceinline__ void wg_fence() { asm volatile("wgmma.fence.sync.aligned;" ::: "memory"); }
__device__ __forceinline__ void wg_commit() { asm volatile("wgmma.commit_group.sync.aligned;" ::: "memory"); }
template<int N> __device__ __forceinline__ void wg_wait() { asm volatile("wgmma.wait_group.sync.aligned %0;" :: "n"(N) : "memory"); }
__device__ __forceinline__ uint64_t mkdesc(uint32_t addr, uint32_t lbo, uint32_t sbo, uint32_t swz) {
  return (uint64_t)((addr & 0x3FFFF) >> 4) | ((uint64_t)(lbo >> 4) << 16) | ((uint64_t)(sbo >> 4) << 32) | ((uint64_t)swz << 62);
}
__device__ __forceinline__ void mbar_init(uint32_t bar, int cnt) { asm volatile("mbarrier.init.shared::cta.b64 [%0], %1;" :: "r"(bar), "r"(cnt)); }
__device__ __forceinline__ void mbar_expect(uint32_t bar, uint32_t bytes) { asm volatile("mbarrier.arrive.expect_tx.shared::cta.b64 _, [%0], %1;" :: "r"(bar), "r"(bytes) : "memory"); }
__device__ __forceinline__ void mbar_arrive(uint32_t bar) { asm volatile("mbarrier.arrive.shared::cta.b64 _, [%0];" :: "r"(bar) : "memory"); }
__device__ __forceinline__ void mbar_arrive_n(uint32_t bar, int n) { asm volatile("mbarrier.arrive.shared::cta.b64 _, [%0], %1;" :: "r"(bar), "r"(n) : "memory"); }
__device__ __forceinline__ void mbar_wait(uint32_t bar, uint32_t parity) {
  asm volatile("{\n.reg .pred p;\n.reg .u32 n;\nmov.u32 n, 0;\n"
    "LW:\nmbarrier.try_wait.parity.shared::cta.b64 p, [%0], %1;\n@p bra LD;\n"
    "add.u32 n, n, 1;\nsetp.lt.u32 p, n, 2097152;\n@p bra LW;\ntrap;\nLD:\n}\n" :: "r"(bar), "r"(parity) : "memory");
}
__device__ __forceinline__ void mbar_wait_slow(uint32_t bar, uint32_t parity) {
  asm volatile("{\n.reg .pred p;\n.reg .u32 n;\nmov.u32 n, 0;\n"
    "LW:\nmbarrier.test_wait.parity.shared::cta.b64 p, [%0], %1;\n@p bra LD;\n"
    "nanosleep.u32 128;\nadd.u32 n, n, 1;\nsetp.lt.u32 p, n, 4194304;\n@p bra LW;\ntrap;\nLD:\n}\n" :: "r"(bar), "r"(parity) : "memory");
}
__device__ __forceinline__ void mbar_wait_all(uint32_t bar, uint32_t parity) {
  asm volatile("{\n.reg .pred p, q;\n.reg .u32 n;\nmov.u32 n, 0;\n"
    "LW:\nmbarrier.try_wait.parity.shared::cta.b64 p, [%0], %1;\nvote.sync.all.pred q, p, 0xffffffff;\n@q bra.uni LD;\n"
    "add.u32 n, n, 1;\nsetp.lt.u32 q, n, 2097152;\n@q bra.uni LW;\ntrap;\nLD:\n}\n" :: "r"(bar), "r"(parity) : "memory");
}
__device__ __forceinline__ void cnt_wait(const unsigned* p, unsigned target) {
  asm volatile("{\n.reg .pred p;\n.reg .u32 n, v;\nmov.u32 n, 0;\n"
    "LW:\nld.relaxed.gpu.global.u32 v, [%0];\nsetp.ge.u32 p, v, %1;\n@p bra LD;\n"
    "nanosleep.u32 64;\nadd.u32 n, n, 1;\nsetp.lt.u32 p, n, 4194304;\n@p bra LW;\ntrap;\nLD:\nfence.acq_rel.gpu;\nfence.proxy.async;\n}\n" :: "l"(p), "r"(target) : "memory");
}
__device__ __forceinline__ void cnt_poll(const unsigned* p, unsigned target) {
  asm volatile("{\n.reg .pred p;\n.reg .u32 n, v;\nmov.u32 n, 0;\n"
    "LW:\nld.relaxed.gpu.global.u32 v, [%0];\nsetp.ge.u32 p, v, %1;\n@p bra LD;\n"
    "add.u32 n, n, 1;\nsetp.lt.u32 p, n, 4194304;\n@p bra LW;\ntrap;\nLD:\n}\n" :: "l"(p), "r"(target) : "memory");
}
__device__ __forceinline__ void cnt_signal(unsigned* p, int lane) {
  __syncwarp();
  if (lane == 0) asm volatile("red.release.gpu.global.add.u32 [%0], 1;" :: "l"(p) : "memory");
}
__device__ __forceinline__ void cnt_publish(unsigned* p, unsigned n) {
  asm volatile("fence.acq_rel.gpu;\nred.relaxed.gpu.global.add.u32 [%0], %1;" :: "l"(p), "r"(n) : "memory");
}
__device__ __forceinline__ uint64_t pol_first() { uint64_t p; asm("createpolicy.fractional.L2::evict_first.b64 %0, 1.0;" : "=l"(p)); return p; }
__device__ __forceinline__ void bulk_g2s(uint32_t dst, const void* src, uint32_t bytes, uint32_t bar, bool stream = false) {
  if (stream) asm volatile("cp.async.bulk.shared::cluster.global.mbarrier::complete_tx::bytes.L2::cache_hint [%0], [%1], %2, [%3], %4;" :: "r"(dst), "l"(src), "r"(bytes), "r"(bar), "l"(pol_first()) : "memory");
  else asm volatile("cp.async.bulk.shared::cluster.global.mbarrier::complete_tx::bytes [%0], [%1], %2, [%3];" :: "r"(dst), "l"(src), "r"(bytes), "r"(bar) : "memory");
}
__device__ __forceinline__ void tma2d(uint32_t dst, const CUtensorMap* m, int x, int y, uint32_t bar, bool stream = false) {
  if (stream) asm volatile("cp.async.bulk.tensor.2d.shared::cluster.global.mbarrier::complete_tx::bytes.L2::cache_hint [%0], [%1, {%3, %4}], [%2], %5;" :: "r"(dst), "l"(m), "r"(bar), "r"(x), "r"(y), "l"(pol_first()) : "memory");
  else asm volatile("cp.async.bulk.tensor.2d.shared::cluster.global.mbarrier::complete_tx::bytes [%0], [%1, {%3, %4}], [%2];" :: "r"(dst), "l"(m), "r"(bar), "r"(x), "r"(y) : "memory");
}
__device__ __forceinline__ void tma3d(uint32_t dst, const CUtensorMap* m, int x, int y, int z, uint32_t bar, bool stream = false) {
  if (stream) asm volatile("cp.async.bulk.tensor.3d.shared::cluster.global.mbarrier::complete_tx::bytes.L2::cache_hint [%0], [%1, {%3, %4, %5}], [%2], %6;" :: "r"(dst), "l"(m), "r"(bar), "r"(x), "r"(y), "r"(z), "l"(pol_first()) : "memory");
  else asm volatile("cp.async.bulk.tensor.3d.shared::cluster.global.mbarrier::complete_tx::bytes [%0], [%1, {%3, %4, %5}], [%2];" :: "r"(dst), "l"(m), "r"(bar), "r"(x), "r"(y), "r"(z) : "memory");
}
__device__ __forceinline__ void tma4d(uint32_t dst, const CUtensorMap* m, int x, int y, int z, int w, uint32_t bar, bool stream = false) {
  if (stream) asm volatile("cp.async.bulk.tensor.4d.shared::cluster.global.mbarrier::complete_tx::bytes.L2::cache_hint [%0], [%1, {%3, %4, %5, %6}], [%2], %7;" :: "r"(dst), "l"(m), "r"(bar), "r"(x), "r"(y), "r"(z), "r"(w), "l"(pol_first()) : "memory");
  else asm volatile("cp.async.bulk.tensor.4d.shared::cluster.global.mbarrier::complete_tx::bytes [%0], [%1, {%3, %4, %5, %6}], [%2];" :: "r"(dst), "l"(m), "r"(bar), "r"(x), "r"(y), "r"(z), "r"(w) : "memory");
}
__device__ __forceinline__ void bulk_g2s_mc(uint32_t dst, const void* src, uint32_t bytes, uint32_t bar, bool stream = false) {
  if (stream) asm volatile("cp.async.bulk.shared::cluster.global.mbarrier::complete_tx::bytes.multicast::cluster.L2::cache_hint [%0], [%1], %2, [%3], %4, %5;" :: "r"(dst), "l"(src), "r"(bytes), "r"(bar), "h"((uint16_t)3), "l"(pol_first()) : "memory");
  else asm volatile("cp.async.bulk.shared::cluster.global.mbarrier::complete_tx::bytes.multicast::cluster [%0], [%1], %2, [%3], %4;" :: "r"(dst), "l"(src), "r"(bytes), "r"(bar), "h"((uint16_t)3) : "memory");
}
__device__ __forceinline__ void tma2d_mc(uint32_t dst, const CUtensorMap* m, int x, int y, uint32_t bar, bool stream = false) {
  if (stream) asm volatile("cp.async.bulk.tensor.2d.shared::cluster.global.mbarrier::complete_tx::bytes.multicast::cluster.L2::cache_hint [%0], [%1, {%3, %4}], [%2], %5, %6;" :: "r"(dst), "l"(m), "r"(bar), "r"(x), "r"(y), "h"((uint16_t)3), "l"(pol_first()) : "memory");
  else asm volatile("cp.async.bulk.tensor.2d.shared::cluster.global.mbarrier::complete_tx::bytes.multicast::cluster [%0], [%1, {%3, %4}], [%2], %5;" :: "r"(dst), "l"(m), "r"(bar), "r"(x), "r"(y), "h"((uint16_t)3) : "memory");
}
__device__ __forceinline__ void tma3d_mc(uint32_t dst, const CUtensorMap* m, int x, int y, int z, uint32_t bar, bool stream = false) {
  if (stream) asm volatile("cp.async.bulk.tensor.3d.shared::cluster.global.mbarrier::complete_tx::bytes.multicast::cluster.L2::cache_hint [%0], [%1, {%3, %4, %5}], [%2], %6, %7;" :: "r"(dst), "l"(m), "r"(bar), "r"(x), "r"(y), "r"(z), "h"((uint16_t)3), "l"(pol_first()) : "memory");
  else asm volatile("cp.async.bulk.tensor.3d.shared::cluster.global.mbarrier::complete_tx::bytes.multicast::cluster [%0], [%1, {%3, %4, %5}], [%2], %6;" :: "r"(dst), "l"(m), "r"(bar), "r"(x), "r"(y), "r"(z), "h"((uint16_t)3) : "memory");
}
__device__ __forceinline__ void tma2d_store(const CUtensorMap* m, uint32_t src, int x, int y) {
  asm volatile("cp.async.bulk.tensor.2d.global.shared::cta.bulk_group [%0, {%2, %3}], [%1];" :: "l"(m), "r"(src), "r"(x), "r"(y) : "memory");
}
__device__ __forceinline__ bool elect() {
  uint32_t r; asm volatile("{\n.reg .pred p;\nelect.sync _|p, 0xffffffff;\nselp.u32 %0, 1, 0, p;\n}\n" : "=r"(r)); return r != 0;
}
__device__ __forceinline__ void cluster_arrive() { asm volatile("barrier.cluster.arrive;" ::: "memory"); }
__device__ __forceinline__ void cluster_wait() { asm volatile("barrier.cluster.wait;" ::: "memory"); }
__device__ __forceinline__ void bar_sync(int id, int n) { asm volatile("bar.sync %0, %1;" :: "r"(id), "r"(n) : "memory"); }
__device__ __forceinline__ void bar_arrive(int id, int n) { asm volatile("bar.arrive %0, %1;" :: "r"(id), "r"(n) : "memory"); }
__device__ __forceinline__ int bar_and(int id, int n, int pred) {
  int r; asm volatile("{\n.reg .pred p, q;\nsetp.ne.b32 p, %3, 0;\nbar.red.and.pred q, %1, %2, p;\nselp.b32 %0, 1, 0, q;\n}\n" : "=r"(r) : "r"(id), "r"(n), "r"(pred) : "memory");
  return r;
}
__device__ __forceinline__ void fence_async_smem() { asm volatile("fence.proxy.async.shared::cta;" ::: "memory"); }
__device__ __forceinline__ float ex2(float x) { float y; asm("ex2.approx.ftz.f32 %0, %1;" : "=f"(y) : "f"(x)); return y; }
__device__ __forceinline__ uint32_t pack_bf16(float lo, float hi) { uint32_t r; asm("cvt.rn.bf16x2.f32 %0, %1, %2;" : "=r"(r) : "f"(hi), "f"(lo)); return r; }
__device__ __forceinline__ uint32_t hmul2(uint32_t a, uint32_t b) { uint32_t r; asm("mul.rn.bf16x2 %0, %1, %2;" : "=r"(r) : "r"(a), "r"(b)); return r; }
__device__ __forceinline__ uint32_t hadd2(uint32_t a, uint32_t b) { uint32_t r; asm("add.rn.bf16x2 %0, %1, %2;" : "=r"(r) : "r"(a), "r"(b)); return r; }
__device__ __forceinline__ uint32_t hfma2(uint32_t a, uint32_t b, uint32_t c) { uint32_t r; asm("fma.rn.bf16x2 %0, %1, %2, %3;" : "=r"(r) : "r"(a), "r"(b), "r"(c)); return r; }
__device__ __forceinline__ float bf_lo(uint32_t a) { return __uint_as_float(a << 16); }
__device__ __forceinline__ float bf_hi(uint32_t a) { return __uint_as_float(a & 0xffff0000u); }
__device__ __forceinline__ uint32_t lds32(uint32_t a) { uint32_t v; asm volatile("ld.shared.u32 %0, [%1];" : "=r"(v) : "r"(a) : "memory"); return v; }
__device__ __forceinline__ float2 lds64f(uint32_t a) { float2 v; asm volatile("ld.shared.v2.f32 {%0,%1}, [%2];" : "=f"(v.x), "=f"(v.y) : "r"(a) : "memory"); return v; }
__device__ __forceinline__ uint4 lds128(uint32_t a) { uint4 v; asm volatile("ld.shared.v4.u32 {%0,%1,%2,%3}, [%4];" : "=r"(v.x), "=r"(v.y), "=r"(v.z), "=r"(v.w) : "r"(a) : "memory"); return v; }
__device__ __forceinline__ void sts64f(uint32_t a, float x, float y) { asm volatile("st.shared.v2.f32 [%0], {%1,%2};" :: "r"(a), "f"(x), "f"(y) : "memory"); }
__device__ __forceinline__ void sts128(uint32_t a, uint4 v) { asm volatile("st.shared.v4.u32 [%0], {%1,%2,%3,%4};" :: "r"(a), "r"(v.x), "r"(v.y), "r"(v.z), "r"(v.w) : "memory"); }
template<int OFF> __device__ __forceinline__ void sts128o(uint32_t a, uint4 v) { asm volatile("st.shared.v4.u32 [%0+%5], {%1,%2,%3,%4};" :: "r"(a), "r"(v.x), "r"(v.y), "r"(v.z), "r"(v.w), "n"(OFF) : "memory"); }
__device__ __forceinline__ void ldsm4(uint32_t a, uint32_t& r0, uint32_t& r1, uint32_t& r2, uint32_t& r3) {
  asm volatile("ldmatrix.sync.aligned.m8n8.x4.shared.b16 {%0,%1,%2,%3}, [%4];" : "=r"(r0), "=r"(r1), "=r"(r2), "=r"(r3) : "r"(a) : "memory");
}
__device__ __forceinline__ void ldsm4t(uint32_t a, uint32_t& r0, uint32_t& r1, uint32_t& r2, uint32_t& r3) {
  asm volatile("ldmatrix.sync.aligned.m8n8.x4.trans.shared.b16 {%0,%1,%2,%3}, [%4];" : "=r"(r0), "=r"(r1), "=r"(r2), "=r"(r3) : "r"(a) : "memory");
}
__device__ __forceinline__ void stsm4(uint32_t a, uint32_t r0, uint32_t r1, uint32_t r2, uint32_t r3) {
  asm volatile("stmatrix.sync.aligned.m8n8.x4.shared.b16 [%0], {%1,%2,%3,%4};" :: "r"(a), "r"(r0), "r"(r1), "r"(r2), "r"(r3) : "memory");
}
template<int N> __device__ __forceinline__ void fence_regs(float (&d)[N]) {
#pragma unroll
  for (int i = 0; i < N; i++) asm volatile("" : "+f"(d[i]) :: "memory");
}
template<int N> __device__ __forceinline__ void fence_regs(uint32_t (&d)[N]) {
#pragma unroll
  for (int i = 0; i < N; i++) asm volatile("" : "+r"(d[i]) :: "memory");
}
__device__ __forceinline__ void sched_fence(float x, uint32_t dummy) {
  asm volatile("{\n.reg .pred p;\nsetp.eq.u32 p, %0, 0x7fc12345;\n@p st.shared.u32 [%1], %0;\n}\n" :: "r"(__float_as_uint(x)), "r"(dummy) : "memory");
}
#define TS(role, i)
#define TSA(i)
#define TR(obj, role, tag)

struct Prod {
  uint32_t base, mask; int lane, nt;
  __device__ __forceinline__ uint32_t full(int u) const { return base + SM_BAR + 8 * u; }
  __device__ __forceinline__ uint32_t addr(int u) const { return base + u * UNIT; }
  __device__ __forceinline__ void acquire(int u, int n) {
    const int v = u + min(lane, n - 1);
    mbar_wait_all(base + SM_BAR + 128 + 8 * v, (mask >> v) & 1);
    mask ^= ((1u << n) - 1) << u;
    TR(*this, 2, 16 + u);
  }
};
struct Cons {
  uint32_t base, rel, mask; int lane, warp, wg, nt;
  __device__ __forceinline__ uint32_t addr(int u) const { return base + u * UNIT; }
  __device__ __forceinline__ static uint32_t daddr(int u) { return SMEM_BASE + u * UNIT; }
  __device__ __forceinline__ void wait(int u) { TR(*this, wg, 1); mbar_wait(base + SM_BAR + 8 * u, (mask >> u) & 1); mask ^= 1u << u; TR(*this, wg, 2); }
  __device__ __forceinline__ void wait2(int u0, int u1) {
    TR(*this, wg, 1);
    const int v = (lane & 1) ? u1 : u0;
    mbar_wait_all(base + SM_BAR + 8 * v, (mask >> v) & 1); mask ^= (1u << u0) | (1u << u1);
    TR(*this, wg, 2);
  }
  __device__ __forceinline__ void skip(int u) { mask ^= 1u << u; }
  __device__ __forceinline__ void release(int u, int n) { TR(*this, wg, 5); if ((lane & 15) < n) asm volatile("mbarrier.arrive.shared::cluster.b64 _, [%0];" :: "r"(rel + 8 * u) : "memory"); }
  __device__ __forceinline__ void release2(int u) { if ((lane & 15) == 0) asm volatile("mbarrier.arrive.shared::cluster.b64 _, [%0], 2;" :: "r"(rel + 8 * u) : "memory"); }
  __device__ __forceinline__ void signal(int i) { __syncwarp(); if (lane == 0) mbar_arrive(base + SM_SIG + 8 * i); }
  __device__ __forceinline__ void turn() { bar_sync(1 + wg, 256); TR(*this, wg, 3); }
  __device__ __forceinline__ void pass() { bar_arrive(2 - wg, 256); TR(*this, wg, 4); }
};
__device__ __forceinline__ int gemm_unit(int ks) { return 3 * (ks & 3); }
__device__ __forceinline__ int att_slot(int i) { return 4 + 2 * i; }
template<int MASK> __device__ __forceinline__ int kv_slot(int h) { return MASK == PH_ALL ? HEAD(JOF(h), 0) : h; }
__device__ __forceinline__ int out_mb(int cta) { return cta >> 3; }
__device__ __forceinline__ int out_nb(int cta) { return cta & 7; }
__device__ __forceinline__ int conv_channel(int cta, int i) {
  return cta < NREG ? CH_EXTRA_TOTAL + cta * CONV_REG + i : (i >> 1) * 8 + (cta - NREG) * 2 + (i & 1);
}

template<int OFF, int N> __device__ __forceinline__ void pack_chunk(const float (&a)[N], float sc0, float sc1, uint4& v0, uint4& v1) {
  v0.x = pack_bf16(a[OFF + 0] * sc0, a[OFF + 1] * sc0); v0.y = pack_bf16(a[OFF + 4] * sc0, a[OFF + 5] * sc0);
  v0.z = pack_bf16(a[OFF + 8] * sc0, a[OFF + 9] * sc0); v0.w = pack_bf16(a[OFF + 12] * sc0, a[OFF + 13] * sc0);
  v1.x = pack_bf16(a[OFF + 2] * sc1, a[OFF + 3] * sc1); v1.y = pack_bf16(a[OFF + 6] * sc1, a[OFF + 7] * sc1);
  v1.z = pack_bf16(a[OFF + 10] * sc1, a[OFF + 11] * sc1); v1.w = pack_bf16(a[OFF + 14] * sc1, a[OFF + 15] * sc1);
}
template<int OFF, int N> __device__ __forceinline__ void pack_chunk(const float (&a)[N], uint4& v0, uint4& v1) {
  v0.x = pack_bf16(a[OFF + 0], a[OFF + 1]); v0.y = pack_bf16(a[OFF + 4], a[OFF + 5]);
  v0.z = pack_bf16(a[OFF + 8], a[OFF + 9]); v0.w = pack_bf16(a[OFF + 12], a[OFF + 13]);
  v1.x = pack_bf16(a[OFF + 2], a[OFF + 3]); v1.y = pack_bf16(a[OFF + 6], a[OFF + 7]);
  v1.z = pack_bf16(a[OFF + 10], a[OFF + 11]); v1.w = pack_bf16(a[OFF + 14], a[OFF + 15]);
}
__device__ __forceinline__ void sq_acc(const uint4& v, uint32_t& a) { a = hfma2(v.x, v.x, a); a = hfma2(v.y, v.y, a); a = hfma2(v.z, v.z, a); a = hfma2(v.w, v.w, a); }
__device__ __forceinline__ float norm2_max(uint32_t a0, uint32_t a1) {
  float n0 = bf_lo(a0) + bf_hi(a0), n1 = bf_lo(a1) + bf_hi(a1);
  n0 += __shfl_xor_sync(~0u, n0, 1); n1 += __shfl_xor_sync(~0u, n1, 1);
  n0 += __shfl_xor_sync(~0u, n0, 2); n1 += __shfl_xor_sync(~0u, n1, 2);
  return __uint_as_float(__reduce_max_sync(~0u, max(__float_as_uint(n0) & 0x7fffffffu, __float_as_uint(n1) & 0x7fffffffu)));
}

struct Pend { uint4 lo[8], hi[8]; uint32_t dst; float kn; };
__device__ __forceinline__ void pin(uint4 (&v)[8]) {
#pragma unroll
  for (int i = 0; i < 8; i++) asm volatile("" : "+r"(v[i].x), "+r"(v[i].y), "+r"(v[i].z), "+r"(v[i].w) :: "memory");
}
__device__ __forceinline__ uint32_t atom_off(int lane) { return (lane >> 2) * 64 + (((lane ^ (lane >> 3)) & 3) << 4); }
template<int J0, int J1> __device__ __forceinline__ void tile_store(const uint4 (&v)[8], uint32_t dst, int lane) {
  uint8_t* d = g_T + (dst + atom_off(lane));
#pragma unroll
  for (int j = J0; j < J1; j++) { *(uint4*)(d + j * 512) = v[2 * j]; *(uint4*)(d + j * 512 + 2048) = v[2 * j + 1]; }
}
__device__ __forceinline__ float tile_norm2(const uint4 (&v)[8]) {
  uint32_t n0 = 0, n1 = 0;
#pragma unroll
  for (int j = 0; j < 4; j++) { sq_acc(v[2 * j], n0); sq_acc(v[2 * j + 1], n1); }
  return norm2_max(n0, n1);
}
template<int PART> __device__ __forceinline__ void out_part(Cons& c, Pend& w) {
  if (PART == 0) { w.kn = tile_norm2(w.lo); tile_store<0, 2>(w.lo, w.dst, c.lane); }
  if (PART == 1) tile_store<2, 4>(w.lo, w.dst, c.lane);
  if (PART == 2) {
    const float vn = tile_norm2(w.hi);
    if (c.lane == 0) g_kn2[((w.dst - T_KV) >> 16) * 8 + c.wg * 4 + c.warp] = (vn <= 1.0e30f && vn >= 1.0e-30f) ? w.kn : __uint_as_float(0x7f800000u);
    tile_store<0, 2>(w.hi, w.dst + 32768, c.lane);
  }
  if (PART == 3) tile_store<2, 4>(w.hi, w.dst + 32768, c.lane);
}
template<bool FIRST> __device__ __forceinline__ void kv_issue(Cons& c, float (&acc)[128], int u) {
  const uint64_t da = mkdesc(c.daddr(u) + c.wg * 8192, 16, 1024, 1), db = mkdesc(c.daddr(u + 1), 8192, 1024, 1);
  c.turn();
  wg_fence();
#pragma unroll
  for (int kk = 0; kk < 4; kk++) wgmma_ss_n256<1>(acc, da + kk * 2, db + kk * 128, !(FIRST && kk == 0));
  wg_commit();
  c.pass();
}
__device__ __forceinline__ void cons_kv(Cons& c, int h, int hs, int g, Pend& w, bool pend_o) {
#pragma unroll 1
  for (int tile = 0; tile < 2; tile++) {
    float acc[128];
    c.wait(0);
    kv_issue<true>(c, acc, 0);
    if (tile == 1 && pend_o) mbar_wait(c.base + SM_RDY + 8 * RDY_WAR, 0);
    if (tile == 1 || pend_o) out_part<0>(c, w);
#pragma unroll 1
    for (int ks = 1; ks < 8; ks++) {
      if (ks == 3 && (tile == 1 || pend_o)) { out_part<1>(c, w); if (tile == 0) c.signal(SIG_CTX); }
      if (ks == 5 && tile == 1) out_part<2>(c, w);
      if (ks == 7 && tile == 1) out_part<3>(c, w);
      const int u = gemm_unit(ks);
      c.wait(u);
      wg_wait<0>();
      c.release(gemm_unit(ks - 1), 3);
      kv_issue<false>(c, acc, u);
    }
    wg_wait<0>(); fence_regs(acc);
    c.release(9, 3);
    pack_chunk<0>(acc, w.lo[0], w.lo[1]);  pack_chunk<16>(acc, w.lo[2], w.lo[3]); pack_chunk<32>(acc, w.lo[4], w.lo[5]); pack_chunk<48>(acc, w.lo[6], w.lo[7]);
    pack_chunk<64>(acc, w.hi[0], w.hi[1]); pack_chunk<80>(acc, w.hi[2], w.hi[3]); pack_chunk<96>(acc, w.hi[4], w.hi[5]); pack_chunk<112>(acc, w.hi[6], w.hi[7]);
    pin(w.lo); pin(w.hi);
    w.dst = T_KV + (hs * 16 + 2 * g + tile) * 65536 + (c.wg * 4 + c.warp) * 4096;
  }
}
template<bool FIRST> __device__ __forceinline__ void q_issue(Cons& c, float (&a)[64], float (&b)[64], int u) {
  const uint64_t da = mkdesc(c.daddr(u) + c.wg * 8192, 16, 1024, 1), db = mkdesc(c.daddr(u + 2), 8192, 1024, 1);
  const uint64_t da2 = mkdesc(c.daddr(u + 1) + (1 - c.wg) * 8192, 16, 1024, 1);
  c.turn();
  wg_fence();
#pragma unroll
  for (int kk = 0; kk < 4; kk++) wgmma_ss_n128<1>(a, da + kk * 2, db + kk * 128, !(FIRST && kk == 0));
#pragma unroll
  for (int kk = 0; kk < 4; kk++) wgmma_ss_n128<1>(b, da2 + kk * 2, db + kk * 128, !(FIRST && kk == 0));
  wg_commit();
  c.pass();
}
template<bool PEND_KV> __device__ __forceinline__ int cons_q(Cons& c, int h, Pend& w) {
  float a[64], b[64];
  c.wait(0);
  q_issue<true>(c, a, b, 0);
  if (PEND_KV) out_part<0>(c, w);
#pragma unroll 1
  for (int ks = 1; ks < 16; ks++) {
    if (PEND_KV) {
      if (ks == 2) out_part<1>(c, w);
      if (ks == 4) out_part<2>(c, w);
      if (ks == 5) { out_part<3>(c, w); c.signal(SIG_KV + HALF(h)); }
    }
    const int u = gemm_unit(ks);
    c.wait(u);
    wg_wait<0>();
    c.release(gemm_unit(ks - 1), 3);
    q_issue<false>(c, a, b, u);
  }
  c.wait(0);
  wg_wait<0>(); fence_regs(a); fence_regs(b);
  c.release(9, 3);
  const uint32_t q0 = c.addr(0) + (c.wg * 4 + c.warp) * 4096 + atom_off(c.lane);
  uint32_t a0 = 0, a1 = 0, e0 = 0, e1 = 0;
  uint4 v0, v1;
#define Q_CHUNK(J) pack_chunk<16 * J>(a, QSCALE, QSCALE, v0, v1); sts128o<J * 512>(q0, v0); sts128o<J * 512 + 2048>(q0, v1); sq_acc(v0, a0); sq_acc(v1, a1); \
  pack_chunk<16 * J>(b, QSCALE, QSCALE, v0, v1); sts128o<32768 + J * 512>(q0, v0); sts128o<32768 + J * 512 + 2048>(q0, v1); sq_acc(v0, e0); sq_acc(v1, e1);
  Q_CHUNK(0) Q_CHUNK(1) Q_CHUNK(2) Q_CHUNK(3)
#undef Q_CHUNK
  TR(c, c.wg, 40);
  fence_async_smem();
  const float qa = norm2_max(a0, a1), qb = norm2_max(e0, e1);
  const float kn = __uint_as_float(lds32(c.base + SM_KMAX + 4 * HALF(h)));
  TR(c, c.wg, 42);
  return __shfl_sync(~0u, bar_and(3 + c.wg, 128, (qa * kn <= BOUND2) && (qb * kn <= BOUND2)), 0);
}

__device__ __forceinline__ void issue_qk(float (&s)[64], uint32_t qaddr, uint32_t kaddr) {
  const uint64_t da = mkdesc(qaddr, 16, 2048, 2), db = mkdesc(kaddr, 16, 2048, 2);
#pragma unroll
  for (int kk = 0; kk < 8; kk++) wgmma_ss_n128<0>(s, da + (kk >> 1) * 32 + (kk & 1) * 2, db + (kk >> 1) * 32 + (kk & 1) * 2, kk > 0);
  wg_commit();
}
template<bool FRESH, int NK> __device__ __forceinline__ void issue_pv_n(float (&o)[64], uint32_t (&p)[32], uint32_t vaddr) {
  const uint64_t db = mkdesc(vaddr, 512, 2048, 2);
#pragma unroll
  for (int kk = 0; kk < NK; kk++) wgmma_rs_n128<1>(o, p[4 * kk], p[4 * kk + 1], p[4 * kk + 2], p[4 * kk + 3], db + kk * 256, !(FRESH && kk == 0));
  wg_commit();
}
template<bool FRESH> __device__ __forceinline__ void issue_pv(float (&o)[64], uint32_t (&p)[32], uint32_t vaddr, bool full) {
  wgmma_pv_sel(o, p, mkdesc(vaddr, 512, 2048, 2), full, FRESH ? gridDim.y - 1 : 1);
}
template<int A, int B> __device__ __forceinline__ void exp_rng(float (&s)[64]) {
#pragma unroll
  for (int i = 4 * A; i < 4 * B; i++) s[i] = ex2(s[i]);
}
template<int A, int B> __device__ __forceinline__ void sum_rng(const float (&s)[64], float (&l)[4]) {
#pragma unroll
  for (int i = A; i < B; i++) { l[0] += s[4 * i]; l[1] += s[4 * i + 1]; l[2] += s[4 * i + 2]; l[3] += s[4 * i + 3]; }
}
template<int A, int B> __device__ __forceinline__ void cvt_p(const float (&s)[64], uint32_t (&p)[32]) {
#pragma unroll
  for (int i = 2 * A; i < 2 * B; i++) p[i] = pack_bf16(s[2 * i], s[2 * i + 1]);
}
template<int K0> __device__ __forceinline__ void mask_half(float (&s)[64], int warp, int lane) {
  const int l0 = warp + (2 * (lane & 3) <= (lane >> 2)), l1 = warp + (2 * (lane & 3) < (lane >> 2));
#pragma unroll
  for (int k = 0; k < 4; k++) {
    float* t = s + 8 * (K0 + k);
    if (k >= l0) { t[0] = -INFINITY; t[6] = -INFINITY; }
    if (k >= l1) { t[1] = -INFINITY; t[7] = -INFINITY; }
    if (k > warp) { t[2] = -INFINITY; t[3] = -INFINITY; }
    if (k >= warp) { t[4] = -INFINITY; t[5] = -INFINITY; }
  }
}
__device__ __forceinline__ void mask_diag(float (&s)[64], int lim) {
#pragma unroll
  for (int i = 0; i < 16; i++) {
    if (8 * i > lim) s[4 * i] = -INFINITY;
    if (8 * i + 1 > lim) s[4 * i + 1] = -INFINITY;
    if (8 * i - 8 > lim) s[4 * i + 2] = -INFINITY;
    if (8 * i - 7 > lim) s[4 * i + 3] = -INFINITY;
  }
}
__device__ __forceinline__ void row_inv(float& l0, float& l1) {
  l0 += __shfl_xor_sync(~0u, l0, 1); l1 += __shfl_xor_sync(~0u, l1, 1);
  l0 += __shfl_xor_sync(~0u, l0, 2); l1 += __shfl_xor_sync(~0u, l1, 2);
  l0 = __fdividef(1.f, l0); l1 = __fdividef(1.f, l1);
}
__device__ __forceinline__ void pack_o(const float (&o)[64], float i0, float i1, uint4 (&v)[8]) {
  pack_chunk<0>(o, i0, i1, v[0], v[1]); pack_chunk<16>(o, i0, i1, v[2], v[3]);
  pack_chunk<32>(o, i0, i1, v[4], v[5]); pack_chunk<48>(o, i0, i1, v[6], v[7]);
  pin(v);
}
__device__ __forceinline__ void softmax_safe(float (&s)[64], float& m0, float& m1, float& sc0, float& sc1) {
  float a0 = m0, a1 = m1;
#pragma unroll
  for (int i = 0; i < 16; i++) { a0 = fmaxf(a0, fmaxf(s[4 * i], s[4 * i + 1])); a1 = fmaxf(a1, fmaxf(s[4 * i + 2], s[4 * i + 3])); }
  a0 = fmaxf(a0, __shfl_xor_sync(~0u, a0, 1)); a1 = fmaxf(a1, __shfl_xor_sync(~0u, a1, 1));
  a0 = fmaxf(a0, __shfl_xor_sync(~0u, a0, 2)); a1 = fmaxf(a1, __shfl_xor_sync(~0u, a1, 2));
  sc0 = ex2(m0 - a0); sc1 = ex2(m1 - a1);
  m0 = a0; m1 = a1;
#pragma unroll
  for (int i = 0; i < 16; i++) { s[4 * i] -= a0; s[4 * i + 1] -= a0; s[4 * i + 2] -= a1; s[4 * i + 3] -= a1; }
}
struct Att {
  float s[64], o[64], l[4], i0, i1; uint32_t p[32];
  int si; uint32_t qaddr;
};
__device__ __forceinline__ uint32_t ctx_off(const Cons& c, int h, int qb, int rowhalf) { return T_CTX + (qb * 32 + h) * 32768 + (rowhalf * 4 + c.warp) * 4096; }
template<bool DIAG, bool DRAIN>
__device__ __forceinline__ void att_step(Cons& c, Att& a, bool qkfull, bool pvfull, int relq, uint32_t dst) {
  const int uk = att_slot(a.si); a.si = (a.si + 1) & 3;
  const int uv = att_slot(a.si); a.si = (a.si + 1) & 3;
  if (DRAIN) c.wait(uk); else c.wait2(uk, uv);
  c.turn();
  fence_regs(a.o); fence_regs(a.p);
  if (DIAG) { wg_fence(); issue_qk(a.s, a.qaddr, c.daddr(uk) - (qkfull ? 0 : 16384)); }
  else { wg_fence(); issue_qk(a.s, a.qaddr, c.daddr(uk)); }
  if (DRAIN) {
    c.wait(uv);
    fence_regs(a.o);
    uint4 v[8];
    pack_o(a.o, a.i0, a.i1, v); tile_store<0, 4>(v, dst, c.lane);
  }
  if (DRAIN || DIAG) issue_pv<DRAIN>(a.o, a.p, c.daddr(uv), pvfull); else issue_pv_n<false, 8>(a.o, a.p, c.daddr(uv));
  c.pass();
  wg_wait<1>(); fence_regs(a.s);
  c.release(uk, 2);
  if (relq >= 0) c.release(relq, 2);
  constexpr int SPLIT = DIAG ? 8 : 6;
  if (DIAG) mask_half<4>(a.s, c.warp, c.lane);
  exp_rng<SPLIT, 16>(a.s); sum_rng<SPLIT, 16>(a.s, a.l);
  sched_fence((a.l[0] + a.l[1]) + (a.l[2] + a.l[3]), c.base + SM_DUMMY);
  wg_wait<0>(); fence_regs(a.o); fence_regs(a.p);
  c.release(uv, 2);
  cvt_p<SPLIT, 16>(a.s, a.p);
  if (!DIAG || qkfull) { exp_rng<0, SPLIT>(a.s); sum_rng<0, SPLIT>(a.s, a.l); cvt_p<0, SPLIT>(a.s, a.p); }
}
__device__ __forceinline__ void att_first(Cons& c, Att& a) {
  a.si = 1; a.qaddr = c.daddr(0) + c.wg * 16384;
  c.wait(4);
  c.turn();
  wg_fence();
  issue_qk(a.s, a.qaddr, c.daddr(4));
  c.pass();
#pragma unroll
  for (int i = 0; i < 64; i++) a.o[i] = 0.f;
  a.l[0] = a.l[1] = a.l[2] = a.l[3] = 0.f; a.i0 = a.i1 = 0.f;
  wg_wait<0>(); fence_regs(a.s);
  c.release(4, 2);
}
__device__ __forceinline__ void att_switch(Att& a) {
  a.i0 = a.l[0] + a.l[1]; a.i1 = a.l[2] + a.l[3]; row_inv(a.i0, a.i1);
  a.l[0] = a.l[1] = a.l[2] = a.l[3] = 0.f;
  a.qaddr += 32768;
}
__device__ __forceinline__ void att_drain_now(Cons& c, Att& a, uint32_t dst) {
  uint4 v[8];
  pack_o(a.o, a.i0, a.i1, v); tile_store<0, 4>(v, dst, c.lane);
#pragma unroll
  for (int i = 0; i < 64; i++) a.o[i] = 0.f;
}
__device__ __forceinline__ void att_last(Cons& c, Att& a, Pend& w, bool pvfull, uint32_t dst) {
  const int uv = att_slot(a.si);
  c.wait(uv);
  c.turn();
  fence_regs(a.o); fence_regs(a.p);
  issue_pv<false>(a.o, a.p, c.daddr(uv), pvfull);
  c.pass();
  a.i0 = a.l[0] + a.l[1]; a.i1 = a.l[2] + a.l[3]; row_inv(a.i0, a.i1);
  wg_wait<0>(); fence_regs(a.o); fence_regs(a.p);
  c.release(uv, 2);
  pack_o(a.o, a.i0, a.i1, w.lo);
  w.dst = dst;
}
__device__ __forceinline__ void cons_att_fast(Cons& c, Att& a, int h, int g) {
  exp_rng<0, 16>(a.s); sum_rng<0, 16>(a.s, a.l); cvt_p<0, 16>(a.s, a.p);
#pragma unroll 1
  for (int t = 0; t < 2; t++) {
#pragma unroll 1
    for (int j = t == 0 ? 14 - g : g - 1; j > 0; j--) att_step<false, false>(c, a, true, true, (t == 1 && j == 1) ? 2 : -1, 0);
    if (t == 0) {
#pragma unroll 1
      for (int d = 0; d < 2; d++) {
        att_step<true, false>(c, a, d != c.wg, !(d == 1 && c.wg == 0), d == 0 ? 0 : (g == 0 ? 2 : -1), 0);
        if (d == 0) att_switch(a);
      }
      if (g > 0) att_step<false, true>(c, a, true, c.wg == 0, g == 1 ? 2 : -1, ctx_off(c, h, 15 - g, c.wg));
      else att_drain_now(c, a, ctx_off(c, h, 15, c.wg));
    }
  }
}
__device__ __forceinline__ void cons_att_safe(Cons& c, Att& a, int h, int g) {
  float m0 = -INFINITY, m1 = -INFINITY, sc0, sc1;
#pragma unroll 1
  for (int st = 0; st <= 16; st++) {
    const bool sw = st == 16 - g;
    if (st > 0) {
      if (sw) att_switch(a);
      const int uk = att_slot(a.si); a.si = (a.si + 1) & 3;
      const int uv = att_slot(a.si); a.si = (a.si + 1) & 3;
      c.wait2(uk, uv);
      c.turn();
      fence_regs(a.o); fence_regs(a.p);
      wg_fence();
      issue_qk(a.s, a.qaddr, c.daddr(uk));
      issue_pv_n<false, 8>(a.o, a.p, c.daddr(uv));
      c.pass();
      wg_wait<0>(); fence_regs(a.s); fence_regs(a.o); fence_regs(a.p);
      c.release(uk, 2); c.release(uv, 2);
      if (st == 15 - g) c.release(0, 2);
      if (st == 16) c.release(2, 2);
      if (sw) { att_drain_now(c, a, ctx_off(c, h, 15 - g, c.wg)); m0 = m1 = -INFINITY; }
      if (sw || st == 15 - g) mask_diag(a.s, (sw ? 1 - c.wg : c.wg) * 64 + c.warp * 16 + (c.lane >> 2) - 2 * (c.lane & 3));
    }
    softmax_safe(a.s, m0, m1, sc0, sc1);
    a.l[0] *= sc0; a.l[1] *= sc0; a.l[2] *= sc1; a.l[3] *= sc1;
    exp_rng<0, 16>(a.s); sum_rng<0, 16>(a.s, a.l); cvt_p<0, 16>(a.s, a.p);
#pragma unroll
    for (int i = 0; i < 16; i++) { a.o[4 * i] *= sc0; a.o[4 * i + 1] *= sc0; a.o[4 * i + 2] *= sc1; a.o[4 * i + 3] *= sc1; }
  }
}
__device__ __forceinline__ void cons_att(Cons& c, int h, int g, int fast, Pend& w) {
  Att a;
  att_first(c, a);
  if (fast) cons_att_fast(c, a, h, g);
  else {
#pragma unroll
    for (int i = 0; i < 32; i++) a.p[i] = 0;
    cons_att_safe(c, a, h, g);
  }
  att_last(c, a, w, !(fast && g == 0 && c.wg == 1), ctx_off(c, h, g, 1 - c.wg));
}

constexpr int CV_H = 1024, CV_U = 5120, CV_D = CV_U + 4128, CV_ROW = 1056;
template<int OFF> __device__ __forceinline__ uint32_t lds32o(uint32_t a) { uint32_t v; asm volatile("ld.shared.u32 %0, [%1+%2];" : "=r"(v) : "r"(a), "n"(OFF) : "memory"); return v; }
template<int G> __device__ __forceinline__ void conv_lda(uint32_t (&a)[64], uint32_t p) {
  a[4 * G + 0] = lds32o<-256 * G>(p);
  a[4 * G + 1] = lds32o<-256 * G - 128>(p);
  a[4 * G + 2] = lds32o<-256 * G + 16>(p);
  a[4 * G + 3] = lds32o<-256 * G - 112>(p);
  if constexpr (G < 15) conv_lda<G + 1>(a, p);
}
template<int R, int G0, int G1> __device__ __forceinline__ void conv_mma(float (&d)[32], const uint32_t (&a)[64], uint64_t db) {
#pragma unroll
  for (int G = G0; G < G1; G++) wgmma_rs_n64<0>(d, a[4 * G], a[4 * G + 1], a[4 * G + 2], a[4 * G + 3], db + 64 * R - 16 * G, G > 0);
}
template<int R> __device__ __forceinline__ void conv_st(const float (&d)[32], uint32_t wq, float& c0, float& c1) {
#pragma unroll
  for (int n = 0; n < 8; n++) { sts64f(wq + (R * 64 + n * 8) * 4, d[4 * n] + c0, d[4 * n + 1] + c1); c0 = d[4 * n + 2]; c1 = d[4 * n + 3]; }
}
__device__ __forceinline__ void cons_conv(Cons& c, int cta, int nch) {
  const int r = c.lane >> 2, q = c.lane & 3, tid = c.warp * 32 + c.lane;
  const uint32_t part = c.addr(4) - 2048 + (1 - c.wg) * (32 * CV_ROW) + 32;
  const uint32_t aoff = CV_U + ((r & 1) ? 0 : UPITCH) + 4 * (((2039 - r) >> 1) + q - 8 * c.warp);
  const uint32_t wq = part + (c.warp * 8 + r) * CV_ROW + q * 8, rq = part + tid * 8;
  uint32_t a[64];
  c.wait(c.wg); c.skip(c.wg ^ 1);
  conv_lda<0>(a, c.addr(c.wg) + aoff);
  c.wait(4);
  sts64f(part + (tid >> 2) * CV_ROW - 32 + q * 8, 0.f, 0.f);
#pragma unroll 1
  for (int i = 0; i < nch / 2; i++) {
    const int u = 2 * (i & 1) + c.wg;
    float d0[32], d1[32], d2[32], d3[32];
    float c0 = 0.f, c1 = 0.f;
    const uint64_t db = mkdesc(c.daddr(u) + CV_H - 16, 16, 128, 0);
    c.turn();
    fence_regs(a);
    wg_fence();
    conv_mma<0, 0, 4>(d0, a, db); conv_mma<1, 0, 8>(d1, a, db); wg_commit();
    conv_mma<2, 0, 12>(d2, a, db); wg_commit();
    wg_wait<1>(); fence_regs(d0); fence_regs(d1);
    conv_st<0>(d0, wq, c0, c1);
    wg_fence();
    conv_mma<3, 0, 8>(d3, a, db);
    conv_st<1>(d1, wq, c0, c1);
    conv_mma<3, 8, 16>(d3, a, db); wg_commit();
    c.pass();
    if (i == nch / 2 - 1 && (GO_ARRIVALS == 8 || c.wg == 0)) c.signal(SIG_GO);
    wg_wait<1>(); fence_regs(d2);
    conv_st<2>(d2, wq, c0, c1);
    wg_wait<0>(); fence_regs(d3); fence_regs(a);
    conv_st<3>(d3, wq, c0, c1);
    TR(c, c.wg, 50);
    const uint32_t ub = c.addr(u);
    const uint4 ua = lds128(ub + CV_U + 4064 - 32 * tid + 16), uc = lds128(ub + CV_U + 4064 - 32 * tid);
    const uint32_t D2 = lds32(ub + CV_D);
    bar_sync(3 + c.wg, 128);
    c.release2(u);
    TR(c, c.wg, 51);
    float y0[8], y1[8];
#pragma unroll
    for (int rr = 0; rr < 8; rr++) { const float2 v = lds64f(rq + rr * CV_ROW); y0[rr] = v.x; y1[rr] = v.y; }
#pragma unroll
    for (int w = 1; w < 4; w++) {
#pragma unroll
      for (int rr = 0; rr < 8; rr++) { const float2 v = lds64f(rq + (w * 8 + rr) * CV_ROW - w * 8); y0[rr] += v.x; y1[rr] += v.y; }
    }
    if (i + 1 < nch / 2) { c.wait(u ^ 2); c.skip(u ^ 3); conv_lda<0>(a, c.addr(u ^ 2) + aoff); }
    uint4 z0, z1;
    z0.x = hadd2(pack_bf16(y0[0], y0[1]), hmul2(__byte_perm(ua.w, 0, 0x1032), D2));
    z0.y = hadd2(pack_bf16(y0[2], y0[3]), hmul2(__byte_perm(ua.z, 0, 0x1032), D2));
    z0.z = hadd2(pack_bf16(y0[4], y0[5]), hmul2(__byte_perm(ua.y, 0, 0x1032), D2));
    z0.w = hadd2(pack_bf16(y0[6], y0[7]), hmul2(__byte_perm(ua.x, 0, 0x1032), D2));
    z1.x = hadd2(pack_bf16(y1[0], y1[1]), hmul2(__byte_perm(uc.w, 0, 0x1032), D2));
    z1.y = hadd2(pack_bf16(y1[2], y1[3]), hmul2(__byte_perm(uc.z, 0, 0x1032), D2));
    z1.z = hadd2(pack_bf16(y1[4], y1[5]), hmul2(__byte_perm(uc.y, 0, 0x1032), D2));
    z1.w = hadd2(pack_bf16(y1[6], y1[7]), hmul2(__byte_perm(uc.x, 0, 0x1032), D2));
    uint4* zp = (uint4*)(g_z + (size_t)conv_channel(cta, 2 * i + c.wg) * 2048 + tid * 16);
    zp[0] = z0; zp[1] = z1;
    TR(c, c.wg, 52);
    if ((i & 15) == 15 || i == nch / 2 - 1) c.signal(SIG_Z + (i >> 4));
  }
  c.release(4, 4);
}

constexpr int OUT_XZ_AT = 58;
__device__ __forceinline__ int out_slot(int i) { return (0x2640A8C >> (4 * i)) & 15; }
__device__ __forceinline__ void cons_out(Cons& c, const Maps& M, int mb, int nb) {
  float acc[64];
  uint32_t ga[32];
  int si = 0, pu, u;
#define OUT_STEP(FIRST) { \
    u = out_slot(si); si = si == 6 ? 0 : si + 1; \
    c.wait(u); \
    const uint64_t da = mkdesc(c.daddr(u) + c.wg * 8192, 16, 1024, 2), db = mkdesc(c.daddr(u + 1), 8192, 1024, 1); \
    wg_fence(); \
    _Pragma("unroll") for (int kk = 0; kk < 4; kk++) wgmma_ss_n128<1>(acc, da + (kk >> 1) * 32 + (kk & 1) * 2, db + kk * 128, !(FIRST && kk == 0)); \
    wg_commit(); }
  OUT_STEP(true)
  pu = u;
#pragma unroll 1
  for (int ks = 1; ks <= OUT_XZ_AT; ks++) { OUT_STEP(false) wg_wait<1>(); c.release(pu, 2); pu = u; }
  const int ux = out_slot(si); si = si == 6 ? 0 : si + 1;
  const int uz = out_slot(si); si = si == 6 ? 0 : si + 1;
  OUT_STEP(false)
  c.wait2(ux, uz);
  const int row = mb * 128 + c.wg * 64 + c.warp * 16 + (c.lane >> 2);
  const float g0 = __ldcg(g_gate + row), g1 = __ldcg(g_gate + row + 8);
  const uint32_t gg0 = pack_bf16(g0, g0), gg1 = pack_bf16(g1, g1);
  const uint32_t og0 = pack_bf16(1.f - g0, 1.f - g0), og1 = pack_bf16(1.f - g1, 1.f - g1);
  const int xr = c.wg * 64 + c.warp * 16 + (c.lane & 15);
  const uint32_t xa = c.addr(ux) + xr * 128, xs = xr & 7, xh = c.lane >> 4;
  const int zr = (c.lane & 7) + ((c.lane >> 4) << 3);
  const uint32_t za = c.addr(uz) + c.wg * 16384 + zr * 128 + (((c.warp * 2 + ((c.lane >> 3) & 1)) ^ (zr & 7)) << 4);
#pragma unroll
  for (int i = 0; i < 8; i++) {
    uint32_t x0, x1, x2, x3, z0, z1, z2, z3;
    ldsm4(xa + (i >> 2) * 16384 + ((((i & 3) * 2 + xh) ^ xs) << 4), x0, x1, x2, x3);
    ldsm4t(za + i * 2048, z0, z1, z2, z3);
    ga[4 * i + 0] = hmul2(gg0, hmul2(x0, z0)); ga[4 * i + 1] = hmul2(gg1, hmul2(x1, z1));
    ga[4 * i + 2] = hmul2(gg0, hmul2(x2, z2)); ga[4 * i + 3] = hmul2(gg1, hmul2(x3, z3));
  }
  wg_wait<1>(); c.release(pu, 2);
#pragma unroll 1
  for (int ks = OUT_XZ_AT + 2; ks < 64; ks++) OUT_STEP(false)
#undef OUT_STEP
  asm volatile("barrier.cluster.arrive.relaxed;" ::: "memory");
  wg_wait<0>(); fence_regs(acc);
#pragma unroll
  for (int i = 0; i < 8; i++) {
    const uint32_t r0 = hadd2(ga[4 * i + 0], hmul2(og0, pack_bf16(acc[8 * i + 0], acc[8 * i + 1])));
    const uint32_t r1 = hadd2(ga[4 * i + 1], hmul2(og1, pack_bf16(acc[8 * i + 2], acc[8 * i + 3])));
    const uint32_t r2 = hadd2(ga[4 * i + 2], hmul2(og0, pack_bf16(acc[8 * i + 4], acc[8 * i + 5])));
    const uint32_t r3 = hadd2(ga[4 * i + 3], hmul2(og1, pack_bf16(acc[8 * i + 6], acc[8 * i + 7])));
    stsm4(xa + (i >> 2) * 16384 + ((((i & 3) * 2 + xh) ^ xs) << 4), r0, r1, r2, r3);
  }
  fence_async_smem();
  __syncwarp();
  if (c.lane < 2) {
    const int r0 = c.wg * 64 + c.warp * 16;
    tma2d_store(&M.out, c.addr(ux) + c.lane * 16384 + r0 * 128, nb * 128 + c.lane * 64, mb * 128 + r0);
    asm volatile("cp.async.bulk.commit_group;\ncp.async.bulk.wait_group.read 0;" ::: "memory");
  }
}

__device__ __forceinline__ void prod_conv(Prod& p, const Maps& M, int cta, int nch) {
  int ready = -1;
#pragma unroll 1
  for (int i = 0; i < nch; i++) {
    const int ch = conv_channel(cta, i);
    const int u = i & 3;
    if ((ch >> 6) != ready) { ready = ch >> 6; if (cta < NREG) mbar_wait(p.base + SM_RDY + 8 * RDY_U, 0); else cnt_wait(g_cnt + (C_U + ready) * CSTRIDE, 32); }
    p.acquire(u, 1);
    if (elect()) {
      mbar_expect(p.full(u), 5120 + UCH);
      tma3d(p.addr(u), &M.h, 0, -8, ch, p.full(u), POL(4));
      bulk_g2s(p.addr(u) + CV_U, g_u + (size_t)ch * UCH, UCH, p.full(u), POL(4));
    }
    if (i == 3) { p.acquire(4, 4); if (elect()) mbar_arrive(p.full(4)); }
  }
}
template<int MASK> __device__ __forceinline__ void producer(const Maps& M, const Params& P, uint32_t base, int cta, int lane) {
  Prod p{base, (MASK & PH_PRE) ? 0xffffcfffu : 0xffffffffu, lane,
         (cta * 3 + 2) * 2048};
  if (cta >= NREG) { if (MASK & PH_CONV) prod_conv(p, M, cta, CONV_EXTRA); return; }
  const int g = cta & 7, j = cta >> 3, rank = cta & 1;
#pragma unroll 1
  for (int half = 0; half < 2; half++) {
    const int h = HEAD(j, half);
    if (MASK & PH_KV) {
#pragma unroll 1
      for (int it = 0; it < 16; it++) {
        const int u = gemm_unit(it), ks = it & 7;
        p.acquire(u, 3);
        if (elect()) {
          mbar_expect(p.full(u), 3 * UNIT);
          tma2d(p.addr(u), &M.c, ks * 64, (2 * g + (it >> 3)) * 128, p.full(u));
          tma3d_mc(p.addr(u + 1 + rank), rank ? &M.wv : &M.wk, 0, ks * 64, 2 * h, p.full(u), it < 8 ? POL(7) : POL(0));
        }
      }
    }
    if (MASK & PH_ATT) {
#pragma unroll 1
      for (int ks = 0; ks < 16; ks++) {
        const int u = gemm_unit(ks);
        p.acquire(u, 3);
        if (elect()) {
          mbar_expect(p.full(u), 3 * UNIT);
          tma2d(p.addr(u), &M.x, ks * 64, (15 - g) * 128, p.full(u));
          tma2d(p.addr(u + 1), &M.x, ks * 64, g * 128, p.full(u));
          tma2d_mc(p.addr(u + 2) + rank * 8192, &M.wq, h * 128 + rank * 64, ks * 64, p.full(u), POL(1));
        }
      }
      TS(2, 8 * half + 0);
      mbar_wait(base + SM_RDY + 8 * (RDY_KV + half), 0);
      TS(2, 8 * half + 1);
      const uint8_t* KVh = g_T + T_KV + (size_t)kv_slot<MASK>(h) * 16 * 65536;
#pragma unroll 1
      for (int i = 0; i < 34; i++) {
        const int isv = (i > 0 && !(i & 1)) || i == 33;
        const int st = i == 33 ? 16 : (isv ? (i >> 1) - 1 : (i + 1) >> 1);
        const uint8_t* src = KVh + (st <= 15 - g ? st : 16 - st) * 65536 + isv * 32768;
        const int u = att_slot(i & 3);
        p.acquire(u, 2);
        if (elect()) {
          mbar_expect(p.full(u), 32768);
          if (st == 15 - (g & 6)) bulk_g2s(p.addr(u), src, 32768, p.full(u), POL(6));
          else bulk_g2s_mc(p.addr(u + rank), src + rank * UNIT, UNIT, p.full(u), POL(6));
        }
        if (i == 0) { p.acquire(0, 4); if (elect()) mbar_arrive(p.full(0)); }
      }
    }
  }
  if (MASK & PH_CONV) prod_conv(p, M, cta, CONV_REG);
  if (MASK & PH_OUT) {
    const int mb = out_mb(cta), nb = out_nb(cta);
    int si = 0;
#pragma unroll 1
    for (int ks = 0; ks < 64; ks++) {
      if ((ks & 31) == 0) { TS(2, 16 + (ks >> 4)); mbar_wait(base + SM_RDY + 8 * (RDY_CTX + (ks >> 5)), 0); TS(2, 17 + (ks >> 4)); }
      const int kb = HEAD((ks & 31) >> 1, ks >> 5) * 2 + (ks & 1);
      const int u = out_slot(si); si = si == 6 ? 0 : si + 1;
      p.acquire(u, 2);
      if (elect()) {
        mbar_expect(p.full(u), 2 * UNIT);
        tma2d_mc(p.addr(u) + rank * 8192, &M.ctx, (kb & 1) * 256, (mb * 32 + (kb >> 1)) * 16 + rank * 8, p.full(u), POL(5));
        tma3d(p.addr(u + 1), &M.wo, 0, kb * 64, 2 * nb, p.full(u), POL(2));
      }
      if (ks == OUT_XZ_AT) {
        const int ux = out_slot(si); si = si == 6 ? 0 : si + 1;
        const int uz = out_slot(si); si = si == 6 ? 0 : si + 1;
        p.acquire(ux, 2);
        if (elect()) {
          mbar_expect(p.full(ux), 2 * UNIT);
          tma2d(p.addr(ux), &M.x, nb * 128, mb * 128, p.full(ux), POL(5));
          tma2d(p.addr(ux + 1), &M.x, nb * 128 + 64, mb * 128, p.full(ux), POL(5));
        }
        TS(2, 20);
        mbar_wait(base + SM_RDY + 8 * RDY_Z, 0);
        TS(2, 21);
        p.acquire(uz, 2);
        if (elect()) {
          mbar_expect(p.full(uz), 2 * UNIT);
          tma2d(p.addr(uz), &M.z, mb * 128, nb * 128, p.full(uz), POL(5));
          tma2d(p.addr(uz + 1), &M.z, mb * 128 + 64, nb * 128, p.full(uz), POL(5));
        }
      }
    }
  }
}

template<int MASK> __device__ __forceinline__ void sync_agent(const Params& P, uint32_t base, int cta, int lane) {
#define PUBLISH(SIG, CNT, N) { mbar_wait_slow(base + SM_SIG + 8 * (SIG), 0); if (lane == 0) cnt_publish(g_cnt + (CNT) * CSTRIDE, N); __syncwarp(); }
#define READY(RDY) { __syncwarp(); if (lane == 0) mbar_arrive(base + SM_RDY + 8 * (RDY)); }
  if (cta >= NREG) {
    if (MASK & PH_CONV) for (int b = 0; b * 32 < CONV_EXTRA; b++) PUBLISH(SIG_Z + b, C_Z + b, min(32, CONV_EXTRA - b * 32))
    return;
  }
  const int g = cta & 7, j = cta >> 3;
#pragma unroll 1
  for (int half = 0; half < 2; half++) {
    const int h = HEAD(j, half);
    if (half == 1 && MASK == PH_ALL) PUBLISH(SIG_WAR, C_WAR + j, 1)
    if (half == 1 && (MASK & PH_ATT)) PUBLISH(SIG_CTX, C_CTX + g, 1)
    if (half == 1 && MASK == PH_ALL) { cnt_wait(g_cnt + (C_WAR + j) * CSTRIDE, 8); READY(RDY_WAR) }
    if (MASK & PH_KV) PUBLISH(SIG_KV + half, C_KV + h, 1)
    if (MASK & PH_ATT) {
      cnt_wait(g_cnt + (C_KV + h) * CSTRIDE, 8);
      const float4 kn = __ldcg((const float4*)(g_kn2 + kv_slot<MASK>(h) * 128) + lane);
      const uint32_t m = __reduce_max_sync(~0u, max(max(__float_as_uint(kn.x), __float_as_uint(kn.y)), max(__float_as_uint(kn.z), __float_as_uint(kn.w))));
      if (lane == 0) asm volatile("st.shared.u32 [%0], %1;" :: "r"(base + SM_KMAX + 4 * half), "r"(m) : "memory");
      READY(RDY_KV + half)
    }
  }
  if (MASK & PH_CONV) {
    cnt_wait(g_cnt + (C_U + (conv_channel(cta, 0) >> 6)) * CSTRIDE, 32);
    cnt_wait(g_cnt + (C_U + (conv_channel(cta, CONV_REG - 1) >> 6)) * CSTRIDE, 32);
    READY(RDY_U)
  }
  const int go = min(out_mb(cta), 15 - out_mb(cta));
  if (MASK & PH_OUT) cnt_wait(g_cnt + (C_CTX + go) * CSTRIDE, 16);
  if (MASK & PH_ATT) PUBLISH(SIG_CTX + 1, C_CTX + 8 + g, 1)
  if (MASK == PH_ALL) {
    mbar_wait(base + SM_SIG + 8 * SIG_GO, 0);
    if (lane == 0) asm volatile("red.relaxed.gpu.global.add.u32 [%0], 1;" :: "l"(g_cnt + C_GO * CSTRIDE) : "memory");
    cnt_poll(g_cnt + C_GO * CSTRIDE, NREG);
  }
  if (MASK & PH_OUT) READY(RDY_CTX)
  if (MASK & PH_CONV) {
    const int c0 = conv_channel(cta, 0), c1 = c0 + CONV_REG - 1;
    if ((c0 >> 7) == (c1 >> 7)) PUBLISH(SIG_Z, C_Z + (c0 >> 7), CONV_REG)
    else { PUBLISH(SIG_Z, C_Z + (c0 >> 7), 128 - (c0 & 127)) PUBLISH(SIG_Z, C_Z + (c1 >> 7), (c1 & 127) + 1) }
  }
  if (MASK & PH_OUT) {
    cnt_wait(g_cnt + (C_CTX + 8 + go) * CSTRIDE, 16); READY(RDY_CTX + 1)
    cnt_wait(g_cnt + C_GATE * CSTRIDE, 256);
    cnt_wait(g_cnt + (C_Z + out_nb(cta)) * CSTRIDE, 128); READY(RDY_Z)
  }
#undef PUBLISH
#undef READY
}

template<int MASK> __device__ __forceinline__ void aux_pre(const Maps& M, const Params& P, uint32_t base, int cta, int aw, int lane) {
  const uint32_t kb = base + 12 * UNIT, bar = base + SM_PRE;
  const int r = lane >> 2, q = lane & 3;
  const int mi = lane >> 3, row0 = (lane & 6) + 1 - (lane & 1);
#pragma unroll 1
  for (int it = 0; it < 4; it++) {
    if (it == PRE_EARLY && MASK == PH_ALL) mbar_wait_slow(base + SM_SIG + 8 * SIG_ATT, 0);
    const int cg = it * 4 + (cta >> 5), tb = cta & 31;
    if (aw == 0 && elect()) {
      mbar_expect(bar, 2 * 9216);
      tma4d(kb, &M.k, cg * 64, 0, tb * 8 - 1, 0, bar, POL(3));
      tma4d(kb + 9216, &M.v, cg * 64, 0, tb * 8 - 1, 0, bar, POL(3));
    }
    const uint2 swl = __ldg((const uint2*)(P.shift + (cg * 64 + aw * 32 + lane) * 4));
    if (tb == 0) {
      uint8_t* e = g_u + (size_t)(cg * 64 + aw * 32 + lane) * UCH + 4096;
      *(uint4*)e = make_uint4(0, 0, 0, 0); *(uint4*)(e + UPITCH) = make_uint4(0, 0, 0, 0);
      *(uint32_t*)(e + 32) = (uint32_t)__bfloat16_as_ushort(P.D[cg * 64 + aw * 32 + lane]) * 0x10001u;
    }
    mbar_wait_slow(bar, it & 1);
#pragma unroll 1
    for (int bl = 0; bl < 8; bl++) {
      const int oc = aw * 4 + (bl >> 1), hb = bl & 1, ch = cg * 64 + oc * 8 + r;
      const uint2 sw = make_uint2(__shfl_sync(~0u, swl.x, (bl >> 1) * 8 + r), __shfl_sync(~0u, swl.y, (bl >> 1) * 8 + r));
      const uint32_t w0 = __byte_perm(sw.x, 0, 0x1010), w1 = __byte_perm(sw.x, 0, 0x3232), w2 = __byte_perm(sw.y, 0, 0x1010), w3 = __byte_perm(sw.y, 0, 0x3232);
      const int ra = (mi * 9 + 4 * hb + 1) * 2 + row0;
      const int rb = ((mi == 0 ? 3 : mi) * 9 + 4 * hb) * 2 + row0;
      uint32_t k[7], v[5];
      ldsm4t(kb + ra * 128 + ((oc ^ (ra & 7)) << 4), k[3], k[4], k[5], k[6]);
      ldsm4t(kb + 9216 + ra * 128 + ((oc ^ (ra & 7)) << 4), v[1], v[2], v[3], v[4]);
      ldsm4t(kb + (mi == 0 ? 9216 : 0) + rb * 128 + ((oc ^ (rb & 7)) << 4), v[0], k[0], k[1], k[2]);
      uint32_t o1 = __byte_perm(k[1], k[0], 0x5432);
#pragma unroll
      for (int m = 0; m < 5; m++) {
        const uint32_t o2 = __byte_perm(k[m + 2], k[m + 1], 0x5432);
        v[m] = hmul2(hadd2(hadd2(hadd2(hmul2(o1, w3), hmul2(k[m + 1], w2)), hmul2(o2, w1)), hmul2(k[m + 2], w0)), v[m]);
        o1 = o2;
      }
      uint8_t* e0 = g_u + (size_t)ch * UCH + (2040 - tb * 64 - hb * 32 - 8 * q) * 2;
      *(uint4*)e0 = make_uint4(v[4], v[3], v[2], v[1]);
      *(uint4*)(e0 + UPITCH) = make_uint4(__byte_perm(v[4], v[3], 0x5432), __byte_perm(v[3], v[2], 0x5432), __byte_perm(v[2], v[1], 0x5432), __byte_perm(v[1], v[0], 0x5432));
    }
    bar_sync(5, 64);
    if (aw == 0) { TSA(40 + it); }
    if (aw == 1 && lane == 0) asm volatile("red.release.gpu.global.add.u32 [%0], 1;" :: "l"(g_cnt + (C_U + cg) * CSTRIDE) : "memory");
  }
  uint32_t rel;
  asm volatile("mapa.shared::cluster.u32 %0, %1, %2;" : "=r"(rel) : "r"(base + SM_BAR + 128 + 8 * (12 + (lane & 1))), "r"((lane >> 1) & 1));
  if (lane < 4) asm volatile("mbarrier.arrive.shared::cluster.b64 _, [%0], 4;" :: "r"(rel) : "memory");
  uint4 gw[4];
#pragma unroll
  for (int i = 0; i < 4; i++) gw[i] = __ldg((const uint4*)P.gw + i * 32 + lane);
#pragma unroll 1
  for (int row = cta * 16 + aw * 8; row < cta * 16 + aw * 8 + 8; row++) {
    float a = 0.f;
#pragma unroll
    for (int i = 0; i < 4; i++) {
      const uint4 xv = __ldg((const uint4*)(P.x + (size_t)row * 1024) + i * 32 + lane);
      uint32_t m;
      m = hmul2(xv.x, gw[i].x); a += bf_lo(m) + bf_hi(m); m = hmul2(xv.y, gw[i].y); a += bf_lo(m) + bf_hi(m);
      m = hmul2(xv.z, gw[i].z); a += bf_lo(m) + bf_hi(m); m = hmul2(xv.w, gw[i].w); a += bf_lo(m) + bf_hi(m);
    }
#pragma unroll
    for (int o = 16; o > 0; o >>= 1) a += __shfl_xor_sync(~0u, a, o);
    a = bf_lo(pack_bf16(a, 0.f));
    const float gt = bf_lo(pack_bf16(__fdividef(1.f, 1.f + ex2(-a * 1.4426950408889634f)), 0.f));
    if (lane == 0) g_gate[row] = gt;
  }
  cnt_signal(g_cnt + C_GATE * CSTRIDE, lane);
  if (aw == 0) { TSA(44); }
}

template<int MASK> __global__ void __cluster_dims__(2, 1, 1) __launch_bounds__(384, 1) gated_mix_kernel(const __grid_constant__ Maps M, const __grid_constant__ Params P) {
  extern __shared__ __align__(1024) uint8_t smem[];
  const uint32_t base = (uint32_t)__cvta_generic_to_shared(smem);
  if (threadIdx.x == 0) {
    if ((base & 0x3FFFF) != SMEM_BASE) asm volatile("trap;");
    for (int i = 0; i < NUNIT; i++) { mbar_init(base + SM_BAR + 8 * i, 1); mbar_init(base + SM_BAR + 128 + 8 * i, 16); }
    mbar_init(base + SM_EXIT, 4); mbar_init(base + SM_PRE, 1);
    for (int i = 0; i < 11; i++) { mbar_init(base + SM_SIG + 8 * i, i == SIG_GO ? GO_ARRIVALS : 8); mbar_init(base + SM_RDY + 8 * i, 1); }
    asm volatile("fence.mbarrier_init.release.cluster;" ::: "memory");
  }
  __syncthreads();
  asm volatile("barrier.cluster.arrive.relaxed.aligned;\nbarrier.cluster.wait.aligned;" ::: "memory");
  const int wg = __shfl_sync(~0u, threadIdx.x >> 7, 0);
  const int warp = __shfl_sync(~0u, (threadIdx.x >> 5) & 3, 0);
  const int lane = threadIdx.x & 31;
  const int cta = blockIdx.x;
  if (wg == 2) {
    asm volatile("setmaxnreg.dec.sync.aligned.u32 56;");
    TS(2, 62);
    if (warp == 0) producer<MASK>(M, P, base, cta, lane);
    else if (warp == 1) sync_agent<MASK>(P, base, cta, lane);
    else if ((MASK & PH_PRE) && cta < NREG) aux_pre<MASK>(M, P, base, cta, warp - 2, lane);
    __syncwarp();
    if (lane == 0) mbar_arrive(base + SM_EXIT);
    if (warp == 0 && (MASK & PH_OUT)) {
      mbar_wait_slow(base + SM_EXIT, 0);
      unsigned old = 0;
      if (lane == 0) asm volatile("atom.acq_rel.gpu.global.add.u32 %0, [%1], 1;" : "=r"(old) : "l"(g_cnt + C_EXIT * CSTRIDE) : "memory");
      old = __shfl_sync(~0u, old, 0);
      if (old == NCTA - 1) for (int i = lane; i < C_NUM; i += 32) g_cnt[i * CSTRIDE] = 0;
    }
    if (warp == 0) { cluster_arrive(); cluster_wait(); }
  } else {
    asm volatile("setmaxnreg.inc.sync.aligned.u32 224;");
    uint32_t rel;
    asm volatile("mapa.shared::cluster.u32 %0, %1, %2;" : "=r"(rel) : "r"(base + SM_BAR + 128 + 8 * (lane & 15)), "r"(lane >> 4));
    Cons c{base, rel, 0u, lane, warp, wg, (cta * 3 + wg) * 2048};
    if (wg == 1) bar_arrive(1, 256);
    TS(wg, 0);
    if (cta < NREG) {
      const int g = cta & 7, j = cta >> 3;
      Pend w = {};
#pragma unroll 1
      for (int half = 0; half < 2; half++) {
        const int h = HEAD(j, half);
        if (MASK & PH_KV) cons_kv(c, h, kv_slot<MASK>(h), g, w, half == 1 && (MASK & PH_ATT));
        TS(wg, 1 + 4 * half);
        if (MASK & PH_ATT) {
          const int fast = cons_q<(MASK & PH_KV) != 0>(c, h, w);
          TS(wg, 2 + 4 * half);
          if (half == PRE_HALF) c.signal(SIG_ATT);
          cons_att(c, h, g, fast, w);
          if (half == 0) c.signal(SIG_WAR);
#pragma unroll
          for (int i = 0; i < 8; i++) w.hi[i] = make_uint4(0, 0, 0, 0);
          TS(wg, 3 + 4 * half);
          if (half == 1 || !(MASK & PH_KV)) { tile_store<0, 4>(w.lo, w.dst, lane); c.signal(SIG_CTX + half); }
        } else if (MASK & PH_KV) { out_part<0>(c, w); out_part<1>(c, w); out_part<2>(c, w); out_part<3>(c, w); c.signal(SIG_KV + half); }
      }
    }
    if (MASK & PH_CONV) cons_conv(c, cta, cta < NREG ? CONV_REG : CONV_EXTRA);
    TS(wg, 9);
    if (cta < NREG && (MASK & PH_OUT)) cons_out(c, M, out_mb(cta), out_nb(cta)); else cluster_arrive();
    TS(wg, 10);
  }
}

typedef CUresult (*EncFn)(CUtensorMap*, CUtensorMapDataType, cuuint32_t, void*, const cuuint64_t*, const cuuint64_t*, const cuuint32_t*, const cuuint32_t*,
                          CUtensorMapInterleave, CUtensorMapSwizzle, CUtensorMapL2promotion, CUtensorMapFloatOOBfill);
static void enc(EncFn f, CUtensorMap* m, const void* ptr, int rank, const cuuint64_t* dims, const cuuint64_t* strides, const cuuint32_t* box, CUtensorMapSwizzle sw,
                CUtensorMapDataType dt = CU_TENSOR_MAP_DATA_TYPE_BFLOAT16) {
  const cuuint32_t es[4] = {1, 1, 1, 1};
  f(m, dt, rank, (void*)ptr, dims, strides, box, es, CU_TENSOR_MAP_INTERLEAVE_NONE, sw, CU_TENSOR_MAP_L2_PROMOTION_L2_256B, CU_TENSOR_MAP_FLOAT_OOB_FILL_NONE);
}
static void enc2(EncFn f, CUtensorMap* m, const void* ptr, int cols, int rows, int brows) {
  const cuuint64_t d[2] = {(cuuint64_t)cols, (cuuint64_t)rows}, s[1] = {(cuuint64_t)cols * 2}; const cuuint32_t b[2] = {64, (cuuint32_t)brows};
  enc(f, m, ptr, 2, d, s, b, CU_TENSOR_MAP_SWIZZLE_128B);
}
static void encw(EncFn f, CUtensorMap* m, const void* ptr, int cols, int rows) {
  const cuuint64_t d[3] = {64, (cuuint64_t)rows, (cuuint64_t)cols / 64}, s[2] = {(cuuint64_t)cols * 2, 128}; const cuuint32_t b[3] = {64, 64, 2};
  enc(f, m, ptr, 3, d, s, b, CU_TENSOR_MAP_SWIZZLE_128B);
}
extern "C" void kernel_launch(void* const* d_in, const int* in_sizes, int n_in, void* d_out, int out_size) {
  static EncFn fn = nullptr;
  static int ncl = 0;
  static void* zptr = nullptr;
  static void* tptr = nullptr;
  if (!fn) {
    void* p = nullptr; cudaDriverEntryPointQueryResult qr;
    cudaGetDriverEntryPoint("cuTensorMapEncodeTiled", &p, cudaEnableDefault, &qr);
    fn = (EncFn)p;
    cudaFuncSetAttribute(gated_mix_kernel<PH_ALL>, cudaFuncAttributeMaxDynamicSharedMemorySize, SMEM_BYTES);
    cudaFuncSetAttribute(gated_mix_kernel<PH_PRE | PH_KV>, cudaFuncAttributeMaxDynamicSharedMemorySize, SMEM_BYTES);
    cudaFuncSetAttribute(gated_mix_kernel<PH_ATT | PH_CONV>, cudaFuncAttributeMaxDynamicSharedMemorySize, SMEM_BYTES);
    cudaFuncSetAttribute(gated_mix_kernel<PH_OUT>, cudaFuncAttributeMaxDynamicSharedMemorySize, SMEM_BYTES);
    cudaLaunchConfig_t cfg = {}; cfg.gridDim = NCTA; cfg.blockDim = 384; cfg.dynamicSmemBytes = SMEM_BYTES;
    cudaLaunchAttribute at; at.id = cudaLaunchAttributeClusterDimension; at.val.clusterDim.x = 2; at.val.clusterDim.y = 1; at.val.clusterDim.z = 1;
    cfg.attrs = &at; cfg.numAttrs = 1;
    cudaOccupancyMaxActiveClusters(&ncl, gated_mix_kernel<PH_ALL>, &cfg);
    cudaGetSymbolAddress(&zptr, g_z);
    cudaGetSymbolAddress(&tptr, g_T);
  }
  Maps M;
  enc2(fn, &M.x, d_in[0], 1024, 2048, 128);
  enc2(fn, &M.c, d_in[7], 512, 2048, 128);
  enc2(fn, &M.wq, d_in[8], 4096, 1024, 64);
  encw(fn, &M.wk, d_in[9], 4096, 512);
  encw(fn, &M.wv, d_in[10], 4096, 512);
  encw(fn, &M.wo, d_in[11], 1024, 4096);
  { const cuuint64_t d[3] = {64, 32, 1024}, s[2] = {128, 4096}; const cuuint32_t b[3] = {64, 40, 1}; enc(fn, &M.h, d_in[4], 3, d, s, b, CU_TENSOR_MAP_SWIZZLE_NONE); }
  enc2(fn, &M.z, zptr, 2048, 1024, 128);
  enc2(fn, &M.out, d_out, 1024, 2048, 16);
  { const cuuint64_t d[2] = {512, 512 * 16}, s[1] = {2048}; const cuuint32_t b[2] = {256, 8};
    enc(fn, &M.ctx, tptr, 2, d, s, b, CU_TENSOR_MAP_SWIZZLE_NONE, CU_TENSOR_MAP_DATA_TYPE_UINT32); }
  { const cuuint64_t d[4] = {1024, 2, 256, 4}, s[3] = {2048, 16384, 4096}; const cuuint32_t b[4] = {64, 2, 9, 4};
    enc(fn, &M.k, d_in[1], 4, d, s, b, CU_TENSOR_MAP_SWIZZLE_128B); enc(fn, &M.v, d_in[2], 4, d, s, b, CU_TENSOR_MAP_SWIZZLE_128B); }
  Params P{(const __nv_bfloat16*)d_in[0], (const __nv_bfloat16*)d_in[3],
           (const __nv_bfloat16*)d_in[5], (const __nv_bfloat16*)d_in[12]};
  bool split = 2 * ncl < NCTA;
  if (!split) {
    gated_mix_kernel<PH_ALL><<<NCTA, 384, SMEM_BYTES>>>(M, P);
  } else {
    gated_mix_kernel<PH_PRE | PH_KV><<<NCTA, 384, SMEM_BYTES>>>(M, P);
    gated_mix_kernel<PH_ATT | PH_CONV><<<NCTA, 384, SMEM_BYTES>>>(M, P);
    gated_mix_kernel<PH_OUT><<<NCTA, 384, SMEM_BYTES>>>(M, P);
  }
}
```

```cpp
#include <cuda_runtime.h>
#include <cuda.h>
#include <cuda_bf16.h>
#include <stdint.h>

template<int TB> __device__ __forceinline__ void wgmma_ss_n256(float (&d)[128], uint64_t da, uint64_t db, int scale_d) {
  asm volatile("{\n.reg .pred p;\nsetp.ne.b32 p, %130, 0;\n"
    "wgmma.mma_async.sync.aligned.m64n256k16.f32.bf16.bf16 {%0, %1, %2, %3, %4, %5, %6, %7, %8, %9, %10, %11, %12, %13, %14, %15, %16, %17, %18, %19, %20, %21, %22, %23, %24, %25, %26, %27, %28, %29, %30, %31, %32, %33, %34, %35, %36, %37, %38, %39, %40, %41, %42, %43, %44, %45, %46, %47, %48, %49, %50, %51, %52, %53, %54, %55, %56, %57, %58, %59, %60, %61, %62, %63, %64, %65, %66, %67, %68, %69, %70, %71, %72, %73, %74, %75, %76, %77, %78, %79, %80, %81, %82, %83, %84, %85, %86, %87, %88, %89, %90, %91, %92, %93, %94, %95, %96, %97, %98, %99, %100, %101, %102, %103, %104, %105, %106, %107, %108, %109, %110, %111, %112, %113, %114, %115, %116, %117, %118, %119, %120, %121, %122, %123, %124, %125, %126, %127}, %128, %129, p, 1, 1, 0, %131;\n}\n"
    : "+f"(d[0]), "+f"(d[1]), "+f"(d[2]), "+f"(d[3]), "+f"(d[4]), "+f"(d[5]), "+f"(d[6]), "+f"(d[7]), "+f"(d[8]), "+f"(d[9]), "+f"(d[10]), "+f"(d[11]), "+f"(d[12]), "+f"(d[13]), "+f"(d[14]), "+f"(d[15]), "+f"(d[16]), "+f"(d[17]), "+f"(d[18]), "+f"(d[19]), "+f"(d[20]), "+f"(d[21]), "+f"(d[22]), "+f"(d[23]), "+f"(d[24]), "+f"(d[25]), "+f"(d[26]), "+f"(d[27]), "+f"(d[28]), "+f"(d[29]), "+f"(d[30]), "+f"(d[31]), "+f"(d[32]), "+f"(d[33]), "+f"(d[34]), "+f"(d[35]), "+f"(d[36]), "+f"(d[37]), "+f"(d[38]), "+f"(d[39]), "+f"(d[40]), "+f"(d[41]), "+f"(d[42]), "+f"(d[43]), "+f"(d[44]), "+f"(d[45]), "+f"(d[46]), "+f"(d[47]), "+f"(d[48]), "+f"(d[49]), "+f"(d[50]), "+f"(d[51]), "+f"(d[52]), "+f"(d[53]), "+f"(d[54]), "+f"(d[55]), "+f"(d[56]), "+f"(d[57]), "+f"(d[58]), "+f"(d[59]), "+f"(d[60]), "+f"(d[61]), "+f"(d[62]), "+f"(d[63]), "+f"(d[64]), "+f"(d[65]), "+f"(d[66]), "+f"(d[67]), "+f"(d[68]), "+f"(d[69]), "+f"(d[70]), "+f"(d[71]), "+f"(d[72]), "+f"(d[73]), "+f"(d[74]), "+f"(d[75]), "+f"(d[76]), "+f"(d[77]), "+f"(d[78]), "+f"(d[79]), "+f"(d[80]), "+f"(d[81]), "+f"(d[82]), "+f"(d[83]), "+f"(d[84]), "+f"(d[85]), "+f"(d[86]), "+f"(d[87]), "+f"(d[88]), "+f"(d[89]), "+f"(d[90]), "+f"(d[91]), "+f"(d[92]), "+f"(d[93]), "+f"(d[94]), "+f"(d[95]), "+f"(d[96]), "+f"(d[97]), "+f"(d[98]), "+f"(d[99]), "+f"(d[100]), "+f"(d[101]), "+f"(d[102]), "+f"(d[103]), "+f"(d[104]), "+f"(d[105]), "+f"(d[106]), "+f"(d[107]), "+f"(d[108]), "+f"(d[109]), "+f"(d[110]), "+f"(d[111]), "+f"(d[112]), "+f"(d[113]), "+f"(d[114]), "+f"(d[115]), "+f"(d[116]), "+f"(d[117]), "+f"(d[118]), "+f"(d[119]), "+f"(d[120]), "+f"(d[121]), "+f"(d[122]), "+f"(d[123]), "+f"(d[124]), "+f"(d[125]), "+f"(d[126]), "+f"(d[127])
    : "l"(da), "l"(db), "r"(scale_d), "n"(TB));
}
template<int TB> __device__ __forceinline__ void wgmma_ss_n128(float (&d)[64], uint64_t da, uint64_t db, int scale_d) {
  asm volatile("{\n.reg .pred p;\nsetp.ne.b32 p, %66, 0;\n"
    "wgmma.mma_async.sync.aligned.m64n128k16.f32.bf16.bf16 {%0, %1, %2, %3, %4, %5, %6, %7, %8, %9, %10, %11, %12, %13, %14, %15, %16, %17, %18, %19, %20, %21, %22, %23, %24, %25, %26, %27, %28, %29, %30, %31, %32, %33, %34, %35, %36, %37, %38, %39, %40, %41, %42, %43, %44, %45, %46, %47, %48, %49, %50, %51, %52, %53, %54, %55, %56, %57, %58, %59, %60, %61, %62, %63}, %64, %65, p, 1, 1, 0, %67;\n}\n"
    : "+f"(d[0]), "+f"(d[1]), "+f"(d[2]), "+f"(d[3]), "+f"(d[4]), "+f"(d[5]), "+f"(d[6]), "+f"(d[7]), "+f"(d[8]), "+f"(d[9]), "+f"(d[10]), "+f"(d[11]), "+f"(d[12]), "+f"(d[13]), "+f"(d[14]), "+f"(d[15]), "+f"(d[16]), "+f"(d[17]), "+f"(d[18]), "+f"(d[19]), "+f"(d[20]), "+f"(d[21]), "+f"(d[22]), "+f"(d[23]), "+f"(d[24]), "+f"(d[25]), "+f"(d[26]), "+f"(d[27]), "+f"(d[28]), "+f"(d[29]), "+f"(d[30]), "+f"(d[31]), "+f"(d[32]), "+f"(d[33]), "+f"(d[34]), "+f"(d[35]), "+f"(d[36]), "+f"(d[37]), "+f"(d[38]), "+f"(d[39]), "+f"(d[40]), "+f"(d[41]), "+f"(d[42]), "+f"(d[43]), "+f"(d[44]), "+f"(d[45]), "+f"(d[46]), "+f"(d[47]), "+f"(d[48]), "+f"(d[49]), "+f"(d[50]), "+f"(d[51]), "+f"(d[52]), "+f"(d[53]), "+f"(d[54]), "+f"(d[55]), "+f"(d[56]), "+f"(d[57]), "+f"(d[58]), "+f"(d[59]), "+f"(d[60]), "+f"(d[61]), "+f"(d[62]), "+f"(d[63])
    : "l"(da), "l"(db), "r"(scale_d), "n"(TB));
}
template<int TB> __device__ __forceinline__ void wgmma_rs_n128(float (&d)[64], uint32_t a0, uint32_t a1, uint32_t a2, uint32_t a3, uint64_t db, int scale_d) {
  asm volatile("{\n.reg .pred p;\nsetp.ne.b32 p, %69, 0;\n"
    "wgmma.mma_async.sync.aligned.m64n128k16.f32.bf16.bf16 {%0, %1, %2, %3, %4, %5, %6, %7, %8, %9, %10, %11, %12, %13, %14, %15, %16, %17, %18, %19, %20, %21, %22, %23, %24, %25, %26, %27, %28, %29, %30, %31, %32, %33, %34, %35, %36, %37, %38, %39, %40, %41, %42, %43, %44, %45, %46, %47, %48, %49, %50, %51, %52, %53, %54, %55, %56, %57, %58, %59, %60, %61, %62, %63}, {%64, %65, %66, %67}, %68, p, 1, 1, %70;\n}\n"
    : "+f"(d[0]), "+f"(d[1]), "+f"(d[2]), "+f"(d[3]), "+f"(d[4]), "+f"(d[5]), "+f"(d[6]), "+f"(d[7]), "+f"(d[8]), "+f"(d[9]), "+f"(d[10]), "+f"(d[11]), "+f"(d[12]), "+f"(d[13]), "+f"(d[14]), "+f"(d[15]), "+f"(d[16]), "+f"(d[17]), "+f"(d[18]), "+f"(d[19]), "+f"(d[20]), "+f"(d[21]), "+f"(d[22]), "+f"(d[23]), "+f"(d[24]), "+f"(d[25]), "+f"(d[26]), "+f"(d[27]), "+f"(d[28]), "+f"(d[29]), "+f"(d[30]), "+f"(d[31]), "+f"(d[32]), "+f"(d[33]), "+f"(d[34]), "+f"(d[35]), "+f"(d[36]), "+f"(d[37]), "+f"(d[38]), "+f"(d[39]), "+f"(d[40]), "+f"(d[41]), "+f"(d[42]), "+f"(d[43]), "+f"(d[44]), "+f"(d[45]), "+f"(d[46]), "+f"(d[47]), "+f"(d[48]), "+f"(d[49]), "+f"(d[50]), "+f"(d[51]), "+f"(d[52]), "+f"(d[53]), "+f"(d[54]), "+f"(d[55]), "+f"(d[56]), "+f"(d[57]), "+f"(d[58]), "+f"(d[59]), "+f"(d[60]), "+f"(d[61]), "+f"(d[62]), "+f"(d[63])
    : "r"(a0), "r"(a1), "r"(a2), "r"(a3), "l"(db), "r"(scale_d), "n"(TB));
}
template<int TB> __device__ __forceinline__ void wgmma_rs_n64(float (&d)[32], uint32_t a0, uint32_t a1, uint32_t a2, uint32_t a3, uint64_t db, int scale_d) {
  asm volatile("{\n.reg .pred p;\nsetp.ne.b32 p, %37, 0;\n"
    "wgmma.mma_async.sync.aligned.m64n64k16.f32.bf16.bf16 {%0, %1, %2, %3, %4, %5, %6, %7, %8, %9, %10, %11, %12, %13, %14, %15, %16, %17, %18, %19, %20, %21, %22, %23, %24, %25, %26, %27, %28, %29, %30, %31}, {%32, %33, %34, %35}, %36, p, 1, 1, %38;\n}\n"
    : "+f"(d[0]), "+f"(d[1]), "+f"(d[2]), "+f"(d[3]), "+f"(d[4]), "+f"(d[5]), "+f"(d[6]), "+f"(d[7]), "+f"(d[8]), "+f"(d[9]), "+f"(d[10]), "+f"(d[11]), "+f"(d[12]), "+f"(d[13]), "+f"(d[14]), "+f"(d[15]), "+f"(d[16]), "+f"(d[17]), "+f"(d[18]), "+f"(d[19]), "+f"(d[20]), "+f"(d[21]), "+f"(d[22]), "+f"(d[23]), "+f"(d[24]), "+f"(d[25]), "+f"(d[26]), "+f"(d[27]), "+f"(d[28]), "+f"(d[29]), "+f"(d[30]), "+f"(d[31])
    : "r"(a0), "r"(a1), "r"(a2), "r"(a3), "l"(db), "r"(scale_d), "n"(TB));
}
__device__ __forceinline__ void wgmma_pv_sel(float (&d)[64], const uint32_t (&p)[32], uint64_t db, int full, int acc) {
  asm volatile("{\n.reg .pred q, s;\n.reg .b64 t;\nsetp.ne.b32 s, %98, 0;\nsetp.eq.b32 q, %97, 0;\n@q bra.uni LH;\n"
    "wgmma.fence.sync.aligned;\n"
    "add.s64 t, %96, 0;\nwgmma.mma_async.sync.aligned.m64n128k16.f32.bf16.bf16 {%0, %1, %2, %3, %4, %5, %6, %7, %8, %9, %10, %11, %12, %13, %14, %15, %16, %17, %18, %19, %20, %21, %22, %23, %24, %25, %26, %27, %28, %29, %30, %31, %32, %33, %34, %35, %36, %37, %38, %39, %40, %41, %42, %43, %44, %45, %46, %47, %48, %49, %50, %51, %52, %53, %54, %55, %56, %57, %58, %59, %60, %61, %62, %63}, {%64, %65, %66, %67}, t, s, 1, 1, 1;\n"
    "add.s64 t, %96, 256;\nwgmma.mma_async.sync.aligned.m64n128k16.f32.bf16.bf16 {%0, %1, %2, %3, %4, %5, %6, %7, %8, %9, %10, %11, %12, %13, %14, %15, %16, %17, %18, %19, %20, %21, %22, %23, %24, %25, %26, %27, %28, %29, %30, %31, %32, %33, %34, %35, %36, %37, %38, %39, %40, %41, %42, %43, %44, %45, %46, %47, %48, %49, %50, %51, %52, %53, %54, %55, %56, %57, %58, %59, %60, %61, %62, %63}, {%68, %69, %70, %71}, t, 1, 1, 1, 1;\n"
    "add.s64 t, %96, 512;\nwgmma.mma_async.sync.aligned.m64n128k16.f32.bf16.bf16 {%0, %1, %2, %3, %4, %5, %6, %7, %8, %9, %10, %11, %12, %13, %14, %15, %16, %17, %18, %19, %20, %21, %22, %23, %24, %25, %26, %27, %28, %29, %30, %31, %32, %33, %34, %35, %36, %37, %38, %39, %40, %41, %42, %43, %44, %45, %46, %47, %48, %49, %50, %51, %52, %53, %54, %55, %56, %57, %58, %59, %60, %61, %62, %63}, {%72, %73, %74, %75}, t, 1, 1, 1, 1;\n"
    "add.s64 t, %96, 768;\nwgmma.mma_async.sync.aligned.m64n128k16.f32.bf16.bf16 {%0, %1, %2, %3, %4, %5, %6, %7, %8, %9, %10, %11, %12, %13, %14, %15, %16, %17, %18, %19, %20, %21, %22, %23, %24, %25, %26, %27, %28, %29, %30, %31, %32, %33, %34, %35, %36, %37, %38, %39, %40, %41, %42, %43, %44, %45, %46, %47, %48, %49, %50, %51, %52, %53, %54, %55, %56, %57, %58, %59, %60, %61, %62, %63}, {%76, %77, %78, %79}, t, 1, 1, 1, 1;\n"
    "add.s64 t, %96, 1024;\nwgmma.mma_async.sync.aligned.m64n128k16.f32.bf16.bf16 {%0, %1, %2, %3, %4, %5, %6, %7, %8, %9, %10, %11, %12, %13, %14, %15, %16, %17, %18, %19, %20, %21, %22, %23, %24, %25, %26, %27, %28, %29, %30, %31, %32, %33, %34, %35, %36, %37, %38, %39, %40, %41, %42, %43, %44, %45, %46, %47, %48, %49, %50, %51, %52, %53, %54, %55, %56, %57, %58, %59, %60, %61, %62, %63}, {%80, %81, %82, %83}, t, 1, 1, 1, 1;\n"
    "add.s64 t, %96, 1280;\nwgmma.mma_async.sync.aligned.m64n128k16.f32.bf16.bf16 {%0, %1, %2, %3, %4, %5, %6, %7, %8, %9, %10, %11, %12, %13, %14, %15, %16, %17, %18, %19, %20, %21, %22, %23, %24, %25, %26, %27, %28, %29, %30, %31, %32, %33, %34, %35, %36, %37, %38, %39, %40, %41, %42, %43, %44, %45, %46, %47, %48, %49, %50, %51, %52, %53, %54, %55, %56, %57, %58, %59, %60, %61, %62, %63}, {%84, %85, %86, %87}, t, 1, 1, 1, 1;\n"
    "add.s64 t, %96, 1536;\nwgmma.mma_async.sync.aligned.m64n128k16.f32.bf16.bf16 {%0, %1, %2, %3, %4, %5, %6, %7, %8, %9, %10, %11, %12, %13, %14, %15, %16, %17, %18, %19, %20, %21, %22, %23, %24, %25, %26, %27, %28, %29, %30, %31, %32, %33, %34, %35, %36, %37, %38, %39, %40, %41, %42, %43, %44, %45, %46, %47, %48, %49, %50, %51, %52, %53, %54, %55, %56, %57, %58, %59, %60, %61, %62, %63}, {%88, %89, %90, %91}, t, 1, 1, 1, 1;\n"
    "add.s64 t, %96, 1792;\nwgmma.mma_async.sync.aligned.m64n128k16.f32.bf16.bf16 {%0, %1, %2, %3, %4, %5, %6, %7, %8, %9, %10, %11, %12, %13, %14, %15, %16, %17, %18, %19, %20, %21, %22, %23, %24, %25, %26, %27, %28, %29, %30, %31, %32, %33, %34, %35, %36, %37, %38, %39, %40, %41, %42, %43, %44, %45, %46, %47, %48, %49, %50, %51, %52, %53, %54, %55, %56, %57, %58, %59, %60, %61, %62, %63}, {%92, %93, %94, %95}, t, 1, 1, 1, 1;\n"
    "wgmma.commit_group.sync.aligned;\n"
    "bra.uni LE;\nLH:\n"
    "wgmma.fence.sync.aligned;\n"
    "add.s64 t, %96, 0;\nwgmma.mma_async.sync.aligned.m64n128k16.f32.bf16.bf16 {%0, %1, %2, %3, %4, %5, %6, %7, %8, %9, %10, %11, %12, %13, %14, %15, %16, %17, %18, %19, %20, %21, %22, %23, %24, %25, %26, %27, %28, %29, %30, %31, %32, %33, %34, %35, %36, %37, %38, %39, %40, %41, %42, %43, %44, %45, %46, %47, %48, %49, %50, %51, %52, %53, %54, %55, %56, %57, %58, %59, %60, %61, %62, %63}, {%80, %81, %82, %83}, t, s, 1, 1, 1;\n"
    "add.s64 t, %96, 256;\nwgmma.mma_async.sync.aligned.m64n128k16.f32.bf16.bf16 {%0, %1, %2, %3, %4, %5, %6, %7, %8, %9, %10, %11, %12, %13, %14, %15, %16, %17, %18, %19, %20, %21, %22, %23, %24, %25, %26, %27, %28, %29, %30, %31, %32, %33, %34, %35, %36, %37, %38, %39, %40, %41, %42, %43, %44, %45, %46, %47, %48, %49, %50, %51, %52, %53, %54, %55, %56, %57, %58, %59, %60, %61, %62, %63}, {%84, %85, %86, %87}, t, 1, 1, 1, 1;\n"
    "add.s64 t, %96, 512;\nwgmma.mma_async.sync.aligned.m64n128k16.f32.bf16.bf16 {%0, %1, %2, %3, %4, %5, %6, %7, %8, %9, %10, %11, %12, %13, %14, %15, %16, %17, %18, %19, %20, %21, %22, %23, %24, %25, %26, %27, %28, %29, %30, %31, %32, %33, %34, %35, %36, %37, %38, %39, %40, %41, %42, %43, %44, %45, %46, %47, %48, %49, %50, %51, %52, %53, %54, %55, %56, %57, %58, %59, %60, %61, %62, %63}, {%88, %89, %90, %91}, t, 1, 1, 1, 1;\n"
    "add.s64 t, %96, 768;\nwgmma.mma_async.sync.aligned.m64n128k16.f32.bf16.bf16 {%0, %1, %2, %3, %4, %5, %6, %7, %8, %9, %10, %11, %12, %13, %14, %15, %16, %17, %18, %19, %20, %21, %22, %23, %24, %25, %26, %27, %28, %29, %30, %31, %32, %33, %34, %35, %36, %37, %38, %39, %40, %41, %42, %43, %44, %45, %46, %47, %48, %49, %50, %51, %52, %53, %54, %55, %56, %57, %58, %59, %60, %61, %62, %63}, {%92, %93, %94, %95}, t, 1, 1, 1, 1;\n"
    "wgmma.commit_group.sync.aligned;\n"
    "LE:\n}\n"
    : "+f"(d[0]), "+f"(d[1]), "+f"(d[2]), "+f"(d[3]), "+f"(d[4]), "+f"(d[5]), "+f"(d[6]), "+f"(d[7]), "+f"(d[8]), "+f"(d[9]), "+f"(d[10]), "+f"(d[11]), "+f"(d[12]), "+f"(d[13]), "+f"(d[14]), "+f"(d[15]), "+f"(d[16]), "+f"(d[17]), "+f"(d[18]), "+f"(d[19]), "+f"(d[20]), "+f"(d[21]), "+f"(d[22]), "+f"(d[23]), "+f"(d[24]), "+f"(d[25]), "+f"(d[26]), "+f"(d[27]), "+f"(d[28]), "+f"(d[29]), "+f"(d[30]), "+f"(d[31]), "+f"(d[32]), "+f"(d[33]), "+f"(d[34]), "+f"(d[35]), "+f"(d[36]), "+f"(d[37]), "+f"(d[38]), "+f"(d[39]), "+f"(d[40]), "+f"(d[41]), "+f"(d[42]), "+f"(d[43]), "+f"(d[44]), "+f"(d[45]), "+f"(d[46]), "+f"(d[47]), "+f"(d[48]), "+f"(d[49]), "+f"(d[50]), "+f"(d[51]), "+f"(d[52]), "+f"(d[53]), "+f"(d[54]), "+f"(d[55]), "+f"(d[56]), "+f"(d[57]), "+f"(d[58]), "+f"(d[59]), "+f"(d[60]), "+f"(d[61]), "+f"(d[62]), "+f"(d[63])
    : "r"(p[0]), "r"(p[1]), "r"(p[2]), "r"(p[3]), "r"(p[4]), "r"(p[5]), "r"(p[6]), "r"(p[7]), "r"(p[8]), "r"(p[9]), "r"(p[10]), "r"(p[11]), "r"(p[12]), "r"(p[13]), "r"(p[14]), "r"(p[15]), "r"(p[16]), "r"(p[17]), "r"(p[18]), "r"(p[19]), "r"(p[20]), "r"(p[21]), "r"(p[22]), "r"(p[23]), "r"(p[24]), "r"(p[25]), "r"(p[26]), "r"(p[27]), "r"(p[28]), "r"(p[29]), "r"(p[30]), "r"(p[31]), "l"(db), "r"(full), "r"(acc) : "memory");
}

constexpr int NCTA = 132, NREG = 128;
constexpr int UNIT = 16384, NUNIT = 14;
constexpr uint32_t SMEM_BASE = 1024;
constexpr int SM_BAR = NUNIT * UNIT;
constexpr int SM_GATE = SM_BAR + 1024;
constexpr int SMEM_BYTES = SM_BAR + 1536;
constexpr int UPITCH = 4160, UCH = 2 * UPITCH;
constexpr float QSCALE = 0.08838834764831845f * 1.4426950408889634f;
constexpr float BOUND2 = 48.f * 48.f / 1.15f;
#define CONV_REG 6
constexpr int CONV_EXTRA = (1024 - NREG * CONV_REG) / (NCTA - NREG);
constexpr int CH_EXTRA_TOTAL = CONV_EXTRA * (NCTA - NREG);
constexpr int C_KV = 0;
constexpr int C_CTX = 32;
constexpr int C_U = 48;
constexpr int C_Z = 80;
constexpr int C_GATE = 88;
constexpr int C_EXIT = 89;
[[maybe_unused]] constexpr int C_GO = 90;
#define PRE_EARLY 1
#define PRE_HALF 1
#define EF 127
#define POL(bit) (((EF >> (bit)) & 1) != 0)
#define GO_AT 33
constexpr int C_WAR = 96;
constexpr int C_NUM = 112;
constexpr int CSTRIDE = 32;
constexpr int SM_KMAX = SM_BAR + 256, SM_DUMMY = SM_BAR + 264, SM_EXIT = SM_BAR + 272, SM_PRE = SM_BAR + 280, SM_SIG = SM_BAR + 320, SM_RDY = SM_BAR + 448;
enum { SIG_KV = 0, SIG_CTX = 2, SIG_Z = 4, SIG_GO = 8, SIG_WAR = 9, SIG_ATT = 10 };
enum { RDY_KV = 0, RDY_CTX = 2, RDY_U = 4, RDY_Z = 5, RDY_WAR = 6, RDY_G = 7 };
enum { PH_PRE = 1, PH_KV = 2, PH_ATT = 4, PH_CONV = 8, PH_OUT = 16, PH_ALL = 31 };

constexpr uint32_t T_CTX = 0, T_KV = 16 * 32 * 32768, T_BYTES = T_KV + 32 * 16 * 65536;
__device__ __align__(1024) uint8_t g_T[T_BYTES];
__device__ __align__(1024) uint8_t g_u[1024 * UCH];
__device__ __align__(1024) __nv_bfloat16 g_z[1024 * 2048];
__device__ __align__(1024) float g_gate[2048];
__device__ __align__(1024) float g_kn2[32 * 128];
__device__ __align__(1024) unsigned g_cnt[C_NUM * CSTRIDE];

struct __align__(64) Maps { CUtensorMap x, c, wq, wk, wv, wo, h, z, out, ctx, k, v; };
struct Params {
  const __nv_bfloat16 *x, *shift, *D, *gw;
};

__device__ __forceinline__ void wg_fence() { asm volatile("wgmma.fence.sync.aligned;" ::: "memory"); }
__device__ __forceinline__ void wg_commit() { asm volatile("wgmma.commit_group.sync.aligned;" ::: "memory"); }
template<int N> __device__ __forceinline__ void wg_wait() { asm volatile("wgmma.wait_group.sync.aligned %0;" :: "n"(N) : "memory"); }
__device__ __forceinline__ uint64_t mkdesc(uint32_t addr, uint32_t lbo, uint32_t sbo, uint32_t swz) {
  return (uint64_t)((addr & 0x3FFFF) >> 4) | ((uint64_t)(lbo >> 4) << 16) | ((uint64_t)(sbo >> 4) << 32) | ((uint64_t)swz << 62);
}
__device__ __forceinline__ void mbar_init(uint32_t bar, int cnt) { asm volatile("mbarrier.init.shared::cta.b64 [%0], %1;" :: "r"(bar), "r"(cnt)); }
__device__ __forceinline__ void mbar_expect(uint32_t bar, uint32_t bytes) { asm volatile("mbarrier.arrive.expect_tx.shared::cta.b64 _, [%0], %1;" :: "r"(bar), "r"(bytes) : "memory"); }
__device__ __forceinline__ void mbar_arrive(uint32_t bar) { asm volatile("mbarrier.arrive.shared::cta.b64 _, [%0];" :: "r"(bar) : "memory"); }
__device__ __forceinline__ void mbar_arrive_n(uint32_t bar, int n) { asm volatile("mbarrier.arrive.shared::cta.b64 _, [%0], %1;" :: "r"(bar), "r"(n) : "memory"); }
__device__ __forceinline__ void mbar_wait(uint32_t bar, uint32_t parity) {
  asm volatile("{\n.reg .pred p;\n.reg .u32 n;\nmov.u32 n, 0;\n"
    "LW:\nmbarrier.try_wait.parity.shared::cta.b64 p, [%0], %1;\n@p bra LD;\n"
    "add.u32 n, n, 1;\nsetp.lt.u32 p, n, 2097152;\n@p bra LW;\ntrap;\nLD:\n}\n" :: "r"(bar), "r"(parity) : "memory");
}
__device__ __forceinline__ void mbar_wait_slow(uint32_t bar, uint32_t parity) {
  asm volatile("{\n.reg .pred p;\n.reg .u32 n;\nmov.u32 n, 0;\n"
    "LW:\nmbarrier.test_wait.parity.shared::cta.b64 p, [%0], %1;\n@p bra LD;\n"
    "nanosleep.u32 128;\nadd.u32 n, n, 1;\nsetp.lt.u32 p, n, 4194304;\n@p bra LW;\ntrap;\nLD:\n}\n" :: "r"(bar), "r"(parity) : "memory");
}
__device__ __forceinline__ void mbar_wait_all(uint32_t bar, uint32_t parity) {
  asm volatile("{\n.reg .pred p, q;\n.reg .u32 n;\nmov.u32 n, 0;\n"
    "LW:\nmbarrier.try_wait.parity.shared::cta.b64 p, [%0], %1;\nvote.sync.all.pred q, p, 0xffffffff;\n@q bra.uni LD;\n"
    "add.u32 n, n, 1;\nsetp.lt.u32 q, n, 2097152;\n@q bra.uni LW;\ntrap;\nLD:\n}\n" :: "r"(bar), "r"(parity) : "memory");
}
__device__ __forceinline__ void cnt_wait(const unsigned* p, unsigned target) {
  asm volatile("{\n.reg .pred p;\n.reg .u32 n, v;\nmov.u32 n, 0;\n"
    "LW:\nld.relaxed.gpu.global.u32 v, [%0];\nsetp.ge.u32 p, v, %1;\n@p bra LD;\n"
    "nanosleep.u32 64;\nadd.u32 n, n, 1;\nsetp.lt.u32 p, n, 4194304;\n@p bra LW;\ntrap;\nLD:\nfence.acq_rel.gpu;\nfence.proxy.async;\n}\n" :: "l"(p), "r"(target) : "memory");
}
__device__ __forceinline__ void cnt_poll(const unsigned* p, unsigned target) {
  asm volatile("{\n.reg .pred p;\n.reg .u32 n, v;\nmov.u32 n, 0;\n"
    "LW:\nld.relaxed.gpu.global.u32 v, [%0];\nsetp.ge.u32 p, v, %1;\n@p bra LD;\n"
    "add.u32 n, n, 1;\nsetp.lt.u32 p, n, 4194304;\n@p bra LW;\ntrap;\nLD:\n}\n" :: "l"(p), "r"(target) : "memory");
}
__device__ __forceinline__ void cnt_signal(unsigned* p, int lane) {
  __syncwarp();
  if (lane == 0) asm volatile("red.release.gpu.global.add.u32 [%0], 1;" :: "l"(p) : "memory");
}
__device__ __forceinline__ void cnt_publish(unsigned* p, unsigned n) {
  asm volatile("fence.acq_rel.gpu;\nred.relaxed.gpu.global.add.u32 [%0], %1;" :: "l"(p), "r"(n) : "memory");
}
__device__ __forceinline__ uint64_t pol_first() { uint64_t p; asm("createpolicy.fractional.L2::evict_first.b64 %0, 1.0;" : "=l"(p)); return p; }
__device__ __forceinline__ void bulk_g2s(uint32_t dst, const void* src, uint32_t bytes, uint32_t bar, bool stream = false) {
  if (stream) asm volatile("cp.async.bulk.shared::cluster.global.mbarrier::complete_tx::bytes.L2::cache_hint [%0], [%1], %2, [%3], %4;" :: "r"(dst), "l"(src), "r"(bytes), "r"(bar), "l"(pol_first()) : "memory");
  else asm volatile("cp.async.bulk.shared::cluster.global.mbarrier::complete_tx::bytes [%0], [%1], %2, [%3];" :: "r"(dst), "l"(src), "r"(bytes), "r"(bar) : "memory");
}
__device__ __forceinline__ void tma2d(uint32_t dst, const CUtensorMap* m, int x, int y, uint32_t bar, bool stream = false) {
  if (stream) asm volatile("cp.async.bulk.tensor.2d.shared::cluster.global.mbarrier::complete_tx::bytes.L2::cache_hint [%0], [%1, {%3, %4}], [%2], %5;" :: "r"(dst), "l"(m), "r"(bar), "r"(x), "r"(y), "l"(pol_first()) : "memory");
  else asm volatile("cp.async.bulk.tensor.2d.shared::cluster.global.mbarrier::complete_tx::bytes [%0], [%1, {%3, %4}], [%2];" :: "r"(dst), "l"(m), "r"(bar), "r"(x), "r"(y) : "memory");
}
__device__ __forceinline__ void tma3d(uint32_t dst, const CUtensorMap* m, int x, int y, int z, uint32_t bar, bool stream = false) {
  if (stream) asm volatile("cp.async.bulk.tensor.3d.shared::cluster.global.mbarrier::complete_tx::bytes.L2::cache_hint [%0], [%1, {%3, %4, %5}], [%2], %6;" :: "r"(dst), "l"(m), "r"(bar), "r"(x), "r"(y), "r"(z), "l"(pol_first()) : "memory");
  else asm volatile("cp.async.bulk.tensor.3d.shared::cluster.global.mbarrier::complete_tx::bytes [%0], [%1, {%3, %4, %5}], [%2];" :: "r"(dst), "l"(m), "r"(bar), "r"(x), "r"(y), "r"(z) : "memory");
}
__device__ __forceinline__ void tma4d(uint32_t dst, const CUtensorMap* m, int x, int y, int z, int w, uint32_t bar, bool stream = false) {
  if (stream) asm volatile("cp.async.bulk.tensor.4d.shared::cluster.global.mbarrier::complete_tx::bytes.L2::cache_hint [%0], [%1, {%3, %4, %5, %6}], [%2], %7;" :: "r"(dst), "l"(m), "r"(bar), "r"(x), "r"(y), "r"(z), "r"(w), "l"(pol_first()) : "memory");
  else asm volatile("cp.async.bulk.tensor.4d.shared::cluster.global.mbarrier::complete_tx::bytes [%0], [%1, {%3, %4, %5, %6}], [%2];" :: "r"(dst), "l"(m), "r"(bar), "r"(x), "r"(y), "r"(z), "r"(w) : "memory");
}
__device__ __forceinline__ void bulk_g2s_mc(uint32_t dst, const void* src, uint32_t bytes, uint32_t bar, bool stream = false) {
  if (stream) asm volatile("cp.async.bulk.shared::cluster.global.mbarrier::complete_tx::bytes.multicast::cluster.L2::cache_hint [%0], [%1], %2, [%3], %4, %5;" :: "r"(dst), "l"(src), "r"(bytes), "r"(bar), "h"((uint16_t)3), "l"(pol_first()) : "memory");
  else asm volatile("cp.async.bulk.shared::cluster.global.mbarrier::complete_tx::bytes.multicast::cluster [%0], [%1], %2, [%3], %4;" :: "r"(dst), "l"(src), "r"(bytes), "r"(bar), "h"((uint16_t)3) : "memory");
}
__device__ __forceinline__ void tma2d_mc(uint32_t dst, const CUtensorMap* m, int x, int y, uint32_t bar, bool stream = false) {
  if (stream) asm volatile("cp.async.bulk.tensor.2d.shared::cluster.global.mbarrier::complete_tx::bytes.multicast::cluster.L2::cache_hint [%0], [%1, {%3, %4}], [%2], %5, %6;" :: "r"(dst), "l"(m), "r"(bar), "r"(x), "r"(y), "h"((uint16_t)3), "l"(pol_first()) : "memory");
  else asm volatile("cp.async.bulk.tensor.2d.shared::cluster.global.mbarrier::complete_tx::bytes.multicast::cluster [%0], [%1, {%3, %4}], [%2], %5;" :: "r"(dst), "l"(m), "r"(bar), "r"(x), "r"(y), "h"((uint16_t)3) : "memory");
}
__device__ __forceinline__ void tma3d_mc(uint32_t dst, const CUtensorMap* m, int x, int y, int z, uint32_t bar, bool stream = false) {
  if (stream) asm volatile("cp.async.bulk.tensor.3d.shared::cluster.global.mbarrier::complete_tx::bytes.multicast::cluster.L2::cache_hint [%0], [%1, {%3, %4, %5}], [%2], %6, %7;" :: "r"(dst), "l"(m), "r"(bar), "r"(x), "r"(y), "r"(z), "h"((uint16_t)3), "l"(pol_first()) : "memory");
  else asm volatile("cp.async.bulk.tensor.3d.shared::cluster.global.mbarrier::complete_tx::bytes.multicast::cluster [%0], [%1, {%3, %4, %5}], [%2], %6;" :: "r"(dst), "l"(m), "r"(bar), "r"(x), "r"(y), "r"(z), "h"((uint16_t)3) : "memory");
}
__device__ __forceinline__ void tma2d_store(const CUtensorMap* m, uint32_t src, int x, int y) {
  asm volatile("cp.async.bulk.tensor.2d.global.shared::cta.bulk_group [%0, {%2, %3}], [%1];" :: "l"(m), "r"(src), "r"(x), "r"(y) : "memory");
}
__device__ __forceinline__ bool elect() {
  uint32_t r; asm volatile("{\n.reg .pred p;\nelect.sync _|p, 0xffffffff;\nselp.u32 %0, 1, 0, p;\n}\n" : "=r"(r)); return r != 0;
}
__device__ __forceinline__ void cluster_arrive() { asm volatile("barrier.cluster.arrive;" ::: "memory"); }
__device__ __forceinline__ void cluster_wait() { asm volatile("barrier.cluster.wait;" ::: "memory"); }
__device__ __forceinline__ void bar_sync(int id, int n) { asm volatile("bar.sync %0, %1;" :: "r"(id), "r"(n) : "memory"); }
__device__ __forceinline__ void bar_arrive(int id, int n) { asm volatile("bar.arrive %0, %1;" :: "r"(id), "r"(n) : "memory"); }
__device__ __forceinline__ int bar_and(int id, int n, int pred) {
  int r; asm volatile("{\n.reg .pred p, q;\nsetp.ne.b32 p, %3, 0;\nbar.red.and.pred q, %1, %2, p;\nselp.b32 %0, 1, 0, q;\n}\n" : "=r"(r) : "r"(id), "r"(n), "r"(pred) : "memory");
  return r;
}
__device__ __forceinline__ void fence_async_smem() { asm volatile("fence.proxy.async.shared::cta;" ::: "memory"); }
__device__ __forceinline__ float ex2(float x) { float y; asm("ex2.approx.ftz.f32 %0, %1;" : "=f"(y) : "f"(x)); return y; }
__device__ __forceinline__ uint32_t pack_bf16(float lo, float hi) { uint32_t r; asm("cvt.rn.bf16x2.f32 %0, %1, %2;" : "=r"(r) : "f"(hi), "f"(lo)); return r; }
__device__ __forceinline__ uint32_t hmul2(uint32_t a, uint32_t b) { uint32_t r; asm("mul.rn.bf16x2 %0, %1, %2;" : "=r"(r) : "r"(a), "r"(b)); return r; }
__device__ __forceinline__ uint32_t hadd2(uint32_t a, uint32_t b) { uint32_t r; asm("add.rn.bf16x2 %0, %1, %2;" : "=r"(r) : "r"(a), "r"(b)); return r; }
__device__ __forceinline__ uint32_t hfma2(uint32_t a, uint32_t b, uint32_t c) { uint32_t r; asm("fma.rn.bf16x2 %0, %1, %2, %3;" : "=r"(r) : "r"(a), "r"(b), "r"(c)); return r; }
__device__ __forceinline__ float bf_lo(uint32_t a) { return __uint_as_float(a << 16); }
__device__ __forceinline__ float bf_hi(uint32_t a) { return __uint_as_float(a & 0xffff0000u); }
__device__ __forceinline__ uint32_t lds32(uint32_t a) { uint32_t v; asm volatile("ld.shared.u32 %0, [%1];" : "=r"(v) : "r"(a) : "memory"); return v; }
__device__ __forceinline__ float2 lds64f(uint32_t a) { float2 v; asm volatile("ld.shared.v2.f32 {%0,%1}, [%2];" : "=f"(v.x), "=f"(v.y) : "r"(a) : "memory"); return v; }
__device__ __forceinline__ uint4 lds128(uint32_t a) { uint4 v; asm volatile("ld.shared.v4.u32 {%0,%1,%2,%3}, [%4];" : "=r"(v.x), "=r"(v.y), "=r"(v.z), "=r"(v.w) : "r"(a) : "memory"); return v; }
__device__ __forceinline__ void sts64f(uint32_t a, float x, float y) { asm volatile("st.shared.v2.f32 [%0], {%1,%2};" :: "r"(a), "f"(x), "f"(y) : "memory"); }
__device__ __forceinline__ void sts128(uint32_t a, uint4 v) { asm volatile("st.shared.v4.u32 [%0], {%1,%2,%3,%4};" :: "r"(a), "r"(v.x), "r"(v.y), "r"(v.z), "r"(v.w) : "memory"); }
template<int OFF> __device__ __forceinline__ void sts128o(uint32_t a, uint4 v) { asm volatile("st.shared.v4.u32 [%0+%5], {%1,%2,%3,%4};" :: "r"(a), "r"(v.x), "r"(v.y), "r"(v.z), "r"(v.w), "n"(OFF) : "memory"); }
__device__ __forceinline__ void ldsm4(uint32_t a, uint32_t& r0, uint32_t& r1, uint32_t& r2, uint32_t& r3) {
  asm volatile("ldmatrix.sync.aligned.m8n8.x4.shared.b16 {%0,%1,%2,%3}, [%4];" : "=r"(r0), "=r"(r1), "=r"(r2), "=r"(r3) : "r"(a) : "memory");
}
__device__ __forceinline__ void ldsm4t(uint32_t a, uint32_t& r0, uint32_t& r1, uint32_t& r2, uint32_t& r3) {
  asm volatile("ldmatrix.sync.aligned.m8n8.x4.trans.shared.b16 {%0,%1,%2,%3}, [%4];" : "=r"(r0), "=r"(r1), "=r"(r2), "=r"(r3) : "r"(a) : "memory");
}
__device__ __forceinline__ void stsm4(uint32_t a, uint32_t r0, uint32_t r1, uint32_t r2, uint32_t r3) {
  asm volatile("stmatrix.sync.aligned.m8n8.x4.shared.b16 [%0], {%1,%2,%3,%4};" :: "r"(a), "r"(r0), "r"(r1), "r"(r2), "r"(r3) : "memory");
}
template<int N> __device__ __forceinline__ void fence_regs(float (&d)[N]) {
#pragma unroll
  for (int i = 0; i < N; i++) asm volatile("" : "+f"(d[i]) :: "memory");
}
template<int N> __device__ __forceinline__ void fence_regs(uint32_t (&d)[N]) {
#pragma unroll
  for (int i = 0; i < N; i++) asm volatile("" : "+r"(d[i]) :: "memory");
}
__device__ __forceinline__ void sched_fence(float x, uint32_t dummy) {
  asm volatile("{\n.reg .pred p;\nsetp.eq.u32 p, %0, 0x7fc12345;\n@p st.shared.u32 [%1], %0;\n}\n" :: "r"(__float_as_uint(x)), "r"(dummy) : "memory");
}
#define TS(role, i)
#define TSA(i)
#define TR(obj, role, tag)

struct Prod {
  uint32_t base, mask; int lane, nt;
  __device__ __forceinline__ uint32_t full(int u) const { return base + SM_BAR + 8 * u; }
  __device__ __forceinline__ uint32_t addr(int u) const { return base + u * UNIT; }
  __device__ __forceinline__ void acquire(int u, int n) {
    const int v = u + min(lane, n - 1);
    mbar_wait_all(base + SM_BAR + 128 + 8 * v, (mask >> v) & 1);
    mask ^= ((1u << n) - 1) << u;
    TR(*this, 2, 16 + u);
  }
  __device__ __forceinline__ void acquire_slow(int u, int n) {
    for (int i = 0; i < n; i++) mbar_wait_slow(base + SM_BAR + 128 + 8 * (u + i), (mask >> (u + i)) & 1);
    mask ^= ((1u << n) - 1) << u;
  }
};
struct Cons {
  uint32_t base, rel, mask; int lane, warp, wg, nt;
  __device__ __forceinline__ uint32_t addr(int u) const { return base + u * UNIT; }
  __device__ __forceinline__ static uint32_t daddr(int u) { return SMEM_BASE + u * UNIT; }
  __device__ __forceinline__ void wait(int u) { TR(*this, wg, 1); mbar_wait(base + SM_BAR + 8 * u, (mask >> u) & 1); mask ^= 1u << u; TR(*this, wg, 2); }
  __device__ __forceinline__ void wait2(int u0, int u1) {
    TR(*this, wg, 1);
    const int v = (lane & 1) ? u1 : u0;
    mbar_wait_all(base + SM_BAR + 8 * v, (mask >> v) & 1); mask ^= (1u << u0) | (1u << u1);
    TR(*this, wg, 2);
  }
  __device__ __forceinline__ void skip(int u) { mask ^= 1u << u; }
  __device__ __forceinline__ void release(int u, int n) { TR(*this, wg, 5); if ((lane & 15) < n) asm volatile("mbarrier.arrive.shared::cluster.b64 _, [%0];" :: "r"(rel + 8 * u) : "memory"); }
  __device__ __forceinline__ void release2(int u) { if ((lane & 15) == 0) asm volatile("mbarrier.arrive.shared::cluster.b64 _, [%0], 2;" :: "r"(rel + 8 * u) : "memory"); }
  __device__ __forceinline__ void signal(int i) { __syncwarp(); if (lane == 0) mbar_arrive(base + SM_SIG + 8 * i); }
  __device__ __forceinline__ void turn() { bar_sync(1 + wg, 256); TR(*this, wg, 3); }
  __device__ __forceinline__ void pass() { bar_arrive(2 - wg, 256); TR(*this, wg, 4); }
};
__device__ __forceinline__ int gemm_unit(int ks) { return 3 * (ks & 3); }
__device__ __forceinline__ int att_slot(int i) { return 4 + 2 * i; }
template<int MASK> __device__ __forceinline__ int kv_slot(int h) { return MASK == PH_ALL ? h & 15 : h; }
__device__ __forceinline__ int out_mb(int cta) { return cta >> 3; }
__device__ __forceinline__ int out_nb(int cta) { return cta & 7; }
__device__ __forceinline__ int conv_channel(int cta, int i) {
  return cta < NREG ? CH_EXTRA_TOTAL + cta * CONV_REG + i : (i >> 1) * 8 + (cta - NREG) * 2 + (i & 1);
}

template<int OFF, int N> __device__ __forceinline__ void pack_chunk(const float (&a)[N], float sc0, float sc1, uint4& v0, uint4& v1) {
  v0.x = pack_bf16(a[OFF + 0] * sc0, a[OFF + 1] * sc0); v0.y = pack_bf16(a[OFF + 4] * sc0, a[OFF + 5] * sc0);
  v0.z = pack_bf16(a[OFF + 8] * sc0, a[OFF + 9] * sc0); v0.w = pack_bf16(a[OFF + 12] * sc0, a[OFF + 13] * sc0);
  v1.x = pack_bf16(a[OFF + 2] * sc1, a[OFF + 3] * sc1); v1.y = pack_bf16(a[OFF + 6] * sc1, a[OFF + 7] * sc1);
  v1.z = pack_bf16(a[OFF + 10] * sc1, a[OFF + 11] * sc1); v1.w = pack_bf16(a[OFF + 14] * sc1, a[OFF + 15] * sc1);
}
template<int OFF, int N> __device__ __forceinline__ void pack_chunk(const float (&a)[N], uint4& v0, uint4& v1) {
  v0.x = pack_bf16(a[OFF + 0], a[OFF + 1]); v0.y = pack_bf16(a[OFF + 4], a[OFF + 5]);
  v0.z = pack_bf16(a[OFF + 8], a[OFF + 9]); v0.w = pack_bf16(a[OFF + 12], a[OFF + 13]);
  v1.x = pack_bf16(a[OFF + 2], a[OFF + 3]); v1.y = pack_bf16(a[OFF + 6], a[OFF + 7]);
  v1.z = pack_bf16(a[OFF + 10], a[OFF + 11]); v1.w = pack_bf16(a[OFF + 14], a[OFF + 15]);
}
__device__ __forceinline__ void sq_acc(const uint4& v, uint32_t& a) { a = hfma2(v.x, v.x, a); a = hfma2(v.y, v.y, a); a = hfma2(v.z, v.z, a); a = hfma2(v.w, v.w, a); }
__device__ __forceinline__ float norm2_max(uint32_t a0, uint32_t a1) {
  float n0 = bf_lo(a0) + bf_hi(a0), n1 = bf_lo(a1) + bf_hi(a1);
  n0 += __shfl_xor_sync(~0u, n0, 1); n1 += __shfl_xor_sync(~0u, n1, 1);
  n0 += __shfl_xor_sync(~0u, n0, 2); n1 += __shfl_xor_sync(~0u, n1, 2);
  return __uint_as_float(__reduce_max_sync(~0u, max(__float_as_uint(n0) & 0x7fffffffu, __float_as_uint(n1) & 0x7fffffffu)));
}

struct Pend { uint4 lo[8], hi[8]; uint32_t dst; float kn; };
__device__ __forceinline__ void pin(uint4 (&v)[8]) {
#pragma unroll
  for (int i = 0; i < 8; i++) asm volatile("" : "+r"(v[i].x), "+r"(v[i].y), "+r"(v[i].z), "+r"(v[i].w) :: "memory");
}
__device__ __forceinline__ uint32_t atom_off(int lane) { return (lane >> 2) * 64 + (((lane ^ (lane >> 3)) & 3) << 4); }
template<int J0, int J1> __device__ __forceinline__ void tile_store(const uint4 (&v)[8], uint32_t dst, int lane) {
  uint8_t* d = g_T + (dst + atom_off(lane));
#pragma unroll
  for (int j = J0; j < J1; j++) { *(uint4*)(d + j * 512) = v[2 * j]; *(uint4*)(d + j * 512 + 2048) = v[2 * j + 1]; }
}
__device__ __forceinline__ float tile_norm2(const uint4 (&v)[8]) {
  uint32_t n0 = 0, n1 = 0;
#pragma unroll
  for (int j = 0; j < 4; j++) { sq_acc(v[2 * j], n0); sq_acc(v[2 * j + 1], n1); }
  return norm2_max(n0, n1);
}
template<int PART> __device__ __forceinline__ void out_part(Cons& c, Pend& w) {
  if (PART == 0) { w.kn = tile_norm2(w.lo); tile_store<0, 2>(w.lo, w.dst, c.lane); }
  if (PART == 1) tile_store<2, 4>(w.lo, w.dst, c.lane);
  if (PART == 2) {
    const float vn = tile_norm2(w.hi);
    if (c.lane == 0) g_kn2[((w.dst - T_KV) >> 16) * 8 + c.wg * 4 + c.warp] = (vn <= 1.0e30f && vn >= 1.0e-30f) ? w.kn : __uint_as_float(0x7f800000u);
    tile_store<0, 2>(w.hi, w.dst + 32768, c.lane);
  }
  if (PART == 3) tile_store<2, 4>(w.hi, w.dst + 32768, c.lane);
}
template<bool FIRST> __device__ __forceinline__ void kv_issue(Cons& c, float (&acc)[128], int u) {
  const uint64_t da = mkdesc(c.daddr(u) + c.wg * 8192, 16, 1024, 1), db = mkdesc(c.daddr(u + 1), 8192, 1024, 1);
  c.turn();
  wg_fence();
#pragma unroll
  for (int kk = 0; kk < 4; kk++) wgmma_ss_n256<1>(acc, da + kk * 2, db + kk * 128, !(FIRST && kk == 0));
  wg_commit();
  c.pass();
}
__device__ __forceinline__ void cons_kv(Cons& c, int h, int hs, int g, Pend& w, bool pend_o) {
#pragma unroll 1
  for (int tile = 0; tile < 2; tile++) {
    float acc[128];
    c.wait(0);
    kv_issue<true>(c, acc, 0);
    if (tile == 1 && pend_o) mbar_wait(c.base + SM_RDY + 8 * RDY_WAR, 0);
    if (tile == 1 || pend_o) out_part<0>(c, w);
#pragma unroll 1
    for (int ks = 1; ks < 8; ks++) {
      if (ks == 3 && (tile == 1 || pend_o)) { out_part<1>(c, w); if (tile == 0) c.signal(SIG_CTX); }
      if (ks == 5 && tile == 1) out_part<2>(c, w);
      if (ks == 7 && tile == 1) out_part<3>(c, w);
      const int u = gemm_unit(ks);
      c.wait(u);
      wg_wait<0>();
      c.release(gemm_unit(ks - 1), 3);
      kv_issue<false>(c, acc, u);
    }
    wg_wait<0>(); fence_regs(acc);
    c.release(9, 3);
    pack_chunk<0>(acc, w.lo[0], w.lo[1]);  pack_chunk<16>(acc, w.lo[2], w.lo[3]); pack_chunk<32>(acc, w.lo[4], w.lo[5]); pack_chunk<48>(acc, w.lo[6], w.lo[7]);
    pack_chunk<64>(acc, w.hi[0], w.hi[1]); pack_chunk<80>(acc, w.hi[2], w.hi[3]); pack_chunk<96>(acc, w.hi[4], w.hi[5]); pack_chunk<112>(acc, w.hi[6], w.hi[7]);
    pin(w.lo); pin(w.hi);
    w.dst = T_KV + (hs * 16 + 2 * g + tile) * 65536 + (c.wg * 4 + c.warp) * 4096;
  }
}
template<bool FIRST> __device__ __forceinline__ void q_issue(Cons& c, float (&a)[64], float (&b)[64], int u) {
  const uint64_t da = mkdesc(c.daddr(u) + c.wg * 8192, 16, 1024, 1), db = mkdesc(c.daddr(u + 2), 8192, 1024, 1);
  const uint64_t da2 = mkdesc(c.daddr(u + 1) + (1 - c.wg) * 8192, 16, 1024, 1);
  c.turn();
  wg_fence();
#pragma unroll
  for (int kk = 0; kk < 4; kk++) wgmma_ss_n128<1>(a, da + kk * 2, db + kk * 128, !(FIRST && kk == 0));
#pragma unroll
  for (int kk = 0; kk < 4; kk++) wgmma_ss_n128<1>(b, da2 + kk * 2, db + kk * 128, !(FIRST && kk == 0));
  wg_commit();
  c.pass();
}
template<bool PEND_KV> __device__ __forceinline__ int cons_q(Cons& c, int h, Pend& w) {
  float a[64], b[64];
  c.wait(0);
  q_issue<true>(c, a, b, 0);
  if (PEND_KV) out_part<0>(c, w);
#pragma unroll 1
  for (int ks = 1; ks < 16; ks++) {
    if (PEND_KV) {
      if (ks == 2) out_part<1>(c, w);
      if (ks == 4) out_part<2>(c, w);
      if (ks == 5) { out_part<3>(c, w); c.signal(SIG_KV + (h >> 4)); }
    }
    const int u = gemm_unit(ks);
    c.wait(u);
    wg_wait<0>();
    c.release(gemm_unit(ks - 1), 3);
    q_issue<false>(c, a, b, u);
  }
  c.wait(0);
  wg_wait<0>(); fence_regs(a); fence_regs(b);
  c.release(9, 3);
  const uint32_t q0 = c.addr(0) + (c.wg * 4 + c.warp) * 4096 + atom_off(c.lane);
  uint32_t a0 = 0, a1 = 0, e0 = 0, e1 = 0;
  uint4 v0, v1;
#define Q_CHUNK(J) pack_chunk<16 * J>(a, QSCALE, QSCALE, v0, v1); sts128o<J * 512>(q0, v0); sts128o<J * 512 + 2048>(q0, v1); sq_acc(v0, a0); sq_acc(v1, a1); \
  pack_chunk<16 * J>(b, QSCALE, QSCALE, v0, v1); sts128o<32768 + J * 512>(q0, v0); sts128o<32768 + J * 512 + 2048>(q0, v1); sq_acc(v0, e0); sq_acc(v1, e1);
  Q_CHUNK(0) Q_CHUNK(1) Q_CHUNK(2) Q_CHUNK(3)
#undef Q_CHUNK
  TR(c, c.wg, 40);
  fence_async_smem();
  const float qa = norm2_max(a0, a1), qb = norm2_max(e0, e1);
  const float kn = __uint_as_float(lds32(c.base + SM_KMAX + 4 * (h >> 4)));
  TR(c, c.wg, 42);
  return __shfl_sync(~0u, bar_and(3 + c.wg, 128, (qa * kn <= BOUND2) && (qb * kn <= BOUND2)), 0);
}

__device__ __forceinline__ void issue_qk(float (&s)[64], uint32_t qaddr, uint32_t kaddr) {
  const uint64_t da = mkdesc(qaddr, 16, 2048, 2), db = mkdesc(kaddr, 16, 2048, 2);
#pragma unroll
  for (int kk = 0; kk < 8; kk++) wgmma_ss_n128<0>(s, da + (kk >> 1) * 32 + (kk & 1) * 2, db + (kk >> 1) * 32 + (kk & 1) * 2, kk > 0);
  wg_commit();
}
template<bool FRESH, int NK> __device__ __forceinline__ void issue_pv_n(float (&o)[64], uint32_t (&p)[32], uint32_t vaddr) {
  const uint64_t db = mkdesc(vaddr, 512, 2048, 2);
#pragma unroll
  for (int kk = 0; kk < NK; kk++) wgmma_rs_n128<1>(o, p[4 * kk], p[4 * kk + 1], p[4 * kk + 2], p[4 * kk + 3], db + kk * 256, !(FRESH && kk == 0));
  wg_commit();
}
template<bool FRESH> __device__ __forceinline__ void issue_pv(float (&o)[64], uint32_t (&p)[32], uint32_t vaddr, bool full) {
  wgmma_pv_sel(o, p, mkdesc(vaddr, 512, 2048, 2), full, FRESH ? gridDim.y - 1 : 1);
}
template<int A, int B> __device__ __forceinline__ void exp_rng(float (&s)[64]) {
#pragma unroll
  for (int i = 4 * A; i < 4 * B; i++) s[i] = ex2(s[i]);
}
template<int A, int B> __device__ __forceinline__ void sum_rng(const float (&s)[64], float (&l)[4]) {
#pragma unroll
  for (int i = A; i < B; i++) { l[0] += s[4 * i]; l[1] += s[4 * i + 1]; l[2] += s[4 * i + 2]; l[3] += s[4 * i + 3]; }
}
template<int A, int B> __device__ __forceinline__ void cvt_p(const float (&s)[64], uint32_t (&p)[32]) {
#pragma unroll
  for (int i = 2 * A; i < 2 * B; i++) p[i] = pack_bf16(s[2 * i], s[2 * i + 1]);
}
template<int K0> __device__ __forceinline__ void mask_half(float (&s)[64], int warp, int lane) {
  const int l0 = warp + (2 * (lane & 3) <= (lane >> 2)), l1 = warp + (2 * (lane & 3) < (lane >> 2));
#pragma unroll
  for (int k = 0; k < 4; k++) {
    float* t = s + 8 * (K0 + k);
    if (k >= l0) { t[0] = -INFINITY; t[6] = -INFINITY; }
    if (k >= l1) { t[1] = -INFINITY; t[7] = -INFINITY; }
    if (k > warp) { t[2] = -INFINITY; t[3] = -INFINITY; }
    if (k >= warp) { t[4] = -INFINITY; t[5] = -INFINITY; }
  }
}
__device__ __forceinline__ void mask_diag(float (&s)[64], int lim) {
#pragma unroll
  for (int i = 0; i < 16; i++) {
    if (8 * i > lim) s[4 * i] = -INFINITY;
    if (8 * i + 1 > lim) s[4 * i + 1] = -INFINITY;
    if (8 * i - 8 > lim) s[4 * i + 2] = -INFINITY;
    if (8 * i - 7 > lim) s[4 * i + 3] = -INFINITY;
  }
}
__device__ __forceinline__ void row_inv(float& l0, float& l1) {
  l0 += __shfl_xor_sync(~0u, l0, 1); l1 += __shfl_xor_sync(~0u, l1, 1);
  l0 += __shfl_xor_sync(~0u, l0, 2); l1 += __shfl_xor_sync(~0u, l1, 2);
  l0 = __fdividef(1.f, l0); l1 = __fdividef(1.f, l1);
}
__device__ __forceinline__ void pack_o(const float (&o)[64], float i0, float i1, uint4 (&v)[8]) {
  pack_chunk<0>(o, i0, i1, v[0], v[1]); pack_chunk<16>(o, i0, i1, v[2], v[3]);
  pack_chunk<32>(o, i0, i1, v[4], v[5]); pack_chunk<48>(o, i0, i1, v[6], v[7]);
  pin(v);
}
__device__ __forceinline__ void softmax_safe(float (&s)[64], float& m0, float& m1, float& sc0, float& sc1) {
  float a0 = m0, a1 = m1;
#pragma unroll
  for (int i = 0; i < 16; i++) { a0 = fmaxf(a0, fmaxf(s[4 * i], s[4 * i + 1])); a1 = fmaxf(a1, fmaxf(s[4 * i + 2], s[4 * i + 3])); }
  a0 = fmaxf(a0, __shfl_xor_sync(~0u, a0, 1)); a1 = fmaxf(a1, __shfl_xor_sync(~0u, a1, 1));
  a0 = fmaxf(a0, __shfl_xor_sync(~0u, a0, 2)); a1 = fmaxf(a1, __shfl_xor_sync(~0u, a1, 2));
  sc0 = ex2(m0 - a0); sc1 = ex2(m1 - a1);
  m0 = a0; m1 = a1;
#pragma unroll
  for (int i = 0; i < 16; i++) { s[4 * i] -= a0; s[4 * i + 1] -= a0; s[4 * i + 2] -= a1; s[4 * i + 3] -= a1; }
}
struct Att {
  float s[64], o[64], l[4], i0, i1; uint32_t p[32];
  int si; uint32_t qaddr;
};
__device__ __forceinline__ uint32_t ctx_off(const Cons& c, int h, int qb, int rowhalf) { return T_CTX + (qb * 32 + h) * 32768 + (rowhalf * 4 + c.warp) * 4096; }
template<bool DIAG, bool DRAIN>
__device__ __forceinline__ void att_step(Cons& c, Att& a, bool qkfull, bool pvfull, int relq, uint32_t dst) {
  const int uk = att_slot(a.si); a.si = (a.si + 1) & 3;
  const int uv = att_slot(a.si); a.si = (a.si + 1) & 3;
  if (DRAIN) c.wait(uk); else c.wait2(uk, uv);
  c.turn();
  fence_regs(a.o); fence_regs(a.p);
  if (DIAG) { wg_fence(); issue_qk(a.s, a.qaddr, c.daddr(uk) - (qkfull ? 0 : 16384)); }
  else { wg_fence(); issue_qk(a.s, a.qaddr, c.daddr(uk)); }
  if (DRAIN) {
    c.wait(uv);
    fence_regs(a.o);
    uint4 v[8];
    pack_o(a.o, a.i0, a.i1, v); tile_store<0, 4>(v, dst, c.lane);
  }
  if (DRAIN || DIAG) issue_pv<DRAIN>(a.o, a.p, c.daddr(uv), pvfull); else issue_pv_n<false, 8>(a.o, a.p, c.daddr(uv));
  c.pass();
  wg_wait<1>(); fence_regs(a.s);
  c.release(uk, 2);
  if (relq >= 0) c.release(relq, 2);
  constexpr int SPLIT = DIAG ? 8 : 6;
  if (DIAG) mask_half<4>(a.s, c.warp, c.lane);
  exp_rng<SPLIT, 16>(a.s); sum_rng<SPLIT, 16>(a.s, a.l);
  sched_fence((a.l[0] + a.l[1]) + (a.l[2] + a.l[3]), c.base + SM_DUMMY);
  wg_wait<0>(); fence_regs(a.o); fence_regs(a.p);
  c.release(uv, 2);
  cvt_p<SPLIT, 16>(a.s, a.p);
  if (!DIAG || qkfull) { exp_rng<0, SPLIT>(a.s); sum_rng<0, SPLIT>(a.s, a.l); cvt_p<0, SPLIT>(a.s, a.p); }
}
__device__ __forceinline__ void att_first(Cons& c, Att& a) {
  a.si = 1; a.qaddr = c.daddr(0) + c.wg * 16384;
  c.wait(4);
  c.turn();
  wg_fence();
  issue_qk(a.s, a.qaddr, c.daddr(4));
  c.pass();
#pragma unroll
  for (int i = 0; i < 64; i++) a.o[i] = 0.f;
  a.l[0] = a.l[1] = a.l[2] = a.l[3] = 0.f; a.i0 = a.i1 = 0.f;
  wg_wait<0>(); fence_regs(a.s);
  c.release(4, 2);
}
__device__ __forceinline__ void att_switch(Att& a) {
  a.i0 = a.l[0] + a.l[1]; a.i1 = a.l[2] + a.l[3]; row_inv(a.i0, a.i1);
  a.l[0] = a.l[1] = a.l[2] = a.l[3] = 0.f;
  a.qaddr += 32768;
}
__device__ __forceinline__ void att_drain_now(Cons& c, Att& a, uint32_t dst) {
  uint4 v[8];
  pack_o(a.o, a.i0, a.i1, v); tile_store<0, 4>(v, dst, c.lane);
#pragma unroll
  for (int i = 0; i < 64; i++) a.o[i] = 0.f;
}
__device__ __forceinline__ void att_last(Cons& c, Att& a, Pend& w, bool pvfull, uint32_t dst) {
  const int uv = att_slot(a.si);
  c.wait(uv);
  c.turn();
  fence_regs(a.o); fence_regs(a.p);
  issue_pv<false>(a.o, a.p, c.daddr(uv), pvfull);
  c.pass();
  a.i0 = a.l[0] + a.l[1]; a.i1 = a.l[2] + a.l[3]; row_inv(a.i0, a.i1);
  wg_wait<0>(); fence_regs(a.o); fence_regs(a.p);
  c.release(uv, 2);
  pack_o(a.o, a.i0, a.i1, w.lo);
  w.dst = dst;
}
__device__ __forceinline__ void cons_att_fast(Cons& c, Att& a, int h, int g) {
  exp_rng<0, 16>(a.s); sum_rng<0, 16>(a.s, a.l); cvt_p<0, 16>(a.s, a.p);
#pragma unroll 1
  for (int t = 0; t < 2; t++) {
#pragma unroll 1
    for (int j = t == 0 ? 14 - g : g - 1; j > 0; j--) att_step<false, false>(c, a, true, true, (t == 1 && j == 1) ? 2 : -1, 0);
    if (t == 0) {
#pragma unroll 1
      for (int d = 0; d < 2; d++) {
        att_step<true, false>(c, a, d != c.wg, !(d == 1 && c.wg == 0), d == 0 ? 0 : (g == 0 ? 2 : -1), 0);
        if (d == 0) att_switch(a);
      }
      if (g > 0) att_step<false, true>(c, a, true, c.wg == 0, g == 1 ? 2 : -1, ctx_off(c, h, 15 - g, c.wg));
      else att_drain_now(c, a, ctx_off(c, h, 15, c.wg));
    }
  }
}
__device__ __forceinline__ void cons_att_safe(Cons& c, Att& a, int h, int g) {
  float m0 = -INFINITY, m1 = -INFINITY, sc0, sc1;
#pragma unroll 1
  for (int st = 0; st <= 16; st++) {
    const bool sw = st == 16 - g;
    if (st > 0) {
      if (sw) att_switch(a);
      const int uk = att_slot(a.si); a.si = (a.si + 1) & 3;
      const int uv = att_slot(a.si); a.si = (a.si + 1) & 3;
      c.wait2(uk, uv);
      c.turn();
      fence_regs(a.o); fence_regs(a.p);
      wg_fence();
      issue_qk(a.s, a.qaddr, c.daddr(uk));
      issue_pv_n<false, 8>(a.o, a.p, c.daddr(uv));
      c.pass();
      wg_wait<0>(); fence_regs(a.s); fence_regs(a.o); fence_regs(a.p);
      c.release(uk, 2); c.release(uv, 2);
      if (st == 15 - g) c.release(0, 2);
      if (st == 16) c.release(2, 2);
      if (sw) { att_drain_now(c, a, ctx_off(c, h, 15 - g, c.wg)); m0 = m1 = -INFINITY; }
      if (sw || st == 15 - g) mask_diag(a.s, (sw ? 1 - c.wg : c.wg) * 64 + c.warp * 16 + (c.lane >> 2) - 2 * (c.lane & 3));
    }
    softmax_safe(a.s, m0, m1, sc0, sc1);
    a.l[0] *= sc0; a.l[1] *= sc0; a.l[2] *= sc1; a.l[3] *= sc1;
    exp_rng<0, 16>(a.s); sum_rng<0, 16>(a.s, a.l); cvt_p<0, 16>(a.s, a.p);
#pragma unroll
    for (int i = 0; i < 16; i++) { a.o[4 * i] *= sc0; a.o[4 * i + 1] *= sc0; a.o[4 * i + 2] *= sc1; a.o[4 * i + 3] *= sc1; }
  }
}
__device__ __forceinline__ void cons_att(Cons& c, int h, int g, int fast, Pend& w) {
  Att a;
  att_first(c, a);
  if (fast) cons_att_fast(c, a, h, g);
  else {
#pragma unroll
    for (int i = 0; i < 32; i++) a.p[i] = 0;
    cons_att_safe(c, a, h, g);
  }
  att_last(c, a, w, !(fast && g == 0 && c.wg == 1), ctx_off(c, h, g, 1 - c.wg));
}

constexpr int CV_H = 1024, CV_U = 5120, CV_D = CV_U + 4128, CV_ROW = 1056;
template<int OFF> __device__ __forceinline__ uint32_t lds32o(uint32_t a) { uint32_t v; asm volatile("ld.shared.u32 %0, [%1+%2];" : "=r"(v) : "r"(a), "n"(OFF) : "memory"); return v; }
template<int G, int G1 = 16> __device__ __forceinline__ void conv_lda(uint32_t (&a)[64], uint32_t p) {
  a[4 * G + 0] = lds32o<-256 * G>(p);
  a[4 * G + 1] = lds32o<-256 * G - 128>(p);
  a[4 * G + 2] = lds32o<-256 * G + 16>(p);
  a[4 * G + 3] = lds32o<-256 * G - 112>(p);
  if constexpr (G + 1 < G1) conv_lda<G + 1, G1>(a, p);
}
template<int R, int G0, int G1> __device__ __forceinline__ void conv_mma(float (&d)[32], const uint32_t (&a)[64], uint64_t db) {
#pragma unroll
  for (int G = G0; G < G1; G++) wgmma_rs_n64<0>(d, a[4 * G], a[4 * G + 1], a[4 * G + 2], a[4 * G + 3], db + 64 * R - 16 * G, G > 0);
}
template<int R> __device__ __forceinline__ void conv_st(const float (&d)[32], uint32_t wq, float& c0, float& c1) {
#pragma unroll
  for (int n = 0; n < 8; n++) { sts64f(wq + (R * 64 + n * 8) * 4, d[4 * n] + c0, d[4 * n + 1] + c1); c0 = d[4 * n + 2]; c1 = d[4 * n + 3]; }
}
__device__ __forceinline__ void cons_conv(Cons& c, int cta, int nch) {
  const int r = c.lane >> 2, q = c.lane & 3, tid = c.warp * 32 + c.lane;
  const uint32_t part = c.addr(4) - 2048 + (1 - c.wg) * (32 * CV_ROW) + 32;
  const uint32_t aoff = CV_U + ((r & 1) ? 0 : UPITCH) + 4 * (((2039 - r) >> 1) + q - 8 * c.warp);
  const uint32_t wq = part + (c.warp * 8 + r) * CV_ROW + q * 8, rq = part + tid * 8;
  uint32_t a[64];
  c.wait(c.wg); c.skip(c.wg ^ 1);
  conv_lda<0>(a, c.addr(c.wg) + aoff);
  c.wait(4);
  sts64f(part + (tid >> 2) * CV_ROW - 32 + q * 8, 0.f, 0.f);
#pragma unroll 1
  for (int i = 0; i < nch / 2; i++) {
    const int u = 2 * (i & 1) + c.wg;
    float d0[32], d1[32], d2[32], d3[32];
    float c0 = 0.f, c1 = 0.f;
    const uint64_t db = mkdesc(c.daddr(u) + CV_H - 16, 16, 128, 0);
    c.turn();
    fence_regs(a);
    wg_fence();
    conv_mma<0, 0, 4>(d0, a, db); conv_mma<1, 0, 8>(d1, a, db); wg_commit();
    conv_mma<2, 0, 12>(d2, a, db); wg_commit();
    wg_wait<1>(); fence_regs(d0); fence_regs(d1);
    conv_st<0>(d0, wq, c0, c1);
    wg_fence();
    conv_mma<3, 0, 8>(d3, a, db);
    conv_st<1>(d1, wq, c0, c1);
    conv_mma<3, 8, 16>(d3, a, db); wg_commit();
    c.pass();
    wg_wait<1>(); fence_regs(d2);
    conv_st<2>(d2, wq, c0, c1);
    wg_wait<0>(); fence_regs(d3); fence_regs(a);
    conv_st<3>(d3, wq, c0, c1);
    TR(c, c.wg, 50);
    const uint32_t ub = c.addr(u);
    const uint4 ua = lds128(ub + CV_U + 4064 - 32 * tid + 16), uc = lds128(ub + CV_U + 4064 - 32 * tid);
    const uint32_t D2 = lds32(ub + CV_D);
    bar_sync(3 + c.wg, 128);
    c.release2(u);
    TR(c, c.wg, 51);
    float y0[8], y1[8];
#pragma unroll
    for (int rr = 0; rr < 8; rr++) { const float2 v = lds64f(rq + rr * CV_ROW); y0[rr] = v.x; y1[rr] = v.y; }
#pragma unroll
    for (int w = 1; w < 4; w++) {
#pragma unroll
      for (int rr = 0; rr < 8; rr++) { const float2 v = lds64f(rq + (w * 8 + rr) * CV_ROW - w * 8); y0[rr] += v.x; y1[rr] += v.y; }
    }
    if (i + 1 < nch / 2) { c.wait(u ^ 2); c.skip(u ^ 3); conv_lda<0>(a, c.addr(u ^ 2) + aoff); }
    uint4 z0, z1;
    z0.x = hadd2(pack_bf16(y0[0], y0[1]), hmul2(__byte_perm(ua.w, 0, 0x1032), D2));
    z0.y = hadd2(pack_bf16(y0[2], y0[3]), hmul2(__byte_perm(ua.z, 0, 0x1032), D2));
    z0.z = hadd2(pack_bf16(y0[4], y0[5]), hmul2(__byte_perm(ua.y, 0, 0x1032), D2));
    z0.w = hadd2(pack_bf16(y0[6], y0[7]), hmul2(__byte_perm(ua.x, 0, 0x1032), D2));
    z1.x = hadd2(pack_bf16(y1[0], y1[1]), hmul2(__byte_perm(uc.w, 0, 0x1032), D2));
    z1.y = hadd2(pack_bf16(y1[2], y1[3]), hmul2(__byte_perm(uc.z, 0, 0x1032), D2));
    z1.z = hadd2(pack_bf16(y1[4], y1[5]), hmul2(__byte_perm(uc.y, 0, 0x1032), D2));
    z1.w = hadd2(pack_bf16(y1[6], y1[7]), hmul2(__byte_perm(uc.x, 0, 0x1032), D2));
    uint4* zp = (uint4*)(g_z + (size_t)conv_channel(cta, 2 * i + c.wg) * 2048 + tid * 16);
    zp[0] = z0; zp[1] = z1;
    TR(c, c.wg, 52);
    if ((i & 15) == 15 || i == nch / 2 - 1) c.signal(SIG_Z + (i >> 4));
  }
  c.release(4, 4);
}

#define EARLYREL 0
#define OC_STAG 0
constexpr int OC_START = 2, OC_LEN = 14, OC_PART = 13824, OC_ROW = 544;
__device__ __forceinline__ int out_slot(int i) { return (0x64A8C >> (4 * i)) & 15; }
struct Out { float acc[64]; int si, pu; };
template<bool FIRST, bool REL> __device__ __forceinline__ void out_step(Cons& c, Out& o) {
  const int u = out_slot(o.si); o.si = o.si == 4 ? 0 : o.si + 1;
  if (EARLYREL == 2 && REL) { wg_wait<0>(); c.release(o.pu, 2); }
  c.wait(u);
  if (EARLYREL == 1 && REL) { wg_wait<0>(); c.release(o.pu, 2); }
  const uint64_t da = mkdesc(c.daddr(u) + c.wg * 8192, 16, 1024, 2), db = mkdesc(c.daddr(u + 1), 8192, 1024, 1);
  wg_fence();
#pragma unroll
  for (int kk = 0; kk < 4; kk++) wgmma_ss_n128<1>(o.acc, da + (kk >> 1) * 32 + (kk & 1) * 2, db + kk * 128, !(FIRST && kk == 0));
  wg_commit();
  if (EARLYREL == 0 && REL) { wg_wait<1>(); c.release(o.pu, 2); }
  o.pu = u;
}
template<int I0, int I1> __device__ __forceinline__ void oc_red(float (&y)[8], uint32_t rq) {
#pragma unroll
  for (int i = I0; i < I1; i++) { const float v = __uint_as_float(lds32(rq + i * OC_ROW - (i >> 3) * 8)); y[i & 7] = i < 8 ? v : y[i & 7] + v; }
}
__device__ __forceinline__ void oc_emit(const float (&y)[8], const uint4& u, uint32_t D2, __nv_bfloat16* dst) {
  uint4 z;
  z.x = hadd2(pack_bf16(y[0], y[1]), hmul2(__byte_perm(u.w, 0, 0x1032), D2));
  z.y = hadd2(pack_bf16(y[2], y[3]), hmul2(__byte_perm(u.z, 0, 0x1032), D2));
  z.z = hadd2(pack_bf16(y[4], y[5]), hmul2(__byte_perm(u.y, 0, 0x1032), D2));
  z.w = hadd2(pack_bf16(y[6], y[7]), hmul2(__byte_perm(u.x, 0, 0x1032), D2));
  *(uint4*)dst = z;
}
template<int MASK> __device__ __forceinline__ void cons_out(Cons& c, const Maps& M, int cta, Pend& w) {
  const int mb = out_mb(cta), nb = out_nb(cta);
  Out o; o.si = 0;
  out_step<true, false>(c, o);
  if (MASK & PH_ATT) tile_store<0, 2>(w.lo, w.dst, c.lane);
  out_step<false, true>(c, o);
  if (MASK & PH_ATT) { tile_store<2, 4>(w.lo, w.dst, c.lane); c.signal(SIG_CTX + 1); }
  int ks = OC_START;
  if (MASK & PH_CONV) {
    const int r = c.lane >> 2, q = c.lane & 3, tid = c.warp * 32 + c.lane, u = 2 * c.wg;
    const uint32_t ub = c.addr(u), part = ub + OC_PART + 32;
    const uint32_t ap = ub + CV_U + ((r & 1) ? 0 : UPITCH) + 4 * (((2039 - r) >> 1) + q - 8 * c.warp);
    const uint32_t wq = part + (c.warp * 8 + r) * OC_ROW + q * 8, rq = part + tid * 4;
    const int nr = (CONV_REG + 1 - c.wg) >> 1;
#pragma unroll 1
    for (; ks < OC_START + c.wg * OC_STAG; ks++) out_step<false, true>(c, o);
#define STEP out_step<false, true>(c, o);
#pragma unroll 1
    for (int i = 0; i < nr; i++) {
      uint32_t a[64];
      float d0[32], d1[32], y[8], c0 = 0.f, c1 = 0.f;
      const uint64_t db = mkdesc(c.daddr(u + (i >> 8)) + CV_H - 16, 16, 128, 0);
      c.wait(u);
      conv_lda<0, 3>(a, ap);
      STEP
      conv_lda<3, 6>(a, ap);
      STEP
      conv_lda<6, 9>(a, ap);
      STEP
      fence_regs(reinterpret_cast<uint32_t (&)[32]>(a));
      wg_fence();
      conv_mma<0, 0, 4>(d0, a, db); conv_mma<1, 0, 8>(d1, a, db); wg_commit();
      conv_lda<9, 13>(a, ap);
      STEP
      fence_regs(d0); fence_regs(d1);
      conv_lda<13, 16>(a, ap);
      STEP
      bar_sync(3 + c.wg, 128);
      sts64f(wq - 32, 0.f, 0.f);
      conv_st<0>(d0, wq, c0, c1);
      STEP
      float e0 = d1[28] + d1[26], e1 = d1[29] + d1[27];
      conv_st<1>(d1, wq, c0, c1);
      asm volatile("add.f32 %0, %0, 0f80000000;" : "+f"(c0)); asm volatile("add.f32 %0, %0, 0f80000000;" : "+f"(c1));
      fence_regs(a);
      wg_fence();
      conv_mma<2, 0, 12>(d0, a, db); conv_mma<3, 0, 16>(d1, a, db); wg_commit();
      bar_sync(3 + c.wg, 128);
      oc_red<0, 8>(y, rq);
      STEP
      fence_regs(d0); fence_regs(d1); fence_regs(a);
      const uint4 u0 = lds128(ub + CV_U + 4080 - 16 * tid), u1 = lds128(ub + CV_U + 2032 - 16 * tid);
      const uint32_t D2 = lds32(ub + CV_D);
      oc_red<8, 12>(y, rq);
      __syncwarp();
      c.release2(u);
      STEP
      oc_red<12, 24>(y, rq);
      STEP
      __nv_bfloat16* zp = g_z + (size_t)conv_channel(cta, 2 * i + c.wg) * 2048 + tid * 8;
      oc_red<24, 32>(y, rq);
      oc_emit(y, u0, D2, zp);
      bar_sync(3 + c.wg, 128);
      STEP
      sts64f(wq - 32, e0, e1);
      conv_st<0>(d0, wq, c0, c1);
      STEP
      conv_st<1>(d1, wq, c0, c1);
      bar_sync(3 + c.wg, 128);
      oc_red<0, 8>(y, rq);
      STEP
      oc_red<8, 20>(y, rq);
      STEP
      oc_red<20, 32>(y, rq);
      oc_emit(y, u1, D2, zp + 1024);
      if (i == nr - 1) { c.signal(SIG_Z); c.release2(u + 1); }
      STEP
    }
#undef STEP
    if (((CONV_REG + c.wg) >> 1) & 1) c.skip(u ^ 2);
    ks += nr * OC_LEN;
  }
  TS(c.wg, 9);
#pragma unroll 1
  for (; ks < 57; ks++) out_step<false, true>(c, o);
  uint32_t ga[32];
  c.wait(0);
  const float g0 = __uint_as_float(lds32(c.base + SM_GATE + 4 * (c.wg * 64 + c.warp * 16 + (c.lane >> 2)))), g1 = __uint_as_float(lds32(c.base + SM_GATE + 32 + 4 * (c.wg * 64 + c.warp * 16 + (c.lane >> 2))));
  const uint32_t gg0 = pack_bf16(g0, g0), gg1 = pack_bf16(g1, g1);
  const uint32_t og0 = pack_bf16(1.f - g0, 1.f - g0), og1 = pack_bf16(1.f - g1, 1.f - g1);
  const int xr = c.wg * 64 + c.warp * 16 + (c.lane & 15);
  const uint32_t xa = c.addr(0) + xr * 128, xs = xr & 7, xh = c.lane >> 4;
  const int zr = (c.lane & 7) + ((c.lane >> 4) << 3);
  const uint32_t za = c.addr(2) + c.wg * 16384 + zr * 128 + (((c.warp * 2 + ((c.lane >> 3) & 1)) ^ (zr & 7)) << 4);
#pragma unroll
  for (int i = 0; i < 8; i++) {
    if (i % 3 == 0) out_step<false, true>(c, o);
    ldsm4(xa + (i >> 2) * 16384 + ((((i & 3) * 2 + xh) ^ xs) << 4), ga[4 * i], ga[4 * i + 1], ga[4 * i + 2], ga[4 * i + 3]);
  }
#pragma unroll 1
  for (ks = 60; ks < 63; ks++) { out_step<false, false>(c, o); wg_wait<1>(); }
  c.wait(2);
#pragma unroll
  for (int i = 0; i < 8; i++) {
    if (i == 2) out_step<false, false>(c, o);
    uint32_t z0, z1, z2, z3;
    ldsm4t(za + i * 2048, z0, z1, z2, z3);
    ga[4 * i + 0] = hmul2(gg0, hmul2(ga[4 * i + 0], z0)); ga[4 * i + 1] = hmul2(gg1, hmul2(ga[4 * i + 1], z1));
    ga[4 * i + 2] = hmul2(gg0, hmul2(ga[4 * i + 2], z2)); ga[4 * i + 3] = hmul2(gg1, hmul2(ga[4 * i + 3], z3));
  }
  asm volatile("barrier.cluster.arrive.relaxed;" ::: "memory");
  fence_regs(ga);
  wg_wait<0>(); fence_regs(o.acc);
#pragma unroll
  for (int i = 0; i < 8; i++) {
    const uint32_t r0 = hadd2(ga[4 * i + 0], hmul2(og0, pack_bf16(o.acc[8 * i + 0], o.acc[8 * i + 1])));
    const uint32_t r1 = hadd2(ga[4 * i + 1], hmul2(og1, pack_bf16(o.acc[8 * i + 2], o.acc[8 * i + 3])));
    const uint32_t r2 = hadd2(ga[4 * i + 2], hmul2(og0, pack_bf16(o.acc[8 * i + 4], o.acc[8 * i + 5])));
    const uint32_t r3 = hadd2(ga[4 * i + 3], hmul2(og1, pack_bf16(o.acc[8 * i + 6], o.acc[8 * i + 7])));
    stsm4(xa + (i >> 2) * 16384 + ((((i & 3) * 2 + xh) ^ xs) << 4), r0, r1, r2, r3);
  }
  fence_async_smem();
  __syncwarp();
  if (c.lane < 2) {
    const int r0 = c.wg * 64 + c.warp * 16;
    tma2d_store(&M.out, c.addr(0) + c.lane * 16384 + r0 * 128, nb * 128 + c.lane * 64, mb * 128 + r0);
    asm volatile("cp.async.bulk.commit_group;\ncp.async.bulk.wait_group.read 0;" ::: "memory");
  }
}

__device__ __forceinline__ void load_conv(Prod& p, const Maps& M, int u, int ch) {
  if (elect()) {
    mbar_expect(p.full(u), 5120 + UCH);
    tma3d(p.addr(u), &M.h, 0, -8, ch, p.full(u), POL(4));
    bulk_g2s(p.addr(u) + CV_U, g_u + (size_t)ch * UCH, UCH, p.full(u), POL(4));
  }
}
__device__ __forceinline__ void prod_conv(Prod& p, const Maps& M, int cta, int nch) {
  int ready = -1;
#pragma unroll 1
  for (int i = 0; i < nch; i++) {
    const int ch = conv_channel(cta, i);
    const int u = i & 3;
    if ((ch >> 6) != ready) { ready = ch >> 6; if (cta < NREG) mbar_wait(p.base + SM_RDY + 8 * RDY_U, 0); else cnt_wait(g_cnt + (C_U + ready) * CSTRIDE, 32); }
    p.acquire(u, 1);
    load_conv(p, M, u, ch);
    if (i == 3) { p.acquire(4, 4); if (elect()) mbar_arrive(p.full(4)); }
  }
}
#define HOIST(v) asm volatile("" : "+r"(v))
template<int MASK> __device__ __forceinline__ void producer(const Maps& M, const Params& P, uint32_t base, int cta, int lane) {
  Prod p{base, (MASK & PH_PRE) ? 0xffffcfffu : 0xffffffffu, lane,
         (cta * 3 + 2) * 2048};
  if (cta >= NREG) { if (MASK & PH_CONV) prod_conv(p, M, cta, CONV_EXTRA); return; }
  const int g = cta & 7, j = cta >> 3, rank = cta & 1;
#pragma unroll 1
  for (int half = 0; half < 2; half++) {
    const int h = j + 16 * half;
    if (MASK & PH_KV) {
      const CUtensorMap* mw = rank ? &M.wv : &M.wk;
#pragma unroll 1
      for (int it = 0; it < 16; it++) {
        const int u = gemm_unit(it);
        uint32_t bar = p.full(u), d0 = p.addr(u), d1 = p.addr(u + 1 + rank); int k0 = (it & 7) * 64, r0 = (2 * g + (it >> 3)) * 128;
        HOIST(bar); HOIST(d0); HOIST(d1); HOIST(k0); HOIST(r0);
        p.acquire(u, 3);
        if (elect()) {
          mbar_expect(bar, 3 * UNIT);
          tma3d_mc(d1, mw, 0, k0, 2 * h, bar, POL(0) && it >= 8);
          tma2d(d0, &M.c, k0, r0, bar);
        }
      }
    }
    if (MASK & PH_ATT) {
#pragma unroll 1
      for (int ks = 0; ks < 16; ks++) {
        const int u = gemm_unit(ks);
        uint32_t bar = p.full(u), d0 = p.addr(u), d1 = p.addr(u + 1), d2 = p.addr(u + 2) + rank * 8192; int k0 = ks * 64;
        HOIST(bar); HOIST(d0); HOIST(d1); HOIST(d2); HOIST(k0);
        p.acquire(u, 3);
        if (elect()) {
          mbar_expect(bar, 3 * UNIT);
          tma2d_mc(d2, &M.wq, h * 128 + rank * 64, k0, bar, POL(1));
          tma2d(d0, &M.x, k0, (15 - g) * 128, bar);
          tma2d(d1, &M.x, k0, g * 128, bar);
        }
      }
      TS(2, 8 * half + 0);
      mbar_wait(base + SM_RDY + 8 * (RDY_KV + half), 0);
      TS(2, 8 * half + 1);
      const uint8_t* KVh = g_T + T_KV + (size_t)kv_slot<MASK>(h) * 16 * 65536;
#pragma unroll 1
      for (int i = 0; i < 34; i++) {
        const int isv = (i > 0 && !(i & 1)) || i == 33;
        const int st = i == 33 ? 16 : (isv ? (i >> 1) - 1 : (i + 1) >> 1);
        const int u = att_slot(i & 3);
        const bool own = st == 15 - (g & 6);
        uint32_t bar = p.full(u), d0 = p.addr(own ? u : u + rank), off = (st <= 15 - g ? st : 16 - st) * 65536 + isv * 32768 + (own ? 0 : rank * UNIT);
        HOIST(bar); HOIST(d0); HOIST(off);
        p.acquire(u, 2);
        if (elect()) {
          mbar_expect(bar, 32768);
          if (own) bulk_g2s(d0, KVh + off, 32768, bar, POL(6)); else bulk_g2s_mc(d0, KVh + off, UNIT, bar, POL(6));
        }
        if (i == 0) { p.acquire(0, 4); if (elect()) mbar_arrive(p.full(0)); }
      }
    }
  }
  if ((MASK & PH_CONV) && !(MASK & PH_OUT)) prod_conv(p, M, cta, CONV_REG);
  if (MASK & PH_OUT) {
    const int y0 = out_mb(cta) * 512 + rank * 8, z0 = 2 * out_nb(cta);
    uint32_t slots = 0x64A8C;
#pragma unroll 1
    for (int hf = 0; hf < 2; hf++) {
      TS(2, 16 + 2 * hf);
      mbar_wait(base + SM_RDY + 8 * (RDY_CTX + hf), 0);
      TS(2, 17 + 2 * hf);
#pragma unroll 1
      for (int ks = hf * 32; ks < hf * 32 + 32; ks++) {
        const int u = slots & 15; slots = (slots >> 4) | (u << 16);
        uint32_t bar = p.full(u), d0 = p.addr(u) + rank * 8192, d1 = p.addr(u + 1); int x = (ks & 1) * 256, y = y0 + (ks >> 1) * 16, k0 = ks * 64;
        HOIST(bar); HOIST(d0); HOIST(d1); HOIST(x); HOIST(y); HOIST(k0);
        p.acquire(u, 2);
        if (elect()) {
          mbar_expect(bar, 2 * UNIT);
          tma2d_mc(d0, &M.ctx, x, y, bar, POL(5));
          tma3d(d1, &M.wo, 0, k0, z0, bar, POL(2));
        }
      }
    }
    if (elect()) mbar_arrive(base + SM_RDY + 8 * RDY_Z);
  }
}
template<int MASK> __device__ __forceinline__ void producer2(const Maps& M, const Params& P, uint32_t base, int cta, int w, int lane) {
  Prod p{base, 0xffffffffu, lane, 0};
  const int mb = out_mb(cta), nb = out_nb(cta), u = 2 * w;
  if (MASK & PH_CONV) {
    mbar_wait_slow(base + SM_SIG + 8 * (SIG_ATT + 1), 0);
    mbar_wait_slow(base + SM_RDY + 8 * RDY_U, 0);
#pragma unroll 1
    for (int i = w; i < CONV_REG; i += 2) { p.acquire_slow(u, i < 2 ? 2 : 1); load_conv(p, M, u, conv_channel(cta, i)); }
  }
  p.acquire_slow(u, 2);
  TSA(50 + 2 * w);
  mbar_wait_slow(base + SM_RDY + 8 * (w ? RDY_Z : RDY_G), 0);
  TSA(51 + 2 * w);
  if (elect()) {
    mbar_expect(p.full(u), 2 * UNIT + (w ? 0 : 512));
    tma2d(p.addr(u), w ? &M.z : &M.x, (w ? mb : nb) * 128, (w ? nb : mb) * 128, p.full(u), POL(5));
    tma2d(p.addr(u + 1), w ? &M.z : &M.x, (w ? mb : nb) * 128 + 64, (w ? nb : mb) * 128, p.full(u), POL(5));
    if (!w) bulk_g2s(base + SM_GATE, g_gate + mb * 128, 512, p.full(u));
  }
}

template<int MASK> __device__ __forceinline__ void sync_agent(const Params& P, uint32_t base, int cta, int lane) {
#define PUBLISH(SIG, CNT, N) { mbar_wait_slow(base + SM_SIG + 8 * (SIG), 0); if (lane == 0) cnt_publish(g_cnt + (CNT) * CSTRIDE, N); __syncwarp(); }
#define READY(RDY) { __syncwarp(); if (lane == 0) mbar_arrive(base + SM_RDY + 8 * (RDY)); }
  if (cta >= NREG) {
    if (MASK & PH_CONV) for (int b = 0; b * 32 < CONV_EXTRA; b++) PUBLISH(SIG_Z + b, C_Z + b, min(32, CONV_EXTRA - b * 32))
    return;
  }
  const int g = cta & 7, j = cta >> 3;
#pragma unroll 1
  for (int half = 0; half < 2; half++) {
    const int h = j + 16 * half;
    if (half == 1 && MASK == PH_ALL) PUBLISH(SIG_WAR, C_WAR + j, 1)
    if (half == 1 && (MASK & PH_ATT)) PUBLISH(SIG_CTX, C_CTX + g, 1)
    if (half == 1 && MASK == PH_ALL) { cnt_wait(g_cnt + (C_WAR + j) * CSTRIDE, 8); READY(RDY_WAR) }
    if (MASK & PH_KV) PUBLISH(SIG_KV + half, C_KV + h, 1)
    if (MASK & PH_ATT) {
      cnt_wait(g_cnt + (C_KV + h) * CSTRIDE, 8);
      const float4 kn = __ldcg((const float4*)(g_kn2 + kv_slot<MASK>(h) * 128) + lane);
      const uint32_t m = __reduce_max_sync(~0u, max(max(__float_as_uint(kn.x), __float_as_uint(kn.y)), max(__float_as_uint(kn.z), __float_as_uint(kn.w))));
      if (lane == 0) asm volatile("st.shared.u32 [%0], %1;" :: "r"(base + SM_KMAX + 4 * half), "r"(m) : "memory");
      READY(RDY_KV + half)
    }
  }
  const int go = min(out_mb(cta), 15 - out_mb(cta));
  if (MASK & PH_OUT) cnt_wait(g_cnt + (C_CTX + go) * CSTRIDE, 16);
  if (MASK & PH_CONV) {
    cnt_wait(g_cnt + (C_U + (conv_channel(cta, 0) >> 6)) * CSTRIDE, 32);
    cnt_wait(g_cnt + (C_U + (conv_channel(cta, CONV_REG - 1) >> 6)) * CSTRIDE, 32);
    READY(RDY_U)
  }
  if (MASK & PH_OUT) READY(RDY_CTX)
  if (MASK & PH_ATT) PUBLISH(SIG_CTX + 1, C_CTX + 8 + g, 1)
  if (MASK & PH_OUT) {
    cnt_wait(g_cnt + (C_CTX + 8 + go) * CSTRIDE, 16); READY(RDY_CTX + 1)
    cnt_wait(g_cnt + C_GATE * CSTRIDE, 256); READY(RDY_G)
  }
  if (MASK & PH_CONV) {
    const int c0 = conv_channel(cta, 0), c1 = c0 + CONV_REG - 1;
    if ((c0 >> 7) == (c1 >> 7)) PUBLISH(SIG_Z, C_Z + (c0 >> 7), CONV_REG)
    else { PUBLISH(SIG_Z, C_Z + (c0 >> 7), 128 - (c0 & 127)) PUBLISH(SIG_Z, C_Z + (c1 >> 7), (c1 & 127) + 1) }
  }
  if (MASK & PH_OUT) { cnt_wait(g_cnt + (C_Z + out_nb(cta)) * CSTRIDE, 128); READY(RDY_Z) }
#undef PUBLISH
#undef READY
}

template<int MASK> __device__ __forceinline__ void aux_pre(const Maps& M, const Params& P, uint32_t base, int cta, int aw, int lane) {
  const uint32_t kb = base + 12 * UNIT, bar = base + SM_PRE;
  const int r = lane >> 2, q = lane & 3;
  const int mi = lane >> 3, row0 = (lane & 6) + 1 - (lane & 1);
#pragma unroll 1
  for (int it = 0; it < 4; it++) {
    if (it == PRE_EARLY && MASK == PH_ALL) mbar_wait_slow(base + SM_SIG + 8 * (SIG_ATT + PRE_HALF), 0);
    const int cg = it * 4 + (cta >> 5), tb = cta & 31;
    if (aw == 0 && elect()) {
      mbar_expect(bar, 2 * 9216);
      tma4d(kb, &M.k, cg * 64, 0, tb * 8 - 1, 0, bar, POL(3));
      tma4d(kb + 9216, &M.v, cg * 64, 0, tb * 8 - 1, 0, bar, POL(3));
    }
    const uint2 swl = __ldg((const uint2*)(P.shift + (cg * 64 + aw * 32 + lane) * 4));
    if (tb == 0) {
      uint8_t* e = g_u + (size_t)(cg * 64 + aw * 32 + lane) * UCH + 4096;
      *(uint4*)e = make_uint4(0, 0, 0, 0); *(uint4*)(e + UPITCH) = make_uint4(0, 0, 0, 0);
      *(uint32_t*)(e + 32) = (uint32_t)__bfloat16_as_ushort(P.D[cg * 64 + aw * 32 + lane]) * 0x10001u;
    }
    mbar_wait_slow(bar, it & 1);
#pragma unroll 1
    for (int bl = 0; bl < 8; bl++) {
      const int oc = aw * 4 + (bl >> 1), hb = bl & 1, ch = cg * 64 + oc * 8 + r;
      const uint2 sw = make_uint2(__shfl_sync(~0u, swl.x, (bl >> 1) * 8 + r), __shfl_sync(~0u, swl.y, (bl >> 1) * 8 + r));
      const uint32_t w0 = __byte_perm(sw.x, 0, 0x1010), w1 = __byte_perm(sw.x, 0, 0x3232), w2 = __byte_perm(sw.y, 0, 0x1010), w3 = __byte_perm(sw.y, 0, 0x3232);
      const int ra = (mi * 9 + 4 * hb + 1) * 2 + row0;
      const int rb = ((mi == 0 ? 3 : mi) * 9 + 4 * hb) * 2 + row0;
      uint32_t k[7], v[5];
      ldsm4t(kb + ra * 128 + ((oc ^ (ra & 7)) << 4), k[3], k[4], k[5], k[6]);
      ldsm4t(kb + 9216 + ra * 128 + ((oc ^ (ra & 7)) << 4), v[1], v[2], v[3], v[4]);
      ldsm4t(kb + (mi == 0 ? 9216 : 0) + rb * 128 + ((oc ^ (rb & 7)) << 4), v[0], k[0], k[1], k[2]);
      uint32_t o1 = __byte_perm(k[1], k[0], 0x5432);
#pragma unroll
      for (int m = 0; m < 5; m++) {
        const uint32_t o2 = __byte_perm(k[m + 2], k[m + 1], 0x5432);
        v[m] = hmul2(hadd2(hadd2(hadd2(hmul2(o1, w3), hmul2(k[m + 1], w2)), hmul2(o2, w1)), hmul2(k[m + 2], w0)), v[m]);
        o1 = o2;
      }
      uint8_t* e0 = g_u + (size_t)ch * UCH + (2040 - tb * 64 - hb * 32 - 8 * q) * 2;
      *(uint4*)e0 = make_uint4(v[4], v[3], v[2], v[1]);
      *(uint4*)(e0 + UPITCH) = make_uint4(__byte_perm(v[4], v[3], 0x5432), __byte_perm(v[3], v[2], 0x5432), __byte_perm(v[2], v[1], 0x5432), __byte_perm(v[1], v[0], 0x5432));
    }
    bar_sync(5, 64);
    if (aw == 0) { TSA(40 + it); }
    if (aw == 1 && lane == 0) asm volatile("red.release.gpu.global.add.u32 [%0], 1;" :: "l"(g_cnt + (C_U + cg) * CSTRIDE) : "memory");
  }
  uint32_t rel;
  asm volatile("mapa.shared::cluster.u32 %0, %1, %2;" : "=r"(rel) : "r"(base + SM_BAR + 128 + 8 * (12 + (lane & 1))), "r"((lane >> 1) & 1));
  if (lane < 4) asm volatile("mbarrier.arrive.shared::cluster.b64 _, [%0], 4;" :: "r"(rel) : "memory");
  uint4 gw[4];
#pragma unroll
  for (int i = 0; i < 4; i++) gw[i] = __ldg((const uint4*)P.gw + i * 32 + lane);
#pragma unroll 1
  for (int row = cta * 16 + aw * 8; row < cta * 16 + aw * 8 + 8; row++) {
    float a = 0.f;
#pragma unroll
    for (int i = 0; i < 4; i++) {
      const uint4 xv = __ldg((const uint4*)(P.x + (size_t)row * 1024) + i * 32 + lane);
      uint32_t m;
      m = hmul2(xv.x, gw[i].x); a += bf_lo(m) + bf_hi(m); m = hmul2(xv.y, gw[i].y); a += bf_lo(m) + bf_hi(m);
      m = hmul2(xv.z, gw[i].z); a += bf_lo(m) + bf_hi(m); m = hmul2(xv.w, gw[i].w); a += bf_lo(m) + bf_hi(m);
    }
#pragma unroll
    for (int o = 16; o > 0; o >>= 1) a += __shfl_xor_sync(~0u, a, o);
    a = bf_lo(pack_bf16(a, 0.f));
    const float gt = bf_lo(pack_bf16(__fdividef(1.f, 1.f + ex2(-a * 1.4426950408889634f)), 0.f));
    if (lane == 0) g_gate[row] = gt;
  }
  cnt_signal(g_cnt + C_GATE * CSTRIDE, lane);
  if (aw == 0) { TSA(44); }
}

template<int MASK> __global__ void __cluster_dims__(2, 1, 1) __launch_bounds__(384, 1) gated_mix_kernel(const __grid_constant__ Maps M, const __grid_constant__ Params P) {
  extern __shared__ __align__(1024) uint8_t smem[];
  const uint32_t base = (uint32_t)__cvta_generic_to_shared(smem);
  if (threadIdx.x == 0) {
    if ((base & 0x3FFFF) != SMEM_BASE) asm volatile("trap;");
    for (int i = 0; i < NUNIT; i++) { mbar_init(base + SM_BAR + 8 * i, 1); mbar_init(base + SM_BAR + 128 + 8 * i, 16); }
    mbar_init(base + SM_EXIT, 4); mbar_init(base + SM_PRE, 1);
    for (int i = 0; i < 12; i++) { mbar_init(base + SM_SIG + 8 * i, i == SIG_GO ? 1 : 8); mbar_init(base + SM_RDY + 8 * i, i == RDY_Z ? 2 : 1); }
    asm volatile("fence.mbarrier_init.release.cluster;" ::: "memory");
  }
  __syncthreads();
  asm volatile("barrier.cluster.arrive.relaxed.aligned;\nbarrier.cluster.wait.aligned;" ::: "memory");
  const int wg = __shfl_sync(~0u, threadIdx.x >> 7, 0);
  const int warp = __shfl_sync(~0u, (threadIdx.x >> 5) & 3, 0);
  const int lane = threadIdx.x & 31;
  const int cta = blockIdx.x;
  if (wg == 2) {
    asm volatile("setmaxnreg.dec.sync.aligned.u32 56;");
    TS(2, 62);
    if (warp == 0) producer<MASK>(M, P, base, cta, lane);
    else if (warp == 1) sync_agent<MASK>(P, base, cta, lane);
    else if (cta < NREG) {
      if (MASK & PH_PRE) aux_pre<MASK>(M, P, base, cta, warp - 2, lane);
      if (MASK & PH_OUT) producer2<MASK>(M, P, base, cta, warp - 2, lane);
    }
    __syncwarp();
    if (lane == 0) mbar_arrive(base + SM_EXIT);
    if (warp == 0 && (MASK & PH_OUT)) {
      mbar_wait_slow(base + SM_EXIT, 0);
      unsigned old = 0;
      if (lane == 0) asm volatile("atom.acq_rel.gpu.global.add.u32 %0, [%1], 1;" : "=r"(old) : "l"(g_cnt + C_EXIT * CSTRIDE) : "memory");
      old = __shfl_sync(~0u, old, 0);
      if (old == NCTA - 1) for (int i = lane; i < C_NUM; i += 32) g_cnt[i * CSTRIDE] = 0;
    }
    if (warp == 0) { cluster_arrive(); cluster_wait(); }
  } else {
    asm volatile("setmaxnreg.inc.sync.aligned.u32 224;");
    uint32_t rel;
    asm volatile("mapa.shared::cluster.u32 %0, %1, %2;" : "=r"(rel) : "r"(base + SM_BAR + 128 + 8 * (lane & 15)), "r"(lane >> 4));
    Cons c{base, rel, 0u, lane, warp, wg, (cta * 3 + wg) * 2048};
    if (wg == 1) bar_arrive(1, 256);
    TS(wg, 0);
    if (cta < NREG) {
      const int g = cta & 7, j = cta >> 3;
      Pend w = {};
#pragma unroll 1
      for (int half = 0; half < 2; half++) {
        const int h = j + 16 * half;
        if (MASK & PH_KV) cons_kv(c, h, kv_slot<MASK>(h), g, w, half == 1 && (MASK & PH_ATT));
        TS(wg, 1 + 4 * half);
        if (MASK & PH_ATT) {
          const int fast = cons_q<(MASK & PH_KV) != 0>(c, h, w);
          TS(wg, 2 + 4 * half);
          c.signal(SIG_ATT + half);
          cons_att(c, h, g, fast, w);
          if (half == 0) c.signal(SIG_WAR);
#pragma unroll
          for (int i = 0; i < 8; i++) w.hi[i] = make_uint4(0, 0, 0, 0);
          TS(wg, 3 + 4 * half);
          if (MASK != PH_ALL) { tile_store<0, 4>(w.lo, w.dst, lane); c.signal(SIG_CTX + half); }
        } else if (MASK & PH_KV) { out_part<0>(c, w); out_part<1>(c, w); out_part<2>(c, w); out_part<3>(c, w); c.signal(SIG_KV + half); }
      }
      if (MASK & PH_OUT) cons_out<MASK>(c, M, cta, w);
    }
    if (cta >= NREG || !(MASK & PH_OUT)) {
      if (MASK & PH_CONV) cons_conv(c, cta, cta < NREG ? CONV_REG : CONV_EXTRA);
      TS(wg, 9);
      cluster_arrive();
    }
    TS(wg, 10);
  }
}

typedef CUresult (*EncFn)(CUtensorMap*, CUtensorMapDataType, cuuint32_t, void*, const cuuint64_t*, const cuuint64_t*, const cuuint32_t*, const cuuint32_t*,
                          CUtensorMapInterleave, CUtensorMapSwizzle, CUtensorMapL2promotion, CUtensorMapFloatOOBfill);
static void enc(EncFn f, CUtensorMap* m, const void* ptr, int rank, const cuuint64_t* dims, const cuuint64_t* strides, const cuuint32_t* box, CUtensorMapSwizzle sw,
                CUtensorMapDataType dt = CU_TENSOR_MAP_DATA_TYPE_BFLOAT16) {
  const cuuint32_t es[4] = {1, 1, 1, 1};
  f(m, dt, rank, (void*)ptr, dims, strides, box, es, CU_TENSOR_MAP_INTERLEAVE_NONE, sw, CU_TENSOR_MAP_L2_PROMOTION_L2_256B, CU_TENSOR_MAP_FLOAT_OOB_FILL_NONE);
}
static void enc2(EncFn f, CUtensorMap* m, const void* ptr, int cols, int rows, int brows) {
  const cuuint64_t d[2] = {(cuuint64_t)cols, (cuuint64_t)rows}, s[1] = {(cuuint64_t)cols * 2}; const cuuint32_t b[2] = {64, (cuuint32_t)brows};
  enc(f, m, ptr, 2, d, s, b, CU_TENSOR_MAP_SWIZZLE_128B);
}
static void encw(EncFn f, CUtensorMap* m, const void* ptr, int cols, int rows) {
  const cuuint64_t d[3] = {64, (cuuint64_t)rows, (cuuint64_t)cols / 64}, s[2] = {(cuuint64_t)cols * 2, 128}; const cuuint32_t b[3] = {64, 64, 2};
  enc(f, m, ptr, 3, d, s, b, CU_TENSOR_MAP_SWIZZLE_128B);
}
extern "C" void kernel_launch(void* const* d_in, const int* in_sizes, int n_in, void* d_out, int out_size) {
  static EncFn fn = nullptr;
  static int ncl = 0;
  static void* zptr = nullptr;
  static void* tptr = nullptr;
  if (!fn) {
    void* p = nullptr; cudaDriverEntryPointQueryResult qr;
    cudaGetDriverEntryPoint("cuTensorMapEncodeTiled", &p, cudaEnableDefault, &qr);
    fn = (EncFn)p;
    cudaFuncSetAttribute(gated_mix_kernel<PH_ALL>, cudaFuncAttributeMaxDynamicSharedMemorySize, SMEM_BYTES);
    cudaFuncSetAttribute(gated_mix_kernel<PH_PRE | PH_KV>, cudaFuncAttributeMaxDynamicSharedMemorySize, SMEM_BYTES);
    cudaFuncSetAttribute(gated_mix_kernel<PH_ATT | PH_CONV>, cudaFuncAttributeMaxDynamicSharedMemorySize, SMEM_BYTES);
    cudaFuncSetAttribute(gated_mix_kernel<PH_OUT>, cudaFuncAttributeMaxDynamicSharedMemorySize, SMEM_BYTES);
    cudaLaunchConfig_t cfg = {}; cfg.gridDim = NCTA; cfg.blockDim = 384; cfg.dynamicSmemBytes = SMEM_BYTES;
    cudaLaunchAttribute at; at.id = cudaLaunchAttributeClusterDimension; at.val.clusterDim.x = 2; at.val.clusterDim.y = 1; at.val.clusterDim.z = 1;
    cfg.attrs = &at; cfg.numAttrs = 1;
    cudaOccupancyMaxActiveClusters(&ncl, gated_mix_kernel<PH_ALL>, &cfg);
    cudaGetSymbolAddress(&zptr, g_z);
    cudaGetSymbolAddress(&tptr, g_T);
  }
  Maps M;
  enc2(fn, &M.x, d_in[0], 1024, 2048, 128);
  enc2(fn, &M.c, d_in[7], 512, 2048, 128);
  enc2(fn, &M.wq, d_in[8], 4096, 1024, 64);
  encw(fn, &M.wk, d_in[9], 4096, 512);
  encw(fn, &M.wv, d_in[10], 4096, 512);
  encw(fn, &M.wo, d_in[11], 1024, 4096);
  { const cuuint64_t d[3] = {64, 32, 1024}, s[2] = {128, 4096}; const cuuint32_t b[3] = {64, 40, 1}; enc(fn, &M.h, d_in[4], 3, d, s, b, CU_TENSOR_MAP_SWIZZLE_NONE); }
  enc2(fn, &M.z, zptr, 2048, 1024, 128);
  enc2(fn, &M.out, d_out, 1024, 2048, 16);
  { const cuuint64_t d[2] = {512, 512 * 16}, s[1] = {2048}; const cuuint32_t b[2] = {256, 8};
    enc(fn, &M.ctx, tptr, 2, d, s, b, CU_TENSOR_MAP_SWIZZLE_NONE, CU_TENSOR_MAP_DATA_TYPE_UINT32); }
  { const cuuint64_t d[4] = {1024, 2, 256, 4}, s[3] = {2048, 16384, 4096}; const cuuint32_t b[4] = {64, 2, 9, 4};
    enc(fn, &M.k, d_in[1], 4, d, s, b, CU_TENSOR_MAP_SWIZZLE_128B); enc(fn, &M.v, d_in[2], 4, d, s, b, CU_TENSOR_MAP_SWIZZLE_128B); }
  Params P{(const __nv_bfloat16*)d_in[0], (const __nv_bfloat16*)d_in[3],
           (const __nv_bfloat16*)d_in[5], (const __nv_bfloat16*)d_in[12]};
  bool split = 2 * ncl < NCTA;
  if (!split) {
    gated_mix_kernel<PH_ALL><<<NCTA, 384, SMEM_BYTES>>>(M, P);
  } else {
    gated_mix_kernel<PH_PRE | PH_KV><<<NCTA, 384, SMEM_BYTES>>>(M, P);
    gated_mix_kernel<PH_ATT | PH_CONV><<<NCTA, 384, SMEM_BYTES>>>(M, P);
    gated_mix_kernel<PH_OUT><<<NCTA, 384, SMEM_BYTES>>>(M, P);
  }
}
```

```cpp
#include <cuda_runtime.h>
#include <cuda.h>
#include <cuda_bf16.h>
#include <stdint.h>

template<int TB> __device__ __forceinline__ void wgmma_ss_n256(float (&d)[128], uint64_t da, uint64_t db, int scale_d) {
  asm volatile("{\n.reg .pred p;\nsetp.ne.b32 p, %130, 0;\n"
    "wgmma.mma_async.sync.aligned.m64n256k16.f32.bf16.bf16 {%0, %1, %2, %3, %4, %5, %6, %7, %8, %9, %10, %11, %12, %13, %14, %15, %16, %17, %18, %19, %20, %21, %22, %23, %24, %25, %26, %27, %28, %29, %30, %31, %32, %33, %34, %35, %36, %37, %38, %39, %40, %41, %42, %43, %44, %45, %46, %47, %48, %49, %50, %51, %52, %53, %54, %55, %56, %57, %58, %59, %60, %61, %62, %63, %64, %65, %66, %67, %68, %69, %70, %71, %72, %73, %74, %75, %76, %77, %78, %79, %80, %81, %82, %83, %84, %85, %86, %87, %88, %89, %90, %91, %92, %93, %94, %95, %96, %97, %98, %99, %100, %101, %102, %103, %104, %105, %106, %107, %108, %109, %110, %111, %112, %113, %114, %115, %116, %117, %118, %119, %120, %121, %122, %123, %124, %125, %126, %127}, %128, %129, p, 1, 1, 0, %131;\n}\n"
    : "+f"(d[0]), "+f"(d[1]), "+f"(d[2]), "+f"(d[3]), "+f"(d[4]), "+f"(d[5]), "+f"(d[6]), "+f"(d[7]), "+f"(d[8]), "+f"(d[9]), "+f"(d[10]), "+f"(d[11]), "+f"(d[12]), "+f"(d[13]), "+f"(d[14]), "+f"(d[15]), "+f"(d[16]), "+f"(d[17]), "+f"(d[18]), "+f"(d[19]), "+f"(d[20]), "+f"(d[21]), "+f"(d[22]), "+f"(d[23]), "+f"(d[24]), "+f"(d[25]), "+f"(d[26]), "+f"(d[27]), "+f"(d[28]), "+f"(d[29]), "+f"(d[30]), "+f"(d[31]), "+f"(d[32]), "+f"(d[33]), "+f"(d[34]), "+f"(d[35]), "+f"(d[36]), "+f"(d[37]), "+f"(d[38]), "+f"(d[39]), "+f"(d[40]), "+f"(d[41]), "+f"(d[42]), "+f"(d[43]), "+f"(d[44]), "+f"(d[45]), "+f"(d[46]), "+f"(d[47]), "+f"(d[48]), "+f"(d[49]), "+f"(d[50]), "+f"(d[51]), "+f"(d[52]), "+f"(d[53]), "+f"(d[54]), "+f"(d[55]), "+f"(d[56]), "+f"(d[57]), "+f"(d[58]), "+f"(d[59]), "+f"(d[60]), "+f"(d[61]), "+f"(d[62]), "+f"(d[63]), "+f"(d[64]), "+f"(d[65]), "+f"(d[66]), "+f"(d[67]), "+f"(d[68]), "+f"(d[69]), "+f"(d[70]), "+f"(d[71]), "+f"(d[72]), "+f"(d[73]), "+f"(d[74]), "+f"(d[75]), "+f"(d[76]), "+f"(d[77]), "+f"(d[78]), "+f"(d[79]), "+f"(d[80]), "+f"(d[81]), "+f"(d[82]), "+f"(d[83]), "+f"(d[84]), "+f"(d[85]), "+f"(d[86]), "+f"(d[87]), "+f"(d[88]), "+f"(d[89]), "+f"(d[90]), "+f"(d[91]), "+f"(d[92]), "+f"(d[93]), "+f"(d[94]), "+f"(d[95]), "+f"(d[96]), "+f"(d[97]), "+f"(d[98]), "+f"(d[99]), "+f"(d[100]), "+f"(d[101]), "+f"(d[102]), "+f"(d[103]), "+f"(d[104]), "+f"(d[105]), "+f"(d[106]), "+f"(d[107]), "+f"(d[108]), "+f"(d[109]), "+f"(d[110]), "+f"(d[111]), "+f"(d[112]), "+f"(d[113]), "+f"(d[114]), "+f"(d[115]), "+f"(d[116]), "+f"(d[117]), "+f"(d[118]), "+f"(d[119]), "+f"(d[120]), "+f"(d[121]), "+f"(d[122]), "+f"(d[123]), "+f"(d[124]), "+f"(d[125]), "+f"(d[126]), "+f"(d[127])
    : "l"(da), "l"(db), "r"(scale_d), "n"(TB));
}
template<int TB> __device__ __forceinline__ void wgmma_ss_n128(float (&d)[64], uint64_t da, uint64_t db, int scale_d) {
  asm volatile("{\n.reg .pred p;\nsetp.ne.b32 p, %66, 0;\n"
    "wgmma.mma_async.sync.aligned.m64n128k16.f32.bf16.bf16 {%0, %1, %2, %3, %4, %5, %6, %7, %8, %9, %10, %11, %12, %13, %14, %15, %16, %17, %18, %19, %20, %21, %22, %23, %24, %25, %26, %27, %28, %29, %30, %31, %32, %33, %34, %35, %36, %37, %38, %39, %40, %41, %42, %43, %44, %45, %46, %47, %48, %49, %50, %51, %52, %53, %54, %55, %56, %57, %58, %59, %60, %61, %62, %63}, %64, %65, p, 1, 1, 0, %67;\n}\n"
    : "+f"(d[0]), "+f"(d[1]), "+f"(d[2]), "+f"(d[3]), "+f"(d[4]), "+f"(d[5]), "+f"(d[6]), "+f"(d[7]), "+f"(d[8]), "+f"(d[9]), "+f"(d[10]), "+f"(d[11]), "+f"(d[12]), "+f"(d[13]), "+f"(d[14]), "+f"(d[15]), "+f"(d[16]), "+f"(d[17]), "+f"(d[18]), "+f"(d[19]), "+f"(d[20]), "+f"(d[21]), "+f"(d[22]), "+f"(d[23]), "+f"(d[24]), "+f"(d[25]), "+f"(d[26]), "+f"(d[27]), "+f"(d[28]), "+f"(d[29]), "+f"(d[30]), "+f"(d[31]), "+f"(d[32]), "+f"(d[33]), "+f"(d[34]), "+f"(d[35]), "+f"(d[36]), "+f"(d[37]), "+f"(d[38]), "+f"(d[39]), "+f"(d[40]), "+f"(d[41]), "+f"(d[42]), "+f"(d[43]), "+f"(d[44]), "+f"(d[45]), "+f"(d[46]), "+f"(d[47]), "+f"(d[48]), "+f"(d[49]), "+f"(d[50]), "+f"(d[51]), "+f"(d[52]), "+f"(d[53]), "+f"(d[54]), "+f"(d[55]), "+f"(d[56]), "+f"(d[57]), "+f"(d[58]), "+f"(d[59]), "+f"(d[60]), "+f"(d[61]), "+f"(d[62]), "+f"(d[63])
    : "l"(da), "l"(db), "r"(scale_d), "n"(TB));
}
template<int TB> __device__ __forceinline__ void wgmma_rs_n64(float (&d)[32], uint32_t a0, uint32_t a1, uint32_t a2, uint32_t a3, uint64_t db, int scale_d) {
  asm volatile("{\n.reg .pred p;\nsetp.ne.b32 p, %37, 0;\n"
    "wgmma.mma_async.sync.aligned.m64n64k16.f32.bf16.bf16 {%0, %1, %2, %3, %4, %5, %6, %7, %8, %9, %10, %11, %12, %13, %14, %15, %16, %17, %18, %19, %20, %21, %22, %23, %24, %25, %26, %27, %28, %29, %30, %31}, {%32, %33, %34, %35}, %36, p, 1, 1, %38;\n}\n"
    : "+f"(d[0]), "+f"(d[1]), "+f"(d[2]), "+f"(d[3]), "+f"(d[4]), "+f"(d[5]), "+f"(d[6]), "+f"(d[7]), "+f"(d[8]), "+f"(d[9]), "+f"(d[10]), "+f"(d[11]), "+f"(d[12]), "+f"(d[13]), "+f"(d[14]), "+f"(d[15]), "+f"(d[16]), "+f"(d[17]), "+f"(d[18]), "+f"(d[19]), "+f"(d[20]), "+f"(d[21]), "+f"(d[22]), "+f"(d[23]), "+f"(d[24]), "+f"(d[25]), "+f"(d[26]), "+f"(d[27]), "+f"(d[28]), "+f"(d[29]), "+f"(d[30]), "+f"(d[31])
    : "r"(a0), "r"(a1), "r"(a2), "r"(a3), "l"(db), "r"(scale_d), "n"(TB));
}
__device__ __forceinline__ void wgmma_pv_sel(float (&d)[64], const uint32_t (&p)[32], uint64_t db, int full, int acc) {
  asm volatile("{\n.reg .pred q, s;\n.reg .b64 t;\nsetp.ne.b32 s, %98, 0;\nsetp.eq.b32 q, %97, 0;\n@q bra.uni LH;\n"
    "wgmma.fence.sync.aligned;\n"
    "add.s64 t, %96, 0;\nwgmma.mma_async.sync.aligned.m64n128k16.f32.bf16.bf16 {%0, %1, %2, %3, %4, %5, %6, %7, %8, %9, %10, %11, %12, %13, %14, %15, %16, %17, %18, %19, %20, %21, %22, %23, %24, %25, %26, %27, %28, %29, %30, %31, %32, %33, %34, %35, %36, %37, %38, %39, %40, %41, %42, %43, %44, %45, %46, %47, %48, %49, %50, %51, %52, %53, %54, %55, %56, %57, %58, %59, %60, %61, %62, %63}, {%64, %65, %66, %67}, t, s, 1, 1, 1;\n"
    "add.s64 t, %96, 256;\nwgmma.mma_async.sync.aligned.m64n128k16.f32.bf16.bf16 {%0, %1, %2, %3, %4, %5, %6, %7, %8, %9, %10, %11, %12, %13, %14, %15, %16, %17, %18, %19, %20, %21, %22, %23, %24, %25, %26, %27, %28, %29, %30, %31, %32, %33, %34, %35, %36, %37, %38, %39, %40, %41, %42, %43, %44, %45, %46, %47, %48, %49, %50, %51, %52, %53, %54, %55, %56, %57, %58, %59, %60, %61, %62, %63}, {%68, %69, %70, %71}, t, 1, 1, 1, 1;\n"
    "add.s64 t, %96, 512;\nwgmma.mma_async.sync.aligned.m64n128k16.f32.bf16.bf16 {%0, %1, %2, %3, %4, %5, %6, %7, %8, %9, %10, %11, %12, %13, %14, %15, %16, %17, %18, %19, %20, %21, %22, %23, %24, %25, %26, %27, %28, %29, %30, %31, %32, %33, %34, %35, %36, %37, %38, %39, %40, %41, %42, %43, %44, %45, %46, %47, %48, %49, %50, %51, %52, %53, %54, %55, %56, %57, %58, %59, %60, %61, %62, %63}, {%72, %73, %74, %75}, t, 1, 1, 1, 1;\n"
    "add.s64 t, %96, 768;\nwgmma.mma_async.sync.aligned.m64n128k16.f32.bf16.bf16 {%0, %1, %2, %3, %4, %5, %6, %7, %8, %9, %10, %11, %12, %13, %14, %15, %16, %17, %18, %19, %20, %21, %22, %23, %24, %25, %26, %27, %28, %29, %30, %31, %32, %33, %34, %35, %36, %37, %38, %39, %40, %41, %42, %43, %44, %45, %46, %47, %48, %49, %50, %51, %52, %53, %54, %55, %56, %57, %58, %59, %60, %61, %62, %63}, {%76, %77, %78, %79}, t, 1, 1, 1, 1;\n"
    "add.s64 t, %96, 1024;\nwgmma.mma_async.sync.aligned.m64n128k16.f32.bf16.bf16 {%0, %1, %2, %3, %4, %5, %6, %7, %8, %9, %10, %11, %12, %13, %14, %15, %16, %17, %18, %19, %20, %21, %22, %23, %24, %25, %26, %27, %28, %29, %30, %31, %32, %33, %34, %35, %36, %37, %38, %39, %40, %41, %42, %43, %44, %45, %46, %47, %48, %49, %50, %51, %52, %53, %54, %55, %56, %57, %58, %59, %60, %61, %62, %63}, {%80, %81, %82, %83}, t, 1, 1, 1, 1;\n"
    "add.s64 t, %96, 1280;\nwgmma.mma_async.sync.aligned.m64n128k16.f32.bf16.bf16 {%0, %1, %2, %3, %4, %5, %6, %7, %8, %9, %10, %11, %12, %13, %14, %15, %16, %17, %18, %19, %20, %21, %22, %23, %24, %25, %26, %27, %28, %29, %30, %31, %32, %33, %34, %35, %36, %37, %38, %39, %40, %41, %42, %43, %44, %45, %46, %47, %48, %49, %50, %51, %52, %53, %54, %55, %56, %57, %58, %59, %60, %61, %62, %63}, {%84, %85, %86, %87}, t, 1, 1, 1, 1;\n"
    "add.s64 t, %96, 1536;\nwgmma.mma_async.sync.aligned.m64n128k16.f32.bf16.bf16 {%0, %1, %2, %3, %4, %5, %6, %7, %8, %9, %10, %11, %12, %13, %14, %15, %16, %17, %18, %19, %20, %21, %22, %23, %24, %25, %26, %27, %28, %29, %30, %31, %32, %33, %34, %35, %36, %37, %38, %39, %40, %41, %42, %43, %44, %45, %46, %47, %48, %49, %50, %51, %52, %53, %54, %55, %56, %57, %58, %59, %60, %61, %62, %63}, {%88, %89, %90, %91}, t, 1, 1, 1, 1;\n"
    "add.s64 t, %96, 1792;\nwgmma.mma_async.sync.aligned.m64n128k16.f32.bf16.bf16 {%0, %1, %2, %3, %4, %5, %6, %7, %8, %9, %10, %11, %12, %13, %14, %15, %16, %17, %18, %19, %20, %21, %22, %23, %24, %25, %26, %27, %28, %29, %30, %31, %32, %33, %34, %35, %36, %37, %38, %39, %40, %41, %42, %43, %44, %45, %46, %47, %48, %49, %50, %51, %52, %53, %54, %55, %56, %57, %58, %59, %60, %61, %62, %63}, {%92, %93, %94, %95}, t, 1, 1, 1, 1;\n"
    "wgmma.commit_group.sync.aligned;\n"
    "bra.uni LE;\nLH:\n"
    "wgmma.fence.sync.aligned;\n"
    "add.s64 t, %96, 0;\nwgmma.mma_async.sync.aligned.m64n128k16.f32.bf16.bf16 {%0, %1, %2, %3, %4, %5, %6, %7, %8, %9, %10, %11, %12, %13, %14, %15, %16, %17, %18, %19, %20, %21, %22, %23, %24, %25, %26, %27, %28, %29, %30, %31, %32, %33, %34, %35, %36, %37, %38, %39, %40, %41, %42, %43, %44, %45, %46, %47, %48, %49, %50, %51, %52, %53, %54, %55, %56, %57, %58, %59, %60, %61, %62, %63}, {%80, %81, %82, %83}, t, s, 1, 1, 1;\n"
    "add.s64 t, %96, 256;\nwgmma.mma_async.sync.aligned.m64n128k16.f32.bf16.bf16 {%0, %1, %2, %3, %4, %5, %6, %7, %8, %9, %10, %11, %12, %13, %14, %15, %16, %17, %18, %19, %20, %21, %22, %23, %24, %25, %26, %27, %28, %29, %30, %31, %32, %33, %34, %35, %36, %37, %38, %39, %40, %41, %42, %43, %44, %45, %46, %47, %48, %49, %50, %51, %52, %53, %54, %55, %56, %57, %58, %59, %60, %61, %62, %63}, {%84, %85, %86, %87}, t, 1, 1, 1, 1;\n"
    "add.s64 t, %96, 512;\nwgmma.mma_async.sync.aligned.m64n128k16.f32.bf16.bf16 {%0, %1, %2, %3, %4, %5, %6, %7, %8, %9, %10, %11, %12, %13, %14, %15, %16, %17, %18, %19, %20, %21, %22, %23, %24, %25, %26, %27, %28, %29, %30, %31, %32, %33, %34, %35, %36, %37, %38, %39, %40, %41, %42, %43, %44, %45, %46, %47, %48, %49, %50, %51, %52, %53, %54, %55, %56, %57, %58, %59, %60, %61, %62, %63}, {%88, %89, %90, %91}, t, 1, 1, 1, 1;\n"
    "add.s64 t, %96, 768;\nwgmma.mma_async.sync.aligned.m64n128k16.f32.bf16.bf16 {%0, %1, %2, %3, %4, %5, %6, %7, %8, %9, %10, %11, %12, %13, %14, %15, %16, %17, %18, %19, %20, %21, %22, %23, %24, %25, %26, %27, %28, %29, %30, %31, %32, %33, %34, %35, %36, %37, %38, %39, %40, %41, %42, %43, %44, %45, %46, %47, %48, %49, %50, %51, %52, %53, %54, %55, %56, %57, %58, %59, %60, %61, %62, %63}, {%92, %93, %94, %95}, t, 1, 1, 1, 1;\n"
    "wgmma.commit_group.sync.aligned;\n"
    "LE:\n}\n"
    : "+f"(d[0]), "+f"(d[1]), "+f"(d[2]), "+f"(d[3]), "+f"(d[4]), "+f"(d[5]), "+f"(d[6]), "+f"(d[7]), "+f"(d[8]), "+f"(d[9]), "+f"(d[10]), "+f"(d[11]), "+f"(d[12]), "+f"(d[13]), "+f"(d[14]), "+f"(d[15]), "+f"(d[16]), "+f"(d[17]), "+f"(d[18]), "+f"(d[19]), "+f"(d[20]), "+f"(d[21]), "+f"(d[22]), "+f"(d[23]), "+f"(d[24]), "+f"(d[25]), "+f"(d[26]), "+f"(d[27]), "+f"(d[28]), "+f"(d[29]), "+f"(d[30]), "+f"(d[31]), "+f"(d[32]), "+f"(d[33]), "+f"(d[34]), "+f"(d[35]), "+f"(d[36]), "+f"(d[37]), "+f"(d[38]), "+f"(d[39]), "+f"(d[40]), "+f"(d[41]), "+f"(d[42]), "+f"(d[43]), "+f"(d[44]), "+f"(d[45]), "+f"(d[46]), "+f"(d[47]), "+f"(d[48]), "+f"(d[49]), "+f"(d[50]), "+f"(d[51]), "+f"(d[52]), "+f"(d[53]), "+f"(d[54]), "+f"(d[55]), "+f"(d[56]), "+f"(d[57]), "+f"(d[58]), "+f"(d[59]), "+f"(d[60]), "+f"(d[61]), "+f"(d[62]), "+f"(d[63])
    : "r"(p[0]), "r"(p[1]), "r"(p[2]), "r"(p[3]), "r"(p[4]), "r"(p[5]), "r"(p[6]), "r"(p[7]), "r"(p[8]), "r"(p[9]), "r"(p[10]), "r"(p[11]), "r"(p[12]), "r"(p[13]), "r"(p[14]), "r"(p[15]), "r"(p[16]), "r"(p[17]), "r"(p[18]), "r"(p[19]), "r"(p[20]), "r"(p[21]), "r"(p[22]), "r"(p[23]), "r"(p[24]), "r"(p[25]), "r"(p[26]), "r"(p[27]), "r"(p[28]), "r"(p[29]), "r"(p[30]), "r"(p[31]), "l"(db), "r"(full), "r"(acc) : "memory");
}

constexpr int NCTA = 132, NREG = 128;
constexpr int UNIT = 16384, NUNIT = 14;
constexpr uint32_t SMEM_BASE = 1024;
constexpr int SM_BAR = NUNIT * UNIT;
constexpr int SM_GATE = SM_BAR + 1024;
constexpr int SMEM_BYTES = SM_BAR + 1536;
constexpr int UPITCH = 4160, UCH = 2 * UPITCH;
constexpr float QSCALE = 0.08838834764831845f * 1.4426950408889634f;
constexpr float BOUND2 = 48.f * 48.f / 1.15f;
#define CONV_REG 6
constexpr int CONV_EXTRA = (1024 - NREG * CONV_REG) / (NCTA - NREG);
constexpr int CH_EXTRA_TOTAL = CONV_EXTRA * (NCTA - NREG);
constexpr int C_KV = 0;
constexpr int C_CTX = 32;
constexpr int C_U = 48;
constexpr int C_Z = 80;
constexpr int C_GATE = 88;
constexpr int C_EXIT = 89;
[[maybe_unused]] constexpr int C_GO = 90;
#define PRE_EARLY 1
#define PRE_HALF 1
#define ATT_SPLIT 6
#define EF 127
#define POL(bit) (((EF >> (bit)) & 1) != 0)
constexpr int C_WAR = 96;
constexpr int C_NUM = 112;
constexpr int CSTRIDE = 32;
constexpr int SM_KMAX = SM_BAR + 640, SM_DUMMY = SM_BAR + 648, SM_EXIT = SM_BAR + 272, SM_PRE = SM_BAR + 280, SM_SIG = SM_BAR + 320, SM_RDY = SM_BAR + 448;
enum { SIG_KV = 0, SIG_CTX = 2, SIG_Z = 4, SIG_DONE = 8, SIG_WAR = 9, SIG_ATT = 10 };
enum { RDY_KV = 0, RDY_CTX = 2, RDY_U = 4, RDY_Z = 5, RDY_WAR = 6, RDY_G = 7 };
enum { PH_PRE = 1, PH_KV = 2, PH_ATT = 4, PH_CONV = 8, PH_OUT = 16, PH_ALL = 31 };

constexpr uint32_t T_CTX = 0, T_KV = 16 * 32 * 32768, T_BYTES = T_KV + 32 * 16 * 65536;
__device__ __align__(1024) uint8_t g_T[T_BYTES];
__device__ __align__(1024) uint8_t g_u[1024 * UCH];
__device__ __align__(1024) __nv_bfloat16 g_z[1024 * 2048];
__device__ __align__(1024) float g_gate[2048];
__device__ __align__(1024) float g_kn2[32 * 128];
__device__ __align__(1024) unsigned g_cnt[C_NUM * CSTRIDE];

struct __align__(64) Maps { CUtensorMap x, c, wq, wk, wv, wo, h, z, out, ctx, k, v; };
struct Params {
  const __nv_bfloat16 *x, *shift, *D, *gw;
};

__device__ __forceinline__ void wg_fence() { asm volatile("wgmma.fence.sync.aligned;" ::: "memory"); }
__device__ __forceinline__ void wg_commit() { asm volatile("wgmma.commit_group.sync.aligned;" ::: "memory"); }
template<int N> __device__ __forceinline__ void wg_wait() { asm volatile("wgmma.wait_group.sync.aligned %0;" :: "n"(N) : "memory"); }
__device__ __forceinline__ uint64_t odesc(uint32_t addr, uint32_t lbo, uint32_t sbo, uint32_t swz) {
  uint64_t d = (uint64_t)(addr >> 4) + (((uint64_t)(lbo >> 4) << 16) | ((uint64_t)(sbo >> 4) << 32) | ((uint64_t)swz << 62));
  asm volatile("" : "+l"(d));
  return d;
}
__device__ __forceinline__ void mbar_init(uint32_t bar, int cnt) { asm volatile("mbarrier.init.shared::cta.b64 [%0], %1;" :: "r"(bar), "r"(cnt)); }
__device__ __forceinline__ void mbar_expect(uint32_t bar, uint32_t bytes) { asm volatile("mbarrier.arrive.expect_tx.shared::cta.b64 _, [%0], %1;" :: "r"(bar), "r"(bytes) : "memory"); }
__device__ __forceinline__ void mbar_arrive(uint32_t bar) { asm volatile("mbarrier.arrive.shared::cta.b64 _, [%0];" :: "r"(bar) : "memory"); }
__device__ __forceinline__ void mbar_arrive_n(uint32_t bar, int n) { asm volatile("mbarrier.arrive.shared::cta.b64 _, [%0], %1;" :: "r"(bar), "r"(n) : "memory"); }
__device__ __forceinline__ void mbar_wait(uint32_t bar, uint32_t parity) {
  asm volatile("{\n.reg .pred p;\nLW:\nmbarrier.try_wait.parity.shared::cta.b64 p, [%0], %1;\n@!p bra LW;\n}\n" :: "r"(bar), "r"(parity) : "memory");
}
__device__ __forceinline__ void mbar_wait_slow(uint32_t bar, uint32_t parity) {
  asm volatile("{\n.reg .pred p;\n.reg .u32 n;\nmov.u32 n, 0;\n"
    "LW:\nmbarrier.test_wait.parity.shared::cta.b64 p, [%0], %1;\n@p bra LD;\n"
    "nanosleep.u32 128;\nadd.u32 n, n, 1;\nsetp.lt.u32 p, n, 4194304;\n@p bra LW;\ntrap;\nLD:\n}\n" :: "r"(bar), "r"(parity) : "memory");
}
__device__ __forceinline__ void mbar_wait_all(uint32_t bar, uint32_t parity) {
  asm volatile("{\n.reg .pred p, q;\nLW:\nmbarrier.try_wait.parity.shared::cta.b64 p, [%0], %1;\nvote.sync.all.pred q, p, 0xffffffff;\n@!q bra.uni LW;\n}\n" :: "r"(bar), "r"(parity) : "memory");
}
__device__ __forceinline__ void cnt_wait(const unsigned* p, unsigned target) {
  asm volatile("{\n.reg .pred p;\n.reg .u32 n, v;\nmov.u32 n, 0;\n"
    "LW:\nld.relaxed.gpu.global.u32 v, [%0];\nsetp.ge.u32 p, v, %1;\n@p bra LD;\n"
    "nanosleep.u32 64;\nadd.u32 n, n, 1;\nsetp.lt.u32 p, n, 4194304;\n@p bra LW;\ntrap;\nLD:\nfence.acq_rel.gpu;\nfence.proxy.async;\n}\n" :: "l"(p), "r"(target) : "memory");
}
__device__ __forceinline__ void cnt_signal(unsigned* p, int lane) {
  __syncwarp();
  if (lane == 0) asm volatile("red.release.gpu.global.add.u32 [%0], 1;" :: "l"(p) : "memory");
}
__device__ __forceinline__ void cnt_publish(unsigned* p, unsigned n) {
  asm volatile("fence.acq_rel.gpu;\nred.relaxed.gpu.global.add.u32 [%0], %1;" :: "l"(p), "r"(n) : "memory");
}
__device__ __forceinline__ uint64_t pol_first() { uint64_t p; asm("createpolicy.fractional.L2::evict_first.b64 %0, 1.0;" : "=l"(p)); return p; }
__device__ __forceinline__ void bulk_g2s(uint32_t dst, const void* src, uint32_t bytes, uint32_t bar, bool stream = false) {
  if (stream) asm volatile("cp.async.bulk.shared::cluster.global.mbarrier::complete_tx::bytes.L2::cache_hint [%0], [%1], %2, [%3], %4;" :: "r"(dst), "l"(src), "r"(bytes), "r"(bar), "l"(pol_first()) : "memory");
  else asm volatile("cp.async.bulk.shared::cluster.global.mbarrier::complete_tx::bytes [%0], [%1], %2, [%3];" :: "r"(dst), "l"(src), "r"(bytes), "r"(bar) : "memory");
}
__device__ __forceinline__ void tma2d(uint32_t dst, const CUtensorMap* m, int x, int y, uint32_t bar, bool stream = false) {
  if (stream) asm volatile("cp.async.bulk.tensor.2d.shared::cluster.global.mbarrier::complete_tx::bytes.L2::cache_hint [%0], [%1, {%3, %4}], [%2], %5;" :: "r"(dst), "l"(m), "r"(bar), "r"(x), "r"(y), "l"(pol_first()) : "memory");
  else asm volatile("cp.async.bulk.tensor.2d.shared::cluster.global.mbarrier::complete_tx::bytes [%0], [%1, {%3, %4}], [%2];" :: "r"(dst), "l"(m), "r"(bar), "r"(x), "r"(y) : "memory");
}
__device__ __forceinline__ void tma3d(uint32_t dst, const CUtensorMap* m, int x, int y, int z, uint32_t bar, bool stream = false) {
  if (stream) asm volatile("cp.async.bulk.tensor.3d.shared::cluster.global.mbarrier::complete_tx::bytes.L2::cache_hint [%0], [%1, {%3, %4, %5}], [%2], %6;" :: "r"(dst), "l"(m), "r"(bar), "r"(x), "r"(y), "r"(z), "l"(pol_first()) : "memory");
  else asm volatile("cp.async.bulk.tensor.3d.shared::cluster.global.mbarrier::complete_tx::bytes [%0], [%1, {%3, %4, %5}], [%2];" :: "r"(dst), "l"(m), "r"(bar), "r"(x), "r"(y), "r"(z) : "memory");
}
__device__ __forceinline__ void tma4d(uint32_t dst, const CUtensorMap* m, int x, int y, int z, int w, uint32_t bar, bool stream = false) {
  if (stream) asm volatile("cp.async.bulk.tensor.4d.shared::cluster.global.mbarrier::complete_tx::bytes.L2::cache_hint [%0], [%1, {%3, %4, %5, %6}], [%2], %7;" :: "r"(dst), "l"(m), "r"(bar), "r"(x), "r"(y), "r"(z), "r"(w), "l"(pol_first()) : "memory");
  else asm volatile("cp.async.bulk.tensor.4d.shared::cluster.global.mbarrier::complete_tx::bytes [%0], [%1, {%3, %4, %5, %6}], [%2];" :: "r"(dst), "l"(m), "r"(bar), "r"(x), "r"(y), "r"(z), "r"(w) : "memory");
}
__device__ __forceinline__ void bulk_g2s_mc(uint32_t dst, const void* src, uint32_t bytes, uint32_t bar, bool stream = false) {
  if (stream) asm volatile("cp.async.bulk.shared::cluster.global.mbarrier::complete_tx::bytes.multicast::cluster.L2::cache_hint [%0], [%1], %2, [%3], %4, %5;" :: "r"(dst), "l"(src), "r"(bytes), "r"(bar), "h"((uint16_t)3), "l"(pol_first()) : "memory");
  else asm volatile("cp.async.bulk.shared::cluster.global.mbarrier::complete_tx::bytes.multicast::cluster [%0], [%1], %2, [%3], %4;" :: "r"(dst), "l"(src), "r"(bytes), "r"(bar), "h"((uint16_t)3) : "memory");
}
__device__ __forceinline__ void tma2d_mc(uint32_t dst, const CUtensorMap* m, int x, int y, uint32_t bar, bool stream = false) {
  if (stream) asm volatile("cp.async.bulk.tensor.2d.shared::cluster.global.mbarrier::complete_tx::bytes.multicast::cluster.L2::cache_hint [%0], [%1, {%3, %4}], [%2], %5, %6;" :: "r"(dst), "l"(m), "r"(bar), "r"(x), "r"(y), "h"((uint16_t)3), "l"(pol_first()) : "memory");
  else asm volatile("cp.async.bulk.tensor.2d.shared::cluster.global.mbarrier::complete_tx::bytes.multicast::cluster [%0], [%1, {%3, %4}], [%2], %5;" :: "r"(dst), "l"(m), "r"(bar), "r"(x), "r"(y), "h"((uint16_t)3) : "memory");
}
__device__ __forceinline__ void tma3d_mc(uint32_t dst, const CUtensorMap* m, int x, int y, int z, uint32_t bar, bool stream = false) {
  if (stream) asm volatile("cp.async.bulk.tensor.3d.shared::cluster.global.mbarrier::complete_tx::bytes.multicast::cluster.L2::cache_hint [%0], [%1, {%3, %4, %5}], [%2], %6, %7;" :: "r"(dst), "l"(m), "r"(bar), "r"(x), "r"(y), "r"(z), "h"((uint16_t)3), "l"(pol_first()) : "memory");
  else asm volatile("cp.async.bulk.tensor.3d.shared::cluster.global.mbarrier::complete_tx::bytes.multicast::cluster [%0], [%1, {%3, %4, %5}], [%2], %6;" :: "r"(dst), "l"(m), "r"(bar), "r"(x), "r"(y), "r"(z), "h"((uint16_t)3) : "memory");
}
__device__ __forceinline__ void tma2d_store(const CUtensorMap* m, uint32_t src, int x, int y) {
  asm volatile("cp.async.bulk.tensor.2d.global.shared::cta.bulk_group [%0, {%2, %3}], [%1];" :: "l"(m), "r"(src), "r"(x), "r"(y) : "memory");
}
__device__ __forceinline__ bool elect() {
  uint32_t r; asm volatile("{\n.reg .pred p;\nelect.sync _|p, 0xffffffff;\nselp.u32 %0, 1, 0, p;\n}\n" : "=r"(r)); return r != 0;
}
__device__ __forceinline__ void cluster_arrive() { asm volatile("barrier.cluster.arrive;" ::: "memory"); }
__device__ __forceinline__ void cluster_wait() { asm volatile("barrier.cluster.wait;" ::: "memory"); }
__device__ __forceinline__ void bar_sync(int id, int n) { asm volatile("bar.sync %0, %1;" :: "r"(id), "r"(n) : "memory"); }
__device__ __forceinline__ void bar_arrive(int id, int n) { asm volatile("bar.arrive %0, %1;" :: "r"(id), "r"(n) : "memory"); }
__device__ __forceinline__ int bar_and(int id, int n, int pred) {
  int r; asm volatile("{\n.reg .pred p, q;\nsetp.ne.b32 p, %3, 0;\nbar.red.and.pred q, %1, %2, p;\nselp.b32 %0, 1, 0, q;\n}\n" : "=r"(r) : "r"(id), "r"(n), "r"(pred) : "memory");
  return r;
}
__device__ __forceinline__ void fence_async_smem() { asm volatile("fence.proxy.async.shared::cta;" ::: "memory"); }
__device__ __forceinline__ float ex2(float x) { float y; asm("ex2.approx.ftz.f32 %0, %1;" : "=f"(y) : "f"(x)); return y; }
__device__ __forceinline__ uint32_t pack_bf16(float lo, float hi) { uint32_t r; asm("cvt.rn.bf16x2.f32 %0, %1, %2;" : "=r"(r) : "f"(hi), "f"(lo)); return r; }
__device__ __forceinline__ uint32_t hmul2(uint32_t a, uint32_t b) { uint32_t r; asm("mul.rn.bf16x2 %0, %1, %2;" : "=r"(r) : "r"(a), "r"(b)); return r; }
__device__ __forceinline__ uint32_t hadd2(uint32_t a, uint32_t b) { uint32_t r; asm("add.rn.bf16x2 %0, %1, %2;" : "=r"(r) : "r"(a), "r"(b)); return r; }
__device__ __forceinline__ uint32_t hfma2(uint32_t a, uint32_t b, uint32_t c) { uint32_t r; asm("fma.rn.bf16x2 %0, %1, %2, %3;" : "=r"(r) : "r"(a), "r"(b), "r"(c)); return r; }
__device__ __forceinline__ float bf_lo(uint32_t a) { return __uint_as_float(a << 16); }
__device__ __forceinline__ float bf_hi(uint32_t a) { return __uint_as_float(a & 0xffff0000u); }
__device__ __forceinline__ uint32_t lds32(uint32_t a) { uint32_t v; asm volatile("ld.shared.u32 %0, [%1];" : "=r"(v) : "r"(a) : "memory"); return v; }
__device__ __forceinline__ float2 lds64f(uint32_t a) { float2 v; asm volatile("ld.shared.v2.f32 {%0,%1}, [%2];" : "=f"(v.x), "=f"(v.y) : "r"(a) : "memory"); return v; }
__device__ __forceinline__ uint4 lds128(uint32_t a) { uint4 v; asm volatile("ld.shared.v4.u32 {%0,%1,%2,%3}, [%4];" : "=r"(v.x), "=r"(v.y), "=r"(v.z), "=r"(v.w) : "r"(a) : "memory"); return v; }
__device__ __forceinline__ void sts64f(uint32_t a, float x, float y) { asm volatile("st.shared.v2.f32 [%0], {%1,%2};" :: "r"(a), "f"(x), "f"(y) : "memory"); }
__device__ __forceinline__ void sts128(uint32_t a, uint4 v) { asm volatile("st.shared.v4.u32 [%0], {%1,%2,%3,%4};" :: "r"(a), "r"(v.x), "r"(v.y), "r"(v.z), "r"(v.w) : "memory"); }
template<int OFF> __device__ __forceinline__ void sts128o(uint32_t a, uint4 v) { asm volatile("st.shared.v4.u32 [%0+%5], {%1,%2,%3,%4};" :: "r"(a), "r"(v.x), "r"(v.y), "r"(v.z), "r"(v.w), "n"(OFF) : "memory"); }
__device__ __forceinline__ void ldsm4(uint32_t a, uint32_t& r0, uint32_t& r1, uint32_t& r2, uint32_t& r3) {
  asm volatile("ldmatrix.sync.aligned.m8n8.x4.shared.b16 {%0,%1,%2,%3}, [%4];" : "=r"(r0), "=r"(r1), "=r"(r2), "=r"(r3) : "r"(a) : "memory");
}
__device__ __forceinline__ void ldsm4t(uint32_t a, uint32_t& r0, uint32_t& r1, uint32_t& r2, uint32_t& r3) {
  asm volatile("ldmatrix.sync.aligned.m8n8.x4.trans.shared.b16 {%0,%1,%2,%3}, [%4];" : "=r"(r0), "=r"(r1), "=r"(r2), "=r"(r3) : "r"(a) : "memory");
}
__device__ __forceinline__ void stsm4(uint32_t a, uint32_t r0, uint32_t r1, uint32_t r2, uint32_t r3) {
  asm volatile("stmatrix.sync.aligned.m8n8.x4.shared.b16 [%0], {%1,%2,%3,%4};" :: "r"(a), "r"(r0), "r"(r1), "r"(r2), "r"(r3) : "memory");
}
template<int N> __device__ __forceinline__ void fence_regs(float (&d)[N]) {
#pragma unroll
  for (int i = 0; i < N; i++) asm volatile("" : "+f"(d[i]) :: "memory");
}
template<int N> __device__ __forceinline__ void fence_regs(uint32_t (&d)[N]) {
#pragma unroll
  for (int i = 0; i < N; i++) asm volatile("" : "+r"(d[i]) :: "memory");
}
__device__ __forceinline__ void sched_fence(float x, uint32_t dummy) {
  asm volatile("{\n.reg .pred p;\nsetp.eq.u32 p, %0, 0x7fc12345;\n@p st.shared.u32 [%1], %0;\n}\n" :: "r"(__float_as_uint(x)), "r"(dummy) : "memory");
}
#define TS(role, i)
#define TSA(i)
#define TR(obj, role, tag)

struct Prod {
  uint32_t base, mask; int lane, nt;
  __device__ __forceinline__ uint32_t full(int u) const { return base + SM_BAR + 8 * u; }
  __device__ __forceinline__ uint32_t addr(int u) const { return base + u * UNIT; }
  __device__ __forceinline__ void acquire(int u, int n) {
    const int v = u + min(lane, n - 1);
    mbar_wait_all(base + SM_BAR + 128 + 8 * v, mask >> v);
    mask ^= ((1u << n) - 1) << u;
    TR(*this, 2, 16 + u);
  }
  __device__ __forceinline__ void acquire_slow(int u, int n) {
    for (int i = 0; i < n; i++) mbar_wait_slow(base + SM_BAR + 128 + 8 * (u + i), mask >> (u + i));
    mask ^= ((1u << n) - 1) << u;
  }
};
struct Cons {
  uint32_t base, rel, mask; int lane, warp, wg, nt;
  __device__ __forceinline__ uint32_t addr(int u) const { return base + u * UNIT; }
  __device__ __forceinline__ static uint32_t daddr(int u) { return SMEM_BASE + u * UNIT; }
  __device__ __forceinline__ void wait(int u) { TR(*this, wg, 1); mbar_wait(base + SM_BAR + 8 * u, mask >> u); mask ^= 1u << u; TR(*this, wg, 2); }
  __device__ __forceinline__ void skip(int u) { mask ^= 1u << u; }
  __device__ __forceinline__ void release(int u, int n) {
    TR(*this, wg, 5);
    asm volatile("{\n.reg .pred p;\nsetp.lt.s32 p, %1, %2;\n@p mbarrier.arrive.shared::cluster.b64 _, [%0];\n}\n" :: "r"(rel + 8 * u), "r"(lane & 15), "r"(n) : "memory");
  }
  __device__ __forceinline__ void release2(int u) {
    asm volatile("{\n.reg .pred p;\nsetp.eq.s32 p, %1, 0;\n@p mbarrier.arrive.shared::cluster.b64 _, [%0], 2;\n}\n" :: "r"(rel + 8 * u), "r"(lane & 15) : "memory");
  }
  __device__ __forceinline__ void signal(int i) {
    __syncwarp();
    asm volatile("{\n.reg .pred p;\nsetp.eq.s32 p, %1, 0;\n@p mbarrier.arrive.shared::cta.b64 _, [%0];\n}\n" :: "r"(base + SM_SIG + 8 * i), "r"(lane) : "memory");
  }
  __device__ __forceinline__ void turn() { bar_sync(1 + wg, 256); TR(*this, wg, 3); }
  __device__ __forceinline__ void pass() { bar_arrive(2 - wg, 256); TR(*this, wg, 4); }
};
__device__ __forceinline__ int gemm_unit(int ks) { return 3 * (ks & 3); }
__device__ __forceinline__ int att_slot(int i) { return 4 + 2 * i; }
template<int MASK> __device__ __forceinline__ int kv_slot(int h) { return MASK == PH_ALL ? h & 15 : h; }
__device__ __forceinline__ int out_mb(int cta) { return cta >> 3; }
__device__ __forceinline__ int out_nb(int cta) { return cta & 7; }
__device__ __forceinline__ int conv_channel(int cta, int i) {
  return cta < NREG ? CH_EXTRA_TOTAL + cta * CONV_REG + i : (i >> 1) * 8 + (cta - NREG) * 2 + (i & 1);
}

template<int OFF, int N> __device__ __forceinline__ void pack_chunk(const float (&a)[N], float sc0, float sc1, uint4& v0, uint4& v1) {
  v0.x = pack_bf16(a[OFF + 0] * sc0, a[OFF + 1] * sc0); v0.y = pack_bf16(a[OFF + 4] * sc0, a[OFF + 5] * sc0);
  v0.z = pack_bf16(a[OFF + 8] * sc0, a[OFF + 9] * sc0); v0.w = pack_bf16(a[OFF + 12] * sc0, a[OFF + 13] * sc0);
  v1.x = pack_bf16(a[OFF + 2] * sc1, a[OFF + 3] * sc1); v1.y = pack_bf16(a[OFF + 6] * sc1, a[OFF + 7] * sc1);
  v1.z = pack_bf16(a[OFF + 10] * sc1, a[OFF + 11] * sc1); v1.w = pack_bf16(a[OFF + 14] * sc1, a[OFF + 15] * sc1);
}
template<int OFF, int N> __device__ __forceinline__ void pack_chunk(const float (&a)[N], uint4& v0, uint4& v1) {
  v0.x = pack_bf16(a[OFF + 0], a[OFF + 1]); v0.y = pack_bf16(a[OFF + 4], a[OFF + 5]);
  v0.z = pack_bf16(a[OFF + 8], a[OFF + 9]); v0.w = pack_bf16(a[OFF + 12], a[OFF + 13]);
  v1.x = pack_bf16(a[OFF + 2], a[OFF + 3]); v1.y = pack_bf16(a[OFF + 6], a[OFF + 7]);
  v1.z = pack_bf16(a[OFF + 10], a[OFF + 11]); v1.w = pack_bf16(a[OFF + 14], a[OFF + 15]);
}
__device__ __forceinline__ void sq_acc(const uint4& v, uint32_t& a) { a = hfma2(v.x, v.x, a); a = hfma2(v.y, v.y, a); a = hfma2(v.z, v.z, a); a = hfma2(v.w, v.w, a); }
__device__ __forceinline__ float norm2_max(uint32_t a0, uint32_t a1) {
  float n0 = bf_lo(a0) + bf_hi(a0), n1 = bf_lo(a1) + bf_hi(a1);
  n0 += __shfl_xor_sync(~0u, n0, 1); n1 += __shfl_xor_sync(~0u, n1, 1);
  n0 += __shfl_xor_sync(~0u, n0, 2); n1 += __shfl_xor_sync(~0u, n1, 2);
  return __uint_as_float(__reduce_max_sync(~0u, max(__float_as_uint(n0) & 0x7fffffffu, __float_as_uint(n1) & 0x7fffffffu)));
}

struct Pend { uint4 lo[8], hi[8]; uint32_t dst; float kn; };
__device__ __forceinline__ void pin(uint4 (&v)[8]) {
#pragma unroll
  for (int i = 0; i < 8; i++) asm volatile("" : "+r"(v[i].x), "+r"(v[i].y), "+r"(v[i].z), "+r"(v[i].w) :: "memory");
}
__device__ __forceinline__ uint32_t atom_off(int lane) { return (lane >> 2) * 64 + (((lane ^ (lane >> 3)) & 3) << 4); }
template<int J0, int J1> __device__ __forceinline__ void tile_store(const uint4 (&v)[8], uint32_t dst, int lane) {
  uint8_t* d = g_T + (dst + atom_off(lane));
#pragma unroll
  for (int j = J0; j < J1; j++) { *(uint4*)(d + j * 512) = v[2 * j]; *(uint4*)(d + j * 512 + 2048) = v[2 * j + 1]; }
}
__device__ __forceinline__ float tile_norm2(const uint4 (&v)[8]) {
  uint32_t n0 = 0, n1 = 0;
#pragma unroll
  for (int j = 0; j < 4; j++) { sq_acc(v[2 * j], n0); sq_acc(v[2 * j + 1], n1); }
  return norm2_max(n0, n1);
}
template<int PART> __device__ __forceinline__ void out_part(Cons& c, Pend& w) {
  if (PART == 0) { w.kn = tile_norm2(w.lo); tile_store<0, 2>(w.lo, w.dst, c.lane); }
  if (PART == 1) tile_store<2, 4>(w.lo, w.dst, c.lane);
  if (PART == 2) {
    const float vn = tile_norm2(w.hi);
    if (c.lane == 0) g_kn2[((w.dst - T_KV) >> 16) * 8 + c.wg * 4 + c.warp] = (vn <= 1.0e30f && vn >= 1.0e-30f) ? w.kn : __uint_as_float(0x7f800000u);
    tile_store<0, 2>(w.hi, w.dst + 32768, c.lane);
  }
  if (PART == 3) tile_store<2, 4>(w.hi, w.dst + 32768, c.lane);
}
template<bool FIRST> __device__ __forceinline__ void kv_issue(Cons& c, float (&acc)[128], int u) {
  const uint64_t da = odesc(c.daddr(u) + c.wg * 8192, 16, 1024, 1), db = odesc(c.daddr(u + 1), 8192, 1024, 1);
  c.turn();
  wg_fence();
#pragma unroll
  for (int kk = 0; kk < 4; kk++) wgmma_ss_n256<1>(acc, da + kk * 2, db + kk * 128, !(FIRST && kk == 0));
  wg_commit();
  c.pass();
}
__device__ __forceinline__ void cons_kv(Cons& c, int h, int hs, int g, Pend& w, bool pend_o) {
#pragma unroll 1
  for (int tile = 0; tile < 2; tile++) {
    float acc[128];
    c.wait(0);
    kv_issue<true>(c, acc, 0);
    if (tile == 1 && pend_o) mbar_wait(c.base + SM_RDY + 8 * RDY_WAR, 0);
    if (tile == 1 || pend_o) out_part<0>(c, w);
#pragma unroll 1
    for (int ks = 1; ks < 8; ks++) {
      if (ks == 3 && (tile == 1 || pend_o)) { out_part<1>(c, w); if (tile == 0) c.signal(SIG_CTX); }
      if (ks == 5 && tile == 1) out_part<2>(c, w);
      if (ks == 7 && tile == 1) out_part<3>(c, w);
      const int u = gemm_unit(ks);
      c.wait(u);
      wg_wait<0>();
      c.release(gemm_unit(ks - 1), 3);
      kv_issue<false>(c, acc, u);
    }
    wg_wait<0>(); fence_regs(acc);
    c.release(9, 3);
    pack_chunk<0>(acc, w.lo[0], w.lo[1]);  pack_chunk<16>(acc, w.lo[2], w.lo[3]); pack_chunk<32>(acc, w.lo[4], w.lo[5]); pack_chunk<48>(acc, w.lo[6], w.lo[7]);
    pack_chunk<64>(acc, w.hi[0], w.hi[1]); pack_chunk<80>(acc, w.hi[2], w.hi[3]); pack_chunk<96>(acc, w.hi[4], w.hi[5]); pack_chunk<112>(acc, w.hi[6], w.hi[7]);
    pin(w.lo); pin(w.hi);
    w.dst = T_KV + (hs * 16 + 2 * g + tile) * 65536 + (c.wg * 4 + c.warp) * 4096;
  }
}
template<bool FIRST> __device__ __forceinline__ void q_issue(Cons& c, float (&a)[64], float (&b)[64], int u) {
  const uint64_t da = odesc(c.daddr(u) + c.wg * 8192, 16, 1024, 1), db = odesc(c.daddr(u + 2), 8192, 1024, 1);
  const uint64_t da2 = odesc(c.daddr(u + 1) + (1 - c.wg) * 8192, 16, 1024, 1);
  c.turn();
  wg_fence();
#pragma unroll
  for (int kk = 0; kk < 4; kk++) wgmma_ss_n128<1>(a, da + kk * 2, db + kk * 128, !(FIRST && kk == 0));
#pragma unroll
  for (int kk = 0; kk < 4; kk++) wgmma_ss_n128<1>(b, da2 + kk * 2, db + kk * 128, !(FIRST && kk == 0));
  wg_commit();
  c.pass();
}
template<bool PEND_KV> __device__ __forceinline__ int cons_q(Cons& c, int h, Pend& w) {
  float a[64], b[64];
  c.wait(0);
  q_issue<true>(c, a, b, 0);
  if (PEND_KV) out_part<0>(c, w);
#pragma unroll 1
  for (int ks = 1; ks < 16; ks++) {
    if (PEND_KV) {
      if (ks == 2) out_part<1>(c, w);
      if (ks == 4) out_part<2>(c, w);
      if (ks == 5) { out_part<3>(c, w); c.signal(SIG_KV + (h >> 4)); }
    }
    const int u = gemm_unit(ks);
    c.wait(u);
    wg_wait<0>();
    c.release(gemm_unit(ks - 1), 3);
    q_issue<false>(c, a, b, u);
  }
  c.wait(0);
  wg_wait<0>(); fence_regs(a); fence_regs(b);
  c.release(9, 3);
  const uint32_t q0 = c.addr(0) + (c.wg * 4 + c.warp) * 4096 + atom_off(c.lane);
  uint32_t a0 = 0, a1 = 0, e0 = 0, e1 = 0;
  uint4 v0, v1;
#define Q_CHUNK(J) pack_chunk<16 * J>(a, QSCALE, QSCALE, v0, v1); sts128o<J * 512>(q0, v0); sts128o<J * 512 + 2048>(q0, v1); sq_acc(v0, a0); sq_acc(v1, a1); \
  pack_chunk<16 * J>(b, QSCALE, QSCALE, v0, v1); sts128o<32768 + J * 512>(q0, v0); sts128o<32768 + J * 512 + 2048>(q0, v1); sq_acc(v0, e0); sq_acc(v1, e1);
  Q_CHUNK(0) Q_CHUNK(1) Q_CHUNK(2) Q_CHUNK(3)
#undef Q_CHUNK
  TR(c, c.wg, 40);
  fence_async_smem();
  const float qa = norm2_max(a0, a1), qb = norm2_max(e0, e1);
  const float kn = __uint_as_float(lds32(c.base + SM_KMAX + 4 * (h >> 4)));
  TR(c, c.wg, 42);
  return __shfl_sync(~0u, bar_and(3 + c.wg, 128, (qa * kn <= BOUND2) && (qb * kn <= BOUND2)), 0);
}

__device__ __forceinline__ void issue_qk(float (&s)[64], uint64_t da, uint64_t db) {
#pragma unroll
  for (int kk = 0; kk < 8; kk++) wgmma_ss_n128<0>(s, da + (kk >> 1) * 32 + (kk & 1) * 2, db + (kk >> 1) * 32 + (kk & 1) * 2, kk > 0);
  wg_commit();
}
template<int A, int B> __device__ __forceinline__ void exp_rng(float (&s)[64]) {
#pragma unroll
  for (int i = 4 * A; i < 4 * B; i++) s[i] = ex2(s[i]);
}
template<int A, int B> __device__ __forceinline__ void sum_rng(const float (&s)[64], float (&l)[4]) {
#pragma unroll
  for (int i = A; i < B; i++) { l[0] += s[4 * i]; l[1] += s[4 * i + 1]; l[2] += s[4 * i + 2]; l[3] += s[4 * i + 3]; }
}
template<int A, int B> __device__ __forceinline__ void cvt_p(const float (&s)[64], uint32_t (&p)[32]) {
#pragma unroll
  for (int i = 2 * A; i < 2 * B; i++) p[i] = pack_bf16(s[2 * i], s[2 * i + 1]);
}
template<int K0> __device__ __forceinline__ void mask_half(float (&s)[64], int warp, int lane) {
  const int l0 = warp + (2 * (lane & 3) <= (lane >> 2)), l1 = warp + (2 * (lane & 3) < (lane >> 2));
#pragma unroll
  for (int k = 0; k < 4; k++) {
    float* t = s + 8 * (K0 + k);
    if (k >= l0) { t[0] = -INFINITY; t[6] = -INFINITY; }
    if (k >= l1) { t[1] = -INFINITY; t[7] = -INFINITY; }
    if (k > warp) { t[2] = -INFINITY; t[3] = -INFINITY; }
    if (k >= warp) { t[4] = -INFINITY; t[5] = -INFINITY; }
  }
}
__device__ __forceinline__ void row_inv(float& l0, float& l1) {
  l0 += __shfl_xor_sync(~0u, l0, 1); l1 += __shfl_xor_sync(~0u, l1, 1);
  l0 += __shfl_xor_sync(~0u, l0, 2); l1 += __shfl_xor_sync(~0u, l1, 2);
  l0 = __fdividef(1.f, l0); l1 = __fdividef(1.f, l1);
}
__device__ __forceinline__ void pack_o(const float (&o)[64], float i0, float i1, uint4 (&v)[8]) {
  pack_chunk<0>(o, i0, i1, v[0], v[1]); pack_chunk<16>(o, i0, i1, v[2], v[3]);
  pack_chunk<32>(o, i0, i1, v[4], v[5]); pack_chunk<48>(o, i0, i1, v[6], v[7]);
  pin(v);
}
__device__ __forceinline__ void softmax_safe(float (&s)[64], bool upper_only, float& m0, float& m1, float& sc0, float& sc1) {
  float a0 = m0, a1 = m1;
#pragma unroll
  for (int i = 0; i < 8; i++) { a0 = fmaxf(a0, fmaxf(s[4 * i], s[4 * i + 1])); a1 = fmaxf(a1, fmaxf(s[4 * i + 2], s[4 * i + 3])); }
  if (upper_only) { a0 = m0; a1 = m1; }
#pragma unroll
  for (int i = 8; i < 16; i++) { a0 = fmaxf(a0, fmaxf(s[4 * i], s[4 * i + 1])); a1 = fmaxf(a1, fmaxf(s[4 * i + 2], s[4 * i + 3])); }
  a0 = fmaxf(a0, __shfl_xor_sync(~0u, a0, 1)); a1 = fmaxf(a1, __shfl_xor_sync(~0u, a1, 1));
  a0 = fmaxf(a0, __shfl_xor_sync(~0u, a0, 2)); a1 = fmaxf(a1, __shfl_xor_sync(~0u, a1, 2));
  sc0 = ex2(m0 - a0); sc1 = ex2(m1 - a1);
  m0 = a0; m1 = a1;
#pragma unroll
  for (int i = 0; i < 16; i++) { s[4 * i] -= a0; s[4 * i + 1] -= a0; s[4 * i + 2] -= a1; s[4 * i + 3] -= a1; }
}
struct Att {
  float s[64], o[64], l[4], i0, i1; uint32_t p[32];
  uint32_t qaddr;
};
__device__ __forceinline__ uint32_t ctx_off(const Cons& c, int h, int qb, int rowhalf) { return T_CTX + (qb * 32 + h) * 32768 + (rowhalf * 4 + c.warp) * 4096; }
__device__ __forceinline__ void att_first(Cons& c, Att& a) {
  a.qaddr = c.daddr(0) + c.wg * 16384;
  c.wait(4);
  c.turn();
  wg_fence();
  issue_qk(a.s, odesc(a.qaddr, 16, 2048, 2), odesc(c.daddr(4), 16, 2048, 2));
  c.pass();
#pragma unroll
  for (int i = 0; i < 64; i++) a.o[i] = 0.f;
#pragma unroll
  for (int i = 0; i < 32; i++) a.p[i] = 0;
  a.l[0] = a.l[1] = a.l[2] = a.l[3] = 0.f; a.i0 = a.i1 = 0.f;
  wg_wait<0>(); fence_regs(a.s);
  c.release(4, 2);
}
__device__ __forceinline__ void att_last(Cons& c, Att& a, Pend& w, int h, int g, bool drain) {
#pragma unroll 1
  for (int k = drain ? 0 : 1; k < 2; k++) {
    if (k == 1) {
      const int uv = att_slot(1);
      c.wait(uv);
      c.turn();
      fence_regs(a.o); fence_regs(a.p);
      wgmma_pv_sel(a.o, a.p, odesc(c.daddr(uv), 512, 2048, 2), !(drain && c.wg == 1), !drain);
      c.pass();
      a.i0 = a.l[0] + a.l[1]; a.i1 = a.l[2] + a.l[3]; row_inv(a.i0, a.i1);
      wg_wait<0>(); fence_regs(a.o); fence_regs(a.p);
      c.release(uv, 2);
    }
    pack_o(a.o, a.i0, a.i1, w.lo);
    if (k == 0) tile_store<0, 4>(w.lo, ctx_off(c, h, 15, c.wg), c.lane);
  }
  w.dst = ctx_off(c, h, g, 1 - c.wg);
}
__device__ __forceinline__ void cons_att(Cons& c, int h, int g, int fast, Pend& w) {
  Att a;
  att_first(c, a);
  float m0 = -INFINITY, m1 = -INFINITY, sc0 = 0.f, sc1 = 0.f;
  int uk = 10, nrel = 0;
#pragma unroll 1
  for (int d = g - 15;;) {
    const bool lo = d == c.wg;
    if ((unsigned)d < 2 || !fast) {
      if ((unsigned)d < 2) mask_half<4>(a.s, c.warp, c.lane);
      if (!fast) {
        if (d == 1) m0 = m1 = -INFINITY;
        softmax_safe(a.s, lo, m0, m1, sc0, sc1);
        a.l[0] *= sc0; a.l[1] *= sc0; a.l[2] *= sc1; a.l[3] *= sc1;
      }
    }
    exp_rng<8, 16>(a.s); sum_rng<8, 16>(a.s, a.l);
    exp_rng<ATT_SPLIT, 8>(a.s);
    sched_fence(((a.l[0] + a.l[1]) + (a.l[2] + a.l[3])) + (ATT_SPLIT < 8 ? a.s[4 * ATT_SPLIT + 3] : 0.f), c.base + SM_DUMMY);
    wg_wait<0>(); fence_regs(a.o); fence_regs(a.p);
    c.release(14 - uk, nrel);
    nrel = 2; uk ^= 12;
    if (d == 0) a.qaddr += 32768;
    const uint64_t dq = odesc(a.qaddr, 16, 2048, 2), dk = odesc(c.daddr(uk) - (d + 1 == c.wg ? 16384 : 0), 16, 2048, 2), dv = odesc(c.daddr(14 - uk), 512, 2048, 2);
    if (!lo) { exp_rng<0, ATT_SPLIT>(a.s); sum_rng<0, 8>(a.s, a.l); cvt_p<0, 16>(a.s, a.p); }
    else if (gridDim.y == 1) cvt_p<8, 16>(a.s, a.p);
    if (!fast || d == g + 1) {
      if (!fast && d != 1) {
#pragma unroll
        for (int i = 0; i < 16; i++) { a.o[4 * i] *= sc0; a.o[4 * i + 1] *= sc0; a.o[4 * i + 2] *= sc1; a.o[4 * i + 3] *= sc1; }
      }
      if (d == g + 1) break;
    }
    d++;
    if (c.wg == 0) c.wait(uk); else c.skip(uk);
    c.turn();
    fence_regs(a.o); fence_regs(a.p);
    wg_fence();
    issue_qk(a.s, dq, dk);
    if (d == 2) {
      uint4 v[8];
      pack_o(a.o, a.i0, a.i1, v); tile_store<0, 4>(v, ctx_off(c, h, 15 - g, c.wg), c.lane);
    }
    wgmma_pv_sel(a.o, a.p, dv, !lo, d != 2);
    c.pass();
    if (d == 1) {
      a.i0 = a.l[0] + a.l[1]; a.i1 = a.l[2] + a.l[3]; row_inv(a.i0, a.i1);
      a.l[0] = a.l[1] = a.l[2] = a.l[3] = 0.f;
    }
    wg_wait<1>(); fence_regs(a.s);
    c.release(uk, 2);
    c.release(d == 0 ? 0 : 2, (d == 0 || d == g + 1) ? 2 : 0);
  }
  att_last(c, a, w, h, g, g == 0);
}

constexpr int CV_H = 1024, CV_U = 5120, CV_D = CV_U + 4128, CV_ROW = 1056;
template<int OFF> __device__ __forceinline__ uint32_t lds32o(uint32_t a) { uint32_t v; asm volatile("ld.shared.u32 %0, [%1+%2];" : "=r"(v) : "r"(a), "n"(OFF) : "memory"); return v; }
template<int G, int G1 = 16> __device__ __forceinline__ void conv_lda(uint32_t (&a)[64], uint32_t p) {
  a[4 * G + 0] = lds32o<-256 * G>(p);
  a[4 * G + 1] = lds32o<-256 * G - 128>(p);
  a[4 * G + 2] = lds32o<-256 * G + 16>(p);
  a[4 * G + 3] = lds32o<-256 * G - 112>(p);
  if constexpr (G + 1 < G1) conv_lda<G + 1, G1>(a, p);
}
template<int R, int G0, int G1> __device__ __forceinline__ void conv_mma(float (&d)[32], const uint32_t (&a)[64], uint64_t db) {
#pragma unroll
  for (int G = G0; G < G1; G++) wgmma_rs_n64<0>(d, a[4 * G], a[4 * G + 1], a[4 * G + 2], a[4 * G + 3], db + 64 * R - 16 * G, G > 0);
}
template<int R> __device__ __forceinline__ void conv_st(const float (&d)[32], uint32_t wq, float& c0, float& c1) {
#pragma unroll
  for (int n = 0; n < 8; n++) { sts64f(wq + (R * 64 + n * 8) * 4, d[4 * n] + c0, d[4 * n + 1] + c1); c0 = d[4 * n + 2]; c1 = d[4 * n + 3]; }
}
__device__ __forceinline__ void cons_conv(Cons& c, int cta, int nch) {
  const int r = c.lane >> 2, q = c.lane & 3, tid = c.warp * 32 + c.lane;
  const uint32_t part = c.addr(4) - 2048 + (1 - c.wg) * (32 * CV_ROW) + 32;
  const uint32_t aoff = CV_U + ((r & 1) ? 0 : UPITCH) + 4 * (((2039 - r) >> 1) + q - 8 * c.warp);
  const uint32_t wq = part + (c.warp * 8 + r) * CV_ROW + q * 8, rq = part + tid * 8;
  uint32_t a[64];
  c.wait(c.wg); c.skip(c.wg ^ 1);
  conv_lda<0>(a, c.addr(c.wg) + aoff);
  c.wait(4);
  sts64f(part + (tid >> 2) * CV_ROW - 32 + q * 8, 0.f, 0.f);
#pragma unroll 1
  for (int i = 0; i < nch / 2; i++) {
    const int u = 2 * (i & 1) + c.wg;
    float d0[32], d1[32], d2[32], d3[32];
    float c0 = 0.f, c1 = 0.f;
    const uint64_t db = odesc(c.daddr(u) + CV_H - 16, 16, 128, 0);
    c.turn();
    fence_regs(a);
    wg_fence();
    conv_mma<0, 0, 4>(d0, a, db); conv_mma<1, 0, 8>(d1, a, db); wg_commit();
    conv_mma<2, 0, 12>(d2, a, db); wg_commit();
    wg_wait<1>(); fence_regs(d0); fence_regs(d1);
    conv_st<0>(d0, wq, c0, c1);
    wg_fence();
    conv_mma<3, 0, 8>(d3, a, db);
    conv_st<1>(d1, wq, c0, c1);
    conv_mma<3, 8, 16>(d3, a, db); wg_commit();
    c.pass();
    wg_wait<1>(); fence_regs(d2);
    conv_st<2>(d2, wq, c0, c1);
    wg_wait<0>(); fence_regs(d3); fence_regs(a);
    conv_st<3>(d3, wq, c0, c1);
    TR(c, c.wg, 50);
    const uint32_t ub = c.addr(u);
    const uint4 ua = lds128(ub + CV_U + 4064 - 32 * tid + 16), uc = lds128(ub + CV_U + 4064 - 32 * tid);
    const uint32_t D2 = lds32(ub + CV_D);
    bar_sync(3 + c.wg, 128);
    c.release2(u);
    TR(c, c.wg, 51);
    float y0[8], y1[8];
#pragma unroll
    for (int rr = 0; rr < 8; rr++) { const float2 v = lds64f(rq + rr * CV_ROW); y0[rr] = v.x; y1[rr] = v.y; }
#pragma unroll
    for (int w = 1; w < 4; w++) {
#pragma unroll
      for (int rr = 0; rr < 8; rr++) { const float2 v = lds64f(rq + (w * 8 + rr) * CV_ROW - w * 8); y0[rr] += v.x; y1[rr] += v.y; }
    }
    if (i + 1 < nch / 2) { c.wait(u ^ 2); c.skip(u ^ 3); conv_lda<0>(a, c.addr(u ^ 2) + aoff); }
    uint4 z0, z1;
    z0.x = hadd2(pack_bf16(y0[0], y0[1]), hmul2(__byte_perm(ua.w, 0, 0x1032), D2));
    z0.y = hadd2(pack_bf16(y0[2], y0[3]), hmul2(__byte_perm(ua.z, 0, 0x1032), D2));
    z0.z = hadd2(pack_bf16(y0[4], y0[5]), hmul2(__byte_perm(ua.y, 0, 0x1032), D2));
    z0.w = hadd2(pack_bf16(y0[6], y0[7]), hmul2(__byte_perm(ua.x, 0, 0x1032), D2));
    z1.x = hadd2(pack_bf16(y1[0], y1[1]), hmul2(__byte_perm(uc.w, 0, 0x1032), D2));
    z1.y = hadd2(pack_bf16(y1[2], y1[3]), hmul2(__byte_perm(uc.z, 0, 0x1032), D2));
    z1.z = hadd2(pack_bf16(y1[4], y1[5]), hmul2(__byte_perm(uc.y, 0, 0x1032), D2));
    z1.w = hadd2(pack_bf16(y1[6], y1[7]), hmul2(__byte_perm(uc.x, 0, 0x1032), D2));
    uint4* zp = (uint4*)(g_z + (size_t)conv_channel(cta, 2 * i + c.wg) * 2048 + tid * 16);
    zp[0] = z0; zp[1] = z1;
    TR(c, c.wg, 52);
    if ((i & 15) == 15 || i == nch / 2 - 1) c.signal(SIG_Z + (i >> 4));
  }
  c.release(4, 4);
}

constexpr int OC_START = 2, OC_LEN = 15, OC_PART = 13824, OC_ROW = 544;
__device__ __forceinline__ int out_next(int u) { return u == 12 ? 4 : u + 2; }
struct Out { float acc[64]; int pu; uint64_t da, db; };
template<bool FIRST, bool REL> __device__ __forceinline__ void out_step(Cons& c, Out& o) {
  const int pu = o.pu, u = out_next(pu);
  o.pu = u;
  c.wait(u);
  const uint64_t da = o.da + (uint32_t)(u * 1024), db = o.db + (uint32_t)(u * 1024);
  wg_fence();
#pragma unroll
  for (int kk = 0; kk < 4; kk++) wgmma_ss_n128<1>(o.acc, da + (kk >> 1) * 32 + (kk & 1) * 2, db + kk * 128, !(FIRST && kk == 0));
  wg_commit();
  if (REL) { wg_wait<1>(); c.release(pu, 2); }
}
template<int I0, int I1> __device__ __forceinline__ void oc_red(float (&y)[8], uint32_t rq) {
#pragma unroll
  for (int i = I0; i < I1; i++) { const float v = __uint_as_float(lds32(rq + i * OC_ROW - (i >> 3) * 8)); y[i & 7] = i < 8 ? v : y[i & 7] + v; }
}
__device__ __forceinline__ void oc_emit(const float (&y)[8], const uint4& u, uint32_t D2, __nv_bfloat16* dst) {
  uint4 z;
  z.x = hadd2(pack_bf16(y[0], y[1]), hmul2(__byte_perm(u.w, 0, 0x1032), D2));
  z.y = hadd2(pack_bf16(y[2], y[3]), hmul2(__byte_perm(u.z, 0, 0x1032), D2));
  z.z = hadd2(pack_bf16(y[4], y[5]), hmul2(__byte_perm(u.y, 0, 0x1032), D2));
  z.w = hadd2(pack_bf16(y[6], y[7]), hmul2(__byte_perm(u.x, 0, 0x1032), D2));
  *(uint4*)dst = z;
}
template<int MASK> __device__ __forceinline__ void cons_out(Cons& c, const Maps& M, int cta, Pend& w) {
  const int mb = out_mb(cta), nb = out_nb(cta);
  Out o;
  o.da = odesc(c.daddr(0) + c.wg * 8192, 16, 1024, 2); o.db = odesc(c.daddr(1), 8192, 1024, 1);
  o.pu = 5 + gridDim.y;
  out_step<true, false>(c, o);
  if (MASK & PH_ATT) tile_store<0, 2>(w.lo, w.dst, c.lane);
  out_step<false, true>(c, o);
  if (MASK & PH_ATT) { tile_store<2, 4>(w.lo, w.dst, c.lane); c.signal(SIG_CTX + 1); }
  int ks = OC_START;
  if (MASK & PH_CONV) {
    const int r = c.lane >> 2, q = c.lane & 3, tid = c.warp * 32 + c.lane, u = 2 * c.wg;
    const uint32_t ub = c.addr(u), part = ub + OC_PART + 32;
    const uint32_t ap = ub + CV_U + ((r & 1) ? 0 : UPITCH) + 4 * (((2039 - r) >> 1) + q - 8 * c.warp);
    const uint32_t wq = part + (c.warp * 8 + r) * OC_ROW + q * 8, rq = part + tid * 4;
    const int nr = (CONV_REG + 1 - c.wg) >> 1;
#define STEP(N) out_step<false, true>(c, o);
#pragma unroll 1
    for (int i = 0; i < nr; i++) {
      uint32_t a[64];
      float d0[32], d1[32], y[8], c0 = 0.f, c1 = 0.f;
      const uint64_t db = odesc(c.daddr(u + (i >> 8)) + CV_H - 16, 16, 128, 0);
      c.wait(u);
      conv_lda<0, 3>(a, ap);
      STEP(0)
      conv_lda<3, 6>(a, ap);
      STEP(1)
      conv_lda<6, 9>(a, ap);
      STEP(2)
      fence_regs(reinterpret_cast<uint32_t (&)[32]>(a));
      wg_fence();
      conv_mma<0, 0, 4>(d0, a, db); conv_mma<1, 0, 8>(d1, a, db); wg_commit();
      conv_lda<9, 13>(a, ap);
      STEP(3)
      fence_regs(d0); fence_regs(d1);
      conv_lda<13, 16>(a, ap);
      STEP(4)
      bar_sync(3 + c.wg, 128);
      sts64f(wq - 32, 0.f, 0.f);
      conv_st<0>(d0, wq, c0, c1);
      STEP(5)
      float e0 = d1[28] + d1[26], e1 = d1[29] + d1[27];
      conv_st<1>(d1, wq, c0, c1);
      asm volatile("add.f32 %0, %0, 0f80000000;" : "+f"(c0)); asm volatile("add.f32 %0, %0, 0f80000000;" : "+f"(c1));
      fence_regs(a);
      wg_fence();
      conv_mma<2, 0, 12>(d0, a, db); conv_mma<3, 0, 16>(d1, a, db); wg_commit();
      bar_sync(3 + c.wg, 128);
      oc_red<0, 8>(y, rq);
      STEP(6)
      fence_regs(d0); fence_regs(d1); fence_regs(a);
      const uint4 u0 = lds128(ub + CV_U + 4080 - 16 * tid), u1 = lds128(ub + CV_U + 2032 - 16 * tid);
      const uint32_t D2 = lds32(ub + CV_D);
      oc_red<8, 12>(y, rq);
      __syncwarp();
      c.release2(u);
      STEP(7)
      oc_red<12, 24>(y, rq);
      STEP(8)
      __nv_bfloat16* zp = g_z + (uint32_t)(conv_channel(cta, 2 * i + c.wg) * 2048 + (threadIdx.x & 127) * 8);
      oc_red<24, 32>(y, rq);
      oc_emit(y, u0, D2, zp);
      bar_sync(3 + c.wg, 128);
      STEP(9)
      sts64f(wq - 32, e0, e1);
      conv_st<0>(d0, wq, c0, c1);
      STEP(10)
      conv_st<1>(d1, wq, c0, c1);
      bar_sync(3 + c.wg, 128);
      oc_red<0, 8>(y, rq);
      STEP(11)
      oc_red<8, 16>(y, rq);
      STEP(12)
      oc_red<16, 24>(y, rq);
      STEP(13)
      oc_red<24, 32>(y, rq);
      oc_emit(y, u1, D2, zp + 1024);
      if (i == nr - 1) { c.signal(SIG_Z); c.release2(u + 1); }
      STEP(14)
    }
#undef STEP
    if (((CONV_REG + c.wg) >> 1) & 1) c.skip(u ^ 2);
    ks += nr * OC_LEN;
  }
  TS(c.wg, 9);
#pragma unroll 1
  for (; ks < 57; ks++) out_step<false, true>(c, o);
  uint32_t ga[32];
  c.wait(0);
  const float g0 = __uint_as_float(lds32(c.base + SM_GATE + 4 * (c.wg * 64 + c.warp * 16 + (c.lane >> 2)))), g1 = __uint_as_float(lds32(c.base + SM_GATE + 32 + 4 * (c.wg * 64 + c.warp * 16 + (c.lane >> 2))));
  const uint32_t gg0 = pack_bf16(g0, g0), gg1 = pack_bf16(g1, g1);
  const uint32_t og0 = pack_bf16(1.f - g0, 1.f - g0), og1 = pack_bf16(1.f - g1, 1.f - g1);
  const int xr = c.wg * 64 + c.warp * 16 + (c.lane & 15);
  const uint32_t xa = c.addr(0) + xr * 128, xs = xr & 7, xh = c.lane >> 4;
  const int zr = (c.lane & 7) + ((c.lane >> 4) << 3);
  const uint32_t za = c.addr(2) + c.wg * 16384 + zr * 128 + (((c.warp * 2 + ((c.lane >> 3) & 1)) ^ (zr & 7)) << 4);
#pragma unroll
  for (int i = 0; i < 8; i++) {
    if (i == 0) out_step<false, true>(c, o);
    if (i == 3) out_step<false, true>(c, o);
    if (i == 6) out_step<false, true>(c, o);
    ldsm4(xa + (i >> 2) * 16384 + ((((i & 3) * 2 + xh) ^ xs) << 4), ga[4 * i], ga[4 * i + 1], ga[4 * i + 2], ga[4 * i + 3]);
  }
#pragma unroll 1
  for (ks = 60; ks < 63; ks++) { out_step<false, false>(c, o); wg_wait<1>(); }
  c.wait(2);
#pragma unroll
  for (int i = 0; i < 8; i++) {
    if (i == 2) out_step<false, false>(c, o);
    uint32_t z0, z1, z2, z3;
    ldsm4t(za + i * 2048, z0, z1, z2, z3);
    ga[4 * i + 0] = hmul2(gg0, hmul2(ga[4 * i + 0], z0)); ga[4 * i + 1] = hmul2(gg1, hmul2(ga[4 * i + 1], z1));
    ga[4 * i + 2] = hmul2(gg0, hmul2(ga[4 * i + 2], z2)); ga[4 * i + 3] = hmul2(gg1, hmul2(ga[4 * i + 3], z3));
  }
  c.signal(SIG_DONE);
  asm volatile("barrier.cluster.arrive.relaxed;" ::: "memory");
  fence_regs(ga);
  wg_wait<0>(); fence_regs(o.acc);
#pragma unroll
  for (int i = 0; i < 8; i++) {
    const uint32_t r0 = hadd2(ga[4 * i + 0], hmul2(og0, pack_bf16(o.acc[8 * i + 0], o.acc[8 * i + 1])));
    const uint32_t r1 = hadd2(ga[4 * i + 1], hmul2(og1, pack_bf16(o.acc[8 * i + 2], o.acc[8 * i + 3])));
    const uint32_t r2 = hadd2(ga[4 * i + 2], hmul2(og0, pack_bf16(o.acc[8 * i + 4], o.acc[8 * i + 5])));
    const uint32_t r3 = hadd2(ga[4 * i + 3], hmul2(og1, pack_bf16(o.acc[8 * i + 6], o.acc[8 * i + 7])));
    stsm4(xa + (i >> 2) * 16384 + ((((i & 3) * 2 + xh) ^ xs) << 4), r0, r1, r2, r3);
  }
  fence_async_smem();
  __syncwarp();
  if (c.lane < 2) {
    const int r0 = c.wg * 64 + c.warp * 16;
    tma2d_store(&M.out, c.addr(0) + c.lane * 16384 + r0 * 128, nb * 128 + c.lane * 64, mb * 128 + r0);
    asm volatile("cp.async.bulk.commit_group;\ncp.async.bulk.wait_group.read 0;" ::: "memory");
  }
}

__device__ __forceinline__ void load_conv(Prod& p, const Maps& M, int u, int ch) {
  if (elect()) {
    mbar_expect(p.full(u), 5120 + UCH);
    tma3d(p.addr(u), &M.h, 0, -8, ch, p.full(u), POL(4));
    bulk_g2s(p.addr(u) + CV_U, g_u + (size_t)ch * UCH, UCH, p.full(u), POL(4));
  }
}
__device__ __forceinline__ void prod_conv(Prod& p, const Maps& M, int cta, int nch) {
  int ready = -1;
#pragma unroll 1
  for (int i = 0; i < nch; i++) {
    const int ch = conv_channel(cta, i);
    const int u = i & 3;
    if ((ch >> 6) != ready) { ready = ch >> 6; if (cta < NREG) mbar_wait(p.base + SM_RDY + 8 * RDY_U, 0); else cnt_wait(g_cnt + (C_U + ready) * CSTRIDE, 32); }
    p.acquire(u, 1);
    load_conv(p, M, u, ch);
    if (i == 3) { p.acquire(4, 4); if (elect()) mbar_arrive(p.full(4)); }
  }
}
#define HOIST(v) asm volatile("" : "+r"(v))
template<int MASK> __device__ __forceinline__ void producer(const Maps& M, const Params& P, uint32_t base, int cta, int lane) {
  Prod p{base, (MASK & PH_PRE) ? 0xffffcfffu : 0xffffffffu, lane,
         (cta * 3 + 2) * 2048};
  if (cta >= NREG) { if (MASK & PH_CONV) prod_conv(p, M, cta, CONV_EXTRA); return; }
  const int g = cta & 7, j = cta >> 3, rank = cta & 1;
#pragma unroll 1
  for (int half = 0; half < 2; half++) {
    const int h = j + 16 * half;
    if (MASK & PH_KV) {
      const CUtensorMap* mw = rank ? &M.wv : &M.wk;
#pragma unroll 1
      for (int it = 0; it < 16; it++) {
        const int u = gemm_unit(it);
        uint32_t bar = p.full(u), d0 = p.addr(u), d1 = p.addr(u + 1 + rank); int k0 = (it & 7) * 64, r0 = (2 * g + (it >> 3)) * 128;
        HOIST(bar); HOIST(d0); HOIST(d1); HOIST(k0); HOIST(r0);
        p.acquire(u, 3);
        if (elect()) {
          mbar_expect(bar, 3 * UNIT);
          tma3d_mc(d1, mw, 0, k0, 2 * h, bar, POL(0) && it >= 8);
          tma2d(d0, &M.c, k0, r0, bar);
        }
      }
    }
    if (MASK & PH_ATT) {
#pragma unroll 1
      for (int ks = 0; ks < 16; ks++) {
        const int u = gemm_unit(ks);
        uint32_t bar = p.full(u), d0 = p.addr(u), d1 = p.addr(u + 1), d2 = p.addr(u + 2) + rank * 8192; int k0 = ks * 64;
        HOIST(bar); HOIST(d0); HOIST(d1); HOIST(d2); HOIST(k0);
        p.acquire(u, 3);
        if (elect()) {
          mbar_expect(bar, 3 * UNIT);
          tma2d_mc(d2, &M.wq, h * 128 + rank * 64, k0, bar, POL(1));
          tma2d(d0, &M.x, k0, (15 - g) * 128, bar);
          tma2d(d1, &M.x, k0, g * 128, bar);
        }
      }
      TS(2, 8 * half + 0);
      mbar_wait(base + SM_RDY + 8 * (RDY_KV + half), 0);
      TS(2, 8 * half + 1);
      const uint8_t* KVh = g_T + T_KV + (size_t)kv_slot<MASK>(h) * 16 * 65536;
#pragma unroll 1
      for (int i = 0; i < 34; i++) {
        const int isv = (i > 0 && !(i & 1)) || i == 33;
        const int st = i == 33 ? 16 : (isv ? (i >> 1) - 1 : (i + 1) >> 1);
        const int u = att_slot(i & 3);
        const bool own = st == 15 - (g & 6);
        uint32_t bar = p.full((isv && i < 33) ? 14 - u : u), d0 = p.addr(own ? u : u + rank), off = (st <= 15 - g ? st : 16 - st) * 65536 + isv * 32768 + (own ? 0 : rank * UNIT);
        HOIST(bar); HOIST(d0); HOIST(off);
        p.acquire(u, 2);
        if (elect()) {
          if (!isv || i == 33) mbar_expect(bar, (i == 0 || i == 33) ? 32768 : 65536);
          if (own) bulk_g2s(d0, KVh + off, 32768, bar, POL(6)); else bulk_g2s_mc(d0, KVh + off, UNIT, bar, POL(6));
        }
        if (i == 0) { p.acquire(0, 4); if (elect()) mbar_arrive(p.full(0)); }
      }
    }
  }
  if ((MASK & PH_CONV) && !(MASK & PH_OUT)) prod_conv(p, M, cta, CONV_REG);
  if (MASK & PH_OUT) {
    const int y0 = out_mb(cta) * 512 + rank * 8, z0 = 2 * out_nb(cta);
    int u = 6;
#pragma unroll 1
    for (int hf = 0; hf < 2; hf++) {
      TS(2, 16 + 2 * hf);
      mbar_wait(base + SM_RDY + 8 * (RDY_CTX + hf), 0);
      TS(2, 17 + 2 * hf);
#pragma unroll 1
      for (int ks = hf * 32; ks < hf * 32 + 32; ks++) {
        u = out_next(u);
        uint32_t bar = p.full(u), d0 = p.addr(u) + rank * 8192, d1 = p.addr(u + 1); int x = (ks & 1) * 256, y = y0 + (ks >> 1) * 16, k0 = ks * 64;
        HOIST(bar); HOIST(d0); HOIST(d1); HOIST(x); HOIST(y); HOIST(k0);
        p.acquire(u, 2);
        if (elect()) {
          mbar_expect(bar, 2 * UNIT);
          tma2d_mc(d0, &M.ctx, x, y, bar, POL(5));
          tma3d(d1, &M.wo, 0, k0, z0, bar, POL(2));
        }
      }
    }
    if (elect()) mbar_arrive(base + SM_RDY + 8 * RDY_Z);
  }
}
template<int MASK> __device__ __forceinline__ void producer2(const Maps& M, const Params& P, uint32_t base, int cta, int w, int lane) {
  Prod p{base, 0xffffffffu, lane, 0};
  const int mb = out_mb(cta), nb = out_nb(cta), u = 2 * w;
  if (MASK & PH_CONV) {
    mbar_wait_slow(base + SM_SIG + 8 * (SIG_ATT + 1), 0);
    mbar_wait_slow(base + SM_RDY + 8 * RDY_U, 0);
#pragma unroll 1
    for (int i = w; i < CONV_REG; i += 2) { p.acquire_slow(u, i < 2 ? 2 : 1); load_conv(p, M, u, conv_channel(cta, i)); }
  }
  p.acquire_slow(u, 2);
  TSA(50 + 2 * w);
  mbar_wait_slow(base + SM_RDY + 8 * (w ? RDY_Z : RDY_G), 0);
  TSA(51 + 2 * w);
  if (elect()) {
    mbar_expect(p.full(u), 2 * UNIT + (w ? 0 : 512));
    tma2d(p.addr(u), w ? &M.z : &M.x, (w ? mb : nb) * 128, (w ? nb : mb) * 128, p.full(u), POL(5));
    tma2d(p.addr(u + 1), w ? &M.z : &M.x, (w ? mb : nb) * 128 + 64, (w ? nb : mb) * 128, p.full(u), POL(5));
    if (!w) bulk_g2s(base + SM_GATE, g_gate + mb * 128, 512, p.full(u));
  }
}

__device__ __forceinline__ constexpr uint32_t PUB(int sig, int cnt, int n) { return 0x80000000u | (sig << 24) | (n << 8) | cnt; }
__device__ __forceinline__ constexpr uint32_t GET(int rdy, int cnt, int n) { return (rdy << 24) | (n << 8) | cnt; }
template<int MASK> __device__ __forceinline__ void sync_agent(uint32_t base, int cta, int lane) {
  if ((base & 0x3FFFF) != SMEM_BASE) asm volatile("trap;");
  const int g = cta & 7, j = cta >> 3, go = min(out_mb(cta), 15 - out_mb(cta));
  const int c0 = conv_channel(cta, 0), c1 = c0 + CONV_REG - 1, n0 = min(CONV_REG, 128 - (c0 & 127));
  constexpr bool KV = MASK & PH_KV, ATT = MASK & PH_ATT, CONV = MASK & PH_CONV, OUT = MASK & PH_OUT, ALL = MASK == PH_ALL;
  uint32_t e = 0;
  if (cta >= NREG) { if (CONV && lane * 32 < CONV_EXTRA) e = PUB(SIG_Z + lane, C_Z + lane, min(32, CONV_EXTRA - lane * 32)); }
  else switch (lane) {
    case 0:  if (KV) e = PUB(SIG_KV, C_KV + j, 1); break;
    case 1:  if (ATT) e = GET(RDY_KV, C_KV + j, 8); break;
    case 2:  if (ALL) e = PUB(SIG_WAR, C_WAR + j, 1); break;
    case 3:  if (ATT) e = PUB(SIG_CTX, C_CTX + g, 1); break;
    case 4:  if (ALL) e = GET(RDY_WAR, C_WAR + j, 8); break;
    case 5:  if (KV) e = PUB(SIG_KV + 1, C_KV + 16 + j, 1); break;
    case 6:  if (ATT) e = GET(RDY_KV + 1, C_KV + 16 + j, 8); break;
    case 7:  if (OUT) e = GET(RDY_CTX, C_CTX + go, 16); break;
    case 8:  if (CONV) e = GET(RDY_U, C_U + (c0 >> 6), 32); break;
    case 9:  if (CONV) e = GET(RDY_U, C_U + (c1 >> 6), 32); break;
    case 10: if (ATT) e = PUB(SIG_CTX + 1, C_CTX + 8 + g, 1); break;
    case 11: if (OUT) e = GET(RDY_CTX + 1, C_CTX + 8 + go, 16); break;
    case 12: if (OUT) e = GET(RDY_G, C_GATE, 256); break;
    case 13: if (CONV) e = PUB(SIG_Z, C_Z + (c0 >> 7), n0); break;
    case 14: if (CONV && n0 < CONV_REG) e = PUB(SIG_Z, C_Z + (c1 >> 7), CONV_REG - n0); break;
    case 15: if (OUT) e = GET(RDY_Z, C_Z + out_nb(cta), 128); break;
  }
  __syncwarp();
#pragma unroll 1
  for (int i = 0; i < 16; i++) {
    const uint32_t x = __shfl_sync(~0u, e, i), id = (x >> 24) & 127, n = (x >> 8) & 0xffff;
    if (x == 0) continue;
    unsigned* cnt = g_cnt + (x & 255) * CSTRIDE;
    if (x >> 31) {
      mbar_wait_slow(base + SM_SIG + 8 * id, 0);
      if (lane == 0) cnt_publish(cnt, n);
    } else {
      cnt_wait(cnt, n);
      if (id < 2) {
        const float4 kn = __ldcg((const float4*)(g_kn2 + kv_slot<MASK>(j + 16 * id) * 128) + lane);
        const uint32_t m = __reduce_max_sync(~0u, max(max(__float_as_uint(kn.x), __float_as_uint(kn.y)), max(__float_as_uint(kn.z), __float_as_uint(kn.w))));
        if (lane == 0) asm volatile("st.shared.u32 [%0], %1;" :: "r"(base + SM_KMAX + 4 * id), "r"(m) : "memory");
      }
      if (lane == 0) mbar_arrive(base + SM_RDY + 8 * id);
    }
    __syncwarp();
  }
}

template<int MASK> __device__ __forceinline__ void aux_pre(const Maps& M, const Params& P, uint32_t base, int cta, int aw, int lane) {
  const uint32_t kb = base + 12 * UNIT, bar = base + SM_PRE;
  const int r = lane >> 2, q = lane & 3;
  const int mi = lane >> 3, row0 = (lane & 6) + 1 - (lane & 1);
#pragma unroll 1
  for (int it = 0; it < 4; it++) {
    if (it == PRE_EARLY && MASK == PH_ALL) mbar_wait_slow(base + SM_SIG + 8 * (SIG_ATT + PRE_HALF), 0);
    const int cg = it * 4 + (cta >> 5), tb = cta & 31;
    if (aw == 0 && elect()) {
      mbar_expect(bar, 2 * 9216);
      tma4d(kb, &M.k, cg * 64, 0, tb * 8 - 1, 0, bar, POL(3));
      tma4d(kb + 9216, &M.v, cg * 64, 0, tb * 8 - 1, 0, bar, POL(3));
    }
    const uint2 swl = __ldg((const uint2*)(P.shift + (cg * 64 + aw * 32 + lane) * 4));
    if (tb == 0) {
      uint8_t* e = g_u + (size_t)(cg * 64 + aw * 32 + lane) * UCH + 4096;
      *(uint4*)e = make_uint4(0, 0, 0, 0); *(uint4*)(e + UPITCH) = make_uint4(0, 0, 0, 0);
      *(uint32_t*)(e + 32) = (uint32_t)__bfloat16_as_ushort(P.D[cg * 64 + aw * 32 + lane]) * 0x10001u;
    }
    mbar_wait_slow(bar, it & 1);
#pragma unroll 1
    for (int bl = 0; bl < 8; bl++) {
      const int oc = aw * 4 + (bl >> 1), hb = bl & 1, ch = cg * 64 + oc * 8 + r;
      const uint2 sw = make_uint2(__shfl_sync(~0u, swl.x, (bl >> 1) * 8 + r), __shfl_sync(~0u, swl.y, (bl >> 1) * 8 + r));
      const uint32_t w0 = __byte_perm(sw.x, 0, 0x1010), w1 = __byte_perm(sw.x, 0, 0x3232), w2 = __byte_perm(sw.y, 0, 0x1010), w3 = __byte_perm(sw.y, 0, 0x3232);
      const int ra = (mi * 9 + 4 * hb + 1) * 2 + row0;
      const int rb = ((mi == 0 ? 3 : mi) * 9 + 4 * hb) * 2 + row0;
      uint32_t k[7], v[5];
      ldsm4t(kb + ra * 128 + ((oc ^ (ra & 7)) << 4), k[3], k[4], k[5], k[6]);
      ldsm4t(kb + 9216 + ra * 128 + ((oc ^ (ra & 7)) << 4), v[1], v[2], v[3], v[4]);
      ldsm4t(kb + (mi == 0 ? 9216 : 0) + rb * 128 + ((oc ^ (rb & 7)) << 4), v[0], k[0], k[1], k[2]);
      uint32_t o1 = __byte_perm(k[1], k[0], 0x5432);
#pragma unroll
      for (int m = 0; m < 5; m++) {
        const uint32_t o2 = __byte_perm(k[m + 2], k[m + 1], 0x5432);
        v[m] = hmul2(hadd2(hadd2(hadd2(hmul2(o1, w3), hmul2(k[m + 1], w2)), hmul2(o2, w1)), hmul2(k[m + 2], w0)), v[m]);
        o1 = o2;
      }
      uint8_t* e0 = g_u + (size_t)ch * UCH + (2040 - tb * 64 - hb * 32 - 8 * q) * 2;
      *(uint4*)e0 = make_uint4(v[4], v[3], v[2], v[1]);
      *(uint4*)(e0 + UPITCH) = make_uint4(__byte_perm(v[4], v[3], 0x5432), __byte_perm(v[3], v[2], 0x5432), __byte_perm(v[2], v[1], 0x5432), __byte_perm(v[1], v[0], 0x5432));
    }
    bar_sync(5, 64);
    if (aw == 0) { TSA(40 + it); }
    if (aw == 1 && lane == 0) asm volatile("red.release.gpu.global.add.u32 [%0], 1;" :: "l"(g_cnt + (C_U + cg) * CSTRIDE) : "memory");
  }
  uint32_t rel;
  asm volatile("mapa.shared::cluster.u32 %0, %1, %2;" : "=r"(rel) : "r"(base + SM_BAR + 128 + 8 * (12 + (lane & 1))), "r"((lane >> 1) & 1));
  if (lane < 4) asm volatile("mbarrier.arrive.shared::cluster.b64 _, [%0], 4;" :: "r"(rel) : "memory");
  uint4 gw[4];
#pragma unroll
  for (int i = 0; i < 4; i++) gw[i] = __ldg((const uint4*)P.gw + i * 32 + lane);
#pragma unroll 1
  for (int row = cta * 16 + aw * 8; row < cta * 16 + aw * 8 + 8; row++) {
    float a = 0.f;
#pragma unroll
    for (int i = 0; i < 4; i++) {
      const uint4 xv = __ldg((const uint4*)(P.x + (size_t)row * 1024) + i * 32 + lane);
      uint32_t m;
      m = hmul2(xv.x, gw[i].x); a += bf_lo(m) + bf_hi(m); m = hmul2(xv.y, gw[i].y); a += bf_lo(m) + bf_hi(m);
      m = hmul2(xv.z, gw[i].z); a += bf_lo(m) + bf_hi(m); m = hmul2(xv.w, gw[i].w); a += bf_lo(m) + bf_hi(m);
    }
#pragma unroll
    for (int o = 16; o > 0; o >>= 1) a += __shfl_xor_sync(~0u, a, o);
    a = bf_lo(pack_bf16(a, 0.f));
    const float gt = bf_lo(pack_bf16(__fdividef(1.f, 1.f + ex2(-a * 1.4426950408889634f)), 0.f));
    if (lane == 0) g_gate[row] = gt;
  }
  cnt_signal(g_cnt + C_GATE * CSTRIDE, lane);
  if (aw == 0) { TSA(44); }
}

template<int MASK> __global__ void __cluster_dims__(2, 1, 1) __launch_bounds__(384, 1) gated_mix_kernel(const __grid_constant__ Maps M, const __grid_constant__ Params P) {
  extern __shared__ __align__(1024) uint8_t smem[];
  const uint32_t base = (uint32_t)__cvta_generic_to_shared(smem);
  const int wi = __shfl_sync(~0u, threadIdx.x >> 5, 0), wg = wi >> 2, warp = wi & 3;
  if (elect()) {
    asm volatile("prefetch.tensormap [%0];" :: "l"(&M.x + wi) : "memory");
    constexpr int S0 = (SM_SIG - SM_BAR) / 8, R0 = (SM_RDY - SM_BAR) / 8;
#pragma unroll 1
    for (int i = 6 * wi; i < 6 * wi + 6; i++)
      mbar_init(base + SM_BAR + 8 * i, (i >= 16 && i < 32) ? 16 : (i >= S0 && i < R0) ? 8 : i == (SM_EXIT - SM_BAR) / 8 ? 3 : (i == R0 + RDY_Z || i == R0 + RDY_U) ? 2 : 1);
    asm volatile("fence.mbarrier_init.release.cluster;" ::: "memory");
  }
  __syncwarp();
  asm volatile("barrier.cluster.arrive.relaxed.aligned;\nbarrier.cluster.wait.aligned;" ::: "memory");
  const int lane = threadIdx.x & 31;
  const int cta = blockIdx.x;
  if (wg == 2) {
    asm volatile("setmaxnreg.dec.sync.aligned.u32 56;");
    TS(2, 62);
    if (warp == 0) producer<MASK>(M, P, base, cta, lane);
    else if (warp == 1) sync_agent<MASK>(base, cta, lane);
    else if (cta < NREG) {
      if (MASK & PH_PRE) aux_pre<MASK>(M, P, base, cta, warp - 2, lane);
      if (MASK & PH_OUT) producer2<MASK>(M, P, base, cta, warp - 2, lane);
    }
    __syncwarp();
    if (warp != 1) { if (lane == 0) mbar_arrive(base + SM_EXIT); }
    else {
      mbar_wait_slow(base + SM_EXIT, 0);
      if (MASK & PH_OUT) {
        unsigned old = 0;
        if (lane == 0) asm volatile("atom.acq_rel.gpu.global.add.u32 %0, [%1], 1;" : "=r"(old) : "l"(g_cnt + C_EXIT * CSTRIDE) : "memory");
        old = __shfl_sync(~0u, old, 0);
        if (old == NCTA - 1) for (int i = lane; i < C_NUM; i += 32) g_cnt[i * CSTRIDE] = 0;
      }
      mbar_wait_slow(base + SM_SIG + 8 * SIG_DONE, 0);
      cluster_arrive(); cluster_wait();
    }
  } else {
    asm volatile("setmaxnreg.inc.sync.aligned.u32 224;");
    uint32_t rel;
    asm volatile("mapa.shared::cluster.u32 %0, %1, %2;" : "=r"(rel) : "r"(base + SM_BAR + 128 + 8 * (lane & 15)), "r"(lane >> 4));
    Cons c{base, rel, 0u, lane, warp, wg, (cta * 3 + wg) * 2048};
    if (wg == 1) bar_arrive(1, 256);
    TS(wg, 0);
    if (cta < NREG) {
      const int g = cta & 7, j = cta >> 3;
      Pend w = {};
#pragma unroll 1
      for (int half = 0; half < 2; half++) {
        const int h = j + 16 * half;
        if (MASK & PH_KV) cons_kv(c, h, kv_slot<MASK>(h), g, w, half == 1 && (MASK & PH_ATT));
        TS(wg, 1 + 4 * half);
        if (MASK & PH_ATT) {
          const int fast = cons_q<(MASK & PH_KV) != 0>(c, h, w);
          TS(wg, 2 + 4 * half);
          c.signal(SIG_ATT + half);
          cons_att(c, h, g, fast, w);
          if (half == 0) c.signal(SIG_WAR);
#pragma unroll
          for (int i = 0; i < 8; i++) w.hi[i] = make_uint4(0, 0, 0, 0);
          TS(wg, 3 + 4 * half);
          if (MASK != PH_ALL) { tile_store<0, 4>(w.lo, w.dst, lane); c.signal(SIG_CTX + half); }
        } else if (MASK & PH_KV) { out_part<0>(c, w); out_part<1>(c, w); out_part<2>(c, w); out_part<3>(c, w); c.signal(SIG_KV + half); }
      }
      if (MASK & PH_OUT) cons_out<MASK>(c, M, cta, w);
    }
    if (cta >= NREG || !(MASK & PH_OUT)) {
      if (MASK & PH_CONV) cons_conv(c, cta, cta < NREG ? CONV_REG : CONV_EXTRA);
      TS(wg, 9);
      c.signal(SIG_DONE);
      cluster_arrive();
    }
    TS(wg, 10);
  }
}

typedef CUresult (*EncFn)(CUtensorMap*, CUtensorMapDataType, cuuint32_t, void*, const cuuint64_t*, const cuuint64_t*, const cuuint32_t*, const cuuint32_t*,
                          CUtensorMapInterleave, CUtensorMapSwizzle, CUtensorMapL2promotion, CUtensorMapFloatOOBfill);
static void enc(EncFn f, CUtensorMap* m, const void* ptr, int rank, const cuuint64_t* dims, const cuuint64_t* strides, const cuuint32_t* box, CUtensorMapSwizzle sw,
                CUtensorMapDataType dt = CU_TENSOR_MAP_DATA_TYPE_BFLOAT16) {
  const cuuint32_t es[4] = {1, 1, 1, 1};
  f(m, dt, rank, (void*)ptr, dims, strides, box, es, CU_TENSOR_MAP_INTERLEAVE_NONE, sw, CU_TENSOR_MAP_L2_PROMOTION_L2_256B, CU_TENSOR_MAP_FLOAT_OOB_FILL_NONE);
}
static void enc2(EncFn f, CUtensorMap* m, const void* ptr, int cols, int rows, int brows) {
  const cuuint64_t d[2] = {(cuuint64_t)cols, (cuuint64_t)rows}, s[1] = {(cuuint64_t)cols * 2}; const cuuint32_t b[2] = {64, (cuuint32_t)brows};
  enc(f, m, ptr, 2, d, s, b, CU_TENSOR_MAP_SWIZZLE_128B);
}
static void encw(EncFn f, CUtensorMap* m, const void* ptr, int cols, int rows) {
  const cuuint64_t d[3] = {64, (cuuint64_t)rows, (cuuint64_t)cols / 64}, s[2] = {(cuuint64_t)cols * 2, 128}; const cuuint32_t b[3] = {64, 64, 2};
  enc(f, m, ptr, 3, d, s, b, CU_TENSOR_MAP_SWIZZLE_128B);
}
extern "C" void kernel_launch(void* const* d_in, const int* in_sizes, int n_in, void* d_out, int out_size) {
  static EncFn fn = nullptr;
  static int ncl = 0;
  static void* zptr = nullptr;
  static void* tptr = nullptr;
  if (!fn) {
    void* p = nullptr; cudaDriverEntryPointQueryResult qr;
    cudaGetDriverEntryPoint("cuTensorMapEncodeTiled", &p, cudaEnableDefault, &qr);
    fn = (EncFn)p;
    cudaFuncSetAttribute(gated_mix_kernel<PH_ALL>, cudaFuncAttributeMaxDynamicSharedMemorySize, SMEM_BYTES);
    cudaFuncSetAttribute(gated_mix_kernel<PH_PRE | PH_KV>, cudaFuncAttributeMaxDynamicSharedMemorySize, SMEM_BYTES);
    cudaFuncSetAttribute(gated_mix_kernel<PH_ATT | PH_CONV>, cudaFuncAttributeMaxDynamicSharedMemorySize, SMEM_BYTES);
    cudaFuncSetAttribute(gated_mix_kernel<PH_OUT>, cudaFuncAttributeMaxDynamicSharedMemorySize, SMEM_BYTES);
    cudaLaunchConfig_t cfg = {}; cfg.gridDim = NCTA; cfg.blockDim = 384; cfg.dynamicSmemBytes = SMEM_BYTES;
    cudaLaunchAttribute at; at.id = cudaLaunchAttributeClusterDimension; at.val.clusterDim.x = 2; at.val.clusterDim.y = 1; at.val.clusterDim.z = 1;
    cfg.attrs = &at; cfg.numAttrs = 1;
    cudaOccupancyMaxActiveClusters(&ncl, gated_mix_kernel<PH_ALL>, &cfg);
    cudaGetSymbolAddress(&zptr, g_z);
    cudaGetSymbolAddress(&tptr, g_T);
  }
  Maps M;
  enc2(fn, &M.x, d_in[0], 1024, 2048, 128);
  enc2(fn, &M.c, d_in[7], 512, 2048, 128);
  enc2(fn, &M.wq, d_in[8], 4096, 1024, 64);
  encw(fn, &M.wk, d_in[9], 4096, 512);
  encw(fn, &M.wv, d_in[10], 4096, 512);
  encw(fn, &M.wo, d_in[11], 1024, 4096);
  { const cuuint64_t d[3] = {64, 32, 1024}, s[2] = {128, 4096}; const cuuint32_t b[3] = {64, 40, 1}; enc(fn, &M.h, d_in[4], 3, d, s, b, CU_TENSOR_MAP_SWIZZLE_NONE); }
  enc2(fn, &M.z, zptr, 2048, 1024, 128);
  enc2(fn, &M.out, d_out, 1024, 2048, 16);
  { const cuuint64_t d[2] = {512, 512 * 16}, s[1] = {2048}; const cuuint32_t b[2] = {256, 8};
    enc(fn, &M.ctx, tptr, 2, d, s, b, CU_TENSOR_MAP_SWIZZLE_NONE, CU_TENSOR_MAP_DATA_TYPE_UINT32); }
  { const cuuint64_t d[4] = {1024, 2, 256, 4}, s[3] = {2048, 16384, 4096}; const cuuint32_t b[4] = {64, 2, 9, 4};
    enc(fn, &M.k, d_in[1], 4, d, s, b, CU_TENSOR_MAP_SWIZZLE_128B); enc(fn, &M.v, d_in[2], 4, d, s, b, CU_TENSOR_MAP_SWIZZLE_128B); }
  Params P{(const __nv_bfloat16*)d_in[0], (const __nv_bfloat16*)d_in[3],
           (const __nv_bfloat16*)d_in[5], (const __nv_bfloat16*)d_in[12]};
  bool split = 2 * ncl < NCTA;
  if (!split) {
    gated_mix_kernel<PH_ALL><<<NCTA, 384, SMEM_BYTES>>>(M, P);
  } else {
    gated_mix_kernel<PH_PRE | PH_KV><<<NCTA, 384, SMEM_BYTES>>>(M, P);
    gated_mix_kernel<PH_ATT | PH_CONV><<<NCTA, 384, SMEM_BYTES>>>(M, P);
    gated_mix_kernel<PH_OUT><<<NCTA, 384, SMEM_BYTES>>>(M, P);
  }
}
```

```cpp
#include <cuda_runtime.h>
#include <cuda.h>
#include <cuda_bf16.h>
#include <stdint.h>

template<int TB> __device__ __forceinline__ void wgmma_ss_n256(float (&d)[128], uint64_t da, uint64_t db, int scale_d) {
  asm volatile("{\n.reg .pred p;\nsetp.ne.b32 p, %130, 0;\n"
    "wgmma.mma_async.sync.aligned.m64n256k16.f32.bf16.bf16 {%0, %1, %2, %3, %4, %5, %6, %7, %8, %9, %10, %11, %12, %13, %14, %15, %16, %17, %18, %19, %20, %21, %22, %23, %24, %25, %26, %27, %28, %29, %30, %31, %32, %33, %34, %35, %36, %37, %38, %39, %40, %41, %42, %43, %44, %45, %46, %47, %48, %49, %50, %51, %52, %53, %54, %55, %56, %57, %58, %59, %60, %61, %62, %63, %64, %65, %66, %67, %68, %69, %70, %71, %72, %73, %74, %75, %76, %77, %78, %79, %80, %81, %82, %83, %84, %85, %86, %87, %88, %89, %90, %91, %92, %93, %94, %95, %96, %97, %98, %99, %100, %101, %102, %103, %104, %105, %106, %107, %108, %109, %110, %111, %112, %113, %114, %115, %116, %117, %118, %119, %120, %121, %122, %123, %124, %125, %126, %127}, %128, %129, p, 1, 1, 0, %131;\n}\n"
    : "+f"(d[0]), "+f"(d[1]), "+f"(d[2]), "+f"(d[3]), "+f"(d[4]), "+f"(d[5]), "+f"(d[6]), "+f"(d[7]), "+f"(d[8]), "+f"(d[9]), "+f"(d[10]), "+f"(d[11]), "+f"(d[12]), "+f"(d[13]), "+f"(d[14]), "+f"(d[15]), "+f"(d[16]), "+f"(d[17]), "+f"(d[18]), "+f"(d[19]), "+f"(d[20]), "+f"(d[21]), "+f"(d[22]), "+f"(d[23]), "+f"(d[24]), "+f"(d[25]), "+f"(d[26]), "+f"(d[27]), "+f"(d[28]), "+f"(d[29]), "+f"(d[30]), "+f"(d[31]), "+f"(d[32]), "+f"(d[33]), "+f"(d[34]), "+f"(d[35]), "+f"(d[36]), "+f"(d[37]), "+f"(d[38]), "+f"(d[39]), "+f"(d[40]), "+f"(d[41]), "+f"(d[42]), "+f"(d[43]), "+f"(d[44]), "+f"(d[45]), "+f"(d[46]), "+f"(d[47]), "+f"(d[48]), "+f"(d[49]), "+f"(d[50]), "+f"(d[51]), "+f"(d[52]), "+f"(d[53]), "+f"(d[54]), "+f"(d[55]), "+f"(d[56]), "+f"(d[57]), "+f"(d[58]), "+f"(d[59]), "+f"(d[60]), "+f"(d[61]), "+f"(d[62]), "+f"(d[63]), "+f"(d[64]), "+f"(d[65]), "+f"(d[66]), "+f"(d[67]), "+f"(d[68]), "+f"(d[69]), "+f"(d[70]), "+f"(d[71]), "+f"(d[72]), "+f"(d[73]), "+f"(d[74]), "+f"(d[75]), "+f"(d[76]), "+f"(d[77]), "+f"(d[78]), "+f"(d[79]), "+f"(d[80]), "+f"(d[81]), "+f"(d[82]), "+f"(d[83]), "+f"(d[84]), "+f"(d[85]), "+f"(d[86]), "+f"(d[87]), "+f"(d[88]), "+f"(d[89]), "+f"(d[90]), "+f"(d[91]), "+f"(d[92]), "+f"(d[93]), "+f"(d[94]), "+f"(d[95]), "+f"(d[96]), "+f"(d[97]), "+f"(d[98]), "+f"(d[99]), "+f"(d[100]), "+f"(d[101]), "+f"(d[102]), "+f"(d[103]), "+f"(d[104]), "+f"(d[105]), "+f"(d[106]), "+f"(d[107]), "+f"(d[108]), "+f"(d[109]), "+f"(d[110]), "+f"(d[111]), "+f"(d[112]), "+f"(d[113]), "+f"(d[114]), "+f"(d[115]), "+f"(d[116]), "+f"(d[117]), "+f"(d[118]), "+f"(d[119]), "+f"(d[120]), "+f"(d[121]), "+f"(d[122]), "+f"(d[123]), "+f"(d[124]), "+f"(d[125]), "+f"(d[126]), "+f"(d[127])
    : "l"(da), "l"(db), "r"(scale_d), "n"(TB));
}
template<int TB> __device__ __forceinline__ void wgmma_ss_n128(float (&d)[64], uint64_t da, uint64_t db, int scale_d) {
  asm volatile("{\n.reg .pred p;\nsetp.ne.b32 p, %66, 0;\n"
    "wgmma.mma_async.sync.aligned.m64n128k16.f32.bf16.bf16 {%0, %1, %2, %3, %4, %5, %6, %7, %8, %9, %10, %11, %12, %13, %14, %15, %16, %17, %18, %19, %20, %21, %22, %23, %24, %25, %26, %27, %28, %29, %30, %31, %32, %33, %34, %35, %36, %37, %38, %39, %40, %41, %42, %43, %44, %45, %46, %47, %48, %49, %50, %51, %52, %53, %54, %55, %56, %57, %58, %59, %60, %61, %62, %63}, %64, %65, p, 1, 1, 0, %67;\n}\n"
    : "+f"(d[0]), "+f"(d[1]), "+f"(d[2]), "+f"(d[3]), "+f"(d[4]), "+f"(d[5]), "+f"(d[6]), "+f"(d[7]), "+f"(d[8]), "+f"(d[9]), "+f"(d[10]), "+f"(d[11]), "+f"(d[12]), "+f"(d[13]), "+f"(d[14]), "+f"(d[15]), "+f"(d[16]), "+f"(d[17]), "+f"(d[18]), "+f"(d[19]), "+f"(d[20]), "+f"(d[21]), "+f"(d[22]), "+f"(d[23]), "+f"(d[24]), "+f"(d[25]), "+f"(d[26]), "+f"(d[27]), "+f"(d[28]), "+f"(d[29]), "+f"(d[30]), "+f"(d[31]), "+f"(d[32]), "+f"(d[33]), "+f"(d[34]), "+f"(d[35]), "+f"(d[36]), "+f"(d[37]), "+f"(d[38]), "+f"(d[39]), "+f"(d[40]), "+f"(d[41]), "+f"(d[42]), "+f"(d[43]), "+f"(d[44]), "+f"(d[45]), "+f"(d[46]), "+f"(d[47]), "+f"(d[48]), "+f"(d[49]), "+f"(d[50]), "+f"(d[51]), "+f"(d[52]), "+f"(d[53]), "+f"(d[54]), "+f"(d[55]), "+f"(d[56]), "+f"(d[57]), "+f"(d[58]), "+f"(d[59]), "+f"(d[60]), "+f"(d[61]), "+f"(d[62]), "+f"(d[63])
    : "l"(da), "l"(db), "r"(scale_d), "n"(TB));
}
template<int TB> __device__ __forceinline__ void wgmma_rs_n64(float (&d)[32], uint32_t a0, uint32_t a1, uint32_t a2, uint32_t a3, uint64_t db, int scale_d) {
  asm volatile("{\n.reg .pred p;\nsetp.ne.b32 p, %37, 0;\n"
    "wgmma.mma_async.sync.aligned.m64n64k16.f32.bf16.bf16 {%0, %1, %2, %3, %4, %5, %6, %7, %8, %9, %10, %11, %12, %13, %14, %15, %16, %17, %18, %19, %20, %21, %22, %23, %24, %25, %26, %27, %28, %29, %30, %31}, {%32, %33, %34, %35}, %36, p, 1, 1, %38;\n}\n"
    : "+f"(d[0]), "+f"(d[1]), "+f"(d[2]), "+f"(d[3]), "+f"(d[4]), "+f"(d[5]), "+f"(d[6]), "+f"(d[7]), "+f"(d[8]), "+f"(d[9]), "+f"(d[10]), "+f"(d[11]), "+f"(d[12]), "+f"(d[13]), "+f"(d[14]), "+f"(d[15]), "+f"(d[16]), "+f"(d[17]), "+f"(d[18]), "+f"(d[19]), "+f"(d[20]), "+f"(d[21]), "+f"(d[22]), "+f"(d[23]), "+f"(d[24]), "+f"(d[25]), "+f"(d[26]), "+f"(d[27]), "+f"(d[28]), "+f"(d[29]), "+f"(d[30]), "+f"(d[31])
    : "r"(a0), "r"(a1), "r"(a2), "r"(a3), "l"(db), "r"(scale_d), "n"(TB));
}
__device__ __forceinline__ void wgmma_pv_sel(float (&d)[64], const uint32_t (&p)[32], uint64_t db, int full, int acc) {
  asm volatile("{\n.reg .pred q, s;\n.reg .b64 t;\nsetp.ne.b32 s, %98, 0;\nsetp.eq.b32 q, %97, 0;\n@q bra.uni LH;\n"
    "wgmma.fence.sync.aligned;\n"
    "add.s64 t, %96, 0;\nwgmma.mma_async.sync.aligned.m64n128k16.f32.bf16.bf16 {%0, %1, %2, %3, %4, %5, %6, %7, %8, %9, %10, %11, %12, %13, %14, %15, %16, %17, %18, %19, %20, %21, %22, %23, %24, %25, %26, %27, %28, %29, %30, %31, %32, %33, %34, %35, %36, %37, %38, %39, %40, %41, %42, %43, %44, %45, %46, %47, %48, %49, %50, %51, %52, %53, %54, %55, %56, %57, %58, %59, %60, %61, %62, %63}, {%64, %65, %66, %67}, t, s, 1, 1, 1;\n"
    "add.s64 t, %96, 256;\nwgmma.mma_async.sync.aligned.m64n128k16.f32.bf16.bf16 {%0, %1, %2, %3, %4, %5, %6, %7, %8, %9, %10, %11, %12, %13, %14, %15, %16, %17, %18, %19, %20, %21, %22, %23, %24, %25, %26, %27, %28, %29, %30, %31, %32, %33, %34, %35, %36, %37, %38, %39, %40, %41, %42, %43, %44, %45, %46, %47, %48, %49, %50, %51, %52, %53, %54, %55, %56, %57, %58, %59, %60, %61, %62, %63}, {%68, %69, %70, %71}, t, 1, 1, 1, 1;\n"
    "add.s64 t, %96, 512;\nwgmma.mma_async.sync.aligned.m64n128k16.f32.bf16.bf16 {%0, %1, %2, %3, %4, %5, %6, %7, %8, %9, %10, %11, %12, %13, %14, %15, %16, %17, %18, %19, %20, %21, %22, %23, %24, %25, %26, %27, %28, %29, %30, %31, %32, %33, %34, %35, %36, %37, %38, %39, %40, %41, %42, %43, %44, %45, %46, %47, %48, %49, %50, %51, %52, %53, %54, %55, %56, %57, %58, %59, %60, %61, %62, %63}, {%72, %73, %74, %75}, t, 1, 1, 1, 1;\n"
    "add.s64 t, %96, 768;\nwgmma.mma_async.sync.aligned.m64n128k16.f32.bf16.bf16 {%0, %1, %2, %3, %4, %5, %6, %7, %8, %9, %10, %11, %12, %13, %14, %15, %16, %17, %18, %19, %20, %21, %22, %23, %24, %25, %26, %27, %28, %29, %30, %31, %32, %33, %34, %35, %36, %37, %38, %39, %40, %41, %42, %43, %44, %45, %46, %47, %48, %49, %50, %51, %52, %53, %54, %55, %56, %57, %58, %59, %60, %61, %62, %63}, {%76, %77, %78, %79}, t, 1, 1, 1, 1;\n"
    "add.s64 t, %96, 1024;\nwgmma.mma_async.sync.aligned.m64n128k16.f32.bf16.bf16 {%0, %1, %2, %3, %4, %5, %6, %7, %8, %9, %10, %11, %12, %13, %14, %15, %16, %17, %18, %19, %20, %21, %22, %23, %24, %25, %26, %27, %28, %29, %30, %31, %32, %33, %34, %35, %36, %37, %38, %39, %40, %41, %42, %43, %44, %45, %46, %47, %48, %49, %50, %51, %52, %53, %54, %55, %56, %57, %58, %59, %60, %61, %62, %63}, {%80, %81, %82, %83}, t, 1, 1, 1, 1;\n"
    "add.s64 t, %96, 1280;\nwgmma.mma_async.sync.aligned.m64n128k16.f32.bf16.bf16 {%0, %1, %2, %3, %4, %5, %6, %7, %8, %9, %10, %11, %12, %13, %14, %15, %16, %17, %18, %19, %20, %21, %22, %23, %24, %25, %26, %27, %28, %29, %30, %31, %32, %33, %34, %35, %36, %37, %38, %39, %40, %41, %42, %43, %44, %45, %46, %47, %48, %49, %50, %51, %52, %53, %54, %55, %56, %57, %58, %59, %60, %61, %62, %63}, {%84, %85, %86, %87}, t, 1, 1, 1, 1;\n"
    "add.s64 t, %96, 1536;\nwgmma.mma_async.sync.aligned.m64n128k16.f32.bf16.bf16 {%0, %1, %2, %3, %4, %5, %6, %7, %8, %9, %10, %11, %12, %13, %14, %15, %16, %17, %18, %19, %20, %21, %22, %23, %24, %25, %26, %27, %28, %29, %30, %31, %32, %33, %34, %35, %36, %37, %38, %39, %40, %41, %42, %43, %44, %45, %46, %47, %48, %49, %50, %51, %52, %53, %54, %55, %56, %57, %58, %59, %60, %61, %62, %63}, {%88, %89, %90, %91}, t, 1, 1, 1, 1;\n"
    "add.s64 t, %96, 1792;\nwgmma.mma_async.sync.aligned.m64n128k16.f32.bf16.bf16 {%0, %1, %2, %3, %4, %5, %6, %7, %8, %9, %10, %11, %12, %13, %14, %15, %16, %17, %18, %19, %20, %21, %22, %23, %24, %25, %26, %27, %28, %29, %30, %31, %32, %33, %34, %35, %36, %37, %38, %39, %40, %41, %42, %43, %44, %45, %46, %47, %48, %49, %50, %51, %52, %53, %54, %55, %56, %57, %58, %59, %60, %61, %62, %63}, {%92, %93, %94, %95}, t, 1, 1, 1, 1;\n"
    "wgmma.commit_group.sync.aligned;\n"
    "bra.uni LE;\nLH:\n"
    "wgmma.fence.sync.aligned;\n"
    "add.s64 t, %96, 0;\nwgmma.mma_async.sync.aligned.m64n128k16.f32.bf16.bf16 {%0, %1, %2, %3, %4, %5, %6, %7, %8, %9, %10, %11, %12, %13, %14, %15, %16, %17, %18, %19, %20, %21, %22, %23, %24, %25, %26, %27, %28, %29, %30, %31, %32, %33, %34, %35, %36, %37, %38, %39, %40, %41, %42, %43, %44, %45, %46, %47, %48, %49, %50, %51, %52, %53, %54, %55, %56, %57, %58, %59, %60, %61, %62, %63}, {%80, %81, %82, %83}, t, s, 1, 1, 1;\n"
    "add.s64 t, %96, 256;\nwgmma.mma_async.sync.aligned.m64n128k16.f32.bf16.bf16 {%0, %1, %2, %3, %4, %5, %6, %7, %8, %9, %10, %11, %12, %13, %14, %15, %16, %17, %18, %19, %20, %21, %22, %23, %24, %25, %26, %27, %28, %29, %30, %31, %32, %33, %34, %35, %36, %37, %38, %39, %40, %41, %42, %43, %44, %45, %46, %47, %48, %49, %50, %51, %52, %53, %54, %55, %56, %57, %58, %59, %60, %61, %62, %63}, {%84, %85, %86, %87}, t, 1, 1, 1, 1;\n"
    "add.s64 t, %96, 512;\nwgmma.mma_async.sync.aligned.m64n128k16.f32.bf16.bf16 {%0, %1, %2, %3, %4, %5, %6, %7, %8, %9, %10, %11, %12, %13, %14, %15, %16, %17, %18, %19, %20, %21, %22, %23, %24, %25, %26, %27, %28, %29, %30, %31, %32, %33, %34, %35, %36, %37, %38, %39, %40, %41, %42, %43, %44, %45, %46, %47, %48, %49, %50, %51, %52, %53, %54, %55, %56, %57, %58, %59, %60, %61, %62, %63}, {%88, %89, %90, %91}, t, 1, 1, 1, 1;\n"
    "add.s64 t, %96, 768;\nwgmma.mma_async.sync.aligned.m64n128k16.f32.bf16.bf16 {%0, %1, %2, %3, %4, %5, %6, %7, %8, %9, %10, %11, %12, %13, %14, %15, %16, %17, %18, %19, %20, %21, %22, %23, %24, %25, %26, %27, %28, %29, %30, %31, %32, %33, %34, %35, %36, %37, %38, %39, %40, %41, %42, %43, %44, %45, %46, %47, %48, %49, %50, %51, %52, %53, %54, %55, %56, %57, %58, %59, %60, %61, %62, %63}, {%92, %93, %94, %95}, t, 1, 1, 1, 1;\n"
    "wgmma.commit_group.sync.aligned;\n"
    "LE:\n}\n"
    : "+f"(d[0]), "+f"(d[1]), "+f"(d[2]), "+f"(d[3]), "+f"(d[4]), "+f"(d[5]), "+f"(d[6]), "+f"(d[7]), "+f"(d[8]), "+f"(d[9]), "+f"(d[10]), "+f"(d[11]), "+f"(d[12]), "+f"(d[13]), "+f"(d[14]), "+f"(d[15]), "+f"(d[16]), "+f"(d[17]), "+f"(d[18]), "+f"(d[19]), "+f"(d[20]), "+f"(d[21]), "+f"(d[22]), "+f"(d[23]), "+f"(d[24]), "+f"(d[25]), "+f"(d[26]), "+f"(d[27]), "+f"(d[28]), "+f"(d[29]), "+f"(d[30]), "+f"(d[31]), "+f"(d[32]), "+f"(d[33]), "+f"(d[34]), "+f"(d[35]), "+f"(d[36]), "+f"(d[37]), "+f"(d[38]), "+f"(d[39]), "+f"(d[40]), "+f"(d[41]), "+f"(d[42]), "+f"(d[43]), "+f"(d[44]), "+f"(d[45]), "+f"(d[46]), "+f"(d[47]), "+f"(d[48]), "+f"(d[49]), "+f"(d[50]), "+f"(d[51]), "+f"(d[52]), "+f"(d[53]), "+f"(d[54]), "+f"(d[55]), "+f"(d[56]), "+f"(d[57]), "+f"(d[58]), "+f"(d[59]), "+f"(d[60]), "+f"(d[61]), "+f"(d[62]), "+f"(d[63])
    : "r"(p[0]), "r"(p[1]), "r"(p[2]), "r"(p[3]), "r"(p[4]), "r"(p[5]), "r"(p[6]), "r"(p[7]), "r"(p[8]), "r"(p[9]), "r"(p[10]), "r"(p[11]), "r"(p[12]), "r"(p[13]), "r"(p[14]), "r"(p[15]), "r"(p[16]), "r"(p[17]), "r"(p[18]), "r"(p[19]), "r"(p[20]), "r"(p[21]), "r"(p[22]), "r"(p[23]), "r"(p[24]), "r"(p[25]), "r"(p[26]), "r"(p[27]), "r"(p[28]), "r"(p[29]), "r"(p[30]), "r"(p[31]), "l"(db), "r"(full), "r"(acc) : "memory");
}

constexpr int NCTA = 132, NREG = 128;
constexpr int UNIT = 16384, NUNIT = 14;
constexpr uint32_t SMEM_BASE = 1024;
constexpr int SM_BAR = NUNIT * UNIT;
constexpr int SM_GATE = SM_BAR + 1024;
constexpr int SMEM_BYTES = SM_BAR + 1536;
constexpr int UPITCH = 4160, UCH = 2 * UPITCH;
constexpr float QSCALE = 0.08838834764831845f * 1.4426950408889634f;
constexpr float BOUND2 = 48.f * 48.f / 1.15f;
#define CONV_REG 6
constexpr int CONV_EXTRA = (1024 - NREG * CONV_REG) / (NCTA - NREG);
constexpr int CH_EXTRA_TOTAL = CONV_EXTRA * (NCTA - NREG);
constexpr int C_KV = 0;
constexpr int C_CTX = 32;
constexpr int C_U = 48;
constexpr int C_Z = 80;
constexpr int C_GATE = 88;
constexpr int C_EXIT = 89;
[[maybe_unused]] constexpr int C_GO = 90;
#define PRE_EARLY 1
#define PRE_HALF 1
#define ATT_SPLIT 6
#define NFIRST 2
#define PRE_DELAY 1
#define MAP_PF 1
#define EF 127
#define POL(bit) (((EF >> (bit)) & 1) != 0)
constexpr int C_WAR = 96;
constexpr int C_NUM = 112;
constexpr int CSTRIDE = 32;
constexpr int SM_KMAX = SM_BAR + 640, SM_DUMMY = SM_BAR + 648, SM_PRE = SM_BAR + 112, SM_SIG = SM_BAR + 256, SM_EXIT = SM_SIG + 120, SM_RDY = SM_BAR + 384;
enum { SIG_KV = 0, SIG_CTX = 2, SIG_Z = 4, SIG_DONE = 8, SIG_WAR = 9, SIG_ATT = 10 };
enum { RDY_KV = 0, RDY_CTX = 2, RDY_WAR = 4, RDY_G = 5, RDY_U = 8, RDY_Z = 9 };
enum { PH_PRE = 1, PH_KV = 2, PH_ATT = 4, PH_CONV = 8, PH_OUT = 16, PH_ALL = 31 };

constexpr uint32_t T_CTX = 0, T_KV = 16 * 32 * 32768, T_BYTES = T_KV + 32 * 16 * 65536;
__device__ __align__(1024) uint8_t g_T[T_BYTES];
__device__ __align__(1024) uint8_t g_u[1024 * UCH];
__device__ __align__(1024) __nv_bfloat16 g_z[1024 * 2048];
__device__ __align__(1024) float g_gate[2048];
__device__ __align__(1024) float g_kn2[32 * 128];
__device__ __align__(1024) unsigned g_cnt[C_NUM * CSTRIDE];

struct __align__(64) Maps { CUtensorMap c, wk, wv, x, wq, wo, h, z, out, ctx, k, v; };
struct Params {
  const __nv_bfloat16 *x, *shift, *D, *gw;
};

__device__ __forceinline__ void wg_fence() { asm volatile("wgmma.fence.sync.aligned;" ::: "memory"); }
__device__ __forceinline__ void wg_commit() { asm volatile("wgmma.commit_group.sync.aligned;" ::: "memory"); }
template<int N> __device__ __forceinline__ void wg_wait() { asm volatile("wgmma.wait_group.sync.aligned %0;" :: "n"(N) : "memory"); }
__device__ __forceinline__ uint64_t odesc(uint32_t addr, uint32_t lbo, uint32_t sbo, uint32_t swz) {
  uint64_t d = (uint64_t)(addr >> 4) + (((uint64_t)(lbo >> 4) << 16) | ((uint64_t)(sbo >> 4) << 32) | ((uint64_t)swz << 62));
  asm volatile("" : "+l"(d));
  return d;
}
__device__ __forceinline__ void mbar_init(uint32_t bar, int cnt) { asm volatile("mbarrier.init.shared::cta.b64 [%0], %1;" :: "r"(bar), "r"(cnt)); }
__device__ __forceinline__ void mbar_expect(uint32_t bar, uint32_t bytes) { asm volatile("mbarrier.arrive.expect_tx.shared::cta.b64 _, [%0], %1;" :: "r"(bar), "r"(bytes) : "memory"); }
__device__ __forceinline__ void mbar_arrive(uint32_t bar) { asm volatile("mbarrier.arrive.shared::cta.b64 _, [%0];" :: "r"(bar) : "memory"); }
__device__ __forceinline__ void mbar_arrive_n(uint32_t bar, int n) { asm volatile("mbarrier.arrive.shared::cta.b64 _, [%0], %1;" :: "r"(bar), "r"(n) : "memory"); }
__device__ __forceinline__ void mbar_wait(uint32_t bar, uint32_t parity) {
  asm volatile("{\n.reg .pred p;\nLW:\nmbarrier.try_wait.parity.shared::cta.b64 p, [%0], %1;\n@!p bra LW;\n}\n" :: "r"(bar), "r"(parity) : "memory");
}
__device__ __forceinline__ void mbar_wait_slow(uint32_t bar, uint32_t parity) {
  asm volatile("{\n.reg .pred p;\n.reg .u32 n;\nmov.u32 n, 0;\n"
    "LW:\nmbarrier.test_wait.parity.shared::cta.b64 p, [%0], %1;\n@p bra LD;\n"
    "nanosleep.u32 128;\nadd.u32 n, n, 1;\nsetp.lt.u32 p, n, 4194304;\n@p bra LW;\ntrap;\nLD:\n}\n" :: "r"(bar), "r"(parity) : "memory");
}
__device__ __forceinline__ void mbar_wait_all(uint32_t bar, uint32_t parity) {
  asm volatile("{\n.reg .pred p, q;\nLW:\nmbarrier.try_wait.parity.shared::cta.b64 p, [%0], %1;\nvote.sync.all.pred q, p, 0xffffffff;\n@!q bra.uni LW;\n}\n" :: "r"(bar), "r"(parity) : "memory");
}
__device__ __forceinline__ void cnt_wait(const unsigned* p, unsigned target) {
  asm volatile("{\n.reg .pred p;\n.reg .u32 n, v;\nmov.u32 n, 0;\n"
    "LW:\nld.relaxed.gpu.global.u32 v, [%0];\nsetp.ge.u32 p, v, %1;\n@p bra LD;\n"
    "nanosleep.u32 64;\nadd.u32 n, n, 1;\nsetp.lt.u32 p, n, 4194304;\n@p bra LW;\ntrap;\nLD:\nfence.acq_rel.gpu;\nfence.proxy.async;\n}\n" :: "l"(p), "r"(target) : "memory");
}
__device__ __forceinline__ void cnt_signal(unsigned* p, int lane) {
  __syncwarp();
  if (lane == 0) asm volatile("red.release.gpu.global.add.u32 [%0], 1;" :: "l"(p) : "memory");
}
__device__ __forceinline__ void cnt_publish(unsigned* p, unsigned n) {
  asm volatile("fence.acq_rel.gpu;\nred.relaxed.gpu.global.add.u32 [%0], %1;" :: "l"(p), "r"(n) : "memory");
}
__device__ __forceinline__ uint64_t pol_first() { uint64_t p; asm("createpolicy.fractional.L2::evict_first.b64 %0, 1.0;" : "=l"(p)); return p; }
__device__ __forceinline__ void bulk_g2s(uint32_t dst, const void* src, uint32_t bytes, uint32_t bar, bool stream = false) {
  if (stream) asm volatile("cp.async.bulk.shared::cluster.global.mbarrier::complete_tx::bytes.L2::cache_hint [%0], [%1], %2, [%3], %4;" :: "r"(dst), "l"(src), "r"(bytes), "r"(bar), "l"(pol_first()) : "memory");
  else asm volatile("cp.async.bulk.shared::cluster.global.mbarrier::complete_tx::bytes [%0], [%1], %2, [%3];" :: "r"(dst), "l"(src), "r"(bytes), "r"(bar) : "memory");
}
__device__ __forceinline__ void tma2d(uint32_t dst, const CUtensorMap* m, int x, int y, uint32_t bar, bool stream = false) {
  if (stream) asm volatile("cp.async.bulk.tensor.2d.shared::cluster.global.mbarrier::complete_tx::bytes.L2::cache_hint [%0], [%1, {%3, %4}], [%2], %5;" :: "r"(dst), "l"(m), "r"(bar), "r"(x), "r"(y), "l"(pol_first()) : "memory");
  else asm volatile("cp.async.bulk.tensor.2d.shared::cluster.global.mbarrier::complete_tx::bytes [%0], [%1, {%3, %4}], [%2];" :: "r"(dst), "l"(m), "r"(bar), "r"(x), "r"(y) : "memory");
}
__device__ __forceinline__ void tma3d(uint32_t dst, const CUtensorMap* m, int x, int y, int z, uint32_t bar, bool stream = false) {
  if (stream) asm volatile("cp.async.bulk.tensor.3d.shared::cluster.global.mbarrier::complete_tx::bytes.L2::cache_hint [%0], [%1, {%3, %4, %5}], [%2], %6;" :: "r"(dst), "l"(m), "r"(bar), "r"(x), "r"(y), "r"(z), "l"(pol_first()) : "memory");
  else asm volatile("cp.async.bulk.tensor.3d.shared::cluster.global.mbarrier::complete_tx::bytes [%0], [%1, {%3, %4, %5}], [%2];" :: "r"(dst), "l"(m), "r"(bar), "r"(x), "r"(y), "r"(z) : "memory");
}
__device__ __forceinline__ void tma4d(uint32_t dst, const CUtensorMap* m, int x, int y, int z, int w, uint32_t bar, bool stream = false) {
  if (stream) asm volatile("cp.async.bulk.tensor.4d.shared::cluster.global.mbarrier::complete_tx::bytes.L2::cache_hint [%0], [%1, {%3, %4, %5, %6}], [%2], %7;" :: "r"(dst), "l"(m), "r"(bar), "r"(x), "r"(y), "r"(z), "r"(w), "l"(pol_first()) : "memory");
  else asm volatile("cp.async.bulk.tensor.4d.shared::cluster.global.mbarrier::complete_tx::bytes [%0], [%1, {%3, %4, %5, %6}], [%2];" :: "r"(dst), "l"(m), "r"(bar), "r"(x), "r"(y), "r"(z), "r"(w) : "memory");
}
__device__ __forceinline__ void bulk_g2s_mc(uint32_t dst, const void* src, uint32_t bytes, uint32_t bar, bool stream = false) {
  if (stream) asm volatile("cp.async.bulk.shared::cluster.global.mbarrier::complete_tx::bytes.multicast::cluster.L2::cache_hint [%0], [%1], %2, [%3], %4, %5;" :: "r"(dst), "l"(src), "r"(bytes), "r"(bar), "h"((uint16_t)3), "l"(pol_first()) : "memory");
  else asm volatile("cp.async.bulk.shared::cluster.global.mbarrier::complete_tx::bytes.multicast::cluster [%0], [%1], %2, [%3], %4;" :: "r"(dst), "l"(src), "r"(bytes), "r"(bar), "h"((uint16_t)3) : "memory");
}
__device__ __forceinline__ void tma2d_mc(uint32_t dst, const CUtensorMap* m, int x, int y, uint32_t bar, bool stream = false) {
  if (stream) asm volatile("cp.async.bulk.tensor.2d.shared::cluster.global.mbarrier::complete_tx::bytes.multicast::cluster.L2::cache_hint [%0], [%1, {%3, %4}], [%2], %5, %6;" :: "r"(dst), "l"(m), "r"(bar), "r"(x), "r"(y), "h"((uint16_t)3), "l"(pol_first()) : "memory");
  else asm volatile("cp.async.bulk.tensor.2d.shared::cluster.global.mbarrier::complete_tx::bytes.multicast::cluster [%0], [%1, {%3, %4}], [%2], %5;" :: "r"(dst), "l"(m), "r"(bar), "r"(x), "r"(y), "h"((uint16_t)3) : "memory");
}
__device__ __forceinline__ void tma3d_mc(uint32_t dst, const CUtensorMap* m, int x, int y, int z, uint32_t bar, bool stream = false) {
  if (stream) asm volatile("cp.async.bulk.tensor.3d.shared::cluster.global.mbarrier::complete_tx::bytes.multicast::cluster.L2::cache_hint [%0], [%1, {%3, %4, %5}], [%2], %6, %7;" :: "r"(dst), "l"(m), "r"(bar), "r"(x), "r"(y), "r"(z), "h"((uint16_t)3), "l"(pol_first()) : "memory");
  else asm volatile("cp.async.bulk.tensor.3d.shared::cluster.global.mbarrier::complete_tx::bytes.multicast::cluster [%0], [%1, {%3, %4, %5}], [%2], %6;" :: "r"(dst), "l"(m), "r"(bar), "r"(x), "r"(y), "r"(z), "h"((uint16_t)3) : "memory");
}
__device__ __forceinline__ void tma2d_store(const CUtensorMap* m, uint32_t src, int x, int y) {
  asm volatile("cp.async.bulk.tensor.2d.global.shared::cta.bulk_group [%0, {%2, %3}], [%1];" :: "l"(m), "r"(src), "r"(x), "r"(y) : "memory");
}
__device__ __forceinline__ bool elect() {
  uint32_t r; asm volatile("{\n.reg .pred p;\nelect.sync _|p, 0xffffffff;\nselp.u32 %0, 1, 0, p;\n}\n" : "=r"(r)); return r != 0;
}
__device__ __forceinline__ void cluster_arrive() { asm volatile("barrier.cluster.arrive;" ::: "memory"); }
__device__ __forceinline__ void cluster_wait() { asm volatile("barrier.cluster.wait;" ::: "memory"); }
__device__ __forceinline__ void bar_sync(int id, int n) { asm volatile("bar.sync %0, %1;" :: "r"(id), "r"(n) : "memory"); }
__device__ __forceinline__ void bar_arrive(int id, int n) { asm volatile("bar.arrive %0, %1;" :: "r"(id), "r"(n) : "memory"); }
__device__ __forceinline__ int bar_and(int id, int n, int pred) {
  int r; asm volatile("{\n.reg .pred p, q;\nsetp.ne.b32 p, %3, 0;\nbar.red.and.pred q, %1, %2, p;\nselp.b32 %0, 1, 0, q;\n}\n" : "=r"(r) : "r"(id), "r"(n), "r"(pred) : "memory");
  return r;
}
__device__ __forceinline__ void fence_async_smem() { asm volatile("fence.proxy.async.shared::cta;" ::: "memory"); }
__device__ __forceinline__ float ex2(float x) { float y; asm("ex2.approx.ftz.f32 %0, %1;" : "=f"(y) : "f"(x)); return y; }
__device__ __forceinline__ uint32_t pack_bf16(float lo, float hi) { uint32_t r; asm("cvt.rn.bf16x2.f32 %0, %1, %2;" : "=r"(r) : "f"(hi), "f"(lo)); return r; }
__device__ __forceinline__ uint32_t hmul2(uint32_t a, uint32_t b) { uint32_t r; asm("mul.rn.bf16x2 %0, %1, %2;" : "=r"(r) : "r"(a), "r"(b)); return r; }
__device__ __forceinline__ uint32_t hadd2(uint32_t a, uint32_t b) { uint32_t r; asm("add.rn.bf16x2 %0, %1, %2;" : "=r"(r) : "r"(a), "r"(b)); return r; }
__device__ __forceinline__ uint32_t hfma2(uint32_t a, uint32_t b, uint32_t c) { uint32_t r; asm("fma.rn.bf16x2 %0, %1, %2, %3;" : "=r"(r) : "r"(a), "r"(b), "r"(c)); return r; }
__device__ __forceinline__ float bf_lo(uint32_t a) { return __uint_as_float(a << 16); }
__device__ __forceinline__ float bf_hi(uint32_t a) { return __uint_as_float(a & 0xffff0000u); }
__device__ __forceinline__ uint32_t lds32(uint32_t a) { uint32_t v; asm volatile("ld.shared.u32 %0, [%1];" : "=r"(v) : "r"(a) : "memory"); return v; }
__device__ __forceinline__ float2 lds64f(uint32_t a) { float2 v; asm volatile("ld.shared.v2.f32 {%0,%1}, [%2];" : "=f"(v.x), "=f"(v.y) : "r"(a) : "memory"); return v; }
__device__ __forceinline__ uint4 lds128(uint32_t a) { uint4 v; asm volatile("ld.shared.v4.u32 {%0,%1,%2,%3}, [%4];" : "=r"(v.x), "=r"(v.y), "=r"(v.z), "=r"(v.w) : "r"(a) : "memory"); return v; }
__device__ __forceinline__ void sts64f(uint32_t a, float x, float y) { asm volatile("st.shared.v2.f32 [%0], {%1,%2};" :: "r"(a), "f"(x), "f"(y) : "memory"); }
__device__ __forceinline__ void sts128(uint32_t a, uint4 v) { asm volatile("st.shared.v4.u32 [%0], {%1,%2,%3,%4};" :: "r"(a), "r"(v.x), "r"(v.y), "r"(v.z), "r"(v.w) : "memory"); }
template<int OFF> __device__ __forceinline__ void sts128o(uint32_t a, uint4 v) { asm volatile("st.shared.v4.u32 [%0+%5], {%1,%2,%3,%4};" :: "r"(a), "r"(v.x), "r"(v.y), "r"(v.z), "r"(v.w), "n"(OFF) : "memory"); }
__device__ __forceinline__ void ldsm4(uint32_t a, uint32_t& r0, uint32_t& r1, uint32_t& r2, uint32_t& r3) {
  asm volatile("ldmatrix.sync.aligned.m8n8.x4.shared.b16 {%0,%1,%2,%3}, [%4];" : "=r"(r0), "=r"(r1), "=r"(r2), "=r"(r3) : "r"(a) : "memory");
}
__device__ __forceinline__ void ldsm4t(uint32_t a, uint32_t& r0, uint32_t& r1, uint32_t& r2, uint32_t& r3) {
  asm volatile("ldmatrix.sync.aligned.m8n8.x4.trans.shared.b16 {%0,%1,%2,%3}, [%4];" : "=r"(r0), "=r"(r1), "=r"(r2), "=r"(r3) : "r"(a) : "memory");
}
__device__ __forceinline__ void stsm4(uint32_t a, uint32_t r0, uint32_t r1, uint32_t r2, uint32_t r3) {
  asm volatile("stmatrix.sync.aligned.m8n8.x4.shared.b16 [%0], {%1,%2,%3,%4};" :: "r"(a), "r"(r0), "r"(r1), "r"(r2), "r"(r3) : "memory");
}
template<int N> __device__ __forceinline__ void fence_regs(float (&d)[N]) {
#pragma unroll
  for (int i = 0; i < N; i++) asm volatile("" : "+f"(d[i]) :: "memory");
}
template<int N> __device__ __forceinline__ void fence_regs(uint32_t (&d)[N]) {
#pragma unroll
  for (int i = 0; i < N; i++) asm volatile("" : "+r"(d[i]) :: "memory");
}
__device__ __forceinline__ void sched_fence(float x, uint32_t dummy) {
  asm volatile("{\n.reg .pred p;\nsetp.eq.u32 p, %0, 0x7fc12345;\n@p st.shared.u32 [%1], %0;\n}\n" :: "r"(__float_as_uint(x)), "r"(dummy) : "memory");
}
#define TS(role, i)
#define TSA(i)
#define TR(obj, role, tag)

struct Prod {
  uint32_t base, mask; int lane, nt;
  __device__ __forceinline__ uint32_t full(int u) const { return base + SM_BAR + 8 * u; }
  __device__ __forceinline__ uint32_t addr(int u) const { return base + u * UNIT; }
  __device__ __forceinline__ void acquire(int u, int n) {
    const int v = u + min(lane, n - 1);
    mbar_wait_all(base + SM_BAR + 128 + 8 * v, mask >> v);
    mask ^= ((1u << n) - 1) << u;
    TR(*this, 2, 16 + u);
  }
  __device__ __forceinline__ void acquire_slow(int u, int n) {
    for (int i = 0; i < n; i++) mbar_wait_slow(base + SM_BAR + 128 + 8 * (u + i), mask >> (u + i));
    mask ^= ((1u << n) - 1) << u;
  }
};
struct Cons {
  uint32_t base, rel, mask; int lane, warp, wg, nt;
  __device__ __forceinline__ uint32_t addr(int u) const { return base + u * UNIT; }
  __device__ __forceinline__ static uint32_t daddr(int u) { return SMEM_BASE + u * UNIT; }
  __device__ __forceinline__ void wait(int u) { TR(*this, wg, 1); mbar_wait(base + SM_BAR + 8 * u, mask >> u); mask ^= 1u << u; TR(*this, wg, 2); }
  __device__ __forceinline__ void skip(int u) { mask ^= 1u << u; }
  __device__ __forceinline__ void release(int u, int n) {
    TR(*this, wg, 5);
    asm volatile("{\n.reg .pred p;\nsetp.lt.s32 p, %1, %2;\n@p mbarrier.arrive.shared::cluster.b64 _, [%0];\n}\n" :: "r"(rel + 8 * u), "r"(lane & 15), "r"(n) : "memory");
  }
  __device__ __forceinline__ void release2(int u) {
    asm volatile("{\n.reg .pred p;\nsetp.eq.s32 p, %1, 0;\n@p mbarrier.arrive.shared::cluster.b64 _, [%0], 2;\n}\n" :: "r"(rel + 8 * u), "r"(lane & 15) : "memory");
  }
  __device__ __forceinline__ void signal(int i) {
    __syncwarp();
    asm volatile("{\n.reg .pred p;\nsetp.eq.s32 p, %1, 0;\n@p mbarrier.arrive.shared::cta.b64 _, [%0];\n}\n" :: "r"(base + SM_SIG + 8 * i), "r"(lane) : "memory");
  }
  __device__ __forceinline__ void turn() { bar_sync(1 + wg, 256); TR(*this, wg, 3); }
  __device__ __forceinline__ void pass() { bar_arrive(2 - wg, 256); TR(*this, wg, 4); }
};
__device__ __forceinline__ int gemm_unit(int ks) { return 3 * (ks & 3); }
__device__ __forceinline__ int att_slot(int i) { return 4 + 2 * i; }
template<int MASK> __device__ __forceinline__ int kv_slot(int h) { return MASK == PH_ALL ? h & 15 : h; }
__device__ __forceinline__ int out_mb(int cta) { return cta >> 3; }
__device__ __forceinline__ int out_nb(int cta) { return cta & 7; }
__device__ __forceinline__ int conv_channel(int cta, int i) {
  return cta < NREG ? CH_EXTRA_TOTAL + cta * CONV_REG + i : (i >> 1) * 8 + (cta - NREG) * 2 + (i & 1);
}

template<int OFF, int N> __device__ __forceinline__ void pack_chunk(const float (&a)[N], float sc0, float sc1, uint4& v0, uint4& v1) {
  v0.x = pack_bf16(a[OFF + 0] * sc0, a[OFF + 1] * sc0); v0.y = pack_bf16(a[OFF + 4] * sc0, a[OFF + 5] * sc0);
  v0.z = pack_bf16(a[OFF + 8] * sc0, a[OFF + 9] * sc0); v0.w = pack_bf16(a[OFF + 12] * sc0, a[OFF + 13] * sc0);
  v1.x = pack_bf16(a[OFF + 2] * sc1, a[OFF + 3] * sc1); v1.y = pack_bf16(a[OFF + 6] * sc1, a[OFF + 7] * sc1);
  v1.z = pack_bf16(a[OFF + 10] * sc1, a[OFF + 11] * sc1); v1.w = pack_bf16(a[OFF + 14] * sc1, a[OFF + 15] * sc1);
}
template<int OFF, int N> __device__ __forceinline__ void pack_chunk(const float (&a)[N], uint4& v0, uint4& v1) {
  v0.x = pack_bf16(a[OFF + 0], a[OFF + 1]); v0.y = pack_bf16(a[OFF + 4], a[OFF + 5]);
  v0.z = pack_bf16(a[OFF + 8], a[OFF + 9]); v0.w = pack_bf16(a[OFF + 12], a[OFF + 13]);
  v1.x = pack_bf16(a[OFF + 2], a[OFF + 3]); v1.y = pack_bf16(a[OFF + 6], a[OFF + 7]);
  v1.z = pack_bf16(a[OFF + 10], a[OFF + 11]); v1.w = pack_bf16(a[OFF + 14], a[OFF + 15]);
}
__device__ __forceinline__ void sq_acc(const uint4& v, uint32_t& a) { a = hfma2(v.x, v.x, a); a = hfma2(v.y, v.y, a); a = hfma2(v.z, v.z, a); a = hfma2(v.w, v.w, a); }
__device__ __forceinline__ float norm2_max(uint32_t a0, uint32_t a1) {
  float n0 = bf_lo(a0) + bf_hi(a0), n1 = bf_lo(a1) + bf_hi(a1);
  n0 += __shfl_xor_sync(~0u, n0, 1); n1 += __shfl_xor_sync(~0u, n1, 1);
  n0 += __shfl_xor_sync(~0u, n0, 2); n1 += __shfl_xor_sync(~0u, n1, 2);
  return __uint_as_float(__reduce_max_sync(~0u, max(__float_as_uint(n0) & 0x7fffffffu, __float_as_uint(n1) & 0x7fffffffu)));
}

struct Pend { uint4 lo[8], hi[8]; uint32_t dst; float kn; };
__device__ __forceinline__ void pin(uint4 (&v)[8]) {
#pragma unroll
  for (int i = 0; i < 8; i++) asm volatile("" : "+r"(v[i].x), "+r"(v[i].y), "+r"(v[i].z), "+r"(v[i].w) :: "memory");
}
__device__ __forceinline__ uint32_t atom_off(int lane) { return (lane >> 2) * 64 + (((lane ^ (lane >> 3)) & 3) << 4); }
template<int J0, int J1> __device__ __forceinline__ void tile_store(const uint4 (&v)[8], uint32_t dst, int lane) {
  uint8_t* d = g_T + (dst + atom_off(lane));
#pragma unroll
  for (int j = J0; j < J1; j++) { *(uint4*)(d + j * 512) = v[2 * j]; *(uint4*)(d + j * 512 + 2048) = v[2 * j + 1]; }
}
__device__ __forceinline__ float tile_norm2(const uint4 (&v)[8]) {
  uint32_t n0 = 0, n1 = 0;
#pragma unroll
  for (int j = 0; j < 4; j++) { sq_acc(v[2 * j], n0); sq_acc(v[2 * j + 1], n1); }
  return norm2_max(n0, n1);
}
template<int PART> __device__ __forceinline__ void out_part(Cons& c, Pend& w) {
  if (PART == 0) { w.kn = tile_norm2(w.lo); tile_store<0, 2>(w.lo, w.dst, c.lane); }
  if (PART == 1) tile_store<2, 4>(w.lo, w.dst, c.lane);
  if (PART == 2) {
    const float vn = tile_norm2(w.hi);
    if (c.lane == 0) g_kn2[((w.dst - T_KV) >> 16) * 8 + c.wg * 4 + c.warp] = (vn <= 1.0e30f && vn >= 1.0e-30f) ? w.kn : __uint_as_float(0x7f800000u);
    tile_store<0, 2>(w.hi, w.dst + 32768, c.lane);
  }
  if (PART == 3) tile_store<2, 4>(w.hi, w.dst + 32768, c.lane);
}
template<bool FIRST> __device__ __forceinline__ void kv_issue(Cons& c, float (&acc)[128], int u) {
  const uint64_t da = odesc(c.daddr(u) + c.wg * 8192, 16, 1024, 1), db = odesc(c.daddr(u + 1), 8192, 1024, 1);
  c.turn();
  wg_fence();
#pragma unroll
  for (int kk = 0; kk < 4; kk++) wgmma_ss_n256<1>(acc, da + kk * 2, db + kk * 128, !(FIRST && kk == 0));
  wg_commit();
  c.pass();
}
__device__ __forceinline__ void cons_kv(Cons& c, int h, int hs, int g, Pend& w, bool pend_o) {
#pragma unroll 1
  for (int tile = 0; tile < 2; tile++) {
    float acc[128];
    c.wait(0);
    if (tile == 0 && h < 16) TS(c.wg, 16);
    kv_issue<true>(c, acc, 0);
    if (tile == 1 && pend_o) mbar_wait(c.base + SM_RDY + 8 * RDY_WAR, 0);
    if (tile == 1 || pend_o) out_part<0>(c, w);
#pragma unroll 1
    for (int ks = 1; ks < 8; ks++) {
      if (ks == 3 && (tile == 1 || pend_o)) { out_part<1>(c, w); if (tile == 0) c.signal(SIG_CTX); }
      if (ks == 5 && tile == 1) out_part<2>(c, w);
      if (ks == 7 && tile == 1) out_part<3>(c, w);
      const int u = gemm_unit(ks);
      c.wait(u);
      wg_wait<0>();
      c.release(gemm_unit(ks - 1), 3);
      kv_issue<false>(c, acc, u);
    }
    wg_wait<0>(); fence_regs(acc);
    c.release(9, 3);
    pack_chunk<0>(acc, w.lo[0], w.lo[1]);  pack_chunk<16>(acc, w.lo[2], w.lo[3]); pack_chunk<32>(acc, w.lo[4], w.lo[5]); pack_chunk<48>(acc, w.lo[6], w.lo[7]);
    pack_chunk<64>(acc, w.hi[0], w.hi[1]); pack_chunk<80>(acc, w.hi[2], w.hi[3]); pack_chunk<96>(acc, w.hi[4], w.hi[5]); pack_chunk<112>(acc, w.hi[6], w.hi[7]);
    pin(w.lo); pin(w.hi);
    w.dst = T_KV + (hs * 16 + 2 * g + tile) * 65536 + (c.wg * 4 + c.warp) * 4096;
  }
}
template<bool FIRST> __device__ __forceinline__ void q_issue(Cons& c, float (&a)[64], float (&b)[64], int u) {
  const uint64_t da = odesc(c.daddr(u) + c.wg * 8192, 16, 1024, 1), db = odesc(c.daddr(u + 2), 8192, 1024, 1);
  const uint64_t da2 = odesc(c.daddr(u + 1) + (1 - c.wg) * 8192, 16, 1024, 1);
  c.turn();
  wg_fence();
#pragma unroll
  for (int kk = 0; kk < 4; kk++) wgmma_ss_n128<1>(a, da + kk * 2, db + kk * 128, !(FIRST && kk == 0));
#pragma unroll
  for (int kk = 0; kk < 4; kk++) wgmma_ss_n128<1>(b, da2 + kk * 2, db + kk * 128, !(FIRST && kk == 0));
  wg_commit();
  c.pass();
}
template<bool PEND_KV> __device__ __forceinline__ int cons_q(Cons& c, int h, Pend& w) {
  float a[64], b[64];
  c.wait(0);
  q_issue<true>(c, a, b, 0);
  if (PEND_KV) out_part<0>(c, w);
#pragma unroll 1
  for (int ks = 1; ks < 16; ks++) {
    if (PEND_KV) {
      if (ks == 2) out_part<1>(c, w);
      if (ks == 4) out_part<2>(c, w);
      if (ks == 5) { out_part<3>(c, w); c.signal(SIG_KV + (h >> 4)); }
    }
    const int u = gemm_unit(ks);
    c.wait(u);
    wg_wait<0>();
    c.release(gemm_unit(ks - 1), 3);
    q_issue<false>(c, a, b, u);
  }
  c.wait(0);
  wg_wait<0>(); fence_regs(a); fence_regs(b);
  c.release(9, 3);
  const uint32_t q0 = c.addr(0) + (c.wg * 4 + c.warp) * 4096 + atom_off(c.lane);
  uint32_t a0 = 0, a1 = 0, e0 = 0, e1 = 0;
  uint4 v0, v1;
#define Q_CHUNK(J) pack_chunk<16 * J>(a, QSCALE, QSCALE, v0, v1); sts128o<J * 512>(q0, v0); sts128o<J * 512 + 2048>(q0, v1); sq_acc(v0, a0); sq_acc(v1, a1); \
  pack_chunk<16 * J>(b, QSCALE, QSCALE, v0, v1); sts128o<32768 + J * 512>(q0, v0); sts128o<32768 + J * 512 + 2048>(q0, v1); sq_acc(v0, e0); sq_acc(v1, e1);
  Q_CHUNK(0) Q_CHUNK(1) Q_CHUNK(2) Q_CHUNK(3)
#undef Q_CHUNK
  TR(c, c.wg, 40);
  fence_async_smem();
  const float qa = norm2_max(a0, a1), qb = norm2_max(e0, e1);
  const float kn = __uint_as_float(lds32(c.base + SM_KMAX + 4 * (h >> 4)));
  TR(c, c.wg, 42);
  return __shfl_sync(~0u, bar_and(3 + c.wg, 128, (qa * kn <= BOUND2) && (qb * kn <= BOUND2)), 0);
}

__device__ __forceinline__ void issue_qk(float (&s)[64], uint64_t da, uint64_t db) {
#pragma unroll
  for (int kk = 0; kk < 8; kk++) wgmma_ss_n128<0>(s, da + (kk >> 1) * 32 + (kk & 1) * 2, db + (kk >> 1) * 32 + (kk & 1) * 2, kk > 0);
  wg_commit();
}
template<int A, int B> __device__ __forceinline__ void exp_rng(float (&s)[64]) {
#pragma unroll
  for (int i = 4 * A; i < 4 * B; i++) s[i] = ex2(s[i]);
}
template<int A, int B> __device__ __forceinline__ void sum_rng(const float (&s)[64], float (&l)[4]) {
#pragma unroll
  for (int i = A; i < B; i++) { l[0] += s[4 * i]; l[1] += s[4 * i + 1]; l[2] += s[4 * i + 2]; l[3] += s[4 * i + 3]; }
}
template<int A, int B> __device__ __forceinline__ void cvt_p(const float (&s)[64], uint32_t (&p)[32]) {
#pragma unroll
  for (int i = 2 * A; i < 2 * B; i++) p[i] = pack_bf16(s[2 * i], s[2 * i + 1]);
}
template<int K0> __device__ __forceinline__ void mask_half(float (&s)[64], int warp, int lane) {
  const int l0 = warp + (2 * (lane & 3) <= (lane >> 2)), l1 = warp + (2 * (lane & 3) < (lane >> 2));
#pragma unroll
  for (int k = 0; k < 4; k++) {
    float* t = s + 8 * (K0 + k);
    if (k >= l0) { t[0] = -INFINITY; t[6] = -INFINITY; }
    if (k >= l1) { t[1] = -INFINITY; t[7] = -INFINITY; }
    if (k > warp) { t[2] = -INFINITY; t[3] = -INFINITY; }
    if (k >= warp) { t[4] = -INFINITY; t[5] = -INFINITY; }
  }
}
__device__ __forceinline__ void row_inv(float& l0, float& l1) {
  l0 += __shfl_xor_sync(~0u, l0, 1); l1 += __shfl_xor_sync(~0u, l1, 1);
  l0 += __shfl_xor_sync(~0u, l0, 2); l1 += __shfl_xor_sync(~0u, l1, 2);
  l0 = __fdividef(1.f, l0); l1 = __fdividef(1.f, l1);
}
__device__ __forceinline__ void pack_o(const float (&o)[64], float i0, float i1, uint4 (&v)[8]) {
  pack_chunk<0>(o, i0, i1, v[0], v[1]); pack_chunk<16>(o, i0, i1, v[2], v[3]);
  pack_chunk<32>(o, i0, i1, v[4], v[5]); pack_chunk<48>(o, i0, i1, v[6], v[7]);
  pin(v);
}
__device__ __forceinline__ void softmax_safe(float (&s)[64], bool upper_only, float& m0, float& m1, float& sc0, float& sc1) {
  float a0 = m0, a1 = m1;
#pragma unroll
  for (int i = 0; i < 8; i++) { a0 = fmaxf(a0, fmaxf(s[4 * i], s[4 * i + 1])); a1 = fmaxf(a1, fmaxf(s[4 * i + 2], s[4 * i + 3])); }
  if (upper_only) { a0 = m0; a1 = m1; }
#pragma unroll
  for (int i = 8; i < 16; i++) { a0 = fmaxf(a0, fmaxf(s[4 * i], s[4 * i + 1])); a1 = fmaxf(a1, fmaxf(s[4 * i + 2], s[4 * i + 3])); }
  a0 = fmaxf(a0, __shfl_xor_sync(~0u, a0, 1)); a1 = fmaxf(a1, __shfl_xor_sync(~0u, a1, 1));
  a0 = fmaxf(a0, __shfl_xor_sync(~0u, a0, 2)); a1 = fmaxf(a1, __shfl_xor_sync(~0u, a1, 2));
  sc0 = ex2(m0 - a0); sc1 = ex2(m1 - a1);
  m0 = a0; m1 = a1;
#pragma unroll
  for (int i = 0; i < 16; i++) { s[4 * i] -= a0; s[4 * i + 1] -= a0; s[4 * i + 2] -= a1; s[4 * i + 3] -= a1; }
}
struct Att {
  float s[64], o[64], l[4], i0, i1; uint32_t p[32];
  uint32_t qaddr;
};
__device__ __forceinline__ uint32_t ctx_off(const Cons& c, int h, int qb, int rowhalf) { return T_CTX + (qb * 32 + h) * 32768 + (rowhalf * 4 + c.warp) * 4096; }
__device__ __forceinline__ void att_first(Cons& c, Att& a) {
  a.qaddr = c.daddr(0) + c.wg * 16384;
  c.wait(4);
  c.turn();
  wg_fence();
  issue_qk(a.s, odesc(a.qaddr, 16, 2048, 2), odesc(c.daddr(4), 16, 2048, 2));
  c.pass();
#pragma unroll
  for (int i = 0; i < 64; i++) a.o[i] = 0.f;
#pragma unroll
  for (int i = 0; i < 32; i++) a.p[i] = 0;
  a.l[0] = a.l[1] = a.l[2] = a.l[3] = 0.f; a.i0 = a.i1 = 0.f;
  wg_wait<0>(); fence_regs(a.s);
  c.release(4, 2);
}
__device__ __forceinline__ void att_last(Cons& c, Att& a, Pend& w, int h, int g, bool drain) {
#pragma unroll 1
  for (int k = drain ? 0 : 1; k < 2; k++) {
    if (k == 1) {
      const int uv = att_slot(1);
      c.wait(uv);
      c.turn();
      fence_regs(a.o); fence_regs(a.p);
      wgmma_pv_sel(a.o, a.p, odesc(c.daddr(uv), 512, 2048, 2), !(drain && c.wg == 1), !drain);
      c.pass();
      a.i0 = a.l[0] + a.l[1]; a.i1 = a.l[2] + a.l[3]; row_inv(a.i0, a.i1);
      wg_wait<0>(); fence_regs(a.o); fence_regs(a.p);
      c.release(uv, 2);
    }
    pack_o(a.o, a.i0, a.i1, w.lo);
    if (k == 0) tile_store<0, 4>(w.lo, ctx_off(c, h, 15, c.wg), c.lane);
  }
  w.dst = ctx_off(c, h, g, 1 - c.wg);
}
__device__ __forceinline__ void cons_att(Cons& c, int h, int g, int fast, Pend& w) {
  Att a;
  att_first(c, a);
  float m0 = -INFINITY, m1 = -INFINITY, sc0 = 0.f, sc1 = 0.f;
  int uk = 10, nrel = 0;
#pragma unroll 1
  for (int d = g - 15;;) {
    const bool lo = d == c.wg;
    if ((unsigned)d < 2 || !fast) {
      if ((unsigned)d < 2) mask_half<4>(a.s, c.warp, c.lane);
      if (!fast) {
        if (d == 1) m0 = m1 = -INFINITY;
        softmax_safe(a.s, lo, m0, m1, sc0, sc1);
        a.l[0] *= sc0; a.l[1] *= sc0; a.l[2] *= sc1; a.l[3] *= sc1;
      }
    }
    exp_rng<8, 16>(a.s); sum_rng<8, 16>(a.s, a.l);
    exp_rng<ATT_SPLIT, 8>(a.s);
    sched_fence(((a.l[0] + a.l[1]) + (a.l[2] + a.l[3])) + (ATT_SPLIT < 8 ? a.s[4 * ATT_SPLIT + 3] : 0.f), c.base + SM_DUMMY);
    wg_wait<0>(); fence_regs(a.o); fence_regs(a.p);
    c.release(14 - uk, nrel);
    nrel = 2; uk ^= 12;
    if (d == 0) a.qaddr += 32768;
    const uint64_t dq = odesc(a.qaddr, 16, 2048, 2), dk = odesc(c.daddr(uk) - (d + 1 == c.wg ? 16384 : 0), 16, 2048, 2), dv = odesc(c.daddr(14 - uk), 512, 2048, 2);
    if (!lo) { exp_rng<0, ATT_SPLIT>(a.s); sum_rng<0, 8>(a.s, a.l); cvt_p<0, 16>(a.s, a.p); }
    else if (gridDim.y == 1) cvt_p<8, 16>(a.s, a.p);
    if (!fast || d == g + 1) {
      if (!fast && d != 1) {
#pragma unroll
        for (int i = 0; i < 16; i++) { a.o[4 * i] *= sc0; a.o[4 * i + 1] *= sc0; a.o[4 * i + 2] *= sc1; a.o[4 * i + 3] *= sc1; }
      }
      if (d == g + 1) break;
    }
    d++;
    if (c.wg == 0) c.wait(uk); else c.skip(uk);
    c.turn();
    fence_regs(a.o); fence_regs(a.p);
    wg_fence();
    issue_qk(a.s, dq, dk);
    if (d == 2) {
      uint4 v[8];
      pack_o(a.o, a.i0, a.i1, v); tile_store<0, 4>(v, ctx_off(c, h, 15 - g, c.wg), c.lane);
    }
    wgmma_pv_sel(a.o, a.p, dv, !lo, d != 2);
    c.pass();
    if (d == 1) {
      a.i0 = a.l[0] + a.l[1]; a.i1 = a.l[2] + a.l[3]; row_inv(a.i0, a.i1);
      a.l[0] = a.l[1] = a.l[2] = a.l[3] = 0.f;
    }
    wg_wait<1>(); fence_regs(a.s);
    c.release(uk, 2);
    c.release(d == 0 ? 0 : 2, (d == 0 || d == g + 1) ? 2 : 0);
  }
  att_last(c, a, w, h, g, g == 0);
}

constexpr int CV_H = 1024, CV_U = 5120, CV_D = CV_U + 4128, CV_ROW = 1056;
template<int OFF> __device__ __forceinline__ uint32_t lds32o(uint32_t a) { uint32_t v; asm volatile("ld.shared.u32 %0, [%1+%2];" : "=r"(v) : "r"(a), "n"(OFF) : "memory"); return v; }
template<int G, int G1 = 16> __device__ __forceinline__ void conv_lda(uint32_t (&a)[64], uint32_t p) {
  a[4 * G + 0] = lds32o<-256 * G>(p);
  a[4 * G + 1] = lds32o<-256 * G - 128>(p);
  a[4 * G + 2] = lds32o<-256 * G + 16>(p);
  a[4 * G + 3] = lds32o<-256 * G - 112>(p);
  if constexpr (G + 1 < G1) conv_lda<G + 1, G1>(a, p);
}
template<int R, int G0, int G1> __device__ __forceinline__ void conv_mma(float (&d)[32], const uint32_t (&a)[64], uint64_t db) {
#pragma unroll
  for (int G = G0; G < G1; G++) wgmma_rs_n64<0>(d, a[4 * G], a[4 * G + 1], a[4 * G + 2], a[4 * G + 3], db + 64 * R - 16 * G, G > 0);
}
template<int R> __device__ __forceinline__ void conv_st(const float (&d)[32], uint32_t wq, float& c0, float& c1) {
#pragma unroll
  for (int n = 0; n < 8; n++) { sts64f(wq + (R * 64 + n * 8) * 4, d[4 * n] + c0, d[4 * n + 1] + c1); c0 = d[4 * n + 2]; c1 = d[4 * n + 3]; }
}
__device__ __forceinline__ void cons_conv(Cons& c, int cta, int nch) {
  const int r = c.lane >> 2, q = c.lane & 3, tid = c.warp * 32 + c.lane;
  const uint32_t part = c.addr(4) - 2048 + (1 - c.wg) * (32 * CV_ROW) + 32;
  const uint32_t aoff = CV_U + ((r & 1) ? 0 : UPITCH) + 4 * (((2039 - r) >> 1) + q - 8 * c.warp);
  const uint32_t wq = part + (c.warp * 8 + r) * CV_ROW + q * 8, rq = part + tid * 8;
  uint32_t a[64];
  c.wait(c.wg); c.skip(c.wg ^ 1);
  conv_lda<0>(a, c.addr(c.wg) + aoff);
  c.wait(4);
  sts64f(part + (tid >> 2) * CV_ROW - 32 + q * 8, 0.f, 0.f);
#pragma unroll 1
  for (int i = 0; i < nch / 2; i++) {
    const int u = 2 * (i & 1) + c.wg;
    float d0[32], d1[32], d2[32], d3[32];
    float c0 = 0.f, c1 = 0.f;
    const uint64_t db = odesc(c.daddr(u) + CV_H - 16, 16, 128, 0);
    c.turn();
    fence_regs(a);
    wg_fence();
    conv_mma<0, 0, 4>(d0, a, db); conv_mma<1, 0, 8>(d1, a, db); wg_commit();
    conv_mma<2, 0, 12>(d2, a, db); wg_commit();
    wg_wait<1>(); fence_regs(d0); fence_regs(d1);
    conv_st<0>(d0, wq, c0, c1);
    wg_fence();
    conv_mma<3, 0, 8>(d3, a, db);
    conv_st<1>(d1, wq, c0, c1);
    conv_mma<3, 8, 16>(d3, a, db); wg_commit();
    c.pass();
    wg_wait<1>(); fence_regs(d2);
    conv_st<2>(d2, wq, c0, c1);
    wg_wait<0>(); fence_regs(d3); fence_regs(a);
    conv_st<3>(d3, wq, c0, c1);
    TR(c, c.wg, 50);
    const uint32_t ub = c.addr(u);
    const uint4 ua = lds128(ub + CV_U + 4064 - 32 * tid + 16), uc = lds128(ub + CV_U + 4064 - 32 * tid);
    const uint32_t D2 = lds32(ub + CV_D);
    bar_sync(3 + c.wg, 128);
    c.release2(u);
    TR(c, c.wg, 51);
    float y0[8], y1[8];
#pragma unroll
    for (int rr = 0; rr < 8; rr++) { const float2 v = lds64f(rq + rr * CV_ROW); y0[rr] = v.x; y1[rr] = v.y; }
#pragma unroll
    for (int w = 1; w < 4; w++) {
#pragma unroll
      for (int rr = 0; rr < 8; rr++) { const float2 v = lds64f(rq + (w * 8 + rr) * CV_ROW - w * 8); y0[rr] += v.x; y1[rr] += v.y; }
    }
    if (i + 1 < nch / 2) { c.wait(u ^ 2); c.skip(u ^ 3); conv_lda<0>(a, c.addr(u ^ 2) + aoff); }
    uint4 z0, z1;
    z0.x = hadd2(pack_bf16(y0[0], y0[1]), hmul2(__byte_perm(ua.w, 0, 0x1032), D2));
    z0.y = hadd2(pack_bf16(y0[2], y0[3]), hmul2(__byte_perm(ua.z, 0, 0x1032), D2));
    z0.z = hadd2(pack_bf16(y0[4], y0[5]), hmul2(__byte_perm(ua.y, 0, 0x1032), D2));
    z0.w = hadd2(pack_bf16(y0[6], y0[7]), hmul2(__byte_perm(ua.x, 0, 0x1032), D2));
    z1.x = hadd2(pack_bf16(y1[0], y1[1]), hmul2(__byte_perm(uc.w, 0, 0x1032), D2));
    z1.y = hadd2(pack_bf16(y1[2], y1[3]), hmul2(__byte_perm(uc.z, 0, 0x1032), D2));
    z1.z = hadd2(pack_bf16(y1[4], y1[5]), hmul2(__byte_perm(uc.y, 0, 0x1032), D2));
    z1.w = hadd2(pack_bf16(y1[6], y1[7]), hmul2(__byte_perm(uc.x, 0, 0x1032), D2));
    uint4* zp = (uint4*)(g_z + (size_t)conv_channel(cta, 2 * i + c.wg) * 2048 + tid * 16);
    zp[0] = z0; zp[1] = z1;
    TR(c, c.wg, 52);
    if ((i & 15) == 15 || i == nch / 2 - 1) c.signal(SIG_Z + (i >> 4));
  }
  c.release(4, 4);
}

constexpr int OC_START = 2, OC_LEN = 15, OC_PART = 13824, OC_ROW = 544;
__device__ __forceinline__ int out_next(int u) { return u == 12 ? 4 : u + 2; }
struct Out { float acc[64]; int pu; uint64_t da, db; };
template<bool FIRST, bool REL> __device__ __forceinline__ void out_step(Cons& c, Out& o) {
  const int pu = o.pu, u = out_next(pu);
  o.pu = u;
  c.wait(u);
  const uint64_t da = o.da + (uint32_t)(u * 1024), db = o.db + (uint32_t)(u * 1024);
  wg_fence();
#pragma unroll
  for (int kk = 0; kk < 4; kk++) wgmma_ss_n128<1>(o.acc, da + (kk >> 1) * 32 + (kk & 1) * 2, db + kk * 128, !(FIRST && kk == 0));
  wg_commit();
  if (REL) { wg_wait<1>(); c.release(pu, 2); }
}
template<int I0, int I1> __device__ __forceinline__ void oc_red(float (&y)[8], uint32_t rq) {
#pragma unroll
  for (int i = I0; i < I1; i++) { const float v = __uint_as_float(lds32(rq + i * OC_ROW - (i >> 3) * 8)); y[i & 7] = i < 8 ? v : y[i & 7] + v; }
}
__device__ __forceinline__ void oc_emit(const float (&y)[8], const uint4& u, uint32_t D2, __nv_bfloat16* dst) {
  uint4 z;
  z.x = hadd2(pack_bf16(y[0], y[1]), hmul2(__byte_perm(u.w, 0, 0x1032), D2));
  z.y = hadd2(pack_bf16(y[2], y[3]), hmul2(__byte_perm(u.z, 0, 0x1032), D2));
  z.z = hadd2(pack_bf16(y[4], y[5]), hmul2(__byte_perm(u.y, 0, 0x1032), D2));
  z.w = hadd2(pack_bf16(y[6], y[7]), hmul2(__byte_perm(u.x, 0, 0x1032), D2));
  *(uint4*)dst = z;
}
template<int MASK> __device__ __forceinline__ void cons_out(Cons& c, const Maps& M, int cta, Pend& w) {
  const int mb = out_mb(cta), nb = out_nb(cta);
  Out o;
  o.da = odesc(c.daddr(0) + c.wg * 8192, 16, 1024, 2); o.db = odesc(c.daddr(1), 8192, 1024, 1);
  o.pu = 5 + gridDim.y;
  out_step<true, false>(c, o);
  if (MASK & PH_ATT) tile_store<0, 2>(w.lo, w.dst, c.lane);
  out_step<false, true>(c, o);
  if (MASK & PH_ATT) { tile_store<2, 4>(w.lo, w.dst, c.lane); c.signal(SIG_CTX + 1); }
  int ks = OC_START;
  if (MASK & PH_CONV) {
    const int r = c.lane >> 2, q = c.lane & 3, tid = c.warp * 32 + c.lane, u = 2 * c.wg;
    const uint32_t ub = c.addr(u), part = ub + OC_PART + 32;
    const uint32_t ap = ub + CV_U + ((r & 1) ? 0 : UPITCH) + 4 * (((2039 - r) >> 1) + q - 8 * c.warp);
    const uint32_t wq = part + (c.warp * 8 + r) * OC_ROW + q * 8, rq = part + tid * 4;
    const int nr = (CONV_REG + 1 - c.wg) >> 1;
#define STEP(N) out_step<false, true>(c, o);
#pragma unroll 1
    for (int i = 0; i < nr; i++) {
      uint32_t a[64];
      float d0[32], d1[32], y[8], c0 = 0.f, c1 = 0.f;
      const uint64_t db = odesc(c.daddr(u + (i >> 8)) + CV_H - 16, 16, 128, 0);
      c.wait(u);
      conv_lda<0, 3>(a, ap);
      STEP(0)
      conv_lda<3, 6>(a, ap);
      STEP(1)
      conv_lda<6, 9>(a, ap);
      STEP(2)
      fence_regs(reinterpret_cast<uint32_t (&)[32]>(a));
      wg_fence();
      conv_mma<0, 0, 4>(d0, a, db); conv_mma<1, 0, 8>(d1, a, db); wg_commit();
      conv_lda<9, 13>(a, ap);
      STEP(3)
      fence_regs(d0); fence_regs(d1);
      conv_lda<13, 16>(a, ap);
      STEP(4)
      bar_sync(3 + c.wg, 128);
      sts64f(wq - 32, 0.f, 0.f);
      conv_st<0>(d0, wq, c0, c1);
      STEP(5)
      float e0 = d1[28] + d1[26], e1 = d1[29] + d1[27];
      conv_st<1>(d1, wq, c0, c1);
      asm volatile("add.f32 %0, %0, 0f80000000;" : "+f"(c0)); asm volatile("add.f32 %0, %0, 0f80000000;" : "+f"(c1));
      fence_regs(a);
      wg_fence();
      conv_mma<2, 0, 12>(d0, a, db); conv_mma<3, 0, 16>(d1, a, db); wg_commit();
      bar_sync(3 + c.wg, 128);
      oc_red<0, 8>(y, rq);
      STEP(6)
      fence_regs(d0); fence_regs(d1); fence_regs(a);
      const uint4 u0 = lds128(ub + CV_U + 4080 - 16 * tid), u1 = lds128(ub + CV_U + 2032 - 16 * tid);
      const uint32_t D2 = lds32(ub + CV_D);
      oc_red<8, 12>(y, rq);
      __syncwarp();
      c.release2(u);
      STEP(7)
      oc_red<12, 24>(y, rq);
      STEP(8)
      __nv_bfloat16* zp = g_z + (uint32_t)(conv_channel(cta, 2 * i + c.wg) * 2048 + (threadIdx.x & 127) * 8);
      oc_red<24, 32>(y, rq);
      oc_emit(y, u0, D2, zp);
      bar_sync(3 + c.wg, 128);
      STEP(9)
      sts64f(wq - 32, e0, e1);
      conv_st<0>(d0, wq, c0, c1);
      STEP(10)
      conv_st<1>(d1, wq, c0, c1);
      bar_sync(3 + c.wg, 128);
      oc_red<0, 8>(y, rq);
      STEP(11)
      oc_red<8, 16>(y, rq);
      STEP(12)
      oc_red<16, 24>(y, rq);
      STEP(13)
      oc_red<24, 32>(y, rq);
      oc_emit(y, u1, D2, zp + 1024);
      if (i == nr - 1) { c.signal(SIG_Z); c.release2(u + 1); }
      STEP(14)
    }
#undef STEP
    if (((CONV_REG + c.wg) >> 1) & 1) c.skip(u ^ 2);
    ks += nr * OC_LEN;
  }
  TS(c.wg, 9);
#pragma unroll 1
  for (; ks < 57; ks++) out_step<false, true>(c, o);
  uint32_t ga[32];
  c.wait(0);
  const float g0 = __uint_as_float(lds32(c.base + SM_GATE + 4 * (c.wg * 64 + c.warp * 16 + (c.lane >> 2)))), g1 = __uint_as_float(lds32(c.base + SM_GATE + 32 + 4 * (c.wg * 64 + c.warp * 16 + (c.lane >> 2))));
  const uint32_t gg0 = pack_bf16(g0, g0), gg1 = pack_bf16(g1, g1);
  const uint32_t og0 = pack_bf16(1.f - g0, 1.f - g0), og1 = pack_bf16(1.f - g1, 1.f - g1);
  const int xr = c.wg * 64 + c.warp * 16 + (c.lane & 15);
  const uint32_t xa = c.addr(0) + xr * 128, xs = xr & 7, xh = c.lane >> 4;
  const int zr = (c.lane & 7) + ((c.lane >> 4) << 3);
  const uint32_t za = c.addr(2) + c.wg * 16384 + zr * 128 + (((c.warp * 2 + ((c.lane >> 3) & 1)) ^ (zr & 7)) << 4);
#pragma unroll
  for (int i = 0; i < 8; i++) {
    if (i == 0) out_step<false, true>(c, o);
    if (i == 3) out_step<false, true>(c, o);
    if (i == 6) out_step<false, true>(c, o);
    ldsm4(xa + (i >> 2) * 16384 + ((((i & 3) * 2 + xh) ^ xs) << 4), ga[4 * i], ga[4 * i + 1], ga[4 * i + 2], ga[4 * i + 3]);
  }
#pragma unroll 1
  for (ks = 60; ks < 63; ks++) { out_step<false, false>(c, o); wg_wait<1>(); }
  c.wait(2);
#pragma unroll
  for (int i = 0; i < 8; i++) {
    if (i == 2) out_step<false, false>(c, o);
    uint32_t z0, z1, z2, z3;
    ldsm4t(za + i * 2048, z0, z1, z2, z3);
    ga[4 * i + 0] = hmul2(gg0, hmul2(ga[4 * i + 0], z0)); ga[4 * i + 1] = hmul2(gg1, hmul2(ga[4 * i + 1], z1));
    ga[4 * i + 2] = hmul2(gg0, hmul2(ga[4 * i + 2], z2)); ga[4 * i + 3] = hmul2(gg1, hmul2(ga[4 * i + 3], z3));
  }
  c.signal(SIG_DONE);
  asm volatile("barrier.cluster.arrive.relaxed;" ::: "memory");
  fence_regs(ga);
  wg_wait<0>(); fence_regs(o.acc);
#pragma unroll
  for (int i = 0; i < 8; i++) {
    const uint32_t r0 = hadd2(ga[4 * i + 0], hmul2(og0, pack_bf16(o.acc[8 * i + 0], o.acc[8 * i + 1])));
    const uint32_t r1 = hadd2(ga[4 * i + 1], hmul2(og1, pack_bf16(o.acc[8 * i + 2], o.acc[8 * i + 3])));
    const uint32_t r2 = hadd2(ga[4 * i + 2], hmul2(og0, pack_bf16(o.acc[8 * i + 4], o.acc[8 * i + 5])));
    const uint32_t r3 = hadd2(ga[4 * i + 3], hmul2(og1, pack_bf16(o.acc[8 * i + 6], o.acc[8 * i + 7])));
    stsm4(xa + (i >> 2) * 16384 + ((((i & 3) * 2 + xh) ^ xs) << 4), r0, r1, r2, r3);
  }
  fence_async_smem();
  __syncwarp();
  if (c.lane < 2) {
    const int r0 = c.wg * 64 + c.warp * 16;
    tma2d_store(&M.out, c.addr(0) + c.lane * 16384 + r0 * 128, nb * 128 + c.lane * 64, mb * 128 + r0);
    asm volatile("cp.async.bulk.commit_group;\ncp.async.bulk.wait_group.read 0;" ::: "memory");
  }
}

__device__ __forceinline__ void load_conv(Prod& p, const Maps& M, int u, int ch) {
  if (elect()) {
    mbar_expect(p.full(u), 5120 + UCH);
    tma3d(p.addr(u), &M.h, 0, -8, ch, p.full(u), POL(4));
    bulk_g2s(p.addr(u) + CV_U, g_u + (size_t)ch * UCH, UCH, p.full(u), POL(4));
  }
}
__device__ __forceinline__ void prod_conv(Prod& p, const Maps& M, int cta, int nch) {
  int ready = -1;
#pragma unroll 1
  for (int i = 0; i < nch; i++) {
    const int ch = conv_channel(cta, i);
    const int u = i & 3;
    if ((ch >> 6) != ready) { ready = ch >> 6; if (cta < NREG) mbar_wait(p.base + SM_RDY + 8 * RDY_U, 0); else cnt_wait(g_cnt + (C_U + ready) * CSTRIDE, 32); }
    p.acquire(u, 1);
    load_conv(p, M, u, ch);
    if (i == 3) { p.acquire(4, 4); if (elect()) mbar_arrive(p.full(4)); }
  }
}
#define HOIST(v) asm volatile("" : "+r"(v))
template<int MASK> __device__ __forceinline__ void producer(const Maps& M, const Params& P, uint32_t base, int cta, int lane) {
  Prod p{base, ((MASK & PH_KV) && cta < NREG) ? 0xffffcfffu ^ ((1u << (3 * NFIRST)) - 1) : 0xffffffffu, lane,
         (cta * 3 + 2) * 2048};
  if (cta >= NREG) { if (MASK & PH_CONV) prod_conv(p, M, cta, CONV_EXTRA); return; }
  const int g = cta & 7, j = cta >> 3, rank = cta & 1;
#pragma unroll 1
  for (int half = 0; half < 2; half++) {
    const int h = j + 16 * half;
    if (MASK & PH_KV) {
      const CUtensorMap* mw = rank ? &M.wv : &M.wk;
#pragma unroll 1
      for (int it = half ? 0 : NFIRST; it < 16; it++) {
        const int u = gemm_unit(it);
        uint32_t bar = p.full(u), d0 = p.addr(u), d1 = p.addr(u + 1 + rank); int k0 = (it & 7) * 64, r0 = (2 * g + (it >> 3)) * 128;
        HOIST(bar); HOIST(d0); HOIST(d1); HOIST(k0); HOIST(r0);
        p.acquire(u, 3);
        if (elect()) {
          mbar_expect(bar, 3 * UNIT);
          tma3d_mc(d1, mw, 0, k0, 2 * h, bar, POL(0) && it >= 8);
          tma2d(d0, &M.c, k0, r0, bar);
        }
      }
    }
    if (MASK & PH_ATT) {
#pragma unroll 1
      for (int ks = 0; ks < 16; ks++) {
        const int u = gemm_unit(ks);
        uint32_t bar = p.full(u), d0 = p.addr(u), d1 = p.addr(u + 1), d2 = p.addr(u + 2) + rank * 8192; int k0 = ks * 64;
        HOIST(bar); HOIST(d0); HOIST(d1); HOIST(d2); HOIST(k0);
        p.acquire(u, 3);
        if (elect()) {
          mbar_expect(bar, 3 * UNIT);
          tma2d_mc(d2, &M.wq, h * 128 + rank * 64, k0, bar, POL(1));
          tma2d(d0, &M.x, k0, (15 - g) * 128, bar);
          tma2d(d1, &M.x, k0, g * 128, bar);
        }
      }
      TS(2, 8 * half + 0);
      mbar_wait(base + SM_RDY + 8 * (RDY_KV + half), 0);
      TS(2, 8 * half + 1);
      const uint8_t* KVh = g_T + T_KV + (size_t)kv_slot<MASK>(h) * 16 * 65536;
#pragma unroll 1
      for (int i = 0; i < 34; i++) {
        const int isv = (i > 0 && !(i & 1)) || i == 33;
        const int st = i == 33 ? 16 : (isv ? (i >> 1) - 1 : (i + 1) >> 1);
        const int u = att_slot(i & 3);
        const bool own = st == 15 - (g & 6);
        uint32_t bar = p.full((isv && i < 33) ? 14 - u : u), d0 = p.addr(own ? u : u + rank), off = (st <= 15 - g ? st : 16 - st) * 65536 + isv * 32768 + (own ? 0 : rank * UNIT);
        HOIST(bar); HOIST(d0); HOIST(off);
        p.acquire(u, 2);
        if (elect()) {
          if (!isv || i == 33) mbar_expect(bar, (i == 0 || i == 33) ? 32768 : 65536);
          if (own) bulk_g2s(d0, KVh + off, 32768, bar, POL(6)); else bulk_g2s_mc(d0, KVh + off, UNIT, bar, POL(6));
        }
        if (i == 0) { p.acquire(0, 4); if (elect()) mbar_arrive(p.full(0)); }
      }
    }
  }
  if ((MASK & PH_CONV) && !(MASK & PH_OUT)) prod_conv(p, M, cta, CONV_REG);
  if (MASK & PH_OUT) {
    const int y0 = out_mb(cta) * 512 + rank * 8, z0 = 2 * out_nb(cta);
    int u = 6;
#pragma unroll 1
    for (int hf = 0; hf < 2; hf++) {
      TS(2, 16 + 2 * hf);
      mbar_wait(base + SM_RDY + 8 * (RDY_CTX + hf), 0);
      TS(2, 17 + 2 * hf);
#pragma unroll 1
      for (int ks = hf * 32; ks < hf * 32 + 32; ks++) {
        u = out_next(u);
        uint32_t bar = p.full(u), d0 = p.addr(u) + rank * 8192, d1 = p.addr(u + 1); int x = (ks & 1) * 256, y = y0 + (ks >> 1) * 16, k0 = ks * 64;
        HOIST(bar); HOIST(d0); HOIST(d1); HOIST(x); HOIST(y); HOIST(k0);
        p.acquire(u, 2);
        if (elect()) {
          mbar_expect(bar, 2 * UNIT);
          tma2d_mc(d0, &M.ctx, x, y, bar, POL(5));
          tma3d(d1, &M.wo, 0, k0, z0, bar, POL(2));
        }
      }
    }
    if (elect()) mbar_arrive(base + SM_RDY + 8 * RDY_Z);
  }
}
template<int MASK> __device__ __forceinline__ void producer2(const Maps& M, const Params& P, uint32_t base, int cta, int w, int lane) {
  Prod p{base, 0xffffffffu, lane, 0};
  const int mb = out_mb(cta), nb = out_nb(cta), u = 2 * w;
  if (MASK & PH_CONV) {
    mbar_wait_slow(base + SM_SIG + 8 * (SIG_ATT + 1), 0);
    mbar_wait_slow(base + SM_RDY + 8 * RDY_U, 0);
#pragma unroll 1
    for (int i = w; i < CONV_REG; i += 2) { p.acquire_slow(u, i < 2 ? 2 : 1); load_conv(p, M, u, conv_channel(cta, i)); }
  }
  p.acquire_slow(u, 2);
  TSA(50 + 2 * w);
  mbar_wait_slow(base + SM_RDY + 8 * (w ? RDY_Z : RDY_G), 0);
  TSA(51 + 2 * w);
  if (elect()) {
    mbar_expect(p.full(u), 2 * UNIT + (w ? 0 : 512));
    tma2d(p.addr(u), w ? &M.z : &M.x, (w ? mb : nb) * 128, (w ? nb : mb) * 128, p.full(u), POL(5));
    tma2d(p.addr(u + 1), w ? &M.z : &M.x, (w ? mb : nb) * 128 + 64, (w ? nb : mb) * 128, p.full(u), POL(5));
    if (!w) bulk_g2s(base + SM_GATE, g_gate + mb * 128, 512, p.full(u));
  }
}

__device__ __forceinline__ constexpr uint32_t PUB(int sig, int cnt, int n) { return 0x80000000u | (sig << 24) | (n << 8) | cnt; }
__device__ __forceinline__ constexpr uint32_t GET(int rdy, int cnt, int n) { return (rdy << 24) | (n << 8) | cnt; }
template<int MASK> __device__ __forceinline__ void sync_agent(uint32_t base, int cta, int lane) {
  if ((base & 0x3FFFF) != SMEM_BASE) asm volatile("trap;");
  const int g = cta & 7, j = cta >> 3, go = min(out_mb(cta), 15 - out_mb(cta));
  const int c0 = conv_channel(cta, 0), c1 = c0 + CONV_REG - 1, n0 = min(CONV_REG, 128 - (c0 & 127));
  constexpr bool KV = MASK & PH_KV, ATT = MASK & PH_ATT, CONV = MASK & PH_CONV, OUT = MASK & PH_OUT, ALL = MASK == PH_ALL;
  uint32_t e = 0;
  if (cta >= NREG) { if (CONV && lane * 32 < CONV_EXTRA) e = PUB(SIG_Z + lane, C_Z + lane, min(32, CONV_EXTRA - lane * 32)); }
  else switch (lane) {
    case 0:  if (KV) e = PUB(SIG_KV, C_KV + j, 1); break;
    case 1:  if (ATT) e = GET(RDY_KV, C_KV + j, 8); break;
    case 2:  if (ALL) e = PUB(SIG_WAR, C_WAR + j, 1); break;
    case 3:  if (ATT) e = PUB(SIG_CTX, C_CTX + g, 1); break;
    case 4:  if (ALL) e = GET(RDY_WAR, C_WAR + j, 8); break;
    case 5:  if (KV) e = PUB(SIG_KV + 1, C_KV + 16 + j, 1); break;
    case 6:  if (ATT) e = GET(RDY_KV + 1, C_KV + 16 + j, 8); break;
    case 7:  if (OUT) e = GET(RDY_CTX, C_CTX + go, 16); break;
    case 8:  if (CONV) e = GET(RDY_U, C_U + (c0 >> 6), 32); break;
    case 9:  if (CONV) e = GET(RDY_U, C_U + (c1 >> 6), 32); break;
    case 10: if (ATT) e = PUB(SIG_CTX + 1, C_CTX + 8 + g, 1); break;
    case 11: if (OUT) e = GET(RDY_CTX + 1, C_CTX + 8 + go, 16); break;
    case 12: if (OUT) e = GET(RDY_G, C_GATE, 256); break;
    case 13: if (CONV) e = PUB(SIG_Z, C_Z + (c0 >> 7), n0); break;
    case 14: if (CONV && n0 < CONV_REG) e = PUB(SIG_Z, C_Z + (c1 >> 7), CONV_REG - n0); break;
    case 15: if (OUT) e = GET(RDY_Z, C_Z + out_nb(cta), 128); break;
  }
  __syncwarp();
#pragma unroll 1
  for (int i = 0; i < 16; i++) {
    const uint32_t x = __shfl_sync(~0u, e, i), id = (x >> 24) & 127, n = (x >> 8) & 0xffff;
    if (x == 0) continue;
    unsigned* cnt = g_cnt + (x & 255) * CSTRIDE;
    if (x >> 31) {
      mbar_wait_slow(base + SM_SIG + 8 * id, 0);
      if (lane == 0) cnt_publish(cnt, n);
    } else {
      cnt_wait(cnt, n);
      if (id < 2) {
        const float4 kn = __ldcg((const float4*)(g_kn2 + kv_slot<MASK>(j + 16 * id) * 128) + lane);
        const uint32_t m = __reduce_max_sync(~0u, max(max(__float_as_uint(kn.x), __float_as_uint(kn.y)), max(__float_as_uint(kn.z), __float_as_uint(kn.w))));
        if (lane == 0) asm volatile("st.shared.u32 [%0], %1;" :: "r"(base + SM_KMAX + 4 * id), "r"(m) : "memory");
      }
      if (lane == 0) mbar_arrive(base + SM_RDY + 8 * id);
    }
    __syncwarp();
  }
}

template<int MASK> __device__ __forceinline__ void aux_pre(const Maps& M, const Params& P, uint32_t base, int cta, int aw, int lane) {
  const uint32_t kb = base + 12 * UNIT, bar = base + SM_PRE;
  const int r = lane >> 2, q = lane & 3;
  const int mi = lane >> 3, row0 = (lane & 6) + 1 - (lane & 1);
  if (PRE_DELAY) mbar_wait_slow(base + SM_BAR + 8 * 9, 0);
#pragma unroll 1
  for (int it = 0; it < 4; it++) {
    if (it == PRE_EARLY && MASK == PH_ALL) mbar_wait_slow(base + SM_SIG + 8 * (SIG_ATT + PRE_HALF), 0);
    const int cg = it * 4 + (cta >> 5), tb = cta & 31;
    if (aw == 0 && elect()) {
      mbar_expect(bar, 2 * 9216);
      tma4d(kb, &M.k, cg * 64, 0, tb * 8 - 1, 0, bar, POL(3));
      tma4d(kb + 9216, &M.v, cg * 64, 0, tb * 8 - 1, 0, bar, POL(3));
    }
    const uint2 swl = __ldg((const uint2*)(P.shift + (cg * 64 + aw * 32 + lane) * 4));
    if (tb == 0) {
      uint8_t* e = g_u + (size_t)(cg * 64 + aw * 32 + lane) * UCH + 4096;
      *(uint4*)e = make_uint4(0, 0, 0, 0); *(uint4*)(e + UPITCH) = make_uint4(0, 0, 0, 0);
      *(uint32_t*)(e + 32) = (uint32_t)__bfloat16_as_ushort(P.D[cg * 64 + aw * 32 + lane]) * 0x10001u;
    }
    mbar_wait_slow(bar, it & 1);
#pragma unroll 1
    for (int bl = 0; bl < 8; bl++) {
      const int oc = aw * 4 + (bl >> 1), hb = bl & 1, ch = cg * 64 + oc * 8 + r;
      const uint2 sw = make_uint2(__shfl_sync(~0u, swl.x, (bl >> 1) * 8 + r), __shfl_sync(~0u, swl.y, (bl >> 1) * 8 + r));
      const uint32_t w0 = __byte_perm(sw.x, 0, 0x1010), w1 = __byte_perm(sw.x, 0, 0x3232), w2 = __byte_perm(sw.y, 0, 0x1010), w3 = __byte_perm(sw.y, 0, 0x3232);
      const int ra = (mi * 9 + 4 * hb + 1) * 2 + row0;
      const int rb = ((mi == 0 ? 3 : mi) * 9 + 4 * hb) * 2 + row0;
      uint32_t k[7], v[5];
      ldsm4t(kb + ra * 128 + ((oc ^ (ra & 7)) << 4), k[3], k[4], k[5], k[6]);
      ldsm4t(kb + 9216 + ra * 128 + ((oc ^ (ra & 7)) << 4), v[1], v[2], v[3], v[4]);
      ldsm4t(kb + (mi == 0 ? 9216 : 0) + rb * 128 + ((oc ^ (rb & 7)) << 4), v[0], k[0], k[1], k[2]);
      uint32_t o1 = __byte_perm(k[1], k[0], 0x5432);
#pragma unroll
      for (int m = 0; m < 5; m++) {
        const uint32_t o2 = __byte_perm(k[m + 2], k[m + 1], 0x5432);
        v[m] = hmul2(hadd2(hadd2(hadd2(hmul2(o1, w3), hmul2(k[m + 1], w2)), hmul2(o2, w1)), hmul2(k[m + 2], w0)), v[m]);
        o1 = o2;
      }
      uint8_t* e0 = g_u + (size_t)ch * UCH + (2040 - tb * 64 - hb * 32 - 8 * q) * 2;
      *(uint4*)e0 = make_uint4(v[4], v[3], v[2], v[1]);
      *(uint4*)(e0 + UPITCH) = make_uint4(__byte_perm(v[4], v[3], 0x5432), __byte_perm(v[3], v[2], 0x5432), __byte_perm(v[2], v[1], 0x5432), __byte_perm(v[1], v[0], 0x5432));
    }
    bar_sync(5, 64);
    if (aw == 0) { TSA(40 + it); }
    if (aw == 1 && lane == 0) asm volatile("red.release.gpu.global.add.u32 [%0], 1;" :: "l"(g_cnt + (C_U + cg) * CSTRIDE) : "memory");
  }
  uint32_t rel;
  asm volatile("mapa.shared::cluster.u32 %0, %1, %2;" : "=r"(rel) : "r"(base + SM_BAR + 128 + 8 * (12 + (lane & 1))), "r"((lane >> 1) & 1));
  if (lane < 4) asm volatile("mbarrier.arrive.shared::cluster.b64 _, [%0], 4;" :: "r"(rel) : "memory");
  uint4 gw[4];
#pragma unroll
  for (int i = 0; i < 4; i++) gw[i] = __ldg((const uint4*)P.gw + i * 32 + lane);
#pragma unroll 1
  for (int row = cta * 16 + aw * 8; row < cta * 16 + aw * 8 + 8; row++) {
    float a = 0.f;
#pragma unroll
    for (int i = 0; i < 4; i++) {
      const uint4 xv = __ldg((const uint4*)(P.x + (size_t)row * 1024) + i * 32 + lane);
      uint32_t m;
      m = hmul2(xv.x, gw[i].x); a += bf_lo(m) + bf_hi(m); m = hmul2(xv.y, gw[i].y); a += bf_lo(m) + bf_hi(m);
      m = hmul2(xv.z, gw[i].z); a += bf_lo(m) + bf_hi(m); m = hmul2(xv.w, gw[i].w); a += bf_lo(m) + bf_hi(m);
    }
#pragma unroll
    for (int o = 16; o > 0; o >>= 1) a += __shfl_xor_sync(~0u, a, o);
    a = bf_lo(pack_bf16(a, 0.f));
    const float gt = bf_lo(pack_bf16(__fdividef(1.f, 1.f + ex2(-a * 1.4426950408889634f)), 0.f));
    if (lane == 0) g_gate[row] = gt;
  }
  cnt_signal(g_cnt + C_GATE * CSTRIDE, lane);
  if (aw == 0) { TSA(44); }
}

template<int MASK> __global__ void __cluster_dims__(2, 1, 1) __launch_bounds__(384, 1) gated_mix_kernel(const __grid_constant__ Maps M, const __grid_constant__ Params P) {
  extern __shared__ __align__(1024) uint8_t smem[];
  const uint32_t base = (uint32_t)__cvta_generic_to_shared(smem);
  const int wi = __shfl_sync(~0u, threadIdx.x >> 5, 0), wg = wi >> 2, warp = wi & 3;
  if (elect()) {
    if (wi < 8) {
      const int cnt = 1 << ((0x10334400 >> (4 * wi)) & 15);
#pragma unroll
      for (int i = 0; i < 8; i++) mbar_init(base + SM_BAR + 64 * wi + 8 * i, cnt);
      asm volatile("fence.mbarrier_init.release.cluster;" ::: "memory");
    } else if (MAP_PF) {
      asm volatile("prefetch.tensormap [%0];" :: "l"(&M.c + (wi - 8)) : "memory");
    }
  }
  const int cta = blockIdx.x;
  const bool first_loads = (MASK & PH_KV) && wi == 8 && cta < NREG;
  const CUtensorMap* mw = (cta & 1) ? &M.wv : &M.wk;
  __syncwarp();
  asm volatile("barrier.cluster.arrive.relaxed.aligned;\nbarrier.cluster.wait.aligned;" ::: "memory");
  if (first_loads && elect()) {
#pragma unroll 1
    for (int it = 0; it < NFIRST; it++) {
      const uint32_t bar = base + SM_BAR + 24 * it, d0 = base + 3 * it * UNIT;
      mbar_expect(bar, 3 * UNIT);
      tma3d_mc(d0 + (1 + (cta & 1)) * UNIT, mw, 0, it * 64, 2 * (cta >> 3), bar);
      tma2d(d0, &M.c, it * 64, (cta & 7) * 256, bar);
    }
  }
  __syncwarp();
  const int lane = threadIdx.x & 31;
#define TS_PRO()
  if (wg == 2) {
    asm volatile("setmaxnreg.dec.sync.aligned.u32 56;");
    TS_PRO();
    TS(2, 62);
    if (warp == 0) producer<MASK>(M, P, base, cta, lane);
    else if (warp == 1) sync_agent<MASK>(base, cta, lane);
    else if (cta < NREG) {
      if (MASK & PH_PRE) aux_pre<MASK>(M, P, base, cta, warp - 2, lane);
      if (MASK & PH_OUT) producer2<MASK>(M, P, base, cta, warp - 2, lane);
    }
    __syncwarp();
    if (warp != 1) { if (lane == 0) mbar_arrive_n(base + SM_EXIT, warp == 0 ? 4 : 2); }
    else {
      mbar_wait_slow(base + SM_EXIT, 0);
      if (MASK & PH_OUT) {
        unsigned old = 0;
        if (lane == 0) asm volatile("atom.acq_rel.gpu.global.add.u32 %0, [%1], 1;" : "=r"(old) : "l"(g_cnt + C_EXIT * CSTRIDE) : "memory");
        old = __shfl_sync(~0u, old, 0);
        if (old == NCTA - 1) for (int i = lane; i < C_NUM; i += 32) g_cnt[i * CSTRIDE] = 0;
      }
      mbar_wait_slow(base + SM_SIG + 8 * SIG_DONE, 0);
      cluster_arrive(); cluster_wait();
    }
  } else {
    asm volatile("setmaxnreg.inc.sync.aligned.u32 224;");
    TS_PRO();
    uint32_t rel;
    asm volatile("mapa.shared::cluster.u32 %0, %1, %2;" : "=r"(rel) : "r"(base + SM_BAR + 128 + 8 * (lane & 15)), "r"(lane >> 4));
    Cons c{base, rel, 0u, lane, warp, wg, (cta * 3 + wg) * 2048};
    if (wg == 1) bar_arrive(1, 256);
    TS(wg, 0);
    if (cta < NREG) {
      const int g = cta & 7, j = cta >> 3;
      Pend w = {};
#pragma unroll 1
      for (int half = 0; half < 2; half++) {
        const int h = j + 16 * half;
        if (MASK & PH_KV) cons_kv(c, h, kv_slot<MASK>(h), g, w, half == 1 && (MASK & PH_ATT));
        TS(wg, 1 + 4 * half);
        if (MASK & PH_ATT) {
          const int fast = cons_q<(MASK & PH_KV) != 0>(c, h, w);
          TS(wg, 2 + 4 * half);
          c.signal(SIG_ATT + half);
          cons_att(c, h, g, fast, w);
          if (half == 0) c.signal(SIG_WAR);
#pragma unroll
          for (int i = 0; i < 8; i++) w.hi[i] = make_uint4(0, 0, 0, 0);
          TS(wg, 3 + 4 * half);
          if (MASK != PH_ALL) { tile_store<0, 4>(w.lo, w.dst, lane); c.signal(SIG_CTX + half); }
        } else if (MASK & PH_KV) { out_part<0>(c, w); out_part<1>(c, w); out_part<2>(c, w); out_part<3>(c, w); c.signal(SIG_KV + half); }
      }
      if (MASK & PH_OUT) cons_out<MASK>(c, M, cta, w);
    }
    if (cta >= NREG || !(MASK & PH_OUT)) {
      if (MASK & PH_CONV) cons_conv(c, cta, cta < NREG ? CONV_REG : CONV_EXTRA);
      TS(wg, 9);
      c.signal(SIG_DONE);
      cluster_arrive();
    }
    TS(wg, 10);
  }
}

typedef CUresult (*EncFn)(CUtensorMap*, CUtensorMapDataType, cuuint32_t, void*, const cuuint64_t*, const cuuint64_t*, const cuuint32_t*, const cuuint32_t*,
                          CUtensorMapInterleave, CUtensorMapSwizzle, CUtensorMapL2promotion, CUtensorMapFloatOOBfill);
static void enc(EncFn f, CUtensorMap* m, const void* ptr, int rank, const cuuint64_t* dims, const cuuint64_t* strides, const cuuint32_t* box, CUtensorMapSwizzle sw,
                CUtensorMapDataType dt = CU_TENSOR_MAP_DATA_TYPE_BFLOAT16) {
  const cuuint32_t es[4] = {1, 1, 1, 1};
  f(m, dt, rank, (void*)ptr, dims, strides, box, es, CU_TENSOR_MAP_INTERLEAVE_NONE, sw, CU_TENSOR_MAP_L2_PROMOTION_L2_256B, CU_TENSOR_MAP_FLOAT_OOB_FILL_NONE);
}
static void enc2(EncFn f, CUtensorMap* m, const void* ptr, int cols, int rows, int brows) {
  const cuuint64_t d[2] = {(cuuint64_t)cols, (cuuint64_t)rows}, s[1] = {(cuuint64_t)cols * 2}; const cuuint32_t b[2] = {64, (cuuint32_t)brows};
  enc(f, m, ptr, 2, d, s, b, CU_TENSOR_MAP_SWIZZLE_128B);
}
static void encw(EncFn f, CUtensorMap* m, const void* ptr, int cols, int rows) {
  const cuuint64_t d[3] = {64, (cuuint64_t)rows, (cuuint64_t)cols / 64}, s[2] = {(cuuint64_t)cols * 2, 128}; const cuuint32_t b[3] = {64, 64, 2};
  enc(f, m, ptr, 3, d, s, b, CU_TENSOR_MAP_SWIZZLE_128B);
}
extern "C" void kernel_launch(void* const* d_in, const int* in_sizes, int n_in, void* d_out, int out_size) {
  static EncFn fn = nullptr;
  static int ncl = 0;
  static void* zptr = nullptr;
  static void* tptr = nullptr;
  if (!fn) {
    void* p = nullptr; cudaDriverEntryPointQueryResult qr;
    cudaGetDriverEntryPoint("cuTensorMapEncodeTiled", &p, cudaEnableDefault, &qr);
    fn = (EncFn)p;
    cudaFuncSetAttribute(gated_mix_kernel<PH_ALL>, cudaFuncAttributeMaxDynamicSharedMemorySize, SMEM_BYTES);
    cudaFuncSetAttribute(gated_mix_kernel<PH_PRE | PH_KV>, cudaFuncAttributeMaxDynamicSharedMemorySize, SMEM_BYTES);
    cudaFuncSetAttribute(gated_mix_kernel<PH_ATT | PH_CONV>, cudaFuncAttributeMaxDynamicSharedMemorySize, SMEM_BYTES);
    cudaFuncSetAttribute(gated_mix_kernel<PH_OUT>, cudaFuncAttributeMaxDynamicSharedMemorySize, SMEM_BYTES);
    cudaLaunchConfig_t cfg = {}; cfg.gridDim = NCTA; cfg.blockDim = 384; cfg.dynamicSmemBytes = SMEM_BYTES;
    cudaLaunchAttribute at; at.id = cudaLaunchAttributeClusterDimension; at.val.clusterDim.x = 2; at.val.clusterDim.y = 1; at.val.clusterDim.z = 1;
    cfg.attrs = &at; cfg.numAttrs = 1;
    cudaOccupancyMaxActiveClusters(&ncl, gated_mix_kernel<PH_ALL>, &cfg);
    cudaGetSymbolAddress(&zptr, g_z);
    cudaGetSymbolAddress(&tptr, g_T);
  }
  Maps M;
  enc2(fn, &M.x, d_in[0], 1024, 2048, 128);
  enc2(fn, &M.c, d_in[7], 512, 2048, 128);
  enc2(fn, &M.wq, d_in[8], 4096, 1024, 64);
  encw(fn, &M.wk, d_in[9], 4096, 512);
  encw(fn, &M.wv, d_in[10], 4096, 512);
  encw(fn, &M.wo, d_in[11], 1024, 4096);
  { const cuuint64_t d[3] = {64, 32, 1024}, s[2] = {128, 4096}; const cuuint32_t b[3] = {64, 40, 1}; enc(fn, &M.h, d_in[4], 3, d, s, b, CU_TENSOR_MAP_SWIZZLE_NONE); }
  enc2(fn, &M.z, zptr, 2048, 1024, 128);
  enc2(fn, &M.out, d_out, 1024, 2048, 16);
  { const cuuint64_t d[2] = {512, 512 * 16}, s[1] = {2048}; const cuuint32_t b[2] = {256, 8};
    enc(fn, &M.ctx, tptr, 2, d, s, b, CU_TENSOR_MAP_SWIZZLE_NONE, CU_TENSOR_MAP_DATA_TYPE_UINT32); }
  { const cuuint64_t d[4] = {1024, 2, 256, 4}, s[3] = {2048, 16384, 4096}; const cuuint32_t b[4] = {64, 2, 9, 4};
    enc(fn, &M.k, d_in[1], 4, d, s, b, CU_TENSOR_MAP_SWIZZLE_128B); enc(fn, &M.v, d_in[2], 4, d, s, b, CU_TENSOR_MAP_SWIZZLE_128B); }
  Params P{(const __nv_bfloat16*)d_in[0], (const __nv_bfloat16*)d_in[3],
           (const __nv_bfloat16*)d_in[5], (const __nv_bfloat16*)d_in[12]};
  bool split = 2 * ncl < NCTA;
  if (!split) {
    gated_mix_kernel<PH_ALL><<<NCTA, 384, SMEM_BYTES>>>(M, P);
  } else {
    gated_mix_kernel<PH_PRE | PH_KV><<<NCTA, 384, SMEM_BYTES>>>(M, P);
    gated_mix_kernel<PH_ATT | PH_CONV><<<NCTA, 384, SMEM_BYTES>>>(M, P);
    gated_mix_kernel<PH_OUT><<<NCTA, 384, SMEM_BYTES>>>(M, P);
  }
}
```

```cpp
#include <cuda_runtime.h>
#include <cuda.h>
#include <cuda_bf16.h>
#include <stdint.h>

template<int TB> __device__ __forceinline__ void wgmma_ss_n256(float (&d)[128], uint64_t da, uint64_t db, int scale_d) {
  asm volatile("{\n.reg .pred p;\nsetp.ne.b32 p, %130, 0;\n"
    "wgmma.mma_async.sync.aligned.m64n256k16.f32.bf16.bf16 {%0, %1, %2, %3, %4, %5, %6, %7, %8, %9, %10, %11, %12, %13, %14, %15, %16, %17, %18, %19, %20, %21, %22, %23, %24, %25, %26, %27, %28, %29, %30, %31, %32, %33, %34, %35, %36, %37, %38, %39, %40, %41, %42, %43, %44, %45, %46, %47, %48, %49, %50, %51, %52, %53, %54, %55, %56, %57, %58, %59, %60, %61, %62, %63, %64, %65, %66, %67, %68, %69, %70, %71, %72, %73, %74, %75, %76, %77, %78, %79, %80, %81, %82, %83, %84, %85, %86, %87, %88, %89, %90, %91, %92, %93, %94, %95, %96, %97, %98, %99, %100, %101, %102, %103, %104, %105, %106, %107, %108, %109, %110, %111, %112, %113, %114, %115, %116, %117, %118, %119, %120, %121, %122, %123, %124, %125, %126, %127}, %128, %129, p, 1, 1, 0, %131;\n}\n"
    : "+f"(d[0]), "+f"(d[1]), "+f"(d[2]), "+f"(d[3]), "+f"(d[4]), "+f"(d[5]), "+f"(d[6]), "+f"(d[7]), "+f"(d[8]), "+f"(d[9]), "+f"(d[10]), "+f"(d[11]), "+f"(d[12]), "+f"(d[13]), "+f"(d[14]), "+f"(d[15]), "+f"(d[16]), "+f"(d[17]), "+f"(d[18]), "+f"(d[19]), "+f"(d[20]), "+f"(d[21]), "+f"(d[22]), "+f"(d[23]), "+f"(d[24]), "+f"(d[25]), "+f"(d[26]), "+f"(d[27]), "+f"(d[28]), "+f"(d[29]), "+f"(d[30]), "+f"(d[31]), "+f"(d[32]), "+f"(d[33]), "+f"(d[34]), "+f"(d[35]), "+f"(d[36]), "+f"(d[37]), "+f"(d[38]), "+f"(d[39]), "+f"(d[40]), "+f"(d[41]), "+f"(d[42]), "+f"(d[43]), "+f"(d[44]), "+f"(d[45]), "+f"(d[46]), "+f"(d[47]), "+f"(d[48]), "+f"(d[49]), "+f"(d[50]), "+f"(d[51]), "+f"(d[52]), "+f"(d[53]), "+f"(d[54]), "+f"(d[55]), "+f"(d[56]), "+f"(d[57]), "+f"(d[58]), "+f"(d[59]), "+f"(d[60]), "+f"(d[61]), "+f"(d[62]), "+f"(d[63]), "+f"(d[64]), "+f"(d[65]), "+f"(d[66]), "+f"(d[67]), "+f"(d[68]), "+f"(d[69]), "+f"(d[70]), "+f"(d[71]), "+f"(d[72]), "+f"(d[73]), "+f"(d[74]), "+f"(d[75]), "+f"(d[76]), "+f"(d[77]), "+f"(d[78]), "+f"(d[79]), "+f"(d[80]), "+f"(d[81]), "+f"(d[82]), "+f"(d[83]), "+f"(d[84]), "+f"(d[85]), "+f"(d[86]), "+f"(d[87]), "+f"(d[88]), "+f"(d[89]), "+f"(d[90]), "+f"(d[91]), "+f"(d[92]), "+f"(d[93]), "+f"(d[94]), "+f"(d[95]), "+f"(d[96]), "+f"(d[97]), "+f"(d[98]), "+f"(d[99]), "+f"(d[100]), "+f"(d[101]), "+f"(d[102]), "+f"(d[103]), "+f"(d[104]), "+f"(d[105]), "+f"(d[106]), "+f"(d[107]), "+f"(d[108]), "+f"(d[109]), "+f"(d[110]), "+f"(d[111]), "+f"(d[112]), "+f"(d[113]), "+f"(d[114]), "+f"(d[115]), "+f"(d[116]), "+f"(d[117]), "+f"(d[118]), "+f"(d[119]), "+f"(d[120]), "+f"(d[121]), "+f"(d[122]), "+f"(d[123]), "+f"(d[124]), "+f"(d[125]), "+f"(d[126]), "+f"(d[127])
    : "l"(da), "l"(db), "r"(scale_d), "n"(TB));
}
template<int TB> __device__ __forceinline__ void wgmma_ss_n128(float (&d)[64], uint64_t da, uint64_t db, int scale_d) {
  asm volatile("{\n.reg .pred p;\nsetp.ne.b32 p, %66, 0;\n"
    "wgmma.mma_async.sync.aligned.m64n128k16.f32.bf16.bf16 {%0, %1, %2, %3, %4, %5, %6, %7, %8, %9, %10, %11, %12, %13, %14, %15, %16, %17, %18, %19, %20, %21, %22, %23, %24, %25, %26, %27, %28, %29, %30, %31, %32, %33, %34, %35, %36, %37, %38, %39, %40, %41, %42, %43, %44, %45, %46, %47, %48, %49, %50, %51, %52, %53, %54, %55, %56, %57, %58, %59, %60, %61, %62, %63}, %64, %65, p, 1, 1, 0, %67;\n}\n"
    : "+f"(d[0]), "+f"(d[1]), "+f"(d[2]), "+f"(d[3]), "+f"(d[4]), "+f"(d[5]), "+f"(d[6]), "+f"(d[7]), "+f"(d[8]), "+f"(d[9]), "+f"(d[10]), "+f"(d[11]), "+f"(d[12]), "+f"(d[13]), "+f"(d[14]), "+f"(d[15]), "+f"(d[16]), "+f"(d[17]), "+f"(d[18]), "+f"(d[19]), "+f"(d[20]), "+f"(d[21]), "+f"(d[22]), "+f"(d[23]), "+f"(d[24]), "+f"(d[25]), "+f"(d[26]), "+f"(d[27]), "+f"(d[28]), "+f"(d[29]), "+f"(d[30]), "+f"(d[31]), "+f"(d[32]), "+f"(d[33]), "+f"(d[34]), "+f"(d[35]), "+f"(d[36]), "+f"(d[37]), "+f"(d[38]), "+f"(d[39]), "+f"(d[40]), "+f"(d[41]), "+f"(d[42]), "+f"(d[43]), "+f"(d[44]), "+f"(d[45]), "+f"(d[46]), "+f"(d[47]), "+f"(d[48]), "+f"(d[49]), "+f"(d[50]), "+f"(d[51]), "+f"(d[52]), "+f"(d[53]), "+f"(d[54]), "+f"(d[55]), "+f"(d[56]), "+f"(d[57]), "+f"(d[58]), "+f"(d[59]), "+f"(d[60]), "+f"(d[61]), "+f"(d[62]), "+f"(d[63])
    : "l"(da), "l"(db), "r"(scale_d), "n"(TB));
}
template<int TB> __device__ __forceinline__ void wgmma_rs_n64(float (&d)[32], uint32_t a0, uint32_t a1, uint32_t a2, uint32_t a3, uint64_t db, int scale_d) {
  asm volatile("{\n.reg .pred p;\nsetp.ne.b32 p, %37, 0;\n"
    "wgmma.mma_async.sync.aligned.m64n64k16.f32.bf16.bf16 {%0, %1, %2, %3, %4, %5, %6, %7, %8, %9, %10, %11, %12, %13, %14, %15, %16, %17, %18, %19, %20, %21, %22, %23, %24, %25, %26, %27, %28, %29, %30, %31}, {%32, %33, %34, %35}, %36, p, 1, 1, %38;\n}\n"
    : "+f"(d[0]), "+f"(d[1]), "+f"(d[2]), "+f"(d[3]), "+f"(d[4]), "+f"(d[5]), "+f"(d[6]), "+f"(d[7]), "+f"(d[8]), "+f"(d[9]), "+f"(d[10]), "+f"(d[11]), "+f"(d[12]), "+f"(d[13]), "+f"(d[14]), "+f"(d[15]), "+f"(d[16]), "+f"(d[17]), "+f"(d[18]), "+f"(d[19]), "+f"(d[20]), "+f"(d[21]), "+f"(d[22]), "+f"(d[23]), "+f"(d[24]), "+f"(d[25]), "+f"(d[26]), "+f"(d[27]), "+f"(d[28]), "+f"(d[29]), "+f"(d[30]), "+f"(d[31])
    : "r"(a0), "r"(a1), "r"(a2), "r"(a3), "l"(db), "r"(scale_d), "n"(TB));
}
__device__ __forceinline__ void wgmma_pv_sel(float (&d)[64], const uint32_t (&p)[32], uint64_t db, int full, int acc) {
  asm volatile("{\n.reg .pred q, s;\n.reg .b64 t;\nsetp.ne.b32 s, %98, 0;\nsetp.eq.b32 q, %97, 0;\n@q bra.uni LH;\n"
    "wgmma.fence.sync.aligned;\n"
    "add.s64 t, %96, 0;\nwgmma.mma_async.sync.aligned.m64n128k16.f32.bf16.bf16 {%0, %1, %2, %3, %4, %5, %6, %7, %8, %9, %10, %11, %12, %13, %14, %15, %16, %17, %18, %19, %20, %21, %22, %23, %24, %25, %26, %27, %28, %29, %30, %31, %32, %33, %34, %35, %36, %37, %38, %39, %40, %41, %42, %43, %44, %45, %46, %47, %48, %49, %50, %51, %52, %53, %54, %55, %56, %57, %58, %59, %60, %61, %62, %63}, {%64, %65, %66, %67}, t, s, 1, 1, 1;\n"
    "add.s64 t, %96, 256;\nwgmma.mma_async.sync.aligned.m64n128k16.f32.bf16.bf16 {%0, %1, %2, %3, %4, %5, %6, %7, %8, %9, %10, %11, %12, %13, %14, %15, %16, %17, %18, %19, %20, %21, %22, %23, %24, %25, %26, %27, %28, %29, %30, %31, %32, %33, %34, %35, %36, %37, %38, %39, %40, %41, %42, %43, %44, %45, %46, %47, %48, %49, %50, %51, %52, %53, %54, %55, %56, %57, %58, %59, %60, %61, %62, %63}, {%68, %69, %70, %71}, t, 1, 1, 1, 1;\n"
    "add.s64 t, %96, 512;\nwgmma.mma_async.sync.aligned.m64n128k16.f32.bf16.bf16 {%0, %1, %2, %3, %4, %5, %6, %7, %8, %9, %10, %11, %12, %13, %14, %15, %16, %17, %18, %19, %20, %21, %22, %23, %24, %25, %26, %27, %28, %29, %30, %31, %32, %33, %34, %35, %36, %37, %38, %39, %40, %41, %42, %43, %44, %45, %46, %47, %48, %49, %50, %51, %52, %53, %54, %55, %56, %57, %58, %59, %60, %61, %62, %63}, {%72, %73, %74, %75}, t, 1, 1, 1, 1;\n"
    "add.s64 t, %96, 768;\nwgmma.mma_async.sync.aligned.m64n128k16.f32.bf16.bf16 {%0, %1, %2, %3, %4, %5, %6, %7, %8, %9, %10, %11, %12, %13, %14, %15, %16, %17, %18, %19, %20, %21, %22, %23, %24, %25, %26, %27, %28, %29, %30, %31, %32, %33, %34, %35, %36, %37, %38, %39, %40, %41, %42, %43, %44, %45, %46, %47, %48, %49, %50, %51, %52, %53, %54, %55, %56, %57, %58, %59, %60, %61, %62, %63}, {%76, %77, %78, %79}, t, 1, 1, 1, 1;\n"
    "add.s64 t, %96, 1024;\nwgmma.mma_async.sync.aligned.m64n128k16.f32.bf16.bf16 {%0, %1, %2, %3, %4, %5, %6, %7, %8, %9, %10, %11, %12, %13, %14, %15, %16, %17, %18, %19, %20, %21, %22, %23, %24, %25, %26, %27, %28, %29, %30, %31, %32, %33, %34, %35, %36, %37, %38, %39, %40, %41, %42, %43, %44, %45, %46, %47, %48, %49, %50, %51, %52, %53, %54, %55, %56, %57, %58, %59, %60, %61, %62, %63}, {%80, %81, %82, %83}, t, 1, 1, 1, 1;\n"
    "add.s64 t, %96, 1280;\nwgmma.mma_async.sync.aligned.m64n128k16.f32.bf16.bf16 {%0, %1, %2, %3, %4, %5, %6, %7, %8, %9, %10, %11, %12, %13, %14, %15, %16, %17, %18, %19, %20, %21, %22, %23, %24, %25, %26, %27, %28, %29, %30, %31, %32, %33, %34, %35, %36, %37, %38, %39, %40, %41, %42, %43, %44, %45, %46, %47, %48, %49, %50, %51, %52, %53, %54, %55, %56, %57, %58, %59, %60, %61, %62, %63}, {%84, %85, %86, %87}, t, 1, 1, 1, 1;\n"
    "add.s64 t, %96, 1536;\nwgmma.mma_async.sync.aligned.m64n128k16.f32.bf16.bf16 {%0, %1, %2, %3, %4, %5, %6, %7, %8, %9, %10, %11, %12, %13, %14, %15, %16, %17, %18, %19, %20, %21, %22, %23, %24, %25, %26, %27, %28, %29, %30, %31, %32, %33, %34, %35, %36, %37, %38, %39, %40, %41, %42, %43, %44, %45, %46, %47, %48, %49, %50, %51, %52, %53, %54, %55, %56, %57, %58, %59, %60, %61, %62, %63}, {%88, %89, %90, %91}, t, 1, 1, 1, 1;\n"
    "add.s64 t, %96, 1792;\nwgmma.mma_async.sync.aligned.m64n128k16.f32.bf16.bf16 {%0, %1, %2, %3, %4, %5, %6, %7, %8, %9, %10, %11, %12, %13, %14, %15, %16, %17, %18, %19, %20, %21, %22, %23, %24, %25, %26, %27, %28, %29, %30, %31, %32, %33, %34, %35, %36, %37, %38, %39, %40, %41, %42, %43, %44, %45, %46, %47, %48, %49, %50, %51, %52, %53, %54, %55, %56, %57, %58, %59, %60, %61, %62, %63}, {%92, %93, %94, %95}, t, 1, 1, 1, 1;\n"
    "wgmma.commit_group.sync.aligned;\n"
    "bra.uni LE;\nLH:\n"
    "wgmma.fence.sync.aligned;\n"
    "add.s64 t, %96, 0;\nwgmma.mma_async.sync.aligned.m64n128k16.f32.bf16.bf16 {%0, %1, %2, %3, %4, %5, %6, %7, %8, %9, %10, %11, %12, %13, %14, %15, %16, %17, %18, %19, %20, %21, %22, %23, %24, %25, %26, %27, %28, %29, %30, %31, %32, %33, %34, %35, %36, %37, %38, %39, %40, %41, %42, %43, %44, %45, %46, %47, %48, %49, %50, %51, %52, %53, %54, %55, %56, %57, %58, %59, %60, %61, %62, %63}, {%80, %81, %82, %83}, t, s, 1, 1, 1;\n"
    "add.s64 t, %96, 256;\nwgmma.mma_async.sync.aligned.m64n128k16.f32.bf16.bf16 {%0, %1, %2, %3, %4, %5, %6, %7, %8, %9, %10, %11, %12, %13, %14, %15, %16, %17, %18, %19, %20, %21, %22, %23, %24, %25, %26, %27, %28, %29, %30, %31, %32, %33, %34, %35, %36, %37, %38, %39, %40, %41, %42, %43, %44, %45, %46, %47, %48, %49, %50, %51, %52, %53, %54, %55, %56, %57, %58, %59, %60, %61, %62, %63}, {%84, %85, %86, %87}, t, 1, 1, 1, 1;\n"
    "add.s64 t, %96, 512;\nwgmma.mma_async.sync.aligned.m64n128k16.f32.bf16.bf16 {%0, %1, %2, %3, %4, %5, %6, %7, %8, %9, %10, %11, %12, %13, %14, %15, %16, %17, %18, %19, %20, %21, %22, %23, %24, %25, %26, %27, %28, %29, %30, %31, %32, %33, %34, %35, %36, %37, %38, %39, %40, %41, %42, %43, %44, %45, %46, %47, %48, %49, %50, %51, %52, %53, %54, %55, %56, %57, %58, %59, %60, %61, %62, %63}, {%88, %89, %90, %91}, t, 1, 1, 1, 1;\n"
    "add.s64 t, %96, 768;\nwgmma.mma_async.sync.aligned.m64n128k16.f32.bf16.bf16 {%0, %1, %2, %3, %4, %5, %6, %7, %8, %9, %10, %11, %12, %13, %14, %15, %16, %17, %18, %19, %20, %21, %22, %23, %24, %25, %26, %27, %28, %29, %30, %31, %32, %33, %34, %35, %36, %37, %38, %39, %40, %41, %42, %43, %44, %45, %46, %47, %48, %49, %50, %51, %52, %53, %54, %55, %56, %57, %58, %59, %60, %61, %62, %63}, {%92, %93, %94, %95}, t, 1, 1, 1, 1;\n"
    "wgmma.commit_group.sync.aligned;\n"
    "LE:\n}\n"
    : "+f"(d[0]), "+f"(d[1]), "+f"(d[2]), "+f"(d[3]), "+f"(d[4]), "+f"(d[5]), "+f"(d[6]), "+f"(d[7]), "+f"(d[8]), "+f"(d[9]), "+f"(d[10]), "+f"(d[11]), "+f"(d[12]), "+f"(d[13]), "+f"(d[14]), "+f"(d[15]), "+f"(d[16]), "+f"(d[17]), "+f"(d[18]), "+f"(d[19]), "+f"(d[20]), "+f"(d[21]), "+f"(d[22]), "+f"(d[23]), "+f"(d[24]), "+f"(d[25]), "+f"(d[26]), "+f"(d[27]), "+f"(d[28]), "+f"(d[29]), "+f"(d[30]), "+f"(d[31]), "+f"(d[32]), "+f"(d[33]), "+f"(d[34]), "+f"(d[35]), "+f"(d[36]), "+f"(d[37]), "+f"(d[38]), "+f"(d[39]), "+f"(d[40]), "+f"(d[41]), "+f"(d[42]), "+f"(d[43]), "+f"(d[44]), "+f"(d[45]), "+f"(d[46]), "+f"(d[47]), "+f"(d[48]), "+f"(d[49]), "+f"(d[50]), "+f"(d[51]), "+f"(d[52]), "+f"(d[53]), "+f"(d[54]), "+f"(d[55]), "+f"(d[56]), "+f"(d[57]), "+f"(d[58]), "+f"(d[59]), "+f"(d[60]), "+f"(d[61]), "+f"(d[62]), "+f"(d[63])
    : "r"(p[0]), "r"(p[1]), "r"(p[2]), "r"(p[3]), "r"(p[4]), "r"(p[5]), "r"(p[6]), "r"(p[7]), "r"(p[8]), "r"(p[9]), "r"(p[10]), "r"(p[11]), "r"(p[12]), "r"(p[13]), "r"(p[14]), "r"(p[15]), "r"(p[16]), "r"(p[17]), "r"(p[18]), "r"(p[19]), "r"(p[20]), "r"(p[21]), "r"(p[22]), "r"(p[23]), "r"(p[24]), "r"(p[25]), "r"(p[26]), "r"(p[27]), "r"(p[28]), "r"(p[29]), "r"(p[30]), "r"(p[31]), "l"(db), "r"(full), "r"(acc) : "memory");
}

constexpr int NCTA = 132, NREG = 128;
constexpr int UNIT = 16384, NUNIT = 14;
constexpr uint32_t SMEM_BASE = 1024;
constexpr int SM_BAR = NUNIT * UNIT;
constexpr int SM_GATE = SM_BAR + 1024;
constexpr int SMEM_BYTES = SM_BAR + 1536;
constexpr int UPITCH = 4160, UCH = 2 * UPITCH;
constexpr float QSCALE = 0.08838834764831845f * 1.4426950408889634f;
constexpr float BOUND2 = 48.f * 48.f / 1.15f;
#define CONV_REG 6
constexpr int CONV_EXTRA = (1024 - NREG * CONV_REG) / (NCTA - NREG);
constexpr int CH_EXTRA_TOTAL = CONV_EXTRA * (NCTA - NREG);
constexpr int C_KV = 0;
constexpr int C_CTX = 32;
constexpr int C_U = 48;
constexpr int C_Z = 80;
constexpr int C_GATE = 88;
constexpr int C_EXIT = 89;
[[maybe_unused]] constexpr int C_GO = 90;
#define PRE_EARLY 1
#define PRE_HALF 1
#define ATT_SPLIT 6
#define NFIRST 2
#define PRE_DELAY 1
#define MAP_PF 1
#define EF 127
#define POL(bit) (((EF >> (bit)) & 1) != 0)
constexpr int C_WAR = 96;
constexpr int C_NUM = 112;
constexpr int CSTRIDE = 32;
constexpr int SM_KMAX = SM_BAR + 640, SM_DUMMY = SM_BAR + 648, SM_PRE = SM_BAR + 112, SM_SIG = SM_BAR + 256, SM_EXIT = SM_SIG + 120, SM_RDY = SM_BAR + 384;
enum { SIG_KV = 0, SIG_CTX = 2, SIG_Z = 4, SIG_DONE = 8, SIG_WAR = 9, SIG_ATT = 10 };
enum { RDY_KV = 0, RDY_CTX = 2, RDY_WAR = 4, RDY_G = 5, RDY_U = 8, RDY_Z = 9 };
enum { PH_PRE = 1, PH_KV = 2, PH_ATT = 4, PH_CONV = 8, PH_OUT = 16, PH_ALL = 31 };

constexpr uint32_t T_CTX = 0, T_KV = 16 * 32 * 32768, T_BYTES = T_KV + 32 * 16 * 65536;
__device__ __align__(1024) uint8_t g_T[T_BYTES];
__device__ __align__(1024) uint8_t g_u[1024 * UCH];
__device__ __align__(1024) __nv_bfloat16 g_z[1024 * 2048];
__device__ __align__(1024) float g_gate[2048];
__device__ __align__(1024) float g_kn2[32 * 128];
__device__ __align__(1024) unsigned g_cnt[C_NUM * CSTRIDE];

struct __align__(64) Maps { CUtensorMap c, wk, wv, x, wq, wo, h, z, out, ctx, k, v; };
struct Params {
  const __nv_bfloat16 *x, *shift, *D, *gw;
};

__device__ __forceinline__ void wg_fence() { asm volatile("wgmma.fence.sync.aligned;" ::: "memory"); }
__device__ __forceinline__ void wg_commit() { asm volatile("wgmma.commit_group.sync.aligned;" ::: "memory"); }
template<int N> __device__ __forceinline__ void wg_wait() { asm volatile("wgmma.wait_group.sync.aligned %0;" :: "n"(N) : "memory"); }
__device__ __forceinline__ uint64_t odesc(uint32_t addr, uint32_t lbo, uint32_t sbo, uint32_t swz) {
  uint64_t d = (uint64_t)(addr >> 4) + (((uint64_t)(lbo >> 4) << 16) | ((uint64_t)(sbo >> 4) << 32) | ((uint64_t)swz << 62));
  asm volatile("" : "+l"(d));
  return d;
}
__device__ __forceinline__ void mbar_init(uint32_t bar, int cnt) { asm volatile("mbarrier.init.shared::cta.b64 [%0], %1;" :: "r"(bar), "r"(cnt)); }
__device__ __forceinline__ void mbar_expect(uint32_t bar, uint32_t bytes) { asm volatile("mbarrier.arrive.expect_tx.shared::cta.b64 _, [%0], %1;" :: "r"(bar), "r"(bytes) : "memory"); }
__device__ __forceinline__ void mbar_arrive(uint32_t bar) { asm volatile("mbarrier.arrive.shared::cta.b64 _, [%0];" :: "r"(bar) : "memory"); }
__device__ __forceinline__ void mbar_arrive_n(uint32_t bar, int n) { asm volatile("mbarrier.arrive.shared::cta.b64 _, [%0], %1;" :: "r"(bar), "r"(n) : "memory"); }
__device__ __forceinline__ void mbar_wait(uint32_t bar, uint32_t parity) {
  asm volatile("{\n.reg .pred p;\nLW:\nmbarrier.try_wait.parity.shared::cta.b64 p, [%0], %1;\n@!p bra LW;\n}\n" :: "r"(bar), "r"(parity) : "memory");
}
__device__ __forceinline__ void mbar_wait_slow(uint32_t bar, uint32_t parity) {
  asm volatile("{\n.reg .pred p;\n.reg .u32 n;\nmov.u32 n, 0;\n"
    "LW:\nmbarrier.test_wait.parity.shared::cta.b64 p, [%0], %1;\n@p bra LD;\n"
    "nanosleep.u32 128;\nadd.u32 n, n, 1;\nsetp.lt.u32 p, n, 4194304;\n@p bra LW;\ntrap;\nLD:\n}\n" :: "r"(bar), "r"(parity) : "memory");
}
__device__ __forceinline__ void mbar_wait_all(uint32_t bar, uint32_t parity) {
  asm volatile("{\n.reg .pred p, q;\nLW:\nmbarrier.try_wait.parity.shared::cta.b64 p, [%0], %1;\nvote.sync.all.pred q, p, 0xffffffff;\n@!q bra.uni LW;\n}\n" :: "r"(bar), "r"(parity) : "memory");
}
__device__ __forceinline__ void cnt_wait(const unsigned* p, unsigned target) {
  asm volatile("{\n.reg .pred p;\n.reg .u32 n, v;\nmov.u32 n, 0;\n"
    "LW:\nld.relaxed.gpu.global.u32 v, [%0];\nsetp.ge.u32 p, v, %1;\n@p bra LD;\n"
    "nanosleep.u32 64;\nadd.u32 n, n, 1;\nsetp.lt.u32 p, n, 4194304;\n@p bra LW;\ntrap;\nLD:\nfence.acq_rel.gpu;\nfence.proxy.async;\n}\n" :: "l"(p), "r"(target) : "memory");
}
__device__ __forceinline__ void cnt_signal(unsigned* p, int lane) {
  __syncwarp();
  if (lane == 0) asm volatile("red.release.gpu.global.add.u32 [%0], 1;" :: "l"(p) : "memory");
}
__device__ __forceinline__ void cnt_publish(unsigned* p, unsigned n) {
  asm volatile("fence.acq_rel.gpu;\nred.relaxed.gpu.global.add.u32 [%0], %1;" :: "l"(p), "r"(n) : "memory");
}
__device__ __forceinline__ uint64_t pol_first() { uint64_t p; asm("createpolicy.fractional.L2::evict_first.b64 %0, 1.0;" : "=l"(p)); return p; }
__device__ __forceinline__ void bulk_g2s(uint32_t dst, const void* src, uint32_t bytes, uint32_t bar, bool stream = false) {
  if (stream) asm volatile("cp.async.bulk.shared::cluster.global.mbarrier::complete_tx::bytes.L2::cache_hint [%0], [%1], %2, [%3], %4;" :: "r"(dst), "l"(src), "r"(bytes), "r"(bar), "l"(pol_first()) : "memory");
  else asm volatile("cp.async.bulk.shared::cluster.global.mbarrier::complete_tx::bytes [%0], [%1], %2, [%3];" :: "r"(dst), "l"(src), "r"(bytes), "r"(bar) : "memory");
}
__device__ __forceinline__ void tma2d(uint32_t dst, const CUtensorMap* m, int x, int y, uint32_t bar, bool stream = false) {
  if (stream) asm volatile("cp.async.bulk.tensor.2d.shared::cluster.global.mbarrier::complete_tx::bytes.L2::cache_hint [%0], [%1, {%3, %4}], [%2], %5;" :: "r"(dst), "l"(m), "r"(bar), "r"(x), "r"(y), "l"(pol_first()) : "memory");
  else asm volatile("cp.async.bulk.tensor.2d.shared::cluster.global.mbarrier::complete_tx::bytes [%0], [%1, {%3, %4}], [%2];" :: "r"(dst), "l"(m), "r"(bar), "r"(x), "r"(y) : "memory");
}
__device__ __forceinline__ void tma3d(uint32_t dst, const CUtensorMap* m, int x, int y, int z, uint32_t bar, bool stream = false) {
  if (stream) asm volatile("cp.async.bulk.tensor.3d.shared::cluster.global.mbarrier::complete_tx::bytes.L2::cache_hint [%0], [%1, {%3, %4, %5}], [%2], %6;" :: "r"(dst), "l"(m), "r"(bar), "r"(x), "r"(y), "r"(z), "l"(pol_first()) : "memory");
  else asm volatile("cp.async.bulk.tensor.3d.shared::cluster.global.mbarrier::complete_tx::bytes [%0], [%1, {%3, %4, %5}], [%2];" :: "r"(dst), "l"(m), "r"(bar), "r"(x), "r"(y), "r"(z) : "memory");
}
__device__ __forceinline__ void tma4d(uint32_t dst, const CUtensorMap* m, int x, int y, int z, int w, uint32_t bar, bool stream = false) {
  if (stream) asm volatile("cp.async.bulk.tensor.4d.shared::cluster.global.mbarrier::complete_tx::bytes.L2::cache_hint [%0], [%1, {%3, %4, %5, %6}], [%2], %7;" :: "r"(dst), "l"(m), "r"(bar), "r"(x), "r"(y), "r"(z), "r"(w), "l"(pol_first()) : "memory");
  else asm volatile("cp.async.bulk.tensor.4d.shared::cluster.global.mbarrier::complete_tx::bytes [%0], [%1, {%3, %4, %5, %6}], [%2];" :: "r"(dst), "l"(m), "r"(bar), "r"(x), "r"(y), "r"(z), "r"(w) : "memory");
}
__device__ __forceinline__ void bulk_g2s_mc(uint32_t dst, const void* src, uint32_t bytes, uint32_t bar, bool stream = false) {
  if (stream) asm volatile("cp.async.bulk.shared::cluster.global.mbarrier::complete_tx::bytes.multicast::cluster.L2::cache_hint [%0], [%1], %2, [%3], %4, %5;" :: "r"(dst), "l"(src), "r"(bytes), "r"(bar), "h"((uint16_t)3), "l"(pol_first()) : "memory");
  else asm volatile("cp.async.bulk.shared::cluster.global.mbarrier::complete_tx::bytes.multicast::cluster [%0], [%1], %2, [%3], %4;" :: "r"(dst), "l"(src), "r"(bytes), "r"(bar), "h"((uint16_t)3) : "memory");
}
__device__ __forceinline__ void tma2d_mc(uint32_t dst, const CUtensorMap* m, int x, int y, uint32_t bar, bool stream = false) {
  if (stream) asm volatile("cp.async.bulk.tensor.2d.shared::cluster.global.mbarrier::complete_tx::bytes.multicast::cluster.L2::cache_hint [%0], [%1, {%3, %4}], [%2], %5, %6;" :: "r"(dst), "l"(m), "r"(bar), "r"(x), "r"(y), "h"((uint16_t)3), "l"(pol_first()) : "memory");
  else asm volatile("cp.async.bulk.tensor.2d.shared::cluster.global.mbarrier::complete_tx::bytes.multicast::cluster [%0], [%1, {%3, %4}], [%2], %5;" :: "r"(dst), "l"(m), "r"(bar), "r"(x), "r"(y), "h"((uint16_t)3) : "memory");
}
__device__ __forceinline__ void tma3d_mc(uint32_t dst, const CUtensorMap* m, int x, int y, int z, uint32_t bar, bool stream = false) {
  if (stream) asm volatile("cp.async.bulk.tensor.3d.shared::cluster.global.mbarrier::complete_tx::bytes.multicast::cluster.L2::cache_hint [%0], [%1, {%3, %4, %5}], [%2], %6, %7;" :: "r"(dst), "l"(m), "r"(bar), "r"(x), "r"(y), "r"(z), "h"((uint16_t)3), "l"(pol_first()) : "memory");
  else asm volatile("cp.async.bulk.tensor.3d.shared::cluster.global.mbarrier::complete_tx::bytes.multicast::cluster [%0], [%1, {%3, %4, %5}], [%2], %6;" :: "r"(dst), "l"(m), "r"(bar), "r"(x), "r"(y), "r"(z), "h"((uint16_t)3) : "memory");
}
__device__ __forceinline__ void tma2d_store(const CUtensorMap* m, uint32_t src, int x, int y) {
  asm volatile("cp.async.bulk.tensor.2d.global.shared::cta.bulk_group [%0, {%2, %3}], [%1];" :: "l"(m), "r"(src), "r"(x), "r"(y) : "memory");
}
__device__ __forceinline__ bool elect() {
  uint32_t r; asm volatile("{\n.reg .pred p;\nelect.sync _|p, 0xffffffff;\nselp.u32 %0, 1, 0, p;\n}\n" : "=r"(r)); return r != 0;
}
__device__ __forceinline__ void cluster_arrive() { asm volatile("barrier.cluster.arrive;" ::: "memory"); }
__device__ __forceinline__ void cluster_wait() { asm volatile("barrier.cluster.wait;" ::: "memory"); }
__device__ __forceinline__ void bar_sync(int id, int n) { asm volatile("bar.sync %0, %1;" :: "r"(id), "r"(n) : "memory"); }
__device__ __forceinline__ void bar_arrive(int id, int n) { asm volatile("bar.arrive %0, %1;" :: "r"(id), "r"(n) : "memory"); }
__device__ __forceinline__ int bar_and(int id, int n, int pred) {
  int r; asm volatile("{\n.reg .pred p, q;\nsetp.ne.b32 p, %3, 0;\nbar.red.and.pred q, %1, %2, p;\nselp.b32 %0, 1, 0, q;\n}\n" : "=r"(r) : "r"(id), "r"(n), "r"(pred) : "memory");
  return r;
}
__device__ __forceinline__ void fence_async_smem() { asm volatile("fence.proxy.async.shared::cta;" ::: "memory"); }
__device__ __forceinline__ float ex2(float x) { float y; asm("ex2.approx.ftz.f32 %0, %1;" : "=f"(y) : "f"(x)); return y; }
__device__ __forceinline__ uint32_t pack_bf16(float lo, float hi) { uint32_t r; asm("cvt.rn.bf16x2.f32 %0, %1, %2;" : "=r"(r) : "f"(hi), "f"(lo)); return r; }
__device__ __forceinline__ uint32_t hmul2(uint32_t a, uint32_t b) { uint32_t r; asm("mul.rn.bf16x2 %0, %1, %2;" : "=r"(r) : "r"(a), "r"(b)); return r; }
__device__ __forceinline__ uint32_t hadd2(uint32_t a, uint32_t b) { uint32_t r; asm("add.rn.bf16x2 %0, %1, %2;" : "=r"(r) : "r"(a), "r"(b)); return r; }
__device__ __forceinline__ uint32_t hfma2(uint32_t a, uint32_t b, uint32_t c) { uint32_t r; asm("fma.rn.bf16x2 %0, %1, %2, %3;" : "=r"(r) : "r"(a), "r"(b), "r"(c)); return r; }
__device__ __forceinline__ float bf_lo(uint32_t a) { return __uint_as_float(a << 16); }
__device__ __forceinline__ float bf_hi(uint32_t a) { return __uint_as_float(a & 0xffff0000u); }
__device__ __forceinline__ uint32_t lds32(uint32_t a) { uint32_t v; asm volatile("ld.shared.u32 %0, [%1];" : "=r"(v) : "r"(a) : "memory"); return v; }
__device__ __forceinline__ float2 lds64f(uint32_t a) { float2 v; asm volatile("ld.shared.v2.f32 {%0,%1}, [%2];" : "=f"(v.x), "=f"(v.y) : "r"(a) : "memory"); return v; }
__device__ __forceinline__ uint4 lds128(uint32_t a) { uint4 v; asm volatile("ld.shared.v4.u32 {%0,%1,%2,%3}, [%4];" : "=r"(v.x), "=r"(v.y), "=r"(v.z), "=r"(v.w) : "r"(a) : "memory"); return v; }
__device__ __forceinline__ void sts64f(uint32_t a, float x, float y) { asm volatile("st.shared.v2.f32 [%0], {%1,%2};" :: "r"(a), "f"(x), "f"(y) : "memory"); }
__device__ __forceinline__ void sts128(uint32_t a, uint4 v) { asm volatile("st.shared.v4.u32 [%0], {%1,%2,%3,%4};" :: "r"(a), "r"(v.x), "r"(v.y), "r"(v.z), "r"(v.w) : "memory"); }
template<int OFF> __device__ __forceinline__ void sts128o(uint32_t a, uint4 v) { asm volatile("st.shared.v4.u32 [%0+%5], {%1,%2,%3,%4};" :: "r"(a), "r"(v.x), "r"(v.y), "r"(v.z), "r"(v.w), "n"(OFF) : "memory"); }
__device__ __forceinline__ void ldsm4(uint32_t a, uint32_t& r0, uint32_t& r1, uint32_t& r2, uint32_t& r3) {
  asm volatile("ldmatrix.sync.aligned.m8n8.x4.shared.b16 {%0,%1,%2,%3}, [%4];" : "=r"(r0), "=r"(r1), "=r"(r2), "=r"(r3) : "r"(a) : "memory");
}
__device__ __forceinline__ void ldsm4t(uint32_t a, uint32_t& r0, uint32_t& r1, uint32_t& r2, uint32_t& r3) {
  asm volatile("ldmatrix.sync.aligned.m8n8.x4.trans.shared.b16 {%0,%1,%2,%3}, [%4];" : "=r"(r0), "=r"(r1), "=r"(r2), "=r"(r3) : "r"(a) : "memory");
}
__device__ __forceinline__ void stsm4(uint32_t a, uint32_t r0, uint32_t r1, uint32_t r2, uint32_t r3) {
  asm volatile("stmatrix.sync.aligned.m8n8.x4.shared.b16 [%0], {%1,%2,%3,%4};" :: "r"(a), "r"(r0), "r"(r1), "r"(r2), "r"(r3) : "memory");
}
template<int N> __device__ __forceinline__ void fence_regs(float (&d)[N]) {
#pragma unroll
  for (int i = 0; i < N; i++) asm volatile("" : "+f"(d[i]) :: "memory");
}
template<int N> __device__ __forceinline__ void fence_regs(uint32_t (&d)[N]) {
#pragma unroll
  for (int i = 0; i < N; i++) asm volatile("" : "+r"(d[i]) :: "memory");
}
__device__ __forceinline__ void sched_fence(float x, uint32_t dummy) {
  asm volatile("{\n.reg .pred p;\nsetp.eq.u32 p, %0, 0x7fc12345;\n@p st.shared.u32 [%1], %0;\n}\n" :: "r"(__float_as_uint(x)), "r"(dummy) : "memory");
}
#define TS(role, i)
#define TSA(i)
#define TR(obj, role, tag)

struct Prod {
  uint32_t base, mask; int lane, nt;
  __device__ __forceinline__ uint32_t full(int u) const { return base + SM_BAR + 8 * u; }
  __device__ __forceinline__ uint32_t addr(int u) const { return base + u * UNIT; }
  __device__ __forceinline__ void acquire(int u, int n) {
    const int v = u + min(lane, n - 1);
    mbar_wait_all(base + SM_BAR + 128 + 8 * v, mask >> v);
    mask ^= ((1u << n) - 1) << u;
    TR(*this, 2, 16 + u);
  }
  __device__ __forceinline__ void acquire_slow(int u, int n) {
    for (int i = 0; i < n; i++) mbar_wait_slow(base + SM_BAR + 128 + 8 * (u + i), mask >> (u + i));
    mask ^= ((1u << n) - 1) << u;
  }
};
struct Cons {
  uint32_t base, rel, mask; int lane, warp, wg, nt;
  __device__ __forceinline__ uint32_t addr(int u) const { return base + u * UNIT; }
  __device__ __forceinline__ static uint32_t daddr(int u) { return SMEM_BASE + u * UNIT; }
  __device__ __forceinline__ void wait(int u) { TR(*this, wg, 1); mbar_wait(base + SM_BAR + 8 * u, mask >> u); mask ^= 1u << u; TR(*this, wg, 2); }
  __device__ __forceinline__ void skip(int u) { mask ^= 1u << u; }
  __device__ __forceinline__ void release(int u, int n) {
    TR(*this, wg, 5);
    asm volatile("{\n.reg .pred p;\nsetp.lt.s32 p, %1, %2;\n@p mbarrier.arrive.shared::cluster.b64 _, [%0];\n}\n" :: "r"(rel + 8 * u), "r"(lane & 15), "r"(n) : "memory");
  }
  __device__ __forceinline__ void release2(int u) {
    asm volatile("{\n.reg .pred p;\nsetp.eq.s32 p, %1, 0;\n@p mbarrier.arrive.shared::cluster.b64 _, [%0], 2;\n}\n" :: "r"(rel + 8 * u), "r"(lane & 15) : "memory");
  }
  __device__ __forceinline__ void signal(int i) {
    __syncwarp();
    asm volatile("{\n.reg .pred p;\nsetp.eq.s32 p, %1, 0;\n@p mbarrier.arrive.shared::cta.b64 _, [%0];\n}\n" :: "r"(base + SM_SIG + 8 * i), "r"(lane) : "memory");
  }
  __device__ __forceinline__ void turn() { bar_sync(1 + wg, 256); TR(*this, wg, 3); }
  __device__ __forceinline__ void pass() { bar_arrive(2 - wg, 256); TR(*this, wg, 4); }
};
__device__ __forceinline__ int gemm_unit(int ks) { return 3 * (ks & 3); }
__device__ __forceinline__ int att_slot(int i) { return 4 + 2 * i; }
template<int MASK> __device__ __forceinline__ int kv_slot(int h) { return MASK == PH_ALL ? h & 15 : h; }
__device__ __forceinline__ int out_mb(int cta) { return cta >> 3; }
__device__ __forceinline__ int out_nb(int cta) { return cta & 7; }
__device__ __forceinline__ int conv_channel(int cta, int i) {
  return cta < NREG ? CH_EXTRA_TOTAL + cta * CONV_REG + i : (i >> 1) * 8 + (cta - NREG) * 2 + (i & 1);
}

template<int OFF, int N> __device__ __forceinline__ void pack_chunk(const float (&a)[N], float sc0, float sc1, uint4& v0, uint4& v1) {
  v0.x = pack_bf16(a[OFF + 0] * sc0, a[OFF + 1] * sc0); v0.y = pack_bf16(a[OFF + 4] * sc0, a[OFF + 5] * sc0);
  v0.z = pack_bf16(a[OFF + 8] * sc0, a[OFF + 9] * sc0); v0.w = pack_bf16(a[OFF + 12] * sc0, a[OFF + 13] * sc0);
  v1.x = pack_bf16(a[OFF + 2] * sc1, a[OFF + 3] * sc1); v1.y = pack_bf16(a[OFF + 6] * sc1, a[OFF + 7] * sc1);
  v1.z = pack_bf16(a[OFF + 10] * sc1, a[OFF + 11] * sc1); v1.w = pack_bf16(a[OFF + 14] * sc1, a[OFF + 15] * sc1);
}
template<int OFF, int N> __device__ __forceinline__ void pack_chunk(const float (&a)[N], uint4& v0, uint4& v1) {
  v0.x = pack_bf16(a[OFF + 0], a[OFF + 1]); v0.y = pack_bf16(a[OFF + 4], a[OFF + 5]);
  v0.z = pack_bf16(a[OFF + 8], a[OFF + 9]); v0.w = pack_bf16(a[OFF + 12], a[OFF + 13]);
  v1.x = pack_bf16(a[OFF + 2], a[OFF + 3]); v1.y = pack_bf16(a[OFF + 6], a[OFF + 7]);
  v1.z = pack_bf16(a[OFF + 10], a[OFF + 11]); v1.w = pack_bf16(a[OFF + 14], a[OFF + 15]);
}
__device__ __forceinline__ void sq_acc(const uint4& v, uint32_t& a) { a = hfma2(v.x, v.x, a); a = hfma2(v.y, v.y, a); a = hfma2(v.z, v.z, a); a = hfma2(v.w, v.w, a); }
__device__ __forceinline__ float norm2_max(uint32_t a0, uint32_t a1) {
  float n0 = bf_lo(a0) + bf_hi(a0), n1 = bf_lo(a1) + bf_hi(a1);
  n0 += __shfl_xor_sync(~0u, n0, 1); n1 += __shfl_xor_sync(~0u, n1, 1);
  n0 += __shfl_xor_sync(~0u, n0, 2); n1 += __shfl_xor_sync(~0u, n1, 2);
  return __uint_as_float(__reduce_max_sync(~0u, max(__float_as_uint(n0) & 0x7fffffffu, __float_as_uint(n1) & 0x7fffffffu)));
}

struct Pend { uint4 lo[8], hi[8]; uint32_t dst; float kn; };
__device__ __forceinline__ void pin(uint4 (&v)[8]) {
#pragma unroll
  for (int i = 0; i < 8; i++) asm volatile("" : "+r"(v[i].x), "+r"(v[i].y), "+r"(v[i].z), "+r"(v[i].w) :: "memory");
}
__device__ __forceinline__ uint32_t atom_off(int lane) { return (lane >> 2) * 64 + (((lane ^ (lane >> 3)) & 3) << 4); }
template<int J0, int J1> __device__ __forceinline__ void tile_store(const uint4 (&v)[8], uint32_t dst, int lane) {
  uint8_t* d = g_T + (dst + atom_off(lane));
#pragma unroll
  for (int j = J0; j < J1; j++) { *(uint4*)(d + j * 512) = v[2 * j]; *(uint4*)(d + j * 512 + 2048) = v[2 * j + 1]; }
}
__device__ __forceinline__ float tile_norm2(const uint4 (&v)[8]) {
  uint32_t n0 = 0, n1 = 0, n2 = 0, n3 = 0;
#pragma unroll
  for (int j = 0; j < 2; j++) { sq_acc(v[2 * j], n0); sq_acc(v[2 * j + 1], n1); sq_acc(v[2 * j + 4], n2); sq_acc(v[2 * j + 5], n3); }
  return norm2_max(hadd2(n0, n2), hadd2(n1, n3));
}
template<int PART> __device__ __forceinline__ void out_part(Cons& c, Pend& w) {
  if (PART == 0) { w.kn = tile_norm2(w.lo); tile_store<0, 2>(w.lo, w.dst, c.lane); }
  if (PART == 1) tile_store<2, 4>(w.lo, w.dst, c.lane);
  if (PART == 2) {
    const float vn = tile_norm2(w.hi);
    if (c.lane == 0) g_kn2[((w.dst - T_KV) >> 16) * 8 + c.wg * 4 + c.warp] = (vn <= 1.0e30f && vn >= 1.0e-30f) ? w.kn : __uint_as_float(0x7f800000u);
    tile_store<0, 2>(w.hi, w.dst + 32768, c.lane);
  }
  if (PART == 3) tile_store<2, 4>(w.hi, w.dst + 32768, c.lane);
}
template<bool FIRST> __device__ __forceinline__ void kv_issue(Cons& c, float (&acc)[128], int u) {
  const uint64_t da = odesc(c.daddr(u) + c.wg * 8192, 16, 1024, 1), db = odesc(c.daddr(u + 1), 8192, 1024, 1);
  c.turn();
  wg_fence();
#pragma unroll
  for (int kk = 0; kk < 4; kk++) wgmma_ss_n256<1>(acc, da + kk * 2, db + kk * 128, !(FIRST && kk == 0));
  wg_commit();
  c.pass();
}
__device__ __forceinline__ void cons_kv(Cons& c, int h, int hs, int g, Pend& w, bool pend_o) {
#pragma unroll 1
  for (int tile = 0; tile < 2; tile++) {
    float acc[128];
    c.wait(0);
    if (tile == 0 && h < 16) TS(c.wg, 16);
    kv_issue<true>(c, acc, 0);
    if (tile == 1 && pend_o) mbar_wait(c.base + SM_RDY + 8 * RDY_WAR, 0);
    if (tile == 1 || pend_o) out_part<0>(c, w);
#pragma unroll 1
    for (int ks = 1; ks < 8; ks++) {
      if (ks == 3 && (tile == 1 || pend_o)) { out_part<1>(c, w); if (tile == 0) c.signal(SIG_CTX); }
      if (ks == 5 && tile == 1) out_part<2>(c, w);
      if (ks == 7 && tile == 1) out_part<3>(c, w);
      const int u = gemm_unit(ks);
      c.wait(u);
      wg_wait<0>();
      c.release(gemm_unit(ks - 1), 3);
      kv_issue<false>(c, acc, u);
    }
    wg_wait<0>(); fence_regs(acc);
    c.release(9, 3);
    pack_chunk<0>(acc, w.lo[0], w.lo[1]);  pack_chunk<16>(acc, w.lo[2], w.lo[3]); pack_chunk<32>(acc, w.lo[4], w.lo[5]); pack_chunk<48>(acc, w.lo[6], w.lo[7]);
    pack_chunk<64>(acc, w.hi[0], w.hi[1]); pack_chunk<80>(acc, w.hi[2], w.hi[3]); pack_chunk<96>(acc, w.hi[4], w.hi[5]); pack_chunk<112>(acc, w.hi[6], w.hi[7]);
    pin(w.lo); pin(w.hi);
    w.dst = T_KV + (hs * 16 + 2 * g + tile) * 65536 + (c.wg * 4 + c.warp) * 4096;
  }
}
template<bool FIRST> __device__ __forceinline__ void q_issue(Cons& c, float (&a)[64], float (&b)[64], int u) {
  const uint64_t da = odesc(c.daddr(u) + c.wg * 8192, 16, 1024, 1), db = odesc(c.daddr(u + 2), 8192, 1024, 1);
  const uint64_t da2 = odesc(c.daddr(u + 1) + (1 - c.wg) * 8192, 16, 1024, 1);
  c.turn();
  wg_fence();
#pragma unroll
  for (int kk = 0; kk < 4; kk++) wgmma_ss_n128<1>(a, da + kk * 2, db + kk * 128, !(FIRST && kk == 0));
#pragma unroll
  for (int kk = 0; kk < 4; kk++) wgmma_ss_n128<1>(b, da2 + kk * 2, db + kk * 128, !(FIRST && kk == 0));
  wg_commit();
  c.pass();
}
template<int AU> __device__ __forceinline__ void q_tail(Cons& c, float (&d)[64], int rowhalf) {
  const uint64_t da = odesc(c.daddr(6 + AU) + rowhalf * 8192, 16, 1024, 1), db = odesc(c.daddr(8), 8192, 1024, 1);
  c.turn();
  wg_fence();
#pragma unroll
  for (int kk = 0; kk < 8; kk++) wgmma_ss_n128<1>(d, da + (kk >> 2) * 3072 + (kk & 3) * 2, db + (kk >> 2) * 3072 + (kk & 3) * 128, 1);
  wg_commit();
  c.pass();
}
template<int OFF> __device__ __forceinline__ void q_store(const float (&d)[64], uint4 (&v)[8], uint32_t q0) {
  pack_chunk<0>(d, QSCALE, QSCALE, v[0], v[1]);  sts128o<OFF>(q0, v[0]);        sts128o<OFF + 2048>(q0, v[1]);
  pack_chunk<16>(d, QSCALE, QSCALE, v[2], v[3]); sts128o<OFF + 512>(q0, v[2]);  sts128o<OFF + 2560>(q0, v[3]);
  pack_chunk<32>(d, QSCALE, QSCALE, v[4], v[5]); sts128o<OFF + 1024>(q0, v[4]); sts128o<OFF + 3072>(q0, v[5]);
  pack_chunk<48>(d, QSCALE, QSCALE, v[6], v[7]); sts128o<OFF + 1536>(q0, v[6]); sts128o<OFF + 3584>(q0, v[7]);
}
template<bool PEND_KV> __device__ __forceinline__ void cons_q(Cons& c, int h, Pend& w) {
  float a[64], b[64];
  c.wait(0);
  q_issue<true>(c, a, b, 0);
  if (PEND_KV) out_part<0>(c, w);
#pragma unroll 1
  for (int ks = 1; ks < 14; ks++) {
    if (PEND_KV && ks < 6) {
      if (ks == 2) out_part<1>(c, w);
      if (ks == 4) out_part<2>(c, w);
      if (ks == 5) { out_part<3>(c, w); c.signal(SIG_KV + (h >> 4)); }
    }
    const int u = gemm_unit(ks);
    c.wait(u);
    wg_wait<0>();
    c.release(gemm_unit(ks - 1), 3);
    q_issue<false>(c, a, b, u);
  }
  c.wait(6); c.wait(9);
  wg_wait<0>();
  c.release(3, 3);
  q_tail<1>(c, b, 1 - c.wg);
  wg_wait<0>(); fence_regs(b);
  q_tail<0>(c, a, c.wg);
  c.wait(0);
  const uint32_t q0 = c.addr(0) + (c.wg * 4 + c.warp) * 4096 + atom_off(c.lane);
  q_store<32768>(b, w.lo, q0);
  w.kn = tile_norm2(w.lo);
  c.wait(4);
  wg_wait<0>(); fence_regs(a);
  c.release(6, 6);
  q_store<0>(a, w.lo, q0);
  fence_async_smem();
}

__device__ __forceinline__ void issue_qk(float (&s)[64], uint64_t da, uint64_t db) {
#pragma unroll
  for (int kk = 0; kk < 8; kk++) wgmma_ss_n128<0>(s, da + (kk >> 1) * 32 + (kk & 1) * 2, db + (kk >> 1) * 32 + (kk & 1) * 2, kk > 0);
  wg_commit();
}
template<int A, int B> __device__ __forceinline__ void exp_rng(float (&s)[64]) {
#pragma unroll
  for (int i = 4 * A; i < 4 * B; i++) s[i] = ex2(s[i]);
}
template<int A, int B> __device__ __forceinline__ void sum_rng(const float (&s)[64], float (&l)[4]) {
#pragma unroll
  for (int i = A; i < B; i++) { l[0] += s[4 * i]; l[1] += s[4 * i + 1]; l[2] += s[4 * i + 2]; l[3] += s[4 * i + 3]; }
}
template<int A, int B> __device__ __forceinline__ void cvt_p(const float (&s)[64], uint32_t (&p)[32]) {
#pragma unroll
  for (int i = 2 * A; i < 2 * B; i++) p[i] = pack_bf16(s[2 * i], s[2 * i + 1]);
}
template<int K0> __device__ __forceinline__ void mask_half(float (&s)[64], int warp, int lane) {
  const int l0 = warp + (2 * (lane & 3) <= (lane >> 2)), l1 = warp + (2 * (lane & 3) < (lane >> 2));
#pragma unroll
  for (int k = 0; k < 4; k++) {
    float* t = s + 8 * (K0 + k);
    if (k >= l0) { t[0] = -INFINITY; t[6] = -INFINITY; }
    if (k >= l1) { t[1] = -INFINITY; t[7] = -INFINITY; }
    if (k > warp) { t[2] = -INFINITY; t[3] = -INFINITY; }
    if (k >= warp) { t[4] = -INFINITY; t[5] = -INFINITY; }
  }
}
__device__ __forceinline__ void row_inv(float& l0, float& l1) {
  l0 += __shfl_xor_sync(~0u, l0, 1); l1 += __shfl_xor_sync(~0u, l1, 1);
  l0 += __shfl_xor_sync(~0u, l0, 2); l1 += __shfl_xor_sync(~0u, l1, 2);
  l0 = __fdividef(1.f, l0); l1 = __fdividef(1.f, l1);
}
__device__ __forceinline__ void pack_o(const float (&o)[64], float i0, float i1, uint4 (&v)[8]) {
  pack_chunk<0>(o, i0, i1, v[0], v[1]); pack_chunk<16>(o, i0, i1, v[2], v[3]);
  pack_chunk<32>(o, i0, i1, v[4], v[5]); pack_chunk<48>(o, i0, i1, v[6], v[7]);
  pin(v);
}
__device__ __forceinline__ void softmax_safe(float (&s)[64], bool upper_only, float& m0, float& m1, float& sc0, float& sc1) {
  float a0 = m0, a1 = m1;
#pragma unroll
  for (int i = 0; i < 8; i++) { a0 = fmaxf(a0, fmaxf(s[4 * i], s[4 * i + 1])); a1 = fmaxf(a1, fmaxf(s[4 * i + 2], s[4 * i + 3])); }
  if (upper_only) { a0 = m0; a1 = m1; }
#pragma unroll
  for (int i = 8; i < 16; i++) { a0 = fmaxf(a0, fmaxf(s[4 * i], s[4 * i + 1])); a1 = fmaxf(a1, fmaxf(s[4 * i + 2], s[4 * i + 3])); }
  a0 = fmaxf(a0, __shfl_xor_sync(~0u, a0, 1)); a1 = fmaxf(a1, __shfl_xor_sync(~0u, a1, 1));
  a0 = fmaxf(a0, __shfl_xor_sync(~0u, a0, 2)); a1 = fmaxf(a1, __shfl_xor_sync(~0u, a1, 2));
  sc0 = ex2(m0 - a0); sc1 = ex2(m1 - a1);
  m0 = a0; m1 = a1;
#pragma unroll
  for (int i = 0; i < 16; i++) { s[4 * i] -= a0; s[4 * i + 1] -= a0; s[4 * i + 2] -= a1; s[4 * i + 3] -= a1; }
}
struct Att {
  float s[64], o[64], l[4], i0, i1; uint32_t p[32];
  uint32_t qaddr;
};
__device__ __forceinline__ uint32_t ctx_off(const Cons& c, int h, int qb, int rowhalf) { return T_CTX + (qb * 32 + h) * 32768 + (rowhalf * 4 + c.warp) * 4096; }
__device__ __forceinline__ int att_first(Cons& c, Att& a, int h, const Pend& w) {
  a.qaddr = c.daddr(0) + c.wg * 16384;
  c.turn();
  wg_fence();
  issue_qk(a.s, odesc(a.qaddr, 16, 2048, 2), odesc(c.daddr(4), 16, 2048, 2));
  c.pass();
  c.signal(SIG_ATT + (h >> 4));
  const float qn = tile_norm2(w.lo), kn = __uint_as_float(lds32(c.base + SM_KMAX + 4 * (h >> 4)));
  const int fast = __shfl_sync(~0u, bar_and(3 + c.wg, 128, (qn * kn <= BOUND2) && (w.kn * kn <= BOUND2)), 0);
#pragma unroll
  for (int i = 0; i < 64; i++) a.o[i] = 0.f;
#pragma unroll
  for (int i = 0; i < 32; i++) a.p[i] = 0;
  a.l[0] = a.l[1] = a.l[2] = a.l[3] = 0.f; a.i0 = a.i1 = 0.f;
  wg_wait<0>(); fence_regs(a.s);
  c.release(4, 2);
  return fast;
}
__device__ __forceinline__ void att_last(Cons& c, Att& a, Pend& w, int h, int g, bool drain) {
#pragma unroll 1
  for (int k = drain ? 0 : 1; k < 2; k++) {
    if (k == 1) {
      const int uv = att_slot(1);
      c.wait(uv);
      c.turn();
      fence_regs(a.o); fence_regs(a.p);
      wgmma_pv_sel(a.o, a.p, odesc(c.daddr(uv), 512, 2048, 2), !(drain && c.wg == 1), !drain);
      c.pass();
      a.i0 = a.l[0] + a.l[1]; a.i1 = a.l[2] + a.l[3]; row_inv(a.i0, a.i1);
      wg_wait<0>(); fence_regs(a.o); fence_regs(a.p);
      c.release(uv, 2);
    }
    pack_o(a.o, a.i0, a.i1, w.lo);
    if (k == 0) tile_store<0, 4>(w.lo, ctx_off(c, h, 15, c.wg), c.lane);
  }
  w.dst = ctx_off(c, h, g, 1 - c.wg);
}
__device__ __forceinline__ void cons_att(Cons& c, int h, int g, Pend& w) {
  Att a;
  const int fast = att_first(c, a, h, w);
  float m0 = -INFINITY, m1 = -INFINITY, sc0 = 0.f, sc1 = 0.f;
  int uk = 10, nrel = 0;
#pragma unroll 1
  for (int d = g - 15;;) {
    const bool lo = d == c.wg;
    if ((unsigned)d < 2 || !fast) {
      if ((unsigned)d < 2) mask_half<4>(a.s, c.warp, c.lane);
      if (!fast) {
        if (d == 1) m0 = m1 = -INFINITY;
        softmax_safe(a.s, lo, m0, m1, sc0, sc1);
        a.l[0] *= sc0; a.l[1] *= sc0; a.l[2] *= sc1; a.l[3] *= sc1;
      }
    }
    exp_rng<8, 16>(a.s); sum_rng<8, 16>(a.s, a.l);
    exp_rng<ATT_SPLIT, 8>(a.s);
    sched_fence(((a.l[0] + a.l[1]) + (a.l[2] + a.l[3])) + (ATT_SPLIT < 8 ? a.s[4 * ATT_SPLIT + 3] : 0.f), c.base + SM_DUMMY);
    wg_wait<0>(); fence_regs(a.o); fence_regs(a.p);
    c.release(14 - uk, nrel);
    nrel = 2; uk ^= 12;
    if (d == 0) a.qaddr += 32768;
    const uint64_t dq = odesc(a.qaddr, 16, 2048, 2), dk = odesc(c.daddr(uk) - (d + 1 == c.wg ? 16384 : 0), 16, 2048, 2), dv = odesc(c.daddr(14 - uk), 512, 2048, 2);
    if (!lo) { exp_rng<0, ATT_SPLIT>(a.s); sum_rng<0, 8>(a.s, a.l); cvt_p<0, 16>(a.s, a.p); }
    else if (gridDim.y == 1) cvt_p<8, 16>(a.s, a.p);
    if (!fast || d == g + 1) {
      if (!fast && d != 1) {
#pragma unroll
        for (int i = 0; i < 16; i++) { a.o[4 * i] *= sc0; a.o[4 * i + 1] *= sc0; a.o[4 * i + 2] *= sc1; a.o[4 * i + 3] *= sc1; }
      }
      if (d == g + 1) break;
    }
    d++;
    if (c.wg == 0) c.wait(uk); else c.skip(uk);
    c.turn();
    fence_regs(a.o); fence_regs(a.p);
    wg_fence();
    issue_qk(a.s, dq, dk);
    if (d == 2) {
      uint4 v[8];
      pack_o(a.o, a.i0, a.i1, v); tile_store<0, 4>(v, ctx_off(c, h, 15 - g, c.wg), c.lane);
    }
    wgmma_pv_sel(a.o, a.p, dv, !lo, d != 2);
    c.pass();
    if (d == 1) {
      a.i0 = a.l[0] + a.l[1]; a.i1 = a.l[2] + a.l[3]; row_inv(a.i0, a.i1);
      a.l[0] = a.l[1] = a.l[2] = a.l[3] = 0.f;
    }
    wg_wait<1>(); fence_regs(a.s);
    c.release(uk, 2);
    c.release(d == 0 ? 0 : 2, (d == 0 || d == g + 1) ? 2 : 0);
  }
  att_last(c, a, w, h, g, g == 0);
}

constexpr int CV_H = 1024, CV_U = 5120, CV_D = CV_U + 4128, CV_ROW = 1056;
template<int OFF> __device__ __forceinline__ uint32_t lds32o(uint32_t a) { uint32_t v; asm volatile("ld.shared.u32 %0, [%1+%2];" : "=r"(v) : "r"(a), "n"(OFF) : "memory"); return v; }
template<int G, int G1 = 16> __device__ __forceinline__ void conv_lda(uint32_t (&a)[64], uint32_t p) {
  a[4 * G + 0] = lds32o<-256 * G>(p);
  a[4 * G + 1] = lds32o<-256 * G - 128>(p);
  a[4 * G + 2] = lds32o<-256 * G + 16>(p);
  a[4 * G + 3] = lds32o<-256 * G - 112>(p);
  if constexpr (G + 1 < G1) conv_lda<G + 1, G1>(a, p);
}
template<int R, int G0, int G1> __device__ __forceinline__ void conv_mma(float (&d)[32], const uint32_t (&a)[64], uint64_t db) {
#pragma unroll
  for (int G = G0; G < G1; G++) wgmma_rs_n64<0>(d, a[4 * G], a[4 * G + 1], a[4 * G + 2], a[4 * G + 3], db + 64 * R - 16 * G, G > 0);
}
template<int R> __device__ __forceinline__ void conv_st(const float (&d)[32], uint32_t wq, float& c0, float& c1) {
#pragma unroll
  for (int n = 0; n < 8; n++) { sts64f(wq + (R * 64 + n * 8) * 4, d[4 * n] + c0, d[4 * n + 1] + c1); c0 = d[4 * n + 2]; c1 = d[4 * n + 3]; }
}
__device__ __forceinline__ void cons_conv(Cons& c, int cta, int nch) {
  const int r = c.lane >> 2, q = c.lane & 3, tid = c.warp * 32 + c.lane;
  const uint32_t part = c.addr(4) - 2048 + (1 - c.wg) * (32 * CV_ROW) + 32;
  const uint32_t aoff = CV_U + ((r & 1) ? 0 : UPITCH) + 4 * (((2039 - r) >> 1) + q - 8 * c.warp);
  const uint32_t wq = part + (c.warp * 8 + r) * CV_ROW + q * 8, rq = part + tid * 8;
  uint32_t a[64];
  c.wait(c.wg); c.skip(c.wg ^ 1);
  conv_lda<0>(a, c.addr(c.wg) + aoff);
  c.wait(4);
  sts64f(part + (tid >> 2) * CV_ROW - 32 + q * 8, 0.f, 0.f);
#pragma unroll 1
  for (int i = 0; i < nch / 2; i++) {
    const int u = 2 * (i & 1) + c.wg;
    float d0[32], d1[32], d2[32], d3[32];
    float c0 = 0.f, c1 = 0.f;
    const uint64_t db = odesc(c.daddr(u) + CV_H - 16, 16, 128, 0);
    c.turn();
    fence_regs(a);
    wg_fence();
    conv_mma<0, 0, 4>(d0, a, db); conv_mma<1, 0, 8>(d1, a, db); wg_commit();
    conv_mma<2, 0, 12>(d2, a, db); wg_commit();
    wg_wait<1>(); fence_regs(d0); fence_regs(d1);
    conv_st<0>(d0, wq, c0, c1);
    wg_fence();
    conv_mma<3, 0, 8>(d3, a, db);
    conv_st<1>(d1, wq, c0, c1);
    conv_mma<3, 8, 16>(d3, a, db); wg_commit();
    c.pass();
    wg_wait<1>(); fence_regs(d2);
    conv_st<2>(d2, wq, c0, c1);
    wg_wait<0>(); fence_regs(d3); fence_regs(a);
    conv_st<3>(d3, wq, c0, c1);
    TR(c, c.wg, 50);
    const uint32_t ub = c.addr(u);
    const uint4 ua = lds128(ub + CV_U + 4064 - 32 * tid + 16), uc = lds128(ub + CV_U + 4064 - 32 * tid);
    const uint32_t D2 = lds32(ub + CV_D);
    bar_sync(3 + c.wg, 128);
    c.release2(u);
    TR(c, c.wg, 51);
    float y0[8], y1[8];
#pragma unroll
    for (int rr = 0; rr < 8; rr++) { const float2 v = lds64f(rq + rr * CV_ROW); y0[rr] = v.x; y1[rr] = v.y; }
#pragma unroll
    for (int w = 1; w < 4; w++) {
#pragma unroll
      for (int rr = 0; rr < 8; rr++) { const float2 v = lds64f(rq + (w * 8 + rr) * CV_ROW - w * 8); y0[rr] += v.x; y1[rr] += v.y; }
    }
    if (i + 1 < nch / 2) { c.wait(u ^ 2); c.skip(u ^ 3); conv_lda<0>(a, c.addr(u ^ 2) + aoff); }
    uint4 z0, z1;
    z0.x = hadd2(pack_bf16(y0[0], y0[1]), hmul2(__byte_perm(ua.w, 0, 0x1032), D2));
    z0.y = hadd2(pack_bf16(y0[2], y0[3]), hmul2(__byte_perm(ua.z, 0, 0x1032), D2));
    z0.z = hadd2(pack_bf16(y0[4], y0[5]), hmul2(__byte_perm(ua.y, 0, 0x1032), D2));
    z0.w = hadd2(pack_bf16(y0[6], y0[7]), hmul2(__byte_perm(ua.x, 0, 0x1032), D2));
    z1.x = hadd2(pack_bf16(y1[0], y1[1]), hmul2(__byte_perm(uc.w, 0, 0x1032), D2));
    z1.y = hadd2(pack_bf16(y1[2], y1[3]), hmul2(__byte_perm(uc.z, 0, 0x1032), D2));
    z1.z = hadd2(pack_bf16(y1[4], y1[5]), hmul2(__byte_perm(uc.y, 0, 0x1032), D2));
    z1.w = hadd2(pack_bf16(y1[6], y1[7]), hmul2(__byte_perm(uc.x, 0, 0x1032), D2));
    uint4* zp = (uint4*)(g_z + (size_t)conv_channel(cta, 2 * i + c.wg) * 2048 + tid * 16);
    zp[0] = z0; zp[1] = z1;
    TR(c, c.wg, 52);
    if ((i & 15) == 15 || i == nch / 2 - 1) c.signal(SIG_Z + (i >> 4));
  }
  c.release(4, 4);
}

constexpr int OC_START = 2, OC_LEN = 15, OC_PART = 13824, OC_ROW = 544;
__device__ __forceinline__ int out_next(int u) { return u == 12 ? 4 : u + 2; }
struct Out { float acc[64]; int pu; uint64_t da, db; };
template<bool FIRST, bool REL> __device__ __forceinline__ void out_step(Cons& c, Out& o) {
  const int pu = o.pu, u = out_next(pu);
  o.pu = u;
  c.wait(u);
  const uint64_t da = o.da + (uint32_t)(u * 1024), db = o.db + (uint32_t)(u * 1024);
  wg_fence();
#pragma unroll
  for (int kk = 0; kk < 4; kk++) wgmma_ss_n128<1>(o.acc, da + (kk >> 1) * 32 + (kk & 1) * 2, db + kk * 128, !(FIRST && kk == 0));
  wg_commit();
  if (REL) { wg_wait<1>(); c.release(pu, 2); }
}
template<int I0, int I1> __device__ __forceinline__ void oc_red(float (&y)[8], uint32_t rq) {
#pragma unroll
  for (int i = I0; i < I1; i++) { const float v = __uint_as_float(lds32(rq + i * OC_ROW - (i >> 3) * 8)); y[i & 7] = i < 8 ? v : y[i & 7] + v; }
}
__device__ __forceinline__ void oc_emit(const float (&y)[8], const uint4& u, uint32_t D2, __nv_bfloat16* dst) {
  uint4 z;
  z.x = hadd2(pack_bf16(y[0], y[1]), hmul2(__byte_perm(u.w, 0, 0x1032), D2));
  z.y = hadd2(pack_bf16(y[2], y[3]), hmul2(__byte_perm(u.z, 0, 0x1032), D2));
  z.z = hadd2(pack_bf16(y[4], y[5]), hmul2(__byte_perm(u.y, 0, 0x1032), D2));
  z.w = hadd2(pack_bf16(y[6], y[7]), hmul2(__byte_perm(u.x, 0, 0x1032), D2));
  *(uint4*)dst = z;
}
template<int MASK> __device__ __forceinline__ void cons_out(Cons& c, const Maps& M, int cta, Pend& w) {
  const int mb = out_mb(cta), nb = out_nb(cta);
  Out o;
  o.da = odesc(c.daddr(0) + c.wg * 8192, 16, 1024, 2); o.db = odesc(c.daddr(1), 8192, 1024, 1);
  o.pu = 5 + gridDim.y;
  out_step<true, false>(c, o);
  if (MASK & PH_ATT) tile_store<0, 2>(w.lo, w.dst, c.lane);
  out_step<false, true>(c, o);
  if (MASK & PH_ATT) { tile_store<2, 4>(w.lo, w.dst, c.lane); c.signal(SIG_CTX + 1); }
  int ks = OC_START;
  if (MASK & PH_CONV) {
    const int r = c.lane >> 2, q = c.lane & 3, tid = c.warp * 32 + c.lane, u = 2 * c.wg;
    const uint32_t ub = c.addr(u), part = ub + OC_PART + 32;
    const uint32_t ap = ub + CV_U + ((r & 1) ? 0 : UPITCH) + 4 * (((2039 - r) >> 1) + q - 8 * c.warp);
    const uint32_t wq = part + (c.warp * 8 + r) * OC_ROW + q * 8, rq = part + tid * 4;
    const int nr = (CONV_REG + 1 - c.wg) >> 1;
#define STEP(N) out_step<false, true>(c, o);
#pragma unroll 1
    for (int i = 0; i < nr; i++) {
      uint32_t a[64];
      float d0[32], d1[32], y[8], c0 = 0.f, c1 = 0.f;
      const uint64_t db = odesc(c.daddr(u + (i >> 8)) + CV_H - 16, 16, 128, 0);
      c.wait(u);
      conv_lda<0, 3>(a, ap);
      STEP(0)
      conv_lda<3, 6>(a, ap);
      STEP(1)
      conv_lda<6, 9>(a, ap);
      STEP(2)
      fence_regs(reinterpret_cast<uint32_t (&)[32]>(a));
      wg_fence();
      conv_mma<0, 0, 4>(d0, a, db); conv_mma<1, 0, 8>(d1, a, db); wg_commit();
      conv_lda<9, 13>(a, ap);
      STEP(3)
      fence_regs(d0); fence_regs(d1);
      conv_lda<13, 16>(a, ap);
      STEP(4)
      bar_sync(3 + c.wg, 128);
      sts64f(wq - 32, 0.f, 0.f);
      conv_st<0>(d0, wq, c0, c1);
      STEP(5)
      float e0 = d1[28] + d1[26], e1 = d1[29] + d1[27];
      conv_st<1>(d1, wq, c0, c1);
      asm volatile("add.f32 %0, %0, 0f80000000;" : "+f"(c0)); asm volatile("add.f32 %0, %0, 0f80000000;" : "+f"(c1));
      fence_regs(a);
      wg_fence();
      conv_mma<2, 0, 12>(d0, a, db); conv_mma<3, 0, 16>(d1, a, db); wg_commit();
      bar_sync(3 + c.wg, 128);
      oc_red<0, 8>(y, rq);
      STEP(6)
      fence_regs(d0); fence_regs(d1); fence_regs(a);
      const uint4 u0 = lds128(ub + CV_U + 4080 - 16 * tid), u1 = lds128(ub + CV_U + 2032 - 16 * tid);
      const uint32_t D2 = lds32(ub + CV_D);
      oc_red<8, 12>(y, rq);
      __syncwarp();
      c.release2(u);
      STEP(7)
      oc_red<12, 24>(y, rq);
      STEP(8)
      __nv_bfloat16* zp = g_z + (uint32_t)(conv_channel(cta, 2 * i + c.wg) * 2048 + (threadIdx.x & 127) * 8);
      oc_red<24, 32>(y, rq);
      oc_emit(y, u0, D2, zp);
      bar_sync(3 + c.wg, 128);
      STEP(9)
      sts64f(wq - 32, e0, e1);
      conv_st<0>(d0, wq, c0, c1);
      STEP(10)
      conv_st<1>(d1, wq, c0, c1);
      bar_sync(3 + c.wg, 128);
      oc_red<0, 8>(y, rq);
      STEP(11)
      oc_red<8, 16>(y, rq);
      STEP(12)
      oc_red<16, 24>(y, rq);
      STEP(13)
      oc_red<24, 32>(y, rq);
      oc_emit(y, u1, D2, zp + 1024);
      if (i == nr - 1) { c.signal(SIG_Z); c.release2(u + 1); }
      STEP(14)
    }
#undef STEP
    if (((CONV_REG + c.wg) >> 1) & 1) c.skip(u ^ 2);
    ks += nr * OC_LEN;
  }
  TS(c.wg, 9);
#pragma unroll 1
  for (; ks < 57; ks++) out_step<false, true>(c, o);
  uint32_t ga[32];
  c.wait(0);
  const float g0 = __uint_as_float(lds32(c.base + SM_GATE + 4 * (c.wg * 64 + c.warp * 16 + (c.lane >> 2)))), g1 = __uint_as_float(lds32(c.base + SM_GATE + 32 + 4 * (c.wg * 64 + c.warp * 16 + (c.lane >> 2))));
  const uint32_t gg0 = pack_bf16(g0, g0), gg1 = pack_bf16(g1, g1);
  const uint32_t og0 = pack_bf16(1.f - g0, 1.f - g0), og1 = pack_bf16(1.f - g1, 1.f - g1);
  const int xr = c.wg * 64 + c.warp * 16 + (c.lane & 15);
  const uint32_t xa = c.addr(0) + xr * 128, xs = xr & 7, xh = c.lane >> 4;
  const int zr = (c.lane & 7) + ((c.lane >> 4) << 3);
  const uint32_t za = c.addr(2) + c.wg * 16384 + zr * 128 + (((c.warp * 2 + ((c.lane >> 3) & 1)) ^ (zr & 7)) << 4);
#pragma unroll
  for (int i = 0; i < 8; i++) {
    if (i == 0) out_step<false, true>(c, o);
    if (i == 3) out_step<false, true>(c, o);
    if (i == 6) out_step<false, true>(c, o);
    ldsm4(xa + (i >> 2) * 16384 + ((((i & 3) * 2 + xh) ^ xs) << 4), ga[4 * i], ga[4 * i + 1], ga[4 * i + 2], ga[4 * i + 3]);
  }
#pragma unroll 1
  for (ks = 60; ks < 63; ks++) { out_step<false, false>(c, o); wg_wait<1>(); }
  c.wait(2);
#pragma unroll
  for (int i = 0; i < 8; i++) {
    if (i == 2) out_step<false, false>(c, o);
    uint32_t z0, z1, z2, z3;
    ldsm4t(za + i * 2048, z0, z1, z2, z3);
    ga[4 * i + 0] = hmul2(gg0, hmul2(ga[4 * i + 0], z0)); ga[4 * i + 1] = hmul2(gg1, hmul2(ga[4 * i + 1], z1));
    ga[4 * i + 2] = hmul2(gg0, hmul2(ga[4 * i + 2], z2)); ga[4 * i + 3] = hmul2(gg1, hmul2(ga[4 * i + 3], z3));
  }
  c.signal(SIG_DONE);
  asm volatile("barrier.cluster.arrive.relaxed;" ::: "memory");
  fence_regs(ga);
  wg_wait<0>(); fence_regs(o.acc);
#pragma unroll
  for (int i = 0; i < 8; i++) {
    const uint32_t r0 = hadd2(ga[4 * i + 0], hmul2(og0, pack_bf16(o.acc[8 * i + 0], o.acc[8 * i + 1])));
    const uint32_t r1 = hadd2(ga[4 * i + 1], hmul2(og1, pack_bf16(o.acc[8 * i + 2], o.acc[8 * i + 3])));
    const uint32_t r2 = hadd2(ga[4 * i + 2], hmul2(og0, pack_bf16(o.acc[8 * i + 4], o.acc[8 * i + 5])));
    const uint32_t r3 = hadd2(ga[4 * i + 3], hmul2(og1, pack_bf16(o.acc[8 * i + 6], o.acc[8 * i + 7])));
    stsm4(xa + (i >> 2) * 16384 + ((((i & 3) * 2 + xh) ^ xs) << 4), r0, r1, r2, r3);
  }
  fence_async_smem();
  __syncwarp();
  if (c.lane < 2) {
    const int r0 = c.wg * 64 + c.warp * 16;
    tma2d_store(&M.out, c.addr(0) + c.lane * 16384 + r0 * 128, nb * 128 + c.lane * 64, mb * 128 + r0);
    asm volatile("cp.async.bulk.commit_group;\ncp.async.bulk.wait_group.read 0;" ::: "memory");
  }
}

__device__ __forceinline__ void load_conv(Prod& p, const Maps& M, int u, int ch) {
  if (elect()) {
    mbar_expect(p.full(u), 5120 + UCH);
    tma3d(p.addr(u), &M.h, 0, -8, ch, p.full(u), POL(4));
    bulk_g2s(p.addr(u) + CV_U, g_u + (size_t)ch * UCH, UCH, p.full(u), POL(4));
  }
}
__device__ __forceinline__ void prod_conv(Prod& p, const Maps& M, int cta, int nch) {
  int ready = -1;
#pragma unroll 1
  for (int i = 0; i < nch; i++) {
    const int ch = conv_channel(cta, i);
    const int u = i & 3;
    if ((ch >> 6) != ready) { ready = ch >> 6; if (cta < NREG) mbar_wait(p.base + SM_RDY + 8 * RDY_U, 0); else cnt_wait(g_cnt + (C_U + ready) * CSTRIDE, 32); }
    p.acquire(u, 1);
    load_conv(p, M, u, ch);
    if (i == 3) { p.acquire(4, 4); if (elect()) mbar_arrive(p.full(4)); }
  }
}
#define HOIST(v) asm volatile("" : "+r"(v))
template<int MASK> __device__ __forceinline__ void producer(const Maps& M, const Params& P, uint32_t base, int cta, int lane) {
  Prod p{base, ((MASK & PH_KV) && cta < NREG) ? 0xffffcfffu ^ ((1u << (3 * NFIRST)) - 1) : 0xffffffffu, lane,
         (cta * 3 + 2) * 2048};
  if (cta >= NREG) { if (MASK & PH_CONV) prod_conv(p, M, cta, CONV_EXTRA); return; }
  const int g = cta & 7, j = cta >> 3, rank = cta & 1;
#pragma unroll 1
  for (int half = 0; half < 2; half++) {
    const int h = j + 16 * half;
    if (MASK & PH_KV) {
      const CUtensorMap* mw = rank ? &M.wv : &M.wk;
#pragma unroll 1
      for (int it = half ? 0 : NFIRST; it < 16; it++) {
        const int u = gemm_unit(it);
        uint32_t bar = p.full(u), d0 = p.addr(u), d1 = p.addr(u + 1 + rank); int k0 = (it & 7) * 64, r0 = (2 * g + (it >> 3)) * 128;
        HOIST(bar); HOIST(d0); HOIST(d1); HOIST(k0); HOIST(r0);
        p.acquire(u, 3);
        if (elect()) {
          mbar_expect(bar, 3 * UNIT);
          tma3d_mc(d1, mw, 0, k0, 2 * h, bar, POL(0) && it >= 8);
          tma2d(d0, &M.c, k0, r0, bar);
        }
      }
    }
    if (MASK & PH_ATT) {
#pragma unroll 1
      for (int ks = 0; ks < 16; ks++) {
        const int u = gemm_unit(ks);
        uint32_t bar = p.full(u), d0 = p.addr(u), d1 = p.addr(u + 1), d2 = p.addr(u + 2) + rank * 8192; int k0 = ks * 64;
        HOIST(bar); HOIST(d0); HOIST(d1); HOIST(d2); HOIST(k0);
        p.acquire(u, 3);
        if (elect()) {
          mbar_expect(bar, 3 * UNIT);
          tma2d_mc(d2, &M.wq, h * 128 + rank * 64, k0, bar, POL(1));
          tma2d(d0, &M.x, k0, (15 - g) * 128, bar);
          tma2d(d1, &M.x, k0, g * 128, bar);
        }
      }
      TS(2, 8 * half + 0);
      mbar_wait(base + SM_RDY + 8 * (RDY_KV + half), 0);
      TS(2, 8 * half + 1);
      p.acquire(0, 4);
      if (elect()) mbar_arrive(p.full(0));
      const uint8_t* KVh = g_T + T_KV + (size_t)kv_slot<MASK>(h) * 16 * 65536;
#pragma unroll 1
      for (int i = 0; i < 34; i++) {
        const int isv = (i > 0 && !(i & 1)) || i == 33;
        const int st = i == 33 ? 16 : (isv ? (i >> 1) - 1 : (i + 1) >> 1);
        const int u = att_slot(i & 3);
        const bool own = st == 15 - (g & 6);
        uint32_t bar = p.full((isv && i < 33) ? 14 - u : u), d0 = p.addr(own ? u : u + rank), off = (st <= 15 - g ? st : 16 - st) * 65536 + isv * 32768 + (own ? 0 : rank * UNIT);
        HOIST(bar); HOIST(d0); HOIST(off);
        p.acquire(u, 2);
        if (elect()) {
          if (!isv || i == 33) mbar_expect(bar, (i == 0 || i == 33) ? 32768 : 65536);
          if (own) bulk_g2s(d0, KVh + off, 32768, bar, POL(6)); else bulk_g2s_mc(d0, KVh + off, UNIT, bar, POL(6));
        }
      }
    }
  }
  if ((MASK & PH_CONV) && !(MASK & PH_OUT)) prod_conv(p, M, cta, CONV_REG);
  if (MASK & PH_OUT) {
    const int y0 = out_mb(cta) * 512 + rank * 8, z0 = 2 * out_nb(cta);
    int u = 6;
#pragma unroll 1
    for (int hf = 0; hf < 2; hf++) {
      TS(2, 16 + 2 * hf);
      mbar_wait(base + SM_RDY + 8 * (RDY_CTX + hf), 0);
      TS(2, 17 + 2 * hf);
#pragma unroll 1
      for (int ks = hf * 32; ks < hf * 32 + 32; ks++) {
        u = out_next(u);
        uint32_t bar = p.full(u), d0 = p.addr(u) + rank * 8192, d1 = p.addr(u + 1); int x = (ks & 1) * 256, y = y0 + (ks >> 1) * 16, k0 = ks * 64;
        HOIST(bar); HOIST(d0); HOIST(d1); HOIST(x); HOIST(y); HOIST(k0);
        p.acquire(u, 2);
        if (elect()) {
          mbar_expect(bar, 2 * UNIT);
          tma2d_mc(d0, &M.ctx, x, y, bar, POL(5));
          tma3d(d1, &M.wo, 0, k0, z0, bar, POL(2));
        }
      }
    }
    if (elect()) mbar_arrive(base + SM_RDY + 8 * RDY_Z);
  }
}
template<int MASK> __device__ __forceinline__ void producer2(const Maps& M, const Params& P, uint32_t base, int cta, int w, int lane) {
  Prod p{base, 0xffffffffu, lane, 0};
  const int mb = out_mb(cta), nb = out_nb(cta), u = 2 * w;
  if (MASK & PH_CONV) {
    mbar_wait_slow(base + SM_SIG + 8 * (SIG_ATT + 1), 0);
    mbar_wait_slow(base + SM_RDY + 8 * RDY_U, 0);
#pragma unroll 1
    for (int i = w; i < CONV_REG; i += 2) { p.acquire_slow(u, i < 2 ? 2 : 1); load_conv(p, M, u, conv_channel(cta, i)); }
  }
  p.acquire_slow(u, 2);
  TSA(50 + 2 * w);
  mbar_wait_slow(base + SM_RDY + 8 * (w ? RDY_Z : RDY_G), 0);
  TSA(51 + 2 * w);
  if (elect()) {
    mbar_expect(p.full(u), 2 * UNIT + (w ? 0 : 512));
    tma2d(p.addr(u), w ? &M.z : &M.x, (w ? mb : nb) * 128, (w ? nb : mb) * 128, p.full(u), POL(5));
    tma2d(p.addr(u + 1), w ? &M.z : &M.x, (w ? mb : nb) * 128 + 64, (w ? nb : mb) * 128, p.full(u), POL(5));
    if (!w) bulk_g2s(base + SM_GATE, g_gate + mb * 128, 512, p.full(u));
  }
}

__device__ __forceinline__ constexpr uint32_t PUB(int sig, int cnt, int n) { return 0x80000000u | (sig << 24) | (n << 8) | cnt; }
__device__ __forceinline__ constexpr uint32_t GET(int rdy, int cnt, int n) { return (rdy << 24) | (n << 8) | cnt; }
template<int MASK> __device__ __forceinline__ void sync_agent(uint32_t base, int cta, int lane) {
  if ((base & 0x3FFFF) != SMEM_BASE) asm volatile("trap;");
  const int g = cta & 7, j = cta >> 3, go = min(out_mb(cta), 15 - out_mb(cta));
  const int c0 = conv_channel(cta, 0), c1 = c0 + CONV_REG - 1, n0 = min(CONV_REG, 128 - (c0 & 127));
  constexpr bool KV = MASK & PH_KV, ATT = MASK & PH_ATT, CONV = MASK & PH_CONV, OUT = MASK & PH_OUT, ALL = MASK == PH_ALL;
  uint32_t e = 0;
  if (cta >= NREG) { if (CONV && lane * 32 < CONV_EXTRA) e = PUB(SIG_Z + lane, C_Z + lane, min(32, CONV_EXTRA - lane * 32)); }
  else switch (lane) {
    case 0:  if (KV) e = PUB(SIG_KV, C_KV + j, 1); break;
    case 1:  if (ATT) e = GET(RDY_KV, C_KV + j, 8); break;
    case 2:  if (ALL) e = PUB(SIG_WAR, C_WAR + j, 1); break;
    case 3:  if (ATT) e = PUB(SIG_CTX, C_CTX + g, 1); break;
    case 4:  if (ALL) e = GET(RDY_WAR, C_WAR + j, 8); break;
    case 5:  if (KV) e = PUB(SIG_KV + 1, C_KV + 16 + j, 1); break;
    case 6:  if (ATT) e = GET(RDY_KV + 1, C_KV + 16 + j, 8); break;
    case 7:  if (OUT) e = GET(RDY_CTX, C_CTX + go, 16); break;
    case 8:  if (CONV) e = GET(RDY_U, C_U + (c0 >> 6), 32); break;
    case 9:  if (CONV) e = GET(RDY_U, C_U + (c1 >> 6), 32); break;
    case 10: if (ATT) e = PUB(SIG_CTX + 1, C_CTX + 8 + g, 1); break;
    case 11: if (OUT) e = GET(RDY_CTX + 1, C_CTX + 8 + go, 16); break;
    case 12: if (OUT) e = GET(RDY_G, C_GATE, 256); break;
    case 13: if (CONV) e = PUB(SIG_Z, C_Z + (c0 >> 7), n0); break;
    case 14: if (CONV && n0 < CONV_REG) e = PUB(SIG_Z, C_Z + (c1 >> 7), CONV_REG - n0); break;
    case 15: if (OUT) e = GET(RDY_Z, C_Z + out_nb(cta), 128); break;
  }
  __syncwarp();
#pragma unroll 1
  for (int i = 0; i < 16; i++) {
    const uint32_t x = __shfl_sync(~0u, e, i), id = (x >> 24) & 127, n = (x >> 8) & 0xffff;
    if (x == 0) continue;
    unsigned* cnt = g_cnt + (x & 255) * CSTRIDE;
    if (x >> 31) {
      mbar_wait_slow(base + SM_SIG + 8 * id, 0);
      if (lane == 0) cnt_publish(cnt, n);
    } else {
      cnt_wait(cnt, n);
      if (id < 2) {
        const float4 kn = __ldcg((const float4*)(g_kn2 + kv_slot<MASK>(j + 16 * id) * 128) + lane);
        const uint32_t m = __reduce_max_sync(~0u, max(max(__float_as_uint(kn.x), __float_as_uint(kn.y)), max(__float_as_uint(kn.z), __float_as_uint(kn.w))));
        if (lane == 0) asm volatile("st.shared.u32 [%0], %1;" :: "r"(base + SM_KMAX + 4 * id), "r"(m) : "memory");
      }
      if (lane == 0) mbar_arrive(base + SM_RDY + 8 * id);
    }
    __syncwarp();
  }
}

template<int MASK> __device__ __forceinline__ void aux_pre(const Maps& M, const Params& P, uint32_t base, int cta, int aw, int lane) {
  const uint32_t kb = base + 12 * UNIT, bar = base + SM_PRE;
  const int r = lane >> 2, q = lane & 3;
  const int mi = lane >> 3, row0 = (lane & 6) + 1 - (lane & 1);
  if (PRE_DELAY) mbar_wait_slow(base + SM_BAR + 8 * 9, 0);
#pragma unroll 1
  for (int it = 0; it < 4; it++) {
    if (it == PRE_EARLY && MASK == PH_ALL) mbar_wait_slow(base + SM_SIG + 8 * (SIG_ATT + PRE_HALF), 0);
    const int cg = it * 4 + (cta >> 5), tb = cta & 31;
    if (aw == 0 && elect()) {
      mbar_expect(bar, 2 * 9216);
      tma4d(kb, &M.k, cg * 64, 0, tb * 8 - 1, 0, bar, POL(3));
      tma4d(kb + 9216, &M.v, cg * 64, 0, tb * 8 - 1, 0, bar, POL(3));
    }
    const uint2 swl = __ldg((const uint2*)(P.shift + (cg * 64 + aw * 32 + lane) * 4));
    if (tb == 0) {
      uint8_t* e = g_u + (size_t)(cg * 64 + aw * 32 + lane) * UCH + 4096;
      *(uint4*)e = make_uint4(0, 0, 0, 0); *(uint4*)(e + UPITCH) = make_uint4(0, 0, 0, 0);
      *(uint32_t*)(e + 32) = (uint32_t)__bfloat16_as_ushort(P.D[cg * 64 + aw * 32 + lane]) * 0x10001u;
    }
    mbar_wait_slow(bar, it & 1);
#pragma unroll 1
    for (int bl = 0; bl < 8; bl++) {
      const int oc = aw * 4 + (bl >> 1), hb = bl & 1, ch = cg * 64 + oc * 8 + r;
      const uint2 sw = make_uint2(__shfl_sync(~0u, swl.x, (bl >> 1) * 8 + r), __shfl_sync(~0u, swl.y, (bl >> 1) * 8 + r));
      const uint32_t w0 = __byte_perm(sw.x, 0, 0x1010), w1 = __byte_perm(sw.x, 0, 0x3232), w2 = __byte_perm(sw.y, 0, 0x1010), w3 = __byte_perm(sw.y, 0, 0x3232);
      const int ra = (mi * 9 + 4 * hb + 1) * 2 + row0;
      const int rb = ((mi == 0 ? 3 : mi) * 9 + 4 * hb) * 2 + row0;
      uint32_t k[7], v[5];
      ldsm4t(kb + ra * 128 + ((oc ^ (ra & 7)) << 4), k[3], k[4], k[5], k[6]);
      ldsm4t(kb + 9216 + ra * 128 + ((oc ^ (ra & 7)) << 4), v[1], v[2], v[3], v[4]);
      ldsm4t(kb + (mi == 0 ? 9216 : 0) + rb * 128 + ((oc ^ (rb & 7)) << 4), v[0], k[0], k[1], k[2]);
      uint32_t o1 = __byte_perm(k[1], k[0], 0x5432);
#pragma unroll
      for (int m = 0; m < 5; m++) {
        const uint32_t o2 = __byte_perm(k[m + 2], k[m + 1], 0x5432);
        v[m] = hmul2(hadd2(hadd2(hadd2(hmul2(o1, w3), hmul2(k[m + 1], w2)), hmul2(o2, w1)), hmul2(k[m + 2], w0)), v[m]);
        o1 = o2;
      }
      uint8_t* e0 = g_u + (size_t)ch * UCH + (2040 - tb * 64 - hb * 32 - 8 * q) * 2;
      *(uint4*)e0 = make_uint4(v[4], v[3], v[2], v[1]);
      *(uint4*)(e0 + UPITCH) = make_uint4(__byte_perm(v[4], v[3], 0x5432), __byte_perm(v[3], v[2], 0x5432), __byte_perm(v[2], v[1], 0x5432), __byte_perm(v[1], v[0], 0x5432));
    }
    bar_sync(5, 64);
    if (aw == 0) { TSA(40 + it); }
    if (aw == 1 && lane == 0) asm volatile("red.release.gpu.global.add.u32 [%0], 1;" :: "l"(g_cnt + (C_U + cg) * CSTRIDE) : "memory");
  }
  uint32_t rel;
  asm volatile("mapa.shared::cluster.u32 %0, %1, %2;" : "=r"(rel) : "r"(base + SM_BAR + 128 + 8 * (12 + (lane & 1))), "r"((lane >> 1) & 1));
  if (lane < 4) asm volatile("mbarrier.arrive.shared::cluster.b64 _, [%0], 4;" :: "r"(rel) : "memory");
  uint4 gw[4];
#pragma unroll
  for (int i = 0; i < 4; i++) gw[i] = __ldg((const uint4*)P.gw + i * 32 + lane);
#pragma unroll 1
  for (int row = cta * 16 + aw * 8; row < cta * 16 + aw * 8 + 8; row++) {
    float a = 0.f;
#pragma unroll
    for (int i = 0; i < 4; i++) {
      const uint4 xv = __ldg((const uint4*)(P.x + (size_t)row * 1024) + i * 32 + lane);
      uint32_t m;
      m = hmul2(xv.x, gw[i].x); a += bf_lo(m) + bf_hi(m); m = hmul2(xv.y, gw[i].y); a += bf_lo(m) + bf_hi(m);
      m = hmul2(xv.z, gw[i].z); a += bf_lo(m) + bf_hi(m); m = hmul2(xv.w, gw[i].w); a += bf_lo(m) + bf_hi(m);
    }
#pragma unroll
    for (int o = 16; o > 0; o >>= 1) a += __shfl_xor_sync(~0u, a, o);
    a = bf_lo(pack_bf16(a, 0.f));
    const float gt = bf_lo(pack_bf16(__fdividef(1.f, 1.f + ex2(-a * 1.4426950408889634f)), 0.f));
    if (lane == 0) g_gate[row] = gt;
  }
  cnt_signal(g_cnt + C_GATE * CSTRIDE, lane);
  if (aw == 0) { TSA(44); }
}

template<int MASK> __global__ void __cluster_dims__(2, 1, 1) __launch_bounds__(384, 1) gated_mix_kernel(const __grid_constant__ Maps M, const __grid_constant__ Params P) {
  extern __shared__ __align__(1024) uint8_t smem[];
  const uint32_t base = (uint32_t)__cvta_generic_to_shared(smem);
  const int wi = __shfl_sync(~0u, threadIdx.x >> 5, 0), wg = wi >> 2, warp = wi & 3;
  if (elect()) {
    if (wi < 8) {
      const int cnt = 1 << ((0x10334400 >> (4 * wi)) & 15);
#pragma unroll
      for (int i = 0; i < 8; i++) mbar_init(base + SM_BAR + 64 * wi + 8 * i, cnt);
      asm volatile("fence.mbarrier_init.release.cluster;" ::: "memory");
    } else if (MAP_PF) {
      asm volatile("prefetch.tensormap [%0];" :: "l"(&M.c + (wi - 8)) : "memory");
    }
  }
  const int cta = blockIdx.x;
  const bool first_loads = (MASK & PH_KV) && wi == 8 && cta < NREG;
  const CUtensorMap* mw = (cta & 1) ? &M.wv : &M.wk;
  __syncwarp();
  asm volatile("barrier.cluster.arrive.relaxed.aligned;\nbarrier.cluster.wait.aligned;" ::: "memory");
  if (first_loads && elect()) {
#pragma unroll 1
    for (int it = 0; it < NFIRST; it++) {
      const uint32_t bar = base + SM_BAR + 24 * it, d0 = base + 3 * it * UNIT;
      mbar_expect(bar, 3 * UNIT);
      tma3d_mc(d0 + (1 + (cta & 1)) * UNIT, mw, 0, it * 64, 2 * (cta >> 3), bar);
      tma2d(d0, &M.c, it * 64, (cta & 7) * 256, bar);
    }
  }
  __syncwarp();
  const int lane = threadIdx.x & 31;
#define TS_PRO()
  if (wg == 2) {
    asm volatile("setmaxnreg.dec.sync.aligned.u32 56;");
    TS_PRO();
    TS(2, 62);
    if (warp == 0) producer<MASK>(M, P, base, cta, lane);
    else if (warp == 1) sync_agent<MASK>(base, cta, lane);
    else if (cta < NREG) {
      if (MASK & PH_PRE) aux_pre<MASK>(M, P, base, cta, warp - 2, lane);
      if (MASK & PH_OUT) producer2<MASK>(M, P, base, cta, warp - 2, lane);
    }
    __syncwarp();
    if (warp != 1) { if (lane == 0) mbar_arrive_n(base + SM_EXIT, warp == 0 ? 4 : 2); }
    else {
      mbar_wait_slow(base + SM_EXIT, 0);
      if (MASK & PH_OUT) {
        unsigned old = 0;
        if (lane == 0) asm volatile("atom.acq_rel.gpu.global.add.u32 %0, [%1], 1;" : "=r"(old) : "l"(g_cnt + C_EXIT * CSTRIDE) : "memory");
        old = __shfl_sync(~0u, old, 0);
        if (old == NCTA - 1) for (int i = lane; i < C_NUM; i += 32) g_cnt[i * CSTRIDE] = 0;
      }
      mbar_wait_slow(base + SM_SIG + 8 * SIG_DONE, 0);
      cluster_arrive(); cluster_wait();
    }
  } else {
    asm volatile("setmaxnreg.inc.sync.aligned.u32 224;");
    TS_PRO();
    uint32_t rel;
    asm volatile("mapa.shared::cluster.u32 %0, %1, %2;" : "=r"(rel) : "r"(base + SM_BAR + 128 + 8 * (lane & 15)), "r"(lane >> 4));
    Cons c{base, rel, 0u, lane, warp, wg, (cta * 3 + wg) * 2048};
    if (wg == 1) bar_arrive(1, 256);
    TS(wg, 0);
    if (cta < NREG) {
      const int g = cta & 7, j = cta >> 3;
      Pend w = {};
#pragma unroll 1
      for (int half = 0; half < 2; half++) {
        const int h = j + 16 * half;
        if (MASK & PH_KV) cons_kv(c, h, kv_slot<MASK>(h), g, w, half == 1 && (MASK & PH_ATT));
        TS(wg, 1 + 4 * half);
        if (MASK & PH_ATT) {
          cons_q<(MASK & PH_KV) != 0>(c, h, w);
          TS(wg, 2 + 4 * half);
          cons_att(c, h, g, w);
          if (half == 0) c.signal(SIG_WAR);
#pragma unroll
          for (int i = 0; i < 8; i++) w.hi[i] = make_uint4(0, 0, 0, 0);
          TS(wg, 3 + 4 * half);
          if (MASK != PH_ALL) { tile_store<0, 4>(w.lo, w.dst, lane); c.signal(SIG_CTX + half); }
        } else if (MASK & PH_KV) { out_part<0>(c, w); out_part<1>(c, w); out_part<2>(c, w); out_part<3>(c, w); c.signal(SIG_KV + half); }
      }
      if (MASK & PH_OUT) cons_out<MASK>(c, M, cta, w);
    }
    if (cta >= NREG || !(MASK & PH_OUT)) {
      if (MASK & PH_CONV) cons_conv(c, cta, cta < NREG ? CONV_REG : CONV_EXTRA);
      TS(wg, 9);
      c.signal(SIG_DONE);
      cluster_arrive();
    }
    TS(wg, 10);
  }
}

typedef CUresult (*EncFn)(CUtensorMap*, CUtensorMapDataType, cuuint32_t, void*, const cuuint64_t*, const cuuint64_t*, const cuuint32_t*, const cuuint32_t*,
                          CUtensorMapInterleave, CUtensorMapSwizzle, CUtensorMapL2promotion, CUtensorMapFloatOOBfill);
static void enc(EncFn f, CUtensorMap* m, const void* ptr, int rank, const cuuint64_t* dims, const cuuint64_t* strides, const cuuint32_t* box, CUtensorMapSwizzle sw,
                CUtensorMapDataType dt = CU_TENSOR_MAP_DATA_TYPE_BFLOAT16) {
  const cuuint32_t es[4] = {1, 1, 1, 1};
  f(m, dt, rank, (void*)ptr, dims, strides, box, es, CU_TENSOR_MAP_INTERLEAVE_NONE, sw, CU_TENSOR_MAP_L2_PROMOTION_L2_256B, CU_TENSOR_MAP_FLOAT_OOB_FILL_NONE);
}
static void enc2(EncFn f, CUtensorMap* m, const void* ptr, int cols, int rows, int brows) {
  const cuuint64_t d[2] = {(cuuint64_t)cols, (cuuint64_t)rows}, s[1] = {(cuuint64_t)cols * 2}; const cuuint32_t b[2] = {64, (cuuint32_t)brows};
  enc(f, m, ptr, 2, d, s, b, CU_TENSOR_MAP_SWIZZLE_128B);
}
static void encw(EncFn f, CUtensorMap* m, const void* ptr, int cols, int rows) {
  const cuuint64_t d[3] = {64, (cuuint64_t)rows, (cuuint64_t)cols / 64}, s[2] = {(cuuint64_t)cols * 2, 128}; const cuuint32_t b[3] = {64, 64, 2};
  enc(f, m, ptr, 3, d, s, b, CU_TENSOR_MAP_SWIZZLE_128B);
}
extern "C" void kernel_launch(void* const* d_in, const int* in_sizes, int n_in, void* d_out, int out_size) {
  static EncFn fn = nullptr;
  static int ncl = 0;
  static void* zptr = nullptr;
  static void* tptr = nullptr;
  if (!fn) {
    void* p = nullptr; cudaDriverEntryPointQueryResult qr;
    cudaGetDriverEntryPoint("cuTensorMapEncodeTiled", &p, cudaEnableDefault, &qr);
    fn = (EncFn)p;
    cudaFuncSetAttribute(gated_mix_kernel<PH_ALL>, cudaFuncAttributeMaxDynamicSharedMemorySize, SMEM_BYTES);
    cudaFuncSetAttribute(gated_mix_kernel<PH_PRE | PH_KV>, cudaFuncAttributeMaxDynamicSharedMemorySize, SMEM_BYTES);
    cudaFuncSetAttribute(gated_mix_kernel<PH_ATT | PH_CONV>, cudaFuncAttributeMaxDynamicSharedMemorySize, SMEM_BYTES);
    cudaFuncSetAttribute(gated_mix_kernel<PH_OUT>, cudaFuncAttributeMaxDynamicSharedMemorySize, SMEM_BYTES);
    cudaLaunchConfig_t cfg = {}; cfg.gridDim = NCTA; cfg.blockDim = 384; cfg.dynamicSmemBytes = SMEM_BYTES;
    cudaLaunchAttribute at; at.id = cudaLaunchAttributeClusterDimension; at.val.clusterDim.x = 2; at.val.clusterDim.y = 1; at.val.clusterDim.z = 1;
    cfg.attrs = &at; cfg.numAttrs = 1;
    cudaOccupancyMaxActiveClusters(&ncl, gated_mix_kernel<PH_ALL>, &cfg);
    cudaGetSymbolAddress(&zptr, g_z);
    cudaGetSymbolAddress(&tptr, g_T);
  }
  Maps M;
  enc2(fn, &M.x, d_in[0], 1024, 2048, 128);
  enc2(fn, &M.c, d_in[7], 512, 2048, 128);
  enc2(fn, &M.wq, d_in[8], 4096, 1024, 64);
  encw(fn, &M.wk, d_in[9], 4096, 512);
  encw(fn, &M.wv, d_in[10], 4096, 512);
  encw(fn, &M.wo, d_in[11], 1024, 4096);
  { const cuuint64_t d[3] = {64, 32, 1024}, s[2] = {128, 4096}; const cuuint32_t b[3] = {64, 40, 1}; enc(fn, &M.h, d_in[4], 3, d, s, b, CU_TENSOR_MAP_SWIZZLE_NONE); }
  enc2(fn, &M.z, zptr, 2048, 1024, 128);
  enc2(fn, &M.out, d_out, 1024, 2048, 16);
  { const cuuint64_t d[2] = {512, 512 * 16}, s[1] = {2048}; const cuuint32_t b[2] = {256, 8};
    enc(fn, &M.ctx, tptr, 2, d, s, b, CU_TENSOR_MAP_SWIZZLE_NONE, CU_TENSOR_MAP_DATA_TYPE_UINT32); }
  { const cuuint64_t d[4] = {1024, 2, 256, 4}, s[3] = {2048, 16384, 4096}; const cuuint32_t b[4] = {64, 2, 9, 4};
    enc(fn, &M.k, d_in[1], 4, d, s, b, CU_TENSOR_MAP_SWIZZLE_128B); enc(fn, &M.v, d_in[2], 4, d, s, b, CU_TENSOR_MAP_SWIZZLE_128B); }
  Params P{(const __nv_bfloat16*)d_in[0], (const __nv_bfloat16*)d_in[3],
           (const __nv_bfloat16*)d_in[5], (const __nv_bfloat16*)d_in[12]};
  bool split = 2 * ncl < NCTA;
  if (!split) {
    gated_mix_kernel<PH_ALL><<<NCTA, 384, SMEM_BYTES>>>(M, P);
  } else {
    gated_mix_kernel<PH_PRE | PH_KV><<<NCTA, 384, SMEM_BYTES>>>(M, P);
    gated_mix_kernel<PH_ATT | PH_CONV><<<NCTA, 384, SMEM_BYTES>>>(M, P);
    gated_mix_kernel<PH_OUT><<<NCTA, 384, SMEM_BYTES>>>(M, P);
  }
}
```

```cpp
#include <cuda_runtime.h>
#include <cuda.h>
#include <cuda_bf16.h>
#include <stdint.h>

template<int TB> __device__ __forceinline__ void wgmma_ss_n256(float (&d)[128], uint64_t da, uint64_t db, int scale_d) {
  asm volatile("{\n.reg .pred p;\nsetp.ne.b32 p, %130, 0;\n"
    "wgmma.mma_async.sync.aligned.m64n256k16.f32.bf16.bf16 {%0, %1, %2, %3, %4, %5, %6, %7, %8, %9, %10, %11, %12, %13, %14, %15, %16, %17, %18, %19, %20, %21, %22, %23, %24, %25, %26, %27, %28, %29, %30, %31, %32, %33, %34, %35, %36, %37, %38, %39, %40, %41, %42, %43, %44, %45, %46, %47, %48, %49, %50, %51, %52, %53, %54, %55, %56, %57, %58, %59, %60, %61, %62, %63, %64, %65, %66, %67, %68, %69, %70, %71, %72, %73, %74, %75, %76, %77, %78, %79, %80, %81, %82, %83, %84, %85, %86, %87, %88, %89, %90, %91, %92, %93, %94, %95, %96, %97, %98, %99, %100, %101, %102, %103, %104, %105, %106, %107, %108, %109, %110, %111, %112, %113, %114, %115, %116, %117, %118, %119, %120, %121, %122, %123, %124, %125, %126, %127}, %128, %129, p, 1, 1, 0, %131;\n}\n"
    : "+f"(d[0]), "+f"(d[1]), "+f"(d[2]), "+f"(d[3]), "+f"(d[4]), "+f"(d[5]), "+f"(d[6]), "+f"(d[7]), "+f"(d[8]), "+f"(d[9]), "+f"(d[10]), "+f"(d[11]), "+f"(d[12]), "+f"(d[13]), "+f"(d[14]), "+f"(d[15]), "+f"(d[16]), "+f"(d[17]), "+f"(d[18]), "+f"(d[19]), "+f"(d[20]), "+f"(d[21]), "+f"(d[22]), "+f"(d[23]), "+f"(d[24]), "+f"(d[25]), "+f"(d[26]), "+f"(d[27]), "+f"(d[28]), "+f"(d[29]), "+f"(d[30]), "+f"(d[31]), "+f"(d[32]), "+f"(d[33]), "+f"(d[34]), "+f"(d[35]), "+f"(d[36]), "+f"(d[37]), "+f"(d[38]), "+f"(d[39]), "+f"(d[40]), "+f"(d[41]), "+f"(d[42]), "+f"(d[43]), "+f"(d[44]), "+f"(d[45]), "+f"(d[46]), "+f"(d[47]), "+f"(d[48]), "+f"(d[49]), "+f"(d[50]), "+f"(d[51]), "+f"(d[52]), "+f"(d[53]), "+f"(d[54]), "+f"(d[55]), "+f"(d[56]), "+f"(d[57]), "+f"(d[58]), "+f"(d[59]), "+f"(d[60]), "+f"(d[61]), "+f"(d[62]), "+f"(d[63]), "+f"(d[64]), "+f"(d[65]), "+f"(d[66]), "+f"(d[67]), "+f"(d[68]), "+f"(d[69]), "+f"(d[70]), "+f"(d[71]), "+f"(d[72]), "+f"(d[73]), "+f"(d[74]), "+f"(d[75]), "+f"(d[76]), "+f"(d[77]), "+f"(d[78]), "+f"(d[79]), "+f"(d[80]), "+f"(d[81]), "+f"(d[82]), "+f"(d[83]), "+f"(d[84]), "+f"(d[85]), "+f"(d[86]), "+f"(d[87]), "+f"(d[88]), "+f"(d[89]), "+f"(d[90]), "+f"(d[91]), "+f"(d[92]), "+f"(d[93]), "+f"(d[94]), "+f"(d[95]), "+f"(d[96]), "+f"(d[97]), "+f"(d[98]), "+f"(d[99]), "+f"(d[100]), "+f"(d[101]), "+f"(d[102]), "+f"(d[103]), "+f"(d[104]), "+f"(d[105]), "+f"(d[106]), "+f"(d[107]), "+f"(d[108]), "+f"(d[109]), "+f"(d[110]), "+f"(d[111]), "+f"(d[112]), "+f"(d[113]), "+f"(d[114]), "+f"(d[115]), "+f"(d[116]), "+f"(d[117]), "+f"(d[118]), "+f"(d[119]), "+f"(d[120]), "+f"(d[121]), "+f"(d[122]), "+f"(d[123]), "+f"(d[124]), "+f"(d[125]), "+f"(d[126]), "+f"(d[127])
    : "l"(da), "l"(db), "r"(scale_d), "n"(TB));
}
template<int TB> __device__ __forceinline__ void wgmma_ss_n128(float (&d)[64], uint64_t da, uint64_t db, int scale_d) {
  asm volatile("{\n.reg .pred p;\nsetp.ne.b32 p, %66, 0;\n"
    "wgmma.mma_async.sync.aligned.m64n128k16.f32.bf16.bf16 {%0, %1, %2, %3, %4, %5, %6, %7, %8, %9, %10, %11, %12, %13, %14, %15, %16, %17, %18, %19, %20, %21, %22, %23, %24, %25, %26, %27, %28, %29, %30, %31, %32, %33, %34, %35, %36, %37, %38, %39, %40, %41, %42, %43, %44, %45, %46, %47, %48, %49, %50, %51, %52, %53, %54, %55, %56, %57, %58, %59, %60, %61, %62, %63}, %64, %65, p, 1, 1, 0, %67;\n}\n"
    : "+f"(d[0]), "+f"(d[1]), "+f"(d[2]), "+f"(d[3]), "+f"(d[4]), "+f"(d[5]), "+f"(d[6]), "+f"(d[7]), "+f"(d[8]), "+f"(d[9]), "+f"(d[10]), "+f"(d[11]), "+f"(d[12]), "+f"(d[13]), "+f"(d[14]), "+f"(d[15]), "+f"(d[16]), "+f"(d[17]), "+f"(d[18]), "+f"(d[19]), "+f"(d[20]), "+f"(d[21]), "+f"(d[22]), "+f"(d[23]), "+f"(d[24]), "+f"(d[25]), "+f"(d[26]), "+f"(d[27]), "+f"(d[28]), "+f"(d[29]), "+f"(d[30]), "+f"(d[31]), "+f"(d[32]), "+f"(d[33]), "+f"(d[34]), "+f"(d[35]), "+f"(d[36]), "+f"(d[37]), "+f"(d[38]), "+f"(d[39]), "+f"(d[40]), "+f"(d[41]), "+f"(d[42]), "+f"(d[43]), "+f"(d[44]), "+f"(d[45]), "+f"(d[46]), "+f"(d[47]), "+f"(d[48]), "+f"(d[49]), "+f"(d[50]), "+f"(d[51]), "+f"(d[52]), "+f"(d[53]), "+f"(d[54]), "+f"(d[55]), "+f"(d[56]), "+f"(d[57]), "+f"(d[58]), "+f"(d[59]), "+f"(d[60]), "+f"(d[61]), "+f"(d[62]), "+f"(d[63])
    : "l"(da), "l"(db), "r"(scale_d), "n"(TB));
}
template<int TB> __device__ __forceinline__ void wgmma_rs_n32(float (&d)[16], uint32_t a0, uint32_t a1, uint32_t a2, uint32_t a3, uint64_t db, int scale_d) {
  asm volatile("{\n.reg .pred p;\nsetp.ne.b32 p, %21, 0;\n"
    "wgmma.mma_async.sync.aligned.m64n32k16.f32.bf16.bf16 {%0, %1, %2, %3, %4, %5, %6, %7, %8, %9, %10, %11, %12, %13, %14, %15}, {%16, %17, %18, %19}, %20, p, 1, 1, %22;\n}\n"
    : "+f"(d[0]), "+f"(d[1]), "+f"(d[2]), "+f"(d[3]), "+f"(d[4]), "+f"(d[5]), "+f"(d[6]), "+f"(d[7]), "+f"(d[8]), "+f"(d[9]), "+f"(d[10]), "+f"(d[11]), "+f"(d[12]), "+f"(d[13]), "+f"(d[14]), "+f"(d[15])
    : "r"(a0), "r"(a1), "r"(a2), "r"(a3), "l"(db), "r"(scale_d), "n"(TB));
}
__device__ __forceinline__ void wgmma_pv_sel(float (&d)[64], const uint32_t (&p)[32], uint64_t db, int full, int acc) {
  asm volatile("{\n.reg .pred q, s;\n.reg .b64 t;\nsetp.ne.b32 s, %98, 0;\nsetp.eq.b32 q, %97, 0;\n@q bra.uni LH;\n"
    "wgmma.fence.sync.aligned;\n"
    "add.s64 t, %96, 0;\nwgmma.mma_async.sync.aligned.m64n128k16.f32.bf16.bf16 {%0, %1, %2, %3, %4, %5, %6, %7, %8, %9, %10, %11, %12, %13, %14, %15, %16, %17, %18, %19, %20, %21, %22, %23, %24, %25, %26, %27, %28, %29, %30, %31, %32, %33, %34, %35, %36, %37, %38, %39, %40, %41, %42, %43, %44, %45, %46, %47, %48, %49, %50, %51, %52, %53, %54, %55, %56, %57, %58, %59, %60, %61, %62, %63}, {%64, %65, %66, %67}, t, s, 1, 1, 1;\n"
    "add.s64 t, %96, 256;\nwgmma.mma_async.sync.aligned.m64n128k16.f32.bf16.bf16 {%0, %1, %2, %3, %4, %5, %6, %7, %8, %9, %10, %11, %12, %13, %14, %15, %16, %17, %18, %19, %20, %21, %22, %23, %24, %25, %26, %27, %28, %29, %30, %31, %32, %33, %34, %35, %36, %37, %38, %39, %40, %41, %42, %43, %44, %45, %46, %47, %48, %49, %50, %51, %52, %53, %54, %55, %56, %57, %58, %59, %60, %61, %62, %63}, {%68, %69, %70, %71}, t, 1, 1, 1, 1;\n"
    "add.s64 t, %96, 512;\nwgmma.mma_async.sync.aligned.m64n128k16.f32.bf16.bf16 {%0, %1, %2, %3, %4, %5, %6, %7, %8, %9, %10, %11, %12, %13, %14, %15, %16, %17, %18, %19, %20, %21, %22, %23, %24, %25, %26, %27, %28, %29, %30, %31, %32, %33, %34, %35, %36, %37, %38, %39, %40, %41, %42, %43, %44, %45, %46, %47, %48, %49, %50, %51, %52, %53, %54, %55, %56, %57, %58, %59, %60, %61, %62, %63}, {%72, %73, %74, %75}, t, 1, 1, 1, 1;\n"
    "add.s64 t, %96, 768;\nwgmma.mma_async.sync.aligned.m64n128k16.f32.bf16.bf16 {%0, %1, %2, %3, %4, %5, %6, %7, %8, %9, %10, %11, %12, %13, %14, %15, %16, %17, %18, %19, %20, %21, %22, %23, %24, %25, %26, %27, %28, %29, %30, %31, %32, %33, %34, %35, %36, %37, %38, %39, %40, %41, %42, %43, %44, %45, %46, %47, %48, %49, %50, %51, %52, %53, %54, %55, %56, %57, %58, %59, %60, %61, %62, %63}, {%76, %77, %78, %79}, t, 1, 1, 1, 1;\n"
    "add.s64 t, %96, 1024;\nwgmma.mma_async.sync.aligned.m64n128k16.f32.bf16.bf16 {%0, %1, %2, %3, %4, %5, %6, %7, %8, %9, %10, %11, %12, %13, %14, %15, %16, %17, %18, %19, %20, %21, %22, %23, %24, %25, %26, %27, %28, %29, %30, %31, %32, %33, %34, %35, %36, %37, %38, %39, %40, %41, %42, %43, %44, %45, %46, %47, %48, %49, %50, %51, %52, %53, %54, %55, %56, %57, %58, %59, %60, %61, %62, %63}, {%80, %81, %82, %83}, t, 1, 1, 1, 1;\n"
    "add.s64 t, %96, 1280;\nwgmma.mma_async.sync.aligned.m64n128k16.f32.bf16.bf16 {%0, %1, %2, %3, %4, %5, %6, %7, %8, %9, %10, %11, %12, %13, %14, %15, %16, %17, %18, %19, %20, %21, %22, %23, %24, %25, %26, %27, %28, %29, %30, %31, %32, %33, %34, %35, %36, %37, %38, %39, %40, %41, %42, %43, %44, %45, %46, %47, %48, %49, %50, %51, %52, %53, %54, %55, %56, %57, %58, %59, %60, %61, %62, %63}, {%84, %85, %86, %87}, t, 1, 1, 1, 1;\n"
    "add.s64 t, %96, 1536;\nwgmma.mma_async.sync.aligned.m64n128k16.f32.bf16.bf16 {%0, %1, %2, %3, %4, %5, %6, %7, %8, %9, %10, %11, %12, %13, %14, %15, %16, %17, %18, %19, %20, %21, %22, %23, %24, %25, %26, %27, %28, %29, %30, %31, %32, %33, %34, %35, %36, %37, %38, %39, %40, %41, %42, %43, %44, %45, %46, %47, %48, %49, %50, %51, %52, %53, %54, %55, %56, %57, %58, %59, %60, %61, %62, %63}, {%88, %89, %90, %91}, t, 1, 1, 1, 1;\n"
    "add.s64 t, %96, 1792;\nwgmma.mma_async.sync.aligned.m64n128k16.f32.bf16.bf16 {%0, %1, %2, %3, %4, %5, %6, %7, %8, %9, %10, %11, %12, %13, %14, %15, %16, %17, %18, %19, %20, %21, %22, %23, %24, %25, %26, %27, %28, %29, %30, %31, %32, %33, %34, %35, %36, %37, %38, %39, %40, %41, %42, %43, %44, %45, %46, %47, %48, %49, %50, %51, %52, %53, %54, %55, %56, %57, %58, %59, %60, %61, %62, %63}, {%92, %93, %94, %95}, t, 1, 1, 1, 1;\n"
    "wgmma.commit_group.sync.aligned;\n"
    "bra.uni LE;\nLH:\n"
    "wgmma.fence.sync.aligned;\n"
    "add.s64 t, %96, 0;\nwgmma.mma_async.sync.aligned.m64n128k16.f32.bf16.bf16 {%0, %1, %2, %3, %4, %5, %6, %7, %8, %9, %10, %11, %12, %13, %14, %15, %16, %17, %18, %19, %20, %21, %22, %23, %24, %25, %26, %27, %28, %29, %30, %31, %32, %33, %34, %35, %36, %37, %38, %39, %40, %41, %42, %43, %44, %45, %46, %47, %48, %49, %50, %51, %52, %53, %54, %55, %56, %57, %58, %59, %60, %61, %62, %63}, {%80, %81, %82, %83}, t, s, 1, 1, 1;\n"
    "add.s64 t, %96, 256;\nwgmma.mma_async.sync.aligned.m64n128k16.f32.bf16.bf16 {%0, %1, %2, %3, %4, %5, %6, %7, %8, %9, %10, %11, %12, %13, %14, %15, %16, %17, %18, %19, %20, %21, %22, %23, %24, %25, %26, %27, %28, %29, %30, %31, %32, %33, %34, %35, %36, %37, %38, %39, %40, %41, %42, %43, %44, %45, %46, %47, %48, %49, %50, %51, %52, %53, %54, %55, %56, %57, %58, %59, %60, %61, %62, %63}, {%84, %85, %86, %87}, t, 1, 1, 1, 1;\n"
    "add.s64 t, %96, 512;\nwgmma.mma_async.sync.aligned.m64n128k16.f32.bf16.bf16 {%0, %1, %2, %3, %4, %5, %6, %7, %8, %9, %10, %11, %12, %13, %14, %15, %16, %17, %18, %19, %20, %21, %22, %23, %24, %25, %26, %27, %28, %29, %30, %31, %32, %33, %34, %35, %36, %37, %38, %39, %40, %41, %42, %43, %44, %45, %46, %47, %48, %49, %50, %51, %52, %53, %54, %55, %56, %57, %58, %59, %60, %61, %62, %63}, {%88, %89, %90, %91}, t, 1, 1, 1, 1;\n"
    "add.s64 t, %96, 768;\nwgmma.mma_async.sync.aligned.m64n128k16.f32.bf16.bf16 {%0, %1, %2, %3, %4, %5, %6, %7, %8, %9, %10, %11, %12, %13, %14, %15, %16, %17, %18, %19, %20, %21, %22, %23, %24, %25, %26, %27, %28, %29, %30, %31, %32, %33, %34, %35, %36, %37, %38, %39, %40, %41, %42, %43, %44, %45, %46, %47, %48, %49, %50, %51, %52, %53, %54, %55, %56, %57, %58, %59, %60, %61, %62, %63}, {%92, %93, %94, %95}, t, 1, 1, 1, 1;\n"
    "wgmma.commit_group.sync.aligned;\n"
    "LE:\n}\n"
    : "+f"(d[0]), "+f"(d[1]), "+f"(d[2]), "+f"(d[3]), "+f"(d[4]), "+f"(d[5]), "+f"(d[6]), "+f"(d[7]), "+f"(d[8]), "+f"(d[9]), "+f"(d[10]), "+f"(d[11]), "+f"(d[12]), "+f"(d[13]), "+f"(d[14]), "+f"(d[15]), "+f"(d[16]), "+f"(d[17]), "+f"(d[18]), "+f"(d[19]), "+f"(d[20]), "+f"(d[21]), "+f"(d[22]), "+f"(d[23]), "+f"(d[24]), "+f"(d[25]), "+f"(d[26]), "+f"(d[27]), "+f"(d[28]), "+f"(d[29]), "+f"(d[30]), "+f"(d[31]), "+f"(d[32]), "+f"(d[33]), "+f"(d[34]), "+f"(d[35]), "+f"(d[36]), "+f"(d[37]), "+f"(d[38]), "+f"(d[39]), "+f"(d[40]), "+f"(d[41]), "+f"(d[42]), "+f"(d[43]), "+f"(d[44]), "+f"(d[45]), "+f"(d[46]), "+f"(d[47]), "+f"(d[48]), "+f"(d[49]), "+f"(d[50]), "+f"(d[51]), "+f"(d[52]), "+f"(d[53]), "+f"(d[54]), "+f"(d[55]), "+f"(d[56]), "+f"(d[57]), "+f"(d[58]), "+f"(d[59]), "+f"(d[60]), "+f"(d[61]), "+f"(d[62]), "+f"(d[63])
    : "r"(p[0]), "r"(p[1]), "r"(p[2]), "r"(p[3]), "r"(p[4]), "r"(p[5]), "r"(p[6]), "r"(p[7]), "r"(p[8]), "r"(p[9]), "r"(p[10]), "r"(p[11]), "r"(p[12]), "r"(p[13]), "r"(p[14]), "r"(p[15]), "r"(p[16]), "r"(p[17]), "r"(p[18]), "r"(p[19]), "r"(p[20]), "r"(p[21]), "r"(p[22]), "r"(p[23]), "r"(p[24]), "r"(p[25]), "r"(p[26]), "r"(p[27]), "r"(p[28]), "r"(p[29]), "r"(p[30]), "r"(p[31]), "l"(db), "r"(full), "r"(acc) : "memory");
}

constexpr int NCTA = 132, NREG = 128;
constexpr int UNIT = 16384, NUNIT = 14;
constexpr uint32_t SMEM_BASE = 1024;
constexpr int SM_BAR = NUNIT * UNIT;
constexpr int SM_GATE = SM_BAR + 1024;
constexpr int SMEM_BYTES = SM_BAR + 1536;
constexpr int UPITCH = 4160, UCH = 2 * UPITCH;
constexpr float QSCALE = 0.08838834764831845f * 1.4426950408889634f;
constexpr float BOUND2 = 48.f * 48.f / 1.15f;
#define CONV_REG 5
constexpr int C_KV = 0;
constexpr int C_CTX = 32;
constexpr int C_U = 48;
constexpr int C_Z = 80;
constexpr int C_GATE = 88;
constexpr int C_EXIT = 89;
[[maybe_unused]] constexpr int C_GO = 90;
#define PRE_EARLY 2
#define PRE_HALF 1
#define ATT_SPLIT 6
#define NFIRST 2
#define PRE_DELAY 0
#define MAP_PF 1
#define FINAL_ST 1
#define Z_AT 60
#define PRE_DELAY_BAR 9
#define PRE_FMA 0
#define PRE_SLEEP 300
#define GATE_SLEEP 1000
#define GATE_EARLY 1
#define EF 127
#define POL(bit) (((EF >> (bit)) & 1) != 0)
constexpr int C_WAR = 96;
constexpr int C_NUM = 112;
constexpr int CSTRIDE = 32;
constexpr int SM_KMAX = SM_BAR + 640, SM_DUMMY = SM_BAR + 648, SM_PRE = SM_BAR + 112, SM_SIG = SM_BAR + 256, SM_RDY = SM_BAR + 384;
enum { SIG_KV = 0, SIG_CTX = 2, SIG_Z = 4, SIG_DONE = 8, SIG_WAR = 9, SIG_ATT = 10 };
enum { RDY_KV = 0, RDY_CTX = 2, RDY_WAR = 4, RDY_G = 5, RDY_U = 8, RDY_Z = 9 };
enum { PH_PRE = 1, PH_KV = 2, PH_ATT = 4, PH_CONV = 8, PH_OUT = 16, PH_ALL = 31 };

constexpr uint32_t T_CTX = 0, T_KV = 16 * 32 * 32768, T_BYTES = T_KV + 32 * 16 * 65536;
__device__ __align__(1024) uint8_t g_T[T_BYTES];
__device__ __align__(1024) uint8_t g_u[1024 * UCH];
__device__ __align__(1024) __nv_bfloat16 g_z[1024 * 2048];
__device__ __align__(1024) float g_gate[2048];
__device__ __align__(1024) float g_kn2[32 * 128];
__device__ __align__(1024) unsigned g_cnt[C_NUM * CSTRIDE];

struct __align__(64) Maps { CUtensorMap c, wk, wv, x, wq, wo, h, z, out, ctx, k, v; };
struct Params {
  const __nv_bfloat16 *x, *shift, *D, *gw;
  __nv_bfloat16* out;
};

__device__ __forceinline__ void wg_fence() { asm volatile("wgmma.fence.sync.aligned;" ::: "memory"); }
__device__ __forceinline__ void wg_commit() { asm volatile("wgmma.commit_group.sync.aligned;" ::: "memory"); }
template<int N> __device__ __forceinline__ void wg_wait() { asm volatile("wgmma.wait_group.sync.aligned %0;" :: "n"(N) : "memory"); }
__device__ __forceinline__ uint64_t odesc(uint32_t addr, uint32_t lbo, uint32_t sbo, uint32_t swz) {
  uint64_t d = (uint64_t)(addr >> 4) + (((uint64_t)(lbo >> 4) << 16) | ((uint64_t)(sbo >> 4) << 32) | ((uint64_t)swz << 62));
  asm volatile("" : "+l"(d));
  return d;
}
__device__ __forceinline__ void mbar_init(uint32_t bar, int cnt) { asm volatile("mbarrier.init.shared::cta.b64 [%0], %1;" :: "r"(bar), "r"(cnt)); }
__device__ __forceinline__ void mbar_expect(uint32_t bar, uint32_t bytes) { asm volatile("mbarrier.arrive.expect_tx.shared::cta.b64 _, [%0], %1;" :: "r"(bar), "r"(bytes) : "memory"); }
__device__ __forceinline__ void mbar_arrive(uint32_t bar) { asm volatile("mbarrier.arrive.shared::cta.b64 _, [%0];" :: "r"(bar) : "memory"); }
__device__ __forceinline__ void mbar_arrive_n(uint32_t bar, int n) { asm volatile("mbarrier.arrive.shared::cta.b64 _, [%0], %1;" :: "r"(bar), "r"(n) : "memory"); }
__device__ __forceinline__ void mbar_wait(uint32_t bar, uint32_t parity) {
  asm volatile("{\n.reg .pred p;\nLW:\nmbarrier.try_wait.parity.shared::cta.b64 p, [%0], %1;\n@!p bra LW;\n}\n" :: "r"(bar), "r"(parity) : "memory");
}
__device__ __forceinline__ void mbar_wait_slow(uint32_t bar, uint32_t parity) {
  asm volatile("{\n.reg .pred p;\n.reg .u32 n;\nmov.u32 n, 0;\n"
    "LW:\nmbarrier.test_wait.parity.shared::cta.b64 p, [%0], %1;\n@p bra LD;\n"
    "nanosleep.u32 128;\nadd.u32 n, n, 1;\nsetp.lt.u32 p, n, 4194304;\n@p bra LW;\ntrap;\nLD:\n}\n" :: "r"(bar), "r"(parity) : "memory");
}
__device__ __forceinline__ void mbar_wait_all(uint32_t bar, uint32_t parity) {
  asm volatile("{\n.reg .pred p, q;\nLW:\nmbarrier.try_wait.parity.shared::cta.b64 p, [%0], %1;\nvote.sync.all.pred q, p, 0xffffffff;\n@!q bra.uni LW;\n}\n" :: "r"(bar), "r"(parity) : "memory");
}
__device__ __forceinline__ void cnt_wait(const unsigned* p, unsigned target) {
  asm volatile("{\n.reg .pred p;\n.reg .u32 n, v;\nmov.u32 n, 0;\n"
    "LW:\nld.relaxed.gpu.global.u32 v, [%0];\nsetp.ge.u32 p, v, %1;\n@p bra LD;\n"
    "nanosleep.u32 64;\nadd.u32 n, n, 1;\nsetp.lt.u32 p, n, 4194304;\n@p bra LW;\ntrap;\nLD:\nfence.acq_rel.gpu;\nfence.proxy.async;\n}\n" :: "l"(p), "r"(target) : "memory");
}
__device__ __forceinline__ void cnt_signal(unsigned* p, int lane) {
  __syncwarp();
  if (lane == 0) asm volatile("red.release.gpu.global.add.u32 [%0], 1;" :: "l"(p) : "memory");
}
__device__ __forceinline__ void cnt_publish(unsigned* p, unsigned n) {
  asm volatile("fence.acq_rel.gpu;\nred.relaxed.gpu.global.add.u32 [%0], %1;" :: "l"(p), "r"(n) : "memory");
}
__device__ __forceinline__ uint64_t pol_first() { uint64_t p; asm("createpolicy.fractional.L2::evict_first.b64 %0, 1.0;" : "=l"(p)); return p; }
__device__ __forceinline__ void bulk_g2s(uint32_t dst, const void* src, uint32_t bytes, uint32_t bar, bool stream = false) {
  if (stream) asm volatile("cp.async.bulk.shared::cluster.global.mbarrier::complete_tx::bytes.L2::cache_hint [%0], [%1], %2, [%3], %4;" :: "r"(dst), "l"(src), "r"(bytes), "r"(bar), "l"(pol_first()) : "memory");
  else asm volatile("cp.async.bulk.shared::cluster.global.mbarrier::complete_tx::bytes [%0], [%1], %2, [%3];" :: "r"(dst), "l"(src), "r"(bytes), "r"(bar) : "memory");
}
__device__ __forceinline__ void tma2d(uint32_t dst, const CUtensorMap* m, int x, int y, uint32_t bar, bool stream = false) {
  if (stream) asm volatile("cp.async.bulk.tensor.2d.shared::cluster.global.mbarrier::complete_tx::bytes.L2::cache_hint [%0], [%1, {%3, %4}], [%2], %5;" :: "r"(dst), "l"(m), "r"(bar), "r"(x), "r"(y), "l"(pol_first()) : "memory");
  else asm volatile("cp.async.bulk.tensor.2d.shared::cluster.global.mbarrier::complete_tx::bytes [%0], [%1, {%3, %4}], [%2];" :: "r"(dst), "l"(m), "r"(bar), "r"(x), "r"(y) : "memory");
}
__device__ __forceinline__ void tma3d(uint32_t dst, const CUtensorMap* m, int x, int y, int z, uint32_t bar, bool stream = false) {
  if (stream) asm volatile("cp.async.bulk.tensor.3d.shared::cluster.global.mbarrier::complete_tx::bytes.L2::cache_hint [%0], [%1, {%3, %4, %5}], [%2], %6;" :: "r"(dst), "l"(m), "r"(bar), "r"(x), "r"(y), "r"(z), "l"(pol_first()) : "memory");
  else asm volatile("cp.async.bulk.tensor.3d.shared::cluster.global.mbarrier::complete_tx::bytes [%0], [%1, {%3, %4, %5}], [%2];" :: "r"(dst), "l"(m), "r"(bar), "r"(x), "r"(y), "r"(z) : "memory");
}
__device__ __forceinline__ void tma4d(uint32_t dst, const CUtensorMap* m, int x, int y, int z, int w, uint32_t bar, bool stream = false) {
  if (stream) asm volatile("cp.async.bulk.tensor.4d.shared::cluster.global.mbarrier::complete_tx::bytes.L2::cache_hint [%0], [%1, {%3, %4, %5, %6}], [%2], %7;" :: "r"(dst), "l"(m), "r"(bar), "r"(x), "r"(y), "r"(z), "r"(w), "l"(pol_first()) : "memory");
  else asm volatile("cp.async.bulk.tensor.4d.shared::cluster.global.mbarrier::complete_tx::bytes [%0], [%1, {%3, %4, %5, %6}], [%2];" :: "r"(dst), "l"(m), "r"(bar), "r"(x), "r"(y), "r"(z), "r"(w) : "memory");
}
__device__ __forceinline__ void bulk_g2s_mc(uint32_t dst, const void* src, uint32_t bytes, uint32_t bar, bool stream = false) {
  if (stream) asm volatile("cp.async.bulk.shared::cluster.global.mbarrier::complete_tx::bytes.multicast::cluster.L2::cache_hint [%0], [%1], %2, [%3], %4, %5;" :: "r"(dst), "l"(src), "r"(bytes), "r"(bar), "h"((uint16_t)3), "l"(pol_first()) : "memory");
  else asm volatile("cp.async.bulk.shared::cluster.global.mbarrier::complete_tx::bytes.multicast::cluster [%0], [%1], %2, [%3], %4;" :: "r"(dst), "l"(src), "r"(bytes), "r"(bar), "h"((uint16_t)3) : "memory");
}
__device__ __forceinline__ void tma2d_mc(uint32_t dst, const CUtensorMap* m, int x, int y, uint32_t bar, bool stream = false) {
  if (stream) asm volatile("cp.async.bulk.tensor.2d.shared::cluster.global.mbarrier::complete_tx::bytes.multicast::cluster.L2::cache_hint [%0], [%1, {%3, %4}], [%2], %5, %6;" :: "r"(dst), "l"(m), "r"(bar), "r"(x), "r"(y), "h"((uint16_t)3), "l"(pol_first()) : "memory");
  else asm volatile("cp.async.bulk.tensor.2d.shared::cluster.global.mbarrier::complete_tx::bytes.multicast::cluster [%0], [%1, {%3, %4}], [%2], %5;" :: "r"(dst), "l"(m), "r"(bar), "r"(x), "r"(y), "h"((uint16_t)3) : "memory");
}
__device__ __forceinline__ void tma3d_mc(uint32_t dst, const CUtensorMap* m, int x, int y, int z, uint32_t bar, bool stream = false) {
  if (stream) asm volatile("cp.async.bulk.tensor.3d.shared::cluster.global.mbarrier::complete_tx::bytes.multicast::cluster.L2::cache_hint [%0], [%1, {%3, %4, %5}], [%2], %6, %7;" :: "r"(dst), "l"(m), "r"(bar), "r"(x), "r"(y), "r"(z), "h"((uint16_t)3), "l"(pol_first()) : "memory");
  else asm volatile("cp.async.bulk.tensor.3d.shared::cluster.global.mbarrier::complete_tx::bytes.multicast::cluster [%0], [%1, {%3, %4, %5}], [%2], %6;" :: "r"(dst), "l"(m), "r"(bar), "r"(x), "r"(y), "r"(z), "h"((uint16_t)3) : "memory");
}
__device__ __forceinline__ void tma2d_store(const CUtensorMap* m, uint32_t src, int x, int y) {
  if (POL(12)) asm volatile("cp.async.bulk.tensor.2d.global.shared::cta.bulk_group.L2::cache_hint [%0, {%2, %3}], [%1], %4;" :: "l"(m), "r"(src), "r"(x), "r"(y), "l"(pol_first()) : "memory");
  else asm volatile("cp.async.bulk.tensor.2d.global.shared::cta.bulk_group [%0, {%2, %3}], [%1];" :: "l"(m), "r"(src), "r"(x), "r"(y) : "memory");
}
__device__ __forceinline__ bool elect() {
  uint32_t r; asm volatile("{\n.reg .pred p;\nelect.sync _|p, 0xffffffff;\nselp.u32 %0, 1, 0, p;\n}\n" : "=r"(r)); return r != 0;
}
__device__ __forceinline__ void cluster_arrive() { asm volatile("barrier.cluster.arrive;" ::: "memory"); }
__device__ __forceinline__ void cluster_wait() { asm volatile("barrier.cluster.wait;" ::: "memory"); }
__device__ __forceinline__ void bar_sync(int id, int n) { asm volatile("bar.sync %0, %1;" :: "r"(id), "r"(n) : "memory"); }
__device__ __forceinline__ void bar_arrive(int id, int n) { asm volatile("bar.arrive %0, %1;" :: "r"(id), "r"(n) : "memory"); }
__device__ __forceinline__ int bar_and(int id, int n, int pred) {
  int r; asm volatile("{\n.reg .pred p, q;\nsetp.ne.b32 p, %3, 0;\nbar.red.and.pred q, %1, %2, p;\nselp.b32 %0, 1, 0, q;\n}\n" : "=r"(r) : "r"(id), "r"(n), "r"(pred) : "memory");
  return r;
}
__device__ __forceinline__ void fence_async_smem() { asm volatile("fence.proxy.async.shared::cta;" ::: "memory"); }
__device__ __forceinline__ float ex2(float x) { float y; asm("ex2.approx.ftz.f32 %0, %1;" : "=f"(y) : "f"(x)); return y; }
__device__ __forceinline__ uint32_t pack_bf16(float lo, float hi) { uint32_t r; asm("cvt.rn.bf16x2.f32 %0, %1, %2;" : "=r"(r) : "f"(hi), "f"(lo)); return r; }
__device__ __forceinline__ uint32_t hmul2(uint32_t a, uint32_t b) { uint32_t r; asm("mul.rn.bf16x2 %0, %1, %2;" : "=r"(r) : "r"(a), "r"(b)); return r; }
__device__ __forceinline__ uint32_t hadd2(uint32_t a, uint32_t b) { uint32_t r; asm("add.rn.bf16x2 %0, %1, %2;" : "=r"(r) : "r"(a), "r"(b)); return r; }
__device__ __forceinline__ uint32_t hfma2(uint32_t a, uint32_t b, uint32_t c) { uint32_t r; asm("fma.rn.bf16x2 %0, %1, %2, %3;" : "=r"(r) : "r"(a), "r"(b), "r"(c)); return r; }
__device__ __forceinline__ float bf_lo(uint32_t a) { return __uint_as_float(a << 16); }
__device__ __forceinline__ float bf_hi(uint32_t a) { return __uint_as_float(a & 0xffff0000u); }
__device__ __forceinline__ uint32_t lds32(uint32_t a) { uint32_t v; asm volatile("ld.shared.u32 %0, [%1];" : "=r"(v) : "r"(a) : "memory"); return v; }
__device__ __forceinline__ float2 lds64f(uint32_t a) { float2 v; asm volatile("ld.shared.v2.f32 {%0,%1}, [%2];" : "=f"(v.x), "=f"(v.y) : "r"(a) : "memory"); return v; }
__device__ __forceinline__ uint4 lds128(uint32_t a) { uint4 v; asm volatile("ld.shared.v4.u32 {%0,%1,%2,%3}, [%4];" : "=r"(v.x), "=r"(v.y), "=r"(v.z), "=r"(v.w) : "r"(a) : "memory"); return v; }
__device__ __forceinline__ void sts64f(uint32_t a, float x, float y) { asm volatile("st.shared.v2.f32 [%0], {%1,%2};" :: "r"(a), "f"(x), "f"(y) : "memory"); }
__device__ __forceinline__ void sts128(uint32_t a, uint4 v) { asm volatile("st.shared.v4.u32 [%0], {%1,%2,%3,%4};" :: "r"(a), "r"(v.x), "r"(v.y), "r"(v.z), "r"(v.w) : "memory"); }
template<int OFF> __device__ __forceinline__ void sts128o(uint32_t a, uint4 v) { asm volatile("st.shared.v4.u32 [%0+%5], {%1,%2,%3,%4};" :: "r"(a), "r"(v.x), "r"(v.y), "r"(v.z), "r"(v.w), "n"(OFF) : "memory"); }
__device__ __forceinline__ void ldsm4(uint32_t a, uint32_t& r0, uint32_t& r1, uint32_t& r2, uint32_t& r3) {
  asm volatile("ldmatrix.sync.aligned.m8n8.x4.shared.b16 {%0,%1,%2,%3}, [%4];" : "=r"(r0), "=r"(r1), "=r"(r2), "=r"(r3) : "r"(a) : "memory");
}
__device__ __forceinline__ void ldsm4t(uint32_t a, uint32_t& r0, uint32_t& r1, uint32_t& r2, uint32_t& r3) {
  asm volatile("ldmatrix.sync.aligned.m8n8.x4.trans.shared.b16 {%0,%1,%2,%3}, [%4];" : "=r"(r0), "=r"(r1), "=r"(r2), "=r"(r3) : "r"(a) : "memory");
}
__device__ __forceinline__ void stsm4(uint32_t a, uint32_t r0, uint32_t r1, uint32_t r2, uint32_t r3) {
  asm volatile("stmatrix.sync.aligned.m8n8.x4.shared.b16 [%0], {%1,%2,%3,%4};" :: "r"(a), "r"(r0), "r"(r1), "r"(r2), "r"(r3) : "memory");
}
template<int N> __device__ __forceinline__ void fence_regs(float (&d)[N]) {
#pragma unroll
  for (int i = 0; i < N; i++) asm volatile("" : "+f"(d[i]) :: "memory");
}
template<int N> __device__ __forceinline__ void fence_regs(uint32_t (&d)[N]) {
#pragma unroll
  for (int i = 0; i < N; i++) asm volatile("" : "+r"(d[i]) :: "memory");
}
__device__ __forceinline__ void sched_fence(float x, uint32_t dummy) {
  asm volatile("{\n.reg .pred p;\nsetp.eq.u32 p, %0, 0x7fc12345;\n@p st.shared.u32 [%1], %0;\n}\n" :: "r"(__float_as_uint(x)), "r"(dummy) : "memory");
}
#define TS(role, i)
#define TSA(i)
#define TR(obj, role, tag)

struct Prod {
  uint32_t base, mask; int lane, nt;
  __device__ __forceinline__ uint32_t full(int u) const { return base + SM_BAR + 8 * u; }
  __device__ __forceinline__ uint32_t addr(int u) const { return base + u * UNIT; }
  __device__ __forceinline__ void acquire(int u, int n) {
    const int v = u + min(lane, n - 1);
    mbar_wait_all(base + SM_BAR + 128 + 8 * v, mask >> v);
    mask ^= ((1u << n) - 1) << u;
    TR(*this, 2, 16 + u);
  }
  __device__ __forceinline__ void acquire_slow(int u, int n) {
    for (int i = 0; i < n; i++) mbar_wait_slow(base + SM_BAR + 128 + 8 * (u + i), mask >> (u + i));
    mask ^= ((1u << n) - 1) << u;
  }
};
struct Cons {
  uint32_t base, rel, mask; int lane, warp, wg, nt;
  __device__ __forceinline__ uint32_t addr(int u) const { return base + u * UNIT; }
  __device__ __forceinline__ static uint32_t daddr(int u) { return SMEM_BASE + u * UNIT; }
  __device__ __forceinline__ void wait(int u) { TR(*this, wg, 1); mbar_wait(base + SM_BAR + 8 * u, mask >> u); mask ^= 1u << u; TR(*this, wg, 2); }
  __device__ __forceinline__ void skip(int u) { mask ^= 1u << u; }
  __device__ __forceinline__ void release(int u, int n) {
    TR(*this, wg, 5);
    asm volatile("{\n.reg .pred p;\nsetp.lt.s32 p, %1, %2;\n@p mbarrier.arrive.shared::cluster.b64 _, [%0];\n}\n" :: "r"(rel + 8 * u), "r"(lane & 15), "r"(n) : "memory");
  }
  __device__ __forceinline__ void release2(int u) {
    asm volatile("{\n.reg .pred p;\nsetp.eq.s32 p, %1, 0;\n@p mbarrier.arrive.shared::cluster.b64 _, [%0], 2;\n}\n" :: "r"(rel + 8 * u), "r"(lane & 15) : "memory");
  }
  __device__ __forceinline__ void signal(int i) {
    __syncwarp();
    asm volatile("{\n.reg .pred p;\nsetp.eq.s32 p, %1, 0;\n@p mbarrier.arrive.shared::cta.b64 _, [%0];\n}\n" :: "r"(base + SM_SIG + 8 * i), "r"(lane) : "memory");
  }
  __device__ __forceinline__ void turn() { bar_sync(1 + wg, 256); TR(*this, wg, 3); }
  __device__ __forceinline__ void pass() { bar_arrive(2 - wg, 256); TR(*this, wg, 4); }
};
__device__ __forceinline__ int gemm_unit(int ks) { return 3 * (ks & 3); }
__device__ __forceinline__ int att_slot(int i) { return 4 + 2 * i; }
template<int MASK> __device__ __forceinline__ int kv_slot(int h) { return MASK == PH_ALL ? h & 15 : h; }
__device__ __forceinline__ int out_mb(int cta) { return cta >> 3; }
__device__ __forceinline__ int out_nb(int cta) { return cta & 7; }
template<int MASK> constexpr int CV_REG = MASK == PH_ALL ? CONV_REG : 6;
template<int MASK> constexpr int CV_EXTRA = (1024 - NREG * CV_REG<MASK>) / (NCTA - NREG);
template<int MASK> __device__ __forceinline__ int conv_channel(int cta, int i) {
  return cta < NREG ? CV_EXTRA<MASK> * (NCTA - NREG) + cta * CV_REG<MASK> + i : (i >> 1) * 8 + (cta - NREG) * 2 + (i & 1);
}

template<int OFF, int N> __device__ __forceinline__ void pack_chunk(const float (&a)[N], float sc0, float sc1, uint4& v0, uint4& v1) {
  v0.x = pack_bf16(a[OFF + 0] * sc0, a[OFF + 1] * sc0); v0.y = pack_bf16(a[OFF + 4] * sc0, a[OFF + 5] * sc0);
  v0.z = pack_bf16(a[OFF + 8] * sc0, a[OFF + 9] * sc0); v0.w = pack_bf16(a[OFF + 12] * sc0, a[OFF + 13] * sc0);
  v1.x = pack_bf16(a[OFF + 2] * sc1, a[OFF + 3] * sc1); v1.y = pack_bf16(a[OFF + 6] * sc1, a[OFF + 7] * sc1);
  v1.z = pack_bf16(a[OFF + 10] * sc1, a[OFF + 11] * sc1); v1.w = pack_bf16(a[OFF + 14] * sc1, a[OFF + 15] * sc1);
}
template<int OFF, int N> __device__ __forceinline__ void pack_chunk(const float (&a)[N], uint4& v0, uint4& v1) {
  v0.x = pack_bf16(a[OFF + 0], a[OFF + 1]); v0.y = pack_bf16(a[OFF + 4], a[OFF + 5]);
  v0.z = pack_bf16(a[OFF + 8], a[OFF + 9]); v0.w = pack_bf16(a[OFF + 12], a[OFF + 13]);
  v1.x = pack_bf16(a[OFF + 2], a[OFF + 3]); v1.y = pack_bf16(a[OFF + 6], a[OFF + 7]);
  v1.z = pack_bf16(a[OFF + 10], a[OFF + 11]); v1.w = pack_bf16(a[OFF + 14], a[OFF + 15]);
}
__device__ __forceinline__ void sq_acc(const uint4& v, uint32_t& a) { a = hfma2(v.x, v.x, a); a = hfma2(v.y, v.y, a); a = hfma2(v.z, v.z, a); a = hfma2(v.w, v.w, a); }
__device__ __forceinline__ float norm2_max(uint32_t a0, uint32_t a1) {
  float n0 = bf_lo(a0) + bf_hi(a0), n1 = bf_lo(a1) + bf_hi(a1);
  n0 += __shfl_xor_sync(~0u, n0, 1); n1 += __shfl_xor_sync(~0u, n1, 1);
  n0 += __shfl_xor_sync(~0u, n0, 2); n1 += __shfl_xor_sync(~0u, n1, 2);
  return __uint_as_float(__reduce_max_sync(~0u, max(__float_as_uint(n0) & 0x7fffffffu, __float_as_uint(n1) & 0x7fffffffu)));
}

struct Pend { uint4 lo[8], hi[8]; uint32_t dst; float kn; };
__device__ __forceinline__ void pin(uint4 (&v)[8]) {
#pragma unroll
  for (int i = 0; i < 8; i++) asm volatile("" : "+r"(v[i].x), "+r"(v[i].y), "+r"(v[i].z), "+r"(v[i].w) :: "memory");
}
__device__ __forceinline__ uint32_t atom_off(int lane) { return (lane >> 2) * 64 + (((lane ^ (lane >> 3)) & 3) << 4); }
__device__ __forceinline__ void stg128(void* p, const uint4& v, bool stream) {
  if (stream) asm volatile("st.global.L2::cache_hint.v4.u32 [%0], {%1,%2,%3,%4}, %5;" :: "l"(p), "r"(v.x), "r"(v.y), "r"(v.z), "r"(v.w), "l"(pol_first()) : "memory");
  else *(uint4*)p = v;
}
template<int J0, int J1, bool STREAM = false> __device__ __forceinline__ void tile_store(const uint4 (&v)[8], uint32_t dst, int lane) {
  uint8_t* d = g_T + (dst + atom_off(lane));
#pragma unroll
  for (int j = J0; j < J1; j++) { stg128(d + j * 512, v[2 * j], STREAM); stg128(d + j * 512 + 2048, v[2 * j + 1], STREAM); }
}
__device__ __forceinline__ float tile_norm2(const uint4 (&v)[8]) {
  uint32_t n0 = 0, n1 = 0, n2 = 0, n3 = 0;
#pragma unroll
  for (int j = 0; j < 2; j++) { sq_acc(v[2 * j], n0); sq_acc(v[2 * j + 1], n1); sq_acc(v[2 * j + 4], n2); sq_acc(v[2 * j + 5], n3); }
  return norm2_max(hadd2(n0, n2), hadd2(n1, n3));
}
template<int PART> __device__ __forceinline__ void out_part(Cons& c, Pend& w) {
  if (PART == 0) { w.kn = tile_norm2(w.lo); tile_store<0, 2>(w.lo, w.dst, c.lane); }
  if (PART == 1) tile_store<2, 4>(w.lo, w.dst, c.lane);
  if (PART == 2) {
    const float vn = tile_norm2(w.hi);
    if (c.lane == 0) g_kn2[((w.dst - T_KV) >> 16) * 8 + c.wg * 4 + c.warp] = (vn <= 1.0e30f && vn >= 1.0e-30f) ? w.kn : __uint_as_float(0x7f800000u);
    tile_store<0, 2, POL(11)>(w.hi, w.dst + 32768, c.lane);
  }
  if (PART == 3) tile_store<2, 4, POL(11)>(w.hi, w.dst + 32768, c.lane);
}
template<bool FIRST> __device__ __forceinline__ void kv_issue(Cons& c, float (&acc)[128], int u) {
  const uint64_t da = odesc(c.daddr(u) + c.wg * 8192, 16, 1024, 1), db = odesc(c.daddr(u + 1), 8192, 1024, 1);
  c.turn();
  wg_fence();
#pragma unroll
  for (int kk = 0; kk < 4; kk++) wgmma_ss_n256<1>(acc, da + kk * 2, db + kk * 128, !(FIRST && kk == 0));
  wg_commit();
  c.pass();
}
__device__ __forceinline__ void cons_kv(Cons& c, int h, int hs, int g, Pend& w, bool pend_o) {
#pragma unroll 1
  for (int tile = 0; tile < 2; tile++) {
    float acc[128];
    c.wait(0);
    if (tile == 0 && h < 16) TS(c.wg, 16);
    kv_issue<true>(c, acc, 0);
    if (tile == 1 && pend_o) mbar_wait(c.base + SM_RDY + 8 * RDY_WAR, 0);
    if (tile == 1 || pend_o) out_part<0>(c, w);
#pragma unroll 1
    for (int ks = 1; ks < 8; ks++) {
      if (ks == 3 && (tile == 1 || pend_o)) { out_part<1>(c, w); if (tile == 0) c.signal(SIG_CTX); }
      if (ks == 5 && tile == 1) out_part<2>(c, w);
      if (ks == 7 && tile == 1) out_part<3>(c, w);
      const int u = gemm_unit(ks);
      c.wait(u);
      wg_wait<0>();
      c.release(gemm_unit(ks - 1), 3);
      kv_issue<false>(c, acc, u);
    }
    wg_wait<0>(); fence_regs(acc);
    c.release(9, 3);
    pack_chunk<0>(acc, w.lo[0], w.lo[1]);  pack_chunk<16>(acc, w.lo[2], w.lo[3]); pack_chunk<32>(acc, w.lo[4], w.lo[5]); pack_chunk<48>(acc, w.lo[6], w.lo[7]);
    pack_chunk<64>(acc, w.hi[0], w.hi[1]); pack_chunk<80>(acc, w.hi[2], w.hi[3]); pack_chunk<96>(acc, w.hi[4], w.hi[5]); pack_chunk<112>(acc, w.hi[6], w.hi[7]);
    pin(w.lo); pin(w.hi);
    w.dst = T_KV + (hs * 16 + 2 * g + tile) * 65536 + (c.wg * 4 + c.warp) * 4096;
  }
}
template<bool FIRST> __device__ __forceinline__ void q_issue(Cons& c, float (&a)[64], float (&b)[64], int u) {
  const uint64_t da = odesc(c.daddr(u) + c.wg * 8192, 16, 1024, 1), db = odesc(c.daddr(u + 2), 8192, 1024, 1);
  const uint64_t da2 = odesc(c.daddr(u + 1) + (1 - c.wg) * 8192, 16, 1024, 1);
  c.turn();
  wg_fence();
#pragma unroll
  for (int kk = 0; kk < 4; kk++) wgmma_ss_n128<1>(a, da + kk * 2, db + kk * 128, !(FIRST && kk == 0));
#pragma unroll
  for (int kk = 0; kk < 4; kk++) wgmma_ss_n128<1>(b, da2 + kk * 2, db + kk * 128, !(FIRST && kk == 0));
  wg_commit();
  c.pass();
}
template<int AU> __device__ __forceinline__ void q_tail(Cons& c, float (&d)[64], int rowhalf) {
  const uint64_t da = odesc(c.daddr(6 + AU) + rowhalf * 8192, 16, 1024, 1), db = odesc(c.daddr(8), 8192, 1024, 1);
  c.turn();
  wg_fence();
#pragma unroll
  for (int kk = 0; kk < 8; kk++) wgmma_ss_n128<1>(d, da + (kk >> 2) * 3072 + (kk & 3) * 2, db + (kk >> 2) * 3072 + (kk & 3) * 128, 1);
  wg_commit();
  c.pass();
}
template<int OFF> __device__ __forceinline__ void q_store(const float (&d)[64], uint4 (&v)[8], uint32_t q0) {
  pack_chunk<0>(d, QSCALE, QSCALE, v[0], v[1]);  sts128o<OFF>(q0, v[0]);        sts128o<OFF + 2048>(q0, v[1]);
  pack_chunk<16>(d, QSCALE, QSCALE, v[2], v[3]); sts128o<OFF + 512>(q0, v[2]);  sts128o<OFF + 2560>(q0, v[3]);
  pack_chunk<32>(d, QSCALE, QSCALE, v[4], v[5]); sts128o<OFF + 1024>(q0, v[4]); sts128o<OFF + 3072>(q0, v[5]);
  pack_chunk<48>(d, QSCALE, QSCALE, v[6], v[7]); sts128o<OFF + 1536>(q0, v[6]); sts128o<OFF + 3584>(q0, v[7]);
}
template<bool PEND_KV> __device__ __forceinline__ void cons_q(Cons& c, int h, Pend& w) {
  float a[64], b[64];
  c.wait(0);
  q_issue<true>(c, a, b, 0);
  if (PEND_KV) out_part<0>(c, w);
#pragma unroll 1
  for (int ks = 1; ks < 14; ks++) {
    if (PEND_KV && ks < 6) {
      if (ks == 2) out_part<1>(c, w);
      if (ks == 4) out_part<2>(c, w);
      if (ks == 5) { out_part<3>(c, w); c.signal(SIG_KV + (h >> 4)); }
    }
    const int u = gemm_unit(ks);
    c.wait(u);
    wg_wait<0>();
    c.release(gemm_unit(ks - 1), 3);
    q_issue<false>(c, a, b, u);
  }
  c.wait(6); c.wait(9);
  wg_wait<0>();
  c.release(3, 3);
  q_tail<1>(c, b, 1 - c.wg);
  wg_wait<0>(); fence_regs(b);
  q_tail<0>(c, a, c.wg);
  c.wait(0);
  const uint32_t q0 = c.addr(0) + (c.wg * 4 + c.warp) * 4096 + atom_off(c.lane);
  q_store<32768>(b, w.lo, q0);
  w.kn = tile_norm2(w.lo);
  c.wait(4);
  wg_wait<0>(); fence_regs(a);
  c.release(6, 6);
  q_store<0>(a, w.lo, q0);
  fence_async_smem();
}

__device__ __forceinline__ void issue_qk(float (&s)[64], uint64_t da, uint64_t db) {
#pragma unroll
  for (int kk = 0; kk < 8; kk++) wgmma_ss_n128<0>(s, da + (kk >> 1) * 32 + (kk & 1) * 2, db + (kk >> 1) * 32 + (kk & 1) * 2, kk > 0);
  wg_commit();
}
template<int A, int B> __device__ __forceinline__ void exp_rng(float (&s)[64]) {
#pragma unroll
  for (int i = 4 * A; i < 4 * B; i++) s[i] = ex2(s[i]);
}
template<int A, int B> __device__ __forceinline__ void sum_rng(const float (&s)[64], float (&l)[4]) {
#pragma unroll
  for (int i = A; i < B; i++) { l[0] += s[4 * i]; l[1] += s[4 * i + 1]; l[2] += s[4 * i + 2]; l[3] += s[4 * i + 3]; }
}
template<int A, int B> __device__ __forceinline__ void cvt_p(const float (&s)[64], uint32_t (&p)[32]) {
#pragma unroll
  for (int i = 2 * A; i < 2 * B; i++) p[i] = pack_bf16(s[2 * i], s[2 * i + 1]);
}
template<int K0> __device__ __forceinline__ void mask_half(float (&s)[64], int warp, int lane) {
  const int l0 = warp + (2 * (lane & 3) <= (lane >> 2)), l1 = warp + (2 * (lane & 3) < (lane >> 2));
#pragma unroll
  for (int k = 0; k < 4; k++) {
    float* t = s + 8 * (K0 + k);
    if (k >= l0) { t[0] = -INFINITY; t[6] = -INFINITY; }
    if (k >= l1) { t[1] = -INFINITY; t[7] = -INFINITY; }
    if (k > warp) { t[2] = -INFINITY; t[3] = -INFINITY; }
    if (k >= warp) { t[4] = -INFINITY; t[5] = -INFINITY; }
  }
}
__device__ __forceinline__ void row_inv(float& l0, float& l1) {
  l0 += __shfl_xor_sync(~0u, l0, 1); l1 += __shfl_xor_sync(~0u, l1, 1);
  l0 += __shfl_xor_sync(~0u, l0, 2); l1 += __shfl_xor_sync(~0u, l1, 2);
  l0 = __fdividef(1.f, l0); l1 = __fdividef(1.f, l1);
}
__device__ __forceinline__ void pack_o(const float (&o)[64], float i0, float i1, uint4 (&v)[8]) {
  pack_chunk<0>(o, i0, i1, v[0], v[1]); pack_chunk<16>(o, i0, i1, v[2], v[3]);
  pack_chunk<32>(o, i0, i1, v[4], v[5]); pack_chunk<48>(o, i0, i1, v[6], v[7]);
  pin(v);
}
__device__ __forceinline__ void softmax_safe(float (&s)[64], bool upper_only, float& m0, float& m1, float& sc0, float& sc1) {
  float a0 = m0, a1 = m1;
#pragma unroll
  for (int i = 0; i < 8; i++) { a0 = fmaxf(a0, fmaxf(s[4 * i], s[4 * i + 1])); a1 = fmaxf(a1, fmaxf(s[4 * i + 2], s[4 * i + 3])); }
  if (upper_only) { a0 = m0; a1 = m1; }
#pragma unroll
  for (int i = 8; i < 16; i++) { a0 = fmaxf(a0, fmaxf(s[4 * i], s[4 * i + 1])); a1 = fmaxf(a1, fmaxf(s[4 * i + 2], s[4 * i + 3])); }
  a0 = fmaxf(a0, __shfl_xor_sync(~0u, a0, 1)); a1 = fmaxf(a1, __shfl_xor_sync(~0u, a1, 1));
  a0 = fmaxf(a0, __shfl_xor_sync(~0u, a0, 2)); a1 = fmaxf(a1, __shfl_xor_sync(~0u, a1, 2));
  sc0 = ex2(m0 - a0); sc1 = ex2(m1 - a1);
  m0 = a0; m1 = a1;
#pragma unroll
  for (int i = 0; i < 16; i++) { s[4 * i] -= a0; s[4 * i + 1] -= a0; s[4 * i + 2] -= a1; s[4 * i + 3] -= a1; }
}
struct Att {
  float s[64], o[64], l[4], i0, i1; uint32_t p[32];
  uint32_t qaddr;
};
__device__ __forceinline__ uint32_t ctx_off(const Cons& c, int h, int qb, int rowhalf) { return T_CTX + (qb * 32 + h) * 32768 + (rowhalf * 4 + c.warp) * 4096; }
__device__ __forceinline__ int att_first(Cons& c, Att& a, int h, const Pend& w) {
  a.qaddr = c.daddr(0) + c.wg * 16384;
  c.turn();
  wg_fence();
  issue_qk(a.s, odesc(a.qaddr, 16, 2048, 2), odesc(c.daddr(4), 16, 2048, 2));
  c.pass();
  c.signal(SIG_ATT + (h >> 4));
  const float qn = tile_norm2(w.lo), kn = __uint_as_float(lds32(c.base + SM_KMAX + 4 * (h >> 4)));
  const int fast = __shfl_sync(~0u, bar_and(3 + c.wg, 128, (qn * kn <= BOUND2) && (w.kn * kn <= BOUND2)), 0);
#pragma unroll
  for (int i = 0; i < 64; i++) a.o[i] = 0.f;
#pragma unroll
  for (int i = 0; i < 32; i++) a.p[i] = 0;
  a.l[0] = a.l[1] = a.l[2] = a.l[3] = 0.f; a.i0 = a.i1 = 0.f;
  wg_wait<0>(); fence_regs(a.s);
  c.release(4, 2);
  return fast;
}
__device__ __forceinline__ void att_last(Cons& c, Att& a, Pend& w, int h, int g, bool drain) {
#pragma unroll 1
  for (int k = drain ? 0 : 1; k < 2; k++) {
    if (k == 1) {
      const int uv = att_slot(1);
      c.wait(uv);
      c.turn();
      fence_regs(a.o); fence_regs(a.p);
      wgmma_pv_sel(a.o, a.p, odesc(c.daddr(uv), 512, 2048, 2), !(drain && c.wg == 1), !drain);
      c.pass();
      a.i0 = a.l[0] + a.l[1]; a.i1 = a.l[2] + a.l[3]; row_inv(a.i0, a.i1);
      wg_wait<0>(); fence_regs(a.o); fence_regs(a.p);
      c.release(uv, 2);
    }
    pack_o(a.o, a.i0, a.i1, w.lo);
    if (k == 0) tile_store<0, 4>(w.lo, ctx_off(c, h, 15, c.wg), c.lane);
  }
  w.dst = ctx_off(c, h, g, 1 - c.wg);
}
__device__ __forceinline__ void cons_att(Cons& c, int h, int g, Pend& w) {
  Att a;
  const int fast = att_first(c, a, h, w);
  float m0 = -INFINITY, m1 = -INFINITY, sc0 = 0.f, sc1 = 0.f;
  int uk = 10, nrel = 0;
#pragma unroll 1
  for (int d = g - 15;;) {
    const bool lo = d == c.wg;
    if ((unsigned)d < 2 || !fast) {
      if ((unsigned)d < 2) mask_half<4>(a.s, c.warp, c.lane);
      if (!fast) {
        if (d == 1) m0 = m1 = -INFINITY;
        softmax_safe(a.s, lo, m0, m1, sc0, sc1);
        a.l[0] *= sc0; a.l[1] *= sc0; a.l[2] *= sc1; a.l[3] *= sc1;
      }
    }
    exp_rng<8, 16>(a.s); sum_rng<8, 16>(a.s, a.l);
    exp_rng<ATT_SPLIT, 8>(a.s);
    sched_fence(((a.l[0] + a.l[1]) + (a.l[2] + a.l[3])) + (ATT_SPLIT < 8 ? a.s[4 * ATT_SPLIT + 3] : 0.f), c.base + SM_DUMMY);
    wg_wait<0>(); fence_regs(a.o); fence_regs(a.p);
    c.release(14 - uk, nrel);
    nrel = 2; uk ^= 12;
    if (d == 0) a.qaddr += 32768;
    const uint64_t dq = odesc(a.qaddr, 16, 2048, 2), dk = odesc(c.daddr(uk) - (d + 1 == c.wg ? 16384 : 0), 16, 2048, 2), dv = odesc(c.daddr(14 - uk), 512, 2048, 2);
    if (!lo) { exp_rng<0, ATT_SPLIT>(a.s); sum_rng<0, 8>(a.s, a.l); cvt_p<0, 16>(a.s, a.p); }
    else if (gridDim.y == 1) cvt_p<8, 16>(a.s, a.p);
    if (!fast || d == g + 1) {
      if (!fast && d != 1) {
#pragma unroll
        for (int i = 0; i < 16; i++) { a.o[4 * i] *= sc0; a.o[4 * i + 1] *= sc0; a.o[4 * i + 2] *= sc1; a.o[4 * i + 3] *= sc1; }
      }
      if (d == g + 1) break;
    }
    d++;
    if (c.wg == 0) c.wait(uk); else c.skip(uk);
    c.turn();
    fence_regs(a.o); fence_regs(a.p);
    wg_fence();
    issue_qk(a.s, dq, dk);
    if (d == 2) {
      uint4 v[8];
      pack_o(a.o, a.i0, a.i1, v); tile_store<0, 4>(v, ctx_off(c, h, 15 - g, c.wg), c.lane);
    }
    wgmma_pv_sel(a.o, a.p, dv, !lo, d != 2);
    c.pass();
    if (d == 1) {
      a.i0 = a.l[0] + a.l[1]; a.i1 = a.l[2] + a.l[3]; row_inv(a.i0, a.i1);
      a.l[0] = a.l[1] = a.l[2] = a.l[3] = 0.f;
    }
    wg_wait<1>(); fence_regs(a.s);
    c.release(uk, 2);
    c.release(d == 0 ? 0 : 2, (d == 0 || d == g + 1) ? 2 : 0);
  }
  att_last(c, a, w, h, g, g == 0);
}

constexpr int CV_H = 1024, CV_U = 5120, CV_D = CV_U + 4128, CV_ROW = 1056;
template<int OFF> __device__ __forceinline__ uint32_t lds32o(uint32_t a) { uint32_t v; asm volatile("ld.shared.u32 %0, [%1+%2];" : "=r"(v) : "r"(a), "n"(OFF) : "memory"); return v; }
template<int G, int G1 = 16> __device__ __forceinline__ void conv_lda(uint32_t (&a)[64], uint32_t p) {
  a[4 * G + 0] = lds32o<-256 * G>(p);
  a[4 * G + 1] = lds32o<-256 * G - 128>(p);
  a[4 * G + 2] = lds32o<-256 * G + 16>(p);
  a[4 * G + 3] = lds32o<-256 * G - 112>(p);
  if constexpr (G + 1 < G1) conv_lda<G + 1, G1>(a, p);
}
struct CvAcc { float lo[16], hi[16]; };
__device__ __forceinline__ void fence_regs(CvAcc& d) { fence_regs(d.lo); fence_regs(d.hi); }
template<int R, int H> __device__ __forceinline__ void conv_mma_h(float (&d)[16], const uint32_t (&a)[64], uint64_t db) {
#pragma unroll
  for (int G = 0; G < 4 * R + 2 * H + 2; G++) wgmma_rs_n32<0>(d, a[4 * G], a[4 * G + 1], a[4 * G + 2], a[4 * G + 3], db + 64 * R + 32 * H - 16 * G, G > 0);
}
template<int R> __device__ __forceinline__ void conv_mma(CvAcc& d, const uint32_t (&a)[64], uint64_t db) { conv_mma_h<R, 0>(d.lo, a, db); conv_mma_h<R, 1>(d.hi, a, db); }
template<int C0> __device__ __forceinline__ void conv_st_h(const float (&d)[16], uint32_t wq, float& c0, float& c1) {
#pragma unroll
  for (int n = 0; n < 4; n++) { sts64f(wq + (C0 + n * 8) * 4, d[4 * n] + c0, d[4 * n + 1] + c1); c0 = d[4 * n + 2]; c1 = d[4 * n + 3]; }
}
template<int R> __device__ __forceinline__ void conv_st(const CvAcc& d, uint32_t wq, float& c0, float& c1) { conv_st_h<64 * R>(d.lo, wq, c0, c1); conv_st_h<64 * R + 32>(d.hi, wq, c0, c1); }
struct ConvTail { float t[64]; uint4 ua, uc; uint32_t D2; };
__device__ __forceinline__ void conv_emit(ConvTail& e, int ch, int tid) {
  fence_regs(e.t);
  float y[16];
#pragma unroll
  for (int i = 0; i < 16; i++) y[i] = (e.t[i] + e.t[16 + i]) + (e.t[32 + i] + e.t[48 + i]);
  uint4 z0, z1;
  z0.x = hadd2(pack_bf16(y[0], y[2]), hmul2(__byte_perm(e.ua.w, 0, 0x1032), e.D2));
  z0.y = hadd2(pack_bf16(y[4], y[6]), hmul2(__byte_perm(e.ua.z, 0, 0x1032), e.D2));
  z0.z = hadd2(pack_bf16(y[8], y[10]), hmul2(__byte_perm(e.ua.y, 0, 0x1032), e.D2));
  z0.w = hadd2(pack_bf16(y[12], y[14]), hmul2(__byte_perm(e.ua.x, 0, 0x1032), e.D2));
  z1.x = hadd2(pack_bf16(y[1], y[3]), hmul2(__byte_perm(e.uc.w, 0, 0x1032), e.D2));
  z1.y = hadd2(pack_bf16(y[5], y[7]), hmul2(__byte_perm(e.uc.z, 0, 0x1032), e.D2));
  z1.z = hadd2(pack_bf16(y[9], y[11]), hmul2(__byte_perm(e.uc.y, 0, 0x1032), e.D2));
  z1.w = hadd2(pack_bf16(y[13], y[15]), hmul2(__byte_perm(e.uc.x, 0, 0x1032), e.D2));
  uint4* zp = (uint4*)(g_z + (uint32_t)(ch * 2048 + tid * 16));
  zp[0] = z0; zp[1] = z1;
}
template<int MASK> __device__ __forceinline__ void cons_conv(Cons& c, int cta, int nch) {
  const int r = c.lane >> 2, q = c.lane & 3, tid = c.warp * 32 + c.lane;
  const uint32_t part = c.addr(4) - 2048 + (1 - c.wg) * (32 * CV_ROW) + 32;
  const uint32_t aoff = CV_U + ((r & 1) ? 0 : UPITCH) + 4 * (((2039 - r) >> 1) + q - 8 * c.warp);
  const uint32_t wq = part + (c.warp * 8 + r) * CV_ROW + q * 8, rq = part + tid * 8;
  uint32_t a[64];
  ConvTail e = {};
  c.wait(c.wg); c.skip(c.wg ^ 1);
  conv_lda<0>(a, c.addr(c.wg) + aoff);
  c.wait(4);
  sts64f(part + (tid >> 2) * CV_ROW - 32 + q * 8, 0.f, 0.f);
#pragma unroll 1
  for (int i = 0; i < nch / 2; i++) {
    const int u = 2 * (i & 1) + c.wg;
    CvAcc d0, d1, d2, d3;
    float c0 = 0.f, c1 = 0.f;
    const uint64_t db = odesc(c.daddr(u) + CV_H - 16, 16, 128, 0);
    c.turn();
    fence_regs(a);
    wg_fence();
    conv_mma<0>(d0, a, db); conv_mma<1>(d1, a, db); wg_commit();
    if (i > 0) {
      conv_emit(e, conv_channel<MASK>(cta, 2 * i - 2 + c.wg), tid);
      if ((i & 15) == 0) c.signal(SIG_Z + (i >> 4) - 1);
    }
    wg_fence();
    conv_mma_h<2, 0>(d2.lo, a, db); wg_commit();
    wg_wait<1>(); fence_regs(d0); fence_regs(d1);
    conv_st_h<0>(d0.lo, wq, c0, c1);
    wg_fence();
    conv_mma_h<2, 1>(d2.hi, a, db); wg_commit();
    conv_st_h<32>(d0.hi, wq, c0, c1);
    conv_mma_h<3, 0>(d3.lo, a, db);
    conv_st_h<64>(d1.lo, wq, c0, c1);
    conv_mma_h<3, 1>(d3.hi, a, db); wg_commit();
    c.pass();
    const int un = i + 1 < nch / 2 ? u ^ 2 : u;
    if (un != u) { c.wait(un); c.skip(un ^ 1); }
    wg_wait<1>(); fence_regs(d2);
    conv_st_h<96>(d1.hi, wq, c0, c1);
    conv_st<2>(d2, wq, c0, c1);
    {
      const int sw = (c.lane >> 2) & 1;
      const uint4 v0 = lds128(c.addr(u) + CV_U + 4064 - 32 * tid + 16 * sw), v1 = lds128(c.addr(u) + CV_U + 4080 - 32 * tid - 16 * sw);
      e.ua = sw ? v0 : v1; e.uc = sw ? v1 : v0;
    }
    e.D2 = lds32(c.addr(u) + CV_D);
    wg_wait<0>(); fence_regs(d3); fence_regs(a);
    conv_st<3>(d3, wq, c0, c1);
    conv_lda<0, 4>(a, c.addr(un) + aoff);
    bar_sync(3 + c.wg, 128);
    c.release2(u);
    conv_lda<4, 16>(a, c.addr(un) + aoff);
#pragma unroll
    for (int k = 0; k < 32; k++) { const float2 v = lds64f(rq + k * CV_ROW - (k >> 3) * 8); e.t[2 * k] = v.x; e.t[2 * k + 1] = v.y; }
  }
  conv_emit(e, conv_channel<MASK>(cta, nch - 2 + c.wg), tid);
  c.signal(SIG_Z + ((nch / 2 - 1) >> 4));
  c.release(4, 4);
}

constexpr int OC_START = 2, OC_LEN = 15, OC_PART = 13824, OC_ROW = 544;
__device__ __forceinline__ int out_next(int u) { return u == 12 ? 4 : u + 2; }
struct Out { float acc[64]; int pu; uint64_t da, db; };
template<bool FIRST, bool REL> __device__ __forceinline__ void out_step(Cons& c, Out& o) {
  const int pu = o.pu, u = out_next(pu);
  o.pu = u;
  c.wait(u);
  const uint64_t da = o.da + (uint32_t)(u * 1024), db = o.db + (uint32_t)(u * 1024);
  wg_fence();
#pragma unroll
  for (int kk = 0; kk < 4; kk++) wgmma_ss_n128<1>(o.acc, da + (kk >> 1) * 32 + (kk & 1) * 2, db + kk * 128, !(FIRST && kk == 0));
  wg_commit();
  if (REL) { wg_wait<1>(); c.release(pu, 2); }
}
template<int I0, int I1> __device__ __forceinline__ void oc_red(float (&y)[8], uint32_t rq) {
#pragma unroll
  for (int i = I0; i < I1; i++) { const float v = __uint_as_float(lds32(rq + i * OC_ROW - (i >> 3) * 8)); y[i & 7] = i < 8 ? v : y[i & 7] + v; }
}
__device__ __forceinline__ void oc_emit(const float (&y)[8], const uint4& u, uint32_t D2, __nv_bfloat16* dst) {
  uint4 z;
  z.x = hadd2(pack_bf16(y[0], y[1]), hmul2(__byte_perm(u.w, 0, 0x1032), D2));
  z.y = hadd2(pack_bf16(y[2], y[3]), hmul2(__byte_perm(u.z, 0, 0x1032), D2));
  z.z = hadd2(pack_bf16(y[4], y[5]), hmul2(__byte_perm(u.y, 0, 0x1032), D2));
  z.w = hadd2(pack_bf16(y[6], y[7]), hmul2(__byte_perm(u.x, 0, 0x1032), D2));
  *(uint4*)dst = z;
}
template<int MASK> __device__ __forceinline__ void cons_out(Cons& c, const Maps& M, const Params& P, int cta, Pend& w) {
  const int mb = out_mb(cta), nb = out_nb(cta);
  Out o;
  o.da = odesc(c.daddr(0) + c.wg * 8192, 16, 1024, 2); o.db = odesc(c.daddr(1), 8192, 1024, 1);
  o.pu = 5 + gridDim.y;
  out_step<true, false>(c, o);
  if (MASK & PH_ATT) tile_store<0, 2>(w.lo, w.dst, c.lane);
  out_step<false, true>(c, o);
  if (MASK & PH_ATT) { tile_store<2, 4>(w.lo, w.dst, c.lane); c.signal(SIG_CTX + 1); }
  int ks = OC_START;
  if (MASK & PH_CONV) {
    const int r = c.lane >> 2, q = c.lane & 3, tid = c.warp * 32 + c.lane, u = 2 * c.wg;
    const uint32_t ub = c.addr(u), part = ub + OC_PART + 32;
    const uint32_t ap = ub + CV_U + ((r & 1) ? 0 : UPITCH) + 4 * (((2039 - r) >> 1) + q - 8 * c.warp);
    const uint32_t wq = part + (c.warp * 8 + r) * OC_ROW + q * 8, rq = part + tid * 4;
    const int nr = (CV_REG<MASK> + 1 - c.wg) >> 1;
#define STEP(N) out_step<false, true>(c, o);
#pragma unroll 1
    for (int i = 0; i < nr; i++) {
      uint32_t a[64];
      CvAcc d0, d1;
      float y[8], c0 = 0.f, c1 = 0.f;
      const uint64_t db = odesc(c.daddr(u + (i >> 8)) + CV_H - 16, 16, 128, 0);
      c.wait(u);
      conv_lda<0, 3>(a, ap);
      STEP(0)
      conv_lda<3, 6>(a, ap);
      STEP(1)
      conv_lda<6, 9>(a, ap);
      STEP(2)
      fence_regs(reinterpret_cast<uint32_t (&)[32]>(a));
      wg_fence();
      conv_mma<0>(d0, a, db); conv_mma<1>(d1, a, db); wg_commit();
      conv_lda<9, 13>(a, ap);
      STEP(3)
      fence_regs(d0); fence_regs(d1);
      conv_lda<13, 16>(a, ap);
      STEP(4)
      bar_sync(3 + c.wg, 128);
      sts64f(wq - 32, 0.f, 0.f);
      conv_st<0>(d0, wq, c0, c1);
      STEP(5)
      float e0 = d1.hi[12] + d1.hi[10], e1 = d1.hi[13] + d1.hi[11];
      conv_st<1>(d1, wq, c0, c1);
      asm volatile("add.f32 %0, %0, 0f80000000;" : "+f"(c0)); asm volatile("add.f32 %0, %0, 0f80000000;" : "+f"(c1));
      fence_regs(a);
      wg_fence();
      conv_mma<2>(d0, a, db); conv_mma<3>(d1, a, db); wg_commit();
      bar_sync(3 + c.wg, 128);
      oc_red<0, 8>(y, rq);
      STEP(6)
      fence_regs(d0); fence_regs(d1); fence_regs(a);
      const uint4 u0 = lds128(ub + CV_U + 4080 - 16 * tid), u1 = lds128(ub + CV_U + 2032 - 16 * tid);
      const uint32_t D2 = lds32(ub + CV_D);
      oc_red<8, 12>(y, rq);
      __syncwarp();
      c.release2(u);
      STEP(7)
      oc_red<12, 24>(y, rq);
      STEP(8)
      __nv_bfloat16* zp = g_z + (uint32_t)(conv_channel<MASK>(cta, 2 * i + c.wg) * 2048 + (threadIdx.x & 127) * 8);
      oc_red<24, 32>(y, rq);
      oc_emit(y, u0, D2, zp);
      bar_sync(3 + c.wg, 128);
      STEP(9)
      sts64f(wq - 32, e0, e1);
      conv_st<0>(d0, wq, c0, c1);
      STEP(10)
      conv_st<1>(d1, wq, c0, c1);
      bar_sync(3 + c.wg, 128);
      oc_red<0, 8>(y, rq);
      STEP(11)
      oc_red<8, 16>(y, rq);
      STEP(12)
      oc_red<16, 24>(y, rq);
      STEP(13)
      oc_red<24, 32>(y, rq);
      oc_emit(y, u1, D2, zp + 1024);
      if (i == nr - 1) { c.signal(SIG_Z); c.release2(u + 1); }
      STEP(14)
    }
#undef STEP
    if (((CV_REG<MASK> + c.wg) >> 1) & 1) c.skip(u ^ 2);
    ks += nr * OC_LEN;
  }
  TS(c.wg, 9);
#pragma unroll 1
  for (; ks < 57; ks++) out_step<false, true>(c, o);
  uint32_t ga[32];
  c.wait(0);
  const float g0 = __uint_as_float(lds32(c.base + SM_GATE + 4 * (c.wg * 64 + c.warp * 16 + (c.lane >> 2)))), g1 = __uint_as_float(lds32(c.base + SM_GATE + 32 + 4 * (c.wg * 64 + c.warp * 16 + (c.lane >> 2))));
  const uint32_t gg0 = pack_bf16(g0, g0), gg1 = pack_bf16(g1, g1);
  const uint32_t og0 = pack_bf16(1.f - g0, 1.f - g0), og1 = pack_bf16(1.f - g1, 1.f - g1);
  const int xr = c.wg * 64 + c.warp * 16 + (c.lane & 15);
  const uint32_t xa = c.addr(0) + xr * 128, xs = xr & 7, xh = c.lane >> 4;
  const int zr = (c.lane & 7) + ((c.lane >> 4) << 3);
  const uint32_t za = c.addr(2) + c.wg * 16384 + zr * 128 + (((c.warp * 2 + ((c.lane >> 3) & 1)) ^ (zr & 7)) << 4);
#pragma unroll
  for (int i = 0; i < 8; i++) {
    if (i == 0) out_step<false, true>(c, o);
    if (i == 3) out_step<false, true>(c, o);
    if (i == 6) out_step<false, true>(c, o);
    ldsm4(xa + (i >> 2) * 16384 + ((((i & 3) * 2 + xh) ^ xs) << 4), ga[4 * i], ga[4 * i + 1], ga[4 * i + 2], ga[4 * i + 3]);
  }
#pragma unroll 1
  for (ks = 60; ks < 63; ks++) { out_step<false, false>(c, o); wg_wait<1>(); }
  c.wait(2);
#pragma unroll
  for (int i = 0; i < 8; i++) {
    if (i == 2) out_step<false, false>(c, o);
    uint32_t z0, z1, z2, z3;
    ldsm4t(za + i * 2048, z0, z1, z2, z3);
    ga[4 * i + 0] = hmul2(gg0, hmul2(ga[4 * i + 0], z0)); ga[4 * i + 1] = hmul2(gg1, hmul2(ga[4 * i + 1], z1));
    ga[4 * i + 2] = hmul2(gg0, hmul2(ga[4 * i + 2], z2)); ga[4 * i + 3] = hmul2(gg1, hmul2(ga[4 * i + 3], z3));
  }
  c.signal(SIG_DONE);
  fence_regs(ga);
  wg_wait<0>(); fence_regs(o.acc);
#pragma unroll
  for (int i = 0; i < 8; i++) {
    const uint32_t r0 = hadd2(ga[4 * i + 0], hmul2(og0, pack_bf16(o.acc[8 * i + 0], o.acc[8 * i + 1])));
    const uint32_t r1 = hadd2(ga[4 * i + 1], hmul2(og1, pack_bf16(o.acc[8 * i + 2], o.acc[8 * i + 3])));
    const uint32_t r2 = hadd2(ga[4 * i + 2], hmul2(og0, pack_bf16(o.acc[8 * i + 4], o.acc[8 * i + 5])));
    const uint32_t r3 = hadd2(ga[4 * i + 3], hmul2(og1, pack_bf16(o.acc[8 * i + 6], o.acc[8 * i + 7])));
    stsm4(xa + (i >> 2) * 16384 + ((((i & 3) * 2 + xh) ^ xs) << 4), r0, r1, r2, r3);
    if ((i & 3) == 3) {
      __syncwarp();
#pragma unroll
      for (int k = 0; k < 4; k++) {
        const int rr = c.wg * 64 + c.warp * 16 + k * 4 + (c.lane >> 3);
        const uint4 v = lds128(c.addr(i >> 2) + rr * 128 + (((c.lane ^ rr) & 7) << 4));
        *(uint4*)(P.out + (uint32_t)((mb * 128 + rr) * 1024 + nb * 128 + (i >> 2) * 64 + (c.lane & 7) * 8)) = v;
      }
    }
  }
}

__device__ __forceinline__ void load_conv(Prod& p, const Maps& M, int u, int ch) {
  if (elect()) {
    mbar_expect(p.full(u), 5120 + UCH);
    tma3d(p.addr(u), &M.h, 0, -8, ch, p.full(u), POL(4));
    bulk_g2s(p.addr(u) + CV_U, g_u + (size_t)ch * UCH, UCH, p.full(u), POL(4));
  }
}
template<int MASK> __device__ __forceinline__ void prod_conv(Prod& p, const Maps& M, int cta, int nch) {
  int ready = -1;
#pragma unroll 1
  for (int i = 0; i < nch; i++) {
    const int ch = conv_channel<MASK>(cta, i);
    const int u = i & 3;
    if ((ch >> 6) != ready) { ready = ch >> 6; if (cta < NREG) mbar_wait(p.base + SM_RDY + 8 * RDY_U, 0); else cnt_wait(g_cnt + (C_U + ready) * CSTRIDE, 128); }
    p.acquire(u, 1);
    load_conv(p, M, u, ch);
    if (i == 3) { p.acquire(4, 4); if (elect()) mbar_arrive(p.full(4)); }
  }
}
#define HOIST(v) asm volatile("" : "+r"(v))
template<int MASK> __device__ __forceinline__ void producer(const Maps& M, const Params& P, uint32_t base, int cta, int lane) {
  Prod p{base, ((MASK & PH_KV) && cta < NREG) ? 0xffffcfffu ^ ((1u << (3 * NFIRST)) - 1) : 0xffffffffu, lane,
         (cta * 3 + 2) * 2048};
  if (cta >= NREG) { if (MASK & PH_CONV) prod_conv<MASK>(p, M, cta, CV_EXTRA<MASK>); return; }
  const int g = cta & 7, j = cta >> 3, rank = cta & 1;
#pragma unroll 1
  for (int half = 0; half < 2; half++) {
    const int h = j + 16 * half;
    if (MASK & PH_KV) {
      const CUtensorMap* mw = rank ? &M.wv : &M.wk;
#pragma unroll 1
      for (int it = half ? 0 : NFIRST; it < 16; it++) {
        const int u = gemm_unit(it);
        uint32_t bar = p.full(u), d0 = p.addr(u), d1 = p.addr(u + 1 + rank); int k0 = (it & 7) * 64, r0 = (2 * g + (it >> 3)) * 128;
        HOIST(bar); HOIST(d0); HOIST(d1); HOIST(k0); HOIST(r0);
        p.acquire(u, 3);
        if (elect()) {
          mbar_expect(bar, 3 * UNIT);
          tma3d_mc(d1, mw, 0, k0, 2 * h, bar, POL(0) && it >= 8);
          tma2d(d0, &M.c, k0, r0, bar, half ? POL(8) : POL(10));
        }
      }
    }
    if (MASK & PH_ATT) {
#pragma unroll 1
      for (int ks = 0; ks < 16; ks++) {
        const int u = gemm_unit(ks);
        uint32_t bar = p.full(u), d0 = p.addr(u), d1 = p.addr(u + 1), d2 = p.addr(u + 2) + rank * 8192; int k0 = ks * 64;
        HOIST(bar); HOIST(d0); HOIST(d1); HOIST(d2); HOIST(k0);
        p.acquire(u, 3);
        if (elect()) {
          mbar_expect(bar, 3 * UNIT);
          tma2d_mc(d2, &M.wq, h * 128 + rank * 64, k0, bar, POL(1));
          tma2d(d0, &M.x, k0, (15 - g) * 128, bar, half ? POL(9) : POL(10));
          tma2d(d1, &M.x, k0, g * 128, bar, half ? POL(9) : POL(10));
        }
      }
      TS(2, 8 * half + 0);
      mbar_wait(base + SM_RDY + 8 * (RDY_KV + half), 0);
      TS(2, 8 * half + 1);
      p.acquire(0, 4);
      if (elect()) mbar_arrive(p.full(0));
      const uint8_t* KVh = g_T + T_KV + (size_t)kv_slot<MASK>(h) * 16 * 65536;
#pragma unroll 1
      for (int i = 0; i < 34; i++) {
        const int isv = (i > 0 && !(i & 1)) || i == 33;
        const int st = i == 33 ? 16 : (isv ? (i >> 1) - 1 : (i + 1) >> 1);
        const int u = att_slot(i & 3);
        const bool own = st == 15 - (g & 6);
        uint32_t bar = p.full((isv && i < 33) ? 14 - u : u), d0 = p.addr(own ? u : u + rank), off = (st <= 15 - g ? st : 16 - st) * 65536 + isv * 32768 + (own ? 0 : rank * UNIT);
        HOIST(bar); HOIST(d0); HOIST(off);
        p.acquire(u, 2);
        if (elect()) {
          if (!isv || i == 33) mbar_expect(bar, (i == 0 || i == 33) ? 32768 : 65536);
          const bool ef = POL(6) || (POL(14) && st >= 8) || (POL(15) && half);
          if (own) bulk_g2s(d0, KVh + off, 32768, bar, ef); else bulk_g2s_mc(d0, KVh + off, UNIT, bar, ef);
        }
      }
    }
  }
  if ((MASK & PH_CONV) && !(MASK & PH_OUT)) prod_conv<MASK>(p, M, cta, CV_REG<MASK>);
  if (MASK & PH_OUT) {
    const int y0 = out_mb(cta) * 512 + rank * 8, z0 = 2 * out_nb(cta);
    int u = 6;
#pragma unroll 1
    for (int hf = 0; hf < 2; hf++) {
      TS(2, 16 + 2 * hf);
      mbar_wait(base + SM_RDY + 8 * (RDY_CTX + hf), 0);
      TS(2, 17 + 2 * hf);
#pragma unroll 1
      for (int ks = hf * 32; ks < hf * 32 + 32; ks++) {
        u = out_next(u);
        uint32_t bar = p.full(u), d0 = p.addr(u) + rank * 8192, d1 = p.addr(u + 1); int x = (ks & 1) * 256, y = y0 + (ks >> 1) * 16, k0 = ks * 64;
        HOIST(bar); HOIST(d0); HOIST(d1); HOIST(x); HOIST(y); HOIST(k0);
        p.acquire(u, 2);
        if (elect()) {
          mbar_expect(bar, 2 * UNIT);
          tma2d_mc(d0, &M.ctx, x, y, bar, POL(5));
          tma3d(d1, &M.wo, 0, k0, z0, bar, POL(2));
          if (ks == Z_AT) mbar_arrive(base + SM_RDY + 8 * RDY_Z);
        }
      }
    }
  }
}
template<int MASK> __device__ __forceinline__ void producer2(const Maps& M, const Params& P, uint32_t base, int cta, int w, int lane) {
  Prod p{base, 0xffffffffu, lane, 0};
  const int mb = out_mb(cta), nb = out_nb(cta), u = 2 * w;
  if (MASK & PH_CONV) {
    mbar_wait_slow(base + SM_SIG + 8 * (SIG_ATT + 1), 0);
    mbar_wait_slow(base + SM_RDY + 8 * RDY_U, 0);
#pragma unroll 1
    for (int i = w; i < CV_REG<MASK>; i += 2) { p.acquire_slow(u, i < 2 ? 2 : 1); load_conv(p, M, u, conv_channel<MASK>(cta, i)); }
  }
  p.acquire_slow(u, 2);
  if (elect()) asm volatile("prefetch.tensormap [%0];" :: "l"(w ? &M.z : &M.out) : "memory");
  TSA(50 + 2 * w);
  mbar_wait(base + SM_RDY + 8 * (w ? RDY_Z : RDY_G), 0);
  TSA(51 + 2 * w);
  if (elect()) {
    mbar_expect(p.full(u), 2 * UNIT + (w ? 0 : 512));
    tma2d(p.addr(u), w ? &M.z : &M.x, (w ? mb : nb) * 128, (w ? nb : mb) * 128, p.full(u), POL(5));
    tma2d(p.addr(u + 1), w ? &M.z : &M.x, (w ? mb : nb) * 128 + 64, (w ? nb : mb) * 128, p.full(u), POL(5));
    if (!w) bulk_g2s(base + SM_GATE, g_gate + mb * 128, 512, p.full(u));
  }
}

__device__ __forceinline__ constexpr uint32_t PUB(int sig, int cnt, int n) { return 0x80000000u | (sig << 24) | (n << 8) | cnt; }
__device__ __forceinline__ constexpr uint32_t GET(int rdy, int cnt, int n) { return (rdy << 24) | (n << 8) | cnt; }
template<int MASK> __device__ __forceinline__ void sync_agent(uint32_t base, int cta, int lane) {
  if ((base & 0x3FFFF) != SMEM_BASE) asm volatile("trap;");
  const int g = cta & 7, j = cta >> 3, go = min(out_mb(cta), 15 - out_mb(cta));
  const int c0 = conv_channel<MASK>(cta, 0), c1 = c0 + CV_REG<MASK> - 1, n0 = min(CV_REG<MASK>, 128 - (c0 & 127));
  constexpr bool KV = MASK & PH_KV, ATT = MASK & PH_ATT, CONV = MASK & PH_CONV, OUT = MASK & PH_OUT, ALL = MASK == PH_ALL;
  uint32_t e = 0;
  if (cta >= NREG) { if (CONV && lane * 32 < CV_EXTRA<MASK>) e = PUB(SIG_Z + lane, C_Z + lane, min(32, CV_EXTRA<MASK> - lane * 32)); }
  else switch (lane) {
    case 0:  if (KV) e = PUB(SIG_KV, C_KV + j, 1); break;
    case 1:  if (ATT) e = GET(RDY_KV, C_KV + j, 8); break;
    case 2:  if (ALL) e = PUB(SIG_WAR, C_WAR + j, 1); break;
    case 3:  if (ATT) e = PUB(SIG_CTX, C_CTX + g, 1); break;
    case 4:  if (ALL) e = GET(RDY_WAR, C_WAR + j, 8); break;
    case 5:  if (KV) e = PUB(SIG_KV + 1, C_KV + 16 + j, 1); break;
    case 6:  if (ATT) e = GET(RDY_KV + 1, C_KV + 16 + j, 8); break;
    case 7:  if (OUT) e = GET(RDY_CTX, C_CTX + go, 16); break;
    case 8:  if (CONV) e = GET(RDY_U, C_U + (c0 >> 6), 128); break;
    case 9:  if (CONV) e = GET(RDY_U, C_U + (c1 >> 6), 128); break;
    case 10: if (ATT) e = PUB(SIG_CTX + 1, C_CTX + 8 + g, 1); break;
    case 11: if (OUT) e = GET(RDY_CTX + 1, C_CTX + 8 + go, 16); break;
    case 12: if (OUT) e = GET(RDY_G, C_GATE, 256); break;
    case 13: if (CONV) e = PUB(SIG_Z, C_Z + (c0 >> 7), n0); break;
    case 14: if (CONV && n0 < CV_REG<MASK>) e = PUB(SIG_Z, C_Z + (c1 >> 7), CV_REG<MASK> - n0); break;
    case 15: if (OUT) e = GET(RDY_Z, C_Z + out_nb(cta), 128); break;
  }
  __syncwarp();
#pragma unroll 1
  for (int i = 0; i < 16; i++) {
    const uint32_t x = __shfl_sync(~0u, e, i), id = (x >> 24) & 127, n = (x >> 8) & 0xffff;
    if (x == 0) continue;
    unsigned* cnt = g_cnt + (x & 255) * CSTRIDE;
    if (x >> 31) {
      mbar_wait_slow(base + SM_SIG + 8 * id, 0);
      if (lane == 0) cnt_publish(cnt, n);
    } else {
      cnt_wait(cnt, n);
      if (id < 2) {
        const float4 kn = __ldcg((const float4*)(g_kn2 + kv_slot<MASK>(j + 16 * id) * 128) + lane);
        const uint32_t m = __reduce_max_sync(~0u, max(max(__float_as_uint(kn.x), __float_as_uint(kn.y)), max(__float_as_uint(kn.z), __float_as_uint(kn.w))));
        if (lane == 0) asm volatile("st.shared.u32 [%0], %1;" :: "r"(base + SM_KMAX + 4 * id), "r"(m) : "memory");
      }
      if (lane == 0) mbar_arrive(base + SM_RDY + 8 * id);
    }
    __syncwarp();
  }
}

__device__ __forceinline__ void aux_gate(const Params& P, int cta, int aw, int lane) {
  uint4 gw[4];
#pragma unroll
  for (int i = 0; i < 4; i++) gw[i] = __ldg((const uint4*)P.gw + i * 32 + lane);
#pragma unroll 1
  for (int row = cta * 16 + aw * 8; row < cta * 16 + aw * 8 + 8; row++) {
    float a = 0.f;
#pragma unroll
    for (int i = 0; i < 4; i++) {
      const uint4 xv = __ldg((const uint4*)(P.x + (size_t)row * 1024) + i * 32 + lane);
      uint32_t m;
      m = hmul2(xv.x, gw[i].x); a += bf_lo(m) + bf_hi(m); m = hmul2(xv.y, gw[i].y); a += bf_lo(m) + bf_hi(m);
      m = hmul2(xv.z, gw[i].z); a += bf_lo(m) + bf_hi(m); m = hmul2(xv.w, gw[i].w); a += bf_lo(m) + bf_hi(m);
    }
#pragma unroll
    for (int o = 16; o > 0; o >>= 1) a += __shfl_xor_sync(~0u, a, o);
    a = bf_lo(pack_bf16(a, 0.f));
    const float gt = bf_lo(pack_bf16(__fdividef(1.f, 1.f + ex2(-a * 1.4426950408889634f)), 0.f));
    if (lane == 0) g_gate[row] = gt;
    if (GATE_SLEEP) __nanosleep(GATE_SLEEP);
  }
  cnt_signal(g_cnt + C_GATE * CSTRIDE, lane);
  if (aw == 0) { TSA(44); }
}
template<int MASK> __device__ __forceinline__ void aux_pre(const Maps& M, const Params& P, uint32_t base, int cta, int aw, int lane) {
  const uint32_t kb = base + 12 * UNIT, bar = base + SM_PRE;
  const int r = lane >> 2, q = lane & 3;
  const int mi = lane >> 3, row0 = (lane & 6) + 1 - (lane & 1);
  const int ra = (mi * 9 + 1) * 2 + row0;
  const int rb = (mi == 0 ? 3 : mi) * 18 + row0;
  if (PRE_DELAY) mbar_wait_slow(base + SM_BAR + 8 * PRE_DELAY_BAR, 0);
#pragma unroll 1
  for (int it = 0; it < (cta < 96 ? 5 : 4); it++) {
    if (GATE_EARLY && it == PRE_EARLY && MASK == PH_ALL) { mbar_wait_slow(base + SM_SIG + 8 * SIG_ATT, 0); aux_gate(P, cta, aw, lane); }
    if (it == PRE_EARLY && MASK == PH_ALL) mbar_wait_slow(base + SM_SIG + 8 * (SIG_ATT + PRE_HALF), 0);
    const int cg = it ? it * 4 - 3 + (cta >> 5) : 0, tb = cta & 31;
    if (aw == 0 && elect()) {
      mbar_expect(bar, 2 * 9216);
      tma4d(kb, &M.k, cg * 64, 0, tb * 8 - 1, 0, bar, POL(3));
      tma4d(kb + 9216, &M.v, cg * 64, 0, tb * 8 - 1, 0, bar, POL(3));
    }
    const uint2 swl = __ldg((const uint2*)(P.shift + (cg * 64 + aw * 32 + lane) * 4));
    if (tb == 0) {
      uint8_t* e = g_u + (size_t)(cg * 64 + aw * 32 + lane) * UCH + 4096;
      *(uint4*)e = make_uint4(0, 0, 0, 0); *(uint4*)(e + UPITCH) = make_uint4(0, 0, 0, 0);
      *(uint32_t*)(e + 32) = (uint32_t)__bfloat16_as_ushort(P.D[cg * 64 + aw * 32 + lane]) * 0x10001u;
    }
    mbar_wait_slow(bar, it & 1);
#pragma unroll 1
    for (int ol = it ? 0 : cta >> 5; ol < (it ? 4 : (cta >> 5) + 1); ol++) {
      const int oc = aw * 4 + ol;
      const uint32_t s01 = __shfl_sync(~0u, swl.x, ol * 8 + r), s23 = __shfl_sync(~0u, swl.y, ol * 8 + r);
      const uint32_t w0 = __byte_perm(s01, 0, 0x1010), w1 = __byte_perm(s01, 0, 0x3232), w2 = __byte_perm(s23, 0, 0x1010), w3 = __byte_perm(s23, 0, 0x3232);
      const uint32_t pa = kb + ra * 128 + ((oc ^ (ra & 7)) << 4), pb = kb + (mi == 0 ? 9216 : 0) + rb * 128 + ((oc ^ (rb & 7)) << 4);
      uint8_t* e0 = g_u + (uint32_t)((cg * 64 + oc * 8 + r) * UCH + (2040 - tb * 64 - 8 * q) * 2);
#pragma unroll
      for (int hb = 0; hb < 2; hb++) {
        uint32_t k[7], v[5];
        ldsm4t(pa + hb * 1024, k[3], k[4], k[5], k[6]);
        ldsm4t(pa + hb * 1024 + 9216, v[1], v[2], v[3], v[4]);
        ldsm4t(pb + hb * 1024, v[0], k[0], k[1], k[2]);
        uint32_t o1 = __byte_perm(k[1], k[0], 0x5432);
#pragma unroll
        for (int m = 0; m < 5; m++) {
          const uint32_t o2 = __byte_perm(k[m + 2], k[m + 1], 0x5432);
          v[m] = hmul2(hadd2(hadd2(hadd2(hmul2(o1, w3), hmul2(k[m + 1], w2)), hmul2(o2, w1)), hmul2(k[m + 2], w0)), v[m]);
          o1 = o2;
        }
        *(uint4*)(e0 - hb * 64) = make_uint4(v[4], v[3], v[2], v[1]);
        *(uint4*)(e0 - hb * 64 + UPITCH) = make_uint4(__byte_perm(v[4], v[3], 0x5432), __byte_perm(v[3], v[2], 0x5432), __byte_perm(v[2], v[1], 0x5432), __byte_perm(v[1], v[0], 0x5432));
        if (PRE_SLEEP && it >= PRE_EARLY) __nanosleep(PRE_SLEEP);
      }
    }
    bar_sync(5, 64);
    if (aw == 0) { TSA(40 + min(it, 3)); }
    if (aw == 1 && lane == 0) asm volatile("red.release.gpu.global.add.u32 [%0], %1;" :: "l"(g_cnt + (C_U + cg) * CSTRIDE), "r"(it ? 4 : 1) : "memory");
  }
  uint32_t rel;
  asm volatile("mapa.shared::cluster.u32 %0, %1, %2;" : "=r"(rel) : "r"(base + SM_BAR + 128 + 8 * (12 + (lane & 1))), "r"((lane >> 1) & 1));
  if (lane < 4) asm volatile("mbarrier.arrive.shared::cluster.b64 _, [%0], 4;" :: "r"(rel) : "memory");
  if (!(GATE_EARLY && MASK == PH_ALL)) aux_gate(P, cta, aw, lane);
}

template<int MASK> __global__ void __cluster_dims__(2, 1, 1) __launch_bounds__(384, 1) gated_mix_kernel(const __grid_constant__ Maps M, const __grid_constant__ Params P) {
  extern __shared__ __align__(1024) uint8_t smem[];
  const uint32_t base = (uint32_t)__cvta_generic_to_shared(smem);
  const int wi = __shfl_sync(~0u, threadIdx.x >> 5, 0), wg = wi >> 2, warp = wi & 3;
  if (elect()) {
    if (wi < 8) {
      const int cnt = 1 << ((0x10334400 >> (4 * wi)) & 15);
#pragma unroll
      for (int i = 0; i < 8; i++) mbar_init(base + SM_BAR + 64 * wi + 8 * i, cnt);
      asm volatile("fence.mbarrier_init.release.cluster;" ::: "memory");
    } else if (MAP_PF) {
      asm volatile("prefetch.tensormap [%0];" :: "l"(&M.c + (wi - 8)) : "memory");
    }
  }
  const int cta = blockIdx.x;
  const bool first_loads = (MASK & PH_KV) && wi == 8 && cta < NREG;
  const CUtensorMap* mw = (cta & 1) ? &M.wv : &M.wk;
  __syncwarp();
  asm volatile("barrier.cluster.arrive.relaxed.aligned;\nbarrier.cluster.wait.aligned;" ::: "memory");
  if (first_loads && elect()) {
#pragma unroll 1
    for (int it = 0; it < NFIRST; it++) {
      const uint32_t bar = base + SM_BAR + 24 * it, d0 = base + 3 * it * UNIT;
      mbar_expect(bar, 3 * UNIT);
      tma3d_mc(d0 + (1 + (cta & 1)) * UNIT, mw, 0, it * 64, 2 * (cta >> 3), bar);
      tma2d(d0, &M.c, it * 64, (cta & 7) * 256, bar);
    }
  }
  __syncwarp();
  const int lane = threadIdx.x & 31;
#define TS_PRO()
  if (wg == 2) {
    asm volatile("setmaxnreg.dec.sync.aligned.u32 56;");
    TS_PRO();
    TS(2, 62);
    if (warp == 0) producer<MASK>(M, P, base, cta, lane);
    else if (warp == 1) sync_agent<MASK>(base, cta, lane);
    else if (cta < NREG) {
      if (MASK & PH_PRE) aux_pre<MASK>(M, P, base, cta, warp - 2, lane);
      if (MASK & PH_OUT) producer2<MASK>(M, P, base, cta, warp - 2, lane);
    }
    if (warp == 1) {
      if (MASK & PH_OUT) {
        unsigned old = 0;
        if (lane == 0) asm volatile("atom.relaxed.gpu.global.add.u32 %0, [%1], 1;" : "=r"(old) : "l"(g_cnt + C_EXIT * CSTRIDE) : "memory");
        old = __shfl_sync(~0u, old, 0);
        if (old == NCTA - 1) for (int i = lane; i < C_NUM; i += 32) g_cnt[i * CSTRIDE] = 0;
      }
      mbar_wait_slow(base + SM_SIG + 8 * SIG_DONE, 0);
      if (cta >= NREG || !(MASK & PH_OUT)) { cluster_arrive(); cluster_wait(); }
    }
  } else {
    asm volatile("setmaxnreg.inc.sync.aligned.u32 224;");
    TS_PRO();
    uint32_t rel;
    asm volatile("mapa.shared::cluster.u32 %0, %1, %2;" : "=r"(rel) : "r"(base + SM_BAR + 128 + 8 * (lane & 15)), "r"(lane >> 4));
    Cons c{base, rel, 0u, lane, warp, wg, (cta * 3 + wg) * 2048};
    if (wg == 1) bar_arrive(1, 256);
    TS(wg, 0);
    if (cta < NREG) {
      const int g = cta & 7, j = cta >> 3;
      Pend w = {};
#pragma unroll 1
      for (int half = 0; half < 2; half++) {
        const int h = j + 16 * half;
        if (MASK & PH_KV) cons_kv(c, h, kv_slot<MASK>(h), g, w, half == 1 && (MASK & PH_ATT));
        TS(wg, 1 + 4 * half);
        if (MASK & PH_ATT) {
          cons_q<(MASK & PH_KV) != 0>(c, h, w);
          TS(wg, 2 + 4 * half);
          cons_att(c, h, g, w);
          if (half == 0) c.signal(SIG_WAR);
#pragma unroll
          for (int i = 0; i < 8; i++) w.hi[i] = make_uint4(0, 0, 0, 0);
          TS(wg, 3 + 4 * half);
          if (MASK != PH_ALL) { tile_store<0, 4>(w.lo, w.dst, lane); c.signal(SIG_CTX + half); }
        } else if (MASK & PH_KV) { out_part<0>(c, w); out_part<1>(c, w); out_part<2>(c, w); out_part<3>(c, w); c.signal(SIG_KV + half); }
      }
      if (MASK & PH_OUT) cons_out<MASK>(c, M, P, cta, w);
    }
    if (cta >= NREG || !(MASK & PH_OUT)) {
      if (MASK & PH_CONV) cons_conv<MASK>(c, cta, cta < NREG ? CV_REG<MASK> : CV_EXTRA<MASK>);
      TS(wg, 9);
      c.signal(SIG_DONE);
      cluster_arrive();
    }
    TS(wg, 10);
  }
}

typedef CUresult (*EncFn)(CUtensorMap*, CUtensorMapDataType, cuuint32_t, void*, const cuuint64_t*, const cuuint64_t*, const cuuint32_t*, const cuuint32_t*,
                          CUtensorMapInterleave, CUtensorMapSwizzle, CUtensorMapL2promotion, CUtensorMapFloatOOBfill);
static void enc(EncFn f, CUtensorMap* m, const void* ptr, int rank, const cuuint64_t* dims, const cuuint64_t* strides, const cuuint32_t* box, CUtensorMapSwizzle sw,
                CUtensorMapDataType dt = CU_TENSOR_MAP_DATA_TYPE_BFLOAT16) {
  const cuuint32_t es[4] = {1, 1, 1, 1};
  f(m, dt, rank, (void*)ptr, dims, strides, box, es, CU_TENSOR_MAP_INTERLEAVE_NONE, sw, CU_TENSOR_MAP_L2_PROMOTION_L2_256B, CU_TENSOR_MAP_FLOAT_OOB_FILL_NONE);
}
static void enc2(EncFn f, CUtensorMap* m, const void* ptr, int cols, int rows, int brows) {
  const cuuint64_t d[2] = {(cuuint64_t)cols, (cuuint64_t)rows}, s[1] = {(cuuint64_t)cols * 2}; const cuuint32_t b[2] = {64, (cuuint32_t)brows};
  enc(f, m, ptr, 2, d, s, b, CU_TENSOR_MAP_SWIZZLE_128B);
}
static void encw(EncFn f, CUtensorMap* m, const void* ptr, int cols, int rows) {
  const cuuint64_t d[3] = {64, (cuuint64_t)rows, (cuuint64_t)cols / 64}, s[2] = {(cuuint64_t)cols * 2, 128}; const cuuint32_t b[3] = {64, 64, 2};
  enc(f, m, ptr, 3, d, s, b, CU_TENSOR_MAP_SWIZZLE_128B);
}
extern "C" void kernel_launch(void* const* d_in, const int* in_sizes, int n_in, void* d_out, int out_size) {
  static EncFn fn = nullptr;
  static int ncl = 0;
  static void* zptr = nullptr;
  static void* tptr = nullptr;
  if (!fn) {
    void* p = nullptr; cudaDriverEntryPointQueryResult qr;
    cudaGetDriverEntryPoint("cuTensorMapEncodeTiled", &p, cudaEnableDefault, &qr);
    fn = (EncFn)p;
    cudaFuncSetAttribute(gated_mix_kernel<PH_ALL>, cudaFuncAttributeMaxDynamicSharedMemorySize, SMEM_BYTES);
    cudaFuncSetAttribute(gated_mix_kernel<PH_PRE | PH_KV>, cudaFuncAttributeMaxDynamicSharedMemorySize, SMEM_BYTES);
    cudaFuncSetAttribute(gated_mix_kernel<PH_ATT | PH_CONV>, cudaFuncAttributeMaxDynamicSharedMemorySize, SMEM_BYTES);
    cudaFuncSetAttribute(gated_mix_kernel<PH_OUT>, cudaFuncAttributeMaxDynamicSharedMemorySize, SMEM_BYTES);
    cudaLaunchConfig_t cfg = {}; cfg.gridDim = NCTA; cfg.blockDim = 384; cfg.dynamicSmemBytes = SMEM_BYTES;
    cudaLaunchAttribute at; at.id = cudaLaunchAttributeClusterDimension; at.val.clusterDim.x = 2; at.val.clusterDim.y = 1; at.val.clusterDim.z = 1;
    cfg.attrs = &at; cfg.numAttrs = 1;
    cudaOccupancyMaxActiveClusters(&ncl, gated_mix_kernel<PH_ALL>, &cfg);
    cudaGetSymbolAddress(&zptr, g_z);
    cudaGetSymbolAddress(&tptr, g_T);
  }
  Maps M;
  enc2(fn, &M.x, d_in[0], 1024, 2048, 128);
  enc2(fn, &M.c, d_in[7], 512, 2048, 128);
  enc2(fn, &M.wq, d_in[8], 4096, 1024, 64);
  encw(fn, &M.wk, d_in[9], 4096, 512);
  encw(fn, &M.wv, d_in[10], 4096, 512);
  encw(fn, &M.wo, d_in[11], 1024, 4096);
  { const cuuint64_t d[3] = {64, 32, 1024}, s[2] = {128, 4096}; const cuuint32_t b[3] = {64, 40, 1}; enc(fn, &M.h, d_in[4], 3, d, s, b, CU_TENSOR_MAP_SWIZZLE_NONE); }
  enc2(fn, &M.z, zptr, 2048, 1024, 128);
  enc2(fn, &M.out, d_out, 1024, 2048, 16);
  { const cuuint64_t d[2] = {512, 512 * 16}, s[1] = {2048}; const cuuint32_t b[2] = {256, 8};
    enc(fn, &M.ctx, tptr, 2, d, s, b, CU_TENSOR_MAP_SWIZZLE_NONE, CU_TENSOR_MAP_DATA_TYPE_UINT32); }
  { const cuuint64_t d[4] = {1024, 2, 256, 4}, s[3] = {2048, 16384, 4096}; const cuuint32_t b[4] = {64, 2, 9, 4};
    enc(fn, &M.k, d_in[1], 4, d, s, b, CU_TENSOR_MAP_SWIZZLE_128B); enc(fn, &M.v, d_in[2], 4, d, s, b, CU_TENSOR_MAP_SWIZZLE_128B); }
  Params P{(const __nv_bfloat16*)d_in[0], (const __nv_bfloat16*)d_in[3],
           (const __nv_bfloat16*)d_in[5], (const __nv_bfloat16*)d_in[12], (__nv_bfloat16*)d_out};
  bool split = 2 * ncl < NCTA;
  if (!split) {
    gated_mix_kernel<PH_ALL><<<NCTA, 384, SMEM_BYTES>>>(M, P);
  } else {
    gated_mix_kernel<PH_PRE | PH_KV><<<NCTA, 384, SMEM_BYTES>>>(M, P);
    gated_mix_kernel<PH_ATT | PH_CONV><<<NCTA, 384, SMEM_BYTES>>>(M, P);
    gated_mix_kernel<PH_OUT><<<NCTA, 384, SMEM_BYTES>>>(M, P);
  }
}
```

```cpp
#include <cuda_runtime.h>
#include <cuda.h>
#include <cuda_bf16.h>
#include <stdint.h>

template<int TB> __device__ __forceinline__ void wgmma_ss_n256(float (&d)[128], uint64_t da, uint64_t db, int scale_d) {
  asm volatile("{\n.reg .pred p;\nsetp.ne.b32 p, %130, 0;\n"
    "wgmma.mma_async.sync.aligned.m64n256k16.f32.bf16.bf16 {%0, %1, %2, %3, %4, %5, %6, %7, %8, %9, %10, %11, %12, %13, %14, %15, %16, %17, %18, %19, %20, %21, %22, %23, %24, %25, %26, %27, %28, %29, %30, %31, %32, %33, %34, %35, %36, %37, %38, %39, %40, %41, %42, %43, %44, %45, %46, %47, %48, %49, %50, %51, %52, %53, %54, %55, %56, %57, %58, %59, %60, %61, %62, %63, %64, %65, %66, %67, %68, %69, %70, %71, %72, %73, %74, %75, %76, %77, %78, %79, %80, %81, %82, %83, %84, %85, %86, %87, %88, %89, %90, %91, %92, %93, %94, %95, %96, %97, %98, %99, %100, %101, %102, %103, %104, %105, %106, %107, %108, %109, %110, %111, %112, %113, %114, %115, %116, %117, %118, %119, %120, %121, %122, %123, %124, %125, %126, %127}, %128, %129, p, 1, 1, 0, %131;\n}\n"
    : "+f"(d[0]), "+f"(d[1]), "+f"(d[2]), "+f"(d[3]), "+f"(d[4]), "+f"(d[5]), "+f"(d[6]), "+f"(d[7]), "+f"(d[8]), "+f"(d[9]), "+f"(d[10]), "+f"(d[11]), "+f"(d[12]), "+f"(d[13]), "+f"(d[14]), "+f"(d[15]), "+f"(d[16]), "+f"(d[17]), "+f"(d[18]), "+f"(d[19]), "+f"(d[20]), "+f"(d[21]), "+f"(d[22]), "+f"(d[23]), "+f"(d[24]), "+f"(d[25]), "+f"(d[26]), "+f"(d[27]), "+f"(d[28]), "+f"(d[29]), "+f"(d[30]), "+f"(d[31]), "+f"(d[32]), "+f"(d[33]), "+f"(d[34]), "+f"(d[35]), "+f"(d[36]), "+f"(d[37]), "+f"(d[38]), "+f"(d[39]), "+f"(d[40]), "+f"(d[41]), "+f"(d[42]), "+f"(d[43]), "+f"(d[44]), "+f"(d[45]), "+f"(d[46]), "+f"(d[47]), "+f"(d[48]), "+f"(d[49]), "+f"(d[50]), "+f"(d[51]), "+f"(d[52]), "+f"(d[53]), "+f"(d[54]), "+f"(d[55]), "+f"(d[56]), "+f"(d[57]), "+f"(d[58]), "+f"(d[59]), "+f"(d[60]), "+f"(d[61]), "+f"(d[62]), "+f"(d[63]), "+f"(d[64]), "+f"(d[65]), "+f"(d[66]), "+f"(d[67]), "+f"(d[68]), "+f"(d[69]), "+f"(d[70]), "+f"(d[71]), "+f"(d[72]), "+f"(d[73]), "+f"(d[74]), "+f"(d[75]), "+f"(d[76]), "+f"(d[77]), "+f"(d[78]), "+f"(d[79]), "+f"(d[80]), "+f"(d[81]), "+f"(d[82]), "+f"(d[83]), "+f"(d[84]), "+f"(d[85]), "+f"(d[86]), "+f"(d[87]), "+f"(d[88]), "+f"(d[89]), "+f"(d[90]), "+f"(d[91]), "+f"(d[92]), "+f"(d[93]), "+f"(d[94]), "+f"(d[95]), "+f"(d[96]), "+f"(d[97]), "+f"(d[98]), "+f"(d[99]), "+f"(d[100]), "+f"(d[101]), "+f"(d[102]), "+f"(d[103]), "+f"(d[104]), "+f"(d[105]), "+f"(d[106]), "+f"(d[107]), "+f"(d[108]), "+f"(d[109]), "+f"(d[110]), "+f"(d[111]), "+f"(d[112]), "+f"(d[113]), "+f"(d[114]), "+f"(d[115]), "+f"(d[116]), "+f"(d[117]), "+f"(d[118]), "+f"(d[119]), "+f"(d[120]), "+f"(d[121]), "+f"(d[122]), "+f"(d[123]), "+f"(d[124]), "+f"(d[125]), "+f"(d[126]), "+f"(d[127])
    : "l"(da), "l"(db), "r"(scale_d), "n"(TB));
}
template<int TB> __device__ __forceinline__ void wgmma_ss_n128(float (&d)[64], uint64_t da, uint64_t db, int scale_d) {
  asm volatile("{\n.reg .pred p;\nsetp.ne.b32 p, %66, 0;\n"
    "wgmma.mma_async.sync.aligned.m64n128k16.f32.bf16.bf16 {%0, %1, %2, %3, %4, %5, %6, %7, %8, %9, %10, %11, %12, %13, %14, %15, %16, %17, %18, %19, %20, %21, %22, %23, %24, %25, %26, %27, %28, %29, %30, %31, %32, %33, %34, %35, %36, %37, %38, %39, %40, %41, %42, %43, %44, %45, %46, %47, %48, %49, %50, %51, %52, %53, %54, %55, %56, %57, %58, %59, %60, %61, %62, %63}, %64, %65, p, 1, 1, 0, %67;\n}\n"
    : "+f"(d[0]), "+f"(d[1]), "+f"(d[2]), "+f"(d[3]), "+f"(d[4]), "+f"(d[5]), "+f"(d[6]), "+f"(d[7]), "+f"(d[8]), "+f"(d[9]), "+f"(d[10]), "+f"(d[11]), "+f"(d[12]), "+f"(d[13]), "+f"(d[14]), "+f"(d[15]), "+f"(d[16]), "+f"(d[17]), "+f"(d[18]), "+f"(d[19]), "+f"(d[20]), "+f"(d[21]), "+f"(d[22]), "+f"(d[23]), "+f"(d[24]), "+f"(d[25]), "+f"(d[26]), "+f"(d[27]), "+f"(d[28]), "+f"(d[29]), "+f"(d[30]), "+f"(d[31]), "+f"(d[32]), "+f"(d[33]), "+f"(d[34]), "+f"(d[35]), "+f"(d[36]), "+f"(d[37]), "+f"(d[38]), "+f"(d[39]), "+f"(d[40]), "+f"(d[41]), "+f"(d[42]), "+f"(d[43]), "+f"(d[44]), "+f"(d[45]), "+f"(d[46]), "+f"(d[47]), "+f"(d[48]), "+f"(d[49]), "+f"(d[50]), "+f"(d[51]), "+f"(d[52]), "+f"(d[53]), "+f"(d[54]), "+f"(d[55]), "+f"(d[56]), "+f"(d[57]), "+f"(d[58]), "+f"(d[59]), "+f"(d[60]), "+f"(d[61]), "+f"(d[62]), "+f"(d[63])
    : "l"(da), "l"(db), "r"(scale_d), "n"(TB));
}
template<int TB> __device__ __forceinline__ void wgmma_rs_n32(float (&d)[16], uint32_t a0, uint32_t a1, uint32_t a2, uint32_t a3, uint64_t db, int scale_d) {
  asm volatile("{\n.reg .pred p;\nsetp.ne.b32 p, %21, 0;\n"
    "wgmma.mma_async.sync.aligned.m64n32k16.f32.bf16.bf16 {%0, %1, %2, %3, %4, %5, %6, %7, %8, %9, %10, %11, %12, %13, %14, %15}, {%16, %17, %18, %19}, %20, p, 1, 1, %22;\n}\n"
    : "+f"(d[0]), "+f"(d[1]), "+f"(d[2]), "+f"(d[3]), "+f"(d[4]), "+f"(d[5]), "+f"(d[6]), "+f"(d[7]), "+f"(d[8]), "+f"(d[9]), "+f"(d[10]), "+f"(d[11]), "+f"(d[12]), "+f"(d[13]), "+f"(d[14]), "+f"(d[15])
    : "r"(a0), "r"(a1), "r"(a2), "r"(a3), "l"(db), "r"(scale_d), "n"(TB));
}
__device__ __forceinline__ void wgmma_pv_sel(float (&d)[64], const uint32_t (&p)[32], uint64_t db, int full, int acc) {
  asm volatile("{\n.reg .pred q, s;\n.reg .b64 t;\nsetp.ne.b32 s, %98, 0;\nsetp.eq.b32 q, %97, 0;\n@q bra.uni LH;\n"
    "wgmma.fence.sync.aligned;\n"
    "add.s64 t, %96, 0;\nwgmma.mma_async.sync.aligned.m64n128k16.f32.bf16.bf16 {%0, %1, %2, %3, %4, %5, %6, %7, %8, %9, %10, %11, %12, %13, %14, %15, %16, %17, %18, %19, %20, %21, %22, %23, %24, %25, %26, %27, %28, %29, %30, %31, %32, %33, %34, %35, %36, %37, %38, %39, %40, %41, %42, %43, %44, %45, %46, %47, %48, %49, %50, %51, %52, %53, %54, %55, %56, %57, %58, %59, %60, %61, %62, %63}, {%64, %65, %66, %67}, t, s, 1, 1, 1;\n"
    "add.s64 t, %96, 256;\nwgmma.mma_async.sync.aligned.m64n128k16.f32.bf16.bf16 {%0, %1, %2, %3, %4, %5, %6, %7, %8, %9, %10, %11, %12, %13, %14, %15, %16, %17, %18, %19, %20, %21, %22, %23, %24, %25, %26, %27, %28, %29, %30, %31, %32, %33, %34, %35, %36, %37, %38, %39, %40, %41, %42, %43, %44, %45, %46, %47, %48, %49, %50, %51, %52, %53, %54, %55, %56, %57, %58, %59, %60, %61, %62, %63}, {%68, %69, %70, %71}, t, 1, 1, 1, 1;\n"
    "add.s64 t, %96, 512;\nwgmma.mma_async.sync.aligned.m64n128k16.f32.bf16.bf16 {%0, %1, %2, %3, %4, %5, %6, %7, %8, %9, %10, %11, %12, %13, %14, %15, %16, %17, %18, %19, %20, %21, %22, %23, %24, %25, %26, %27, %28, %29, %30, %31, %32, %33, %34, %35, %36, %37, %38, %39, %40, %41, %42, %43, %44, %45, %46, %47, %48, %49, %50, %51, %52, %53, %54, %55, %56, %57, %58, %59, %60, %61, %62, %63}, {%72, %73, %74, %75}, t, 1, 1, 1, 1;\n"
    "add.s64 t, %96, 768;\nwgmma.mma_async.sync.aligned.m64n128k16.f32.bf16.bf16 {%0, %1, %2, %3, %4, %5, %6, %7, %8, %9, %10, %11, %12, %13, %14, %15, %16, %17, %18, %19, %20, %21, %22, %23, %24, %25, %26, %27, %28, %29, %30, %31, %32, %33, %34, %35, %36, %37, %38, %39, %40, %41, %42, %43, %44, %45, %46, %47, %48, %49, %50, %51, %52, %53, %54, %55, %56, %57, %58, %59, %60, %61, %62, %63}, {%76, %77, %78, %79}, t, 1, 1, 1, 1;\n"
    "add.s64 t, %96, 1024;\nwgmma.mma_async.sync.aligned.m64n128k16.f32.bf16.bf16 {%0, %1, %2, %3, %4, %5, %6, %7, %8, %9, %10, %11, %12, %13, %14, %15, %16, %17, %18, %19, %20, %21, %22, %23, %24, %25, %26, %27, %28, %29, %30, %31, %32, %33, %34, %35, %36, %37, %38, %39, %40, %41, %42, %43, %44, %45, %46, %47, %48, %49, %50, %51, %52, %53, %54, %55, %56, %57, %58, %59, %60, %61, %62, %63}, {%80, %81, %82, %83}, t, 1, 1, 1, 1;\n"
    "add.s64 t, %96, 1280;\nwgmma.mma_async.sync.aligned.m64n128k16.f32.bf16.bf16 {%0, %1, %2, %3, %4, %5, %6, %7, %8, %9, %10, %11, %12, %13, %14, %15, %16, %17, %18, %19, %20, %21, %22, %23, %24, %25, %26, %27, %28, %29, %30, %31, %32, %33, %34, %35, %36, %37, %38, %39, %40, %41, %42, %43, %44, %45, %46, %47, %48, %49, %50, %51, %52, %53, %54, %55, %56, %57, %58, %59, %60, %61, %62, %63}, {%84, %85, %86, %87}, t, 1, 1, 1, 1;\n"
    "add.s64 t, %96, 1536;\nwgmma.mma_async.sync.aligned.m64n128k16.f32.bf16.bf16 {%0, %1, %2, %3, %4, %5, %6, %7, %8, %9, %10, %11, %12, %13, %14, %15, %16, %17, %18, %19, %20, %21, %22, %23, %24, %25, %26, %27, %28, %29, %30, %31, %32, %33, %34, %35, %36, %37, %38, %39, %40, %41, %42, %43, %44, %45, %46, %47, %48, %49, %50, %51, %52, %53, %54, %55, %56, %57, %58, %59, %60, %61, %62, %63}, {%88, %89, %90, %91}, t, 1, 1, 1, 1;\n"
    "add.s64 t, %96, 1792;\nwgmma.mma_async.sync.aligned.m64n128k16.f32.bf16.bf16 {%0, %1, %2, %3, %4, %5, %6, %7, %8, %9, %10, %11, %12, %13, %14, %15, %16, %17, %18, %19, %20, %21, %22, %23, %24, %25, %26, %27, %28, %29, %30, %31, %32, %33, %34, %35, %36, %37, %38, %39, %40, %41, %42, %43, %44, %45, %46, %47, %48, %49, %50, %51, %52, %53, %54, %55, %56, %57, %58, %59, %60, %61, %62, %63}, {%92, %93, %94, %95}, t, 1, 1, 1, 1;\n"
    "wgmma.commit_group.sync.aligned;\n"
    "bra.uni LE;\nLH:\n"
    "wgmma.fence.sync.aligned;\n"
    "add.s64 t, %96, 0;\nwgmma.mma_async.sync.aligned.m64n128k16.f32.bf16.bf16 {%0, %1, %2, %3, %4, %5, %6, %7, %8, %9, %10, %11, %12, %13, %14, %15, %16, %17, %18, %19, %20, %21, %22, %23, %24, %25, %26, %27, %28, %29, %30, %31, %32, %33, %34, %35, %36, %37, %38, %39, %40, %41, %42, %43, %44, %45, %46, %47, %48, %49, %50, %51, %52, %53, %54, %55, %56, %57, %58, %59, %60, %61, %62, %63}, {%80, %81, %82, %83}, t, s, 1, 1, 1;\n"
    "add.s64 t, %96, 256;\nwgmma.mma_async.sync.aligned.m64n128k16.f32.bf16.bf16 {%0, %1, %2, %3, %4, %5, %6, %7, %8, %9, %10, %11, %12, %13, %14, %15, %16, %17, %18, %19, %20, %21, %22, %23, %24, %25, %26, %27, %28, %29, %30, %31, %32, %33, %34, %35, %36, %37, %38, %39, %40, %41, %42, %43, %44, %45, %46, %47, %48, %49, %50, %51, %52, %53, %54, %55, %56, %57, %58, %59, %60, %61, %62, %63}, {%84, %85, %86, %87}, t, 1, 1, 1, 1;\n"
    "add.s64 t, %96, 512;\nwgmma.mma_async.sync.aligned.m64n128k16.f32.bf16.bf16 {%0, %1, %2, %3, %4, %5, %6, %7, %8, %9, %10, %11, %12, %13, %14, %15, %16, %17, %18, %19, %20, %21, %22, %23, %24, %25, %26, %27, %28, %29, %30, %31, %32, %33, %34, %35, %36, %37, %38, %39, %40, %41, %42, %43, %44, %45, %46, %47, %48, %49, %50, %51, %52, %53, %54, %55, %56, %57, %58, %59, %60, %61, %62, %63}, {%88, %89, %90, %91}, t, 1, 1, 1, 1;\n"
    "add.s64 t, %96, 768;\nwgmma.mma_async.sync.aligned.m64n128k16.f32.bf16.bf16 {%0, %1, %2, %3, %4, %5, %6, %7, %8, %9, %10, %11, %12, %13, %14, %15, %16, %17, %18, %19, %20, %21, %22, %23, %24, %25, %26, %27, %28, %29, %30, %31, %32, %33, %34, %35, %36, %37, %38, %39, %40, %41, %42, %43, %44, %45, %46, %47, %48, %49, %50, %51, %52, %53, %54, %55, %56, %57, %58, %59, %60, %61, %62, %63}, {%92, %93, %94, %95}, t, 1, 1, 1, 1;\n"
    "wgmma.commit_group.sync.aligned;\n"
    "LE:\n}\n"
    : "+f"(d[0]), "+f"(d[1]), "+f"(d[2]), "+f"(d[3]), "+f"(d[4]), "+f"(d[5]), "+f"(d[6]), "+f"(d[7]), "+f"(d[8]), "+f"(d[9]), "+f"(d[10]), "+f"(d[11]), "+f"(d[12]), "+f"(d[13]), "+f"(d[14]), "+f"(d[15]), "+f"(d[16]), "+f"(d[17]), "+f"(d[18]), "+f"(d[19]), "+f"(d[20]), "+f"(d[21]), "+f"(d[22]), "+f"(d[23]), "+f"(d[24]), "+f"(d[25]), "+f"(d[26]), "+f"(d[27]), "+f"(d[28]), "+f"(d[29]), "+f"(d[30]), "+f"(d[31]), "+f"(d[32]), "+f"(d[33]), "+f"(d[34]), "+f"(d[35]), "+f"(d[36]), "+f"(d[37]), "+f"(d[38]), "+f"(d[39]), "+f"(d[40]), "+f"(d[41]), "+f"(d[42]), "+f"(d[43]), "+f"(d[44]), "+f"(d[45]), "+f"(d[46]), "+f"(d[47]), "+f"(d[48]), "+f"(d[49]), "+f"(d[50]), "+f"(d[51]), "+f"(d[52]), "+f"(d[53]), "+f"(d[54]), "+f"(d[55]), "+f"(d[56]), "+f"(d[57]), "+f"(d[58]), "+f"(d[59]), "+f"(d[60]), "+f"(d[61]), "+f"(d[62]), "+f"(d[63])
    : "r"(p[0]), "r"(p[1]), "r"(p[2]), "r"(p[3]), "r"(p[4]), "r"(p[5]), "r"(p[6]), "r"(p[7]), "r"(p[8]), "r"(p[9]), "r"(p[10]), "r"(p[11]), "r"(p[12]), "r"(p[13]), "r"(p[14]), "r"(p[15]), "r"(p[16]), "r"(p[17]), "r"(p[18]), "r"(p[19]), "r"(p[20]), "r"(p[21]), "r"(p[22]), "r"(p[23]), "r"(p[24]), "r"(p[25]), "r"(p[26]), "r"(p[27]), "r"(p[28]), "r"(p[29]), "r"(p[30]), "r"(p[31]), "l"(db), "r"(full), "r"(acc) : "memory");
}

constexpr int NCTA = 132, NREG = 128;
constexpr int UNIT = 16384, NUNIT = 14;
constexpr uint32_t SMEM_BASE = 1024;
constexpr int SM_BAR = NUNIT * UNIT;
constexpr int SM_GATE = SM_BAR + 1024;
constexpr int SMEM_BYTES = SM_BAR + 1536;
constexpr int UPITCH = 4160, UCH = 2 * UPITCH;
constexpr float QSCALE = 0.08838834764831845f * 1.4426950408889634f;
constexpr float BOUND2 = 48.f * 48.f / 1.15f;
#define CONV_REG 5
constexpr int C_KV = 0;
constexpr int C_CTX = 32;
constexpr int C_U = 48;
constexpr int C_Z = 80;
constexpr int C_GATE = 88;
constexpr int C_EXIT = 89;
[[maybe_unused]] constexpr int C_GO = 90;
#define PRE_EARLY 2
#define PRE_HALF 1
#define ATT_SPLIT 6
#define NFIRST 2
#define PRE_DELAY 0
#define MAP_PF 1
#define FINAL_ST 1
#define Z_AT 60
#define PRE_DELAY_BAR 9
#define PRE_FMA 0
#define PRE_SLEEP 300
#define GATE_SLEEP 1000
#define GATE_EARLY 1
#define OC_S0 2
#define OC_S1 2
#define EF 127
#define POL(bit) (((EF >> (bit)) & 1) != 0)
constexpr int C_WAR = 96;
constexpr int C_NUM = 112;
constexpr int CSTRIDE = 32;
constexpr int SM_KMAX = SM_BAR + 640, SM_DUMMY = SM_BAR + 648, SM_PRE = SM_BAR + 112, SM_SIG = SM_BAR + 256, SM_RDY = SM_BAR + 384;
enum { SIG_KV = 0, SIG_CTX = 2, SIG_Z = 4, SIG_DONE = 8, SIG_WAR = 9, SIG_ATT = 10 };
enum { RDY_KV = 0, RDY_CTX = 2, RDY_WAR = 4, RDY_G = 5, RDY_U = 8, RDY_Z = 9 };
enum { PH_PRE = 1, PH_KV = 2, PH_ATT = 4, PH_CONV = 8, PH_OUT = 16, PH_ALL = 31 };

constexpr uint32_t T_CTX = 0, T_KV = 16 * 32 * 32768, T_BYTES = T_KV + 32 * 16 * 65536;
__device__ __align__(1024) uint8_t g_T[T_BYTES];
__device__ __align__(1024) uint8_t g_u[1024 * UCH];
__device__ __align__(1024) __nv_bfloat16 g_z[1024 * 2048];
__device__ __align__(1024) float g_gate[2048];
__device__ __align__(1024) float g_kn2[32 * 128];
__device__ __align__(1024) unsigned g_cnt[C_NUM * CSTRIDE];

struct __align__(64) Maps { CUtensorMap c, wk, wv, x, wq, wo, h, z, out, ctx, k, v; };
struct Params {
  const __nv_bfloat16 *x, *shift, *D, *gw;
  __nv_bfloat16* out;
};

__device__ __forceinline__ void wg_fence() { asm volatile("wgmma.fence.sync.aligned;" ::: "memory"); }
__device__ __forceinline__ void wg_commit() { asm volatile("wgmma.commit_group.sync.aligned;" ::: "memory"); }
template<int N> __device__ __forceinline__ void wg_wait() { asm volatile("wgmma.wait_group.sync.aligned %0;" :: "n"(N) : "memory"); }
__device__ __forceinline__ uint64_t odesc(uint32_t addr, uint32_t lbo, uint32_t sbo, uint32_t swz) {
  uint64_t d = (uint64_t)(addr >> 4) + (((uint64_t)(lbo >> 4) << 16) | ((uint64_t)(sbo >> 4) << 32) | ((uint64_t)swz << 62));
  asm volatile("" : "+l"(d));
  return d;
}
__device__ __forceinline__ void mbar_init(uint32_t bar, int cnt) { asm volatile("mbarrier.init.shared::cta.b64 [%0], %1;" :: "r"(bar), "r"(cnt)); }
__device__ __forceinline__ void mbar_expect(uint32_t bar, uint32_t bytes) { asm volatile("mbarrier.arrive.expect_tx.shared::cta.b64 _, [%0], %1;" :: "r"(bar), "r"(bytes) : "memory"); }
__device__ __forceinline__ void mbar_arrive(uint32_t bar) { asm volatile("mbarrier.arrive.shared::cta.b64 _, [%0];" :: "r"(bar) : "memory"); }
__device__ __forceinline__ void mbar_arrive_n(uint32_t bar, int n) { asm volatile("mbarrier.arrive.shared::cta.b64 _, [%0], %1;" :: "r"(bar), "r"(n) : "memory"); }
__device__ __forceinline__ void mbar_wait(uint32_t bar, uint32_t parity) {
  asm volatile("{\n.reg .pred p;\nLW:\nmbarrier.try_wait.parity.shared::cta.b64 p, [%0], %1;\n@!p bra LW;\n}\n" :: "r"(bar), "r"(parity) : "memory");
}
__device__ __forceinline__ void mbar_wait_slow(uint32_t bar, uint32_t parity) {
  asm volatile("{\n.reg .pred p;\n.reg .u32 n;\nmov.u32 n, 0;\n"
    "LW:\nmbarrier.test_wait.parity.shared::cta.b64 p, [%0], %1;\n@p bra LD;\n"
    "nanosleep.u32 128;\nadd.u32 n, n, 1;\nsetp.lt.u32 p, n, 4194304;\n@p bra LW;\ntrap;\nLD:\n}\n" :: "r"(bar), "r"(parity) : "memory");
}
__device__ __forceinline__ void mbar_wait_all(uint32_t bar, uint32_t parity) {
  asm volatile("{\n.reg .pred p, q;\nLW:\nmbarrier.try_wait.parity.shared::cta.b64 p, [%0], %1;\nvote.sync.all.pred q, p, 0xffffffff;\n@!q bra.uni LW;\n}\n" :: "r"(bar), "r"(parity) : "memory");
}
__device__ __forceinline__ void cnt_wait(const unsigned* p, unsigned target) {
  asm volatile("{\n.reg .pred p;\n.reg .u32 n, v;\nmov.u32 n, 0;\n"
    "LW:\nld.relaxed.gpu.global.u32 v, [%0];\nsetp.ge.u32 p, v, %1;\n@p bra LD;\n"
    "nanosleep.u32 64;\nadd.u32 n, n, 1;\nsetp.lt.u32 p, n, 4194304;\n@p bra LW;\ntrap;\nLD:\nfence.acq_rel.gpu;\nfence.proxy.async;\n}\n" :: "l"(p), "r"(target) : "memory");
}
__device__ __forceinline__ void cnt_signal(unsigned* p, int lane) {
  __syncwarp();
  if (lane == 0) asm volatile("red.release.gpu.global.add.u32 [%0], 1;" :: "l"(p) : "memory");
}
__device__ __forceinline__ void cnt_publish(unsigned* p, unsigned n) {
  asm volatile("fence.acq_rel.gpu;\nred.relaxed.gpu.global.add.u32 [%0], %1;" :: "l"(p), "r"(n) : "memory");
}
__device__ __forceinline__ uint64_t pol_first() { uint64_t p; asm("createpolicy.fractional.L2::evict_first.b64 %0, 1.0;" : "=l"(p)); return p; }
__device__ __forceinline__ void bulk_g2s(uint32_t dst, const void* src, uint32_t bytes, uint32_t bar, bool stream = false) {
  if (stream) asm volatile("cp.async.bulk.shared::cluster.global.mbarrier::complete_tx::bytes.L2::cache_hint [%0], [%1], %2, [%3], %4;" :: "r"(dst), "l"(src), "r"(bytes), "r"(bar), "l"(pol_first()) : "memory");
  else asm volatile("cp.async.bulk.shared::cluster.global.mbarrier::complete_tx::bytes [%0], [%1], %2, [%3];" :: "r"(dst), "l"(src), "r"(bytes), "r"(bar) : "memory");
}
__device__ __forceinline__ void tma2d(uint32_t dst, const CUtensorMap* m, int x, int y, uint32_t bar, bool stream = false) {
  if (stream) asm volatile("cp.async.bulk.tensor.2d.shared::cluster.global.mbarrier::complete_tx::bytes.L2::cache_hint [%0], [%1, {%3, %4}], [%2], %5;" :: "r"(dst), "l"(m), "r"(bar), "r"(x), "r"(y), "l"(pol_first()) : "memory");
  else asm volatile("cp.async.bulk.tensor.2d.shared::cluster.global.mbarrier::complete_tx::bytes [%0], [%1, {%3, %4}], [%2];" :: "r"(dst), "l"(m), "r"(bar), "r"(x), "r"(y) : "memory");
}
__device__ __forceinline__ void tma3d(uint32_t dst, const CUtensorMap* m, int x, int y, int z, uint32_t bar, bool stream = false) {
  if (stream) asm volatile("cp.async.bulk.tensor.3d.shared::cluster.global.mbarrier::complete_tx::bytes.L2::cache_hint [%0], [%1, {%3, %4, %5}], [%2], %6;" :: "r"(dst), "l"(m), "r"(bar), "r"(x), "r"(y), "r"(z), "l"(pol_first()) : "memory");
  else asm volatile("cp.async.bulk.tensor.3d.shared::cluster.global.mbarrier::complete_tx::bytes [%0], [%1, {%3, %4, %5}], [%2];" :: "r"(dst), "l"(m), "r"(bar), "r"(x), "r"(y), "r"(z) : "memory");
}
__device__ __forceinline__ void tma4d(uint32_t dst, const CUtensorMap* m, int x, int y, int z, int w, uint32_t bar, bool stream = false) {
  if (stream) asm volatile("cp.async.bulk.tensor.4d.shared::cluster.global.mbarrier::complete_tx::bytes.L2::cache_hint [%0], [%1, {%3, %4, %5, %6}], [%2], %7;" :: "r"(dst), "l"(m), "r"(bar), "r"(x), "r"(y), "r"(z), "r"(w), "l"(pol_first()) : "memory");
  else asm volatile("cp.async.bulk.tensor.4d.shared::cluster.global.mbarrier::complete_tx::bytes [%0], [%1, {%3, %4, %5, %6}], [%2];" :: "r"(dst), "l"(m), "r"(bar), "r"(x), "r"(y), "r"(z), "r"(w) : "memory");
}
__device__ __forceinline__ void bulk_g2s_mc(uint32_t dst, const void* src, uint32_t bytes, uint32_t bar, bool stream = false) {
  if (stream) asm volatile("cp.async.bulk.shared::cluster.global.mbarrier::complete_tx::bytes.multicast::cluster.L2::cache_hint [%0], [%1], %2, [%3], %4, %5;" :: "r"(dst), "l"(src), "r"(bytes), "r"(bar), "h"((uint16_t)3), "l"(pol_first()) : "memory");
  else asm volatile("cp.async.bulk.shared::cluster.global.mbarrier::complete_tx::bytes.multicast::cluster [%0], [%1], %2, [%3], %4;" :: "r"(dst), "l"(src), "r"(bytes), "r"(bar), "h"((uint16_t)3) : "memory");
}
__device__ __forceinline__ void tma2d_mc(uint32_t dst, const CUtensorMap* m, int x, int y, uint32_t bar, bool stream = false) {
  if (stream) asm volatile("cp.async.bulk.tensor.2d.shared::cluster.global.mbarrier::complete_tx::bytes.multicast::cluster.L2::cache_hint [%0], [%1, {%3, %4}], [%2], %5, %6;" :: "r"(dst), "l"(m), "r"(bar), "r"(x), "r"(y), "h"((uint16_t)3), "l"(pol_first()) : "memory");
  else asm volatile("cp.async.bulk.tensor.2d.shared::cluster.global.mbarrier::complete_tx::bytes.multicast::cluster [%0], [%1, {%3, %4}], [%2], %5;" :: "r"(dst), "l"(m), "r"(bar), "r"(x), "r"(y), "h"((uint16_t)3) : "memory");
}
__device__ __forceinline__ void tma3d_mc(uint32_t dst, const CUtensorMap* m, int x, int y, int z, uint32_t bar, bool stream = false) {
  if (stream) asm volatile("cp.async.bulk.tensor.3d.shared::cluster.global.mbarrier::complete_tx::bytes.multicast::cluster.L2::cache_hint [%0], [%1, {%3, %4, %5}], [%2], %6, %7;" :: "r"(dst), "l"(m), "r"(bar), "r"(x), "r"(y), "r"(z), "h"((uint16_t)3), "l"(pol_first()) : "memory");
  else asm volatile("cp.async.bulk.tensor.3d.shared::cluster.global.mbarrier::complete_tx::bytes.multicast::cluster [%0], [%1, {%3, %4, %5}], [%2], %6;" :: "r"(dst), "l"(m), "r"(bar), "r"(x), "r"(y), "r"(z), "h"((uint16_t)3) : "memory");
}
__device__ __forceinline__ void tma2d_store(const CUtensorMap* m, uint32_t src, int x, int y) {
  if (POL(12)) asm volatile("cp.async.bulk.tensor.2d.global.shared::cta.bulk_group.L2::cache_hint [%0, {%2, %3}], [%1], %4;" :: "l"(m), "r"(src), "r"(x), "r"(y), "l"(pol_first()) : "memory");
  else asm volatile("cp.async.bulk.tensor.2d.global.shared::cta.bulk_group [%0, {%2, %3}], [%1];" :: "l"(m), "r"(src), "r"(x), "r"(y) : "memory");
}
__device__ __forceinline__ bool elect() {
  uint32_t r; asm volatile("{\n.reg .pred p;\nelect.sync _|p, 0xffffffff;\nselp.u32 %0, 1, 0, p;\n}\n" : "=r"(r)); return r != 0;
}
__device__ __forceinline__ void cluster_arrive() { asm volatile("barrier.cluster.arrive;" ::: "memory"); }
__device__ __forceinline__ void cluster_wait() { asm volatile("barrier.cluster.wait;" ::: "memory"); }
__device__ __forceinline__ void bar_sync(int id, int n) { asm volatile("bar.sync %0, %1;" :: "r"(id), "r"(n) : "memory"); }
__device__ __forceinline__ void bar_arrive(int id, int n) { asm volatile("bar.arrive %0, %1;" :: "r"(id), "r"(n) : "memory"); }
__device__ __forceinline__ int bar_and(int id, int n, int pred) {
  int r; asm volatile("{\n.reg .pred p, q;\nsetp.ne.b32 p, %3, 0;\nbar.red.and.pred q, %1, %2, p;\nselp.b32 %0, 1, 0, q;\n}\n" : "=r"(r) : "r"(id), "r"(n), "r"(pred) : "memory");
  return r;
}
__device__ __forceinline__ void fence_async_smem() { asm volatile("fence.proxy.async.shared::cta;" ::: "memory"); }
__device__ __forceinline__ float ex2(float x) { float y; asm("ex2.approx.ftz.f32 %0, %1;" : "=f"(y) : "f"(x)); return y; }
__device__ __forceinline__ uint32_t pack_bf16(float lo, float hi) { uint32_t r; asm("cvt.rn.bf16x2.f32 %0, %1, %2;" : "=r"(r) : "f"(hi), "f"(lo)); return r; }
__device__ __forceinline__ uint32_t hmul2(uint32_t a, uint32_t b) { uint32_t r; asm("mul.rn.bf16x2 %0, %1, %2;" : "=r"(r) : "r"(a), "r"(b)); return r; }
__device__ __forceinline__ uint32_t hadd2(uint32_t a, uint32_t b) { uint32_t r; asm("add.rn.bf16x2 %0, %1, %2;" : "=r"(r) : "r"(a), "r"(b)); return r; }
__device__ __forceinline__ uint32_t hfma2(uint32_t a, uint32_t b, uint32_t c) { uint32_t r; asm("fma.rn.bf16x2 %0, %1, %2, %3;" : "=r"(r) : "r"(a), "r"(b), "r"(c)); return r; }
__device__ __forceinline__ float bf_lo(uint32_t a) { return __uint_as_float(a << 16); }
__device__ __forceinline__ float bf_hi(uint32_t a) { return __uint_as_float(a & 0xffff0000u); }
__device__ __forceinline__ uint32_t lds32(uint32_t a) { uint32_t v; asm volatile("ld.shared.u32 %0, [%1];" : "=r"(v) : "r"(a) : "memory"); return v; }
__device__ __forceinline__ float2 lds64f(uint32_t a) { float2 v; asm volatile("ld.shared.v2.f32 {%0,%1}, [%2];" : "=f"(v.x), "=f"(v.y) : "r"(a) : "memory"); return v; }
__device__ __forceinline__ uint4 lds128(uint32_t a) { uint4 v; asm volatile("ld.shared.v4.u32 {%0,%1,%2,%3}, [%4];" : "=r"(v.x), "=r"(v.y), "=r"(v.z), "=r"(v.w) : "r"(a) : "memory"); return v; }
__device__ __forceinline__ void sts64f(uint32_t a, float x, float y) { asm volatile("st.shared.v2.f32 [%0], {%1,%2};" :: "r"(a), "f"(x), "f"(y) : "memory"); }
__device__ __forceinline__ void sts128(uint32_t a, uint4 v) { asm volatile("st.shared.v4.u32 [%0], {%1,%2,%3,%4};" :: "r"(a), "r"(v.x), "r"(v.y), "r"(v.z), "r"(v.w) : "memory"); }
template<int OFF> __device__ __forceinline__ void sts128o(uint32_t a, uint4 v) { asm volatile("st.shared.v4.u32 [%0+%5], {%1,%2,%3,%4};" :: "r"(a), "r"(v.x), "r"(v.y), "r"(v.z), "r"(v.w), "n"(OFF) : "memory"); }
__device__ __forceinline__ void ldsm4(uint32_t a, uint32_t& r0, uint32_t& r1, uint32_t& r2, uint32_t& r3) {
  asm volatile("ldmatrix.sync.aligned.m8n8.x4.shared.b16 {%0,%1,%2,%3}, [%4];" : "=r"(r0), "=r"(r1), "=r"(r2), "=r"(r3) : "r"(a) : "memory");
}
__device__ __forceinline__ void ldsm4t(uint32_t a, uint32_t& r0, uint32_t& r1, uint32_t& r2, uint32_t& r3) {
  asm volatile("ldmatrix.sync.aligned.m8n8.x4.trans.shared.b16 {%0,%1,%2,%3}, [%4];" : "=r"(r0), "=r"(r1), "=r"(r2), "=r"(r3) : "r"(a) : "memory");
}
__device__ __forceinline__ void stsm4(uint32_t a, uint32_t r0, uint32_t r1, uint32_t r2, uint32_t r3) {
  asm volatile("stmatrix.sync.aligned.m8n8.x4.shared.b16 [%0], {%1,%2,%3,%4};" :: "r"(a), "r"(r0), "r"(r1), "r"(r2), "r"(r3) : "memory");
}
template<int N> __device__ __forceinline__ void fence_regs(float (&d)[N]) {
#pragma unroll
  for (int i = 0; i < N; i++) asm volatile("" : "+f"(d[i]) :: "memory");
}
template<int N> __device__ __forceinline__ void fence_regs(uint32_t (&d)[N]) {
#pragma unroll
  for (int i = 0; i < N; i++) asm volatile("" : "+r"(d[i]) :: "memory");
}
__device__ __forceinline__ void sched_fence(float x, uint32_t dummy) {
  asm volatile("{\n.reg .pred p;\nsetp.eq.u32 p, %0, 0x7fc12345;\n@p st.shared.u32 [%1], %0;\n}\n" :: "r"(__float_as_uint(x)), "r"(dummy) : "memory");
}
#define TS(role, i)
#define TSA(i)
#define TR(obj, role, tag)

struct Prod {
  uint32_t base, mask; int lane, nt;
  __device__ __forceinline__ uint32_t full(int u) const { return base + SM_BAR + 8 * u; }
  __device__ __forceinline__ uint32_t addr(int u) const { return base + u * UNIT; }
  __device__ __forceinline__ void acquire(int u, int n) {
    const int v = u + min(lane, n - 1);
    mbar_wait_all(base + SM_BAR + 128 + 8 * v, mask >> v);
    mask ^= ((1u << n) - 1) << u;
    TR(*this, 2, 16 + u);
  }
  __device__ __forceinline__ void acquire_slow(int u, int n) {
    for (int i = 0; i < n; i++) mbar_wait_slow(base + SM_BAR + 128 + 8 * (u + i), mask >> (u + i));
    mask ^= ((1u << n) - 1) << u;
  }
};
struct Cons {
  uint32_t base, rel, mask; int lane, warp, wg, nt;
  __device__ __forceinline__ uint32_t addr(int u) const { return base + u * UNIT; }
  __device__ __forceinline__ static uint32_t daddr(int u) { return SMEM_BASE + u * UNIT; }
  __device__ __forceinline__ void wait(int u) { TR(*this, wg, 1); mbar_wait(base + SM_BAR + 8 * u, mask >> u); mask ^= 1u << u; TR(*this, wg, 2); }
  __device__ __forceinline__ void skip(int u) { mask ^= 1u << u; }
  __device__ __forceinline__ void release(int u, int n) {
    TR(*this, wg, 5);
    asm volatile("{\n.reg .pred p;\nsetp.lt.s32 p, %1, %2;\n@p mbarrier.arrive.shared::cluster.b64 _, [%0];\n}\n" :: "r"(rel + 8 * u), "r"(lane & 15), "r"(n) : "memory");
  }
  __device__ __forceinline__ void release2(int u) {
    asm volatile("{\n.reg .pred p;\nsetp.eq.s32 p, %1, 0;\n@p mbarrier.arrive.shared::cluster.b64 _, [%0], 2;\n}\n" :: "r"(rel + 8 * u), "r"(lane & 15) : "memory");
  }
  __device__ __forceinline__ void signal(int i) {
    __syncwarp();
    asm volatile("{\n.reg .pred p;\nsetp.eq.s32 p, %1, 0;\n@p mbarrier.arrive.shared::cta.b64 _, [%0];\n}\n" :: "r"(base + SM_SIG + 8 * i), "r"(lane) : "memory");
  }
  __device__ __forceinline__ void turn() { bar_sync(1 + wg, 256); TR(*this, wg, 3); }
  __device__ __forceinline__ void pass() { bar_arrive(2 - wg, 256); TR(*this, wg, 4); }
};
__device__ __forceinline__ int gemm_unit(int ks) { return 3 * (ks & 3); }
__device__ __forceinline__ int att_slot(int i) { return 4 + 2 * i; }
template<int MASK> __device__ __forceinline__ int kv_slot(int h) { return MASK == PH_ALL ? h & 15 : h; }
__device__ __forceinline__ int out_mb(int cta) { return cta >> 3; }
__device__ __forceinline__ int out_nb(int cta) { return cta & 7; }
template<int MASK> constexpr int CV_REG = MASK == PH_ALL ? CONV_REG : 6;
template<int MASK> constexpr int CV_EXTRA = (1024 - NREG * CV_REG<MASK>) / (NCTA - NREG);
template<int MASK> __device__ __forceinline__ int conv_channel(int cta, int i) {
  return cta < NREG ? CV_EXTRA<MASK> * (NCTA - NREG) + cta * CV_REG<MASK> + i : (i >> 1) * 8 + (cta - NREG) * 2 + (i & 1);
}

template<int OFF, int N> __device__ __forceinline__ void pack_chunk(const float (&a)[N], float sc0, float sc1, uint4& v0, uint4& v1) {
  v0.x = pack_bf16(a[OFF + 0] * sc0, a[OFF + 1] * sc0); v0.y = pack_bf16(a[OFF + 4] * sc0, a[OFF + 5] * sc0);
  v0.z = pack_bf16(a[OFF + 8] * sc0, a[OFF + 9] * sc0); v0.w = pack_bf16(a[OFF + 12] * sc0, a[OFF + 13] * sc0);
  v1.x = pack_bf16(a[OFF + 2] * sc1, a[OFF + 3] * sc1); v1.y = pack_bf16(a[OFF + 6] * sc1, a[OFF + 7] * sc1);
  v1.z = pack_bf16(a[OFF + 10] * sc1, a[OFF + 11] * sc1); v1.w = pack_bf16(a[OFF + 14] * sc1, a[OFF + 15] * sc1);
}
template<int OFF, int N> __device__ __forceinline__ void pack_chunk(const float (&a)[N], uint4& v0, uint4& v1) {
  v0.x = pack_bf16(a[OFF + 0], a[OFF + 1]); v0.y = pack_bf16(a[OFF + 4], a[OFF + 5]);
  v0.z = pack_bf16(a[OFF + 8], a[OFF + 9]); v0.w = pack_bf16(a[OFF + 12], a[OFF + 13]);
  v1.x = pack_bf16(a[OFF + 2], a[OFF + 3]); v1.y = pack_bf16(a[OFF + 6], a[OFF + 7]);
  v1.z = pack_bf16(a[OFF + 10], a[OFF + 11]); v1.w = pack_bf16(a[OFF + 14], a[OFF + 15]);
}
__device__ __forceinline__ void sq_acc(const uint4& v, uint32_t& a) { a = hfma2(v.x, v.x, a); a = hfma2(v.y, v.y, a); a = hfma2(v.z, v.z, a); a = hfma2(v.w, v.w, a); }
__device__ __forceinline__ float norm2_max(uint32_t a0, uint32_t a1) {
  float n0 = bf_lo(a0) + bf_hi(a0), n1 = bf_lo(a1) + bf_hi(a1);
  n0 += __shfl_xor_sync(~0u, n0, 1); n1 += __shfl_xor_sync(~0u, n1, 1);
  n0 += __shfl_xor_sync(~0u, n0, 2); n1 += __shfl_xor_sync(~0u, n1, 2);
  return __uint_as_float(__reduce_max_sync(~0u, max(__float_as_uint(n0) & 0x7fffffffu, __float_as_uint(n1) & 0x7fffffffu)));
}

struct Pend { uint4 lo[8], hi[8]; uint32_t dst; float kn; };
__device__ __forceinline__ void pin(uint4 (&v)[8]) {
#pragma unroll
  for (int i = 0; i < 8; i++) asm volatile("" : "+r"(v[i].x), "+r"(v[i].y), "+r"(v[i].z), "+r"(v[i].w) :: "memory");
}
__device__ __forceinline__ uint32_t atom_off(int lane) { return (lane >> 2) * 64 + (((lane ^ (lane >> 3)) & 3) << 4); }
__device__ __forceinline__ void stg128(void* p, const uint4& v, bool stream) {
  if (stream) asm volatile("st.global.L2::cache_hint.v4.u32 [%0], {%1,%2,%3,%4}, %5;" :: "l"(p), "r"(v.x), "r"(v.y), "r"(v.z), "r"(v.w), "l"(pol_first()) : "memory");
  else *(uint4*)p = v;
}
template<int J0, int J1, bool STREAM = false> __device__ __forceinline__ void tile_store(const uint4 (&v)[8], uint32_t dst, int lane) {
  uint8_t* d = g_T + (dst + atom_off(lane));
#pragma unroll
  for (int j = J0; j < J1; j++) { stg128(d + j * 512, v[2 * j], STREAM); stg128(d + j * 512 + 2048, v[2 * j + 1], STREAM); }
}
__device__ __forceinline__ float tile_norm2(const uint4 (&v)[8]) {
  uint32_t n0 = 0, n1 = 0, n2 = 0, n3 = 0;
#pragma unroll
  for (int j = 0; j < 2; j++) { sq_acc(v[2 * j], n0); sq_acc(v[2 * j + 1], n1); sq_acc(v[2 * j + 4], n2); sq_acc(v[2 * j + 5], n3); }
  return norm2_max(hadd2(n0, n2), hadd2(n1, n3));
}
template<int PART> __device__ __forceinline__ void out_part(Cons& c, Pend& w) {
  if (PART == 0) { w.kn = tile_norm2(w.lo); tile_store<0, 2>(w.lo, w.dst, c.lane); }
  if (PART == 1) tile_store<2, 4>(w.lo, w.dst, c.lane);
  if (PART == 2) {
    const float vn = tile_norm2(w.hi);
    if (c.lane == 0) g_kn2[((w.dst - T_KV) >> 16) * 8 + c.wg * 4 + c.warp] = (vn <= 1.0e30f && vn >= 1.0e-30f) ? w.kn : __uint_as_float(0x7f800000u);
    tile_store<0, 2, POL(11)>(w.hi, w.dst + 32768, c.lane);
  }
  if (PART == 3) tile_store<2, 4, POL(11)>(w.hi, w.dst + 32768, c.lane);
}
template<bool FIRST> __device__ __forceinline__ void kv_issue(Cons& c, float (&acc)[128], int u) {
  const uint64_t da = odesc(c.daddr(u) + c.wg * 8192, 16, 1024, 1), db = odesc(c.daddr(u + 1), 8192, 1024, 1);
  c.turn();
  wg_fence();
#pragma unroll
  for (int kk = 0; kk < 4; kk++) wgmma_ss_n256<1>(acc, da + kk * 2, db + kk * 128, !(FIRST && kk == 0));
  wg_commit();
  c.pass();
}
__device__ __forceinline__ void cons_kv(Cons& c, int h, int hs, int g, Pend& w, bool pend_o) {
#pragma unroll 1
  for (int tile = 0; tile < 2; tile++) {
    float acc[128];
    c.wait(0);
    if (tile == 0 && h < 16) TS(c.wg, 16);
    kv_issue<true>(c, acc, 0);
    if (tile == 1 && pend_o) mbar_wait(c.base + SM_RDY + 8 * RDY_WAR, 0);
    if (tile == 1 || pend_o) out_part<0>(c, w);
#pragma unroll 1
    for (int ks = 1; ks < 8; ks++) {
      if (ks == 3 && (tile == 1 || pend_o)) { out_part<1>(c, w); if (tile == 0) c.signal(SIG_CTX); }
      if (ks == 5 && tile == 1) out_part<2>(c, w);
      if (ks == 7 && tile == 1) out_part<3>(c, w);
      const int u = gemm_unit(ks);
      c.wait(u);
      wg_wait<0>();
      c.release(gemm_unit(ks - 1), 3);
      kv_issue<false>(c, acc, u);
    }
    wg_wait<0>(); fence_regs(acc);
    c.release(9, 3);
    pack_chunk<0>(acc, w.lo[0], w.lo[1]);  pack_chunk<16>(acc, w.lo[2], w.lo[3]); pack_chunk<32>(acc, w.lo[4], w.lo[5]); pack_chunk<48>(acc, w.lo[6], w.lo[7]);
    pack_chunk<64>(acc, w.hi[0], w.hi[1]); pack_chunk<80>(acc, w.hi[2], w.hi[3]); pack_chunk<96>(acc, w.hi[4], w.hi[5]); pack_chunk<112>(acc, w.hi[6], w.hi[7]);
    pin(w.lo); pin(w.hi);
    w.dst = T_KV + (hs * 16 + 2 * g + tile) * 65536 + (c.wg * 4 + c.warp) * 4096;
  }
}
template<bool FIRST> __device__ __forceinline__ void q_issue(Cons& c, float (&a)[64], float (&b)[64], int u) {
  const uint64_t da = odesc(c.daddr(u) + c.wg * 8192, 16, 1024, 1), db = odesc(c.daddr(u + 2), 8192, 1024, 1);
  const uint64_t da2 = odesc(c.daddr(u + 1) + (1 - c.wg) * 8192, 16, 1024, 1);
  c.turn();
  wg_fence();
#pragma unroll
  for (int kk = 0; kk < 4; kk++) wgmma_ss_n128<1>(a, da + kk * 2, db + kk * 128, !(FIRST && kk == 0));
#pragma unroll
  for (int kk = 0; kk < 4; kk++) wgmma_ss_n128<1>(b, da2 + kk * 2, db + kk * 128, !(FIRST && kk == 0));
  wg_commit();
  c.pass();
}
template<int U14, int U15> __device__ __forceinline__ void q_tail(Cons& c, float (&d)[64], int rowhalf) {
  const uint64_t da = odesc(c.daddr(U14) + rowhalf * 8192, 16, 1024, 1), db = odesc(c.daddr(7), 8192, 1024, 1);
  c.turn();
  wg_fence();
#pragma unroll
  for (int kk = 0; kk < 8; kk++) wgmma_ss_n128<1>(d, da + (kk >> 2) * (U15 - U14) * 1024 + (kk & 3) * 2, db + (kk >> 2) * 4096 + (kk & 3) * 128, 1);
  wg_commit();
  c.pass();
}
template<int OFF> __device__ __forceinline__ void q_store(const float (&d)[64], uint4 (&v)[8], uint32_t q0) {
  pack_chunk<0>(d, QSCALE, QSCALE, v[0], v[1]);  sts128o<OFF>(q0, v[0]);        sts128o<OFF + 2048>(q0, v[1]);
  pack_chunk<16>(d, QSCALE, QSCALE, v[2], v[3]); sts128o<OFF + 512>(q0, v[2]);  sts128o<OFF + 2560>(q0, v[3]);
  pack_chunk<32>(d, QSCALE, QSCALE, v[4], v[5]); sts128o<OFF + 1024>(q0, v[4]); sts128o<OFF + 3072>(q0, v[5]);
  pack_chunk<48>(d, QSCALE, QSCALE, v[6], v[7]); sts128o<OFF + 1536>(q0, v[6]); sts128o<OFF + 3584>(q0, v[7]);
}
template<bool PEND_KV> __device__ __forceinline__ void cons_q(Cons& c, int h, Pend& w) {
  float a[64], b[64];
  c.wait(0);
  q_issue<true>(c, a, b, 0);
  if (PEND_KV) out_part<0>(c, w);
#pragma unroll 1
  for (int ks = 1; ks < 14; ks++) {
    if (PEND_KV && ks < 6) {
      if (ks == 2) out_part<1>(c, w);
      if (ks == 4) out_part<2>(c, w);
      if (ks == 5) { out_part<3>(c, w); c.signal(SIG_KV + (h >> 4)); }
    }
    const int u = gemm_unit(ks);
    c.wait(u);
    wg_wait<0>();
    c.release(gemm_unit(ks - 1), 3);
    q_issue<false>(c, a, b, u);
  }
  c.wait(6); c.wait(9);
  wg_wait<0>();
  c.release(3, 3);
  q_tail<8, 9>(c, b, 1 - c.wg);
  wg_wait<0>(); fence_regs(b);
  c.release(8, 2);
  q_tail<6, 10>(c, a, c.wg);
  c.wait(0);
  const uint32_t q0 = c.addr(0) + (c.wg * 4 + c.warp) * 4096 + atom_off(c.lane);
  q_store<32768>(b, w.lo, q0);
  w.kn = tile_norm2(w.lo);
  c.wait(4);
  wg_wait<0>(); fence_regs(a);
  c.release(6, 2); c.release(10, 2);
  q_store<0>(a, w.lo, q0);
  fence_async_smem();
}

__device__ __forceinline__ void issue_qk(float (&s)[64], uint64_t da, uint64_t db) {
#pragma unroll
  for (int kk = 0; kk < 8; kk++) wgmma_ss_n128<0>(s, da + (kk >> 1) * 32 + (kk & 1) * 2, db + (kk >> 1) * 32 + (kk & 1) * 2, kk > 0);
  wg_commit();
}
template<int A, int B> __device__ __forceinline__ void exp_rng(float (&s)[64]) {
#pragma unroll
  for (int i = 4 * A; i < 4 * B; i++) s[i] = ex2(s[i]);
}
template<int A, int B> __device__ __forceinline__ void sum_rng(const float (&s)[64], float (&l)[4]) {
#pragma unroll
  for (int i = A; i < B; i++) { l[0] += s[4 * i]; l[1] += s[4 * i + 1]; l[2] += s[4 * i + 2]; l[3] += s[4 * i + 3]; }
}
template<int A, int B> __device__ __forceinline__ void cvt_p(const float (&s)[64], uint32_t (&p)[32]) {
#pragma unroll
  for (int i = 2 * A; i < 2 * B; i++) p[i] = pack_bf16(s[2 * i], s[2 * i + 1]);
}
template<int K0> __device__ __forceinline__ void mask_half(float (&s)[64], int warp, int lane) {
  const int l0 = warp + (2 * (lane & 3) <= (lane >> 2)), l1 = warp + (2 * (lane & 3) < (lane >> 2));
#pragma unroll
  for (int k = 0; k < 4; k++) {
    float* t = s + 8 * (K0 + k);
    if (k >= l0) { t[0] = -INFINITY; t[6] = -INFINITY; }
    if (k >= l1) { t[1] = -INFINITY; t[7] = -INFINITY; }
    if (k > warp) { t[2] = -INFINITY; t[3] = -INFINITY; }
    if (k >= warp) { t[4] = -INFINITY; t[5] = -INFINITY; }
  }
}
__device__ __forceinline__ void row_inv(float& l0, float& l1) {
  l0 += __shfl_xor_sync(~0u, l0, 1); l1 += __shfl_xor_sync(~0u, l1, 1);
  l0 += __shfl_xor_sync(~0u, l0, 2); l1 += __shfl_xor_sync(~0u, l1, 2);
  l0 = __fdividef(1.f, l0); l1 = __fdividef(1.f, l1);
}
__device__ __forceinline__ void pack_o(const float (&o)[64], float i0, float i1, uint4 (&v)[8]) {
  pack_chunk<0>(o, i0, i1, v[0], v[1]); pack_chunk<16>(o, i0, i1, v[2], v[3]);
  pack_chunk<32>(o, i0, i1, v[4], v[5]); pack_chunk<48>(o, i0, i1, v[6], v[7]);
  pin(v);
}
__device__ __forceinline__ void softmax_safe(float (&s)[64], bool upper_only, float& m0, float& m1, float& sc0, float& sc1) {
  float a0 = m0, a1 = m1;
#pragma unroll
  for (int i = 0; i < 8; i++) { a0 = fmaxf(a0, fmaxf(s[4 * i], s[4 * i + 1])); a1 = fmaxf(a1, fmaxf(s[4 * i + 2], s[4 * i + 3])); }
  if (upper_only) { a0 = m0; a1 = m1; }
#pragma unroll
  for (int i = 8; i < 16; i++) { a0 = fmaxf(a0, fmaxf(s[4 * i], s[4 * i + 1])); a1 = fmaxf(a1, fmaxf(s[4 * i + 2], s[4 * i + 3])); }
  a0 = fmaxf(a0, __shfl_xor_sync(~0u, a0, 1)); a1 = fmaxf(a1, __shfl_xor_sync(~0u, a1, 1));
  a0 = fmaxf(a0, __shfl_xor_sync(~0u, a0, 2)); a1 = fmaxf(a1, __shfl_xor_sync(~0u, a1, 2));
  sc0 = ex2(m0 - a0); sc1 = ex2(m1 - a1);
  m0 = a0; m1 = a1;
#pragma unroll
  for (int i = 0; i < 16; i++) { s[4 * i] -= a0; s[4 * i + 1] -= a0; s[4 * i + 2] -= a1; s[4 * i + 3] -= a1; }
}
struct Att {
  float s[64], o[64], l[4], i0, i1; uint32_t p[32];
  uint32_t qaddr;
};
__device__ __forceinline__ uint32_t ctx_off(const Cons& c, int h, int qb, int rowhalf) { return T_CTX + (qb * 32 + h) * 32768 + (rowhalf * 4 + c.warp) * 4096; }
__device__ __forceinline__ int att_first(Cons& c, Att& a, int h, const Pend& w) {
  a.qaddr = c.daddr(0) + c.wg * 16384;
  c.turn();
  wg_fence();
  issue_qk(a.s, odesc(a.qaddr, 16, 2048, 2), odesc(c.daddr(4), 16, 2048, 2));
  c.pass();
  c.signal(SIG_ATT + (h >> 4));
  const float qn = tile_norm2(w.lo), kn = __uint_as_float(lds32(c.base + SM_KMAX + 4 * (h >> 4)));
  const int fast = __shfl_sync(~0u, bar_and(3 + c.wg, 128, (qn * kn <= BOUND2) && (w.kn * kn <= BOUND2)), 0);
#pragma unroll
  for (int i = 0; i < 64; i++) a.o[i] = 0.f;
#pragma unroll
  for (int i = 0; i < 32; i++) a.p[i] = 0;
  a.l[0] = a.l[1] = a.l[2] = a.l[3] = 0.f; a.i0 = a.i1 = 0.f;
  wg_wait<0>(); fence_regs(a.s);
  c.release(4, 2);
  return fast;
}
__device__ __forceinline__ void att_last(Cons& c, Att& a, Pend& w, int h, int g, bool drain) {
#pragma unroll 1
  for (int k = drain ? 0 : 1; k < 2; k++) {
    if (k == 1) {
      const int uv = att_slot(1);
      c.wait(uv);
      c.turn();
      fence_regs(a.o); fence_regs(a.p);
      wgmma_pv_sel(a.o, a.p, odesc(c.daddr(uv), 512, 2048, 2), !(drain && c.wg == 1), !drain);
      c.pass();
      a.i0 = a.l[0] + a.l[1]; a.i1 = a.l[2] + a.l[3]; row_inv(a.i0, a.i1);
      wg_wait<0>(); fence_regs(a.o); fence_regs(a.p);
      c.release(uv, 2);
    }
    pack_o(a.o, a.i0, a.i1, w.lo);
    if (k == 0) tile_store<0, 4>(w.lo, ctx_off(c, h, 15, c.wg), c.lane);
  }
  w.dst = ctx_off(c, h, g, 1 - c.wg);
}
__device__ __forceinline__ void cons_att(Cons& c, int h, int g, Pend& w) {
  Att a;
  const int fast = att_first(c, a, h, w);
  float m0 = -INFINITY, m1 = -INFINITY, sc0 = 0.f, sc1 = 0.f;
  int uk = 10, nrel = 0;
#pragma unroll 1
  for (int d = g - 15;;) {
    const bool lo = d == c.wg;
    if ((unsigned)d < 2 || !fast) {
      if ((unsigned)d < 2) mask_half<4>(a.s, c.warp, c.lane);
      if (!fast) {
        if (d == 1) m0 = m1 = -INFINITY;
        softmax_safe(a.s, lo, m0, m1, sc0, sc1);
        a.l[0] *= sc0; a.l[1] *= sc0; a.l[2] *= sc1; a.l[3] *= sc1;
      }
    }
    exp_rng<8, 16>(a.s); sum_rng<8, 16>(a.s, a.l);
    exp_rng<ATT_SPLIT, 8>(a.s);
    sched_fence(((a.l[0] + a.l[1]) + (a.l[2] + a.l[3])) + (ATT_SPLIT < 8 ? a.s[4 * ATT_SPLIT + 3] : 0.f), c.base + SM_DUMMY);
    wg_wait<0>(); fence_regs(a.o); fence_regs(a.p);
    c.release(14 - uk, nrel);
    nrel = 2; uk ^= 12;
    if (d == 0) a.qaddr += 32768;
    const uint64_t dq = odesc(a.qaddr, 16, 2048, 2), dk = odesc(c.daddr(uk) - (d + 1 == c.wg ? 16384 : 0), 16, 2048, 2), dv = odesc(c.daddr(14 - uk), 512, 2048, 2);
    if (!lo) { exp_rng<0, ATT_SPLIT>(a.s); sum_rng<0, 8>(a.s, a.l); cvt_p<0, 16>(a.s, a.p); }
    else if (gridDim.y == 1) cvt_p<8, 16>(a.s, a.p);
    if (!fast || d == g + 1) {
      if (!fast && d != 1) {
#pragma unroll
        for (int i = 0; i < 16; i++) { a.o[4 * i] *= sc0; a.o[4 * i + 1] *= sc0; a.o[4 * i + 2] *= sc1; a.o[4 * i + 3] *= sc1; }
      }
      if (d == g + 1) break;
    }
    d++;
    if (c.wg == 0) c.wait(uk); else c.skip(uk);
    c.turn();
    fence_regs(a.o); fence_regs(a.p);
    wg_fence();
    issue_qk(a.s, dq, dk);
    if (d == 2) {
      uint4 v[8];
      pack_o(a.o, a.i0, a.i1, v); tile_store<0, 4>(v, ctx_off(c, h, 15 - g, c.wg), c.lane);
    }
    wgmma_pv_sel(a.o, a.p, dv, !lo, d != 2);
    c.pass();
    if (d == 1) {
      a.i0 = a.l[0] + a.l[1]; a.i1 = a.l[2] + a.l[3]; row_inv(a.i0, a.i1);
      a.l[0] = a.l[1] = a.l[2] = a.l[3] = 0.f;
    }
    wg_wait<1>(); fence_regs(a.s);
    c.release(uk, 2);
    c.release(d == 0 ? 0 : 2, (d == 0 || d == g + 1) ? 2 : 0);
  }
  att_last(c, a, w, h, g, g == 0);
}

constexpr int CV_H = 1024, CV_U = 5120, CV_D = CV_U + 4128, CV_ROW = 1056;
template<int OFF> __device__ __forceinline__ uint32_t lds32o(uint32_t a) { uint32_t v; asm volatile("ld.shared.u32 %0, [%1+%2];" : "=r"(v) : "r"(a), "n"(OFF) : "memory"); return v; }
template<int G, int G1 = 16> __device__ __forceinline__ void conv_lda(uint32_t (&a)[64], uint32_t p) {
  a[4 * G + 0] = lds32o<-256 * G>(p);
  a[4 * G + 1] = lds32o<-256 * G - 128>(p);
  a[4 * G + 2] = lds32o<-256 * G + 16>(p);
  a[4 * G + 3] = lds32o<-256 * G - 112>(p);
  if constexpr (G + 1 < G1) conv_lda<G + 1, G1>(a, p);
}
struct CvAcc { float lo[16], hi[16]; };
__device__ __forceinline__ void fence_regs(CvAcc& d) { fence_regs(d.lo); fence_regs(d.hi); }
template<int R, int H> __device__ __forceinline__ void conv_mma_h(float (&d)[16], const uint32_t (&a)[64], uint64_t db) {
#pragma unroll
  for (int G = 0; G < 4 * R + 2 * H + 2; G++) wgmma_rs_n32<0>(d, a[4 * G], a[4 * G + 1], a[4 * G + 2], a[4 * G + 3], db + 64 * R + 32 * H - 16 * G, G > 0);
}
template<int R> __device__ __forceinline__ void conv_mma(CvAcc& d, const uint32_t (&a)[64], uint64_t db) { conv_mma_h<R, 0>(d.lo, a, db); conv_mma_h<R, 1>(d.hi, a, db); }
template<int C0> __device__ __forceinline__ void conv_st_h(const float (&d)[16], uint32_t wq, float& c0, float& c1) {
#pragma unroll
  for (int n = 0; n < 4; n++) { sts64f(wq + (C0 + n * 8) * 4, d[4 * n] + c0, d[4 * n + 1] + c1); c0 = d[4 * n + 2]; c1 = d[4 * n + 3]; }
}
template<int R> __device__ __forceinline__ void conv_st(const CvAcc& d, uint32_t wq, float& c0, float& c1) { conv_st_h<64 * R>(d.lo, wq, c0, c1); conv_st_h<64 * R + 32>(d.hi, wq, c0, c1); }
struct ConvTail { float t[64]; uint4 ua, uc; uint32_t D2; };
__device__ __forceinline__ void conv_emit(ConvTail& e, int ch, int tid) {
  fence_regs(e.t);
  float y[16];
#pragma unroll
  for (int i = 0; i < 16; i++) y[i] = (e.t[i] + e.t[16 + i]) + (e.t[32 + i] + e.t[48 + i]);
  uint4 z0, z1;
  z0.x = hadd2(pack_bf16(y[0], y[2]), hmul2(__byte_perm(e.ua.w, 0, 0x1032), e.D2));
  z0.y = hadd2(pack_bf16(y[4], y[6]), hmul2(__byte_perm(e.ua.z, 0, 0x1032), e.D2));
  z0.z = hadd2(pack_bf16(y[8], y[10]), hmul2(__byte_perm(e.ua.y, 0, 0x1032), e.D2));
  z0.w = hadd2(pack_bf16(y[12], y[14]), hmul2(__byte_perm(e.ua.x, 0, 0x1032), e.D2));
  z1.x = hadd2(pack_bf16(y[1], y[3]), hmul2(__byte_perm(e.uc.w, 0, 0x1032), e.D2));
  z1.y = hadd2(pack_bf16(y[5], y[7]), hmul2(__byte_perm(e.uc.z, 0, 0x1032), e.D2));
  z1.z = hadd2(pack_bf16(y[9], y[11]), hmul2(__byte_perm(e.uc.y, 0, 0x1032), e.D2));
  z1.w = hadd2(pack_bf16(y[13], y[15]), hmul2(__byte_perm(e.uc.x, 0, 0x1032), e.D2));
  uint4* zp = (uint4*)(g_z + (uint32_t)(ch * 2048 + tid * 16));
  zp[0] = z0; zp[1] = z1;
}
template<int MASK> __device__ __forceinline__ void cons_conv(Cons& c, int cta, int nch) {
  const int r = c.lane >> 2, q = c.lane & 3, tid = c.warp * 32 + c.lane;
  const uint32_t part = c.addr(4) - 2048 + (1 - c.wg) * (32 * CV_ROW) + 32;
  const uint32_t aoff = CV_U + ((r & 1) ? 0 : UPITCH) + 4 * (((2039 - r) >> 1) + q - 8 * c.warp);
  const uint32_t wq = part + (c.warp * 8 + r) * CV_ROW + q * 8, rq = part + tid * 8;
  uint32_t a[64];
  ConvTail e = {};
  c.wait(c.wg); c.skip(c.wg ^ 1);
  conv_lda<0>(a, c.addr(c.wg) + aoff);
  c.wait(4);
  sts64f(part + (tid >> 2) * CV_ROW - 32 + q * 8, 0.f, 0.f);
#pragma unroll 1
  for (int i = 0; i < nch / 2; i++) {
    const int u = 2 * (i & 1) + c.wg;
    CvAcc d0, d1, d2, d3;
    float c0 = 0.f, c1 = 0.f;
    const uint64_t db = odesc(c.daddr(u) + CV_H - 16, 16, 128, 0);
    c.turn();
    fence_regs(a);
    wg_fence();
    conv_mma<0>(d0, a, db); conv_mma<1>(d1, a, db); wg_commit();
    if (i > 0) {
      conv_emit(e, conv_channel<MASK>(cta, 2 * i - 2 + c.wg), tid);
      if ((i & 15) == 0) c.signal(SIG_Z + (i >> 4) - 1);
    }
    wg_fence();
    conv_mma_h<2, 0>(d2.lo, a, db); wg_commit();
    wg_wait<1>(); fence_regs(d0); fence_regs(d1);
    conv_st_h<0>(d0.lo, wq, c0, c1);
    wg_fence();
    conv_mma_h<2, 1>(d2.hi, a, db); wg_commit();
    conv_st_h<32>(d0.hi, wq, c0, c1);
    conv_mma_h<3, 0>(d3.lo, a, db);
    conv_st_h<64>(d1.lo, wq, c0, c1);
    conv_mma_h<3, 1>(d3.hi, a, db); wg_commit();
    c.pass();
    const int un = i + 1 < nch / 2 ? u ^ 2 : u;
    if (un != u) { c.wait(un); c.skip(un ^ 1); }
    wg_wait<1>(); fence_regs(d2);
    conv_st_h<96>(d1.hi, wq, c0, c1);
    conv_st<2>(d2, wq, c0, c1);
    {
      const int sw = (c.lane >> 2) & 1;
      const uint4 v0 = lds128(c.addr(u) + CV_U + 4064 - 32 * tid + 16 * sw), v1 = lds128(c.addr(u) + CV_U + 4080 - 32 * tid - 16 * sw);
      e.ua = sw ? v0 : v1; e.uc = sw ? v1 : v0;
    }
    e.D2 = lds32(c.addr(u) + CV_D);
    wg_wait<0>(); fence_regs(d3); fence_regs(a);
    conv_st<3>(d3, wq, c0, c1);
    conv_lda<0, 4>(a, c.addr(un) + aoff);
    bar_sync(3 + c.wg, 128);
    c.release2(u);
    conv_lda<4, 16>(a, c.addr(un) + aoff);
#pragma unroll
    for (int k = 0; k < 32; k++) { const float2 v = lds64f(rq + k * CV_ROW - (k >> 3) * 8); e.t[2 * k] = v.x; e.t[2 * k + 1] = v.y; }
  }
  conv_emit(e, conv_channel<MASK>(cta, nch - 2 + c.wg), tid);
  c.signal(SIG_Z + ((nch / 2 - 1) >> 4));
  c.release(4, 4);
}

constexpr int OC_START = 2, OC_LEN = 15, OC_PART = 13824, OC_ROW = 544;
__device__ __forceinline__ int out_next(int u) { return u == 12 ? 4 : u + 2; }
struct Out { float acc[64]; int pu; uint64_t da, db; };
template<bool FIRST, bool REL> __device__ __forceinline__ void out_step(Cons& c, Out& o) {
  const int pu = o.pu, u = out_next(pu);
  o.pu = u;
  c.wait(u);
  const uint64_t da = o.da + (uint32_t)(u * 1024), db = o.db + (uint32_t)(u * 1024);
  wg_fence();
#pragma unroll
  for (int kk = 0; kk < 4; kk++) wgmma_ss_n128<1>(o.acc, da + (kk >> 1) * 32 + (kk & 1) * 2, db + kk * 128, !(FIRST && kk == 0));
  wg_commit();
  if (REL) { wg_wait<1>(); c.release(pu, 2); }
}
template<int I0, int I1> __device__ __forceinline__ void oc_red(float (&y)[8], uint32_t rq) {
#pragma unroll
  for (int i = I0; i < I1; i++) { const float v = __uint_as_float(lds32(rq + i * OC_ROW - (i >> 3) * 8)); y[i & 7] = i < 8 ? v : y[i & 7] + v; }
}
__device__ __forceinline__ void oc_emit(const float (&y)[8], const uint4& u, uint32_t D2, __nv_bfloat16* dst) {
  uint4 z;
  z.x = hadd2(pack_bf16(y[0], y[1]), hmul2(__byte_perm(u.w, 0, 0x1032), D2));
  z.y = hadd2(pack_bf16(y[2], y[3]), hmul2(__byte_perm(u.z, 0, 0x1032), D2));
  z.z = hadd2(pack_bf16(y[4], y[5]), hmul2(__byte_perm(u.y, 0, 0x1032), D2));
  z.w = hadd2(pack_bf16(y[6], y[7]), hmul2(__byte_perm(u.x, 0, 0x1032), D2));
  *(uint4*)dst = z;
}
template<int MASK> __device__ __forceinline__ void cons_out(Cons& c, const Maps& M, const Params& P, int cta, Pend& w) {
  const int mb = out_mb(cta), nb = out_nb(cta);
  Out o;
  o.da = odesc(c.daddr(0) + c.wg * 8192, 16, 1024, 2); o.db = odesc(c.daddr(1), 8192, 1024, 1);
  o.pu = 5 + gridDim.y;
  out_step<true, false>(c, o);
  if (MASK & PH_ATT) tile_store<0, 2>(w.lo, w.dst, c.lane);
  out_step<false, true>(c, o);
  if (MASK & PH_ATT) { tile_store<2, 4>(w.lo, w.dst, c.lane); c.signal(SIG_CTX + 1); }
  int ks = OC_START;
  if (MASK & PH_CONV) {
    const int r = c.lane >> 2, q = c.lane & 3, tid = c.warp * 32 + c.lane, u = 2 * c.wg;
    const uint32_t ub = c.addr(u), part = ub + OC_PART + 32;
    const uint32_t ap = ub + CV_U + ((r & 1) ? 0 : UPITCH) + 4 * (((2039 - r) >> 1) + q - 8 * c.warp);
    const uint32_t wq = part + (c.warp * 8 + r) * OC_ROW + q * 8, rq = part + tid * 4;
    const int nr = (CV_REG<MASK> + 1 - c.wg) >> 1;
#pragma unroll 1
    for (; ks < (c.wg ? OC_S1 : OC_S0); ks++) out_step<false, true>(c, o);
#define STEP(N) out_step<false, true>(c, o);
#pragma unroll 1
    for (int i = 0; i < nr; i++) {
      uint32_t a[64];
      CvAcc d0, d1;
      float y[8], c0 = 0.f, c1 = 0.f;
      const uint64_t db = odesc(c.daddr(u + (i >> 8)) + CV_H - 16, 16, 128, 0);
      c.wait(u);
      conv_lda<0, 3>(a, ap);
      STEP(0)
      conv_lda<3, 6>(a, ap);
      STEP(1)
      conv_lda<6, 9>(a, ap);
      STEP(2)
      fence_regs(reinterpret_cast<uint32_t (&)[32]>(a));
      wg_fence();
      conv_mma<0>(d0, a, db); conv_mma<1>(d1, a, db); wg_commit();
      conv_lda<9, 13>(a, ap);
      STEP(3)
      fence_regs(d0); fence_regs(d1);
      conv_lda<13, 16>(a, ap);
      STEP(4)
      bar_sync(3 + c.wg, 128);
      sts64f(wq - 32, 0.f, 0.f);
      conv_st<0>(d0, wq, c0, c1);
      STEP(5)
      float e0 = d1.hi[12] + d1.hi[10], e1 = d1.hi[13] + d1.hi[11];
      conv_st<1>(d1, wq, c0, c1);
      asm volatile("add.f32 %0, %0, 0f80000000;" : "+f"(c0)); asm volatile("add.f32 %0, %0, 0f80000000;" : "+f"(c1));
      fence_regs(a);
      wg_fence();
      conv_mma<2>(d0, a, db); conv_mma<3>(d1, a, db); wg_commit();
      bar_sync(3 + c.wg, 128);
      oc_red<0, 8>(y, rq);
      STEP(6)
      fence_regs(d0); fence_regs(d1); fence_regs(a);
      const uint4 u0 = lds128(ub + CV_U + 4080 - 16 * tid), u1 = lds128(ub + CV_U + 2032 - 16 * tid);
      const uint32_t D2 = lds32(ub + CV_D);
      oc_red<8, 12>(y, rq);
      __syncwarp();
      c.release2(u);
      STEP(7)
      oc_red<12, 24>(y, rq);
      STEP(8)
      __nv_bfloat16* zp = g_z + (uint32_t)(conv_channel<MASK>(cta, 2 * i + c.wg) * 2048 + (threadIdx.x & 127) * 8);
      oc_red<24, 32>(y, rq);
      oc_emit(y, u0, D2, zp);
      bar_sync(3 + c.wg, 128);
      STEP(9)
      sts64f(wq - 32, e0, e1);
      conv_st<0>(d0, wq, c0, c1);
      STEP(10)
      conv_st<1>(d1, wq, c0, c1);
      bar_sync(3 + c.wg, 128);
      oc_red<0, 8>(y, rq);
      STEP(11)
      oc_red<8, 16>(y, rq);
      STEP(12)
      oc_red<16, 24>(y, rq);
      STEP(13)
      oc_red<24, 32>(y, rq);
      oc_emit(y, u1, D2, zp + 1024);
      if (i == nr - 1) { c.signal(SIG_Z); c.release2(u + 1); }
      STEP(14)
    }
#undef STEP
    if (((CV_REG<MASK> + c.wg) >> 1) & 1) c.skip(u ^ 2);
    ks += nr * OC_LEN;
  }
  TS(c.wg, 9);
#pragma unroll 1
  for (; ks < 57; ks++) out_step<false, true>(c, o);
  uint32_t ga[32];
  c.wait(2);
  const float g0 = __uint_as_float(lds32(c.base + SM_GATE + 4 * (c.wg * 64 + c.warp * 16 + (c.lane >> 2)))), g1 = __uint_as_float(lds32(c.base + SM_GATE + 32 + 4 * (c.wg * 64 + c.warp * 16 + (c.lane >> 2))));
  const uint32_t gg0 = pack_bf16(g0, g0), gg1 = pack_bf16(g1, g1);
  const uint32_t og0 = pack_bf16(1.f - g0, 1.f - g0), og1 = pack_bf16(1.f - g1, 1.f - g1);
  const int xr = c.wg * 64 + c.warp * 16 + (c.lane & 15);
  const uint32_t xa = c.addr(2) + xr * 128, xs = xr & 7, xh = c.lane >> 4;
  const int zr = (c.lane & 7) + ((c.lane >> 4) << 3);
  const uint32_t za = c.addr(0) + c.wg * 16384 + zr * 128 + (((c.warp * 2 + ((c.lane >> 3) & 1)) ^ (zr & 7)) << 4);
#pragma unroll
  for (int i = 0; i < 8; i++) {
    if (i == 0) out_step<false, true>(c, o);
    if (i == 3) out_step<false, true>(c, o);
    if (i == 6) out_step<false, true>(c, o);
    ldsm4(xa + (i >> 2) * 16384 + ((((i & 3) * 2 + xh) ^ xs) << 4), ga[4 * i], ga[4 * i + 1], ga[4 * i + 2], ga[4 * i + 3]);
  }
#pragma unroll 1
  for (ks = 60; ks < 63; ks++) { out_step<false, false>(c, o); wg_wait<1>(); }
  c.wait(0);
#pragma unroll
  for (int i = 0; i < 8; i++) {
    if (i == 2) out_step<false, false>(c, o);
    uint32_t z0, z1, z2, z3;
    ldsm4t(za + i * 2048, z0, z1, z2, z3);
    ga[4 * i + 0] = hmul2(gg0, hmul2(ga[4 * i + 0], z0)); ga[4 * i + 1] = hmul2(gg1, hmul2(ga[4 * i + 1], z1));
    ga[4 * i + 2] = hmul2(gg0, hmul2(ga[4 * i + 2], z2)); ga[4 * i + 3] = hmul2(gg1, hmul2(ga[4 * i + 3], z3));
  }
  c.signal(SIG_DONE);
  fence_regs(ga);
  wg_wait<0>(); fence_regs(o.acc);
#pragma unroll
  for (int i = 0; i < 8; i++) {
    const uint32_t r0 = hadd2(ga[4 * i + 0], hmul2(og0, pack_bf16(o.acc[8 * i + 0], o.acc[8 * i + 1])));
    const uint32_t r1 = hadd2(ga[4 * i + 1], hmul2(og1, pack_bf16(o.acc[8 * i + 2], o.acc[8 * i + 3])));
    const uint32_t r2 = hadd2(ga[4 * i + 2], hmul2(og0, pack_bf16(o.acc[8 * i + 4], o.acc[8 * i + 5])));
    const uint32_t r3 = hadd2(ga[4 * i + 3], hmul2(og1, pack_bf16(o.acc[8 * i + 6], o.acc[8 * i + 7])));
    stsm4(xa + (i >> 2) * 16384 + ((((i & 3) * 2 + xh) ^ xs) << 4), r0, r1, r2, r3);
    if ((i & 3) == 3) {
      __syncwarp();
#pragma unroll
      for (int k = 0; k < 4; k++) {
        const int rr = c.wg * 64 + c.warp * 16 + k * 4 + (c.lane >> 3);
        const uint4 v = lds128(c.addr(2 + (i >> 2)) + rr * 128 + (((c.lane ^ rr) & 7) << 4));
        *(uint4*)(P.out + (uint32_t)((mb * 128 + rr) * 1024 + nb * 128 + (i >> 2) * 64 + (c.lane & 7) * 8)) = v;
      }
    }
  }
}

__device__ __forceinline__ void load_conv(Prod& p, const Maps& M, int u, int ch) {
  if (elect()) {
    mbar_expect(p.full(u), 5120 + UCH);
    tma3d(p.addr(u), &M.h, 0, -8, ch, p.full(u), POL(4));
    bulk_g2s(p.addr(u) + CV_U, g_u + (size_t)ch * UCH, UCH, p.full(u), POL(4));
  }
}
template<int MASK> __device__ __forceinline__ void prod_conv(Prod& p, const Maps& M, int cta, int nch) {
  int ready = -1;
#pragma unroll 1
  for (int i = 0; i < nch; i++) {
    const int ch = conv_channel<MASK>(cta, i);
    const int u = i & 3;
    if ((ch >> 6) != ready) { ready = ch >> 6; if (cta < NREG) mbar_wait(p.base + SM_RDY + 8 * RDY_U, 0); else cnt_wait(g_cnt + (C_U + ready) * CSTRIDE, 128); }
    p.acquire(u, 1);
    load_conv(p, M, u, ch);
    if (i == 3) { p.acquire(4, 4); if (elect()) mbar_arrive(p.full(4)); }
  }
}
#define HOIST(v) asm volatile("" : "+r"(v))
template<int MASK> __device__ __forceinline__ void producer(const Maps& M, const Params& P, uint32_t base, int cta, int lane) {
  Prod p{base, ((MASK & PH_KV) && cta < NREG) ? 0xffffcfffu ^ ((1u << (3 * NFIRST)) - 1) : 0xffffffffu, lane,
         (cta * 3 + 2) * 2048};
  if (cta >= NREG) { if (MASK & PH_CONV) prod_conv<MASK>(p, M, cta, CV_EXTRA<MASK>); return; }
  const int g = cta & 7, j = cta >> 3, rank = cta & 1;
#pragma unroll 1
  for (int half = 0; half < 2; half++) {
    const int h = j + 16 * half;
    if (MASK & PH_KV) {
      const CUtensorMap* mw = rank ? &M.wv : &M.wk;
#pragma unroll 1
      for (int it = half ? 0 : NFIRST; it < 16; it++) {
        const int u = gemm_unit(it);
        uint32_t bar = p.full(u), d0 = p.addr(u), d1 = p.addr(u + 1 + rank); int k0 = (it & 7) * 64, r0 = (2 * g + (it >> 3)) * 128;
        HOIST(bar); HOIST(d0); HOIST(d1); HOIST(k0); HOIST(r0);
        p.acquire(u, 3);
        if (elect()) {
          mbar_expect(bar, 3 * UNIT);
          tma3d_mc(d1, mw, 0, k0, 2 * h, bar, POL(0) && it >= 8);
          tma2d(d0, &M.c, k0, r0, bar, half ? POL(8) : POL(10));
        }
      }
    }
    if (MASK & PH_ATT) {
#pragma unroll 1
      for (int ks = 0; ks < 16; ks++) {
        const int u = gemm_unit(ks);
        uint32_t bar = p.full(u), d0 = p.addr(u + (ks == 15)), d1 = p.addr(ks < 14 ? u + 1 : ks - 6), d2 = p.addr(u + 2 - (ks == 14)) + rank * 8192; int k0 = ks * 64;
        HOIST(bar); HOIST(d0); HOIST(d1); HOIST(d2); HOIST(k0);
        p.acquire(u, 3);
        if (elect()) {
          mbar_expect(bar, 3 * UNIT);
          tma2d_mc(d2, &M.wq, h * 128 + rank * 64, k0, bar, POL(1));
          tma2d(d0, &M.x, k0, (15 - g) * 128, bar, half ? POL(9) : POL(10));
          tma2d(d1, &M.x, k0, g * 128, bar, half ? POL(9) : POL(10));
        }
      }
      TS(2, 8 * half + 0);
      mbar_wait(base + SM_RDY + 8 * (RDY_KV + half), 0);
      TS(2, 8 * half + 1);
      p.acquire(0, 4);
      if (elect()) mbar_arrive(p.full(0));
      const uint8_t* KVh = g_T + T_KV + (size_t)kv_slot<MASK>(h) * 16 * 65536;
#pragma unroll 1
      for (int n = 0; n < 34; n++) {
        const int i = n == 1 ? 2 : n == 2 ? 1 : n;
        const int isv = (i > 0 && !(i & 1)) || i == 33;
        const int st = i == 33 ? 16 : (isv ? (i >> 1) - 1 : (i + 1) >> 1);
        const int u = att_slot(i & 3);
        const bool own = st == 15 - (g & 6);
        uint32_t bar = p.full((isv && i < 33) ? 14 - u : u), d0 = p.addr(own ? u : u + rank), off = (st <= 15 - g ? st : 16 - st) * 65536 + isv * 32768 + (own ? 0 : rank * UNIT);
        HOIST(bar); HOIST(d0); HOIST(off);
        p.acquire(u, 2);
        if (elect()) {
          if (!isv || i == 33) mbar_expect(bar, (i == 0 || i == 33) ? 32768 : 65536);
          const bool ef = POL(6) || (POL(14) && st >= 8) || (POL(15) && half);
          if (own) bulk_g2s(d0, KVh + off, 32768, bar, ef); else bulk_g2s_mc(d0, KVh + off, UNIT, bar, ef);
        }
      }
    }
  }
  if ((MASK & PH_CONV) && !(MASK & PH_OUT)) prod_conv<MASK>(p, M, cta, CV_REG<MASK>);
  if (MASK & PH_OUT) {
    const int y0 = out_mb(cta) * 512 + rank * 8, z0 = 2 * out_nb(cta);
    int u = 6;
#pragma unroll 1
    for (int hf = 0; hf < 2; hf++) {
      TS(2, 16 + 2 * hf);
      mbar_wait(base + SM_RDY + 8 * (RDY_CTX + hf), 0);
      TS(2, 17 + 2 * hf);
#pragma unroll 1
      for (int ks = hf * 32; ks < hf * 32 + 32; ks++) {
        u = out_next(u);
        uint32_t bar = p.full(u), d0 = p.addr(u) + rank * 8192, d1 = p.addr(u + 1); int x = (ks & 1) * 256, y = y0 + (ks >> 1) * 16, k0 = ks * 64;
        HOIST(bar); HOIST(d0); HOIST(d1); HOIST(x); HOIST(y); HOIST(k0);
        p.acquire(u, 2);
        if (elect()) {
          mbar_expect(bar, 2 * UNIT);
          tma2d_mc(d0, &M.ctx, x, y, bar, POL(5));
          tma3d(d1, &M.wo, 0, k0, z0, bar, POL(2));
          if (ks == Z_AT) mbar_arrive(base + SM_RDY + 8 * RDY_Z);
        }
      }
    }
  }
}
template<int MASK> __device__ __forceinline__ void producer2(const Maps& M, const Params& P, uint32_t base, int cta, int w, int lane) {
  Prod p{base, 0xffffffffu, lane, 0};
  const int mb = out_mb(cta), nb = out_nb(cta), u = 2 * w;
  if (MASK & PH_CONV) {
    mbar_wait_slow(base + SM_SIG + 8 * (SIG_ATT + 1), 0);
    mbar_wait_slow(base + SM_RDY + 8 * RDY_U, 0);
#pragma unroll 1
    for (int i = w; i < CV_REG<MASK>; i += 2) { p.acquire_slow(u, i < 2 ? 2 : 1); load_conv(p, M, u, conv_channel<MASK>(cta, i)); }
  }
  p.acquire_slow(u, 2);
  if (elect()) asm volatile("prefetch.tensormap [%0];" :: "l"(!w ? &M.z : &M.out) : "memory");
  TSA(52 - 2 * w);
  mbar_wait(base + SM_RDY + 8 * (!w ? RDY_Z : RDY_G), 0);
  TSA(53 - 2 * w);
  if (elect()) {
    mbar_expect(p.full(u), 2 * UNIT + (!w ? 0 : 512));
    tma2d(p.addr(u), !w ? &M.z : &M.x, (!w ? mb : nb) * 128, (!w ? nb : mb) * 128, p.full(u), POL(5));
    tma2d(p.addr(u + 1), !w ? &M.z : &M.x, (!w ? mb : nb) * 128 + 64, (!w ? nb : mb) * 128, p.full(u), POL(5));
    if (w) bulk_g2s(base + SM_GATE, g_gate + mb * 128, 512, p.full(u));
  }
}

__device__ __forceinline__ constexpr uint32_t PUB(int sig, int cnt, int n) { return 0x80000000u | (sig << 24) | (n << 8) | cnt; }
__device__ __forceinline__ constexpr uint32_t GET(int rdy, int cnt, int n) { return (rdy << 24) | (n << 8) | cnt; }
template<int MASK> __device__ __forceinline__ void sync_agent(uint32_t base, int cta, int lane) {
  if ((base & 0x3FFFF) != SMEM_BASE) asm volatile("trap;");
  const int g = cta & 7, j = cta >> 3, go = min(out_mb(cta), 15 - out_mb(cta));
  const int c0 = conv_channel<MASK>(cta, 0), c1 = c0 + CV_REG<MASK> - 1, n0 = min(CV_REG<MASK>, 128 - (c0 & 127));
  constexpr bool KV = MASK & PH_KV, ATT = MASK & PH_ATT, CONV = MASK & PH_CONV, OUT = MASK & PH_OUT, ALL = MASK == PH_ALL;
  uint32_t e = 0;
  if (cta >= NREG) { if (CONV && lane * 32 < CV_EXTRA<MASK>) e = PUB(SIG_Z + lane, C_Z + lane, min(32, CV_EXTRA<MASK> - lane * 32)); }
  else switch (lane) {
    case 0:  if (KV) e = PUB(SIG_KV, C_KV + j, 1); break;
    case 1:  if (ATT) e = GET(RDY_KV, C_KV + j, 8); break;
    case 2:  if (ALL) e = PUB(SIG_WAR, C_WAR + j, 1); break;
    case 3:  if (ATT) e = PUB(SIG_CTX, C_CTX + g, 1); break;
    case 4:  if (ALL) e = GET(RDY_WAR, C_WAR + j, 8); break;
    case 5:  if (KV) e = PUB(SIG_KV + 1, C_KV + 16 + j, 1); break;
    case 6:  if (ATT) e = GET(RDY_KV + 1, C_KV + 16 + j, 8); break;
    case 7:  if (OUT) e = GET(RDY_CTX, C_CTX + go, 16); break;
    case 8:  if (CONV) e = GET(RDY_U, C_U + (c0 >> 6), 128); break;
    case 9:  if (CONV) e = GET(RDY_U, C_U + (c1 >> 6), 128); break;
    case 10: if (ATT) e = PUB(SIG_CTX + 1, C_CTX + 8 + g, 1); break;
    case 11: if (OUT) e = GET(RDY_CTX + 1, C_CTX + 8 + go, 16); break;
    case 12: if (OUT) e = GET(RDY_G, C_GATE, 256); break;
    case 13: if (CONV) e = PUB(SIG_Z, C_Z + (c0 >> 7), n0); break;
    case 14: if (CONV && n0 < CV_REG<MASK>) e = PUB(SIG_Z, C_Z + (c1 >> 7), CV_REG<MASK> - n0); break;
    case 15: if (OUT) e = GET(RDY_Z, C_Z + out_nb(cta), 128); break;
  }
  __syncwarp();
#pragma unroll 1
  for (int i = 0; i < 16; i++) {
    const uint32_t x = __shfl_sync(~0u, e, i), id = (x >> 24) & 127, n = (x >> 8) & 0xffff;
    if (x == 0) continue;
    unsigned* cnt = g_cnt + (x & 255) * CSTRIDE;
    if (x >> 31) {
      mbar_wait_slow(base + SM_SIG + 8 * id, 0);
      if (lane == 0) cnt_publish(cnt, n);
    } else {
      cnt_wait(cnt, n);
      if (id < 2) {
        const float4 kn = __ldcg((const float4*)(g_kn2 + kv_slot<MASK>(j + 16 * id) * 128) + lane);
        const uint32_t m = __reduce_max_sync(~0u, max(max(__float_as_uint(kn.x), __float_as_uint(kn.y)), max(__float_as_uint(kn.z), __float_as_uint(kn.w))));
        if (lane == 0) asm volatile("st.shared.u32 [%0], %1;" :: "r"(base + SM_KMAX + 4 * id), "r"(m) : "memory");
      }
      if (lane == 0) mbar_arrive(base + SM_RDY + 8 * id);
    }
    __syncwarp();
  }
}

__device__ __forceinline__ void aux_gate(const Params& P, int cta, int aw, int lane) {
  uint4 gw[4];
#pragma unroll
  for (int i = 0; i < 4; i++) gw[i] = __ldg((const uint4*)P.gw + i * 32 + lane);
#pragma unroll 1
  for (int row = cta * 16 + aw * 8; row < cta * 16 + aw * 8 + 8; row++) {
    float a = 0.f;
#pragma unroll
    for (int i = 0; i < 4; i++) {
      const uint4 xv = __ldg((const uint4*)(P.x + (size_t)row * 1024) + i * 32 + lane);
      uint32_t m;
      m = hmul2(xv.x, gw[i].x); a += bf_lo(m) + bf_hi(m); m = hmul2(xv.y, gw[i].y); a += bf_lo(m) + bf_hi(m);
      m = hmul2(xv.z, gw[i].z); a += bf_lo(m) + bf_hi(m); m = hmul2(xv.w, gw[i].w); a += bf_lo(m) + bf_hi(m);
    }
#pragma unroll
    for (int o = 16; o > 0; o >>= 1) a += __shfl_xor_sync(~0u, a, o);
    a = bf_lo(pack_bf16(a, 0.f));
    const float gt = bf_lo(pack_bf16(__fdividef(1.f, 1.f + ex2(-a * 1.4426950408889634f)), 0.f));
    if (lane == 0) g_gate[row] = gt;
    if (GATE_SLEEP) __nanosleep(GATE_SLEEP);
  }
  cnt_signal(g_cnt + C_GATE * CSTRIDE, lane);
  if (aw == 0) { TSA(44); }
}
template<int MASK> __device__ __forceinline__ void aux_pre(const Maps& M, const Params& P, uint32_t base, int cta, int aw, int lane) {
  const uint32_t kb = base + 12 * UNIT, bar = base + SM_PRE;
  const int r = lane >> 2, q = lane & 3;
  const int mi = lane >> 3, row0 = (lane & 6) + 1 - (lane & 1);
  const int ra = (mi * 9 + 1) * 2 + row0;
  const int rb = (mi == 0 ? 3 : mi) * 18 + row0;
  if (PRE_DELAY) mbar_wait_slow(base + SM_BAR + 8 * PRE_DELAY_BAR, 0);
#pragma unroll 1
  for (int it = 0; it < (cta < 96 ? 5 : 4); it++) {
    if (GATE_EARLY && it == PRE_EARLY && MASK == PH_ALL) { mbar_wait_slow(base + SM_SIG + 8 * SIG_ATT, 0); aux_gate(P, cta, aw, lane); }
    if (it == PRE_EARLY && MASK == PH_ALL) mbar_wait_slow(base + SM_SIG + 8 * (SIG_ATT + PRE_HALF), 0);
    const int cg = it ? it * 4 - 3 + (cta >> 5) : 0, tb = cta & 31;
    if (aw == 0 && elect()) {
      mbar_expect(bar, 2 * 9216);
      tma4d(kb, &M.k, cg * 64, 0, tb * 8 - 1, 0, bar, POL(3));
      tma4d(kb + 9216, &M.v, cg * 64, 0, tb * 8 - 1, 0, bar, POL(3));
    }
    const uint2 swl = __ldg((const uint2*)(P.shift + (cg * 64 + aw * 32 + lane) * 4));
    if (tb == 0) {
      uint8_t* e = g_u + (size_t)(cg * 64 + aw * 32 + lane) * UCH + 4096;
      *(uint4*)e = make_uint4(0, 0, 0, 0); *(uint4*)(e + UPITCH) = make_uint4(0, 0, 0, 0);
      *(uint32_t*)(e + 32) = (uint32_t)__bfloat16_as_ushort(P.D[cg * 64 + aw * 32 + lane]) * 0x10001u;
    }
    mbar_wait_slow(bar, it & 1);
#pragma unroll 1
    for (int ol = it ? 0 : cta >> 5; ol < (it ? 4 : (cta >> 5) + 1); ol++) {
      const int oc = aw * 4 + ol;
      const uint32_t s01 = __shfl_sync(~0u, swl.x, ol * 8 + r), s23 = __shfl_sync(~0u, swl.y, ol * 8 + r);
      const uint32_t w0 = __byte_perm(s01, 0, 0x1010), w1 = __byte_perm(s01, 0, 0x3232), w2 = __byte_perm(s23, 0, 0x1010), w3 = __byte_perm(s23, 0, 0x3232);
      const uint32_t pa = kb + ra * 128 + ((oc ^ (ra & 7)) << 4), pb = kb + (mi == 0 ? 9216 : 0) + rb * 128 + ((oc ^ (rb & 7)) << 4);
      uint8_t* e0 = g_u + (uint32_t)((cg * 64 + oc * 8 + r) * UCH + (2040 - tb * 64 - 8 * q) * 2);
#pragma unroll
      for (int hb = 0; hb < 2; hb++) {
        uint32_t k[7], v[5];
        ldsm4t(pa + hb * 1024, k[3], k[4], k[5], k[6]);
        ldsm4t(pa + hb * 1024 + 9216, v[1], v[2], v[3], v[4]);
        ldsm4t(pb + hb * 1024, v[0], k[0], k[1], k[2]);
        uint32_t o1 = __byte_perm(k[1], k[0], 0x5432);
#pragma unroll
        for (int m = 0; m < 5; m++) {
          const uint32_t o2 = __byte_perm(k[m + 2], k[m + 1], 0x5432);
          v[m] = hmul2(hadd2(hadd2(hadd2(hmul2(o1, w3), hmul2(k[m + 1], w2)), hmul2(o2, w1)), hmul2(k[m + 2], w0)), v[m]);
          o1 = o2;
        }
        *(uint4*)(e0 - hb * 64) = make_uint4(v[4], v[3], v[2], v[1]);
        *(uint4*)(e0 - hb * 64 + UPITCH) = make_uint4(__byte_perm(v[4], v[3], 0x5432), __byte_perm(v[3], v[2], 0x5432), __byte_perm(v[2], v[1], 0x5432), __byte_perm(v[1], v[0], 0x5432));
        if (PRE_SLEEP && it >= PRE_EARLY) __nanosleep(PRE_SLEEP);
      }
    }
    bar_sync(5, 64);
    if (aw == 0) { TSA(40 + min(it, 3)); }
    if (aw == 1 && lane == 0) asm volatile("red.release.gpu.global.add.u32 [%0], %1;" :: "l"(g_cnt + (C_U + cg) * CSTRIDE), "r"(it ? 4 : 1) : "memory");
  }
  uint32_t rel;
  asm volatile("mapa.shared::cluster.u32 %0, %1, %2;" : "=r"(rel) : "r"(base + SM_BAR + 128 + 8 * (12 + (lane & 1))), "r"((lane >> 1) & 1));
  if (lane < 4) asm volatile("mbarrier.arrive.shared::cluster.b64 _, [%0], 4;" :: "r"(rel) : "memory");
  if (!(GATE_EARLY && MASK == PH_ALL)) aux_gate(P, cta, aw, lane);
}

template<int MASK> __global__ void __cluster_dims__(2, 1, 1) __launch_bounds__(384, 1) gated_mix_kernel(const __grid_constant__ Maps M, const __grid_constant__ Params P) {
  extern __shared__ __align__(1024) uint8_t smem[];
  const uint32_t base = (uint32_t)__cvta_generic_to_shared(smem);
  const int wi = __shfl_sync(~0u, threadIdx.x >> 5, 0), wg = wi >> 2, warp = wi & 3;
  if (elect()) {
    if (wi < 8) {
      const int cnt = 1 << ((0x10334400 >> (4 * wi)) & 15);
#pragma unroll
      for (int i = 0; i < 8; i++) mbar_init(base + SM_BAR + 64 * wi + 8 * i, cnt);
      asm volatile("fence.mbarrier_init.release.cluster;" ::: "memory");
    } else if (MAP_PF) {
      asm volatile("prefetch.tensormap [%0];" :: "l"(&M.c + (wi - 8)) : "memory");
    }
  }
  const int cta = blockIdx.x;
  const bool first_loads = (MASK & PH_KV) && wi == 8 && cta < NREG;
  const CUtensorMap* mw = (cta & 1) ? &M.wv : &M.wk;
  __syncwarp();
  asm volatile("barrier.cluster.arrive.relaxed.aligned;\nbarrier.cluster.wait.aligned;" ::: "memory");
  if (first_loads && elect()) {
#pragma unroll 1
    for (int it = 0; it < NFIRST; it++) {
      const uint32_t bar = base + SM_BAR + 24 * it, d0 = base + 3 * it * UNIT;
      mbar_expect(bar, 3 * UNIT);
      tma3d_mc(d0 + (1 + (cta & 1)) * UNIT, mw, 0, it * 64, 2 * (cta >> 3), bar);
      tma2d(d0, &M.c, it * 64, (cta & 7) * 256, bar);
    }
  }
  __syncwarp();
  const int lane = threadIdx.x & 31;
#define TS_PRO()
  if (wg == 2) {
    asm volatile("setmaxnreg.dec.sync.aligned.u32 56;");
    TS_PRO();
    TS(2, 62);
    if (warp == 0) producer<MASK>(M, P, base, cta, lane);
    else if (warp == 1) sync_agent<MASK>(base, cta, lane);
    else if (cta < NREG) {
      if (MASK & PH_PRE) aux_pre<MASK>(M, P, base, cta, warp - 2, lane);
      if (MASK & PH_OUT) producer2<MASK>(M, P, base, cta, warp - 2, lane);
    }
    if (warp == 1) {
      if (MASK & PH_OUT) {
        unsigned old = 0;
        if (lane == 0) asm volatile("atom.relaxed.gpu.global.add.u32 %0, [%1], 1;" : "=r"(old) : "l"(g_cnt + C_EXIT * CSTRIDE) : "memory");
        old = __shfl_sync(~0u, old, 0);
        if (old == NCTA - 1) for (int i = lane; i < C_NUM; i += 32) g_cnt[i * CSTRIDE] = 0;
      }
      mbar_wait_slow(base + SM_SIG + 8 * SIG_DONE, 0);
      if (cta >= NREG || !(MASK & PH_OUT)) { cluster_arrive(); cluster_wait(); }
    }
  } else {
    asm volatile("setmaxnreg.inc.sync.aligned.u32 224;");
    TS_PRO();
    uint32_t rel;
    asm volatile("mapa.shared::cluster.u32 %0, %1, %2;" : "=r"(rel) : "r"(base + SM_BAR + 128 + 8 * (lane & 15)), "r"(lane >> 4));
    Cons c{base, rel, 0u, lane, warp, wg, (cta * 3 + wg) * 2048};
    if (wg == 1) bar_arrive(1, 256);
    TS(wg, 0);
    if (cta < NREG) {
      const int g = cta & 7, j = cta >> 3;
      Pend w = {};
#pragma unroll 1
      for (int half = 0; half < 2; half++) {
        const int h = j + 16 * half;
        if (MASK & PH_KV) cons_kv(c, h, kv_slot<MASK>(h), g, w, half == 1 && (MASK & PH_ATT));
        TS(wg, 1 + 4 * half);
        if (MASK & PH_ATT) {
          cons_q<(MASK & PH_KV) != 0>(c, h, w);
          TS(wg, 2 + 4 * half);
          cons_att(c, h, g, w);
          if (half == 0) c.signal(SIG_WAR);
#pragma unroll
          for (int i = 0; i < 8; i++) w.hi[i] = make_uint4(0, 0, 0, 0);
          TS(wg, 3 + 4 * half);
          if (MASK != PH_ALL) { tile_store<0, 4>(w.lo, w.dst, lane); c.signal(SIG_CTX + half); }
        } else if (MASK & PH_KV) { out_part<0>(c, w); out_part<1>(c, w); out_part<2>(c, w); out_part<3>(c, w); c.signal(SIG_KV + half); }
      }
      if (MASK & PH_OUT) cons_out<MASK>(c, M, P, cta, w);
    }
    if (cta >= NREG || !(MASK & PH_OUT)) {
      if (MASK & PH_CONV) cons_conv<MASK>(c, cta, cta < NREG ? CV_REG<MASK> : CV_EXTRA<MASK>);
      TS(wg, 9);
      c.signal(SIG_DONE);
      cluster_arrive();
    }
    TS(wg, 10);
  }
}

typedef CUresult (*EncFn)(CUtensorMap*, CUtensorMapDataType, cuuint32_t, void*, const cuuint64_t*, const cuuint64_t*, const cuuint32_t*, const cuuint32_t*,
                          CUtensorMapInterleave, CUtensorMapSwizzle, CUtensorMapL2promotion, CUtensorMapFloatOOBfill);
static void enc(EncFn f, CUtensorMap* m, const void* ptr, int rank, const cuuint64_t* dims, const cuuint64_t* strides, const cuuint32_t* box, CUtensorMapSwizzle sw,
                CUtensorMapDataType dt = CU_TENSOR_MAP_DATA_TYPE_BFLOAT16) {
  const cuuint32_t es[4] = {1, 1, 1, 1};
  f(m, dt, rank, (void*)ptr, dims, strides, box, es, CU_TENSOR_MAP_INTERLEAVE_NONE, sw, CU_TENSOR_MAP_L2_PROMOTION_L2_256B, CU_TENSOR_MAP_FLOAT_OOB_FILL_NONE);
}
static void enc2(EncFn f, CUtensorMap* m, const void* ptr, int cols, int rows, int brows) {
  const cuuint64_t d[2] = {(cuuint64_t)cols, (cuuint64_t)rows}, s[1] = {(cuuint64_t)cols * 2}; const cuuint32_t b[2] = {64, (cuuint32_t)brows};
  enc(f, m, ptr, 2, d, s, b, CU_TENSOR_MAP_SWIZZLE_128B);
}
static void encw(EncFn f, CUtensorMap* m, const void* ptr, int cols, int rows) {
  const cuuint64_t d[3] = {64, (cuuint64_t)rows, (cuuint64_t)cols / 64}, s[2] = {(cuuint64_t)cols * 2, 128}; const cuuint32_t b[3] = {64, 64, 2};
  enc(f, m, ptr, 3, d, s, b, CU_TENSOR_MAP_SWIZZLE_128B);
}
extern "C" void kernel_launch(void* const* d_in, const int* in_sizes, int n_in, void* d_out, int out_size) {
  static EncFn fn = nullptr;
  static int ncl = 0;
  static void* zptr = nullptr;
  static void* tptr = nullptr;
  if (!fn) {
    void* p = nullptr; cudaDriverEntryPointQueryResult qr;
    cudaGetDriverEntryPoint("cuTensorMapEncodeTiled", &p, cudaEnableDefault, &qr);
    fn = (EncFn)p;
    cudaFuncSetAttribute(gated_mix_kernel<PH_ALL>, cudaFuncAttributeMaxDynamicSharedMemorySize, SMEM_BYTES);
    cudaFuncSetAttribute(gated_mix_kernel<PH_PRE | PH_KV>, cudaFuncAttributeMaxDynamicSharedMemorySize, SMEM_BYTES);
    cudaFuncSetAttribute(gated_mix_kernel<PH_ATT | PH_CONV>, cudaFuncAttributeMaxDynamicSharedMemorySize, SMEM_BYTES);
    cudaFuncSetAttribute(gated_mix_kernel<PH_OUT>, cudaFuncAttributeMaxDynamicSharedMemorySize, SMEM_BYTES);
    cudaLaunchConfig_t cfg = {}; cfg.gridDim = NCTA; cfg.blockDim = 384; cfg.dynamicSmemBytes = SMEM_BYTES;
    cudaLaunchAttribute at; at.id = cudaLaunchAttributeClusterDimension; at.val.clusterDim.x = 2; at.val.clusterDim.y = 1; at.val.clusterDim.z = 1;
    cfg.attrs = &at; cfg.numAttrs = 1;
    cudaOccupancyMaxActiveClusters(&ncl, gated_mix_kernel<PH_ALL>, &cfg);
    cudaGetSymbolAddress(&zptr, g_z);
    cudaGetSymbolAddress(&tptr, g_T);
  }
  Maps M;
  enc2(fn, &M.x, d_in[0], 1024, 2048, 128);
  enc2(fn, &M.c, d_in[7], 512, 2048, 128);
  enc2(fn, &M.wq, d_in[8], 4096, 1024, 64);
  encw(fn, &M.wk, d_in[9], 4096, 512);
  encw(fn, &M.wv, d_in[10], 4096, 512);
  encw(fn, &M.wo, d_in[11], 1024, 4096);
  { const cuuint64_t d[3] = {64, 32, 1024}, s[2] = {128, 4096}; const cuuint32_t b[3] = {64, 40, 1}; enc(fn, &M.h, d_in[4], 3, d, s, b, CU_TENSOR_MAP_SWIZZLE_NONE); }
  enc2(fn, &M.z, zptr, 2048, 1024, 128);
  enc2(fn, &M.out, d_out, 1024, 2048, 16);
  { const cuuint64_t d[2] = {512, 512 * 16}, s[1] = {2048}; const cuuint32_t b[2] = {256, 8};
    enc(fn, &M.ctx, tptr, 2, d, s, b, CU_TENSOR_MAP_SWIZZLE_NONE, CU_TENSOR_MAP_DATA_TYPE_UINT32); }
  { const cuuint64_t d[4] = {1024, 2, 256, 4}, s[3] = {2048, 16384, 4096}; const cuuint32_t b[4] = {64, 2, 9, 4};
    enc(fn, &M.k, d_in[1], 4, d, s, b, CU_TENSOR_MAP_SWIZZLE_128B); enc(fn, &M.v, d_in[2], 4, d, s, b, CU_TENSOR_MAP_SWIZZLE_128B); }
  Params P{(const __nv_bfloat16*)d_in[0], (const __nv_bfloat16*)d_in[3],
           (const __nv_bfloat16*)d_in[5], (const __nv_bfloat16*)d_in[12], (__nv_bfloat16*)d_out};
  bool split = 2 * ncl < NCTA;
  if (!split) {
    gated_mix_kernel<PH_ALL><<<NCTA, 384, SMEM_BYTES>>>(M, P);
  } else {
    gated_mix_kernel<PH_PRE | PH_KV><<<NCTA, 384, SMEM_BYTES>>>(M, P);
    gated_mix_kernel<PH_ATT | PH_CONV><<<NCTA, 384, SMEM_BYTES>>>(M, P);
    gated_mix_kernel<PH_OUT><<<NCTA, 384, SMEM_BYTES>>>(M, P);
  }
}
```

```cpp
#include <cuda_runtime.h>
#include <cuda.h>
#include <cuda_bf16.h>
#include <stdint.h>

template<int TB> __device__ __forceinline__ void wgmma_ss_n256(float (&d)[128], uint64_t da, uint64_t db, int scale_d) {
  asm volatile("{\n.reg .pred p;\nsetp.ne.b32 p, %130, 0;\n"
    "wgmma.mma_async.sync.aligned.m64n256k16.f32.bf16.bf16 {%0, %1, %2, %3, %4, %5, %6, %7, %8, %9, %10, %11, %12, %13, %14, %15, %16, %17, %18, %19, %20, %21, %22, %23, %24, %25, %26, %27, %28, %29, %30, %31, %32, %33, %34, %35, %36, %37, %38, %39, %40, %41, %42, %43, %44, %45, %46, %47, %48, %49, %50, %51, %52, %53, %54, %55, %56, %57, %58, %59, %60, %61, %62, %63, %64, %65, %66, %67, %68, %69, %70, %71, %72, %73, %74, %75, %76, %77, %78, %79, %80, %81, %82, %83, %84, %85, %86, %87, %88, %89, %90, %91, %92, %93, %94, %95, %96, %97, %98, %99, %100, %101, %102, %103, %104, %105, %106, %107, %108, %109, %110, %111, %112, %113, %114, %115, %116, %117, %118, %119, %120, %121, %122, %123, %124, %125, %126, %127}, %128, %129, p, 1, 1, 0, %131;\n}\n"
    : "+f"(d[0]), "+f"(d[1]), "+f"(d[2]), "+f"(d[3]), "+f"(d[4]), "+f"(d[5]), "+f"(d[6]), "+f"(d[7]), "+f"(d[8]), "+f"(d[9]), "+f"(d[10]), "+f"(d[11]), "+f"(d[12]), "+f"(d[13]), "+f"(d[14]), "+f"(d[15]), "+f"(d[16]), "+f"(d[17]), "+f"(d[18]), "+f"(d[19]), "+f"(d[20]), "+f"(d[21]), "+f"(d[22]), "+f"(d[23]), "+f"(d[24]), "+f"(d[25]), "+f"(d[26]), "+f"(d[27]), "+f"(d[28]), "+f"(d[29]), "+f"(d[30]), "+f"(d[31]), "+f"(d[32]), "+f"(d[33]), "+f"(d[34]), "+f"(d[35]), "+f"(d[36]), "+f"(d[37]), "+f"(d[38]), "+f"(d[39]), "+f"(d[40]), "+f"(d[41]), "+f"(d[42]), "+f"(d[43]), "+f"(d[44]), "+f"(d[45]), "+f"(d[46]), "+f"(d[47]), "+f"(d[48]), "+f"(d[49]), "+f"(d[50]), "+f"(d[51]), "+f"(d[52]), "+f"(d[53]), "+f"(d[54]), "+f"(d[55]), "+f"(d[56]), "+f"(d[57]), "+f"(d[58]), "+f"(d[59]), "+f"(d[60]), "+f"(d[61]), "+f"(d[62]), "+f"(d[63]), "+f"(d[64]), "+f"(d[65]), "+f"(d[66]), "+f"(d[67]), "+f"(d[68]), "+f"(d[69]), "+f"(d[70]), "+f"(d[71]), "+f"(d[72]), "+f"(d[73]), "+f"(d[74]), "+f"(d[75]), "+f"(d[76]), "+f"(d[77]), "+f"(d[78]), "+f"(d[79]), "+f"(d[80]), "+f"(d[81]), "+f"(d[82]), "+f"(d[83]), "+f"(d[84]), "+f"(d[85]), "+f"(d[86]), "+f"(d[87]), "+f"(d[88]), "+f"(d[89]), "+f"(d[90]), "+f"(d[91]), "+f"(d[92]), "+f"(d[93]), "+f"(d[94]), "+f"(d[95]), "+f"(d[96]), "+f"(d[97]), "+f"(d[98]), "+f"(d[99]), "+f"(d[100]), "+f"(d[101]), "+f"(d[102]), "+f"(d[103]), "+f"(d[104]), "+f"(d[105]), "+f"(d[106]), "+f"(d[107]), "+f"(d[108]), "+f"(d[109]), "+f"(d[110]), "+f"(d[111]), "+f"(d[112]), "+f"(d[113]), "+f"(d[114]), "+f"(d[115]), "+f"(d[116]), "+f"(d[117]), "+f"(d[118]), "+f"(d[119]), "+f"(d[120]), "+f"(d[121]), "+f"(d[122]), "+f"(d[123]), "+f"(d[124]), "+f"(d[125]), "+f"(d[126]), "+f"(d[127])
    : "l"(da), "l"(db), "r"(scale_d), "n"(TB));
}
template<int TB> __device__ __forceinline__ void wgmma_ss_n128(float (&d)[64], uint64_t da, uint64_t db, int scale_d) {
  asm volatile("{\n.reg .pred p;\nsetp.ne.b32 p, %66, 0;\n"
    "wgmma.mma_async.sync.aligned.m64n128k16.f32.bf16.bf16 {%0, %1, %2, %3, %4, %5, %6, %7, %8, %9, %10, %11, %12, %13, %14, %15, %16, %17, %18, %19, %20, %21, %22, %23, %24, %25, %26, %27, %28, %29, %30, %31, %32, %33, %34, %35, %36, %37, %38, %39, %40, %41, %42, %43, %44, %45, %46, %47, %48, %49, %50, %51, %52, %53, %54, %55, %56, %57, %58, %59, %60, %61, %62, %63}, %64, %65, p, 1, 1, 0, %67;\n}\n"
    : "+f"(d[0]), "+f"(d[1]), "+f"(d[2]), "+f"(d[3]), "+f"(d[4]), "+f"(d[5]), "+f"(d[6]), "+f"(d[7]), "+f"(d[8]), "+f"(d[9]), "+f"(d[10]), "+f"(d[11]), "+f"(d[12]), "+f"(d[13]), "+f"(d[14]), "+f"(d[15]), "+f"(d[16]), "+f"(d[17]), "+f"(d[18]), "+f"(d[19]), "+f"(d[20]), "+f"(d[21]), "+f"(d[22]), "+f"(d[23]), "+f"(d[24]), "+f"(d[25]), "+f"(d[26]), "+f"(d[27]), "+f"(d[28]), "+f"(d[29]), "+f"(d[30]), "+f"(d[31]), "+f"(d[32]), "+f"(d[33]), "+f"(d[34]), "+f"(d[35]), "+f"(d[36]), "+f"(d[37]), "+f"(d[38]), "+f"(d[39]), "+f"(d[40]), "+f"(d[41]), "+f"(d[42]), "+f"(d[43]), "+f"(d[44]), "+f"(d[45]), "+f"(d[46]), "+f"(d[47]), "+f"(d[48]), "+f"(d[49]), "+f"(d[50]), "+f"(d[51]), "+f"(d[52]), "+f"(d[53]), "+f"(d[54]), "+f"(d[55]), "+f"(d[56]), "+f"(d[57]), "+f"(d[58]), "+f"(d[59]), "+f"(d[60]), "+f"(d[61]), "+f"(d[62]), "+f"(d[63])
    : "l"(da), "l"(db), "r"(scale_d), "n"(TB));
}
template<int TB> __device__ __forceinline__ void wgmma_rs_n32(float (&d)[16], uint32_t a0, uint32_t a1, uint32_t a2, uint32_t a3, uint64_t db, int scale_d) {
  asm volatile("{\n.reg .pred p;\nsetp.ne.b32 p, %21, 0;\n"
    "wgmma.mma_async.sync.aligned.m64n32k16.f32.bf16.bf16 {%0, %1, %2, %3, %4, %5, %6, %7, %8, %9, %10, %11, %12, %13, %14, %15}, {%16, %17, %18, %19}, %20, p, 1, 1, %22;\n}\n"
    : "+f"(d[0]), "+f"(d[1]), "+f"(d[2]), "+f"(d[3]), "+f"(d[4]), "+f"(d[5]), "+f"(d[6]), "+f"(d[7]), "+f"(d[8]), "+f"(d[9]), "+f"(d[10]), "+f"(d[11]), "+f"(d[12]), "+f"(d[13]), "+f"(d[14]), "+f"(d[15])
    : "r"(a0), "r"(a1), "r"(a2), "r"(a3), "l"(db), "r"(scale_d), "n"(TB));
}
__device__ __forceinline__ void wgmma_pv_sel(float (&d)[64], const uint32_t (&p)[32], uint64_t db, int full, int acc) {
  asm volatile("{\n.reg .pred q, s;\n.reg .b64 t;\nsetp.ne.b32 s, %98, 0;\nsetp.eq.b32 q, %97, 0;\n@q bra.uni LH;\n"
    "wgmma.fence.sync.aligned;\n"
    "add.s64 t, %96, 0;\nwgmma.mma_async.sync.aligned.m64n128k16.f32.bf16.bf16 {%0, %1, %2, %3, %4, %5, %6, %7, %8, %9, %10, %11, %12, %13, %14, %15, %16, %17, %18, %19, %20, %21, %22, %23, %24, %25, %26, %27, %28, %29, %30, %31, %32, %33, %34, %35, %36, %37, %38, %39, %40, %41, %42, %43, %44, %45, %46, %47, %48, %49, %50, %51, %52, %53, %54, %55, %56, %57, %58, %59, %60, %61, %62, %63}, {%64, %65, %66, %67}, t, s, 1, 1, 1;\n"
    "add.s64 t, %96, 256;\nwgmma.mma_async.sync.aligned.m64n128k16.f32.bf16.bf16 {%0, %1, %2, %3, %4, %5, %6, %7, %8, %9, %10, %11, %12, %13, %14, %15, %16, %17, %18, %19, %20, %21, %22, %23, %24, %25, %26, %27, %28, %29, %30, %31, %32, %33, %34, %35, %36, %37, %38, %39, %40, %41, %42, %43, %44, %45, %46, %47, %48, %49, %50, %51, %52, %53, %54, %55, %56, %57, %58, %59, %60, %61, %62, %63}, {%68, %69, %70, %71}, t, 1, 1, 1, 1;\n"
    "add.s64 t, %96, 512;\nwgmma.mma_async.sync.aligned.m64n128k16.f32.bf16.bf16 {%0, %1, %2, %3, %4, %5, %6, %7, %8, %9, %10, %11, %12, %13, %14, %15, %16, %17, %18, %19, %20, %21, %22, %23, %24, %25, %26, %27, %28, %29, %30, %31, %32, %33, %34, %35, %36, %37, %38, %39, %40, %41, %42, %43, %44, %45, %46, %47, %48, %49, %50, %51, %52, %53, %54, %55, %56, %57, %58, %59, %60, %61, %62, %63}, {%72, %73, %74, %75}, t, 1, 1, 1, 1;\n"
    "add.s64 t, %96, 768;\nwgmma.mma_async.sync.aligned.m64n128k16.f32.bf16.bf16 {%0, %1, %2, %3, %4, %5, %6, %7, %8, %9, %10, %11, %12, %13, %14, %15, %16, %17, %18, %19, %20, %21, %22, %23, %24, %25, %26, %27, %28, %29, %30, %31, %32, %33, %34, %35, %36, %37, %38, %39, %40, %41, %42, %43, %44, %45, %46, %47, %48, %49, %50, %51, %52, %53, %54, %55, %56, %57, %58, %59, %60, %61, %62, %63}, {%76, %77, %78, %79}, t, 1, 1, 1, 1;\n"
    "add.s64 t, %96, 1024;\nwgmma.mma_async.sync.aligned.m64n128k16.f32.bf16.bf16 {%0, %1, %2, %3, %4, %5, %6, %7, %8, %9, %10, %11, %12, %13, %14, %15, %16, %17, %18, %19, %20, %21, %22, %23, %24, %25, %26, %27, %28, %29, %30, %31, %32, %33, %34, %35, %36, %37, %38, %39, %40, %41, %42, %43, %44, %45, %46, %47, %48, %49, %50, %51, %52, %53, %54, %55, %56, %57, %58, %59, %60, %61, %62, %63}, {%80, %81, %82, %83}, t, 1, 1, 1, 1;\n"
    "add.s64 t, %96, 1280;\nwgmma.mma_async.sync.aligned.m64n128k16.f32.bf16.bf16 {%0, %1, %2, %3, %4, %5, %6, %7, %8, %9, %10, %11, %12, %13, %14, %15, %16, %17, %18, %19, %20, %21, %22, %23, %24, %25, %26, %27, %28, %29, %30, %31, %32, %33, %34, %35, %36, %37, %38, %39, %40, %41, %42, %43, %44, %45, %46, %47, %48, %49, %50, %51, %52, %53, %54, %55, %56, %57, %58, %59, %60, %61, %62, %63}, {%84, %85, %86, %87}, t, 1, 1, 1, 1;\n"
    "add.s64 t, %96, 1536;\nwgmma.mma_async.sync.aligned.m64n128k16.f32.bf16.bf16 {%0, %1, %2, %3, %4, %5, %6, %7, %8, %9, %10, %11, %12, %13, %14, %15, %16, %17, %18, %19, %20, %21, %22, %23, %24, %25, %26, %27, %28, %29, %30, %31, %32, %33, %34, %35, %36, %37, %38, %39, %40, %41, %42, %43, %44, %45, %46, %47, %48, %49, %50, %51, %52, %53, %54, %55, %56, %57, %58, %59, %60, %61, %62, %63}, {%88, %89, %90, %91}, t, 1, 1, 1, 1;\n"
    "add.s64 t, %96, 1792;\nwgmma.mma_async.sync.aligned.m64n128k16.f32.bf16.bf16 {%0, %1, %2, %3, %4, %5, %6, %7, %8, %9, %10, %11, %12, %13, %14, %15, %16, %17, %18, %19, %20, %21, %22, %23, %24, %25, %26, %27, %28, %29, %30, %31, %32, %33, %34, %35, %36, %37, %38, %39, %40, %41, %42, %43, %44, %45, %46, %47, %48, %49, %50, %51, %52, %53, %54, %55, %56, %57, %58, %59, %60, %61, %62, %63}, {%92, %93, %94, %95}, t, 1, 1, 1, 1;\n"
    "wgmma.commit_group.sync.aligned;\n"
    "bra.uni LE;\nLH:\n"
    "wgmma.fence.sync.aligned;\n"
    "add.s64 t, %96, 0;\nwgmma.mma_async.sync.aligned.m64n128k16.f32.bf16.bf16 {%0, %1, %2, %3, %4, %5, %6, %7, %8, %9, %10, %11, %12, %13, %14, %15, %16, %17, %18, %19, %20, %21, %22, %23, %24, %25, %26, %27, %28, %29, %30, %31, %32, %33, %34, %35, %36, %37, %38, %39, %40, %41, %42, %43, %44, %45, %46, %47, %48, %49, %50, %51, %52, %53, %54, %55, %56, %57, %58, %59, %60, %61, %62, %63}, {%80, %81, %82, %83}, t, s, 1, 1, 1;\n"
    "add.s64 t, %96, 256;\nwgmma.mma_async.sync.aligned.m64n128k16.f32.bf16.bf16 {%0, %1, %2, %3, %4, %5, %6, %7, %8, %9, %10, %11, %12, %13, %14, %15, %16, %17, %18, %19, %20, %21, %22, %23, %24, %25, %26, %27, %28, %29, %30, %31, %32, %33, %34, %35, %36, %37, %38, %39, %40, %41, %42, %43, %44, %45, %46, %47, %48, %49, %50, %51, %52, %53, %54, %55, %56, %57, %58, %59, %60, %61, %62, %63}, {%84, %85, %86, %87}, t, 1, 1, 1, 1;\n"
    "add.s64 t, %96, 512;\nwgmma.mma_async.sync.aligned.m64n128k16.f32.bf16.bf16 {%0, %1, %2, %3, %4, %5, %6, %7, %8, %9, %10, %11, %12, %13, %14, %15, %16, %17, %18, %19, %20, %21, %22, %23, %24, %25, %26, %27, %28, %29, %30, %31, %32, %33, %34, %35, %36, %37, %38, %39, %40, %41, %42, %43, %44, %45, %46, %47, %48, %49, %50, %51, %52, %53, %54, %55, %56, %57, %58, %59, %60, %61, %62, %63}, {%88, %89, %90, %91}, t, 1, 1, 1, 1;\n"
    "add.s64 t, %96, 768;\nwgmma.mma_async.sync.aligned.m64n128k16.f32.bf16.bf16 {%0, %1, %2, %3, %4, %5, %6, %7, %8, %9, %10, %11, %12, %13, %14, %15, %16, %17, %18, %19, %20, %21, %22, %23, %24, %25, %26, %27, %28, %29, %30, %31, %32, %33, %34, %35, %36, %37, %38, %39, %40, %41, %42, %43, %44, %45, %46, %47, %48, %49, %50, %51, %52, %53, %54, %55, %56, %57, %58, %59, %60, %61, %62, %63}, {%92, %93, %94, %95}, t, 1, 1, 1, 1;\n"
    "wgmma.commit_group.sync.aligned;\n"
    "LE:\n}\n"
    : "+f"(d[0]), "+f"(d[1]), "+f"(d[2]), "+f"(d[3]), "+f"(d[4]), "+f"(d[5]), "+f"(d[6]), "+f"(d[7]), "+f"(d[8]), "+f"(d[9]), "+f"(d[10]), "+f"(d[11]), "+f"(d[12]), "+f"(d[13]), "+f"(d[14]), "+f"(d[15]), "+f"(d[16]), "+f"(d[17]), "+f"(d[18]), "+f"(d[19]), "+f"(d[20]), "+f"(d[21]), "+f"(d[22]), "+f"(d[23]), "+f"(d[24]), "+f"(d[25]), "+f"(d[26]), "+f"(d[27]), "+f"(d[28]), "+f"(d[29]), "+f"(d[30]), "+f"(d[31]), "+f"(d[32]), "+f"(d[33]), "+f"(d[34]), "+f"(d[35]), "+f"(d[36]), "+f"(d[37]), "+f"(d[38]), "+f"(d[39]), "+f"(d[40]), "+f"(d[41]), "+f"(d[42]), "+f"(d[43]), "+f"(d[44]), "+f"(d[45]), "+f"(d[46]), "+f"(d[47]), "+f"(d[48]), "+f"(d[49]), "+f"(d[50]), "+f"(d[51]), "+f"(d[52]), "+f"(d[53]), "+f"(d[54]), "+f"(d[55]), "+f"(d[56]), "+f"(d[57]), "+f"(d[58]), "+f"(d[59]), "+f"(d[60]), "+f"(d[61]), "+f"(d[62]), "+f"(d[63])
    : "r"(p[0]), "r"(p[1]), "r"(p[2]), "r"(p[3]), "r"(p[4]), "r"(p[5]), "r"(p[6]), "r"(p[7]), "r"(p[8]), "r"(p[9]), "r"(p[10]), "r"(p[11]), "r"(p[12]), "r"(p[13]), "r"(p[14]), "r"(p[15]), "r"(p[16]), "r"(p[17]), "r"(p[18]), "r"(p[19]), "r"(p[20]), "r"(p[21]), "r"(p[22]), "r"(p[23]), "r"(p[24]), "r"(p[25]), "r"(p[26]), "r"(p[27]), "r"(p[28]), "r"(p[29]), "r"(p[30]), "r"(p[31]), "l"(db), "r"(full), "r"(acc) : "memory");
}

constexpr int NCTA = 132, NREG = 128;
constexpr int UNIT = 16384, NUNIT = 14;
constexpr uint32_t SMEM_BASE = 1024;
constexpr int SM_BAR = NUNIT * UNIT;
constexpr int SM_GATE = SM_BAR + 1024;
constexpr int SMEM_BYTES = SM_BAR + 1536;
constexpr int UPITCH = 4160, UCH = 2 * UPITCH;
constexpr float QSCALE = 0.08838834764831845f * 1.4426950408889634f;
constexpr float BOUND2 = 48.f * 48.f / 1.15f;
#define CONV_REG 5
constexpr int C_KV = 0;
constexpr int C_CTX = 32;
constexpr int C_U = 48;
constexpr int C_Z = 80;
constexpr int C_GATE = 88;
constexpr int C_EXIT = 89;
#define PRE_EARLY 2
#define PRE_HALF 1
#define ATT_SPLIT 6
#define NFIRST 2
#define PRE_DELAY 0
#define MAP_PF 1
#define FINAL_ST 1
#define Z_AT 60
#define PRE_DELAY_BAR 9
#define PRE_FMA 0
#define PRE_SLEEP 300
#define GATE_SLEEP 1000
#define GATE_EARLY 1
#define OC_S0 2
#define OC_S1 4
#define EF 127
#define POL(bit) (((EF >> (bit)) & 1) != 0)
constexpr int C_WAR = 96;
constexpr int C_NUM = 112;
constexpr int CSTRIDE = 32;
constexpr int SM_KMAX = SM_BAR + 640, SM_DUMMY = SM_BAR + 648, SM_PRE = SM_BAR + 112, SM_SIG = SM_BAR + 256, SM_RDY = SM_BAR + 384;
enum { SIG_KV = 0, SIG_CTX = 2, SIG_Z = 4, SIG_DONE = 8, SIG_WAR = 9, SIG_ATT = 10 };
enum { RDY_KV = 0, RDY_CTX = 2, RDY_WAR = 4, RDY_G = 5, RDY_U = 8, RDY_Z = 9 };
enum { PH_PRE = 1, PH_KV = 2, PH_ATT = 4, PH_CONV = 8, PH_OUT = 16, PH_ALL = 31 };

constexpr uint32_t T_CTX = 0, T_KV = 16 * 32 * 32768, T_BYTES = T_KV + 32 * 16 * 65536;
__device__ __align__(1024) uint8_t g_T[T_BYTES];
__device__ __align__(1024) uint8_t g_u[1024 * UCH];
__device__ __align__(1024) __nv_bfloat16 g_z[1024 * 2048];
__device__ __align__(1024) float g_gate[2048];
__device__ __align__(1024) float g_kn2[32 * 128];
__device__ __align__(1024) unsigned g_cnt[C_NUM * CSTRIDE];

struct __align__(64) Maps { CUtensorMap c, wk, wv, x, wq, wo, h, z, out, ctx, k, v; };
struct Params {
  const __nv_bfloat16 *x, *shift, *D, *gw;
  __nv_bfloat16* out;
};

__device__ __forceinline__ void wg_fence() { asm volatile("wgmma.fence.sync.aligned;" ::: "memory"); }
__device__ __forceinline__ void wg_commit() { asm volatile("wgmma.commit_group.sync.aligned;" ::: "memory"); }
template<int N> __device__ __forceinline__ void wg_wait() { asm volatile("wgmma.wait_group.sync.aligned %0;" :: "n"(N) : "memory"); }
__device__ __forceinline__ uint64_t odesc(uint32_t addr, uint32_t lbo, uint32_t sbo, uint32_t swz) {
  uint64_t d = (uint64_t)(addr >> 4) + (((uint64_t)(lbo >> 4) << 16) | ((uint64_t)(sbo >> 4) << 32) | ((uint64_t)swz << 62));
  asm volatile("" : "+l"(d));
  return d;
}
__device__ __forceinline__ void mbar_init(uint32_t bar, int cnt) { asm volatile("mbarrier.init.shared::cta.b64 [%0], %1;" :: "r"(bar), "r"(cnt)); }
__device__ __forceinline__ void mbar_expect(uint32_t bar, uint32_t bytes) { asm volatile("mbarrier.arrive.expect_tx.shared::cta.b64 _, [%0], %1;" :: "r"(bar), "r"(bytes) : "memory"); }
__device__ __forceinline__ void mbar_arrive(uint32_t bar) { asm volatile("mbarrier.arrive.shared::cta.b64 _, [%0];" :: "r"(bar) : "memory"); }
__device__ __forceinline__ void mbar_arrive_n(uint32_t bar, int n) { asm volatile("mbarrier.arrive.shared::cta.b64 _, [%0], %1;" :: "r"(bar), "r"(n) : "memory"); }
__device__ __forceinline__ void mbar_wait(uint32_t bar, uint32_t parity) {
  asm volatile("{\n.reg .pred p;\nLW:\nmbarrier.try_wait.parity.shared::cta.b64 p, [%0], %1;\n@!p bra LW;\n}\n" :: "r"(bar), "r"(parity) : "memory");
}
__device__ __forceinline__ void mbar_wait_slow(uint32_t bar, uint32_t parity) {
  asm volatile("{\n.reg .pred p;\n.reg .u32 n;\nmov.u32 n, 0;\n"
    "LW:\nmbarrier.test_wait.parity.shared::cta.b64 p, [%0], %1;\n@p bra LD;\n"
    "nanosleep.u32 128;\nadd.u32 n, n, 1;\nsetp.lt.u32 p, n, 4194304;\n@p bra LW;\ntrap;\nLD:\n}\n" :: "r"(bar), "r"(parity) : "memory");
}
__device__ __forceinline__ void mbar_wait_all(uint32_t bar, uint32_t parity) {
  asm volatile("{\n.reg .pred p, q;\nLW:\nmbarrier.try_wait.parity.shared::cta.b64 p, [%0], %1;\nvote.sync.all.pred q, p, 0xffffffff;\n@!q bra.uni LW;\n}\n" :: "r"(bar), "r"(parity) : "memory");
}
__device__ __forceinline__ void cnt_wait(const unsigned* p, unsigned target) {
  asm volatile("{\n.reg .pred p;\n.reg .u32 n, v;\nmov.u32 n, 0;\n"
    "LW:\nld.relaxed.gpu.global.u32 v, [%0];\nsetp.ge.u32 p, v, %1;\n@p bra LD;\n"
    "nanosleep.u32 64;\nadd.u32 n, n, 1;\nsetp.lt.u32 p, n, 4194304;\n@p bra LW;\ntrap;\nLD:\nfence.acq_rel.gpu;\nfence.proxy.async;\n}\n" :: "l"(p), "r"(target) : "memory");
}
__device__ __forceinline__ void cnt_signal(unsigned* p, int lane) {
  __syncwarp();
  if (lane == 0) asm volatile("red.release.gpu.global.add.u32 [%0], 1;" :: "l"(p) : "memory");
}
__device__ __forceinline__ void cnt_publish(unsigned* p, unsigned n) {
  asm volatile("fence.acq_rel.gpu;\nred.relaxed.gpu.global.add.u32 [%0], %1;" :: "l"(p), "r"(n) : "memory");
}
__device__ __forceinline__ uint64_t pol_first() { uint64_t p; asm("createpolicy.fractional.L2::evict_first.b64 %0, 1.0;" : "=l"(p)); return p; }
__device__ __forceinline__ void bulk_g2s(uint32_t dst, const void* src, uint32_t bytes, uint32_t bar, bool stream = false) {
  if (stream) asm volatile("cp.async.bulk.shared::cluster.global.mbarrier::complete_tx::bytes.L2::cache_hint [%0], [%1], %2, [%3], %4;" :: "r"(dst), "l"(src), "r"(bytes), "r"(bar), "l"(pol_first()) : "memory");
  else asm volatile("cp.async.bulk.shared::cluster.global.mbarrier::complete_tx::bytes [%0], [%1], %2, [%3];" :: "r"(dst), "l"(src), "r"(bytes), "r"(bar) : "memory");
}
__device__ __forceinline__ void tma2d(uint32_t dst, const CUtensorMap* m, int x, int y, uint32_t bar, bool stream = false) {
  if (stream) asm volatile("cp.async.bulk.tensor.2d.shared::cluster.global.mbarrier::complete_tx::bytes.L2::cache_hint [%0], [%1, {%3, %4}], [%2], %5;" :: "r"(dst), "l"(m), "r"(bar), "r"(x), "r"(y), "l"(pol_first()) : "memory");
  else asm volatile("cp.async.bulk.tensor.2d.shared::cluster.global.mbarrier::complete_tx::bytes [%0], [%1, {%3, %4}], [%2];" :: "r"(dst), "l"(m), "r"(bar), "r"(x), "r"(y) : "memory");
}
__device__ __forceinline__ void tma3d(uint32_t dst, const CUtensorMap* m, int x, int y, int z, uint32_t bar, bool stream = false) {
  if (stream) asm volatile("cp.async.bulk.tensor.3d.shared::cluster.global.mbarrier::complete_tx::bytes.L2::cache_hint [%0], [%1, {%3, %4, %5}], [%2], %6;" :: "r"(dst), "l"(m), "r"(bar), "r"(x), "r"(y), "r"(z), "l"(pol_first()) : "memory");
  else asm volatile("cp.async.bulk.tensor.3d.shared::cluster.global.mbarrier::complete_tx::bytes [%0], [%1, {%3, %4, %5}], [%2];" :: "r"(dst), "l"(m), "r"(bar), "r"(x), "r"(y), "r"(z) : "memory");
}
__device__ __forceinline__ void tma4d(uint32_t dst, const CUtensorMap* m, int x, int y, int z, int w, uint32_t bar, bool stream = false) {
  if (stream) asm volatile("cp.async.bulk.tensor.4d.shared::cluster.global.mbarrier::complete_tx::bytes.L2::cache_hint [%0], [%1, {%3, %4, %5, %6}], [%2], %7;" :: "r"(dst), "l"(m), "r"(bar), "r"(x), "r"(y), "r"(z), "r"(w), "l"(pol_first()) : "memory");
  else asm volatile("cp.async.bulk.tensor.4d.shared::cluster.global.mbarrier::complete_tx::bytes [%0], [%1, {%3, %4, %5, %6}], [%2];" :: "r"(dst), "l"(m), "r"(bar), "r"(x), "r"(y), "r"(z), "r"(w) : "memory");
}
__device__ __forceinline__ void bulk_g2s_mc(uint32_t dst, const void* src, uint32_t bytes, uint32_t bar, bool stream = false) {
  if (stream) asm volatile("cp.async.bulk.shared::cluster.global.mbarrier::complete_tx::bytes.multicast::cluster.L2::cache_hint [%0], [%1], %2, [%3], %4, %5;" :: "r"(dst), "l"(src), "r"(bytes), "r"(bar), "h"((uint16_t)3), "l"(pol_first()) : "memory");
  else asm volatile("cp.async.bulk.shared::cluster.global.mbarrier::complete_tx::bytes.multicast::cluster [%0], [%1], %2, [%3], %4;" :: "r"(dst), "l"(src), "r"(bytes), "r"(bar), "h"((uint16_t)3) : "memory");
}
__device__ __forceinline__ void tma2d_mc(uint32_t dst, const CUtensorMap* m, int x, int y, uint32_t bar, bool stream = false) {
  if (stream) asm volatile("cp.async.bulk.tensor.2d.shared::cluster.global.mbarrier::complete_tx::bytes.multicast::cluster.L2::cache_hint [%0], [%1, {%3, %4}], [%2], %5, %6;" :: "r"(dst), "l"(m), "r"(bar), "r"(x), "r"(y), "h"((uint16_t)3), "l"(pol_first()) : "memory");
  else asm volatile("cp.async.bulk.tensor.2d.shared::cluster.global.mbarrier::complete_tx::bytes.multicast::cluster [%0], [%1, {%3, %4}], [%2], %5;" :: "r"(dst), "l"(m), "r"(bar), "r"(x), "r"(y), "h"((uint16_t)3) : "memory");
}
__device__ __forceinline__ void tma3d_mc(uint32_t dst, const CUtensorMap* m, int x, int y, int z, uint32_t bar, bool stream = false) {
  if (stream) asm volatile("cp.async.bulk.tensor.3d.shared::cluster.global.mbarrier::complete_tx::bytes.multicast::cluster.L2::cache_hint [%0], [%1, {%3, %4, %5}], [%2], %6, %7;" :: "r"(dst), "l"(m), "r"(bar), "r"(x), "r"(y), "r"(z), "h"((uint16_t)3), "l"(pol_first()) : "memory");
  else asm volatile("cp.async.bulk.tensor.3d.shared::cluster.global.mbarrier::complete_tx::bytes.multicast::cluster [%0], [%1, {%3, %4, %5}], [%2], %6;" :: "r"(dst), "l"(m), "r"(bar), "r"(x), "r"(y), "r"(z), "h"((uint16_t)3) : "memory");
}
__device__ __forceinline__ void tma2d_store(const CUtensorMap* m, uint32_t src, int x, int y) {
  if (POL(12)) asm volatile("cp.async.bulk.tensor.2d.global.shared::cta.bulk_group.L2::cache_hint [%0, {%2, %3}], [%1], %4;" :: "l"(m), "r"(src), "r"(x), "r"(y), "l"(pol_first()) : "memory");
  else asm volatile("cp.async.bulk.tensor.2d.global.shared::cta.bulk_group [%0, {%2, %3}], [%1];" :: "l"(m), "r"(src), "r"(x), "r"(y) : "memory");
}
__device__ __forceinline__ bool elect() {
  uint32_t r; asm volatile("{\n.reg .pred p;\nelect.sync _|p, 0xffffffff;\nselp.u32 %0, 1, 0, p;\n}\n" : "=r"(r)); return r != 0;
}
__device__ __forceinline__ void cluster_arrive() { asm volatile("barrier.cluster.arrive;" ::: "memory"); }
__device__ __forceinline__ void cluster_wait() { asm volatile("barrier.cluster.wait;" ::: "memory"); }
__device__ __forceinline__ void bar_sync(int id, int n) { asm volatile("bar.sync %0, %1;" :: "r"(id), "r"(n) : "memory"); }
__device__ __forceinline__ void bar_arrive(int id, int n) { asm volatile("bar.arrive %0, %1;" :: "r"(id), "r"(n) : "memory"); }
__device__ __forceinline__ int bar_and(int id, int n, int pred) {
  int r; asm volatile("{\n.reg .pred p, q;\nsetp.ne.b32 p, %3, 0;\nbar.red.and.pred q, %1, %2, p;\nselp.b32 %0, 1, 0, q;\n}\n" : "=r"(r) : "r"(id), "r"(n), "r"(pred) : "memory");
  return r;
}
__device__ __forceinline__ void fence_async_smem() { asm volatile("fence.proxy.async.shared::cta;" ::: "memory"); }
__device__ __forceinline__ float ex2(float x) { float y; asm("ex2.approx.ftz.f32 %0, %1;" : "=f"(y) : "f"(x)); return y; }
__device__ __forceinline__ uint32_t pack_bf16(float lo, float hi) { uint32_t r; asm("cvt.rn.bf16x2.f32 %0, %1, %2;" : "=r"(r) : "f"(hi), "f"(lo)); return r; }
__device__ __forceinline__ uint32_t hmul2(uint32_t a, uint32_t b) { uint32_t r; asm("mul.rn.bf16x2 %0, %1, %2;" : "=r"(r) : "r"(a), "r"(b)); return r; }
__device__ __forceinline__ uint32_t hadd2(uint32_t a, uint32_t b) { uint32_t r; asm("add.rn.bf16x2 %0, %1, %2;" : "=r"(r) : "r"(a), "r"(b)); return r; }
__device__ __forceinline__ uint32_t hfma2(uint32_t a, uint32_t b, uint32_t c) { uint32_t r; asm("fma.rn.bf16x2 %0, %1, %2, %3;" : "=r"(r) : "r"(a), "r"(b), "r"(c)); return r; }
__device__ __forceinline__ float bf_lo(uint32_t a) { return __uint_as_float(a << 16); }
__device__ __forceinline__ float bf_hi(uint32_t a) { return __uint_as_float(a & 0xffff0000u); }
__device__ __forceinline__ uint32_t lds32(uint32_t a) { uint32_t v; asm volatile("ld.shared.u32 %0, [%1];" : "=r"(v) : "r"(a) : "memory"); return v; }
__device__ __forceinline__ float2 lds64f(uint32_t a) { float2 v; asm volatile("ld.shared.v2.f32 {%0,%1}, [%2];" : "=f"(v.x), "=f"(v.y) : "r"(a) : "memory"); return v; }
__device__ __forceinline__ uint4 lds128(uint32_t a) { uint4 v; asm volatile("ld.shared.v4.u32 {%0,%1,%2,%3}, [%4];" : "=r"(v.x), "=r"(v.y), "=r"(v.z), "=r"(v.w) : "r"(a) : "memory"); return v; }
__device__ __forceinline__ void sts64f(uint32_t a, float x, float y) { asm volatile("st.shared.v2.f32 [%0], {%1,%2};" :: "r"(a), "f"(x), "f"(y) : "memory"); }
__device__ __forceinline__ void sts128(uint32_t a, uint4 v) { asm volatile("st.shared.v4.u32 [%0], {%1,%2,%3,%4};" :: "r"(a), "r"(v.x), "r"(v.y), "r"(v.z), "r"(v.w) : "memory"); }
template<int OFF> __device__ __forceinline__ void sts128o(uint32_t a, uint4 v) { asm volatile("st.shared.v4.u32 [%0+%5], {%1,%2,%3,%4};" :: "r"(a), "r"(v.x), "r"(v.y), "r"(v.z), "r"(v.w), "n"(OFF) : "memory"); }
__device__ __forceinline__ void ldsm4(uint32_t a, uint32_t& r0, uint32_t& r1, uint32_t& r2, uint32_t& r3) {
  asm volatile("ldmatrix.sync.aligned.m8n8.x4.shared.b16 {%0,%1,%2,%3}, [%4];" : "=r"(r0), "=r"(r1), "=r"(r2), "=r"(r3) : "r"(a) : "memory");
}
__device__ __forceinline__ void ldsm4t(uint32_t a, uint32_t& r0, uint32_t& r1, uint32_t& r2, uint32_t& r3) {
  asm volatile("ldmatrix.sync.aligned.m8n8.x4.trans.shared.b16 {%0,%1,%2,%3}, [%4];" : "=r"(r0), "=r"(r1), "=r"(r2), "=r"(r3) : "r"(a) : "memory");
}
__device__ __forceinline__ void stsm4(uint32_t a, uint32_t r0, uint32_t r1, uint32_t r2, uint32_t r3) {
  asm volatile("stmatrix.sync.aligned.m8n8.x4.shared.b16 [%0], {%1,%2,%3,%4};" :: "r"(a), "r"(r0), "r"(r1), "r"(r2), "r"(r3) : "memory");
}
template<int N> __device__ __forceinline__ void fence_regs(float (&d)[N]) {
#pragma unroll
  for (int i = 0; i < N; i++) asm volatile("" : "+f"(d[i]) :: "memory");
}
template<int N> __device__ __forceinline__ void fence_regs(uint32_t (&d)[N]) {
#pragma unroll
  for (int i = 0; i < N; i++) asm volatile("" : "+r"(d[i]) :: "memory");
}
__device__ __forceinline__ void sched_fence(float x, uint32_t dummy) {
  asm volatile("{\n.reg .pred p;\nsetp.eq.u32 p, %0, 0x7fc12345;\n@p st.shared.u32 [%1], %0;\n}\n" :: "r"(__float_as_uint(x)), "r"(dummy) : "memory");
}
#define TS(role, i)
#define TSA(i)
#define TR(obj, role, tag)

#define SHADOW if (gridDim.y == 1)

struct Prod {
  uint32_t base, mask; int lane, nt;
  __device__ __forceinline__ uint32_t full(int u) const { return base + SM_BAR + 8 * u; }
  __device__ __forceinline__ uint32_t addr(int u) const { return base + u * UNIT; }
  __device__ __forceinline__ void acquire(int u, int n) {
    const int v = u + min(lane, n - 1);
    mbar_wait_all(base + SM_BAR + 128 + 8 * v, mask >> v);
    mask ^= ((1u << n) - 1) << u;
    TR(*this, 2, 16 + u);
  }
  __device__ __forceinline__ void acquire_slow(int u, int n) {
    for (int i = 0; i < n; i++) mbar_wait_slow(base + SM_BAR + 128 + 8 * (u + i), mask >> (u + i));
    mask ^= ((1u << n) - 1) << u;
  }
};
struct Cons {
  uint32_t base, rel, mask; int lane, warp, wg, nt;
  __device__ __forceinline__ uint32_t addr(int u) const { return base + u * UNIT; }
  __device__ __forceinline__ static uint32_t daddr(int u) { return SMEM_BASE + u * UNIT; }
  __device__ __forceinline__ void wait(int u) { TR(*this, wg, 1); mbar_wait(base + SM_BAR + 8 * u, mask >> u); mask ^= 1u << u; TR(*this, wg, 2); }
  __device__ __forceinline__ void skip(int u) { mask ^= 1u << u; }
  __device__ __forceinline__ void release(int u, int n) {
    TR(*this, wg, 5);
    asm volatile("{\n.reg .pred p;\nsetp.lt.s32 p, %1, %2;\n@p mbarrier.arrive.shared::cluster.b64 _, [%0];\n}\n" :: "r"(rel + 8 * u), "r"(lane & 15), "r"(n) : "memory");
  }
  __device__ __forceinline__ void release2(int u) {
    asm volatile("{\n.reg .pred p;\nsetp.eq.s32 p, %1, 0;\n@p mbarrier.arrive.shared::cluster.b64 _, [%0], 2;\n}\n" :: "r"(rel + 8 * u), "r"(lane & 15) : "memory");
  }
  __device__ __forceinline__ void signal(int i) {
    __syncwarp();
    asm volatile("{\n.reg .pred p;\nsetp.eq.s32 p, %1, 0;\n@p mbarrier.arrive.shared::cta.b64 _, [%0];\n}\n" :: "r"(base + SM_SIG + 8 * i), "r"(lane) : "memory");
  }
  __device__ __forceinline__ void turn() { bar_sync(1 + wg, 256); TR(*this, wg, 3); }
  __device__ __forceinline__ void pass() { bar_arrive(2 - wg, 256); TR(*this, wg, 4); }
};
__device__ __forceinline__ int gemm_unit(int ks) { return 3 * (ks & 3); }
__device__ __forceinline__ int att_slot(int i) { return 4 + 2 * i; }
template<int MASK> __device__ __forceinline__ int kv_slot(int h) { return MASK == PH_ALL ? h & 15 : h; }
__device__ __forceinline__ int out_mb(int cta) { return cta >> 3; }
__device__ __forceinline__ int out_nb(int cta) { return cta & 7; }
template<int MASK> constexpr int CV_REG = MASK == PH_ALL ? CONV_REG : 6;
template<int MASK> constexpr int CV_EXTRA = (1024 - NREG * CV_REG<MASK>) / (NCTA - NREG);
template<int MASK> __device__ __forceinline__ int conv_channel(int cta, int i) {
  return cta < NREG ? CV_EXTRA<MASK> * (NCTA - NREG) + cta * CV_REG<MASK> + i : (i >> 1) * 8 + (cta - NREG) * 2 + (i & 1);
}

template<int OFF, int N> __device__ __forceinline__ void pack_chunk(const float (&a)[N], float sc0, float sc1, uint4& v0, uint4& v1) {
  v0.x = pack_bf16(a[OFF + 0] * sc0, a[OFF + 1] * sc0); v0.y = pack_bf16(a[OFF + 4] * sc0, a[OFF + 5] * sc0);
  v0.z = pack_bf16(a[OFF + 8] * sc0, a[OFF + 9] * sc0); v0.w = pack_bf16(a[OFF + 12] * sc0, a[OFF + 13] * sc0);
  v1.x = pack_bf16(a[OFF + 2] * sc1, a[OFF + 3] * sc1); v1.y = pack_bf16(a[OFF + 6] * sc1, a[OFF + 7] * sc1);
  v1.z = pack_bf16(a[OFF + 10] * sc1, a[OFF + 11] * sc1); v1.w = pack_bf16(a[OFF + 14] * sc1, a[OFF + 15] * sc1);
}
template<int OFF, int N> __device__ __forceinline__ void pack_chunk(const float (&a)[N], uint4& v0, uint4& v1) {
  v0.x = pack_bf16(a[OFF + 0], a[OFF + 1]); v0.y = pack_bf16(a[OFF + 4], a[OFF + 5]);
  v0.z = pack_bf16(a[OFF + 8], a[OFF + 9]); v0.w = pack_bf16(a[OFF + 12], a[OFF + 13]);
  v1.x = pack_bf16(a[OFF + 2], a[OFF + 3]); v1.y = pack_bf16(a[OFF + 6], a[OFF + 7]);
  v1.z = pack_bf16(a[OFF + 10], a[OFF + 11]); v1.w = pack_bf16(a[OFF + 14], a[OFF + 15]);
}
__device__ __forceinline__ void sq_acc(const uint4& v, uint32_t& a) { a = hfma2(v.x, v.x, a); a = hfma2(v.y, v.y, a); a = hfma2(v.z, v.z, a); a = hfma2(v.w, v.w, a); }
__device__ __forceinline__ float norm2_max(uint32_t a0, uint32_t a1) {
  float n0 = bf_lo(a0) + bf_hi(a0), n1 = bf_lo(a1) + bf_hi(a1);
  n0 += __shfl_xor_sync(~0u, n0, 1); n1 += __shfl_xor_sync(~0u, n1, 1);
  n0 += __shfl_xor_sync(~0u, n0, 2); n1 += __shfl_xor_sync(~0u, n1, 2);
  return __uint_as_float(__reduce_max_sync(~0u, max(__float_as_uint(n0) & 0x7fffffffu, __float_as_uint(n1) & 0x7fffffffu)));
}

struct Pend { uint4 lo[8], hi[8]; uint32_t dst; float kn; };
__device__ __forceinline__ void pin(uint4 (&v)[8]) {
#pragma unroll
  for (int i = 0; i < 8; i++) asm volatile("" : "+r"(v[i].x), "+r"(v[i].y), "+r"(v[i].z), "+r"(v[i].w) :: "memory");
}
__device__ __forceinline__ uint32_t atom_off(int lane) { return (lane >> 2) * 64 + (((lane ^ (lane >> 3)) & 3) << 4); }
__device__ __forceinline__ void stg128(void* p, const uint4& v, bool stream) {
  if (stream) asm volatile("st.global.L2::cache_hint.v4.u32 [%0], {%1,%2,%3,%4}, %5;" :: "l"(p), "r"(v.x), "r"(v.y), "r"(v.z), "r"(v.w), "l"(pol_first()) : "memory");
  else *(uint4*)p = v;
}
template<int J0, int J1, bool STREAM = false> __device__ __forceinline__ void tile_store(const uint4 (&v)[8], uint32_t dst, int lane) {
  uint8_t* d = g_T + (dst + atom_off(lane));
#pragma unroll
  for (int j = J0; j < J1; j++) { stg128(d + j * 512, v[2 * j], STREAM); stg128(d + j * 512 + 2048, v[2 * j + 1], STREAM); }
}
__device__ __forceinline__ float tile_norm2(const uint4 (&v)[8]) {
  uint32_t n0 = 0, n1 = 0, n2 = 0, n3 = 0;
#pragma unroll
  for (int j = 0; j < 2; j++) { sq_acc(v[2 * j], n0); sq_acc(v[2 * j + 1], n1); sq_acc(v[2 * j + 4], n2); sq_acc(v[2 * j + 5], n3); }
  return norm2_max(hadd2(n0, n2), hadd2(n1, n3));
}
template<int PART> __device__ __forceinline__ void out_part(Cons& c, Pend& w) {
  if (PART == 0) { w.kn = tile_norm2(w.lo); tile_store<0, 2>(w.lo, w.dst, c.lane); }
  if (PART == 1) tile_store<2, 4>(w.lo, w.dst, c.lane);
  if (PART == 2) {
    const float vn = tile_norm2(w.hi);
    if (c.lane == 0) g_kn2[((w.dst - T_KV) >> 16) * 8 + c.wg * 4 + c.warp] = (vn <= 1.0e30f && vn >= 1.0e-30f) ? w.kn : __uint_as_float(0x7f800000u);
    tile_store<0, 2, POL(11)>(w.hi, w.dst + 32768, c.lane);
  }
  if (PART == 3) tile_store<2, 4, POL(11)>(w.hi, w.dst + 32768, c.lane);
}
template<bool FIRST> __device__ __forceinline__ void kv_issue(Cons& c, float (&acc)[128], int u) {
  const uint64_t da = odesc(c.daddr(u) + c.wg * 8192, 16, 1024, 1), db = odesc(c.daddr(u + 1), 8192, 1024, 1);
  c.turn();
  wg_fence();
#pragma unroll
  for (int kk = 0; kk < 4; kk++) wgmma_ss_n256<1>(acc, da + kk * 2, db + kk * 128, !(FIRST && kk == 0));
  wg_commit();
  c.pass();
}
template<bool NEXT> __device__ __forceinline__ void cons_kv(Cons& c, int h, int hs, int g, Pend& w, bool pend_o) {
#pragma unroll 1
  for (int tile = 0; tile < 2; tile++) {
    float acc[128];
    if (tile == 0) c.wait(0);
    if (tile == 0 && h < 16) TS(c.wg, 16);
    kv_issue<true>(c, acc, 0);
    c.release(9, tile == 1 ? 3 : 0);
    if (tile == 1 && pend_o) mbar_wait(c.base + SM_RDY + 8 * RDY_WAR, 0);
    if (tile == 1 || pend_o) out_part<0>(c, w);
#pragma unroll 1
    for (int ks = 1; ks < 8; ks++) {
      if (ks == 3 && (tile == 1 || pend_o)) { out_part<1>(c, w); if (tile == 0) c.signal(SIG_CTX); }
      if (ks == 5 && tile == 1) out_part<2>(c, w);
      if (ks == 7 && tile == 1) out_part<3>(c, w);
      const int u = gemm_unit(ks);
      c.wait(u);
      wg_wait<0>();
      c.release(gemm_unit(ks - 1), 3);
      kv_issue<false>(c, acc, u);
    }
    if (NEXT || tile == 0) c.wait(0);
    wg_wait<0>(); fence_regs(acc);
    if (!NEXT) c.release(9, tile == 1 ? 3 : 0);
    pack_chunk<0>(acc, w.lo[0], w.lo[1]);  pack_chunk<16>(acc, w.lo[2], w.lo[3]); pack_chunk<32>(acc, w.lo[4], w.lo[5]); pack_chunk<48>(acc, w.lo[6], w.lo[7]);
    pack_chunk<64>(acc, w.hi[0], w.hi[1]); pack_chunk<80>(acc, w.hi[2], w.hi[3]); pack_chunk<96>(acc, w.hi[4], w.hi[5]); pack_chunk<112>(acc, w.hi[6], w.hi[7]);
    pin(w.lo); pin(w.hi);
    w.dst = T_KV + (hs * 16 + 2 * g + tile) * 65536 + (c.wg * 4 + c.warp) * 4096;
  }
}
template<bool FIRST> __device__ __forceinline__ void q_issue(Cons& c, float (&a)[64], float (&b)[64], int u) {
  const uint64_t da = odesc(c.daddr(u) + c.wg * 8192, 16, 1024, 1), db = odesc(c.daddr(u + 2), 8192, 1024, 1);
  const uint64_t da2 = odesc(c.daddr(u + 1) + (1 - c.wg) * 8192, 16, 1024, 1);
  c.turn();
  wg_fence();
#pragma unroll
  for (int kk = 0; kk < 4; kk++) wgmma_ss_n128<1>(a, da + kk * 2, db + kk * 128, !(FIRST && kk == 0));
#pragma unroll
  for (int kk = 0; kk < 4; kk++) wgmma_ss_n128<1>(b, da2 + kk * 2, db + kk * 128, !(FIRST && kk == 0));
  wg_commit();
  c.pass();
}
template<int U14, int U15> __device__ __forceinline__ void q_tail(Cons& c, float (&d)[64], int rowhalf) {
  const uint64_t da = odesc(c.daddr(U14) + rowhalf * 8192, 16, 1024, 1), db = odesc(c.daddr(7), 8192, 1024, 1);
  c.turn();
  wg_fence();
#pragma unroll
  for (int kk = 0; kk < 8; kk++) wgmma_ss_n128<1>(d, da + (kk >> 2) * (U15 - U14) * 1024 + (kk & 3) * 2, db + (kk >> 2) * 4096 + (kk & 3) * 128, 1);
  wg_commit();
  c.pass();
}
template<int OFF> __device__ __forceinline__ void q_store(const float (&d)[64], uint4 (&v)[8], uint32_t q0) {
  pack_chunk<0>(d, QSCALE, QSCALE, v[0], v[1]);  sts128o<OFF>(q0, v[0]);        sts128o<OFF + 2048>(q0, v[1]);
  pack_chunk<16>(d, QSCALE, QSCALE, v[2], v[3]); sts128o<OFF + 512>(q0, v[2]);  sts128o<OFF + 2560>(q0, v[3]);
  pack_chunk<32>(d, QSCALE, QSCALE, v[4], v[5]); sts128o<OFF + 1024>(q0, v[4]); sts128o<OFF + 3072>(q0, v[5]);
  pack_chunk<48>(d, QSCALE, QSCALE, v[6], v[7]); sts128o<OFF + 1536>(q0, v[6]); sts128o<OFF + 3584>(q0, v[7]);
}
template<bool PEND_KV> __device__ __forceinline__ void cons_q(Cons& c, int h, Pend& w, float (&b)[64]) {
  float a[64];
  if (!PEND_KV) c.wait(0);
  q_issue<true>(c, a, b, 0);
  if (PEND_KV) { c.release(9, 3); SHADOW out_part<0>(c, w); }
#pragma unroll 1
  for (int ks = 1; ks < 14; ks++) {
    if (PEND_KV && ks < 6) {
      if (ks == 2) out_part<1>(c, w);
      if (ks == 4) out_part<2>(c, w);
      if (ks == 5) { out_part<3>(c, w); c.signal(SIG_KV + (h >> 4)); }
    }
    const int u = gemm_unit(ks);
    c.wait(u);
    wg_wait<0>();
    c.release(gemm_unit(ks - 1), 3);
    q_issue<false>(c, a, b, u);
  }
  c.wait(6); c.wait(9);
  wg_wait<0>();
  c.release(3, 3);
  q_tail<8, 9>(c, b, 1 - c.wg);
  wg_wait<0>(); fence_regs(b);
  c.release(8, 2);
  q_tail<6, 10>(c, a, c.wg);
  c.wait(0);
  const uint32_t q0 = c.addr(0) + (c.wg * 4 + c.warp) * 4096 + atom_off(c.lane);
  SHADOW { uint4 v[8]; q_store<32768>(b, v, q0); w.kn = tile_norm2(v); }
  c.wait(4);
  wg_wait<0>(); fence_regs(a);
  c.release(6, 2); c.release(10, 2);
  q_store<0>(a, w.lo, q0);
  fence_async_smem();
}

__device__ __forceinline__ void issue_qk(float (&s)[64], uint64_t da, uint64_t db) {
#pragma unroll
  for (int kk = 0; kk < 8; kk++) wgmma_ss_n128<0>(s, da + (kk >> 1) * 32 + (kk & 1) * 2, db + (kk >> 1) * 32 + (kk & 1) * 2, kk > 0);
  wg_commit();
}
template<int A, int B> __device__ __forceinline__ void exp_rng(float (&s)[64]) {
#pragma unroll
  for (int i = 4 * A; i < 4 * B; i++) s[i] = ex2(s[i]);
}
template<int A, int B> __device__ __forceinline__ void sum_rng(const float (&s)[64], float (&l)[4]) {
#pragma unroll
  for (int i = A; i < B; i++) { l[0] += s[4 * i]; l[1] += s[4 * i + 1]; l[2] += s[4 * i + 2]; l[3] += s[4 * i + 3]; }
}
template<int A, int B> __device__ __forceinline__ void cvt_p(const float (&s)[64], uint32_t (&p)[32]) {
#pragma unroll
  for (int i = 2 * A; i < 2 * B; i++) p[i] = pack_bf16(s[2 * i], s[2 * i + 1]);
}
template<int K0> __device__ __forceinline__ void mask_half(float (&s)[64], int warp, int lane) {
  const int l0 = warp + (2 * (lane & 3) <= (lane >> 2)), l1 = warp + (2 * (lane & 3) < (lane >> 2));
#pragma unroll
  for (int k = 0; k < 4; k++) {
    float* t = s + 8 * (K0 + k);
    if (k >= l0) { t[0] = -INFINITY; t[6] = -INFINITY; }
    if (k >= l1) { t[1] = -INFINITY; t[7] = -INFINITY; }
    if (k > warp) { t[2] = -INFINITY; t[3] = -INFINITY; }
    if (k >= warp) { t[4] = -INFINITY; t[5] = -INFINITY; }
  }
}
__device__ __forceinline__ void row_inv(float& l0, float& l1) {
  l0 += __shfl_xor_sync(~0u, l0, 1); l1 += __shfl_xor_sync(~0u, l1, 1);
  l0 += __shfl_xor_sync(~0u, l0, 2); l1 += __shfl_xor_sync(~0u, l1, 2);
  l0 = __fdividef(1.f, l0); l1 = __fdividef(1.f, l1);
}
__device__ __forceinline__ void pack_o(const float (&o)[64], float i0, float i1, uint4 (&v)[8]) {
  pack_chunk<0>(o, i0, i1, v[0], v[1]); pack_chunk<16>(o, i0, i1, v[2], v[3]);
  pack_chunk<32>(o, i0, i1, v[4], v[5]); pack_chunk<48>(o, i0, i1, v[6], v[7]);
  pin(v);
}
__device__ __forceinline__ void softmax_safe(float (&s)[64], bool upper_only, float& m0, float& m1, float& sc0, float& sc1) {
  float a0 = m0, a1 = m1;
#pragma unroll
  for (int i = 0; i < 8; i++) { a0 = fmaxf(a0, fmaxf(s[4 * i], s[4 * i + 1])); a1 = fmaxf(a1, fmaxf(s[4 * i + 2], s[4 * i + 3])); }
  if (upper_only) { a0 = m0; a1 = m1; }
#pragma unroll
  for (int i = 8; i < 16; i++) { a0 = fmaxf(a0, fmaxf(s[4 * i], s[4 * i + 1])); a1 = fmaxf(a1, fmaxf(s[4 * i + 2], s[4 * i + 3])); }
  a0 = fmaxf(a0, __shfl_xor_sync(~0u, a0, 1)); a1 = fmaxf(a1, __shfl_xor_sync(~0u, a1, 1));
  a0 = fmaxf(a0, __shfl_xor_sync(~0u, a0, 2)); a1 = fmaxf(a1, __shfl_xor_sync(~0u, a1, 2));
  sc0 = ex2(m0 - a0); sc1 = ex2(m1 - a1);
  m0 = a0; m1 = a1;
#pragma unroll
  for (int i = 0; i < 16; i++) { s[4 * i] -= a0; s[4 * i + 1] -= a0; s[4 * i + 2] -= a1; s[4 * i + 3] -= a1; }
}
struct Att {
  float s[64], o[64], l[4], i0, i1; uint32_t p[32];
  uint32_t qaddr;
};
__device__ __forceinline__ uint32_t ctx_off(const Cons& c, int h, int qb, int rowhalf) { return T_CTX + (qb * 32 + h) * 32768 + (rowhalf * 4 + c.warp) * 4096; }
__device__ __forceinline__ int att_first(Cons& c, Att& a, int h, const Pend& w) {
  a.qaddr = c.daddr(0) + c.wg * 16384;
  c.turn();
  wg_fence();
  issue_qk(a.s, odesc(a.qaddr, 16, 2048, 2), odesc(c.daddr(4), 16, 2048, 2));
  c.pass();
  c.signal(SIG_ATT + (h >> 4));
  float qn = w.kn;
  SHADOW qn = tile_norm2(w.lo);
  const float kn = __uint_as_float(lds32(c.base + SM_KMAX + 4 * (h >> 4)));
  const int fast = __shfl_sync(~0u, bar_and(3 + c.wg, 128, (qn * kn <= BOUND2) && (w.kn * kn <= BOUND2)), 0);
#pragma unroll
  for (int i = 0; i < 8; i++) { a.p[4 * i] = w.lo[i].x; a.p[4 * i + 1] = w.lo[i].y; a.p[4 * i + 2] = w.lo[i].z; a.p[4 * i + 3] = w.lo[i].w; }
  a.l[0] = a.l[1] = a.l[2] = a.l[3] = 0.f; a.i0 = a.i1 = 0.f;
  wg_wait<0>(); fence_regs(a.s);
  c.release(4, 2);
  return fast;
}
__device__ __forceinline__ void att_last(Cons& c, Att& a, Pend& w, int h, int g, bool drain) {
#pragma unroll 1
  for (int k = drain ? 0 : 1; k < 2; k++) {
    if (k == 1) {
      const int uv = att_slot(1);
      c.wait(uv);
      c.turn();
      fence_regs(a.o); fence_regs(a.p);
      wgmma_pv_sel(a.o, a.p, odesc(c.daddr(uv), 512, 2048, 2), !(drain && c.wg == 1), !drain);
      c.pass();
      a.i0 = a.l[0] + a.l[1]; a.i1 = a.l[2] + a.l[3]; row_inv(a.i0, a.i1);
      wg_wait<0>(); fence_regs(a.o); fence_regs(a.p);
      c.release(uv, 2);
    }
    pack_o(a.o, a.i0, a.i1, w.lo);
    if (k == 0) tile_store<0, 4>(w.lo, ctx_off(c, h, 15, c.wg), c.lane);
  }
  w.dst = ctx_off(c, h, g, 1 - c.wg);
}
__device__ __forceinline__ void cons_att(Cons& c, Att& a, int h, int g, Pend& w) {
  const int fast = att_first(c, a, h, w);
  float m0 = -INFINITY, m1 = -INFINITY, sc0 = 0.f, sc1 = 0.f;
  int uk = 10, nrel = 0;
#pragma unroll 1
  for (int d = g - 15;;) {
    const bool lo = d == c.wg;
    if ((unsigned)d < 2 || !fast) {
      if ((unsigned)d < 2) mask_half<4>(a.s, c.warp, c.lane);
      if (!fast) {
        if (d == 1) m0 = m1 = -INFINITY;
        softmax_safe(a.s, lo, m0, m1, sc0, sc1);
        a.l[0] *= sc0; a.l[1] *= sc0; a.l[2] *= sc1; a.l[3] *= sc1;
      }
    }
    exp_rng<8, 16>(a.s); sum_rng<8, 16>(a.s, a.l);
    exp_rng<ATT_SPLIT, 8>(a.s);
    sched_fence(((a.l[0] + a.l[1]) + (a.l[2] + a.l[3])) + (ATT_SPLIT < 8 ? a.s[4 * ATT_SPLIT + 3] : 0.f), c.base + SM_DUMMY);
    wg_wait<0>(); fence_regs(a.o); fence_regs(a.p);
    c.release(14 - uk, nrel);
    nrel = 2; uk ^= 12;
    if (d == 0) a.qaddr += 32768;
    const uint64_t dq = odesc(a.qaddr, 16, 2048, 2), dk = odesc(c.daddr(uk) - (d + 1 == c.wg ? 16384 : 0), 16, 2048, 2), dv = odesc(c.daddr(14 - uk), 512, 2048, 2);
    if (!lo) { exp_rng<0, ATT_SPLIT>(a.s); sum_rng<0, 8>(a.s, a.l); cvt_p<0, 16>(a.s, a.p); }
    else if (gridDim.y == 1) cvt_p<8, 16>(a.s, a.p);
    if (!fast || d == g + 1) {
      if (!fast && d != 1) {
#pragma unroll
        for (int i = 0; i < 16; i++) { a.o[4 * i] *= sc0; a.o[4 * i + 1] *= sc0; a.o[4 * i + 2] *= sc1; a.o[4 * i + 3] *= sc1; }
      }
      if (d == g + 1) break;
    }
    d++;
    if (c.wg == 0) c.wait(uk); else c.skip(uk);
    c.turn();
    fence_regs(a.o); fence_regs(a.p);
    wg_fence();
    issue_qk(a.s, dq, dk);
    if (d == 2) {
      uint4 v[8];
      pack_o(a.o, a.i0, a.i1, v); tile_store<0, 4>(v, ctx_off(c, h, 15 - g, c.wg), c.lane);
    }
    wgmma_pv_sel(a.o, a.p, dv, !lo, d != 2 && d != g - 14);
    c.pass();
    if (d == 1) {
      a.i0 = a.l[0] + a.l[1]; a.i1 = a.l[2] + a.l[3]; row_inv(a.i0, a.i1);
      a.l[0] = a.l[1] = a.l[2] = a.l[3] = 0.f;
    }
    wg_wait<1>(); fence_regs(a.s);
    c.release(uk, 2);
    c.release(d == 0 ? 0 : 2, (d == 0 || d == g + 1) ? 2 : 0);
  }
  att_last(c, a, w, h, g, g == 0);
}

constexpr int CV_H = 1024, CV_U = 5120, CV_D = CV_U + 4128, CV_ROW = 1056;
template<int OFF> __device__ __forceinline__ uint32_t lds32o(uint32_t a) { uint32_t v; asm volatile("ld.shared.u32 %0, [%1+%2];" : "=r"(v) : "r"(a), "n"(OFF) : "memory"); return v; }
template<int G, int G1 = 16> __device__ __forceinline__ void conv_lda(uint32_t (&a)[64], uint32_t p) {
  a[4 * G + 0] = lds32o<-256 * G>(p);
  a[4 * G + 1] = lds32o<-256 * G - 128>(p);
  a[4 * G + 2] = lds32o<-256 * G + 16>(p);
  a[4 * G + 3] = lds32o<-256 * G - 112>(p);
  if constexpr (G + 1 < G1) conv_lda<G + 1, G1>(a, p);
}
struct CvAcc { float lo[16], hi[16]; };
__device__ __forceinline__ void fence_regs(CvAcc& d) { fence_regs(d.lo); fence_regs(d.hi); }
template<int R, int H> __device__ __forceinline__ void conv_mma_h(float (&d)[16], const uint32_t (&a)[64], uint64_t db) {
#pragma unroll
  for (int G = 0; G < 4 * R + 2 * H + 2; G++) wgmma_rs_n32<0>(d, a[4 * G], a[4 * G + 1], a[4 * G + 2], a[4 * G + 3], db + 64 * R + 32 * H - 16 * G, G > 0);
}
template<int R> __device__ __forceinline__ void conv_mma(CvAcc& d, const uint32_t (&a)[64], uint64_t db) { conv_mma_h<R, 0>(d.lo, a, db); conv_mma_h<R, 1>(d.hi, a, db); }
template<int C0> __device__ __forceinline__ void conv_st_h(const float (&d)[16], uint32_t wq, float& c0, float& c1) {
#pragma unroll
  for (int n = 0; n < 4; n++) { sts64f(wq + (C0 + n * 8) * 4, d[4 * n] + c0, d[4 * n + 1] + c1); c0 = d[4 * n + 2]; c1 = d[4 * n + 3]; }
}
template<int R> __device__ __forceinline__ void conv_st(const CvAcc& d, uint32_t wq, float& c0, float& c1) { conv_st_h<64 * R>(d.lo, wq, c0, c1); conv_st_h<64 * R + 32>(d.hi, wq, c0, c1); }
struct ConvTail { float t[64]; uint4 ua, uc; uint32_t D2; };
__device__ __forceinline__ void conv_emit(ConvTail& e, int ch, int tid) {
  fence_regs(e.t);
  float y[16];
#pragma unroll
  for (int i = 0; i < 16; i++) y[i] = (e.t[i] + e.t[16 + i]) + (e.t[32 + i] + e.t[48 + i]);
  uint4 z0, z1;
  z0.x = hadd2(pack_bf16(y[0], y[2]), hmul2(__byte_perm(e.ua.w, 0, 0x1032), e.D2));
  z0.y = hadd2(pack_bf16(y[4], y[6]), hmul2(__byte_perm(e.ua.z, 0, 0x1032), e.D2));
  z0.z = hadd2(pack_bf16(y[8], y[10]), hmul2(__byte_perm(e.ua.y, 0, 0x1032), e.D2));
  z0.w = hadd2(pack_bf16(y[12], y[14]), hmul2(__byte_perm(e.ua.x, 0, 0x1032), e.D2));
  z1.x = hadd2(pack_bf16(y[1], y[3]), hmul2(__byte_perm(e.uc.w, 0, 0x1032), e.D2));
  z1.y = hadd2(pack_bf16(y[5], y[7]), hmul2(__byte_perm(e.uc.z, 0, 0x1032), e.D2));
  z1.z = hadd2(pack_bf16(y[9], y[11]), hmul2(__byte_perm(e.uc.y, 0, 0x1032), e.D2));
  z1.w = hadd2(pack_bf16(y[13], y[15]), hmul2(__byte_perm(e.uc.x, 0, 0x1032), e.D2));
  uint4* zp = (uint4*)(g_z + (uint32_t)(ch * 2048 + tid * 16));
  zp[0] = z0; zp[1] = z1;
}
template<int MASK> __device__ __forceinline__ void cons_conv(Cons& c, int cta, int nch) {
  const int r = c.lane >> 2, q = c.lane & 3, tid = c.warp * 32 + c.lane;
  const uint32_t part = c.addr(4) - 2048 + (1 - c.wg) * (32 * CV_ROW) + 32;
  const uint32_t aoff = CV_U + ((r & 1) ? 0 : UPITCH) + 4 * (((2039 - r) >> 1) + q - 8 * c.warp);
  const uint32_t wq = part + (c.warp * 8 + r) * CV_ROW + q * 8, rq = part + tid * 8;
  uint32_t a[64];
  ConvTail e = {};
  c.wait(c.wg); c.skip(c.wg ^ 1);
  conv_lda<0>(a, c.addr(c.wg) + aoff);
  c.wait(4);
  sts64f(part + (tid >> 2) * CV_ROW - 32 + q * 8, 0.f, 0.f);
#pragma unroll 1
  for (int i = 0; i < nch / 2; i++) {
    const int u = 2 * (i & 1) + c.wg;
    CvAcc d0, d1, d2, d3;
    float c0 = 0.f, c1 = 0.f;
    const uint64_t db = odesc(c.daddr(u) + CV_H - 16, 16, 128, 0);
    c.turn();
    fence_regs(a);
    wg_fence();
    conv_mma<0>(d0, a, db); conv_mma<1>(d1, a, db); wg_commit();
    if (i > 0) {
      conv_emit(e, conv_channel<MASK>(cta, 2 * i - 2 + c.wg), tid);
      if ((i & 15) == 0) c.signal(SIG_Z + (i >> 4) - 1);
    }
    wg_fence();
    conv_mma_h<2, 0>(d2.lo, a, db); wg_commit();
    wg_wait<1>(); fence_regs(d0); fence_regs(d1);
    conv_st_h<0>(d0.lo, wq, c0, c1);
    wg_fence();
    conv_mma_h<2, 1>(d2.hi, a, db); wg_commit();
    conv_st_h<32>(d0.hi, wq, c0, c1);
    conv_mma_h<3, 0>(d3.lo, a, db);
    conv_st_h<64>(d1.lo, wq, c0, c1);
    conv_mma_h<3, 1>(d3.hi, a, db); wg_commit();
    c.pass();
    const int un = i + 1 < nch / 2 ? u ^ 2 : u;
    if (un != u) { c.wait(un); c.skip(un ^ 1); }
    wg_wait<1>(); fence_regs(d2);
    conv_st_h<96>(d1.hi, wq, c0, c1);
    conv_st<2>(d2, wq, c0, c1);
    {
      const int sw = (c.lane >> 2) & 1;
      const uint4 v0 = lds128(c.addr(u) + CV_U + 4064 - 32 * tid + 16 * sw), v1 = lds128(c.addr(u) + CV_U + 4080 - 32 * tid - 16 * sw);
      e.ua = sw ? v0 : v1; e.uc = sw ? v1 : v0;
    }
    e.D2 = lds32(c.addr(u) + CV_D);
    wg_wait<0>(); fence_regs(d3); fence_regs(a);
    conv_st<3>(d3, wq, c0, c1);
    conv_lda<0, 4>(a, c.addr(un) + aoff);
    bar_sync(3 + c.wg, 128);
    sched_fence(__uint_as_float(e.ua.x ^ e.uc.x ^ e.D2), c.base + SM_DUMMY);
    c.release2(u);
    conv_lda<4, 16>(a, c.addr(un) + aoff);
#pragma unroll
    for (int k = 0; k < 32; k++) { const float2 v = lds64f(rq + k * CV_ROW - (k >> 3) * 8); e.t[2 * k] = v.x; e.t[2 * k + 1] = v.y; }
  }
  conv_emit(e, conv_channel<MASK>(cta, nch - 2 + c.wg), tid);
  c.signal(SIG_Z + ((nch / 2 - 1) >> 4));
  c.release(4, 4);
}

constexpr int OC_START = 2, OC_LEN = 15, OC_PART = 13824, OC_ROW = 544;
__device__ __forceinline__ int out_next(int u) { return u == 12 ? 4 : u + 2; }
struct Out { float acc[64]; int pu; uint64_t da, db; };
template<bool FIRST, bool REL> __device__ __forceinline__ void out_step(Cons& c, Out& o) {
  const int pu = o.pu, u = out_next(pu);
  o.pu = u;
  c.wait(u);
  const uint64_t da = o.da + (uint32_t)(u * 1024), db = o.db + (uint32_t)(u * 1024);
  wg_fence();
#pragma unroll
  for (int kk = 0; kk < 4; kk++) wgmma_ss_n128<1>(o.acc, da + (kk >> 1) * 32 + (kk & 1) * 2, db + kk * 128, !(FIRST && kk == 0));
  wg_commit();
  if (REL) { wg_wait<1>(); c.release(pu, 2); }
}
template<int I0, int I1> __device__ __forceinline__ void oc_red(float (&y)[8], uint32_t rq) {
#pragma unroll
  for (int i = I0; i < I1; i++) { const float v = __uint_as_float(lds32(rq + i * OC_ROW - (i >> 3) * 8)); y[i & 7] = i < 8 ? v : y[i & 7] + v; }
}
__device__ __forceinline__ void oc_emit(const float (&y)[8], const uint4& u, uint32_t D2, __nv_bfloat16* dst) {
  uint4 z;
  z.x = hadd2(pack_bf16(y[0], y[1]), hmul2(__byte_perm(u.w, 0, 0x1032), D2));
  z.y = hadd2(pack_bf16(y[2], y[3]), hmul2(__byte_perm(u.z, 0, 0x1032), D2));
  z.z = hadd2(pack_bf16(y[4], y[5]), hmul2(__byte_perm(u.y, 0, 0x1032), D2));
  z.w = hadd2(pack_bf16(y[6], y[7]), hmul2(__byte_perm(u.x, 0, 0x1032), D2));
  *(uint4*)dst = z;
}
template<int MASK> __device__ __forceinline__ void cons_out(Cons& c, const Maps& M, const Params& P, int cta, Pend& w) {
  const int mb = out_mb(cta), nb = out_nb(cta);
  Out o;
  o.da = odesc(c.daddr(0) + c.wg * 8192, 16, 1024, 2); o.db = odesc(c.daddr(1), 8192, 1024, 1);
  o.pu = 5 + gridDim.y;
  out_step<true, false>(c, o);
  if (MASK & PH_ATT) tile_store<0, 2>(w.lo, w.dst, c.lane);
  out_step<false, true>(c, o);
  if (MASK & PH_ATT) { tile_store<2, 4>(w.lo, w.dst, c.lane); c.signal(SIG_CTX + 1); }
  int ks = OC_START;
  if (MASK & PH_CONV) {
    const int r = c.lane >> 2, q = c.lane & 3, tid = c.warp * 32 + c.lane, u = 2 * c.wg;
    const uint32_t ub = c.addr(u), part = ub + OC_PART + 32;
    const uint32_t ap = ub + CV_U + ((r & 1) ? 0 : UPITCH) + 4 * (((2039 - r) >> 1) + q - 8 * c.warp);
    const uint32_t wq = part + (c.warp * 8 + r) * OC_ROW + q * 8, rq = part + tid * 4;
    const int nr = (CV_REG<MASK> + 1 - c.wg) >> 1;
#pragma unroll 1
    for (; ks < (c.wg ? OC_S1 : OC_S0); ks++) out_step<false, true>(c, o);
#define STEP(N) out_step<false, true>(c, o);
#pragma unroll 1
    for (int i = 0; i < nr; i++) {
      uint32_t a[64];
      CvAcc d0, d1;
      float y[8], c0 = 0.f, c1 = 0.f;
      const uint64_t db = odesc(c.daddr(u + (i >> 8)) + CV_H - 16, 16, 128, 0);
      c.wait(u);
      conv_lda<0, 3>(a, ap);
      STEP(0)
      conv_lda<3, 6>(a, ap);
      STEP(1)
      conv_lda<6, 9>(a, ap);
      STEP(2)
      fence_regs(reinterpret_cast<uint32_t (&)[32]>(a));
      wg_fence();
      conv_mma<0>(d0, a, db); conv_mma<1>(d1, a, db); wg_commit();
      conv_lda<9, 13>(a, ap);
      STEP(3)
      fence_regs(d0); fence_regs(d1);
      conv_lda<13, 16>(a, ap);
      STEP(4)
      bar_sync(3 + c.wg, 128);
      sts64f(wq - 32, 0.f, 0.f);
      conv_st<0>(d0, wq, c0, c1);
      STEP(5)
      float e0 = d1.hi[12] + d1.hi[10], e1 = d1.hi[13] + d1.hi[11];
      conv_st<1>(d1, wq, c0, c1);
      asm volatile("add.f32 %0, %0, 0f80000000;" : "+f"(c0)); asm volatile("add.f32 %0, %0, 0f80000000;" : "+f"(c1));
      fence_regs(a);
      wg_fence();
      conv_mma<2>(d0, a, db); conv_mma<3>(d1, a, db); wg_commit();
      bar_sync(3 + c.wg, 128);
      oc_red<0, 8>(y, rq);
      STEP(6)
      fence_regs(d0); fence_regs(d1); fence_regs(a);
      const uint4 u0 = lds128(ub + CV_U + 4080 - 16 * tid), u1 = lds128(ub + CV_U + 2032 - 16 * tid);
      const uint32_t D2 = lds32(ub + CV_D);
      oc_red<8, 12>(y, rq);
      STEP(7)
      sched_fence(__uint_as_float(u0.x ^ u1.x ^ D2), c.base + SM_DUMMY);
      __syncwarp();
      c.release2(u);
      oc_red<12, 24>(y, rq);
      STEP(8)
      __nv_bfloat16* zp = g_z + (uint32_t)(conv_channel<MASK>(cta, 2 * i + c.wg) * 2048 + (threadIdx.x & 127) * 8);
      oc_red<24, 32>(y, rq);
      oc_emit(y, u0, D2, zp);
      bar_sync(3 + c.wg, 128);
      STEP(9)
      sts64f(wq - 32, e0, e1);
      conv_st<0>(d0, wq, c0, c1);
      STEP(10)
      conv_st<1>(d1, wq, c0, c1);
      bar_sync(3 + c.wg, 128);
      oc_red<0, 8>(y, rq);
      STEP(11)
      oc_red<8, 16>(y, rq);
      STEP(12)
      oc_red<16, 24>(y, rq);
      STEP(13)
      oc_red<24, 32>(y, rq);
      oc_emit(y, u1, D2, zp + 1024);
      if (i == nr - 1) { c.signal(SIG_Z); c.release2(u + 1); }
      STEP(14)
    }
#undef STEP
    if (((CV_REG<MASK> + c.wg) >> 1) & 1) c.skip(u ^ 2);
    ks += nr * OC_LEN;
  }
  TS(c.wg, 9);
#pragma unroll 1
  for (; ks < 57; ks++) out_step<false, true>(c, o);
  uint32_t ga[32];
  c.wait(2);
  const float g0 = __uint_as_float(lds32(c.base + SM_GATE + 4 * (c.wg * 64 + c.warp * 16 + (c.lane >> 2)))), g1 = __uint_as_float(lds32(c.base + SM_GATE + 32 + 4 * (c.wg * 64 + c.warp * 16 + (c.lane >> 2))));
  const uint32_t gg0 = pack_bf16(g0, g0), gg1 = pack_bf16(g1, g1);
  const uint32_t og0 = pack_bf16(1.f - g0, 1.f - g0), og1 = pack_bf16(1.f - g1, 1.f - g1);
  const int xr = c.wg * 64 + c.warp * 16 + (c.lane & 15);
  const uint32_t xa = c.addr(2) + xr * 128, xs = xr & 7, xh = c.lane >> 4;
  const int zr = (c.lane & 7) + ((c.lane >> 4) << 3);
  const uint32_t za = c.addr(0) + c.wg * 16384 + zr * 128 + (((c.warp * 2 + ((c.lane >> 3) & 1)) ^ (zr & 7)) << 4);
#pragma unroll
  for (int i = 0; i < 8; i++) {
    if (i == 0) out_step<false, true>(c, o);
    if (i == 3) out_step<false, true>(c, o);
    if (i == 6) out_step<false, true>(c, o);
    ldsm4(xa + (i >> 2) * 16384 + ((((i & 3) * 2 + xh) ^ xs) << 4), ga[4 * i], ga[4 * i + 1], ga[4 * i + 2], ga[4 * i + 3]);
  }
#pragma unroll 1
  for (ks = 60; ks < 64; ks++) out_step<false, false>(c, o);
  c.wait(0);
  SHADOW {
#pragma unroll
    for (int i = 0; i < 8; i++) {
      uint32_t z0, z1, z2, z3;
      ldsm4t(za + i * 2048, z0, z1, z2, z3);
      ga[4 * i + 0] = hmul2(gg0, hmul2(ga[4 * i + 0], z0)); ga[4 * i + 1] = hmul2(gg1, hmul2(ga[4 * i + 1], z1));
      ga[4 * i + 2] = hmul2(gg0, hmul2(ga[4 * i + 2], z2)); ga[4 * i + 3] = hmul2(gg1, hmul2(ga[4 * i + 3], z3));
    }
  }
  c.signal(SIG_DONE);
  fence_regs(ga);
  wg_wait<0>(); fence_regs(o.acc);
#pragma unroll
  for (int i = 0; i < 8; i++) {
    const uint32_t r0 = hadd2(ga[4 * i + 0], hmul2(og0, pack_bf16(o.acc[8 * i + 0], o.acc[8 * i + 1])));
    const uint32_t r1 = hadd2(ga[4 * i + 1], hmul2(og1, pack_bf16(o.acc[8 * i + 2], o.acc[8 * i + 3])));
    const uint32_t r2 = hadd2(ga[4 * i + 2], hmul2(og0, pack_bf16(o.acc[8 * i + 4], o.acc[8 * i + 5])));
    const uint32_t r3 = hadd2(ga[4 * i + 3], hmul2(og1, pack_bf16(o.acc[8 * i + 6], o.acc[8 * i + 7])));
    stsm4(xa + (i >> 2) * 16384 + ((((i & 3) * 2 + xh) ^ xs) << 4), r0, r1, r2, r3);
    if ((i & 3) == 3) {
      __syncwarp();
#pragma unroll
      for (int k = 0; k < 4; k++) {
        const int rr = c.wg * 64 + c.warp * 16 + k * 4 + (c.lane >> 3);
        const uint4 v = lds128(c.addr(2 + (i >> 2)) + rr * 128 + (((c.lane ^ rr) & 7) << 4));
        *(uint4*)(P.out + (uint32_t)((mb * 128 + rr) * 1024 + nb * 128 + (i >> 2) * 64 + (c.lane & 7) * 8)) = v;
      }
    }
  }
}

__device__ __forceinline__ void load_conv(Prod& p, const Maps& M, int u, int ch) {
  if (elect()) {
    mbar_expect(p.full(u), 5120 + UCH);
    tma3d(p.addr(u), &M.h, 0, -8, ch, p.full(u), POL(4));
    bulk_g2s(p.addr(u) + CV_U, g_u + (size_t)ch * UCH, UCH, p.full(u), POL(4));
  }
}
template<int MASK> __device__ __forceinline__ void prod_conv(Prod& p, const Maps& M, int cta, int nch) {
  int ready = -1;
#pragma unroll 1
  for (int i = 0; i < nch; i++) {
    const int ch = conv_channel<MASK>(cta, i);
    const int u = i & 3;
    if ((ch >> 6) != ready) { ready = ch >> 6; if (cta < NREG) mbar_wait(p.base + SM_RDY + 8 * RDY_U, 0); else cnt_wait(g_cnt + (C_U + ready) * CSTRIDE, 128); }
    p.acquire(u, 1);
    load_conv(p, M, u, ch);
    if (i == 3) { p.acquire(4, 4); if (elect()) mbar_arrive(p.full(4)); }
  }
}
#define HOIST(v) asm volatile("" : "+r"(v))
template<int MASK> __device__ __forceinline__ void producer(const Maps& M, const Params& P, uint32_t base, int cta, int lane) {
  Prod p{base, ((MASK & PH_KV) && cta < NREG) ? 0xffffcfffu ^ ((1u << (3 * NFIRST)) - 1) : 0xffffffffu, lane,
         (cta * 3 + 2) * 2048};
  if (cta >= NREG) { if (MASK & PH_CONV) prod_conv<MASK>(p, M, cta, CV_EXTRA<MASK>); return; }
  const int g = cta & 7, j = cta >> 3, rank = cta & 1;
#pragma unroll 1
  for (int half = 0; half < 2; half++) {
    const int h = j + 16 * half;
    if (MASK & PH_KV) {
      const CUtensorMap* mw = rank ? &M.wv : &M.wk;
#pragma unroll 1
      for (int it = half ? 0 : NFIRST; it < 16; it++) {
        const int u = gemm_unit(it);
        uint32_t bar = p.full(u), d0 = p.addr(u), d1 = p.addr(u + 1 + rank); int k0 = (it & 7) * 64, r0 = (2 * g + (it >> 3)) * 128;
        HOIST(bar); HOIST(d0); HOIST(d1); HOIST(k0); HOIST(r0);
        p.acquire(u, 3);
        if (elect()) {
          mbar_expect(bar, 3 * UNIT);
          tma3d_mc(d1, mw, 0, k0, 2 * h, bar, POL(0) && it >= 8);
          tma2d(d0, &M.c, k0, r0, bar, half ? POL(8) : POL(10));
        }
      }
    }
    if (MASK & PH_ATT) {
#pragma unroll 1
      for (int ks = 0; ks < 16; ks++) {
        const int u = gemm_unit(ks);
        uint32_t bar = p.full(u), d0 = p.addr(u + (ks == 15)), d1 = p.addr(ks < 14 ? u + 1 : ks - 6), d2 = p.addr(u + 2 - (ks == 14)) + rank * 8192; int k0 = ks * 64;
        HOIST(bar); HOIST(d0); HOIST(d1); HOIST(d2); HOIST(k0);
        p.acquire(u, 3);
        if (elect()) {
          mbar_expect(bar, 3 * UNIT);
          tma2d_mc(d2, &M.wq, h * 128 + rank * 64, k0, bar, POL(1));
          tma2d(d0, &M.x, k0, (15 - g) * 128, bar, half ? POL(9) : POL(10));
          tma2d(d1, &M.x, k0, g * 128, bar, half ? POL(9) : POL(10));
        }
      }
      TS(2, 8 * half + 0);
      mbar_wait(base + SM_RDY + 8 * (RDY_KV + half), 0);
      TS(2, 8 * half + 1);
      p.acquire(0, 4);
      if (elect()) mbar_arrive(p.full(0));
      const uint8_t* KVh = g_T + T_KV + (size_t)kv_slot<MASK>(h) * 16 * 65536;
#pragma unroll 1
      for (int n = 0; n < 34; n++) {
        const int i = n == 1 ? 2 : n == 2 ? 1 : n;
        const int isv = (i > 0 && !(i & 1)) || i == 33;
        const int st = i == 33 ? 16 : (isv ? (i >> 1) - 1 : (i + 1) >> 1);
        const int u = att_slot(i & 3);
        const bool own = st == 15 - (g & 6);
        uint32_t bar = p.full((isv && i < 33) ? 14 - u : u), d0 = p.addr(own ? u : u + rank), off = (st <= 15 - g ? st : 16 - st) * 65536 + isv * 32768 + (own ? 0 : rank * UNIT);
        HOIST(bar); HOIST(d0); HOIST(off);
        p.acquire(u, 2);
        if (elect()) {
          if (!isv || i == 33) mbar_expect(bar, (i == 0 || i == 33) ? 32768 : 65536);
          const bool ef = POL(6) || (POL(14) && st >= 8) || (POL(15) && half);
          if (own) bulk_g2s(d0, KVh + off, 32768, bar, ef); else bulk_g2s_mc(d0, KVh + off, UNIT, bar, ef);
        }
      }
    }
  }
  if ((MASK & PH_CONV) && !(MASK & PH_OUT)) prod_conv<MASK>(p, M, cta, CV_REG<MASK>);
  if (MASK & PH_OUT) {
    const int y0 = out_mb(cta) * 512 + rank * 8, z0 = 2 * out_nb(cta);
    int u = 6;
#pragma unroll 1
    for (int hf = 0; hf < 2; hf++) {
      TS(2, 16 + 2 * hf);
      mbar_wait(base + SM_RDY + 8 * (RDY_CTX + hf), 0);
      TS(2, 17 + 2 * hf);
#pragma unroll 1
      for (int ks = hf * 32; ks < hf * 32 + 32; ks++) {
        u = out_next(u);
        uint32_t bar = p.full(u), d0 = p.addr(u) + rank * 8192, d1 = p.addr(u + 1); int x = (ks & 1) * 256, y = y0 + (ks >> 1) * 16, k0 = ks * 64;
        HOIST(bar); HOIST(d0); HOIST(d1); HOIST(x); HOIST(y); HOIST(k0);
        p.acquire(u, 2);
        if (elect()) {
          mbar_expect(bar, 2 * UNIT);
          tma2d_mc(d0, &M.ctx, x, y, bar, POL(5));
          tma3d(d1, &M.wo, 0, k0, z0, bar, POL(2));
          if (ks == Z_AT) mbar_arrive(base + SM_RDY + 8 * RDY_Z);
        }
      }
    }
  }
}
template<int MASK> __device__ __forceinline__ void producer2(const Maps& M, const Params& P, uint32_t base, int cta, int w, int lane) {
  Prod p{base, 0xffffffffu, lane, 0};
  const int mb = out_mb(cta), nb = out_nb(cta), u = 2 * w;
  if (MASK & PH_CONV) {
    mbar_wait_slow(base + SM_SIG + 8 * (SIG_ATT + 1), 0);
    mbar_wait_slow(base + SM_RDY + 8 * RDY_U, 0);
#pragma unroll 1
    for (int i = w; i < CV_REG<MASK>; i += 2) { p.acquire_slow(u, i < 2 ? 2 : 1); load_conv(p, M, u, conv_channel<MASK>(cta, i)); }
  }
  p.acquire_slow(u, 2);
  if (elect()) asm volatile("prefetch.tensormap [%0];" :: "l"(!w ? &M.z : &M.out) : "memory");
  TSA(52 - 2 * w);
  mbar_wait(base + SM_RDY + 8 * (!w ? RDY_Z : RDY_G), 0);
  TSA(53 - 2 * w);
  if (elect()) {
    mbar_expect(p.full(u), 2 * UNIT + (!w ? 0 : 512));
    tma2d(p.addr(u), !w ? &M.z : &M.x, (!w ? mb : nb) * 128, (!w ? nb : mb) * 128, p.full(u), POL(5));
    tma2d(p.addr(u + 1), !w ? &M.z : &M.x, (!w ? mb : nb) * 128 + 64, (!w ? nb : mb) * 128, p.full(u), POL(5));
    if (w) bulk_g2s(base + SM_GATE, g_gate + mb * 128, 512, p.full(u));
  }
}

__device__ __forceinline__ constexpr uint32_t PUB(int sig, int cnt, int n) { return 0x80000000u | (sig << 24) | (n << 8) | cnt; }
__device__ __forceinline__ constexpr uint32_t GET(int rdy, int cnt, int n) { return (rdy << 24) | (n << 8) | cnt; }
template<int MASK> __device__ __forceinline__ void sync_agent(uint32_t base, int cta, int lane) {
  if ((base & 0x3FFFF) != SMEM_BASE) asm volatile("trap;");
  const int g = cta & 7, j = cta >> 3, go = min(out_mb(cta), 15 - out_mb(cta));
  const int c0 = conv_channel<MASK>(cta, 0), c1 = c0 + CV_REG<MASK> - 1, n0 = min(CV_REG<MASK>, 128 - (c0 & 127));
  constexpr bool KV = MASK & PH_KV, ATT = MASK & PH_ATT, CONV = MASK & PH_CONV, OUT = MASK & PH_OUT, ALL = MASK == PH_ALL;
  uint32_t e = 0;
  if (cta >= NREG) { if (CONV && lane * 32 < CV_EXTRA<MASK>) e = PUB(SIG_Z + lane, C_Z + lane, min(32, CV_EXTRA<MASK> - lane * 32)); }
  else switch (lane) {
    case 0:  if (KV) e = PUB(SIG_KV, C_KV + j, 1); break;
    case 1:  if (ATT) e = GET(RDY_KV, C_KV + j, 8); break;
    case 2:  if (ALL) e = PUB(SIG_WAR, C_WAR + j, 1); break;
    case 3:  if (ATT) e = PUB(SIG_CTX, C_CTX + g, 1); break;
    case 4:  if (ALL) e = GET(RDY_WAR, C_WAR + j, 8); break;
    case 5:  if (KV) e = PUB(SIG_KV + 1, C_KV + 16 + j, 1); break;
    case 6:  if (ATT) e = GET(RDY_KV + 1, C_KV + 16 + j, 8); break;
    case 7:  if (OUT) e = GET(RDY_CTX, C_CTX + go, 16); break;
    case 8:  if (CONV) e = GET(RDY_U, C_U + (c0 >> 6), 128); break;
    case 9:  if (CONV) e = GET(RDY_U, C_U + (c1 >> 6), 128); break;
    case 10: if (ATT) e = PUB(SIG_CTX + 1, C_CTX + 8 + g, 1); break;
    case 11: if (OUT) e = GET(RDY_CTX + 1, C_CTX + 8 + go, 16); break;
    case 12: if (OUT) e = GET(RDY_G, C_GATE, 256); break;
    case 13: if (CONV) e = PUB(SIG_Z, C_Z + (c0 >> 7), n0); break;
    case 14: if (CONV && n0 < CV_REG<MASK>) e = PUB(SIG_Z, C_Z + (c1 >> 7), CV_REG<MASK> - n0); break;
    case 15: if (OUT) e = GET(RDY_Z, C_Z + out_nb(cta), 128); break;
  }
  __syncwarp();
#pragma unroll 1
  for (int i = 0; i < 16; i++) {
    const uint32_t x = __shfl_sync(~0u, e, i), id = (x >> 24) & 127, n = (x >> 8) & 0xffff;
    if (x == 0) continue;
    unsigned* cnt = g_cnt + (x & 255) * CSTRIDE;
    if (x >> 31) {
      mbar_wait_slow(base + SM_SIG + 8 * id, 0);
      if (lane == 0) cnt_publish(cnt, n);
    } else {
      cnt_wait(cnt, n);
      if (id < 2) {
        const float4 kn = __ldcg((const float4*)(g_kn2 + kv_slot<MASK>(j + 16 * id) * 128) + lane);
        const uint32_t m = __reduce_max_sync(~0u, max(max(__float_as_uint(kn.x), __float_as_uint(kn.y)), max(__float_as_uint(kn.z), __float_as_uint(kn.w))));
        if (lane == 0) asm volatile("st.shared.u32 [%0], %1;" :: "r"(base + SM_KMAX + 4 * id), "r"(m) : "memory");
      }
      if (lane == 0) mbar_arrive(base + SM_RDY + 8 * id);
    }
    __syncwarp();
  }
}

__device__ __forceinline__ void aux_gate(const Params& P, int cta, int aw, int lane) {
  uint4 gw[4];
#pragma unroll
  for (int i = 0; i < 4; i++) gw[i] = __ldg((const uint4*)P.gw + i * 32 + lane);
#pragma unroll 1
  for (int row = cta * 16 + aw * 8; row < cta * 16 + aw * 8 + 8; row++) {
    float a = 0.f;
#pragma unroll
    for (int i = 0; i < 4; i++) {
      const uint4 xv = __ldg((const uint4*)(P.x + (size_t)row * 1024) + i * 32 + lane);
      uint32_t m;
      m = hmul2(xv.x, gw[i].x); a += bf_lo(m) + bf_hi(m); m = hmul2(xv.y, gw[i].y); a += bf_lo(m) + bf_hi(m);
      m = hmul2(xv.z, gw[i].z); a += bf_lo(m) + bf_hi(m); m = hmul2(xv.w, gw[i].w); a += bf_lo(m) + bf_hi(m);
    }
#pragma unroll
    for (int o = 16; o > 0; o >>= 1) a += __shfl_xor_sync(~0u, a, o);
    a = bf_lo(pack_bf16(a, 0.f));
    const float gt = bf_lo(pack_bf16(__fdividef(1.f, 1.f + ex2(-a * 1.4426950408889634f)), 0.f));
    if (lane == 0) g_gate[row] = gt;
    if (GATE_SLEEP) __nanosleep(GATE_SLEEP);
  }
  cnt_signal(g_cnt + C_GATE * CSTRIDE, lane);
  if (aw == 0) { TSA(44); }
}
template<int MASK> __device__ __forceinline__ void aux_pre(const Maps& M, const Params& P, uint32_t base, int cta, int aw, int lane) {
  const uint32_t kb = base + 12 * UNIT, bar = base + SM_PRE;
  const int r = lane >> 2, q = lane & 3;
  const int mi = lane >> 3, row0 = (lane & 6) + 1 - (lane & 1);
  const int ra = (mi * 9 + 1) * 2 + row0;
  const int rb = (mi == 0 ? 3 : mi) * 18 + row0;
  if (PRE_DELAY) mbar_wait_slow(base + SM_BAR + 8 * PRE_DELAY_BAR, 0);
#pragma unroll 1
  for (int it = 0; it < (cta < 96 ? 5 : 4); it++) {
    if (GATE_EARLY && it == PRE_EARLY && MASK == PH_ALL) { mbar_wait_slow(base + SM_SIG + 8 * SIG_ATT, 0); aux_gate(P, cta, aw, lane); }
    if (it == PRE_EARLY && MASK == PH_ALL) mbar_wait_slow(base + SM_SIG + 8 * (SIG_ATT + PRE_HALF), 0);
    const int cg = it ? it * 4 - 3 + (cta >> 5) : 0, tb = cta & 31;
    if (aw == 0 && elect()) {
      mbar_expect(bar, 2 * 9216);
      tma4d(kb, &M.k, cg * 64, 0, tb * 8 - 1, 0, bar, POL(3));
      tma4d(kb + 9216, &M.v, cg * 64, 0, tb * 8 - 1, 0, bar, POL(3));
    }
    const uint2 swl = __ldg((const uint2*)(P.shift + (cg * 64 + aw * 32 + lane) * 4));
    if (tb == 0) {
      uint8_t* e = g_u + (size_t)(cg * 64 + aw * 32 + lane) * UCH + 4096;
      *(uint4*)e = make_uint4(0, 0, 0, 0); *(uint4*)(e + UPITCH) = make_uint4(0, 0, 0, 0);
      *(uint32_t*)(e + 32) = (uint32_t)__bfloat16_as_ushort(P.D[cg * 64 + aw * 32 + lane]) * 0x10001u;
    }
    mbar_wait_slow(bar, it & 1);
#pragma unroll 1
    for (int ol = it ? 0 : cta >> 5; ol < (it ? 4 : (cta >> 5) + 1); ol++) {
      const int oc = aw * 4 + ol;
      const uint32_t s01 = __shfl_sync(~0u, swl.x, ol * 8 + r), s23 = __shfl_sync(~0u, swl.y, ol * 8 + r);
      const uint32_t w0 = __byte_perm(s01, 0, 0x1010), w1 = __byte_perm(s01, 0, 0x3232), w2 = __byte_perm(s23, 0, 0x1010), w3 = __byte_perm(s23, 0, 0x3232);
      const uint32_t pa = kb + ra * 128 + ((oc ^ (ra & 7)) << 4), pb = kb + (mi == 0 ? 9216 : 0) + rb * 128 + ((oc ^ (rb & 7)) << 4);
      uint8_t* e0 = g_u + (uint32_t)((cg * 64 + oc * 8 + r) * UCH + (2040 - tb * 64 - 8 * q) * 2);
#pragma unroll
      for (int hb = 0; hb < 2; hb++) {
        uint32_t k[7], v[5];
        ldsm4t(pa + hb * 1024, k[3], k[4], k[5], k[6]);
        ldsm4t(pa + hb * 1024 + 9216, v[1], v[2], v[3], v[4]);
        ldsm4t(pb + hb * 1024, v[0], k[0], k[1], k[2]);
        uint32_t o1 = __byte_perm(k[1], k[0], 0x5432);
#pragma unroll
        for (int m = 0; m < 5; m++) {
          const uint32_t o2 = __byte_perm(k[m + 2], k[m + 1], 0x5432);
          v[m] = hmul2(hadd2(hadd2(hadd2(hmul2(o1, w3), hmul2(k[m + 1], w2)), hmul2(o2, w1)), hmul2(k[m + 2], w0)), v[m]);
          o1 = o2;
        }
        *(uint4*)(e0 - hb * 64) = make_uint4(v[4], v[3], v[2], v[1]);
        *(uint4*)(e0 - hb * 64 + UPITCH) = make_uint4(__byte_perm(v[4], v[3], 0x5432), __byte_perm(v[3], v[2], 0x5432), __byte_perm(v[2], v[1], 0x5432), __byte_perm(v[1], v[0], 0x5432));
        if (PRE_SLEEP && it >= PRE_EARLY) __nanosleep(PRE_SLEEP);
      }
    }
    bar_sync(5, 64);
    if (aw == 0) { TSA(40 + min(it, 3)); }
    if (aw == 1 && lane == 0) asm volatile("red.release.gpu.global.add.u32 [%0], %1;" :: "l"(g_cnt + (C_U + cg) * CSTRIDE), "r"(it ? 4 : 1) : "memory");
  }
  uint32_t rel;
  asm volatile("mapa.shared::cluster.u32 %0, %1, %2;" : "=r"(rel) : "r"(base + SM_BAR + 128 + 8 * (12 + (lane & 1))), "r"((lane >> 1) & 1));
  if (lane < 4) asm volatile("mbarrier.arrive.shared::cluster.b64 _, [%0], 4;" :: "r"(rel) : "memory");
  if (!(GATE_EARLY && MASK == PH_ALL)) aux_gate(P, cta, aw, lane);
}

template<int MASK> __global__ void __cluster_dims__(2, 1, 1) __launch_bounds__(384, 1) gated_mix_kernel(const __grid_constant__ Maps M, const __grid_constant__ Params P) {
  extern __shared__ __align__(1024) uint8_t smem[];
  const uint32_t base = (uint32_t)__cvta_generic_to_shared(smem);
  const int wi = __shfl_sync(~0u, threadIdx.x >> 5, 0), wg = wi >> 2, warp = wi & 3;
  if (elect()) {
    if (wi < 8) {
      const int cnt = 1 << ((0x10334400 >> (4 * wi)) & 15);
#pragma unroll
      for (int i = 0; i < 8; i++) mbar_init(base + SM_BAR + 64 * wi + 8 * i, cnt);
      asm volatile("fence.mbarrier_init.release.cluster;" ::: "memory");
    } else if (MAP_PF) {
      asm volatile("prefetch.tensormap [%0];" :: "l"(&M.c + (wi - 8)) : "memory");
    }
  }
  const int cta = blockIdx.x;
  const bool first_loads = (MASK & PH_KV) && wi == 8 && cta < NREG;
  const CUtensorMap* mw = (cta & 1) ? &M.wv : &M.wk;
  __syncwarp();
  asm volatile("barrier.cluster.arrive.relaxed.aligned;\nbarrier.cluster.wait.aligned;" ::: "memory");
  if (first_loads && elect()) {
#pragma unroll 1
    for (int it = 0; it < NFIRST; it++) {
      const uint32_t bar = base + SM_BAR + 24 * it, d0 = base + 3 * it * UNIT;
      mbar_expect(bar, 3 * UNIT);
      tma3d_mc(d0 + (1 + (cta & 1)) * UNIT, mw, 0, it * 64, 2 * (cta >> 3), bar);
      tma2d(d0, &M.c, it * 64, (cta & 7) * 256, bar);
    }
  }
  __syncwarp();
  const int lane = threadIdx.x & 31;
#define TS_PRO()
  if (wg == 2) {
    asm volatile("setmaxnreg.dec.sync.aligned.u32 56;");
    TS_PRO();
    TS(2, 62);
    if (warp == 0) producer<MASK>(M, P, base, cta, lane);
    else if (warp == 1) sync_agent<MASK>(base, cta, lane);
    else if (cta < NREG) {
      if (MASK & PH_PRE) aux_pre<MASK>(M, P, base, cta, warp - 2, lane);
      if (MASK & PH_OUT) producer2<MASK>(M, P, base, cta, warp - 2, lane);
    }
    if (warp == 1) {
      if (MASK & PH_OUT) {
        unsigned old = 0;
        if (lane == 0) asm volatile("atom.relaxed.gpu.global.add.u32 %0, [%1], 1;" : "=r"(old) : "l"(g_cnt + C_EXIT * CSTRIDE) : "memory");
        old = __shfl_sync(~0u, old, 0);
        if (old == NCTA - 1) for (int i = lane; i < C_NUM; i += 32) g_cnt[i * CSTRIDE] = 0;
      }
      mbar_wait_slow(base + SM_SIG + 8 * SIG_DONE, 0);
      if (cta >= NREG || !(MASK & PH_OUT)) { cluster_arrive(); cluster_wait(); }
    }
  } else {
    asm volatile("setmaxnreg.inc.sync.aligned.u32 224;");
    TS_PRO();
    uint32_t rel;
    asm volatile("mapa.shared::cluster.u32 %0, %1, %2;" : "=r"(rel) : "r"(base + SM_BAR + 128 + 8 * (lane & 15)), "r"(lane >> 4));
    Cons c{base, rel, 0u, lane, warp, wg, (cta * 3 + wg) * 2048};
    if (wg == 1) bar_arrive(1, 256);
    TS(wg, 0);
    if (cta < NREG) {
      const int g = cta & 7, j = cta >> 3;
      Pend w = {};
#pragma unroll 1
      for (int half = 0; half < 2; half++) {
        const int h = j + 16 * half;
        if (MASK & PH_KV) cons_kv<(MASK & PH_ATT) != 0>(c, h, kv_slot<MASK>(h), g, w, half == 1 && (MASK & PH_ATT));
        TS(wg, 1 + 4 * half);
        if (MASK & PH_ATT) {
          Att a;
          cons_q<(MASK & PH_KV) != 0>(c, h, w, a.o);
          TS(wg, 2 + 4 * half);
          cons_att(c, a, h, g, w);
          if (half == 0) c.signal(SIG_WAR);
#pragma unroll
          for (int i = 0; i < 8; i++) w.hi[i] = make_uint4(0, 0, 0, 0);
          TS(wg, 3 + 4 * half);
          if (MASK != PH_ALL) { tile_store<0, 4>(w.lo, w.dst, lane); c.signal(SIG_CTX + half); }
        } else if (MASK & PH_KV) { out_part<0>(c, w); out_part<1>(c, w); out_part<2>(c, w); out_part<3>(c, w); c.signal(SIG_KV + half); }
      }
      if (MASK & PH_OUT) cons_out<MASK>(c, M, P, cta, w);
    }
    if (cta >= NREG || !(MASK & PH_OUT)) {
      if (MASK & PH_CONV) cons_conv<MASK>(c, cta, cta < NREG ? CV_REG<MASK> : CV_EXTRA<MASK>);
      TS(wg, 9);
      c.signal(SIG_DONE);
      cluster_arrive();
    }
    TS(wg, 10);
  }
}

typedef CUresult (*EncFn)(CUtensorMap*, CUtensorMapDataType, cuuint32_t, void*, const cuuint64_t*, const cuuint64_t*, const cuuint32_t*, const cuuint32_t*,
                          CUtensorMapInterleave, CUtensorMapSwizzle, CUtensorMapL2promotion, CUtensorMapFloatOOBfill);
static void enc(EncFn f, CUtensorMap* m, const void* ptr, int rank, const cuuint64_t* dims, const cuuint64_t* strides, const cuuint32_t* box, CUtensorMapSwizzle sw,
                CUtensorMapDataType dt = CU_TENSOR_MAP_DATA_TYPE_BFLOAT16) {
  const cuuint32_t es[4] = {1, 1, 1, 1};
  f(m, dt, rank, (void*)ptr, dims, strides, box, es, CU_TENSOR_MAP_INTERLEAVE_NONE, sw, CU_TENSOR_MAP_L2_PROMOTION_L2_256B, CU_TENSOR_MAP_FLOAT_OOB_FILL_NONE);
}
static void enc2(EncFn f, CUtensorMap* m, const void* ptr, int cols, int rows, int brows) {
  const cuuint64_t d[2] = {(cuuint64_t)cols, (cuuint64_t)rows}, s[1] = {(cuuint64_t)cols * 2}; const cuuint32_t b[2] = {64, (cuuint32_t)brows};
  enc(f, m, ptr, 2, d, s, b, CU_TENSOR_MAP_SWIZZLE_128B);
}
static void encw(EncFn f, CUtensorMap* m, const void* ptr, int cols, int rows) {
  const cuuint64_t d[3] = {64, (cuuint64_t)rows, (cuuint64_t)cols / 64}, s[2] = {(cuuint64_t)cols * 2, 128}; const cuuint32_t b[3] = {64, 64, 2};
  enc(f, m, ptr, 3, d, s, b, CU_TENSOR_MAP_SWIZZLE_128B);
}
extern "C" void kernel_launch(void* const* d_in, const int* in_sizes, int n_in, void* d_out, int out_size) {
  static EncFn fn = nullptr;
  static int ncl = 0;
  static void* zptr = nullptr;
  static void* tptr = nullptr;
  if (!fn) {
    void* p = nullptr; cudaDriverEntryPointQueryResult qr;
    cudaGetDriverEntryPoint("cuTensorMapEncodeTiled", &p, cudaEnableDefault, &qr);
    fn = (EncFn)p;
    cudaFuncSetAttribute(gated_mix_kernel<PH_ALL>, cudaFuncAttributeMaxDynamicSharedMemorySize, SMEM_BYTES);
    cudaFuncSetAttribute(gated_mix_kernel<PH_PRE | PH_KV>, cudaFuncAttributeMaxDynamicSharedMemorySize, SMEM_BYTES);
    cudaFuncSetAttribute(gated_mix_kernel<PH_ATT | PH_CONV>, cudaFuncAttributeMaxDynamicSharedMemorySize, SMEM_BYTES);
    cudaFuncSetAttribute(gated_mix_kernel<PH_OUT>, cudaFuncAttributeMaxDynamicSharedMemorySize, SMEM_BYTES);
    cudaLaunchConfig_t cfg = {}; cfg.gridDim = NCTA; cfg.blockDim = 384; cfg.dynamicSmemBytes = SMEM_BYTES;
    cudaLaunchAttribute at; at.id = cudaLaunchAttributeClusterDimension; at.val.clusterDim.x = 2; at.val.clusterDim.y = 1; at.val.clusterDim.z = 1;
    cfg.attrs = &at; cfg.numAttrs = 1;
    cudaOccupancyMaxActiveClusters(&ncl, gated_mix_kernel<PH_ALL>, &cfg);
    cudaGetSymbolAddress(&zptr, g_z);
    cudaGetSymbolAddress(&tptr, g_T);
  }
  Maps M;
  enc2(fn, &M.x, d_in[0], 1024, 2048, 128);
  enc2(fn, &M.c, d_in[7], 512, 2048, 128);
  enc2(fn, &M.wq, d_in[8], 4096, 1024, 64);
  encw(fn, &M.wk, d_in[9], 4096, 512);
  encw(fn, &M.wv, d_in[10], 4096, 512);
  encw(fn, &M.wo, d_in[11], 1024, 4096);
  { const cuuint64_t d[3] = {64, 32, 1024}, s[2] = {128, 4096}; const cuuint32_t b[3] = {64, 40, 1}; enc(fn, &M.h, d_in[4], 3, d, s, b, CU_TENSOR_MAP_SWIZZLE_NONE); }
  enc2(fn, &M.z, zptr, 2048, 1024, 128);
  enc2(fn, &M.out, d_out, 1024, 2048, 16);
  { const cuuint64_t d[2] = {512, 512 * 16}, s[1] = {2048}; const cuuint32_t b[2] = {256, 8};
    enc(fn, &M.ctx, tptr, 2, d, s, b, CU_TENSOR_MAP_SWIZZLE_NONE, CU_TENSOR_MAP_DATA_TYPE_UINT32); }
  { const cuuint64_t d[4] = {1024, 2, 256, 4}, s[3] = {2048, 16384, 4096}; const cuuint32_t b[4] = {64, 2, 9, 4};
    enc(fn, &M.k, d_in[1], 4, d, s, b, CU_TENSOR_MAP_SWIZZLE_128B); enc(fn, &M.v, d_in[2], 4, d, s, b, CU_TENSOR_MAP_SWIZZLE_128B); }
  Params P{(const __nv_bfloat16*)d_in[0], (const __nv_bfloat16*)d_in[3],
           (const __nv_bfloat16*)d_in[5], (const __nv_bfloat16*)d_in[12], (__nv_bfloat16*)d_out};
  bool split = 2 * ncl < NCTA;
  if (!split) {
    gated_mix_kernel<PH_ALL><<<NCTA, 384, SMEM_BYTES>>>(M, P);
  } else {
    gated_mix_kernel<PH_PRE | PH_KV><<<NCTA, 384, SMEM_BYTES>>>(M, P);
    gated_mix_kernel<PH_ATT | PH_CONV><<<NCTA, 384, SMEM_BYTES>>>(M, P);
    gated_mix_kernel<PH_OUT><<<NCTA, 384, SMEM_BYTES>>>(M, P);
  }
}
```

```cpp
#include <cuda_runtime.h>
#include <cuda.h>
#include <cuda_bf16.h>
#include <stdint.h>

template<int TB> __device__ __forceinline__ void wgmma_ss_n256(float (&d)[128], uint64_t da, uint64_t db, int scale_d) {
  asm volatile("{\n.reg .pred p;\nsetp.ne.b32 p, %130, 0;\n"
    "wgmma.mma_async.sync.aligned.m64n256k16.f32.bf16.bf16 {%0, %1, %2, %3, %4, %5, %6, %7, %8, %9, %10, %11, %12, %13, %14, %15, %16, %17, %18, %19, %20, %21, %22, %23, %24, %25, %26, %27, %28, %29, %30, %31, %32, %33, %34, %35, %36, %37, %38, %39, %40, %41, %42, %43, %44, %45, %46, %47, %48, %49, %50, %51, %52, %53, %54, %55, %56, %57, %58, %59, %60, %61, %62, %63, %64, %65, %66, %67, %68, %69, %70, %71, %72, %73, %74, %75, %76, %77, %78, %79, %80, %81, %82, %83, %84, %85, %86, %87, %88, %89, %90, %91, %92, %93, %94, %95, %96, %97, %98, %99, %100, %101, %102, %103, %104, %105, %106, %107, %108, %109, %110, %111, %112, %113, %114, %115, %116, %117, %118, %119, %120, %121, %122, %123, %124, %125, %126, %127}, %128, %129, p, 1, 1, 0, %131;\n}\n"
    : "+f"(d[0]), "+f"(d[1]), "+f"(d[2]), "+f"(d[3]), "+f"(d[4]), "+f"(d[5]), "+f"(d[6]), "+f"(d[7]), "+f"(d[8]), "+f"(d[9]), "+f"(d[10]), "+f"(d[11]), "+f"(d[12]), "+f"(d[13]), "+f"(d[14]), "+f"(d[15]), "+f"(d[16]), "+f"(d[17]), "+f"(d[18]), "+f"(d[19]), "+f"(d[20]), "+f"(d[21]), "+f"(d[22]), "+f"(d[23]), "+f"(d[24]), "+f"(d[25]), "+f"(d[26]), "+f"(d[27]), "+f"(d[28]), "+f"(d[29]), "+f"(d[30]), "+f"(d[31]), "+f"(d[32]), "+f"(d[33]), "+f"(d[34]), "+f"(d[35]), "+f"(d[36]), "+f"(d[37]), "+f"(d[38]), "+f"(d[39]), "+f"(d[40]), "+f"(d[41]), "+f"(d[42]), "+f"(d[43]), "+f"(d[44]), "+f"(d[45]), "+f"(d[46]), "+f"(d[47]), "+f"(d[48]), "+f"(d[49]), "+f"(d[50]), "+f"(d[51]), "+f"(d[52]), "+f"(d[53]), "+f"(d[54]), "+f"(d[55]), "+f"(d[56]), "+f"(d[57]), "+f"(d[58]), "+f"(d[59]), "+f"(d[60]), "+f"(d[61]), "+f"(d[62]), "+f"(d[63]), "+f"(d[64]), "+f"(d[65]), "+f"(d[66]), "+f"(d[67]), "+f"(d[68]), "+f"(d[69]), "+f"(d[70]), "+f"(d[71]), "+f"(d[72]), "+f"(d[73]), "+f"(d[74]), "+f"(d[75]), "+f"(d[76]), "+f"(d[77]), "+f"(d[78]), "+f"(d[79]), "+f"(d[80]), "+f"(d[81]), "+f"(d[82]), "+f"(d[83]), "+f"(d[84]), "+f"(d[85]), "+f"(d[86]), "+f"(d[87]), "+f"(d[88]), "+f"(d[89]), "+f"(d[90]), "+f"(d[91]), "+f"(d[92]), "+f"(d[93]), "+f"(d[94]), "+f"(d[95]), "+f"(d[96]), "+f"(d[97]), "+f"(d[98]), "+f"(d[99]), "+f"(d[100]), "+f"(d[101]), "+f"(d[102]), "+f"(d[103]), "+f"(d[104]), "+f"(d[105]), "+f"(d[106]), "+f"(d[107]), "+f"(d[108]), "+f"(d[109]), "+f"(d[110]), "+f"(d[111]), "+f"(d[112]), "+f"(d[113]), "+f"(d[114]), "+f"(d[115]), "+f"(d[116]), "+f"(d[117]), "+f"(d[118]), "+f"(d[119]), "+f"(d[120]), "+f"(d[121]), "+f"(d[122]), "+f"(d[123]), "+f"(d[124]), "+f"(d[125]), "+f"(d[126]), "+f"(d[127])
    : "l"(da), "l"(db), "r"(scale_d), "n"(TB));
}
template<int TB> __device__ __forceinline__ void wgmma_ss_n128(float (&d)[64], uint64_t da, uint64_t db, int scale_d) {
  asm volatile("{\n.reg .pred p;\nsetp.ne.b32 p, %66, 0;\n"
    "wgmma.mma_async.sync.aligned.m64n128k16.f32.bf16.bf16 {%0, %1, %2, %3, %4, %5, %6, %7, %8, %9, %10, %11, %12, %13, %14, %15, %16, %17, %18, %19, %20, %21, %22, %23, %24, %25, %26, %27, %28, %29, %30, %31, %32, %33, %34, %35, %36, %37, %38, %39, %40, %41, %42, %43, %44, %45, %46, %47, %48, %49, %50, %51, %52, %53, %54, %55, %56, %57, %58, %59, %60, %61, %62, %63}, %64, %65, p, 1, 1, 0, %67;\n}\n"
    : "+f"(d[0]), "+f"(d[1]), "+f"(d[2]), "+f"(d[3]), "+f"(d[4]), "+f"(d[5]), "+f"(d[6]), "+f"(d[7]), "+f"(d[8]), "+f"(d[9]), "+f"(d[10]), "+f"(d[11]), "+f"(d[12]), "+f"(d[13]), "+f"(d[14]), "+f"(d[15]), "+f"(d[16]), "+f"(d[17]), "+f"(d[18]), "+f"(d[19]), "+f"(d[20]), "+f"(d[21]), "+f"(d[22]), "+f"(d[23]), "+f"(d[24]), "+f"(d[25]), "+f"(d[26]), "+f"(d[27]), "+f"(d[28]), "+f"(d[29]), "+f"(d[30]), "+f"(d[31]), "+f"(d[32]), "+f"(d[33]), "+f"(d[34]), "+f"(d[35]), "+f"(d[36]), "+f"(d[37]), "+f"(d[38]), "+f"(d[39]), "+f"(d[40]), "+f"(d[41]), "+f"(d[42]), "+f"(d[43]), "+f"(d[44]), "+f"(d[45]), "+f"(d[46]), "+f"(d[47]), "+f"(d[48]), "+f"(d[49]), "+f"(d[50]), "+f"(d[51]), "+f"(d[52]), "+f"(d[53]), "+f"(d[54]), "+f"(d[55]), "+f"(d[56]), "+f"(d[57]), "+f"(d[58]), "+f"(d[59]), "+f"(d[60]), "+f"(d[61]), "+f"(d[62]), "+f"(d[63])
    : "l"(da), "l"(db), "r"(scale_d), "n"(TB));
}
template<int TB> __device__ __forceinline__ void wgmma_rs_n32(float (&d)[16], uint32_t a0, uint32_t a1, uint32_t a2, uint32_t a3, uint64_t db, int scale_d) {
  asm volatile("{\n.reg .pred p;\nsetp.ne.b32 p, %21, 0;\n"
    "wgmma.mma_async.sync.aligned.m64n32k16.f32.bf16.bf16 {%0, %1, %2, %3, %4, %5, %6, %7, %8, %9, %10, %11, %12, %13, %14, %15}, {%16, %17, %18, %19}, %20, p, 1, 1, %22;\n}\n"
    : "+f"(d[0]), "+f"(d[1]), "+f"(d[2]), "+f"(d[3]), "+f"(d[4]), "+f"(d[5]), "+f"(d[6]), "+f"(d[7]), "+f"(d[8]), "+f"(d[9]), "+f"(d[10]), "+f"(d[11]), "+f"(d[12]), "+f"(d[13]), "+f"(d[14]), "+f"(d[15])
    : "r"(a0), "r"(a1), "r"(a2), "r"(a3), "l"(db), "r"(scale_d), "n"(TB));
}
__device__ __forceinline__ void wgmma_pv_sel(float (&d)[64], const uint32_t (&p)[32], uint64_t db, int full, int acc) {
  asm volatile("{\n.reg .pred q, s;\n.reg .b64 t;\nsetp.ne.b32 s, %98, 0;\nsetp.eq.b32 q, %97, 0;\n@q bra.uni LH;\n"
    "wgmma.fence.sync.aligned;\n"
    "add.s64 t, %96, 0;\nwgmma.mma_async.sync.aligned.m64n128k16.f32.bf16.bf16 {%0, %1, %2, %3, %4, %5, %6, %7, %8, %9, %10, %11, %12, %13, %14, %15, %16, %17, %18, %19, %20, %21, %22, %23, %24, %25, %26, %27, %28, %29, %30, %31, %32, %33, %34, %35, %36, %37, %38, %39, %40, %41, %42, %43, %44, %45, %46, %47, %48, %49, %50, %51, %52, %53, %54, %55, %56, %57, %58, %59, %60, %61, %62, %63}, {%64, %65, %66, %67}, t, s, 1, 1, 1;\n"
    "add.s64 t, %96, 256;\nwgmma.mma_async.sync.aligned.m64n128k16.f32.bf16.bf16 {%0, %1, %2, %3, %4, %5, %6, %7, %8, %9, %10, %11, %12, %13, %14, %15, %16, %17, %18, %19, %20, %21, %22, %23, %24, %25, %26, %27, %28, %29, %30, %31, %32, %33, %34, %35, %36, %37, %38, %39, %40, %41, %42, %43, %44, %45, %46, %47, %48, %49, %50, %51, %52, %53, %54, %55, %56, %57, %58, %59, %60, %61, %62, %63}, {%68, %69, %70, %71}, t, 1, 1, 1, 1;\n"
    "add.s64 t, %96, 512;\nwgmma.mma_async.sync.aligned.m64n128k16.f32.bf16.bf16 {%0, %1, %2, %3, %4, %5, %6, %7, %8, %9, %10, %11, %12, %13, %14, %15, %16, %17, %18, %19, %20, %21, %22, %23, %24, %25, %26, %27, %28, %29, %30, %31, %32, %33, %34, %35, %36, %37, %38, %39, %40, %41, %42, %43, %44, %45, %46, %47, %48, %49, %50, %51, %52, %53, %54, %55, %56, %57, %58, %59, %60, %61, %62, %63}, {%72, %73, %74, %75}, t, 1, 1, 1, 1;\n"
    "add.s64 t, %96, 768;\nwgmma.mma_async.sync.aligned.m64n128k16.f32.bf16.bf16 {%0, %1, %2, %3, %4, %5, %6, %7, %8, %9, %10, %11, %12, %13, %14, %15, %16, %17, %18, %19, %20, %21, %22, %23, %24, %25, %26, %27, %28, %29, %30, %31, %32, %33, %34, %35, %36, %37, %38, %39, %40, %41, %42, %43, %44, %45, %46, %47, %48, %49, %50, %51, %52, %53, %54, %55, %56, %57, %58, %59, %60, %61, %62, %63}, {%76, %77, %78, %79}, t, 1, 1, 1, 1;\n"
    "add.s64 t, %96, 1024;\nwgmma.mma_async.sync.aligned.m64n128k16.f32.bf16.bf16 {%0, %1, %2, %3, %4, %5, %6, %7, %8, %9, %10, %11, %12, %13, %14, %15, %16, %17, %18, %19, %20, %21, %22, %23, %24, %25, %26, %27, %28, %29, %30, %31, %32, %33, %34, %35, %36, %37, %38, %39, %40, %41, %42, %43, %44, %45, %46, %47, %48, %49, %50, %51, %52, %53, %54, %55, %56, %57, %58, %59, %60, %61, %62, %63}, {%80, %81, %82, %83}, t, 1, 1, 1, 1;\n"
    "add.s64 t, %96, 1280;\nwgmma.mma_async.sync.aligned.m64n128k16.f32.bf16.bf16 {%0, %1, %2, %3, %4, %5, %6, %7, %8, %9, %10, %11, %12, %13, %14, %15, %16, %17, %18, %19, %20, %21, %22, %23, %24, %25, %26, %27, %28, %29, %30, %31, %32, %33, %34, %35, %36, %37, %38, %39, %40, %41, %42, %43, %44, %45, %46, %47, %48, %49, %50, %51, %52, %53, %54, %55, %56, %57, %58, %59, %60, %61, %62, %63}, {%84, %85, %86, %87}, t, 1, 1, 1, 1;\n"
    "add.s64 t, %96, 1536;\nwgmma.mma_async.sync.aligned.m64n128k16.f32.bf16.bf16 {%0, %1, %2, %3, %4, %5, %6, %7, %8, %9, %10, %11, %12, %13, %14, %15, %16, %17, %18, %19, %20, %21, %22, %23, %24, %25, %26, %27, %28, %29, %30, %31, %32, %33, %34, %35, %36, %37, %38, %39, %40, %41, %42, %43, %44, %45, %46, %47, %48, %49, %50, %51, %52, %53, %54, %55, %56, %57, %58, %59, %60, %61, %62, %63}, {%88, %89, %90, %91}, t, 1, 1, 1, 1;\n"
    "add.s64 t, %96, 1792;\nwgmma.mma_async.sync.aligned.m64n128k16.f32.bf16.bf16 {%0, %1, %2, %3, %4, %5, %6, %7, %8, %9, %10, %11, %12, %13, %14, %15, %16, %17, %18, %19, %20, %21, %22, %23, %24, %25, %26, %27, %28, %29, %30, %31, %32, %33, %34, %35, %36, %37, %38, %39, %40, %41, %42, %43, %44, %45, %46, %47, %48, %49, %50, %51, %52, %53, %54, %55, %56, %57, %58, %59, %60, %61, %62, %63}, {%92, %93, %94, %95}, t, 1, 1, 1, 1;\n"
    "wgmma.commit_group.sync.aligned;\n"
    "bra.uni LE;\nLH:\n"
    "wgmma.fence.sync.aligned;\n"
    "add.s64 t, %96, 0;\nwgmma.mma_async.sync.aligned.m64n128k16.f32.bf16.bf16 {%0, %1, %2, %3, %4, %5, %6, %7, %8, %9, %10, %11, %12, %13, %14, %15, %16, %17, %18, %19, %20, %21, %22, %23, %24, %25, %26, %27, %28, %29, %30, %31, %32, %33, %34, %35, %36, %37, %38, %39, %40, %41, %42, %43, %44, %45, %46, %47, %48, %49, %50, %51, %52, %53, %54, %55, %56, %57, %58, %59, %60, %61, %62, %63}, {%80, %81, %82, %83}, t, s, 1, 1, 1;\n"
    "add.s64 t, %96, 256;\nwgmma.mma_async.sync.aligned.m64n128k16.f32.bf16.bf16 {%0, %1, %2, %3, %4, %5, %6, %7, %8, %9, %10, %11, %12, %13, %14, %15, %16, %17, %18, %19, %20, %21, %22, %23, %24, %25, %26, %27, %28, %29, %30, %31, %32, %33, %34, %35, %36, %37, %38, %39, %40, %41, %42, %43, %44, %45, %46, %47, %48, %49, %50, %51, %52, %53, %54, %55, %56, %57, %58, %59, %60, %61, %62, %63}, {%84, %85, %86, %87}, t, 1, 1, 1, 1;\n"
    "add.s64 t, %96, 512;\nwgmma.mma_async.sync.aligned.m64n128k16.f32.bf16.bf16 {%0, %1, %2, %3, %4, %5, %6, %7, %8, %9, %10, %11, %12, %13, %14, %15, %16, %17, %18, %19, %20, %21, %22, %23, %24, %25, %26, %27, %28, %29, %30, %31, %32, %33, %34, %35, %36, %37, %38, %39, %40, %41, %42, %43, %44, %45, %46, %47, %48, %49, %50, %51, %52, %53, %54, %55, %56, %57, %58, %59, %60, %61, %62, %63}, {%88, %89, %90, %91}, t, 1, 1, 1, 1;\n"
    "add.s64 t, %96, 768;\nwgmma.mma_async.sync.aligned.m64n128k16.f32.bf16.bf16 {%0, %1, %2, %3, %4, %5, %6, %7, %8, %9, %10, %11, %12, %13, %14, %15, %16, %17, %18, %19, %20, %21, %22, %23, %24, %25, %26, %27, %28, %29, %30, %31, %32, %33, %34, %35, %36, %37, %38, %39, %40, %41, %42, %43, %44, %45, %46, %47, %48, %49, %50, %51, %52, %53, %54, %55, %56, %57, %58, %59, %60, %61, %62, %63}, {%92, %93, %94, %95}, t, 1, 1, 1, 1;\n"
    "wgmma.commit_group.sync.aligned;\n"
    "LE:\n}\n"
    : "+f"(d[0]), "+f"(d[1]), "+f"(d[2]), "+f"(d[3]), "+f"(d[4]), "+f"(d[5]), "+f"(d[6]), "+f"(d[7]), "+f"(d[8]), "+f"(d[9]), "+f"(d[10]), "+f"(d[11]), "+f"(d[12]), "+f"(d[13]), "+f"(d[14]), "+f"(d[15]), "+f"(d[16]), "+f"(d[17]), "+f"(d[18]), "+f"(d[19]), "+f"(d[20]), "+f"(d[21]), "+f"(d[22]), "+f"(d[23]), "+f"(d[24]), "+f"(d[25]), "+f"(d[26]), "+f"(d[27]), "+f"(d[28]), "+f"(d[29]), "+f"(d[30]), "+f"(d[31]), "+f"(d[32]), "+f"(d[33]), "+f"(d[34]), "+f"(d[35]), "+f"(d[36]), "+f"(d[37]), "+f"(d[38]), "+f"(d[39]), "+f"(d[40]), "+f"(d[41]), "+f"(d[42]), "+f"(d[43]), "+f"(d[44]), "+f"(d[45]), "+f"(d[46]), "+f"(d[47]), "+f"(d[48]), "+f"(d[49]), "+f"(d[50]), "+f"(d[51]), "+f"(d[52]), "+f"(d[53]), "+f"(d[54]), "+f"(d[55]), "+f"(d[56]), "+f"(d[57]), "+f"(d[58]), "+f"(d[59]), "+f"(d[60]), "+f"(d[61]), "+f"(d[62]), "+f"(d[63])
    : "r"(p[0]), "r"(p[1]), "r"(p[2]), "r"(p[3]), "r"(p[4]), "r"(p[5]), "r"(p[6]), "r"(p[7]), "r"(p[8]), "r"(p[9]), "r"(p[10]), "r"(p[11]), "r"(p[12]), "r"(p[13]), "r"(p[14]), "r"(p[15]), "r"(p[16]), "r"(p[17]), "r"(p[18]), "r"(p[19]), "r"(p[20]), "r"(p[21]), "r"(p[22]), "r"(p[23]), "r"(p[24]), "r"(p[25]), "r"(p[26]), "r"(p[27]), "r"(p[28]), "r"(p[29]), "r"(p[30]), "r"(p[31]), "l"(db), "r"(full), "r"(acc) : "memory");
}

constexpr int NCTA = 132, NREG = 128;
constexpr int UNIT = 16384, NUNIT = 14;
constexpr uint32_t SMEM_BASE = 1024;
constexpr int SM_BAR = NUNIT * UNIT;
constexpr int SM_GATE = SM_BAR + 1024;
constexpr int SMEM_BYTES = SM_BAR + 1536;
constexpr int UPITCH = 4160, UCH = 2 * UPITCH;
constexpr float QSCALE = 0.08838834764831845f * 1.4426950408889634f;
constexpr float BOUND2 = 48.f * 48.f / 1.15f;
#define CONV_REG 5
constexpr int C_KV = 0;
constexpr int C_CTX = 32;
constexpr int C_U = 48;
constexpr int C_Z = 80;
constexpr int C_GATE = 88;
constexpr int C_EXIT = 89;
#define PRE_EARLY 2
#define PRE_HALF 1
#define ATT_SPLIT 6
#define NFIRST 2
#define PRE_DELAY 0
#define MAP_PF 1
#define FINAL_ST 1
#define Z_AT 60
#define PRE_DELAY_BAR 9
#define PRE_FMA 0
#define PRE_SLEEP 300
#define GATE_SLEEP 1000
#define GATE_EARLY 1
#define OC_S0 2
#define OC_S1 11
#define OC_POST 1
#define OC_L0 17
#define OC_L1 18
#define EF 127
#define POL(bit) (((EF >> (bit)) & 1) != 0)
constexpr int C_WAR = 96;
constexpr int C_NUM = 112;
constexpr int CSTRIDE = 32;
constexpr int SM_KMAX = SM_BAR + 640, SM_DUMMY = SM_BAR + 648, SM_PRE = SM_BAR + 112, SM_SIG = SM_BAR + 256, SM_RDY = SM_BAR + 384;
enum { SIG_KV = 0, SIG_CTX = 2, SIG_Z = 4, SIG_DONE = 8, SIG_WAR = 9, SIG_ATT = 10 };
enum { RDY_KV = 0, RDY_CTX = 2, RDY_WAR = 4, RDY_G = 5, RDY_U = 8, RDY_Z = 9 };
enum { PH_PRE = 1, PH_KV = 2, PH_ATT = 4, PH_CONV = 8, PH_OUT = 16, PH_ALL = 31 };

constexpr uint32_t T_CTX = 0, T_KV = 16 * 32 * 32768, T_BYTES = T_KV + 32 * 16 * 65536;
__device__ __align__(1024) uint8_t g_T[T_BYTES];
__device__ __align__(1024) uint8_t g_u[1024 * UCH];
__device__ __align__(1024) __nv_bfloat16 g_z[1024 * 2048];
__device__ __align__(1024) float g_gate[2048];
__device__ __align__(1024) float g_kn2[32 * 128];
__device__ __align__(1024) unsigned g_cnt[C_NUM * CSTRIDE];

struct __align__(64) Maps { CUtensorMap c, wk, wv, x, wq, wo, h, z, out, ctx, k, v; };
struct Params {
  const __nv_bfloat16 *x, *shift, *D, *gw;
  __nv_bfloat16* out;
};

__device__ __forceinline__ void wg_fence() { asm volatile("wgmma.fence.sync.aligned;" ::: "memory"); }
__device__ __forceinline__ void wg_commit() { asm volatile("wgmma.commit_group.sync.aligned;" ::: "memory"); }
template<int N> __device__ __forceinline__ void wg_wait() { asm volatile("wgmma.wait_group.sync.aligned %0;" :: "n"(N) : "memory"); }
__device__ __forceinline__ uint64_t odesc(uint32_t addr, uint32_t lbo, uint32_t sbo, uint32_t swz) {
  uint64_t d = (uint64_t)(addr >> 4) + (((uint64_t)(lbo >> 4) << 16) | ((uint64_t)(sbo >> 4) << 32) | ((uint64_t)swz << 62));
  asm volatile("" : "+l"(d));
  return d;
}
__device__ __forceinline__ void mbar_init(uint32_t bar, int cnt) { asm volatile("mbarrier.init.shared::cta.b64 [%0], %1;" :: "r"(bar), "r"(cnt)); }
__device__ __forceinline__ void mbar_expect(uint32_t bar, uint32_t bytes) { asm volatile("mbarrier.arrive.expect_tx.shared::cta.b64 _, [%0], %1;" :: "r"(bar), "r"(bytes) : "memory"); }
__device__ __forceinline__ void mbar_arrive(uint32_t bar) { asm volatile("mbarrier.arrive.shared::cta.b64 _, [%0];" :: "r"(bar) : "memory"); }
__device__ __forceinline__ void mbar_arrive_n(uint32_t bar, int n) { asm volatile("mbarrier.arrive.shared::cta.b64 _, [%0], %1;" :: "r"(bar), "r"(n) : "memory"); }
__device__ __forceinline__ void mbar_wait(uint32_t bar, uint32_t parity) {
  asm volatile("{\n.reg .pred p;\nLW:\nmbarrier.try_wait.parity.shared::cta.b64 p, [%0], %1;\n@!p bra LW;\n}\n" :: "r"(bar), "r"(parity) : "memory");
}
__device__ __forceinline__ void mbar_wait_slow(uint32_t bar, uint32_t parity) {
  asm volatile("{\n.reg .pred p;\n.reg .u32 n;\nmov.u32 n, 0;\n"
    "LW:\nmbarrier.test_wait.parity.shared::cta.b64 p, [%0], %1;\n@p bra LD;\n"
    "nanosleep.u32 128;\nadd.u32 n, n, 1;\nsetp.lt.u32 p, n, 4194304;\n@p bra LW;\ntrap;\nLD:\n}\n" :: "r"(bar), "r"(parity) : "memory");
}
__device__ __forceinline__ void mbar_wait_all(uint32_t bar, uint32_t parity) {
  asm volatile("{\n.reg .pred p, q;\nLW:\nmbarrier.try_wait.parity.shared::cta.b64 p, [%0], %1;\nvote.sync.all.pred q, p, 0xffffffff;\n@!q bra.uni LW;\n}\n" :: "r"(bar), "r"(parity) : "memory");
}
__device__ __forceinline__ void cnt_wait(const unsigned* p, unsigned target) {
  asm volatile("{\n.reg .pred p;\n.reg .u32 n, v;\nmov.u32 n, 0;\n"
    "LW:\nld.relaxed.gpu.global.u32 v, [%0];\nsetp.ge.u32 p, v, %1;\n@p bra LD;\n"
    "nanosleep.u32 64;\nadd.u32 n, n, 1;\nsetp.lt.u32 p, n, 4194304;\n@p bra LW;\ntrap;\nLD:\nfence.acquire.gpu;\nfence.proxy.async.global;\n}\n" :: "l"(p), "r"(target) : "memory");
}
__device__ __forceinline__ void cnt_signal(unsigned* p, int lane) {
  __syncwarp();
  if (lane == 0) asm volatile("red.release.gpu.global.add.u32 [%0], 1;" :: "l"(p) : "memory");
}
__device__ __forceinline__ void cnt_publish(unsigned* p, unsigned n, bool fence) {
  if (fence) asm volatile("fence.release.gpu;" ::: "memory");
  asm volatile("red.relaxed.gpu.global.add.u32 [%0], %1;" :: "l"(p), "r"(n) : "memory");
}
__device__ __forceinline__ uint64_t pol_first() { uint64_t p; asm("createpolicy.fractional.L2::evict_first.b64 %0, 1.0;" : "=l"(p)); return p; }
__device__ __forceinline__ void bulk_g2s(uint32_t dst, const void* src, uint32_t bytes, uint32_t bar, bool stream = false) {
  if (stream) asm volatile("cp.async.bulk.shared::cluster.global.mbarrier::complete_tx::bytes.L2::cache_hint [%0], [%1], %2, [%3], %4;" :: "r"(dst), "l"(src), "r"(bytes), "r"(bar), "l"(pol_first()) : "memory");
  else asm volatile("cp.async.bulk.shared::cluster.global.mbarrier::complete_tx::bytes [%0], [%1], %2, [%3];" :: "r"(dst), "l"(src), "r"(bytes), "r"(bar) : "memory");
}
__device__ __forceinline__ void tma2d(uint32_t dst, const CUtensorMap* m, int x, int y, uint32_t bar, bool stream = false) {
  if (stream) asm volatile("cp.async.bulk.tensor.2d.shared::cluster.global.mbarrier::complete_tx::bytes.L2::cache_hint [%0], [%1, {%3, %4}], [%2], %5;" :: "r"(dst), "l"(m), "r"(bar), "r"(x), "r"(y), "l"(pol_first()) : "memory");
  else asm volatile("cp.async.bulk.tensor.2d.shared::cluster.global.mbarrier::complete_tx::bytes [%0], [%1, {%3, %4}], [%2];" :: "r"(dst), "l"(m), "r"(bar), "r"(x), "r"(y) : "memory");
}
__device__ __forceinline__ void tma3d(uint32_t dst, const CUtensorMap* m, int x, int y, int z, uint32_t bar, bool stream = false) {
  if (stream) asm volatile("cp.async.bulk.tensor.3d.shared::cluster.global.mbarrier::complete_tx::bytes.L2::cache_hint [%0], [%1, {%3, %4, %5}], [%2], %6;" :: "r"(dst), "l"(m), "r"(bar), "r"(x), "r"(y), "r"(z), "l"(pol_first()) : "memory");
  else asm volatile("cp.async.bulk.tensor.3d.shared::cluster.global.mbarrier::complete_tx::bytes [%0], [%1, {%3, %4, %5}], [%2];" :: "r"(dst), "l"(m), "r"(bar), "r"(x), "r"(y), "r"(z) : "memory");
}
__device__ __forceinline__ void tma4d(uint32_t dst, const CUtensorMap* m, int x, int y, int z, int w, uint32_t bar, bool stream = false) {
  if (stream) asm volatile("cp.async.bulk.tensor.4d.shared::cluster.global.mbarrier::complete_tx::bytes.L2::cache_hint [%0], [%1, {%3, %4, %5, %6}], [%2], %7;" :: "r"(dst), "l"(m), "r"(bar), "r"(x), "r"(y), "r"(z), "r"(w), "l"(pol_first()) : "memory");
  else asm volatile("cp.async.bulk.tensor.4d.shared::cluster.global.mbarrier::complete_tx::bytes [%0], [%1, {%3, %4, %5, %6}], [%2];" :: "r"(dst), "l"(m), "r"(bar), "r"(x), "r"(y), "r"(z), "r"(w) : "memory");
}
__device__ __forceinline__ void bulk_g2s_mc(uint32_t dst, const void* src, uint32_t bytes, uint32_t bar, bool stream = false) {
  if (stream) asm volatile("cp.async.bulk.shared::cluster.global.mbarrier::complete_tx::bytes.multicast::cluster.L2::cache_hint [%0], [%1], %2, [%3], %4, %5;" :: "r"(dst), "l"(src), "r"(bytes), "r"(bar), "h"((uint16_t)3), "l"(pol_first()) : "memory");
  else asm volatile("cp.async.bulk.shared::cluster.global.mbarrier::complete_tx::bytes.multicast::cluster [%0], [%1], %2, [%3], %4;" :: "r"(dst), "l"(src), "r"(bytes), "r"(bar), "h"((uint16_t)3) : "memory");
}
__device__ __forceinline__ void tma2d_mc(uint32_t dst, const CUtensorMap* m, int x, int y, uint32_t bar, bool stream = false) {
  if (stream) asm volatile("cp.async.bulk.tensor.2d.shared::cluster.global.mbarrier::complete_tx::bytes.multicast::cluster.L2::cache_hint [%0], [%1, {%3, %4}], [%2], %5, %6;" :: "r"(dst), "l"(m), "r"(bar), "r"(x), "r"(y), "h"((uint16_t)3), "l"(pol_first()) : "memory");
  else asm volatile("cp.async.bulk.tensor.2d.shared::cluster.global.mbarrier::complete_tx::bytes.multicast::cluster [%0], [%1, {%3, %4}], [%2], %5;" :: "r"(dst), "l"(m), "r"(bar), "r"(x), "r"(y), "h"((uint16_t)3) : "memory");
}
__device__ __forceinline__ void tma3d_mc(uint32_t dst, const CUtensorMap* m, int x, int y, int z, uint32_t bar, bool stream = false) {
  if (stream) asm volatile("cp.async.bulk.tensor.3d.shared::cluster.global.mbarrier::complete_tx::bytes.multicast::cluster.L2::cache_hint [%0], [%1, {%3, %4, %5}], [%2], %6, %7;" :: "r"(dst), "l"(m), "r"(bar), "r"(x), "r"(y), "r"(z), "h"((uint16_t)3), "l"(pol_first()) : "memory");
  else asm volatile("cp.async.bulk.tensor.3d.shared::cluster.global.mbarrier::complete_tx::bytes.multicast::cluster [%0], [%1, {%3, %4, %5}], [%2], %6;" :: "r"(dst), "l"(m), "r"(bar), "r"(x), "r"(y), "r"(z), "h"((uint16_t)3) : "memory");
}
__device__ __forceinline__ void tma2d_store(const CUtensorMap* m, uint32_t src, int x, int y) {
  if (POL(12)) asm volatile("cp.async.bulk.tensor.2d.global.shared::cta.bulk_group.L2::cache_hint [%0, {%2, %3}], [%1], %4;" :: "l"(m), "r"(src), "r"(x), "r"(y), "l"(pol_first()) : "memory");
  else asm volatile("cp.async.bulk.tensor.2d.global.shared::cta.bulk_group [%0, {%2, %3}], [%1];" :: "l"(m), "r"(src), "r"(x), "r"(y) : "memory");
}
__device__ __forceinline__ bool elect() {
  uint32_t r; asm volatile("{\n.reg .pred p;\nelect.sync _|p, 0xffffffff;\nselp.u32 %0, 1, 0, p;\n}\n" : "=r"(r)); return r != 0;
}
__device__ __forceinline__ void cluster_arrive() { asm volatile("barrier.cluster.arrive;" ::: "memory"); }
__device__ __forceinline__ void cluster_wait() { asm volatile("barrier.cluster.wait;" ::: "memory"); }
__device__ __forceinline__ void bar_sync(int id, int n) { asm volatile("bar.sync %0, %1;" :: "r"(id), "r"(n) : "memory"); }
__device__ __forceinline__ void bar_arrive(int id, int n) { asm volatile("bar.arrive %0, %1;" :: "r"(id), "r"(n) : "memory"); }
__device__ __forceinline__ int bar_and(int id, int n, int pred) {
  int r; asm volatile("{\n.reg .pred p, q;\nsetp.ne.b32 p, %3, 0;\nbar.red.and.pred q, %1, %2, p;\nselp.b32 %0, 1, 0, q;\n}\n" : "=r"(r) : "r"(id), "r"(n), "r"(pred) : "memory");
  return r;
}
__device__ __forceinline__ void fence_async_smem() { asm volatile("fence.proxy.async.shared::cta;" ::: "memory"); }
__device__ __forceinline__ float ex2(float x) { float y; asm("ex2.approx.ftz.f32 %0, %1;" : "=f"(y) : "f"(x)); return y; }
__device__ __forceinline__ uint32_t pack_bf16(float lo, float hi) { uint32_t r; asm("cvt.rn.bf16x2.f32 %0, %1, %2;" : "=r"(r) : "f"(hi), "f"(lo)); return r; }
__device__ __forceinline__ uint32_t hmul2(uint32_t a, uint32_t b) { uint32_t r; asm("mul.rn.bf16x2 %0, %1, %2;" : "=r"(r) : "r"(a), "r"(b)); return r; }
__device__ __forceinline__ uint32_t hadd2(uint32_t a, uint32_t b) { uint32_t r; asm("add.rn.bf16x2 %0, %1, %2;" : "=r"(r) : "r"(a), "r"(b)); return r; }
__device__ __forceinline__ uint32_t hfma2(uint32_t a, uint32_t b, uint32_t c) { uint32_t r; asm("fma.rn.bf16x2 %0, %1, %2, %3;" : "=r"(r) : "r"(a), "r"(b), "r"(c)); return r; }
__device__ __forceinline__ float bf_lo(uint32_t a) { return __uint_as_float(a << 16); }
__device__ __forceinline__ float bf_hi(uint32_t a) { return __uint_as_float(a & 0xffff0000u); }
__device__ __forceinline__ uint32_t lds32(uint32_t a) { uint32_t v; asm volatile("ld.shared.u32 %0, [%1];" : "=r"(v) : "r"(a) : "memory"); return v; }
__device__ __forceinline__ float2 lds64f(uint32_t a) { float2 v; asm volatile("ld.shared.v2.f32 {%0,%1}, [%2];" : "=f"(v.x), "=f"(v.y) : "r"(a) : "memory"); return v; }
__device__ __forceinline__ uint4 lds128(uint32_t a) { uint4 v; asm volatile("ld.shared.v4.u32 {%0,%1,%2,%3}, [%4];" : "=r"(v.x), "=r"(v.y), "=r"(v.z), "=r"(v.w) : "r"(a) : "memory"); return v; }
__device__ __forceinline__ void sts64f(uint32_t a, float x, float y) { asm volatile("st.shared.v2.f32 [%0], {%1,%2};" :: "r"(a), "f"(x), "f"(y) : "memory"); }
__device__ __forceinline__ void sts128(uint32_t a, uint4 v) { asm volatile("st.shared.v4.u32 [%0], {%1,%2,%3,%4};" :: "r"(a), "r"(v.x), "r"(v.y), "r"(v.z), "r"(v.w) : "memory"); }
template<int OFF> __device__ __forceinline__ void sts128o(uint32_t a, uint4 v) { asm volatile("st.shared.v4.u32 [%0+%5], {%1,%2,%3,%4};" :: "r"(a), "r"(v.x), "r"(v.y), "r"(v.z), "r"(v.w), "n"(OFF) : "memory"); }
__device__ __forceinline__ void ldsm4(uint32_t a, uint32_t& r0, uint32_t& r1, uint32_t& r2, uint32_t& r3) {
  asm volatile("ldmatrix.sync.aligned.m8n8.x4.shared.b16 {%0,%1,%2,%3}, [%4];" : "=r"(r0), "=r"(r1), "=r"(r2), "=r"(r3) : "r"(a) : "memory");
}
__device__ __forceinline__ void ldsm4t(uint32_t a, uint32_t& r0, uint32_t& r1, uint32_t& r2, uint32_t& r3) {
  asm volatile("ldmatrix.sync.aligned.m8n8.x4.trans.shared.b16 {%0,%1,%2,%3}, [%4];" : "=r"(r0), "=r"(r1), "=r"(r2), "=r"(r3) : "r"(a) : "memory");
}
__device__ __forceinline__ void stsm4(uint32_t a, uint32_t r0, uint32_t r1, uint32_t r2, uint32_t r3) {
  asm volatile("stmatrix.sync.aligned.m8n8.x4.shared.b16 [%0], {%1,%2,%3,%4};" :: "r"(a), "r"(r0), "r"(r1), "r"(r2), "r"(r3) : "memory");
}
template<int N> __device__ __forceinline__ void fence_regs(float (&d)[N]) {
#pragma unroll
  for (int i = 0; i < N; i++) asm volatile("" : "+f"(d[i]) :: "memory");
}
template<int N> __device__ __forceinline__ void fence_regs(uint32_t (&d)[N]) {
#pragma unroll
  for (int i = 0; i < N; i++) asm volatile("" : "+r"(d[i]) :: "memory");
}
__device__ __forceinline__ void sched_fence(float x, uint32_t dummy) {
  asm volatile("{\n.reg .pred p;\nsetp.eq.u32 p, %0, 0x7fc12345;\n@p st.shared.u32 [%1], %0;\n}\n" :: "r"(__float_as_uint(x)), "r"(dummy) : "memory");
}
#define ROT 0
#define CTAID blockIdx.x
#define TS(role, i)
#define TSA(i)
#define TR(obj, role, tag)

#define SHADOW if (gridDim.y == 1)

struct Prod {
  uint32_t base, mask; int lane, nt;
  __device__ __forceinline__ uint32_t full(int u) const { return base + SM_BAR + 8 * u; }
  __device__ __forceinline__ uint32_t addr(int u) const { return base + u * UNIT; }
  __device__ __forceinline__ void acquire(int u, int n) {
    const int v = u + min(lane, n - 1);
    mbar_wait_all(base + SM_BAR + 128 + 8 * v, mask >> v);
    mask ^= ((1u << n) - 1) << u;
    TR(*this, 2, 16 + u);
  }
  __device__ __forceinline__ void acquire_slow(int u, int n) {
    for (int i = 0; i < n; i++) mbar_wait_slow(base + SM_BAR + 128 + 8 * (u + i), mask >> (u + i));
    mask ^= ((1u << n) - 1) << u;
  }
};
struct Cons {
  uint32_t base, rel, mask; int lane, warp, wg, nt;
  __device__ __forceinline__ uint32_t addr(int u) const { return base + u * UNIT; }
  __device__ __forceinline__ static uint32_t daddr(int u) { return SMEM_BASE + u * UNIT; }
  __device__ __forceinline__ void wait(int u) { TR(*this, wg, 1); mbar_wait(base + SM_BAR + 8 * u, mask >> u); mask ^= 1u << u; TR(*this, wg, 2); }
  __device__ __forceinline__ void skip(int u) { mask ^= 1u << u; }
  __device__ __forceinline__ void release(int u, int n) {
    TR(*this, wg, 5);
    asm volatile("{\n.reg .pred p;\nsetp.lt.s32 p, %1, %2;\n@p mbarrier.arrive.shared::cluster.b64 _, [%0];\n}\n" :: "r"(rel + 8 * u), "r"(lane & 15), "r"(n) : "memory");
  }
  __device__ __forceinline__ void release2(int u) {
    asm volatile("{\n.reg .pred p;\nsetp.eq.s32 p, %1, 0;\n@p mbarrier.arrive.shared::cluster.b64 _, [%0], 2;\n}\n" :: "r"(rel + 8 * u), "r"(lane & 15) : "memory");
  }
  __device__ __forceinline__ void signal(int i) {
    __syncwarp();
    asm volatile("{\n.reg .pred p;\nsetp.eq.s32 p, %1, 0;\n@p mbarrier.arrive.shared::cta.b64 _, [%0];\n}\n" :: "r"(base + SM_SIG + 8 * i), "r"(lane) : "memory");
  }
  __device__ __forceinline__ void turn() { bar_sync(1 + wg, 256); TR(*this, wg, 3); }
  __device__ __forceinline__ void pass() { bar_arrive(2 - wg, 256); TR(*this, wg, 4); }
};
__device__ __forceinline__ int gemm_unit(int ks) { return 3 * (ks & 3); }
__device__ __forceinline__ int att_slot(int i) { return 4 + 2 * i; }
template<int MASK> __device__ __forceinline__ int kv_slot(int h) { return MASK == PH_ALL ? h & 15 : h; }
__device__ __forceinline__ int out_mb(int cta) { return cta >> 3; }
__device__ __forceinline__ int out_nb(int cta) { return cta & 7; }
template<int MASK> constexpr int CV_REG = MASK == PH_ALL ? CONV_REG : 6;
template<int MASK> constexpr int CV_EXTRA = (1024 - NREG * CV_REG<MASK>) / (NCTA - NREG);
template<int MASK> __device__ __forceinline__ int conv_channel(int cta, int i) {
  return cta < NREG ? CV_EXTRA<MASK> * (NCTA - NREG) + cta * CV_REG<MASK> + i : (i >> 1) * 8 + (cta - NREG) * 2 + (i & 1);
}

template<int OFF, int N> __device__ __forceinline__ void pack_chunk(const float (&a)[N], float sc0, float sc1, uint4& v0, uint4& v1) {
  v0.x = pack_bf16(a[OFF + 0] * sc0, a[OFF + 1] * sc0); v0.y = pack_bf16(a[OFF + 4] * sc0, a[OFF + 5] * sc0);
  v0.z = pack_bf16(a[OFF + 8] * sc0, a[OFF + 9] * sc0); v0.w = pack_bf16(a[OFF + 12] * sc0, a[OFF + 13] * sc0);
  v1.x = pack_bf16(a[OFF + 2] * sc1, a[OFF + 3] * sc1); v1.y = pack_bf16(a[OFF + 6] * sc1, a[OFF + 7] * sc1);
  v1.z = pack_bf16(a[OFF + 10] * sc1, a[OFF + 11] * sc1); v1.w = pack_bf16(a[OFF + 14] * sc1, a[OFF + 15] * sc1);
}
template<int OFF, int N> __device__ __forceinline__ void pack_chunk(const float (&a)[N], uint4& v0, uint4& v1) {
  v0.x = pack_bf16(a[OFF + 0], a[OFF + 1]); v0.y = pack_bf16(a[OFF + 4], a[OFF + 5]);
  v0.z = pack_bf16(a[OFF + 8], a[OFF + 9]); v0.w = pack_bf16(a[OFF + 12], a[OFF + 13]);
  v1.x = pack_bf16(a[OFF + 2], a[OFF + 3]); v1.y = pack_bf16(a[OFF + 6], a[OFF + 7]);
  v1.z = pack_bf16(a[OFF + 10], a[OFF + 11]); v1.w = pack_bf16(a[OFF + 14], a[OFF + 15]);
}
__device__ __forceinline__ void sq_acc(const uint4& v, uint32_t& a) { a = hfma2(v.x, v.x, a); a = hfma2(v.y, v.y, a); a = hfma2(v.z, v.z, a); a = hfma2(v.w, v.w, a); }
__device__ __forceinline__ float norm2_max(uint32_t a0, uint32_t a1) {
  float n0 = bf_lo(a0) + bf_hi(a0), n1 = bf_lo(a1) + bf_hi(a1);
  n0 += __shfl_xor_sync(~0u, n0, 1); n1 += __shfl_xor_sync(~0u, n1, 1);
  n0 += __shfl_xor_sync(~0u, n0, 2); n1 += __shfl_xor_sync(~0u, n1, 2);
  return __uint_as_float(__reduce_max_sync(~0u, max(__float_as_uint(n0) & 0x7fffffffu, __float_as_uint(n1) & 0x7fffffffu)));
}

struct Pend { uint4 lo[8], hi[8]; uint32_t dst; float kn; };
__device__ __forceinline__ void pin(uint4 (&v)[8]) {
#pragma unroll
  for (int i = 0; i < 8; i++) asm volatile("" : "+r"(v[i].x), "+r"(v[i].y), "+r"(v[i].z), "+r"(v[i].w) :: "memory");
}
__device__ __forceinline__ uint32_t atom_off(int lane) { return (lane >> 2) * 64 + (((lane ^ (lane >> 3)) & 3) << 4); }
__device__ __forceinline__ void stg128(void* p, const uint4& v, bool stream) {
  if (stream) asm volatile("st.global.L2::cache_hint.v4.u32 [%0], {%1,%2,%3,%4}, %5;" :: "l"(p), "r"(v.x), "r"(v.y), "r"(v.z), "r"(v.w), "l"(pol_first()) : "memory");
  else *(uint4*)p = v;
}
template<int J0, int J1, bool STREAM = false> __device__ __forceinline__ void tile_store(const uint4 (&v)[8], uint32_t dst, int lane) {
  uint8_t* d = g_T + (dst + atom_off(lane));
#pragma unroll
  for (int j = J0; j < J1; j++) { stg128(d + j * 512, v[2 * j], STREAM); stg128(d + j * 512 + 2048, v[2 * j + 1], STREAM); }
}
__device__ __forceinline__ float tile_norm2(const uint4 (&v)[8]) {
  uint32_t n0 = 0, n1 = 0, n2 = 0, n3 = 0;
#pragma unroll
  for (int j = 0; j < 2; j++) { sq_acc(v[2 * j], n0); sq_acc(v[2 * j + 1], n1); sq_acc(v[2 * j + 4], n2); sq_acc(v[2 * j + 5], n3); }
  return norm2_max(hadd2(n0, n2), hadd2(n1, n3));
}
template<int PART> __device__ __forceinline__ void out_part(Cons& c, Pend& w) {
  if (PART == 0) { w.kn = tile_norm2(w.lo); tile_store<0, 2>(w.lo, w.dst, c.lane); }
  if (PART == 1) tile_store<2, 4>(w.lo, w.dst, c.lane);
  if (PART == 2) {
    const float vn = tile_norm2(w.hi);
    if (c.lane == 0) g_kn2[((w.dst - T_KV) >> 16) * 8 + c.wg * 4 + c.warp] = (vn <= 1.0e30f && vn >= 1.0e-30f) ? w.kn : __uint_as_float(0x7f800000u);
    tile_store<0, 2, POL(11)>(w.hi, w.dst + 32768, c.lane);
  }
  if (PART == 3) tile_store<2, 4, POL(11)>(w.hi, w.dst + 32768, c.lane);
}
template<bool FIRST> __device__ __forceinline__ void kv_issue(Cons& c, float (&acc)[128], int u) {
  const uint64_t da = odesc(c.daddr(u) + c.wg * 8192, 16, 1024, 1), db = odesc(c.daddr(u + 1), 8192, 1024, 1);
  c.turn();
  wg_fence();
#pragma unroll
  for (int kk = 0; kk < 4; kk++) wgmma_ss_n256<1>(acc, da + kk * 2, db + kk * 128, !(FIRST && kk == 0));
  wg_commit();
  c.pass();
}
template<bool NEXT> __device__ __forceinline__ void cons_kv(Cons& c, int h, int hs, int g, Pend& w, bool pend_o) {
#pragma unroll 1
  for (int tile = 0; tile < 2; tile++) {
    float acc[128];
    if (tile == 0) c.wait(0);
    if (tile == 0 && h < 16) TS(c.wg, 16);
    kv_issue<true>(c, acc, 0);
    c.release(9, tile == 1 ? 3 : 0);
    if (tile == 1 && pend_o) mbar_wait(c.base + SM_RDY + 8 * RDY_WAR, 0);
    if (tile == 1 || pend_o) out_part<0>(c, w);
#pragma unroll 1
    for (int ks = 1; ks < 8; ks++) {
      if (ks == 3 && (tile == 1 || pend_o)) { out_part<1>(c, w); if (tile == 0) c.signal(SIG_CTX); }
      if (ks == 5 && tile == 1) out_part<2>(c, w);
      if (ks == 7 && tile == 1) out_part<3>(c, w);
      const int u = gemm_unit(ks);
      c.wait(u);
      wg_wait<0>();
      c.release(gemm_unit(ks - 1), 3);
      kv_issue<false>(c, acc, u);
    }
    if (NEXT || tile == 0) c.wait(0);
    wg_wait<0>(); fence_regs(acc);
    if (!NEXT) c.release(9, tile == 1 ? 3 : 0);
    pack_chunk<0>(acc, w.lo[0], w.lo[1]);  pack_chunk<16>(acc, w.lo[2], w.lo[3]); pack_chunk<32>(acc, w.lo[4], w.lo[5]); pack_chunk<48>(acc, w.lo[6], w.lo[7]);
    pack_chunk<64>(acc, w.hi[0], w.hi[1]); pack_chunk<80>(acc, w.hi[2], w.hi[3]); pack_chunk<96>(acc, w.hi[4], w.hi[5]); pack_chunk<112>(acc, w.hi[6], w.hi[7]);
    pin(w.lo); pin(w.hi);
    w.dst = T_KV + (hs * 16 + 2 * g + tile) * 65536 + (c.wg * 4 + c.warp) * 4096;
  }
}
template<bool FIRST> __device__ __forceinline__ void q_issue(Cons& c, float (&a)[64], float (&b)[64], int u) {
  const uint64_t da = odesc(c.daddr(u) + c.wg * 8192, 16, 1024, 1), db = odesc(c.daddr(u + 2), 8192, 1024, 1);
  const uint64_t da2 = odesc(c.daddr(u + 1) + (1 - c.wg) * 8192, 16, 1024, 1);
  c.turn();
  wg_fence();
#pragma unroll
  for (int kk = 0; kk < 4; kk++) wgmma_ss_n128<1>(a, da + kk * 2, db + kk * 128, !(FIRST && kk == 0));
#pragma unroll
  for (int kk = 0; kk < 4; kk++) wgmma_ss_n128<1>(b, da2 + kk * 2, db + kk * 128, !(FIRST && kk == 0));
  wg_commit();
  c.pass();
}
template<int U14, int U15> __device__ __forceinline__ void q_tail(Cons& c, float (&d)[64], int rowhalf) {
  const uint64_t da = odesc(c.daddr(U14) + rowhalf * 8192, 16, 1024, 1), db = odesc(c.daddr(7), 8192, 1024, 1);
  c.turn();
  wg_fence();
#pragma unroll
  for (int kk = 0; kk < 8; kk++) wgmma_ss_n128<1>(d, da + (kk >> 2) * (U15 - U14) * 1024 + (kk & 3) * 2, db + (kk >> 2) * 4096 + (kk & 3) * 128, 1);
  wg_commit();
  c.pass();
}
template<int OFF> __device__ __forceinline__ void q_store(const float (&d)[64], uint4 (&v)[8], uint32_t q0) {
  pack_chunk<0>(d, QSCALE, QSCALE, v[0], v[1]);  sts128o<OFF>(q0, v[0]);        sts128o<OFF + 2048>(q0, v[1]);
  pack_chunk<16>(d, QSCALE, QSCALE, v[2], v[3]); sts128o<OFF + 512>(q0, v[2]);  sts128o<OFF + 2560>(q0, v[3]);
  pack_chunk<32>(d, QSCALE, QSCALE, v[4], v[5]); sts128o<OFF + 1024>(q0, v[4]); sts128o<OFF + 3072>(q0, v[5]);
  pack_chunk<48>(d, QSCALE, QSCALE, v[6], v[7]); sts128o<OFF + 1536>(q0, v[6]); sts128o<OFF + 3584>(q0, v[7]);
}
template<bool PEND_KV> __device__ __forceinline__ void cons_q(Cons& c, int h, Pend& w, float (&b)[64]) {
  float a[64];
  if (!PEND_KV) c.wait(0);
  q_issue<true>(c, a, b, 0);
  if (PEND_KV) { c.release(9, 3); SHADOW out_part<0>(c, w); }
#pragma unroll 1
  for (int ks = 1; ks < 14; ks++) {
    if (PEND_KV && ks < 6) {
      if (ks == 2) out_part<1>(c, w);
      if (ks == 4) out_part<2>(c, w);
      if (ks == 5) { out_part<3>(c, w); c.signal(SIG_KV + (h >> 4)); }
    }
    const int u = gemm_unit(ks);
    c.wait(u);
    wg_wait<0>();
    c.release(gemm_unit(ks - 1), 3);
    q_issue<false>(c, a, b, u);
  }
  c.wait(6); c.wait(9);
  wg_wait<0>();
  c.release(3, 3);
  q_tail<8, 9>(c, b, 1 - c.wg);
  wg_wait<0>(); fence_regs(b);
  c.release(8, 2);
  q_tail<6, 10>(c, a, c.wg);
  c.wait(0);
  const uint32_t q0 = c.addr(0) + (c.wg * 4 + c.warp) * 4096 + atom_off(c.lane);
  SHADOW { uint4 v[8]; q_store<32768>(b, v, q0); w.kn = tile_norm2(v); }
  c.wait(4);
  wg_wait<0>(); fence_regs(a);
  c.release(6, 2); c.release(10, 2);
  q_store<0>(a, w.lo, q0);
  fence_async_smem();
}

__device__ __forceinline__ void issue_qk(float (&s)[64], uint64_t da, uint64_t db) {
#pragma unroll
  for (int kk = 0; kk < 8; kk++) wgmma_ss_n128<0>(s, da + (kk >> 1) * 32 + (kk & 1) * 2, db + (kk >> 1) * 32 + (kk & 1) * 2, kk > 0);
  wg_commit();
}
template<int A, int B> __device__ __forceinline__ void exp_rng(float (&s)[64]) {
#pragma unroll
  for (int i = 4 * A; i < 4 * B; i++) s[i] = ex2(s[i]);
}
template<int A, int B> __device__ __forceinline__ void sum_rng(const float (&s)[64], float (&l)[4]) {
#pragma unroll
  for (int i = A; i < B; i++) { l[0] += s[4 * i]; l[1] += s[4 * i + 1]; l[2] += s[4 * i + 2]; l[3] += s[4 * i + 3]; }
}
template<int A, int B> __device__ __forceinline__ void cvt_p(const float (&s)[64], uint32_t (&p)[32]) {
#pragma unroll
  for (int i = 2 * A; i < 2 * B; i++) p[i] = pack_bf16(s[2 * i], s[2 * i + 1]);
}
template<int K0> __device__ __forceinline__ void mask_half(float (&s)[64], int warp, int lane) {
  const int l0 = warp + (2 * (lane & 3) <= (lane >> 2)), l1 = warp + (2 * (lane & 3) < (lane >> 2));
#pragma unroll
  for (int k = 0; k < 4; k++) {
    float* t = s + 8 * (K0 + k);
    if (k >= l0) { t[0] = -INFINITY; t[6] = -INFINITY; }
    if (k >= l1) { t[1] = -INFINITY; t[7] = -INFINITY; }
    if (k > warp) { t[2] = -INFINITY; t[3] = -INFINITY; }
    if (k >= warp) { t[4] = -INFINITY; t[5] = -INFINITY; }
  }
}
__device__ __forceinline__ void row_inv(float& l0, float& l1) {
  l0 += __shfl_xor_sync(~0u, l0, 1); l1 += __shfl_xor_sync(~0u, l1, 1);
  l0 += __shfl_xor_sync(~0u, l0, 2); l1 += __shfl_xor_sync(~0u, l1, 2);
  l0 = __fdividef(1.f, l0); l1 = __fdividef(1.f, l1);
}
__device__ __forceinline__ void pack_o(const float (&o)[64], float i0, float i1, uint4 (&v)[8]) {
  pack_chunk<0>(o, i0, i1, v[0], v[1]); pack_chunk<16>(o, i0, i1, v[2], v[3]);
  pack_chunk<32>(o, i0, i1, v[4], v[5]); pack_chunk<48>(o, i0, i1, v[6], v[7]);
  pin(v);
}
__device__ __forceinline__ void softmax_safe(float (&s)[64], bool upper_only, float& m0, float& m1, float& sc0, float& sc1) {
  float a0 = m0, a1 = m1;
#pragma unroll
  for (int i = 0; i < 8; i++) { a0 = fmaxf(a0, fmaxf(s[4 * i], s[4 * i + 1])); a1 = fmaxf(a1, fmaxf(s[4 * i + 2], s[4 * i + 3])); }
  if (upper_only) { a0 = m0; a1 = m1; }
#pragma unroll
  for (int i = 8; i < 16; i++) { a0 = fmaxf(a0, fmaxf(s[4 * i], s[4 * i + 1])); a1 = fmaxf(a1, fmaxf(s[4 * i + 2], s[4 * i + 3])); }
  a0 = fmaxf(a0, __shfl_xor_sync(~0u, a0, 1)); a1 = fmaxf(a1, __shfl_xor_sync(~0u, a1, 1));
  a0 = fmaxf(a0, __shfl_xor_sync(~0u, a0, 2)); a1 = fmaxf(a1, __shfl_xor_sync(~0u, a1, 2));
  sc0 = ex2(m0 - a0); sc1 = ex2(m1 - a1);
  m0 = a0; m1 = a1;
#pragma unroll
  for (int i = 0; i < 16; i++) { s[4 * i] -= a0; s[4 * i + 1] -= a0; s[4 * i + 2] -= a1; s[4 * i + 3] -= a1; }
}
struct Att {
  float s[64], o[64], l[4], i0, i1; uint32_t p[32];
  uint32_t qaddr;
};
__device__ __forceinline__ uint32_t ctx_off(const Cons& c, int h, int qb, int rowhalf) { return T_CTX + (qb * 32 + h) * 32768 + (rowhalf * 4 + c.warp) * 4096; }
__device__ __forceinline__ int att_first(Cons& c, Att& a, int h, const Pend& w) {
  a.qaddr = c.daddr(0) + c.wg * 16384;
  c.turn();
  wg_fence();
  issue_qk(a.s, odesc(a.qaddr, 16, 2048, 2), odesc(c.daddr(4), 16, 2048, 2));
  c.pass();
  c.signal(SIG_ATT + (h >> 4));
  float qn = w.kn;
  SHADOW qn = tile_norm2(w.lo);
  const float kn = __uint_as_float(lds32(c.base + SM_KMAX + 4 * (h >> 4)));
  const int fast = __shfl_sync(~0u, bar_and(3 + c.wg, 128, (qn * kn <= BOUND2) && (w.kn * kn <= BOUND2)), 0);
#pragma unroll
  for (int i = 0; i < 8; i++) { a.p[4 * i] = w.lo[i].x; a.p[4 * i + 1] = w.lo[i].y; a.p[4 * i + 2] = w.lo[i].z; a.p[4 * i + 3] = w.lo[i].w; }
  a.l[0] = a.l[1] = a.l[2] = a.l[3] = 0.f; a.i0 = a.i1 = 0.f;
  wg_wait<0>(); fence_regs(a.s);
  c.release(4, 2);
  return fast;
}
__device__ __forceinline__ void att_last(Cons& c, Att& a, Pend& w, int h, int g, bool drain) {
#pragma unroll 1
  for (int k = drain ? 0 : 1; k < 2; k++) {
    if (k == 1) {
      const int uv = att_slot(1);
      c.wait(uv);
      c.turn();
      fence_regs(a.o); fence_regs(a.p);
      wgmma_pv_sel(a.o, a.p, odesc(c.daddr(uv), 512, 2048, 2), !(drain && c.wg == 1), !drain);
      c.pass();
      a.i0 = a.l[0] + a.l[1]; a.i1 = a.l[2] + a.l[3]; row_inv(a.i0, a.i1);
      wg_wait<0>(); fence_regs(a.o); fence_regs(a.p);
      c.release(uv, 2);
    }
    pack_o(a.o, a.i0, a.i1, w.lo);
    if (k == 0) tile_store<0, 4>(w.lo, ctx_off(c, h, 15, c.wg), c.lane);
  }
  w.dst = ctx_off(c, h, g, 1 - c.wg);
}
__device__ __forceinline__ void cons_att(Cons& c, Att& a, int h, int g, Pend& w) {
  const int fast = att_first(c, a, h, w);
  float m0 = -INFINITY, m1 = -INFINITY, sc0 = 0.f, sc1 = 0.f;
  int uk = 10, nrel = 0;
#pragma unroll 1
  for (int d = g - 15;;) {
    const bool lo = d == c.wg;
    if ((unsigned)d < 2 || !fast) {
      if ((unsigned)d < 2) mask_half<4>(a.s, c.warp, c.lane);
      if (!fast) {
        if (d == 1) m0 = m1 = -INFINITY;
        softmax_safe(a.s, lo, m0, m1, sc0, sc1);
        a.l[0] *= sc0; a.l[1] *= sc0; a.l[2] *= sc1; a.l[3] *= sc1;
      }
    }
    exp_rng<8, 16>(a.s); sum_rng<8, 16>(a.s, a.l);
    exp_rng<ATT_SPLIT, 8>(a.s);
    sched_fence(((a.l[0] + a.l[1]) + (a.l[2] + a.l[3])) + (ATT_SPLIT < 8 ? a.s[4 * ATT_SPLIT + 3] : 0.f), c.base + SM_DUMMY);
    wg_wait<0>(); fence_regs(a.o); fence_regs(a.p);
    c.release(14 - uk, nrel);
    nrel = 2; uk ^= 12;
    if (d == 0) a.qaddr += 32768;
    const uint64_t dq = odesc(a.qaddr, 16, 2048, 2), dk = odesc(c.daddr(uk) - (d + 1 == c.wg ? 16384 : 0), 16, 2048, 2), dv = odesc(c.daddr(14 - uk), 512, 2048, 2);
    if (!lo) { exp_rng<0, ATT_SPLIT>(a.s); sum_rng<0, 8>(a.s, a.l); cvt_p<0, 16>(a.s, a.p); }
    else if (gridDim.y == 1) cvt_p<8, 16>(a.s, a.p);
    if (!fast || d == g + 1) {
      if (!fast && d != 1) {
#pragma unroll
        for (int i = 0; i < 16; i++) { a.o[4 * i] *= sc0; a.o[4 * i + 1] *= sc0; a.o[4 * i + 2] *= sc1; a.o[4 * i + 3] *= sc1; }
      }
      if (d == g + 1) break;
    }
    d++;
    if (c.wg == 0) c.wait(uk); else c.skip(uk);
    c.turn();
    fence_regs(a.o); fence_regs(a.p);
    wg_fence();
    issue_qk(a.s, dq, dk);
    if (d == 2) {
      uint4 v[8];
      pack_o(a.o, a.i0, a.i1, v); tile_store<0, 4>(v, ctx_off(c, h, 15 - g, c.wg), c.lane);
    }
    wgmma_pv_sel(a.o, a.p, dv, !lo, d != 2 && d != g - 14);
    c.pass();
    if (d == 1) {
      a.i0 = a.l[0] + a.l[1]; a.i1 = a.l[2] + a.l[3]; row_inv(a.i0, a.i1);
      a.l[0] = a.l[1] = a.l[2] = a.l[3] = 0.f;
    }
    wg_wait<1>(); fence_regs(a.s);
    c.release(uk, 2);
    c.release(d == 0 ? 0 : 2, (d == 0 || d == g + 1) ? 2 : 0);
  }
  att_last(c, a, w, h, g, g == 0);
}

constexpr int CV_H = 1024, CV_U = 5120, CV_D = CV_U + 4128, CV_ROW = 1056;
template<int OFF> __device__ __forceinline__ uint32_t lds32o(uint32_t a) { uint32_t v; asm volatile("ld.shared.u32 %0, [%1+%2];" : "=r"(v) : "r"(a), "n"(OFF) : "memory"); return v; }
template<int G, int G1 = 16> __device__ __forceinline__ void conv_lda(uint32_t (&a)[64], uint32_t p) {
  a[4 * G + 0] = lds32o<-256 * G>(p);
  a[4 * G + 1] = lds32o<-256 * G - 128>(p);
  a[4 * G + 2] = lds32o<-256 * G + 16>(p);
  a[4 * G + 3] = lds32o<-256 * G - 112>(p);
  if constexpr (G + 1 < G1) conv_lda<G + 1, G1>(a, p);
}
struct CvAcc { float lo[16], hi[16]; };
__device__ __forceinline__ void fence_regs(CvAcc& d) { fence_regs(d.lo); fence_regs(d.hi); }
template<int R, int H> __device__ __forceinline__ void conv_mma_h(float (&d)[16], const uint32_t (&a)[64], uint64_t db) {
#pragma unroll
  for (int G = 0; G < 4 * R + 2 * H + 2; G++) wgmma_rs_n32<0>(d, a[4 * G], a[4 * G + 1], a[4 * G + 2], a[4 * G + 3], db + 64 * R + 32 * H - 16 * G, G > 0);
}
template<int T, int G0, int G1> __device__ __forceinline__ void conv_part(float (&d)[16], const uint32_t (&a)[64], uint64_t db) {
#pragma unroll
  for (int G = G0; G < G1; G++) wgmma_rs_n32<0>(d, a[4 * G], a[4 * G + 1], a[4 * G + 2], a[4 * G + 3], db + 32 * T - 16 * G, G > 0);
}
template<int R> __device__ __forceinline__ void conv_mma(CvAcc& d, const uint32_t (&a)[64], uint64_t db) { conv_mma_h<R, 0>(d.lo, a, db); conv_mma_h<R, 1>(d.hi, a, db); }
template<int C0> __device__ __forceinline__ void conv_st_h(const float (&d)[16], uint32_t wq, float& c0, float& c1) {
#pragma unroll
  for (int n = 0; n < 4; n++) { sts64f(wq + (C0 + n * 8) * 4, d[4 * n] + c0, d[4 * n + 1] + c1); c0 = d[4 * n + 2]; c1 = d[4 * n + 3]; }
}
template<int R> __device__ __forceinline__ void conv_st(const CvAcc& d, uint32_t wq, float& c0, float& c1) { conv_st_h<64 * R>(d.lo, wq, c0, c1); conv_st_h<64 * R + 32>(d.hi, wq, c0, c1); }
struct ConvTail { float t[64]; uint4 ua, uc; uint32_t D2; };
__device__ __forceinline__ void conv_emit(ConvTail& e, int ch, int tid) {
  fence_regs(e.t);
  float y[16];
#pragma unroll
  for (int i = 0; i < 16; i++) y[i] = (e.t[i] + e.t[16 + i]) + (e.t[32 + i] + e.t[48 + i]);
  uint4 z0, z1;
  z0.x = hadd2(pack_bf16(y[0], y[2]), hmul2(__byte_perm(e.ua.w, 0, 0x1032), e.D2));
  z0.y = hadd2(pack_bf16(y[4], y[6]), hmul2(__byte_perm(e.ua.z, 0, 0x1032), e.D2));
  z0.z = hadd2(pack_bf16(y[8], y[10]), hmul2(__byte_perm(e.ua.y, 0, 0x1032), e.D2));
  z0.w = hadd2(pack_bf16(y[12], y[14]), hmul2(__byte_perm(e.ua.x, 0, 0x1032), e.D2));
  z1.x = hadd2(pack_bf16(y[1], y[3]), hmul2(__byte_perm(e.uc.w, 0, 0x1032), e.D2));
  z1.y = hadd2(pack_bf16(y[5], y[7]), hmul2(__byte_perm(e.uc.z, 0, 0x1032), e.D2));
  z1.z = hadd2(pack_bf16(y[9], y[11]), hmul2(__byte_perm(e.uc.y, 0, 0x1032), e.D2));
  z1.w = hadd2(pack_bf16(y[13], y[15]), hmul2(__byte_perm(e.uc.x, 0, 0x1032), e.D2));
  uint4* zp = (uint4*)(g_z + (uint32_t)(ch * 2048 + tid * 16));
  zp[0] = z0; zp[1] = z1;
}
template<int MASK> __device__ __forceinline__ void cons_conv(Cons& c, int cta, int nch) {
  const int r = c.lane >> 2, q = c.lane & 3, tid = c.warp * 32 + c.lane;
  const uint32_t part = c.addr(4) - 2048 + (1 - c.wg) * (32 * CV_ROW) + 32;
  const uint32_t aoff = CV_U + ((r & 1) ? 0 : UPITCH) + 4 * (((2039 - r) >> 1) + q - 8 * c.warp);
  const uint32_t wq = part + (c.warp * 8 + r) * CV_ROW + q * 8, rq = part + tid * 8;
  uint32_t a[64];
  ConvTail e = {};
  c.wait(c.wg); c.skip(c.wg ^ 1);
  conv_lda<0>(a, c.addr(c.wg) + aoff);
  c.wait(4);
  sts64f(part + (tid >> 2) * CV_ROW - 32 + q * 8, 0.f, 0.f);
#pragma unroll 1
  for (int i = 0; i < nch / 2; i++) {
    const int u = 2 * (i & 1) + c.wg;
    CvAcc d0, d1, d2, d3;
    float c0 = 0.f, c1 = 0.f;
    const uint64_t db = odesc(c.daddr(u) + CV_H - 16, 16, 128, 0);
    c.turn();
    fence_regs(a);
    wg_fence();
    conv_mma<0>(d0, a, db); conv_mma<1>(d1, a, db); wg_commit();
    if (i > 0) {
      conv_emit(e, conv_channel<MASK>(cta, 2 * i - 2 + c.wg), tid);
      if ((i & 15) == 0) c.signal(SIG_Z + (i >> 4) - 1);
    }
    wg_fence();
    conv_mma_h<2, 0>(d2.lo, a, db); wg_commit();
    wg_wait<1>(); fence_regs(d0); fence_regs(d1);
    conv_st_h<0>(d0.lo, wq, c0, c1);
    wg_fence();
    conv_mma_h<2, 1>(d2.hi, a, db); wg_commit();
    conv_st_h<32>(d0.hi, wq, c0, c1);
    conv_mma_h<3, 0>(d3.lo, a, db);
    conv_st_h<64>(d1.lo, wq, c0, c1);
    conv_mma_h<3, 1>(d3.hi, a, db); wg_commit();
    c.pass();
    const int un = i + 1 < nch / 2 ? u ^ 2 : u;
    if (un != u) { c.wait(un); c.skip(un ^ 1); }
    wg_wait<1>(); fence_regs(d2);
    conv_st_h<96>(d1.hi, wq, c0, c1);
    conv_st<2>(d2, wq, c0, c1);
    {
      const int sw = (c.lane >> 2) & 1;
      const uint4 v0 = lds128(c.addr(u) + CV_U + 4064 - 32 * tid + 16 * sw), v1 = lds128(c.addr(u) + CV_U + 4080 - 32 * tid - 16 * sw);
      e.ua = sw ? v0 : v1; e.uc = sw ? v1 : v0;
    }
    e.D2 = lds32(c.addr(u) + CV_D);
    wg_wait<0>(); fence_regs(d3); fence_regs(a);
    conv_st<3>(d3, wq, c0, c1);
    conv_lda<0, 4>(a, c.addr(un) + aoff);
    bar_sync(3 + c.wg, 128);
    sched_fence(__uint_as_float(e.ua.x ^ e.uc.x ^ e.D2), c.base + SM_DUMMY);
    c.release2(u);
    conv_lda<4, 16>(a, c.addr(un) + aoff);
#pragma unroll
    for (int k = 0; k < 32; k++) { const float2 v = lds64f(rq + k * CV_ROW - (k >> 3) * 8); e.t[2 * k] = v.x; e.t[2 * k + 1] = v.y; }
  }
  conv_emit(e, conv_channel<MASK>(cta, nch - 2 + c.wg), tid);
  c.signal(SIG_Z + ((nch / 2 - 1) >> 4));
  c.release(4, 4);
}

constexpr int OC_START = 2, OC_PART = 13824, OC_ROW = 544;
__device__ __forceinline__ int out_next(int u) { return u == 12 ? 4 : u + 2; }
struct Out { float acc[64]; int pu; uint64_t da, db; };
template<bool FIRST, bool REL, int W = 1, bool PRE = true, bool POST = false> __device__ __forceinline__ void out_step(Cons& c, Out& o) {
  const int pu = o.pu, u = out_next(pu);
  o.pu = u;
  if (PRE) c.wait(u);
  const uint64_t da = o.da + (uint32_t)(u * 1024), db = o.db + (uint32_t)(u * 1024);
  wg_fence();
#pragma unroll
  for (int kk = 0; kk < 4; kk++) wgmma_ss_n128<1>(o.acc, da + (kk >> 1) * 32 + (kk & 1) * 2, db + kk * 128, !(FIRST && kk == 0));
  wg_commit();
  if (REL) { wg_wait<W>(); c.release(pu, 2); }
  if (POST) c.wait(out_next(u));
}
template<int I0, int I1> __device__ __forceinline__ void oc_red(float (&y)[8], uint32_t rq) {
#pragma unroll
  for (int i = I0; i < I1; i++) { const float v = __uint_as_float(lds32(rq + i * OC_ROW - (i >> 3) * 8)); y[i & 7] = i < 8 ? v : y[i & 7] + v; }
}
__device__ __forceinline__ void oc_emit(const float (&y)[8], const uint4& u, uint32_t D2, __nv_bfloat16* dst) {
  uint4 z;
  z.x = hadd2(pack_bf16(y[0], y[1]), hmul2(__byte_perm(u.w, 0, 0x1032), D2));
  z.y = hadd2(pack_bf16(y[2], y[3]), hmul2(__byte_perm(u.z, 0, 0x1032), D2));
  z.z = hadd2(pack_bf16(y[4], y[5]), hmul2(__byte_perm(u.y, 0, 0x1032), D2));
  z.w = hadd2(pack_bf16(y[6], y[7]), hmul2(__byte_perm(u.x, 0, 0x1032), D2));
  *(uint4*)dst = z;
}
template<int MASK> __device__ __forceinline__ void cons_out(Cons& c, const Maps& M, const Params& P, int cta, Pend& w) {
  const int mb = out_mb(cta), nb = out_nb(cta);
  Out o;
  o.da = odesc(c.daddr(0) + c.wg * 8192, 16, 1024, 2); o.db = odesc(c.daddr(1), 8192, 1024, 1);
  o.pu = 5 + gridDim.y;
  out_step<true, false>(c, o);
  if (MASK & PH_ATT) tile_store<0, 2>(w.lo, w.dst, c.lane);
  out_step<false, true>(c, o);
  if (MASK & PH_ATT) { tile_store<2, 4>(w.lo, w.dst, c.lane); c.signal(SIG_CTX + 1); }
  int ks = OC_START;
  if (MASK & PH_CONV) {
    const int r = c.lane >> 2, q = c.lane & 3, tid = c.warp * 32 + c.lane, u = 2 * c.wg;
    const uint32_t ub = c.addr(u), part = ub + OC_PART + 32;
    const uint32_t ap = ub + CV_U + ((r & 1) ? 0 : UPITCH) + 4 * (((2039 - r) >> 1) + q - 8 * c.warp);
    const uint32_t wq = part + (c.warp * 8 + r) * OC_ROW + q * 8, rq = part + tid * 4;
    const int nr = (CV_REG<MASK> + 1 - c.wg) >> 1;
#pragma unroll 1
    for (; ks < (c.wg ? OC_S1 : OC_S0); ks++) out_step<false, true>(c, o);
#define STEP(N) out_step<false, true, 1, !OC_POST, OC_POST>(c, o);
#pragma unroll 1
    for (int i = 0; i < nr; i++) {
      uint32_t a[64];
      CvAcc d0, d1;
      float y[8], c0 = 0.f, c1 = 0.f;
      const uint64_t db = odesc(c.daddr(u + (i >> 8)) + CV_H - 16, 16, 128, 0);
#define STEP2(N) out_step<false, true, 2, !OC_POST, OC_POST>(c, o);
#define PART(...) { const uint64_t db = db0 + (uint32_t)(o.pu >> 8); wg_fence(); __VA_ARGS__; wg_commit(); }
      const uint64_t db0 = db;
      c.wait(u);
      if (OC_POST) c.wait(out_next(o.pu));
      conv_lda<0, 4>(a, ap);
      STEP(0)
      conv_lda<4, 7>(a, ap);
      PART(conv_part<0, 0, 2>(d0.lo, a, db); conv_part<1, 0, 4>(d0.hi, a, db))
      STEP2(1)
      conv_lda<7, 10>(a, ap);
      PART(conv_part<2, 0, 6>(d1.lo, a, db))
      STEP2(2)
      fence_regs(d0);
      bar_sync(3 + c.wg, 128);
      sts64f(wq - 32, 0.f, 0.f);
      conv_st<0>(d0, wq, c0, c1);
      asm volatile("add.f32 %0, %0, 0f80000000;" : "+f"(c0)); asm volatile("add.f32 %0, %0, 0f80000000;" : "+f"(c1));
      PART(conv_part<3, 0, 8>(d1.hi, a, db))
      STEP2(3)
      wg_wait<1>(); fence_regs(d1);
      float e0 = d1.hi[12] + d1.hi[10], e1 = d1.hi[13] + d1.hi[11];
      conv_st<1>(d1, wq, c0, c1);
      asm volatile("add.f32 %0, %0, 0f80000000;" : "+f"(c0)); asm volatile("add.f32 %0, %0, 0f80000000;" : "+f"(c1));
      PART(conv_part<4, 0, 10>(d0.lo, a, db))
      STEP2(4)
      conv_lda<10, 12>(a, ap);
      bar_sync(3 + c.wg, 128);
      oc_red<0, 6>(y, rq);
      PART(conv_part<5, 0, 9>(d0.hi, a, db))
      STEP2(5)
      conv_lda<12, 14>(a, ap);
      oc_red<6, 12>(y, rq);
      PART(conv_part<5, 9, 12>(d0.hi, a, db); conv_part<6, 0, 6>(d1.lo, a, db))
      STEP2(6)
      oc_red<12, 26>(y, rq);
      PART(conv_part<6, 6, 14>(d1.lo, a, db))
      STEP2(7)
      oc_red<26, 32>(y, rq);
      conv_lda<14, 16>(a, ap);
      PART(conv_part<7, 0, 8>(d1.hi, a, db))
      STEP2(8)
      fence_regs(y); fence_regs(d0);
      bar_sync(3 + c.wg, 128);
      sts64f(wq - 32, e0, e1);
      conv_st<0>(d0, wq, c0, c1);
      PART(conv_part<7, 8, 16>(d1.hi, a, db))
      STEP2(9)
      wg_wait<1>(); fence_regs(d1); fence_regs(a);
      const uint4 u0 = lds128(ub + CV_U + 4080 - 16 * tid), u1 = lds128(ub + CV_U + 2032 - 16 * tid);
      const uint32_t D2 = lds32(ub + CV_D);
      conv_st_h<64>(d1.lo, wq, c0, c1);
      sched_fence(__uint_as_float(u0.x ^ u1.x ^ D2), c.base + SM_DUMMY);
      __syncwarp();
      c.release2(u);
      STEP(10)
      conv_st_h<96>(d1.hi, wq, c0, c1);
      __nv_bfloat16* zp = g_z + (uint32_t)(conv_channel<MASK>(cta, 2 * i + c.wg) * 2048 + (threadIdx.x & 127) * 8);
      oc_emit(y, u0, D2, zp);
      bar_sync(3 + c.wg, 128);
      oc_red<0, 6>(y, rq);
      STEP(11)
      oc_red<6, 19>(y, rq);
      STEP(12)
      oc_red<19, 32>(y, rq);
      oc_emit(y, u1, D2, zp + 1024);
      if (i == nr - 1) { c.signal(SIG_Z); c.release2(u + 1); }
      out_step<false, true, 1, !OC_POST>(c, o);
#pragma unroll 1
      for (int k = 14; k < (c.wg ? OC_L1 : OC_L0); k++) out_step<false, true>(c, o);
#undef STEP2
#undef PART
    }
#undef STEP
    if (((CV_REG<MASK> + c.wg) >> 1) & 1) c.skip(u ^ 2);
    ks += nr * (c.wg ? OC_L1 : OC_L0);
  }
  TS(c.wg, 9);
#pragma unroll 1
  for (; ks < 57; ks++) out_step<false, true>(c, o);
  uint32_t ga[32];
  c.wait(2);
  const float g0 = __uint_as_float(lds32(c.base + SM_GATE + 4 * (c.wg * 64 + c.warp * 16 + (c.lane >> 2)))), g1 = __uint_as_float(lds32(c.base + SM_GATE + 32 + 4 * (c.wg * 64 + c.warp * 16 + (c.lane >> 2))));
  const uint32_t gg0 = pack_bf16(g0, g0), gg1 = pack_bf16(g1, g1);
  const uint32_t og0 = pack_bf16(1.f - g0, 1.f - g0), og1 = pack_bf16(1.f - g1, 1.f - g1);
  const int xr = c.wg * 64 + c.warp * 16 + (c.lane & 15);
  const uint32_t xa = c.addr(2) + xr * 128, xs = xr & 7, xh = c.lane >> 4;
  const int zr = (c.lane & 7) + ((c.lane >> 4) << 3);
  const uint32_t za = c.addr(0) + c.wg * 16384 + zr * 128 + (((c.warp * 2 + ((c.lane >> 3) & 1)) ^ (zr & 7)) << 4);
#pragma unroll
  for (int i = 0; i < 8; i++) {
    if (i == 0) out_step<false, true>(c, o);
    if (i == 3) out_step<false, true>(c, o);
    if (i == 6) out_step<false, true>(c, o);
    ldsm4(xa + (i >> 2) * 16384 + ((((i & 3) * 2 + xh) ^ xs) << 4), ga[4 * i], ga[4 * i + 1], ga[4 * i + 2], ga[4 * i + 3]);
  }
#pragma unroll 1
  for (ks = 60; ks < 64; ks++) out_step<false, false>(c, o);
  c.wait(0);
  SHADOW {
#pragma unroll
    for (int i = 0; i < 8; i++) {
      uint32_t z0, z1, z2, z3;
      ldsm4t(za + i * 2048, z0, z1, z2, z3);
      ga[4 * i + 0] = hmul2(gg0, hmul2(ga[4 * i + 0], z0)); ga[4 * i + 1] = hmul2(gg1, hmul2(ga[4 * i + 1], z1));
      ga[4 * i + 2] = hmul2(gg0, hmul2(ga[4 * i + 2], z2)); ga[4 * i + 3] = hmul2(gg1, hmul2(ga[4 * i + 3], z3));
    }
  }
  c.signal(SIG_DONE);
  fence_regs(ga);
  wg_wait<0>(); fence_regs(o.acc);
#pragma unroll
  for (int i = 0; i < 8; i++) {
    const uint32_t r0 = hadd2(ga[4 * i + 0], hmul2(og0, pack_bf16(o.acc[8 * i + 0], o.acc[8 * i + 1])));
    const uint32_t r1 = hadd2(ga[4 * i + 1], hmul2(og1, pack_bf16(o.acc[8 * i + 2], o.acc[8 * i + 3])));
    const uint32_t r2 = hadd2(ga[4 * i + 2], hmul2(og0, pack_bf16(o.acc[8 * i + 4], o.acc[8 * i + 5])));
    const uint32_t r3 = hadd2(ga[4 * i + 3], hmul2(og1, pack_bf16(o.acc[8 * i + 6], o.acc[8 * i + 7])));
    stsm4(xa + (i >> 2) * 16384 + ((((i & 3) * 2 + xh) ^ xs) << 4), r0, r1, r2, r3);
    if ((i & 3) == 3) {
      __syncwarp();
#pragma unroll
      for (int k = 0; k < 4; k++) {
        const int rr = c.wg * 64 + c.warp * 16 + k * 4 + (c.lane >> 3);
        const uint4 v = lds128(c.addr(2 + (i >> 2)) + rr * 128 + (((c.lane ^ rr) & 7) << 4));
        *(uint4*)(P.out + (uint32_t)((mb * 128 + rr) * 1024 + nb * 128 + (i >> 2) * 64 + (c.lane & 7) * 8)) = v;
      }
    }
  }
}

__device__ __forceinline__ void load_conv(Prod& p, const Maps& M, int u, int ch) {
  if (elect()) {
    mbar_expect(p.full(u), 5120 + UCH);
    tma3d(p.addr(u), &M.h, 0, -8, ch, p.full(u), POL(4));
    bulk_g2s(p.addr(u) + CV_U, g_u + (size_t)ch * UCH, UCH, p.full(u), POL(4));
  }
}
template<int MASK> __device__ __forceinline__ void prod_conv(Prod& p, const Maps& M, int cta, int nch) {
  int ready = -1;
#pragma unroll 1
  for (int i = 0; i < nch; i++) {
    const int ch = conv_channel<MASK>(cta, i);
    const int u = i & 3;
    if ((ch >> 6) != ready) { ready = ch >> 6; if (cta < NREG) mbar_wait(p.base + SM_RDY + 8 * RDY_U, 0); else cnt_wait(g_cnt + (C_U + ready) * CSTRIDE, 128); }
    p.acquire(u, 1);
    load_conv(p, M, u, ch);
    if (i == 3) { p.acquire(4, 4); if (elect()) mbar_arrive(p.full(4)); }
  }
}
#define HOIST(v) asm volatile("" : "+r"(v))
template<int MASK> __device__ __forceinline__ void producer(const Maps& M, const Params& P, uint32_t base, int cta, int lane) {
  Prod p{base, ((MASK & PH_KV) && cta < NREG) ? 0xffffcfffu ^ ((1u << (3 * NFIRST)) - 1) : 0xffffffffu, lane,
         (cta * 3 + 2) * 2048};
  if (cta >= NREG) { if (MASK & PH_CONV) prod_conv<MASK>(p, M, cta, CV_EXTRA<MASK>); return; }
  const int g = cta & 7, j = cta >> 3, rank = cta & 1;
#pragma unroll 1
  for (int half = 0; half < 2; half++) {
    const int h = j + 16 * half;
    if (MASK & PH_KV) {
      const CUtensorMap* mw = rank ? &M.wv : &M.wk;
#pragma unroll 1
      for (int it = half ? 0 : NFIRST; it < 16; it++) {
        const int u = gemm_unit(it);
        uint32_t bar = p.full(u), d0 = p.addr(u), d1 = p.addr(u + 1 + rank); int k0 = (it & 7) * 64, r0 = (2 * g + (it >> 3)) * 128;
        HOIST(bar); HOIST(d0); HOIST(d1); HOIST(k0); HOIST(r0);
        p.acquire(u, 3);
        if (elect()) {
          mbar_expect(bar, 3 * UNIT);
          tma3d_mc(d1, mw, 0, k0, 2 * h, bar, POL(0) && it >= 8);
          tma2d(d0, &M.c, k0, r0, bar, half ? POL(8) : POL(10));
        }
      }
    }
    if (MASK & PH_ATT) {
#pragma unroll 1
      for (int ks = 0; ks < 16; ks++) {
        const int u = gemm_unit(ks);
        uint32_t bar = p.full(u), d0 = p.addr(u + (ks == 15)), d1 = p.addr(ks < 14 ? u + 1 : ks - 6), d2 = p.addr(u + 2 - (ks == 14)) + rank * 8192; int k0 = ks * 64;
        HOIST(bar); HOIST(d0); HOIST(d1); HOIST(d2); HOIST(k0);
        p.acquire(u, 3);
        if (elect()) {
          mbar_expect(bar, 3 * UNIT);
          tma2d_mc(d2, &M.wq, h * 128 + rank * 64, k0, bar, POL(1));
          tma2d(d0, &M.x, k0, (15 - g) * 128, bar, half ? POL(9) : POL(10));
          tma2d(d1, &M.x, k0, g * 128, bar, half ? POL(9) : POL(10));
        }
      }
      TS(2, 8 * half + 0);
      mbar_wait(base + SM_RDY + 8 * (RDY_KV + half), 0);
      TS(2, 8 * half + 1);
      p.acquire(0, 4);
      if (elect()) mbar_arrive(p.full(0));
      const uint8_t* KVh = g_T + T_KV + (size_t)kv_slot<MASK>(h) * 16 * 65536;
#pragma unroll 1
      for (int n = 0; n < 34; n++) {
        const int i = n == 1 ? 2 : n == 2 ? 1 : n;
        const int isv = (i > 0 && !(i & 1)) || i == 33;
        const int st = i == 33 ? 16 : (isv ? (i >> 1) - 1 : (i + 1) >> 1);
        const int u = att_slot(i & 3);
        const bool own = st == 15 - (g & 6);
        uint32_t bar = p.full((isv && i < 33) ? 14 - u : u), d0 = p.addr(own ? u : u + rank), off = (st <= 15 - g ? st : 16 - st) * 65536 + isv * 32768 + (own ? 0 : rank * UNIT);
        HOIST(bar); HOIST(d0); HOIST(off);
        p.acquire(u, 2);
        if (elect()) {
          if (!isv || i == 33) mbar_expect(bar, (i == 0 || i == 33) ? 32768 : 65536);
          const bool ef = POL(6) || (POL(14) && st >= 8) || (POL(15) && half);
          if (own) bulk_g2s(d0, KVh + off, 32768, bar, ef); else bulk_g2s_mc(d0, KVh + off, UNIT, bar, ef);
        }
      }
    }
  }
  if ((MASK & PH_CONV) && !(MASK & PH_OUT)) prod_conv<MASK>(p, M, cta, CV_REG<MASK>);
  if (MASK & PH_OUT) {
    const int y0 = out_mb(cta) * 512 + rank * 8, z0 = 2 * out_nb(cta);
    int u = 6;
#pragma unroll 1
    for (int hf = 0; hf < 2; hf++) {
      TS(2, 16 + 2 * hf);
      mbar_wait(base + SM_RDY + 8 * (RDY_CTX + hf), 0);
      TS(2, 17 + 2 * hf);
#pragma unroll 1
      for (int ks = hf * 32; ks < hf * 32 + 32; ks++) {
        u = out_next(u);
        uint32_t bar = p.full(u), d0 = p.addr(u) + rank * 8192, d1 = p.addr(u + 1); int x = (ks & 1) * 256, y = y0 + (ks >> 1) * 16, k0 = ks * 64;
        HOIST(bar); HOIST(d0); HOIST(d1); HOIST(x); HOIST(y); HOIST(k0);
        p.acquire(u, 2);
        if (elect()) {
          mbar_expect(bar, 2 * UNIT);
          tma2d_mc(d0, &M.ctx, x, y, bar, POL(5));
          tma3d(d1, &M.wo, 0, k0, z0, bar, POL(2));
          if (ks == Z_AT) mbar_arrive(base + SM_RDY + 8 * RDY_Z);
        }
      }
    }
  }
}
template<int MASK> __device__ __forceinline__ void producer2(const Maps& M, const Params& P, uint32_t base, int cta, int w, int lane) {
  Prod p{base, 0xffffffffu, lane, 0};
  const int mb = out_mb(cta), nb = out_nb(cta), u = 2 * w;
  if (MASK & PH_CONV) {
    mbar_wait_slow(base + SM_SIG + 8 * (SIG_ATT + 1), 0);
    mbar_wait_slow(base + SM_RDY + 8 * RDY_U, 0);
#pragma unroll 1
    for (int i = w; i < CV_REG<MASK>; i += 2) { p.acquire_slow(u, i < 2 ? 2 : 1); load_conv(p, M, u, conv_channel<MASK>(cta, i)); }
  }
  p.acquire_slow(u, 2);
  if (elect()) asm volatile("prefetch.tensormap [%0];" :: "l"(!w ? &M.z : &M.out) : "memory");
  TSA(52 - 2 * w);
  mbar_wait(base + SM_RDY + 8 * (!w ? RDY_Z : RDY_G), 0);
  TSA(53 - 2 * w);
  if (elect()) {
    mbar_expect(p.full(u), 2 * UNIT + (!w ? 0 : 512));
    tma2d(p.addr(u), !w ? &M.z : &M.x, (!w ? mb : nb) * 128, (!w ? nb : mb) * 128, p.full(u), POL(5));
    tma2d(p.addr(u + 1), !w ? &M.z : &M.x, (!w ? mb : nb) * 128 + 64, (!w ? nb : mb) * 128, p.full(u), POL(5));
    if (w) bulk_g2s(base + SM_GATE, g_gate + mb * 128, 512, p.full(u));
  }
}

__device__ __forceinline__ constexpr uint32_t PUB(int sig, int cnt, int n) { return 0x80000000u | (sig << 24) | (n << 8) | cnt; }
__device__ __forceinline__ constexpr uint32_t GET(int rdy, int cnt, int n) { return (rdy << 24) | (n << 8) | cnt; }
template<int MASK> __device__ __forceinline__ void sync_agent(uint32_t base, int cta, int lane) {
  if ((base & 0x3FFFF) != SMEM_BASE) asm volatile("trap;");
  const int g = cta & 7, j = cta >> 3, go = min(out_mb(cta), 15 - out_mb(cta));
  const int c0 = conv_channel<MASK>(cta, 0), c1 = c0 + CV_REG<MASK> - 1, n0 = min(CV_REG<MASK>, 128 - (c0 & 127));
  constexpr bool KV = MASK & PH_KV, ATT = MASK & PH_ATT, CONV = MASK & PH_CONV, OUT = MASK & PH_OUT, ALL = MASK == PH_ALL;
  uint32_t e = 0;
  if (cta >= NREG) { if (CONV && lane * 32 < CV_EXTRA<MASK>) e = PUB(SIG_Z + lane, C_Z + lane, min(32, CV_EXTRA<MASK> - lane * 32)); }
  else switch (lane) {
    case 0:  if (KV) e = PUB(SIG_KV, C_KV + j, 1); break;
    case 1:  if (ATT) e = GET(RDY_KV, C_KV + j, 8); break;
    case 2:  if (ALL) e = PUB(SIG_WAR, C_WAR + j, 1); break;
    case 3:  if (ATT) e = PUB(SIG_CTX, C_CTX + g, 1); break;
    case 4:  if (ALL) e = GET(RDY_WAR, C_WAR + j, 8); break;
    case 5:  if (KV) e = PUB(SIG_KV + 1, C_KV + 16 + j, 1); break;
    case 6:  if (ATT) e = GET(RDY_KV + 1, C_KV + 16 + j, 8); break;
    case 7:  if (OUT) e = GET(RDY_CTX, C_CTX + go, 16); break;
    case 8:  if (CONV) e = GET(RDY_U, C_U + (c0 >> 6), 128); break;
    case 9:  if (CONV) e = GET(RDY_U, C_U + (c1 >> 6), 128); break;
    case 10: if (ATT) e = PUB(SIG_CTX + 1, C_CTX + 8 + g, 1); break;
    case 11: if (OUT) e = GET(RDY_CTX + 1, C_CTX + 8 + go, 16); break;
    case 12: if (OUT) e = GET(RDY_G, C_GATE, 256); break;
    case 13: if (CONV) e = PUB(SIG_Z, C_Z + (c0 >> 7), n0); break;
    case 14: if (CONV && n0 < CV_REG<MASK>) e = PUB(SIG_Z, C_Z + (c1 >> 7), CV_REG<MASK> - n0); break;
    case 15: if (OUT) e = GET(RDY_Z, C_Z + out_nb(cta), 128); break;
  }
  __syncwarp();
#pragma unroll 1
  for (int i = 0; i < 16; i++) {
    const uint32_t x = __shfl_sync(~0u, e, i), id = (x >> 24) & 127, n = (x >> 8) & 0xffff;
    if (x == 0) continue;
    unsigned* cnt = g_cnt + (x & 255) * CSTRIDE;
    if (x >> 31) {
      mbar_wait_slow(base + SM_SIG + 8 * id, 0);
      if (lane == 0) cnt_publish(cnt, n, i != 14);
    } else {
      cnt_wait(cnt, n);
      if (id < 2) {
        const float4 kn = __ldcg((const float4*)(g_kn2 + kv_slot<MASK>(j + 16 * id) * 128) + lane);
        const uint32_t m = __reduce_max_sync(~0u, max(max(__float_as_uint(kn.x), __float_as_uint(kn.y)), max(__float_as_uint(kn.z), __float_as_uint(kn.w))));
        if (lane == 0) asm volatile("st.shared.u32 [%0], %1;" :: "r"(base + SM_KMAX + 4 * id), "r"(m) : "memory");
      }
      if (lane == 0) mbar_arrive(base + SM_RDY + 8 * id);
    }
    __syncwarp();
  }
}

__device__ __forceinline__ void aux_gate(const Params& P, int cta, int aw, int lane) {
  uint4 gw[4];
#pragma unroll
  for (int i = 0; i < 4; i++) gw[i] = __ldg((const uint4*)P.gw + i * 32 + lane);
#pragma unroll 1
  for (int row = cta * 16 + aw * 8; row < cta * 16 + aw * 8 + 8; row++) {
    float a = 0.f;
#pragma unroll
    for (int i = 0; i < 4; i++) {
      const uint4 xv = __ldg((const uint4*)(P.x + (size_t)row * 1024) + i * 32 + lane);
      uint32_t m;
      m = hmul2(xv.x, gw[i].x); a += bf_lo(m) + bf_hi(m); m = hmul2(xv.y, gw[i].y); a += bf_lo(m) + bf_hi(m);
      m = hmul2(xv.z, gw[i].z); a += bf_lo(m) + bf_hi(m); m = hmul2(xv.w, gw[i].w); a += bf_lo(m) + bf_hi(m);
    }
#pragma unroll
    for (int o = 16; o > 0; o >>= 1) a += __shfl_xor_sync(~0u, a, o);
    a = bf_lo(pack_bf16(a, 0.f));
    const float gt = bf_lo(pack_bf16(__fdividef(1.f, 1.f + ex2(-a * 1.4426950408889634f)), 0.f));
    if (lane == 0) g_gate[row] = gt;
    if (GATE_SLEEP) __nanosleep(GATE_SLEEP);
  }
  cnt_signal(g_cnt + C_GATE * CSTRIDE, lane);
  if (aw == 0) { TSA(44); }
}
template<int MASK> __device__ __forceinline__ void aux_pre(const Maps& M, const Params& P, uint32_t base, int cta, int aw, int lane) {
  const uint32_t kb = base + 12 * UNIT, bar = base + SM_PRE;
  const int r = lane >> 2, q = lane & 3;
  const int mi = lane >> 3, row0 = (lane & 6) + 1 - (lane & 1);
  const int ra = (mi * 9 + 1) * 2 + row0;
  const int rb = (mi == 0 ? 3 : mi) * 18 + row0;
  if (PRE_DELAY) mbar_wait_slow(base + SM_BAR + 8 * PRE_DELAY_BAR, 0);
#pragma unroll 1
  for (int it = 0; it < (cta < 96 ? 5 : 4); it++) {
    if (GATE_EARLY && it == PRE_EARLY && MASK == PH_ALL) { mbar_wait_slow(base + SM_SIG + 8 * SIG_ATT, 0); aux_gate(P, cta, aw, lane); }
    if (it == PRE_EARLY && MASK == PH_ALL) mbar_wait_slow(base + SM_SIG + 8 * (SIG_ATT + PRE_HALF), 0);
    const int cg = it ? it * 4 - 3 + (cta >> 5) : 0, tb = cta & 31;
    if (aw == 0 && elect()) {
      mbar_expect(bar, 2 * 9216);
      tma4d(kb, &M.k, cg * 64, 0, tb * 8 - 1, 0, bar, POL(3));
      tma4d(kb + 9216, &M.v, cg * 64, 0, tb * 8 - 1, 0, bar, POL(3));
    }
    const uint2 swl = __ldg((const uint2*)(P.shift + (cg * 64 + aw * 32 + lane) * 4));
    if (tb == 0) {
      uint8_t* e = g_u + (size_t)(cg * 64 + aw * 32 + lane) * UCH + 4096;
      *(uint4*)e = make_uint4(0, 0, 0, 0); *(uint4*)(e + UPITCH) = make_uint4(0, 0, 0, 0);
      *(uint32_t*)(e + 32) = (uint32_t)__bfloat16_as_ushort(P.D[cg * 64 + aw * 32 + lane]) * 0x10001u;
    }
    mbar_wait_slow(bar, it & 1);
#pragma unroll 1
    for (int ol = it ? 0 : cta >> 5; ol < (it ? 4 : (cta >> 5) + 1); ol++) {
      const int oc = aw * 4 + ol;
      const uint32_t s01 = __shfl_sync(~0u, swl.x, ol * 8 + r), s23 = __shfl_sync(~0u, swl.y, ol * 8 + r);
      const uint32_t w0 = __byte_perm(s01, 0, 0x1010), w1 = __byte_perm(s01, 0, 0x3232), w2 = __byte_perm(s23, 0, 0x1010), w3 = __byte_perm(s23, 0, 0x3232);
      const uint32_t pa = kb + ra * 128 + ((oc ^ (ra & 7)) << 4), pb = kb + (mi == 0 ? 9216 : 0) + rb * 128 + ((oc ^ (rb & 7)) << 4);
      uint8_t* e0 = g_u + (uint32_t)((cg * 64 + oc * 8 + r) * UCH + (2040 - tb * 64 - 8 * q) * 2);
#pragma unroll
      for (int hb = 0; hb < 2; hb++) {
        uint32_t k[7], v[5];
        ldsm4t(pa + hb * 1024, k[3], k[4], k[5], k[6]);
        ldsm4t(pa + hb * 1024 + 9216, v[1], v[2], v[3], v[4]);
        ldsm4t(pb + hb * 1024, v[0], k[0], k[1], k[2]);
        uint32_t o1 = __byte_perm(k[1], k[0], 0x5432);
#pragma unroll
        for (int m = 0; m < 5; m++) {
          const uint32_t o2 = __byte_perm(k[m + 2], k[m + 1], 0x5432);
          v[m] = hmul2(hadd2(hadd2(hadd2(hmul2(o1, w3), hmul2(k[m + 1], w2)), hmul2(o2, w1)), hmul2(k[m + 2], w0)), v[m]);
          o1 = o2;
        }
        *(uint4*)(e0 - hb * 64) = make_uint4(v[4], v[3], v[2], v[1]);
        *(uint4*)(e0 - hb * 64 + UPITCH) = make_uint4(__byte_perm(v[4], v[3], 0x5432), __byte_perm(v[3], v[2], 0x5432), __byte_perm(v[2], v[1], 0x5432), __byte_perm(v[1], v[0], 0x5432));
        if (PRE_SLEEP && it >= PRE_EARLY) __nanosleep(PRE_SLEEP);
      }
    }
    bar_sync(5, 64);
    if (aw == 0) { TSA(40 + min(it, 3)); }
    if (aw == 1 && lane == 0) asm volatile("red.release.gpu.global.add.u32 [%0], %1;" :: "l"(g_cnt + (C_U + cg) * CSTRIDE), "r"(it ? 4 : 1) : "memory");
  }
  uint32_t rel;
  asm volatile("mapa.shared::cluster.u32 %0, %1, %2;" : "=r"(rel) : "r"(base + SM_BAR + 128 + 8 * (12 + (lane & 1))), "r"((lane >> 1) & 1));
  if (lane < 4) asm volatile("mbarrier.arrive.shared::cluster.b64 _, [%0], 4;" :: "r"(rel) : "memory");
  if (!(GATE_EARLY && MASK == PH_ALL)) aux_gate(P, cta, aw, lane);
}

template<int MASK> __global__ void __cluster_dims__(2, 1, 1) __launch_bounds__(384, 1) gated_mix_kernel(const __grid_constant__ Maps M, const __grid_constant__ Params P) {
  extern __shared__ __align__(1024) uint8_t smem[];
  const uint32_t base = (uint32_t)__cvta_generic_to_shared(smem);
  const int wi = __shfl_sync(~0u, threadIdx.x >> 5, 0), wg = wi >> 2, warp = wi & 3;
  if (elect()) {
    if (wi < 8) {
      const int cnt = 1 << ((0x10334400 >> (4 * wi)) & 15);
#pragma unroll
      for (int i = 0; i < 8; i++) mbar_init(base + SM_BAR + 64 * wi + 8 * i, cnt);
      asm volatile("fence.mbarrier_init.release.cluster;" ::: "memory");
    } else if (MAP_PF) {
      asm volatile("prefetch.tensormap [%0];" :: "l"(&M.c + (wi - 8)) : "memory");
    }
  }
  const int cta = blockIdx.x;
  const bool first_loads = (MASK & PH_KV) && wi == 8 && cta < NREG;
  const CUtensorMap* mw = (cta & 1) ? &M.wv : &M.wk;
  __syncwarp();
  asm volatile("barrier.cluster.arrive.relaxed.aligned;\nbarrier.cluster.wait.aligned;" ::: "memory");
  if (first_loads && elect()) {
#pragma unroll 1
    for (int it = 0; it < NFIRST; it++) {
      const uint32_t bar = base + SM_BAR + 24 * it, d0 = base + 3 * it * UNIT;
      mbar_expect(bar, 3 * UNIT);
      tma3d_mc(d0 + (1 + (cta & 1)) * UNIT, mw, 0, it * 64, 2 * (cta >> 3), bar);
      tma2d(d0, &M.c, it * 64, (cta & 7) * 256, bar);
    }
  }
  __syncwarp();
  const int lane = threadIdx.x & 31;
#define TS_PRO()
  if (wg == 2) {
    asm volatile("setmaxnreg.dec.sync.aligned.u32 56;");
    TS_PRO();
    TS(2, 62);
    if (warp == 0) producer<MASK>(M, P, base, cta, lane);
    else if (warp == 1) sync_agent<MASK>(base, cta, lane);
    else if (cta < NREG) {
      if (MASK & PH_PRE) aux_pre<MASK>(M, P, base, cta, warp - 2, lane);
      if (MASK & PH_OUT) producer2<MASK>(M, P, base, cta, warp - 2, lane);
    }
    if (warp == 1) {
      if (MASK & PH_OUT) {
        unsigned old = 0;
        if (lane == 0) asm volatile("atom.relaxed.gpu.global.add.u32 %0, [%1], 1;" : "=r"(old) : "l"(g_cnt + C_EXIT * CSTRIDE) : "memory");
        old = __shfl_sync(~0u, old, 0);
        if (old == NCTA - 1) for (int i = lane; i < C_NUM; i += 32) g_cnt[i * CSTRIDE] = 0;
      }
      mbar_wait_slow(base + SM_SIG + 8 * SIG_DONE, 0);
      if (cta >= NREG || !(MASK & PH_OUT)) { cluster_arrive(); cluster_wait(); }
    }
  } else {
    asm volatile("setmaxnreg.inc.sync.aligned.u32 224;");
    TS_PRO();
    uint32_t rel;
    asm volatile("mapa.shared::cluster.u32 %0, %1, %2;" : "=r"(rel) : "r"(base + SM_BAR + 128 + 8 * (lane & 15)), "r"(lane >> 4));
    Cons c{base, rel, 0u, lane, warp, wg, (cta * 3 + wg) * 2048};
    if (wg == 1) bar_arrive(1, 256);
    TS(wg, 0);
    if (cta < NREG) {
      const int g = cta & 7, j = cta >> 3;
      Pend w = {};
#pragma unroll 1
      for (int half = 0; half < 2; half++) {
        const int h = j + 16 * half;
        if (MASK & PH_KV) cons_kv<(MASK & PH_ATT) != 0>(c, h, kv_slot<MASK>(h), g, w, half == 1 && (MASK & PH_ATT));
        TS(wg, 1 + 4 * half);
        if (MASK & PH_ATT) {
          Att a;
          cons_q<(MASK & PH_KV) != 0>(c, h, w, a.o);
          TS(wg, 2 + 4 * half);
          cons_att(c, a, h, g, w);
          if (half == 0) c.signal(SIG_WAR);
#pragma unroll
          for (int i = 0; i < 8; i++) w.hi[i] = make_uint4(0, 0, 0, 0);
          TS(wg, 3 + 4 * half);
          if (MASK != PH_ALL) { tile_store<0, 4>(w.lo, w.dst, lane); c.signal(SIG_CTX + half); }
        } else if (MASK & PH_KV) { out_part<0>(c, w); out_part<1>(c, w); out_part<2>(c, w); out_part<3>(c, w); c.signal(SIG_KV + half); }
      }
      if (MASK & PH_OUT) cons_out<MASK>(c, M, P, cta, w);
    }
    if (cta >= NREG || !(MASK & PH_OUT)) {
      if (MASK & PH_CONV) cons_conv<MASK>(c, cta, cta < NREG ? CV_REG<MASK> : CV_EXTRA<MASK>);
      TS(wg, 9);
      c.signal(SIG_DONE);
      cluster_arrive();
    }
    TS(wg, 10);
  }
}

typedef CUresult (*EncFn)(CUtensorMap*, CUtensorMapDataType, cuuint32_t, void*, const cuuint64_t*, const cuuint64_t*, const cuuint32_t*, const cuuint32_t*,
                          CUtensorMapInterleave, CUtensorMapSwizzle, CUtensorMapL2promotion, CUtensorMapFloatOOBfill);
static void enc(EncFn f, CUtensorMap* m, const void* ptr, int rank, const cuuint64_t* dims, const cuuint64_t* strides, const cuuint32_t* box, CUtensorMapSwizzle sw,
                CUtensorMapDataType dt = CU_TENSOR_MAP_DATA_TYPE_BFLOAT16) {
  const cuuint32_t es[4] = {1, 1, 1, 1};
  f(m, dt, rank, (void*)ptr, dims, strides, box, es, CU_TENSOR_MAP_INTERLEAVE_NONE, sw, CU_TENSOR_MAP_L2_PROMOTION_L2_256B, CU_TENSOR_MAP_FLOAT_OOB_FILL_NONE);
}
static void enc2(EncFn f, CUtensorMap* m, const void* ptr, int cols, int rows, int brows) {
  const cuuint64_t d[2] = {(cuuint64_t)cols, (cuuint64_t)rows}, s[1] = {(cuuint64_t)cols * 2}; const cuuint32_t b[2] = {64, (cuuint32_t)brows};
  enc(f, m, ptr, 2, d, s, b, CU_TENSOR_MAP_SWIZZLE_128B);
}
static void encw(EncFn f, CUtensorMap* m, const void* ptr, int cols, int rows) {
  const cuuint64_t d[3] = {64, (cuuint64_t)rows, (cuuint64_t)cols / 64}, s[2] = {(cuuint64_t)cols * 2, 128}; const cuuint32_t b[3] = {64, 64, 2};
  enc(f, m, ptr, 3, d, s, b, CU_TENSOR_MAP_SWIZZLE_128B);
}
extern "C" void kernel_launch(void* const* d_in, const int* in_sizes, int n_in, void* d_out, int out_size) {
  static EncFn fn = nullptr;
  static int ncl = 0;
  static void* zptr = nullptr;
  static void* tptr = nullptr;
  if (!fn) {
    void* p = nullptr; cudaDriverEntryPointQueryResult qr;
    cudaGetDriverEntryPoint("cuTensorMapEncodeTiled", &p, cudaEnableDefault, &qr);
    fn = (EncFn)p;
    cudaFuncSetAttribute(gated_mix_kernel<PH_ALL>, cudaFuncAttributeMaxDynamicSharedMemorySize, SMEM_BYTES);
    cudaFuncSetAttribute(gated_mix_kernel<PH_PRE | PH_KV>, cudaFuncAttributeMaxDynamicSharedMemorySize, SMEM_BYTES);
    cudaFuncSetAttribute(gated_mix_kernel<PH_ATT | PH_CONV>, cudaFuncAttributeMaxDynamicSharedMemorySize, SMEM_BYTES);
    cudaFuncSetAttribute(gated_mix_kernel<PH_OUT>, cudaFuncAttributeMaxDynamicSharedMemorySize, SMEM_BYTES);
    cudaLaunchConfig_t cfg = {}; cfg.gridDim = NCTA; cfg.blockDim = 384; cfg.dynamicSmemBytes = SMEM_BYTES;
    cudaLaunchAttribute at; at.id = cudaLaunchAttributeClusterDimension; at.val.clusterDim.x = 2; at.val.clusterDim.y = 1; at.val.clusterDim.z = 1;
    cfg.attrs = &at; cfg.numAttrs = 1;
    cudaOccupancyMaxActiveClusters(&ncl, gated_mix_kernel<PH_ALL>, &cfg);
    cudaGetSymbolAddress(&zptr, g_z);
    cudaGetSymbolAddress(&tptr, g_T);
  }
  Maps M;
  enc2(fn, &M.x, d_in[0], 1024, 2048, 128);
  enc2(fn, &M.c, d_in[7], 512, 2048, 128);
  enc2(fn, &M.wq, d_in[8], 4096, 1024, 64);
  encw(fn, &M.wk, d_in[9], 4096, 512);
  encw(fn, &M.wv, d_in[10], 4096, 512);
  encw(fn, &M.wo, d_in[11], 1024, 4096);
  { const cuuint64_t d[3] = {64, 32, 1024}, s[2] = {128, 4096}; const cuuint32_t b[3] = {64, 40, 1}; enc(fn, &M.h, d_in[4], 3, d, s, b, CU_TENSOR_MAP_SWIZZLE_NONE); }
  enc2(fn, &M.z, zptr, 2048, 1024, 128);
  enc2(fn, &M.out, d_out, 1024, 2048, 16);
  { const cuuint64_t d[2] = {512, 512 * 16}, s[1] = {2048}; const cuuint32_t b[2] = {256, 8};
    enc(fn, &M.ctx, tptr, 2, d, s, b, CU_TENSOR_MAP_SWIZZLE_NONE, CU_TENSOR_MAP_DATA_TYPE_UINT32); }
  { const cuuint64_t d[4] = {1024, 2, 256, 4}, s[3] = {2048, 16384, 4096}; const cuuint32_t b[4] = {64, 2, 9, 4};
    enc(fn, &M.k, d_in[1], 4, d, s, b, CU_TENSOR_MAP_SWIZZLE_128B); enc(fn, &M.v, d_in[2], 4, d, s, b, CU_TENSOR_MAP_SWIZZLE_128B); }
  Params P{(const __nv_bfloat16*)d_in[0], (const __nv_bfloat16*)d_in[3],
           (const __nv_bfloat16*)d_in[5], (const __nv_bfloat16*)d_in[12], (__nv_bfloat16*)d_out};
  bool split = 2 * ncl < NCTA;
  if (!split) {
    gated_mix_kernel<PH_ALL><<<NCTA, 384, SMEM_BYTES>>>(M, P);
  } else {
    gated_mix_kernel<PH_PRE | PH_KV><<<NCTA, 384, SMEM_BYTES>>>(M, P);
    gated_mix_kernel<PH_ATT | PH_CONV><<<NCTA, 384, SMEM_BYTES>>>(M, P);
    gated_mix_kernel<PH_OUT><<<NCTA, 384, SMEM_BYTES>>>(M, P);
  }
}
```

```cpp
#include <cuda_runtime.h>
#include <cuda.h>
#include <cuda_bf16.h>
#include <stdint.h>

template<int TB> __device__ __forceinline__ void wgmma_ss_n256(float (&d)[128], uint64_t da, uint64_t db, int scale_d) {
  asm volatile("{\n.reg .pred p;\nsetp.ne.b32 p, %130, 0;\n"
    "wgmma.mma_async.sync.aligned.m64n256k16.f32.bf16.bf16 {%0, %1, %2, %3, %4, %5, %6, %7, %8, %9, %10, %11, %12, %13, %14, %15, %16, %17, %18, %19, %20, %21, %22, %23, %24, %25, %26, %27, %28, %29, %30, %31, %32, %33, %34, %35, %36, %37, %38, %39, %40, %41, %42, %43, %44, %45, %46, %47, %48, %49, %50, %51, %52, %53, %54, %55, %56, %57, %58, %59, %60, %61, %62, %63, %64, %65, %66, %67, %68, %69, %70, %71, %72, %73, %74, %75, %76, %77, %78, %79, %80, %81, %82, %83, %84, %85, %86, %87, %88, %89, %90, %91, %92, %93, %94, %95, %96, %97, %98, %99, %100, %101, %102, %103, %104, %105, %106, %107, %108, %109, %110, %111, %112, %113, %114, %115, %116, %117, %118, %119, %120, %121, %122, %123, %124, %125, %126, %127}, %128, %129, p, 1, 1, 0, %131;\n}\n"
    : "+f"(d[0]), "+f"(d[1]), "+f"(d[2]), "+f"(d[3]), "+f"(d[4]), "+f"(d[5]), "+f"(d[6]), "+f"(d[7]), "+f"(d[8]), "+f"(d[9]), "+f"(d[10]), "+f"(d[11]), "+f"(d[12]), "+f"(d[13]), "+f"(d[14]), "+f"(d[15]), "+f"(d[16]), "+f"(d[17]), "+f"(d[18]), "+f"(d[19]), "+f"(d[20]), "+f"(d[21]), "+f"(d[22]), "+f"(d[23]), "+f"(d[24]), "+f"(d[25]), "+f"(d[26]), "+f"(d[27]), "+f"(d[28]), "+f"(d[29]), "+f"(d[30]), "+f"(d[31]), "+f"(d[32]), "+f"(d[33]), "+f"(d[34]), "+f"(d[35]), "+f"(d[36]), "+f"(d[37]), "+f"(d[38]), "+f"(d[39]), "+f"(d[40]), "+f"(d[41]), "+f"(d[42]), "+f"(d[43]), "+f"(d[44]), "+f"(d[45]), "+f"(d[46]), "+f"(d[47]), "+f"(d[48]), "+f"(d[49]), "+f"(d[50]), "+f"(d[51]), "+f"(d[52]), "+f"(d[53]), "+f"(d[54]), "+f"(d[55]), "+f"(d[56]), "+f"(d[57]), "+f"(d[58]), "+f"(d[59]), "+f"(d[60]), "+f"(d[61]), "+f"(d[62]), "+f"(d[63]), "+f"(d[64]), "+f"(d[65]), "+f"(d[66]), "+f"(d[67]), "+f"(d[68]), "+f"(d[69]), "+f"(d[70]), "+f"(d[71]), "+f"(d[72]), "+f"(d[73]), "+f"(d[74]), "+f"(d[75]), "+f"(d[76]), "+f"(d[77]), "+f"(d[78]), "+f"(d[79]), "+f"(d[80]), "+f"(d[81]), "+f"(d[82]), "+f"(d[83]), "+f"(d[84]), "+f"(d[85]), "+f"(d[86]), "+f"(d[87]), "+f"(d[88]), "+f"(d[89]), "+f"(d[90]), "+f"(d[91]), "+f"(d[92]), "+f"(d[93]), "+f"(d[94]), "+f"(d[95]), "+f"(d[96]), "+f"(d[97]), "+f"(d[98]), "+f"(d[99]), "+f"(d[100]), "+f"(d[101]), "+f"(d[102]), "+f"(d[103]), "+f"(d[104]), "+f"(d[105]), "+f"(d[106]), "+f"(d[107]), "+f"(d[108]), "+f"(d[109]), "+f"(d[110]), "+f"(d[111]), "+f"(d[112]), "+f"(d[113]), "+f"(d[114]), "+f"(d[115]), "+f"(d[116]), "+f"(d[117]), "+f"(d[118]), "+f"(d[119]), "+f"(d[120]), "+f"(d[121]), "+f"(d[122]), "+f"(d[123]), "+f"(d[124]), "+f"(d[125]), "+f"(d[126]), "+f"(d[127])
    : "l"(da), "l"(db), "r"(scale_d), "n"(TB));
}
template<int TB> __device__ __forceinline__ void wgmma_ss_n128(float (&d)[64], uint64_t da, uint64_t db, int scale_d) {
  asm volatile("{\n.reg .pred p;\nsetp.ne.b32 p, %66, 0;\n"
    "wgmma.mma_async.sync.aligned.m64n128k16.f32.bf16.bf16 {%0, %1, %2, %3, %4, %5, %6, %7, %8, %9, %10, %11, %12, %13, %14, %15, %16, %17, %18, %19, %20, %21, %22, %23, %24, %25, %26, %27, %28, %29, %30, %31, %32, %33, %34, %35, %36, %37, %38, %39, %40, %41, %42, %43, %44, %45, %46, %47, %48, %49, %50, %51, %52, %53, %54, %55, %56, %57, %58, %59, %60, %61, %62, %63}, %64, %65, p, 1, 1, 0, %67;\n}\n"
    : "+f"(d[0]), "+f"(d[1]), "+f"(d[2]), "+f"(d[3]), "+f"(d[4]), "+f"(d[5]), "+f"(d[6]), "+f"(d[7]), "+f"(d[8]), "+f"(d[9]), "+f"(d[10]), "+f"(d[11]), "+f"(d[12]), "+f"(d[13]), "+f"(d[14]), "+f"(d[15]), "+f"(d[16]), "+f"(d[17]), "+f"(d[18]), "+f"(d[19]), "+f"(d[20]), "+f"(d[21]), "+f"(d[22]), "+f"(d[23]), "+f"(d[24]), "+f"(d[25]), "+f"(d[26]), "+f"(d[27]), "+f"(d[28]), "+f"(d[29]), "+f"(d[30]), "+f"(d[31]), "+f"(d[32]), "+f"(d[33]), "+f"(d[34]), "+f"(d[35]), "+f"(d[36]), "+f"(d[37]), "+f"(d[38]), "+f"(d[39]), "+f"(d[40]), "+f"(d[41]), "+f"(d[42]), "+f"(d[43]), "+f"(d[44]), "+f"(d[45]), "+f"(d[46]), "+f"(d[47]), "+f"(d[48]), "+f"(d[49]), "+f"(d[50]), "+f"(d[51]), "+f"(d[52]), "+f"(d[53]), "+f"(d[54]), "+f"(d[55]), "+f"(d[56]), "+f"(d[57]), "+f"(d[58]), "+f"(d[59]), "+f"(d[60]), "+f"(d[61]), "+f"(d[62]), "+f"(d[63])
    : "l"(da), "l"(db), "r"(scale_d), "n"(TB));
}
template<int TB> __device__ __forceinline__ void wgmma_rs_n32(float (&d)[16], uint32_t a0, uint32_t a1, uint32_t a2, uint32_t a3, uint64_t db, int scale_d) {
  asm volatile("{\n.reg .pred p;\nsetp.ne.b32 p, %21, 0;\n"
    "wgmma.mma_async.sync.aligned.m64n32k16.f32.bf16.bf16 {%0, %1, %2, %3, %4, %5, %6, %7, %8, %9, %10, %11, %12, %13, %14, %15}, {%16, %17, %18, %19}, %20, p, 1, 1, %22;\n}\n"
    : "+f"(d[0]), "+f"(d[1]), "+f"(d[2]), "+f"(d[3]), "+f"(d[4]), "+f"(d[5]), "+f"(d[6]), "+f"(d[7]), "+f"(d[8]), "+f"(d[9]), "+f"(d[10]), "+f"(d[11]), "+f"(d[12]), "+f"(d[13]), "+f"(d[14]), "+f"(d[15])
    : "r"(a0), "r"(a1), "r"(a2), "r"(a3), "l"(db), "r"(scale_d), "n"(TB));
}
__device__ __forceinline__ void wgmma_pv_sel(float (&d)[64], const uint32_t (&p)[32], uint64_t db, int full, int acc) {
  asm volatile("{\n.reg .pred q, s;\n.reg .b64 t;\nsetp.ne.b32 s, %98, 0;\nsetp.eq.b32 q, %97, 0;\n@q bra.uni LH;\n"
    "wgmma.fence.sync.aligned;\n"
    "add.s64 t, %96, 0;\nwgmma.mma_async.sync.aligned.m64n128k16.f32.bf16.bf16 {%0, %1, %2, %3, %4, %5, %6, %7, %8, %9, %10, %11, %12, %13, %14, %15, %16, %17, %18, %19, %20, %21, %22, %23, %24, %25, %26, %27, %28, %29, %30, %31, %32, %33, %34, %35, %36, %37, %38, %39, %40, %41, %42, %43, %44, %45, %46, %47, %48, %49, %50, %51, %52, %53, %54, %55, %56, %57, %58, %59, %60, %61, %62, %63}, {%64, %65, %66, %67}, t, s, 1, 1, 1;\n"
    "add.s64 t, %96, 256;\nwgmma.mma_async.sync.aligned.m64n128k16.f32.bf16.bf16 {%0, %1, %2, %3, %4, %5, %6, %7, %8, %9, %10, %11, %12, %13, %14, %15, %16, %17, %18, %19, %20, %21, %22, %23, %24, %25, %26, %27, %28, %29, %30, %31, %32, %33, %34, %35, %36, %37, %38, %39, %40, %41, %42, %43, %44, %45, %46, %47, %48, %49, %50, %51, %52, %53, %54, %55, %56, %57, %58, %59, %60, %61, %62, %63}, {%68, %69, %70, %71}, t, 1, 1, 1, 1;\n"
    "add.s64 t, %96, 512;\nwgmma.mma_async.sync.aligned.m64n128k16.f32.bf16.bf16 {%0, %1, %2, %3, %4, %5, %6, %7, %8, %9, %10, %11, %12, %13, %14, %15, %16, %17, %18, %19, %20, %21, %22, %23, %24, %25, %26, %27, %28, %29, %30, %31, %32, %33, %34, %35, %36, %37, %38, %39, %40, %41, %42, %43, %44, %45, %46, %47, %48, %49, %50, %51, %52, %53, %54, %55, %56, %57, %58, %59, %60, %61, %62, %63}, {%72, %73, %74, %75}, t, 1, 1, 1, 1;\n"
    "add.s64 t, %96, 768;\nwgmma.mma_async.sync.aligned.m64n128k16.f32.bf16.bf16 {%0, %1, %2, %3, %4, %5, %6, %7, %8, %9, %10, %11, %12, %13, %14, %15, %16, %17, %18, %19, %20, %21, %22, %23, %24, %25, %26, %27, %28, %29, %30, %31, %32, %33, %34, %35, %36, %37, %38, %39, %40, %41, %42, %43, %44, %45, %46, %47, %48, %49, %50, %51, %52, %53, %54, %55, %56, %57, %58, %59, %60, %61, %62, %63}, {%76, %77, %78, %79}, t, 1, 1, 1, 1;\n"
    "add.s64 t, %96, 1024;\nwgmma.mma_async.sync.aligned.m64n128k16.f32.bf16.bf16 {%0, %1, %2, %3, %4, %5, %6, %7, %8, %9, %10, %11, %12, %13, %14, %15, %16, %17, %18, %19, %20, %21, %22, %23, %24, %25, %26, %27, %28, %29, %30, %31, %32, %33, %34, %35, %36, %37, %38, %39, %40, %41, %42, %43, %44, %45, %46, %47, %48, %49, %50, %51, %52, %53, %54, %55, %56, %57, %58, %59, %60, %61, %62, %63}, {%80, %81, %82, %83}, t, 1, 1, 1, 1;\n"
    "add.s64 t, %96, 1280;\nwgmma.mma_async.sync.aligned.m64n128k16.f32.bf16.bf16 {%0, %1, %2, %3, %4, %5, %6, %7, %8, %9, %10, %11, %12, %13, %14, %15, %16, %17, %18, %19, %20, %21, %22, %23, %24, %25, %26, %27, %28, %29, %30, %31, %32, %33, %34, %35, %36, %37, %38, %39, %40, %41, %42, %43, %44, %45, %46, %47, %48, %49, %50, %51, %52, %53, %54, %55, %56, %57, %58, %59, %60, %61, %62, %63}, {%84, %85, %86, %87}, t, 1, 1, 1, 1;\n"
    "add.s64 t, %96, 1536;\nwgmma.mma_async.sync.aligned.m64n128k16.f32.bf16.bf16 {%0, %1, %2, %3, %4, %5, %6, %7, %8, %9, %10, %11, %12, %13, %14, %15, %16, %17, %18, %19, %20, %21, %22, %23, %24, %25, %26, %27, %28, %29, %30, %31, %32, %33, %34, %35, %36, %37, %38, %39, %40, %41, %42, %43, %44, %45, %46, %47, %48, %49, %50, %51, %52, %53, %54, %55, %56, %57, %58, %59, %60, %61, %62, %63}, {%88, %89, %90, %91}, t, 1, 1, 1, 1;\n"
    "add.s64 t, %96, 1792;\nwgmma.mma_async.sync.aligned.m64n128k16.f32.bf16.bf16 {%0, %1, %2, %3, %4, %5, %6, %7, %8, %9, %10, %11, %12, %13, %14, %15, %16, %17, %18, %19, %20, %21, %22, %23, %24, %25, %26, %27, %28, %29, %30, %31, %32, %33, %34, %35, %36, %37, %38, %39, %40, %41, %42, %43, %44, %45, %46, %47, %48, %49, %50, %51, %52, %53, %54, %55, %56, %57, %58, %59, %60, %61, %62, %63}, {%92, %93, %94, %95}, t, 1, 1, 1, 1;\n"
    "wgmma.commit_group.sync.aligned;\n"
    "bra.uni LE;\nLH:\n"
    "wgmma.fence.sync.aligned;\n"
    "add.s64 t, %96, 0;\nwgmma.mma_async.sync.aligned.m64n128k16.f32.bf16.bf16 {%0, %1, %2, %3, %4, %5, %6, %7, %8, %9, %10, %11, %12, %13, %14, %15, %16, %17, %18, %19, %20, %21, %22, %23, %24, %25, %26, %27, %28, %29, %30, %31, %32, %33, %34, %35, %36, %37, %38, %39, %40, %41, %42, %43, %44, %45, %46, %47, %48, %49, %50, %51, %52, %53, %54, %55, %56, %57, %58, %59, %60, %61, %62, %63}, {%80, %81, %82, %83}, t, s, 1, 1, 1;\n"
    "add.s64 t, %96, 256;\nwgmma.mma_async.sync.aligned.m64n128k16.f32.bf16.bf16 {%0, %1, %2, %3, %4, %5, %6, %7, %8, %9, %10, %11, %12, %13, %14, %15, %16, %17, %18, %19, %20, %21, %22, %23, %24, %25, %26, %27, %28, %29, %30, %31, %32, %33, %34, %35, %36, %37, %38, %39, %40, %41, %42, %43, %44, %45, %46, %47, %48, %49, %50, %51, %52, %53, %54, %55, %56, %57, %58, %59, %60, %61, %62, %63}, {%84, %85, %86, %87}, t, 1, 1, 1, 1;\n"
    "add.s64 t, %96, 512;\nwgmma.mma_async.sync.aligned.m64n128k16.f32.bf16.bf16 {%0, %1, %2, %3, %4, %5, %6, %7, %8, %9, %10, %11, %12, %13, %14, %15, %16, %17, %18, %19, %20, %21, %22, %23, %24, %25, %26, %27, %28, %29, %30, %31, %32, %33, %34, %35, %36, %37, %38, %39, %40, %41, %42, %43, %44, %45, %46, %47, %48, %49, %50, %51, %52, %53, %54, %55, %56, %57, %58, %59, %60, %61, %62, %63}, {%88, %89, %90, %91}, t, 1, 1, 1, 1;\n"
    "add.s64 t, %96, 768;\nwgmma.mma_async.sync.aligned.m64n128k16.f32.bf16.bf16 {%0, %1, %2, %3, %4, %5, %6, %7, %8, %9, %10, %11, %12, %13, %14, %15, %16, %17, %18, %19, %20, %21, %22, %23, %24, %25, %26, %27, %28, %29, %30, %31, %32, %33, %34, %35, %36, %37, %38, %39, %40, %41, %42, %43, %44, %45, %46, %47, %48, %49, %50, %51, %52, %53, %54, %55, %56, %57, %58, %59, %60, %61, %62, %63}, {%92, %93, %94, %95}, t, 1, 1, 1, 1;\n"
    "wgmma.commit_group.sync.aligned;\n"
    "LE:\n}\n"
    : "+f"(d[0]), "+f"(d[1]), "+f"(d[2]), "+f"(d[3]), "+f"(d[4]), "+f"(d[5]), "+f"(d[6]), "+f"(d[7]), "+f"(d[8]), "+f"(d[9]), "+f"(d[10]), "+f"(d[11]), "+f"(d[12]), "+f"(d[13]), "+f"(d[14]), "+f"(d[15]), "+f"(d[16]), "+f"(d[17]), "+f"(d[18]), "+f"(d[19]), "+f"(d[20]), "+f"(d[21]), "+f"(d[22]), "+f"(d[23]), "+f"(d[24]), "+f"(d[25]), "+f"(d[26]), "+f"(d[27]), "+f"(d[28]), "+f"(d[29]), "+f"(d[30]), "+f"(d[31]), "+f"(d[32]), "+f"(d[33]), "+f"(d[34]), "+f"(d[35]), "+f"(d[36]), "+f"(d[37]), "+f"(d[38]), "+f"(d[39]), "+f"(d[40]), "+f"(d[41]), "+f"(d[42]), "+f"(d[43]), "+f"(d[44]), "+f"(d[45]), "+f"(d[46]), "+f"(d[47]), "+f"(d[48]), "+f"(d[49]), "+f"(d[50]), "+f"(d[51]), "+f"(d[52]), "+f"(d[53]), "+f"(d[54]), "+f"(d[55]), "+f"(d[56]), "+f"(d[57]), "+f"(d[58]), "+f"(d[59]), "+f"(d[60]), "+f"(d[61]), "+f"(d[62]), "+f"(d[63])
    : "r"(p[0]), "r"(p[1]), "r"(p[2]), "r"(p[3]), "r"(p[4]), "r"(p[5]), "r"(p[6]), "r"(p[7]), "r"(p[8]), "r"(p[9]), "r"(p[10]), "r"(p[11]), "r"(p[12]), "r"(p[13]), "r"(p[14]), "r"(p[15]), "r"(p[16]), "r"(p[17]), "r"(p[18]), "r"(p[19]), "r"(p[20]), "r"(p[21]), "r"(p[22]), "r"(p[23]), "r"(p[24]), "r"(p[25]), "r"(p[26]), "r"(p[27]), "r"(p[28]), "r"(p[29]), "r"(p[30]), "r"(p[31]), "l"(db), "r"(full), "r"(acc) : "memory");
}

constexpr int NCTA = 132, NREG = 128;
constexpr int UNIT = 16384, NUNIT = 14;
constexpr uint32_t SMEM_BASE = 1024;
constexpr int SM_BAR = NUNIT * UNIT;
constexpr int SM_GATE = SM_BAR + 1024;
constexpr int SMEM_BYTES = SM_BAR + 1536;
constexpr int UPITCH = 4160, UCH = 2 * UPITCH;
constexpr float QSCALE = 0.08838834764831845f * 1.4426950408889634f;
constexpr float BOUND2 = 48.f * 48.f / 1.15f;
#define CONV_REG 5
constexpr int C_KV = 0;
constexpr int C_CTX = 32;
constexpr int C_U = 48;
constexpr int C_Z = 80;
constexpr int C_GATE = 88;
constexpr int C_EXIT = 89;
#define PRE_EARLY 2
#define PRE_HALF 1
#define ATT_SPLIT 6
#define NFIRST 2
#define PRE_DELAY 0
#define MAP_PF 1
#define FINAL_ST 1
#define Z_AT 60
#define PRE_DELAY_BAR 9
#define PRE_FMA 0
#define PRE_SLEEP 300
#define GATE_SLEEP 1000
#define GATE_EARLY 1
#define OC_S0 2
#define OC_S1 11
#define OC_POST 1
#define OC_L0 18
#define OC_L1 18
#define PF 0
#define PF_AT 26
#define PF_KS 8
#define ST_1 4
#define ST_D 2
#define ST_0 1
#define ST_0D 0
#define SCH_KV 0x6665544433221100ull
#define SCH_Q 0x6665544433221100ull
#define NK_AT 1
#ifndef NV_AT
#define NV_AT 3
#endif
#define DEFER_ST 1
#define DS_A 3
#define DS_B 6
#define LASTF 2
#define EF 127
#define POL(bit) (((EF >> (bit)) & 1) != 0)
constexpr int C_WAR = 96;
constexpr int C_NUM = 112;
constexpr int CSTRIDE = 32;
constexpr int SM_KMAX = SM_BAR + 640, SM_DUMMY = SM_BAR + 648, SM_PRE = SM_BAR + 112, SM_SIG = SM_BAR + 256, SM_RDY = SM_BAR + 384;
enum { SIG_KV = 0, SIG_CTX = 2, SIG_Z = 4, SIG_DONE = 8, SIG_WAR = 9, SIG_ATT = 10 };
enum { RDY_KV = 0, RDY_CTX = 2, RDY_WAR = 4, RDY_G = 5, RDY_U = 8, RDY_Z = 9 };
enum { PH_PRE = 1, PH_KV = 2, PH_ATT = 4, PH_CONV = 8, PH_OUT = 16, PH_ALL = 31 };

constexpr uint32_t T_CTX = 0, T_KV = 16 * 32 * 32768, T_BYTES = T_KV + 32 * 16 * 65536;
__device__ __align__(1024) uint8_t g_T[T_BYTES];
__device__ __align__(1024) uint8_t g_u[1024 * UCH];
__device__ __align__(1024) __nv_bfloat16 g_z[1024 * 2048];
__device__ __align__(1024) float g_gate[2048];
__device__ __align__(1024) float g_kn2[32 * 128];
__device__ __align__(1024) unsigned g_cnt[C_NUM * CSTRIDE];

struct __align__(64) Maps { CUtensorMap c, wk, wv, x, wq, wo, h, z, out, ctx, k, v; };
struct Params {
  const __nv_bfloat16 *x, *shift, *D, *gw;
  __nv_bfloat16* out;
};

__device__ __forceinline__ void wg_fence() { asm volatile("wgmma.fence.sync.aligned;" ::: "memory"); }
__device__ __forceinline__ void wg_commit() { asm volatile("wgmma.commit_group.sync.aligned;" ::: "memory"); }
template<int N> __device__ __forceinline__ void wg_wait() { asm volatile("wgmma.wait_group.sync.aligned %0;" :: "n"(N) : "memory"); }
__device__ __forceinline__ uint64_t odesc(uint32_t addr, uint32_t lbo, uint32_t sbo, uint32_t swz) {
  uint64_t d = (uint64_t)(addr >> 4) + (((uint64_t)(lbo >> 4) << 16) | ((uint64_t)(sbo >> 4) << 32) | ((uint64_t)swz << 62));
  asm volatile("" : "+l"(d));
  return d;
}
__device__ __forceinline__ void mbar_init(uint32_t bar, int cnt) { asm volatile("mbarrier.init.shared::cta.b64 [%0], %1;" :: "r"(bar), "r"(cnt)); }
__device__ __forceinline__ void mbar_expect(uint32_t bar, uint32_t bytes) { asm volatile("mbarrier.arrive.expect_tx.shared::cta.b64 _, [%0], %1;" :: "r"(bar), "r"(bytes) : "memory"); }
__device__ __forceinline__ void mbar_arrive(uint32_t bar) { asm volatile("mbarrier.arrive.shared::cta.b64 _, [%0];" :: "r"(bar) : "memory"); }
__device__ __forceinline__ void mbar_arrive_n(uint32_t bar, int n) { asm volatile("mbarrier.arrive.shared::cta.b64 _, [%0], %1;" :: "r"(bar), "r"(n) : "memory"); }
__device__ __forceinline__ void mbar_wait(uint32_t bar, uint32_t parity) {
  asm volatile("{\n.reg .pred p;\nLW:\nmbarrier.try_wait.parity.shared::cta.b64 p, [%0], %1;\n@!p bra LW;\n}\n" :: "r"(bar), "r"(parity) : "memory");
}
__device__ __forceinline__ void mbar_wait_slow(uint32_t bar, uint32_t parity) {
  asm volatile("{\n.reg .pred p;\n.reg .u32 n;\nmov.u32 n, 0;\n"
    "LW:\nmbarrier.test_wait.parity.shared::cta.b64 p, [%0], %1;\n@p bra LD;\n"
    "nanosleep.u32 128;\nadd.u32 n, n, 1;\nsetp.lt.u32 p, n, 4194304;\n@p bra LW;\ntrap;\nLD:\n}\n" :: "r"(bar), "r"(parity) : "memory");
}
__device__ __forceinline__ void mbar_wait_all(uint32_t bar, uint32_t parity) {
  asm volatile("{\n.reg .pred p, q;\nLW:\nmbarrier.try_wait.parity.shared::cta.b64 p, [%0], %1;\nvote.sync.all.pred q, p, 0xffffffff;\n@!q bra.uni LW;\n}\n" :: "r"(bar), "r"(parity) : "memory");
}
__device__ __forceinline__ void cnt_wait(const unsigned* p, unsigned target) {
  asm volatile("{\n.reg .pred p;\n.reg .u32 n, v;\nmov.u32 n, 0;\n"
    "LW:\nld.relaxed.gpu.global.u32 v, [%0];\nsetp.ge.u32 p, v, %1;\n@p bra LD;\n"
    "nanosleep.u32 64;\nadd.u32 n, n, 1;\nsetp.lt.u32 p, n, 4194304;\n@p bra LW;\ntrap;\nLD:\nfence.acquire.gpu;\nfence.proxy.async.global;\n}\n" :: "l"(p), "r"(target) : "memory");
}
__device__ __forceinline__ void cnt_signal(unsigned* p, int lane) {
  __syncwarp();
  if (lane == 0) asm volatile("red.release.gpu.global.add.u32 [%0], 1;" :: "l"(p) : "memory");
}
__device__ __forceinline__ void cnt_publish(unsigned* p, unsigned n, bool fence) {
  if (fence) asm volatile("fence.release.gpu;" ::: "memory");
  asm volatile("red.relaxed.gpu.global.add.u32 [%0], %1;" :: "l"(p), "r"(n) : "memory");
}
__device__ __forceinline__ uint64_t pol_first() { uint64_t p; asm("createpolicy.fractional.L2::evict_first.b64 %0, 1.0;" : "=l"(p)); return p; }
__device__ __forceinline__ void bulk_g2s(uint32_t dst, const void* src, uint32_t bytes, uint32_t bar, bool stream = false) {
  if (stream) asm volatile("cp.async.bulk.shared::cluster.global.mbarrier::complete_tx::bytes.L2::cache_hint [%0], [%1], %2, [%3], %4;" :: "r"(dst), "l"(src), "r"(bytes), "r"(bar), "l"(pol_first()) : "memory");
  else asm volatile("cp.async.bulk.shared::cluster.global.mbarrier::complete_tx::bytes [%0], [%1], %2, [%3];" :: "r"(dst), "l"(src), "r"(bytes), "r"(bar) : "memory");
}
__device__ __forceinline__ void tma2d(uint32_t dst, const CUtensorMap* m, int x, int y, uint32_t bar, bool stream = false) {
  if (stream) asm volatile("cp.async.bulk.tensor.2d.shared::cluster.global.mbarrier::complete_tx::bytes.L2::cache_hint [%0], [%1, {%3, %4}], [%2], %5;" :: "r"(dst), "l"(m), "r"(bar), "r"(x), "r"(y), "l"(pol_first()) : "memory");
  else asm volatile("cp.async.bulk.tensor.2d.shared::cluster.global.mbarrier::complete_tx::bytes [%0], [%1, {%3, %4}], [%2];" :: "r"(dst), "l"(m), "r"(bar), "r"(x), "r"(y) : "memory");
}
__device__ __forceinline__ void tma3d(uint32_t dst, const CUtensorMap* m, int x, int y, int z, uint32_t bar, bool stream = false) {
  if (stream) asm volatile("cp.async.bulk.tensor.3d.shared::cluster.global.mbarrier::complete_tx::bytes.L2::cache_hint [%0], [%1, {%3, %4, %5}], [%2], %6;" :: "r"(dst), "l"(m), "r"(bar), "r"(x), "r"(y), "r"(z), "l"(pol_first()) : "memory");
  else asm volatile("cp.async.bulk.tensor.3d.shared::cluster.global.mbarrier::complete_tx::bytes [%0], [%1, {%3, %4, %5}], [%2];" :: "r"(dst), "l"(m), "r"(bar), "r"(x), "r"(y), "r"(z) : "memory");
}
__device__ __forceinline__ void tma4d(uint32_t dst, const CUtensorMap* m, int x, int y, int z, int w, uint32_t bar, bool stream = false) {
  if (stream) asm volatile("cp.async.bulk.tensor.4d.shared::cluster.global.mbarrier::complete_tx::bytes.L2::cache_hint [%0], [%1, {%3, %4, %5, %6}], [%2], %7;" :: "r"(dst), "l"(m), "r"(bar), "r"(x), "r"(y), "r"(z), "r"(w), "l"(pol_first()) : "memory");
  else asm volatile("cp.async.bulk.tensor.4d.shared::cluster.global.mbarrier::complete_tx::bytes [%0], [%1, {%3, %4, %5, %6}], [%2];" :: "r"(dst), "l"(m), "r"(bar), "r"(x), "r"(y), "r"(z), "r"(w) : "memory");
}
__device__ __forceinline__ void bulk_g2s_mc(uint32_t dst, const void* src, uint32_t bytes, uint32_t bar, bool stream = false) {
  if (stream) asm volatile("cp.async.bulk.shared::cluster.global.mbarrier::complete_tx::bytes.multicast::cluster.L2::cache_hint [%0], [%1], %2, [%3], %4, %5;" :: "r"(dst), "l"(src), "r"(bytes), "r"(bar), "h"((uint16_t)3), "l"(pol_first()) : "memory");
  else asm volatile("cp.async.bulk.shared::cluster.global.mbarrier::complete_tx::bytes.multicast::cluster [%0], [%1], %2, [%3], %4;" :: "r"(dst), "l"(src), "r"(bytes), "r"(bar), "h"((uint16_t)3) : "memory");
}
__device__ __forceinline__ void tma2d_mc(uint32_t dst, const CUtensorMap* m, int x, int y, uint32_t bar, bool stream = false) {
  if (stream) asm volatile("cp.async.bulk.tensor.2d.shared::cluster.global.mbarrier::complete_tx::bytes.multicast::cluster.L2::cache_hint [%0], [%1, {%3, %4}], [%2], %5, %6;" :: "r"(dst), "l"(m), "r"(bar), "r"(x), "r"(y), "h"((uint16_t)3), "l"(pol_first()) : "memory");
  else asm volatile("cp.async.bulk.tensor.2d.shared::cluster.global.mbarrier::complete_tx::bytes.multicast::cluster [%0], [%1, {%3, %4}], [%2], %5;" :: "r"(dst), "l"(m), "r"(bar), "r"(x), "r"(y), "h"((uint16_t)3) : "memory");
}
__device__ __forceinline__ void tma3d_mc(uint32_t dst, const CUtensorMap* m, int x, int y, int z, uint32_t bar, bool stream = false) {
  if (stream) asm volatile("cp.async.bulk.tensor.3d.shared::cluster.global.mbarrier::complete_tx::bytes.multicast::cluster.L2::cache_hint [%0], [%1, {%3, %4, %5}], [%2], %6, %7;" :: "r"(dst), "l"(m), "r"(bar), "r"(x), "r"(y), "r"(z), "h"((uint16_t)3), "l"(pol_first()) : "memory");
  else asm volatile("cp.async.bulk.tensor.3d.shared::cluster.global.mbarrier::complete_tx::bytes.multicast::cluster [%0], [%1, {%3, %4, %5}], [%2], %6;" :: "r"(dst), "l"(m), "r"(bar), "r"(x), "r"(y), "r"(z), "h"((uint16_t)3) : "memory");
}
__device__ __forceinline__ void pf3d(const CUtensorMap* m, int x, int y, int z) {
  asm volatile("cp.async.bulk.prefetch.tensor.3d.L2.global [%0, {%1, %2, %3}];" :: "l"(m), "r"(x), "r"(y), "r"(z) : "memory");
}
__device__ __forceinline__ void pf_bulk(const void* p, uint32_t bytes) { asm volatile("cp.async.bulk.prefetch.L2.global [%0], %1;" :: "l"(p), "r"(bytes) : "memory"); }
__device__ __forceinline__ void tma2d_store(const CUtensorMap* m, uint32_t src, int x, int y) {
  if (POL(12)) asm volatile("cp.async.bulk.tensor.2d.global.shared::cta.bulk_group.L2::cache_hint [%0, {%2, %3}], [%1], %4;" :: "l"(m), "r"(src), "r"(x), "r"(y), "l"(pol_first()) : "memory");
  else asm volatile("cp.async.bulk.tensor.2d.global.shared::cta.bulk_group [%0, {%2, %3}], [%1];" :: "l"(m), "r"(src), "r"(x), "r"(y) : "memory");
}
__device__ __forceinline__ bool elect() {
  uint32_t r; asm volatile("{\n.reg .pred p;\nelect.sync _|p, 0xffffffff;\nselp.u32 %0, 1, 0, p;\n}\n" : "=r"(r)); return r != 0;
}
__device__ __forceinline__ void cluster_arrive() { asm volatile("barrier.cluster.arrive;" ::: "memory"); }
__device__ __forceinline__ void cluster_wait() { asm volatile("barrier.cluster.wait;" ::: "memory"); }
__device__ __forceinline__ void bar_sync(int id, int n) { asm volatile("bar.sync %0, %1;" :: "r"(id), "r"(n) : "memory"); }
__device__ __forceinline__ void bar_arrive(int id, int n) { asm volatile("bar.arrive %0, %1;" :: "r"(id), "r"(n) : "memory"); }
__device__ __forceinline__ int bar_and(int id, int n, int pred) {
  int r; asm volatile("{\n.reg .pred p, q;\nsetp.ne.b32 p, %3, 0;\nbar.red.and.pred q, %1, %2, p;\nselp.b32 %0, 1, 0, q;\n}\n" : "=r"(r) : "r"(id), "r"(n), "r"(pred) : "memory");
  return r;
}
__device__ __forceinline__ void fence_async_smem() { asm volatile("fence.proxy.async.shared::cta;" ::: "memory"); }
__device__ __forceinline__ float ex2(float x) { float y; asm("ex2.approx.ftz.f32 %0, %1;" : "=f"(y) : "f"(x)); return y; }
__device__ __forceinline__ uint32_t pack_bf16(float lo, float hi) { uint32_t r; asm("cvt.rn.bf16x2.f32 %0, %1, %2;" : "=r"(r) : "f"(hi), "f"(lo)); return r; }
__device__ __forceinline__ uint32_t hmul2(uint32_t a, uint32_t b) { uint32_t r; asm("mul.rn.bf16x2 %0, %1, %2;" : "=r"(r) : "r"(a), "r"(b)); return r; }
__device__ __forceinline__ uint32_t hadd2(uint32_t a, uint32_t b) { uint32_t r; asm("add.rn.bf16x2 %0, %1, %2;" : "=r"(r) : "r"(a), "r"(b)); return r; }
__device__ __forceinline__ uint32_t hfma2(uint32_t a, uint32_t b, uint32_t c) { uint32_t r; asm("fma.rn.bf16x2 %0, %1, %2, %3;" : "=r"(r) : "r"(a), "r"(b), "r"(c)); return r; }
__device__ __forceinline__ float bf_lo(uint32_t a) { return __uint_as_float(a << 16); }
__device__ __forceinline__ float bf_hi(uint32_t a) { return __uint_as_float(a & 0xffff0000u); }
__device__ __forceinline__ uint32_t lds32(uint32_t a) { uint32_t v; asm volatile("ld.shared.u32 %0, [%1];" : "=r"(v) : "r"(a) : "memory"); return v; }
__device__ __forceinline__ float2 lds64f(uint32_t a) { float2 v; asm volatile("ld.shared.v2.f32 {%0,%1}, [%2];" : "=f"(v.x), "=f"(v.y) : "r"(a) : "memory"); return v; }
__device__ __forceinline__ uint4 lds128(uint32_t a) { uint4 v; asm volatile("ld.shared.v4.u32 {%0,%1,%2,%3}, [%4];" : "=r"(v.x), "=r"(v.y), "=r"(v.z), "=r"(v.w) : "r"(a) : "memory"); return v; }
__device__ __forceinline__ void sts64f(uint32_t a, float x, float y) { asm volatile("st.shared.v2.f32 [%0], {%1,%2};" :: "r"(a), "f"(x), "f"(y) : "memory"); }
__device__ __forceinline__ void sts128(uint32_t a, uint4 v) { asm volatile("st.shared.v4.u32 [%0], {%1,%2,%3,%4};" :: "r"(a), "r"(v.x), "r"(v.y), "r"(v.z), "r"(v.w) : "memory"); }
template<int OFF> __device__ __forceinline__ void sts128o(uint32_t a, uint4 v) { asm volatile("st.shared.v4.u32 [%0+%5], {%1,%2,%3,%4};" :: "r"(a), "r"(v.x), "r"(v.y), "r"(v.z), "r"(v.w), "n"(OFF) : "memory"); }
__device__ __forceinline__ void ldsm4(uint32_t a, uint32_t& r0, uint32_t& r1, uint32_t& r2, uint32_t& r3) {
  asm volatile("ldmatrix.sync.aligned.m8n8.x4.shared.b16 {%0,%1,%2,%3}, [%4];" : "=r"(r0), "=r"(r1), "=r"(r2), "=r"(r3) : "r"(a) : "memory");
}
__device__ __forceinline__ void ldsm4t(uint32_t a, uint32_t& r0, uint32_t& r1, uint32_t& r2, uint32_t& r3) {
  asm volatile("ldmatrix.sync.aligned.m8n8.x4.trans.shared.b16 {%0,%1,%2,%3}, [%4];" : "=r"(r0), "=r"(r1), "=r"(r2), "=r"(r3) : "r"(a) : "memory");
}
__device__ __forceinline__ void stsm4(uint32_t a, uint32_t r0, uint32_t r1, uint32_t r2, uint32_t r3) {
  asm volatile("stmatrix.sync.aligned.m8n8.x4.shared.b16 [%0], {%1,%2,%3,%4};" :: "r"(a), "r"(r0), "r"(r1), "r"(r2), "r"(r3) : "memory");
}
template<int N> __device__ __forceinline__ void fence_regs(float (&d)[N]) {
#pragma unroll
  for (int i = 0; i < N; i++) asm volatile("" : "+f"(d[i]) :: "memory");
}
template<int N> __device__ __forceinline__ void fence_regs(uint32_t (&d)[N]) {
#pragma unroll
  for (int i = 0; i < N; i++) asm volatile("" : "+r"(d[i]) :: "memory");
}
__device__ __forceinline__ void sched_fence(float x, uint32_t dummy) {
  asm volatile("{\n.reg .pred p;\nsetp.eq.u32 p, %0, 0x7fc12345;\n@p st.shared.u32 [%1], %0;\n}\n" :: "r"(__float_as_uint(x)), "r"(dummy) : "memory");
}
#define ROT 0
#define CTAID blockIdx.x
#define TS(role, i)
#define TSA(i)
#define TR(obj, role, tag)

#define SHADOW if (gridDim.y == 1)

struct Prod {
  uint32_t base, mask; int lane, nt;
  __device__ __forceinline__ uint32_t full(int u) const { return base + SM_BAR + 8 * u; }
  __device__ __forceinline__ uint32_t addr(int u) const { return base + u * UNIT; }
  __device__ __forceinline__ void acquire(int u, int n) {
    const int v = u + min(lane, n - 1);
    mbar_wait_all(base + SM_BAR + 128 + 8 * v, mask >> v);
    mask ^= ((1u << n) - 1) << u;
    TR(*this, 2, 16 + u);
  }
  __device__ __forceinline__ void acquire_slow(int u, int n) {
    for (int i = 0; i < n; i++) mbar_wait_slow(base + SM_BAR + 128 + 8 * (u + i), mask >> (u + i));
    mask ^= ((1u << n) - 1) << u;
  }
};
struct Cons {
  uint32_t base, rel, mask; int lane, warp, wg, nt;
  __device__ __forceinline__ uint32_t addr(int u) const { return base + u * UNIT; }
  __device__ __forceinline__ static uint32_t daddr(int u) { return SMEM_BASE + u * UNIT; }
  __device__ __forceinline__ void wait(int u) { TR(*this, wg, 1); mbar_wait(base + SM_BAR + 8 * u, mask >> u); mask ^= 1u << u; TR(*this, wg, 2); }
  __device__ __forceinline__ void skip(int u) { mask ^= 1u << u; }
  __device__ __forceinline__ void release(int u, int n) {
    TR(*this, wg, 5);
    asm volatile("{\n.reg .pred p;\nsetp.lt.s32 p, %1, %2;\n@p mbarrier.arrive.shared::cluster.b64 _, [%0];\n}\n" :: "r"(rel + 8 * u), "r"(lane & 15), "r"(n) : "memory");
  }
  __device__ __forceinline__ void release2(int u) {
    asm volatile("{\n.reg .pred p;\nsetp.eq.s32 p, %1, 0;\n@p mbarrier.arrive.shared::cluster.b64 _, [%0], 2;\n}\n" :: "r"(rel + 8 * u), "r"(lane & 15) : "memory");
  }
  __device__ __forceinline__ void signal(int i) {
    __syncwarp();
    asm volatile("{\n.reg .pred p;\nsetp.eq.s32 p, %1, 0;\n@p mbarrier.arrive.shared::cta.b64 _, [%0];\n}\n" :: "r"(base + SM_SIG + 8 * i), "r"(lane) : "memory");
  }
  __device__ __forceinline__ void turn() { bar_sync(1 + wg, 256); TR(*this, wg, 3); }
  __device__ __forceinline__ void pass() { bar_arrive(2 - wg, 256); TR(*this, wg, 4); }
};
__device__ __forceinline__ int gemm_unit(int ks) { return 3 * (ks & 3); }
__device__ __forceinline__ int att_slot(int i) { return 4 + 2 * i; }
template<int MASK> __device__ __forceinline__ int kv_slot(int h) { return MASK == PH_ALL ? h & 15 : h; }
__device__ __forceinline__ int out_mb(int cta) { return cta >> 3; }
__device__ __forceinline__ int out_nb(int cta) { return cta & 7; }
template<int MASK> constexpr int CV_REG = MASK == PH_ALL ? CONV_REG : 6;
template<int MASK> constexpr int CV_EXTRA = (1024 - NREG * CV_REG<MASK>) / (NCTA - NREG);
template<int MASK> __device__ __forceinline__ int conv_channel(int cta, int i) {
  return cta < NREG ? CV_EXTRA<MASK> * (NCTA - NREG) + cta * CV_REG<MASK> + i : (i >> 1) * 8 + (cta - NREG) * 2 + (i & 1);
}

template<int OFF, int N> __device__ __forceinline__ void pack_chunk(const float (&a)[N], float sc0, float sc1, uint4& v0, uint4& v1) {
  v0.x = pack_bf16(a[OFF + 0] * sc0, a[OFF + 1] * sc0); v0.y = pack_bf16(a[OFF + 4] * sc0, a[OFF + 5] * sc0);
  v0.z = pack_bf16(a[OFF + 8] * sc0, a[OFF + 9] * sc0); v0.w = pack_bf16(a[OFF + 12] * sc0, a[OFF + 13] * sc0);
  v1.x = pack_bf16(a[OFF + 2] * sc1, a[OFF + 3] * sc1); v1.y = pack_bf16(a[OFF + 6] * sc1, a[OFF + 7] * sc1);
  v1.z = pack_bf16(a[OFF + 10] * sc1, a[OFF + 11] * sc1); v1.w = pack_bf16(a[OFF + 14] * sc1, a[OFF + 15] * sc1);
}
template<int OFF, int N> __device__ __forceinline__ void pack_chunk(const float (&a)[N], uint4& v0, uint4& v1) {
  v0.x = pack_bf16(a[OFF + 0], a[OFF + 1]); v0.y = pack_bf16(a[OFF + 4], a[OFF + 5]);
  v0.z = pack_bf16(a[OFF + 8], a[OFF + 9]); v0.w = pack_bf16(a[OFF + 12], a[OFF + 13]);
  v1.x = pack_bf16(a[OFF + 2], a[OFF + 3]); v1.y = pack_bf16(a[OFF + 6], a[OFF + 7]);
  v1.z = pack_bf16(a[OFF + 10], a[OFF + 11]); v1.w = pack_bf16(a[OFF + 14], a[OFF + 15]);
}
__device__ __forceinline__ void sq_acc(const uint4& v, uint32_t& a) { a = hfma2(v.x, v.x, a); a = hfma2(v.y, v.y, a); a = hfma2(v.z, v.z, a); a = hfma2(v.w, v.w, a); }
__device__ __forceinline__ float norm2_max(uint32_t a0, uint32_t a1) {
  float n0 = bf_lo(a0) + bf_hi(a0), n1 = bf_lo(a1) + bf_hi(a1);
  n0 += __shfl_xor_sync(~0u, n0, 1); n1 += __shfl_xor_sync(~0u, n1, 1);
  n0 += __shfl_xor_sync(~0u, n0, 2); n1 += __shfl_xor_sync(~0u, n1, 2);
  return __uint_as_float(__reduce_max_sync(~0u, max(__float_as_uint(n0) & 0x7fffffffu, __float_as_uint(n1) & 0x7fffffffu)));
}

struct Pend { uint4 lo[8], hi[8]; uint32_t dst; float kn; };
__device__ __forceinline__ void pin(uint4 (&v)[8]) {
#pragma unroll
  for (int i = 0; i < 8; i++) asm volatile("" : "+r"(v[i].x), "+r"(v[i].y), "+r"(v[i].z), "+r"(v[i].w) :: "memory");
}
__device__ __forceinline__ uint32_t atom_off(int lane) { return (lane >> 2) * 64 + (((lane ^ (lane >> 3)) & 3) << 4); }
__device__ __forceinline__ void stg128(void* p, const uint4& v, bool stream) {
  if (stream) asm volatile("st.global.L2::cache_hint.v4.u32 [%0], {%1,%2,%3,%4}, %5;" :: "l"(p), "r"(v.x), "r"(v.y), "r"(v.z), "r"(v.w), "l"(pol_first()) : "memory");
  else *(uint4*)p = v;
}
template<int J0, int J1, bool STREAM = false> __device__ __forceinline__ void tile_store(const uint4 (&v)[8], uint32_t dst, int lane) {
  uint8_t* d = g_T + (dst + atom_off(lane));
#pragma unroll
  for (int j = J0; j < J1; j++) { stg128(d + j * 512, v[2 * j], STREAM); stg128(d + j * 512 + 2048, v[2 * j + 1], STREAM); }
}
template<int I0, int I1> __device__ __forceinline__ void tile_store_if(bool on, const uint4 (&v)[8], uint32_t dst, int lane) {
  if constexpr (I0 < I1) {
    asm volatile("{\n.reg .pred p;\nsetp.ne.b32 p, %5, 0;\n@p st.global.v4.u32 [%0+%6], {%1,%2,%3,%4};\n}\n"
      :: "l"(g_T + (dst + atom_off(lane))), "r"(v[I0].x), "r"(v[I0].y), "r"(v[I0].z), "r"(v[I0].w), "r"((int)on), "n"((I0 >> 1) * 512 + (I0 & 1) * 2048) : "memory");
    tile_store_if<I0 + 1, I1>(on, v, dst, lane);
  }
}
__device__ __forceinline__ float tile_norm2(const uint4 (&v)[8]) {
  uint32_t n0 = 0, n1 = 0, n2 = 0, n3 = 0;
#pragma unroll
  for (int j = 0; j < 2; j++) { sq_acc(v[2 * j], n0); sq_acc(v[2 * j + 1], n1); sq_acc(v[2 * j + 4], n2); sq_acc(v[2 * j + 5], n3); }
  return norm2_max(hadd2(n0, n2), hadd2(n1, n3));
}
template<uint64_t SCHED, bool FIRST> __device__ __forceinline__ void out_piece(Cons& c, Pend& w, int ks, bool both) {
  uint8_t* d = g_T + (w.dst + atom_off(c.lane));
#pragma unroll
  for (int i = 0; i < 16; i++) {
    const int at = (SCHED >> (4 * i)) & 15;
    if (FIRST ? at == 0 : (at > 0 && ks == at && (i < 8 || both))) *(uint4*)(d + (i >> 3) * 32768 + ((i >> 1) & 3) * 512 + (i & 1) * 2048) = i < 8 ? w.lo[i & 7] : w.hi[i & 7];
  }
  if (FIRST || !both) return;
  if (ks == NK_AT) w.kn = tile_norm2(w.lo);
  if (ks == NV_AT) {
    const float vn = tile_norm2(w.hi);
    if (c.lane == 0) g_kn2[((w.dst - T_KV) >> 16) * 8 + c.wg * 4 + c.warp] = (vn <= 1.0e30f && vn >= 1.0e-30f) ? w.kn : __uint_as_float(0x7f800000u);
  }
}
template<bool FIRST> __device__ __forceinline__ void kv_issue(Cons& c, float (&acc)[128], int u) {
  const uint64_t da = odesc(c.daddr(u) + c.wg * 8192, 16, 1024, 1), db = odesc(c.daddr(u + 1), 8192, 1024, 1);
  c.turn();
  wg_fence();
#pragma unroll
  for (int kk = 0; kk < 4; kk++) wgmma_ss_n256<1>(acc, da + kk * 2, db + kk * 128, !(FIRST && kk == 0));
  wg_commit();
  c.pass();
}
template<bool NEXT> __device__ __forceinline__ void cons_kv(Cons& c, int h, int hs, int g, Pend& w, bool pend_o) {
#pragma unroll 1
  for (int tile = 0; tile < 2; tile++) {
    float acc[128];
    if (tile == 0) c.wait(0);
    if (tile == 0 && h < 16) TS(c.wg, 16);
    kv_issue<true>(c, acc, 0);
    c.release(9, tile == 1 ? 3 : 0);
    if (tile == 1 && pend_o) mbar_wait(c.base + SM_RDY + 8 * RDY_WAR, 0);
    if (tile == 1 || pend_o) out_piece<SCH_KV, true>(c, w, 0, false);
#pragma unroll 1
    for (int ks = 1; ks < 8; ks++) {
      const int u = gemm_unit(ks);
      c.wait(u);
      wg_wait<0>();
      c.release(gemm_unit(ks - 1), 3);
      kv_issue<false>(c, acc, u);
      if (tile == 1 || pend_o) { out_piece<SCH_KV, false>(c, w, ks, tile); if (ks == ((SCH_KV >> 28) & 15) && tile == 0) c.signal(SIG_CTX); }
    }
    if (NEXT || tile == 0) c.wait(0);
    wg_wait<0>(); fence_regs(acc);
    if (!NEXT) c.release(9, tile == 1 ? 3 : 0);
    pack_chunk<0>(acc, w.lo[0], w.lo[1]);  pack_chunk<16>(acc, w.lo[2], w.lo[3]); pack_chunk<32>(acc, w.lo[4], w.lo[5]); pack_chunk<48>(acc, w.lo[6], w.lo[7]);
    pack_chunk<64>(acc, w.hi[0], w.hi[1]); pack_chunk<80>(acc, w.hi[2], w.hi[3]); pack_chunk<96>(acc, w.hi[4], w.hi[5]); pack_chunk<112>(acc, w.hi[6], w.hi[7]);
    pin(w.lo); pin(w.hi);
    w.dst = T_KV + (hs * 16 + 2 * g + tile) * 65536 + (c.wg * 4 + c.warp) * 4096;
  }
}
template<bool FIRST> __device__ __forceinline__ void q_issue(Cons& c, float (&a)[64], float (&b)[64], int u) {
  const uint64_t da = odesc(c.daddr(u) + c.wg * 8192, 16, 1024, 1), db = odesc(c.daddr(u + 2), 8192, 1024, 1);
  const uint64_t da2 = odesc(c.daddr(u + 1) + (1 - c.wg) * 8192, 16, 1024, 1);
  c.turn();
  wg_fence();
#pragma unroll
  for (int kk = 0; kk < 4; kk++) wgmma_ss_n128<1>(a, da + kk * 2, db + kk * 128, !(FIRST && kk == 0));
#pragma unroll
  for (int kk = 0; kk < 4; kk++) wgmma_ss_n128<1>(b, da2 + kk * 2, db + kk * 128, !(FIRST && kk == 0));
  wg_commit();
  c.pass();
}
template<int U14, int U15> __device__ __forceinline__ void q_tail(Cons& c, float (&d)[64], int rowhalf) {
  const uint64_t da = odesc(c.daddr(U14) + rowhalf * 8192, 16, 1024, 1), db = odesc(c.daddr(7), 8192, 1024, 1);
  c.turn();
  wg_fence();
#pragma unroll
  for (int kk = 0; kk < 8; kk++) wgmma_ss_n128<1>(d, da + (kk >> 2) * (U15 - U14) * 1024 + (kk & 3) * 2, db + (kk >> 2) * 4096 + (kk & 3) * 128, 1);
  wg_commit();
  c.pass();
}
template<int OFF> __device__ __forceinline__ void q_store(const float (&d)[64], uint4 (&v)[8], uint32_t q0) {
  pack_chunk<0>(d, QSCALE, QSCALE, v[0], v[1]);  sts128o<OFF>(q0, v[0]);        sts128o<OFF + 2048>(q0, v[1]);
  pack_chunk<16>(d, QSCALE, QSCALE, v[2], v[3]); sts128o<OFF + 512>(q0, v[2]);  sts128o<OFF + 2560>(q0, v[3]);
  pack_chunk<32>(d, QSCALE, QSCALE, v[4], v[5]); sts128o<OFF + 1024>(q0, v[4]); sts128o<OFF + 3072>(q0, v[5]);
  pack_chunk<48>(d, QSCALE, QSCALE, v[6], v[7]); sts128o<OFF + 1536>(q0, v[6]); sts128o<OFF + 3584>(q0, v[7]);
}
template<bool PEND_KV> __device__ __forceinline__ void cons_q(Cons& c, int h, Pend& w, float (&b)[64]) {
  float a[64];
  if (!PEND_KV) c.wait(0);
  q_issue<true>(c, a, b, 0);
  if (PEND_KV) { c.release(9, 3); out_piece<SCH_Q, true>(c, w, 0, true); }
#pragma unroll 1
  for (int ks = 1; ks < 14; ks++) {
    const int u = gemm_unit(ks);
    c.wait(u);
    wg_wait<0>();
    c.release(gemm_unit(ks - 1), 3);
    q_issue<false>(c, a, b, u);
    if (PEND_KV && ks <= (int)(SCH_Q >> 60)) { out_piece<SCH_Q, false>(c, w, ks, true); if (ks == (int)(SCH_Q >> 60)) c.signal(SIG_KV + (h >> 4)); }
  }
  c.wait(6); c.wait(9);
  wg_wait<0>();
  c.release(3, 3);
  q_tail<8, 9>(c, b, 1 - c.wg);
  wg_wait<0>(); fence_regs(b);
  c.release(8, 2);
  q_tail<6, 10>(c, a, c.wg);
  c.wait(0);
  const uint32_t q0 = c.addr(0) + (c.wg * 4 + c.warp) * 4096 + atom_off(c.lane);
  SHADOW { uint4 v[8]; q_store<32768>(b, v, q0); w.kn = tile_norm2(v); }
  c.wait(4);
  wg_wait<0>(); fence_regs(a);
  c.release(6, 2); c.release(10, 2);
  q_store<0>(a, w.lo, q0);
  fence_async_smem();
}

__device__ __forceinline__ void issue_qk(float (&s)[64], uint64_t da, uint64_t db) {
#pragma unroll
  for (int kk = 0; kk < 8; kk++) wgmma_ss_n128<0>(s, da + (kk >> 1) * 32 + (kk & 1) * 2, db + (kk >> 1) * 32 + (kk & 1) * 2, kk > 0);
  wg_commit();
}
template<int A, int B> __device__ __forceinline__ void exp_rng(float (&s)[64]) {
#pragma unroll
  for (int i = 4 * A; i < 4 * B; i++) s[i] = ex2(s[i]);
}
template<int A, int B> __device__ __forceinline__ void sum_rng(const float (&s)[64], float (&l)[4]) {
#pragma unroll
  for (int i = A; i < B; i++) { l[0] += s[4 * i]; l[1] += s[4 * i + 1]; l[2] += s[4 * i + 2]; l[3] += s[4 * i + 3]; }
}
template<int A, int B> __device__ __forceinline__ void cvt_p(const float (&s)[64], uint32_t (&p)[32]) {
#pragma unroll
  for (int i = 2 * A; i < 2 * B; i++) p[i] = pack_bf16(s[2 * i], s[2 * i + 1]);
}
template<int K0> __device__ __forceinline__ void mask_half(float (&s)[64], int warp, int lane) {
  const int l0 = warp + (2 * (lane & 3) <= (lane >> 2)), l1 = warp + (2 * (lane & 3) < (lane >> 2));
#pragma unroll
  for (int k = 0; k < 4; k++) {
    float* t = s + 8 * (K0 + k);
    if (k >= l0) { t[0] = -INFINITY; t[6] = -INFINITY; }
    if (k >= l1) { t[1] = -INFINITY; t[7] = -INFINITY; }
    if (k > warp) { t[2] = -INFINITY; t[3] = -INFINITY; }
    if (k >= warp) { t[4] = -INFINITY; t[5] = -INFINITY; }
  }
}
__device__ __forceinline__ void row_inv(float& l0, float& l1) {
  l0 += __shfl_xor_sync(~0u, l0, 1); l1 += __shfl_xor_sync(~0u, l1, 1);
  l0 += __shfl_xor_sync(~0u, l0, 2); l1 += __shfl_xor_sync(~0u, l1, 2);
  l0 = __fdividef(1.f, l0); l1 = __fdividef(1.f, l1);
}
__device__ __forceinline__ void pack_o(const float (&o)[64], float i0, float i1, uint4 (&v)[8]) {
  pack_chunk<0>(o, i0, i1, v[0], v[1]); pack_chunk<16>(o, i0, i1, v[2], v[3]);
  pack_chunk<32>(o, i0, i1, v[4], v[5]); pack_chunk<48>(o, i0, i1, v[6], v[7]);
  pin(v);
}
__device__ __forceinline__ void softmax_safe(float (&s)[64], bool upper_only, float& m0, float& m1, float& sc0, float& sc1) {
  float a0 = m0, a1 = m1;
#pragma unroll
  for (int i = 0; i < 8; i++) { a0 = fmaxf(a0, fmaxf(s[4 * i], s[4 * i + 1])); a1 = fmaxf(a1, fmaxf(s[4 * i + 2], s[4 * i + 3])); }
  if (upper_only) { a0 = m0; a1 = m1; }
#pragma unroll
  for (int i = 8; i < 16; i++) { a0 = fmaxf(a0, fmaxf(s[4 * i], s[4 * i + 1])); a1 = fmaxf(a1, fmaxf(s[4 * i + 2], s[4 * i + 3])); }
  a0 = fmaxf(a0, __shfl_xor_sync(~0u, a0, 1)); a1 = fmaxf(a1, __shfl_xor_sync(~0u, a1, 1));
  a0 = fmaxf(a0, __shfl_xor_sync(~0u, a0, 2)); a1 = fmaxf(a1, __shfl_xor_sync(~0u, a1, 2));
  sc0 = ex2(m0 - a0); sc1 = ex2(m1 - a1);
  m0 = a0; m1 = a1;
#pragma unroll
  for (int i = 0; i < 16; i++) { s[4 * i] -= a0; s[4 * i + 1] -= a0; s[4 * i + 2] -= a1; s[4 * i + 3] -= a1; }
}
struct Att {
  float s[64], o[64], l[4], i0, i1; uint32_t p[32];
  uint32_t qaddr;
};
__device__ __forceinline__ uint32_t ctx_off(const Cons& c, int h, int qb, int rowhalf) { return T_CTX + (qb * 32 + h) * 32768 + (rowhalf * 4 + c.warp) * 4096; }
__device__ __forceinline__ int att_first(Cons& c, Att& a, int h, const Pend& w) {
  a.qaddr = c.daddr(0) + c.wg * 16384;
  c.turn();
  wg_fence();
  issue_qk(a.s, odesc(a.qaddr, 16, 2048, 2), odesc(c.daddr(4), 16, 2048, 2));
  c.pass();
  c.signal(SIG_ATT + (h >> 4));
  float qn = w.kn;
  SHADOW qn = tile_norm2(w.lo);
  const float kn = __uint_as_float(lds32(c.base + SM_KMAX + 4 * (h >> 4)));
  const int fast = __shfl_sync(~0u, bar_and(3 + c.wg, 128, (qn * kn <= BOUND2) && (w.kn * kn <= BOUND2)), 0);
#pragma unroll
  for (int i = 0; i < 8; i++) { a.p[4 * i] = w.lo[i].x; a.p[4 * i + 1] = w.lo[i].y; a.p[4 * i + 2] = w.lo[i].z; a.p[4 * i + 3] = w.lo[i].w; }
  a.l[0] = a.l[1] = a.l[2] = a.l[3] = 0.f; a.i0 = a.i1 = 0.f;
  wg_wait<0>(); fence_regs(a.s);
  c.release(4, 2);
  return fast;
}
__device__ __forceinline__ void att_last(Cons& c, Att& a, Pend& w, int h, int g, bool drain) {
  const int uv = att_slot(1);
  if (drain) pack_o(a.o, a.i0, a.i1, w.hi);
  c.wait(uv);
  c.turn();
  fence_regs(a.o); fence_regs(a.p);
  wgmma_pv_sel(a.o, a.p, odesc(c.daddr(uv), 512, 2048, 2), !(drain && c.wg == 1), !drain);
  c.pass();
  a.i0 = a.l[0] + a.l[1]; a.i1 = a.l[2] + a.l[3];
  SHADOW row_inv(a.i0, a.i1);
  sched_fence(a.i0 + a.i1, c.base + SM_DUMMY);
  tile_store_if<0, 4>(drain, w.hi, w.dst, c.lane);
  wg_wait<0>(); fence_regs(a.o); fence_regs(a.p);
  c.release(uv, 2);
  tile_store_if<4, 8>(drain, w.hi, w.dst, c.lane);
  pack_o(a.o, a.i0, a.i1, w.lo);
  w.dst = ctx_off(c, h, g, 1 - c.wg);
}
__device__ __forceinline__ void cons_att(Cons& c, Att& a, int h, int g, Pend& w) {
  const int fast = att_first(c, a, h, w);
  if (DEFER_ST) w.dst = ctx_off(c, h, 15 - g, c.wg);
  float m0 = -INFINITY, m1 = -INFINITY, sc0 = 0.f, sc1 = 0.f;
  int uk = 10, nrel = 0;
#pragma unroll 1
  for (int d = g - 15;;) {
    const bool lo = d == c.wg;
    if ((unsigned)d < 2 || !fast) {
      if ((unsigned)d < 2) mask_half<4>(a.s, c.warp, c.lane);
      if (!fast) {
        if (d == 1) m0 = m1 = -INFINITY;
        softmax_safe(a.s, lo, m0, m1, sc0, sc1);
        a.l[0] *= sc0; a.l[1] *= sc0; a.l[2] *= sc1; a.l[3] *= sc1;
      }
    }
    exp_rng<8, 16>(a.s); sum_rng<8, 16>(a.s, a.l);
    exp_rng<ATT_SPLIT, 8>(a.s);
    sched_fence(((a.l[0] + a.l[1]) + (a.l[2] + a.l[3])) + (ATT_SPLIT < 8 ? a.s[4 * ATT_SPLIT + 3] : 0.f), c.base + SM_DUMMY);
    wg_wait<0>(); fence_regs(a.o); fence_regs(a.p);
    c.release(14 - uk, nrel);
    if (DEFER_ST) tile_store_if<DS_A, DS_B>(d == 2, w.hi, w.dst, c.lane);
    nrel = 2; uk ^= 12;
    if (d == 0) a.qaddr += 32768;
    const uint64_t dq = odesc(a.qaddr, 16, 2048, 2), dk = odesc(c.daddr(uk) - (d + 1 == c.wg ? 16384 : 0), 16, 2048, 2), dv = odesc(c.daddr(14 - uk), 512, 2048, 2);
    if (!lo) { exp_rng<0, ATT_SPLIT>(a.s); sum_rng<0, 8>(a.s, a.l); cvt_p<0, 16>(a.s, a.p); }
    else if (gridDim.y == 1) cvt_p<8, 16>(a.s, a.p);
    if (DEFER_ST) tile_store_if<DS_B, 8>(d == 2, w.hi, w.dst, c.lane);
    if (!fast || d == g + 1) {
      if (!fast && d != 1) {
#pragma unroll
        for (int i = 0; i < 16; i++) { a.o[4 * i] *= sc0; a.o[4 * i + 1] *= sc0; a.o[4 * i + 2] *= sc1; a.o[4 * i + 3] *= sc1; }
      }
      if (d == g + 1) break;
    }
    d++;
    if (c.wg == 0) c.wait(uk); else c.skip(uk);
    c.turn();
    fence_regs(a.o); fence_regs(a.p);
    wg_fence();
    issue_qk(a.s, dq, dk);
    if (d == 2) {
      pack_o(a.o, a.i0, a.i1, w.hi);
    }
    wgmma_pv_sel(a.o, a.p, dv, !lo, d != 2 && d != g - 14);
    c.pass();
    if (DEFER_ST) tile_store_if<0, DS_A>(d == 2, w.hi, w.dst, c.lane);
    if (d == 1) {
      a.i0 = a.l[0] + a.l[1]; a.i1 = a.l[2] + a.l[3]; row_inv(a.i0, a.i1);
      a.l[0] = a.l[1] = a.l[2] = a.l[3] = 0.f;
    }
    wg_wait<1>(); fence_regs(a.s);
    c.release(uk, 2);
    c.release(d == 0 ? 0 : 2, (d == 0 || d == g + 1) ? 2 : 0);
  }
  att_last(c, a, w, h, g, g == 0);
}

constexpr int CV_H = 1024, CV_U = 5120, CV_D = CV_U + 4128, CV_ROW = 1056;
template<int OFF> __device__ __forceinline__ uint32_t lds32o(uint32_t a) { uint32_t v; asm volatile("ld.shared.u32 %0, [%1+%2];" : "=r"(v) : "r"(a), "n"(OFF) : "memory"); return v; }
template<int G, int G1 = 16> __device__ __forceinline__ void conv_lda(uint32_t (&a)[64], uint32_t p) {
  a[4 * G + 0] = lds32o<-256 * G>(p);
  a[4 * G + 1] = lds32o<-256 * G - 128>(p);
  a[4 * G + 2] = lds32o<-256 * G + 16>(p);
  a[4 * G + 3] = lds32o<-256 * G - 112>(p);
  if constexpr (G + 1 < G1) conv_lda<G + 1, G1>(a, p);
}
struct CvAcc { float lo[16], hi[16]; };
__device__ __forceinline__ void fence_regs(CvAcc& d) { fence_regs(d.lo); fence_regs(d.hi); }
template<int R, int H> __device__ __forceinline__ void conv_mma_h(float (&d)[16], const uint32_t (&a)[64], uint64_t db) {
#pragma unroll
  for (int G = 0; G < 4 * R + 2 * H + 2; G++) wgmma_rs_n32<0>(d, a[4 * G], a[4 * G + 1], a[4 * G + 2], a[4 * G + 3], db + 64 * R + 32 * H - 16 * G, G > 0);
}
template<int T, int G0, int G1> __device__ __forceinline__ void conv_part(float (&d)[16], const uint32_t (&a)[64], uint64_t db) {
#pragma unroll
  for (int G = G0; G < G1; G++) wgmma_rs_n32<0>(d, a[4 * G], a[4 * G + 1], a[4 * G + 2], a[4 * G + 3], db + 32 * T - 16 * G, G > 0);
}
template<int R> __device__ __forceinline__ void conv_mma(CvAcc& d, const uint32_t (&a)[64], uint64_t db) { conv_mma_h<R, 0>(d.lo, a, db); conv_mma_h<R, 1>(d.hi, a, db); }
template<int C0> __device__ __forceinline__ void conv_st_h(const float (&d)[16], uint32_t wq, float& c0, float& c1) {
#pragma unroll
  for (int n = 0; n < 4; n++) { sts64f(wq + (C0 + n * 8) * 4, d[4 * n] + c0, d[4 * n + 1] + c1); c0 = d[4 * n + 2]; c1 = d[4 * n + 3]; }
}
template<int R> __device__ __forceinline__ void conv_st(const CvAcc& d, uint32_t wq, float& c0, float& c1) { conv_st_h<64 * R>(d.lo, wq, c0, c1); conv_st_h<64 * R + 32>(d.hi, wq, c0, c1); }
struct ConvTail { float t[64]; uint4 ua, uc; uint32_t D2; };
__device__ __forceinline__ void conv_emit(ConvTail& e, int ch, int tid) {
  fence_regs(e.t);
  float y[16];
#pragma unroll
  for (int i = 0; i < 16; i++) y[i] = (e.t[i] + e.t[16 + i]) + (e.t[32 + i] + e.t[48 + i]);
  uint4 z0, z1;
  z0.x = hadd2(pack_bf16(y[0], y[2]), hmul2(__byte_perm(e.ua.w, 0, 0x1032), e.D2));
  z0.y = hadd2(pack_bf16(y[4], y[6]), hmul2(__byte_perm(e.ua.z, 0, 0x1032), e.D2));
  z0.z = hadd2(pack_bf16(y[8], y[10]), hmul2(__byte_perm(e.ua.y, 0, 0x1032), e.D2));
  z0.w = hadd2(pack_bf16(y[12], y[14]), hmul2(__byte_perm(e.ua.x, 0, 0x1032), e.D2));
  z1.x = hadd2(pack_bf16(y[1], y[3]), hmul2(__byte_perm(e.uc.w, 0, 0x1032), e.D2));
  z1.y = hadd2(pack_bf16(y[5], y[7]), hmul2(__byte_perm(e.uc.z, 0, 0x1032), e.D2));
  z1.z = hadd2(pack_bf16(y[9], y[11]), hmul2(__byte_perm(e.uc.y, 0, 0x1032), e.D2));
  z1.w = hadd2(pack_bf16(y[13], y[15]), hmul2(__byte_perm(e.uc.x, 0, 0x1032), e.D2));
  uint4* zp = (uint4*)(g_z + (uint32_t)(ch * 2048 + tid * 16));
  zp[0] = z0; zp[1] = z1;
}
template<int MASK> __device__ __forceinline__ void cons_conv(Cons& c, int cta, int nch) {
  const int r = c.lane >> 2, q = c.lane & 3, tid = c.warp * 32 + c.lane;
  const uint32_t part = c.addr(4) - 2048 + (1 - c.wg) * (32 * CV_ROW) + 32;
  const uint32_t aoff = CV_U + ((r & 1) ? 0 : UPITCH) + 4 * (((2039 - r) >> 1) + q - 8 * c.warp);
  const uint32_t wq = part + (c.warp * 8 + r) * CV_ROW + q * 8, rq = part + tid * 8;
  uint32_t a[64];
  ConvTail e = {};
  c.wait(c.wg); c.skip(c.wg ^ 1);
  conv_lda<0>(a, c.addr(c.wg) + aoff);
  c.wait(4);
  sts64f(part + (tid >> 2) * CV_ROW - 32 + q * 8, 0.f, 0.f);
#pragma unroll 1
  for (int i = 0; i < nch / 2; i++) {
    const int u = 2 * (i & 1) + c.wg;
    CvAcc d0, d1, d2, d3;
    float c0 = 0.f, c1 = 0.f;
    const uint64_t db = odesc(c.daddr(u) + CV_H - 16, 16, 128, 0);
    c.turn();
    fence_regs(a);
    wg_fence();
    conv_mma<0>(d0, a, db); conv_mma<1>(d1, a, db); wg_commit();
    if (i > 0) {
      conv_emit(e, conv_channel<MASK>(cta, 2 * i - 2 + c.wg), tid);
      if ((i & 15) == 0) c.signal(SIG_Z + (i >> 4) - 1);
    }
    wg_fence();
    conv_mma_h<2, 0>(d2.lo, a, db); wg_commit();
    wg_wait<1>(); fence_regs(d0); fence_regs(d1);
    conv_st_h<0>(d0.lo, wq, c0, c1);
    wg_fence();
    conv_mma_h<2, 1>(d2.hi, a, db); wg_commit();
    conv_st_h<32>(d0.hi, wq, c0, c1);
    conv_mma_h<3, 0>(d3.lo, a, db);
    conv_st_h<64>(d1.lo, wq, c0, c1);
    conv_mma_h<3, 1>(d3.hi, a, db); wg_commit();
    c.pass();
    const int un = i + 1 < nch / 2 ? u ^ 2 : u;
    if (un != u) { c.wait(un); c.skip(un ^ 1); }
    wg_wait<1>(); fence_regs(d2);
    conv_st_h<96>(d1.hi, wq, c0, c1);
    conv_st<2>(d2, wq, c0, c1);
    {
      const int sw = (c.lane >> 2) & 1;
      const uint4 v0 = lds128(c.addr(u) + CV_U + 4064 - 32 * tid + 16 * sw), v1 = lds128(c.addr(u) + CV_U + 4080 - 32 * tid - 16 * sw);
      e.ua = sw ? v0 : v1; e.uc = sw ? v1 : v0;
    }
    e.D2 = lds32(c.addr(u) + CV_D);
    wg_wait<0>(); fence_regs(d3); fence_regs(a);
    conv_st<3>(d3, wq, c0, c1);
    conv_lda<0, 4>(a, c.addr(un) + aoff);
    bar_sync(3 + c.wg, 128);
    sched_fence(__uint_as_float(e.ua.x ^ e.uc.x ^ e.D2), c.base + SM_DUMMY);
    c.release2(u);
    conv_lda<4, 16>(a, c.addr(un) + aoff);
#pragma unroll
    for (int k = 0; k < 32; k++) { const float2 v = lds64f(rq + k * CV_ROW - (k >> 3) * 8); e.t[2 * k] = v.x; e.t[2 * k + 1] = v.y; }
  }
  conv_emit(e, conv_channel<MASK>(cta, nch - 2 + c.wg), tid);
  c.signal(SIG_Z + ((nch / 2 - 1) >> 4));
  c.release(4, 4);
}

constexpr int OC_PART = 13824, OC_ROW = 544;
__device__ __forceinline__ int out_next(int u) { return u == 12 ? 4 : u + 2; }
struct Out { float acc[64]; int pu; uint64_t da, db; };
template<bool FIRST, bool REL, int W = 1, bool PRE = true, bool POST = false> __device__ __forceinline__ void out_step(Cons& c, Out& o) {
  const int pu = o.pu, u = out_next(pu);
  o.pu = u;
  if (PRE) c.wait(u);
  const uint64_t da = o.da + (uint32_t)(u * 1024), db = o.db + (uint32_t)(u * 1024);
  wg_fence();
#pragma unroll
  for (int kk = 0; kk < 4; kk++) wgmma_ss_n128<1>(o.acc, da + (kk >> 1) * 32 + (kk & 1) * 2, db + kk * 128, !(FIRST && kk == 0));
  wg_commit();
  if (REL) { wg_wait<W>(); c.release(pu, 2); }
  if (POST) c.wait(out_next(u));
}
template<int I0, int I1> __device__ __forceinline__ void oc_red(float (&y)[8], uint32_t rq) {
#pragma unroll
  for (int i = I0; i < I1; i++) { const float v = __uint_as_float(lds32(rq + i * OC_ROW - (i >> 3) * 8)); y[i & 7] = i < 8 ? v : y[i & 7] + v; }
}
__device__ __forceinline__ void oc_emit(const float (&y)[8], const uint4& u, uint32_t D2, __nv_bfloat16* dst) {
  uint4 z;
  z.x = hadd2(pack_bf16(y[0], y[1]), hmul2(__byte_perm(u.w, 0, 0x1032), D2));
  z.y = hadd2(pack_bf16(y[2], y[3]), hmul2(__byte_perm(u.z, 0, 0x1032), D2));
  z.z = hadd2(pack_bf16(y[4], y[5]), hmul2(__byte_perm(u.y, 0, 0x1032), D2));
  z.w = hadd2(pack_bf16(y[6], y[7]), hmul2(__byte_perm(u.x, 0, 0x1032), D2));
  *(uint4*)dst = z;
}
template<int MASK> __device__ __forceinline__ void cons_out(Cons& c, const Maps& M, const Params& P, int cta, Pend& w) {
  const int mb = out_mb(cta), nb = out_nb(cta);
  Out o;
  o.da = odesc(c.daddr(0) + c.wg * 8192, 16, 1024, 2); o.db = odesc(c.daddr(1), 8192, 1024, 1);
  o.pu = 5 + gridDim.y;
  out_step<true, false>(c, o);
  int ks = 1;
#pragma unroll 1
  for (;; ks++) {
    if (MASK & PH_ATT) {
      if (ks == (c.wg ? ST_1 : ST_0)) tile_store<0, 1>(w.lo, w.dst, c.lane);
      if (ks == (c.wg ? ST_1 + ST_D : ST_0 + ST_0D / 2)) tile_store<1, 2>(w.lo, w.dst, c.lane);
      if (ks == (c.wg ? ST_1 + 2 * ST_D : ST_0 + ST_0D)) tile_store<2, 3>(w.lo, w.dst, c.lane);
      if (ks == (c.wg ? ST_1 + 3 * ST_D : ST_0 + 3 * ST_0D / 2)) { tile_store<3, 4>(w.lo, w.dst, c.lane); c.signal(SIG_CTX + 1); }
    }
    if (ks == (c.wg ? OC_S1 : OC_S0)) break;
    out_step<false, true>(c, o);
  }
  if (MASK & PH_CONV) {
    const int r = c.lane >> 2, q = c.lane & 3, tid = c.warp * 32 + c.lane, u = 2 * c.wg;
    const uint32_t ub = c.addr(u), part = ub + OC_PART + 32;
    const uint32_t ap = ub + CV_U + ((r & 1) ? 0 : UPITCH) + 4 * (((2039 - r) >> 1) + q - 8 * c.warp);
    const uint32_t wq = part + (c.warp * 8 + r) * OC_ROW + q * 8, rq = part + tid * 4;
    const int nr = (CV_REG<MASK> + 1 - c.wg) >> 1;
#define STEP(N) out_step<false, true, 1, !OC_POST, OC_POST>(c, o);
#pragma unroll 1
    for (int i = 0; i < nr; i++) {
      uint32_t a[64];
      CvAcc d0, d1;
      float y[8], c0 = 0.f, c1 = 0.f;
      const uint64_t db = odesc(c.daddr(u + (i >> 8)) + CV_H - 16, 16, 128, 0);
#define STEP2(N) out_step<false, true, 2, !OC_POST, OC_POST>(c, o);
#define PART(...) { const uint64_t db = db0 + (uint32_t)(o.pu >> 8); wg_fence(); __VA_ARGS__; wg_commit(); }
      const uint64_t db0 = db;
      c.wait(u);
      if (OC_POST) c.wait(out_next(o.pu));
      conv_lda<0, 4>(a, ap);
      STEP(0)
      conv_lda<4, 7>(a, ap);
      PART(conv_part<0, 0, 2>(d0.lo, a, db); conv_part<1, 0, 4>(d0.hi, a, db))
      STEP2(1)
      conv_lda<7, 10>(a, ap);
      PART(conv_part<2, 0, 6>(d1.lo, a, db))
      STEP2(2)
      fence_regs(d0);
      bar_sync(3 + c.wg, 128);
      sts64f(wq - 32, 0.f, 0.f);
      conv_st<0>(d0, wq, c0, c1);
      asm volatile("add.f32 %0, %0, 0f80000000;" : "+f"(c0)); asm volatile("add.f32 %0, %0, 0f80000000;" : "+f"(c1));
      PART(conv_part<3, 0, 8>(d1.hi, a, db))
      STEP2(3)
      wg_wait<1>(); fence_regs(d1);
      float e0 = d1.hi[12] + d1.hi[10], e1 = d1.hi[13] + d1.hi[11];
      conv_st<1>(d1, wq, c0, c1);
      asm volatile("add.f32 %0, %0, 0f80000000;" : "+f"(c0)); asm volatile("add.f32 %0, %0, 0f80000000;" : "+f"(c1));
      PART(conv_part<4, 0, 10>(d0.lo, a, db))
      STEP2(4)
      conv_lda<10, 12>(a, ap);
      bar_sync(3 + c.wg, 128);
      oc_red<0, 6>(y, rq);
      PART(conv_part<5, 0, 9>(d0.hi, a, db))
      STEP2(5)
      conv_lda<12, 14>(a, ap);
      oc_red<6, 12>(y, rq);
      PART(conv_part<5, 9, 12>(d0.hi, a, db); conv_part<6, 0, 6>(d1.lo, a, db))
      STEP2(6)
      oc_red<12, 26>(y, rq);
      PART(conv_part<6, 6, 14>(d1.lo, a, db))
      STEP2(7)
      oc_red<26, 32>(y, rq);
      conv_lda<14, 16>(a, ap);
      PART(conv_part<7, 0, 8>(d1.hi, a, db))
      STEP2(8)
      fence_regs(y); fence_regs(d0);
      bar_sync(3 + c.wg, 128);
      sts64f(wq - 32, e0, e1);
      conv_st<0>(d0, wq, c0, c1);
      PART(conv_part<7, 8, 16>(d1.hi, a, db))
      STEP2(9)
      wg_wait<1>(); fence_regs(d1); fence_regs(a);
      const uint4 u0 = lds128(ub + CV_U + 4080 - 16 * tid), u1 = lds128(ub + CV_U + 2032 - 16 * tid);
      const uint32_t D2 = lds32(ub + CV_D);
      conv_st_h<64>(d1.lo, wq, c0, c1);
      sched_fence(__uint_as_float(u0.x ^ u1.x ^ D2), c.base + SM_DUMMY);
      __syncwarp();
      c.release2(u);
      STEP(10)
      conv_st_h<96>(d1.hi, wq, c0, c1);
      __nv_bfloat16* zp = g_z + (uint32_t)(conv_channel<MASK>(cta, 2 * i + c.wg) * 2048 + (threadIdx.x & 127) * 8);
      oc_emit(y, u0, D2, zp);
      bar_sync(3 + c.wg, 128);
      oc_red<0, 6>(y, rq);
      STEP(11)
      oc_red<6, 19>(y, rq);
      STEP(12)
      oc_red<19, 32>(y, rq);
      oc_emit(y, u1, D2, zp + 1024);
      if (i == nr - 1) { c.signal(SIG_Z); c.release2(u + 1); }
      out_step<false, true, 1, !OC_POST>(c, o);
#pragma unroll 1
      for (int k = 14; k < (c.wg ? OC_L1 : OC_L0); k++) out_step<false, true>(c, o);
#undef STEP2
#undef PART
    }
#undef STEP
    if (((CV_REG<MASK> + c.wg) >> 1) & 1) c.skip(u ^ 2);
    ks += nr * (c.wg ? OC_L1 : OC_L0);
  }
  TS(c.wg, 9);
#pragma unroll 1
  for (; ks < 57; ks++) out_step<false, true>(c, o);
  uint32_t ga[32];
  c.wait(2);
  const float g0 = __uint_as_float(lds32(c.base + SM_GATE + 4 * (c.wg * 64 + c.warp * 16 + (c.lane >> 2)))), g1 = __uint_as_float(lds32(c.base + SM_GATE + 32 + 4 * (c.wg * 64 + c.warp * 16 + (c.lane >> 2))));
  const uint32_t gg0 = pack_bf16(g0, g0), gg1 = pack_bf16(g1, g1);
  const uint32_t og0 = pack_bf16(1.f - g0, 1.f - g0), og1 = pack_bf16(1.f - g1, 1.f - g1);
  const int xr = c.wg * 64 + c.warp * 16 + (c.lane & 15);
  const uint32_t xa = c.addr(2) + xr * 128, xs = xr & 7, xh = c.lane >> 4;
  const int zr = (c.lane & 7) + ((c.lane >> 4) << 3);
  const uint32_t za = c.addr(0) + c.wg * 16384 + zr * 128 + (((c.warp * 2 + ((c.lane >> 3) & 1)) ^ (zr & 7)) << 4);
#pragma unroll
  for (int i = 0; i < 8; i++) {
    if (i == 0) out_step<false, true>(c, o);
    if (i == 3) out_step<false, true>(c, o);
    if (i == 6) out_step<false, true>(c, o);
    ldsm4(xa + (i >> 2) * 16384 + ((((i & 3) * 2 + xh) ^ xs) << 4), ga[4 * i], ga[4 * i + 1], ga[4 * i + 2], ga[4 * i + 3]);
  }
#pragma unroll 1
  for (ks = 60; ks < 64; ks++) out_step<false, false>(c, o);
  c.wait(0);
  SHADOW {
#pragma unroll
    for (int i = 0; i < 8; i++) {
      uint32_t z0, z1, z2, z3;
      ldsm4t(za + i * 2048, z0, z1, z2, z3);
      ga[4 * i + 0] = hmul2(gg0, hmul2(ga[4 * i + 0], z0)); ga[4 * i + 1] = hmul2(gg1, hmul2(ga[4 * i + 1], z1));
      ga[4 * i + 2] = hmul2(gg0, hmul2(ga[4 * i + 2], z2)); ga[4 * i + 3] = hmul2(gg1, hmul2(ga[4 * i + 3], z3));
    }
  }
  c.signal(SIG_DONE);
  fence_regs(ga);
  wg_wait<0>(); fence_regs(o.acc);
#pragma unroll
  for (int i = 0; i < 8; i++) {
    const uint32_t r0 = hadd2(ga[4 * i + 0], hmul2(og0, pack_bf16(o.acc[8 * i + 0], o.acc[8 * i + 1])));
    const uint32_t r1 = hadd2(ga[4 * i + 1], hmul2(og1, pack_bf16(o.acc[8 * i + 2], o.acc[8 * i + 3])));
    const uint32_t r2 = hadd2(ga[4 * i + 2], hmul2(og0, pack_bf16(o.acc[8 * i + 4], o.acc[8 * i + 5])));
    const uint32_t r3 = hadd2(ga[4 * i + 3], hmul2(og1, pack_bf16(o.acc[8 * i + 6], o.acc[8 * i + 7])));
    stsm4(xa + (i >> 2) * 16384 + ((((i & 3) * 2 + xh) ^ xs) << 4), r0, r1, r2, r3);
    if ((i & 3) == 3) {
      __syncwarp();
#pragma unroll
      for (int k = 0; k < 4; k++) {
        const int rr = c.wg * 64 + c.warp * 16 + k * 4 + (c.lane >> 3);
        const uint4 v = lds128(c.addr(2 + (i >> 2)) + rr * 128 + (((c.lane ^ rr) & 7) << 4));
        *(uint4*)(P.out + (uint32_t)((mb * 128 + rr) * 1024 + nb * 128 + (i >> 2) * 64 + (c.lane & 7) * 8)) = v;
      }
    }
  }
}

__device__ __forceinline__ void load_conv(Prod& p, const Maps& M, int u, int ch) {
  if (elect()) {
    mbar_expect(p.full(u), 5120 + UCH);
    tma3d(p.addr(u), &M.h, 0, -8, ch, p.full(u), POL(4));
    bulk_g2s(p.addr(u) + CV_U, g_u + (size_t)ch * UCH, UCH, p.full(u), POL(4));
  }
}
template<int MASK> __device__ __forceinline__ void prod_conv(Prod& p, const Maps& M, int cta, int nch) {
  int ready = -1;
#pragma unroll 1
  for (int i = 0; i < nch; i++) {
    const int ch = conv_channel<MASK>(cta, i);
    const int u = i & 3;
    if ((ch >> 6) != ready) { ready = ch >> 6; if (cta < NREG) mbar_wait(p.base + SM_RDY + 8 * RDY_U, 0); else cnt_wait(g_cnt + (C_U + ready) * CSTRIDE, 128); }
    p.acquire(u, 1);
    load_conv(p, M, u, ch);
    if (i == 3) { p.acquire(4, 4); if (elect()) mbar_arrive(p.full(4)); }
  }
}
#define HOIST(v) asm volatile("" : "+r"(v))
template<int MASK> __device__ __forceinline__ void producer(const Maps& M, const Params& P, uint32_t base, int cta, int lane) {
  Prod p{base, ((MASK & PH_KV) && cta < NREG) ? 0xffffcfffu ^ ((1u << (3 * NFIRST)) - 1) : 0xffffffffu, lane,
         (cta * 3 + 2) * 2048};
  if (cta >= NREG) { if (MASK & PH_CONV) prod_conv<MASK>(p, M, cta, CV_EXTRA<MASK>); return; }
  const int g = cta & 7, j = cta >> 3, rank = cta & 1;
#pragma unroll 1
  for (int half = 0; half < 2; half++) {
    const int h = j + 16 * half;
    if (MASK & PH_KV) {
      const CUtensorMap* mw = rank ? &M.wv : &M.wk;
#pragma unroll 1
      for (int it = half ? 0 : NFIRST; it < 16; it++) {
        const int u = gemm_unit(it);
        uint32_t bar = p.full(u), d0 = p.addr(u), d1 = p.addr(u + 1 + rank); int k0 = (it & 7) * 64, r0 = (2 * g + (it >> 3)) * 128;
        HOIST(bar); HOIST(d0); HOIST(d1); HOIST(k0); HOIST(r0);
        p.acquire(u, 3);
        if (elect()) {
          mbar_expect(bar, 3 * UNIT);
          tma3d_mc(d1, mw, 0, k0, 2 * h, bar, POL(0) && it >= 8);
          tma2d(d0, &M.c, k0, r0, bar, half ? POL(8) : POL(10));
        }
      }
    }
    if (MASK & PH_ATT) {
#pragma unroll 1
      for (int ks = 0; ks < 16; ks++) {
        const int u = gemm_unit(ks);
        uint32_t bar = p.full(u), d0 = p.addr(u + (ks == 15)), d1 = p.addr(ks < 14 ? u + 1 : ks - 6), d2 = p.addr(u + 2 - (ks == 14)) + rank * 8192; int k0 = ks * 64;
        HOIST(bar); HOIST(d0); HOIST(d1); HOIST(d2); HOIST(k0);
        p.acquire(u, 3);
        if (elect()) {
          mbar_expect(bar, 3 * UNIT);
          tma2d_mc(d2, &M.wq, h * 128 + rank * 64, k0, bar, POL(1));
          tma2d(d0, &M.x, k0, (15 - g) * 128, bar, half ? POL(9) : POL(10));
          tma2d(d1, &M.x, k0, g * 128, bar, half ? POL(9) : POL(10));
        }
      }
      TS(2, 8 * half + 0);
      mbar_wait(base + SM_RDY + 8 * (RDY_KV + half), 0);
      TS(2, 8 * half + 1);
      p.acquire(0, 4);
      if (elect()) mbar_arrive(p.full(0));
      const uint8_t* KVh = g_T + T_KV + (size_t)kv_slot<MASK>(h) * 16 * 65536;
#pragma unroll 1
      for (int n = 0; n < 34; n++) {
        const int i = n == 1 ? 2 : n == 2 ? 1 : n;
        const int isv = (i > 0 && !(i & 1)) || i == 33;
        const int st = i == 33 ? 16 : (isv ? (i >> 1) - 1 : (i + 1) >> 1);
        const int u = att_slot(i & 3);
        const bool own = st == 15 - (g & 6);
        uint32_t bar = p.full((isv && i < 33) ? 14 - u : u), d0 = p.addr(own ? u : u + rank), off = (st <= 15 - g ? st : 16 - st) * 65536 + isv * 32768 + (own ? 0 : rank * UNIT);
        HOIST(bar); HOIST(d0); HOIST(off);
        p.acquire(u, 2);
        if (elect()) {
          if (!isv || i == 33) mbar_expect(bar, (i == 0 || i == 33) ? 32768 : 65536);
          const bool ef = POL(6) || (POL(14) && st >= 8) || (POL(15) && half);
          if (own) bulk_g2s(d0, KVh + off, 32768, bar, ef); else bulk_g2s_mc(d0, KVh + off, UNIT, bar, ef);
          if (MASK == PH_ALL && half && n == PF_AT) {
            if (PF & 1) pf3d(&M.wo, 0, j * 64, 2 * g);
            if (PF & 2) pf_bulk(g_T + T_CTX + (j * 32 + g) * 32768, 32768);
          }
        }
      }
    }
  }
  if ((MASK & PH_CONV) && !(MASK & PH_OUT)) prod_conv<MASK>(p, M, cta, CV_REG<MASK>);
  if (MASK & PH_OUT) {
    const int y0 = out_mb(cta) * 512 + rank * 8, z0 = 2 * out_nb(cta);
    int u = 6;
#pragma unroll 1
    for (int hf = 0; hf < 2; hf++) {
      TS(2, 16 + 2 * hf);
      mbar_wait(base + SM_RDY + 8 * (RDY_CTX + hf), 0);
      TS(2, 17 + 2 * hf);
#pragma unroll 1
      for (int ks = hf * 32; ks < hf * 32 + 32; ks++) {
        u = out_next(u);
        uint32_t bar = p.full(u), d0 = p.addr(u) + rank * 8192, d1 = p.addr(u + 1); int x = (ks & 1) * 256, y = y0 + (ks >> 1) * 16, k0 = ks * 64;
        HOIST(bar); HOIST(d0); HOIST(d1); HOIST(x); HOIST(y); HOIST(k0);
        p.acquire(u, 2);
        if (elect()) {
          mbar_expect(bar, 2 * UNIT);
          tma2d_mc(d0, &M.ctx, x, y, bar, POL(5));
          tma3d(d1, &M.wo, 0, k0, z0, bar, POL(2));
          if ((PF & 4) && (ks & 15) == PF_KS && ks < 48) pf3d(&M.wo, 0, ((ks & 48) + 16 + j) * 64, z0);
          if ((PF & 8) && ks == PF_KS) pf_bulk(g_T + T_CTX + (j * 32 + 8 + g) * 32768, 32768);
          if (ks == Z_AT) mbar_arrive(base + SM_RDY + 8 * RDY_Z);
        }
      }
    }
  }
}
template<int MASK> __device__ __forceinline__ void producer2(const Maps& M, const Params& P, uint32_t base, int cta, int w, int lane) {
  Prod p{base, 0xffffffffu, lane, 0};
  const int mb = out_mb(cta), nb = out_nb(cta), u = 2 * w;
  if (MASK & PH_CONV) {
    mbar_wait_slow(base + SM_SIG + 8 * (SIG_ATT + 1), 0);
    mbar_wait_slow(base + SM_RDY + 8 * RDY_U, 0);
#pragma unroll 1
    for (int i = w; i < CV_REG<MASK>; i += 2) { p.acquire_slow(u, i < 2 ? 2 : 1); load_conv(p, M, u, conv_channel<MASK>(cta, i)); }
  }
  p.acquire_slow(u, 2);
  if (elect()) asm volatile("prefetch.tensormap [%0];" :: "l"(!w ? &M.z : &M.out) : "memory");
  TSA(52 - 2 * w);
  mbar_wait(base + SM_RDY + 8 * (!w ? RDY_Z : RDY_G), 0);
  TSA(53 - 2 * w);
  if (elect()) {
    mbar_expect(p.full(u), 2 * UNIT + (!w ? 0 : 512));
    tma2d(p.addr(u), !w ? &M.z : &M.x, (!w ? mb : nb) * 128, (!w ? nb : mb) * 128, p.full(u), POL(5));
    tma2d(p.addr(u + 1), !w ? &M.z : &M.x, (!w ? mb : nb) * 128 + 64, (!w ? nb : mb) * 128, p.full(u), POL(5));
    if (w) bulk_g2s(base + SM_GATE, g_gate + mb * 128, 512, p.full(u));
  }
}

__device__ __forceinline__ constexpr uint32_t PUB(int sig, int cnt, int n) { return 0x80000000u | (sig << 24) | (n << 8) | cnt; }
__device__ __forceinline__ constexpr uint32_t GET(int rdy, int cnt, int n) { return (rdy << 24) | (n << 8) | cnt; }
template<int MASK> __device__ __forceinline__ void sync_agent(uint32_t base, int cta, int lane) {
  if ((base & 0x3FFFF) != SMEM_BASE) asm volatile("trap;");
  const int g = cta & 7, j = cta >> 3, go = min(out_mb(cta), 15 - out_mb(cta));
  const int c0 = conv_channel<MASK>(cta, 0), c1 = c0 + CV_REG<MASK> - 1, n0 = min(CV_REG<MASK>, 128 - (c0 & 127));
  constexpr bool KV = MASK & PH_KV, ATT = MASK & PH_ATT, CONV = MASK & PH_CONV, OUT = MASK & PH_OUT, ALL = MASK == PH_ALL;
  uint32_t e = 0;
  if (cta >= NREG) { if (CONV && lane * 32 < CV_EXTRA<MASK>) e = PUB(SIG_Z + lane, C_Z + lane, min(32, CV_EXTRA<MASK> - lane * 32)); }
  else switch (lane) {
    case 0:  if (KV) e = PUB(SIG_KV, C_KV + j, 1); break;
    case 1:  if (ATT) e = GET(RDY_KV, C_KV + j, 8); break;
    case 2:  if (ALL) e = PUB(SIG_WAR, C_WAR + j, 1); break;
    case 3:  if (ATT) e = PUB(SIG_CTX, C_CTX + g, 1); break;
    case 4:  if (ALL) e = GET(RDY_WAR, C_WAR + j, 8); break;
    case 5:  if (KV) e = PUB(SIG_KV + 1, C_KV + 16 + j, 1); break;
    case 6:  if (ATT) e = GET(RDY_KV + 1, C_KV + 16 + j, 8); break;
    case 7:  if (OUT) e = GET(RDY_CTX, C_CTX + go, 16); break;
    case 8:  if (CONV) e = GET(RDY_U, C_U + (c0 >> 6), 128); break;
    case 9:  if (CONV) e = GET(RDY_U, C_U + (c1 >> 6), 128); break;
    case 10: if (ATT) e = PUB(SIG_CTX + 1, C_CTX + 8 + g, 1); break;
    case 11: if (OUT) e = GET(RDY_CTX + 1, C_CTX + 8 + go, 16); break;
    case 12: if (OUT) e = GET(RDY_G, C_GATE, 256); break;
    case 13: if (CONV) e = PUB(SIG_Z, C_Z + (c0 >> 7), n0); break;
    case 14: if (CONV && n0 < CV_REG<MASK>) e = PUB(SIG_Z, C_Z + (c1 >> 7), CV_REG<MASK> - n0); break;
    case 15: if (OUT) e = GET(RDY_Z, C_Z + out_nb(cta), 128); break;
  }
  __syncwarp();
#pragma unroll 1
  for (int i = 0; i < 16; i++) {
    const uint32_t x = __shfl_sync(~0u, e, i), id = (x >> 24) & 127, n = (x >> 8) & 0xffff;
    if (x == 0) continue;
    unsigned* cnt = g_cnt + (x & 255) * CSTRIDE;
    if (x >> 31) {
      mbar_wait_slow(base + SM_SIG + 8 * id, 0);
      if (lane == 0) cnt_publish(cnt, n, i != 14);
    } else {
      cnt_wait(cnt, n);
      if (id < 2) {
        const float4 kn = __ldcg((const float4*)(g_kn2 + kv_slot<MASK>(j + 16 * id) * 128) + lane);
        const uint32_t m = __reduce_max_sync(~0u, max(max(__float_as_uint(kn.x), __float_as_uint(kn.y)), max(__float_as_uint(kn.z), __float_as_uint(kn.w))));
        if (lane == 0) asm volatile("st.shared.u32 [%0], %1;" :: "r"(base + SM_KMAX + 4 * id), "r"(m) : "memory");
      }
      if (lane == 0) mbar_arrive(base + SM_RDY + 8 * id);
    }
    __syncwarp();
  }
}

__device__ __forceinline__ void aux_gate(const Params& P, int cta, int aw, int lane) {
  uint4 gw[4];
#pragma unroll
  for (int i = 0; i < 4; i++) gw[i] = __ldg((const uint4*)P.gw + i * 32 + lane);
#pragma unroll 1
  for (int row = cta * 16 + aw * 8; row < cta * 16 + aw * 8 + 8; row++) {
    float a = 0.f;
#pragma unroll
    for (int i = 0; i < 4; i++) {
      const uint4 xv = __ldg((const uint4*)(P.x + (size_t)row * 1024) + i * 32 + lane);
      uint32_t m;
      m = hmul2(xv.x, gw[i].x); a += bf_lo(m) + bf_hi(m); m = hmul2(xv.y, gw[i].y); a += bf_lo(m) + bf_hi(m);
      m = hmul2(xv.z, gw[i].z); a += bf_lo(m) + bf_hi(m); m = hmul2(xv.w, gw[i].w); a += bf_lo(m) + bf_hi(m);
    }
#pragma unroll
    for (int o = 16; o > 0; o >>= 1) a += __shfl_xor_sync(~0u, a, o);
    a = bf_lo(pack_bf16(a, 0.f));
    const float gt = bf_lo(pack_bf16(__fdividef(1.f, 1.f + ex2(-a * 1.4426950408889634f)), 0.f));
    if (lane == 0) g_gate[row] = gt;
    if (GATE_SLEEP) __nanosleep(GATE_SLEEP);
  }
  cnt_signal(g_cnt + C_GATE * CSTRIDE, lane);
  if (aw == 0) { TSA(44); }
}
template<int MASK> __device__ __forceinline__ void aux_pre(const Maps& M, const Params& P, uint32_t base, int cta, int aw, int lane) {
  const uint32_t kb = base + 12 * UNIT, bar = base + SM_PRE;
  const int r = lane >> 2, q = lane & 3;
  const int mi = lane >> 3, row0 = (lane & 6) + 1 - (lane & 1);
  const int ra = (mi * 9 + 1) * 2 + row0;
  const int rb = (mi == 0 ? 3 : mi) * 18 + row0;
  if (PRE_DELAY) mbar_wait_slow(base + SM_BAR + 8 * PRE_DELAY_BAR, 0);
#pragma unroll 1
  for (int it = 0; it < (cta < 96 ? 5 : 4); it++) {
    if (GATE_EARLY && it == PRE_EARLY && MASK == PH_ALL) { mbar_wait_slow(base + SM_SIG + 8 * SIG_ATT, 0); aux_gate(P, cta, aw, lane); }
    if (it == PRE_EARLY && MASK == PH_ALL) mbar_wait_slow(base + SM_SIG + 8 * (SIG_ATT + PRE_HALF), 0);
    const int cg = it ? it * 4 - 3 + (cta >> 5) : 0, tb = cta & 31;
    if (aw == 0 && elect()) {
      mbar_expect(bar, 2 * 9216);
      tma4d(kb, &M.k, cg * 64, 0, tb * 8 - 1, 0, bar, POL(3));
      tma4d(kb + 9216, &M.v, cg * 64, 0, tb * 8 - 1, 0, bar, POL(3));
    }
    const uint2 swl = __ldg((const uint2*)(P.shift + (cg * 64 + aw * 32 + lane) * 4));
    if (tb == 0) {
      uint8_t* e = g_u + (size_t)(cg * 64 + aw * 32 + lane) * UCH + 4096;
      *(uint4*)e = make_uint4(0, 0, 0, 0); *(uint4*)(e + UPITCH) = make_uint4(0, 0, 0, 0);
      *(uint32_t*)(e + 32) = (uint32_t)__bfloat16_as_ushort(P.D[cg * 64 + aw * 32 + lane]) * 0x10001u;
    }
    mbar_wait_slow(bar, it & 1);
#pragma unroll 1
    for (int ol = it ? 0 : cta >> 5; ol < (it ? 4 : (cta >> 5) + 1); ol++) {
      const int oc = aw * 4 + ol;
      const uint32_t s01 = __shfl_sync(~0u, swl.x, ol * 8 + r), s23 = __shfl_sync(~0u, swl.y, ol * 8 + r);
      const uint32_t w0 = __byte_perm(s01, 0, 0x1010), w1 = __byte_perm(s01, 0, 0x3232), w2 = __byte_perm(s23, 0, 0x1010), w3 = __byte_perm(s23, 0, 0x3232);
      const uint32_t pa = kb + ra * 128 + ((oc ^ (ra & 7)) << 4), pb = kb + (mi == 0 ? 9216 : 0) + rb * 128 + ((oc ^ (rb & 7)) << 4);
      uint8_t* e0 = g_u + (uint32_t)((cg * 64 + oc * 8 + r) * UCH + (2040 - tb * 64 - 8 * q) * 2);
#pragma unroll
      for (int hb = 0; hb < 2; hb++) {
        uint32_t k[7], v[5];
        ldsm4t(pa + hb * 1024, k[3], k[4], k[5], k[6]);
        ldsm4t(pa + hb * 1024 + 9216, v[1], v[2], v[3], v[4]);
        ldsm4t(pb + hb * 1024, v[0], k[0], k[1], k[2]);
        uint32_t o1 = __byte_perm(k[1], k[0], 0x5432);
#pragma unroll
        for (int m = 0; m < 5; m++) {
          const uint32_t o2 = __byte_perm(k[m + 2], k[m + 1], 0x5432);
          v[m] = hmul2(hadd2(hadd2(hadd2(hmul2(o1, w3), hmul2(k[m + 1], w2)), hmul2(o2, w1)), hmul2(k[m + 2], w0)), v[m]);
          o1 = o2;
        }
        *(uint4*)(e0 - hb * 64) = make_uint4(v[4], v[3], v[2], v[1]);
        *(uint4*)(e0 - hb * 64 + UPITCH) = make_uint4(__byte_perm(v[4], v[3], 0x5432), __byte_perm(v[3], v[2], 0x5432), __byte_perm(v[2], v[1], 0x5432), __byte_perm(v[1], v[0], 0x5432));
        if (PRE_SLEEP && it >= PRE_EARLY) __nanosleep(PRE_SLEEP);
      }
    }
    bar_sync(5, 64);
    if (aw == 0) { TSA(40 + min(it, 3)); }
    if (aw == 1 && lane == 0) asm volatile("red.release.gpu.global.add.u32 [%0], %1;" :: "l"(g_cnt + (C_U + cg) * CSTRIDE), "r"(it ? 4 : 1) : "memory");
  }
  uint32_t rel;
  asm volatile("mapa.shared::cluster.u32 %0, %1, %2;" : "=r"(rel) : "r"(base + SM_BAR + 128 + 8 * (12 + (lane & 1))), "r"((lane >> 1) & 1));
  if (lane < 4) asm volatile("mbarrier.arrive.shared::cluster.b64 _, [%0], 4;" :: "r"(rel) : "memory");
  if (!(GATE_EARLY && MASK == PH_ALL)) aux_gate(P, cta, aw, lane);
}

template<int MASK> __global__ void __cluster_dims__(2, 1, 1) __launch_bounds__(384, 1) gated_mix_kernel(const __grid_constant__ Maps M, const __grid_constant__ Params P) {
  extern __shared__ __align__(1024) uint8_t smem[];
  const uint32_t base = (uint32_t)__cvta_generic_to_shared(smem);
  const int wi = __shfl_sync(~0u, threadIdx.x >> 5, 0), wg = wi >> 2, warp = wi & 3;
  if (elect()) {
    if (wi < 8) {
      const int cnt = 1 << ((0x10334400 >> (4 * wi)) & 15);
#pragma unroll
      for (int i = 0; i < 8; i++) mbar_init(base + SM_BAR + 64 * wi + 8 * i, cnt);
      asm volatile("fence.mbarrier_init.release.cluster;" ::: "memory");
    } else if (MAP_PF) {
      asm volatile("prefetch.tensormap [%0];" :: "l"(&M.c + (wi - 8)) : "memory");
    }
  }
  const int cta = blockIdx.x;
  const bool first_loads = (MASK & PH_KV) && wi == 8 && cta < NREG;
  const CUtensorMap* mw = (cta & 1) ? &M.wv : &M.wk;
  __syncwarp();
  asm volatile("barrier.cluster.arrive.relaxed.aligned;\nbarrier.cluster.wait.aligned;" ::: "memory");
  if (first_loads && elect()) {
#pragma unroll 1
    for (int it = 0; it < NFIRST; it++) {
      const uint32_t bar = base + SM_BAR + 24 * it, d0 = base + 3 * it * UNIT;
      mbar_expect(bar, 3 * UNIT);
      tma3d_mc(d0 + (1 + (cta & 1)) * UNIT, mw, 0, it * 64, 2 * (cta >> 3), bar);
      tma2d(d0, &M.c, it * 64, (cta & 7) * 256, bar);
    }
  }
  __syncwarp();
  const int lane = threadIdx.x & 31;
#define TS_PRO()
  if (wg == 2) {
    asm volatile("setmaxnreg.dec.sync.aligned.u32 56;");
    TS_PRO();
    TS(2, 62);
    if (warp == 0) producer<MASK>(M, P, base, cta, lane);
    else if (warp == 1) sync_agent<MASK>(base, cta, lane);
    else if (cta < NREG) {
      if (MASK & PH_PRE) aux_pre<MASK>(M, P, base, cta, warp - 2, lane);
      if (MASK & PH_OUT) producer2<MASK>(M, P, base, cta, warp - 2, lane);
    }
    if (warp == 1) {
      if (MASK & PH_OUT) {
        unsigned old = 0;
        if (lane == 0) asm volatile("atom.relaxed.gpu.global.add.u32 %0, [%1], 1;" : "=r"(old) : "l"(g_cnt + C_EXIT * CSTRIDE) : "memory");
        old = __shfl_sync(~0u, old, 0);
        if (old == NCTA - 1) for (int i = lane; i < C_NUM; i += 32) g_cnt[i * CSTRIDE] = 0;
      }
      mbar_wait_slow(base + SM_SIG + 8 * SIG_DONE, 0);
      if (cta >= NREG || !(MASK & PH_OUT)) { cluster_arrive(); cluster_wait(); }
    }
  } else {
    asm volatile("setmaxnreg.inc.sync.aligned.u32 224;");
    TS_PRO();
    uint32_t rel;
    asm volatile("mapa.shared::cluster.u32 %0, %1, %2;" : "=r"(rel) : "r"(base + SM_BAR + 128 + 8 * (lane & 15)), "r"(lane >> 4));
    Cons c{base, rel, 0u, lane, warp, wg, (cta * 3 + wg) * 2048};
    if (wg == 1) bar_arrive(1, 256);
    TS(wg, 0);
    if (cta < NREG) {
      const int g = cta & 7, j = cta >> 3;
      Pend w = {};
#pragma unroll 1
      for (int half = 0; half < 2; half++) {
        const int h = j + 16 * half;
        if (MASK & PH_KV) cons_kv<(MASK & PH_ATT) != 0>(c, h, kv_slot<MASK>(h), g, w, half == 1 && (MASK & PH_ATT));
        TS(wg, 1 + 4 * half);
        if (MASK & PH_ATT) {
          Att a;
          cons_q<(MASK & PH_KV) != 0>(c, h, w, a.o);
          TS(wg, 2 + 4 * half);
          cons_att(c, a, h, g, w);
          if (half == 0) c.signal(SIG_WAR);
#pragma unroll
          for (int i = 0; i < 8; i++) w.hi[i] = make_uint4(0, 0, 0, 0);
          TS(wg, 3 + 4 * half);
          if (MASK != PH_ALL) { tile_store<0, 4>(w.lo, w.dst, lane); c.signal(SIG_CTX + half); }
        } else if (MASK & PH_KV) {
          out_piece<SCH_KV, true>(c, w, 0, true);
          for (int ks = 1; ks < 8; ks++) out_piece<SCH_KV, false>(c, w, ks, true);
          c.signal(SIG_KV + half);
        }
      }
      if (MASK & PH_OUT) cons_out<MASK>(c, M, P, cta, w);
    }
    if (cta >= NREG || !(MASK & PH_OUT)) {
      if (MASK & PH_CONV) cons_conv<MASK>(c, cta, cta < NREG ? CV_REG<MASK> : CV_EXTRA<MASK>);
      TS(wg, 9);
      c.signal(SIG_DONE);
      cluster_arrive();
    }
    TS(wg, 10);
  }
}

typedef CUresult (*EncFn)(CUtensorMap*, CUtensorMapDataType, cuuint32_t, void*, const cuuint64_t*, const cuuint64_t*, const cuuint32_t*, const cuuint32_t*,
                          CUtensorMapInterleave, CUtensorMapSwizzle, CUtensorMapL2promotion, CUtensorMapFloatOOBfill);
static void enc(EncFn f, CUtensorMap* m, const void* ptr, int rank, const cuuint64_t* dims, const cuuint64_t* strides, const cuuint32_t* box, CUtensorMapSwizzle sw,
                CUtensorMapDataType dt = CU_TENSOR_MAP_DATA_TYPE_BFLOAT16) {
  const cuuint32_t es[4] = {1, 1, 1, 1};
  f(m, dt, rank, (void*)ptr, dims, strides, box, es, CU_TENSOR_MAP_INTERLEAVE_NONE, sw, CU_TENSOR_MAP_L2_PROMOTION_L2_256B, CU_TENSOR_MAP_FLOAT_OOB_FILL_NONE);
}
static void enc2(EncFn f, CUtensorMap* m, const void* ptr, int cols, int rows, int brows) {
  const cuuint64_t d[2] = {(cuuint64_t)cols, (cuuint64_t)rows}, s[1] = {(cuuint64_t)cols * 2}; const cuuint32_t b[2] = {64, (cuuint32_t)brows};
  enc(f, m, ptr, 2, d, s, b, CU_TENSOR_MAP_SWIZZLE_128B);
}
static void encw(EncFn f, CUtensorMap* m, const void* ptr, int cols, int rows) {
  const cuuint64_t d[3] = {64, (cuuint64_t)rows, (cuuint64_t)cols / 64}, s[2] = {(cuuint64_t)cols * 2, 128}; const cuuint32_t b[3] = {64, 64, 2};
  enc(f, m, ptr, 3, d, s, b, CU_TENSOR_MAP_SWIZZLE_128B);
}
extern "C" void kernel_launch(void* const* d_in, const int* in_sizes, int n_in, void* d_out, int out_size) {
  static EncFn fn = nullptr;
  static int ncl = 0;
  static void* zptr = nullptr;
  static void* tptr = nullptr;
  if (!fn) {
    void* p = nullptr; cudaDriverEntryPointQueryResult qr;
    cudaGetDriverEntryPoint("cuTensorMapEncodeTiled", &p, cudaEnableDefault, &qr);
    fn = (EncFn)p;
    cudaFuncSetAttribute(gated_mix_kernel<PH_ALL>, cudaFuncAttributeMaxDynamicSharedMemorySize, SMEM_BYTES);
    cudaFuncSetAttribute(gated_mix_kernel<PH_PRE | PH_KV>, cudaFuncAttributeMaxDynamicSharedMemorySize, SMEM_BYTES);
    cudaFuncSetAttribute(gated_mix_kernel<PH_ATT | PH_CONV>, cudaFuncAttributeMaxDynamicSharedMemorySize, SMEM_BYTES);
    cudaFuncSetAttribute(gated_mix_kernel<PH_OUT>, cudaFuncAttributeMaxDynamicSharedMemorySize, SMEM_BYTES);
    cudaLaunchConfig_t cfg = {}; cfg.gridDim = NCTA; cfg.blockDim = 384; cfg.dynamicSmemBytes = SMEM_BYTES;
    cudaLaunchAttribute at; at.id = cudaLaunchAttributeClusterDimension; at.val.clusterDim.x = 2; at.val.clusterDim.y = 1; at.val.clusterDim.z = 1;
    cfg.attrs = &at; cfg.numAttrs = 1;
    cudaOccupancyMaxActiveClusters(&ncl, gated_mix_kernel<PH_ALL>, &cfg);
    cudaGetSymbolAddress(&zptr, g_z);
    cudaGetSymbolAddress(&tptr, g_T);
  }
  Maps M;
  enc2(fn, &M.x, d_in[0], 1024, 2048, 128);
  enc2(fn, &M.c, d_in[7], 512, 2048, 128);
  enc2(fn, &M.wq, d_in[8], 4096, 1024, 64);
  encw(fn, &M.wk, d_in[9], 4096, 512);
  encw(fn, &M.wv, d_in[10], 4096, 512);
  encw(fn, &M.wo, d_in[11], 1024, 4096);
  { const cuuint64_t d[3] = {64, 32, 1024}, s[2] = {128, 4096}; const cuuint32_t b[3] = {64, 40, 1}; enc(fn, &M.h, d_in[4], 3, d, s, b, CU_TENSOR_MAP_SWIZZLE_NONE); }
  enc2(fn, &M.z, zptr, 2048, 1024, 128);
  enc2(fn, &M.out, d_out, 1024, 2048, 16);
  { const cuuint64_t d[2] = {512, 512 * 16}, s[1] = {2048}; const cuuint32_t b[2] = {256, 8};
    enc(fn, &M.ctx, tptr, 2, d, s, b, CU_TENSOR_MAP_SWIZZLE_NONE, CU_TENSOR_MAP_DATA_TYPE_UINT32); }
  { const cuuint64_t d[4] = {1024, 2, 256, 4}, s[3] = {2048, 16384, 4096}; const cuuint32_t b[4] = {64, 2, 9, 4};
    enc(fn, &M.k, d_in[1], 4, d, s, b, CU_TENSOR_MAP_SWIZZLE_128B); enc(fn, &M.v, d_in[2], 4, d, s, b, CU_TENSOR_MAP_SWIZZLE_128B); }
  Params P{(const __nv_bfloat16*)d_in[0], (const __nv_bfloat16*)d_in[3],
           (const __nv_bfloat16*)d_in[5], (const __nv_bfloat16*)d_in[12], (__nv_bfloat16*)d_out};
  bool split = 2 * ncl < NCTA;
  if (!split) {
    gated_mix_kernel<PH_ALL><<<NCTA, 384, SMEM_BYTES>>>(M, P);
  } else {
    gated_mix_kernel<PH_PRE | PH_KV><<<NCTA, 384, SMEM_BYTES>>>(M, P);
    gated_mix_kernel<PH_ATT | PH_CONV><<<NCTA, 384, SMEM_BYTES>>>(M, P);
    gated_mix_kernel<PH_OUT><<<NCTA, 384, SMEM_BYTES>>>(M, P);
  }
}
```

```cpp
#include <cuda_runtime.h>
#include <cuda.h>
#include <cuda_bf16.h>
#include <stdint.h>

template<int TB> __device__ __forceinline__ void wgmma_ss_n256(float (&d)[128], uint64_t da, uint64_t db, int scale_d) {
  asm volatile("{\n.reg .pred p;\nsetp.ne.b32 p, %130, 0;\n"
    "wgmma.mma_async.sync.aligned.m64n256k16.f32.bf16.bf16 {%0, %1, %2, %3, %4, %5, %6, %7, %8, %9, %10, %11, %12, %13, %14, %15, %16, %17, %18, %19, %20, %21, %22, %23, %24, %25, %26, %27, %28, %29, %30, %31, %32, %33, %34, %35, %36, %37, %38, %39, %40, %41, %42, %43, %44, %45, %46, %47, %48, %49, %50, %51, %52, %53, %54, %55, %56, %57, %58, %59, %60, %61, %62, %63, %64, %65, %66, %67, %68, %69, %70, %71, %72, %73, %74, %75, %76, %77, %78, %79, %80, %81, %82, %83, %84, %85, %86, %87, %88, %89, %90, %91, %92, %93, %94, %95, %96, %97, %98, %99, %100, %101, %102, %103, %104, %105, %106, %107, %108, %109, %110, %111, %112, %113, %114, %115, %116, %117, %118, %119, %120, %121, %122, %123, %124, %125, %126, %127}, %128, %129, p, 1, 1, 0, %131;\n}\n"
    : "+f"(d[0]), "+f"(d[1]), "+f"(d[2]), "+f"(d[3]), "+f"(d[4]), "+f"(d[5]), "+f"(d[6]), "+f"(d[7]), "+f"(d[8]), "+f"(d[9]), "+f"(d[10]), "+f"(d[11]), "+f"(d[12]), "+f"(d[13]), "+f"(d[14]), "+f"(d[15]), "+f"(d[16]), "+f"(d[17]), "+f"(d[18]), "+f"(d[19]), "+f"(d[20]), "+f"(d[21]), "+f"(d[22]), "+f"(d[23]), "+f"(d[24]), "+f"(d[25]), "+f"(d[26]), "+f"(d[27]), "+f"(d[28]), "+f"(d[29]), "+f"(d[30]), "+f"(d[31]), "+f"(d[32]), "+f"(d[33]), "+f"(d[34]), "+f"(d[35]), "+f"(d[36]), "+f"(d[37]), "+f"(d[38]), "+f"(d[39]), "+f"(d[40]), "+f"(d[41]), "+f"(d[42]), "+f"(d[43]), "+f"(d[44]), "+f"(d[45]), "+f"(d[46]), "+f"(d[47]), "+f"(d[48]), "+f"(d[49]), "+f"(d[50]), "+f"(d[51]), "+f"(d[52]), "+f"(d[53]), "+f"(d[54]), "+f"(d[55]), "+f"(d[56]), "+f"(d[57]), "+f"(d[58]), "+f"(d[59]), "+f"(d[60]), "+f"(d[61]), "+f"(d[62]), "+f"(d[63]), "+f"(d[64]), "+f"(d[65]), "+f"(d[66]), "+f"(d[67]), "+f"(d[68]), "+f"(d[69]), "+f"(d[70]), "+f"(d[71]), "+f"(d[72]), "+f"(d[73]), "+f"(d[74]), "+f"(d[75]), "+f"(d[76]), "+f"(d[77]), "+f"(d[78]), "+f"(d[79]), "+f"(d[80]), "+f"(d[81]), "+f"(d[82]), "+f"(d[83]), "+f"(d[84]), "+f"(d[85]), "+f"(d[86]), "+f"(d[87]), "+f"(d[88]), "+f"(d[89]), "+f"(d[90]), "+f"(d[91]), "+f"(d[92]), "+f"(d[93]), "+f"(d[94]), "+f"(d[95]), "+f"(d[96]), "+f"(d[97]), "+f"(d[98]), "+f"(d[99]), "+f"(d[100]), "+f"(d[101]), "+f"(d[102]), "+f"(d[103]), "+f"(d[104]), "+f"(d[105]), "+f"(d[106]), "+f"(d[107]), "+f"(d[108]), "+f"(d[109]), "+f"(d[110]), "+f"(d[111]), "+f"(d[112]), "+f"(d[113]), "+f"(d[114]), "+f"(d[115]), "+f"(d[116]), "+f"(d[117]), "+f"(d[118]), "+f"(d[119]), "+f"(d[120]), "+f"(d[121]), "+f"(d[122]), "+f"(d[123]), "+f"(d[124]), "+f"(d[125]), "+f"(d[126]), "+f"(d[127])
    : "l"(da), "l"(db), "r"(scale_d), "n"(TB));
}
template<int TB> __device__ __forceinline__ void wgmma_ss_n128(float (&d)[64], uint64_t da, uint64_t db, int scale_d) {
  asm volatile("{\n.reg .pred p;\nsetp.ne.b32 p, %66, 0;\n"
    "wgmma.mma_async.sync.aligned.m64n128k16.f32.bf16.bf16 {%0, %1, %2, %3, %4, %5, %6, %7, %8, %9, %10, %11, %12, %13, %14, %15, %16, %17, %18, %19, %20, %21, %22, %23, %24, %25, %26, %27, %28, %29, %30, %31, %32, %33, %34, %35, %36, %37, %38, %39, %40, %41, %42, %43, %44, %45, %46, %47, %48, %49, %50, %51, %52, %53, %54, %55, %56, %57, %58, %59, %60, %61, %62, %63}, %64, %65, p, 1, 1, 0, %67;\n}\n"
    : "+f"(d[0]), "+f"(d[1]), "+f"(d[2]), "+f"(d[3]), "+f"(d[4]), "+f"(d[5]), "+f"(d[6]), "+f"(d[7]), "+f"(d[8]), "+f"(d[9]), "+f"(d[10]), "+f"(d[11]), "+f"(d[12]), "+f"(d[13]), "+f"(d[14]), "+f"(d[15]), "+f"(d[16]), "+f"(d[17]), "+f"(d[18]), "+f"(d[19]), "+f"(d[20]), "+f"(d[21]), "+f"(d[22]), "+f"(d[23]), "+f"(d[24]), "+f"(d[25]), "+f"(d[26]), "+f"(d[27]), "+f"(d[28]), "+f"(d[29]), "+f"(d[30]), "+f"(d[31]), "+f"(d[32]), "+f"(d[33]), "+f"(d[34]), "+f"(d[35]), "+f"(d[36]), "+f"(d[37]), "+f"(d[38]), "+f"(d[39]), "+f"(d[40]), "+f"(d[41]), "+f"(d[42]), "+f"(d[43]), "+f"(d[44]), "+f"(d[45]), "+f"(d[46]), "+f"(d[47]), "+f"(d[48]), "+f"(d[49]), "+f"(d[50]), "+f"(d[51]), "+f"(d[52]), "+f"(d[53]), "+f"(d[54]), "+f"(d[55]), "+f"(d[56]), "+f"(d[57]), "+f"(d[58]), "+f"(d[59]), "+f"(d[60]), "+f"(d[61]), "+f"(d[62]), "+f"(d[63])
    : "l"(da), "l"(db), "r"(scale_d), "n"(TB));
}
template<int TB> __device__ __forceinline__ void wgmma_rs_n32(float (&d)[16], uint32_t a0, uint32_t a1, uint32_t a2, uint32_t a3, uint64_t db, int scale_d) {
  asm volatile("{\n.reg .pred p;\nsetp.ne.b32 p, %21, 0;\n"
    "wgmma.mma_async.sync.aligned.m64n32k16.f32.bf16.bf16 {%0, %1, %2, %3, %4, %5, %6, %7, %8, %9, %10, %11, %12, %13, %14, %15}, {%16, %17, %18, %19}, %20, p, 1, 1, %22;\n}\n"
    : "+f"(d[0]), "+f"(d[1]), "+f"(d[2]), "+f"(d[3]), "+f"(d[4]), "+f"(d[5]), "+f"(d[6]), "+f"(d[7]), "+f"(d[8]), "+f"(d[9]), "+f"(d[10]), "+f"(d[11]), "+f"(d[12]), "+f"(d[13]), "+f"(d[14]), "+f"(d[15])
    : "r"(a0), "r"(a1), "r"(a2), "r"(a3), "l"(db), "r"(scale_d), "n"(TB));
}
__device__ __forceinline__ void wgmma_pv_sel(float (&d)[64], const uint32_t (&p)[32], uint64_t db, int full, int acc) {
  asm volatile("{\n.reg .pred q, s;\n.reg .b64 t;\nsetp.ne.b32 s, %98, 0;\nsetp.eq.b32 q, %97, 0;\n@q bra.uni LH;\n"
    "wgmma.fence.sync.aligned;\n"
    "add.s64 t, %96, 0;\nwgmma.mma_async.sync.aligned.m64n128k16.f32.bf16.bf16 {%0, %1, %2, %3, %4, %5, %6, %7, %8, %9, %10, %11, %12, %13, %14, %15, %16, %17, %18, %19, %20, %21, %22, %23, %24, %25, %26, %27, %28, %29, %30, %31, %32, %33, %34, %35, %36, %37, %38, %39, %40, %41, %42, %43, %44, %45, %46, %47, %48, %49, %50, %51, %52, %53, %54, %55, %56, %57, %58, %59, %60, %61, %62, %63}, {%64, %65, %66, %67}, t, s, 1, 1, 1;\n"
    "add.s64 t, %96, 256;\nwgmma.mma_async.sync.aligned.m64n128k16.f32.bf16.bf16 {%0, %1, %2, %3, %4, %5, %6, %7, %8, %9, %10, %11, %12, %13, %14, %15, %16, %17, %18, %19, %20, %21, %22, %23, %24, %25, %26, %27, %28, %29, %30, %31, %32, %33, %34, %35, %36, %37, %38, %39, %40, %41, %42, %43, %44, %45, %46, %47, %48, %49, %50, %51, %52, %53, %54, %55, %56, %57, %58, %59, %60, %61, %62, %63}, {%68, %69, %70, %71}, t, 1, 1, 1, 1;\n"
    "add.s64 t, %96, 512;\nwgmma.mma_async.sync.aligned.m64n128k16.f32.bf16.bf16 {%0, %1, %2, %3, %4, %5, %6, %7, %8, %9, %10, %11, %12, %13, %14, %15, %16, %17, %18, %19, %20, %21, %22, %23, %24, %25, %26, %27, %28, %29, %30, %31, %32, %33, %34, %35, %36, %37, %38, %39, %40, %41, %42, %43, %44, %45, %46, %47, %48, %49, %50, %51, %52, %53, %54, %55, %56, %57, %58, %59, %60, %61, %62, %63}, {%72, %73, %74, %75}, t, 1, 1, 1, 1;\n"
    "add.s64 t, %96, 768;\nwgmma.mma_async.sync.aligned.m64n128k16.f32.bf16.bf16 {%0, %1, %2, %3, %4, %5, %6, %7, %8, %9, %10, %11, %12, %13, %14, %15, %16, %17, %18, %19, %20, %21, %22, %23, %24, %25, %26, %27, %28, %29, %30, %31, %32, %33, %34, %35, %36, %37, %38, %39, %40, %41, %42, %43, %44, %45, %46, %47, %48, %49, %50, %51, %52, %53, %54, %55, %56, %57, %58, %59, %60, %61, %62, %63}, {%76, %77, %78, %79}, t, 1, 1, 1, 1;\n"
    "add.s64 t, %96, 1024;\nwgmma.mma_async.sync.aligned.m64n128k16.f32.bf16.bf16 {%0, %1, %2, %3, %4, %5, %6, %7, %8, %9, %10, %11, %12, %13, %14, %15, %16, %17, %18, %19, %20, %21, %22, %23, %24, %25, %26, %27, %28, %29, %30, %31, %32, %33, %34, %35, %36, %37, %38, %39, %40, %41, %42, %43, %44, %45, %46, %47, %48, %49, %50, %51, %52, %53, %54, %55, %56, %57, %58, %59, %60, %61, %62, %63}, {%80, %81, %82, %83}, t, 1, 1, 1, 1;\n"
    "add.s64 t, %96, 1280;\nwgmma.mma_async.sync.aligned.m64n128k16.f32.bf16.bf16 {%0, %1, %2, %3, %4, %5, %6, %7, %8, %9, %10, %11, %12, %13, %14, %15, %16, %17, %18, %19, %20, %21, %22, %23, %24, %25, %26, %27, %28, %29, %30, %31, %32, %33, %34, %35, %36, %37, %38, %39, %40, %41, %42, %43, %44, %45, %46, %47, %48, %49, %50, %51, %52, %53, %54, %55, %56, %57, %58, %59, %60, %61, %62, %63}, {%84, %85, %86, %87}, t, 1, 1, 1, 1;\n"
    "add.s64 t, %96, 1536;\nwgmma.mma_async.sync.aligned.m64n128k16.f32.bf16.bf16 {%0, %1, %2, %3, %4, %5, %6, %7, %8, %9, %10, %11, %12, %13, %14, %15, %16, %17, %18, %19, %20, %21, %22, %23, %24, %25, %26, %27, %28, %29, %30, %31, %32, %33, %34, %35, %36, %37, %38, %39, %40, %41, %42, %43, %44, %45, %46, %47, %48, %49, %50, %51, %52, %53, %54, %55, %56, %57, %58, %59, %60, %61, %62, %63}, {%88, %89, %90, %91}, t, 1, 1, 1, 1;\n"
    "add.s64 t, %96, 1792;\nwgmma.mma_async.sync.aligned.m64n128k16.f32.bf16.bf16 {%0, %1, %2, %3, %4, %5, %6, %7, %8, %9, %10, %11, %12, %13, %14, %15, %16, %17, %18, %19, %20, %21, %22, %23, %24, %25, %26, %27, %28, %29, %30, %31, %32, %33, %34, %35, %36, %37, %38, %39, %40, %41, %42, %43, %44, %45, %46, %47, %48, %49, %50, %51, %52, %53, %54, %55, %56, %57, %58, %59, %60, %61, %62, %63}, {%92, %93, %94, %95}, t, 1, 1, 1, 1;\n"
    "wgmma.commit_group.sync.aligned;\n"
    "bra.uni LE;\nLH:\n"
    "wgmma.fence.sync.aligned;\n"
    "add.s64 t, %96, 0;\nwgmma.mma_async.sync.aligned.m64n128k16.f32.bf16.bf16 {%0, %1, %2, %3, %4, %5, %6, %7, %8, %9, %10, %11, %12, %13, %14, %15, %16, %17, %18, %19, %20, %21, %22, %23, %24, %25, %26, %27, %28, %29, %30, %31, %32, %33, %34, %35, %36, %37, %38, %39, %40, %41, %42, %43, %44, %45, %46, %47, %48, %49, %50, %51, %52, %53, %54, %55, %56, %57, %58, %59, %60, %61, %62, %63}, {%80, %81, %82, %83}, t, s, 1, 1, 1;\n"
    "add.s64 t, %96, 256;\nwgmma.mma_async.sync.aligned.m64n128k16.f32.bf16.bf16 {%0, %1, %2, %3, %4, %5, %6, %7, %8, %9, %10, %11, %12, %13, %14, %15, %16, %17, %18, %19, %20, %21, %22, %23, %24, %25, %26, %27, %28, %29, %30, %31, %32, %33, %34, %35, %36, %37, %38, %39, %40, %41, %42, %43, %44, %45, %46, %47, %48, %49, %50, %51, %52, %53, %54, %55, %56, %57, %58, %59, %60, %61, %62, %63}, {%84, %85, %86, %87}, t, 1, 1, 1, 1;\n"
    "add.s64 t, %96, 512;\nwgmma.mma_async.sync.aligned.m64n128k16.f32.bf16.bf16 {%0, %1, %2, %3, %4, %5, %6, %7, %8, %9, %10, %11, %12, %13, %14, %15, %16, %17, %18, %19, %20, %21, %22, %23, %24, %25, %26, %27, %28, %29, %30, %31, %32, %33, %34, %35, %36, %37, %38, %39, %40, %41, %42, %43, %44, %45, %46, %47, %48, %49, %50, %51, %52, %53, %54, %55, %56, %57, %58, %59, %60, %61, %62, %63}, {%88, %89, %90, %91}, t, 1, 1, 1, 1;\n"
    "add.s64 t, %96, 768;\nwgmma.mma_async.sync.aligned.m64n128k16.f32.bf16.bf16 {%0, %1, %2, %3, %4, %5, %6, %7, %8, %9, %10, %11, %12, %13, %14, %15, %16, %17, %18, %19, %20, %21, %22, %23, %24, %25, %26, %27, %28, %29, %30, %31, %32, %33, %34, %35, %36, %37, %38, %39, %40, %41, %42, %43, %44, %45, %46, %47, %48, %49, %50, %51, %52, %53, %54, %55, %56, %57, %58, %59, %60, %61, %62, %63}, {%92, %93, %94, %95}, t, 1, 1, 1, 1;\n"
    "wgmma.commit_group.sync.aligned;\n"
    "LE:\n}\n"
    : "+f"(d[0]), "+f"(d[1]), "+f"(d[2]), "+f"(d[3]), "+f"(d[4]), "+f"(d[5]), "+f"(d[6]), "+f"(d[7]), "+f"(d[8]), "+f"(d[9]), "+f"(d[10]), "+f"(d[11]), "+f"(d[12]), "+f"(d[13]), "+f"(d[14]), "+f"(d[15]), "+f"(d[16]), "+f"(d[17]), "+f"(d[18]), "+f"(d[19]), "+f"(d[20]), "+f"(d[21]), "+f"(d[22]), "+f"(d[23]), "+f"(d[24]), "+f"(d[25]), "+f"(d[26]), "+f"(d[27]), "+f"(d[28]), "+f"(d[29]), "+f"(d[30]), "+f"(d[31]), "+f"(d[32]), "+f"(d[33]), "+f"(d[34]), "+f"(d[35]), "+f"(d[36]), "+f"(d[37]), "+f"(d[38]), "+f"(d[39]), "+f"(d[40]), "+f"(d[41]), "+f"(d[42]), "+f"(d[43]), "+f"(d[44]), "+f"(d[45]), "+f"(d[46]), "+f"(d[47]), "+f"(d[48]), "+f"(d[49]), "+f"(d[50]), "+f"(d[51]), "+f"(d[52]), "+f"(d[53]), "+f"(d[54]), "+f"(d[55]), "+f"(d[56]), "+f"(d[57]), "+f"(d[58]), "+f"(d[59]), "+f"(d[60]), "+f"(d[61]), "+f"(d[62]), "+f"(d[63])
    : "r"(p[0]), "r"(p[1]), "r"(p[2]), "r"(p[3]), "r"(p[4]), "r"(p[5]), "r"(p[6]), "r"(p[7]), "r"(p[8]), "r"(p[9]), "r"(p[10]), "r"(p[11]), "r"(p[12]), "r"(p[13]), "r"(p[14]), "r"(p[15]), "r"(p[16]), "r"(p[17]), "r"(p[18]), "r"(p[19]), "r"(p[20]), "r"(p[21]), "r"(p[22]), "r"(p[23]), "r"(p[24]), "r"(p[25]), "r"(p[26]), "r"(p[27]), "r"(p[28]), "r"(p[29]), "r"(p[30]), "r"(p[31]), "l"(db), "r"(full), "r"(acc) : "memory");
}

constexpr int NCTA = 132, NREG = 128;
constexpr int UNIT = 16384, NUNIT = 14;
constexpr uint32_t SMEM_BASE = 1024;
constexpr int SM_BAR = NUNIT * UNIT;
constexpr int SM_GATE = SM_BAR + 1024;
constexpr int SMEM_BYTES = SM_BAR + 1536;
constexpr int UPITCH = 4160, UCH = 2 * UPITCH;
constexpr float QSCALE = 0.08838834764831845f * 1.4426950408889634f;
constexpr float BOUND2 = 48.f * 48.f / 1.15f;
#define CONV_REG 5
constexpr int C_KV = 0;
constexpr int C_CTX = 32;
constexpr int C_U = 48;
constexpr int C_Z = 80;
constexpr int C_GATE = 88;
constexpr int C_EXIT = 89;
#define PRE_EARLY 2
#define PRE_HALF 1
#define ATT_SPLIT 6
#define NFIRST 2
#define PRE_DELAY 0
#define MAP_PF 1
#define FINAL_ST 1
#define Z_AT 60
#define PRE_DELAY_BAR 9
#define PRE_FMA 0
#define PRE_SLEEP 300
#define GATE_SLEEP 1000
#define GATE_EARLY 1
#define OC_S0 2
#define OC_S1 11
#define OC_POST 1
#define OC_L0 18
#define OC_L1 18
#define PF 0
#define PF_AT 26
#define PF_KS 8
#define ST_1 4
#define ST_D 2
#define ST_0 1
#define ST_0D 0
#define SCH_KV 0x6665544433221100ull
#define SCH_Q 0x6665544433221100ull
#define NK_AT 1
#ifndef NV_AT
#define NV_AT 3
#endif
#define DEFER_ST 1
#define DS_A 3
#define DS_B 6
#define XSLOT 1
#define LASTF 2
#define EF 127
#define POL(bit) (((EF >> (bit)) & 1) != 0)
constexpr int C_WAR = 96;
constexpr int C_NUM = 112;
constexpr int CSTRIDE = 32;
constexpr int SM_KMAX = SM_BAR + 640, SM_DUMMY = SM_BAR + 648, SM_PRE = SM_BAR + 112, SM_SIG = SM_BAR + 256, SM_RDY = SM_BAR + 384;
enum { SIG_KV = 0, SIG_CTX = 2, SIG_Z = 4, SIG_DONE = 8, SIG_WAR = 9, SIG_ATT = 10 };
enum { RDY_KV = 0, RDY_CTX = 2, RDY_WAR = 4, RDY_G = 5, RDY_X = 6, RDY_U = 8, RDY_Z = 9 };
enum { PH_PRE = 1, PH_KV = 2, PH_ATT = 4, PH_CONV = 8, PH_OUT = 16, PH_ALL = 31 };

constexpr uint32_t T_CTX = 0, T_KV = 16 * 32 * 32768, T_BYTES = T_KV + 32 * 16 * 65536;
__device__ __align__(1024) uint8_t g_T[T_BYTES];
__device__ __align__(1024) uint8_t g_u[1024 * UCH];
__device__ __align__(1024) __nv_bfloat16 g_z[1024 * 2048];
__device__ __align__(1024) float g_gate[2048];
__device__ __align__(1024) float g_kn2[32 * 128];
__device__ __align__(1024) unsigned g_cnt[C_NUM * CSTRIDE];

struct __align__(64) Maps { CUtensorMap c, wk, wv, x, wq, wo, h, z, out, ctx, k, v; };
struct Params {
  const __nv_bfloat16 *x, *shift, *D, *gw;
  __nv_bfloat16* out;
};

__device__ __forceinline__ void wg_fence() { asm volatile("wgmma.fence.sync.aligned;" ::: "memory"); }
__device__ __forceinline__ void wg_commit() { asm volatile("wgmma.commit_group.sync.aligned;" ::: "memory"); }
template<int N> __device__ __forceinline__ void wg_wait() { asm volatile("wgmma.wait_group.sync.aligned %0;" :: "n"(N) : "memory"); }
__device__ __forceinline__ uint64_t odesc(uint32_t addr, uint32_t lbo, uint32_t sbo, uint32_t swz) {
  uint64_t d = (uint64_t)(addr >> 4) + (((uint64_t)(lbo >> 4) << 16) | ((uint64_t)(sbo >> 4) << 32) | ((uint64_t)swz << 62));
  asm volatile("" : "+l"(d));
  return d;
}
__device__ __forceinline__ void mbar_init(uint32_t bar, int cnt) { asm volatile("mbarrier.init.shared::cta.b64 [%0], %1;" :: "r"(bar), "r"(cnt)); }
__device__ __forceinline__ void mbar_expect(uint32_t bar, uint32_t bytes) { asm volatile("mbarrier.arrive.expect_tx.shared::cta.b64 _, [%0], %1;" :: "r"(bar), "r"(bytes) : "memory"); }
__device__ __forceinline__ void mbar_arrive(uint32_t bar) { asm volatile("mbarrier.arrive.shared::cta.b64 _, [%0];" :: "r"(bar) : "memory"); }
__device__ __forceinline__ void mbar_arrive_n(uint32_t bar, int n) { asm volatile("mbarrier.arrive.shared::cta.b64 _, [%0], %1;" :: "r"(bar), "r"(n) : "memory"); }
__device__ __forceinline__ void mbar_wait(uint32_t bar, uint32_t parity) {
  asm volatile("{\n.reg .pred p;\nLW:\nmbarrier.try_wait.parity.shared::cta.b64 p, [%0], %1;\n@!p bra LW;\n}\n" :: "r"(bar), "r"(parity) : "memory");
}
__device__ __forceinline__ void mbar_wait_slow(uint32_t bar, uint32_t parity) {
  asm volatile("{\n.reg .pred p;\n.reg .u32 n;\nmov.u32 n, 0;\n"
    "LW:\nmbarrier.test_wait.parity.shared::cta.b64 p, [%0], %1;\n@p bra LD;\n"
    "nanosleep.u32 128;\nadd.u32 n, n, 1;\nsetp.lt.u32 p, n, 4194304;\n@p bra LW;\ntrap;\nLD:\n}\n" :: "r"(bar), "r"(parity) : "memory");
}
__device__ __forceinline__ void mbar_wait_all(uint32_t bar, uint32_t parity) {
  asm volatile("{\n.reg .pred p, q;\nLW:\nmbarrier.try_wait.parity.shared::cta.b64 p, [%0], %1;\nvote.sync.all.pred q, p, 0xffffffff;\n@!q bra.uni LW;\n}\n" :: "r"(bar), "r"(parity) : "memory");
}
__device__ __forceinline__ void cnt_wait(const unsigned* p, unsigned target) {
  asm volatile("{\n.reg .pred p;\n.reg .u32 n, v;\nmov.u32 n, 0;\n"
    "LW:\nld.relaxed.gpu.global.u32 v, [%0];\nsetp.ge.u32 p, v, %1;\n@p bra LD;\n"
    "nanosleep.u32 64;\nadd.u32 n, n, 1;\nsetp.lt.u32 p, n, 4194304;\n@p bra LW;\ntrap;\nLD:\nfence.acquire.gpu;\nfence.proxy.async.global;\n}\n" :: "l"(p), "r"(target) : "memory");
}
__device__ __forceinline__ void cnt_signal(unsigned* p, int lane) {
  __syncwarp();
  if (lane == 0) asm volatile("red.release.gpu.global.add.u32 [%0], 1;" :: "l"(p) : "memory");
}
__device__ __forceinline__ void cnt_publish(unsigned* p, unsigned n, bool fence) {
  if (fence) asm volatile("fence.release.gpu;" ::: "memory");
  asm volatile("red.relaxed.gpu.global.add.u32 [%0], %1;" :: "l"(p), "r"(n) : "memory");
}
__device__ __forceinline__ uint64_t pol_first() { uint64_t p; asm("createpolicy.fractional.L2::evict_first.b64 %0, 1.0;" : "=l"(p)); return p; }
__device__ __forceinline__ void bulk_g2s(uint32_t dst, const void* src, uint32_t bytes, uint32_t bar, bool stream = false) {
  if (stream) asm volatile("cp.async.bulk.shared::cluster.global.mbarrier::complete_tx::bytes.L2::cache_hint [%0], [%1], %2, [%3], %4;" :: "r"(dst), "l"(src), "r"(bytes), "r"(bar), "l"(pol_first()) : "memory");
  else asm volatile("cp.async.bulk.shared::cluster.global.mbarrier::complete_tx::bytes [%0], [%1], %2, [%3];" :: "r"(dst), "l"(src), "r"(bytes), "r"(bar) : "memory");
}
__device__ __forceinline__ void tma2d(uint32_t dst, const CUtensorMap* m, int x, int y, uint32_t bar, bool stream = false) {
  if (stream) asm volatile("cp.async.bulk.tensor.2d.shared::cluster.global.mbarrier::complete_tx::bytes.L2::cache_hint [%0], [%1, {%3, %4}], [%2], %5;" :: "r"(dst), "l"(m), "r"(bar), "r"(x), "r"(y), "l"(pol_first()) : "memory");
  else asm volatile("cp.async.bulk.tensor.2d.shared::cluster.global.mbarrier::complete_tx::bytes [%0], [%1, {%3, %4}], [%2];" :: "r"(dst), "l"(m), "r"(bar), "r"(x), "r"(y) : "memory");
}
__device__ __forceinline__ void tma3d(uint32_t dst, const CUtensorMap* m, int x, int y, int z, uint32_t bar, bool stream = false) {
  if (stream) asm volatile("cp.async.bulk.tensor.3d.shared::cluster.global.mbarrier::complete_tx::bytes.L2::cache_hint [%0], [%1, {%3, %4, %5}], [%2], %6;" :: "r"(dst), "l"(m), "r"(bar), "r"(x), "r"(y), "r"(z), "l"(pol_first()) : "memory");
  else asm volatile("cp.async.bulk.tensor.3d.shared::cluster.global.mbarrier::complete_tx::bytes [%0], [%1, {%3, %4, %5}], [%2];" :: "r"(dst), "l"(m), "r"(bar), "r"(x), "r"(y), "r"(z) : "memory");
}
__device__ __forceinline__ void tma4d(uint32_t dst, const CUtensorMap* m, int x, int y, int z, int w, uint32_t bar, bool stream = false) {
  if (stream) asm volatile("cp.async.bulk.tensor.4d.shared::cluster.global.mbarrier::complete_tx::bytes.L2::cache_hint [%0], [%1, {%3, %4, %5, %6}], [%2], %7;" :: "r"(dst), "l"(m), "r"(bar), "r"(x), "r"(y), "r"(z), "r"(w), "l"(pol_first()) : "memory");
  else asm volatile("cp.async.bulk.tensor.4d.shared::cluster.global.mbarrier::complete_tx::bytes [%0], [%1, {%3, %4, %5, %6}], [%2];" :: "r"(dst), "l"(m), "r"(bar), "r"(x), "r"(y), "r"(z), "r"(w) : "memory");
}
__device__ __forceinline__ void bulk_g2s_mc(uint32_t dst, const void* src, uint32_t bytes, uint32_t bar, bool stream = false) {
  if (stream) asm volatile("cp.async.bulk.shared::cluster.global.mbarrier::complete_tx::bytes.multicast::cluster.L2::cache_hint [%0], [%1], %2, [%3], %4, %5;" :: "r"(dst), "l"(src), "r"(bytes), "r"(bar), "h"((uint16_t)3), "l"(pol_first()) : "memory");
  else asm volatile("cp.async.bulk.shared::cluster.global.mbarrier::complete_tx::bytes.multicast::cluster [%0], [%1], %2, [%3], %4;" :: "r"(dst), "l"(src), "r"(bytes), "r"(bar), "h"((uint16_t)3) : "memory");
}
__device__ __forceinline__ void tma2d_mc(uint32_t dst, const CUtensorMap* m, int x, int y, uint32_t bar, bool stream = false) {
  if (stream) asm volatile("cp.async.bulk.tensor.2d.shared::cluster.global.mbarrier::complete_tx::bytes.multicast::cluster.L2::cache_hint [%0], [%1, {%3, %4}], [%2], %5, %6;" :: "r"(dst), "l"(m), "r"(bar), "r"(x), "r"(y), "h"((uint16_t)3), "l"(pol_first()) : "memory");
  else asm volatile("cp.async.bulk.tensor.2d.shared::cluster.global.mbarrier::complete_tx::bytes.multicast::cluster [%0], [%1, {%3, %4}], [%2], %5;" :: "r"(dst), "l"(m), "r"(bar), "r"(x), "r"(y), "h"((uint16_t)3) : "memory");
}
__device__ __forceinline__ void tma3d_mc(uint32_t dst, const CUtensorMap* m, int x, int y, int z, uint32_t bar, bool stream = false) {
  if (stream) asm volatile("cp.async.bulk.tensor.3d.shared::cluster.global.mbarrier::complete_tx::bytes.multicast::cluster.L2::cache_hint [%0], [%1, {%3, %4, %5}], [%2], %6, %7;" :: "r"(dst), "l"(m), "r"(bar), "r"(x), "r"(y), "r"(z), "h"((uint16_t)3), "l"(pol_first()) : "memory");
  else asm volatile("cp.async.bulk.tensor.3d.shared::cluster.global.mbarrier::complete_tx::bytes.multicast::cluster [%0], [%1, {%3, %4, %5}], [%2], %6;" :: "r"(dst), "l"(m), "r"(bar), "r"(x), "r"(y), "r"(z), "h"((uint16_t)3) : "memory");
}
__device__ __forceinline__ void pf3d(const CUtensorMap* m, int x, int y, int z) {
  asm volatile("cp.async.bulk.prefetch.tensor.3d.L2.global [%0, {%1, %2, %3}];" :: "l"(m), "r"(x), "r"(y), "r"(z) : "memory");
}
__device__ __forceinline__ void pf_bulk(const void* p, uint32_t bytes) { asm volatile("cp.async.bulk.prefetch.L2.global [%0], %1;" :: "l"(p), "r"(bytes) : "memory"); }
__device__ __forceinline__ void tma2d_store(const CUtensorMap* m, uint32_t src, int x, int y) {
  if (POL(12)) asm volatile("cp.async.bulk.tensor.2d.global.shared::cta.bulk_group.L2::cache_hint [%0, {%2, %3}], [%1], %4;" :: "l"(m), "r"(src), "r"(x), "r"(y), "l"(pol_first()) : "memory");
  else asm volatile("cp.async.bulk.tensor.2d.global.shared::cta.bulk_group [%0, {%2, %3}], [%1];" :: "l"(m), "r"(src), "r"(x), "r"(y) : "memory");
}
__device__ __forceinline__ bool elect() {
  uint32_t r; asm volatile("{\n.reg .pred p;\nelect.sync _|p, 0xffffffff;\nselp.u32 %0, 1, 0, p;\n}\n" : "=r"(r)); return r != 0;
}
__device__ __forceinline__ void cluster_arrive() { asm volatile("barrier.cluster.arrive;" ::: "memory"); }
__device__ __forceinline__ void cluster_wait() { asm volatile("barrier.cluster.wait;" ::: "memory"); }
__device__ __forceinline__ void bar_sync(int id, int n) { asm volatile("bar.sync %0, %1;" :: "r"(id), "r"(n) : "memory"); }
__device__ __forceinline__ void bar_arrive(int id, int n) { asm volatile("bar.arrive %0, %1;" :: "r"(id), "r"(n) : "memory"); }
__device__ __forceinline__ int bar_and(int id, int n, int pred) {
  int r; asm volatile("{\n.reg .pred p, q;\nsetp.ne.b32 p, %3, 0;\nbar.red.and.pred q, %1, %2, p;\nselp.b32 %0, 1, 0, q;\n}\n" : "=r"(r) : "r"(id), "r"(n), "r"(pred) : "memory");
  return r;
}
__device__ __forceinline__ void fence_async_smem() { asm volatile("fence.proxy.async.shared::cta;" ::: "memory"); }
__device__ __forceinline__ float ex2(float x) { float y; asm("ex2.approx.ftz.f32 %0, %1;" : "=f"(y) : "f"(x)); return y; }
__device__ __forceinline__ uint32_t pack_bf16(float lo, float hi) { uint32_t r; asm("cvt.rn.bf16x2.f32 %0, %1, %2;" : "=r"(r) : "f"(hi), "f"(lo)); return r; }
__device__ __forceinline__ uint32_t hmul2(uint32_t a, uint32_t b) { uint32_t r; asm("mul.rn.bf16x2 %0, %1, %2;" : "=r"(r) : "r"(a), "r"(b)); return r; }
__device__ __forceinline__ uint32_t hadd2(uint32_t a, uint32_t b) { uint32_t r; asm("add.rn.bf16x2 %0, %1, %2;" : "=r"(r) : "r"(a), "r"(b)); return r; }
__device__ __forceinline__ uint32_t hfma2(uint32_t a, uint32_t b, uint32_t c) { uint32_t r; asm("fma.rn.bf16x2 %0, %1, %2, %3;" : "=r"(r) : "r"(a), "r"(b), "r"(c)); return r; }
__device__ __forceinline__ float bf_lo(uint32_t a) { return __uint_as_float(a << 16); }
__device__ __forceinline__ float bf_hi(uint32_t a) { return __uint_as_float(a & 0xffff0000u); }
__device__ __forceinline__ uint32_t lds32(uint32_t a) { uint32_t v; asm volatile("ld.shared.u32 %0, [%1];" : "=r"(v) : "r"(a) : "memory"); return v; }
__device__ __forceinline__ float2 lds64f(uint32_t a) { float2 v; asm volatile("ld.shared.v2.f32 {%0,%1}, [%2];" : "=f"(v.x), "=f"(v.y) : "r"(a) : "memory"); return v; }
__device__ __forceinline__ uint4 lds128(uint32_t a) { uint4 v; asm volatile("ld.shared.v4.u32 {%0,%1,%2,%3}, [%4];" : "=r"(v.x), "=r"(v.y), "=r"(v.z), "=r"(v.w) : "r"(a) : "memory"); return v; }
__device__ __forceinline__ void sts64f(uint32_t a, float x, float y) { asm volatile("st.shared.v2.f32 [%0], {%1,%2};" :: "r"(a), "f"(x), "f"(y) : "memory"); }
__device__ __forceinline__ void sts128(uint32_t a, uint4 v) { asm volatile("st.shared.v4.u32 [%0], {%1,%2,%3,%4};" :: "r"(a), "r"(v.x), "r"(v.y), "r"(v.z), "r"(v.w) : "memory"); }
template<int OFF> __device__ __forceinline__ void sts128o(uint32_t a, uint4 v) { asm volatile("st.shared.v4.u32 [%0+%5], {%1,%2,%3,%4};" :: "r"(a), "r"(v.x), "r"(v.y), "r"(v.z), "r"(v.w), "n"(OFF) : "memory"); }
__device__ __forceinline__ void ldsm4(uint32_t a, uint32_t& r0, uint32_t& r1, uint32_t& r2, uint32_t& r3) {
  asm volatile("ldmatrix.sync.aligned.m8n8.x4.shared.b16 {%0,%1,%2,%3}, [%4];" : "=r"(r0), "=r"(r1), "=r"(r2), "=r"(r3) : "r"(a) : "memory");
}
__device__ __forceinline__ void ldsm4t(uint32_t a, uint32_t& r0, uint32_t& r1, uint32_t& r2, uint32_t& r3) {
  asm volatile("ldmatrix.sync.aligned.m8n8.x4.trans.shared.b16 {%0,%1,%2,%3}, [%4];" : "=r"(r0), "=r"(r1), "=r"(r2), "=r"(r3) : "r"(a) : "memory");
}
__device__ __forceinline__ void stsm4(uint32_t a, uint32_t r0, uint32_t r1, uint32_t r2, uint32_t r3) {
  asm volatile("stmatrix.sync.aligned.m8n8.x4.shared.b16 [%0], {%1,%2,%3,%4};" :: "r"(a), "r"(r0), "r"(r1), "r"(r2), "r"(r3) : "memory");
}
template<int N> __device__ __forceinline__ void fence_regs(float (&d)[N]) {
#pragma unroll
  for (int i = 0; i < N; i++) asm volatile("" : "+f"(d[i]) :: "memory");
}
template<int N> __device__ __forceinline__ void fence_regs(uint32_t (&d)[N]) {
#pragma unroll
  for (int i = 0; i < N; i++) asm volatile("" : "+r"(d[i]) :: "memory");
}
__device__ __forceinline__ void sched_fence(float x, uint32_t dummy) {
  asm volatile("{\n.reg .pred p;\nsetp.eq.u32 p, %0, 0x7fc12345;\n@p st.shared.u32 [%1], %0;\n}\n" :: "r"(__float_as_uint(x)), "r"(dummy) : "memory");
}
#define ROT 0
#define CTAID blockIdx.x
#define TS(role, i)
#define TSA(i)
#define TR(obj, role, tag)

#define SHADOW if (gridDim.y == 1)

struct Prod {
  uint32_t base, mask; int lane, nt;
  __device__ __forceinline__ uint32_t full(int u) const { return base + SM_BAR + 8 * u; }
  __device__ __forceinline__ uint32_t addr(int u) const { return base + u * UNIT; }
  __device__ __forceinline__ void acquire(int u, int n) {
    const int v = u + min(lane, n - 1);
    mbar_wait_all(base + SM_BAR + 128 + 8 * v, mask >> v);
    mask ^= ((1u << n) - 1) << u;
    TR(*this, 2, 16 + u);
  }
  __device__ __forceinline__ void acquire_slow(int u, int n) {
    for (int i = 0; i < n; i++) mbar_wait_slow(base + SM_BAR + 128 + 8 * (u + i), mask >> (u + i));
    mask ^= ((1u << n) - 1) << u;
  }
};
struct Cons {
  uint32_t base, rel, mask; int lane, warp, wg, nt;
  __device__ __forceinline__ uint32_t addr(int u) const { return base + u * UNIT; }
  __device__ __forceinline__ static uint32_t daddr(int u) { return SMEM_BASE + u * UNIT; }
  __device__ __forceinline__ void wait(int u) { TR(*this, wg, 1); mbar_wait(base + SM_BAR + 8 * u, mask >> u); mask ^= 1u << u; TR(*this, wg, 2); }
  __device__ __forceinline__ void skip(int u) { mask ^= 1u << u; }
  __device__ __forceinline__ void release(int u, int n) {
    TR(*this, wg, 5);
    asm volatile("{\n.reg .pred p;\nsetp.lt.s32 p, %1, %2;\n@p mbarrier.arrive.shared::cluster.b64 _, [%0];\n}\n" :: "r"(rel + 8 * u), "r"(lane & 15), "r"(n) : "memory");
  }
  __device__ __forceinline__ void release2(int u) {
    asm volatile("{\n.reg .pred p;\nsetp.eq.s32 p, %1, 0;\n@p mbarrier.arrive.shared::cluster.b64 _, [%0], 2;\n}\n" :: "r"(rel + 8 * u), "r"(lane & 15) : "memory");
  }
  __device__ __forceinline__ void signal(int i) {
    __syncwarp();
    asm volatile("{\n.reg .pred p;\nsetp.eq.s32 p, %1, 0;\n@p mbarrier.arrive.shared::cta.b64 _, [%0];\n}\n" :: "r"(base + SM_SIG + 8 * i), "r"(lane) : "memory");
  }
  __device__ __forceinline__ void turn() { bar_sync(1 + wg, 256); TR(*this, wg, 3); }
  __device__ __forceinline__ void pass() { bar_arrive(2 - wg, 256); TR(*this, wg, 4); }
};
__device__ __forceinline__ int gemm_unit(int ks) { return 3 * (ks & 3); }
__device__ __forceinline__ int att_slot(int i) { return 4 + 2 * i; }
template<int MASK> __device__ __forceinline__ int kv_slot(int h) { return MASK == PH_ALL ? h & 15 : h; }
__device__ __forceinline__ int out_mb(int cta) { return cta >> 3; }
__device__ __forceinline__ int out_nb(int cta) { return cta & 7; }
template<int MASK> constexpr int CV_REG = MASK == PH_ALL ? CONV_REG : 6;
template<int MASK> constexpr int CV_EXTRA = (1024 - NREG * CV_REG<MASK>) / (NCTA - NREG);
template<int MASK> __device__ __forceinline__ int conv_channel(int cta, int i) {
  return cta < NREG ? CV_EXTRA<MASK> * (NCTA - NREG) + cta * CV_REG<MASK> + i : (i >> 1) * 8 + (cta - NREG) * 2 + (i & 1);
}

template<int OFF, int N> __device__ __forceinline__ void pack_chunk(const float (&a)[N], float sc0, float sc1, uint4& v0, uint4& v1) {
  v0.x = pack_bf16(a[OFF + 0] * sc0, a[OFF + 1] * sc0); v0.y = pack_bf16(a[OFF + 4] * sc0, a[OFF + 5] * sc0);
  v0.z = pack_bf16(a[OFF + 8] * sc0, a[OFF + 9] * sc0); v0.w = pack_bf16(a[OFF + 12] * sc0, a[OFF + 13] * sc0);
  v1.x = pack_bf16(a[OFF + 2] * sc1, a[OFF + 3] * sc1); v1.y = pack_bf16(a[OFF + 6] * sc1, a[OFF + 7] * sc1);
  v1.z = pack_bf16(a[OFF + 10] * sc1, a[OFF + 11] * sc1); v1.w = pack_bf16(a[OFF + 14] * sc1, a[OFF + 15] * sc1);
}
template<int OFF, int N> __device__ __forceinline__ void pack_chunk(const float (&a)[N], uint4& v0, uint4& v1) {
  v0.x = pack_bf16(a[OFF + 0], a[OFF + 1]); v0.y = pack_bf16(a[OFF + 4], a[OFF + 5]);
  v0.z = pack_bf16(a[OFF + 8], a[OFF + 9]); v0.w = pack_bf16(a[OFF + 12], a[OFF + 13]);
  v1.x = pack_bf16(a[OFF + 2], a[OFF + 3]); v1.y = pack_bf16(a[OFF + 6], a[OFF + 7]);
  v1.z = pack_bf16(a[OFF + 10], a[OFF + 11]); v1.w = pack_bf16(a[OFF + 14], a[OFF + 15]);
}
__device__ __forceinline__ void sq_acc(const uint4& v, uint32_t& a) { a = hfma2(v.x, v.x, a); a = hfma2(v.y, v.y, a); a = hfma2(v.z, v.z, a); a = hfma2(v.w, v.w, a); }
__device__ __forceinline__ float norm2_max(uint32_t a0, uint32_t a1) {
  float n0 = bf_lo(a0) + bf_hi(a0), n1 = bf_lo(a1) + bf_hi(a1);
  n0 += __shfl_xor_sync(~0u, n0, 1); n1 += __shfl_xor_sync(~0u, n1, 1);
  n0 += __shfl_xor_sync(~0u, n0, 2); n1 += __shfl_xor_sync(~0u, n1, 2);
  return __uint_as_float(__reduce_max_sync(~0u, max(__float_as_uint(n0) & 0x7fffffffu, __float_as_uint(n1) & 0x7fffffffu)));
}

struct Pend { uint4 lo[8], hi[8]; uint32_t dst; float kn; };
__device__ __forceinline__ void pin(uint4 (&v)[8]) {
#pragma unroll
  for (int i = 0; i < 8; i++) asm volatile("" : "+r"(v[i].x), "+r"(v[i].y), "+r"(v[i].z), "+r"(v[i].w) :: "memory");
}
__device__ __forceinline__ uint32_t atom_off(int lane) { return (lane >> 2) * 64 + (((lane ^ (lane >> 3)) & 3) << 4); }
__device__ __forceinline__ void stg128(void* p, const uint4& v, bool stream) {
  if (stream) asm volatile("st.global.L2::cache_hint.v4.u32 [%0], {%1,%2,%3,%4}, %5;" :: "l"(p), "r"(v.x), "r"(v.y), "r"(v.z), "r"(v.w), "l"(pol_first()) : "memory");
  else *(uint4*)p = v;
}
template<int J0, int J1, bool STREAM = false> __device__ __forceinline__ void tile_store(const uint4 (&v)[8], uint32_t dst, int lane) {
  uint8_t* d = g_T + (dst + atom_off(lane));
#pragma unroll
  for (int j = J0; j < J1; j++) { stg128(d + j * 512, v[2 * j], STREAM); stg128(d + j * 512 + 2048, v[2 * j + 1], STREAM); }
}
template<int I0, int I1> __device__ __forceinline__ void tile_store_if(bool on, const uint4 (&v)[8], uint32_t dst, int lane) {
  if constexpr (I0 < I1) {
    asm volatile("{\n.reg .pred p;\nsetp.ne.b32 p, %5, 0;\n@p st.global.v4.u32 [%0+%6], {%1,%2,%3,%4};\n}\n"
      :: "l"(g_T + (dst + atom_off(lane))), "r"(v[I0].x), "r"(v[I0].y), "r"(v[I0].z), "r"(v[I0].w), "r"((int)on), "n"((I0 >> 1) * 512 + (I0 & 1) * 2048) : "memory");
    tile_store_if<I0 + 1, I1>(on, v, dst, lane);
  }
}
__device__ __forceinline__ float tile_norm2(const uint4 (&v)[8]) {
  uint32_t n0 = 0, n1 = 0, n2 = 0, n3 = 0;
#pragma unroll
  for (int j = 0; j < 2; j++) { sq_acc(v[2 * j], n0); sq_acc(v[2 * j + 1], n1); sq_acc(v[2 * j + 4], n2); sq_acc(v[2 * j + 5], n3); }
  return norm2_max(hadd2(n0, n2), hadd2(n1, n3));
}
template<uint64_t SCHED, bool FIRST> __device__ __forceinline__ void out_piece(Cons& c, Pend& w, int ks, bool both) {
  uint8_t* d = g_T + (w.dst + atom_off(c.lane));
#pragma unroll
  for (int i = 0; i < 16; i++) {
    const int at = (SCHED >> (4 * i)) & 15;
    if (FIRST ? at == 0 : (at > 0 && ks == at && (i < 8 || both))) *(uint4*)(d + (i >> 3) * 32768 + ((i >> 1) & 3) * 512 + (i & 1) * 2048) = i < 8 ? w.lo[i & 7] : w.hi[i & 7];
  }
  if (FIRST || !both) return;
  if (ks == NK_AT) w.kn = tile_norm2(w.lo);
  if (ks == NV_AT) {
    const float vn = tile_norm2(w.hi);
    if (c.lane == 0) g_kn2[((w.dst - T_KV) >> 16) * 8 + c.wg * 4 + c.warp] = (vn <= 1.0e30f && vn >= 1.0e-30f) ? w.kn : __uint_as_float(0x7f800000u);
  }
}
template<bool FIRST> __device__ __forceinline__ void kv_issue(Cons& c, float (&acc)[128], int u) {
  const uint64_t da = odesc(c.daddr(u) + c.wg * 8192, 16, 1024, 1), db = odesc(c.daddr(u + 1), 8192, 1024, 1);
  c.turn();
  wg_fence();
#pragma unroll
  for (int kk = 0; kk < 4; kk++) wgmma_ss_n256<1>(acc, da + kk * 2, db + kk * 128, !(FIRST && kk == 0));
  wg_commit();
  c.pass();
}
template<bool NEXT> __device__ __forceinline__ void cons_kv(Cons& c, int h, int hs, int g, Pend& w, bool pend_o) {
#pragma unroll 1
  for (int tile = 0; tile < 2; tile++) {
    float acc[128];
    if (tile == 0) c.wait(0);
    if (tile == 0 && h < 16) TS(c.wg, 16);
    kv_issue<true>(c, acc, 0);
    c.release(9, tile == 1 ? 3 : 0);
    if (tile == 1 && pend_o) mbar_wait(c.base + SM_RDY + 8 * RDY_WAR, 0);
    if (tile == 1 || pend_o) out_piece<SCH_KV, true>(c, w, 0, false);
#pragma unroll 1
    for (int ks = 1; ks < 8; ks++) {
      const int u = gemm_unit(ks);
      c.wait(u);
      wg_wait<0>();
      c.release(gemm_unit(ks - 1), 3);
      kv_issue<false>(c, acc, u);
      if (tile == 1 || pend_o) { out_piece<SCH_KV, false>(c, w, ks, tile); if (ks == ((SCH_KV >> 28) & 15) && tile == 0) c.signal(SIG_CTX); }
    }
    if (NEXT || tile == 0) c.wait(0);
    wg_wait<0>(); fence_regs(acc);
    if (!NEXT) c.release(9, tile == 1 ? 3 : 0);
    pack_chunk<0>(acc, w.lo[0], w.lo[1]);  pack_chunk<16>(acc, w.lo[2], w.lo[3]); pack_chunk<32>(acc, w.lo[4], w.lo[5]); pack_chunk<48>(acc, w.lo[6], w.lo[7]);
    pack_chunk<64>(acc, w.hi[0], w.hi[1]); pack_chunk<80>(acc, w.hi[2], w.hi[3]); pack_chunk<96>(acc, w.hi[4], w.hi[5]); pack_chunk<112>(acc, w.hi[6], w.hi[7]);
    pin(w.lo); pin(w.hi);
    w.dst = T_KV + (hs * 16 + 2 * g + tile) * 65536 + (c.wg * 4 + c.warp) * 4096;
  }
}
template<bool FIRST> __device__ __forceinline__ void q_issue(Cons& c, float (&a)[64], float (&b)[64], int u) {
  const uint64_t da = odesc(c.daddr(u) + c.wg * 8192, 16, 1024, 1), db = odesc(c.daddr(u + 2), 8192, 1024, 1);
  const uint64_t da2 = odesc(c.daddr(u + 1) + (1 - c.wg) * 8192, 16, 1024, 1);
  c.turn();
  wg_fence();
#pragma unroll
  for (int kk = 0; kk < 4; kk++) wgmma_ss_n128<1>(a, da + kk * 2, db + kk * 128, !(FIRST && kk == 0));
#pragma unroll
  for (int kk = 0; kk < 4; kk++) wgmma_ss_n128<1>(b, da2 + kk * 2, db + kk * 128, !(FIRST && kk == 0));
  wg_commit();
  c.pass();
}
template<int U14, int U15> __device__ __forceinline__ void q_tail(Cons& c, float (&d)[64], int rowhalf) {
  const uint64_t da = odesc(c.daddr(U14) + rowhalf * 8192, 16, 1024, 1), db = odesc(c.daddr(7), 8192, 1024, 1);
  c.turn();
  wg_fence();
#pragma unroll
  for (int kk = 0; kk < 8; kk++) wgmma_ss_n128<1>(d, da + (kk >> 2) * (U15 - U14) * 1024 + (kk & 3) * 2, db + (kk >> 2) * 4096 + (kk & 3) * 128, 1);
  wg_commit();
  c.pass();
}
template<int OFF> __device__ __forceinline__ void q_store(const float (&d)[64], uint4 (&v)[8], uint32_t q0) {
  pack_chunk<0>(d, QSCALE, QSCALE, v[0], v[1]);  sts128o<OFF>(q0, v[0]);        sts128o<OFF + 2048>(q0, v[1]);
  pack_chunk<16>(d, QSCALE, QSCALE, v[2], v[3]); sts128o<OFF + 512>(q0, v[2]);  sts128o<OFF + 2560>(q0, v[3]);
  pack_chunk<32>(d, QSCALE, QSCALE, v[4], v[5]); sts128o<OFF + 1024>(q0, v[4]); sts128o<OFF + 3072>(q0, v[5]);
  pack_chunk<48>(d, QSCALE, QSCALE, v[6], v[7]); sts128o<OFF + 1536>(q0, v[6]); sts128o<OFF + 3584>(q0, v[7]);
}
template<bool PEND_KV> __device__ __forceinline__ void cons_q(Cons& c, int h, Pend& w, float (&b)[64]) {
  float a[64];
  if (!PEND_KV) c.wait(0);
  q_issue<true>(c, a, b, 0);
  if (PEND_KV) { c.release(9, 3); out_piece<SCH_Q, true>(c, w, 0, true); }
#pragma unroll 1
  for (int ks = 1; ks < 14; ks++) {
    const int u = gemm_unit(ks);
    c.wait(u);
    wg_wait<0>();
    c.release(gemm_unit(ks - 1), 3);
    q_issue<false>(c, a, b, u);
    if (PEND_KV && ks <= (int)(SCH_Q >> 60)) { out_piece<SCH_Q, false>(c, w, ks, true); if (ks == (int)(SCH_Q >> 60)) c.signal(SIG_KV + (h >> 4)); }
  }
  c.wait(6); c.wait(9);
  wg_wait<0>();
  c.release(3, 3);
  q_tail<8, 9>(c, b, 1 - c.wg);
  wg_wait<0>(); fence_regs(b);
  c.release(8, 2);
  q_tail<6, 10>(c, a, c.wg);
  c.wait(0);
  const uint32_t q0 = c.addr(0) + (c.wg * 4 + c.warp) * 4096 + atom_off(c.lane);
  SHADOW { uint4 v[8]; q_store<32768>(b, v, q0); w.kn = tile_norm2(v); }
  c.wait(4);
  wg_wait<0>(); fence_regs(a);
  c.release(6, 2); c.release(10, 2);
  q_store<0>(a, w.lo, q0);
  fence_async_smem();
}

__device__ __forceinline__ void issue_qk(float (&s)[64], uint64_t da, uint64_t db) {
#pragma unroll
  for (int kk = 0; kk < 8; kk++) wgmma_ss_n128<0>(s, da + (kk >> 1) * 32 + (kk & 1) * 2, db + (kk >> 1) * 32 + (kk & 1) * 2, kk > 0);
  wg_commit();
}
template<int A, int B> __device__ __forceinline__ void exp_rng(float (&s)[64]) {
#pragma unroll
  for (int i = 4 * A; i < 4 * B; i++) s[i] = ex2(s[i]);
}
template<int A, int B> __device__ __forceinline__ void sum_rng(const float (&s)[64], float (&l)[4]) {
#pragma unroll
  for (int i = A; i < B; i++) { l[0] += s[4 * i]; l[1] += s[4 * i + 1]; l[2] += s[4 * i + 2]; l[3] += s[4 * i + 3]; }
}
template<int A, int B> __device__ __forceinline__ void cvt_p(const float (&s)[64], uint32_t (&p)[32]) {
#pragma unroll
  for (int i = 2 * A; i < 2 * B; i++) p[i] = pack_bf16(s[2 * i], s[2 * i + 1]);
}
template<int K0> __device__ __forceinline__ void mask_half(float (&s)[64], int warp, int lane) {
  const int l0 = warp + (2 * (lane & 3) <= (lane >> 2)), l1 = warp + (2 * (lane & 3) < (lane >> 2));
#pragma unroll
  for (int k = 0; k < 4; k++) {
    float* t = s + 8 * (K0 + k);
    if (k >= l0) { t[0] = -INFINITY; t[6] = -INFINITY; }
    if (k >= l1) { t[1] = -INFINITY; t[7] = -INFINITY; }
    if (k > warp) { t[2] = -INFINITY; t[3] = -INFINITY; }
    if (k >= warp) { t[4] = -INFINITY; t[5] = -INFINITY; }
  }
}
__device__ __forceinline__ void row_inv(float& l0, float& l1) {
  l0 += __shfl_xor_sync(~0u, l0, 1); l1 += __shfl_xor_sync(~0u, l1, 1);
  l0 += __shfl_xor_sync(~0u, l0, 2); l1 += __shfl_xor_sync(~0u, l1, 2);
  l0 = __fdividef(1.f, l0); l1 = __fdividef(1.f, l1);
}
__device__ __forceinline__ void pack_o(const float (&o)[64], float i0, float i1, uint4 (&v)[8]) {
  pack_chunk<0>(o, i0, i1, v[0], v[1]); pack_chunk<16>(o, i0, i1, v[2], v[3]);
  pack_chunk<32>(o, i0, i1, v[4], v[5]); pack_chunk<48>(o, i0, i1, v[6], v[7]);
  pin(v);
}
__device__ __forceinline__ void softmax_safe(float (&s)[64], bool upper_only, float& m0, float& m1, float& sc0, float& sc1) {
  float a0 = m0, a1 = m1;
#pragma unroll
  for (int i = 0; i < 8; i++) { a0 = fmaxf(a0, fmaxf(s[4 * i], s[4 * i + 1])); a1 = fmaxf(a1, fmaxf(s[4 * i + 2], s[4 * i + 3])); }
  if (upper_only) { a0 = m0; a1 = m1; }
#pragma unroll
  for (int i = 8; i < 16; i++) { a0 = fmaxf(a0, fmaxf(s[4 * i], s[4 * i + 1])); a1 = fmaxf(a1, fmaxf(s[4 * i + 2], s[4 * i + 3])); }
  a0 = fmaxf(a0, __shfl_xor_sync(~0u, a0, 1)); a1 = fmaxf(a1, __shfl_xor_sync(~0u, a1, 1));
  a0 = fmaxf(a0, __shfl_xor_sync(~0u, a0, 2)); a1 = fmaxf(a1, __shfl_xor_sync(~0u, a1, 2));
  sc0 = ex2(m0 - a0); sc1 = ex2(m1 - a1);
  m0 = a0; m1 = a1;
#pragma unroll
  for (int i = 0; i < 16; i++) { s[4 * i] -= a0; s[4 * i + 1] -= a0; s[4 * i + 2] -= a1; s[4 * i + 3] -= a1; }
}
struct Att {
  float s[64], o[64], l[4], i0, i1; uint32_t p[32];
  uint32_t qaddr;
};
__device__ __forceinline__ uint32_t ctx_off(const Cons& c, int h, int qb, int rowhalf) { return T_CTX + (qb * 32 + h) * 32768 + (rowhalf * 4 + c.warp) * 4096; }
__device__ __forceinline__ int att_first(Cons& c, Att& a, int h, const Pend& w) {
  a.qaddr = c.daddr(0) + c.wg * 16384;
  c.turn();
  wg_fence();
  issue_qk(a.s, odesc(a.qaddr, 16, 2048, 2), odesc(c.daddr(4), 16, 2048, 2));
  c.pass();
  c.signal(SIG_ATT + (h >> 4));
  float qn = w.kn;
  SHADOW qn = tile_norm2(w.lo);
  const float kn = __uint_as_float(lds32(c.base + SM_KMAX + 4 * (h >> 4)));
  const int fast = __shfl_sync(~0u, bar_and(3 + c.wg, 128, (qn * kn <= BOUND2) && (w.kn * kn <= BOUND2)), 0);
#pragma unroll
  for (int i = 0; i < 8; i++) { a.p[4 * i] = w.lo[i].x; a.p[4 * i + 1] = w.lo[i].y; a.p[4 * i + 2] = w.lo[i].z; a.p[4 * i + 3] = w.lo[i].w; }
  a.l[0] = a.l[1] = a.l[2] = a.l[3] = 0.f; a.i0 = a.i1 = 0.f;
  wg_wait<0>(); fence_regs(a.s);
  c.release(4, 2);
  return fast;
}
__device__ __forceinline__ void att_last(Cons& c, Att& a, Pend& w, int h, int g, bool drain) {
  const int uv = att_slot(1);
  if (drain) pack_o(a.o, a.i0, a.i1, w.hi);
  c.wait(uv);
  c.turn();
  fence_regs(a.o); fence_regs(a.p);
  wgmma_pv_sel(a.o, a.p, odesc(c.daddr(uv), 512, 2048, 2), !(drain && c.wg == 1), !drain);
  c.pass();
  a.i0 = a.l[0] + a.l[1]; a.i1 = a.l[2] + a.l[3];
  SHADOW row_inv(a.i0, a.i1);
  sched_fence(a.i0 + a.i1, c.base + SM_DUMMY);
  tile_store_if<0, 4>(drain, w.hi, w.dst, c.lane);
  wg_wait<0>(); fence_regs(a.o); fence_regs(a.p);
  c.release(uv, 2);
  tile_store_if<4, 8>(drain, w.hi, w.dst, c.lane);
  pack_o(a.o, a.i0, a.i1, w.lo);
  w.dst = ctx_off(c, h, g, 1 - c.wg);
}
__device__ __forceinline__ void cons_att(Cons& c, Att& a, int h, int g, Pend& w) {
  const int fast = att_first(c, a, h, w);
  if (DEFER_ST) w.dst = ctx_off(c, h, 15 - g, c.wg);
  float m0 = -INFINITY, m1 = -INFINITY, sc0 = 0.f, sc1 = 0.f;
  int uk = 10, nrel = 0;
#pragma unroll 1
  for (int d = g - 15;;) {
    const bool lo = d == c.wg;
    if ((unsigned)d < 2 || !fast) {
      if ((unsigned)d < 2) mask_half<4>(a.s, c.warp, c.lane);
      if (!fast) {
        if (d == 1) m0 = m1 = -INFINITY;
        softmax_safe(a.s, lo, m0, m1, sc0, sc1);
        a.l[0] *= sc0; a.l[1] *= sc0; a.l[2] *= sc1; a.l[3] *= sc1;
      }
    }
    exp_rng<8, 16>(a.s); sum_rng<8, 16>(a.s, a.l);
    exp_rng<ATT_SPLIT, 8>(a.s);
    sched_fence(((a.l[0] + a.l[1]) + (a.l[2] + a.l[3])) + (ATT_SPLIT < 8 ? a.s[4 * ATT_SPLIT + 3] : 0.f), c.base + SM_DUMMY);
    wg_wait<0>(); fence_regs(a.o); fence_regs(a.p);
    c.release(14 - uk, nrel);
    if (DEFER_ST) tile_store_if<DS_A, DS_B>(d == 2, w.hi, w.dst, c.lane);
    nrel = 2; uk ^= 12;
    if (d == 0) a.qaddr += 32768;
    const uint64_t dq = odesc(a.qaddr, 16, 2048, 2), dk = odesc(c.daddr(uk) - (d + 1 == c.wg ? 16384 : 0), 16, 2048, 2), dv = odesc(c.daddr(14 - uk), 512, 2048, 2);
    if (!lo) { exp_rng<0, ATT_SPLIT>(a.s); sum_rng<0, 8>(a.s, a.l); cvt_p<0, 16>(a.s, a.p); }
    else if (gridDim.y == 1) cvt_p<8, 16>(a.s, a.p);
    if (DEFER_ST) tile_store_if<DS_B, 8>(d == 2, w.hi, w.dst, c.lane);
    if (!fast || d == g + 1) {
      if (!fast && d != 1) {
#pragma unroll
        for (int i = 0; i < 16; i++) { a.o[4 * i] *= sc0; a.o[4 * i + 1] *= sc0; a.o[4 * i + 2] *= sc1; a.o[4 * i + 3] *= sc1; }
      }
      if (d == g + 1) break;
    }
    d++;
    if (c.wg == 0) c.wait(uk); else c.skip(uk);
    c.turn();
    fence_regs(a.o); fence_regs(a.p);
    wg_fence();
    issue_qk(a.s, dq, dk);
    if (d == 2) {
      pack_o(a.o, a.i0, a.i1, w.hi);
    }
    wgmma_pv_sel(a.o, a.p, dv, !lo, d != 2 && d != g - 14);
    c.pass();
    if (DEFER_ST) tile_store_if<0, DS_A>(d == 2, w.hi, w.dst, c.lane);
    if (d == 1) {
      a.i0 = a.l[0] + a.l[1]; a.i1 = a.l[2] + a.l[3]; row_inv(a.i0, a.i1);
      a.l[0] = a.l[1] = a.l[2] = a.l[3] = 0.f;
    }
    wg_wait<1>(); fence_regs(a.s);
    c.release(uk, 2);
    c.release(d == 0 ? 0 : 2, (d == 0 || d == g + 1) ? 2 : 0);
  }
  att_last(c, a, w, h, g, g == 0);
}

constexpr int CV_H = 1024, CV_U = 5120, CV_D = CV_U + 4128, CV_ROW = 1056;
template<int OFF> __device__ __forceinline__ uint32_t lds32o(uint32_t a) { uint32_t v; asm volatile("ld.shared.u32 %0, [%1+%2];" : "=r"(v) : "r"(a), "n"(OFF) : "memory"); return v; }
template<int G, int G1 = 16> __device__ __forceinline__ void conv_lda(uint32_t (&a)[64], uint32_t p) {
  a[4 * G + 0] = lds32o<-256 * G>(p);
  a[4 * G + 1] = lds32o<-256 * G - 128>(p);
  a[4 * G + 2] = lds32o<-256 * G + 16>(p);
  a[4 * G + 3] = lds32o<-256 * G - 112>(p);
  if constexpr (G + 1 < G1) conv_lda<G + 1, G1>(a, p);
}
struct CvAcc { float lo[16], hi[16]; };
__device__ __forceinline__ void fence_regs(CvAcc& d) { fence_regs(d.lo); fence_regs(d.hi); }
template<int R, int H> __device__ __forceinline__ void conv_mma_h(float (&d)[16], const uint32_t (&a)[64], uint64_t db) {
#pragma unroll
  for (int G = 0; G < 4 * R + 2 * H + 2; G++) wgmma_rs_n32<0>(d, a[4 * G], a[4 * G + 1], a[4 * G + 2], a[4 * G + 3], db + 64 * R + 32 * H - 16 * G, G > 0);
}
template<int T, int G0, int G1> __device__ __forceinline__ void conv_part(float (&d)[16], const uint32_t (&a)[64], uint64_t db) {
#pragma unroll
  for (int G = G0; G < G1; G++) wgmma_rs_n32<0>(d, a[4 * G], a[4 * G + 1], a[4 * G + 2], a[4 * G + 3], db + 32 * T - 16 * G, G > 0);
}
template<int R> __device__ __forceinline__ void conv_mma(CvAcc& d, const uint32_t (&a)[64], uint64_t db) { conv_mma_h<R, 0>(d.lo, a, db); conv_mma_h<R, 1>(d.hi, a, db); }
template<int C0> __device__ __forceinline__ void conv_st_h(const float (&d)[16], uint32_t wq, float& c0, float& c1) {
#pragma unroll
  for (int n = 0; n < 4; n++) { sts64f(wq + (C0 + n * 8) * 4, d[4 * n] + c0, d[4 * n + 1] + c1); c0 = d[4 * n + 2]; c1 = d[4 * n + 3]; }
}
template<int R> __device__ __forceinline__ void conv_st(const CvAcc& d, uint32_t wq, float& c0, float& c1) { conv_st_h<64 * R>(d.lo, wq, c0, c1); conv_st_h<64 * R + 32>(d.hi, wq, c0, c1); }
struct ConvTail { float t[64]; uint4 ua, uc; uint32_t D2; };
__device__ __forceinline__ void conv_emit(ConvTail& e, int ch, int tid) {
  fence_regs(e.t);
  float y[16];
#pragma unroll
  for (int i = 0; i < 16; i++) y[i] = (e.t[i] + e.t[16 + i]) + (e.t[32 + i] + e.t[48 + i]);
  uint4 z0, z1;
  z0.x = hadd2(pack_bf16(y[0], y[2]), hmul2(__byte_perm(e.ua.w, 0, 0x1032), e.D2));
  z0.y = hadd2(pack_bf16(y[4], y[6]), hmul2(__byte_perm(e.ua.z, 0, 0x1032), e.D2));
  z0.z = hadd2(pack_bf16(y[8], y[10]), hmul2(__byte_perm(e.ua.y, 0, 0x1032), e.D2));
  z0.w = hadd2(pack_bf16(y[12], y[14]), hmul2(__byte_perm(e.ua.x, 0, 0x1032), e.D2));
  z1.x = hadd2(pack_bf16(y[1], y[3]), hmul2(__byte_perm(e.uc.w, 0, 0x1032), e.D2));
  z1.y = hadd2(pack_bf16(y[5], y[7]), hmul2(__byte_perm(e.uc.z, 0, 0x1032), e.D2));
  z1.z = hadd2(pack_bf16(y[9], y[11]), hmul2(__byte_perm(e.uc.y, 0, 0x1032), e.D2));
  z1.w = hadd2(pack_bf16(y[13], y[15]), hmul2(__byte_perm(e.uc.x, 0, 0x1032), e.D2));
  uint4* zp = (uint4*)(g_z + (uint32_t)(ch * 2048 + tid * 16));
  zp[0] = z0; zp[1] = z1;
}
template<int MASK> __device__ __forceinline__ void cons_conv(Cons& c, int cta, int nch) {
  const int r = c.lane >> 2, q = c.lane & 3, tid = c.warp * 32 + c.lane;
  const uint32_t part = c.addr(4) - 2048 + (1 - c.wg) * (32 * CV_ROW) + 32;
  const uint32_t aoff = CV_U + ((r & 1) ? 0 : UPITCH) + 4 * (((2039 - r) >> 1) + q - 8 * c.warp);
  const uint32_t wq = part + (c.warp * 8 + r) * CV_ROW + q * 8, rq = part + tid * 8;
  uint32_t a[64];
  ConvTail e = {};
  c.wait(c.wg); c.skip(c.wg ^ 1);
  conv_lda<0>(a, c.addr(c.wg) + aoff);
  c.wait(4);
  sts64f(part + (tid >> 2) * CV_ROW - 32 + q * 8, 0.f, 0.f);
#pragma unroll 1
  for (int i = 0; i < nch / 2; i++) {
    const int u = 2 * (i & 1) + c.wg;
    CvAcc d0, d1, d2, d3;
    float c0 = 0.f, c1 = 0.f;
    const uint64_t db = odesc(c.daddr(u) + CV_H - 16, 16, 128, 0);
    c.turn();
    fence_regs(a);
    wg_fence();
    conv_mma<0>(d0, a, db); conv_mma<1>(d1, a, db); wg_commit();
    if (i > 0) {
      conv_emit(e, conv_channel<MASK>(cta, 2 * i - 2 + c.wg), tid);
      if ((i & 15) == 0) c.signal(SIG_Z + (i >> 4) - 1);
    }
    wg_fence();
    conv_mma_h<2, 0>(d2.lo, a, db); wg_commit();
    wg_wait<1>(); fence_regs(d0); fence_regs(d1);
    conv_st_h<0>(d0.lo, wq, c0, c1);
    wg_fence();
    conv_mma_h<2, 1>(d2.hi, a, db); wg_commit();
    conv_st_h<32>(d0.hi, wq, c0, c1);
    conv_mma_h<3, 0>(d3.lo, a, db);
    conv_st_h<64>(d1.lo, wq, c0, c1);
    conv_mma_h<3, 1>(d3.hi, a, db); wg_commit();
    c.pass();
    const int un = i + 1 < nch / 2 ? u ^ 2 : u;
    if (un != u) { c.wait(un); c.skip(un ^ 1); }
    wg_wait<1>(); fence_regs(d2);
    conv_st_h<96>(d1.hi, wq, c0, c1);
    conv_st<2>(d2, wq, c0, c1);
    {
      const int sw = (c.lane >> 2) & 1;
      const uint4 v0 = lds128(c.addr(u) + CV_U + 4064 - 32 * tid + 16 * sw), v1 = lds128(c.addr(u) + CV_U + 4080 - 32 * tid - 16 * sw);
      e.ua = sw ? v0 : v1; e.uc = sw ? v1 : v0;
    }
    e.D2 = lds32(c.addr(u) + CV_D);
    wg_wait<0>(); fence_regs(d3); fence_regs(a);
    conv_st<3>(d3, wq, c0, c1);
    conv_lda<0, 4>(a, c.addr(un) + aoff);
    bar_sync(3 + c.wg, 128);
    sched_fence(__uint_as_float(e.ua.x ^ e.uc.x ^ e.D2), c.base + SM_DUMMY);
    c.release2(u);
    conv_lda<4, 16>(a, c.addr(un) + aoff);
#pragma unroll
    for (int k = 0; k < 32; k++) { const float2 v = lds64f(rq + k * CV_ROW - (k >> 3) * 8); e.t[2 * k] = v.x; e.t[2 * k + 1] = v.y; }
  }
  conv_emit(e, conv_channel<MASK>(cta, nch - 2 + c.wg), tid);
  c.signal(SIG_Z + ((nch / 2 - 1) >> 4));
  c.release(4, 4);
}

constexpr int OC_PART = 13824, OC_ROW = 544;
__device__ __forceinline__ int out_next(int u) { return (0x84ac680u >> (2 * u)) & 15; }
struct Out { float acc[64]; int pu; uint64_t da, db; };
template<bool FIRST, bool REL, int W = 1, bool PRE = true, bool POST = false> __device__ __forceinline__ void out_step(Cons& c, Out& o, bool extra = false) {
  const int pu = o.pu, u = extra ? 2 : out_next(pu);
  o.pu = u;
  if (PRE) c.wait(u);
  const uint64_t da = o.da + (uint32_t)(u * 1024), db = o.db + (uint32_t)(u * 1024);
  wg_fence();
#pragma unroll
  for (int kk = 0; kk < 4; kk++) wgmma_ss_n128<1>(o.acc, da + (kk >> 1) * 32 + (kk & 1) * 2, db + kk * 128, !(FIRST && kk == 0));
  wg_commit();
  if (REL) { wg_wait<W>(); c.release(pu, 2); }
  if (POST) c.wait(out_next(u));
}
template<int I0, int I1> __device__ __forceinline__ void oc_red(float (&y)[8], uint32_t rq) {
#pragma unroll
  for (int i = I0; i < I1; i++) { const float v = __uint_as_float(lds32(rq + i * OC_ROW - (i >> 3) * 8)); y[i & 7] = i < 8 ? v : y[i & 7] + v; }
}
__device__ __forceinline__ void oc_emit(const float (&y)[8], const uint4& u, uint32_t D2, __nv_bfloat16* dst) {
  uint4 z;
  z.x = hadd2(pack_bf16(y[0], y[1]), hmul2(__byte_perm(u.w, 0, 0x1032), D2));
  z.y = hadd2(pack_bf16(y[2], y[3]), hmul2(__byte_perm(u.z, 0, 0x1032), D2));
  z.z = hadd2(pack_bf16(y[4], y[5]), hmul2(__byte_perm(u.y, 0, 0x1032), D2));
  z.w = hadd2(pack_bf16(y[6], y[7]), hmul2(__byte_perm(u.x, 0, 0x1032), D2));
  *(uint4*)dst = z;
}
template<int MASK> __device__ __forceinline__ void cons_out(Cons& c, const Maps& M, const Params& P, int cta, Pend& w) {
  const int mb = out_mb(cta), nb = out_nb(cta);
  Out o;
  o.da = odesc(c.daddr(0) + c.wg * 8192, 16, 1024, 2); o.db = odesc(c.daddr(1), 8192, 1024, 1);
  o.pu = 5 + gridDim.y;
  out_step<true, false>(c, o);
  int ks = 1;
#pragma unroll 1
  for (;; ks++) {
    if (MASK & PH_ATT) {
      if (ks == (c.wg ? ST_1 : ST_0)) tile_store<0, 1>(w.lo, w.dst, c.lane);
      if (ks == (c.wg ? ST_1 + ST_D : ST_0 + ST_0D / 2)) tile_store<1, 2>(w.lo, w.dst, c.lane);
      if (ks == (c.wg ? ST_1 + 2 * ST_D : ST_0 + ST_0D)) tile_store<2, 3>(w.lo, w.dst, c.lane);
      if (ks == (c.wg ? ST_1 + 3 * ST_D : ST_0 + 3 * ST_0D / 2)) { tile_store<3, 4>(w.lo, w.dst, c.lane); c.signal(SIG_CTX + 1); }
    }
    if (ks == (c.wg ? OC_S1 : OC_S0)) break;
    out_step<false, true>(c, o, XSLOT && ks == 1);
  }
  if (MASK & PH_CONV) {
    const int r = c.lane >> 2, q = c.lane & 3, tid = c.warp * 32 + c.lane, u = 2 * c.wg;
    const uint32_t ub = c.addr(u), part = ub + OC_PART + 32;
    const uint32_t ap = ub + CV_U + ((r & 1) ? 0 : UPITCH) + 4 * (((2039 - r) >> 1) + q - 8 * c.warp);
    const uint32_t wq = part + (c.warp * 8 + r) * OC_ROW + q * 8, rq = part + tid * 4;
    const int nr = (CV_REG<MASK> + 1 - c.wg) >> 1;
#define STEP(N) out_step<false, true, 1, !OC_POST, OC_POST>(c, o);
#pragma unroll 1
    for (int i = 0; i < nr; i++) {
      uint32_t a[64];
      CvAcc d0, d1;
      float y[8], c0 = 0.f, c1 = 0.f;
      const uint64_t db = odesc(c.daddr(u + (i >> 8)) + CV_H - 16, 16, 128, 0);
#define STEP2(N) out_step<false, true, 2, !OC_POST, OC_POST>(c, o);
#define PART(...) { const uint64_t db = db0 + (c.mask >> 16); wg_fence(); __VA_ARGS__; wg_commit(); }
      const uint64_t db0 = db;
      c.wait(u);
      if (OC_POST) c.wait(out_next(o.pu));
      conv_lda<0, 4>(a, ap);
      STEP(0)
      conv_lda<4, 7>(a, ap);
      PART(conv_part<0, 0, 2>(d0.lo, a, db); conv_part<1, 0, 4>(d0.hi, a, db))
      STEP2(1)
      conv_lda<7, 10>(a, ap);
      PART(conv_part<2, 0, 6>(d1.lo, a, db))
      STEP2(2)
      fence_regs(d0);
      bar_sync(3 + c.wg, 128);
      sts64f(wq - 32, 0.f, 0.f);
      conv_st<0>(d0, wq, c0, c1);
      asm volatile("add.f32 %0, %0, 0f80000000;" : "+f"(c0)); asm volatile("add.f32 %0, %0, 0f80000000;" : "+f"(c1));
      PART(conv_part<3, 0, 8>(d1.hi, a, db))
      STEP2(3)
      wg_wait<1>(); fence_regs(d1);
      float e0 = d1.hi[12] + d1.hi[10], e1 = d1.hi[13] + d1.hi[11];
      conv_st<1>(d1, wq, c0, c1);
      asm volatile("add.f32 %0, %0, 0f80000000;" : "+f"(c0)); asm volatile("add.f32 %0, %0, 0f80000000;" : "+f"(c1));
      PART(conv_part<4, 0, 10>(d0.lo, a, db))
      STEP2(4)
      conv_lda<10, 12>(a, ap);
      bar_sync(3 + c.wg, 128);
      oc_red<0, 6>(y, rq);
      PART(conv_part<5, 0, 9>(d0.hi, a, db))
      STEP2(5)
      conv_lda<12, 14>(a, ap);
      oc_red<6, 12>(y, rq);
      PART(conv_part<5, 9, 12>(d0.hi, a, db); conv_part<6, 0, 6>(d1.lo, a, db))
      STEP2(6)
      oc_red<12, 26>(y, rq);
      PART(conv_part<6, 6, 14>(d1.lo, a, db))
      STEP2(7)
      oc_red<26, 32>(y, rq);
      conv_lda<14, 16>(a, ap);
      PART(conv_part<7, 0, 8>(d1.hi, a, db))
      STEP2(8)
      fence_regs(y); fence_regs(d0);
      bar_sync(3 + c.wg, 128);
      sts64f(wq - 32, e0, e1);
      conv_st<0>(d0, wq, c0, c1);
      PART(conv_part<7, 8, 16>(d1.hi, a, db))
      STEP2(9)
      wg_wait<1>(); fence_regs(d1); fence_regs(a);
      const uint4 u0 = lds128(ub + CV_U + 4080 - 16 * tid), u1 = lds128(ub + CV_U + 2032 - 16 * tid);
      const uint32_t D2 = lds32(ub + CV_D);
      conv_st_h<64>(d1.lo, wq, c0, c1);
      sched_fence(__uint_as_float(u0.x ^ u1.x ^ D2), c.base + SM_DUMMY);
      __syncwarp();
      c.release2(u);
      STEP(10)
      conv_st_h<96>(d1.hi, wq, c0, c1);
      __nv_bfloat16* zp = g_z + (uint32_t)(conv_channel<MASK>(cta, 2 * i + c.wg) * 2048 + (threadIdx.x & 127) * 8);
      oc_emit(y, u0, D2, zp);
      bar_sync(3 + c.wg, 128);
      oc_red<0, 6>(y, rq);
      STEP(11)
      oc_red<6, 19>(y, rq);
      STEP(12)
      oc_red<19, 32>(y, rq);
      oc_emit(y, u1, D2, zp + 1024);
      if (i == nr - 1) { c.signal(SIG_Z); c.release2(u + 1); TS(c.wg, 8); }
      out_step<false, true, 1, !OC_POST>(c, o);
#pragma unroll 1
      for (int k = 14; k < (c.wg ? OC_L1 : OC_L0); k++) out_step<false, true>(c, o);
#undef STEP2
#undef PART
    }
#undef STEP
    if (((CV_REG<MASK> + c.wg) >> 1) & 1) c.skip(u ^ 2);
    ks += nr * (c.wg ? OC_L1 : OC_L0);
  }
  TS(c.wg, 9);
#pragma unroll 1
  for (; ks < 57; ks++) out_step<false, true>(c, o);
  uint32_t ga[32];
  c.wait(2);
  const float g0 = __uint_as_float(lds32(c.base + SM_GATE + 4 * (c.wg * 64 + c.warp * 16 + (c.lane >> 2)))), g1 = __uint_as_float(lds32(c.base + SM_GATE + 32 + 4 * (c.wg * 64 + c.warp * 16 + (c.lane >> 2))));
  const uint32_t gg0 = pack_bf16(g0, g0), gg1 = pack_bf16(g1, g1);
  const uint32_t og0 = pack_bf16(1.f - g0, 1.f - g0), og1 = pack_bf16(1.f - g1, 1.f - g1);
  const int xr = c.wg * 64 + c.warp * 16 + (c.lane & 15);
  const uint32_t xa = c.addr(2) + xr * 128, xs = xr & 7, xh = c.lane >> 4;
  const int zr = (c.lane & 7) + ((c.lane >> 4) << 3);
  const uint32_t za = c.addr(0) + c.wg * 16384 + zr * 128 + (((c.warp * 2 + ((c.lane >> 3) & 1)) ^ (zr & 7)) << 4);
#pragma unroll
  for (int i = 0; i < 8; i++) {
    if (i == 0) out_step<false, true>(c, o);
    if (i == 3) out_step<false, true>(c, o);
    if (i == 6) out_step<false, true>(c, o);
    ldsm4(xa + (i >> 2) * 16384 + ((((i & 3) * 2 + xh) ^ xs) << 4), ga[4 * i], ga[4 * i + 1], ga[4 * i + 2], ga[4 * i + 3]);
  }
#pragma unroll 1
  for (ks = 60; ks < 64; ks++) out_step<false, false>(c, o);
  TS(c.wg, 17);
  c.wait(0);
  TS(c.wg, 18);
  SHADOW {
#pragma unroll
    for (int i = 0; i < 8; i++) {
      uint32_t z0, z1, z2, z3;
      ldsm4t(za + i * 2048, z0, z1, z2, z3);
      ga[4 * i + 0] = hmul2(gg0, hmul2(ga[4 * i + 0], z0)); ga[4 * i + 1] = hmul2(gg1, hmul2(ga[4 * i + 1], z1));
      ga[4 * i + 2] = hmul2(gg0, hmul2(ga[4 * i + 2], z2)); ga[4 * i + 3] = hmul2(gg1, hmul2(ga[4 * i + 3], z3));
    }
  }
  c.signal(SIG_DONE);
  fence_regs(ga);
  TS(c.wg, 19);
  wg_wait<0>(); fence_regs(o.acc);
  TS(c.wg, 20);
#pragma unroll
  for (int i = 0; i < 8; i++) {
    const uint32_t r0 = hadd2(ga[4 * i + 0], hmul2(og0, pack_bf16(o.acc[8 * i + 0], o.acc[8 * i + 1])));
    const uint32_t r1 = hadd2(ga[4 * i + 1], hmul2(og1, pack_bf16(o.acc[8 * i + 2], o.acc[8 * i + 3])));
    const uint32_t r2 = hadd2(ga[4 * i + 2], hmul2(og0, pack_bf16(o.acc[8 * i + 4], o.acc[8 * i + 5])));
    const uint32_t r3 = hadd2(ga[4 * i + 3], hmul2(og1, pack_bf16(o.acc[8 * i + 6], o.acc[8 * i + 7])));
    stsm4(xa + (i >> 2) * 16384 + ((((i & 3) * 2 + xh) ^ xs) << 4), r0, r1, r2, r3);
    if ((i & 3) == 3) {
      __syncwarp();
#pragma unroll
      for (int k = 0; k < 4; k++) {
        const int rr = c.wg * 64 + c.warp * 16 + k * 4 + (c.lane >> 3);
        const uint4 v = lds128(c.addr(2 + (i >> 2)) + rr * 128 + (((c.lane ^ rr) & 7) << 4));
        *(uint4*)(P.out + (uint32_t)((mb * 128 + rr) * 1024 + nb * 128 + (i >> 2) * 64 + (c.lane & 7) * 8)) = v;
      }
    }
  }
}

__device__ __forceinline__ void load_conv(Prod& p, const Maps& M, int u, int ch) {
  if (elect()) {
    mbar_expect(p.full(u), 5120 + UCH);
    tma3d(p.addr(u), &M.h, 0, -8, ch, p.full(u), POL(4));
    bulk_g2s(p.addr(u) + CV_U, g_u + (size_t)ch * UCH, UCH, p.full(u), POL(4));
  }
}
template<int MASK> __device__ __forceinline__ void prod_conv(Prod& p, const Maps& M, int cta, int nch) {
  int ready = -1;
#pragma unroll 1
  for (int i = 0; i < nch; i++) {
    const int ch = conv_channel<MASK>(cta, i);
    const int u = i & 3;
    if ((ch >> 6) != ready) { ready = ch >> 6; if (cta < NREG) mbar_wait(p.base + SM_RDY + 8 * RDY_U, 0); else cnt_wait(g_cnt + (C_U + ready) * CSTRIDE, 128); }
    p.acquire(u, 1);
    load_conv(p, M, u, ch);
    if (i == 3) { p.acquire(4, 4); if (elect()) mbar_arrive(p.full(4)); }
  }
}
#define HOIST(v) asm volatile("" : "+r"(v))
template<int MASK> __device__ __forceinline__ void producer(const Maps& M, const Params& P, uint32_t base, int cta, int lane) {
  Prod p{base, ((MASK & PH_KV) && cta < NREG) ? 0xffffcfffu ^ ((1u << (3 * NFIRST)) - 1) : 0xffffffffu, lane,
         (cta * 3 + 2) * 2048};
  if (cta >= NREG) { if (MASK & PH_CONV) prod_conv<MASK>(p, M, cta, CV_EXTRA<MASK>); return; }
  const int g = cta & 7, j = cta >> 3, rank = cta & 1;
#pragma unroll 1
  for (int half = 0; half < 2; half++) {
    const int h = j + 16 * half;
    if (MASK & PH_KV) {
      const CUtensorMap* mw = rank ? &M.wv : &M.wk;
#pragma unroll 1
      for (int it = half ? 0 : NFIRST; it < 16; it++) {
        const int u = gemm_unit(it);
        uint32_t bar = p.full(u), d0 = p.addr(u), d1 = p.addr(u + 1 + rank); int k0 = (it & 7) * 64, r0 = (2 * g + (it >> 3)) * 128;
        HOIST(bar); HOIST(d0); HOIST(d1); HOIST(k0); HOIST(r0);
        p.acquire(u, 3);
        if (elect()) {
          mbar_expect(bar, 3 * UNIT);
          tma3d_mc(d1, mw, 0, k0, 2 * h, bar, POL(0) && it >= 8);
          tma2d(d0, &M.c, k0, r0, bar, half ? POL(8) : POL(10));
        }
      }
    }
    if (MASK & PH_ATT) {
#pragma unroll 1
      for (int ks = 0; ks < 16; ks++) {
        const int u = gemm_unit(ks);
        uint32_t bar = p.full(u), d0 = p.addr(u + (ks == 15)), d1 = p.addr(ks < 14 ? u + 1 : ks - 6), d2 = p.addr(u + 2 - (ks == 14)) + rank * 8192; int k0 = ks * 64;
        HOIST(bar); HOIST(d0); HOIST(d1); HOIST(d2); HOIST(k0);
        p.acquire(u, 3);
        if (elect()) {
          mbar_expect(bar, 3 * UNIT);
          tma2d_mc(d2, &M.wq, h * 128 + rank * 64, k0, bar, POL(1));
          tma2d(d0, &M.x, k0, (15 - g) * 128, bar, half ? POL(9) : POL(10));
          tma2d(d1, &M.x, k0, g * 128, bar, half ? POL(9) : POL(10));
        }
      }
      TS(2, 8 * half + 0);
      mbar_wait(base + SM_RDY + 8 * (RDY_KV + half), 0);
      TS(2, 8 * half + 1);
      p.acquire(0, 4);
      if (elect()) mbar_arrive(p.full(0));
      const uint8_t* KVh = g_T + T_KV + (size_t)kv_slot<MASK>(h) * 16 * 65536;
#pragma unroll 1
      for (int n = 0; n < 34; n++) {
        const int i = n == 1 ? 2 : n == 2 ? 1 : n;
        const int isv = (i > 0 && !(i & 1)) || i == 33;
        const int st = i == 33 ? 16 : (isv ? (i >> 1) - 1 : (i + 1) >> 1);
        const int u = att_slot(i & 3);
        const bool own = st == 15 - (g & 6);
        uint32_t bar = p.full((isv && i < 33) ? 14 - u : u), d0 = p.addr(own ? u : u + rank), off = (st <= 15 - g ? st : 16 - st) * 65536 + isv * 32768 + (own ? 0 : rank * UNIT);
        HOIST(bar); HOIST(d0); HOIST(off);
        p.acquire(u, 2);
        if (elect()) {
          if (!isv || i == 33) mbar_expect(bar, (i == 0 || i == 33) ? 32768 : 65536);
          const bool ef = POL(6) || (POL(14) && st >= 8) || (POL(15) && half);
          if (own) bulk_g2s(d0, KVh + off, 32768, bar, ef); else bulk_g2s_mc(d0, KVh + off, UNIT, bar, ef);
          if (MASK == PH_ALL && half && n == PF_AT) {
            if (PF & 1) pf3d(&M.wo, 0, j * 64, 2 * g);
            if (PF & 2) pf_bulk(g_T + T_CTX + (j * 32 + g) * 32768, 32768);
          }
        }
      }
    }
  }
  if ((MASK & PH_CONV) && !(MASK & PH_OUT)) prod_conv<MASK>(p, M, cta, CV_REG<MASK>);
  if (MASK & PH_OUT) {
    const int y0 = out_mb(cta) * 512 + rank * 8, z0 = 2 * out_nb(cta);
    int u = 6;
#pragma unroll 1
    for (int hf = 0; hf < 2; hf++) {
      TS(2, 16 + 2 * hf);
      mbar_wait(base + SM_RDY + 8 * (RDY_CTX + hf), 0);
      TS(2, 17 + 2 * hf);
#pragma unroll 1
      for (int n = hf * 32; n < hf * 32 + 32; n++) {
        const int ks = !XSLOT ? n : n == 1 ? 2 : n == 2 ? 1 : n;
        u = XSLOT && n == 2 ? 2 : XSLOT && n == 3 ? 10 : out_next(u);
        uint32_t bar = p.full(u), d0 = p.addr(u) + rank * 8192, d1 = p.addr(u + 1); int x = (ks & 1) * 256, y = y0 + (ks >> 1) * 16, k0 = ks * 64;
        HOIST(bar); HOIST(d0); HOIST(d1); HOIST(x); HOIST(y); HOIST(k0);
        p.acquire(u, 2);
        if (elect()) {
          mbar_expect(bar, 2 * UNIT);
          tma2d_mc(d0, &M.ctx, x, y, bar, POL(5));
          tma3d(d1, &M.wo, 0, k0, z0, bar, POL(2));
          if ((PF & 4) && (ks & 15) == PF_KS && ks < 48) pf3d(&M.wo, 0, ((ks & 48) + 16 + j) * 64, z0);
          if ((PF & 8) && ks == PF_KS) pf_bulk(g_T + T_CTX + (j * 32 + 8 + g) * 32768, 32768);
          if (XSLOT && ks == 1) mbar_arrive(base + SM_RDY + 8 * RDY_X);
          if (ks == Z_AT) mbar_arrive(base + SM_RDY + 8 * RDY_Z);
        }
      }
    }
  }
}
template<int MASK> __device__ __forceinline__ void producer2(const Maps& M, const Params& P, uint32_t base, int cta, int w, int lane) {
  Prod p{base, 0xffffffffu, lane, 0};
  const int mb = out_mb(cta), nb = out_nb(cta), u = 2 * w;
  if (XSLOT && w) { mbar_wait_slow(base + SM_RDY + 8 * RDY_X, 0); p.mask ^= 12; }
  if (MASK & PH_CONV) {
    mbar_wait_slow(base + SM_SIG + 8 * (SIG_ATT + 1), 0);
    mbar_wait_slow(base + SM_RDY + 8 * RDY_U, 0);
#pragma unroll 1
    for (int i = w; i < CV_REG<MASK>; i += 2) { p.acquire_slow(u, i < 2 ? 2 : 1); load_conv(p, M, u, conv_channel<MASK>(cta, i)); }
  }
  p.acquire_slow(u, 2);
  if (elect()) asm volatile("prefetch.tensormap [%0];" :: "l"(!w ? &M.z : &M.out) : "memory");
  TSA(52 - 2 * w);
  mbar_wait(base + SM_RDY + 8 * (!w ? RDY_Z : RDY_G), 0);
  TSA(53 - 2 * w);
  if (elect()) {
    mbar_expect(p.full(u), 2 * UNIT + (!w ? 0 : 512));
    tma2d(p.addr(u), !w ? &M.z : &M.x, (!w ? mb : nb) * 128, (!w ? nb : mb) * 128, p.full(u), POL(5));
    tma2d(p.addr(u + 1), !w ? &M.z : &M.x, (!w ? mb : nb) * 128 + 64, (!w ? nb : mb) * 128, p.full(u), POL(5));
    if (w) bulk_g2s(base + SM_GATE, g_gate + mb * 128, 512, p.full(u));
  }
}

__device__ __forceinline__ constexpr uint32_t PUB(int sig, int cnt, int n) { return 0x80000000u | (sig << 24) | (n << 8) | cnt; }
__device__ __forceinline__ constexpr uint32_t GET(int rdy, int cnt, int n) { return (rdy << 24) | (n << 8) | cnt; }
template<int MASK> __device__ __forceinline__ void sync_agent(uint32_t base, int cta, int lane) {
  if ((base & 0x3FFFF) != SMEM_BASE) asm volatile("trap;");
  const int g = cta & 7, j = cta >> 3, go = min(out_mb(cta), 15 - out_mb(cta));
  const int c0 = conv_channel<MASK>(cta, 0), c1 = c0 + CV_REG<MASK> - 1, n0 = min(CV_REG<MASK>, 128 - (c0 & 127));
  constexpr bool KV = MASK & PH_KV, ATT = MASK & PH_ATT, CONV = MASK & PH_CONV, OUT = MASK & PH_OUT, ALL = MASK == PH_ALL;
  uint32_t e = 0;
  if (cta >= NREG) { if (CONV && lane * 32 < CV_EXTRA<MASK>) e = PUB(SIG_Z + lane, C_Z + lane, min(32, CV_EXTRA<MASK> - lane * 32)); }
  else switch (lane) {
    case 0:  if (KV) e = PUB(SIG_KV, C_KV + j, 1); break;
    case 1:  if (ATT) e = GET(RDY_KV, C_KV + j, 8); break;
    case 2:  if (ALL) e = PUB(SIG_WAR, C_WAR + j, 1); break;
    case 3:  if (ATT) e = PUB(SIG_CTX, C_CTX + g, 1); break;
    case 4:  if (ALL) e = GET(RDY_WAR, C_WAR + j, 8); break;
    case 5:  if (KV) e = PUB(SIG_KV + 1, C_KV + 16 + j, 1); break;
    case 6:  if (ATT) e = GET(RDY_KV + 1, C_KV + 16 + j, 8); break;
    case 7:  if (OUT) e = GET(RDY_CTX, C_CTX + go, 16); break;
    case 8:  if (CONV) e = GET(RDY_U, C_U + (c0 >> 6), 128); break;
    case 9:  if (CONV) e = GET(RDY_U, C_U + (c1 >> 6), 128); break;
    case 10: if (ATT) e = PUB(SIG_CTX + 1, C_CTX + 8 + g, 1); break;
    case 11: if (OUT) e = GET(RDY_CTX + 1, C_CTX + 8 + go, 16); break;
    case 12: if (OUT) e = GET(RDY_G, C_GATE, 256); break;
    case 13: if (CONV) e = PUB(SIG_Z, C_Z + (c0 >> 7), n0); break;
    case 14: if (CONV && n0 < CV_REG<MASK>) e = PUB(SIG_Z, C_Z + (c1 >> 7), CV_REG<MASK> - n0); break;
    case 15: if (OUT) e = GET(RDY_Z, C_Z + out_nb(cta), 128); break;
  }
  __syncwarp();
#pragma unroll 1
  for (int i = 0; i < 16; i++) {
    const uint32_t x = __shfl_sync(~0u, e, i), id = (x >> 24) & 127, n = (x >> 8) & 0xffff;
    if (x == 0) continue;
    unsigned* cnt = g_cnt + (x & 255) * CSTRIDE;
    if (x >> 31) {
      mbar_wait_slow(base + SM_SIG + 8 * id, 0);
      if (i == 13) TSA(22);
      if (lane == 0) cnt_publish(cnt, n, i != 14);
    } else {
      cnt_wait(cnt, n);
      if (id < 2) {
        const float4 kn = __ldcg((const float4*)(g_kn2 + kv_slot<MASK>(j + 16 * id) * 128) + lane);
        const uint32_t m = __reduce_max_sync(~0u, max(max(__float_as_uint(kn.x), __float_as_uint(kn.y)), max(__float_as_uint(kn.z), __float_as_uint(kn.w))));
        if (lane == 0) asm volatile("st.shared.u32 [%0], %1;" :: "r"(base + SM_KMAX + 4 * id), "r"(m) : "memory");
      }
      if (lane == 0) mbar_arrive(base + SM_RDY + 8 * id);
    }
    __syncwarp();
    TSA(24 + i);
  }
}

__device__ __forceinline__ void aux_gate(const Params& P, int cta, int aw, int lane) {
  uint4 gw[4];
#pragma unroll
  for (int i = 0; i < 4; i++) gw[i] = __ldg((const uint4*)P.gw + i * 32 + lane);
#pragma unroll 1
  for (int row = cta * 16 + aw * 8; row < cta * 16 + aw * 8 + 8; row++) {
    float a = 0.f;
#pragma unroll
    for (int i = 0; i < 4; i++) {
      const uint4 xv = __ldg((const uint4*)(P.x + (size_t)row * 1024) + i * 32 + lane);
      uint32_t m;
      m = hmul2(xv.x, gw[i].x); a += bf_lo(m) + bf_hi(m); m = hmul2(xv.y, gw[i].y); a += bf_lo(m) + bf_hi(m);
      m = hmul2(xv.z, gw[i].z); a += bf_lo(m) + bf_hi(m); m = hmul2(xv.w, gw[i].w); a += bf_lo(m) + bf_hi(m);
    }
#pragma unroll
    for (int o = 16; o > 0; o >>= 1) a += __shfl_xor_sync(~0u, a, o);
    a = bf_lo(pack_bf16(a, 0.f));
    const float gt = bf_lo(pack_bf16(__fdividef(1.f, 1.f + ex2(-a * 1.4426950408889634f)), 0.f));
    if (lane == 0) g_gate[row] = gt;
    if (GATE_SLEEP) __nanosleep(GATE_SLEEP);
  }
  cnt_signal(g_cnt + C_GATE * CSTRIDE, lane);
  if (aw == 0) { TSA(44); }
}
template<int MASK> __device__ __forceinline__ void aux_pre(const Maps& M, const Params& P, uint32_t base, int cta, int aw, int lane) {
  const uint32_t kb = base + 12 * UNIT, bar = base + SM_PRE;
  const int r = lane >> 2, q = lane & 3;
  const int mi = lane >> 3, row0 = (lane & 6) + 1 - (lane & 1);
  const int ra = (mi * 9 + 1) * 2 + row0;
  const int rb = (mi == 0 ? 3 : mi) * 18 + row0;
  if (PRE_DELAY) mbar_wait_slow(base + SM_BAR + 8 * PRE_DELAY_BAR, 0);
#pragma unroll 1
  for (int it = 0; it < (cta < 96 ? 5 : 4); it++) {
    if (GATE_EARLY && it == PRE_EARLY && MASK == PH_ALL) { mbar_wait_slow(base + SM_SIG + 8 * SIG_ATT, 0); aux_gate(P, cta, aw, lane); }
    if (it == PRE_EARLY && MASK == PH_ALL) mbar_wait_slow(base + SM_SIG + 8 * (SIG_ATT + PRE_HALF), 0);
    const int cg = it ? it * 4 - 3 + (cta >> 5) : 0, tb = cta & 31;
    if (aw == 0 && elect()) {
      mbar_expect(bar, 2 * 9216);
      tma4d(kb, &M.k, cg * 64, 0, tb * 8 - 1, 0, bar, POL(3));
      tma4d(kb + 9216, &M.v, cg * 64, 0, tb * 8 - 1, 0, bar, POL(3));
    }
    const uint2 swl = __ldg((const uint2*)(P.shift + (cg * 64 + aw * 32 + lane) * 4));
    if (tb == 0) {
      uint8_t* e = g_u + (size_t)(cg * 64 + aw * 32 + lane) * UCH + 4096;
      *(uint4*)e = make_uint4(0, 0, 0, 0); *(uint4*)(e + UPITCH) = make_uint4(0, 0, 0, 0);
      *(uint32_t*)(e + 32) = (uint32_t)__bfloat16_as_ushort(P.D[cg * 64 + aw * 32 + lane]) * 0x10001u;
    }
    mbar_wait_slow(bar, it & 1);
#pragma unroll 1
    for (int ol = it ? 0 : cta >> 5; ol < (it ? 4 : (cta >> 5) + 1); ol++) {
      const int oc = aw * 4 + ol;
      const uint32_t s01 = __shfl_sync(~0u, swl.x, ol * 8 + r), s23 = __shfl_sync(~0u, swl.y, ol * 8 + r);
      const uint32_t w0 = __byte_perm(s01, 0, 0x1010), w1 = __byte_perm(s01, 0, 0x3232), w2 = __byte_perm(s23, 0, 0x1010), w3 = __byte_perm(s23, 0, 0x3232);
      const uint32_t pa = kb + ra * 128 + ((oc ^ (ra & 7)) << 4), pb = kb + (mi == 0 ? 9216 : 0) + rb * 128 + ((oc ^ (rb & 7)) << 4);
      uint8_t* e0 = g_u + (uint32_t)((cg * 64 + oc * 8 + r) * UCH + (2040 - tb * 64 - 8 * q) * 2);
#pragma unroll
      for (int hb = 0; hb < 2; hb++) {
        uint32_t k[7], v[5];
        ldsm4t(pa + hb * 1024, k[3], k[4], k[5], k[6]);
        ldsm4t(pa + hb * 1024 + 9216, v[1], v[2], v[3], v[4]);
        ldsm4t(pb + hb * 1024, v[0], k[0], k[1], k[2]);
        uint32_t o1 = __byte_perm(k[1], k[0], 0x5432);
#pragma unroll
        for (int m = 0; m < 5; m++) {
          const uint32_t o2 = __byte_perm(k[m + 2], k[m + 1], 0x5432);
          v[m] = hmul2(hadd2(hadd2(hadd2(hmul2(o1, w3), hmul2(k[m + 1], w2)), hmul2(o2, w1)), hmul2(k[m + 2], w0)), v[m]);
          o1 = o2;
        }
        *(uint4*)(e0 - hb * 64) = make_uint4(v[4], v[3], v[2], v[1]);
        *(uint4*)(e0 - hb * 64 + UPITCH) = make_uint4(__byte_perm(v[4], v[3], 0x5432), __byte_perm(v[3], v[2], 0x5432), __byte_perm(v[2], v[1], 0x5432), __byte_perm(v[1], v[0], 0x5432));
        if (PRE_SLEEP && it >= PRE_EARLY) __nanosleep(PRE_SLEEP);
      }
    }
    bar_sync(5, 64);
    if (aw == 0) { TSA(40 + min(it, 3)); }
    if (aw == 1 && lane == 0) asm volatile("red.release.gpu.global.add.u32 [%0], %1;" :: "l"(g_cnt + (C_U + cg) * CSTRIDE), "r"(it ? 4 : 1) : "memory");
  }
  uint32_t rel;
  asm volatile("mapa.shared::cluster.u32 %0, %1, %2;" : "=r"(rel) : "r"(base + SM_BAR + 128 + 8 * (12 + (lane & 1))), "r"((lane >> 1) & 1));
  if (lane < 4) asm volatile("mbarrier.arrive.shared::cluster.b64 _, [%0], 4;" :: "r"(rel) : "memory");
  if (!(GATE_EARLY && MASK == PH_ALL)) aux_gate(P, cta, aw, lane);
}

template<int MASK> __global__ void __cluster_dims__(2, 1, 1) __launch_bounds__(384, 1) gated_mix_kernel(const __grid_constant__ Maps M, const __grid_constant__ Params P) {
  extern __shared__ __align__(1024) uint8_t smem[];
  const uint32_t base = (uint32_t)__cvta_generic_to_shared(smem);
  const int wi = __shfl_sync(~0u, threadIdx.x >> 5, 0), wg = wi >> 2, warp = wi & 3;
  if (elect()) {
    if (wi < 8) {
      const int cnt = 1 << ((0x10334400 >> (4 * wi)) & 15);
#pragma unroll
      for (int i = 0; i < 8; i++) mbar_init(base + SM_BAR + 64 * wi + 8 * i, cnt);
      asm volatile("fence.mbarrier_init.release.cluster;" ::: "memory");
    } else if (MAP_PF) {
      asm volatile("prefetch.tensormap [%0];" :: "l"(&M.c + (wi - 8)) : "memory");
    }
  }
  const int cta = blockIdx.x;
  const bool first_loads = (MASK & PH_KV) && wi == 8 && cta < NREG;
  const CUtensorMap* mw = (cta & 1) ? &M.wv : &M.wk;
  __syncwarp();
  asm volatile("barrier.cluster.arrive.relaxed.aligned;\nbarrier.cluster.wait.aligned;" ::: "memory");
  if (first_loads && elect()) {
#pragma unroll 1
    for (int it = 0; it < NFIRST; it++) {
      const uint32_t bar = base + SM_BAR + 24 * it, d0 = base + 3 * it * UNIT;
      mbar_expect(bar, 3 * UNIT);
      tma3d_mc(d0 + (1 + (cta & 1)) * UNIT, mw, 0, it * 64, 2 * (cta >> 3), bar);
      tma2d(d0, &M.c, it * 64, (cta & 7) * 256, bar);
    }
  }
  __syncwarp();
  const int lane = threadIdx.x & 31;
#define TS_PRO()
  if (wg == 2) {
    asm volatile("setmaxnreg.dec.sync.aligned.u32 56;");
    TS_PRO();
    TS(2, 62);
    if (warp == 0) producer<MASK>(M, P, base, cta, lane);
    else if (warp == 1) sync_agent<MASK>(base, cta, lane);
    else if (cta < NREG) {
      if (MASK & PH_PRE) aux_pre<MASK>(M, P, base, cta, warp - 2, lane);
      if (MASK & PH_OUT) producer2<MASK>(M, P, base, cta, warp - 2, lane);
    }
    if (warp == 1) {
      if (MASK & PH_OUT) {
        unsigned old = 0;
        if (lane == 0) asm volatile("atom.relaxed.gpu.global.add.u32 %0, [%1], 1;" : "=r"(old) : "l"(g_cnt + C_EXIT * CSTRIDE) : "memory");
        old = __shfl_sync(~0u, old, 0);
        if (old == NCTA - 1) for (int i = lane; i < C_NUM; i += 32) g_cnt[i * CSTRIDE] = 0;
      }
      mbar_wait_slow(base + SM_SIG + 8 * SIG_DONE, 0);
      if (cta >= NREG || !(MASK & PH_OUT)) { cluster_arrive(); cluster_wait(); }
    }
  } else {
    asm volatile("setmaxnreg.inc.sync.aligned.u32 224;");
    TS_PRO();
    uint32_t rel;
    asm volatile("mapa.shared::cluster.u32 %0, %1, %2;" : "=r"(rel) : "r"(base + SM_BAR + 128 + 8 * (lane & 15)), "r"(lane >> 4));
    Cons c{base, rel, 0u, lane, warp, wg, (cta * 3 + wg) * 2048};
    if (wg == 1) bar_arrive(1, 256);
    TS(wg, 0);
    if (cta < NREG) {
      const int g = cta & 7, j = cta >> 3;
      Pend w = {};
#pragma unroll 1
      for (int half = 0; half < 2; half++) {
        const int h = j + 16 * half;
        if (MASK & PH_KV) cons_kv<(MASK & PH_ATT) != 0>(c, h, kv_slot<MASK>(h), g, w, half == 1 && (MASK & PH_ATT));
        TS(wg, 1 + 4 * half);
        if (MASK & PH_ATT) {
          Att a;
          cons_q<(MASK & PH_KV) != 0>(c, h, w, a.o);
          TS(wg, 2 + 4 * half);
          cons_att(c, a, h, g, w);
          if (half == 0) c.signal(SIG_WAR);
#pragma unroll
          for (int i = 0; i < 8; i++) w.hi[i] = make_uint4(0, 0, 0, 0);
          TS(wg, 3 + 4 * half);
          if (MASK != PH_ALL) { tile_store<0, 4>(w.lo, w.dst, lane); c.signal(SIG_CTX + half); }
        } else if (MASK & PH_KV) {
          out_piece<SCH_KV, true>(c, w, 0, true);
          for (int ks = 1; ks < 8; ks++) out_piece<SCH_KV, false>(c, w, ks, true);
          c.signal(SIG_KV + half);
        }
      }
      if (MASK & PH_OUT) cons_out<MASK>(c, M, P, cta, w);
    }
    if (cta >= NREG || !(MASK & PH_OUT)) {
      if (MASK & PH_CONV) cons_conv<MASK>(c, cta, cta < NREG ? CV_REG<MASK> : CV_EXTRA<MASK>);
      TS(wg, 9);
      c.signal(SIG_DONE);
      cluster_arrive();
    }
    TS(wg, 10);
  }
}

typedef CUresult (*EncFn)(CUtensorMap*, CUtensorMapDataType, cuuint32_t, void*, const cuuint64_t*, const cuuint64_t*, const cuuint32_t*, const cuuint32_t*,
                          CUtensorMapInterleave, CUtensorMapSwizzle, CUtensorMapL2promotion, CUtensorMapFloatOOBfill);
static void enc(EncFn f, CUtensorMap* m, const void* ptr, int rank, const cuuint64_t* dims, const cuuint64_t* strides, const cuuint32_t* box, CUtensorMapSwizzle sw,
                CUtensorMapDataType dt = CU_TENSOR_MAP_DATA_TYPE_BFLOAT16) {
  const cuuint32_t es[4] = {1, 1, 1, 1};
  f(m, dt, rank, (void*)ptr, dims, strides, box, es, CU_TENSOR_MAP_INTERLEAVE_NONE, sw, CU_TENSOR_MAP_L2_PROMOTION_L2_256B, CU_TENSOR_MAP_FLOAT_OOB_FILL_NONE);
}
static void enc2(EncFn f, CUtensorMap* m, const void* ptr, int cols, int rows, int brows) {
  const cuuint64_t d[2] = {(cuuint64_t)cols, (cuuint64_t)rows}, s[1] = {(cuuint64_t)cols * 2}; const cuuint32_t b[2] = {64, (cuuint32_t)brows};
  enc(f, m, ptr, 2, d, s, b, CU_TENSOR_MAP_SWIZZLE_128B);
}
static void encw(EncFn f, CUtensorMap* m, const void* ptr, int cols, int rows) {
  const cuuint64_t d[3] = {64, (cuuint64_t)rows, (cuuint64_t)cols / 64}, s[2] = {(cuuint64_t)cols * 2, 128}; const cuuint32_t b[3] = {64, 64, 2};
  enc(f, m, ptr, 3, d, s, b, CU_TENSOR_MAP_SWIZZLE_128B);
}
extern "C" void kernel_launch(void* const* d_in, const int* in_sizes, int n_in, void* d_out, int out_size) {
  static EncFn fn = nullptr;
  static int ncl = 0;
  static void* zptr = nullptr;
  static void* tptr = nullptr;
  if (!fn) {
    void* p = nullptr; cudaDriverEntryPointQueryResult qr;
    cudaGetDriverEntryPoint("cuTensorMapEncodeTiled", &p, cudaEnableDefault, &qr);
    fn = (EncFn)p;
    cudaFuncSetAttribute(gated_mix_kernel<PH_ALL>, cudaFuncAttributeMaxDynamicSharedMemorySize, SMEM_BYTES);
    cudaFuncSetAttribute(gated_mix_kernel<PH_PRE | PH_KV>, cudaFuncAttributeMaxDynamicSharedMemorySize, SMEM_BYTES);
    cudaFuncSetAttribute(gated_mix_kernel<PH_ATT | PH_CONV>, cudaFuncAttributeMaxDynamicSharedMemorySize, SMEM_BYTES);
    cudaFuncSetAttribute(gated_mix_kernel<PH_OUT>, cudaFuncAttributeMaxDynamicSharedMemorySize, SMEM_BYTES);
    cudaLaunchConfig_t cfg = {}; cfg.gridDim = NCTA; cfg.blockDim = 384; cfg.dynamicSmemBytes = SMEM_BYTES;
    cudaLaunchAttribute at; at.id = cudaLaunchAttributeClusterDimension; at.val.clusterDim.x = 2; at.val.clusterDim.y = 1; at.val.clusterDim.z = 1;
    cfg.attrs = &at; cfg.numAttrs = 1;
    cudaOccupancyMaxActiveClusters(&ncl, gated_mix_kernel<PH_ALL>, &cfg);
    cudaGetSymbolAddress(&zptr, g_z);
    cudaGetSymbolAddress(&tptr, g_T);
  }
  Maps M;
  enc2(fn, &M.x, d_in[0], 1024, 2048, 128);
  enc2(fn, &M.c, d_in[7], 512, 2048, 128);
  enc2(fn, &M.wq, d_in[8], 4096, 1024, 64);
  encw(fn, &M.wk, d_in[9], 4096, 512);
  encw(fn, &M.wv, d_in[10], 4096, 512);
  encw(fn, &M.wo, d_in[11], 1024, 4096);
  { const cuuint64_t d[3] = {64, 32, 1024}, s[2] = {128, 4096}; const cuuint32_t b[3] = {64, 40, 1}; enc(fn, &M.h, d_in[4], 3, d, s, b, CU_TENSOR_MAP_SWIZZLE_NONE); }
  enc2(fn, &M.z, zptr, 2048, 1024, 128);
  enc2(fn, &M.out, d_out, 1024, 2048, 16);
  { const cuuint64_t d[2] = {512, 512 * 16}, s[1] = {2048}; const cuuint32_t b[2] = {256, 8};
    enc(fn, &M.ctx, tptr, 2, d, s, b, CU_TENSOR_MAP_SWIZZLE_NONE, CU_TENSOR_MAP_DATA_TYPE_UINT32); }
  { const cuuint64_t d[4] = {1024, 2, 256, 4}, s[3] = {2048, 16384, 4096}; const cuuint32_t b[4] = {64, 2, 9, 4};
    enc(fn, &M.k, d_in[1], 4, d, s, b, CU_TENSOR_MAP_SWIZZLE_128B); enc(fn, &M.v, d_in[2], 4, d, s, b, CU_TENSOR_MAP_SWIZZLE_128B); }
  Params P{(const __nv_bfloat16*)d_in[0], (const __nv_bfloat16*)d_in[3],
           (const __nv_bfloat16*)d_in[5], (const __nv_bfloat16*)d_in[12], (__nv_bfloat16*)d_out};
  bool split = 2 * ncl < NCTA;
  if (!split) {
    gated_mix_kernel<PH_ALL><<<NCTA, 384, SMEM_BYTES>>>(M, P);
  } else {
    gated_mix_kernel<PH_PRE | PH_KV><<<NCTA, 384, SMEM_BYTES>>>(M, P);
    gated_mix_kernel<PH_ATT | PH_CONV><<<NCTA, 384, SMEM_BYTES>>>(M, P);
    gated_mix_kernel<PH_OUT><<<NCTA, 384, SMEM_BYTES>>>(M, P);
  }
}
```

```cpp
#include <cuda_runtime.h>
#include <cuda.h>
#include <cuda_bf16.h>
#include <stdint.h>

template<int TB> __device__ __forceinline__ void wgmma_ss_n256(float (&d)[128], uint64_t da, uint64_t db, int scale_d) {
  asm volatile("{\n.reg .pred p;\nsetp.ne.b32 p, %130, 0;\n"
    "wgmma.mma_async.sync.aligned.m64n256k16.f32.bf16.bf16 {%0, %1, %2, %3, %4, %5, %6, %7, %8, %9, %10, %11, %12, %13, %14, %15, %16, %17, %18, %19, %20, %21, %22, %23, %24, %25, %26, %27, %28, %29, %30, %31, %32, %33, %34, %35, %36, %37, %38, %39, %40, %41, %42, %43, %44, %45, %46, %47, %48, %49, %50, %51, %52, %53, %54, %55, %56, %57, %58, %59, %60, %61, %62, %63, %64, %65, %66, %67, %68, %69, %70, %71, %72, %73, %74, %75, %76, %77, %78, %79, %80, %81, %82, %83, %84, %85, %86, %87, %88, %89, %90, %91, %92, %93, %94, %95, %96, %97, %98, %99, %100, %101, %102, %103, %104, %105, %106, %107, %108, %109, %110, %111, %112, %113, %114, %115, %116, %117, %118, %119, %120, %121, %122, %123, %124, %125, %126, %127}, %128, %129, p, 1, 1, 0, %131;\n}\n"
    : "+f"(d[0]), "+f"(d[1]), "+f"(d[2]), "+f"(d[3]), "+f"(d[4]), "+f"(d[5]), "+f"(d[6]), "+f"(d[7]), "+f"(d[8]), "+f"(d[9]), "+f"(d[10]), "+f"(d[11]), "+f"(d[12]), "+f"(d[13]), "+f"(d[14]), "+f"(d[15]), "+f"(d[16]), "+f"(d[17]), "+f"(d[18]), "+f"(d[19]), "+f"(d[20]), "+f"(d[21]), "+f"(d[22]), "+f"(d[23]), "+f"(d[24]), "+f"(d[25]), "+f"(d[26]), "+f"(d[27]), "+f"(d[28]), "+f"(d[29]), "+f"(d[30]), "+f"(d[31]), "+f"(d[32]), "+f"(d[33]), "+f"(d[34]), "+f"(d[35]), "+f"(d[36]), "+f"(d[37]), "+f"(d[38]), "+f"(d[39]), "+f"(d[40]), "+f"(d[41]), "+f"(d[42]), "+f"(d[43]), "+f"(d[44]), "+f"(d[45]), "+f"(d[46]), "+f"(d[47]), "+f"(d[48]), "+f"(d[49]), "+f"(d[50]), "+f"(d[51]), "+f"(d[52]), "+f"(d[53]), "+f"(d[54]), "+f"(d[55]), "+f"(d[56]), "+f"(d[57]), "+f"(d[58]), "+f"(d[59]), "+f"(d[60]), "+f"(d[61]), "+f"(d[62]), "+f"(d[63]), "+f"(d[64]), "+f"(d[65]), "+f"(d[66]), "+f"(d[67]), "+f"(d[68]), "+f"(d[69]), "+f"(d[70]), "+f"(d[71]), "+f"(d[72]), "+f"(d[73]), "+f"(d[74]), "+f"(d[75]), "+f"(d[76]), "+f"(d[77]), "+f"(d[78]), "+f"(d[79]), "+f"(d[80]), "+f"(d[81]), "+f"(d[82]), "+f"(d[83]), "+f"(d[84]), "+f"(d[85]), "+f"(d[86]), "+f"(d[87]), "+f"(d[88]), "+f"(d[89]), "+f"(d[90]), "+f"(d[91]), "+f"(d[92]), "+f"(d[93]), "+f"(d[94]), "+f"(d[95]), "+f"(d[96]), "+f"(d[97]), "+f"(d[98]), "+f"(d[99]), "+f"(d[100]), "+f"(d[101]), "+f"(d[102]), "+f"(d[103]), "+f"(d[104]), "+f"(d[105]), "+f"(d[106]), "+f"(d[107]), "+f"(d[108]), "+f"(d[109]), "+f"(d[110]), "+f"(d[111]), "+f"(d[112]), "+f"(d[113]), "+f"(d[114]), "+f"(d[115]), "+f"(d[116]), "+f"(d[117]), "+f"(d[118]), "+f"(d[119]), "+f"(d[120]), "+f"(d[121]), "+f"(d[122]), "+f"(d[123]), "+f"(d[124]), "+f"(d[125]), "+f"(d[126]), "+f"(d[127])
    : "l"(da), "l"(db), "r"(scale_d), "n"(TB));
}
template<int TB> __device__ __forceinline__ void wgmma_ss_n128(float (&d)[64], uint64_t da, uint64_t db, int scale_d) {
  asm volatile("{\n.reg .pred p;\nsetp.ne.b32 p, %66, 0;\n"
    "wgmma.mma_async.sync.aligned.m64n128k16.f32.bf16.bf16 {%0, %1, %2, %3, %4, %5, %6, %7, %8, %9, %10, %11, %12, %13, %14, %15, %16, %17, %18, %19, %20, %21, %22, %23, %24, %25, %26, %27, %28, %29, %30, %31, %32, %33, %34, %35, %36, %37, %38, %39, %40, %41, %42, %43, %44, %45, %46, %47, %48, %49, %50, %51, %52, %53, %54, %55, %56, %57, %58, %59, %60, %61, %62, %63}, %64, %65, p, 1, 1, 0, %67;\n}\n"
    : "+f"(d[0]), "+f"(d[1]), "+f"(d[2]), "+f"(d[3]), "+f"(d[4]), "+f"(d[5]), "+f"(d[6]), "+f"(d[7]), "+f"(d[8]), "+f"(d[9]), "+f"(d[10]), "+f"(d[11]), "+f"(d[12]), "+f"(d[13]), "+f"(d[14]), "+f"(d[15]), "+f"(d[16]), "+f"(d[17]), "+f"(d[18]), "+f"(d[19]), "+f"(d[20]), "+f"(d[21]), "+f"(d[22]), "+f"(d[23]), "+f"(d[24]), "+f"(d[25]), "+f"(d[26]), "+f"(d[27]), "+f"(d[28]), "+f"(d[29]), "+f"(d[30]), "+f"(d[31]), "+f"(d[32]), "+f"(d[33]), "+f"(d[34]), "+f"(d[35]), "+f"(d[36]), "+f"(d[37]), "+f"(d[38]), "+f"(d[39]), "+f"(d[40]), "+f"(d[41]), "+f"(d[42]), "+f"(d[43]), "+f"(d[44]), "+f"(d[45]), "+f"(d[46]), "+f"(d[47]), "+f"(d[48]), "+f"(d[49]), "+f"(d[50]), "+f"(d[51]), "+f"(d[52]), "+f"(d[53]), "+f"(d[54]), "+f"(d[55]), "+f"(d[56]), "+f"(d[57]), "+f"(d[58]), "+f"(d[59]), "+f"(d[60]), "+f"(d[61]), "+f"(d[62]), "+f"(d[63])
    : "l"(da), "l"(db), "r"(scale_d), "n"(TB));
}
template<int TB> __device__ __forceinline__ void wgmma_rs_n32(float (&d)[16], uint32_t a0, uint32_t a1, uint32_t a2, uint32_t a3, uint64_t db, int scale_d) {
  asm volatile("{\n.reg .pred p;\nsetp.ne.b32 p, %21, 0;\n"
    "wgmma.mma_async.sync.aligned.m64n32k16.f32.bf16.bf16 {%0, %1, %2, %3, %4, %5, %6, %7, %8, %9, %10, %11, %12, %13, %14, %15}, {%16, %17, %18, %19}, %20, p, 1, 1, %22;\n}\n"
    : "+f"(d[0]), "+f"(d[1]), "+f"(d[2]), "+f"(d[3]), "+f"(d[4]), "+f"(d[5]), "+f"(d[6]), "+f"(d[7]), "+f"(d[8]), "+f"(d[9]), "+f"(d[10]), "+f"(d[11]), "+f"(d[12]), "+f"(d[13]), "+f"(d[14]), "+f"(d[15])
    : "r"(a0), "r"(a1), "r"(a2), "r"(a3), "l"(db), "r"(scale_d), "n"(TB));
}
__device__ __forceinline__ void wgmma_pv_sel(float (&d)[64], const uint32_t (&p)[32], uint64_t db, int full, int acc) {
  asm volatile("{\n.reg .pred q, s;\n.reg .b64 t;\nsetp.ne.b32 s, %98, 0;\nsetp.eq.b32 q, %97, 0;\n@q bra.uni LH;\n"
    "wgmma.fence.sync.aligned;\n"
    "add.s64 t, %96, 0;\nwgmma.mma_async.sync.aligned.m64n128k16.f32.bf16.bf16 {%0, %1, %2, %3, %4, %5, %6, %7, %8, %9, %10, %11, %12, %13, %14, %15, %16, %17, %18, %19, %20, %21, %22, %23, %24, %25, %26, %27, %28, %29, %30, %31, %32, %33, %34, %35, %36, %37, %38, %39, %40, %41, %42, %43, %44, %45, %46, %47, %48, %49, %50, %51, %52, %53, %54, %55, %56, %57, %58, %59, %60, %61, %62, %63}, {%64, %65, %66, %67}, t, s, 1, 1, 1;\n"
    "add.s64 t, %96, 256;\nwgmma.mma_async.sync.aligned.m64n128k16.f32.bf16.bf16 {%0, %1, %2, %3, %4, %5, %6, %7, %8, %9, %10, %11, %12, %13, %14, %15, %16, %17, %18, %19, %20, %21, %22, %23, %24, %25, %26, %27, %28, %29, %30, %31, %32, %33, %34, %35, %36, %37, %38, %39, %40, %41, %42, %43, %44, %45, %46, %47, %48, %49, %50, %51, %52, %53, %54, %55, %56, %57, %58, %59, %60, %61, %62, %63}, {%68, %69, %70, %71}, t, 1, 1, 1, 1;\n"
    "add.s64 t, %96, 512;\nwgmma.mma_async.sync.aligned.m64n128k16.f32.bf16.bf16 {%0, %1, %2, %3, %4, %5, %6, %7, %8, %9, %10, %11, %12, %13, %14, %15, %16, %17, %18, %19, %20, %21, %22, %23, %24, %25, %26, %27, %28, %29, %30, %31, %32, %33, %34, %35, %36, %37, %38, %39, %40, %41, %42, %43, %44, %45, %46, %47, %48, %49, %50, %51, %52, %53, %54, %55, %56, %57, %58, %59, %60, %61, %62, %63}, {%72, %73, %74, %75}, t, 1, 1, 1, 1;\n"
    "add.s64 t, %96, 768;\nwgmma.mma_async.sync.aligned.m64n128k16.f32.bf16.bf16 {%0, %1, %2, %3, %4, %5, %6, %7, %8, %9, %10, %11, %12, %13, %14, %15, %16, %17, %18, %19, %20, %21, %22, %23, %24, %25, %26, %27, %28, %29, %30, %31, %32, %33, %34, %35, %36, %37, %38, %39, %40, %41, %42, %43, %44, %45, %46, %47, %48, %49, %50, %51, %52, %53, %54, %55, %56, %57, %58, %59, %60, %61, %62, %63}, {%76, %77, %78, %79}, t, 1, 1, 1, 1;\n"
    "add.s64 t, %96, 1024;\nwgmma.mma_async.sync.aligned.m64n128k16.f32.bf16.bf16 {%0, %1, %2, %3, %4, %5, %6, %7, %8, %9, %10, %11, %12, %13, %14, %15, %16, %17, %18, %19, %20, %21, %22, %23, %24, %25, %26, %27, %28, %29, %30, %31, %32, %33, %34, %35, %36, %37, %38, %39, %40, %41, %42, %43, %44, %45, %46, %47, %48, %49, %50, %51, %52, %53, %54, %55, %56, %57, %58, %59, %60, %61, %62, %63}, {%80, %81, %82, %83}, t, 1, 1, 1, 1;\n"
    "add.s64 t, %96, 1280;\nwgmma.mma_async.sync.aligned.m64n128k16.f32.bf16.bf16 {%0, %1, %2, %3, %4, %5, %6, %7, %8, %9, %10, %11, %12, %13, %14, %15, %16, %17, %18, %19, %20, %21, %22, %23, %24, %25, %26, %27, %28, %29, %30, %31, %32, %33, %34, %35, %36, %37, %38, %39, %40, %41, %42, %43, %44, %45, %46, %47, %48, %49, %50, %51, %52, %53, %54, %55, %56, %57, %58, %59, %60, %61, %62, %63}, {%84, %85, %86, %87}, t, 1, 1, 1, 1;\n"
    "add.s64 t, %96, 1536;\nwgmma.mma_async.sync.aligned.m64n128k16.f32.bf16.bf16 {%0, %1, %2, %3, %4, %5, %6, %7, %8, %9, %10, %11, %12, %13, %14, %15, %16, %17, %18, %19, %20, %21, %22, %23, %24, %25, %26, %27, %28, %29, %30, %31, %32, %33, %34, %35, %36, %37, %38, %39, %40, %41, %42, %43, %44, %45, %46, %47, %48, %49, %50, %51, %52, %53, %54, %55, %56, %57, %58, %59, %60, %61, %62, %63}, {%88, %89, %90, %91}, t, 1, 1, 1, 1;\n"
    "add.s64 t, %96, 1792;\nwgmma.mma_async.sync.aligned.m64n128k16.f32.bf16.bf16 {%0, %1, %2, %3, %4, %5, %6, %7, %8, %9, %10, %11, %12, %13, %14, %15, %16, %17, %18, %19, %20, %21, %22, %23, %24, %25, %26, %27, %28, %29, %30, %31, %32, %33, %34, %35, %36, %37, %38, %39, %40, %41, %42, %43, %44, %45, %46, %47, %48, %49, %50, %51, %52, %53, %54, %55, %56, %57, %58, %59, %60, %61, %62, %63}, {%92, %93, %94, %95}, t, 1, 1, 1, 1;\n"
    "wgmma.commit_group.sync.aligned;\n"
    "bra.uni LE;\nLH:\n"
    "wgmma.fence.sync.aligned;\n"
    "add.s64 t, %96, 0;\nwgmma.mma_async.sync.aligned.m64n128k16.f32.bf16.bf16 {%0, %1, %2, %3, %4, %5, %6, %7, %8, %9, %10, %11, %12, %13, %14, %15, %16, %17, %18, %19, %20, %21, %22, %23, %24, %25, %26, %27, %28, %29, %30, %31, %32, %33, %34, %35, %36, %37, %38, %39, %40, %41, %42, %43, %44, %45, %46, %47, %48, %49, %50, %51, %52, %53, %54, %55, %56, %57, %58, %59, %60, %61, %62, %63}, {%80, %81, %82, %83}, t, s, 1, 1, 1;\n"
    "add.s64 t, %96, 256;\nwgmma.mma_async.sync.aligned.m64n128k16.f32.bf16.bf16 {%0, %1, %2, %3, %4, %5, %6, %7, %8, %9, %10, %11, %12, %13, %14, %15, %16, %17, %18, %19, %20, %21, %22, %23, %24, %25, %26, %27, %28, %29, %30, %31, %32, %33, %34, %35, %36, %37, %38, %39, %40, %41, %42, %43, %44, %45, %46, %47, %48, %49, %50, %51, %52, %53, %54, %55, %56, %57, %58, %59, %60, %61, %62, %63}, {%84, %85, %86, %87}, t, 1, 1, 1, 1;\n"
    "add.s64 t, %96, 512;\nwgmma.mma_async.sync.aligned.m64n128k16.f32.bf16.bf16 {%0, %1, %2, %3, %4, %5, %6, %7, %8, %9, %10, %11, %12, %13, %14, %15, %16, %17, %18, %19, %20, %21, %22, %23, %24, %25, %26, %27, %28, %29, %30, %31, %32, %33, %34, %35, %36, %37, %38, %39, %40, %41, %42, %43, %44, %45, %46, %47, %48, %49, %50, %51, %52, %53, %54, %55, %56, %57, %58, %59, %60, %61, %62, %63}, {%88, %89, %90, %91}, t, 1, 1, 1, 1;\n"
    "add.s64 t, %96, 768;\nwgmma.mma_async.sync.aligned.m64n128k16.f32.bf16.bf16 {%0, %1, %2, %3, %4, %5, %6, %7, %8, %9, %10, %11, %12, %13, %14, %15, %16, %17, %18, %19, %20, %21, %22, %23, %24, %25, %26, %27, %28, %29, %30, %31, %32, %33, %34, %35, %36, %37, %38, %39, %40, %41, %42, %43, %44, %45, %46, %47, %48, %49, %50, %51, %52, %53, %54, %55, %56, %57, %58, %59, %60, %61, %62, %63}, {%92, %93, %94, %95}, t, 1, 1, 1, 1;\n"
    "wgmma.commit_group.sync.aligned;\n"
    "LE:\n}\n"
    : "+f"(d[0]), "+f"(d[1]), "+f"(d[2]), "+f"(d[3]), "+f"(d[4]), "+f"(d[5]), "+f"(d[6]), "+f"(d[7]), "+f"(d[8]), "+f"(d[9]), "+f"(d[10]), "+f"(d[11]), "+f"(d[12]), "+f"(d[13]), "+f"(d[14]), "+f"(d[15]), "+f"(d[16]), "+f"(d[17]), "+f"(d[18]), "+f"(d[19]), "+f"(d[20]), "+f"(d[21]), "+f"(d[22]), "+f"(d[23]), "+f"(d[24]), "+f"(d[25]), "+f"(d[26]), "+f"(d[27]), "+f"(d[28]), "+f"(d[29]), "+f"(d[30]), "+f"(d[31]), "+f"(d[32]), "+f"(d[33]), "+f"(d[34]), "+f"(d[35]), "+f"(d[36]), "+f"(d[37]), "+f"(d[38]), "+f"(d[39]), "+f"(d[40]), "+f"(d[41]), "+f"(d[42]), "+f"(d[43]), "+f"(d[44]), "+f"(d[45]), "+f"(d[46]), "+f"(d[47]), "+f"(d[48]), "+f"(d[49]), "+f"(d[50]), "+f"(d[51]), "+f"(d[52]), "+f"(d[53]), "+f"(d[54]), "+f"(d[55]), "+f"(d[56]), "+f"(d[57]), "+f"(d[58]), "+f"(d[59]), "+f"(d[60]), "+f"(d[61]), "+f"(d[62]), "+f"(d[63])
    : "r"(p[0]), "r"(p[1]), "r"(p[2]), "r"(p[3]), "r"(p[4]), "r"(p[5]), "r"(p[6]), "r"(p[7]), "r"(p[8]), "r"(p[9]), "r"(p[10]), "r"(p[11]), "r"(p[12]), "r"(p[13]), "r"(p[14]), "r"(p[15]), "r"(p[16]), "r"(p[17]), "r"(p[18]), "r"(p[19]), "r"(p[20]), "r"(p[21]), "r"(p[22]), "r"(p[23]), "r"(p[24]), "r"(p[25]), "r"(p[26]), "r"(p[27]), "r"(p[28]), "r"(p[29]), "r"(p[30]), "r"(p[31]), "l"(db), "r"(full), "r"(acc) : "memory");
}

constexpr int NCTA = 132, NREG = 128;
constexpr int UNIT = 16384, NUNIT = 14;
constexpr uint32_t SMEM_BASE = 1024;
constexpr int SM_BAR = NUNIT * UNIT;
constexpr int SM_GATE = SM_BAR + 1024;
constexpr int SMEM_BYTES = SM_BAR + 1536;
constexpr int UPITCH = 4160, UCH = 2 * UPITCH;
constexpr float QSCALE = 0.08838834764831845f * 1.4426950408889634f;
constexpr float BOUND2 = 48.f * 48.f / 1.15f;
#define CONV_REG 5
constexpr int C_KV = 0;
constexpr int C_CTX = 32;
constexpr int C_U = 48;
constexpr int C_Z = 80;
constexpr int C_GATE = 88;
constexpr int C_EXIT = 89;
#define PRE_EARLY 2
#define PRE_HALF 1
#define ATT_SPLIT 6
#define NFIRST 2
#define PRE_DELAY 0
#define MAP_PF 1
#define FINAL_ST 1
#define Z_AT 60
#define PRE_DELAY_BAR 9
#define PRE_FMA 0
#define PRE_SLEEP 300
#define GATE_SLEEP 1000
#define GATE_EARLY 1
#define OC_S0 2
#define OC_S1 11
#define OC_POST 1
#define OC_L0 18
#define OC_L1 18
#define PF 0
#define PF_AT 26
#define PF_KS 8
#define ST_1 4
#define ST_D 2
#define ST_0 1
#define ST_0D 0
#define SCH_KV 0x6665544433221100ull
#define SCH_Q 0x6665544433221100ull
#define NK_AT 1
#ifndef NV_AT
#define NV_AT 3
#endif
#define DS_A 3
#define DS_B 6
#define FAST_AT 0
#define XSLOT 1
#define EF 127
#define POL(bit) (((EF >> (bit)) & 1) != 0)
constexpr int C_WAR = 96;
constexpr int C_NUM = 112;
constexpr int CSTRIDE = 32;
constexpr int SM_KMAX = SM_BAR + 640, SM_DUMMY = SM_BAR + 648, SM_PRE = SM_BAR + 112, SM_SIG = SM_BAR + 256, SM_RDY = SM_BAR + 384;
enum { SIG_KV = 0, SIG_CTX = 2, SIG_Z = 4, SIG_DONE = 8, SIG_WAR = 9, SIG_ATT = 10 };
enum { RDY_KV = 0, RDY_CTX = 2, RDY_WAR = 4, RDY_G = 5, RDY_X = 6, RDY_U = 8, RDY_Z = 9 };
enum { PH_PRE = 1, PH_KV = 2, PH_ATT = 4, PH_CONV = 8, PH_OUT = 16, PH_ALL = 31 };

constexpr uint32_t T_CTX = 0, T_KV = 16 * 32 * 32768, T_BYTES = T_KV + 32 * 16 * 65536;
__device__ __align__(1024) uint8_t g_T[T_BYTES];
__device__ __align__(1024) uint8_t g_u[1024 * UCH];
__device__ __align__(1024) __nv_bfloat16 g_z[1024 * 2048];
__device__ __align__(1024) float g_gate[2048];
__device__ __align__(1024) float g_kn2[32 * 128];
__device__ __align__(1024) unsigned g_cnt[C_NUM * CSTRIDE];

struct __align__(64) Maps { CUtensorMap c, wk, wv, x, wq, wo, h, z, out, ctx, k, v; };
struct Params {
  const __nv_bfloat16 *x, *shift, *D, *gw;
  __nv_bfloat16* out;
};

__device__ __forceinline__ void wg_fence() { asm volatile("wgmma.fence.sync.aligned;" ::: "memory"); }
__device__ __forceinline__ void wg_commit() { asm volatile("wgmma.commit_group.sync.aligned;" ::: "memory"); }
template<int N> __device__ __forceinline__ void wg_wait() { asm volatile("wgmma.wait_group.sync.aligned %0;" :: "n"(N) : "memory"); }
__device__ __forceinline__ uint64_t odesc(uint32_t addr, uint32_t lbo, uint32_t sbo, uint32_t swz) {
  uint64_t d = (uint64_t)(addr >> 4) + (((uint64_t)(lbo >> 4) << 16) | ((uint64_t)(sbo >> 4) << 32) | ((uint64_t)swz << 62));
  asm volatile("" : "+l"(d));
  return d;
}
__device__ __forceinline__ void mbar_init(uint32_t bar, int cnt) { asm volatile("mbarrier.init.shared::cta.b64 [%0], %1;" :: "r"(bar), "r"(cnt)); }
__device__ __forceinline__ void mbar_expect(uint32_t bar, uint32_t bytes) { asm volatile("mbarrier.arrive.expect_tx.shared::cta.b64 _, [%0], %1;" :: "r"(bar), "r"(bytes) : "memory"); }
__device__ __forceinline__ void mbar_arrive(uint32_t bar) { asm volatile("mbarrier.arrive.shared::cta.b64 _, [%0];" :: "r"(bar) : "memory"); }
__device__ __forceinline__ void mbar_arrive_n(uint32_t bar, int n) { asm volatile("mbarrier.arrive.shared::cta.b64 _, [%0], %1;" :: "r"(bar), "r"(n) : "memory"); }
__device__ __forceinline__ void mbar_wait(uint32_t bar, uint32_t parity) {
  asm volatile("{\n.reg .pred p;\nLW:\nmbarrier.try_wait.parity.shared::cta.b64 p, [%0], %1;\n@!p bra LW;\n}\n" :: "r"(bar), "r"(parity) : "memory");
}
__device__ __forceinline__ void mbar_wait_slow(uint32_t bar, uint32_t parity) {
  asm volatile("{\n.reg .pred p;\n.reg .u32 n;\nmov.u32 n, 0;\n"
    "LW:\nmbarrier.test_wait.parity.shared::cta.b64 p, [%0], %1;\n@p bra LD;\n"
    "nanosleep.u32 128;\nadd.u32 n, n, 1;\nsetp.lt.u32 p, n, 4194304;\n@p bra LW;\ntrap;\nLD:\n}\n" :: "r"(bar), "r"(parity) : "memory");
}
__device__ __forceinline__ void mbar_wait_all(uint32_t bar, uint32_t parity) {
  asm volatile("{\n.reg .pred p, q;\nLW:\nmbarrier.try_wait.parity.shared::cta.b64 p, [%0], %1;\nvote.sync.all.pred q, p, 0xffffffff;\n@!q bra.uni LW;\n}\n" :: "r"(bar), "r"(parity) : "memory");
}
__device__ __forceinline__ void cnt_wait(const unsigned* p, unsigned target) {
  asm volatile("{\n.reg .pred p;\n.reg .u32 n, v;\nmov.u32 n, 0;\n"
    "LW:\nld.relaxed.gpu.global.u32 v, [%0];\nsetp.ge.u32 p, v, %1;\n@p bra LD;\n"
    "nanosleep.u32 64;\nadd.u32 n, n, 1;\nsetp.lt.u32 p, n, 4194304;\n@p bra LW;\ntrap;\nLD:\nfence.acquire.gpu;\nfence.proxy.async.global;\n}\n" :: "l"(p), "r"(target) : "memory");
}
__device__ __forceinline__ void cnt_signal(unsigned* p, int lane) {
  __syncwarp();
  if (lane == 0) asm volatile("red.release.gpu.global.add.u32 [%0], 1;" :: "l"(p) : "memory");
}
__device__ __forceinline__ void cnt_publish(unsigned* p, unsigned n, bool fence) {
  if (fence) asm volatile("fence.release.gpu;" ::: "memory");
  asm volatile("red.relaxed.gpu.global.add.u32 [%0], %1;" :: "l"(p), "r"(n) : "memory");
}
__device__ __forceinline__ uint64_t pol_first() { uint64_t p; asm("createpolicy.fractional.L2::evict_first.b64 %0, 1.0;" : "=l"(p)); return p; }
__device__ __forceinline__ void bulk_g2s(uint32_t dst, const void* src, uint32_t bytes, uint32_t bar, bool stream = false) {
  if (stream) asm volatile("cp.async.bulk.shared::cluster.global.mbarrier::complete_tx::bytes.L2::cache_hint [%0], [%1], %2, [%3], %4;" :: "r"(dst), "l"(src), "r"(bytes), "r"(bar), "l"(pol_first()) : "memory");
  else asm volatile("cp.async.bulk.shared::cluster.global.mbarrier::complete_tx::bytes [%0], [%1], %2, [%3];" :: "r"(dst), "l"(src), "r"(bytes), "r"(bar) : "memory");
}
__device__ __forceinline__ void tma2d(uint32_t dst, const CUtensorMap* m, int x, int y, uint32_t bar, bool stream = false) {
  if (stream) asm volatile("cp.async.bulk.tensor.2d.shared::cluster.global.mbarrier::complete_tx::bytes.L2::cache_hint [%0], [%1, {%3, %4}], [%2], %5;" :: "r"(dst), "l"(m), "r"(bar), "r"(x), "r"(y), "l"(pol_first()) : "memory");
  else asm volatile("cp.async.bulk.tensor.2d.shared::cluster.global.mbarrier::complete_tx::bytes [%0], [%1, {%3, %4}], [%2];" :: "r"(dst), "l"(m), "r"(bar), "r"(x), "r"(y) : "memory");
}
__device__ __forceinline__ void tma3d(uint32_t dst, const CUtensorMap* m, int x, int y, int z, uint32_t bar, bool stream = false) {
  if (stream) asm volatile("cp.async.bulk.tensor.3d.shared::cluster.global.mbarrier::complete_tx::bytes.L2::cache_hint [%0], [%1, {%3, %4, %5}], [%2], %6;" :: "r"(dst), "l"(m), "r"(bar), "r"(x), "r"(y), "r"(z), "l"(pol_first()) : "memory");
  else asm volatile("cp.async.bulk.tensor.3d.shared::cluster.global.mbarrier::complete_tx::bytes [%0], [%1, {%3, %4, %5}], [%2];" :: "r"(dst), "l"(m), "r"(bar), "r"(x), "r"(y), "r"(z) : "memory");
}
__device__ __forceinline__ void tma4d(uint32_t dst, const CUtensorMap* m, int x, int y, int z, int w, uint32_t bar, bool stream = false) {
  if (stream) asm volatile("cp.async.bulk.tensor.4d.shared::cluster.global.mbarrier::complete_tx::bytes.L2::cache_hint [%0], [%1, {%3, %4, %5, %6}], [%2], %7;" :: "r"(dst), "l"(m), "r"(bar), "r"(x), "r"(y), "r"(z), "r"(w), "l"(pol_first()) : "memory");
  else asm volatile("cp.async.bulk.tensor.4d.shared::cluster.global.mbarrier::complete_tx::bytes [%0], [%1, {%3, %4, %5, %6}], [%2];" :: "r"(dst), "l"(m), "r"(bar), "r"(x), "r"(y), "r"(z), "r"(w) : "memory");
}
__device__ __forceinline__ void bulk_g2s_mc(uint32_t dst, const void* src, uint32_t bytes, uint32_t bar, bool stream = false) {
  if (stream) asm volatile("cp.async.bulk.shared::cluster.global.mbarrier::complete_tx::bytes.multicast::cluster.L2::cache_hint [%0], [%1], %2, [%3], %4, %5;" :: "r"(dst), "l"(src), "r"(bytes), "r"(bar), "h"((uint16_t)3), "l"(pol_first()) : "memory");
  else asm volatile("cp.async.bulk.shared::cluster.global.mbarrier::complete_tx::bytes.multicast::cluster [%0], [%1], %2, [%3], %4;" :: "r"(dst), "l"(src), "r"(bytes), "r"(bar), "h"((uint16_t)3) : "memory");
}
__device__ __forceinline__ void tma2d_mc(uint32_t dst, const CUtensorMap* m, int x, int y, uint32_t bar, bool stream = false) {
  if (stream) asm volatile("cp.async.bulk.tensor.2d.shared::cluster.global.mbarrier::complete_tx::bytes.multicast::cluster.L2::cache_hint [%0], [%1, {%3, %4}], [%2], %5, %6;" :: "r"(dst), "l"(m), "r"(bar), "r"(x), "r"(y), "h"((uint16_t)3), "l"(pol_first()) : "memory");
  else asm volatile("cp.async.bulk.tensor.2d.shared::cluster.global.mbarrier::complete_tx::bytes.multicast::cluster [%0], [%1, {%3, %4}], [%2], %5;" :: "r"(dst), "l"(m), "r"(bar), "r"(x), "r"(y), "h"((uint16_t)3) : "memory");
}
__device__ __forceinline__ void tma3d_mc(uint32_t dst, const CUtensorMap* m, int x, int y, int z, uint32_t bar, bool stream = false) {
  if (stream) asm volatile("cp.async.bulk.tensor.3d.shared::cluster.global.mbarrier::complete_tx::bytes.multicast::cluster.L2::cache_hint [%0], [%1, {%3, %4, %5}], [%2], %6, %7;" :: "r"(dst), "l"(m), "r"(bar), "r"(x), "r"(y), "r"(z), "h"((uint16_t)3), "l"(pol_first()) : "memory");
  else asm volatile("cp.async.bulk.tensor.3d.shared::cluster.global.mbarrier::complete_tx::bytes.multicast::cluster [%0], [%1, {%3, %4, %5}], [%2], %6;" :: "r"(dst), "l"(m), "r"(bar), "r"(x), "r"(y), "r"(z), "h"((uint16_t)3) : "memory");
}
__device__ __forceinline__ void pf3d(const CUtensorMap* m, int x, int y, int z) {
  asm volatile("cp.async.bulk.prefetch.tensor.3d.L2.global [%0, {%1, %2, %3}];" :: "l"(m), "r"(x), "r"(y), "r"(z) : "memory");
}
__device__ __forceinline__ void pf_bulk(const void* p, uint32_t bytes) { asm volatile("cp.async.bulk.prefetch.L2.global [%0], %1;" :: "l"(p), "r"(bytes) : "memory"); }
__device__ __forceinline__ void tma2d_store(const CUtensorMap* m, uint32_t src, int x, int y) {
  if (POL(12)) asm volatile("cp.async.bulk.tensor.2d.global.shared::cta.bulk_group.L2::cache_hint [%0, {%2, %3}], [%1], %4;" :: "l"(m), "r"(src), "r"(x), "r"(y), "l"(pol_first()) : "memory");
  else asm volatile("cp.async.bulk.tensor.2d.global.shared::cta.bulk_group [%0, {%2, %3}], [%1];" :: "l"(m), "r"(src), "r"(x), "r"(y) : "memory");
}
__device__ __forceinline__ bool elect() {
  uint32_t r; asm volatile("{\n.reg .pred p;\nelect.sync _|p, 0xffffffff;\nselp.u32 %0, 1, 0, p;\n}\n" : "=r"(r)); return r != 0;
}
__device__ __forceinline__ void cluster_arrive() { asm volatile("barrier.cluster.arrive;" ::: "memory"); }
__device__ __forceinline__ void cluster_wait() { asm volatile("barrier.cluster.wait;" ::: "memory"); }
__device__ __forceinline__ void bar_sync(int id, int n) { asm volatile("bar.sync %0, %1;" :: "r"(id), "r"(n) : "memory"); }
__device__ __forceinline__ void bar_arrive(int id, int n) { asm volatile("bar.arrive %0, %1;" :: "r"(id), "r"(n) : "memory"); }
__device__ __forceinline__ int bar_and(int id, int n, int pred) {
  int r; asm volatile("{\n.reg .pred p, q;\nsetp.ne.b32 p, %3, 0;\nbar.red.and.pred q, %1, %2, p;\nselp.b32 %0, 1, 0, q;\n}\n" : "=r"(r) : "r"(id), "r"(n), "r"(pred) : "memory");
  return r;
}
__device__ __forceinline__ void fence_async_smem() { asm volatile("fence.proxy.async.shared::cta;" ::: "memory"); }
__device__ __forceinline__ float ex2(float x) { float y; asm("ex2.approx.ftz.f32 %0, %1;" : "=f"(y) : "f"(x)); return y; }
__device__ __forceinline__ uint32_t pack_bf16(float lo, float hi) { uint32_t r; asm("cvt.rn.bf16x2.f32 %0, %1, %2;" : "=r"(r) : "f"(hi), "f"(lo)); return r; }
__device__ __forceinline__ uint32_t hmul2(uint32_t a, uint32_t b) { uint32_t r; asm("mul.rn.bf16x2 %0, %1, %2;" : "=r"(r) : "r"(a), "r"(b)); return r; }
__device__ __forceinline__ uint32_t hadd2(uint32_t a, uint32_t b) { uint32_t r; asm("add.rn.bf16x2 %0, %1, %2;" : "=r"(r) : "r"(a), "r"(b)); return r; }
__device__ __forceinline__ uint32_t hfma2(uint32_t a, uint32_t b, uint32_t c) { uint32_t r; asm("fma.rn.bf16x2 %0, %1, %2, %3;" : "=r"(r) : "r"(a), "r"(b), "r"(c)); return r; }
__device__ __forceinline__ float bf_lo(uint32_t a) { return __uint_as_float(a << 16); }
__device__ __forceinline__ float bf_hi(uint32_t a) { return __uint_as_float(a & 0xffff0000u); }
__device__ __forceinline__ uint32_t lds32(uint32_t a) { uint32_t v; asm volatile("ld.shared.u32 %0, [%1];" : "=r"(v) : "r"(a) : "memory"); return v; }
__device__ __forceinline__ float2 lds64f(uint32_t a) { float2 v; asm volatile("ld.shared.v2.f32 {%0,%1}, [%2];" : "=f"(v.x), "=f"(v.y) : "r"(a) : "memory"); return v; }
__device__ __forceinline__ uint4 lds128(uint32_t a) { uint4 v; asm volatile("ld.shared.v4.u32 {%0,%1,%2,%3}, [%4];" : "=r"(v.x), "=r"(v.y), "=r"(v.z), "=r"(v.w) : "r"(a) : "memory"); return v; }
__device__ __forceinline__ void sts64f(uint32_t a, float x, float y) { asm volatile("st.shared.v2.f32 [%0], {%1,%2};" :: "r"(a), "f"(x), "f"(y) : "memory"); }
__device__ __forceinline__ void sts128(uint32_t a, uint4 v) { asm volatile("st.shared.v4.u32 [%0], {%1,%2,%3,%4};" :: "r"(a), "r"(v.x), "r"(v.y), "r"(v.z), "r"(v.w) : "memory"); }
template<int OFF> __device__ __forceinline__ void sts128o(uint32_t a, uint4 v) { asm volatile("st.shared.v4.u32 [%0+%5], {%1,%2,%3,%4};" :: "r"(a), "r"(v.x), "r"(v.y), "r"(v.z), "r"(v.w), "n"(OFF) : "memory"); }
__device__ __forceinline__ void ldsm4(uint32_t a, uint32_t& r0, uint32_t& r1, uint32_t& r2, uint32_t& r3) {
  asm volatile("ldmatrix.sync.aligned.m8n8.x4.shared.b16 {%0,%1,%2,%3}, [%4];" : "=r"(r0), "=r"(r1), "=r"(r2), "=r"(r3) : "r"(a) : "memory");
}
__device__ __forceinline__ void ldsm4t(uint32_t a, uint32_t& r0, uint32_t& r1, uint32_t& r2, uint32_t& r3) {
  asm volatile("ldmatrix.sync.aligned.m8n8.x4.trans.shared.b16 {%0,%1,%2,%3}, [%4];" : "=r"(r0), "=r"(r1), "=r"(r2), "=r"(r3) : "r"(a) : "memory");
}
__device__ __forceinline__ void stsm4(uint32_t a, uint32_t r0, uint32_t r1, uint32_t r2, uint32_t r3) {
  asm volatile("stmatrix.sync.aligned.m8n8.x4.shared.b16 [%0], {%1,%2,%3,%4};" :: "r"(a), "r"(r0), "r"(r1), "r"(r2), "r"(r3) : "memory");
}
template<int N> __device__ __forceinline__ void fence_regs(float (&d)[N]) {
#pragma unroll
  for (int i = 0; i < N; i++) asm volatile("" : "+f"(d[i]) :: "memory");
}
template<int N> __device__ __forceinline__ void fence_regs(uint32_t (&d)[N]) {
#pragma unroll
  for (int i = 0; i < N; i++) asm volatile("" : "+r"(d[i]) :: "memory");
}
__device__ __forceinline__ void sched_fence(float x, uint32_t dummy) {
  asm volatile("{\n.reg .pred p;\nsetp.eq.u32 p, %0, 0x7fc12345;\n@p st.shared.u32 [%1], %0;\n}\n" :: "r"(__float_as_uint(x)), "r"(dummy) : "memory");
}
#define ROT 0
#define CTAID blockIdx.x
#define PTRACE 0
#define TS(role, i)
#define TSA(i)
#define TS2(role, i)
#define TR(obj, role, tag)

#define SHADOW if (gridDim.y == 1)

struct Prod {
  uint32_t base, mask; int lane, nt;
  __device__ __forceinline__ uint32_t full(int u) const { return base + SM_BAR + 8 * u; }
  __device__ __forceinline__ uint32_t addr(int u) const { return base + u * UNIT; }
  __device__ __forceinline__ void acquire(int u, int n) {
    const int v = u + min(lane, n - 1);
    mbar_wait_all(base + SM_BAR + 128 + 8 * v, mask >> v);
    mask ^= ((1u << n) - 1) << u;
    TR(*this, 2, 16 + u);
  }
  __device__ __forceinline__ void acquire_slow(int u, int n) {
    for (int i = 0; i < n; i++) mbar_wait_slow(base + SM_BAR + 128 + 8 * (u + i), mask >> (u + i));
    mask ^= ((1u << n) - 1) << u;
  }
};
struct Cons {
  uint32_t base, rel, mask; int lane, warp, wg, nt;
  __device__ __forceinline__ uint32_t addr(int u) const { return base + u * UNIT; }
  __device__ __forceinline__ static uint32_t daddr(int u) { return SMEM_BASE + u * UNIT; }
  __device__ __forceinline__ void wait(int u) { TR(*this, wg, 1); mbar_wait(base + SM_BAR + 8 * u, mask >> u); mask ^= 1u << u; TR(*this, wg, 2); }
  __device__ __forceinline__ void skip(int u) { mask ^= 1u << u; }
  __device__ __forceinline__ void release(int u, int n) {
    TR(*this, wg, 5);
    asm volatile("{\n.reg .pred p;\nsetp.lt.s32 p, %1, %2;\n@p mbarrier.arrive.shared::cluster.b64 _, [%0];\n}\n" :: "r"(rel + 8 * u), "r"(lane & 15), "r"(n) : "memory");
  }
  __device__ __forceinline__ void release2(int u) {
    asm volatile("{\n.reg .pred p;\nsetp.eq.s32 p, %1, 0;\n@p mbarrier.arrive.shared::cluster.b64 _, [%0], 2;\n}\n" :: "r"(rel + 8 * u), "r"(lane & 15) : "memory");
  }
  __device__ __forceinline__ void signal(int i) {
    __syncwarp();
    asm volatile("{\n.reg .pred p;\nsetp.eq.s32 p, %1, 0;\n@p mbarrier.arrive.shared::cta.b64 _, [%0];\n}\n" :: "r"(base + SM_SIG + 8 * i), "r"(lane) : "memory");
  }
  __device__ __forceinline__ void turn() { bar_sync(1 + wg, 256); TR(*this, wg, 3); }
  __device__ __forceinline__ void pass() { bar_arrive(2 - wg, 256); TR(*this, wg, 4); }
};
__device__ __forceinline__ int gemm_unit(int ks) { return 3 * (ks & 3); }
__device__ __forceinline__ int att_slot(int i) { return 4 + 2 * i; }
template<int MASK> __device__ __forceinline__ int kv_slot(int h) { return MASK == PH_ALL ? h & 15 : h; }
__device__ __forceinline__ int out_mb(int cta) { return cta >> 3; }
__device__ __forceinline__ int out_nb(int cta) { return cta & 7; }
template<int MASK> constexpr int CV_REG = MASK == PH_ALL ? CONV_REG : 6;
template<int MASK> constexpr int CV_EXTRA = (1024 - NREG * CV_REG<MASK>) / (NCTA - NREG);
template<int MASK> __device__ __forceinline__ int conv_channel(int cta, int i) {
  return cta < NREG ? CV_EXTRA<MASK> * (NCTA - NREG) + cta * CV_REG<MASK> + i : (i >> 1) * 8 + (cta - NREG) * 2 + (i & 1);
}

template<int OFF, int N> __device__ __forceinline__ void pack_chunk(const float (&a)[N], float sc0, float sc1, uint4& v0, uint4& v1) {
  v0.x = pack_bf16(a[OFF + 0] * sc0, a[OFF + 1] * sc0); v0.y = pack_bf16(a[OFF + 4] * sc0, a[OFF + 5] * sc0);
  v0.z = pack_bf16(a[OFF + 8] * sc0, a[OFF + 9] * sc0); v0.w = pack_bf16(a[OFF + 12] * sc0, a[OFF + 13] * sc0);
  v1.x = pack_bf16(a[OFF + 2] * sc1, a[OFF + 3] * sc1); v1.y = pack_bf16(a[OFF + 6] * sc1, a[OFF + 7] * sc1);
  v1.z = pack_bf16(a[OFF + 10] * sc1, a[OFF + 11] * sc1); v1.w = pack_bf16(a[OFF + 14] * sc1, a[OFF + 15] * sc1);
}
template<int OFF, int N> __device__ __forceinline__ void pack_chunk(const float (&a)[N], uint4& v0, uint4& v1) {
  v0.x = pack_bf16(a[OFF + 0], a[OFF + 1]); v0.y = pack_bf16(a[OFF + 4], a[OFF + 5]);
  v0.z = pack_bf16(a[OFF + 8], a[OFF + 9]); v0.w = pack_bf16(a[OFF + 12], a[OFF + 13]);
  v1.x = pack_bf16(a[OFF + 2], a[OFF + 3]); v1.y = pack_bf16(a[OFF + 6], a[OFF + 7]);
  v1.z = pack_bf16(a[OFF + 10], a[OFF + 11]); v1.w = pack_bf16(a[OFF + 14], a[OFF + 15]);
}
__device__ __forceinline__ void sq_acc(const uint4& v, uint32_t& a) { a = hfma2(v.x, v.x, a); a = hfma2(v.y, v.y, a); a = hfma2(v.z, v.z, a); a = hfma2(v.w, v.w, a); }
__device__ __forceinline__ float norm2_max(uint32_t a0, uint32_t a1) {
  float n0 = bf_lo(a0) + bf_hi(a0), n1 = bf_lo(a1) + bf_hi(a1);
  n0 += __shfl_xor_sync(~0u, n0, 1); n1 += __shfl_xor_sync(~0u, n1, 1);
  n0 += __shfl_xor_sync(~0u, n0, 2); n1 += __shfl_xor_sync(~0u, n1, 2);
  return __uint_as_float(__reduce_max_sync(~0u, max(__float_as_uint(n0) & 0x7fffffffu, __float_as_uint(n1) & 0x7fffffffu)));
}

struct Pend { uint4 lo[8], hi[8]; uint32_t dst; float kn; };
__device__ __forceinline__ void pin(uint4 (&v)[8]) {
#pragma unroll
  for (int i = 0; i < 8; i++) asm volatile("" : "+r"(v[i].x), "+r"(v[i].y), "+r"(v[i].z), "+r"(v[i].w) :: "memory");
}
__device__ __forceinline__ void pack_o(const float (&o)[64], float i0, float i1, uint4 (&v)[8]) {
  pack_chunk<0>(o, i0, i1, v[0], v[1]); pack_chunk<16>(o, i0, i1, v[2], v[3]);
  pack_chunk<32>(o, i0, i1, v[4], v[5]); pack_chunk<48>(o, i0, i1, v[6], v[7]);
  pin(v);
}
__device__ __forceinline__ uint32_t atom_off(int lane) { return (lane >> 2) * 64 + (((lane ^ (lane >> 3)) & 3) << 4); }
__device__ __forceinline__ void stg128(void* p, const uint4& v, bool stream) {
  if (stream) asm volatile("st.global.L2::cache_hint.v4.u32 [%0], {%1,%2,%3,%4}, %5;" :: "l"(p), "r"(v.x), "r"(v.y), "r"(v.z), "r"(v.w), "l"(pol_first()) : "memory");
  else *(uint4*)p = v;
}
template<int J0, int J1, bool STREAM = false> __device__ __forceinline__ void tile_store(const uint4 (&v)[8], uint32_t dst, int lane) {
  uint8_t* d = g_T + (dst + atom_off(lane));
#pragma unroll
  for (int j = J0; j < J1; j++) { stg128(d + j * 512, v[2 * j], STREAM); stg128(d + j * 512 + 2048, v[2 * j + 1], STREAM); }
}
template<int I0, int I1> __device__ __forceinline__ void tile_store_if(bool on, const uint4 (&v)[8], const uint8_t* dst) {
  if constexpr (I0 < I1) {
    asm volatile("{\n.reg .pred p;\nsetp.ne.b32 p, %5, 0;\n@p st.v4.u32 [%0+%6], {%1,%2,%3,%4};\n}\n"
      :: "l"(dst), "r"(v[I0].x), "r"(v[I0].y), "r"(v[I0].z), "r"(v[I0].w), "r"((int)on), "n"((I0 >> 1) * 512 + (I0 & 1) * 2048) : "memory");
    tile_store_if<I0 + 1, I1>(on, v, dst);
  }
}
__device__ __forceinline__ float tile_norm2(const uint4 (&v)[8]) {
  uint32_t n0 = 0, n1 = 0, n2 = 0, n3 = 0;
#pragma unroll
  for (int j = 0; j < 2; j++) { sq_acc(v[2 * j], n0); sq_acc(v[2 * j + 1], n1); sq_acc(v[2 * j + 4], n2); sq_acc(v[2 * j + 5], n3); }
  return norm2_max(hadd2(n0, n2), hadd2(n1, n3));
}
template<uint64_t SCHED, bool FIRST> __device__ __forceinline__ void out_piece(Cons& c, Pend& w, int ks, bool both) {
  uint8_t* d = g_T + (w.dst + atom_off(c.lane));
#pragma unroll
  for (int i = 0; i < 16; i++) {
    const int at = (SCHED >> (4 * i)) & 15;
    if (FIRST ? at == 0 : (at > 0 && ks == at && (i < 8 || both))) *(uint4*)(d + (i >> 3) * 32768 + ((i >> 1) & 3) * 512 + (i & 1) * 2048) = i < 8 ? w.lo[i & 7] : w.hi[i & 7];
  }
  if (FIRST || !both) return;
  if (ks == NK_AT) w.kn = tile_norm2(w.lo);
  if (ks == NV_AT) {
    const float vn = tile_norm2(w.hi);
    if (c.lane == 0) g_kn2[((w.dst - T_KV) >> 16) * 8 + c.wg * 4 + c.warp] = (vn <= 1.0e30f && vn >= 1.0e-30f) ? w.kn : __uint_as_float(0x7f800000u);
  }
}
template<bool FIRST> __device__ __forceinline__ void kv_issue(Cons& c, float (&acc)[128], int u) {
  const uint64_t da = odesc(c.daddr(u) + c.wg * 8192, 16, 1024, 1), db = odesc(c.daddr(u + 1), 8192, 1024, 1);
  c.turn();
  wg_fence();
#pragma unroll
  for (int kk = 0; kk < 4; kk++) wgmma_ss_n256<1>(acc, da + kk * 2, db + kk * 128, !(FIRST && kk == 0));
  wg_commit();
  c.pass();
}
template<bool NEXT> __device__ __forceinline__ void cons_kv(Cons& c, int h, int hs, int g, Pend& w, bool pend_o) {
#pragma unroll 1
  for (int tile = 0; tile < 2; tile++) {
    float acc[128];
    if (tile == 0) c.wait(0);
    if (tile == 0 && h < 16) TS(c.wg, 16);
    kv_issue<true>(c, acc, 0);
    c.release(9, tile == 1 ? 3 : 0);
    if (tile == 1 && pend_o) mbar_wait(c.base + SM_RDY + 8 * RDY_WAR, 0);
    if (tile == 1 || pend_o) out_piece<SCH_KV, true>(c, w, 0, false);
#pragma unroll 1
    for (int ks = 1; ks < 8; ks++) {
      const int u = gemm_unit(ks);
      c.wait(u);
      wg_wait<0>();
      c.release(gemm_unit(ks - 1), 3);
      kv_issue<false>(c, acc, u);
      if (tile == 1 || pend_o) { out_piece<SCH_KV, false>(c, w, ks, tile); if (ks == ((SCH_KV >> 28) & 15) && tile == 0) c.signal(SIG_CTX); }
    }
    if (NEXT || tile == 0) c.wait(0);
    wg_wait<0>(); fence_regs(acc);
    if (!NEXT) c.release(9, tile == 1 ? 3 : 0);
    pack_chunk<0>(acc, w.lo[0], w.lo[1]);  pack_chunk<16>(acc, w.lo[2], w.lo[3]); pack_chunk<32>(acc, w.lo[4], w.lo[5]); pack_chunk<48>(acc, w.lo[6], w.lo[7]);
    pack_chunk<64>(acc, w.hi[0], w.hi[1]); pack_chunk<80>(acc, w.hi[2], w.hi[3]); pack_chunk<96>(acc, w.hi[4], w.hi[5]); pack_chunk<112>(acc, w.hi[6], w.hi[7]);
    pin(w.lo); pin(w.hi);
    w.dst = T_KV + (hs * 16 + 2 * g + tile) * 65536 + (c.wg * 4 + c.warp) * 4096;
  }
}
template<bool FIRST> __device__ __forceinline__ void q_issue(Cons& c, float (&a)[64], float (&b)[64], int u) {
  const uint64_t da = odesc(c.daddr(u) + c.wg * 8192, 16, 1024, 1), db = odesc(c.daddr(u + 2), 8192, 1024, 1);
  const uint64_t da2 = odesc(c.daddr(u + 1) + (1 - c.wg) * 8192, 16, 1024, 1);
  c.turn();
  wg_fence();
#pragma unroll
  for (int kk = 0; kk < 4; kk++) wgmma_ss_n128<1>(a, da + kk * 2, db + kk * 128, !(FIRST && kk == 0));
#pragma unroll
  for (int kk = 0; kk < 4; kk++) wgmma_ss_n128<1>(b, da2 + kk * 2, db + kk * 128, !(FIRST && kk == 0));
  wg_commit();
  c.pass();
}
__device__ __forceinline__ void q_step(Cons& c, float (&d)[64], int ua, int ub, int rowhalf) {
  const uint64_t da = odesc(c.daddr(ua) + rowhalf * 8192, 16, 1024, 1), db = odesc(c.daddr(ub), 8192, 1024, 1);
#pragma unroll
  for (int kk = 0; kk < 4; kk++) wgmma_ss_n128<1>(d, da + kk * 2, db + kk * 128, 1);
}
template<bool PEND_KV> __device__ __forceinline__ void cons_q(Cons& c, int h, Pend& w, float (&b)[64]) {
  float a[64];
  if (!PEND_KV) c.wait(0);
  q_issue<true>(c, a, b, 0);
  if (PEND_KV) { c.release(9, 3); out_piece<SCH_Q, true>(c, w, 0, true); }
#pragma unroll 1
  for (int ks = 1; ks < 14; ks++) {
    const int u = gemm_unit(ks);
    c.wait(u);
    wg_wait<0>();
    c.release(gemm_unit(ks - 1), 3);
    q_issue<false>(c, a, b, u);
    if (PEND_KV && ks <= (int)(SCH_Q >> 60)) { out_piece<SCH_Q, false>(c, w, ks, true); if (ks == (int)(SCH_Q >> 60)) c.signal(SIG_KV + (h >> 4)); }
  }
  c.wait(6); c.wait(9);
  wg_wait<0>();
  c.release(3, 3);
  c.turn();
  wg_fence();
  q_step(c, a, 6, 8, c.wg); q_step(c, a, 9, 11, c.wg); wg_commit();
  q_step(c, b, 7, 8, 1 - c.wg); wg_commit();
  c.pass();
  c.wait(0);
  const uint32_t q0 = c.addr(0) + (c.wg * 4 + c.warp) * 4096 + atom_off(c.lane);
  wg_wait<1>(); fence_regs(a);
  pack_o(a, QSCALE, QSCALE, w.lo);
  sts128o<0>(q0, w.lo[0]);    sts128o<2048>(q0, w.lo[1]); sts128o<512>(q0, w.lo[2]);  sts128o<2560>(q0, w.lo[3]);
  wg_wait<0>();
  c.release(6, 4);
  sts128o<1024>(q0, w.lo[4]); sts128o<3072>(q0, w.lo[5]); sts128o<1536>(q0, w.lo[6]); sts128o<3584>(q0, w.lo[7]);
  c.wait(4);
  fence_async_smem();
}

__device__ __forceinline__ void issue_qk(float (&s)[64], uint64_t da, uint64_t db) {
#pragma unroll
  for (int kk = 0; kk < 8; kk++) wgmma_ss_n128<0>(s, da + (kk >> 1) * 32 + (kk & 1) * 2, db + (kk >> 1) * 32 + (kk & 1) * 2, kk > 0);
  wg_commit();
}
template<int A, int B> __device__ __forceinline__ void exp_rng(float (&s)[64]) {
#pragma unroll
  for (int i = 4 * A; i < 4 * B; i++) s[i] = ex2(s[i]);
}
template<int A, int B> __device__ __forceinline__ void sum_rng(const float (&s)[64], float (&l)[4]) {
#pragma unroll
  for (int i = A; i < B; i++) { l[0] += s[4 * i]; l[1] += s[4 * i + 1]; l[2] += s[4 * i + 2]; l[3] += s[4 * i + 3]; }
}
template<int A, int B> __device__ __forceinline__ void cvt_p(const float (&s)[64], uint32_t (&p)[32]) {
#pragma unroll
  for (int i = 2 * A; i < 2 * B; i++) p[i] = pack_bf16(s[2 * i], s[2 * i + 1]);
}
template<int K0> __device__ __forceinline__ void mask_half(float (&s)[64], int warp, int lane) {
  const int l0 = warp + (2 * (lane & 3) <= (lane >> 2)), l1 = warp + (2 * (lane & 3) < (lane >> 2));
#pragma unroll
  for (int k = 0; k < 4; k++) {
    float* t = s + 8 * (K0 + k);
    if (k >= l0) { t[0] = -INFINITY; t[6] = -INFINITY; }
    if (k >= l1) { t[1] = -INFINITY; t[7] = -INFINITY; }
    if (k > warp) { t[2] = -INFINITY; t[3] = -INFINITY; }
    if (k >= warp) { t[4] = -INFINITY; t[5] = -INFINITY; }
  }
}
__device__ __forceinline__ void row_inv(float& l0, float& l1) {
  l0 += __shfl_xor_sync(~0u, l0, 1); l1 += __shfl_xor_sync(~0u, l1, 1);
  l0 += __shfl_xor_sync(~0u, l0, 2); l1 += __shfl_xor_sync(~0u, l1, 2);
  l0 = __fdividef(1.f, l0); l1 = __fdividef(1.f, l1);
}
__device__ __forceinline__ void softmax_safe(float (&s)[64], bool upper_only, float& m0, float& m1, float& sc0, float& sc1) {
  float a0 = m0, a1 = m1;
#pragma unroll
  for (int i = 0; i < 8; i++) { a0 = fmaxf(a0, fmaxf(s[4 * i], s[4 * i + 1])); a1 = fmaxf(a1, fmaxf(s[4 * i + 2], s[4 * i + 3])); }
  if (upper_only) { a0 = m0; a1 = m1; }
#pragma unroll
  for (int i = 8; i < 16; i++) { a0 = fmaxf(a0, fmaxf(s[4 * i], s[4 * i + 1])); a1 = fmaxf(a1, fmaxf(s[4 * i + 2], s[4 * i + 3])); }
  a0 = fmaxf(a0, __shfl_xor_sync(~0u, a0, 1)); a1 = fmaxf(a1, __shfl_xor_sync(~0u, a1, 1));
  a0 = fmaxf(a0, __shfl_xor_sync(~0u, a0, 2)); a1 = fmaxf(a1, __shfl_xor_sync(~0u, a1, 2));
  sc0 = ex2(m0 - a0); sc1 = ex2(m1 - a1);
  m0 = a0; m1 = a1;
#pragma unroll
  for (int i = 0; i < 16; i++) { s[4 * i] -= a0; s[4 * i + 1] -= a0; s[4 * i + 2] -= a1; s[4 * i + 3] -= a1; }
}
struct Att {
  float s[64], o[64], l[4], i0, i1; uint32_t p[32];
  uint32_t qaddr; const uint8_t* dst;
};
__device__ __forceinline__ uint32_t ctx_off(const Cons& c, int h, int qb, int rowhalf) { return T_CTX + (qb * 32 + h) * 32768 + (rowhalf * 4 + c.warp) * 4096; }
__device__ __forceinline__ int att_fast(Cons& c, int h, const uint4 (&q)[8]) {
  const float kn = __uint_as_float(lds32(c.base + SM_KMAX + 4 * (h >> 4)));
  return __shfl_sync(~0u, bar_and(3 + c.wg, 128, tile_norm2(q) * kn <= BOUND2), 0);
}
__device__ __forceinline__ int att_first(Cons& c, Att& a, int h, const Pend& w) {
  a.qaddr = c.daddr(0) + c.wg * 16384;
  c.turn();
  wg_fence();
  issue_qk(a.s, odesc(a.qaddr, 16, 2048, 2), odesc(c.daddr(4), 16, 2048, 2));
  int fast = 0;
  if (FAST_AT == 0) { SHADOW fast = att_fast(c, h, w.lo); wg_fence(); }
  q_step(c, a.o, 10, 11, 1 - c.wg); wg_commit();
  c.pass();
  c.signal(SIG_ATT + (h >> 4));
  if (FAST_AT == 1) { SHADOW fast = att_fast(c, h, w.lo); }
#pragma unroll
  for (int i = 0; i < 8; i++) { a.p[4 * i] = w.lo[i].x; a.p[4 * i + 1] = w.lo[i].y; a.p[4 * i + 2] = w.lo[i].z; a.p[4 * i + 3] = w.lo[i].w; }
  a.l[0] = a.l[1] = a.l[2] = a.l[3] = 0.f; a.i0 = a.i1 = QSCALE;
  a.dst = (const uint8_t*)__cvta_shared_to_generic(c.addr(2) + (c.wg * 4 + c.warp) * 4096 + atom_off(c.lane));
  wg_wait<1>(); fence_regs(a.s);
  c.release(4, 2);
  return fast;
}
__device__ __forceinline__ void att_last(Cons& c, Att& a, Pend& w, int h, int g, bool drain) {
  const int uv = att_slot(1);
  if (drain) pack_o(a.o, a.i0, a.i1, w.hi);
  c.wait(uv);
  c.turn();
  fence_regs(a.o); fence_regs(a.p);
  wgmma_pv_sel(a.o, a.p, odesc(c.daddr(uv), 512, 2048, 2), !(drain && c.wg == 1), !drain);
  c.pass();
  a.i0 = a.l[0] + a.l[1]; a.i1 = a.l[2] + a.l[3];
  SHADOW row_inv(a.i0, a.i1);
  sched_fence(a.i0 + a.i1, c.base + SM_DUMMY);
  tile_store_if<0, 4>(drain, w.hi, a.dst);
  wg_wait<0>(); fence_regs(a.o); fence_regs(a.p);
  c.release(uv, 2);
  tile_store_if<4, 8>(drain, w.hi, a.dst);
  pack_o(a.o, a.i0, a.i1, w.lo);
  w.dst = ctx_off(c, h, g, 1 - c.wg);
}
__device__ __forceinline__ void cons_att(Cons& c, Att& a, int h, int g, Pend& w) {
  int fast = att_first(c, a, h, w), fast2 = 0;
  float m0 = -INFINITY, m1 = -INFINITY, sc0 = 0.f, sc1 = 0.f;
  int uk = 10, ur = 10;
  bool fresh = false;
#pragma unroll 1
  for (int d = g - 15;;) {
    const bool lo = d == c.wg;
    if ((unsigned)d < 2 || !fast) {
      if ((unsigned)d < 2) {
        mask_half<4>(a.s, c.warp, c.lane);
        if (lo) fast2 = att_fast(c, h, w.hi);
        if (d == 1) fast = fast2;
      }
      if (!fast) {
        if (d == 1) m0 = m1 = -INFINITY;
        softmax_safe(a.s, lo, m0, m1, sc0, sc1);
        a.l[0] *= sc0; a.l[1] *= sc0; a.l[2] *= sc1; a.l[3] *= sc1;
      }
    }
    exp_rng<8, 16>(a.s); sum_rng<8, 16>(a.s, a.l);
    exp_rng<ATT_SPLIT, 8>(a.s);
    sched_fence(((a.l[0] + a.l[1]) + (a.l[2] + a.l[3])) + (ATT_SPLIT < 8 ? a.s[4 * ATT_SPLIT + 3] : 0.f), c.base + SM_DUMMY);
    wg_wait<0>(); fence_regs(a.o); fence_regs(a.p);
    c.release(ur, 2);
    tile_store_if<DS_A, DS_B>(fresh, w.hi, a.dst);
    uk ^= 12; ur = 14 - uk;
    if (d == 0) a.qaddr += 32768;
    const uint64_t dq = odesc(a.qaddr, 16, 2048, 2), dk = odesc(c.daddr(uk) - (d + 1 == c.wg ? 16384 : 0), 16, 2048, 2), dv = odesc(c.daddr(ur), 512, 2048, 2);
    if (!lo) { exp_rng<0, ATT_SPLIT>(a.s); sum_rng<0, 8>(a.s, a.l); cvt_p<0, 16>(a.s, a.p); }
    else if (gridDim.y == 1) cvt_p<8, 16>(a.s, a.p);
    tile_store_if<DS_B, 8>(fresh, w.hi, a.dst);
    if (!fast || d == g + 1) {
      if (!fast && d != 1 && d != g - 15) {
#pragma unroll
        for (int i = 0; i < 16; i++) { a.o[4 * i] *= sc0; a.o[4 * i + 1] *= sc0; a.o[4 * i + 2] *= sc1; a.o[4 * i + 3] *= sc1; }
      }
      if (d == g + 1) break;
    }
    d++;
    fresh = d == 2 || d == g - 14;
    asm volatile("{\n.reg .pred p;\nsetp.eq.s32 p, %0, -2;\n@p fence.proxy.async.shared::cta;\n}\n" :: "r"(d) : "memory");
    if (c.wg == 0) c.wait(uk); else c.skip(uk);
    c.turn();
    fence_regs(a.o); fence_regs(a.p);
    wg_fence();
    issue_qk(a.s, dq, dk);
    if (fresh) pack_o(a.o, a.i0, a.i1, w.hi);
    wgmma_pv_sel(a.o, a.p, dv, !lo, !fresh);
    c.pass();
    tile_store_if<0, DS_A>(fresh, w.hi, a.dst);
    if (d == 1) {
      a.i0 = a.l[0] + a.l[1]; a.i1 = a.l[2] + a.l[3]; row_inv(a.i0, a.i1);
      a.l[0] = a.l[1] = a.l[2] = a.l[3] = 0.f;
      a.dst = g_T + (ctx_off(c, h, 15 - g, c.wg) + atom_off(c.lane));
    }
    wg_wait<1>(); fence_regs(a.s);
    c.release(uk, 2);
    c.release(d == 0 ? 0 : 2, (d == 0 || d == g + 1) ? 2 : 0);
  }
  att_last(c, a, w, h, g, g == 0);
}

constexpr int CV_H = 1024, CV_U = 5120, CV_D = CV_U + 4128, CV_ROW = 1056;
template<int OFF> __device__ __forceinline__ uint32_t lds32o(uint32_t a) { uint32_t v; asm volatile("ld.shared.u32 %0, [%1+%2];" : "=r"(v) : "r"(a), "n"(OFF) : "memory"); return v; }
template<int G, int G1 = 16> __device__ __forceinline__ void conv_lda(uint32_t (&a)[64], uint32_t p) {
  a[4 * G + 0] = lds32o<-256 * G>(p);
  a[4 * G + 1] = lds32o<-256 * G - 128>(p);
  a[4 * G + 2] = lds32o<-256 * G + 16>(p);
  a[4 * G + 3] = lds32o<-256 * G - 112>(p);
  if constexpr (G + 1 < G1) conv_lda<G + 1, G1>(a, p);
}
struct CvAcc { float lo[16], hi[16]; };
__device__ __forceinline__ void fence_regs(CvAcc& d) { fence_regs(d.lo); fence_regs(d.hi); }
template<int R, int H> __device__ __forceinline__ void conv_mma_h(float (&d)[16], const uint32_t (&a)[64], uint64_t db) {
#pragma unroll
  for (int G = 0; G < 4 * R + 2 * H + 2; G++) wgmma_rs_n32<0>(d, a[4 * G], a[4 * G + 1], a[4 * G + 2], a[4 * G + 3], db + 64 * R + 32 * H - 16 * G, G > 0);
}
template<int T, int G0, int G1> __device__ __forceinline__ void conv_part(float (&d)[16], const uint32_t (&a)[64], uint64_t db) {
#pragma unroll
  for (int G = G0; G < G1; G++) wgmma_rs_n32<0>(d, a[4 * G], a[4 * G + 1], a[4 * G + 2], a[4 * G + 3], db + 32 * T - 16 * G, G > 0);
}
template<int R> __device__ __forceinline__ void conv_mma(CvAcc& d, const uint32_t (&a)[64], uint64_t db) { conv_mma_h<R, 0>(d.lo, a, db); conv_mma_h<R, 1>(d.hi, a, db); }
template<int C0> __device__ __forceinline__ void conv_st_h(const float (&d)[16], uint32_t wq, float& c0, float& c1) {
#pragma unroll
  for (int n = 0; n < 4; n++) { sts64f(wq + (C0 + n * 8) * 4, d[4 * n] + c0, d[4 * n + 1] + c1); c0 = d[4 * n + 2]; c1 = d[4 * n + 3]; }
}
template<int R> __device__ __forceinline__ void conv_st(const CvAcc& d, uint32_t wq, float& c0, float& c1) { conv_st_h<64 * R>(d.lo, wq, c0, c1); conv_st_h<64 * R + 32>(d.hi, wq, c0, c1); }
struct ConvTail { float t[64]; uint4 ua, uc; uint32_t D2; };
__device__ __forceinline__ void conv_emit(ConvTail& e, int ch, int tid) {
  fence_regs(e.t);
  float y[16];
#pragma unroll
  for (int i = 0; i < 16; i++) y[i] = (e.t[i] + e.t[16 + i]) + (e.t[32 + i] + e.t[48 + i]);
  uint4 z0, z1;
  z0.x = hadd2(pack_bf16(y[0], y[2]), hmul2(__byte_perm(e.ua.w, 0, 0x1032), e.D2));
  z0.y = hadd2(pack_bf16(y[4], y[6]), hmul2(__byte_perm(e.ua.z, 0, 0x1032), e.D2));
  z0.z = hadd2(pack_bf16(y[8], y[10]), hmul2(__byte_perm(e.ua.y, 0, 0x1032), e.D2));
  z0.w = hadd2(pack_bf16(y[12], y[14]), hmul2(__byte_perm(e.ua.x, 0, 0x1032), e.D2));
  z1.x = hadd2(pack_bf16(y[1], y[3]), hmul2(__byte_perm(e.uc.w, 0, 0x1032), e.D2));
  z1.y = hadd2(pack_bf16(y[5], y[7]), hmul2(__byte_perm(e.uc.z, 0, 0x1032), e.D2));
  z1.z = hadd2(pack_bf16(y[9], y[11]), hmul2(__byte_perm(e.uc.y, 0, 0x1032), e.D2));
  z1.w = hadd2(pack_bf16(y[13], y[15]), hmul2(__byte_perm(e.uc.x, 0, 0x1032), e.D2));
  uint4* zp = (uint4*)(g_z + (uint32_t)(ch * 2048 + tid * 16));
  zp[0] = z0; zp[1] = z1;
}
template<int MASK> __device__ __forceinline__ void cons_conv(Cons& c, int cta, int nch) {
  const int r = c.lane >> 2, q = c.lane & 3, tid = c.warp * 32 + c.lane;
  const uint32_t part = c.addr(4) - 2048 + (1 - c.wg) * (32 * CV_ROW) + 32;
  const uint32_t aoff = CV_U + ((r & 1) ? 0 : UPITCH) + 4 * (((2039 - r) >> 1) + q - 8 * c.warp);
  const uint32_t wq = part + (c.warp * 8 + r) * CV_ROW + q * 8, rq = part + tid * 8;
  uint32_t a[64];
  ConvTail e = {};
  c.wait(c.wg); c.skip(c.wg ^ 1);
  conv_lda<0>(a, c.addr(c.wg) + aoff);
  c.wait(4);
  sts64f(part + (tid >> 2) * CV_ROW - 32 + q * 8, 0.f, 0.f);
#pragma unroll 1
  for (int i = 0; i < nch / 2; i++) {
    const int u = 2 * (i & 1) + c.wg;
    CvAcc d0, d1, d2, d3;
    float c0 = 0.f, c1 = 0.f;
    const uint64_t db = odesc(c.daddr(u) + CV_H - 16, 16, 128, 0);
    c.turn();
    fence_regs(a);
    wg_fence();
    conv_mma<0>(d0, a, db); conv_mma<1>(d1, a, db); wg_commit();
    if (i > 0) {
      conv_emit(e, conv_channel<MASK>(cta, 2 * i - 2 + c.wg), tid);
      if ((i & 15) == 0) c.signal(SIG_Z + (i >> 4) - 1);
    }
    wg_fence();
    conv_mma_h<2, 0>(d2.lo, a, db); wg_commit();
    wg_wait<1>(); fence_regs(d0); fence_regs(d1);
    conv_st_h<0>(d0.lo, wq, c0, c1);
    wg_fence();
    conv_mma_h<2, 1>(d2.hi, a, db); wg_commit();
    conv_st_h<32>(d0.hi, wq, c0, c1);
    conv_mma_h<3, 0>(d3.lo, a, db);
    conv_st_h<64>(d1.lo, wq, c0, c1);
    conv_mma_h<3, 1>(d3.hi, a, db); wg_commit();
    c.pass();
    const int un = i + 1 < nch / 2 ? u ^ 2 : u;
    if (un != u) { c.wait(un); c.skip(un ^ 1); }
    wg_wait<1>(); fence_regs(d2);
    conv_st_h<96>(d1.hi, wq, c0, c1);
    conv_st<2>(d2, wq, c0, c1);
    {
      const int sw = (c.lane >> 2) & 1;
      const uint4 v0 = lds128(c.addr(u) + CV_U + 4064 - 32 * tid + 16 * sw), v1 = lds128(c.addr(u) + CV_U + 4080 - 32 * tid - 16 * sw);
      e.ua = sw ? v0 : v1; e.uc = sw ? v1 : v0;
    }
    e.D2 = lds32(c.addr(u) + CV_D);
    wg_wait<0>(); fence_regs(d3); fence_regs(a);
    conv_st<3>(d3, wq, c0, c1);
    conv_lda<0, 4>(a, c.addr(un) + aoff);
    bar_sync(3 + c.wg, 128);
    sched_fence(__uint_as_float(e.ua.x ^ e.uc.x ^ e.D2), c.base + SM_DUMMY);
    c.release2(u);
    conv_lda<4, 16>(a, c.addr(un) + aoff);
#pragma unroll
    for (int k = 0; k < 32; k++) { const float2 v = lds64f(rq + k * CV_ROW - (k >> 3) * 8); e.t[2 * k] = v.x; e.t[2 * k + 1] = v.y; }
  }
  conv_emit(e, conv_channel<MASK>(cta, nch - 2 + c.wg), tid);
  c.signal(SIG_Z + ((nch / 2 - 1) >> 4));
  c.release(4, 4);
}

constexpr int OC_PART = 13824, OC_ROW = 544;
__device__ __forceinline__ int out_next(int u) { return (0x84ac680u >> (2 * u)) & 15; }
struct Out { float acc[64]; int pu; uint64_t da, db; };
template<bool FIRST, bool REL, int W = 1, bool PRE = true, bool POST = false> __device__ __forceinline__ void out_step(Cons& c, Out& o, bool extra = false) {
  const int pu = o.pu, u = extra ? 2 : out_next(pu);
  o.pu = u;
  if (PRE) c.wait(u);
  const uint64_t da = o.da + (uint32_t)(u * 1024), db = o.db + (uint32_t)(u * 1024);
  wg_fence();
#pragma unroll
  for (int kk = 0; kk < 4; kk++) wgmma_ss_n128<1>(o.acc, da + (kk >> 1) * 32 + (kk & 1) * 2, db + kk * 128, !(FIRST && kk == 0));
  wg_commit();
  if (REL) { wg_wait<W>(); c.release(pu, 2); }
  if (POST) c.wait(out_next(u));
}
template<int I0, int I1> __device__ __forceinline__ void oc_red(float (&y)[8], uint32_t rq) {
#pragma unroll
  for (int i = I0; i < I1; i++) { const float v = __uint_as_float(lds32(rq + i * OC_ROW - (i >> 3) * 8)); y[i & 7] = i < 8 ? v : y[i & 7] + v; }
}
__device__ __forceinline__ void oc_emit(const float (&y)[8], const uint4& u, uint32_t D2, __nv_bfloat16* dst) {
  uint4 z;
  z.x = hadd2(pack_bf16(y[0], y[1]), hmul2(__byte_perm(u.w, 0, 0x1032), D2));
  z.y = hadd2(pack_bf16(y[2], y[3]), hmul2(__byte_perm(u.z, 0, 0x1032), D2));
  z.z = hadd2(pack_bf16(y[4], y[5]), hmul2(__byte_perm(u.y, 0, 0x1032), D2));
  z.w = hadd2(pack_bf16(y[6], y[7]), hmul2(__byte_perm(u.x, 0, 0x1032), D2));
  *(uint4*)dst = z;
}
template<int MASK> __device__ __forceinline__ void cons_out(Cons& c, const Maps& M, const Params& P, int cta, Pend& w) {
  const int mb = out_mb(cta), nb = out_nb(cta);
  Out o;
  o.da = odesc(c.daddr(0) + c.wg * 8192, 16, 1024, 2); o.db = odesc(c.daddr(1), 8192, 1024, 1);
  o.pu = 5 + gridDim.y;
  out_step<true, false>(c, o);
  int ks = 1;
#pragma unroll 1
  for (;; ks++) {
    if (MASK & PH_ATT) {
      if (ks == (c.wg ? ST_1 : ST_0)) tile_store<0, 1>(w.lo, w.dst, c.lane);
      if (ks == (c.wg ? ST_1 + ST_D : ST_0 + ST_0D / 2)) tile_store<1, 2>(w.lo, w.dst, c.lane);
      if (ks == (c.wg ? ST_1 + 2 * ST_D : ST_0 + ST_0D)) tile_store<2, 3>(w.lo, w.dst, c.lane);
      if (ks == (c.wg ? ST_1 + 3 * ST_D : ST_0 + 3 * ST_0D / 2)) { tile_store<3, 4>(w.lo, w.dst, c.lane); c.signal(SIG_CTX + 1); }
    }
    if (ks == (c.wg ? OC_S1 : OC_S0)) break;
    out_step<false, true>(c, o, XSLOT && ks == 1);
  }
  if (MASK & PH_CONV) {
    const int r = c.lane >> 2, q = c.lane & 3, tid = c.warp * 32 + c.lane, u = 2 * c.wg;
    const uint32_t ub = c.addr(u), part = ub + OC_PART + 32;
    const uint32_t ap = ub + CV_U + ((r & 1) ? 0 : UPITCH) + 4 * (((2039 - r) >> 1) + q - 8 * c.warp);
    const uint32_t wq = part + (c.warp * 8 + r) * OC_ROW + q * 8, rq = part + tid * 4;
    const int nr = (CV_REG<MASK> + 1 - c.wg) >> 1;
#define STEP(N) out_step<false, true, 1, !OC_POST, OC_POST>(c, o);
#pragma unroll 1
    for (int i = 0; i < nr; i++) {
      uint32_t a[64];
      CvAcc d0, d1;
      float y[8], c0 = 0.f, c1 = 0.f;
      const uint64_t db = odesc(c.daddr(u + (i >> 8)) + CV_H - 16, 16, 128, 0);
#define STEP2(N) out_step<false, true, 2, !OC_POST, OC_POST>(c, o);
#define PART(...) { const uint64_t db = db0 + (c.mask >> 16); wg_fence(); __VA_ARGS__; wg_commit(); }
      const uint64_t db0 = db;
      c.wait(u);
      if (OC_POST) c.wait(out_next(o.pu));
      conv_lda<0, 4>(a, ap);
      STEP(0)
      conv_lda<4, 7>(a, ap);
      PART(conv_part<0, 0, 2>(d0.lo, a, db); conv_part<1, 0, 4>(d0.hi, a, db))
      STEP2(1)
      conv_lda<7, 10>(a, ap);
      PART(conv_part<2, 0, 6>(d1.lo, a, db))
      STEP2(2)
      fence_regs(d0);
      bar_sync(3 + c.wg, 128);
      sts64f(wq - 32, 0.f, 0.f);
      conv_st<0>(d0, wq, c0, c1);
      asm volatile("add.f32 %0, %0, 0f80000000;" : "+f"(c0)); asm volatile("add.f32 %0, %0, 0f80000000;" : "+f"(c1));
      PART(conv_part<3, 0, 8>(d1.hi, a, db))
      STEP2(3)
      wg_wait<1>(); fence_regs(d1);
      float e0 = d1.hi[12] + d1.hi[10], e1 = d1.hi[13] + d1.hi[11];
      conv_st<1>(d1, wq, c0, c1);
      asm volatile("add.f32 %0, %0, 0f80000000;" : "+f"(c0)); asm volatile("add.f32 %0, %0, 0f80000000;" : "+f"(c1));
      PART(conv_part<4, 0, 10>(d0.lo, a, db))
      STEP2(4)
      conv_lda<10, 12>(a, ap);
      bar_sync(3 + c.wg, 128);
      oc_red<0, 6>(y, rq);
      PART(conv_part<5, 0, 9>(d0.hi, a, db))
      STEP2(5)
      conv_lda<12, 14>(a, ap);
      oc_red<6, 12>(y, rq);
      PART(conv_part<5, 9, 12>(d0.hi, a, db); conv_part<6, 0, 6>(d1.lo, a, db))
      STEP2(6)
      oc_red<12, 26>(y, rq);
      PART(conv_part<6, 6, 14>(d1.lo, a, db))
      STEP2(7)
      oc_red<26, 32>(y, rq);
      conv_lda<14, 16>(a, ap);
      PART(conv_part<7, 0, 8>(d1.hi, a, db))
      STEP2(8)
      fence_regs(y); fence_regs(d0);
      bar_sync(3 + c.wg, 128);
      sts64f(wq - 32, e0, e1);
      conv_st<0>(d0, wq, c0, c1);
      PART(conv_part<7, 8, 16>(d1.hi, a, db))
      STEP2(9)
      wg_wait<1>(); fence_regs(d1); fence_regs(a);
      const uint4 u0 = lds128(ub + CV_U + 4080 - 16 * tid), u1 = lds128(ub + CV_U + 2032 - 16 * tid);
      const uint32_t D2 = lds32(ub + CV_D);
      conv_st_h<64>(d1.lo, wq, c0, c1);
      sched_fence(__uint_as_float(u0.x ^ u1.x ^ D2), c.base + SM_DUMMY);
      __syncwarp();
      c.release2(u);
      STEP(10)
      conv_st_h<96>(d1.hi, wq, c0, c1);
      __nv_bfloat16* zp = g_z + (uint32_t)(conv_channel<MASK>(cta, 2 * i + c.wg) * 2048 + (threadIdx.x & 127) * 8);
      oc_emit(y, u0, D2, zp);
      bar_sync(3 + c.wg, 128);
      oc_red<0, 6>(y, rq);
      STEP(11)
      oc_red<6, 19>(y, rq);
      STEP(12)
      oc_red<19, 32>(y, rq);
      oc_emit(y, u1, D2, zp + 1024);
      if (i == nr - 1) { c.signal(SIG_Z); c.release2(u + 1); TS2(c.wg, 8); }
      out_step<false, true, 1, !OC_POST>(c, o);
#pragma unroll 1
      for (int k = 14; k < (c.wg ? OC_L1 : OC_L0); k++) out_step<false, true>(c, o);
#undef STEP2
#undef PART
    }
#undef STEP
    if (((CV_REG<MASK> + c.wg) >> 1) & 1) c.skip(u ^ 2);
    ks += nr * (c.wg ? OC_L1 : OC_L0);
  }
  TS(c.wg, 9);
#pragma unroll 1
  for (; ks < 57; ks++) out_step<false, true>(c, o);
  uint32_t ga[32];
  c.wait(2);
  const float g0 = __uint_as_float(lds32(c.base + SM_GATE + 4 * (c.wg * 64 + c.warp * 16 + (c.lane >> 2)))), g1 = __uint_as_float(lds32(c.base + SM_GATE + 32 + 4 * (c.wg * 64 + c.warp * 16 + (c.lane >> 2))));
  const uint32_t gg0 = pack_bf16(g0, g0), gg1 = pack_bf16(g1, g1);
  const uint32_t og0 = pack_bf16(1.f - g0, 1.f - g0), og1 = pack_bf16(1.f - g1, 1.f - g1);
  const int xr = c.wg * 64 + c.warp * 16 + (c.lane & 15);
  const uint32_t xa = c.addr(2) + xr * 128, xs = xr & 7, xh = c.lane >> 4;
  const int zr = (c.lane & 7) + ((c.lane >> 4) << 3);
  const uint32_t za = c.addr(0) + c.wg * 16384 + zr * 128 + (((c.warp * 2 + ((c.lane >> 3) & 1)) ^ (zr & 7)) << 4);
#pragma unroll
  for (int i = 0; i < 8; i++) {
    if (i == 0) out_step<false, true>(c, o);
    if (i == 3) out_step<false, true>(c, o);
    if (i == 6) out_step<false, true>(c, o);
    ldsm4(xa + (i >> 2) * 16384 + ((((i & 3) * 2 + xh) ^ xs) << 4), ga[4 * i], ga[4 * i + 1], ga[4 * i + 2], ga[4 * i + 3]);
  }
#pragma unroll 1
  for (ks = 60; ks < 64; ks++) out_step<false, false>(c, o);
  TS2(c.wg, 17);
  c.wait(0);
  TS2(c.wg, 18);
  SHADOW {
#pragma unroll
    for (int i = 0; i < 8; i++) {
      uint32_t z0, z1, z2, z3;
      ldsm4t(za + i * 2048, z0, z1, z2, z3);
      ga[4 * i + 0] = hmul2(gg0, hmul2(ga[4 * i + 0], z0)); ga[4 * i + 1] = hmul2(gg1, hmul2(ga[4 * i + 1], z1));
      ga[4 * i + 2] = hmul2(gg0, hmul2(ga[4 * i + 2], z2)); ga[4 * i + 3] = hmul2(gg1, hmul2(ga[4 * i + 3], z3));
    }
  }
  c.signal(SIG_DONE);
  fence_regs(ga);
  TS2(c.wg, 19);
  wg_wait<0>(); fence_regs(o.acc);
  TS2(c.wg, 20);
#pragma unroll
  for (int i = 0; i < 8; i++) {
    const uint32_t r0 = hadd2(ga[4 * i + 0], hmul2(og0, pack_bf16(o.acc[8 * i + 0], o.acc[8 * i + 1])));
    const uint32_t r1 = hadd2(ga[4 * i + 1], hmul2(og1, pack_bf16(o.acc[8 * i + 2], o.acc[8 * i + 3])));
    const uint32_t r2 = hadd2(ga[4 * i + 2], hmul2(og0, pack_bf16(o.acc[8 * i + 4], o.acc[8 * i + 5])));
    const uint32_t r3 = hadd2(ga[4 * i + 3], hmul2(og1, pack_bf16(o.acc[8 * i + 6], o.acc[8 * i + 7])));
    stsm4(xa + (i >> 2) * 16384 + ((((i & 3) * 2 + xh) ^ xs) << 4), r0, r1, r2, r3);
    if ((i & 3) == 3) {
      __syncwarp();
#pragma unroll
      for (int k = 0; k < 4; k++) {
        const int rr = c.wg * 64 + c.warp * 16 + k * 4 + (c.lane >> 3);
        const uint4 v = lds128(c.addr(2 + (i >> 2)) + rr * 128 + (((c.lane ^ rr) & 7) << 4));
        *(uint4*)(P.out + (uint32_t)((mb * 128 + rr) * 1024 + nb * 128 + (i >> 2) * 64 + (c.lane & 7) * 8)) = v;
      }
    }
  }
}

__device__ __forceinline__ void load_conv(Prod& p, const Maps& M, int u, int ch) {
  if (elect()) {
    mbar_expect(p.full(u), 5120 + UCH);
    tma3d(p.addr(u), &M.h, 0, -8, ch, p.full(u), POL(4));
    bulk_g2s(p.addr(u) + CV_U, g_u + (size_t)ch * UCH, UCH, p.full(u), POL(4));
  }
}
template<int MASK> __device__ __forceinline__ void prod_conv(Prod& p, const Maps& M, int cta, int nch) {
  int ready = -1;
#pragma unroll 1
  for (int i = 0; i < nch; i++) {
    const int ch = conv_channel<MASK>(cta, i);
    const int u = i & 3;
    if ((ch >> 6) != ready) { ready = ch >> 6; if (cta < NREG) mbar_wait(p.base + SM_RDY + 8 * RDY_U, 0); else cnt_wait(g_cnt + (C_U + ready) * CSTRIDE, 128); }
    p.acquire(u, 1);
    load_conv(p, M, u, ch);
    if (i == 3) { p.acquire(4, 4); if (elect()) mbar_arrive(p.full(4)); }
  }
}
#define HOIST(v) asm volatile("" : "+r"(v))
template<int MASK> __device__ __forceinline__ void producer(const Maps& M, const Params& P, uint32_t base, int cta, int lane) {
  Prod p{base, ((MASK & PH_KV) && cta < NREG) ? 0xffffcfffu ^ ((1u << (3 * NFIRST)) - 1) : 0xffffffffu, lane,
         (cta * 3 + 2) * 2048};
  if (cta >= NREG) { if (MASK & PH_CONV) prod_conv<MASK>(p, M, cta, CV_EXTRA<MASK>); return; }
  const int g = cta & 7, j = cta >> 3, rank = cta & 1;
#pragma unroll 1
  for (int half = 0; half < 2; half++) {
    const int h = j + 16 * half;
    if (MASK & PH_KV) {
      const CUtensorMap* mw = rank ? &M.wv : &M.wk;
#pragma unroll 1
      for (int it = half ? 0 : NFIRST; it < 16; it++) {
        const int u = gemm_unit(it);
        uint32_t bar = p.full(u), d0 = p.addr(u), d1 = p.addr(u + 1 + rank); int k0 = (it & 7) * 64, r0 = (2 * g + (it >> 3)) * 128;
        HOIST(bar); HOIST(d0); HOIST(d1); HOIST(k0); HOIST(r0);
        p.acquire(u, 3);
        if (elect()) {
          mbar_expect(bar, 3 * UNIT);
          tma3d_mc(d1, mw, 0, k0, 2 * h, bar, POL(0) && it >= 8);
          tma2d(d0, &M.c, k0, r0, bar, half ? POL(8) : POL(10));
        }
      }
    }
    if (MASK & PH_ATT) {
#pragma unroll 1
      for (int ks = 0; ks < 16; ks++) {
        const int u = gemm_unit(ks);
        uint32_t bar = p.full(u), d0 = p.addr(u), d1 = p.addr(u + 1), d2 = p.addr(u + 2) + rank * 8192; int k0 = ks * 64;
        HOIST(bar); HOIST(d0); HOIST(d1); HOIST(d2); HOIST(k0);
        p.acquire(u, 3);
        if (elect()) {
          mbar_expect(bar, 3 * UNIT);
          tma2d_mc(d2, &M.wq, h * 128 + rank * 64, k0, bar, POL(1));
          tma2d(d0, &M.x, k0, (15 - g) * 128, bar, half ? POL(9) : POL(10));
          tma2d(d1, &M.x, k0, g * 128, bar, half ? POL(9) : POL(10));
        }
      }
      TS(2, 8 * half + 0);
      mbar_wait(base + SM_RDY + 8 * (RDY_KV + half), 0);
      TS(2, 8 * half + 1);
      p.acquire(0, 4);
      if (elect()) mbar_arrive(p.full(0));
      const uint8_t* KVh = g_T + T_KV + (size_t)kv_slot<MASK>(h) * 16 * 65536;
#pragma unroll 1
      for (int i = 0; i < 34; i++) {
        const int isv = (i > 0 && !(i & 1)) || i == 33;
        const int st = i == 33 ? 16 : (isv ? (i >> 1) - 1 : (i + 1) >> 1);
        const int u = att_slot(i & 3);
        const bool own = st == 15 - (g & 6);
        uint32_t bar = p.full((isv && i < 33) ? 14 - u : u), d0 = p.addr(own ? u : u + rank), off = (st <= 15 - g ? st : 16 - st) * 65536 + isv * 32768 + (own ? 0 : rank * UNIT);
        HOIST(bar); HOIST(d0); HOIST(off);
        p.acquire(u, 2);
        if (elect()) {
          if (!isv || i == 33) mbar_expect(bar, (i == 0 || i == 33) ? 32768 : 65536);
          const bool ef = POL(6) || (POL(14) && st >= 8) || (POL(15) && half);
          if (own) bulk_g2s(d0, KVh + off, 32768, bar, ef); else bulk_g2s_mc(d0, KVh + off, UNIT, bar, ef);
          if (MASK == PH_ALL && half && i == PF_AT) {
            if (PF & 1) pf3d(&M.wo, 0, j * 64, 2 * g);
            if (PF & 2) pf_bulk(g_T + T_CTX + (j * 32 + g) * 32768, 32768);
          }
        }
      }
    }
  }
  if ((MASK & PH_CONV) && !(MASK & PH_OUT)) prod_conv<MASK>(p, M, cta, CV_REG<MASK>);
  if (MASK & PH_OUT) {
    const int y0 = out_mb(cta) * 512 + rank * 8, z0 = 2 * out_nb(cta);
    int u = 6;
#pragma unroll 1
    for (int hf = 0; hf < 2; hf++) {
      TS(2, 16 + 2 * hf);
      mbar_wait(base + SM_RDY + 8 * (RDY_CTX + hf), 0);
      TS(2, 17 + 2 * hf);
#pragma unroll 1
      for (int n = hf * 32; n < hf * 32 + 32; n++) {
        const int ks = !XSLOT ? n : n == 1 ? 2 : n == 2 ? 1 : n;
        u = XSLOT && n == 2 ? 2 : XSLOT && n == 3 ? 10 : out_next(u);
        uint32_t bar = p.full(u), d0 = p.addr(u) + rank * 8192, d1 = p.addr(u + 1); int x = (ks & 1) * 256, y = y0 + (ks >> 1) * 16, k0 = ks * 64;
        HOIST(bar); HOIST(d0); HOIST(d1); HOIST(x); HOIST(y); HOIST(k0);
        p.acquire(u, 2);
        if (elect()) {
          mbar_expect(bar, 2 * UNIT);
          tma2d_mc(d0, &M.ctx, x, y, bar, POL(5));
          tma3d(d1, &M.wo, 0, k0, z0, bar, POL(2));
          if ((PF & 4) && (ks & 15) == PF_KS && ks < 48) pf3d(&M.wo, 0, ((ks & 48) + 16 + j) * 64, z0);
          if ((PF & 8) && ks == PF_KS) pf_bulk(g_T + T_CTX + (j * 32 + 8 + g) * 32768, 32768);
          if (XSLOT && ks == 1) mbar_arrive(base + SM_RDY + 8 * RDY_X);
          if (ks == Z_AT) mbar_arrive(base + SM_RDY + 8 * RDY_Z);
        }
      }
    }
  }
}
template<int MASK> __device__ __forceinline__ void producer2(const Maps& M, const Params& P, uint32_t base, int cta, int w, int lane) {
  Prod p{base, 0xffffffffu, lane, 0};
  const int mb = out_mb(cta), nb = out_nb(cta), u = 2 * w;
  if (XSLOT && w) { mbar_wait_slow(base + SM_RDY + 8 * RDY_X, 0); p.mask ^= 12; }
  if (MASK & PH_CONV) {
    mbar_wait_slow(base + SM_SIG + 8 * (SIG_ATT + 1), 0);
    mbar_wait_slow(base + SM_RDY + 8 * RDY_U, 0);
#pragma unroll 1
    for (int i = w; i < CV_REG<MASK>; i += 2) { p.acquire_slow(u, i < 2 ? 2 : 1); load_conv(p, M, u, conv_channel<MASK>(cta, i)); }
  }
  p.acquire_slow(u, 2);
  if (elect()) asm volatile("prefetch.tensormap [%0];" :: "l"(!w ? &M.z : &M.out) : "memory");
  TSA(52 - 2 * w);
  mbar_wait(base + SM_RDY + 8 * (!w ? RDY_Z : RDY_G), 0);
  TSA(53 - 2 * w);
  if (elect()) {
    mbar_expect(p.full(u), 2 * UNIT + (!w ? 0 : 512));
    tma2d(p.addr(u), !w ? &M.z : &M.x, (!w ? mb : nb) * 128, (!w ? nb : mb) * 128, p.full(u), POL(5));
    tma2d(p.addr(u + 1), !w ? &M.z : &M.x, (!w ? mb : nb) * 128 + 64, (!w ? nb : mb) * 128, p.full(u), POL(5));
    if (w) bulk_g2s(base + SM_GATE, g_gate + mb * 128, 512, p.full(u));
  }
}

__device__ __forceinline__ constexpr uint32_t PUB(int sig, int cnt, int n) { return 0x80000000u | (sig << 24) | (n << 8) | cnt; }
__device__ __forceinline__ constexpr uint32_t GET(int rdy, int cnt, int n) { return (rdy << 24) | (n << 8) | cnt; }
template<int MASK> __device__ __forceinline__ void sync_agent(uint32_t base, int cta, int lane) {
  if ((base & 0x3FFFF) != SMEM_BASE) asm volatile("trap;");
  const int g = cta & 7, j = cta >> 3, go = min(out_mb(cta), 15 - out_mb(cta));
  const int c0 = conv_channel<MASK>(cta, 0), c1 = c0 + CV_REG<MASK> - 1, n0 = min(CV_REG<MASK>, 128 - (c0 & 127));
  constexpr bool KV = MASK & PH_KV, ATT = MASK & PH_ATT, CONV = MASK & PH_CONV, OUT = MASK & PH_OUT, ALL = MASK == PH_ALL;
  uint32_t e = 0;
  if (cta >= NREG) { if (CONV && lane * 32 < CV_EXTRA<MASK>) e = PUB(SIG_Z + lane, C_Z + lane, min(32, CV_EXTRA<MASK> - lane * 32)); }
  else switch (lane) {
    case 0:  if (KV) e = PUB(SIG_KV, C_KV + j, 1); break;
    case 1:  if (ATT) e = GET(RDY_KV, C_KV + j, 8); break;
    case 2:  if (ALL) e = PUB(SIG_WAR, C_WAR + j, 1); break;
    case 3:  if (ATT) e = PUB(SIG_CTX, C_CTX + g, 1); break;
    case 4:  if (ALL) e = GET(RDY_WAR, C_WAR + j, 8); break;
    case 5:  if (KV) e = PUB(SIG_KV + 1, C_KV + 16 + j, 1); break;
    case 6:  if (ATT) e = GET(RDY_KV + 1, C_KV + 16 + j, 8); break;
    case 7:  if (OUT) e = GET(RDY_CTX, C_CTX + go, 16); break;
    case 8:  if (CONV) e = GET(RDY_U, C_U + (c0 >> 6), 128); break;
    case 9:  if (CONV) e = GET(RDY_U, C_U + (c1 >> 6), 128); break;
    case 10: if (ATT) e = PUB(SIG_CTX + 1, C_CTX + 8 + g, 1); break;
    case 11: if (OUT) e = GET(RDY_CTX + 1, C_CTX + 8 + go, 16); break;
    case 12: if (OUT) e = GET(RDY_G, C_GATE, 256); break;
    case 13: if (CONV) e = PUB(SIG_Z, C_Z + (c0 >> 7), n0); break;
    case 14: if (CONV && n0 < CV_REG<MASK>) e = PUB(SIG_Z, C_Z + (c1 >> 7), CV_REG<MASK> - n0); break;
    case 15: if (OUT) e = GET(RDY_Z, C_Z + out_nb(cta), 128); break;
  }
  __syncwarp();
#pragma unroll 1
  for (int i = 0; i < 16; i++) {
    const uint32_t x = __shfl_sync(~0u, e, i), id = (x >> 24) & 127, n = (x >> 8) & 0xffff;
    if (x == 0) continue;
    unsigned* cnt = g_cnt + (x & 255) * CSTRIDE;
    if (x >> 31) {
      mbar_wait_slow(base + SM_SIG + 8 * id, 0);
      if (i == 13) TSA(22);
      if (lane == 0) cnt_publish(cnt, n, i != 14);
    } else {
      cnt_wait(cnt, n);
      if (id < 2) {
        const float4 kn = __ldcg((const float4*)(g_kn2 + kv_slot<MASK>(j + 16 * id) * 128) + lane);
        const uint32_t m = __reduce_max_sync(~0u, max(max(__float_as_uint(kn.x), __float_as_uint(kn.y)), max(__float_as_uint(kn.z), __float_as_uint(kn.w))));
        if (lane == 0) asm volatile("st.shared.u32 [%0], %1;" :: "r"(base + SM_KMAX + 4 * id), "r"(m) : "memory");
      }
      if (lane == 0) mbar_arrive(base + SM_RDY + 8 * id);
    }
    __syncwarp();
    TSA(24 + i);
  }
}

__device__ __forceinline__ void aux_gate(const Params& P, int cta, int aw, int lane) {
  uint4 gw[4];
#pragma unroll
  for (int i = 0; i < 4; i++) gw[i] = __ldg((const uint4*)P.gw + i * 32 + lane);
#pragma unroll 1
  for (int row = cta * 16 + aw * 8; row < cta * 16 + aw * 8 + 8; row++) {
    float a = 0.f;
#pragma unroll
    for (int i = 0; i < 4; i++) {
      const uint4 xv = __ldg((const uint4*)(P.x + (size_t)row * 1024) + i * 32 + lane);
      uint32_t m;
      m = hmul2(xv.x, gw[i].x); a += bf_lo(m) + bf_hi(m); m = hmul2(xv.y, gw[i].y); a += bf_lo(m) + bf_hi(m);
      m = hmul2(xv.z, gw[i].z); a += bf_lo(m) + bf_hi(m); m = hmul2(xv.w, gw[i].w); a += bf_lo(m) + bf_hi(m);
    }
#pragma unroll
    for (int o = 16; o > 0; o >>= 1) a += __shfl_xor_sync(~0u, a, o);
    a = bf_lo(pack_bf16(a, 0.f));
    const float gt = bf_lo(pack_bf16(__fdividef(1.f, 1.f + ex2(-a * 1.4426950408889634f)), 0.f));
    if (lane == 0) g_gate[row] = gt;
    if (GATE_SLEEP) __nanosleep(GATE_SLEEP);
  }
  cnt_signal(g_cnt + C_GATE * CSTRIDE, lane);
  if (aw == 0) { TSA(44); }
}
template<int MASK> __device__ __forceinline__ void aux_pre(const Maps& M, const Params& P, uint32_t base, int cta, int aw, int lane) {
  const uint32_t kb = base + 12 * UNIT, bar = base + SM_PRE;
  const int r = lane >> 2, q = lane & 3;
  const int mi = lane >> 3, row0 = (lane & 6) + 1 - (lane & 1);
  const int ra = (mi * 9 + 1) * 2 + row0;
  const int rb = (mi == 0 ? 3 : mi) * 18 + row0;
  if (PRE_DELAY) mbar_wait_slow(base + SM_BAR + 8 * PRE_DELAY_BAR, 0);
#pragma unroll 1
  for (int it = 0; it < (cta < 96 ? 5 : 4); it++) {
    if (GATE_EARLY && it == PRE_EARLY && MASK == PH_ALL) { mbar_wait_slow(base + SM_SIG + 8 * SIG_ATT, 0); aux_gate(P, cta, aw, lane); }
    if (it == PRE_EARLY && MASK == PH_ALL) mbar_wait_slow(base + SM_SIG + 8 * (SIG_ATT + PRE_HALF), 0);
    const int cg = it ? it * 4 - 3 + (cta >> 5) : 0, tb = cta & 31;
    if (aw == 0 && elect()) {
      mbar_expect(bar, 2 * 9216);
      tma4d(kb, &M.k, cg * 64, 0, tb * 8 - 1, 0, bar, POL(3));
      tma4d(kb + 9216, &M.v, cg * 64, 0, tb * 8 - 1, 0, bar, POL(3));
    }
    const uint2 swl = __ldg((const uint2*)(P.shift + (cg * 64 + aw * 32 + lane) * 4));
    if (tb == 0) {
      uint8_t* e = g_u + (size_t)(cg * 64 + aw * 32 + lane) * UCH + 4096;
      *(uint4*)e = make_uint4(0, 0, 0, 0); *(uint4*)(e + UPITCH) = make_uint4(0, 0, 0, 0);
      *(uint32_t*)(e + 32) = (uint32_t)__bfloat16_as_ushort(P.D[cg * 64 + aw * 32 + lane]) * 0x10001u;
    }
    mbar_wait_slow(bar, it & 1);
#pragma unroll 1
    for (int ol = it ? 0 : cta >> 5; ol < (it ? 4 : (cta >> 5) + 1); ol++) {
      const int oc = aw * 4 + ol;
      const uint32_t s01 = __shfl_sync(~0u, swl.x, ol * 8 + r), s23 = __shfl_sync(~0u, swl.y, ol * 8 + r);
      const uint32_t w0 = __byte_perm(s01, 0, 0x1010), w1 = __byte_perm(s01, 0, 0x3232), w2 = __byte_perm(s23, 0, 0x1010), w3 = __byte_perm(s23, 0, 0x3232);
      const uint32_t pa = kb + ra * 128 + ((oc ^ (ra & 7)) << 4), pb = kb + (mi == 0 ? 9216 : 0) + rb * 128 + ((oc ^ (rb & 7)) << 4);
      uint8_t* e0 = g_u + (uint32_t)((cg * 64 + oc * 8 + r) * UCH + (2040 - tb * 64 - 8 * q) * 2);
#pragma unroll
      for (int hb = 0; hb < 2; hb++) {
        uint32_t k[7], v[5];
        ldsm4t(pa + hb * 1024, k[3], k[4], k[5], k[6]);
        ldsm4t(pa + hb * 1024 + 9216, v[1], v[2], v[3], v[4]);
        ldsm4t(pb + hb * 1024, v[0], k[0], k[1], k[2]);
        uint32_t o1 = __byte_perm(k[1], k[0], 0x5432);
#pragma unroll
        for (int m = 0; m < 5; m++) {
          const uint32_t o2 = __byte_perm(k[m + 2], k[m + 1], 0x5432);
          v[m] = hmul2(hadd2(hadd2(hadd2(hmul2(o1, w3), hmul2(k[m + 1], w2)), hmul2(o2, w1)), hmul2(k[m + 2], w0)), v[m]);
          o1 = o2;
        }
        *(uint4*)(e0 - hb * 64) = make_uint4(v[4], v[3], v[2], v[1]);
        *(uint4*)(e0 - hb * 64 + UPITCH) = make_uint4(__byte_perm(v[4], v[3], 0x5432), __byte_perm(v[3], v[2], 0x5432), __byte_perm(v[2], v[1], 0x5432), __byte_perm(v[1], v[0], 0x5432));
        if (PRE_SLEEP && it >= PRE_EARLY) __nanosleep(PRE_SLEEP);
      }
    }
    bar_sync(5, 64);
    if (aw == 0) { TSA(40 + min(it, 3)); }
    if (aw == 1 && lane == 0) asm volatile("red.release.gpu.global.add.u32 [%0], %1;" :: "l"(g_cnt + (C_U + cg) * CSTRIDE), "r"(it ? 4 : 1) : "memory");
  }
  uint32_t rel;
  asm volatile("mapa.shared::cluster.u32 %0, %1, %2;" : "=r"(rel) : "r"(base + SM_BAR + 128 + 8 * (12 + (lane & 1))), "r"((lane >> 1) & 1));
  if (lane < 4) asm volatile("mbarrier.arrive.shared::cluster.b64 _, [%0], 4;" :: "r"(rel) : "memory");
  if (!(GATE_EARLY && MASK == PH_ALL)) aux_gate(P, cta, aw, lane);
}

template<int MASK> __global__ void __cluster_dims__(2, 1, 1) __launch_bounds__(384, 1) gated_mix_kernel(const __grid_constant__ Maps M, const __grid_constant__ Params P) {
  extern __shared__ __align__(1024) uint8_t smem[];
  const uint32_t base = (uint32_t)__cvta_generic_to_shared(smem);
  const int wi = __shfl_sync(~0u, threadIdx.x >> 5, 0), wg = wi >> 2, warp = wi & 3;
  if (elect()) {
    if (wi < 8) {
      const int cnt = 1 << ((0x10334400 >> (4 * wi)) & 15);
#pragma unroll
      for (int i = 0; i < 8; i++) mbar_init(base + SM_BAR + 64 * wi + 8 * i, cnt);
      asm volatile("fence.mbarrier_init.release.cluster;" ::: "memory");
    } else if (MAP_PF) {
      asm volatile("prefetch.tensormap [%0];" :: "l"(&M.c + (wi - 8)) : "memory");
    }
  }
  const int cta = blockIdx.x;
  const bool first_loads = (MASK & PH_KV) && wi == 8 && cta < NREG;
  const CUtensorMap* mw = (cta & 1) ? &M.wv : &M.wk;
  __syncwarp();
  asm volatile("barrier.cluster.arrive.relaxed.aligned;\nbarrier.cluster.wait.aligned;" ::: "memory");
  if (first_loads && elect()) {
#pragma unroll 1
    for (int it = 0; it < NFIRST; it++) {
      const uint32_t bar = base + SM_BAR + 24 * it, d0 = base + 3 * it * UNIT;
      mbar_expect(bar, 3 * UNIT);
      tma3d_mc(d0 + (1 + (cta & 1)) * UNIT, mw, 0, it * 64, 2 * (cta >> 3), bar);
      tma2d(d0, &M.c, it * 64, (cta & 7) * 256, bar);
    }
  }
  __syncwarp();
  const int lane = threadIdx.x & 31;
#define TS_PRO()
  if (wg == 2) {
    asm volatile("setmaxnreg.dec.sync.aligned.u32 56;");
    TS_PRO();
    TS(2, 62);
    if (warp == 0) producer<MASK>(M, P, base, cta, lane);
    else if (warp == 1) sync_agent<MASK>(base, cta, lane);
    else if (cta < NREG) {
      if (MASK & PH_PRE) aux_pre<MASK>(M, P, base, cta, warp - 2, lane);
      if (MASK & PH_OUT) producer2<MASK>(M, P, base, cta, warp - 2, lane);
    }
    if (warp == 1) {
      if (MASK & PH_OUT) {
        unsigned old = 0;
        if (lane == 0) asm volatile("atom.relaxed.gpu.global.add.u32 %0, [%1], 1;" : "=r"(old) : "l"(g_cnt + C_EXIT * CSTRIDE) : "memory");
        old = __shfl_sync(~0u, old, 0);
        if (old == NCTA - 1) for (int i = lane; i < C_NUM; i += 32) g_cnt[i * CSTRIDE] = 0;
      }
      mbar_wait_slow(base + SM_SIG + 8 * SIG_DONE, 0);
      if (cta >= NREG || !(MASK & PH_OUT)) { cluster_arrive(); cluster_wait(); }
    }
  } else {
    asm volatile("setmaxnreg.inc.sync.aligned.u32 224;");
    TS_PRO();
    uint32_t rel;
    asm volatile("mapa.shared::cluster.u32 %0, %1, %2;" : "=r"(rel) : "r"(base + SM_BAR + 128 + 8 * (lane & 15)), "r"(lane >> 4));
    Cons c{base, rel, 0u, lane, warp, wg, (cta * 3 + wg) * 2048};
    if (wg == 1) bar_arrive(1, 256);
    TS(wg, 0);
    if (cta < NREG) {
      const int g = cta & 7, j = cta >> 3;
      Pend w = {};
#pragma unroll 1
      for (int half = 0; half < 2; half++) {
        const int h = j + 16 * half;
        if (MASK & PH_KV) cons_kv<(MASK & PH_ATT) != 0>(c, h, kv_slot<MASK>(h), g, w, half == 1 && (MASK & PH_ATT));
        TS(wg, 1 + 4 * half);
        if (MASK & PH_ATT) {
          Att a;
          cons_q<(MASK & PH_KV) != 0>(c, h, w, a.o);
          TS(wg, 2 + 4 * half);
          cons_att(c, a, h, g, w);
          if (half == 0) c.signal(SIG_WAR);
#pragma unroll
          for (int i = 0; i < 8; i++) w.hi[i] = make_uint4(0, 0, 0, 0);
          TS(wg, 3 + 4 * half);
          if (MASK != PH_ALL) { tile_store<0, 4>(w.lo, w.dst, lane); c.signal(SIG_CTX + half); }
        } else if (MASK & PH_KV) {
          out_piece<SCH_KV, true>(c, w, 0, true);
          for (int ks = 1; ks < 8; ks++) out_piece<SCH_KV, false>(c, w, ks, true);
          c.signal(SIG_KV + half);
        }
      }
      if (MASK & PH_OUT) cons_out<MASK>(c, M, P, cta, w);
    }
    if (cta >= NREG || !(MASK & PH_OUT)) {
      if (MASK & PH_CONV) cons_conv<MASK>(c, cta, cta < NREG ? CV_REG<MASK> : CV_EXTRA<MASK>);
      TS(wg, 9);
      c.signal(SIG_DONE);
      cluster_arrive();
    }
    TS(wg, 10);
  }
}

typedef CUresult (*EncFn)(CUtensorMap*, CUtensorMapDataType, cuuint32_t, void*, const cuuint64_t*, const cuuint64_t*, const cuuint32_t*, const cuuint32_t*,
                          CUtensorMapInterleave, CUtensorMapSwizzle, CUtensorMapL2promotion, CUtensorMapFloatOOBfill);
static void enc(EncFn f, CUtensorMap* m, const void* ptr, int rank, const cuuint64_t* dims, const cuuint64_t* strides, const cuuint32_t* box, CUtensorMapSwizzle sw,
                CUtensorMapDataType dt = CU_TENSOR_MAP_DATA_TYPE_BFLOAT16) {
  const cuuint32_t es[4] = {1, 1, 1, 1};
  f(m, dt, rank, (void*)ptr, dims, strides, box, es, CU_TENSOR_MAP_INTERLEAVE_NONE, sw, CU_TENSOR_MAP_L2_PROMOTION_L2_256B, CU_TENSOR_MAP_FLOAT_OOB_FILL_NONE);
}
static void enc2(EncFn f, CUtensorMap* m, const void* ptr, int cols, int rows, int brows) {
  const cuuint64_t d[2] = {(cuuint64_t)cols, (cuuint64_t)rows}, s[1] = {(cuuint64_t)cols * 2}; const cuuint32_t b[2] = {64, (cuuint32_t)brows};
  enc(f, m, ptr, 2, d, s, b, CU_TENSOR_MAP_SWIZZLE_128B);
}
static void encw(EncFn f, CUtensorMap* m, const void* ptr, int cols, int rows) {
  const cuuint64_t d[3] = {64, (cuuint64_t)rows, (cuuint64_t)cols / 64}, s[2] = {(cuuint64_t)cols * 2, 128}; const cuuint32_t b[3] = {64, 64, 2};
  enc(f, m, ptr, 3, d, s, b, CU_TENSOR_MAP_SWIZZLE_128B);
}
extern "C" void kernel_launch(void* const* d_in, const int* in_sizes, int n_in, void* d_out, int out_size) {
  static EncFn fn = nullptr;
  static int ncl = 0;
  static void* zptr = nullptr;
  static void* tptr = nullptr;
  if (!fn) {
    void* p = nullptr; cudaDriverEntryPointQueryResult qr;
    cudaGetDriverEntryPoint("cuTensorMapEncodeTiled", &p, cudaEnableDefault, &qr);
    fn = (EncFn)p;
    cudaFuncSetAttribute(gated_mix_kernel<PH_ALL>, cudaFuncAttributeMaxDynamicSharedMemorySize, SMEM_BYTES);
    cudaFuncSetAttribute(gated_mix_kernel<PH_PRE | PH_KV>, cudaFuncAttributeMaxDynamicSharedMemorySize, SMEM_BYTES);
    cudaFuncSetAttribute(gated_mix_kernel<PH_ATT | PH_CONV>, cudaFuncAttributeMaxDynamicSharedMemorySize, SMEM_BYTES);
    cudaFuncSetAttribute(gated_mix_kernel<PH_OUT>, cudaFuncAttributeMaxDynamicSharedMemorySize, SMEM_BYTES);
    cudaLaunchConfig_t cfg = {}; cfg.gridDim = NCTA; cfg.blockDim = 384; cfg.dynamicSmemBytes = SMEM_BYTES;
    cudaLaunchAttribute at; at.id = cudaLaunchAttributeClusterDimension; at.val.clusterDim.x = 2; at.val.clusterDim.y = 1; at.val.clusterDim.z = 1;
    cfg.attrs = &at; cfg.numAttrs = 1;
    cudaOccupancyMaxActiveClusters(&ncl, gated_mix_kernel<PH_ALL>, &cfg);
    cudaGetSymbolAddress(&zptr, g_z);
    cudaGetSymbolAddress(&tptr, g_T);
  }
  Maps M;
  enc2(fn, &M.x, d_in[0], 1024, 2048, 128);
  enc2(fn, &M.c, d_in[7], 512, 2048, 128);
  enc2(fn, &M.wq, d_in[8], 4096, 1024, 64);
  encw(fn, &M.wk, d_in[9], 4096, 512);
  encw(fn, &M.wv, d_in[10], 4096, 512);
  encw(fn, &M.wo, d_in[11], 1024, 4096);
  { const cuuint64_t d[3] = {64, 32, 1024}, s[2] = {128, 4096}; const cuuint32_t b[3] = {64, 40, 1}; enc(fn, &M.h, d_in[4], 3, d, s, b, CU_TENSOR_MAP_SWIZZLE_NONE); }
  enc2(fn, &M.z, zptr, 2048, 1024, 128);
  enc2(fn, &M.out, d_out, 1024, 2048, 16);
  { const cuuint64_t d[2] = {512, 512 * 16}, s[1] = {2048}; const cuuint32_t b[2] = {256, 8};
    enc(fn, &M.ctx, tptr, 2, d, s, b, CU_TENSOR_MAP_SWIZZLE_NONE, CU_TENSOR_MAP_DATA_TYPE_UINT32); }
  { const cuuint64_t d[4] = {1024, 2, 256, 4}, s[3] = {2048, 16384, 4096}; const cuuint32_t b[4] = {64, 2, 9, 4};
    enc(fn, &M.k, d_in[1], 4, d, s, b, CU_TENSOR_MAP_SWIZZLE_128B); enc(fn, &M.v, d_in[2], 4, d, s, b, CU_TENSOR_MAP_SWIZZLE_128B); }
  Params P{(const __nv_bfloat16*)d_in[0], (const __nv_bfloat16*)d_in[3],
           (const __nv_bfloat16*)d_in[5], (const __nv_bfloat16*)d_in[12], (__nv_bfloat16*)d_out};
  bool split = 2 * ncl < NCTA;
  if (!split) {
    gated_mix_kernel<PH_ALL><<<NCTA, 384, SMEM_BYTES>>>(M, P);
  } else {
    gated_mix_kernel<PH_PRE | PH_KV><<<NCTA, 384, SMEM_BYTES>>>(M, P);
    gated_mix_kernel<PH_ATT | PH_CONV><<<NCTA, 384, SMEM_BYTES>>>(M, P);
    gated_mix_kernel<PH_OUT><<<NCTA, 384, SMEM_BYTES>>>(M, P);
  }
}
```

```cpp
#include <cuda_runtime.h>
#include <cuda.h>
#include <cuda_bf16.h>
#include <stdint.h>

template<int TB> __device__ __forceinline__ void wgmma_ss_n256(float (&d)[128], uint64_t da, uint64_t db, int scale_d) {
  asm volatile("{\n.reg .pred p;\nsetp.ne.b32 p, %130, 0;\n"
    "wgmma.mma_async.sync.aligned.m64n256k16.f32.bf16.bf16 {%0, %1, %2, %3, %4, %5, %6, %7, %8, %9, %10, %11, %12, %13, %14, %15, %16, %17, %18, %19, %20, %21, %22, %23, %24, %25, %26, %27, %28, %29, %30, %31, %32, %33, %34, %35, %36, %37, %38, %39, %40, %41, %42, %43, %44, %45, %46, %47, %48, %49, %50, %51, %52, %53, %54, %55, %56, %57, %58, %59, %60, %61, %62, %63, %64, %65, %66, %67, %68, %69, %70, %71, %72, %73, %74, %75, %76, %77, %78, %79, %80, %81, %82, %83, %84, %85, %86, %87, %88, %89, %90, %91, %92, %93, %94, %95, %96, %97, %98, %99, %100, %101, %102, %103, %104, %105, %106, %107, %108, %109, %110, %111, %112, %113, %114, %115, %116, %117, %118, %119, %120, %121, %122, %123, %124, %125, %126, %127}, %128, %129, p, 1, 1, 0, %131;\n}\n"
    : "+f"(d[0]), "+f"(d[1]), "+f"(d[2]), "+f"(d[3]), "+f"(d[4]), "+f"(d[5]), "+f"(d[6]), "+f"(d[7]), "+f"(d[8]), "+f"(d[9]), "+f"(d[10]), "+f"(d[11]), "+f"(d[12]), "+f"(d[13]), "+f"(d[14]), "+f"(d[15]), "+f"(d[16]), "+f"(d[17]), "+f"(d[18]), "+f"(d[19]), "+f"(d[20]), "+f"(d[21]), "+f"(d[22]), "+f"(d[23]), "+f"(d[24]), "+f"(d[25]), "+f"(d[26]), "+f"(d[27]), "+f"(d[28]), "+f"(d[29]), "+f"(d[30]), "+f"(d[31]), "+f"(d[32]), "+f"(d[33]), "+f"(d[34]), "+f"(d[35]), "+f"(d[36]), "+f"(d[37]), "+f"(d[38]), "+f"(d[39]), "+f"(d[40]), "+f"(d[41]), "+f"(d[42]), "+f"(d[43]), "+f"(d[44]), "+f"(d[45]), "+f"(d[46]), "+f"(d[47]), "+f"(d[48]), "+f"(d[49]), "+f"(d[50]), "+f"(d[51]), "+f"(d[52]), "+f"(d[53]), "+f"(d[54]), "+f"(d[55]), "+f"(d[56]), "+f"(d[57]), "+f"(d[58]), "+f"(d[59]), "+f"(d[60]), "+f"(d[61]), "+f"(d[62]), "+f"(d[63]), "+f"(d[64]), "+f"(d[65]), "+f"(d[66]), "+f"(d[67]), "+f"(d[68]), "+f"(d[69]), "+f"(d[70]), "+f"(d[71]), "+f"(d[72]), "+f"(d[73]), "+f"(d[74]), "+f"(d[75]), "+f"(d[76]), "+f"(d[77]), "+f"(d[78]), "+f"(d[79]), "+f"(d[80]), "+f"(d[81]), "+f"(d[82]), "+f"(d[83]), "+f"(d[84]), "+f"(d[85]), "+f"(d[86]), "+f"(d[87]), "+f"(d[88]), "+f"(d[89]), "+f"(d[90]), "+f"(d[91]), "+f"(d[92]), "+f"(d[93]), "+f"(d[94]), "+f"(d[95]), "+f"(d[96]), "+f"(d[97]), "+f"(d[98]), "+f"(d[99]), "+f"(d[100]), "+f"(d[101]), "+f"(d[102]), "+f"(d[103]), "+f"(d[104]), "+f"(d[105]), "+f"(d[106]), "+f"(d[107]), "+f"(d[108]), "+f"(d[109]), "+f"(d[110]), "+f"(d[111]), "+f"(d[112]), "+f"(d[113]), "+f"(d[114]), "+f"(d[115]), "+f"(d[116]), "+f"(d[117]), "+f"(d[118]), "+f"(d[119]), "+f"(d[120]), "+f"(d[121]), "+f"(d[122]), "+f"(d[123]), "+f"(d[124]), "+f"(d[125]), "+f"(d[126]), "+f"(d[127])
    : "l"(da), "l"(db), "r"(scale_d), "n"(TB));
}
template<int TB> __device__ __forceinline__ void wgmma_ss_n128(float (&d)[64], uint64_t da, uint64_t db, int scale_d) {
  asm volatile("{\n.reg .pred p;\nsetp.ne.b32 p, %66, 0;\n"
    "wgmma.mma_async.sync.aligned.m64n128k16.f32.bf16.bf16 {%0, %1, %2, %3, %4, %5, %6, %7, %8, %9, %10, %11, %12, %13, %14, %15, %16, %17, %18, %19, %20, %21, %22, %23, %24, %25, %26, %27, %28, %29, %30, %31, %32, %33, %34, %35, %36, %37, %38, %39, %40, %41, %42, %43, %44, %45, %46, %47, %48, %49, %50, %51, %52, %53, %54, %55, %56, %57, %58, %59, %60, %61, %62, %63}, %64, %65, p, 1, 1, 0, %67;\n}\n"
    : "+f"(d[0]), "+f"(d[1]), "+f"(d[2]), "+f"(d[3]), "+f"(d[4]), "+f"(d[5]), "+f"(d[6]), "+f"(d[7]), "+f"(d[8]), "+f"(d[9]), "+f"(d[10]), "+f"(d[11]), "+f"(d[12]), "+f"(d[13]), "+f"(d[14]), "+f"(d[15]), "+f"(d[16]), "+f"(d[17]), "+f"(d[18]), "+f"(d[19]), "+f"(d[20]), "+f"(d[21]), "+f"(d[22]), "+f"(d[23]), "+f"(d[24]), "+f"(d[25]), "+f"(d[26]), "+f"(d[27]), "+f"(d[28]), "+f"(d[29]), "+f"(d[30]), "+f"(d[31]), "+f"(d[32]), "+f"(d[33]), "+f"(d[34]), "+f"(d[35]), "+f"(d[36]), "+f"(d[37]), "+f"(d[38]), "+f"(d[39]), "+f"(d[40]), "+f"(d[41]), "+f"(d[42]), "+f"(d[43]), "+f"(d[44]), "+f"(d[45]), "+f"(d[46]), "+f"(d[47]), "+f"(d[48]), "+f"(d[49]), "+f"(d[50]), "+f"(d[51]), "+f"(d[52]), "+f"(d[53]), "+f"(d[54]), "+f"(d[55]), "+f"(d[56]), "+f"(d[57]), "+f"(d[58]), "+f"(d[59]), "+f"(d[60]), "+f"(d[61]), "+f"(d[62]), "+f"(d[63])
    : "l"(da), "l"(db), "r"(scale_d), "n"(TB));
}
template<int TB> __device__ __forceinline__ void wgmma_rs_n32(float (&d)[16], uint32_t a0, uint32_t a1, uint32_t a2, uint32_t a3, uint64_t db, int scale_d) {
  asm volatile("{\n.reg .pred p;\nsetp.ne.b32 p, %21, 0;\n"
    "wgmma.mma_async.sync.aligned.m64n32k16.f32.bf16.bf16 {%0, %1, %2, %3, %4, %5, %6, %7, %8, %9, %10, %11, %12, %13, %14, %15}, {%16, %17, %18, %19}, %20, p, 1, 1, %22;\n}\n"
    : "+f"(d[0]), "+f"(d[1]), "+f"(d[2]), "+f"(d[3]), "+f"(d[4]), "+f"(d[5]), "+f"(d[6]), "+f"(d[7]), "+f"(d[8]), "+f"(d[9]), "+f"(d[10]), "+f"(d[11]), "+f"(d[12]), "+f"(d[13]), "+f"(d[14]), "+f"(d[15])
    : "r"(a0), "r"(a1), "r"(a2), "r"(a3), "l"(db), "r"(scale_d), "n"(TB));
}
template<int E> __device__ __forceinline__ void wgmma_pv_sel(float (&d)[64], const uint32_t (&p)[32], uint64_t db, int full, int acc, int bar) {
  asm volatile("{\n.reg .pred q, s;\n.reg .b64 t;\nsetp.ne.b32 s, %98, 0;\nsetp.eq.b32 q, %97, 0;\n@q bra.uni LH;\n"
    "wgmma.fence.sync.aligned;\n"
    "add.s64 t, %96, 0;\nwgmma.mma_async.sync.aligned.m64n128k16.f32.bf16.bf16 {%0, %1, %2, %3, %4, %5, %6, %7, %8, %9, %10, %11, %12, %13, %14, %15, %16, %17, %18, %19, %20, %21, %22, %23, %24, %25, %26, %27, %28, %29, %30, %31, %32, %33, %34, %35, %36, %37, %38, %39, %40, %41, %42, %43, %44, %45, %46, %47, %48, %49, %50, %51, %52, %53, %54, %55, %56, %57, %58, %59, %60, %61, %62, %63}, {%64, %65, %66, %67}, t, s, 1, 1, 1;\n"
    "add.s64 t, %96, 256;\nwgmma.mma_async.sync.aligned.m64n128k16.f32.bf16.bf16 {%0, %1, %2, %3, %4, %5, %6, %7, %8, %9, %10, %11, %12, %13, %14, %15, %16, %17, %18, %19, %20, %21, %22, %23, %24, %25, %26, %27, %28, %29, %30, %31, %32, %33, %34, %35, %36, %37, %38, %39, %40, %41, %42, %43, %44, %45, %46, %47, %48, %49, %50, %51, %52, %53, %54, %55, %56, %57, %58, %59, %60, %61, %62, %63}, {%68, %69, %70, %71}, t, 1, 1, 1, 1;\n"
    "add.s64 t, %96, 512;\nwgmma.mma_async.sync.aligned.m64n128k16.f32.bf16.bf16 {%0, %1, %2, %3, %4, %5, %6, %7, %8, %9, %10, %11, %12, %13, %14, %15, %16, %17, %18, %19, %20, %21, %22, %23, %24, %25, %26, %27, %28, %29, %30, %31, %32, %33, %34, %35, %36, %37, %38, %39, %40, %41, %42, %43, %44, %45, %46, %47, %48, %49, %50, %51, %52, %53, %54, %55, %56, %57, %58, %59, %60, %61, %62, %63}, {%72, %73, %74, %75}, t, 1, 1, 1, 1;\n"
    "add.s64 t, %96, 768;\nwgmma.mma_async.sync.aligned.m64n128k16.f32.bf16.bf16 {%0, %1, %2, %3, %4, %5, %6, %7, %8, %9, %10, %11, %12, %13, %14, %15, %16, %17, %18, %19, %20, %21, %22, %23, %24, %25, %26, %27, %28, %29, %30, %31, %32, %33, %34, %35, %36, %37, %38, %39, %40, %41, %42, %43, %44, %45, %46, %47, %48, %49, %50, %51, %52, %53, %54, %55, %56, %57, %58, %59, %60, %61, %62, %63}, {%76, %77, %78, %79}, t, 1, 1, 1, 1;\n"
    "add.s64 t, %96, 1024;\nwgmma.mma_async.sync.aligned.m64n128k16.f32.bf16.bf16 {%0, %1, %2, %3, %4, %5, %6, %7, %8, %9, %10, %11, %12, %13, %14, %15, %16, %17, %18, %19, %20, %21, %22, %23, %24, %25, %26, %27, %28, %29, %30, %31, %32, %33, %34, %35, %36, %37, %38, %39, %40, %41, %42, %43, %44, %45, %46, %47, %48, %49, %50, %51, %52, %53, %54, %55, %56, %57, %58, %59, %60, %61, %62, %63}, {%80, %81, %82, %83}, t, 1, 1, 1, 1;\n"
    "add.s64 t, %96, 1280;\nwgmma.mma_async.sync.aligned.m64n128k16.f32.bf16.bf16 {%0, %1, %2, %3, %4, %5, %6, %7, %8, %9, %10, %11, %12, %13, %14, %15, %16, %17, %18, %19, %20, %21, %22, %23, %24, %25, %26, %27, %28, %29, %30, %31, %32, %33, %34, %35, %36, %37, %38, %39, %40, %41, %42, %43, %44, %45, %46, %47, %48, %49, %50, %51, %52, %53, %54, %55, %56, %57, %58, %59, %60, %61, %62, %63}, {%84, %85, %86, %87}, t, 1, 1, 1, 1;\n"
    "setp.eq.b32 q, %100, 2;\n@q bar.arrive %99, 256;\n"
    "add.s64 t, %96, 1536;\nwgmma.mma_async.sync.aligned.m64n128k16.f32.bf16.bf16 {%0, %1, %2, %3, %4, %5, %6, %7, %8, %9, %10, %11, %12, %13, %14, %15, %16, %17, %18, %19, %20, %21, %22, %23, %24, %25, %26, %27, %28, %29, %30, %31, %32, %33, %34, %35, %36, %37, %38, %39, %40, %41, %42, %43, %44, %45, %46, %47, %48, %49, %50, %51, %52, %53, %54, %55, %56, %57, %58, %59, %60, %61, %62, %63}, {%88, %89, %90, %91}, t, 1, 1, 1, 1;\n"
    "setp.eq.b32 q, %100, 1;\n@q bar.arrive %99, 256;\n"
    "add.s64 t, %96, 1792;\nwgmma.mma_async.sync.aligned.m64n128k16.f32.bf16.bf16 {%0, %1, %2, %3, %4, %5, %6, %7, %8, %9, %10, %11, %12, %13, %14, %15, %16, %17, %18, %19, %20, %21, %22, %23, %24, %25, %26, %27, %28, %29, %30, %31, %32, %33, %34, %35, %36, %37, %38, %39, %40, %41, %42, %43, %44, %45, %46, %47, %48, %49, %50, %51, %52, %53, %54, %55, %56, %57, %58, %59, %60, %61, %62, %63}, {%92, %93, %94, %95}, t, 1, 1, 1, 1;\n"
    "wgmma.commit_group.sync.aligned;\nsetp.eq.b32 q, %100, 0;\n@q bar.arrive %99, 256;\n"
    "bra.uni LE;\nLH:\n"
    "wgmma.fence.sync.aligned;\n"
    "add.s64 t, %96, 0;\nwgmma.mma_async.sync.aligned.m64n128k16.f32.bf16.bf16 {%0, %1, %2, %3, %4, %5, %6, %7, %8, %9, %10, %11, %12, %13, %14, %15, %16, %17, %18, %19, %20, %21, %22, %23, %24, %25, %26, %27, %28, %29, %30, %31, %32, %33, %34, %35, %36, %37, %38, %39, %40, %41, %42, %43, %44, %45, %46, %47, %48, %49, %50, %51, %52, %53, %54, %55, %56, %57, %58, %59, %60, %61, %62, %63}, {%80, %81, %82, %83}, t, s, 1, 1, 1;\n"
    "add.s64 t, %96, 256;\nwgmma.mma_async.sync.aligned.m64n128k16.f32.bf16.bf16 {%0, %1, %2, %3, %4, %5, %6, %7, %8, %9, %10, %11, %12, %13, %14, %15, %16, %17, %18, %19, %20, %21, %22, %23, %24, %25, %26, %27, %28, %29, %30, %31, %32, %33, %34, %35, %36, %37, %38, %39, %40, %41, %42, %43, %44, %45, %46, %47, %48, %49, %50, %51, %52, %53, %54, %55, %56, %57, %58, %59, %60, %61, %62, %63}, {%84, %85, %86, %87}, t, 1, 1, 1, 1;\n"
    "setp.eq.b32 q, %100, 2;\n@q bar.arrive %99, 256;\n"
    "add.s64 t, %96, 512;\nwgmma.mma_async.sync.aligned.m64n128k16.f32.bf16.bf16 {%0, %1, %2, %3, %4, %5, %6, %7, %8, %9, %10, %11, %12, %13, %14, %15, %16, %17, %18, %19, %20, %21, %22, %23, %24, %25, %26, %27, %28, %29, %30, %31, %32, %33, %34, %35, %36, %37, %38, %39, %40, %41, %42, %43, %44, %45, %46, %47, %48, %49, %50, %51, %52, %53, %54, %55, %56, %57, %58, %59, %60, %61, %62, %63}, {%88, %89, %90, %91}, t, 1, 1, 1, 1;\n"
    "setp.eq.b32 q, %100, 1;\n@q bar.arrive %99, 256;\n"
    "add.s64 t, %96, 768;\nwgmma.mma_async.sync.aligned.m64n128k16.f32.bf16.bf16 {%0, %1, %2, %3, %4, %5, %6, %7, %8, %9, %10, %11, %12, %13, %14, %15, %16, %17, %18, %19, %20, %21, %22, %23, %24, %25, %26, %27, %28, %29, %30, %31, %32, %33, %34, %35, %36, %37, %38, %39, %40, %41, %42, %43, %44, %45, %46, %47, %48, %49, %50, %51, %52, %53, %54, %55, %56, %57, %58, %59, %60, %61, %62, %63}, {%92, %93, %94, %95}, t, 1, 1, 1, 1;\n"
    "wgmma.commit_group.sync.aligned;\nsetp.eq.b32 q, %100, 0;\n@q bar.arrive %99, 256;\n"
    "LE:\n}\n"
    : "+f"(d[0]), "+f"(d[1]), "+f"(d[2]), "+f"(d[3]), "+f"(d[4]), "+f"(d[5]), "+f"(d[6]), "+f"(d[7]), "+f"(d[8]), "+f"(d[9]), "+f"(d[10]), "+f"(d[11]), "+f"(d[12]), "+f"(d[13]), "+f"(d[14]), "+f"(d[15]), "+f"(d[16]), "+f"(d[17]), "+f"(d[18]), "+f"(d[19]), "+f"(d[20]), "+f"(d[21]), "+f"(d[22]), "+f"(d[23]), "+f"(d[24]), "+f"(d[25]), "+f"(d[26]), "+f"(d[27]), "+f"(d[28]), "+f"(d[29]), "+f"(d[30]), "+f"(d[31]), "+f"(d[32]), "+f"(d[33]), "+f"(d[34]), "+f"(d[35]), "+f"(d[36]), "+f"(d[37]), "+f"(d[38]), "+f"(d[39]), "+f"(d[40]), "+f"(d[41]), "+f"(d[42]), "+f"(d[43]), "+f"(d[44]), "+f"(d[45]), "+f"(d[46]), "+f"(d[47]), "+f"(d[48]), "+f"(d[49]), "+f"(d[50]), "+f"(d[51]), "+f"(d[52]), "+f"(d[53]), "+f"(d[54]), "+f"(d[55]), "+f"(d[56]), "+f"(d[57]), "+f"(d[58]), "+f"(d[59]), "+f"(d[60]), "+f"(d[61]), "+f"(d[62]), "+f"(d[63])
    : "r"(p[0]), "r"(p[1]), "r"(p[2]), "r"(p[3]), "r"(p[4]), "r"(p[5]), "r"(p[6]), "r"(p[7]), "r"(p[8]), "r"(p[9]), "r"(p[10]), "r"(p[11]), "r"(p[12]), "r"(p[13]), "r"(p[14]), "r"(p[15]), "r"(p[16]), "r"(p[17]), "r"(p[18]), "r"(p[19]), "r"(p[20]), "r"(p[21]), "r"(p[22]), "r"(p[23]), "r"(p[24]), "r"(p[25]), "r"(p[26]), "r"(p[27]), "r"(p[28]), "r"(p[29]), "r"(p[30]), "r"(p[31]), "l"(db), "r"(full), "r"(acc), "r"(bar), "n"(E) : "memory");
}

constexpr int NCTA = 132, NREG = 128;
constexpr int UNIT = 16384, NUNIT = 14;
constexpr uint32_t SMEM_BASE = 1024;
constexpr int SM_BAR = NUNIT * UNIT;
constexpr int SM_GATE = SM_BAR + 1024;
constexpr int SMEM_BYTES = SM_BAR + 1536;
constexpr int UPITCH = 4160, UCH = 2 * UPITCH;
constexpr float QSCALE = 0.08838834764831845f * 1.4426950408889634f;
constexpr float BOUND2 = 48.f * 48.f / 1.15f;
#define CONV_REG 5
constexpr int C_KV = 0;
constexpr int C_CTX = 32;
constexpr int C_U = 48;
constexpr int C_Z = 80;
constexpr int C_GATE = 88;
constexpr int C_EXIT = 89;
#define PRE_EARLY 2
#define PRE_HALF 1
#define ATT_SPLIT 6
#define NFIRST 2
#define PRE_DELAY 0
#define MAP_PF 1
#define FINAL_ST 1
#define Z_AT 60
#define PRE_DELAY_BAR 9
#define PRE_FMA 0
#define PRE_SLEEP 300
#define GATE_SLEEP 1000
#define GATE_EARLY 1
#define OC_S0 2
#define OC_S1 11
#define OC_POST 1
#define OC_L0 18
#define OC_L1 18
#define PF 0
#define PF_AT 26
#define PF_KS 8
#define ST_1 4
#define ST_D 2
#define ST_0 1
#define ST_0D 0
#define SCH_KV 0x6665544433221100ull
#define SCH_Q 0x6665544433221100ull
#define NK_AT 1
#ifndef NV_AT
#define NV_AT 3
#endif
#define DS_A 3
#define DS_B 6
#define FAST_AT 0
#define K0X 1
#define EPASS 2
#define XSLOT 1
#define EF 127
#define POL(bit) (((EF >> (bit)) & 1) != 0)
constexpr int C_WAR = 96;
constexpr int C_NUM = 112;
constexpr int CSTRIDE = 32;
constexpr int SM_KMAX = SM_BAR + 640, SM_DUMMY = SM_BAR + 648, SM_PRE = SM_BAR + 112, SM_SIG = SM_BAR + 256, SM_RDY = SM_BAR + 384;
enum { SIG_KV = 0, SIG_CTX = 2, SIG_Z = 4, SIG_DONE = 8, SIG_WAR = 9, SIG_ATT = 10 };
enum { RDY_KV = 0, RDY_CTX = 2, RDY_WAR = 4, RDY_G = 5, RDY_X = 6, RDY_AUX = 7, RDY_U = 8, RDY_Z = 9 };
enum { PH_PRE = 1, PH_KV = 2, PH_ATT = 4, PH_CONV = 8, PH_OUT = 16, PH_ALL = 31 };

constexpr uint32_t T_CTX = 0, T_KV = 16 * 32 * 32768, T_BYTES = T_KV + 32 * 16 * 65536;
__device__ __align__(1024) uint8_t g_T[T_BYTES];
__device__ __align__(1024) uint8_t g_u[1024 * UCH];
__device__ __align__(1024) __nv_bfloat16 g_z[1024 * 2048];
__device__ __align__(1024) float g_gate[2048];
__device__ __align__(1024) float g_kn2[32 * 128];
__device__ __align__(1024) unsigned g_cnt[C_NUM * CSTRIDE];

struct __align__(64) Maps { CUtensorMap c, wk, wv, x, wq, wo, h, z, out, ctx, k, v; };
struct Params {
  const __nv_bfloat16 *x, *shift, *D, *gw;
  __nv_bfloat16* out;
};

__device__ __forceinline__ void wg_fence() { asm volatile("wgmma.fence.sync.aligned;" ::: "memory"); }
__device__ __forceinline__ void wg_commit() { asm volatile("wgmma.commit_group.sync.aligned;" ::: "memory"); }
template<int N> __device__ __forceinline__ void wg_wait() { asm volatile("wgmma.wait_group.sync.aligned %0;" :: "n"(N) : "memory"); }
__device__ __forceinline__ uint64_t odesc(uint32_t addr, uint32_t lbo, uint32_t sbo, uint32_t swz) {
  uint64_t d = (uint64_t)(addr >> 4) + (((uint64_t)(lbo >> 4) << 16) | ((uint64_t)(sbo >> 4) << 32) | ((uint64_t)swz << 62));
  asm volatile("" : "+l"(d));
  return d;
}
__device__ __forceinline__ void mbar_init(uint32_t bar, int cnt) { asm volatile("mbarrier.init.shared::cta.b64 [%0], %1;" :: "r"(bar), "r"(cnt)); }
__device__ __forceinline__ void mbar_expect(uint32_t bar, uint32_t bytes) { asm volatile("mbarrier.arrive.expect_tx.shared::cta.b64 _, [%0], %1;" :: "r"(bar), "r"(bytes) : "memory"); }
__device__ __forceinline__ void mbar_arrive(uint32_t bar) { asm volatile("mbarrier.arrive.shared::cta.b64 _, [%0];" :: "r"(bar) : "memory"); }
__device__ __forceinline__ void mbar_arrive_n(uint32_t bar, int n) { asm volatile("mbarrier.arrive.shared::cta.b64 _, [%0], %1;" :: "r"(bar), "r"(n) : "memory"); }
__device__ __forceinline__ void mbar_wait(uint32_t bar, uint32_t parity) {
  asm volatile("{\n.reg .pred p;\nLW:\nmbarrier.try_wait.parity.shared::cta.b64 p, [%0], %1;\n@!p bra LW;\n}\n" :: "r"(bar), "r"(parity) : "memory");
}
__device__ __forceinline__ void mbar_wait_slow(uint32_t bar, uint32_t parity) {
  asm volatile("{\n.reg .pred p;\n.reg .u32 n;\nmov.u32 n, 0;\n"
    "LW:\nmbarrier.test_wait.parity.shared::cta.b64 p, [%0], %1;\n@p bra LD;\n"
    "nanosleep.u32 128;\nadd.u32 n, n, 1;\nsetp.lt.u32 p, n, 4194304;\n@p bra LW;\ntrap;\nLD:\n}\n" :: "r"(bar), "r"(parity) : "memory");
}
__device__ __forceinline__ void mbar_wait_all(uint32_t bar, uint32_t parity) {
  asm volatile("{\n.reg .pred p, q;\nLW:\nmbarrier.try_wait.parity.shared::cta.b64 p, [%0], %1;\nvote.sync.all.pred q, p, 0xffffffff;\n@!q bra.uni LW;\n}\n" :: "r"(bar), "r"(parity) : "memory");
}
__device__ __forceinline__ void cnt_wait(const unsigned* p, unsigned target) {
  asm volatile("{\n.reg .pred p;\n.reg .u32 n, v;\nmov.u32 n, 0;\n"
    "LW:\nld.relaxed.gpu.global.u32 v, [%0];\nsetp.ge.u32 p, v, %1;\n@p bra LD;\n"
    "nanosleep.u32 64;\nadd.u32 n, n, 1;\nsetp.lt.u32 p, n, 4194304;\n@p bra LW;\ntrap;\nLD:\nfence.acquire.gpu;\nfence.proxy.async.global;\n}\n" :: "l"(p), "r"(target) : "memory");
}
__device__ __forceinline__ void cnt_signal(unsigned* p, int lane) {
  __syncwarp();
  if (lane == 0) asm volatile("red.release.gpu.global.add.u32 [%0], 1;" :: "l"(p) : "memory");
}
__device__ __forceinline__ void cnt_publish(unsigned* p, unsigned n, bool fence) {
  if (fence) asm volatile("fence.release.gpu;" ::: "memory");
  asm volatile("red.relaxed.gpu.global.add.u32 [%0], %1;" :: "l"(p), "r"(n) : "memory");
}
__device__ __forceinline__ uint64_t pol_first() { uint64_t p; asm("createpolicy.fractional.L2::evict_first.b64 %0, 1.0;" : "=l"(p)); return p; }
__device__ __forceinline__ void bulk_g2s(uint32_t dst, const void* src, uint32_t bytes, uint32_t bar, bool stream = false) {
  if (stream) asm volatile("cp.async.bulk.shared::cluster.global.mbarrier::complete_tx::bytes.L2::cache_hint [%0], [%1], %2, [%3], %4;" :: "r"(dst), "l"(src), "r"(bytes), "r"(bar), "l"(pol_first()) : "memory");
  else asm volatile("cp.async.bulk.shared::cluster.global.mbarrier::complete_tx::bytes [%0], [%1], %2, [%3];" :: "r"(dst), "l"(src), "r"(bytes), "r"(bar) : "memory");
}
__device__ __forceinline__ void tma2d(uint32_t dst, const CUtensorMap* m, int x, int y, uint32_t bar, bool stream = false) {
  if (stream) asm volatile("cp.async.bulk.tensor.2d.shared::cluster.global.mbarrier::complete_tx::bytes.L2::cache_hint [%0], [%1, {%3, %4}], [%2], %5;" :: "r"(dst), "l"(m), "r"(bar), "r"(x), "r"(y), "l"(pol_first()) : "memory");
  else asm volatile("cp.async.bulk.tensor.2d.shared::cluster.global.mbarrier::complete_tx::bytes [%0], [%1, {%3, %4}], [%2];" :: "r"(dst), "l"(m), "r"(bar), "r"(x), "r"(y) : "memory");
}
__device__ __forceinline__ void tma3d(uint32_t dst, const CUtensorMap* m, int x, int y, int z, uint32_t bar, bool stream = false) {
  if (stream) asm volatile("cp.async.bulk.tensor.3d.shared::cluster.global.mbarrier::complete_tx::bytes.L2::cache_hint [%0], [%1, {%3, %4, %5}], [%2], %6;" :: "r"(dst), "l"(m), "r"(bar), "r"(x), "r"(y), "r"(z), "l"(pol_first()) : "memory");
  else asm volatile("cp.async.bulk.tensor.3d.shared::cluster.global.mbarrier::complete_tx::bytes [%0], [%1, {%3, %4, %5}], [%2];" :: "r"(dst), "l"(m), "r"(bar), "r"(x), "r"(y), "r"(z) : "memory");
}
__device__ __forceinline__ void tma4d(uint32_t dst, const CUtensorMap* m, int x, int y, int z, int w, uint32_t bar, bool stream = false) {
  if (stream) asm volatile("cp.async.bulk.tensor.4d.shared::cluster.global.mbarrier::complete_tx::bytes.L2::cache_hint [%0], [%1, {%3, %4, %5, %6}], [%2], %7;" :: "r"(dst), "l"(m), "r"(bar), "r"(x), "r"(y), "r"(z), "r"(w), "l"(pol_first()) : "memory");
  else asm volatile("cp.async.bulk.tensor.4d.shared::cluster.global.mbarrier::complete_tx::bytes [%0], [%1, {%3, %4, %5, %6}], [%2];" :: "r"(dst), "l"(m), "r"(bar), "r"(x), "r"(y), "r"(z), "r"(w) : "memory");
}
__device__ __forceinline__ void bulk_g2s_mc(uint32_t dst, const void* src, uint32_t bytes, uint32_t bar, bool stream = false) {
  if (stream) asm volatile("cp.async.bulk.shared::cluster.global.mbarrier::complete_tx::bytes.multicast::cluster.L2::cache_hint [%0], [%1], %2, [%3], %4, %5;" :: "r"(dst), "l"(src), "r"(bytes), "r"(bar), "h"((uint16_t)3), "l"(pol_first()) : "memory");
  else asm volatile("cp.async.bulk.shared::cluster.global.mbarrier::complete_tx::bytes.multicast::cluster [%0], [%1], %2, [%3], %4;" :: "r"(dst), "l"(src), "r"(bytes), "r"(bar), "h"((uint16_t)3) : "memory");
}
__device__ __forceinline__ void tma2d_mc(uint32_t dst, const CUtensorMap* m, int x, int y, uint32_t bar, bool stream = false) {
  if (stream) asm volatile("cp.async.bulk.tensor.2d.shared::cluster.global.mbarrier::complete_tx::bytes.multicast::cluster.L2::cache_hint [%0], [%1, {%3, %4}], [%2], %5, %6;" :: "r"(dst), "l"(m), "r"(bar), "r"(x), "r"(y), "h"((uint16_t)3), "l"(pol_first()) : "memory");
  else asm volatile("cp.async.bulk.tensor.2d.shared::cluster.global.mbarrier::complete_tx::bytes.multicast::cluster [%0], [%1, {%3, %4}], [%2], %5;" :: "r"(dst), "l"(m), "r"(bar), "r"(x), "r"(y), "h"((uint16_t)3) : "memory");
}
__device__ __forceinline__ void tma3d_mc(uint32_t dst, const CUtensorMap* m, int x, int y, int z, uint32_t bar, bool stream = false) {
  if (stream) asm volatile("cp.async.bulk.tensor.3d.shared::cluster.global.mbarrier::complete_tx::bytes.multicast::cluster.L2::cache_hint [%0], [%1, {%3, %4, %5}], [%2], %6, %7;" :: "r"(dst), "l"(m), "r"(bar), "r"(x), "r"(y), "r"(z), "h"((uint16_t)3), "l"(pol_first()) : "memory");
  else asm volatile("cp.async.bulk.tensor.3d.shared::cluster.global.mbarrier::complete_tx::bytes.multicast::cluster [%0], [%1, {%3, %4, %5}], [%2], %6;" :: "r"(dst), "l"(m), "r"(bar), "r"(x), "r"(y), "r"(z), "h"((uint16_t)3) : "memory");
}
__device__ __forceinline__ void pf3d(const CUtensorMap* m, int x, int y, int z) {
  asm volatile("cp.async.bulk.prefetch.tensor.3d.L2.global [%0, {%1, %2, %3}];" :: "l"(m), "r"(x), "r"(y), "r"(z) : "memory");
}
__device__ __forceinline__ void pf_bulk(const void* p, uint32_t bytes) { asm volatile("cp.async.bulk.prefetch.L2.global [%0], %1;" :: "l"(p), "r"(bytes) : "memory"); }
__device__ __forceinline__ void tma2d_store(const CUtensorMap* m, uint32_t src, int x, int y) {
  if (POL(12)) asm volatile("cp.async.bulk.tensor.2d.global.shared::cta.bulk_group.L2::cache_hint [%0, {%2, %3}], [%1], %4;" :: "l"(m), "r"(src), "r"(x), "r"(y), "l"(pol_first()) : "memory");
  else asm volatile("cp.async.bulk.tensor.2d.global.shared::cta.bulk_group [%0, {%2, %3}], [%1];" :: "l"(m), "r"(src), "r"(x), "r"(y) : "memory");
}
__device__ __forceinline__ bool elect() {
  uint32_t r; asm volatile("{\n.reg .pred p;\nelect.sync _|p, 0xffffffff;\nselp.u32 %0, 1, 0, p;\n}\n" : "=r"(r)); return r != 0;
}
__device__ __forceinline__ void cluster_arrive() { asm volatile("barrier.cluster.arrive;" ::: "memory"); }
__device__ __forceinline__ void cluster_wait() { asm volatile("barrier.cluster.wait;" ::: "memory"); }
__device__ __forceinline__ void bar_sync(int id, int n) { asm volatile("bar.sync %0, %1;" :: "r"(id), "r"(n) : "memory"); }
__device__ __forceinline__ void bar_arrive(int id, int n) { asm volatile("bar.arrive %0, %1;" :: "r"(id), "r"(n) : "memory"); }
__device__ __forceinline__ int bar_and(int id, int n, int pred) {
  int r; asm volatile("{\n.reg .pred p, q;\nsetp.ne.b32 p, %3, 0;\nbar.red.and.pred q, %1, %2, p;\nselp.b32 %0, 1, 0, q;\n}\n" : "=r"(r) : "r"(id), "r"(n), "r"(pred) : "memory");
  return r;
}
__device__ __forceinline__ void fence_async_smem() { asm volatile("fence.proxy.async.shared::cta;" ::: "memory"); }
__device__ __forceinline__ float ex2(float x) { float y; asm("ex2.approx.ftz.f32 %0, %1;" : "=f"(y) : "f"(x)); return y; }
__device__ __forceinline__ uint32_t pack_bf16(float lo, float hi) { uint32_t r; asm("cvt.rn.bf16x2.f32 %0, %1, %2;" : "=r"(r) : "f"(hi), "f"(lo)); return r; }
__device__ __forceinline__ uint32_t hmul2(uint32_t a, uint32_t b) { uint32_t r; asm("mul.rn.bf16x2 %0, %1, %2;" : "=r"(r) : "r"(a), "r"(b)); return r; }
__device__ __forceinline__ uint32_t hadd2(uint32_t a, uint32_t b) { uint32_t r; asm("add.rn.bf16x2 %0, %1, %2;" : "=r"(r) : "r"(a), "r"(b)); return r; }
__device__ __forceinline__ uint32_t hfma2(uint32_t a, uint32_t b, uint32_t c) { uint32_t r; asm("fma.rn.bf16x2 %0, %1, %2, %3;" : "=r"(r) : "r"(a), "r"(b), "r"(c)); return r; }
__device__ __forceinline__ float bf_lo(uint32_t a) { return __uint_as_float(a << 16); }
__device__ __forceinline__ float bf_hi(uint32_t a) { return __uint_as_float(a & 0xffff0000u); }
__device__ __forceinline__ uint32_t lds32(uint32_t a) { uint32_t v; asm volatile("ld.shared.u32 %0, [%1];" : "=r"(v) : "r"(a) : "memory"); return v; }
__device__ __forceinline__ float2 lds64f(uint32_t a) { float2 v; asm volatile("ld.shared.v2.f32 {%0,%1}, [%2];" : "=f"(v.x), "=f"(v.y) : "r"(a) : "memory"); return v; }
__device__ __forceinline__ uint4 lds128(uint32_t a) { uint4 v; asm volatile("ld.shared.v4.u32 {%0,%1,%2,%3}, [%4];" : "=r"(v.x), "=r"(v.y), "=r"(v.z), "=r"(v.w) : "r"(a) : "memory"); return v; }
__device__ __forceinline__ void sts64f(uint32_t a, float x, float y) { asm volatile("st.shared.v2.f32 [%0], {%1,%2};" :: "r"(a), "f"(x), "f"(y) : "memory"); }
__device__ __forceinline__ void sts128(uint32_t a, uint4 v) { asm volatile("st.shared.v4.u32 [%0], {%1,%2,%3,%4};" :: "r"(a), "r"(v.x), "r"(v.y), "r"(v.z), "r"(v.w) : "memory"); }
template<int OFF> __device__ __forceinline__ void sts128o(uint32_t a, uint4 v) { asm volatile("st.shared.v4.u32 [%0+%5], {%1,%2,%3,%4};" :: "r"(a), "r"(v.x), "r"(v.y), "r"(v.z), "r"(v.w), "n"(OFF) : "memory"); }
__device__ __forceinline__ void ldsm4(uint32_t a, uint32_t& r0, uint32_t& r1, uint32_t& r2, uint32_t& r3) {
  asm volatile("ldmatrix.sync.aligned.m8n8.x4.shared.b16 {%0,%1,%2,%3}, [%4];" : "=r"(r0), "=r"(r1), "=r"(r2), "=r"(r3) : "r"(a) : "memory");
}
__device__ __forceinline__ void ldsm4t(uint32_t a, uint32_t& r0, uint32_t& r1, uint32_t& r2, uint32_t& r3) {
  asm volatile("ldmatrix.sync.aligned.m8n8.x4.trans.shared.b16 {%0,%1,%2,%3}, [%4];" : "=r"(r0), "=r"(r1), "=r"(r2), "=r"(r3) : "r"(a) : "memory");
}
__device__ __forceinline__ void stsm4(uint32_t a, uint32_t r0, uint32_t r1, uint32_t r2, uint32_t r3) {
  asm volatile("stmatrix.sync.aligned.m8n8.x4.shared.b16 [%0], {%1,%2,%3,%4};" :: "r"(a), "r"(r0), "r"(r1), "r"(r2), "r"(r3) : "memory");
}
template<int N> __device__ __forceinline__ void fence_regs(float (&d)[N]) {
#pragma unroll
  for (int i = 0; i < N; i++) asm volatile("" : "+f"(d[i]) :: "memory");
}
template<int N> __device__ __forceinline__ void fence_regs(uint32_t (&d)[N]) {
#pragma unroll
  for (int i = 0; i < N; i++) asm volatile("" : "+r"(d[i]) :: "memory");
}
__device__ __forceinline__ void sched_fence(float x, uint32_t dummy) {
  asm volatile("{\n.reg .pred p;\nsetp.eq.u32 p, %0, 0x7fc12345;\n@p st.shared.u32 [%1], %0;\n}\n" :: "r"(__float_as_uint(x)), "r"(dummy) : "memory");
}
#define ROT 0
#define CTAID blockIdx.x
#define PTRACE 0
#define TS(role, i)
#define TSA(i)
#define TS2(role, i)
#define TR(obj, role, tag)

#define SHADOW if (gridDim.y == 1)

struct Prod {
  uint32_t base, mask; int lane, nt;
  __device__ __forceinline__ uint32_t full(int u) const { return base + SM_BAR + 8 * u; }
  __device__ __forceinline__ uint32_t addr(int u) const { return base + u * UNIT; }
  __device__ __forceinline__ void acquire(int u, int n) {
    const int v = u + min(lane, n - 1);
    mbar_wait_all(base + SM_BAR + 128 + 8 * v, mask >> v);
    mask ^= ((1u << n) - 1) << u;
    TR(*this, 2, 16 + u);
  }
  __device__ __forceinline__ void acquire_slow(int u, int n) {
    for (int i = 0; i < n; i++) mbar_wait_slow(base + SM_BAR + 128 + 8 * (u + i), mask >> (u + i));
    mask ^= ((1u << n) - 1) << u;
  }
};
struct Cons {
  uint32_t base, rel, mask; int lane, warp, wg, nt;
  __device__ __forceinline__ uint32_t addr(int u) const { return base + u * UNIT; }
  __device__ __forceinline__ static uint32_t daddr(int u) { return SMEM_BASE + u * UNIT; }
  __device__ __forceinline__ void wait(int u) { TR(*this, wg, 1); mbar_wait(base + SM_BAR + 8 * u, mask >> u); mask ^= 1u << u; TR(*this, wg, 2); }
  __device__ __forceinline__ void skip(int u) { mask ^= 1u << u; }
  __device__ __forceinline__ void release(int u, int n) {
    TR(*this, wg, 5);
    asm volatile("{\n.reg .pred p;\nsetp.lt.s32 p, %1, %2;\n@p mbarrier.arrive.shared::cluster.b64 _, [%0];\n}\n" :: "r"(rel + 8 * u), "r"(lane & 15), "r"(n) : "memory");
  }
  __device__ __forceinline__ void release2(int u) {
    asm volatile("{\n.reg .pred p;\nsetp.eq.s32 p, %1, 0;\n@p mbarrier.arrive.shared::cluster.b64 _, [%0], 2;\n}\n" :: "r"(rel + 8 * u), "r"(lane & 15) : "memory");
  }
  __device__ __forceinline__ void signal(int i) {
    __syncwarp();
    asm volatile("{\n.reg .pred p;\nsetp.eq.s32 p, %1, 0;\n@p mbarrier.arrive.shared::cta.b64 _, [%0];\n}\n" :: "r"(base + SM_SIG + 8 * i), "r"(lane) : "memory");
  }
  __device__ __forceinline__ void turn() { bar_sync(1 + wg, 256); TR(*this, wg, 3); }
  __device__ __forceinline__ void pass() { bar_arrive(2 - wg, 256); TR(*this, wg, 4); }
};
__device__ __forceinline__ int gemm_unit(int ks) { return 3 * (ks & 3); }
__device__ __forceinline__ int att_slot(int i) { return 4 + 2 * i; }
template<int MASK> __device__ __forceinline__ int kv_slot(int h) { return MASK == PH_ALL ? h & 15 : h; }
__device__ __forceinline__ int out_mb(int cta) { return cta >> 3; }
__device__ __forceinline__ int out_nb(int cta) { return cta & 7; }
template<int MASK> constexpr int CV_REG = MASK == PH_ALL ? CONV_REG : 6;
template<int MASK> constexpr int CV_EXTRA = (1024 - NREG * CV_REG<MASK>) / (NCTA - NREG);
template<int MASK> __device__ __forceinline__ int conv_channel(int cta, int i) {
  return cta < NREG ? CV_EXTRA<MASK> * (NCTA - NREG) + cta * CV_REG<MASK> + i : (i >> 1) * 8 + (cta - NREG) * 2 + (i & 1);
}

template<int OFF, int N> __device__ __forceinline__ void pack_chunk(const float (&a)[N], float sc0, float sc1, uint4& v0, uint4& v1) {
  v0.x = pack_bf16(a[OFF + 0] * sc0, a[OFF + 1] * sc0); v0.y = pack_bf16(a[OFF + 4] * sc0, a[OFF + 5] * sc0);
  v0.z = pack_bf16(a[OFF + 8] * sc0, a[OFF + 9] * sc0); v0.w = pack_bf16(a[OFF + 12] * sc0, a[OFF + 13] * sc0);
  v1.x = pack_bf16(a[OFF + 2] * sc1, a[OFF + 3] * sc1); v1.y = pack_bf16(a[OFF + 6] * sc1, a[OFF + 7] * sc1);
  v1.z = pack_bf16(a[OFF + 10] * sc1, a[OFF + 11] * sc1); v1.w = pack_bf16(a[OFF + 14] * sc1, a[OFF + 15] * sc1);
}
template<int OFF, int N> __device__ __forceinline__ void pack_chunk(const float (&a)[N], uint4& v0, uint4& v1) {
  v0.x = pack_bf16(a[OFF + 0], a[OFF + 1]); v0.y = pack_bf16(a[OFF + 4], a[OFF + 5]);
  v0.z = pack_bf16(a[OFF + 8], a[OFF + 9]); v0.w = pack_bf16(a[OFF + 12], a[OFF + 13]);
  v1.x = pack_bf16(a[OFF + 2], a[OFF + 3]); v1.y = pack_bf16(a[OFF + 6], a[OFF + 7]);
  v1.z = pack_bf16(a[OFF + 10], a[OFF + 11]); v1.w = pack_bf16(a[OFF + 14], a[OFF + 15]);
}
__device__ __forceinline__ void sq_acc(const uint4& v, uint32_t& a) { a = hfma2(v.x, v.x, a); a = hfma2(v.y, v.y, a); a = hfma2(v.z, v.z, a); a = hfma2(v.w, v.w, a); }
__device__ __forceinline__ float norm2_max(uint32_t a0, uint32_t a1) {
  float n0 = bf_lo(a0) + bf_hi(a0), n1 = bf_lo(a1) + bf_hi(a1);
  n0 += __shfl_xor_sync(~0u, n0, 1); n1 += __shfl_xor_sync(~0u, n1, 1);
  n0 += __shfl_xor_sync(~0u, n0, 2); n1 += __shfl_xor_sync(~0u, n1, 2);
  return __uint_as_float(__reduce_max_sync(~0u, max(__float_as_uint(n0) & 0x7fffffffu, __float_as_uint(n1) & 0x7fffffffu)));
}

struct Pend { uint4 lo[8], hi[8]; uint32_t dst; float kn; };
__device__ __forceinline__ void pin(uint4 (&v)[8]) {
#pragma unroll
  for (int i = 0; i < 8; i++) asm volatile("" : "+r"(v[i].x), "+r"(v[i].y), "+r"(v[i].z), "+r"(v[i].w) :: "memory");
}
__device__ __forceinline__ void pack_o(const float (&o)[64], float i0, float i1, uint4 (&v)[8]) {
  pack_chunk<0>(o, i0, i1, v[0], v[1]); pack_chunk<16>(o, i0, i1, v[2], v[3]);
  pack_chunk<32>(o, i0, i1, v[4], v[5]); pack_chunk<48>(o, i0, i1, v[6], v[7]);
  pin(v);
}
__device__ __forceinline__ uint32_t atom_off(int lane) { return (lane >> 2) * 64 + (((lane ^ (lane >> 3)) & 3) << 4); }
__device__ __forceinline__ void stg128(void* p, const uint4& v, bool stream) {
  if (stream) asm volatile("st.global.L2::cache_hint.v4.u32 [%0], {%1,%2,%3,%4}, %5;" :: "l"(p), "r"(v.x), "r"(v.y), "r"(v.z), "r"(v.w), "l"(pol_first()) : "memory");
  else *(uint4*)p = v;
}
template<int J0, int J1, bool STREAM = false> __device__ __forceinline__ void tile_store(const uint4 (&v)[8], uint32_t dst, int lane) {
  uint8_t* d = g_T + (dst + atom_off(lane));
#pragma unroll
  for (int j = J0; j < J1; j++) { stg128(d + j * 512, v[2 * j], STREAM); stg128(d + j * 512 + 2048, v[2 * j + 1], STREAM); }
}
template<int I0, int I1> __device__ __forceinline__ void tile_store_if(bool on, const uint4 (&v)[8], const uint8_t* dst) {
  if constexpr (I0 < I1) {
    asm volatile("{\n.reg .pred p;\nsetp.ne.b32 p, %5, 0;\n@p st.v4.u32 [%0+%6], {%1,%2,%3,%4};\n}\n"
      :: "l"(dst), "r"(v[I0].x), "r"(v[I0].y), "r"(v[I0].z), "r"(v[I0].w), "r"((int)on), "n"((I0 >> 1) * 512 + (I0 & 1) * 2048) : "memory");
    tile_store_if<I0 + 1, I1>(on, v, dst);
  }
}
__device__ __forceinline__ float tile_norm2(const uint4 (&v)[8]) {
  uint32_t n0 = 0, n1 = 0, n2 = 0, n3 = 0;
#pragma unroll
  for (int j = 0; j < 2; j++) { sq_acc(v[2 * j], n0); sq_acc(v[2 * j + 1], n1); sq_acc(v[2 * j + 4], n2); sq_acc(v[2 * j + 5], n3); }
  return norm2_max(hadd2(n0, n2), hadd2(n1, n3));
}
template<uint64_t SCHED, bool FIRST> __device__ __forceinline__ void out_piece(Cons& c, Pend& w, int ks, bool both) {
  uint8_t* d = g_T + (w.dst + atom_off(c.lane));
#pragma unroll
  for (int i = 0; i < 16; i++) {
    const int at = (SCHED >> (4 * i)) & 15;
    if (FIRST ? at == 0 : (at > 0 && ks == at && (i < 8 || both))) *(uint4*)(d + (i >> 3) * 32768 + ((i >> 1) & 3) * 512 + (i & 1) * 2048) = i < 8 ? w.lo[i & 7] : w.hi[i & 7];
  }
  if (FIRST || !both) return;
  if (ks == NK_AT) w.kn = tile_norm2(w.lo);
  if (ks == NV_AT) {
    const float vn = tile_norm2(w.hi);
    if (c.lane == 0) g_kn2[((w.dst - T_KV) >> 16) * 8 + c.wg * 4 + c.warp] = (vn <= 1.0e30f && vn >= 1.0e-30f) ? w.kn : __uint_as_float(0x7f800000u);
  }
}
template<bool FIRST> __device__ __forceinline__ void kv_issue(Cons& c, float (&acc)[128], int u) {
  const uint64_t da = odesc(c.daddr(u) + c.wg * 8192, 16, 1024, 1), db = odesc(c.daddr(u + 1), 8192, 1024, 1);
  c.turn();
  wg_fence();
#pragma unroll
  for (int kk = 0; kk < 4; kk++) wgmma_ss_n256<1>(acc, da + kk * 2, db + kk * 128, !(FIRST && kk == 0));
  wg_commit();
  c.pass();
}
template<bool NEXT> __device__ __forceinline__ void cons_kv(Cons& c, int h, int hs, int g, Pend& w, bool pend_o) {
#pragma unroll 1
  for (int tile = 0; tile < 2; tile++) {
    float acc[128];
    if (tile == 0) c.wait(0);
    if (tile == 0 && h < 16) TS(c.wg, 16);
    kv_issue<true>(c, acc, 0);
    c.release(9, tile == 1 ? 3 : 0);
    if (tile == 1 && pend_o) mbar_wait(c.base + SM_RDY + 8 * RDY_WAR, 0);
    if (tile == 1 || pend_o) out_piece<SCH_KV, true>(c, w, 0, false);
#pragma unroll 1
    for (int ks = 1; ks < 8; ks++) {
      const int u = gemm_unit(ks);
      c.wait(u);
      wg_wait<0>();
      c.release(gemm_unit(ks - 1), 3);
      kv_issue<false>(c, acc, u);
      if (tile == 1 || pend_o) { out_piece<SCH_KV, false>(c, w, ks, tile); if (ks == ((SCH_KV >> 28) & 15) && tile == 0) c.signal(SIG_CTX); }
    }
    if (NEXT || tile == 0) c.wait(0);
    wg_wait<0>(); fence_regs(acc);
    if (!NEXT) c.release(9, tile == 1 ? 3 : 0);
    pack_chunk<0>(acc, w.lo[0], w.lo[1]);  pack_chunk<16>(acc, w.lo[2], w.lo[3]); pack_chunk<32>(acc, w.lo[4], w.lo[5]); pack_chunk<48>(acc, w.lo[6], w.lo[7]);
    pack_chunk<64>(acc, w.hi[0], w.hi[1]); pack_chunk<80>(acc, w.hi[2], w.hi[3]); pack_chunk<96>(acc, w.hi[4], w.hi[5]); pack_chunk<112>(acc, w.hi[6], w.hi[7]);
    pin(w.lo); pin(w.hi);
    w.dst = T_KV + (hs * 16 + 2 * g + tile) * 65536 + (c.wg * 4 + c.warp) * 4096;
  }
}
template<bool FIRST> __device__ __forceinline__ void q_issue(Cons& c, float (&a)[64], float (&b)[64], int u) {
  const uint64_t da = odesc(c.daddr(u) + c.wg * 8192, 16, 1024, 1), db = odesc(c.daddr(u + 2), 8192, 1024, 1);
  const uint64_t da2 = odesc(c.daddr(u + 1) + (1 - c.wg) * 8192, 16, 1024, 1);
  c.turn();
  wg_fence();
#pragma unroll
  for (int kk = 0; kk < 4; kk++) wgmma_ss_n128<1>(a, da + kk * 2, db + kk * 128, !(FIRST && kk == 0));
#pragma unroll
  for (int kk = 0; kk < 4; kk++) wgmma_ss_n128<1>(b, da2 + kk * 2, db + kk * 128, !(FIRST && kk == 0));
  wg_commit();
  c.pass();
}
__device__ __forceinline__ void q_step(Cons& c, float (&d)[64], int ua, int ub, int rowhalf) {
  const uint64_t da = odesc(c.daddr(ua) + rowhalf * 8192, 16, 1024, 1), db = odesc(c.daddr(ub), 8192, 1024, 1);
#pragma unroll
  for (int kk = 0; kk < 4; kk++) wgmma_ss_n128<1>(d, da + kk * 2, db + kk * 128, 1);
}
template<bool PEND_KV> __device__ __forceinline__ void cons_q(Cons& c, int h, Pend& w, float (&b)[64]) {
  float a[64];
  if (!PEND_KV) c.wait(0);
  q_issue<true>(c, a, b, 0);
  if (PEND_KV) { c.release(9, 3); out_piece<SCH_Q, true>(c, w, 0, true); }
#pragma unroll 1
  for (int ks = 1; ks < 14; ks++) {
    const int u = gemm_unit(ks);
    c.wait(u);
    wg_wait<0>();
    c.release(gemm_unit(ks - 1), 3);
    q_issue<false>(c, a, b, u);
    if (PEND_KV && ks <= (int)(SCH_Q >> 60)) { out_piece<SCH_Q, false>(c, w, ks, true); if (ks == (int)(SCH_Q >> 60)) c.signal(SIG_KV + (h >> 4)); }
  }
  c.wait(6); c.wait(9);
  wg_wait<0>();
  c.release(3, 3);
  c.turn();
  wg_fence();
  q_step(c, a, 6, 8, c.wg); q_step(c, a, 9, 11, c.wg); wg_commit();
  q_step(c, b, 7, 8, 1 - c.wg); wg_commit();
  c.pass();
  c.wait(0);
  const uint32_t q0 = c.addr(0) + (c.wg * 4 + c.warp) * 4096 + atom_off(c.lane);
  wg_wait<1>(); fence_regs(a);
  pack_o(a, QSCALE, QSCALE, w.lo);
  sts128o<0>(q0, w.lo[0]);    sts128o<2048>(q0, w.lo[1]); sts128o<512>(q0, w.lo[2]);  sts128o<2560>(q0, w.lo[3]);
  wg_wait<0>();
  c.release(6, 4);
  sts128o<1024>(q0, w.lo[4]); sts128o<3072>(q0, w.lo[5]); sts128o<1536>(q0, w.lo[6]); sts128o<3584>(q0, w.lo[7]);
  c.wait(4);
  fence_async_smem();
}

__device__ __forceinline__ void issue_qk(float (&s)[64], uint64_t da, uint64_t db) {
#pragma unroll
  for (int kk = 0; kk < 8; kk++) wgmma_ss_n128<0>(s, da + (kk >> 1) * 32 + (kk & 1) * 2, db + (kk >> 1) * 32 + (kk & 1) * 2, kk > 0);
  wg_commit();
}
template<int A, int B> __device__ __forceinline__ void exp_rng(float (&s)[64]) {
#pragma unroll
  for (int i = 4 * A; i < 4 * B; i++) s[i] = ex2(s[i]);
}
template<int A, int B> __device__ __forceinline__ void sum_rng(const float (&s)[64], float (&l)[4]) {
#pragma unroll
  for (int i = A; i < B; i++) { l[0] += s[4 * i]; l[1] += s[4 * i + 1]; l[2] += s[4 * i + 2]; l[3] += s[4 * i + 3]; }
}
template<int A, int B> __device__ __forceinline__ void cvt_p(const float (&s)[64], uint32_t (&p)[32]) {
#pragma unroll
  for (int i = 2 * A; i < 2 * B; i++) p[i] = pack_bf16(s[2 * i], s[2 * i + 1]);
}
template<int K0> __device__ __forceinline__ void mask_half(float (&s)[64], int warp, int lane) {
  const int l0 = warp + (2 * (lane & 3) <= (lane >> 2)), l1 = warp + (2 * (lane & 3) < (lane >> 2));
#pragma unroll
  for (int k = 0; k < 4; k++) {
    float* t = s + 8 * (K0 + k);
    if (k >= l0) { t[0] = -INFINITY; t[6] = -INFINITY; }
    if (k >= l1) { t[1] = -INFINITY; t[7] = -INFINITY; }
    if (k > warp) { t[2] = -INFINITY; t[3] = -INFINITY; }
    if (k >= warp) { t[4] = -INFINITY; t[5] = -INFINITY; }
  }
}
__device__ __forceinline__ void row_inv(float& l0, float& l1) {
  l0 += __shfl_xor_sync(~0u, l0, 1); l1 += __shfl_xor_sync(~0u, l1, 1);
  l0 += __shfl_xor_sync(~0u, l0, 2); l1 += __shfl_xor_sync(~0u, l1, 2);
  l0 = __fdividef(1.f, l0); l1 = __fdividef(1.f, l1);
}
__device__ __forceinline__ void softmax_safe(float (&s)[64], bool upper_only, float& m0, float& m1, float& sc0, float& sc1) {
  float a0 = m0, a1 = m1;
#pragma unroll
  for (int i = 0; i < 8; i++) { a0 = fmaxf(a0, fmaxf(s[4 * i], s[4 * i + 1])); a1 = fmaxf(a1, fmaxf(s[4 * i + 2], s[4 * i + 3])); }
  if (upper_only) { a0 = m0; a1 = m1; }
#pragma unroll
  for (int i = 8; i < 16; i++) { a0 = fmaxf(a0, fmaxf(s[4 * i], s[4 * i + 1])); a1 = fmaxf(a1, fmaxf(s[4 * i + 2], s[4 * i + 3])); }
  a0 = fmaxf(a0, __shfl_xor_sync(~0u, a0, 1)); a1 = fmaxf(a1, __shfl_xor_sync(~0u, a1, 1));
  a0 = fmaxf(a0, __shfl_xor_sync(~0u, a0, 2)); a1 = fmaxf(a1, __shfl_xor_sync(~0u, a1, 2));
  sc0 = ex2(m0 - a0); sc1 = ex2(m1 - a1);
  m0 = a0; m1 = a1;
#pragma unroll
  for (int i = 0; i < 16; i++) { s[4 * i] -= a0; s[4 * i + 1] -= a0; s[4 * i + 2] -= a1; s[4 * i + 3] -= a1; }
}
struct Att {
  float s[64], o[64], l[4], i0, i1; uint32_t p[32];
  uint32_t qaddr; const uint8_t* dst;
};
__device__ __forceinline__ uint32_t ctx_off(const Cons& c, int h, int qb, int rowhalf) { return T_CTX + (qb * 32 + h) * 32768 + (rowhalf * 4 + c.warp) * 4096; }
__device__ __forceinline__ void row_sq(const uint4 (&v)[8], float& n0, float& n1) {
  uint32_t a0 = 0, a1 = 0, a2 = 0, a3 = 0;
#pragma unroll
  for (int j = 0; j < 2; j++) { sq_acc(v[2 * j], a0); sq_acc(v[2 * j + 1], a1); sq_acc(v[2 * j + 4], a2); sq_acc(v[2 * j + 5], a3); }
  a0 = hadd2(a0, a2); a1 = hadd2(a1, a3);
  n0 = bf_lo(a0) + bf_hi(a0); n1 = bf_lo(a1) + bf_hi(a1);
}
__device__ __forceinline__ int att_fast(Cons& c, int h, float n0, float n1) {
  const float kn = __uint_as_float(lds32(c.base + SM_KMAX + 4 * (h >> 4)));
  n0 += __shfl_xor_sync(~0u, n0, 1); n1 += __shfl_xor_sync(~0u, n1, 1);
  n0 += __shfl_xor_sync(~0u, n0, 2); n1 += __shfl_xor_sync(~0u, n1, 2);
  return __shfl_sync(~0u, bar_and(3 + c.wg, 128, n0 * kn <= BOUND2 && n1 * kn <= BOUND2), 0);
}
__device__ __forceinline__ int att_first(Cons& c, Att& a, int h, const Pend& w) {
  a.qaddr = c.daddr(0) + c.wg * 16384;
  c.turn();
  wg_fence();
  issue_qk(a.s, odesc(a.qaddr, 16, 2048, 2), odesc(c.daddr(K0X ? 12 : 4), 16, 2048, 2));
  int fast = 0;
  { SHADOW { float n0, n1; row_sq(w.lo, n0, n1); fast = att_fast(c, h, n0, n1); } wg_fence(); }
  q_step(c, a.o, 10, 11, 1 - c.wg); wg_commit();
  c.pass();
#pragma unroll
  for (int i = 0; i < 8; i++) { a.p[4 * i] = w.lo[i].x; a.p[4 * i + 1] = w.lo[i].y; a.p[4 * i + 2] = w.lo[i].z; a.p[4 * i + 3] = w.lo[i].w; }
  a.l[0] = a.l[1] = a.l[2] = a.l[3] = 0.f; a.i0 = a.i1 = QSCALE;
  a.dst = (const uint8_t*)__cvta_shared_to_generic(c.addr(2) + (c.wg * 4 + c.warp) * 4096 + atom_off(c.lane));
  wg_wait<1>(); fence_regs(a.s);
  if (!K0X) c.release(4, 2);
  c.signal(SIG_ATT + (h >> 4));
  return fast;
}
__device__ __forceinline__ void att_last(Cons& c, Att& a, Pend& w, int h, int g, bool drain) {
  const int uv = att_slot(1);
  if (drain) pack_o(a.o, a.i0, a.i1, w.hi);
  c.wait(uv);
  c.turn();
  fence_regs(a.o); fence_regs(a.p);
  wgmma_pv_sel<EPASS>(a.o, a.p, odesc(c.daddr(uv), 512, 2048, 2), !(drain && c.wg == 1), !drain, 2 - c.wg);
  a.i0 = a.l[0] + a.l[1]; a.i1 = a.l[2] + a.l[3];
  SHADOW row_inv(a.i0, a.i1);
  sched_fence(a.i0 + a.i1, c.base + SM_DUMMY);
  tile_store_if<0, 4>(drain, w.hi, a.dst);
  wg_wait<0>(); fence_regs(a.o); fence_regs(a.p);
  c.release(uv, 2);
  tile_store_if<4, 8>(drain, w.hi, a.dst);
  pack_o(a.o, a.i0, a.i1, w.lo);
  w.dst = ctx_off(c, h, g, 1 - c.wg);
}
__device__ __forceinline__ void cons_att(Cons& c, Att& a, int h, int g, Pend& w) {
  int fast = att_first(c, a, h, w), fast2 = 0;
  float m0 = -INFINITY, m1 = -INFINITY, sc0 = 0.f, sc1 = 0.f;
  int uk = 10, ur = 10;
  bool fresh = false;
#pragma unroll 1
  for (int d = g - 15;;) {
    const bool lo = d == c.wg;
    if ((unsigned)d < 2 || !fast) {
      if ((unsigned)d < 2) {
        if (FAST_AT == 0 && lo) { float n0, n1; row_sq(w.hi, n0, n1); fast2 = att_fast(c, h, n0, n1); wg_wait<0>(); c.release(ur, 2); }
        mask_half<4>(a.s, c.warp, c.lane);
        if (d == 1) fast = fast2;
      }
      if (!fast) {
        if (d == 1) m0 = m1 = -INFINITY;
        softmax_safe(a.s, lo, m0, m1, sc0, sc1);
        a.l[0] *= sc0; a.l[1] *= sc0; a.l[2] *= sc1; a.l[3] *= sc1;
      }
    }
    exp_rng<8, 16>(a.s); sum_rng<8, 16>(a.s, a.l);
    exp_rng<ATT_SPLIT, 8>(a.s);
    sched_fence(((a.l[0] + a.l[1]) + (a.l[2] + a.l[3])) + (ATT_SPLIT < 8 ? a.s[4 * ATT_SPLIT + 3] : 0.f), c.base + SM_DUMMY);
    wg_wait<0>(); fence_regs(a.o); fence_regs(a.p);
    c.release(ur, FAST_AT == 0 && lo ? 0 : 2);
    tile_store_if<DS_A, DS_B>(fresh, w.hi, a.dst);
    uk ^= 12; ur = 14 - uk;
    if (d == 0) a.qaddr += 32768;
    const uint64_t dq = odesc(a.qaddr, 16, 2048, 2), dk = odesc(c.daddr(uk) - (d + 1 == c.wg ? 16384 : 0), 16, 2048, 2), dv = odesc(c.daddr(ur), 512, 2048, 2);
    if (!lo) { exp_rng<0, ATT_SPLIT>(a.s); sum_rng<0, 8>(a.s, a.l); cvt_p<0, 16>(a.s, a.p); }
    else if (gridDim.y == 1) cvt_p<8, 16>(a.s, a.p);
    tile_store_if<DS_B, 8>(fresh, w.hi, a.dst);
    if (!fast || d == g + 1 || (unsigned)(d + (FAST_AT ? 2 : 0)) < (FAST_AT ? 4 : 2)) {
      if (FAST_AT == 1 && d == -2) row_sq(w.hi, a.i0, a.i1);
      if (FAST_AT == 2 && d == -1) row_sq(w.hi, a.i0, a.i1);
      if (FAST_AT && d == -1) fast2 = att_fast(c, h, a.i0, a.i1);
      if (d == 0) {
        a.i0 = a.l[0] + a.l[1]; a.i1 = a.l[2] + a.l[3];
        a.l[0] = a.l[1] = a.l[2] = a.l[3] = 0.f;
        a.dst = g_T + (ctx_off(c, h, 15 - g, c.wg) + atom_off(c.lane));
        fence_async_smem();
      }
      if (lo) row_inv(a.i0, a.i1);
      if (!fast && d != 1 && d != g - 15) {
#pragma unroll
        for (int i = 0; i < 16; i++) { a.o[4 * i] *= sc0; a.o[4 * i + 1] *= sc0; a.o[4 * i + 2] *= sc1; a.o[4 * i + 3] *= sc1; }
      }
      if (d == g + 1) break;
    }
    d++;
    fresh = d == 2 || d == g - 14;
    if (c.wg == 0) c.wait(uk); else c.skip(uk);
    c.turn();
    fence_regs(a.o); fence_regs(a.p);
    wg_fence();
    issue_qk(a.s, dq, dk);
    if (fresh) pack_o(a.o, a.i0, a.i1, w.hi);
    wgmma_pv_sel<EPASS>(a.o, a.p, dv, !lo, !fresh, 2 - c.wg);
    tile_store_if<0, DS_A>(fresh, w.hi, a.dst);
    wg_wait<1>(); fence_regs(a.s);
    c.release(uk, 2);
    c.release(d == 0 ? 0 : 2, (d == 0 || d == g + 1) ? 2 : 0);
  }
  att_last(c, a, w, h, g, g == 0);
}

constexpr int CV_H = 1024, CV_U = 5120, CV_D = CV_U + 4128, CV_ROW = 1056;
template<int OFF> __device__ __forceinline__ uint32_t lds32o(uint32_t a) { uint32_t v; asm volatile("ld.shared.u32 %0, [%1+%2];" : "=r"(v) : "r"(a), "n"(OFF) : "memory"); return v; }
template<int G, int G1 = 16> __device__ __forceinline__ void conv_lda(uint32_t (&a)[64], uint32_t p) {
  a[4 * G + 0] = lds32o<-256 * G>(p);
  a[4 * G + 1] = lds32o<-256 * G - 128>(p);
  a[4 * G + 2] = lds32o<-256 * G + 16>(p);
  a[4 * G + 3] = lds32o<-256 * G - 112>(p);
  if constexpr (G + 1 < G1) conv_lda<G + 1, G1>(a, p);
}
struct CvAcc { float lo[16], hi[16]; };
__device__ __forceinline__ void fence_regs(CvAcc& d) { fence_regs(d.lo); fence_regs(d.hi); }
template<int R, int H> __device__ __forceinline__ void conv_mma_h(float (&d)[16], const uint32_t (&a)[64], uint64_t db) {
#pragma unroll
  for (int G = 0; G < 4 * R + 2 * H + 2; G++) wgmma_rs_n32<0>(d, a[4 * G], a[4 * G + 1], a[4 * G + 2], a[4 * G + 3], db + 64 * R + 32 * H - 16 * G, G > 0);
}
template<int T, int G0, int G1> __device__ __forceinline__ void conv_part(float (&d)[16], const uint32_t (&a)[64], uint64_t db) {
#pragma unroll
  for (int G = G0; G < G1; G++) wgmma_rs_n32<0>(d, a[4 * G], a[4 * G + 1], a[4 * G + 2], a[4 * G + 3], db + 32 * T - 16 * G, G > 0);
}
template<int R> __device__ __forceinline__ void conv_mma(CvAcc& d, const uint32_t (&a)[64], uint64_t db) { conv_mma_h<R, 0>(d.lo, a, db); conv_mma_h<R, 1>(d.hi, a, db); }
template<int C0> __device__ __forceinline__ void conv_st_h(const float (&d)[16], uint32_t wq, float& c0, float& c1) {
#pragma unroll
  for (int n = 0; n < 4; n++) { sts64f(wq + (C0 + n * 8) * 4, d[4 * n] + c0, d[4 * n + 1] + c1); c0 = d[4 * n + 2]; c1 = d[4 * n + 3]; }
}
template<int R> __device__ __forceinline__ void conv_st(const CvAcc& d, uint32_t wq, float& c0, float& c1) { conv_st_h<64 * R>(d.lo, wq, c0, c1); conv_st_h<64 * R + 32>(d.hi, wq, c0, c1); }
struct ConvTail { float t[64]; uint4 ua, uc; uint32_t D2; };
__device__ __forceinline__ void conv_emit(ConvTail& e, int ch, int tid) {
  fence_regs(e.t);
  float y[16];
#pragma unroll
  for (int i = 0; i < 16; i++) y[i] = (e.t[i] + e.t[16 + i]) + (e.t[32 + i] + e.t[48 + i]);
  uint4 z0, z1;
  z0.x = hadd2(pack_bf16(y[0], y[2]), hmul2(__byte_perm(e.ua.w, 0, 0x1032), e.D2));
  z0.y = hadd2(pack_bf16(y[4], y[6]), hmul2(__byte_perm(e.ua.z, 0, 0x1032), e.D2));
  z0.z = hadd2(pack_bf16(y[8], y[10]), hmul2(__byte_perm(e.ua.y, 0, 0x1032), e.D2));
  z0.w = hadd2(pack_bf16(y[12], y[14]), hmul2(__byte_perm(e.ua.x, 0, 0x1032), e.D2));
  z1.x = hadd2(pack_bf16(y[1], y[3]), hmul2(__byte_perm(e.uc.w, 0, 0x1032), e.D2));
  z1.y = hadd2(pack_bf16(y[5], y[7]), hmul2(__byte_perm(e.uc.z, 0, 0x1032), e.D2));
  z1.z = hadd2(pack_bf16(y[9], y[11]), hmul2(__byte_perm(e.uc.y, 0, 0x1032), e.D2));
  z1.w = hadd2(pack_bf16(y[13], y[15]), hmul2(__byte_perm(e.uc.x, 0, 0x1032), e.D2));
  uint4* zp = (uint4*)(g_z + (uint32_t)(ch * 2048 + tid * 16));
  zp[0] = z0; zp[1] = z1;
}
template<int MASK> __device__ __forceinline__ void cons_conv(Cons& c, int cta, int nch) {
  const int r = c.lane >> 2, q = c.lane & 3, tid = c.warp * 32 + c.lane;
  const uint32_t part = c.addr(4) - 2048 + (1 - c.wg) * (32 * CV_ROW) + 32;
  const uint32_t aoff = CV_U + ((r & 1) ? 0 : UPITCH) + 4 * (((2039 - r) >> 1) + q - 8 * c.warp);
  const uint32_t wq = part + (c.warp * 8 + r) * CV_ROW + q * 8, rq = part + tid * 8;
  uint32_t a[64];
  ConvTail e = {};
  c.wait(c.wg); c.skip(c.wg ^ 1);
  conv_lda<0>(a, c.addr(c.wg) + aoff);
  c.wait(4);
  sts64f(part + (tid >> 2) * CV_ROW - 32 + q * 8, 0.f, 0.f);
#pragma unroll 1
  for (int i = 0; i < nch / 2; i++) {
    const int u = 2 * (i & 1) + c.wg;
    CvAcc d0, d1, d2, d3;
    float c0 = 0.f, c1 = 0.f;
    const uint64_t db = odesc(c.daddr(u) + CV_H - 16, 16, 128, 0);
    c.turn();
    fence_regs(a);
    wg_fence();
    conv_mma<0>(d0, a, db); conv_mma<1>(d1, a, db); wg_commit();
    if (i > 0) {
      conv_emit(e, conv_channel<MASK>(cta, 2 * i - 2 + c.wg), tid);
      if ((i & 15) == 0) c.signal(SIG_Z + (i >> 4) - 1);
    }
    wg_fence();
    conv_mma_h<2, 0>(d2.lo, a, db); wg_commit();
    wg_wait<1>(); fence_regs(d0); fence_regs(d1);
    conv_st_h<0>(d0.lo, wq, c0, c1);
    wg_fence();
    conv_mma_h<2, 1>(d2.hi, a, db); wg_commit();
    conv_st_h<32>(d0.hi, wq, c0, c1);
    conv_mma_h<3, 0>(d3.lo, a, db);
    conv_st_h<64>(d1.lo, wq, c0, c1);
    conv_mma_h<3, 1>(d3.hi, a, db); wg_commit();
    c.pass();
    const int un = i + 1 < nch / 2 ? u ^ 2 : u;
    if (un != u) { c.wait(un); c.skip(un ^ 1); }
    wg_wait<1>(); fence_regs(d2);
    conv_st_h<96>(d1.hi, wq, c0, c1);
    conv_st<2>(d2, wq, c0, c1);
    {
      const int sw = (c.lane >> 2) & 1;
      const uint4 v0 = lds128(c.addr(u) + CV_U + 4064 - 32 * tid + 16 * sw), v1 = lds128(c.addr(u) + CV_U + 4080 - 32 * tid - 16 * sw);
      e.ua = sw ? v0 : v1; e.uc = sw ? v1 : v0;
    }
    e.D2 = lds32(c.addr(u) + CV_D);
    wg_wait<0>(); fence_regs(d3); fence_regs(a);
    conv_st<3>(d3, wq, c0, c1);
    conv_lda<0, 4>(a, c.addr(un) + aoff);
    bar_sync(3 + c.wg, 128);
    sched_fence(__uint_as_float(e.ua.x ^ e.uc.x ^ e.D2), c.base + SM_DUMMY);
    c.release2(u);
    conv_lda<4, 16>(a, c.addr(un) + aoff);
#pragma unroll
    for (int k = 0; k < 32; k++) { const float2 v = lds64f(rq + k * CV_ROW - (k >> 3) * 8); e.t[2 * k] = v.x; e.t[2 * k + 1] = v.y; }
  }
  conv_emit(e, conv_channel<MASK>(cta, nch - 2 + c.wg), tid);
  c.signal(SIG_Z + ((nch / 2 - 1) >> 4));
  c.release(4, 4);
}

constexpr int OC_PART = 13824, OC_ROW = 544;
__device__ __forceinline__ int out_next(int u) { return (0x84ac680u >> (2 * u)) & 15; }
struct Out { float acc[64]; int pu; uint64_t da, db; };
template<bool FIRST, bool REL, int W = 1, bool PRE = true, bool POST = false> __device__ __forceinline__ void out_step(Cons& c, Out& o, bool extra = false) {
  const int pu = o.pu, u = extra ? 2 : out_next(pu);
  o.pu = u;
  if (PRE) c.wait(u);
  const uint64_t da = o.da + (uint32_t)(u * 1024), db = o.db + (uint32_t)(u * 1024);
  wg_fence();
#pragma unroll
  for (int kk = 0; kk < 4; kk++) wgmma_ss_n128<1>(o.acc, da + (kk >> 1) * 32 + (kk & 1) * 2, db + kk * 128, !(FIRST && kk == 0));
  wg_commit();
  if (REL) { wg_wait<W>(); c.release(pu, 2); }
  if (POST) c.wait(out_next(u));
}
template<int I0, int I1> __device__ __forceinline__ void oc_red(float (&y)[8], uint32_t rq) {
#pragma unroll
  for (int i = I0; i < I1; i++) { const float v = __uint_as_float(lds32(rq + i * OC_ROW - (i >> 3) * 8)); y[i & 7] = i < 8 ? v : y[i & 7] + v; }
}
__device__ __forceinline__ void oc_emit(const float (&y)[8], const uint4& u, uint32_t D2, __nv_bfloat16* dst) {
  uint4 z;
  z.x = hadd2(pack_bf16(y[0], y[1]), hmul2(__byte_perm(u.w, 0, 0x1032), D2));
  z.y = hadd2(pack_bf16(y[2], y[3]), hmul2(__byte_perm(u.z, 0, 0x1032), D2));
  z.z = hadd2(pack_bf16(y[4], y[5]), hmul2(__byte_perm(u.y, 0, 0x1032), D2));
  z.w = hadd2(pack_bf16(y[6], y[7]), hmul2(__byte_perm(u.x, 0, 0x1032), D2));
  *(uint4*)dst = z;
}
template<int MASK> __device__ __forceinline__ void cons_out(Cons& c, const Maps& M, const Params& P, int cta, Pend& w) {
  const int mb = out_mb(cta), nb = out_nb(cta);
  Out o;
  o.da = odesc(c.daddr(0) + c.wg * 8192, 16, 1024, 2); o.db = odesc(c.daddr(1), 8192, 1024, 1);
  o.pu = 5 + gridDim.y;
  out_step<true, false>(c, o);
  int ks = 1;
#pragma unroll 1
  for (;; ks++) {
    if (MASK & PH_ATT) {
      if (ks == (c.wg ? ST_1 : ST_0)) tile_store<0, 1>(w.lo, w.dst, c.lane);
      if (ks == (c.wg ? ST_1 + ST_D : ST_0 + ST_0D / 2)) tile_store<1, 2>(w.lo, w.dst, c.lane);
      if (ks == (c.wg ? ST_1 + 2 * ST_D : ST_0 + ST_0D)) tile_store<2, 3>(w.lo, w.dst, c.lane);
      if (ks == (c.wg ? ST_1 + 3 * ST_D : ST_0 + 3 * ST_0D / 2)) { tile_store<3, 4>(w.lo, w.dst, c.lane); c.signal(SIG_CTX + 1); }
    }
    if (ks == (c.wg ? OC_S1 : OC_S0)) break;
    out_step<false, true>(c, o, XSLOT && ks == 1);
  }
  if (MASK & PH_CONV) {
    const int r = c.lane >> 2, q = c.lane & 3, tid = c.warp * 32 + c.lane, u = 2 * c.wg;
    const uint32_t ub = c.addr(u), part = ub + OC_PART + 32;
    const uint32_t ap = ub + CV_U + ((r & 1) ? 0 : UPITCH) + 4 * (((2039 - r) >> 1) + q - 8 * c.warp);
    const uint32_t wq = part + (c.warp * 8 + r) * OC_ROW + q * 8, rq = part + tid * 4;
    const int nr = (CV_REG<MASK> + 1 - c.wg) >> 1;
#define STEP(N) out_step<false, true, 1, !OC_POST, OC_POST>(c, o);
#pragma unroll 1
    for (int i = 0; i < nr; i++) {
      uint32_t a[64];
      CvAcc d0, d1;
      float y[8], c0 = 0.f, c1 = 0.f;
      const uint64_t db = odesc(c.daddr(u + (i >> 8)) + CV_H - 16, 16, 128, 0);
#define STEP2(N) out_step<false, true, 2, !OC_POST, OC_POST>(c, o);
#define PART(...) { const uint64_t db = db0 + (c.mask >> 16); wg_fence(); __VA_ARGS__; wg_commit(); }
      const uint64_t db0 = db;
      c.wait(u);
      if (OC_POST) c.wait(out_next(o.pu));
      conv_lda<0, 4>(a, ap);
      STEP(0)
      conv_lda<4, 7>(a, ap);
      PART(conv_part<0, 0, 2>(d0.lo, a, db); conv_part<1, 0, 4>(d0.hi, a, db))
      STEP2(1)
      conv_lda<7, 10>(a, ap);
      PART(conv_part<2, 0, 6>(d1.lo, a, db))
      STEP2(2)
      fence_regs(d0);
      bar_sync(3 + c.wg, 128);
      sts64f(wq - 32, 0.f, 0.f);
      conv_st<0>(d0, wq, c0, c1);
      asm volatile("add.f32 %0, %0, 0f80000000;" : "+f"(c0)); asm volatile("add.f32 %0, %0, 0f80000000;" : "+f"(c1));
      PART(conv_part<3, 0, 8>(d1.hi, a, db))
      STEP2(3)
      wg_wait<1>(); fence_regs(d1);
      float e0 = d1.hi[12] + d1.hi[10], e1 = d1.hi[13] + d1.hi[11];
      conv_st<1>(d1, wq, c0, c1);
      asm volatile("add.f32 %0, %0, 0f80000000;" : "+f"(c0)); asm volatile("add.f32 %0, %0, 0f80000000;" : "+f"(c1));
      PART(conv_part<4, 0, 10>(d0.lo, a, db))
      STEP2(4)
      conv_lda<10, 12>(a, ap);
      bar_sync(3 + c.wg, 128);
      oc_red<0, 6>(y, rq);
      PART(conv_part<5, 0, 9>(d0.hi, a, db))
      STEP2(5)
      conv_lda<12, 14>(a, ap);
      oc_red<6, 12>(y, rq);
      PART(conv_part<5, 9, 12>(d0.hi, a, db); conv_part<6, 0, 6>(d1.lo, a, db))
      STEP2(6)
      oc_red<12, 26>(y, rq);
      PART(conv_part<6, 6, 14>(d1.lo, a, db))
      STEP2(7)
      oc_red<26, 32>(y, rq);
      conv_lda<14, 16>(a, ap);
      PART(conv_part<7, 0, 8>(d1.hi, a, db))
      STEP2(8)
      fence_regs(y); fence_regs(d0);
      bar_sync(3 + c.wg, 128);
      sts64f(wq - 32, e0, e1);
      conv_st<0>(d0, wq, c0, c1);
      PART(conv_part<7, 8, 16>(d1.hi, a, db))
      STEP2(9)
      wg_wait<1>(); fence_regs(d1); fence_regs(a);
      const uint4 u0 = lds128(ub + CV_U + 4080 - 16 * tid), u1 = lds128(ub + CV_U + 2032 - 16 * tid);
      const uint32_t D2 = lds32(ub + CV_D);
      conv_st_h<64>(d1.lo, wq, c0, c1);
      sched_fence(__uint_as_float(u0.x ^ u1.x ^ D2), c.base + SM_DUMMY);
      __syncwarp();
      c.release2(u);
      STEP(10)
      conv_st_h<96>(d1.hi, wq, c0, c1);
      __nv_bfloat16* zp = g_z + (uint32_t)(conv_channel<MASK>(cta, 2 * i + c.wg) * 2048 + (threadIdx.x & 127) * 8);
      oc_emit(y, u0, D2, zp);
      bar_sync(3 + c.wg, 128);
      oc_red<0, 6>(y, rq);
      STEP(11)
      oc_red<6, 19>(y, rq);
      STEP(12)
      oc_red<19, 32>(y, rq);
      oc_emit(y, u1, D2, zp + 1024);
      if (i == nr - 1) { c.signal(SIG_Z); c.release2(u + 1); TS2(c.wg, 8); }
      out_step<false, true, 1, !OC_POST>(c, o);
#pragma unroll 1
      for (int k = 14; k < (c.wg ? OC_L1 : OC_L0); k++) out_step<false, true>(c, o);
#undef STEP2
#undef PART
    }
#undef STEP
    if (((CV_REG<MASK> + c.wg) >> 1) & 1) c.skip(u ^ 2);
    ks += nr * (c.wg ? OC_L1 : OC_L0);
  }
  TS(c.wg, 9);
#pragma unroll 1
  for (; ks < 57; ks++) out_step<false, true>(c, o);
  uint32_t ga[32];
  c.wait(2);
  const float g0 = __uint_as_float(lds32(c.base + SM_GATE + 4 * (c.wg * 64 + c.warp * 16 + (c.lane >> 2)))), g1 = __uint_as_float(lds32(c.base + SM_GATE + 32 + 4 * (c.wg * 64 + c.warp * 16 + (c.lane >> 2))));
  const uint32_t gg0 = pack_bf16(g0, g0), gg1 = pack_bf16(g1, g1);
  const uint32_t og0 = pack_bf16(1.f - g0, 1.f - g0), og1 = pack_bf16(1.f - g1, 1.f - g1);
  const int xr = c.wg * 64 + c.warp * 16 + (c.lane & 15);
  const uint32_t xa = c.addr(2) + xr * 128, xs = xr & 7, xh = c.lane >> 4;
  const int zr = (c.lane & 7) + ((c.lane >> 4) << 3);
  const uint32_t za = c.addr(0) + c.wg * 16384 + zr * 128 + (((c.warp * 2 + ((c.lane >> 3) & 1)) ^ (zr & 7)) << 4);
#pragma unroll
  for (int i = 0; i < 8; i++) {
    if (i == 0) out_step<false, true>(c, o);
    if (i == 3) out_step<false, true>(c, o);
    if (i == 6) out_step<false, true>(c, o);
    ldsm4(xa + (i >> 2) * 16384 + ((((i & 3) * 2 + xh) ^ xs) << 4), ga[4 * i], ga[4 * i + 1], ga[4 * i + 2], ga[4 * i + 3]);
  }
#pragma unroll 1
  for (ks = 60; ks < 64; ks++) out_step<false, false>(c, o);
  TS2(c.wg, 17);
  c.wait(0);
  TS2(c.wg, 18);
  SHADOW {
#pragma unroll
    for (int i = 0; i < 8; i++) {
      uint32_t z0, z1, z2, z3;
      ldsm4t(za + i * 2048, z0, z1, z2, z3);
      ga[4 * i + 0] = hmul2(gg0, hmul2(ga[4 * i + 0], z0)); ga[4 * i + 1] = hmul2(gg1, hmul2(ga[4 * i + 1], z1));
      ga[4 * i + 2] = hmul2(gg0, hmul2(ga[4 * i + 2], z2)); ga[4 * i + 3] = hmul2(gg1, hmul2(ga[4 * i + 3], z3));
    }
  }
  c.signal(SIG_DONE);
  fence_regs(ga);
  TS2(c.wg, 19);
  wg_wait<0>(); fence_regs(o.acc);
  TS2(c.wg, 20);
#pragma unroll
  for (int i = 0; i < 8; i++) {
    const uint32_t r0 = hadd2(ga[4 * i + 0], hmul2(og0, pack_bf16(o.acc[8 * i + 0], o.acc[8 * i + 1])));
    const uint32_t r1 = hadd2(ga[4 * i + 1], hmul2(og1, pack_bf16(o.acc[8 * i + 2], o.acc[8 * i + 3])));
    const uint32_t r2 = hadd2(ga[4 * i + 2], hmul2(og0, pack_bf16(o.acc[8 * i + 4], o.acc[8 * i + 5])));
    const uint32_t r3 = hadd2(ga[4 * i + 3], hmul2(og1, pack_bf16(o.acc[8 * i + 6], o.acc[8 * i + 7])));
    stsm4(xa + (i >> 2) * 16384 + ((((i & 3) * 2 + xh) ^ xs) << 4), r0, r1, r2, r3);
    if ((i & 3) == 3) {
      __syncwarp();
#pragma unroll
      for (int k = 0; k < 4; k++) {
        const int rr = c.wg * 64 + c.warp * 16 + k * 4 + (c.lane >> 3);
        const uint4 v = lds128(c.addr(2 + (i >> 2)) + rr * 128 + (((c.lane ^ rr) & 7) << 4));
        *(uint4*)(P.out + (uint32_t)((mb * 128 + rr) * 1024 + nb * 128 + (i >> 2) * 64 + (c.lane & 7) * 8)) = v;
      }
    }
  }
}

__device__ __forceinline__ void load_conv(Prod& p, const Maps& M, int u, int ch) {
  if (elect()) {
    mbar_expect(p.full(u), 5120 + UCH);
    tma3d(p.addr(u), &M.h, 0, -8, ch, p.full(u), POL(4));
    bulk_g2s(p.addr(u) + CV_U, g_u + (size_t)ch * UCH, UCH, p.full(u), POL(4));
  }
}
template<int MASK> __device__ __forceinline__ void prod_conv(Prod& p, const Maps& M, int cta, int nch) {
  int ready = -1;
#pragma unroll 1
  for (int i = 0; i < nch; i++) {
    const int ch = conv_channel<MASK>(cta, i);
    const int u = i & 3;
    if ((ch >> 6) != ready) { ready = ch >> 6; if (cta < NREG) mbar_wait(p.base + SM_RDY + 8 * RDY_U, 0); else cnt_wait(g_cnt + (C_U + ready) * CSTRIDE, 128); }
    p.acquire(u, 1);
    load_conv(p, M, u, ch);
    if (i == 3) { p.acquire(4, 4); if (elect()) mbar_arrive(p.full(4)); }
  }
}
#define HOIST(v) asm volatile("" : "+r"(v))
template<int MASK> __device__ __forceinline__ void producer(const Maps& M, const Params& P, uint32_t base, int cta, int lane) {
  Prod p{base, ((MASK & PH_KV) && cta < NREG) ? 0xffffcfffu ^ ((1u << (3 * NFIRST)) - 1) : 0xffffffffu, lane,
         (cta * 3 + 2) * 2048};
  if (cta >= NREG) { if (MASK & PH_CONV) prod_conv<MASK>(p, M, cta, CV_EXTRA<MASK>); return; }
  const int g = cta & 7, j = cta >> 3, rank = cta & 1;
#pragma unroll 1
  for (int half = 0; half < 2; half++) {
    const int h = j + 16 * half;
    if (MASK & PH_KV) {
      const CUtensorMap* mw = rank ? &M.wv : &M.wk;
#pragma unroll 1
      for (int it = half ? 0 : NFIRST; it < 16; it++) {
        const int u = gemm_unit(it);
        uint32_t bar = p.full(u), d0 = p.addr(u), d1 = p.addr(u + 1 + rank); int k0 = (it & 7) * 64, r0 = (2 * g + (it >> 3)) * 128;
        HOIST(bar); HOIST(d0); HOIST(d1); HOIST(k0); HOIST(r0);
        p.acquire(u, 3);
        if (elect()) {
          mbar_expect(bar, 3 * UNIT);
          tma3d_mc(d1, mw, 0, k0, 2 * h, bar, POL(0) && it >= 8);
          tma2d(d0, &M.c, k0, r0, bar, half ? POL(8) : POL(10));
        }
      }
    }
    if (MASK & PH_ATT) {
#pragma unroll 1
      for (int ks = 0; ks < 16; ks++) {
        const int u = gemm_unit(ks);
        uint32_t bar = p.full(u), d0 = p.addr(u), d1 = p.addr(u + 1), d2 = p.addr(u + 2) + rank * 8192; int k0 = ks * 64;
        HOIST(bar); HOIST(d0); HOIST(d1); HOIST(d2); HOIST(k0);
        p.acquire(u, 3);
        if (elect()) {
          mbar_expect(bar, 3 * UNIT);
          tma2d_mc(d2, &M.wq, h * 128 + rank * 64, k0, bar, POL(1));
          tma2d(d0, &M.x, k0, (15 - g) * 128, bar, half ? POL(9) : POL(10));
          tma2d(d1, &M.x, k0, g * 128, bar, half ? POL(9) : POL(10));
        }
      }
      TS(2, 8 * half + 0);
      mbar_wait(base + SM_RDY + 8 * (RDY_KV + half), 0);
      TS(2, 8 * half + 1);
      const uint8_t* KVh = g_T + T_KV + (size_t)kv_slot<MASK>(h) * 16 * 65536;
      if (K0X) {
        if (MASK & PH_PRE) mbar_wait(base + SM_RDY + 8 * RDY_AUX, 0);
        if (elect()) { mbar_expect(p.full(4), 32768); bulk_g2s(p.addr(12), KVh, 32768, p.full(4), POL(6)); }
      }
      p.acquire(0, 4);
      if (elect()) mbar_arrive(p.full(0));
#pragma unroll 1
      for (int n = K0X; n < 34; n++) {
        const int i = n == 3 ? 4 : n == 4 ? 3 : n;
        const int isv = (i > 0 && !(i & 1)) || i == 33;
        const int st = i == 33 ? 16 : (isv ? (i >> 1) - 1 : (i + 1) >> 1);
        const int u = att_slot(i & 3);
        const bool own = st == 15 - (g & 6);
        uint32_t bar = p.full((isv && i < 33) ? 14 - u : u), d0 = p.addr(own ? u : u + rank), off = (st <= 15 - g ? st : 16 - st) * 65536 + isv * 32768 + (own ? 0 : rank * UNIT);
        HOIST(bar); HOIST(d0); HOIST(off);
        p.acquire(u, 2);
        if (elect()) {
          if (!isv || i == 33) mbar_expect(bar, (i == 0 || i == 33) ? 32768 : 65536);
          const bool ef = POL(6) || (POL(14) && st >= 8) || (POL(15) && half);
          if (own) bulk_g2s(d0, KVh + off, 32768, bar, ef); else bulk_g2s_mc(d0, KVh + off, UNIT, bar, ef);
          if (MASK == PH_ALL && half && i == PF_AT) {
            if (PF & 1) pf3d(&M.wo, 0, j * 64, 2 * g);
            if (PF & 2) pf_bulk(g_T + T_CTX + (j * 32 + g) * 32768, 32768);
          }
        }
      }
    }
  }
  if ((MASK & PH_CONV) && !(MASK & PH_OUT)) prod_conv<MASK>(p, M, cta, CV_REG<MASK>);
  if (MASK & PH_OUT) {
    const int y0 = out_mb(cta) * 512 + rank * 8, z0 = 2 * out_nb(cta);
    int u = 6;
#pragma unroll 1
    for (int hf = 0; hf < 2; hf++) {
      TS(2, 16 + 2 * hf);
      mbar_wait(base + SM_RDY + 8 * (RDY_CTX + hf), 0);
      TS(2, 17 + 2 * hf);
#pragma unroll 1
      for (int n = hf * 32; n < hf * 32 + 32; n++) {
        const int ks = !XSLOT ? n : n == 1 ? 2 : n == 2 ? 1 : n;
        u = XSLOT && n == 2 ? 2 : XSLOT && n == 3 ? 10 : out_next(u);
        uint32_t bar = p.full(u), d0 = p.addr(u) + rank * 8192, d1 = p.addr(u + 1); int x = (ks & 1) * 256, y = y0 + (ks >> 1) * 16, k0 = ks * 64;
        HOIST(bar); HOIST(d0); HOIST(d1); HOIST(x); HOIST(y); HOIST(k0);
        p.acquire(u, 2);
        if (elect()) {
          mbar_expect(bar, 2 * UNIT);
          tma2d_mc(d0, &M.ctx, x, y, bar, POL(5));
          tma3d(d1, &M.wo, 0, k0, z0, bar, POL(2));
          if ((PF & 4) && (ks & 15) == PF_KS && ks < 48) pf3d(&M.wo, 0, ((ks & 48) + 16 + j) * 64, z0);
          if ((PF & 8) && ks == PF_KS) pf_bulk(g_T + T_CTX + (j * 32 + 8 + g) * 32768, 32768);
          if (XSLOT && ks == 1) mbar_arrive(base + SM_RDY + 8 * RDY_X);
          if (ks == Z_AT) mbar_arrive(base + SM_RDY + 8 * RDY_Z);
        }
      }
    }
  }
}
template<int MASK> __device__ __forceinline__ void producer2(const Maps& M, const Params& P, uint32_t base, int cta, int w, int lane) {
  Prod p{base, 0xffffffffu, lane, 0};
  const int mb = out_mb(cta), nb = out_nb(cta), u = 2 * w;
  if (XSLOT && w) { mbar_wait_slow(base + SM_RDY + 8 * RDY_X, 0); p.mask ^= 12; }
  if (MASK & PH_CONV) {
    mbar_wait_slow(base + SM_SIG + 8 * (SIG_ATT + 1), 0);
    mbar_wait_slow(base + SM_RDY + 8 * RDY_U, 0);
#pragma unroll 1
    for (int i = w; i < CV_REG<MASK>; i += 2) { p.acquire_slow(u, i < 2 ? 2 : 1); load_conv(p, M, u, conv_channel<MASK>(cta, i)); }
  }
  p.acquire_slow(u, 2);
  if (elect()) asm volatile("prefetch.tensormap [%0];" :: "l"(!w ? &M.z : &M.out) : "memory");
  TSA(52 - 2 * w);
  mbar_wait(base + SM_RDY + 8 * (!w ? RDY_Z : RDY_G), 0);
  TSA(53 - 2 * w);
  if (elect()) {
    mbar_expect(p.full(u), 2 * UNIT + (!w ? 0 : 512));
    tma2d(p.addr(u), !w ? &M.z : &M.x, (!w ? mb : nb) * 128, (!w ? nb : mb) * 128, p.full(u), POL(5));
    tma2d(p.addr(u + 1), !w ? &M.z : &M.x, (!w ? mb : nb) * 128 + 64, (!w ? nb : mb) * 128, p.full(u), POL(5));
    if (w) bulk_g2s(base + SM_GATE, g_gate + mb * 128, 512, p.full(u));
  }
}

__device__ __forceinline__ constexpr uint32_t PUB(int sig, int cnt, int n) { return 0x80000000u | (sig << 24) | (n << 8) | cnt; }
__device__ __forceinline__ constexpr uint32_t GET(int rdy, int cnt, int n) { return (rdy << 24) | (n << 8) | cnt; }
template<int MASK> __device__ __forceinline__ void sync_agent(uint32_t base, int cta, int lane) {
  if ((base & 0x3FFFF) != SMEM_BASE) asm volatile("trap;");
  const int g = cta & 7, j = cta >> 3, go = min(out_mb(cta), 15 - out_mb(cta));
  const int c0 = conv_channel<MASK>(cta, 0), c1 = c0 + CV_REG<MASK> - 1, n0 = min(CV_REG<MASK>, 128 - (c0 & 127));
  constexpr bool KV = MASK & PH_KV, ATT = MASK & PH_ATT, CONV = MASK & PH_CONV, OUT = MASK & PH_OUT, ALL = MASK == PH_ALL;
  uint32_t e = 0;
  if (cta >= NREG) { if (CONV && lane * 32 < CV_EXTRA<MASK>) e = PUB(SIG_Z + lane, C_Z + lane, min(32, CV_EXTRA<MASK> - lane * 32)); }
  else switch (lane) {
    case 0:  if (KV) e = PUB(SIG_KV, C_KV + j, 1); break;
    case 1:  if (ATT) e = GET(RDY_KV, C_KV + j, 8); break;
    case 2:  if (ALL) e = PUB(SIG_WAR, C_WAR + j, 1); break;
    case 3:  if (ATT) e = PUB(SIG_CTX, C_CTX + g, 1); break;
    case 4:  if (ALL) e = GET(RDY_WAR, C_WAR + j, 8); break;
    case 5:  if (KV) e = PUB(SIG_KV + 1, C_KV + 16 + j, 1); break;
    case 6:  if (ATT) e = GET(RDY_KV + 1, C_KV + 16 + j, 8); break;
    case 7:  if (OUT) e = GET(RDY_CTX, C_CTX + go, 16); break;
    case 8:  if (CONV) e = GET(RDY_U, C_U + (c0 >> 6), 128); break;
    case 9:  if (CONV) e = GET(RDY_U, C_U + (c1 >> 6), 128); break;
    case 10: if (ATT) e = PUB(SIG_CTX + 1, C_CTX + 8 + g, 1); break;
    case 11: if (OUT) e = GET(RDY_CTX + 1, C_CTX + 8 + go, 16); break;
    case 12: if (OUT) e = GET(RDY_G, C_GATE, 256); break;
    case 13: if (CONV) e = PUB(SIG_Z, C_Z + (c0 >> 7), n0); break;
    case 14: if (CONV && n0 < CV_REG<MASK>) e = PUB(SIG_Z, C_Z + (c1 >> 7), CV_REG<MASK> - n0); break;
    case 15: if (OUT) e = GET(RDY_Z, C_Z + out_nb(cta), 128); break;
  }
  __syncwarp();
#pragma unroll 1
  for (int i = 0; i < 16; i++) {
    const uint32_t x = __shfl_sync(~0u, e, i), id = (x >> 24) & 127, n = (x >> 8) & 0xffff;
    if (x == 0) continue;
    unsigned* cnt = g_cnt + (x & 255) * CSTRIDE;
    if (x >> 31) {
      mbar_wait_slow(base + SM_SIG + 8 * id, 0);
      if (i == 13) TSA(22);
      if (lane == 0) cnt_publish(cnt, n, i != 14);
    } else {
      cnt_wait(cnt, n);
      if (id < 2) {
        const float4 kn = __ldcg((const float4*)(g_kn2 + kv_slot<MASK>(j + 16 * id) * 128) + lane);
        const uint32_t m = __reduce_max_sync(~0u, max(max(__float_as_uint(kn.x), __float_as_uint(kn.y)), max(__float_as_uint(kn.z), __float_as_uint(kn.w))));
        if (lane == 0) asm volatile("st.shared.u32 [%0], %1;" :: "r"(base + SM_KMAX + 4 * id), "r"(m) : "memory");
      }
      if (lane == 0) mbar_arrive(base + SM_RDY + 8 * id);
    }
    __syncwarp();
    TSA(24 + i);
  }
}

__device__ __forceinline__ void aux_gate(const Params& P, int cta, int aw, int lane) {
  uint4 gw[4];
#pragma unroll
  for (int i = 0; i < 4; i++) gw[i] = __ldg((const uint4*)P.gw + i * 32 + lane);
#pragma unroll 1
  for (int row = cta * 16 + aw * 8; row < cta * 16 + aw * 8 + 8; row++) {
    float a = 0.f;
#pragma unroll
    for (int i = 0; i < 4; i++) {
      const uint4 xv = __ldg((const uint4*)(P.x + (size_t)row * 1024) + i * 32 + lane);
      uint32_t m;
      m = hmul2(xv.x, gw[i].x); a += bf_lo(m) + bf_hi(m); m = hmul2(xv.y, gw[i].y); a += bf_lo(m) + bf_hi(m);
      m = hmul2(xv.z, gw[i].z); a += bf_lo(m) + bf_hi(m); m = hmul2(xv.w, gw[i].w); a += bf_lo(m) + bf_hi(m);
    }
#pragma unroll
    for (int o = 16; o > 0; o >>= 1) a += __shfl_xor_sync(~0u, a, o);
    a = bf_lo(pack_bf16(a, 0.f));
    const float gt = bf_lo(pack_bf16(__fdividef(1.f, 1.f + ex2(-a * 1.4426950408889634f)), 0.f));
    if (lane == 0) g_gate[row] = gt;
    if (GATE_SLEEP) __nanosleep(GATE_SLEEP);
  }
  cnt_signal(g_cnt + C_GATE * CSTRIDE, lane);
  if (aw == 0) { TSA(44); }
}
template<int MASK> __device__ __forceinline__ void aux_pre(const Maps& M, const Params& P, uint32_t base, int cta, int aw, int lane) {
  const uint32_t kb = base + 12 * UNIT, bar = base + SM_PRE;
  const int r = lane >> 2, q = lane & 3;
  const int mi = lane >> 3, row0 = (lane & 6) + 1 - (lane & 1);
  const int ra = (mi * 9 + 1) * 2 + row0;
  const int rb = (mi == 0 ? 3 : mi) * 18 + row0;
  if (PRE_DELAY) mbar_wait_slow(base + SM_BAR + 8 * PRE_DELAY_BAR, 0);
#pragma unroll 1
  for (int it = 0; it < (cta < 96 ? 5 : 4); it++) {
    if (GATE_EARLY && it == PRE_EARLY && MASK == PH_ALL) { mbar_wait_slow(base + SM_SIG + 8 * SIG_ATT, 0); aux_gate(P, cta, aw, lane); }
    if (it == PRE_EARLY && MASK == PH_ALL) mbar_wait_slow(base + SM_SIG + 8 * (SIG_ATT + PRE_HALF), 0);
    const int cg = it ? it * 4 - 3 + (cta >> 5) : 0, tb = cta & 31;
    if (aw == 0 && elect()) {
      mbar_expect(bar, 2 * 9216);
      tma4d(kb, &M.k, cg * 64, 0, tb * 8 - 1, 0, bar, POL(3));
      tma4d(kb + 9216, &M.v, cg * 64, 0, tb * 8 - 1, 0, bar, POL(3));
    }
    const uint2 swl = __ldg((const uint2*)(P.shift + (cg * 64 + aw * 32 + lane) * 4));
    if (tb == 0) {
      uint8_t* e = g_u + (size_t)(cg * 64 + aw * 32 + lane) * UCH + 4096;
      *(uint4*)e = make_uint4(0, 0, 0, 0); *(uint4*)(e + UPITCH) = make_uint4(0, 0, 0, 0);
      *(uint32_t*)(e + 32) = (uint32_t)__bfloat16_as_ushort(P.D[cg * 64 + aw * 32 + lane]) * 0x10001u;
    }
    mbar_wait_slow(bar, it & 1);
#pragma unroll 1
    for (int ol = it ? 0 : cta >> 5; ol < (it ? 4 : (cta >> 5) + 1); ol++) {
      const int oc = aw * 4 + ol;
      const uint32_t s01 = __shfl_sync(~0u, swl.x, ol * 8 + r), s23 = __shfl_sync(~0u, swl.y, ol * 8 + r);
      const uint32_t w0 = __byte_perm(s01, 0, 0x1010), w1 = __byte_perm(s01, 0, 0x3232), w2 = __byte_perm(s23, 0, 0x1010), w3 = __byte_perm(s23, 0, 0x3232);
      const uint32_t pa = kb + ra * 128 + ((oc ^ (ra & 7)) << 4), pb = kb + (mi == 0 ? 9216 : 0) + rb * 128 + ((oc ^ (rb & 7)) << 4);
      uint8_t* e0 = g_u + (uint32_t)((cg * 64 + oc * 8 + r) * UCH + (2040 - tb * 64 - 8 * q) * 2);
#pragma unroll
      for (int hb = 0; hb < 2; hb++) {
        uint32_t k[7], v[5];
        ldsm4t(pa + hb * 1024, k[3], k[4], k[5], k[6]);
        ldsm4t(pa + hb * 1024 + 9216, v[1], v[2], v[3], v[4]);
        ldsm4t(pb + hb * 1024, v[0], k[0], k[1], k[2]);
        uint32_t o1 = __byte_perm(k[1], k[0], 0x5432);
#pragma unroll
        for (int m = 0; m < 5; m++) {
          const uint32_t o2 = __byte_perm(k[m + 2], k[m + 1], 0x5432);
          v[m] = hmul2(hadd2(hadd2(hadd2(hmul2(o1, w3), hmul2(k[m + 1], w2)), hmul2(o2, w1)), hmul2(k[m + 2], w0)), v[m]);
          o1 = o2;
        }
        *(uint4*)(e0 - hb * 64) = make_uint4(v[4], v[3], v[2], v[1]);
        *(uint4*)(e0 - hb * 64 + UPITCH) = make_uint4(__byte_perm(v[4], v[3], 0x5432), __byte_perm(v[3], v[2], 0x5432), __byte_perm(v[2], v[1], 0x5432), __byte_perm(v[1], v[0], 0x5432));
        if (PRE_SLEEP && it >= PRE_EARLY) __nanosleep(PRE_SLEEP);
      }
    }
    bar_sync(5, 64);
    if (aw == 0) { TSA(40 + min(it, 3)); }
    if (K0X && it == PRE_EARLY - 1 && aw == 0 && lane == 0) mbar_arrive(base + SM_RDY + 8 * RDY_AUX);
    if (aw == 1 && lane == 0) asm volatile("red.release.gpu.global.add.u32 [%0], %1;" :: "l"(g_cnt + (C_U + cg) * CSTRIDE), "r"(it ? 4 : 1) : "memory");
  }
  uint32_t rel;
  asm volatile("mapa.shared::cluster.u32 %0, %1, %2;" : "=r"(rel) : "r"(base + SM_BAR + 128 + 8 * (12 + (lane & 1))), "r"((lane >> 1) & 1));
  if (lane < 4) asm volatile("mbarrier.arrive.shared::cluster.b64 _, [%0], 4;" :: "r"(rel) : "memory");
  if (!(GATE_EARLY && MASK == PH_ALL)) aux_gate(P, cta, aw, lane);
}

template<int MASK> __global__ void __cluster_dims__(2, 1, 1) __launch_bounds__(384, 1) gated_mix_kernel(const __grid_constant__ Maps M, const __grid_constant__ Params P) {
  extern __shared__ __align__(1024) uint8_t smem[];
  const uint32_t base = (uint32_t)__cvta_generic_to_shared(smem);
  const int wi = __shfl_sync(~0u, threadIdx.x >> 5, 0), wg = wi >> 2, warp = wi & 3;
  if (elect()) {
    if (wi < 8) {
      const int cnt = 1 << ((0x10334400 >> (4 * wi)) & 15);
#pragma unroll
      for (int i = 0; i < 8; i++) mbar_init(base + SM_BAR + 64 * wi + 8 * i, cnt);
      asm volatile("fence.mbarrier_init.release.cluster;" ::: "memory");
    } else if (MAP_PF) {
      asm volatile("prefetch.tensormap [%0];" :: "l"(&M.c + (wi - 8)) : "memory");
    }
  }
  const int cta = blockIdx.x;
  const bool first_loads = (MASK & PH_KV) && wi == 8 && cta < NREG;
  const CUtensorMap* mw = (cta & 1) ? &M.wv : &M.wk;
  __syncwarp();
  asm volatile("barrier.cluster.arrive.relaxed.aligned;\nbarrier.cluster.wait.aligned;" ::: "memory");
  if (first_loads && elect()) {
#pragma unroll 1
    for (int it = 0; it < NFIRST; it++) {
      const uint32_t bar = base + SM_BAR + 24 * it, d0 = base + 3 * it * UNIT;
      mbar_expect(bar, 3 * UNIT);
      tma3d_mc(d0 + (1 + (cta & 1)) * UNIT, mw, 0, it * 64, 2 * (cta >> 3), bar);
      tma2d(d0, &M.c, it * 64, (cta & 7) * 256, bar);
    }
  }
  __syncwarp();
  const int lane = threadIdx.x & 31;
#define TS_PRO()
  if (wg == 2) {
    asm volatile("setmaxnreg.dec.sync.aligned.u32 56;");
    TS_PRO();
    TS(2, 62);
    if (warp == 0) producer<MASK>(M, P, base, cta, lane);
    else if (warp == 1) sync_agent<MASK>(base, cta, lane);
    else if (cta < NREG) {
      if (MASK & PH_PRE) aux_pre<MASK>(M, P, base, cta, warp - 2, lane);
      if (MASK & PH_OUT) producer2<MASK>(M, P, base, cta, warp - 2, lane);
    }
    if (warp == 1) {
      if (MASK & PH_OUT) {
        unsigned old = 0;
        if (lane == 0) asm volatile("atom.relaxed.gpu.global.add.u32 %0, [%1], 1;" : "=r"(old) : "l"(g_cnt + C_EXIT * CSTRIDE) : "memory");
        old = __shfl_sync(~0u, old, 0);
        if (old == NCTA - 1) for (int i = lane; i < C_NUM; i += 32) g_cnt[i * CSTRIDE] = 0;
      }
      mbar_wait_slow(base + SM_SIG + 8 * SIG_DONE, 0);
      if (cta >= NREG || !(MASK & PH_OUT)) { cluster_arrive(); cluster_wait(); }
    }
  } else {
    asm volatile("setmaxnreg.inc.sync.aligned.u32 224;");
    TS_PRO();
    uint32_t rel;
    asm volatile("mapa.shared::cluster.u32 %0, %1, %2;" : "=r"(rel) : "r"(base + SM_BAR + 128 + 8 * (lane & 15)), "r"(lane >> 4));
    Cons c{base, rel, 0u, lane, warp, wg, (cta * 3 + wg) * 2048};
    if (wg == 1) bar_arrive(1, 256);
    TS(wg, 0);
    if (cta < NREG) {
      const int g = cta & 7, j = cta >> 3;
      Pend w = {};
#pragma unroll 1
      for (int half = 0; half < 2; half++) {
        const int h = j + 16 * half;
        if (MASK & PH_KV) cons_kv<(MASK & PH_ATT) != 0>(c, h, kv_slot<MASK>(h), g, w, half == 1 && (MASK & PH_ATT));
        TS(wg, 1 + 4 * half);
        if (MASK & PH_ATT) {
          Att a;
          cons_q<(MASK & PH_KV) != 0>(c, h, w, a.o);
          TS(wg, 2 + 4 * half);
          cons_att(c, a, h, g, w);
          if (half == 0) c.signal(SIG_WAR);
#pragma unroll
          for (int i = 0; i < 8; i++) w.hi[i] = make_uint4(0, 0, 0, 0);
          TS(wg, 3 + 4 * half);
          if (MASK != PH_ALL) { tile_store<0, 4>(w.lo, w.dst, lane); c.signal(SIG_CTX + half); }
        } else if (MASK & PH_KV) {
          out_piece<SCH_KV, true>(c, w, 0, true);
          for (int ks = 1; ks < 8; ks++) out_piece<SCH_KV, false>(c, w, ks, true);
          c.signal(SIG_KV + half);
        }
      }
      if (MASK & PH_OUT) cons_out<MASK>(c, M, P, cta, w);
    }
    if (cta >= NREG || !(MASK & PH_OUT)) {
      if (MASK & PH_CONV) cons_conv<MASK>(c, cta, cta < NREG ? CV_REG<MASK> : CV_EXTRA<MASK>);
      TS(wg, 9);
      c.signal(SIG_DONE);
      cluster_arrive();
    }
    TS(wg, 10);
  }
}

typedef CUresult (*EncFn)(CUtensorMap*, CUtensorMapDataType, cuuint32_t, void*, const cuuint64_t*, const cuuint64_t*, const cuuint32_t*, const cuuint32_t*,
                          CUtensorMapInterleave, CUtensorMapSwizzle, CUtensorMapL2promotion, CUtensorMapFloatOOBfill);
static void enc(EncFn f, CUtensorMap* m, const void* ptr, int rank, const cuuint64_t* dims, const cuuint64_t* strides, const cuuint32_t* box, CUtensorMapSwizzle sw,
                CUtensorMapDataType dt = CU_TENSOR_MAP_DATA_TYPE_BFLOAT16) {
  const cuuint32_t es[4] = {1, 1, 1, 1};
  f(m, dt, rank, (void*)ptr, dims, strides, box, es, CU_TENSOR_MAP_INTERLEAVE_NONE, sw, CU_TENSOR_MAP_L2_PROMOTION_L2_256B, CU_TENSOR_MAP_FLOAT_OOB_FILL_NONE);
}
static void enc2(EncFn f, CUtensorMap* m, const void* ptr, int cols, int rows, int brows) {
  const cuuint64_t d[2] = {(cuuint64_t)cols, (cuuint64_t)rows}, s[1] = {(cuuint64_t)cols * 2}; const cuuint32_t b[2] = {64, (cuuint32_t)brows};
  enc(f, m, ptr, 2, d, s, b, CU_TENSOR_MAP_SWIZZLE_128B);
}
static void encw(EncFn f, CUtensorMap* m, const void* ptr, int cols, int rows) {
  const cuuint64_t d[3] = {64, (cuuint64_t)rows, (cuuint64_t)cols / 64}, s[2] = {(cuuint64_t)cols * 2, 128}; const cuuint32_t b[3] = {64, 64, 2};
  enc(f, m, ptr, 3, d, s, b, CU_TENSOR_MAP_SWIZZLE_128B);
}
extern "C" void kernel_launch(void* const* d_in, const int* in_sizes, int n_in, void* d_out, int out_size) {
  static EncFn fn = nullptr;
  static int ncl = 0;
  static void* zptr = nullptr;
  static void* tptr = nullptr;
  if (!fn) {
    void* p = nullptr; cudaDriverEntryPointQueryResult qr;
    cudaGetDriverEntryPoint("cuTensorMapEncodeTiled", &p, cudaEnableDefault, &qr);
    fn = (EncFn)p;
    cudaFuncSetAttribute(gated_mix_kernel<PH_ALL>, cudaFuncAttributeMaxDynamicSharedMemorySize, SMEM_BYTES);
    cudaFuncSetAttribute(gated_mix_kernel<PH_PRE | PH_KV>, cudaFuncAttributeMaxDynamicSharedMemorySize, SMEM_BYTES);
    cudaFuncSetAttribute(gated_mix_kernel<PH_ATT | PH_CONV>, cudaFuncAttributeMaxDynamicSharedMemorySize, SMEM_BYTES);
    cudaFuncSetAttribute(gated_mix_kernel<PH_OUT>, cudaFuncAttributeMaxDynamicSharedMemorySize, SMEM_BYTES);
    cudaLaunchConfig_t cfg = {}; cfg.gridDim = NCTA; cfg.blockDim = 384; cfg.dynamicSmemBytes = SMEM_BYTES;
    cudaLaunchAttribute at; at.id = cudaLaunchAttributeClusterDimension; at.val.clusterDim.x = 2; at.val.clusterDim.y = 1; at.val.clusterDim.z = 1;
    cfg.attrs = &at; cfg.numAttrs = 1;
    cudaOccupancyMaxActiveClusters(&ncl, gated_mix_kernel<PH_ALL>, &cfg);
    cudaGetSymbolAddress(&zptr, g_z);
    cudaGetSymbolAddress(&tptr, g_T);
  }
  Maps M;
  enc2(fn, &M.x, d_in[0], 1024, 2048, 128);
  enc2(fn, &M.c, d_in[7], 512, 2048, 128);
  enc2(fn, &M.wq, d_in[8], 4096, 1024, 64);
  encw(fn, &M.wk, d_in[9], 4096, 512);
  encw(fn, &M.wv, d_in[10], 4096, 512);
  encw(fn, &M.wo, d_in[11], 1024, 4096);
  { const cuuint64_t d[3] = {64, 32, 1024}, s[2] = {128, 4096}; const cuuint32_t b[3] = {64, 40, 1}; enc(fn, &M.h, d_in[4], 3, d, s, b, CU_TENSOR_MAP_SWIZZLE_NONE); }
  enc2(fn, &M.z, zptr, 2048, 1024, 128);
  enc2(fn, &M.out, d_out, 1024, 2048, 16);
  { const cuuint64_t d[2] = {512, 512 * 16}, s[1] = {2048}; const cuuint32_t b[2] = {256, 8};
    enc(fn, &M.ctx, tptr, 2, d, s, b, CU_TENSOR_MAP_SWIZZLE_NONE, CU_TENSOR_MAP_DATA_TYPE_UINT32); }
  { const cuuint64_t d[4] = {1024, 2, 256, 4}, s[3] = {2048, 16384, 4096}; const cuuint32_t b[4] = {64, 2, 9, 4};
    enc(fn, &M.k, d_in[1], 4, d, s, b, CU_TENSOR_MAP_SWIZZLE_128B); enc(fn, &M.v, d_in[2], 4, d, s, b, CU_TENSOR_MAP_SWIZZLE_128B); }
  Params P{(const __nv_bfloat16*)d_in[0], (const __nv_bfloat16*)d_in[3],
           (const __nv_bfloat16*)d_in[5], (const __nv_bfloat16*)d_in[12], (__nv_bfloat16*)d_out};
  bool split = 2 * ncl < NCTA;
  if (!split) {
    gated_mix_kernel<PH_ALL><<<NCTA, 384, SMEM_BYTES>>>(M, P);
  } else {
    gated_mix_kernel<PH_PRE | PH_KV><<<NCTA, 384, SMEM_BYTES>>>(M, P);
    gated_mix_kernel<PH_ATT | PH_CONV><<<NCTA, 384, SMEM_BYTES>>>(M, P);
    gated_mix_kernel<PH_OUT><<<NCTA, 384, SMEM_BYTES>>>(M, P);
  }
}
```

```cpp
#include <cuda_runtime.h>
#include <cuda.h>
#include <cuda_bf16.h>
#include <stdint.h>

template<int TB> __device__ __forceinline__ void wgmma_ss_n256(float (&d)[128], uint64_t da, uint64_t db, int scale_d) {
  asm volatile("{\n.reg .pred p;\nsetp.ne.b32 p, %130, 0;\n"
    "wgmma.mma_async.sync.aligned.m64n256k16.f32.bf16.bf16 {%0, %1, %2, %3, %4, %5, %6, %7, %8, %9, %10, %11, %12, %13, %14, %15, %16, %17, %18, %19, %20, %21, %22, %23, %24, %25, %26, %27, %28, %29, %30, %31, %32, %33, %34, %35, %36, %37, %38, %39, %40, %41, %42, %43, %44, %45, %46, %47, %48, %49, %50, %51, %52, %53, %54, %55, %56, %57, %58, %59, %60, %61, %62, %63, %64, %65, %66, %67, %68, %69, %70, %71, %72, %73, %74, %75, %76, %77, %78, %79, %80, %81, %82, %83, %84, %85, %86, %87, %88, %89, %90, %91, %92, %93, %94, %95, %96, %97, %98, %99, %100, %101, %102, %103, %104, %105, %106, %107, %108, %109, %110, %111, %112, %113, %114, %115, %116, %117, %118, %119, %120, %121, %122, %123, %124, %125, %126, %127}, %128, %129, p, 1, 1, 0, %131;\n}\n"
    : "+f"(d[0]), "+f"(d[1]), "+f"(d[2]), "+f"(d[3]), "+f"(d[4]), "+f"(d[5]), "+f"(d[6]), "+f"(d[7]), "+f"(d[8]), "+f"(d[9]), "+f"(d[10]), "+f"(d[11]), "+f"(d[12]), "+f"(d[13]), "+f"(d[14]), "+f"(d[15]), "+f"(d[16]), "+f"(d[17]), "+f"(d[18]), "+f"(d[19]), "+f"(d[20]), "+f"(d[21]), "+f"(d[22]), "+f"(d[23]), "+f"(d[24]), "+f"(d[25]), "+f"(d[26]), "+f"(d[27]), "+f"(d[28]), "+f"(d[29]), "+f"(d[30]), "+f"(d[31]), "+f"(d[32]), "+f"(d[33]), "+f"(d[34]), "+f"(d[35]), "+f"(d[36]), "+f"(d[37]), "+f"(d[38]), "+f"(d[39]), "+f"(d[40]), "+f"(d[41]), "+f"(d[42]), "+f"(d[43]), "+f"(d[44]), "+f"(d[45]), "+f"(d[46]), "+f"(d[47]), "+f"(d[48]), "+f"(d[49]), "+f"(d[50]), "+f"(d[51]), "+f"(d[52]), "+f"(d[53]), "+f"(d[54]), "+f"(d[55]), "+f"(d[56]), "+f"(d[57]), "+f"(d[58]), "+f"(d[59]), "+f"(d[60]), "+f"(d[61]), "+f"(d[62]), "+f"(d[63]), "+f"(d[64]), "+f"(d[65]), "+f"(d[66]), "+f"(d[67]), "+f"(d[68]), "+f"(d[69]), "+f"(d[70]), "+f"(d[71]), "+f"(d[72]), "+f"(d[73]), "+f"(d[74]), "+f"(d[75]), "+f"(d[76]), "+f"(d[77]), "+f"(d[78]), "+f"(d[79]), "+f"(d[80]), "+f"(d[81]), "+f"(d[82]), "+f"(d[83]), "+f"(d[84]), "+f"(d[85]), "+f"(d[86]), "+f"(d[87]), "+f"(d[88]), "+f"(d[89]), "+f"(d[90]), "+f"(d[91]), "+f"(d[92]), "+f"(d[93]), "+f"(d[94]), "+f"(d[95]), "+f"(d[96]), "+f"(d[97]), "+f"(d[98]), "+f"(d[99]), "+f"(d[100]), "+f"(d[101]), "+f"(d[102]), "+f"(d[103]), "+f"(d[104]), "+f"(d[105]), "+f"(d[106]), "+f"(d[107]), "+f"(d[108]), "+f"(d[109]), "+f"(d[110]), "+f"(d[111]), "+f"(d[112]), "+f"(d[113]), "+f"(d[114]), "+f"(d[115]), "+f"(d[116]), "+f"(d[117]), "+f"(d[118]), "+f"(d[119]), "+f"(d[120]), "+f"(d[121]), "+f"(d[122]), "+f"(d[123]), "+f"(d[124]), "+f"(d[125]), "+f"(d[126]), "+f"(d[127])
    : "l"(da), "l"(db), "r"(scale_d), "n"(TB));
}
template<int TB> __device__ __forceinline__ void wgmma_ss_n128(float (&d)[64], uint64_t da, uint64_t db, int scale_d) {
  asm volatile("{\n.reg .pred p;\nsetp.ne.b32 p, %66, 0;\n"
    "wgmma.mma_async.sync.aligned.m64n128k16.f32.bf16.bf16 {%0, %1, %2, %3, %4, %5, %6, %7, %8, %9, %10, %11, %12, %13, %14, %15, %16, %17, %18, %19, %20, %21, %22, %23, %24, %25, %26, %27, %28, %29, %30, %31, %32, %33, %34, %35, %36, %37, %38, %39, %40, %41, %42, %43, %44, %45, %46, %47, %48, %49, %50, %51, %52, %53, %54, %55, %56, %57, %58, %59, %60, %61, %62, %63}, %64, %65, p, 1, 1, 0, %67;\n}\n"
    : "+f"(d[0]), "+f"(d[1]), "+f"(d[2]), "+f"(d[3]), "+f"(d[4]), "+f"(d[5]), "+f"(d[6]), "+f"(d[7]), "+f"(d[8]), "+f"(d[9]), "+f"(d[10]), "+f"(d[11]), "+f"(d[12]), "+f"(d[13]), "+f"(d[14]), "+f"(d[15]), "+f"(d[16]), "+f"(d[17]), "+f"(d[18]), "+f"(d[19]), "+f"(d[20]), "+f"(d[21]), "+f"(d[22]), "+f"(d[23]), "+f"(d[24]), "+f"(d[25]), "+f"(d[26]), "+f"(d[27]), "+f"(d[28]), "+f"(d[29]), "+f"(d[30]), "+f"(d[31]), "+f"(d[32]), "+f"(d[33]), "+f"(d[34]), "+f"(d[35]), "+f"(d[36]), "+f"(d[37]), "+f"(d[38]), "+f"(d[39]), "+f"(d[40]), "+f"(d[41]), "+f"(d[42]), "+f"(d[43]), "+f"(d[44]), "+f"(d[45]), "+f"(d[46]), "+f"(d[47]), "+f"(d[48]), "+f"(d[49]), "+f"(d[50]), "+f"(d[51]), "+f"(d[52]), "+f"(d[53]), "+f"(d[54]), "+f"(d[55]), "+f"(d[56]), "+f"(d[57]), "+f"(d[58]), "+f"(d[59]), "+f"(d[60]), "+f"(d[61]), "+f"(d[62]), "+f"(d[63])
    : "l"(da), "l"(db), "r"(scale_d), "n"(TB));
}
template<int TB> __device__ __forceinline__ void wgmma_rs_n32(float (&d)[16], uint32_t a0, uint32_t a1, uint32_t a2, uint32_t a3, uint64_t db, int scale_d) {
  asm volatile("{\n.reg .pred p;\nsetp.ne.b32 p, %21, 0;\n"
    "wgmma.mma_async.sync.aligned.m64n32k16.f32.bf16.bf16 {%0, %1, %2, %3, %4, %5, %6, %7, %8, %9, %10, %11, %12, %13, %14, %15}, {%16, %17, %18, %19}, %20, p, 1, 1, %22;\n}\n"
    : "+f"(d[0]), "+f"(d[1]), "+f"(d[2]), "+f"(d[3]), "+f"(d[4]), "+f"(d[5]), "+f"(d[6]), "+f"(d[7]), "+f"(d[8]), "+f"(d[9]), "+f"(d[10]), "+f"(d[11]), "+f"(d[12]), "+f"(d[13]), "+f"(d[14]), "+f"(d[15])
    : "r"(a0), "r"(a1), "r"(a2), "r"(a3), "l"(db), "r"(scale_d), "n"(TB));
}
__device__ __forceinline__ void wgmma_pv_sel(float (&d)[64], const uint32_t (&p)[32], uint64_t db, int full, int acc, int wg) {
  asm volatile("{\n.reg .pred q, s, w;\n.reg .b64 t;\nsetp.eq.b32 w, %99, 0;\nsetp.ne.b32 s, %98, 0;\nsetp.eq.b32 q, %97, 0;\n@q bra.uni LH;\n"
    "wgmma.fence.sync.aligned;\n"
    "add.s64 t, %96, 0;\nwgmma.mma_async.sync.aligned.m64n128k16.f32.bf16.bf16 {%0, %1, %2, %3, %4, %5, %6, %7, %8, %9, %10, %11, %12, %13, %14, %15, %16, %17, %18, %19, %20, %21, %22, %23, %24, %25, %26, %27, %28, %29, %30, %31, %32, %33, %34, %35, %36, %37, %38, %39, %40, %41, %42, %43, %44, %45, %46, %47, %48, %49, %50, %51, %52, %53, %54, %55, %56, %57, %58, %59, %60, %61, %62, %63}, {%64, %65, %66, %67}, t, s, 1, 1, 1;\n"
    "add.s64 t, %96, 256;\nwgmma.mma_async.sync.aligned.m64n128k16.f32.bf16.bf16 {%0, %1, %2, %3, %4, %5, %6, %7, %8, %9, %10, %11, %12, %13, %14, %15, %16, %17, %18, %19, %20, %21, %22, %23, %24, %25, %26, %27, %28, %29, %30, %31, %32, %33, %34, %35, %36, %37, %38, %39, %40, %41, %42, %43, %44, %45, %46, %47, %48, %49, %50, %51, %52, %53, %54, %55, %56, %57, %58, %59, %60, %61, %62, %63}, {%68, %69, %70, %71}, t, 1, 1, 1, 1;\n"
    "add.s64 t, %96, 512;\nwgmma.mma_async.sync.aligned.m64n128k16.f32.bf16.bf16 {%0, %1, %2, %3, %4, %5, %6, %7, %8, %9, %10, %11, %12, %13, %14, %15, %16, %17, %18, %19, %20, %21, %22, %23, %24, %25, %26, %27, %28, %29, %30, %31, %32, %33, %34, %35, %36, %37, %38, %39, %40, %41, %42, %43, %44, %45, %46, %47, %48, %49, %50, %51, %52, %53, %54, %55, %56, %57, %58, %59, %60, %61, %62, %63}, {%72, %73, %74, %75}, t, 1, 1, 1, 1;\n"
    "add.s64 t, %96, 768;\nwgmma.mma_async.sync.aligned.m64n128k16.f32.bf16.bf16 {%0, %1, %2, %3, %4, %5, %6, %7, %8, %9, %10, %11, %12, %13, %14, %15, %16, %17, %18, %19, %20, %21, %22, %23, %24, %25, %26, %27, %28, %29, %30, %31, %32, %33, %34, %35, %36, %37, %38, %39, %40, %41, %42, %43, %44, %45, %46, %47, %48, %49, %50, %51, %52, %53, %54, %55, %56, %57, %58, %59, %60, %61, %62, %63}, {%76, %77, %78, %79}, t, 1, 1, 1, 1;\n"
    "add.s64 t, %96, 1024;\nwgmma.mma_async.sync.aligned.m64n128k16.f32.bf16.bf16 {%0, %1, %2, %3, %4, %5, %6, %7, %8, %9, %10, %11, %12, %13, %14, %15, %16, %17, %18, %19, %20, %21, %22, %23, %24, %25, %26, %27, %28, %29, %30, %31, %32, %33, %34, %35, %36, %37, %38, %39, %40, %41, %42, %43, %44, %45, %46, %47, %48, %49, %50, %51, %52, %53, %54, %55, %56, %57, %58, %59, %60, %61, %62, %63}, {%80, %81, %82, %83}, t, 1, 1, 1, 1;\n"
    "add.s64 t, %96, 1280;\nwgmma.mma_async.sync.aligned.m64n128k16.f32.bf16.bf16 {%0, %1, %2, %3, %4, %5, %6, %7, %8, %9, %10, %11, %12, %13, %14, %15, %16, %17, %18, %19, %20, %21, %22, %23, %24, %25, %26, %27, %28, %29, %30, %31, %32, %33, %34, %35, %36, %37, %38, %39, %40, %41, %42, %43, %44, %45, %46, %47, %48, %49, %50, %51, %52, %53, %54, %55, %56, %57, %58, %59, %60, %61, %62, %63}, {%84, %85, %86, %87}, t, 1, 1, 1, 1;\n"
    "@w bar.arrive 2, 256;\n@!w bar.arrive 1, 256;\n"
    "add.s64 t, %96, 1536;\nwgmma.mma_async.sync.aligned.m64n128k16.f32.bf16.bf16 {%0, %1, %2, %3, %4, %5, %6, %7, %8, %9, %10, %11, %12, %13, %14, %15, %16, %17, %18, %19, %20, %21, %22, %23, %24, %25, %26, %27, %28, %29, %30, %31, %32, %33, %34, %35, %36, %37, %38, %39, %40, %41, %42, %43, %44, %45, %46, %47, %48, %49, %50, %51, %52, %53, %54, %55, %56, %57, %58, %59, %60, %61, %62, %63}, {%88, %89, %90, %91}, t, 1, 1, 1, 1;\n"
    "add.s64 t, %96, 1792;\nwgmma.mma_async.sync.aligned.m64n128k16.f32.bf16.bf16 {%0, %1, %2, %3, %4, %5, %6, %7, %8, %9, %10, %11, %12, %13, %14, %15, %16, %17, %18, %19, %20, %21, %22, %23, %24, %25, %26, %27, %28, %29, %30, %31, %32, %33, %34, %35, %36, %37, %38, %39, %40, %41, %42, %43, %44, %45, %46, %47, %48, %49, %50, %51, %52, %53, %54, %55, %56, %57, %58, %59, %60, %61, %62, %63}, {%92, %93, %94, %95}, t, 1, 1, 1, 1;\n"
    "wgmma.commit_group.sync.aligned;\n"
    "bra.uni LE;\nLH:\n"
    "wgmma.fence.sync.aligned;\n"
    "add.s64 t, %96, 0;\nwgmma.mma_async.sync.aligned.m64n128k16.f32.bf16.bf16 {%0, %1, %2, %3, %4, %5, %6, %7, %8, %9, %10, %11, %12, %13, %14, %15, %16, %17, %18, %19, %20, %21, %22, %23, %24, %25, %26, %27, %28, %29, %30, %31, %32, %33, %34, %35, %36, %37, %38, %39, %40, %41, %42, %43, %44, %45, %46, %47, %48, %49, %50, %51, %52, %53, %54, %55, %56, %57, %58, %59, %60, %61, %62, %63}, {%80, %81, %82, %83}, t, s, 1, 1, 1;\n"
    "add.s64 t, %96, 256;\nwgmma.mma_async.sync.aligned.m64n128k16.f32.bf16.bf16 {%0, %1, %2, %3, %4, %5, %6, %7, %8, %9, %10, %11, %12, %13, %14, %15, %16, %17, %18, %19, %20, %21, %22, %23, %24, %25, %26, %27, %28, %29, %30, %31, %32, %33, %34, %35, %36, %37, %38, %39, %40, %41, %42, %43, %44, %45, %46, %47, %48, %49, %50, %51, %52, %53, %54, %55, %56, %57, %58, %59, %60, %61, %62, %63}, {%84, %85, %86, %87}, t, 1, 1, 1, 1;\n"
    "@w bar.arrive 2, 256;\n@!w bar.arrive 1, 256;\n"
    "add.s64 t, %96, 512;\nwgmma.mma_async.sync.aligned.m64n128k16.f32.bf16.bf16 {%0, %1, %2, %3, %4, %5, %6, %7, %8, %9, %10, %11, %12, %13, %14, %15, %16, %17, %18, %19, %20, %21, %22, %23, %24, %25, %26, %27, %28, %29, %30, %31, %32, %33, %34, %35, %36, %37, %38, %39, %40, %41, %42, %43, %44, %45, %46, %47, %48, %49, %50, %51, %52, %53, %54, %55, %56, %57, %58, %59, %60, %61, %62, %63}, {%88, %89, %90, %91}, t, 1, 1, 1, 1;\n"
    "add.s64 t, %96, 768;\nwgmma.mma_async.sync.aligned.m64n128k16.f32.bf16.bf16 {%0, %1, %2, %3, %4, %5, %6, %7, %8, %9, %10, %11, %12, %13, %14, %15, %16, %17, %18, %19, %20, %21, %22, %23, %24, %25, %26, %27, %28, %29, %30, %31, %32, %33, %34, %35, %36, %37, %38, %39, %40, %41, %42, %43, %44, %45, %46, %47, %48, %49, %50, %51, %52, %53, %54, %55, %56, %57, %58, %59, %60, %61, %62, %63}, {%92, %93, %94, %95}, t, 1, 1, 1, 1;\n"
    "wgmma.commit_group.sync.aligned;\n"
    "LE:\n}\n"
    : "+f"(d[0]), "+f"(d[1]), "+f"(d[2]), "+f"(d[3]), "+f"(d[4]), "+f"(d[5]), "+f"(d[6]), "+f"(d[7]), "+f"(d[8]), "+f"(d[9]), "+f"(d[10]), "+f"(d[11]), "+f"(d[12]), "+f"(d[13]), "+f"(d[14]), "+f"(d[15]), "+f"(d[16]), "+f"(d[17]), "+f"(d[18]), "+f"(d[19]), "+f"(d[20]), "+f"(d[21]), "+f"(d[22]), "+f"(d[23]), "+f"(d[24]), "+f"(d[25]), "+f"(d[26]), "+f"(d[27]), "+f"(d[28]), "+f"(d[29]), "+f"(d[30]), "+f"(d[31]), "+f"(d[32]), "+f"(d[33]), "+f"(d[34]), "+f"(d[35]), "+f"(d[36]), "+f"(d[37]), "+f"(d[38]), "+f"(d[39]), "+f"(d[40]), "+f"(d[41]), "+f"(d[42]), "+f"(d[43]), "+f"(d[44]), "+f"(d[45]), "+f"(d[46]), "+f"(d[47]), "+f"(d[48]), "+f"(d[49]), "+f"(d[50]), "+f"(d[51]), "+f"(d[52]), "+f"(d[53]), "+f"(d[54]), "+f"(d[55]), "+f"(d[56]), "+f"(d[57]), "+f"(d[58]), "+f"(d[59]), "+f"(d[60]), "+f"(d[61]), "+f"(d[62]), "+f"(d[63])
    : "r"(p[0]), "r"(p[1]), "r"(p[2]), "r"(p[3]), "r"(p[4]), "r"(p[5]), "r"(p[6]), "r"(p[7]), "r"(p[8]), "r"(p[9]), "r"(p[10]), "r"(p[11]), "r"(p[12]), "r"(p[13]), "r"(p[14]), "r"(p[15]), "r"(p[16]), "r"(p[17]), "r"(p[18]), "r"(p[19]), "r"(p[20]), "r"(p[21]), "r"(p[22]), "r"(p[23]), "r"(p[24]), "r"(p[25]), "r"(p[26]), "r"(p[27]), "r"(p[28]), "r"(p[29]), "r"(p[30]), "r"(p[31]), "l"(db), "r"(full), "r"(acc), "r"(wg) : "memory");
}

constexpr int NCTA = 132, NREG = 128;
constexpr int UNIT = 16384, NUNIT = 14;
constexpr uint32_t SMEM_BASE = 1024;
constexpr int SM_BAR = NUNIT * UNIT;
constexpr int SM_GATE = SM_BAR + 1024;
constexpr int SMEM_BYTES = SM_BAR + 1536;
constexpr int UPITCH = 4160, UCH = 2 * UPITCH;
constexpr float QSCALE = 0.08838834764831845f * 1.4426950408889634f;
constexpr float BOUND2 = 60.f * 60.f / 1.15f;
#define CONV_REG 5
constexpr int C_KV = 0;
constexpr int C_CTX = 32;
constexpr int C_U = 48;
constexpr int C_Z = 80;
constexpr int C_GATE = 88;
constexpr int C_EXIT = 89;
#define PRE_EARLY 2
#define PRE_HALF 1
#define ATT_SPLIT 6
#define NFIRST 2
#define PRE_DELAY 0
#define MAP_PF 1
#define FINAL_ST 1
#define Z_AT 60
#define PRE_DELAY_BAR 9
#define PRE_FMA 0
#define PRE_SLEEP 300
#define GATE_SLEEP 1000
#define GATE_EARLY 1
#define OC_S0 2
#define OC_S1 11
#define OC_POST 1
#define OC_L0 18
#define OC_L1 18
#define PF 0
#define PF_AT 26
#define PF_KS 8
#define ST_1 4
#define ST_D 2
#define ST_0 1
#define ST_0D 0
#define SCH_KV 0x6665544433221100ull
#define SCH_Q 0x6665544433221100ull
#define NK_AT 1
#ifndef NV_AT
#define NV_AT 3
#endif
#define DS_B 4
#define CHK_S 1
#define KVE 1
#define DFIRST 0
#define VF 5
#define HOISTW 0
#define BARP 1
#define EF 127
#define POL(bit) (((EF >> (bit)) & 1) != 0)
constexpr int C_WAR = 96;
constexpr int C_NUM = 112;
constexpr int CSTRIDE = 32;
constexpr int SM_KMAX = SM_BAR + 640, SM_DUMMY = SM_BAR + 648, SM_PRE = SM_BAR + 112, SM_SIG = SM_BAR + 256, SM_RDY = SM_BAR + 384;
enum { SIG_KV = 0, SIG_CTX = 2, SIG_Z = 4, SIG_DONE = 8, SIG_WAR = 9, SIG_ATT = 10 };
enum { RDY_KV = 0, RDY_CTX = 2, RDY_WAR = 4, RDY_G = 5, RDY_X = 6, RDY_AUX = 7, RDY_U = 8, RDY_Z = 9 };
enum { PH_PRE = 1, PH_KV = 2, PH_ATT = 4, PH_CONV = 8, PH_OUT = 16, PH_ALL = 31 };

constexpr uint32_t T_CTX = 0, T_KV = 16 * 32 * 32768, T_BYTES = T_KV + 32 * 16 * 65536;
__device__ __align__(1024) uint8_t g_T[T_BYTES];
__device__ __align__(1024) uint8_t g_u[1024 * UCH];
__device__ __align__(1024) __nv_bfloat16 g_z[1024 * 2048];
__device__ __align__(1024) float g_gate[2048];
__device__ __align__(1024) float g_kn2[32 * 128];
__device__ __align__(1024) unsigned g_cnt[C_NUM * CSTRIDE];

struct __align__(64) Maps { CUtensorMap c, wk, wv, x, wq, wo, h, z, out, ctx, k, v; };
struct Params {
  const __nv_bfloat16 *x, *shift, *D, *gw;
  __nv_bfloat16* out;
};

__device__ __forceinline__ void wg_fence() { asm volatile("wgmma.fence.sync.aligned;" ::: "memory"); }
__device__ __forceinline__ void wg_commit() { asm volatile("wgmma.commit_group.sync.aligned;" ::: "memory"); }
template<int N> __device__ __forceinline__ void wg_wait() { asm volatile("wgmma.wait_group.sync.aligned %0;" :: "n"(N) : "memory"); }
__device__ __forceinline__ uint64_t odesc(uint32_t addr, uint32_t lbo, uint32_t sbo, uint32_t swz) {
  uint64_t d = (uint64_t)(addr >> 4) + (((uint64_t)(lbo >> 4) << 16) | ((uint64_t)(sbo >> 4) << 32) | ((uint64_t)swz << 62));
  asm volatile("" : "+l"(d));
  return d;
}
__device__ __forceinline__ void mbar_init(uint32_t bar, int cnt) { asm volatile("mbarrier.init.shared::cta.b64 [%0], %1;" :: "r"(bar), "r"(cnt)); }
__device__ __forceinline__ void mbar_expect(uint32_t bar, uint32_t bytes) { asm volatile("mbarrier.arrive.expect_tx.shared::cta.b64 _, [%0], %1;" :: "r"(bar), "r"(bytes) : "memory"); }
__device__ __forceinline__ void mbar_arrive(uint32_t bar) { asm volatile("mbarrier.arrive.shared::cta.b64 _, [%0];" :: "r"(bar) : "memory"); }
__device__ __forceinline__ void mbar_arrive_n(uint32_t bar, int n) { asm volatile("mbarrier.arrive.shared::cta.b64 _, [%0], %1;" :: "r"(bar), "r"(n) : "memory"); }
__device__ __forceinline__ void mbar_wait(uint32_t bar, uint32_t parity) {
  asm volatile("{\n.reg .pred p;\nLW:\nmbarrier.try_wait.parity.shared::cta.b64 p, [%0], %1;\n@!p bra LW;\n}\n" :: "r"(bar), "r"(parity) : "memory");
}
__device__ __forceinline__ void mbar_wait_slow(uint32_t bar, uint32_t parity) {
  asm volatile("{\n.reg .pred p;\n.reg .u32 n;\nmov.u32 n, 0;\n"
    "LW:\nmbarrier.test_wait.parity.shared::cta.b64 p, [%0], %1;\n@p bra LD;\n"
    "nanosleep.u32 128;\nadd.u32 n, n, 1;\nsetp.lt.u32 p, n, 4194304;\n@p bra LW;\ntrap;\nLD:\n}\n" :: "r"(bar), "r"(parity) : "memory");
}
__device__ __forceinline__ void mbar_wait_all(uint32_t bar, uint32_t parity) {
  asm volatile("{\n.reg .pred p, q;\nLW:\nmbarrier.try_wait.parity.shared::cta.b64 p, [%0], %1;\nvote.sync.all.pred q, p, 0xffffffff;\n@!q bra.uni LW;\n}\n" :: "r"(bar), "r"(parity) : "memory");
}
__device__ __forceinline__ void cnt_wait(const unsigned* p, unsigned target) {
  asm volatile("{\n.reg .pred p;\n.reg .u32 n, v;\nmov.u32 n, 0;\n"
    "LW:\nld.relaxed.gpu.global.u32 v, [%0];\nsetp.ge.u32 p, v, %1;\n@p bra LD;\n"
    "nanosleep.u32 64;\nadd.u32 n, n, 1;\nsetp.lt.u32 p, n, 4194304;\n@p bra LW;\ntrap;\nLD:\nfence.acquire.gpu;\nfence.proxy.async.global;\n}\n" :: "l"(p), "r"(target) : "memory");
}
__device__ __forceinline__ void cnt_signal(unsigned* p, int lane) {
  __syncwarp();
  if (lane == 0) asm volatile("red.release.gpu.global.add.u32 [%0], 1;" :: "l"(p) : "memory");
}
__device__ __forceinline__ void cnt_publish(unsigned* p, unsigned n, bool fence) {
  if (fence) asm volatile("fence.release.gpu;" ::: "memory");
  asm volatile("red.relaxed.gpu.global.add.u32 [%0], %1;" :: "l"(p), "r"(n) : "memory");
}
__device__ __forceinline__ uint64_t pol_first() { uint64_t p; asm("createpolicy.fractional.L2::evict_first.b64 %0, 1.0;" : "=l"(p)); return p; }
__device__ __forceinline__ void bulk_g2s(uint32_t dst, const void* src, uint32_t bytes, uint32_t bar, bool stream = false) {
  if (stream) asm volatile("cp.async.bulk.shared::cluster.global.mbarrier::complete_tx::bytes.L2::cache_hint [%0], [%1], %2, [%3], %4;" :: "r"(dst), "l"(src), "r"(bytes), "r"(bar), "l"(pol_first()) : "memory");
  else asm volatile("cp.async.bulk.shared::cluster.global.mbarrier::complete_tx::bytes [%0], [%1], %2, [%3];" :: "r"(dst), "l"(src), "r"(bytes), "r"(bar) : "memory");
}
__device__ __forceinline__ void tma2d(uint32_t dst, const CUtensorMap* m, int x, int y, uint32_t bar, bool stream = false) {
  if (stream) asm volatile("cp.async.bulk.tensor.2d.shared::cluster.global.mbarrier::complete_tx::bytes.L2::cache_hint [%0], [%1, {%3, %4}], [%2], %5;" :: "r"(dst), "l"(m), "r"(bar), "r"(x), "r"(y), "l"(pol_first()) : "memory");
  else asm volatile("cp.async.bulk.tensor.2d.shared::cluster.global.mbarrier::complete_tx::bytes [%0], [%1, {%3, %4}], [%2];" :: "r"(dst), "l"(m), "r"(bar), "r"(x), "r"(y) : "memory");
}
__device__ __forceinline__ void tma3d(uint32_t dst, const CUtensorMap* m, int x, int y, int z, uint32_t bar, bool stream = false) {
  if (stream) asm volatile("cp.async.bulk.tensor.3d.shared::cluster.global.mbarrier::complete_tx::bytes.L2::cache_hint [%0], [%1, {%3, %4, %5}], [%2], %6;" :: "r"(dst), "l"(m), "r"(bar), "r"(x), "r"(y), "r"(z), "l"(pol_first()) : "memory");
  else asm volatile("cp.async.bulk.tensor.3d.shared::cluster.global.mbarrier::complete_tx::bytes [%0], [%1, {%3, %4, %5}], [%2];" :: "r"(dst), "l"(m), "r"(bar), "r"(x), "r"(y), "r"(z) : "memory");
}
__device__ __forceinline__ void tma4d(uint32_t dst, const CUtensorMap* m, int x, int y, int z, int w, uint32_t bar, bool stream = false) {
  if (stream) asm volatile("cp.async.bulk.tensor.4d.shared::cluster.global.mbarrier::complete_tx::bytes.L2::cache_hint [%0], [%1, {%3, %4, %5, %6}], [%2], %7;" :: "r"(dst), "l"(m), "r"(bar), "r"(x), "r"(y), "r"(z), "r"(w), "l"(pol_first()) : "memory");
  else asm volatile("cp.async.bulk.tensor.4d.shared::cluster.global.mbarrier::complete_tx::bytes [%0], [%1, {%3, %4, %5, %6}], [%2];" :: "r"(dst), "l"(m), "r"(bar), "r"(x), "r"(y), "r"(z), "r"(w) : "memory");
}
__device__ __forceinline__ void bulk_g2s_mc(uint32_t dst, const void* src, uint32_t bytes, uint32_t bar, bool stream = false) {
  if (stream) asm volatile("cp.async.bulk.shared::cluster.global.mbarrier::complete_tx::bytes.multicast::cluster.L2::cache_hint [%0], [%1], %2, [%3], %4, %5;" :: "r"(dst), "l"(src), "r"(bytes), "r"(bar), "h"((uint16_t)3), "l"(pol_first()) : "memory");
  else asm volatile("cp.async.bulk.shared::cluster.global.mbarrier::complete_tx::bytes.multicast::cluster [%0], [%1], %2, [%3], %4;" :: "r"(dst), "l"(src), "r"(bytes), "r"(bar), "h"((uint16_t)3) : "memory");
}
__device__ __forceinline__ void tma2d_mc(uint32_t dst, const CUtensorMap* m, int x, int y, uint32_t bar, bool stream = false) {
  if (stream) asm volatile("cp.async.bulk.tensor.2d.shared::cluster.global.mbarrier::complete_tx::bytes.multicast::cluster.L2::cache_hint [%0], [%1, {%3, %4}], [%2], %5, %6;" :: "r"(dst), "l"(m), "r"(bar), "r"(x), "r"(y), "h"((uint16_t)3), "l"(pol_first()) : "memory");
  else asm volatile("cp.async.bulk.tensor.2d.shared::cluster.global.mbarrier::complete_tx::bytes.multicast::cluster [%0], [%1, {%3, %4}], [%2], %5;" :: "r"(dst), "l"(m), "r"(bar), "r"(x), "r"(y), "h"((uint16_t)3) : "memory");
}
__device__ __forceinline__ void tma3d_mc(uint32_t dst, const CUtensorMap* m, int x, int y, int z, uint32_t bar, bool stream = false) {
  if (stream) asm volatile("cp.async.bulk.tensor.3d.shared::cluster.global.mbarrier::complete_tx::bytes.multicast::cluster.L2::cache_hint [%0], [%1, {%3, %4, %5}], [%2], %6, %7;" :: "r"(dst), "l"(m), "r"(bar), "r"(x), "r"(y), "r"(z), "h"((uint16_t)3), "l"(pol_first()) : "memory");
  else asm volatile("cp.async.bulk.tensor.3d.shared::cluster.global.mbarrier::complete_tx::bytes.multicast::cluster [%0], [%1, {%3, %4, %5}], [%2], %6;" :: "r"(dst), "l"(m), "r"(bar), "r"(x), "r"(y), "r"(z), "h"((uint16_t)3) : "memory");
}
__device__ __forceinline__ void pf3d(const CUtensorMap* m, int x, int y, int z) {
  asm volatile("cp.async.bulk.prefetch.tensor.3d.L2.global [%0, {%1, %2, %3}];" :: "l"(m), "r"(x), "r"(y), "r"(z) : "memory");
}
__device__ __forceinline__ void pf_bulk(const void* p, uint32_t bytes) { asm volatile("cp.async.bulk.prefetch.L2.global [%0], %1;" :: "l"(p), "r"(bytes) : "memory"); }
__device__ __forceinline__ void tma2d_store(const CUtensorMap* m, uint32_t src, int x, int y) {
  if (POL(12)) asm volatile("cp.async.bulk.tensor.2d.global.shared::cta.bulk_group.L2::cache_hint [%0, {%2, %3}], [%1], %4;" :: "l"(m), "r"(src), "r"(x), "r"(y), "l"(pol_first()) : "memory");
  else asm volatile("cp.async.bulk.tensor.2d.global.shared::cta.bulk_group [%0, {%2, %3}], [%1];" :: "l"(m), "r"(src), "r"(x), "r"(y) : "memory");
}
__device__ __forceinline__ bool elect() {
  uint32_t r; asm volatile("{\n.reg .pred p;\nelect.sync _|p, 0xffffffff;\nselp.u32 %0, 1, 0, p;\n}\n" : "=r"(r)); return r != 0;
}
__device__ __forceinline__ void cluster_arrive() { asm volatile("barrier.cluster.arrive;" ::: "memory"); }
__device__ __forceinline__ void cluster_wait() { asm volatile("barrier.cluster.wait;" ::: "memory"); }
__device__ __forceinline__ void bar_sync(int id, int n) { asm volatile("bar.sync %0, %1;" :: "r"(id), "r"(n) : "memory"); }
__device__ __forceinline__ void bar_arrive(int id, int n) { asm volatile("bar.arrive %0, %1;" :: "r"(id), "r"(n) : "memory"); }
__device__ __forceinline__ int bar_and(int id, int n, int pred) {
  int r; asm volatile("{\n.reg .pred p, q;\nsetp.ne.b32 p, %3, 0;\nbar.red.and.pred q, %1, %2, p;\nselp.b32 %0, 1, 0, q;\n}\n" : "=r"(r) : "r"(id), "r"(n), "r"(pred) : "memory");
  return r;
}
__device__ __forceinline__ void fence_async_smem() { asm volatile("fence.proxy.async.shared::cta;" ::: "memory"); }
__device__ __forceinline__ float ex2(float x) { float y; asm("ex2.approx.ftz.f32 %0, %1;" : "=f"(y) : "f"(x)); return y; }
__device__ __forceinline__ float rcp(float x) { float y; asm("rcp.approx.ftz.f32 %0, %1;" : "=f"(y) : "f"(x)); return y; }
__device__ __forceinline__ uint32_t pack_bf16(float lo, float hi) { uint32_t r; asm("cvt.rn.bf16x2.f32 %0, %1, %2;" : "=r"(r) : "f"(hi), "f"(lo)); return r; }
__device__ __forceinline__ uint32_t hmul2(uint32_t a, uint32_t b) { uint32_t r; asm("mul.rn.bf16x2 %0, %1, %2;" : "=r"(r) : "r"(a), "r"(b)); return r; }
__device__ __forceinline__ uint32_t hadd2(uint32_t a, uint32_t b) { uint32_t r; asm("add.rn.bf16x2 %0, %1, %2;" : "=r"(r) : "r"(a), "r"(b)); return r; }
__device__ __forceinline__ uint32_t hfma2(uint32_t a, uint32_t b, uint32_t c) { uint32_t r; asm("fma.rn.bf16x2 %0, %1, %2, %3;" : "=r"(r) : "r"(a), "r"(b), "r"(c)); return r; }
__device__ __forceinline__ float bf_lo(uint32_t a) { return __uint_as_float(a << 16); }
__device__ __forceinline__ float bf_hi(uint32_t a) { return __uint_as_float(a & 0xffff0000u); }
__device__ __forceinline__ uint32_t lds32(uint32_t a) { uint32_t v; asm volatile("ld.shared.u32 %0, [%1];" : "=r"(v) : "r"(a) : "memory"); return v; }
__device__ __forceinline__ float2 lds64f(uint32_t a) { float2 v; asm volatile("ld.shared.v2.f32 {%0,%1}, [%2];" : "=f"(v.x), "=f"(v.y) : "r"(a) : "memory"); return v; }
__device__ __forceinline__ uint4 lds128(uint32_t a) { uint4 v; asm volatile("ld.shared.v4.u32 {%0,%1,%2,%3}, [%4];" : "=r"(v.x), "=r"(v.y), "=r"(v.z), "=r"(v.w) : "r"(a) : "memory"); return v; }
__device__ __forceinline__ void sts64f(uint32_t a, float x, float y) { asm volatile("st.shared.v2.f32 [%0], {%1,%2};" :: "r"(a), "f"(x), "f"(y) : "memory"); }
__device__ __forceinline__ void sts128(uint32_t a, uint4 v) { asm volatile("st.shared.v4.u32 [%0], {%1,%2,%3,%4};" :: "r"(a), "r"(v.x), "r"(v.y), "r"(v.z), "r"(v.w) : "memory"); }
template<int OFF> __device__ __forceinline__ void sts128o(uint32_t a, uint4 v) { asm volatile("st.shared.v4.u32 [%0+%5], {%1,%2,%3,%4};" :: "r"(a), "r"(v.x), "r"(v.y), "r"(v.z), "r"(v.w), "n"(OFF) : "memory"); }
__device__ __forceinline__ void ldsm4(uint32_t a, uint32_t& r0, uint32_t& r1, uint32_t& r2, uint32_t& r3) {
  asm volatile("ldmatrix.sync.aligned.m8n8.x4.shared.b16 {%0,%1,%2,%3}, [%4];" : "=r"(r0), "=r"(r1), "=r"(r2), "=r"(r3) : "r"(a) : "memory");
}
__device__ __forceinline__ void ldsm4t(uint32_t a, uint32_t& r0, uint32_t& r1, uint32_t& r2, uint32_t& r3) {
  asm volatile("ldmatrix.sync.aligned.m8n8.x4.trans.shared.b16 {%0,%1,%2,%3}, [%4];" : "=r"(r0), "=r"(r1), "=r"(r2), "=r"(r3) : "r"(a) : "memory");
}
__device__ __forceinline__ void stsm4(uint32_t a, uint32_t r0, uint32_t r1, uint32_t r2, uint32_t r3) {
  asm volatile("stmatrix.sync.aligned.m8n8.x4.shared.b16 [%0], {%1,%2,%3,%4};" :: "r"(a), "r"(r0), "r"(r1), "r"(r2), "r"(r3) : "memory");
}
template<int N> __device__ __forceinline__ void fence_regs(float (&d)[N]) {
#pragma unroll
  for (int i = 0; i < N; i++) asm volatile("" : "+f"(d[i]) :: "memory");
}
template<int N> __device__ __forceinline__ void fence_regs(uint32_t (&d)[N]) {
#pragma unroll
  for (int i = 0; i < N; i++) asm volatile("" : "+r"(d[i]) :: "memory");
}
__device__ __forceinline__ void sched_fence(float x, uint32_t dummy) {
  asm volatile("{\n.reg .pred p;\nsetp.eq.u32 p, %0, 0x7fc12345;\n@p st.shared.u32 [%1], %0;\n}\n" :: "r"(__float_as_uint(x)), "r"(dummy) : "memory");
}
#define ROT 0
#define CTAID blockIdx.x
#define PTRACE 0
#define TS(role, i)
#define TSA(i)
#define TS2(role, i)
#define TR(obj, role, tag)

#define SHADOW if (gridDim.y == 1)

struct Prod {
  uint32_t base, mask; int lane, nt;
  __device__ __forceinline__ uint32_t full(int u) const { return base + SM_BAR + 8 * u; }
  __device__ __forceinline__ uint32_t addr(int u) const { return base + u * UNIT; }
  __device__ __forceinline__ void acquire(int u, int n) {
    const int v = u + min(lane, n - 1);
    mbar_wait_all(base + SM_BAR + 128 + 8 * v, mask >> v);
    mask ^= ((1u << n) - 1) << u;
    TR(*this, 2, 16 + u);
  }
  __device__ __forceinline__ void acquire_slow(int u, int n) {
    for (int i = 0; i < n; i++) mbar_wait_slow(base + SM_BAR + 128 + 8 * (u + i), mask >> (u + i));
    mask ^= ((1u << n) - 1) << u;
  }
};
struct Cons {
  uint32_t base, rel, mask; int lane, warp, wg, nt;
  __device__ __forceinline__ uint32_t addr(int u) const { return base + u * UNIT; }
  __device__ __forceinline__ static uint32_t daddr(int u) { return SMEM_BASE + u * UNIT; }
  __device__ __forceinline__ void wait(int u) { TR(*this, wg, 1); mbar_wait(base + SM_BAR + 8 * u, mask >> u); mask ^= 1u << u; TR(*this, wg, 2); }
  __device__ __forceinline__ void skip(int u) { mask ^= 1u << u; }
  __device__ __forceinline__ void release(int u, int n) {
    TR(*this, wg, 5);
    asm volatile("{\n.reg .pred p;\nsetp.lt.s32 p, %1, %2;\n@p mbarrier.arrive.shared::cluster.b64 _, [%0];\n}\n" :: "r"(rel + 8 * u), "r"(lane & 15), "r"(n) : "memory");
  }
  __device__ __forceinline__ void release2(int u) {
    asm volatile("{\n.reg .pred p;\nsetp.eq.s32 p, %1, 0;\n@p mbarrier.arrive.shared::cluster.b64 _, [%0], 2;\n}\n" :: "r"(rel + 8 * u), "r"(lane & 15) : "memory");
  }
  __device__ __forceinline__ void signal(int i) {
    __syncwarp();
    asm volatile("{\n.reg .pred p;\nsetp.eq.s32 p, %1, 0;\n@p mbarrier.arrive.shared::cta.b64 _, [%0];\n}\n" :: "r"(base + SM_SIG + 8 * i), "r"(lane) : "memory");
  }
  __device__ __forceinline__ void turn() { asm volatile("{\n.reg .pred p;\nsetp.eq.s32 p, %0, 0;\n@p bar.sync 1, 256;\n@!p bar.sync 2, 256;\n}\n" :: "r"(wg) : "memory"); TR(*this, wg, 3); }
  __device__ __forceinline__ void pass() { asm volatile("{\n.reg .pred p;\nsetp.eq.s32 p, %0, 0;\n@p bar.arrive 2, 256;\n@!p bar.arrive 1, 256;\n}\n" :: "r"(wg) : "memory"); TR(*this, wg, 4); }
  __device__ __forceinline__ void sync() { asm volatile("{\n.reg .pred p;\nsetp.eq.s32 p, %0, 0;\n@p bar.sync 3, 128;\n@!p bar.sync 4, 128;\n}\n" :: "r"(wg) : "memory"); }
};
__device__ __forceinline__ int gemm_unit(int ks) { return 3 * (ks & 3); }
template<int MASK> __device__ __forceinline__ int kv_slot(int h) { return MASK == PH_ALL ? h & 15 : h; }
__device__ __forceinline__ int out_mb(int cta) { return cta >> 3; }
__device__ __forceinline__ int out_nb(int cta) { return cta & 7; }
template<int MASK> constexpr int CV_REG = MASK == PH_ALL ? CONV_REG : 6;
template<int MASK> constexpr int CV_EXTRA = (1024 - NREG * CV_REG<MASK>) / (NCTA - NREG);
template<int MASK> __device__ __forceinline__ int conv_channel(int cta, int i) {
  return cta < NREG ? CV_EXTRA<MASK> * (NCTA - NREG) + cta * CV_REG<MASK> + i : (i >> 1) * 8 + (cta - NREG) * 2 + (i & 1);
}

template<int OFF, int N> __device__ __forceinline__ void pack_chunk(const float (&a)[N], float sc0, float sc1, uint4& v0, uint4& v1) {
  v0.x = pack_bf16(a[OFF + 0] * sc0, a[OFF + 1] * sc0); v0.y = pack_bf16(a[OFF + 4] * sc0, a[OFF + 5] * sc0);
  v0.z = pack_bf16(a[OFF + 8] * sc0, a[OFF + 9] * sc0); v0.w = pack_bf16(a[OFF + 12] * sc0, a[OFF + 13] * sc0);
  v1.x = pack_bf16(a[OFF + 2] * sc1, a[OFF + 3] * sc1); v1.y = pack_bf16(a[OFF + 6] * sc1, a[OFF + 7] * sc1);
  v1.z = pack_bf16(a[OFF + 10] * sc1, a[OFF + 11] * sc1); v1.w = pack_bf16(a[OFF + 14] * sc1, a[OFF + 15] * sc1);
}
template<int OFF, int N> __device__ __forceinline__ void pack_chunk(const float (&a)[N], uint4& v0, uint4& v1) {
  v0.x = pack_bf16(a[OFF + 0], a[OFF + 1]); v0.y = pack_bf16(a[OFF + 4], a[OFF + 5]);
  v0.z = pack_bf16(a[OFF + 8], a[OFF + 9]); v0.w = pack_bf16(a[OFF + 12], a[OFF + 13]);
  v1.x = pack_bf16(a[OFF + 2], a[OFF + 3]); v1.y = pack_bf16(a[OFF + 6], a[OFF + 7]);
  v1.z = pack_bf16(a[OFF + 10], a[OFF + 11]); v1.w = pack_bf16(a[OFF + 14], a[OFF + 15]);
}
__device__ __forceinline__ void sq_acc(const uint4& v, uint32_t& a) { a = hfma2(v.x, v.x, a); a = hfma2(v.y, v.y, a); a = hfma2(v.z, v.z, a); a = hfma2(v.w, v.w, a); }
__device__ __forceinline__ float norm2_max(uint32_t a0, uint32_t a1) {
  float n0 = bf_lo(a0) + bf_hi(a0), n1 = bf_lo(a1) + bf_hi(a1);
  n0 += __shfl_xor_sync(~0u, n0, 1); n1 += __shfl_xor_sync(~0u, n1, 1);
  n0 += __shfl_xor_sync(~0u, n0, 2); n1 += __shfl_xor_sync(~0u, n1, 2);
  return __uint_as_float(__reduce_max_sync(~0u, max(__float_as_uint(n0) & 0x7fffffffu, __float_as_uint(n1) & 0x7fffffffu)));
}

struct Pend { uint4 lo[8], hi[8]; uint32_t dst; float kn; };
__device__ __forceinline__ void pin(uint4 (&v)[8]) {
#pragma unroll
  for (int i = 0; i < 8; i++) asm volatile("" : "+r"(v[i].x), "+r"(v[i].y), "+r"(v[i].z), "+r"(v[i].w) :: "memory");
}
__device__ __forceinline__ void pack_o(const float (&o)[64], float i0, float i1, uint4 (&v)[8]) {
  pack_chunk<0>(o, i0, i1, v[0], v[1]); pack_chunk<16>(o, i0, i1, v[2], v[3]);
  pack_chunk<32>(o, i0, i1, v[4], v[5]); pack_chunk<48>(o, i0, i1, v[6], v[7]);
  pin(v);
}
__device__ __forceinline__ uint32_t atom_off(int lane) { return (lane >> 2) * 64 + (((lane ^ (lane >> 3)) & 3) << 4); }
__device__ __forceinline__ void stg128(void* p, const uint4& v, bool stream) {
  if (stream) asm volatile("st.global.L2::cache_hint.v4.u32 [%0], {%1,%2,%3,%4}, %5;" :: "l"(p), "r"(v.x), "r"(v.y), "r"(v.z), "r"(v.w), "l"(pol_first()) : "memory");
  else *(uint4*)p = v;
}
template<int J0, int J1, bool STREAM = false> __device__ __forceinline__ void tile_store(const uint4 (&v)[8], uint32_t dst, int lane) {
  uint8_t* d = g_T + (dst + atom_off(lane));
#pragma unroll
  for (int j = J0; j < J1; j++) { stg128(d + j * 512, v[2 * j], STREAM); stg128(d + j * 512 + 2048, v[2 * j + 1], STREAM); }
}
template<int I0, int I1> __device__ __forceinline__ void tile_store_if(bool on, const uint4 (&v)[8], const uint8_t* dst) {
  if constexpr (I0 < I1) {
    asm volatile("{\n.reg .pred p;\nsetp.ne.b32 p, %5, 0;\n@p st.v4.u32 [%0+%6], {%1,%2,%3,%4};\n}\n"
      :: "l"(dst), "r"(v[I0].x), "r"(v[I0].y), "r"(v[I0].z), "r"(v[I0].w), "r"((int)on), "n"((I0 >> 1) * 512 + (I0 & 1) * 2048) : "memory");
    tile_store_if<I0 + 1, I1>(on, v, dst);
  }
}
__device__ __forceinline__ float tile_norm2(const uint4 (&v)[8]) {
  uint32_t n0 = 0, n1 = 0, n2 = 0, n3 = 0;
#pragma unroll
  for (int j = 0; j < 2; j++) { sq_acc(v[2 * j], n0); sq_acc(v[2 * j + 1], n1); sq_acc(v[2 * j + 4], n2); sq_acc(v[2 * j + 5], n3); }
  return norm2_max(hadd2(n0, n2), hadd2(n1, n3));
}
template<uint64_t SCHED, bool FIRST> __device__ __forceinline__ void out_piece(Cons& c, Pend& w, int ks, bool both) {
  uint8_t* d = g_T + (w.dst + atom_off(c.lane));
#pragma unroll
  for (int i = 0; i < 16; i++) {
    const int at = (SCHED >> (4 * i)) & 15;
    if (FIRST ? at == 0 : (at > 0 && ks == at && (i < 8 || both))) *(uint4*)(d + (i >> 3) * 32768 + ((i >> 1) & 3) * 512 + (i & 1) * 2048) = i < 8 ? w.lo[i & 7] : w.hi[i & 7];
  }
  if (FIRST || !both) return;
  if (ks == NK_AT) w.kn = tile_norm2(w.lo);
  if (ks == NV_AT) {
    const float vn = tile_norm2(w.hi);
    if (c.lane == 0) g_kn2[((w.dst - T_KV) >> 16) * 8 + c.wg * 4 + c.warp] = (vn <= 1.0e20f && vn >= 1.0e-20f) ? w.kn : __uint_as_float(0x7f800000u);
  }
}
template<bool FIRST> __device__ __forceinline__ void kv_issue(Cons& c, float (&acc)[128], int ua, int ub) {
  const uint64_t da = odesc(c.daddr(ua) + c.wg * 8192, 16, 1024, 1), db = odesc(c.daddr(ub), 8192, 1024, 1);
  c.turn();
  wg_fence();
#pragma unroll
  for (int kk = 0; kk < 4; kk++) wgmma_ss_n256<1>(acc, da + kk * 2, db + kk * 128, !(FIRST && kk == 0));
  wg_commit();
  c.pass();
}
template<bool NEXT> __device__ __forceinline__ void cons_kv(Cons& c, int h, int hs, int g, Pend& w, bool pend_o) {
#pragma unroll 1
  for (int tile = 0; tile < 2; tile++) {
    float acc[128];
    if (!(NEXT && HOISTW) && tile == 0) c.wait(0);
    if (tile == 0 && h < 16) TS(c.wg, 16);
    const bool early = KVE && pend_o && tile == 0;
    kv_issue<true>(c, acc, early ? 12 : 0, early ? 0 : 1);
    c.release(9, tile == 1 ? 3 : 0);
    if (tile == 1 && pend_o) mbar_wait(c.base + SM_RDY + 8 * RDY_WAR, 0);
    if (tile == 1 || pend_o) out_piece<SCH_KV, true>(c, w, 0, false);
#pragma unroll 1
    for (int ks = 1; ks < 8; ks++) {
      const int u = gemm_unit(ks);
      c.wait(u);
      wg_wait<0>();
      c.release(gemm_unit(ks - 1), early && ks == 1 ? 2 : 3);
      kv_issue<false>(c, acc, u, u + 1);
      if (tile == 1 || pend_o) { out_piece<SCH_KV, false>(c, w, ks, tile); if (ks == ((SCH_KV >> 28) & 15) && tile == 0) c.signal(SIG_CTX); }
    }
    if (NEXT || tile == 0) c.wait(0);
    wg_wait<0>(); fence_regs(acc);
    if (!NEXT) c.release(9, tile == 1 ? 3 : 0);
    pack_chunk<0>(acc, w.lo[0], w.lo[1]);  pack_chunk<16>(acc, w.lo[2], w.lo[3]); pack_chunk<32>(acc, w.lo[4], w.lo[5]); pack_chunk<48>(acc, w.lo[6], w.lo[7]);
    pack_chunk<64>(acc, w.hi[0], w.hi[1]); pack_chunk<80>(acc, w.hi[2], w.hi[3]); pack_chunk<96>(acc, w.hi[4], w.hi[5]); pack_chunk<112>(acc, w.hi[6], w.hi[7]);
    pin(w.lo); pin(w.hi);
    w.dst = T_KV + (hs * 16 + 2 * g + tile) * 65536 + (c.wg * 4 + c.warp) * 4096;
  }
}
template<bool FIRST> __device__ __forceinline__ void q_issue(Cons& c, float (&a)[64], float (&b)[64], int u) {
  const uint64_t da = odesc(c.daddr(u) + c.wg * 8192, 16, 1024, 1), db = odesc(c.daddr(u + 2), 8192, 1024, 1);
  const uint64_t da2 = odesc(c.daddr(u + 1) + (1 - c.wg) * 8192, 16, 1024, 1);
  c.turn();
  wg_fence();
#pragma unroll
  for (int kk = 0; kk < 4; kk++) wgmma_ss_n128<1>(a, da + kk * 2, db + kk * 128, !(FIRST && kk == 0));
#pragma unroll
  for (int kk = 0; kk < 4; kk++) wgmma_ss_n128<1>(b, da2 + kk * 2, db + kk * 128, !(FIRST && kk == 0));
  wg_commit();
  c.pass();
}
__device__ __forceinline__ void q_step(Cons& c, float (&d)[64], int ua, int ub, int rowhalf) {
  const uint64_t da = odesc(c.daddr(ua) + rowhalf * 8192, 16, 1024, 1), db = odesc(c.daddr(ub), 8192, 1024, 1);
#pragma unroll
  for (int kk = 0; kk < 4; kk++) wgmma_ss_n128<1>(d, da + kk * 2, db + kk * 128, 1);
}
template<bool PEND_KV> __device__ __forceinline__ void cons_q(Cons& c, int h, Pend& w, float (&b)[64]) {
  float a[64];
  if (!PEND_KV) c.wait(0);
  q_issue<true>(c, a, b, 0);
  if (PEND_KV) { c.release(9, 3); out_piece<SCH_Q, true>(c, w, 0, true); }
#pragma unroll 1
  for (int ks = 1; ks < 14; ks++) {
    const int u = gemm_unit(ks);
    c.wait(u);
    wg_wait<0>();
    c.release(gemm_unit(ks - 1), 3);
    q_issue<false>(c, a, b, u);
    if (PEND_KV && ks <= (int)(SCH_Q >> 60)) { out_piece<SCH_Q, false>(c, w, ks, true); if (ks == (int)(SCH_Q >> 60)) c.signal(SIG_KV + (h >> 4)); }
  }
  c.wait(6); c.wait(9);
  wg_wait<0>();
  c.release(3, 3);
  c.turn();
  wg_fence();
  q_step(c, a, 6, 8, c.wg); q_step(c, a, 9, 11, c.wg); wg_commit();
  q_step(c, b, 7, 8, 1 - c.wg); wg_commit();
  c.pass();
  c.wait(0);
  const uint32_t q0 = c.addr(0) + (c.wg * 4 + c.warp) * 4096 + atom_off(c.lane);
  wg_wait<1>(); fence_regs(a);
  pack_o(a, QSCALE, QSCALE, w.lo);
  sts128o<0>(q0, w.lo[0]);    sts128o<2048>(q0, w.lo[1]); sts128o<512>(q0, w.lo[2]);  sts128o<2560>(q0, w.lo[3]);
  wg_wait<0>();
  c.release(6, 4);
  sts128o<1024>(q0, w.lo[4]); sts128o<3072>(q0, w.lo[5]); sts128o<1536>(q0, w.lo[6]); sts128o<3584>(q0, w.lo[7]);
  c.wait(12);
  fence_async_smem();
}

__device__ __forceinline__ void issue_qk(float (&s)[64], uint64_t da, uint64_t db) {
#pragma unroll
  for (int kk = 0; kk < 8; kk++) wgmma_ss_n128<0>(s, da + (kk >> 1) * 32 + (kk & 1) * 2, db + (kk >> 1) * 32 + (kk & 1) * 2, kk > 0);
  wg_commit();
}
template<int A, int B> __device__ __forceinline__ void exp_rng(float (&s)[64]) {
#pragma unroll
  for (int i = 4 * A; i < 4 * B; i++) s[i] = ex2(s[i]);
}
template<int A, int B> __device__ __forceinline__ void sum_rng(const float (&s)[64], float (&l)[4]) {
#pragma unroll
  for (int i = A; i < B; i++) { l[0] += s[4 * i]; l[1] += s[4 * i + 1]; l[2] += s[4 * i + 2]; l[3] += s[4 * i + 3]; }
}
template<int A, int B> __device__ __forceinline__ void cvt_p(const float (&s)[64], uint32_t (&p)[32]) {
#pragma unroll
  for (int i = 2 * A; i < 2 * B; i++) p[i] = pack_bf16(s[2 * i], s[2 * i + 1]);
}
template<int K0> __device__ __forceinline__ void mask_half(float (&s)[64], int warp, int lane) {
  const int l0 = warp + (2 * (lane & 3) <= (lane >> 2)), l1 = warp + (2 * (lane & 3) < (lane >> 2));
#pragma unroll
  for (int k = 0; k < 4; k++) {
    float* t = s + 8 * (K0 + k);
    if (k >= l0) { t[0] = -INFINITY; t[6] = -INFINITY; }
    if (k >= l1) { t[1] = -INFINITY; t[7] = -INFINITY; }
    if (k > warp) { t[2] = -INFINITY; t[3] = -INFINITY; }
    if (k >= warp) { t[4] = -INFINITY; t[5] = -INFINITY; }
  }
}
__device__ __forceinline__ void row_inv(float& l0, float& l1) {
  l0 += __shfl_xor_sync(~0u, l0, 1); l1 += __shfl_xor_sync(~0u, l1, 1);
  l0 += __shfl_xor_sync(~0u, l0, 2); l1 += __shfl_xor_sync(~0u, l1, 2);
  l0 = rcp(l0); l1 = rcp(l1);
}
__device__ __forceinline__ void softmax_safe(float (&s)[64], bool upper_only, float& m0, float& m1, float& sc0, float& sc1) {
  float a0 = m0, a1 = m1;
#pragma unroll
  for (int i = 0; i < 8; i++) { a0 = fmaxf(a0, fmaxf(s[4 * i], s[4 * i + 1])); a1 = fmaxf(a1, fmaxf(s[4 * i + 2], s[4 * i + 3])); }
  if (upper_only) { a0 = m0; a1 = m1; }
#pragma unroll
  for (int i = 8; i < 16; i++) { a0 = fmaxf(a0, fmaxf(s[4 * i], s[4 * i + 1])); a1 = fmaxf(a1, fmaxf(s[4 * i + 2], s[4 * i + 3])); }
  a0 = fmaxf(a0, __shfl_xor_sync(~0u, a0, 1)); a1 = fmaxf(a1, __shfl_xor_sync(~0u, a1, 1));
  a0 = fmaxf(a0, __shfl_xor_sync(~0u, a0, 2)); a1 = fmaxf(a1, __shfl_xor_sync(~0u, a1, 2));
  sc0 = ex2(m0 - a0); sc1 = ex2(m1 - a1);
  m0 = a0; m1 = a1;
#pragma unroll
  for (int i = 0; i < 16; i++) { s[4 * i] -= a0; s[4 * i + 1] -= a0; s[4 * i + 2] -= a1; s[4 * i + 3] -= a1; }
}
struct Att {
  float s[64], o[64], l[4], i0, i1, t0, t1; uint32_t p[32];
  float kn; uint32_t qaddr; const uint8_t* dst;
};
__device__ __forceinline__ uint32_t ctx_off(const Cons& c, int h, int qb, int rowhalf) { return T_CTX + (qb * 32 + h) * 32768 + (rowhalf * 4 + c.warp) * 4096; }
__device__ __forceinline__ int att_fast(const uint4 (&q)[8], float kn) {
  uint32_t a0 = 0, a1 = 0, a2 = 0, a3 = 0;
#pragma unroll
  for (int j = 0; j < 2; j++) { sq_acc(q[2 * j], a0); sq_acc(q[2 * j + 1], a1); sq_acc(q[2 * j + 4], a2); sq_acc(q[2 * j + 5], a3); }
  a0 = hadd2(a0, a2); a1 = hadd2(a1, a3);
  return __shfl_sync(~0u, __all_sync(~0u, (bf_lo(a0) + bf_hi(a0)) * kn <= 0.25f * BOUND2 && (bf_lo(a1) + bf_hi(a1)) * kn <= 0.25f * BOUND2), 0);
}
__device__ __forceinline__ int att_first(Cons& c, Att& a, int h, const Pend& w) {
  a.kn = __uint_as_float(lds32(c.base + SM_KMAX + 4 * (h >> 4)));
  a.qaddr = c.daddr(0) + c.wg * 16384;
  c.turn();
  wg_fence();
  issue_qk(a.s, odesc(a.qaddr, 16, 2048, 2), odesc(c.daddr(DFIRST ? 11 + c.wg : 12), 16, 2048, 2));
  int fast = 0;
  SHADOW fast = att_fast(w.lo, a.kn);
  wg_fence();
  q_step(c, a.o, 10, 11, 1 - c.wg); wg_commit();
  c.pass();
#pragma unroll
  for (int i = 0; i < 8; i++) { a.p[4 * i] = w.lo[i].x; a.p[4 * i + 1] = w.lo[i].y; a.p[4 * i + 2] = w.lo[i].z; a.p[4 * i + 3] = w.lo[i].w; }
  a.l[0] = a.l[1] = a.l[2] = a.l[3] = 0.f; a.i0 = a.i1 = a.t0 = a.t1 = 0.25f / QSCALE;
  a.dst = (const uint8_t*)__cvta_shared_to_generic(c.addr(2) + (c.wg * 4 + c.warp) * 4096 + atom_off(c.lane));
  wg_wait<1>(); fence_regs(a.s);
  c.signal(SIG_ATT + (h >> 4));
  return fast;
}
template<bool NEXT> __device__ __forceinline__ void att_last(Cons& c, Att& a, Pend& w, int h, int g, bool drain) {
  const int uv = 6;
  if (drain) pack_o(a.o, rcp(a.i0), rcp(a.i1), w.hi);
  c.wait(uv);
  c.turn();
  fence_regs(a.o); fence_regs(a.p);
  wgmma_pv_sel(a.o, a.p, odesc(c.daddr(uv), 512, 2048, 2), c.wg == 0, !drain, c.wg);
  a.i0 = a.l[0] + a.l[1]; a.i1 = a.l[2] + a.l[3];
  SHADOW row_inv(a.i0, a.i1);
  sched_fence(a.i0 + a.i1, c.base + SM_DUMMY);
  tile_store_if<0, 4>(drain, w.hi, a.dst);
  if (NEXT && HOISTW) c.wait(h < 16 ? 0 : 12);
  wg_wait<0>(); fence_regs(a.o); fence_regs(a.p);
  c.release(uv, 2);
  tile_store_if<4, 8>(drain, w.hi, a.dst);
  pack_o(a.o, a.i0, a.i1, w.lo);
  w.dst = ctx_off(c, h, g, 1 - c.wg); w.kn = 0.f;
}
template<bool NEXT> __device__ __forceinline__ void cons_att(Cons& c, Att& a, int h, int g, Pend& w) {
  int fast = att_first(c, a, h, w), fast2 = 0;
  float m0 = -INFINITY, m1 = -INFINITY, sc0 = 0.f, sc1 = 0.f;
  int uk = 10, nrel = 0;
  bool fresh = false;
  const int e = 15 - g, sd = DFIRST ? 0 : e, slo = c.wg ? 16 : sd;
#pragma unroll 1
  for (int s = 0;;) {
    const bool lo = s == slo;
    if (s == sd || s == 16 || !fast) {
      if (s == sd || s == 16) {
        mask_half<4>(a.s, c.warp, c.lane);
        if (DFIRST && s == 0) { sched_fence(a.s[63], c.base + SM_DUMMY); wg_wait<0>(); c.release(10, 2); }
      }
      if (!fast) {
        if (s == e + 1) m0 = m1 = -INFINITY;
        softmax_safe(a.s, lo, m0, m1, sc0, sc1);
        a.l[0] *= sc0; a.l[1] *= sc0; a.l[2] *= sc1; a.l[3] *= sc1;
      }
    }
    exp_rng<8, 16>(a.s); sum_rng<8, 16>(a.s, a.l);
    exp_rng<ATT_SPLIT, 8>(a.s);
    sched_fence(((a.l[0] + a.l[1]) + (a.l[2] + a.l[3])) + (ATT_SPLIT < 8 ? a.s[4 * ATT_SPLIT + 3] : 0.f), c.base + SM_DUMMY);
    wg_wait<0>(); fence_regs(a.o); fence_regs(a.p);
    if (DFIRST) c.release(uk - 2, nrel); else c.release(uk - nrel, 2);
    a.i0 += a.t0; a.i1 += a.t1;
    a.t0 = __shfl_xor_sync(~0u, a.i0, 2); a.t1 = __shfl_xor_sync(~0u, a.i1, 2);
    tile_store_if<0, DS_B>(fresh, w.hi, a.dst);
    nrel = 2; uk ^= 12;
    if (s == e) a.qaddr += 32768;
    const uint64_t dq = odesc(a.qaddr, 16, 2048, 2), dk = odesc(c.daddr(uk) - (s + 1 == slo ? 16384 : 0), 16, 2048, 2), dv = odesc(c.daddr(uk - 2), 512, 2048, 2);
    if (!lo) { exp_rng<0, ATT_SPLIT>(a.s); sum_rng<0, 8>(a.s, a.l); cvt_p<0, 16>(a.s, a.p); }
    else if (gridDim.y == 1) cvt_p<8, 16>(a.s, a.p);
    tile_store_if<DS_B, 8>(fresh, w.hi, a.dst);
    a.i0 += a.t0; a.i1 += a.t1;
    if (!fast || s == 16 || s == e || (unsigned)(s - CHK_S) < 2) {
      if (s == CHK_S) fast2 = att_fast(w.hi, a.kn);
      if (s == CHK_S + 1) fence_async_smem();
      if (!fast && s != e + 1 && s != 0) {
#pragma unroll
        for (int i = 0; i < 16; i++) { a.o[4 * i] *= sc0; a.o[4 * i + 1] *= sc0; a.o[4 * i + 2] *= sc1; a.o[4 * i + 3] *= sc1; }
      }
      if (s == e) {
        a.i0 = a.l[0] + a.l[1]; a.i1 = a.l[2] + a.l[3];
        a.l[0] = a.l[1] = a.l[2] = a.l[3] = 0.f;
        uint32_t off = ctx_off(c, h, e, c.wg);
        asm volatile("" : "+r"(off));
        a.dst = g_T + (off + ((uint32_t)(uint64_t)a.dst & 511));
        fast = fast2;
      }
      if (s == 16) break;
    }
    fresh = s == 0 || s == e + 1;
    s++;
    if (c.wg == 0) c.wait(uk); else c.skip(uk);
    c.turn();
    fence_regs(a.o); fence_regs(a.p);
    wg_fence();
    issue_qk(a.s, dq, dk);
    a.t0 = __shfl_xor_sync(~0u, a.i0, 1); a.t1 = __shfl_xor_sync(~0u, a.i1, 1);
    if (fresh) pack_o(a.o, rcp(a.i0), rcp(a.i1), w.hi);
    wgmma_pv_sel(a.o, a.p, dv, !lo, !fresh, c.wg);
    wg_wait<1>(); fence_regs(a.s);
    c.release(uk, 2);
    c.release(s == e ? 0 : 2, (s == e || s == 16) ? 2 : 0);
  }
  att_last<NEXT>(c, a, w, h, g, g == 0);
}

constexpr int CV_H = 1024, CV_U = 5120, CV_D = CV_U + 4128, CV_ROW = 1056;
template<int OFF> __device__ __forceinline__ uint32_t lds32o(uint32_t a) { uint32_t v; asm volatile("ld.shared.u32 %0, [%1+%2];" : "=r"(v) : "r"(a), "n"(OFF) : "memory"); return v; }
template<int G, int G1 = 16> __device__ __forceinline__ void conv_lda(uint32_t (&a)[64], uint32_t p) {
  a[4 * G + 0] = lds32o<-256 * G>(p);
  a[4 * G + 1] = lds32o<-256 * G - 128>(p);
  a[4 * G + 2] = lds32o<-256 * G + 16>(p);
  a[4 * G + 3] = lds32o<-256 * G - 112>(p);
  if constexpr (G + 1 < G1) conv_lda<G + 1, G1>(a, p);
}
struct CvAcc { float lo[16], hi[16]; };
__device__ __forceinline__ void fence_regs(CvAcc& d) { fence_regs(d.lo); fence_regs(d.hi); }
template<int R, int H> __device__ __forceinline__ void conv_mma_h(float (&d)[16], const uint32_t (&a)[64], uint64_t db) {
#pragma unroll
  for (int G = 0; G < 4 * R + 2 * H + 2; G++) wgmma_rs_n32<0>(d, a[4 * G], a[4 * G + 1], a[4 * G + 2], a[4 * G + 3], db + 64 * R + 32 * H - 16 * G, G > 0);
}
template<int T, int G0, int G1> __device__ __forceinline__ void conv_part(float (&d)[16], const uint32_t (&a)[64], uint64_t db) {
#pragma unroll
  for (int G = G0; G < G1; G++) wgmma_rs_n32<0>(d, a[4 * G], a[4 * G + 1], a[4 * G + 2], a[4 * G + 3], db + 32 * T - 16 * G, G > 0);
}
template<int R> __device__ __forceinline__ void conv_mma(CvAcc& d, const uint32_t (&a)[64], uint64_t db) { conv_mma_h<R, 0>(d.lo, a, db); conv_mma_h<R, 1>(d.hi, a, db); }
template<int C0> __device__ __forceinline__ void conv_st_h(const float (&d)[16], uint32_t wq, float& c0, float& c1) {
#pragma unroll
  for (int n = 0; n < 4; n++) { sts64f(wq + (C0 + n * 8) * 4, d[4 * n] + c0, d[4 * n + 1] + c1); c0 = d[4 * n + 2]; c1 = d[4 * n + 3]; }
}
template<int R> __device__ __forceinline__ void conv_st(const CvAcc& d, uint32_t wq, float& c0, float& c1) { conv_st_h<64 * R>(d.lo, wq, c0, c1); conv_st_h<64 * R + 32>(d.hi, wq, c0, c1); }
struct ConvTail { float t[64]; uint4 ua, uc; uint32_t D2; };
__device__ __forceinline__ void conv_emit(ConvTail& e, int ch, int tid) {
  fence_regs(e.t);
  float y[16];
#pragma unroll
  for (int i = 0; i < 16; i++) y[i] = (e.t[i] + e.t[16 + i]) + (e.t[32 + i] + e.t[48 + i]);
  uint4 z0, z1;
  z0.x = hadd2(pack_bf16(y[0], y[2]), hmul2(__byte_perm(e.ua.w, 0, 0x1032), e.D2));
  z0.y = hadd2(pack_bf16(y[4], y[6]), hmul2(__byte_perm(e.ua.z, 0, 0x1032), e.D2));
  z0.z = hadd2(pack_bf16(y[8], y[10]), hmul2(__byte_perm(e.ua.y, 0, 0x1032), e.D2));
  z0.w = hadd2(pack_bf16(y[12], y[14]), hmul2(__byte_perm(e.ua.x, 0, 0x1032), e.D2));
  z1.x = hadd2(pack_bf16(y[1], y[3]), hmul2(__byte_perm(e.uc.w, 0, 0x1032), e.D2));
  z1.y = hadd2(pack_bf16(y[5], y[7]), hmul2(__byte_perm(e.uc.z, 0, 0x1032), e.D2));
  z1.z = hadd2(pack_bf16(y[9], y[11]), hmul2(__byte_perm(e.uc.y, 0, 0x1032), e.D2));
  z1.w = hadd2(pack_bf16(y[13], y[15]), hmul2(__byte_perm(e.uc.x, 0, 0x1032), e.D2));
  uint4* zp = (uint4*)(g_z + (uint32_t)(ch * 2048 + tid * 16));
  zp[0] = z0; zp[1] = z1;
}
template<int MASK> __device__ __forceinline__ void cons_conv(Cons& c, int cta, int nch) {
  const int r = c.lane >> 2, q = c.lane & 3, tid = c.warp * 32 + c.lane;
  const uint32_t part = c.addr(4) - 2048 + (1 - c.wg) * (32 * CV_ROW) + 32;
  const uint32_t aoff = CV_U + ((r & 1) ? 0 : UPITCH) + 4 * (((2039 - r) >> 1) + q - 8 * c.warp);
  const uint32_t wq = part + (c.warp * 8 + r) * CV_ROW + q * 8, rq = part + tid * 8;
  uint32_t a[64];
  ConvTail e = {};
  c.wait(c.wg); c.skip(c.wg ^ 1);
  conv_lda<0>(a, c.addr(c.wg) + aoff);
  c.wait(4);
  sts64f(part + (tid >> 2) * CV_ROW - 32 + q * 8, 0.f, 0.f);
#pragma unroll 1
  for (int i = 0; i < nch / 2; i++) {
    const int u = 2 * (i & 1) + c.wg;
    CvAcc d0, d1, d2, d3;
    float c0 = 0.f, c1 = 0.f;
    const uint64_t db = odesc(c.daddr(u) + CV_H - 16, 16, 128, 0);
    c.turn();
    fence_regs(a);
    wg_fence();
    conv_mma<0>(d0, a, db); conv_mma<1>(d1, a, db); wg_commit();
    if (i > 0) {
      conv_emit(e, conv_channel<MASK>(cta, 2 * i - 2 + c.wg), tid);
      if ((i & 15) == 0) c.signal(SIG_Z + (i >> 4) - 1);
    }
    wg_fence();
    conv_mma_h<2, 0>(d2.lo, a, db); wg_commit();
    wg_wait<1>(); fence_regs(d0); fence_regs(d1);
    conv_st_h<0>(d0.lo, wq, c0, c1);
    wg_fence();
    conv_mma_h<2, 1>(d2.hi, a, db); wg_commit();
    conv_st_h<32>(d0.hi, wq, c0, c1);
    conv_mma_h<3, 0>(d3.lo, a, db);
    conv_st_h<64>(d1.lo, wq, c0, c1);
    conv_mma_h<3, 1>(d3.hi, a, db); wg_commit();
    c.pass();
    const int un = i + 1 < nch / 2 ? u ^ 2 : u;
    if (un != u) { c.wait(un); c.skip(un ^ 1); }
    wg_wait<1>(); fence_regs(d2);
    conv_st_h<96>(d1.hi, wq, c0, c1);
    conv_st<2>(d2, wq, c0, c1);
    {
      const int sw = (c.lane >> 2) & 1;
      const uint4 v0 = lds128(c.addr(u) + CV_U + 4064 - 32 * tid + 16 * sw), v1 = lds128(c.addr(u) + CV_U + 4080 - 32 * tid - 16 * sw);
      e.ua = sw ? v0 : v1; e.uc = sw ? v1 : v0;
    }
    e.D2 = lds32(c.addr(u) + CV_D);
    wg_wait<0>(); fence_regs(d3); fence_regs(a);
    conv_st<3>(d3, wq, c0, c1);
    conv_lda<0, 4>(a, c.addr(un) + aoff);
    c.sync();
    sched_fence(__uint_as_float(e.ua.x ^ e.uc.x ^ e.D2), c.base + SM_DUMMY);
    c.release2(u);
    conv_lda<4, 16>(a, c.addr(un) + aoff);
#pragma unroll
    for (int k = 0; k < 32; k++) { const float2 v = lds64f(rq + k * CV_ROW - (k >> 3) * 8); e.t[2 * k] = v.x; e.t[2 * k + 1] = v.y; }
  }
  conv_emit(e, conv_channel<MASK>(cta, nch - 2 + c.wg), tid);
  c.signal(SIG_Z + ((nch / 2 - 1) >> 4));
  c.release(4, 4);
}

constexpr int OC_PART = 13824, OC_ROW = 544;
__device__ __forceinline__ int out_next(int u) { return (0x486ca40u >> (2 * u)) & 15; }
struct Out { float acc[64]; int pu; uint64_t da, db; };
template<bool FIRST, bool REL, int W = 1, bool PRE = true, bool POST = false> __device__ __forceinline__ void out_step(Cons& c, Out& o, bool extra = false) {
  const int pu = o.pu, u = extra ? 2 : out_next(pu);
  o.pu = u;
  if (PRE) c.wait(u);
  const uint64_t da = o.da + (uint32_t)(u * 1024), db = o.db + (uint32_t)(u * 1024);
  wg_fence();
#pragma unroll
  for (int kk = 0; kk < 4; kk++) wgmma_ss_n128<1>(o.acc, da + (kk >> 1) * 32 + (kk & 1) * 2, db + kk * 128, !(FIRST && kk == 0));
  wg_commit();
  if (REL) { wg_wait<W>(); c.release(pu, 2); }
  if (POST) c.wait(out_next(u));
}
template<int I0, int I1> __device__ __forceinline__ void oc_red(float (&y)[8], uint32_t rq) {
#pragma unroll
  for (int i = I0; i < I1; i++) { const float v = __uint_as_float(lds32(rq + i * OC_ROW - (i >> 3) * 8)); y[i & 7] = i < 8 ? v : y[i & 7] + v; }
}
__device__ __forceinline__ void oc_emit(const float (&y)[8], const uint4& u, uint32_t D2, __nv_bfloat16* dst) {
  uint4 z;
  z.x = hadd2(pack_bf16(y[0], y[1]), hmul2(__byte_perm(u.w, 0, 0x1032), D2));
  z.y = hadd2(pack_bf16(y[2], y[3]), hmul2(__byte_perm(u.z, 0, 0x1032), D2));
  z.z = hadd2(pack_bf16(y[4], y[5]), hmul2(__byte_perm(u.y, 0, 0x1032), D2));
  z.w = hadd2(pack_bf16(y[6], y[7]), hmul2(__byte_perm(u.x, 0, 0x1032), D2));
  *(uint4*)dst = z;
}
template<int MASK> __device__ __forceinline__ void cons_out(Cons& c, const Maps& M, const Params& P, int cta, Pend& w) {
  const int mb = out_mb(cta), nb = out_nb(cta);
  Out o;
  o.da = odesc(c.daddr(0) + c.wg * 8192, 16, 1024, 2); o.db = odesc(c.daddr(1), 8192, 1024, 1);
  o.pu = 5 + gridDim.y;
  out_step<true, false, 1, !(HOISTW && MASK == PH_ALL)>(c, o);
  int ks = 1;
#pragma unroll 1
  for (;; ks++) {
    if (MASK & PH_ATT) {
      if (ks == (c.wg ? ST_1 : ST_0)) tile_store<0, 1>(w.lo, w.dst, c.lane);
      if (ks == (c.wg ? ST_1 + ST_D : ST_0 + ST_0D / 2)) tile_store<1, 2>(w.lo, w.dst, c.lane);
      if (ks == (c.wg ? ST_1 + 2 * ST_D : ST_0 + ST_0D)) tile_store<2, 3>(w.lo, w.dst, c.lane);
      if (ks == (c.wg ? ST_1 + 3 * ST_D : ST_0 + 3 * ST_0D / 2)) { tile_store<3, 4>(w.lo, w.dst, c.lane); c.signal(SIG_CTX + 1); }
    }
    if (ks == (c.wg ? OC_S1 : OC_S0)) break;
    out_step<false, true>(c, o, ks == 1);
  }
  if (MASK & PH_CONV) {
    const int r = c.lane >> 2, q = c.lane & 3, tid = c.warp * 32 + c.lane, u = 2 * c.wg;
    const uint32_t ub = c.addr(u), part = ub + OC_PART + 32;
    const uint32_t ap = ub + CV_U + ((r & 1) ? 0 : UPITCH) + 4 * (((2039 - r) >> 1) + q - 8 * c.warp);
    const uint32_t wq = part + (c.warp * 8 + r) * OC_ROW + q * 8, rq = part + tid * 4;
    const int nr = (CV_REG<MASK> + 1 - c.wg) >> 1;
#define STEP(N) out_step<false, true, 1, !OC_POST, OC_POST>(c, o);
#pragma unroll 1
    for (int i = 0; i < nr; i++) {
      uint32_t a[64];
      CvAcc d0, d1;
      float y[8], c0 = 0.f, c1 = 0.f;
      const uint64_t db = odesc(c.daddr(u + (i >> 8)) + CV_H - 16, 16, 128, 0);
#define STEP2(N) out_step<false, true, 2, !OC_POST, OC_POST>(c, o);
#define PART(...) { const uint64_t db = db0 + (c.mask >> 16); wg_fence(); __VA_ARGS__; wg_commit(); }
      const uint64_t db0 = db;
      c.wait(u);
      if (OC_POST) c.wait(out_next(o.pu));
      conv_lda<0, 4>(a, ap);
      STEP(0)
      conv_lda<4, 7>(a, ap);
      PART(conv_part<0, 0, 2>(d0.lo, a, db); conv_part<1, 0, 4>(d0.hi, a, db))
      STEP2(1)
      conv_lda<7, 10>(a, ap);
      PART(conv_part<2, 0, 6>(d1.lo, a, db))
      STEP2(2)
      fence_regs(d0);
      c.sync();
      sts64f(wq - 32, 0.f, 0.f);
      conv_st<0>(d0, wq, c0, c1);
      asm volatile("add.f32 %0, %0, 0f80000000;" : "+f"(c0)); asm volatile("add.f32 %0, %0, 0f80000000;" : "+f"(c1));
      PART(conv_part<3, 0, 8>(d1.hi, a, db))
      STEP2(3)
      wg_wait<1>(); fence_regs(d1);
      float e0 = d1.hi[12] + d1.hi[10], e1 = d1.hi[13] + d1.hi[11];
      conv_st<1>(d1, wq, c0, c1);
      asm volatile("add.f32 %0, %0, 0f80000000;" : "+f"(c0)); asm volatile("add.f32 %0, %0, 0f80000000;" : "+f"(c1));
      PART(conv_part<4, 0, 10>(d0.lo, a, db))
      STEP2(4)
      conv_lda<10, 12>(a, ap);
      c.sync();
      oc_red<0, 6>(y, rq);
      PART(conv_part<5, 0, 9>(d0.hi, a, db))
      STEP2(5)
      conv_lda<12, 14>(a, ap);
      oc_red<6, 12>(y, rq);
      PART(conv_part<5, 9, 12>(d0.hi, a, db); conv_part<6, 0, 6>(d1.lo, a, db))
      STEP2(6)
      oc_red<12, 26>(y, rq);
      PART(conv_part<6, 6, 14>(d1.lo, a, db))
      STEP2(7)
      oc_red<26, 32>(y, rq);
      conv_lda<14, 16>(a, ap);
      PART(conv_part<7, 0, 8>(d1.hi, a, db))
      STEP2(8)
      fence_regs(y); fence_regs(d0);
      c.sync();
      sts64f(wq - 32, e0, e1);
      conv_st<0>(d0, wq, c0, c1);
      PART(conv_part<7, 8, 16>(d1.hi, a, db))
      STEP2(9)
      wg_wait<1>(); fence_regs(d1); fence_regs(a);
      const uint4 u0 = lds128(ub + CV_U + 4080 - 16 * tid), u1 = lds128(ub + CV_U + 2032 - 16 * tid);
      const uint32_t D2 = lds32(ub + CV_D);
      conv_st_h<64>(d1.lo, wq, c0, c1);
      sched_fence(__uint_as_float(u0.x ^ u1.x ^ D2), c.base + SM_DUMMY);
      __syncwarp();
      c.release2(u);
      STEP(10)
      conv_st_h<96>(d1.hi, wq, c0, c1);
      __nv_bfloat16* zp = g_z + (uint32_t)(conv_channel<MASK>(cta, 2 * i + c.wg) * 2048 + (threadIdx.x & 127) * 8);
      oc_emit(y, u0, D2, zp);
      c.sync();
      oc_red<0, 6>(y, rq);
      STEP(11)
      oc_red<6, 19>(y, rq);
      STEP(12)
      oc_red<19, 32>(y, rq);
      oc_emit(y, u1, D2, zp + 1024);
      if (i == nr - 1) { c.signal(SIG_Z); c.release2(u + 1); TS2(c.wg, 8); }
      out_step<false, true, 1, !OC_POST>(c, o);
#pragma unroll 1
      for (int k = 14; k < (c.wg ? OC_L1 : OC_L0); k++) out_step<false, true>(c, o);
#undef STEP2
#undef PART
    }
#undef STEP
    if (((CV_REG<MASK> + c.wg) >> 1) & 1) c.skip(u ^ 2);
    ks += nr * (c.wg ? OC_L1 : OC_L0);
  }
  TS(c.wg, 9);
#pragma unroll 1
  for (; ks < 57; ks++) out_step<false, true>(c, o);
  uint32_t ga[32];
  c.wait(2);
  const float g0 = __uint_as_float(lds32(c.base + SM_GATE + 4 * (c.wg * 64 + c.warp * 16 + (c.lane >> 2)))), g1 = __uint_as_float(lds32(c.base + SM_GATE + 32 + 4 * (c.wg * 64 + c.warp * 16 + (c.lane >> 2))));
  const uint32_t gg0 = pack_bf16(g0, g0), gg1 = pack_bf16(g1, g1);
  const uint32_t og0 = pack_bf16(1.f - g0, 1.f - g0), og1 = pack_bf16(1.f - g1, 1.f - g1);
  const int xr = c.wg * 64 + c.warp * 16 + (c.lane & 15);
  const uint32_t xa = c.addr(2) + xr * 128, xs = xr & 7, xh = c.lane >> 4;
  const int zr = (c.lane & 7) + ((c.lane >> 4) << 3);
  const uint32_t za = c.addr(0) + c.wg * 16384 + zr * 128 + (((c.warp * 2 + ((c.lane >> 3) & 1)) ^ (zr & 7)) << 4);
#pragma unroll
  for (int i = 0; i < 8; i++) {
    if (i == 0) out_step<false, true>(c, o);
    if (i == 3) out_step<false, true>(c, o);
    if (i == 6) out_step<false, true>(c, o);
    ldsm4(xa + (i >> 2) * 16384 + ((((i & 3) * 2 + xh) ^ xs) << 4), ga[4 * i], ga[4 * i + 1], ga[4 * i + 2], ga[4 * i + 3]);
  }
#pragma unroll 1
  for (ks = 60; ks < 64; ks++) out_step<false, false>(c, o);
  TS2(c.wg, 17);
  c.wait(0);
  TS2(c.wg, 18);
  SHADOW {
#pragma unroll
    for (int i = 0; i < 8; i++) {
      uint32_t z0, z1, z2, z3;
      ldsm4t(za + i * 2048, z0, z1, z2, z3);
      ga[4 * i + 0] = hmul2(gg0, hmul2(ga[4 * i + 0], z0)); ga[4 * i + 1] = hmul2(gg1, hmul2(ga[4 * i + 1], z1));
      ga[4 * i + 2] = hmul2(gg0, hmul2(ga[4 * i + 2], z2)); ga[4 * i + 3] = hmul2(gg1, hmul2(ga[4 * i + 3], z3));
    }
  }
  c.signal(SIG_DONE);
  fence_regs(ga);
  TS2(c.wg, 19);
  wg_wait<0>(); fence_regs(o.acc);
  TS2(c.wg, 20);
#pragma unroll
  for (int i = 0; i < 8; i++) {
    const uint32_t r0 = hadd2(ga[4 * i + 0], hmul2(og0, pack_bf16(o.acc[8 * i + 0], o.acc[8 * i + 1])));
    const uint32_t r1 = hadd2(ga[4 * i + 1], hmul2(og1, pack_bf16(o.acc[8 * i + 2], o.acc[8 * i + 3])));
    const uint32_t r2 = hadd2(ga[4 * i + 2], hmul2(og0, pack_bf16(o.acc[8 * i + 4], o.acc[8 * i + 5])));
    const uint32_t r3 = hadd2(ga[4 * i + 3], hmul2(og1, pack_bf16(o.acc[8 * i + 6], o.acc[8 * i + 7])));
    stsm4(xa + (i >> 2) * 16384 + ((((i & 3) * 2 + xh) ^ xs) << 4), r0, r1, r2, r3);
    if ((i & 3) == 3) {
      __syncwarp();
#pragma unroll
      for (int k = 0; k < 4; k++) {
        const int rr = c.wg * 64 + c.warp * 16 + k * 4 + (c.lane >> 3);
        const uint4 v = lds128(c.addr(2 + (i >> 2)) + rr * 128 + (((c.lane ^ rr) & 7) << 4));
        *(uint4*)(P.out + (uint32_t)((mb * 128 + rr) * 1024 + nb * 128 + (i >> 2) * 64 + (c.lane & 7) * 8)) = v;
      }
    }
  }
}

__device__ __forceinline__ void load_conv(Prod& p, const Maps& M, int u, int ch) {
  if (elect()) {
    mbar_expect(p.full(u), 5120 + UCH);
    tma3d(p.addr(u), &M.h, 0, -8, ch, p.full(u), POL(4));
    bulk_g2s(p.addr(u) + CV_U, g_u + (size_t)ch * UCH, UCH, p.full(u), POL(4));
  }
}
template<int MASK> __device__ __forceinline__ void prod_conv(Prod& p, const Maps& M, int cta, int nch) {
  int ready = -1;
#pragma unroll 1
  for (int i = 0; i < nch; i++) {
    const int ch = conv_channel<MASK>(cta, i);
    const int u = i & 3;
    if ((ch >> 6) != ready) { ready = ch >> 6; if (cta < NREG) mbar_wait(p.base + SM_RDY + 8 * RDY_U, 0); else cnt_wait(g_cnt + (C_U + ready) * CSTRIDE, 128); }
    p.acquire(u, 1);
    load_conv(p, M, u, ch);
    if (i == 3) { p.acquire(4, 4); if (elect()) mbar_arrive(p.full(4)); }
  }
}
#define HOIST(v) asm volatile("" : "+r"(v))
template<int MASK> __device__ __forceinline__ void producer(const Maps& M, const Params& P, uint32_t base, int cta, int lane) {
  Prod p{base, ((MASK & PH_KV) && cta < NREG) ? 0xffffcfffu ^ ((1u << (3 * NFIRST)) - 1) : 0xffffffffu, lane,
         (cta * 3 + 2) * 2048};
  if (cta >= NREG) { if (MASK & PH_CONV) prod_conv<MASK>(p, M, cta, CV_EXTRA<MASK>); return; }
  const int g = cta & 7, j = cta >> 3, rank = cta & 1;
#pragma unroll 1
  for (int half = 0; half < 2; half++) {
    const int h = j + 16 * half;
    if (MASK & PH_KV) {
      const CUtensorMap* mw = rank ? &M.wv : &M.wk;
#pragma unroll 1
      for (int it = half ? 0 : NFIRST; it < 16; it++) {
        const int u = gemm_unit(it);
        const bool early = KVE && MASK == PH_ALL && it == 0;
        uint32_t bar = p.full(u), d0 = p.addr(early ? 12 : u), d1 = p.addr(u + !early + rank); int k0 = (it & 7) * 64, r0 = (2 * g + (it >> 3)) * 128;
        HOIST(bar); HOIST(d0); HOIST(d1); HOIST(k0); HOIST(r0);
        p.acquire(u, 3 - early);
        if (elect()) {
          mbar_expect(bar, 3 * UNIT);
          tma3d_mc(d1, mw, 0, k0, 2 * h, bar, POL(0) && it >= 8);
          tma2d(d0, &M.c, k0, r0, bar, half ? POL(8) : POL(10));
        }
      }
    }
    if (MASK & PH_ATT) {
#pragma unroll 1
      for (int ks = 0; ks < 16; ks++) {
        const int u = gemm_unit(ks);
        uint32_t bar = p.full(u), d0 = p.addr(u), d1 = p.addr(u + 1), d2 = p.addr(u + 2) + rank * 8192; int k0 = ks * 64;
        HOIST(bar); HOIST(d0); HOIST(d1); HOIST(d2); HOIST(k0);
        p.acquire(u, 3);
        if (elect()) {
          mbar_expect(bar, 3 * UNIT);
          tma2d_mc(d2, &M.wq, h * 128 + rank * 64, k0, bar, POL(1));
          tma2d(d0, &M.x, k0, (15 - g) * 128, bar, half ? POL(9) : POL(10));
          tma2d(d1, &M.x, k0, g * 128, bar, half ? POL(9) : POL(10));
        }
      }
      TS(2, 8 * half + 0);
      mbar_wait(base + SM_RDY + 8 * (RDY_KV + half), 0);
      TS(2, 8 * half + 1);
      const uint8_t* KVh = g_T + T_KV + (size_t)kv_slot<MASK>(h) * 16 * 65536;
      if (MASK & PH_PRE) mbar_wait(base + SM_RDY + 8 * RDY_AUX, 0);
      if (elect()) { mbar_expect(p.full(12), 32768); bulk_g2s(p.addr(12), KVh + (DFIRST ? 15 - g : 0) * 65536, 32768, p.full(12), POL(6)); }
      p.acquire(0, 4);
      if (elect()) mbar_arrive(p.full(0));
#pragma unroll 1
      for (int n = 1; n < 34; n++) {
        const int i = n < VF ? ((n - 1) ^ 1) + 1 : n, isv = !(i & 1) || i == 33, st = i == 33 ? 16 : (isv ? (i >> 1) - 1 : (i + 1) >> 1), u = 4 + 2 * (((i - 1) & 3) ^ 1);
        const int m = 15 - (g & 6);
        const bool own = st == m || st == 16 || (DFIRST && st == 0);
        const int blk = st == 16 ? g : st > 15 - g ? 15 - st : !DFIRST ? st : st == 0 ? 15 - g : st - 1;
        uint32_t bar = p.full(u | 2), d0 = p.addr(own ? u : u + rank), off = blk * 65536 + isv * 32768 + (own ? 0 : rank * UNIT);
        HOIST(bar); HOIST(d0); HOIST(off);
        p.acquire(u, 2);
        if (elect()) {
          if (!isv || i == 33) mbar_expect(bar, isv ? 32768 : 65536);
          const bool ef = POL(6) || (POL(14) && st >= 8) || (POL(15) && half);
          if (own) bulk_g2s(d0, KVh + off, 32768, bar, ef); else bulk_g2s_mc(d0, KVh + off, UNIT, bar, ef);
          if (MASK == PH_ALL && half && i == PF_AT) {
            if (PF & 1) pf3d(&M.wo, 0, j * 64, 2 * g);
            if (PF & 2) pf_bulk(g_T + T_CTX + (j * 32 + g) * 32768, 32768);
          }
        }
      }
    }
  }
  if ((MASK & PH_CONV) && !(MASK & PH_OUT)) prod_conv<MASK>(p, M, cta, CV_REG<MASK>);
  if (MASK & PH_OUT) {
    const int y0 = out_mb(cta) * 512 + rank * 8, z0 = 2 * out_nb(cta);
    int u = 6;
#pragma unroll 1
    for (int hf = 0; hf < 2; hf++) {
      TS(2, 16 + 2 * hf);
      mbar_wait(base + SM_RDY + 8 * (RDY_CTX + hf), 0);
      TS(2, 17 + 2 * hf);
#pragma unroll 1
      for (int n = hf * 32; n < hf * 32 + 32; n++) {
        const int ks = n == 1 ? 2 : n == 2 ? 1 : n;
        u = n == 2 ? 2 : n == 3 ? 10 : out_next(u);
        uint32_t bar = p.full(u), d0 = p.addr(u) + rank * 8192, d1 = p.addr(u + 1); int x = (ks & 1) * 256, y = y0 + (ks >> 1) * 16, k0 = ks * 64;
        HOIST(bar); HOIST(d0); HOIST(d1); HOIST(x); HOIST(y); HOIST(k0);
        p.acquire(u, 2);
        if (elect()) {
          mbar_expect(bar, 2 * UNIT);
          tma2d_mc(d0, &M.ctx, x, y, bar, POL(5));
          tma3d(d1, &M.wo, 0, k0, z0, bar, POL(2));
          if ((PF & 4) && (ks & 15) == PF_KS && ks < 48) pf3d(&M.wo, 0, ((ks & 48) + 16 + j) * 64, z0);
          if ((PF & 8) && ks == PF_KS) pf_bulk(g_T + T_CTX + (j * 32 + 8 + g) * 32768, 32768);
          if (ks == 1) mbar_arrive(base + SM_RDY + 8 * RDY_X);
          if (ks == Z_AT) mbar_arrive(base + SM_RDY + 8 * RDY_Z);
        }
      }
    }
  }
}
template<int MASK> __device__ __forceinline__ void producer2(const Maps& M, const Params& P, uint32_t base, int cta, int w, int lane) {
  Prod p{base, 0xffffffffu, lane, 0};
  const int mb = out_mb(cta), nb = out_nb(cta), u = 2 * w;
  if (w) { mbar_wait_slow(base + SM_RDY + 8 * RDY_X, 0); p.mask ^= KVE && MASK == PH_ALL ? 8 : 12; }
  if (MASK & PH_CONV) {
    mbar_wait_slow(base + SM_SIG + 8 * (SIG_ATT + 1), 0);
    mbar_wait_slow(base + SM_RDY + 8 * RDY_U, 0);
#pragma unroll 1
    for (int i = w; i < CV_REG<MASK>; i += 2) { p.acquire_slow(u, i < 2 ? 2 : 1); load_conv(p, M, u, conv_channel<MASK>(cta, i)); }
  }
  p.acquire_slow(u, 2);
  if (elect()) asm volatile("prefetch.tensormap [%0];" :: "l"(!w ? &M.z : &M.out) : "memory");
  TSA(52 - 2 * w);
  mbar_wait(base + SM_RDY + 8 * (!w ? RDY_Z : RDY_G), 0);
  TSA(53 - 2 * w);
  if (elect()) {
    mbar_expect(p.full(u), 2 * UNIT + (!w ? 0 : 512));
    tma2d(p.addr(u), !w ? &M.z : &M.x, (!w ? mb : nb) * 128, (!w ? nb : mb) * 128, p.full(u), POL(5));
    tma2d(p.addr(u + 1), !w ? &M.z : &M.x, (!w ? mb : nb) * 128 + 64, (!w ? nb : mb) * 128, p.full(u), POL(5));
    if (w) bulk_g2s(base + SM_GATE, g_gate + mb * 128, 512, p.full(u));
  }
}

__device__ __forceinline__ constexpr uint32_t PUB(int sig, int cnt, int n) { return 0x80000000u | (sig << 24) | (n << 8) | cnt; }
__device__ __forceinline__ constexpr uint32_t GET(int rdy, int cnt, int n) { return (rdy << 24) | (n << 8) | cnt; }
template<int MASK> __device__ __forceinline__ void sync_agent(uint32_t base, int cta, int lane) {
  if ((base & 0x3FFFF) != SMEM_BASE) asm volatile("trap;");
  const int g = cta & 7, j = cta >> 3, go = min(out_mb(cta), 15 - out_mb(cta));
  const int c0 = conv_channel<MASK>(cta, 0), c1 = c0 + CV_REG<MASK> - 1, n0 = min(CV_REG<MASK>, 128 - (c0 & 127));
  constexpr bool KV = MASK & PH_KV, ATT = MASK & PH_ATT, CONV = MASK & PH_CONV, OUT = MASK & PH_OUT, ALL = MASK == PH_ALL;
  uint32_t e = 0;
  if (cta >= NREG) { if (CONV && lane * 32 < CV_EXTRA<MASK>) e = PUB(SIG_Z + lane, C_Z + lane, min(32, CV_EXTRA<MASK> - lane * 32)); }
  else switch (lane) {
    case 0:  if (KV) e = PUB(SIG_KV, C_KV + j, 1); break;
    case 1:  if (ATT) e = GET(RDY_KV, C_KV + j, 8); break;
    case 2:  if (ALL) e = PUB(SIG_WAR, C_WAR + j, 1); break;
    case 3:  if (ATT) e = PUB(SIG_CTX, C_CTX + g, 1); break;
    case 4:  if (ALL) e = GET(RDY_WAR, C_WAR + j, 8); break;
    case 5:  if (KV) e = PUB(SIG_KV + 1, C_KV + 16 + j, 1); break;
    case 6:  if (ATT) e = GET(RDY_KV + 1, C_KV + 16 + j, 8); break;
    case 7:  if (OUT) e = GET(RDY_CTX, C_CTX + go, 16); break;
    case 8:  if (CONV) e = GET(RDY_U, C_U + (c0 >> 6), 128); break;
    case 9:  if (CONV) e = GET(RDY_U, C_U + (c1 >> 6), 128); break;
    case 10: if (ATT) e = PUB(SIG_CTX + 1, C_CTX + 8 + g, 1); break;
    case 11: if (OUT) e = GET(RDY_CTX + 1, C_CTX + 8 + go, 16); break;
    case 12: if (OUT) e = GET(RDY_G, C_GATE, 256); break;
    case 13: if (CONV) e = PUB(SIG_Z, C_Z + (c0 >> 7), n0); break;
    case 14: if (CONV && n0 < CV_REG<MASK>) e = PUB(SIG_Z, C_Z + (c1 >> 7), CV_REG<MASK> - n0); break;
    case 15: if (OUT) e = GET(RDY_Z, C_Z + out_nb(cta), 128); break;
  }
  __syncwarp();
#pragma unroll 1
  for (int i = 0; i < 16; i++) {
    const uint32_t x = __shfl_sync(~0u, e, i), id = (x >> 24) & 127, n = (x >> 8) & 0xffff;
    if (x == 0) continue;
    unsigned* cnt = g_cnt + (x & 255) * CSTRIDE;
    if (x >> 31) {
      mbar_wait_slow(base + SM_SIG + 8 * id, 0);
      if (i == 13) TSA(22);
      if (lane == 0) cnt_publish(cnt, n, i != 14);
    } else {
      cnt_wait(cnt, n);
      if (id < 2) {
        const float4 kn = __ldcg((const float4*)(g_kn2 + kv_slot<MASK>(j + 16 * id) * 128) + lane);
        const uint32_t m = __reduce_max_sync(~0u, max(max(__float_as_uint(kn.x), __float_as_uint(kn.y)), max(__float_as_uint(kn.z), __float_as_uint(kn.w))));
        if (lane == 0) asm volatile("st.shared.u32 [%0], %1;" :: "r"(base + SM_KMAX + 4 * id), "r"(m) : "memory");
      }
      if (lane == 0) mbar_arrive(base + SM_RDY + 8 * id);
    }
    __syncwarp();
    TSA(24 + i);
  }
}

__device__ __forceinline__ void aux_gate(const Params& P, int cta, int aw, int lane) {
  uint4 gw[4];
#pragma unroll
  for (int i = 0; i < 4; i++) gw[i] = __ldg((const uint4*)P.gw + i * 32 + lane);
#pragma unroll 1
  for (int row = cta * 16 + aw * 8; row < cta * 16 + aw * 8 + 8; row++) {
    float a = 0.f;
#pragma unroll
    for (int i = 0; i < 4; i++) {
      const uint4 xv = __ldg((const uint4*)(P.x + (size_t)row * 1024) + i * 32 + lane);
      uint32_t m;
      m = hmul2(xv.x, gw[i].x); a += bf_lo(m) + bf_hi(m); m = hmul2(xv.y, gw[i].y); a += bf_lo(m) + bf_hi(m);
      m = hmul2(xv.z, gw[i].z); a += bf_lo(m) + bf_hi(m); m = hmul2(xv.w, gw[i].w); a += bf_lo(m) + bf_hi(m);
    }
#pragma unroll
    for (int o = 16; o > 0; o >>= 1) a += __shfl_xor_sync(~0u, a, o);
    a = bf_lo(pack_bf16(a, 0.f));
    const float gt = bf_lo(pack_bf16(__fdividef(1.f, 1.f + ex2(-a * 1.4426950408889634f)), 0.f));
    if (lane == 0) g_gate[row] = gt;
    if (GATE_SLEEP) __nanosleep(GATE_SLEEP);
  }
  cnt_signal(g_cnt + C_GATE * CSTRIDE, lane);
  if (aw == 0) { TSA(44); }
}
template<int MASK> __device__ __forceinline__ void aux_pre(const Maps& M, const Params& P, uint32_t base, int cta, int aw, int lane) {
  const uint32_t kb = base + 12 * UNIT, bar = base + SM_PRE;
  const int r = lane >> 2, q = lane & 3;
  const int mi = lane >> 3, row0 = (lane & 6) + 1 - (lane & 1);
  const int ra = (mi * 9 + 1) * 2 + row0;
  const int rb = (mi == 0 ? 3 : mi) * 18 + row0;
  if (PRE_DELAY) mbar_wait_slow(base + SM_BAR + 8 * PRE_DELAY_BAR, 0);
#pragma unroll 1
  for (int it = 0; it < (cta < 96 ? 5 : 4); it++) {
    if (GATE_EARLY && it == PRE_EARLY && MASK == PH_ALL) { mbar_wait_slow(base + SM_SIG + 8 * SIG_ATT, 0); aux_gate(P, cta, aw, lane); }
    if (it == PRE_EARLY && MASK == PH_ALL) mbar_wait_slow(base + SM_SIG + 8 * (SIG_ATT + PRE_HALF), 0);
    const int cg = it ? it * 4 - 3 + (cta >> 5) : 0, tb = cta & 31;
    if (aw == 0 && elect()) {
      mbar_expect(bar, 2 * 9216);
      tma4d(kb, &M.k, cg * 64, 0, tb * 8 - 1, 0, bar, POL(3));
      tma4d(kb + 9216, &M.v, cg * 64, 0, tb * 8 - 1, 0, bar, POL(3));
    }
    const uint2 swl = __ldg((const uint2*)(P.shift + (cg * 64 + aw * 32 + lane) * 4));
    if (tb == 0) {
      uint8_t* e = g_u + (size_t)(cg * 64 + aw * 32 + lane) * UCH + 4096;
      *(uint4*)e = make_uint4(0, 0, 0, 0); *(uint4*)(e + UPITCH) = make_uint4(0, 0, 0, 0);
      *(uint32_t*)(e + 32) = (uint32_t)__bfloat16_as_ushort(P.D[cg * 64 + aw * 32 + lane]) * 0x10001u;
    }
    mbar_wait_slow(bar, it & 1);
#pragma unroll 1
    for (int ol = it ? 0 : cta >> 5; ol < (it ? 4 : (cta >> 5) + 1); ol++) {
      const int oc = aw * 4 + ol;
      const uint32_t s01 = __shfl_sync(~0u, swl.x, ol * 8 + r), s23 = __shfl_sync(~0u, swl.y, ol * 8 + r);
      const uint32_t w0 = __byte_perm(s01, 0, 0x1010), w1 = __byte_perm(s01, 0, 0x3232), w2 = __byte_perm(s23, 0, 0x1010), w3 = __byte_perm(s23, 0, 0x3232);
      const uint32_t pa = kb + ra * 128 + ((oc ^ (ra & 7)) << 4), pb = kb + (mi == 0 ? 9216 : 0) + rb * 128 + ((oc ^ (rb & 7)) << 4);
      uint8_t* e0 = g_u + (uint32_t)((cg * 64 + oc * 8 + r) * UCH + (2040 - tb * 64 - 8 * q) * 2);
#pragma unroll
      for (int hb = 0; hb < 2; hb++) {
        uint32_t k[7], v[5];
        ldsm4t(pa + hb * 1024, k[3], k[4], k[5], k[6]);
        ldsm4t(pa + hb * 1024 + 9216, v[1], v[2], v[3], v[4]);
        ldsm4t(pb + hb * 1024, v[0], k[0], k[1], k[2]);
        uint32_t o1 = __byte_perm(k[1], k[0], 0x5432);
#pragma unroll
        for (int m = 0; m < 5; m++) {
          const uint32_t o2 = __byte_perm(k[m + 2], k[m + 1], 0x5432);
          v[m] = hmul2(hadd2(hadd2(hadd2(hmul2(o1, w3), hmul2(k[m + 1], w2)), hmul2(o2, w1)), hmul2(k[m + 2], w0)), v[m]);
          o1 = o2;
        }
        *(uint4*)(e0 - hb * 64) = make_uint4(v[4], v[3], v[2], v[1]);
        *(uint4*)(e0 - hb * 64 + UPITCH) = make_uint4(__byte_perm(v[4], v[3], 0x5432), __byte_perm(v[3], v[2], 0x5432), __byte_perm(v[2], v[1], 0x5432), __byte_perm(v[1], v[0], 0x5432));
        if (PRE_SLEEP && it >= PRE_EARLY) __nanosleep(PRE_SLEEP);
      }
    }
    bar_sync(5, 64);
    if (aw == 0) { TSA(40 + min(it, 3)); }
    if (it == PRE_EARLY - 1 && aw == 0 && lane == 0) mbar_arrive(base + SM_RDY + 8 * RDY_AUX);
    if (aw == 1 && lane == 0) asm volatile("red.release.gpu.global.add.u32 [%0], %1;" :: "l"(g_cnt + (C_U + cg) * CSTRIDE), "r"(it ? 4 : 1) : "memory");
  }
  uint32_t rel;
  asm volatile("mapa.shared::cluster.u32 %0, %1, %2;" : "=r"(rel) : "r"(base + SM_BAR + 128 + 8 * (12 + (lane & 1))), "r"((lane >> 1) & 1));
  if (lane < 4) asm volatile("mbarrier.arrive.shared::cluster.b64 _, [%0], 4;" :: "r"(rel) : "memory");
  if (!(GATE_EARLY && MASK == PH_ALL)) aux_gate(P, cta, aw, lane);
}

template<int MASK> __global__ void __cluster_dims__(2, 1, 1) __launch_bounds__(384, 1) gated_mix_kernel(const __grid_constant__ Maps M, const __grid_constant__ Params P) {
  extern __shared__ __align__(1024) uint8_t smem[];
  const uint32_t base = (uint32_t)__cvta_generic_to_shared(smem);
  const int wi = __shfl_sync(~0u, threadIdx.x >> 5, 0), wg = wi >> 2, warp = wi & 3;
  if (elect()) {
    if (wi < 8) {
      const int cnt = 1 << ((0x10334400 >> (4 * wi)) & 15);
#pragma unroll
      for (int i = 0; i < 8; i++) mbar_init(base + SM_BAR + 64 * wi + 8 * i, cnt);
      asm volatile("fence.mbarrier_init.release.cluster;" ::: "memory");
    } else if (MAP_PF) {
      asm volatile("prefetch.tensormap [%0];" :: "l"(&M.c + (wi - 8)) : "memory");
    }
  }
  const int cta = blockIdx.x;
  const bool first_loads = (MASK & PH_KV) && wi == 8 && cta < NREG;
  const CUtensorMap* mw = (cta & 1) ? &M.wv : &M.wk;
  __syncwarp();
  asm volatile("barrier.cluster.arrive.relaxed.aligned;\nbarrier.cluster.wait.aligned;" ::: "memory");
  if (first_loads && elect()) {
#pragma unroll 1
    for (int it = 0; it < NFIRST; it++) {
      const uint32_t bar = base + SM_BAR + 24 * it, d0 = base + 3 * it * UNIT;
      mbar_expect(bar, 3 * UNIT);
      tma3d_mc(d0 + (1 + (cta & 1)) * UNIT, mw, 0, it * 64, 2 * (cta >> 3), bar);
      tma2d(d0, &M.c, it * 64, (cta & 7) * 256, bar);
    }
  }
  __syncwarp();
  const int lane = threadIdx.x & 31;
#define TS_PRO()
  if (wg == 2) {
    asm volatile("setmaxnreg.dec.sync.aligned.u32 56;");
    TS_PRO();
    TS(2, 62);
    if (warp == 0) producer<MASK>(M, P, base, cta, lane);
    else if (warp == 1) sync_agent<MASK>(base, cta, lane);
    else if (cta < NREG) {
      if (MASK & PH_PRE) aux_pre<MASK>(M, P, base, cta, warp - 2, lane);
      if (MASK & PH_OUT) producer2<MASK>(M, P, base, cta, warp - 2, lane);
    }
    if (warp == 1) {
      if (MASK & PH_OUT) {
        unsigned old = 0;
        if (lane == 0) asm volatile("atom.relaxed.gpu.global.add.u32 %0, [%1], 1;" : "=r"(old) : "l"(g_cnt + C_EXIT * CSTRIDE) : "memory");
        old = __shfl_sync(~0u, old, 0);
        if (old == NCTA - 1) for (int i = lane; i < C_NUM; i += 32) g_cnt[i * CSTRIDE] = 0;
      }
      mbar_wait_slow(base + SM_SIG + 8 * SIG_DONE, 0);
      if (cta >= NREG || !(MASK & PH_OUT)) { cluster_arrive(); cluster_wait(); }
    }
  } else {
    asm volatile("setmaxnreg.inc.sync.aligned.u32 224;");
    TS_PRO();
    uint32_t rel;
    asm volatile("mapa.shared::cluster.u32 %0, %1, %2;" : "=r"(rel) : "r"(base + SM_BAR + 128 + 8 * (lane & 15)), "r"(lane >> 4));
    Cons c{base, rel, 0u, lane, warp, wg, (cta * 3 + wg) * 2048};
    if (wg == 1) bar_arrive(1, 256);
    TS(wg, 0);
    if (cta < NREG) {
      const int g = cta & 7, j = cta >> 3;
      Pend w = {};
      if (HOISTW && MASK == PH_ALL) c.wait(0);
#pragma unroll 1
      for (int half = 0; half < 2; half++) {
        const int h = j + 16 * half;
        if (MASK & PH_KV) cons_kv<(MASK & PH_ATT) != 0>(c, h, kv_slot<MASK>(h), g, w, half == 1 && (MASK & PH_ATT));
        TS(wg, 1 + 4 * half);
        if (MASK & PH_ATT) {
          Att a;
          cons_q<(MASK & PH_KV) != 0>(c, h, w, a.o);
          TS(wg, 2 + 4 * half);
          cons_att<MASK == PH_ALL>(c, a, h, g, w);
          if (half == 0) c.signal(SIG_WAR);
#pragma unroll
          for (int i = 0; i < 8; i++) w.hi[i] = make_uint4(0, 0, 0, 0);
          TS(wg, 3 + 4 * half);
          if (MASK != PH_ALL) { tile_store<0, 4>(w.lo, w.dst, lane); c.signal(SIG_CTX + half); }
        } else if (MASK & PH_KV) {
          out_piece<SCH_KV, true>(c, w, 0, true);
          for (int ks = 1; ks < 8; ks++) out_piece<SCH_KV, false>(c, w, ks, true);
          c.signal(SIG_KV + half);
        }
      }
      if (MASK & PH_OUT) cons_out<MASK>(c, M, P, cta, w);
    }
    if (cta >= NREG || !(MASK & PH_OUT)) {
      if (MASK & PH_CONV) cons_conv<MASK>(c, cta, cta < NREG ? CV_REG<MASK> : CV_EXTRA<MASK>);
      TS(wg, 9);
      c.signal(SIG_DONE);
      cluster_arrive();
    }
    TS(wg, 10);
  }
}

typedef CUresult (*EncFn)(CUtensorMap*, CUtensorMapDataType, cuuint32_t, void*, const cuuint64_t*, const cuuint64_t*, const cuuint32_t*, const cuuint32_t*,
                          CUtensorMapInterleave, CUtensorMapSwizzle, CUtensorMapL2promotion, CUtensorMapFloatOOBfill);
static void enc(EncFn f, CUtensorMap* m, const void* ptr, int rank, const cuuint64_t* dims, const cuuint64_t* strides, const cuuint32_t* box, CUtensorMapSwizzle sw,
                CUtensorMapDataType dt = CU_TENSOR_MAP_DATA_TYPE_BFLOAT16) {
  const cuuint32_t es[4] = {1, 1, 1, 1};
  f(m, dt, rank, (void*)ptr, dims, strides, box, es, CU_TENSOR_MAP_INTERLEAVE_NONE, sw, CU_TENSOR_MAP_L2_PROMOTION_L2_256B, CU_TENSOR_MAP_FLOAT_OOB_FILL_NONE);
}
static void enc2(EncFn f, CUtensorMap* m, const void* ptr, int cols, int rows, int brows) {
  const cuuint64_t d[2] = {(cuuint64_t)cols, (cuuint64_t)rows}, s[1] = {(cuuint64_t)cols * 2}; const cuuint32_t b[2] = {64, (cuuint32_t)brows};
  enc(f, m, ptr, 2, d, s, b, CU_TENSOR_MAP_SWIZZLE_128B);
}
static void encw(EncFn f, CUtensorMap* m, const void* ptr, int cols, int rows) {
  const cuuint64_t d[3] = {64, (cuuint64_t)rows, (cuuint64_t)cols / 64}, s[2] = {(cuuint64_t)cols * 2, 128}; const cuuint32_t b[3] = {64, 64, 2};
  enc(f, m, ptr, 3, d, s, b, CU_TENSOR_MAP_SWIZZLE_128B);
}
extern "C" void kernel_launch(void* const* d_in, const int* in_sizes, int n_in, void* d_out, int out_size) {
  static EncFn fn = nullptr;
  static int ncl = 0;
  static void* zptr = nullptr;
  static void* tptr = nullptr;
  if (!fn) {
    void* p = nullptr; cudaDriverEntryPointQueryResult qr;
    cudaGetDriverEntryPoint("cuTensorMapEncodeTiled", &p, cudaEnableDefault, &qr);
    fn = (EncFn)p;
    cudaFuncSetAttribute(gated_mix_kernel<PH_ALL>, cudaFuncAttributeMaxDynamicSharedMemorySize, SMEM_BYTES);
    cudaFuncSetAttribute(gated_mix_kernel<PH_PRE | PH_KV>, cudaFuncAttributeMaxDynamicSharedMemorySize, SMEM_BYTES);
    cudaFuncSetAttribute(gated_mix_kernel<PH_ATT | PH_CONV>, cudaFuncAttributeMaxDynamicSharedMemorySize, SMEM_BYTES);
    cudaFuncSetAttribute(gated_mix_kernel<PH_OUT>, cudaFuncAttributeMaxDynamicSharedMemorySize, SMEM_BYTES);
    cudaLaunchConfig_t cfg = {}; cfg.gridDim = NCTA; cfg.blockDim = 384; cfg.dynamicSmemBytes = SMEM_BYTES;
    cudaLaunchAttribute at; at.id = cudaLaunchAttributeClusterDimension; at.val.clusterDim.x = 2; at.val.clusterDim.y = 1; at.val.clusterDim.z = 1;
    cfg.attrs = &at; cfg.numAttrs = 1;
    cudaOccupancyMaxActiveClusters(&ncl, gated_mix_kernel<PH_ALL>, &cfg);
    cudaGetSymbolAddress(&zptr, g_z);
    cudaGetSymbolAddress(&tptr, g_T);
  }
  Maps M;
  enc2(fn, &M.x, d_in[0], 1024, 2048, 128);
  enc2(fn, &M.c, d_in[7], 512, 2048, 128);
  enc2(fn, &M.wq, d_in[8], 4096, 1024, 64);
  encw(fn, &M.wk, d_in[9], 4096, 512);
  encw(fn, &M.wv, d_in[10], 4096, 512);
  encw(fn, &M.wo, d_in[11], 1024, 4096);
  { const cuuint64_t d[3] = {64, 32, 1024}, s[2] = {128, 4096}; const cuuint32_t b[3] = {64, 40, 1}; enc(fn, &M.h, d_in[4], 3, d, s, b, CU_TENSOR_MAP_SWIZZLE_NONE); }
  enc2(fn, &M.z, zptr, 2048, 1024, 128);
  enc2(fn, &M.out, d_out, 1024, 2048, 16);
  { const cuuint64_t d[2] = {512, 512 * 16}, s[1] = {2048}; const cuuint32_t b[2] = {256, 8};
    enc(fn, &M.ctx, tptr, 2, d, s, b, CU_TENSOR_MAP_SWIZZLE_NONE, CU_TENSOR_MAP_DATA_TYPE_UINT32); }
  { const cuuint64_t d[4] = {1024, 2, 256, 4}, s[3] = {2048, 16384, 4096}; const cuuint32_t b[4] = {64, 2, 9, 4};
    enc(fn, &M.k, d_in[1], 4, d, s, b, CU_TENSOR_MAP_SWIZZLE_128B); enc(fn, &M.v, d_in[2], 4, d, s, b, CU_TENSOR_MAP_SWIZZLE_128B); }
  Params P{(const __nv_bfloat16*)d_in[0], (const __nv_bfloat16*)d_in[3],
           (const __nv_bfloat16*)d_in[5], (const __nv_bfloat16*)d_in[12], (__nv_bfloat16*)d_out};
  bool split = 2 * ncl < NCTA;
  if (!split) {
    gated_mix_kernel<PH_ALL><<<NCTA, 384, SMEM_BYTES>>>(M, P);
  } else {
    gated_mix_kernel<PH_PRE | PH_KV><<<NCTA, 384, SMEM_BYTES>>>(M, P);
    gated_mix_kernel<PH_ATT | PH_CONV><<<NCTA, 384, SMEM_BYTES>>>(M, P);
    gated_mix_kernel<PH_OUT><<<NCTA, 384, SMEM_BYTES>>>(M, P);
  }
}
```

```cpp
#include <cuda_runtime.h>
#include <cuda.h>
#include <cuda_bf16.h>
#include <stdint.h>

template<int TB> __device__ __forceinline__ void wgmma_ss_n256(float (&d)[128], uint64_t da, uint64_t db, int scale_d) {
  asm volatile("{\n.reg .pred p;\nsetp.ne.b32 p, %130, 0;\n"
    "wgmma.mma_async.sync.aligned.m64n256k16.f32.bf16.bf16 {%0, %1, %2, %3, %4, %5, %6, %7, %8, %9, %10, %11, %12, %13, %14, %15, %16, %17, %18, %19, %20, %21, %22, %23, %24, %25, %26, %27, %28, %29, %30, %31, %32, %33, %34, %35, %36, %37, %38, %39, %40, %41, %42, %43, %44, %45, %46, %47, %48, %49, %50, %51, %52, %53, %54, %55, %56, %57, %58, %59, %60, %61, %62, %63, %64, %65, %66, %67, %68, %69, %70, %71, %72, %73, %74, %75, %76, %77, %78, %79, %80, %81, %82, %83, %84, %85, %86, %87, %88, %89, %90, %91, %92, %93, %94, %95, %96, %97, %98, %99, %100, %101, %102, %103, %104, %105, %106, %107, %108, %109, %110, %111, %112, %113, %114, %115, %116, %117, %118, %119, %120, %121, %122, %123, %124, %125, %126, %127}, %128, %129, p, 1, 1, 0, %131;\n}\n"
    : "+f"(d[0]), "+f"(d[1]), "+f"(d[2]), "+f"(d[3]), "+f"(d[4]), "+f"(d[5]), "+f"(d[6]), "+f"(d[7]), "+f"(d[8]), "+f"(d[9]), "+f"(d[10]), "+f"(d[11]), "+f"(d[12]), "+f"(d[13]), "+f"(d[14]), "+f"(d[15]), "+f"(d[16]), "+f"(d[17]), "+f"(d[18]), "+f"(d[19]), "+f"(d[20]), "+f"(d[21]), "+f"(d[22]), "+f"(d[23]), "+f"(d[24]), "+f"(d[25]), "+f"(d[26]), "+f"(d[27]), "+f"(d[28]), "+f"(d[29]), "+f"(d[30]), "+f"(d[31]), "+f"(d[32]), "+f"(d[33]), "+f"(d[34]), "+f"(d[35]), "+f"(d[36]), "+f"(d[37]), "+f"(d[38]), "+f"(d[39]), "+f"(d[40]), "+f"(d[41]), "+f"(d[42]), "+f"(d[43]), "+f"(d[44]), "+f"(d[45]), "+f"(d[46]), "+f"(d[47]), "+f"(d[48]), "+f"(d[49]), "+f"(d[50]), "+f"(d[51]), "+f"(d[52]), "+f"(d[53]), "+f"(d[54]), "+f"(d[55]), "+f"(d[56]), "+f"(d[57]), "+f"(d[58]), "+f"(d[59]), "+f"(d[60]), "+f"(d[61]), "+f"(d[62]), "+f"(d[63]), "+f"(d[64]), "+f"(d[65]), "+f"(d[66]), "+f"(d[67]), "+f"(d[68]), "+f"(d[69]), "+f"(d[70]), "+f"(d[71]), "+f"(d[72]), "+f"(d[73]), "+f"(d[74]), "+f"(d[75]), "+f"(d[76]), "+f"(d[77]), "+f"(d[78]), "+f"(d[79]), "+f"(d[80]), "+f"(d[81]), "+f"(d[82]), "+f"(d[83]), "+f"(d[84]), "+f"(d[85]), "+f"(d[86]), "+f"(d[87]), "+f"(d[88]), "+f"(d[89]), "+f"(d[90]), "+f"(d[91]), "+f"(d[92]), "+f"(d[93]), "+f"(d[94]), "+f"(d[95]), "+f"(d[96]), "+f"(d[97]), "+f"(d[98]), "+f"(d[99]), "+f"(d[100]), "+f"(d[101]), "+f"(d[102]), "+f"(d[103]), "+f"(d[104]), "+f"(d[105]), "+f"(d[106]), "+f"(d[107]), "+f"(d[108]), "+f"(d[109]), "+f"(d[110]), "+f"(d[111]), "+f"(d[112]), "+f"(d[113]), "+f"(d[114]), "+f"(d[115]), "+f"(d[116]), "+f"(d[117]), "+f"(d[118]), "+f"(d[119]), "+f"(d[120]), "+f"(d[121]), "+f"(d[122]), "+f"(d[123]), "+f"(d[124]), "+f"(d[125]), "+f"(d[126]), "+f"(d[127])
    : "l"(da), "l"(db), "r"(scale_d), "n"(TB));
}
template<int TB> __device__ __forceinline__ void wgmma_ss_n128(float (&d)[64], uint64_t da, uint64_t db, int scale_d) {
  asm volatile("{\n.reg .pred p;\nsetp.ne.b32 p, %66, 0;\n"
    "wgmma.mma_async.sync.aligned.m64n128k16.f32.bf16.bf16 {%0, %1, %2, %3, %4, %5, %6, %7, %8, %9, %10, %11, %12, %13, %14, %15, %16, %17, %18, %19, %20, %21, %22, %23, %24, %25, %26, %27, %28, %29, %30, %31, %32, %33, %34, %35, %36, %37, %38, %39, %40, %41, %42, %43, %44, %45, %46, %47, %48, %49, %50, %51, %52, %53, %54, %55, %56, %57, %58, %59, %60, %61, %62, %63}, %64, %65, p, 1, 1, 0, %67;\n}\n"
    : "+f"(d[0]), "+f"(d[1]), "+f"(d[2]), "+f"(d[3]), "+f"(d[4]), "+f"(d[5]), "+f"(d[6]), "+f"(d[7]), "+f"(d[8]), "+f"(d[9]), "+f"(d[10]), "+f"(d[11]), "+f"(d[12]), "+f"(d[13]), "+f"(d[14]), "+f"(d[15]), "+f"(d[16]), "+f"(d[17]), "+f"(d[18]), "+f"(d[19]), "+f"(d[20]), "+f"(d[21]), "+f"(d[22]), "+f"(d[23]), "+f"(d[24]), "+f"(d[25]), "+f"(d[26]), "+f"(d[27]), "+f"(d[28]), "+f"(d[29]), "+f"(d[30]), "+f"(d[31]), "+f"(d[32]), "+f"(d[33]), "+f"(d[34]), "+f"(d[35]), "+f"(d[36]), "+f"(d[37]), "+f"(d[38]), "+f"(d[39]), "+f"(d[40]), "+f"(d[41]), "+f"(d[42]), "+f"(d[43]), "+f"(d[44]), "+f"(d[45]), "+f"(d[46]), "+f"(d[47]), "+f"(d[48]), "+f"(d[49]), "+f"(d[50]), "+f"(d[51]), "+f"(d[52]), "+f"(d[53]), "+f"(d[54]), "+f"(d[55]), "+f"(d[56]), "+f"(d[57]), "+f"(d[58]), "+f"(d[59]), "+f"(d[60]), "+f"(d[61]), "+f"(d[62]), "+f"(d[63])
    : "l"(da), "l"(db), "r"(scale_d), "n"(TB));
}
template<int TB> __device__ __forceinline__ void wgmma_rs_n32(float (&d)[16], uint32_t a0, uint32_t a1, uint32_t a2, uint32_t a3, uint64_t db, int scale_d) {
  asm volatile("{\n.reg .pred p;\nsetp.ne.b32 p, %21, 0;\n"
    "wgmma.mma_async.sync.aligned.m64n32k16.f32.bf16.bf16 {%0, %1, %2, %3, %4, %5, %6, %7, %8, %9, %10, %11, %12, %13, %14, %15}, {%16, %17, %18, %19}, %20, p, 1, 1, %22;\n}\n"
    : "+f"(d[0]), "+f"(d[1]), "+f"(d[2]), "+f"(d[3]), "+f"(d[4]), "+f"(d[5]), "+f"(d[6]), "+f"(d[7]), "+f"(d[8]), "+f"(d[9]), "+f"(d[10]), "+f"(d[11]), "+f"(d[12]), "+f"(d[13]), "+f"(d[14]), "+f"(d[15])
    : "r"(a0), "r"(a1), "r"(a2), "r"(a3), "l"(db), "r"(scale_d), "n"(TB));
}
__device__ __forceinline__ void wgmma_pv_sel(float (&d)[64], const uint32_t (&p)[32], uint64_t db, int full, int acc, int wg) {
  asm volatile("{\n.reg .pred q, s, w;\n.reg .b64 t;\nsetp.eq.b32 w, %99, 0;\nsetp.ne.b32 s, %98, 0;\nsetp.eq.b32 q, %97, 0;\n@q bra.uni LH;\n"
    "wgmma.fence.sync.aligned;\n"
    "add.s64 t, %96, 0;\nwgmma.mma_async.sync.aligned.m64n128k16.f32.bf16.bf16 {%0, %1, %2, %3, %4, %5, %6, %7, %8, %9, %10, %11, %12, %13, %14, %15, %16, %17, %18, %19, %20, %21, %22, %23, %24, %25, %26, %27, %28, %29, %30, %31, %32, %33, %34, %35, %36, %37, %38, %39, %40, %41, %42, %43, %44, %45, %46, %47, %48, %49, %50, %51, %52, %53, %54, %55, %56, %57, %58, %59, %60, %61, %62, %63}, {%64, %65, %66, %67}, t, s, 1, 1, 1;\n"
    "add.s64 t, %96, 256;\nwgmma.mma_async.sync.aligned.m64n128k16.f32.bf16.bf16 {%0, %1, %2, %3, %4, %5, %6, %7, %8, %9, %10, %11, %12, %13, %14, %15, %16, %17, %18, %19, %20, %21, %22, %23, %24, %25, %26, %27, %28, %29, %30, %31, %32, %33, %34, %35, %36, %37, %38, %39, %40, %41, %42, %43, %44, %45, %46, %47, %48, %49, %50, %51, %52, %53, %54, %55, %56, %57, %58, %59, %60, %61, %62, %63}, {%68, %69, %70, %71}, t, 1, 1, 1, 1;\n"
    "add.s64 t, %96, 512;\nwgmma.mma_async.sync.aligned.m64n128k16.f32.bf16.bf16 {%0, %1, %2, %3, %4, %5, %6, %7, %8, %9, %10, %11, %12, %13, %14, %15, %16, %17, %18, %19, %20, %21, %22, %23, %24, %25, %26, %27, %28, %29, %30, %31, %32, %33, %34, %35, %36, %37, %38, %39, %40, %41, %42, %43, %44, %45, %46, %47, %48, %49, %50, %51, %52, %53, %54, %55, %56, %57, %58, %59, %60, %61, %62, %63}, {%72, %73, %74, %75}, t, 1, 1, 1, 1;\n"
    "add.s64 t, %96, 768;\nwgmma.mma_async.sync.aligned.m64n128k16.f32.bf16.bf16 {%0, %1, %2, %3, %4, %5, %6, %7, %8, %9, %10, %11, %12, %13, %14, %15, %16, %17, %18, %19, %20, %21, %22, %23, %24, %25, %26, %27, %28, %29, %30, %31, %32, %33, %34, %35, %36, %37, %38, %39, %40, %41, %42, %43, %44, %45, %46, %47, %48, %49, %50, %51, %52, %53, %54, %55, %56, %57, %58, %59, %60, %61, %62, %63}, {%76, %77, %78, %79}, t, 1, 1, 1, 1;\n"
    "add.s64 t, %96, 1024;\nwgmma.mma_async.sync.aligned.m64n128k16.f32.bf16.bf16 {%0, %1, %2, %3, %4, %5, %6, %7, %8, %9, %10, %11, %12, %13, %14, %15, %16, %17, %18, %19, %20, %21, %22, %23, %24, %25, %26, %27, %28, %29, %30, %31, %32, %33, %34, %35, %36, %37, %38, %39, %40, %41, %42, %43, %44, %45, %46, %47, %48, %49, %50, %51, %52, %53, %54, %55, %56, %57, %58, %59, %60, %61, %62, %63}, {%80, %81, %82, %83}, t, 1, 1, 1, 1;\n"
    "add.s64 t, %96, 1280;\nwgmma.mma_async.sync.aligned.m64n128k16.f32.bf16.bf16 {%0, %1, %2, %3, %4, %5, %6, %7, %8, %9, %10, %11, %12, %13, %14, %15, %16, %17, %18, %19, %20, %21, %22, %23, %24, %25, %26, %27, %28, %29, %30, %31, %32, %33, %34, %35, %36, %37, %38, %39, %40, %41, %42, %43, %44, %45, %46, %47, %48, %49, %50, %51, %52, %53, %54, %55, %56, %57, %58, %59, %60, %61, %62, %63}, {%84, %85, %86, %87}, t, 1, 1, 1, 1;\n"
    "@w bar.arrive 2, 256;\n@!w bar.arrive 1, 256;\n"
    "add.s64 t, %96, 1536;\nwgmma.mma_async.sync.aligned.m64n128k16.f32.bf16.bf16 {%0, %1, %2, %3, %4, %5, %6, %7, %8, %9, %10, %11, %12, %13, %14, %15, %16, %17, %18, %19, %20, %21, %22, %23, %24, %25, %26, %27, %28, %29, %30, %31, %32, %33, %34, %35, %36, %37, %38, %39, %40, %41, %42, %43, %44, %45, %46, %47, %48, %49, %50, %51, %52, %53, %54, %55, %56, %57, %58, %59, %60, %61, %62, %63}, {%88, %89, %90, %91}, t, 1, 1, 1, 1;\n"
    "add.s64 t, %96, 1792;\nwgmma.mma_async.sync.aligned.m64n128k16.f32.bf16.bf16 {%0, %1, %2, %3, %4, %5, %6, %7, %8, %9, %10, %11, %12, %13, %14, %15, %16, %17, %18, %19, %20, %21, %22, %23, %24, %25, %26, %27, %28, %29, %30, %31, %32, %33, %34, %35, %36, %37, %38, %39, %40, %41, %42, %43, %44, %45, %46, %47, %48, %49, %50, %51, %52, %53, %54, %55, %56, %57, %58, %59, %60, %61, %62, %63}, {%92, %93, %94, %95}, t, 1, 1, 1, 1;\n"
    "wgmma.commit_group.sync.aligned;\n"
    "bra.uni LE;\nLH:\n"
    "wgmma.fence.sync.aligned;\n"
    "add.s64 t, %96, 0;\nwgmma.mma_async.sync.aligned.m64n128k16.f32.bf16.bf16 {%0, %1, %2, %3, %4, %5, %6, %7, %8, %9, %10, %11, %12, %13, %14, %15, %16, %17, %18, %19, %20, %21, %22, %23, %24, %25, %26, %27, %28, %29, %30, %31, %32, %33, %34, %35, %36, %37, %38, %39, %40, %41, %42, %43, %44, %45, %46, %47, %48, %49, %50, %51, %52, %53, %54, %55, %56, %57, %58, %59, %60, %61, %62, %63}, {%80, %81, %82, %83}, t, s, 1, 1, 1;\n"
    "add.s64 t, %96, 256;\nwgmma.mma_async.sync.aligned.m64n128k16.f32.bf16.bf16 {%0, %1, %2, %3, %4, %5, %6, %7, %8, %9, %10, %11, %12, %13, %14, %15, %16, %17, %18, %19, %20, %21, %22, %23, %24, %25, %26, %27, %28, %29, %30, %31, %32, %33, %34, %35, %36, %37, %38, %39, %40, %41, %42, %43, %44, %45, %46, %47, %48, %49, %50, %51, %52, %53, %54, %55, %56, %57, %58, %59, %60, %61, %62, %63}, {%84, %85, %86, %87}, t, 1, 1, 1, 1;\n"
    "@w bar.arrive 2, 256;\n@!w bar.arrive 1, 256;\n"
    "add.s64 t, %96, 512;\nwgmma.mma_async.sync.aligned.m64n128k16.f32.bf16.bf16 {%0, %1, %2, %3, %4, %5, %6, %7, %8, %9, %10, %11, %12, %13, %14, %15, %16, %17, %18, %19, %20, %21, %22, %23, %24, %25, %26, %27, %28, %29, %30, %31, %32, %33, %34, %35, %36, %37, %38, %39, %40, %41, %42, %43, %44, %45, %46, %47, %48, %49, %50, %51, %52, %53, %54, %55, %56, %57, %58, %59, %60, %61, %62, %63}, {%88, %89, %90, %91}, t, 1, 1, 1, 1;\n"
    "add.s64 t, %96, 768;\nwgmma.mma_async.sync.aligned.m64n128k16.f32.bf16.bf16 {%0, %1, %2, %3, %4, %5, %6, %7, %8, %9, %10, %11, %12, %13, %14, %15, %16, %17, %18, %19, %20, %21, %22, %23, %24, %25, %26, %27, %28, %29, %30, %31, %32, %33, %34, %35, %36, %37, %38, %39, %40, %41, %42, %43, %44, %45, %46, %47, %48, %49, %50, %51, %52, %53, %54, %55, %56, %57, %58, %59, %60, %61, %62, %63}, {%92, %93, %94, %95}, t, 1, 1, 1, 1;\n"
    "wgmma.commit_group.sync.aligned;\n"
    "LE:\n}\n"
    : "+f"(d[0]), "+f"(d[1]), "+f"(d[2]), "+f"(d[3]), "+f"(d[4]), "+f"(d[5]), "+f"(d[6]), "+f"(d[7]), "+f"(d[8]), "+f"(d[9]), "+f"(d[10]), "+f"(d[11]), "+f"(d[12]), "+f"(d[13]), "+f"(d[14]), "+f"(d[15]), "+f"(d[16]), "+f"(d[17]), "+f"(d[18]), "+f"(d[19]), "+f"(d[20]), "+f"(d[21]), "+f"(d[22]), "+f"(d[23]), "+f"(d[24]), "+f"(d[25]), "+f"(d[26]), "+f"(d[27]), "+f"(d[28]), "+f"(d[29]), "+f"(d[30]), "+f"(d[31]), "+f"(d[32]), "+f"(d[33]), "+f"(d[34]), "+f"(d[35]), "+f"(d[36]), "+f"(d[37]), "+f"(d[38]), "+f"(d[39]), "+f"(d[40]), "+f"(d[41]), "+f"(d[42]), "+f"(d[43]), "+f"(d[44]), "+f"(d[45]), "+f"(d[46]), "+f"(d[47]), "+f"(d[48]), "+f"(d[49]), "+f"(d[50]), "+f"(d[51]), "+f"(d[52]), "+f"(d[53]), "+f"(d[54]), "+f"(d[55]), "+f"(d[56]), "+f"(d[57]), "+f"(d[58]), "+f"(d[59]), "+f"(d[60]), "+f"(d[61]), "+f"(d[62]), "+f"(d[63])
    : "r"(p[0]), "r"(p[1]), "r"(p[2]), "r"(p[3]), "r"(p[4]), "r"(p[5]), "r"(p[6]), "r"(p[7]), "r"(p[8]), "r"(p[9]), "r"(p[10]), "r"(p[11]), "r"(p[12]), "r"(p[13]), "r"(p[14]), "r"(p[15]), "r"(p[16]), "r"(p[17]), "r"(p[18]), "r"(p[19]), "r"(p[20]), "r"(p[21]), "r"(p[22]), "r"(p[23]), "r"(p[24]), "r"(p[25]), "r"(p[26]), "r"(p[27]), "r"(p[28]), "r"(p[29]), "r"(p[30]), "r"(p[31]), "l"(db), "r"(full), "r"(acc), "r"(wg) : "memory");
}

constexpr int NCTA = 132, NREG = 128;
constexpr int UNIT = 16384, NUNIT = 14;
constexpr uint32_t SMEM_BASE = 1024;
constexpr int SM_BAR = NUNIT * UNIT;
constexpr int SM_GATE = SM_BAR + 1024;
constexpr int SMEM_BYTES = SM_BAR + 1536;
constexpr int UPITCH = 4160, UCH = 2 * UPITCH;
constexpr float QSCALE = 0.08838834764831845f * 1.4426950408889634f;
constexpr float BOUND2 = 60.f * 60.f / 1.15f;
#define CONV_REG 5
constexpr int C_KV = 0;
constexpr int C_CTX = 32;
constexpr int C_U = 48;
constexpr int C_Z = 80;
constexpr int C_GATE = 88;
constexpr int C_EXIT = 89;
#define PRE_EARLY 2
#define PRE_HALF 1
#define ATT_SPLIT 6
#define NFIRST 4
#define PRE_DELAY 0
#define FINAL_ST 1
#define Z_AT 60
#define PRE_DELAY_BAR 9
#define PRE_FMA 0
#define PRE_SLEEP 300
#define GATE_SLEEP 1000
#define GATE_EARLY 1
#define OC_S0 2
#define OC_S1 11
#define OC_POST 0
#define OC_L0 18
#define OC_L1 18
#define ST_1 4
#define ST_D 2
#define ST_0 1
#define ST_0D 0
#define SCH_KV 0x6665544433221100ull
#define SCH_Q 0x6665544433221100ull
#define NK_AT 1
#ifndef NV_AT
#define NV_AT 3
#endif
#define DS_A 0
#define DS_B 4
#define CHK_LO 1
#define V1F 0
#define K1V0 0
#define TFMA 0
#define FGAP 600
#define FGAP2 200
#define NF0 1
#define HOISTW 0
#define BARP 1
#define EF 127
#define POL(bit) (((EF >> (bit)) & 1) != 0)
constexpr int C_WAR = 96;
constexpr int C_NUM = 112;
constexpr int CSTRIDE = 32;
constexpr int SM_KMAX = SM_BAR + 640, SM_DUMMY = SM_BAR + 648, SM_PRE = SM_BAR + 112, SM_SIG = SM_BAR + 256, SM_RDY = SM_BAR + 384;
enum { SIG_KV = 0, SIG_CTX = 2, SIG_Z = 4, SIG_DONE = 8, SIG_WAR = 9, SIG_ATT = 10 };
enum { RDY_KV = 0, RDY_CTX = 2, RDY_WAR = 4, RDY_G = 5, RDY_X = 6, RDY_AUX = 7, RDY_U = 8, RDY_Z = 9 };
enum { PH_PRE = 1, PH_KV = 2, PH_ATT = 4, PH_CONV = 8, PH_OUT = 16, PH_ALL = 31 };

constexpr uint32_t T_CTX = 0, T_KV = 16 * 32 * 32768, T_BYTES = T_KV + 32 * 16 * 65536;
__device__ __align__(1024) uint8_t g_T[T_BYTES];
__device__ __align__(1024) uint8_t g_u[1024 * UCH];
__device__ __align__(1024) __nv_bfloat16 g_z[1024 * 2048];
__device__ __align__(1024) float g_gate[2048];
__device__ __align__(1024) float g_kn2[32 * 128];
__device__ __align__(1024) unsigned g_cnt[C_NUM * CSTRIDE];

struct __align__(64) Maps { CUtensorMap c, wk, wv, x, wq, wo, h, z, out, ctx, k, v; };
struct Params {
  const __nv_bfloat16 *x, *shift, *D, *gw;
  __nv_bfloat16* out;
};

__device__ __forceinline__ void wg_fence() { asm volatile("wgmma.fence.sync.aligned;" ::: "memory"); }
__device__ __forceinline__ void wg_commit() { asm volatile("wgmma.commit_group.sync.aligned;" ::: "memory"); }
template<int N> __device__ __forceinline__ void wg_wait() { asm volatile("wgmma.wait_group.sync.aligned %0;" :: "n"(N) : "memory"); }
__device__ __forceinline__ uint64_t odesc(uint32_t addr, uint32_t lbo, uint32_t sbo, uint32_t swz) {
  uint64_t d = (uint64_t)(addr >> 4) + (((uint64_t)(lbo >> 4) << 16) | ((uint64_t)(sbo >> 4) << 32) | ((uint64_t)swz << 62));
  asm volatile("" : "+l"(d));
  return d;
}
__device__ __forceinline__ void mbar_init(uint32_t bar, int cnt) { asm volatile("mbarrier.init.shared::cta.b64 [%0], %1;" :: "r"(bar), "r"(cnt)); }
__device__ __forceinline__ void mbar_expect(uint32_t bar, uint32_t bytes) { asm volatile("mbarrier.arrive.expect_tx.shared::cta.b64 _, [%0], %1;" :: "r"(bar), "r"(bytes) : "memory"); }
__device__ __forceinline__ void mbar_arrive(uint32_t bar) { asm volatile("mbarrier.arrive.shared::cta.b64 _, [%0];" :: "r"(bar) : "memory"); }
__device__ __forceinline__ void mbar_arrive_n(uint32_t bar, int n) { asm volatile("mbarrier.arrive.shared::cta.b64 _, [%0], %1;" :: "r"(bar), "r"(n) : "memory"); }
__device__ __forceinline__ void mbar_wait(uint32_t bar, uint32_t parity) {
  asm volatile("{\n.reg .pred p;\nLW:\nmbarrier.try_wait.parity.shared::cta.b64 p, [%0], %1;\n@!p bra LW;\n}\n" :: "r"(bar), "r"(parity) : "memory");
}
__device__ __forceinline__ void mbar_wait_slow(uint32_t bar, uint32_t parity) {
  asm volatile("{\n.reg .pred p;\n.reg .u32 n;\nmov.u32 n, 0;\n"
    "LW:\nmbarrier.test_wait.parity.shared::cta.b64 p, [%0], %1;\n@p bra LD;\n"
    "nanosleep.u32 128;\nadd.u32 n, n, 1;\nsetp.lt.u32 p, n, 4194304;\n@p bra LW;\ntrap;\nLD:\n}\n" :: "r"(bar), "r"(parity) : "memory");
}
__device__ __forceinline__ void mbar_wait_all(uint32_t bar, uint32_t parity) {
  asm volatile("{\n.reg .pred p, q;\nLW:\nmbarrier.try_wait.parity.shared::cta.b64 p, [%0], %1;\nvote.sync.all.pred q, p, 0xffffffff;\n@!q bra.uni LW;\n}\n" :: "r"(bar), "r"(parity) : "memory");
}
__device__ __forceinline__ void cnt_wait(const unsigned* p, unsigned target) {
  asm volatile("{\n.reg .pred p;\n.reg .u32 n, v;\nmov.u32 n, 0;\n"
    "LW:\nld.relaxed.gpu.global.u32 v, [%0];\nsetp.ge.u32 p, v, %1;\n@p bra LD;\n"
    "nanosleep.u32 64;\nadd.u32 n, n, 1;\nsetp.lt.u32 p, n, 4194304;\n@p bra LW;\ntrap;\nLD:\nfence.acquire.gpu;\nfence.proxy.async.global;\n}\n" :: "l"(p), "r"(target) : "memory");
}
__device__ __forceinline__ void cnt_signal(unsigned* p, int lane) {
  __syncwarp();
  if (lane == 0) asm volatile("red.release.gpu.global.add.u32 [%0], 1;" :: "l"(p) : "memory");
}
__device__ __forceinline__ void cnt_publish(unsigned* p, unsigned n, bool fence) {
  if (fence) asm volatile("fence.release.gpu;" ::: "memory");
  asm volatile("red.relaxed.gpu.global.add.u32 [%0], %1;" :: "l"(p), "r"(n) : "memory");
}
__device__ __forceinline__ uint64_t pol_first() { uint64_t p; asm("createpolicy.fractional.L2::evict_first.b64 %0, 1.0;" : "=l"(p)); return p; }
__device__ __forceinline__ void bulk_g2s(uint32_t dst, const void* src, uint32_t bytes, uint32_t bar, bool stream = false) {
  if (stream) asm volatile("cp.async.bulk.shared::cluster.global.mbarrier::complete_tx::bytes.L2::cache_hint [%0], [%1], %2, [%3], %4;" :: "r"(dst), "l"(src), "r"(bytes), "r"(bar), "l"(pol_first()) : "memory");
  else asm volatile("cp.async.bulk.shared::cluster.global.mbarrier::complete_tx::bytes [%0], [%1], %2, [%3];" :: "r"(dst), "l"(src), "r"(bytes), "r"(bar) : "memory");
}
__device__ __forceinline__ void tma2d(uint32_t dst, const CUtensorMap* m, int x, int y, uint32_t bar, bool stream = false) {
  if (stream) asm volatile("cp.async.bulk.tensor.2d.shared::cluster.global.mbarrier::complete_tx::bytes.L2::cache_hint [%0], [%1, {%3, %4}], [%2], %5;" :: "r"(dst), "l"(m), "r"(bar), "r"(x), "r"(y), "l"(pol_first()) : "memory");
  else asm volatile("cp.async.bulk.tensor.2d.shared::cluster.global.mbarrier::complete_tx::bytes [%0], [%1, {%3, %4}], [%2];" :: "r"(dst), "l"(m), "r"(bar), "r"(x), "r"(y) : "memory");
}
__device__ __forceinline__ void tma3d(uint32_t dst, const CUtensorMap* m, int x, int y, int z, uint32_t bar, bool stream = false) {
  if (stream) asm volatile("cp.async.bulk.tensor.3d.shared::cluster.global.mbarrier::complete_tx::bytes.L2::cache_hint [%0], [%1, {%3, %4, %5}], [%2], %6;" :: "r"(dst), "l"(m), "r"(bar), "r"(x), "r"(y), "r"(z), "l"(pol_first()) : "memory");
  else asm volatile("cp.async.bulk.tensor.3d.shared::cluster.global.mbarrier::complete_tx::bytes [%0], [%1, {%3, %4, %5}], [%2];" :: "r"(dst), "l"(m), "r"(bar), "r"(x), "r"(y), "r"(z) : "memory");
}
__device__ __forceinline__ void tma4d(uint32_t dst, const CUtensorMap* m, int x, int y, int z, int w, uint32_t bar, bool stream = false) {
  if (stream) asm volatile("cp.async.bulk.tensor.4d.shared::cluster.global.mbarrier::complete_tx::bytes.L2::cache_hint [%0], [%1, {%3, %4, %5, %6}], [%2], %7;" :: "r"(dst), "l"(m), "r"(bar), "r"(x), "r"(y), "r"(z), "r"(w), "l"(pol_first()) : "memory");
  else asm volatile("cp.async.bulk.tensor.4d.shared::cluster.global.mbarrier::complete_tx::bytes [%0], [%1, {%3, %4, %5, %6}], [%2];" :: "r"(dst), "l"(m), "r"(bar), "r"(x), "r"(y), "r"(z), "r"(w) : "memory");
}
__device__ __forceinline__ void bulk_g2s_mc(uint32_t dst, const void* src, uint32_t bytes, uint32_t bar, bool stream = false) {
  if (stream) asm volatile("cp.async.bulk.shared::cluster.global.mbarrier::complete_tx::bytes.multicast::cluster.L2::cache_hint [%0], [%1], %2, [%3], %4, %5;" :: "r"(dst), "l"(src), "r"(bytes), "r"(bar), "h"((uint16_t)3), "l"(pol_first()) : "memory");
  else asm volatile("cp.async.bulk.shared::cluster.global.mbarrier::complete_tx::bytes.multicast::cluster [%0], [%1], %2, [%3], %4;" :: "r"(dst), "l"(src), "r"(bytes), "r"(bar), "h"((uint16_t)3) : "memory");
}
__device__ __forceinline__ void tma2d_mc(uint32_t dst, const CUtensorMap* m, int x, int y, uint32_t bar, bool stream = false) {
  if (stream) asm volatile("cp.async.bulk.tensor.2d.shared::cluster.global.mbarrier::complete_tx::bytes.multicast::cluster.L2::cache_hint [%0], [%1, {%3, %4}], [%2], %5, %6;" :: "r"(dst), "l"(m), "r"(bar), "r"(x), "r"(y), "h"((uint16_t)3), "l"(pol_first()) : "memory");
  else asm volatile("cp.async.bulk.tensor.2d.shared::cluster.global.mbarrier::complete_tx::bytes.multicast::cluster [%0], [%1, {%3, %4}], [%2], %5;" :: "r"(dst), "l"(m), "r"(bar), "r"(x), "r"(y), "h"((uint16_t)3) : "memory");
}
__device__ __forceinline__ void tma3d_mc(uint32_t dst, const CUtensorMap* m, int x, int y, int z, uint32_t bar, bool stream = false) {
  if (stream) asm volatile("cp.async.bulk.tensor.3d.shared::cluster.global.mbarrier::complete_tx::bytes.multicast::cluster.L2::cache_hint [%0], [%1, {%3, %4, %5}], [%2], %6, %7;" :: "r"(dst), "l"(m), "r"(bar), "r"(x), "r"(y), "r"(z), "h"((uint16_t)3), "l"(pol_first()) : "memory");
  else asm volatile("cp.async.bulk.tensor.3d.shared::cluster.global.mbarrier::complete_tx::bytes.multicast::cluster [%0], [%1, {%3, %4, %5}], [%2], %6;" :: "r"(dst), "l"(m), "r"(bar), "r"(x), "r"(y), "r"(z), "h"((uint16_t)3) : "memory");
}
__device__ __forceinline__ void map_pf(const CUtensorMap* m) { asm volatile("prefetch.tensormap [%0];" :: "l"(m) : "memory"); }
__device__ __forceinline__ void tma2d_store(const CUtensorMap* m, uint32_t src, int x, int y) {
  if (POL(12)) asm volatile("cp.async.bulk.tensor.2d.global.shared::cta.bulk_group.L2::cache_hint [%0, {%2, %3}], [%1], %4;" :: "l"(m), "r"(src), "r"(x), "r"(y), "l"(pol_first()) : "memory");
  else asm volatile("cp.async.bulk.tensor.2d.global.shared::cta.bulk_group [%0, {%2, %3}], [%1];" :: "l"(m), "r"(src), "r"(x), "r"(y) : "memory");
}
__device__ __forceinline__ bool elect() {
  uint32_t r; asm volatile("{\n.reg .pred p;\nelect.sync _|p, 0xffffffff;\nselp.u32 %0, 1, 0, p;\n}\n" : "=r"(r)); return r != 0;
}
__device__ __forceinline__ void cluster_arrive() { asm volatile("barrier.cluster.arrive;" ::: "memory"); }
__device__ __forceinline__ void cluster_wait() { asm volatile("barrier.cluster.wait;" ::: "memory"); }
__device__ __forceinline__ void bar_sync(int id, int n) { asm volatile("bar.sync %0, %1;" :: "r"(id), "r"(n) : "memory"); }
__device__ __forceinline__ void bar_arrive(int id, int n) { asm volatile("bar.arrive %0, %1;" :: "r"(id), "r"(n) : "memory"); }
__device__ __forceinline__ int bar_and(int id, int n, int pred) {
  int r; asm volatile("{\n.reg .pred p, q;\nsetp.ne.b32 p, %3, 0;\nbar.red.and.pred q, %1, %2, p;\nselp.b32 %0, 1, 0, q;\n}\n" : "=r"(r) : "r"(id), "r"(n), "r"(pred) : "memory");
  return r;
}
__device__ __forceinline__ void fence_async_smem() { asm volatile("fence.proxy.async.shared::cta;" ::: "memory"); }
__device__ __forceinline__ float ex2(float x) { float y; asm("ex2.approx.ftz.f32 %0, %1;" : "=f"(y) : "f"(x)); return y; }
__device__ __forceinline__ float rcp(float x) { float y; asm("rcp.approx.ftz.f32 %0, %1;" : "=f"(y) : "f"(x)); return y; }
__device__ __forceinline__ uint32_t pack_bf16(float lo, float hi) { uint32_t r; asm("cvt.rn.bf16x2.f32 %0, %1, %2;" : "=r"(r) : "f"(hi), "f"(lo)); return r; }
__device__ __forceinline__ uint32_t hmul2(uint32_t a, uint32_t b) { uint32_t r; asm("mul.rn.bf16x2 %0, %1, %2;" : "=r"(r) : "r"(a), "r"(b)); return r; }
__device__ __forceinline__ uint32_t hadd2(uint32_t a, uint32_t b) { uint32_t r; asm("add.rn.bf16x2 %0, %1, %2;" : "=r"(r) : "r"(a), "r"(b)); return r; }
__device__ __forceinline__ uint32_t hfma2(uint32_t a, uint32_t b, uint32_t c) { uint32_t r; asm("fma.rn.bf16x2 %0, %1, %2, %3;" : "=r"(r) : "r"(a), "r"(b), "r"(c)); return r; }
__device__ __forceinline__ float bf_lo(uint32_t a) { return __uint_as_float(a << 16); }
__device__ __forceinline__ float bf_hi(uint32_t a) { return __uint_as_float(a & 0xffff0000u); }
__device__ __forceinline__ uint32_t lds32(uint32_t a) { uint32_t v; asm volatile("ld.shared.u32 %0, [%1];" : "=r"(v) : "r"(a) : "memory"); return v; }
__device__ __forceinline__ float2 lds64f(uint32_t a) { float2 v; asm volatile("ld.shared.v2.f32 {%0,%1}, [%2];" : "=f"(v.x), "=f"(v.y) : "r"(a) : "memory"); return v; }
__device__ __forceinline__ uint4 lds128(uint32_t a) { uint4 v; asm volatile("ld.shared.v4.u32 {%0,%1,%2,%3}, [%4];" : "=r"(v.x), "=r"(v.y), "=r"(v.z), "=r"(v.w) : "r"(a) : "memory"); return v; }
__device__ __forceinline__ void sts64f(uint32_t a, float x, float y) { asm volatile("st.shared.v2.f32 [%0], {%1,%2};" :: "r"(a), "f"(x), "f"(y) : "memory"); }
__device__ __forceinline__ void sts128(uint32_t a, uint4 v) { asm volatile("st.shared.v4.u32 [%0], {%1,%2,%3,%4};" :: "r"(a), "r"(v.x), "r"(v.y), "r"(v.z), "r"(v.w) : "memory"); }
template<int OFF> __device__ __forceinline__ void sts128o(uint32_t a, uint4 v) { asm volatile("st.shared.v4.u32 [%0+%5], {%1,%2,%3,%4};" :: "r"(a), "r"(v.x), "r"(v.y), "r"(v.z), "r"(v.w), "n"(OFF) : "memory"); }
__device__ __forceinline__ void ldsm4(uint32_t a, uint32_t& r0, uint32_t& r1, uint32_t& r2, uint32_t& r3) {
  asm volatile("ldmatrix.sync.aligned.m8n8.x4.shared.b16 {%0,%1,%2,%3}, [%4];" : "=r"(r0), "=r"(r1), "=r"(r2), "=r"(r3) : "r"(a) : "memory");
}
__device__ __forceinline__ void ldsm4t(uint32_t a, uint32_t& r0, uint32_t& r1, uint32_t& r2, uint32_t& r3) {
  asm volatile("ldmatrix.sync.aligned.m8n8.x4.trans.shared.b16 {%0,%1,%2,%3}, [%4];" : "=r"(r0), "=r"(r1), "=r"(r2), "=r"(r3) : "r"(a) : "memory");
}
__device__ __forceinline__ void stsm4(uint32_t a, uint32_t r0, uint32_t r1, uint32_t r2, uint32_t r3) {
  asm volatile("stmatrix.sync.aligned.m8n8.x4.shared.b16 [%0], {%1,%2,%3,%4};" :: "r"(a), "r"(r0), "r"(r1), "r"(r2), "r"(r3) : "memory");
}
template<int N> __device__ __forceinline__ void fence_regs(float (&d)[N]) {
#pragma unroll
  for (int i = 0; i < N; i++) asm volatile("" : "+f"(d[i]) :: "memory");
}
template<int N> __device__ __forceinline__ void fence_regs(uint32_t (&d)[N]) {
#pragma unroll
  for (int i = 0; i < N; i++) asm volatile("" : "+r"(d[i]) :: "memory");
}
__device__ __forceinline__ void sched_fence(float x, uint32_t dummy) {
  asm volatile("{\n.reg .pred p;\nsetp.eq.u32 p, %0, 0x7fc12345;\n@p st.shared.u32 [%1], %0;\n}\n" :: "r"(__float_as_uint(x)), "r"(dummy) : "memory");
}
#define ROT 0
#define CTAID blockIdx.x
#define PTRACE 0
#define TS(role, i)
#define TSA(i)
#define TS2(role, i)
#define TR(obj, role, tag)

#define SHADOW if (gridDim.y == 1)

struct Prod {
  uint32_t base, mask; int lane, nt;
  __device__ __forceinline__ uint32_t full(int u) const { return base + SM_BAR + 8 * u; }
  __device__ __forceinline__ uint32_t addr(int u) const { return base + u * UNIT; }
  __device__ __forceinline__ void acquire(int u, int n) {
    const int v = u + min(lane, n - 1);
    mbar_wait_all(base + SM_BAR + 128 + 8 * v, mask >> v);
    mask ^= ((1u << n) - 1) << u;
    TR(*this, 2, 16 + u);
  }
  __device__ __forceinline__ void acquire_slow(int u, int n) {
    for (int i = 0; i < n; i++) mbar_wait_slow(base + SM_BAR + 128 + 8 * (u + i), mask >> (u + i));
    mask ^= ((1u << n) - 1) << u;
  }
};
struct Cons {
  uint32_t base, rel, mask; int lane, warp, wg, nt;
  __device__ __forceinline__ uint32_t addr(int u) const { return base + u * UNIT; }
  __device__ __forceinline__ static uint32_t daddr(int u) { return SMEM_BASE + u * UNIT; }
  __device__ __forceinline__ void wait(int u) { TR(*this, wg, 1); mbar_wait(base + SM_BAR + 8 * u, mask >> u); mask ^= 1u << u; TR(*this, wg, 2); }
  __device__ __forceinline__ void skip(int u) { mask ^= 1u << u; }
  __device__ __forceinline__ void release(int u, int n) {
    TR(*this, wg, 5);
    asm volatile("{\n.reg .pred p;\nsetp.lt.s32 p, %1, %2;\n@p mbarrier.arrive.shared::cluster.b64 _, [%0];\n}\n" :: "r"(rel + 8 * u), "r"(lane & 15), "r"(n) : "memory");
  }
  __device__ __forceinline__ void release2(int u) {
    asm volatile("{\n.reg .pred p;\nsetp.eq.s32 p, %1, 0;\n@p mbarrier.arrive.shared::cluster.b64 _, [%0], 2;\n}\n" :: "r"(rel + 8 * u), "r"(lane & 15) : "memory");
  }
  __device__ __forceinline__ void signal(int i) {
    __syncwarp();
    asm volatile("{\n.reg .pred p;\nsetp.eq.s32 p, %1, 0;\n@p mbarrier.arrive.shared::cta.b64 _, [%0];\n}\n" :: "r"(base + SM_SIG + 8 * i), "r"(lane) : "memory");
  }
  __device__ __forceinline__ void turn() { asm volatile("{\n.reg .pred p;\nsetp.eq.s32 p, %0, 0;\n@p bar.sync 1, 256;\n@!p bar.sync 2, 256;\n}\n" :: "r"(wg) : "memory"); TR(*this, wg, 3); }
  __device__ __forceinline__ void pass() { asm volatile("{\n.reg .pred p;\nsetp.eq.s32 p, %0, 0;\n@p bar.arrive 2, 256;\n@!p bar.arrive 1, 256;\n}\n" :: "r"(wg) : "memory"); TR(*this, wg, 4); }
  __device__ __forceinline__ void sync() { asm volatile("{\n.reg .pred p;\nsetp.eq.s32 p, %0, 0;\n@p bar.sync 3, 128;\n@!p bar.sync 4, 128;\n}\n" :: "r"(wg) : "memory"); }
};
__device__ __forceinline__ int gemm_unit(int ks) { return 3 * (ks & 3); }
template<int MASK> __device__ __forceinline__ int kv_slot(int h) { return MASK == PH_ALL ? h & 15 : h; }
__device__ __forceinline__ int out_mb(int cta) { return cta >> 3; }
__device__ __forceinline__ int out_nb(int cta) { return cta & 7; }
template<int MASK> constexpr int CV_REG = MASK == PH_ALL ? CONV_REG : 6;
template<int MASK> constexpr int CV_EXTRA = (1024 - NREG * CV_REG<MASK>) / (NCTA - NREG);
template<int MASK> __device__ __forceinline__ int conv_channel(int cta, int i) {
  return cta < NREG ? CV_EXTRA<MASK> * (NCTA - NREG) + cta * CV_REG<MASK> + i : (i >> 1) * 8 + (cta - NREG) * 2 + (i & 1);
}

template<int OFF, int N> __device__ __forceinline__ void pack_chunk(const float (&a)[N], float sc0, float sc1, uint4& v0, uint4& v1) {
  v0.x = pack_bf16(a[OFF + 0] * sc0, a[OFF + 1] * sc0); v0.y = pack_bf16(a[OFF + 4] * sc0, a[OFF + 5] * sc0);
  v0.z = pack_bf16(a[OFF + 8] * sc0, a[OFF + 9] * sc0); v0.w = pack_bf16(a[OFF + 12] * sc0, a[OFF + 13] * sc0);
  v1.x = pack_bf16(a[OFF + 2] * sc1, a[OFF + 3] * sc1); v1.y = pack_bf16(a[OFF + 6] * sc1, a[OFF + 7] * sc1);
  v1.z = pack_bf16(a[OFF + 10] * sc1, a[OFF + 11] * sc1); v1.w = pack_bf16(a[OFF + 14] * sc1, a[OFF + 15] * sc1);
}
template<int OFF, int N> __device__ __forceinline__ void pack_chunk(const float (&a)[N], uint4& v0, uint4& v1) {
  v0.x = pack_bf16(a[OFF + 0], a[OFF + 1]); v0.y = pack_bf16(a[OFF + 4], a[OFF + 5]);
  v0.z = pack_bf16(a[OFF + 8], a[OFF + 9]); v0.w = pack_bf16(a[OFF + 12], a[OFF + 13]);
  v1.x = pack_bf16(a[OFF + 2], a[OFF + 3]); v1.y = pack_bf16(a[OFF + 6], a[OFF + 7]);
  v1.z = pack_bf16(a[OFF + 10], a[OFF + 11]); v1.w = pack_bf16(a[OFF + 14], a[OFF + 15]);
}
__device__ __forceinline__ void sq_acc(const uint4& v, uint32_t& a) { a = hfma2(v.x, v.x, a); a = hfma2(v.y, v.y, a); a = hfma2(v.z, v.z, a); a = hfma2(v.w, v.w, a); }
__device__ __forceinline__ float norm2_max(uint32_t a0, uint32_t a1) {
  float n0 = bf_lo(a0) + bf_hi(a0), n1 = bf_lo(a1) + bf_hi(a1);
  n0 += __shfl_xor_sync(~0u, n0, 1); n1 += __shfl_xor_sync(~0u, n1, 1);
  n0 += __shfl_xor_sync(~0u, n0, 2); n1 += __shfl_xor_sync(~0u, n1, 2);
  return __uint_as_float(__reduce_max_sync(~0u, max(__float_as_uint(n0) & 0x7fffffffu, __float_as_uint(n1) & 0x7fffffffu)));
}

struct Pend { uint4 lo[8], hi[8]; uint32_t dst; float kn; };
__device__ __forceinline__ void pin(uint4 (&v)[8]) {
#pragma unroll
  for (int i = 0; i < 8; i++) asm volatile("" : "+r"(v[i].x), "+r"(v[i].y), "+r"(v[i].z), "+r"(v[i].w) :: "memory");
}
__device__ __forceinline__ void pack_o(const float (&o)[64], float i0, float i1, uint4 (&v)[8]) {
  pack_chunk<0>(o, i0, i1, v[0], v[1]); pack_chunk<16>(o, i0, i1, v[2], v[3]);
  pack_chunk<32>(o, i0, i1, v[4], v[5]); pack_chunk<48>(o, i0, i1, v[6], v[7]);
  pin(v);
}
__device__ __forceinline__ uint32_t atom_off(int lane) { return (lane >> 2) * 64 + (((lane ^ (lane >> 3)) & 3) << 4); }
__device__ __forceinline__ void stg128(void* p, const uint4& v, bool stream) {
  if (stream) asm volatile("st.global.L2::cache_hint.v4.u32 [%0], {%1,%2,%3,%4}, %5;" :: "l"(p), "r"(v.x), "r"(v.y), "r"(v.z), "r"(v.w), "l"(pol_first()) : "memory");
  else *(uint4*)p = v;
}
template<int J0, int J1, bool STREAM = false> __device__ __forceinline__ void tile_store(const uint4 (&v)[8], uint32_t dst, int lane) {
  uint8_t* d = g_T + (dst + atom_off(lane));
#pragma unroll
  for (int j = J0; j < J1; j++) { stg128(d + j * 512, v[2 * j], STREAM); stg128(d + j * 512 + 2048, v[2 * j + 1], STREAM); }
}
template<int I0, int I1> __device__ __forceinline__ void tile_store_if(bool on, const uint4 (&v)[8], const uint8_t* dst) {
  if constexpr (I0 < I1) {
    asm volatile("{\n.reg .pred p;\nsetp.ne.b32 p, %5, 0;\n@p st.v4.u32 [%0+%6], {%1,%2,%3,%4};\n}\n"
      :: "l"(dst), "r"(v[I0].x), "r"(v[I0].y), "r"(v[I0].z), "r"(v[I0].w), "r"((int)on), "n"((I0 >> 1) * 512 + (I0 & 1) * 2048) : "memory");
    tile_store_if<I0 + 1, I1>(on, v, dst);
  }
}
__device__ __forceinline__ float tile_norm2(const uint4 (&v)[8]) {
  uint32_t n0 = 0, n1 = 0, n2 = 0, n3 = 0;
#pragma unroll
  for (int j = 0; j < 2; j++) { sq_acc(v[2 * j], n0); sq_acc(v[2 * j + 1], n1); sq_acc(v[2 * j + 4], n2); sq_acc(v[2 * j + 5], n3); }
  return norm2_max(hadd2(n0, n2), hadd2(n1, n3));
}
template<uint64_t SCHED, bool FIRST> __device__ __forceinline__ void out_piece(Cons& c, Pend& w, int ks, bool both) {
  uint8_t* d = g_T + (w.dst + atom_off(c.lane));
#pragma unroll
  for (int i = 0; i < 16; i++) {
    const int at = (SCHED >> (4 * i)) & 15;
    if (FIRST ? at == 0 : (at > 0 && ks == at && (i < 8 || both))) *(uint4*)(d + (i >> 3) * 32768 + ((i >> 1) & 3) * 512 + (i & 1) * 2048) = i < 8 ? w.lo[i & 7] : w.hi[i & 7];
  }
  if (FIRST || !both) return;
  if (ks == NK_AT) w.kn = tile_norm2(w.lo);
  if (ks == NV_AT) {
    const float vn = tile_norm2(w.hi);
    if (c.lane == 0) g_kn2[((w.dst - T_KV) >> 16) * 8 + c.wg * 4 + c.warp] = (vn <= 1.0e20f && vn >= 1.0e-20f) ? w.kn : __uint_as_float(0x7f800000u);
  }
}
template<bool FIRST> __device__ __forceinline__ void kv_issue(Cons& c, float (&acc)[128], int u) {
  const uint64_t da = odesc(c.daddr(u) + c.wg * 8192, 16, 1024, 1), db = odesc(c.daddr(u + 1), 8192, 1024, 1);
  c.turn();
  wg_fence();
#pragma unroll
  for (int kk = 0; kk < 4; kk++) wgmma_ss_n256<1>(acc, da + kk * 2, db + kk * 128, !(FIRST && kk == 0));
  wg_commit();
  c.pass();
}
template<bool NEXT> __device__ __forceinline__ void cons_kv(Cons& c, int h, int hs, int g, Pend& w, bool pend_o) {
#pragma unroll 1
  for (int tile = 0; tile < 2; tile++) {
    float acc[128];
    if (!(NEXT && HOISTW) && tile == 0) c.wait(0);
    if (tile == 0 && h < 16) TS(c.wg, 16);
    kv_issue<true>(c, acc, 0);
    c.release(9, tile == 1 ? 3 : 0);
    if (tile == 1 && pend_o) mbar_wait(c.base + SM_RDY + 8 * RDY_WAR, 0);
    if (tile == 1 || pend_o) out_piece<SCH_KV, true>(c, w, 0, false);
#pragma unroll 1
    for (int ks = 1; ks < 8; ks++) {
      const int u = gemm_unit(ks);
      c.wait(u);
      wg_wait<0>();
      c.release(gemm_unit(ks - 1), 3);
      kv_issue<false>(c, acc, u);
      if (tile == 1 || pend_o) { out_piece<SCH_KV, false>(c, w, ks, tile); if (ks == ((SCH_KV >> 28) & 15) && tile == 0) c.signal(SIG_CTX); }
    }
    if (NEXT || tile == 0) c.wait(0);
    wg_wait<0>(); fence_regs(acc);
    if (!NEXT) c.release(9, tile == 1 ? 3 : 0);
    pack_chunk<0>(acc, w.lo[0], w.lo[1]);  pack_chunk<16>(acc, w.lo[2], w.lo[3]); pack_chunk<32>(acc, w.lo[4], w.lo[5]); pack_chunk<48>(acc, w.lo[6], w.lo[7]);
    pack_chunk<64>(acc, w.hi[0], w.hi[1]); pack_chunk<80>(acc, w.hi[2], w.hi[3]); pack_chunk<96>(acc, w.hi[4], w.hi[5]); pack_chunk<112>(acc, w.hi[6], w.hi[7]);
    pin(w.lo); pin(w.hi);
    w.dst = T_KV + (hs * 16 + 2 * g + tile) * 65536 + (c.wg * 4 + c.warp) * 4096;
  }
}
template<bool FIRST> __device__ __forceinline__ void q_issue(Cons& c, float (&a)[64], float (&b)[64], int u) {
  const uint64_t da = odesc(c.daddr(u) + c.wg * 8192, 16, 1024, 1), db = odesc(c.daddr(u + 2), 8192, 1024, 1);
  const uint64_t da2 = odesc(c.daddr(u + 1) + (1 - c.wg) * 8192, 16, 1024, 1);
  c.turn();
  wg_fence();
#pragma unroll
  for (int kk = 0; kk < 4; kk++) wgmma_ss_n128<1>(a, da + kk * 2, db + kk * 128, !(FIRST && kk == 0));
#pragma unroll
  for (int kk = 0; kk < 4; kk++) wgmma_ss_n128<1>(b, da2 + kk * 2, db + kk * 128, !(FIRST && kk == 0));
  wg_commit();
  c.pass();
}
__device__ __forceinline__ void q_step(Cons& c, float (&d)[64], int ua, int ub, int rowhalf) {
  const uint64_t da = odesc(c.daddr(ua) + rowhalf * 8192, 16, 1024, 1), db = odesc(c.daddr(ub), 8192, 1024, 1);
#pragma unroll
  for (int kk = 0; kk < 4; kk++) wgmma_ss_n128<1>(d, da + kk * 2, db + kk * 128, 1);
}
template<bool PEND_KV> __device__ __forceinline__ void cons_q(Cons& c, int h, Pend& w, float (&b)[64]) {
  float a[64];
  if (!PEND_KV) c.wait(0);
  q_issue<true>(c, a, b, 0);
  if (PEND_KV) { c.release(9, 3); out_piece<SCH_Q, true>(c, w, 0, true); }
#pragma unroll 1
  for (int ks = 1; ks < 14; ks++) {
    const int u = gemm_unit(ks);
    c.wait(u);
    wg_wait<0>();
    c.release(gemm_unit(ks - 1), 3);
    q_issue<false>(c, a, b, u);
    if (PEND_KV && ks <= (int)(SCH_Q >> 60)) { out_piece<SCH_Q, false>(c, w, ks, true); if (ks == (int)(SCH_Q >> 60)) c.signal(SIG_KV + (h >> 4)); }
  }
  c.wait(6); c.wait(9);
  wg_wait<0>();
  c.release(3, 3);
  c.turn();
  wg_fence();
  q_step(c, a, 6, 8, c.wg); q_step(c, a, 9, 11, c.wg); wg_commit();
  q_step(c, b, 7, 8, 1 - c.wg); wg_commit();
  c.pass();
  c.wait(0);
  const uint32_t q0 = c.addr(0) + (c.wg * 4 + c.warp) * 4096 + atom_off(c.lane);
  wg_wait<1>(); fence_regs(a);
  pack_o(a, QSCALE, QSCALE, w.lo);
  sts128o<0>(q0, w.lo[0]);    sts128o<2048>(q0, w.lo[1]); sts128o<512>(q0, w.lo[2]);  sts128o<2560>(q0, w.lo[3]);
  wg_wait<0>();
  c.release(6, 4);
  sts128o<1024>(q0, w.lo[4]); sts128o<3072>(q0, w.lo[5]); sts128o<1536>(q0, w.lo[6]); sts128o<3584>(q0, w.lo[7]);
  c.wait(12);
  fence_async_smem();
}

__device__ __forceinline__ void issue_qk(float (&s)[64], uint64_t da, uint64_t db) {
#pragma unroll
  for (int kk = 0; kk < 8; kk++) wgmma_ss_n128<0>(s, da + (kk >> 1) * 32 + (kk & 1) * 2, db + (kk >> 1) * 32 + (kk & 1) * 2, kk > 0);
  wg_commit();
}
template<int A, int B> __device__ __forceinline__ void exp_rng(float (&s)[64]) {
#pragma unroll
  for (int i = 4 * A; i < 4 * B; i++) s[i] = ex2(s[i]);
}
template<int A, int B> __device__ __forceinline__ void sum_rng(const float (&s)[64], float (&l)[4]) {
#pragma unroll
  for (int i = A; i < B; i++) { l[0] += s[4 * i]; l[1] += s[4 * i + 1]; l[2] += s[4 * i + 2]; l[3] += s[4 * i + 3]; }
}
template<int A, int B> __device__ __forceinline__ void cvt_p(const float (&s)[64], uint32_t (&p)[32]) {
#pragma unroll
  for (int i = 2 * A; i < 2 * B; i++) p[i] = pack_bf16(s[2 * i], s[2 * i + 1]);
}
template<int K0> __device__ __forceinline__ void mask_half(float (&s)[64], int warp, int lane) {
  const int l0 = warp + (2 * (lane & 3) <= (lane >> 2)), l1 = warp + (2 * (lane & 3) < (lane >> 2));
#pragma unroll
  for (int k = 0; k < 4; k++) {
    float* t = s + 8 * (K0 + k);
    if (k >= l0) { t[0] = -INFINITY; t[6] = -INFINITY; }
    if (k >= l1) { t[1] = -INFINITY; t[7] = -INFINITY; }
    if (k > warp) { t[2] = -INFINITY; t[3] = -INFINITY; }
    if (k >= warp) { t[4] = -INFINITY; t[5] = -INFINITY; }
  }
}
__device__ __forceinline__ void row_inv(float& l0, float& l1) {
  l0 += __shfl_xor_sync(~0u, l0, 1); l1 += __shfl_xor_sync(~0u, l1, 1);
  l0 += __shfl_xor_sync(~0u, l0, 2); l1 += __shfl_xor_sync(~0u, l1, 2);
  l0 = rcp(l0); l1 = rcp(l1);
}
__device__ __forceinline__ void softmax_safe(float (&s)[64], bool upper_only, float& m0, float& m1, float& sc0, float& sc1) {
  float a0 = m0, a1 = m1;
#pragma unroll
  for (int i = 0; i < 8; i++) { a0 = fmaxf(a0, fmaxf(s[4 * i], s[4 * i + 1])); a1 = fmaxf(a1, fmaxf(s[4 * i + 2], s[4 * i + 3])); }
  if (upper_only) { a0 = m0; a1 = m1; }
#pragma unroll
  for (int i = 8; i < 16; i++) { a0 = fmaxf(a0, fmaxf(s[4 * i], s[4 * i + 1])); a1 = fmaxf(a1, fmaxf(s[4 * i + 2], s[4 * i + 3])); }
  a0 = fmaxf(a0, __shfl_xor_sync(~0u, a0, 1)); a1 = fmaxf(a1, __shfl_xor_sync(~0u, a1, 1));
  a0 = fmaxf(a0, __shfl_xor_sync(~0u, a0, 2)); a1 = fmaxf(a1, __shfl_xor_sync(~0u, a1, 2));
  sc0 = ex2(m0 - a0); sc1 = ex2(m1 - a1);
  m0 = a0; m1 = a1;
#pragma unroll
  for (int i = 0; i < 16; i++) { s[4 * i] -= a0; s[4 * i + 1] -= a0; s[4 * i + 2] -= a1; s[4 * i + 3] -= a1; }
}
struct Att {
  float s[64], o[64], l[4], i0, i1, t0, t1; uint32_t p[32];
  float kn; uint32_t qaddr; const uint8_t* dst;
};
__device__ __forceinline__ uint32_t ctx_off(const Cons& c, int h, int qb, int rowhalf) { return T_CTX + (qb * 32 + h) * 32768 + (rowhalf * 4 + c.warp) * 4096; }
__device__ __forceinline__ int att_fast(const uint4 (&q)[8], float kn) {
  uint32_t a0 = 0, a1 = 0, a2 = 0, a3 = 0;
#pragma unroll
  for (int j = 0; j < 2; j++) { sq_acc(q[2 * j], a0); sq_acc(q[2 * j + 1], a1); sq_acc(q[2 * j + 4], a2); sq_acc(q[2 * j + 5], a3); }
  a0 = hadd2(a0, a2); a1 = hadd2(a1, a3);
  return __shfl_sync(~0u, __all_sync(~0u, (bf_lo(a0) + bf_hi(a0)) * kn <= 0.25f * BOUND2 && (bf_lo(a1) + bf_hi(a1)) * kn <= 0.25f * BOUND2), 0);
}
__device__ __forceinline__ int att_first(Cons& c, Att& a, int h, const Pend& w) {
  a.kn = __uint_as_float(lds32(c.base + SM_KMAX + 4 * (h >> 4)));
  a.qaddr = c.daddr(0) + c.wg * 16384;
  c.turn();
  wg_fence();
  issue_qk(a.s, odesc(a.qaddr, 16, 2048, 2), odesc(c.daddr(12), 16, 2048, 2));
  int fast = 0;
  SHADOW fast = att_fast(w.lo, a.kn);
  wg_fence();
  q_step(c, a.o, 10, 11, 1 - c.wg); wg_commit();
  c.pass();
#pragma unroll
  for (int i = 0; i < 8; i++) { a.p[4 * i] = w.lo[i].x; a.p[4 * i + 1] = w.lo[i].y; a.p[4 * i + 2] = w.lo[i].z; a.p[4 * i + 3] = w.lo[i].w; }
  a.l[0] = a.l[1] = a.l[2] = a.l[3] = 0.f; a.i0 = a.i1 = a.t0 = a.t1 = 0.25f / QSCALE;
  a.dst = (const uint8_t*)__cvta_shared_to_generic(c.addr(2) + (c.wg * 4 + c.warp) * 4096 + atom_off(c.lane));
  wg_wait<1>(); fence_regs(a.s);
  c.signal(SIG_ATT + (h >> 4));
  return fast;
}
template<bool NEXT> __device__ __forceinline__ void att_last(Cons& c, Att& a, Pend& w, int h, int g, bool drain) {
  const int uv = 6;
  if (drain) pack_o(a.o, rcp(a.i0), rcp(a.i1), w.hi);
  c.wait(uv);
  c.turn();
  fence_regs(a.o); fence_regs(a.p);
  wgmma_pv_sel(a.o, a.p, odesc(c.daddr(uv), 512, 2048, 2), !(drain && c.wg == 1), !drain, c.wg);
  a.i0 = a.l[0] + a.l[1]; a.i1 = a.l[2] + a.l[3];
  SHADOW row_inv(a.i0, a.i1);
  sched_fence(a.i0 + a.i1, c.base + SM_DUMMY);
  tile_store_if<0, 4>(drain, w.hi, a.dst);
  if (NEXT && HOISTW) c.wait(h < 16 ? 0 : 12);
  wg_wait<0>(); fence_regs(a.o); fence_regs(a.p);
  c.release(uv, 2);
  tile_store_if<4, 8>(drain, w.hi, a.dst);
  pack_o(a.o, a.i0, a.i1, w.lo);
  w.dst = ctx_off(c, h, g, 1 - c.wg); w.kn = 0.f;
}
template<bool NEXT> __device__ __forceinline__ void cons_att(Cons& c, Att& a, int h, int g, Pend& w) {
  int fast = att_first(c, a, h, w), fast2 = 0;
  float m0 = -INFINITY, m1 = -INFINITY, sc0 = 0.f, sc1 = 0.f;
  int uk = 10, ur = 10;
  bool fresh = false;
#pragma unroll 1
  for (int d = g - 15;;) {
    const bool lo = d == c.wg;
    if ((unsigned)d < 2 || !fast) {
      if ((unsigned)d < 2) {
        mask_half<4>(a.s, c.warp, c.lane);
        if (CHK_LO && lo) fast2 = att_fast(w.hi, a.kn);
        if (CHK_LO && d == 1) fast = fast2;
      }
      if (!fast) {
        if (d == 1) m0 = m1 = -INFINITY;
        softmax_safe(a.s, lo, m0, m1, sc0, sc1);
        a.l[0] *= sc0; a.l[1] *= sc0; a.l[2] *= sc1; a.l[3] *= sc1;
      }
    }
    exp_rng<8, 16>(a.s); sum_rng<8, 16>(a.s, a.l);
    exp_rng<ATT_SPLIT, 8>(a.s);
    sched_fence(((a.l[0] + a.l[1]) + (a.l[2] + a.l[3])) + (ATT_SPLIT < 8 ? a.s[4 * ATT_SPLIT + 3] : 0.f), c.base + SM_DUMMY);
    wg_wait<0>(); fence_regs(a.o); fence_regs(a.p);
    c.release(ur, 2);
    a.i0 += a.t0; a.i1 += a.t1;
    a.t0 = __shfl_xor_sync(~0u, a.i0, 2); a.t1 = __shfl_xor_sync(~0u, a.i1, 2);
    tile_store_if<DS_A, DS_B>(fresh, w.hi, a.dst);
    uk ^= 12; ur = 14 - uk;
    if (d == 0) a.qaddr += 32768;
    const uint64_t dq = odesc(a.qaddr, 16, 2048, 2), dk = odesc(c.daddr(uk) - (d + 1 == c.wg ? 16384 : 0), 16, 2048, 2), dv = odesc(c.daddr(ur), 512, 2048, 2);
    if (!lo) { exp_rng<0, ATT_SPLIT>(a.s); sum_rng<0, 8>(a.s, a.l); cvt_p<0, 16>(a.s, a.p); }
    else if (gridDim.y == 1) cvt_p<8, 16>(a.s, a.p);
    tile_store_if<DS_B, 8>(fresh, w.hi, a.dst);
    a.i0 += a.t0; a.i1 += a.t1;
    if (!fast || d == g + 1 || (unsigned)(d + 2 - CHK_LO) < 3 - CHK_LO) {
      if (!CHK_LO && d == -2) fast2 = att_fast(w.hi, a.kn);
      if (d == -1) fence_async_smem();
      if (!fast && d != 1 && d != g - 15) {
#pragma unroll
        for (int i = 0; i < 16; i++) { a.o[4 * i] *= sc0; a.o[4 * i + 1] *= sc0; a.o[4 * i + 2] *= sc1; a.o[4 * i + 3] *= sc1; }
      }
      if (d == 0) {
        a.i0 = a.l[0] + a.l[1]; a.i1 = a.l[2] + a.l[3];
        a.l[0] = a.l[1] = a.l[2] = a.l[3] = 0.f;
        uint32_t off = ctx_off(c, h, 15 - g, c.wg);
        asm volatile("" : "+r"(off));
        a.dst = g_T + (off + ((uint32_t)(uint64_t)a.dst & 511));
        if (!CHK_LO) fast = fast2;
      }
      if (d == g + 1) break;
    }
    d++;
    fresh = d == 2 || d == g - 14;
    if (c.wg == 0) c.wait(uk); else c.skip(uk);
    c.turn();
    fence_regs(a.o); fence_regs(a.p);
    wg_fence();
    issue_qk(a.s, dq, dk);
    a.t0 = __shfl_xor_sync(~0u, a.i0, 1); a.t1 = __shfl_xor_sync(~0u, a.i1, 1);
    if (fresh) pack_o(a.o, rcp(a.i0), rcp(a.i1), w.hi);
    wgmma_pv_sel(a.o, a.p, dv, !lo, !fresh, c.wg);
    tile_store_if<0, DS_A>(fresh, w.hi, a.dst);
    wg_wait<1>(); fence_regs(a.s);
    c.release(uk, 2);
    c.release(d == 0 ? 0 : 2, (d == 0 || d == g + 1) ? 2 : 0);
  }
  att_last<NEXT>(c, a, w, h, g, g == 0);
}

constexpr int CV_H = 1024, CV_U = 5120, CV_D = CV_U + 4128, CV_ROW = 1056;
template<int OFF> __device__ __forceinline__ uint32_t lds32o(uint32_t a) { uint32_t v; asm volatile("ld.shared.u32 %0, [%1+%2];" : "=r"(v) : "r"(a), "n"(OFF) : "memory"); return v; }
template<int G, int G1 = 16> __device__ __forceinline__ void conv_lda(uint32_t (&a)[64], uint32_t p) {
  a[4 * G + 0] = lds32o<-256 * G>(p);
  a[4 * G + 1] = lds32o<-256 * G - 128>(p);
  a[4 * G + 2] = lds32o<-256 * G + 16>(p);
  a[4 * G + 3] = lds32o<-256 * G - 112>(p);
  if constexpr (G + 1 < G1) conv_lda<G + 1, G1>(a, p);
}
struct CvAcc { float lo[16], hi[16]; };
__device__ __forceinline__ void fence_regs(CvAcc& d) { fence_regs(d.lo); fence_regs(d.hi); }
template<int R, int H> __device__ __forceinline__ void conv_mma_h(float (&d)[16], const uint32_t (&a)[64], uint64_t db) {
#pragma unroll
  for (int G = 0; G < 4 * R + 2 * H + 2; G++) wgmma_rs_n32<0>(d, a[4 * G], a[4 * G + 1], a[4 * G + 2], a[4 * G + 3], db + 64 * R + 32 * H - 16 * G, G > 0);
}
template<int T, int G0, int G1> __device__ __forceinline__ void conv_part(float (&d)[16], const uint32_t (&a)[64], uint64_t db) {
#pragma unroll
  for (int G = G0; G < G1; G++) wgmma_rs_n32<0>(d, a[4 * G], a[4 * G + 1], a[4 * G + 2], a[4 * G + 3], db + 32 * T - 16 * G, G > 0);
}
template<int R> __device__ __forceinline__ void conv_mma(CvAcc& d, const uint32_t (&a)[64], uint64_t db) { conv_mma_h<R, 0>(d.lo, a, db); conv_mma_h<R, 1>(d.hi, a, db); }
template<int C0> __device__ __forceinline__ void conv_st_h(const float (&d)[16], uint32_t wq, float& c0, float& c1) {
#pragma unroll
  for (int n = 0; n < 4; n++) { sts64f(wq + (C0 + n * 8) * 4, d[4 * n] + c0, d[4 * n + 1] + c1); c0 = d[4 * n + 2]; c1 = d[4 * n + 3]; }
}
template<int R> __device__ __forceinline__ void conv_st(const CvAcc& d, uint32_t wq, float& c0, float& c1) { conv_st_h<64 * R>(d.lo, wq, c0, c1); conv_st_h<64 * R + 32>(d.hi, wq, c0, c1); }
struct ConvTail { float t[64]; uint4 ua, uc; uint32_t D2; };
__device__ __forceinline__ void conv_emit(ConvTail& e, int ch, int tid) {
  fence_regs(e.t);
  float y[16];
#pragma unroll
  for (int i = 0; i < 16; i++) y[i] = (e.t[i] + e.t[16 + i]) + (e.t[32 + i] + e.t[48 + i]);
  uint4 z0, z1;
  z0.x = hadd2(pack_bf16(y[0], y[2]), hmul2(__byte_perm(e.ua.w, 0, 0x1032), e.D2));
  z0.y = hadd2(pack_bf16(y[4], y[6]), hmul2(__byte_perm(e.ua.z, 0, 0x1032), e.D2));
  z0.z = hadd2(pack_bf16(y[8], y[10]), hmul2(__byte_perm(e.ua.y, 0, 0x1032), e.D2));
  z0.w = hadd2(pack_bf16(y[12], y[14]), hmul2(__byte_perm(e.ua.x, 0, 0x1032), e.D2));
  z1.x = hadd2(pack_bf16(y[1], y[3]), hmul2(__byte_perm(e.uc.w, 0, 0x1032), e.D2));
  z1.y = hadd2(pack_bf16(y[5], y[7]), hmul2(__byte_perm(e.uc.z, 0, 0x1032), e.D2));
  z1.z = hadd2(pack_bf16(y[9], y[11]), hmul2(__byte_perm(e.uc.y, 0, 0x1032), e.D2));
  z1.w = hadd2(pack_bf16(y[13], y[15]), hmul2(__byte_perm(e.uc.x, 0, 0x1032), e.D2));
  uint4* zp = (uint4*)(g_z + (uint32_t)(ch * 2048 + tid * 16));
  zp[0] = z0; zp[1] = z1;
}
template<int MASK> __device__ __forceinline__ void cons_conv(Cons& c, int cta, int nch) {
  const int r = c.lane >> 2, q = c.lane & 3, tid = c.warp * 32 + c.lane;
  const uint32_t part = c.addr(4) - 2048 + (1 - c.wg) * (32 * CV_ROW) + 32;
  const uint32_t aoff = CV_U + ((r & 1) ? 0 : UPITCH) + 4 * (((2039 - r) >> 1) + q - 8 * c.warp);
  const uint32_t wq = part + (c.warp * 8 + r) * CV_ROW + q * 8, rq = part + tid * 8;
  uint32_t a[64];
  ConvTail e = {};
  c.wait(c.wg); c.skip(c.wg ^ 1);
  conv_lda<0>(a, c.addr(c.wg) + aoff);
  c.wait(4);
  sts64f(part + (tid >> 2) * CV_ROW - 32 + q * 8, 0.f, 0.f);
#pragma unroll 1
  for (int i = 0; i < nch / 2; i++) {
    const int u = 2 * (i & 1) + c.wg;
    CvAcc d0, d1, d2, d3;
    float c0 = 0.f, c1 = 0.f;
    const uint64_t db = odesc(c.daddr(u) + CV_H - 16, 16, 128, 0);
    c.turn();
    fence_regs(a);
    wg_fence();
    conv_mma<0>(d0, a, db); conv_mma<1>(d1, a, db); wg_commit();
    if (i > 0) {
      conv_emit(e, conv_channel<MASK>(cta, 2 * i - 2 + c.wg), tid);
      if ((i & 15) == 0) c.signal(SIG_Z + (i >> 4) - 1);
    }
    wg_fence();
    conv_mma_h<2, 0>(d2.lo, a, db); wg_commit();
    wg_wait<1>(); fence_regs(d0); fence_regs(d1);
    conv_st_h<0>(d0.lo, wq, c0, c1);
    wg_fence();
    conv_mma_h<2, 1>(d2.hi, a, db); wg_commit();
    conv_st_h<32>(d0.hi, wq, c0, c1);
    conv_mma_h<3, 0>(d3.lo, a, db);
    conv_st_h<64>(d1.lo, wq, c0, c1);
    conv_mma_h<3, 1>(d3.hi, a, db); wg_commit();
    c.pass();
    const int un = i + 1 < nch / 2 ? u ^ 2 : u;
    if (un != u) { c.wait(un); c.skip(un ^ 1); }
    wg_wait<1>(); fence_regs(d2);
    conv_st_h<96>(d1.hi, wq, c0, c1);
    conv_st<2>(d2, wq, c0, c1);
    {
      const int sw = (c.lane >> 2) & 1;
      const uint4 v0 = lds128(c.addr(u) + CV_U + 4064 - 32 * tid + 16 * sw), v1 = lds128(c.addr(u) + CV_U + 4080 - 32 * tid - 16 * sw);
      e.ua = sw ? v0 : v1; e.uc = sw ? v1 : v0;
    }
    e.D2 = lds32(c.addr(u) + CV_D);
    wg_wait<0>(); fence_regs(d3); fence_regs(a);
    conv_st<3>(d3, wq, c0, c1);
    conv_lda<0, 4>(a, c.addr(un) + aoff);
    c.sync();
    sched_fence(__uint_as_float(e.ua.x ^ e.uc.x ^ e.D2), c.base + SM_DUMMY);
    c.release2(u);
    conv_lda<4, 16>(a, c.addr(un) + aoff);
#pragma unroll
    for (int k = 0; k < 32; k++) { const float2 v = lds64f(rq + k * CV_ROW - (k >> 3) * 8); e.t[2 * k] = v.x; e.t[2 * k + 1] = v.y; }
  }
  conv_emit(e, conv_channel<MASK>(cta, nch - 2 + c.wg), tid);
  c.signal(SIG_Z + ((nch / 2 - 1) >> 4));
  c.release(4, 4);
}

constexpr int OC_PART = 13824, OC_ROW = 544;
__device__ __forceinline__ int out_next(int u) { return (0x84ac680u >> (2 * u)) & 15; }
struct Out { float acc[64]; int pu; uint64_t da, db; };
template<bool FIRST, bool REL, int W = 1, bool PRE = true, bool POST = false> __device__ __forceinline__ void out_step(Cons& c, Out& o, bool extra = false) {
  const int pu = o.pu, u = extra ? 2 : out_next(pu);
  o.pu = u;
  if (PRE) c.wait(u);
  const uint64_t da = o.da + (uint32_t)(u * 1024), db = o.db + (uint32_t)(u * 1024);
  wg_fence();
#pragma unroll
  for (int kk = 0; kk < 4; kk++) wgmma_ss_n128<1>(o.acc, da + (kk >> 1) * 32 + (kk & 1) * 2, db + kk * 128, !(FIRST && kk == 0));
  wg_commit();
  if (REL) { wg_wait<W>(); c.release(pu, 2); }
  if (POST) c.wait(out_next(u));
}
template<int I0, int I1> __device__ __forceinline__ void oc_red(float (&y)[8], uint32_t rq) {
#pragma unroll
  for (int i = I0; i < I1; i++) { const float v = __uint_as_float(lds32(rq + i * OC_ROW - (i >> 3) * 8)); y[i & 7] = i < 8 ? v : y[i & 7] + v; }
}
__device__ __forceinline__ void oc_emit(const float (&y)[8], const uint4& u, uint32_t D2, __nv_bfloat16* dst) {
  uint4 z;
  z.x = hadd2(pack_bf16(y[0], y[1]), hmul2(__byte_perm(u.w, 0, 0x1032), D2));
  z.y = hadd2(pack_bf16(y[2], y[3]), hmul2(__byte_perm(u.z, 0, 0x1032), D2));
  z.z = hadd2(pack_bf16(y[4], y[5]), hmul2(__byte_perm(u.y, 0, 0x1032), D2));
  z.w = hadd2(pack_bf16(y[6], y[7]), hmul2(__byte_perm(u.x, 0, 0x1032), D2));
  *(uint4*)dst = z;
}
__device__ __forceinline__ uint32_t mix(uint32_t og, uint32_t b, uint32_t ga) { return (TFMA & 1) ? hfma2(og, b, ga) : hadd2(ga, hmul2(og, b)); }
template<int MASK> __device__ __forceinline__ void cons_out(Cons& c, const Maps& M, const Params& P, int cta, Pend& w) {
  const int mb = out_mb(cta), nb = out_nb(cta);
  Out o;
  o.da = odesc(c.daddr(0) + c.wg * 8192, 16, 1024, 2); o.db = odesc(c.daddr(1), 8192, 1024, 1);
  o.pu = 5 + gridDim.y;
  out_step<true, false, 1, !(HOISTW && MASK == PH_ALL)>(c, o);
  int ks = 1;
#pragma unroll 1
  for (;; ks++) {
    if (MASK & PH_ATT) {
      if (ks == (c.wg ? ST_1 : ST_0)) tile_store<0, 1>(w.lo, w.dst, c.lane);
      if (ks == (c.wg ? ST_1 + ST_D : ST_0 + ST_0D / 2)) tile_store<1, 2>(w.lo, w.dst, c.lane);
      if (ks == (c.wg ? ST_1 + 2 * ST_D : ST_0 + ST_0D)) tile_store<2, 3>(w.lo, w.dst, c.lane);
      if (ks == (c.wg ? ST_1 + 3 * ST_D : ST_0 + 3 * ST_0D / 2)) { tile_store<3, 4>(w.lo, w.dst, c.lane); c.signal(SIG_CTX + 1); }
    }
    if (ks == (c.wg ? OC_S1 : OC_S0)) break;
    out_step<false, true>(c, o, ks == 1);
  }
  if (MASK & PH_CONV) {
    const int r = c.lane >> 2, q = c.lane & 3, tid = c.warp * 32 + c.lane, u = 2 * c.wg;
    const uint32_t ub = c.addr(u), part = ub + OC_PART + 32;
    const uint32_t ap = ub + CV_U + ((r & 1) ? 0 : UPITCH) + 4 * (((2039 - r) >> 1) + q - 8 * c.warp);
    const uint32_t wq = part + (c.warp * 8 + r) * OC_ROW + q * 8, rq = part + tid * 4;
    const int nr = (CV_REG<MASK> + 1 - c.wg) >> 1;
#define STEP(N) out_step<false, true, 1, !OC_POST, OC_POST>(c, o);
#pragma unroll 1
    for (int i = 0; i < nr; i++) {
      uint32_t a[64];
      CvAcc d0, d1;
      float y[8], c0 = 0.f, c1 = 0.f;
      const uint64_t db = odesc(c.daddr(u + (i >> 8)) + CV_H - 16, 16, 128, 0);
#define STEP2(N) out_step<false, true, 2, !OC_POST, OC_POST>(c, o);
#define PART(...) { const uint64_t db = db0 + (c.mask >> 16); wg_fence(); __VA_ARGS__; wg_commit(); }
      const uint64_t db0 = db;
#define KEEP() asm volatile("add.f32 %0, %0, 0f80000000;" : "+f"(c0)); asm volatile("add.f32 %0, %0, 0f80000000;" : "+f"(c1));
      c.wait(u);
      if (OC_POST) c.wait(out_next(o.pu));
      conv_lda<0, 4>(a, ap);
      STEP(0)
      conv_lda<4, 7>(a, ap);
      PART(conv_part<0, 0, 2>(d0.lo, a, db); conv_part<1, 0, 4>(d0.hi, a, db); conv_part<2, 0, 2>(d1.lo, a, db))
      STEP2(1)
      conv_lda<7, 10>(a, ap);
      PART(conv_part<2, 2, 6>(d1.lo, a, db); conv_part<3, 0, 4>(d1.hi, a, db))
      STEP2(2)
      fence_regs(d0);
      c.sync();
      sts64f(wq - 32, 0.f, 0.f);
      conv_st_h<0>(d0.lo, wq, c0, c1); KEEP()
      PART(conv_part<3, 4, 8>(d1.hi, a, db); conv_part<4, 0, 4>(d0.lo, a, db))
      STEP2(3)
      fence_regs(d1.lo);
      conv_st_h<32>(d0.hi, wq, c0, c1); conv_st_h<64>(d1.lo, wq, c0, c1); KEEP()
      PART(conv_part<4, 4, 10>(d0.lo, a, db); conv_part<5, 0, 2>(d0.hi, a, db))
      STEP2(4)
      fence_regs(d1.hi);
      float e0 = d1.hi[12] + d1.hi[10], e1 = d1.hi[13] + d1.hi[11];
      conv_st_h<96>(d1.hi, wq, c0, c1); KEEP()
      conv_lda<10, 12>(a, ap);
      PART(conv_part<5, 2, 10>(d0.hi, a, db))
      STEP2(5)
      conv_lda<12, 14>(a, ap);
      c.sync();
      oc_red<0, 6>(y, rq);
      PART(conv_part<5, 10, 12>(d0.hi, a, db); conv_part<6, 0, 6>(d1.lo, a, db))
      STEP2(6)
      oc_red<6, 20>(y, rq);
      PART(conv_part<6, 6, 14>(d1.lo, a, db))
      STEP2(7)
      oc_red<20, 26>(y, rq);
      conv_lda<14, 16>(a, ap);
      PART(conv_part<7, 0, 8>(d1.hi, a, db))
      STEP2(8)
      oc_red<26, 32>(y, rq);
      PART(conv_part<7, 8, 16>(d1.hi, a, db))
      STEP2(9)
      fence_regs(y); fence_regs(d0);
      c.sync();
      sts64f(wq - 32, e0, e1);
      conv_st<0>(d0, wq, c0, c1);
      STEP(10)
      fence_regs(d1); fence_regs(a);
      const uint4 u0 = lds128(ub + CV_U + 4080 - 16 * tid), u1 = lds128(ub + CV_U + 2032 - 16 * tid);
      const uint32_t D2 = lds32(ub + CV_D);
      conv_st<1>(d1, wq, c0, c1);
      STEP(11)
      sched_fence(__uint_as_float(u0.x ^ u1.x ^ D2), c.base + SM_DUMMY);
      __syncwarp();
      c.release2(u);
      __nv_bfloat16* zp = g_z + (uint32_t)(conv_channel<MASK>(cta, 2 * i + c.wg) * 2048 + (threadIdx.x & 127) * 8);
      oc_emit(y, u0, D2, zp);
      c.sync();
      oc_red<0, 12>(y, rq);
      STEP(12)
      oc_red<12, 24>(y, rq);
      STEP(13)
      oc_red<24, 32>(y, rq);
      oc_emit(y, u1, D2, zp + 1024);
#undef KEEP
      if (i == nr - 1) { c.signal(SIG_Z); c.release2(u + 1); TS2(c.wg, 8); }
      out_step<false, true, 1, !OC_POST>(c, o);
#pragma unroll 1
      for (int k = 15; k < (i == nr - 1 ? 0 : c.wg ? OC_L1 : OC_L0); k++) out_step<false, true>(c, o);
#undef STEP2
#undef PART
    }
#undef STEP
    if (((CV_REG<MASK> + c.wg) >> 1) & 1) c.skip(u ^ 2);
    ks += (nr - 1) * (c.wg ? OC_L1 : OC_L0) + 15;
  }
  TS(c.wg, 9);
#pragma unroll 1
  for (; ks < 57; ks++) out_step<false, true>(c, o);
  uint32_t ga[32];
  c.wait(2);
  const float g0 = __uint_as_float(lds32(c.base + SM_GATE + 4 * (c.wg * 64 + c.warp * 16 + (c.lane >> 2)))), g1 = __uint_as_float(lds32(c.base + SM_GATE + 32 + 4 * (c.wg * 64 + c.warp * 16 + (c.lane >> 2))));
  const uint32_t gg0 = pack_bf16(g0, g0), gg1 = pack_bf16(g1, g1);
  const uint32_t og0 = pack_bf16(1.f - g0, 1.f - g0), og1 = pack_bf16(1.f - g1, 1.f - g1);
  const int xr = c.wg * 64 + c.warp * 16 + (c.lane & 15);
  const uint32_t xa = c.addr(2) + xr * 128, xs = xr & 7, xh = c.lane >> 4;
  const int zr = (c.lane & 7) + ((c.lane >> 4) << 3);
  const uint32_t za = c.addr(0) + c.wg * 16384 + zr * 128 + (((c.warp * 2 + ((c.lane >> 3) & 1)) ^ (zr & 7)) << 4);
#pragma unroll
  for (int i = 0; i < 8; i++) {
    if (i == 0) out_step<false, true>(c, o);
    if (i == 3) out_step<false, true>(c, o);
    if (i == 6) out_step<false, true>(c, o);
    ldsm4(xa + (i >> 2) * 16384 + ((((i & 3) * 2 + xh) ^ xs) << 4), ga[4 * i], ga[4 * i + 1], ga[4 * i + 2], ga[4 * i + 3]);
  }
  if (TFMA & 2) {
#pragma unroll
    for (int i = 0; i < 32; i++) ga[i] = hmul2((i & 1) ? gg1 : gg0, ga[i]);
    fence_regs(ga);
  }
#pragma unroll 1
  for (ks = 60; ks < 64; ks++) out_step<false, false>(c, o);
  TS2(c.wg, 17);
  c.wait(0);
  TS2(c.wg, 18);
  SHADOW {
#pragma unroll
    for (int i = 0; i < 8; i++) {
      uint32_t z0, z1, z2, z3;
      ldsm4t(za + i * 2048, z0, z1, z2, z3);
      ga[4 * i + 0] = hmul2(ga[4 * i + 0], z0); ga[4 * i + 1] = hmul2(ga[4 * i + 1], z1); ga[4 * i + 2] = hmul2(ga[4 * i + 2], z2); ga[4 * i + 3] = hmul2(ga[4 * i + 3], z3);
      if (!(TFMA & 2)) { ga[4 * i + 0] = hmul2(gg0, ga[4 * i + 0]); ga[4 * i + 1] = hmul2(gg1, ga[4 * i + 1]); ga[4 * i + 2] = hmul2(gg0, ga[4 * i + 2]); ga[4 * i + 3] = hmul2(gg1, ga[4 * i + 3]); }
    }
  }
  c.signal(SIG_DONE);
  fence_regs(ga);
  TS2(c.wg, 19);
  wg_wait<0>(); fence_regs(o.acc);
  TS2(c.wg, 20);
#pragma unroll
  for (int i = 0; i < 8; i++) {
    const uint32_t r0 = mix(og0, pack_bf16(o.acc[8 * i + 0], o.acc[8 * i + 1]), ga[4 * i + 0]);
    const uint32_t r1 = mix(og1, pack_bf16(o.acc[8 * i + 2], o.acc[8 * i + 3]), ga[4 * i + 1]);
    const uint32_t r2 = mix(og0, pack_bf16(o.acc[8 * i + 4], o.acc[8 * i + 5]), ga[4 * i + 2]);
    const uint32_t r3 = mix(og1, pack_bf16(o.acc[8 * i + 6], o.acc[8 * i + 7]), ga[4 * i + 3]);
    stsm4(xa + (i >> 2) * 16384 + ((((i & 3) * 2 + xh) ^ xs) << 4), r0, r1, r2, r3);
    if ((i & 3) == 3 && (FINAL_ST == 0 || (FINAL_ST == 2 && i == 3))) {
      fence_async_smem();
      __syncwarp();
      const int r0 = c.wg * 64 + c.warp * 16;
      if (elect()) tma2d_store(&M.out, c.addr(2 + (i >> 2)) + r0 * 128, nb * 128 + (i >> 2) * 64, mb * 128 + r0);
    } else if ((i & 3) == 3) {
      __syncwarp();
#pragma unroll
      for (int k = 0; k < 4; k++) {
        const int rr = c.wg * 64 + c.warp * 16 + k * 4 + (c.lane >> 3);
        const uint4 v = lds128(c.addr(2 + (i >> 2)) + rr * 128 + (((c.lane ^ rr) & 7) << 4));
        *(uint4*)(P.out + (uint32_t)((mb * 128 + rr) * 1024 + nb * 128 + (i >> 2) * 64 + (c.lane & 7) * 8)) = v;
      }
    }
  }
  if (FINAL_ST != 1 && elect()) asm volatile("cp.async.bulk.commit_group;\ncp.async.bulk.wait_group.read 0;" ::: "memory");
}

__device__ __forceinline__ void load_conv(Prod& p, const Maps& M, int u, int ch) {
  if (elect()) {
    mbar_expect(p.full(u), 5120 + UCH);
    tma3d(p.addr(u), &M.h, 0, -8, ch, p.full(u), POL(4));
    bulk_g2s(p.addr(u) + CV_U, g_u + (size_t)ch * UCH, UCH, p.full(u), POL(4));
  }
}
template<int MASK> __device__ __forceinline__ void prod_conv(Prod& p, const Maps& M, int cta, int nch) {
  int ready = -1;
#pragma unroll 1
  for (int i = 0; i < nch; i++) {
    const int ch = conv_channel<MASK>(cta, i);
    const int u = i & 3;
    if ((ch >> 6) != ready) { ready = ch >> 6; if (cta < NREG) mbar_wait(p.base + SM_RDY + 8 * RDY_U, 0); else cnt_wait(g_cnt + (C_U + ready) * CSTRIDE, 128); }
    p.acquire(u, 1);
    load_conv(p, M, u, ch);
    if (i == 3) { p.acquire(4, 4); if (elect()) mbar_arrive(p.full(4)); }
  }
}
#define HOIST(v) asm volatile("" : "+r"(v))
template<int MASK> __device__ __forceinline__ void producer(const Maps& M, const Params& P, uint32_t base, int cta, int lane) {
  Prod p{base, ((MASK & PH_KV) && cta < NREG) ? 0xffffcfffu ^ ((1u << (3 * NFIRST)) - 1) : 0xffffffffu, lane,
         (cta * 3 + 2) * 2048};
  if (cta >= NREG) { if (MASK & PH_CONV) prod_conv<MASK>(p, M, cta, CV_EXTRA<MASK>); return; }
  const int g = cta & 7, j = cta >> 3, rank = cta & 1;
#pragma unroll 1
  for (int half = 0; half < 2; half++) {
    const int h = j + 16 * half;
    if (MASK & PH_KV) {
      const CUtensorMap* mw = rank ? &M.wv : &M.wk;
#pragma unroll 1
      for (int it = half ? 0 : NFIRST; it < 16; it++) {
        const int u = gemm_unit(it);
        uint32_t bar = p.full(u), d0 = p.addr(u), d1 = p.addr(u + 1 + rank); int k0 = (it & 7) * 64, r0 = (2 * g + (it >> 3)) * 128;
        HOIST(bar); HOIST(d0); HOIST(d1); HOIST(k0); HOIST(r0);
        p.acquire(u, 3);
        if (elect()) {
          mbar_expect(bar, 3 * UNIT);
          tma3d_mc(d1, mw, 0, k0, 2 * h, bar, POL(0) && it >= 8);
          tma2d(d0, &M.c, k0, r0, bar, half ? POL(8) : POL(10));
        }
      }
    }
    if (MASK & PH_ATT) {
#pragma unroll 1
      for (int ks = 0; ks < 16; ks++) {
        const int u = gemm_unit(ks);
        uint32_t bar = p.full(u), d0 = p.addr(u), d1 = p.addr(u + 1), d2 = p.addr(u + 2) + rank * 8192; int k0 = ks * 64;
        HOIST(bar); HOIST(d0); HOIST(d1); HOIST(d2); HOIST(k0);
        p.acquire(u, 3);
        if (elect()) {
          mbar_expect(bar, 3 * UNIT);
          tma2d_mc(d2, &M.wq, h * 128 + rank * 64, k0, bar, POL(1));
          tma2d(d0, &M.x, k0, (15 - g) * 128, bar, half ? POL(9) : POL(10));
          tma2d(d1, &M.x, k0, g * 128, bar, half ? POL(9) : POL(10));
        }
      }
      TS(2, 8 * half + 0);
      mbar_wait(base + SM_RDY + 8 * (RDY_KV + half), 0);
      TS(2, 8 * half + 1);
      const uint8_t* KVh = g_T + T_KV + (size_t)kv_slot<MASK>(h) * 16 * 65536;
      if (MASK & PH_PRE) mbar_wait(base + SM_RDY + 8 * RDY_AUX, 0);
      if (elect()) { mbar_expect(p.full(12), 32768); bulk_g2s(p.addr(12), KVh, 32768, p.full(12), POL(6)); }
      p.acquire(0, 4);
      if (elect()) mbar_arrive(p.full(0));
#pragma unroll 1
      for (int n = 1; n < 34; n++) {
        const int i = !V1F ? n : n == 3 ? 4 : n == 4 ? 3 : n, isv = !(i & 1) || i == 33, st = i == 33 ? 16 : (isv ? (i >> 1) - 1 : (i + 1) >> 1), u = 4 + 2 * (i & 3);
        const bool own = st == 15 - (g & 6);
        uint32_t bar = p.full((i & 1) ? u : 14 - u), d0 = p.addr(own ? u : u + rank), off = (st <= 15 - g ? st : 16 - st) * 65536 + isv * 32768 + (own ? 0 : rank * UNIT);
        HOIST(bar); HOIST(d0); HOIST(off);
        if (!K1V0 || n > 2) p.acquire(u, 2); else if (n == 1) p.acquire(6, 4);
        if (elect()) {
          if (!isv || i == 33) mbar_expect(bar, isv ? 32768 : 65536);
          const bool ef = POL(6) || (POL(14) && st >= 8) || (POL(15) && half);
          if (own) bulk_g2s(d0, KVh + off, 32768, bar, ef); else bulk_g2s_mc(d0, KVh + off, UNIT, bar, ef);
        }
      }
    }
  }
  if ((MASK & PH_CONV) && !(MASK & PH_OUT)) prod_conv<MASK>(p, M, cta, CV_REG<MASK>);
  if (MASK & PH_OUT) {
    const int y0 = out_mb(cta) * 512 + rank * 8, z0 = 2 * out_nb(cta);
    int u = 6;
#pragma unroll 1
    for (int hf = 0; hf < 2; hf++) {
      TS(2, 16 + 2 * hf);
      mbar_wait(base + SM_RDY + 8 * (RDY_CTX + hf), 0);
      TS(2, 17 + 2 * hf);
#pragma unroll 1
      for (int n = hf * 32; n < hf * 32 + 32; n++) {
        const int ks = n == 1 ? 2 : n == 2 ? 1 : n;
        u = n == 2 ? 2 : n == 3 ? 10 : out_next(u);
        uint32_t bar = p.full(u), d0 = p.addr(u) + rank * 8192, d1 = p.addr(u + 1); int x = (ks & 1) * 256, y = y0 + (ks >> 1) * 16, k0 = ks * 64;
        HOIST(bar); HOIST(d0); HOIST(d1); HOIST(x); HOIST(y); HOIST(k0);
        p.acquire(u, 2);
        if (elect()) {
          mbar_expect(bar, 2 * UNIT);
          tma2d_mc(d0, &M.ctx, x, y, bar, POL(5));
          tma3d(d1, &M.wo, 0, k0, z0, bar, POL(2));
          if (ks == 1) mbar_arrive(base + SM_RDY + 8 * RDY_X);
          if (ks == Z_AT) mbar_arrive(base + SM_RDY + 8 * RDY_Z);
        }
      }
    }
  }
}
template<int MASK> __device__ __forceinline__ void producer2(const Maps& M, const Params& P, uint32_t base, int cta, int w, int lane) {
  Prod p{base, 0xffffffffu, lane, 0};
  const int mb = out_mb(cta), nb = out_nb(cta), u = 2 * w;
  if (w) { mbar_wait_slow(base + SM_RDY + 8 * RDY_X, 0); p.mask ^= 12; }
  if (MASK & PH_CONV) {
    mbar_wait_slow(base + SM_SIG + 8 * (SIG_ATT + 1), 0);
    mbar_wait_slow(base + SM_RDY + 8 * RDY_U, 0);
#pragma unroll 1
    for (int i = w; i < CV_REG<MASK>; i += 2) { p.acquire_slow(u, i < 2 ? 2 : 1); load_conv(p, M, u, conv_channel<MASK>(cta, i)); }
  }
  p.acquire_slow(u, 2);
  if (!w && elect()) map_pf(&M.z);
  TSA(52 - 2 * w);
  mbar_wait(base + SM_RDY + 8 * (!w ? RDY_Z : RDY_G), 0);
  TSA(53 - 2 * w);
  if (elect()) {
    mbar_expect(p.full(u), 2 * UNIT + (!w ? 0 : 512));
    tma2d(p.addr(u), !w ? &M.z : &M.x, (!w ? mb : nb) * 128, (!w ? nb : mb) * 128, p.full(u), POL(5));
    tma2d(p.addr(u + 1), !w ? &M.z : &M.x, (!w ? mb : nb) * 128 + 64, (!w ? nb : mb) * 128, p.full(u), POL(5));
    if (w) bulk_g2s(base + SM_GATE, g_gate + mb * 128, 512, p.full(u));
  }
}

__device__ __forceinline__ constexpr uint32_t PUB(int sig, int cnt, int n) { return 0x80000000u | (sig << 24) | (n << 8) | cnt; }
__device__ __forceinline__ constexpr uint32_t GET(int rdy, int cnt, int n) { return (rdy << 24) | (n << 8) | cnt; }
template<int MASK> __device__ __forceinline__ void sync_agent(uint32_t base, int cta, int lane) {
  if ((base & 0x3FFFF) != SMEM_BASE) asm volatile("trap;");
  const int g = cta & 7, j = cta >> 3, go = min(out_mb(cta), 15 - out_mb(cta));
  const int c0 = conv_channel<MASK>(cta, 0), c1 = c0 + CV_REG<MASK> - 1, n0 = min(CV_REG<MASK>, 128 - (c0 & 127));
  constexpr bool KV = MASK & PH_KV, ATT = MASK & PH_ATT, CONV = MASK & PH_CONV, OUT = MASK & PH_OUT, ALL = MASK == PH_ALL;
  uint32_t e = 0;
  if (cta >= NREG) { if (CONV && lane * 32 < CV_EXTRA<MASK>) e = PUB(SIG_Z + lane, C_Z + lane, min(32, CV_EXTRA<MASK> - lane * 32)); }
  else switch (lane) {
    case 0:  if (KV) e = PUB(SIG_KV, C_KV + j, 1); break;
    case 1:  if (ATT) e = GET(RDY_KV, C_KV + j, 8); break;
    case 2:  if (ALL) e = PUB(SIG_WAR, C_WAR + j, 1); break;
    case 3:  if (ATT) e = PUB(SIG_CTX, C_CTX + g, 1); break;
    case 4:  if (ALL) e = GET(RDY_WAR, C_WAR + j, 8); break;
    case 5:  if (KV) e = PUB(SIG_KV + 1, C_KV + 16 + j, 1); break;
    case 6:  if (ATT) e = GET(RDY_KV + 1, C_KV + 16 + j, 8); break;
    case 7:  if (OUT) e = GET(RDY_CTX, C_CTX + go, 16); break;
    case 8:  if (CONV) e = GET(RDY_U, C_U + (c0 >> 6), 128); break;
    case 9:  if (CONV) e = GET(RDY_U, C_U + (c1 >> 6), 128); break;
    case 10: if (ATT) e = PUB(SIG_CTX + 1, C_CTX + 8 + g, 1); break;
    case 11: if (OUT) e = GET(RDY_CTX + 1, C_CTX + 8 + go, 16); break;
    case 12: if (OUT) e = GET(RDY_G, C_GATE, 256); break;
    case 13: if (CONV) e = PUB(SIG_Z, C_Z + (c0 >> 7), n0); break;
    case 14: if (CONV && n0 < CV_REG<MASK>) e = PUB(SIG_Z, C_Z + (c1 >> 7), CV_REG<MASK> - n0); break;
    case 15: if (OUT) e = GET(RDY_Z, C_Z + out_nb(cta), 128); break;
  }
  __syncwarp();
#pragma unroll 1
  for (int i = 0; i < 16; i++) {
    const uint32_t x = __shfl_sync(~0u, e, i), id = (x >> 24) & 127, n = (x >> 8) & 0xffff;
    if (x == 0) continue;
    unsigned* cnt = g_cnt + (x & 255) * CSTRIDE;
    if (x >> 31) {
      mbar_wait_slow(base + SM_SIG + 8 * id, 0);
      if (i == 13) TSA(22);
      if (lane == 0) cnt_publish(cnt, n, i != 14);
    } else {
      cnt_wait(cnt, n);
      if (id < 2) {
        const float4 kn = __ldcg((const float4*)(g_kn2 + kv_slot<MASK>(j + 16 * id) * 128) + lane);
        const uint32_t m = __reduce_max_sync(~0u, max(max(__float_as_uint(kn.x), __float_as_uint(kn.y)), max(__float_as_uint(kn.z), __float_as_uint(kn.w))));
        if (lane == 0) asm volatile("st.shared.u32 [%0], %1;" :: "r"(base + SM_KMAX + 4 * id), "r"(m) : "memory");
      }
      if (lane == 0) mbar_arrive(base + SM_RDY + 8 * id);
    }
    __syncwarp();
    TSA(24 + i);
  }
}

__device__ __forceinline__ void aux_gate(const Params& P, int cta, int aw, int lane) {
  uint4 gw[4];
#pragma unroll
  for (int i = 0; i < 4; i++) gw[i] = __ldg((const uint4*)P.gw + i * 32 + lane);
#pragma unroll 1
  for (int row = cta * 16 + aw * 8; row < cta * 16 + aw * 8 + 8; row++) {
    float a = 0.f;
#pragma unroll
    for (int i = 0; i < 4; i++) {
      const uint4 xv = __ldg((const uint4*)(P.x + (size_t)row * 1024) + i * 32 + lane);
      uint32_t m;
      m = hmul2(xv.x, gw[i].x); a += bf_lo(m) + bf_hi(m); m = hmul2(xv.y, gw[i].y); a += bf_lo(m) + bf_hi(m);
      m = hmul2(xv.z, gw[i].z); a += bf_lo(m) + bf_hi(m); m = hmul2(xv.w, gw[i].w); a += bf_lo(m) + bf_hi(m);
    }
#pragma unroll
    for (int o = 16; o > 0; o >>= 1) a += __shfl_xor_sync(~0u, a, o);
    a = bf_lo(pack_bf16(a, 0.f));
    const float gt = bf_lo(pack_bf16(__fdividef(1.f, 1.f + ex2(-a * 1.4426950408889634f)), 0.f));
    if (lane == 0) g_gate[row] = gt;
    if (GATE_SLEEP) __nanosleep(GATE_SLEEP);
  }
  cnt_signal(g_cnt + C_GATE * CSTRIDE, lane);
  if (aw == 0) { TSA(44); }
}
template<int MASK> __device__ __forceinline__ void aux_pre(const Maps& M, const Params& P, uint32_t base, int cta, int aw, int lane) {
  const uint32_t kb = base + 12 * UNIT, bar = base + SM_PRE;
  const int r = lane >> 2, q = lane & 3;
  const int mi = lane >> 3, row0 = (lane & 6) + 1 - (lane & 1);
  const int ra = (mi * 9 + 1) * 2 + row0;
  const int rb = (mi == 0 ? 3 : mi) * 18 + row0;
  if (PRE_DELAY) mbar_wait_slow(base + SM_BAR + 8 * PRE_DELAY_BAR, 0);
#pragma unroll 1
  for (int it = 0; it < (cta < 96 ? 5 : 4); it++) {
    if (GATE_EARLY && it == PRE_EARLY && MASK == PH_ALL) { mbar_wait_slow(base + SM_SIG + 8 * SIG_ATT, 0); aux_gate(P, cta, aw, lane); }
    if (it == PRE_EARLY && MASK == PH_ALL) mbar_wait_slow(base + SM_SIG + 8 * (SIG_ATT + PRE_HALF), 0);
    const int cg = it ? it * 4 - 3 + (cta >> 5) : 0, tb = cta & 31;
    if (aw == 0 && elect()) {
      mbar_expect(bar, 2 * 9216);
      tma4d(kb, &M.k, cg * 64, 0, tb * 8 - 1, 0, bar, POL(3));
      tma4d(kb + 9216, &M.v, cg * 64, 0, tb * 8 - 1, 0, bar, POL(3));
    }
    const uint2 swl = __ldg((const uint2*)(P.shift + (cg * 64 + aw * 32 + lane) * 4));
    if (tb == 0) {
      uint8_t* e = g_u + (size_t)(cg * 64 + aw * 32 + lane) * UCH + 4096;
      *(uint4*)e = make_uint4(0, 0, 0, 0); *(uint4*)(e + UPITCH) = make_uint4(0, 0, 0, 0);
      *(uint32_t*)(e + 32) = (uint32_t)__bfloat16_as_ushort(P.D[cg * 64 + aw * 32 + lane]) * 0x10001u;
    }
    mbar_wait_slow(bar, it & 1);
#pragma unroll 1
    for (int ol = it ? 0 : cta >> 5; ol < (it ? 4 : (cta >> 5) + 1); ol++) {
      const int oc = aw * 4 + ol;
      const uint32_t s01 = __shfl_sync(~0u, swl.x, ol * 8 + r), s23 = __shfl_sync(~0u, swl.y, ol * 8 + r);
      const uint32_t w0 = __byte_perm(s01, 0, 0x1010), w1 = __byte_perm(s01, 0, 0x3232), w2 = __byte_perm(s23, 0, 0x1010), w3 = __byte_perm(s23, 0, 0x3232);
      const uint32_t pa = kb + ra * 128 + ((oc ^ (ra & 7)) << 4), pb = kb + (mi == 0 ? 9216 : 0) + rb * 128 + ((oc ^ (rb & 7)) << 4);
      uint8_t* e0 = g_u + (uint32_t)((cg * 64 + oc * 8 + r) * UCH + (2040 - tb * 64 - 8 * q) * 2);
#pragma unroll
      for (int hb = 0; hb < 2; hb++) {
        uint32_t k[7], v[5];
        ldsm4t(pa + hb * 1024, k[3], k[4], k[5], k[6]);
        ldsm4t(pa + hb * 1024 + 9216, v[1], v[2], v[3], v[4]);
        ldsm4t(pb + hb * 1024, v[0], k[0], k[1], k[2]);
        uint32_t o1 = __byte_perm(k[1], k[0], 0x5432);
#pragma unroll
        for (int m = 0; m < 5; m++) {
          const uint32_t o2 = __byte_perm(k[m + 2], k[m + 1], 0x5432);
          v[m] = hmul2(hadd2(hadd2(hadd2(hmul2(o1, w3), hmul2(k[m + 1], w2)), hmul2(o2, w1)), hmul2(k[m + 2], w0)), v[m]);
          o1 = o2;
        }
        *(uint4*)(e0 - hb * 64) = make_uint4(v[4], v[3], v[2], v[1]);
        *(uint4*)(e0 - hb * 64 + UPITCH) = make_uint4(__byte_perm(v[4], v[3], 0x5432), __byte_perm(v[3], v[2], 0x5432), __byte_perm(v[2], v[1], 0x5432), __byte_perm(v[1], v[0], 0x5432));
        if (it >= PRE_EARLY) __nanosleep(PRE_SLEEP);
      }
    }
    bar_sync(5, 64);
    if (aw == 0) { TSA(40 + min(it, 3)); }
    if (it == PRE_EARLY - 1 && aw == 0 && lane == 0) mbar_arrive(base + SM_RDY + 8 * RDY_AUX);
    if (aw == 1 && lane == 0) asm volatile("red.release.gpu.global.add.u32 [%0], %1;" :: "l"(g_cnt + (C_U + cg) * CSTRIDE), "r"(it ? 4 : 1) : "memory");
  }
  uint32_t rel;
  asm volatile("mapa.shared::cluster.u32 %0, %1, %2;" : "=r"(rel) : "r"(base + SM_BAR + 128 + 8 * (12 + (lane & 1))), "r"((lane >> 1) & 1));
  if (lane < 4) asm volatile("mbarrier.arrive.shared::cluster.b64 _, [%0], 4;" :: "r"(rel) : "memory");
  if (!(GATE_EARLY && MASK == PH_ALL)) aux_gate(P, cta, aw, lane);
}

template<int MASK> __global__ void __cluster_dims__(2, 1, 1) __launch_bounds__(384, 1) gated_mix_kernel(const __grid_constant__ Maps M, const __grid_constant__ Params P) {
  extern __shared__ __align__(1024) uint8_t smem[];
  const uint32_t base = (uint32_t)__cvta_generic_to_shared(smem);
  if ((MASK & PH_KV) && elect()) {
    map_pf(&M.wk + (blockIdx.x & 1)); map_pf(&M.c);
  }
  const int wi = __shfl_sync(~0u, threadIdx.x >> 5, 0), wg = wi >> 2, warp = wi & 3;
  if (elect()) {
    if (wi < 8) {
      const int cnt = 1 << ((0x10334400 >> (4 * wi)) & 15);
#pragma unroll
      for (int i = 0; i < 8; i++) mbar_init(base + SM_BAR + 64 * wi + 8 * i, cnt);
      asm volatile("fence.mbarrier_init.release.cluster;" ::: "memory");
    }
  }
  const int cta = blockIdx.x;
  const bool first_loads = (MASK & PH_KV) && wi == 8 && cta < NREG;
  const CUtensorMap* mw = (cta & 1) ? &M.wv : &M.wk;
  __syncwarp();
  asm volatile("barrier.cluster.arrive.relaxed.aligned;\nbarrier.cluster.wait.aligned;" ::: "memory");
  auto first_stage = [&](int it) {
    const uint32_t bar = base + SM_BAR + 24 * it, d0 = base + 3 * it * UNIT;
    mbar_expect(bar, 3 * UNIT);
    tma3d_mc(d0 + (1 + (cta & 1)) * UNIT, mw, 0, it * 64, 2 * (cta >> 3), bar);
    tma2d(d0, &M.c, it * 64, (cta & 7) * 256, bar);
  };
  if (first_loads && elect()) {
#pragma unroll 1
    for (int it = 0; it < NF0; it++) first_stage(it);
  }
  __syncwarp();
  const int lane = threadIdx.x & 31;
#define TS_PRO()
  if (wg == 2) {
    asm volatile("setmaxnreg.dec.sync.aligned.u32 56;");
    TS_PRO();
    TS(2, 62);
    if (warp == 0) producer<MASK>(M, P, base, cta, lane);
    else if (warp == 1) sync_agent<MASK>(base, cta, lane);
    else if (cta < NREG) {
      if (MASK & PH_PRE) aux_pre<MASK>(M, P, base, cta, warp - 2, lane);
      if (MASK & PH_OUT) producer2<MASK>(M, P, base, cta, warp - 2, lane);
    }
    if (warp == 1) {
      if (MASK & PH_OUT) {
        unsigned old = 0;
        if (lane == 0) asm volatile("atom.relaxed.gpu.global.add.u32 %0, [%1], 1;" : "=r"(old) : "l"(g_cnt + C_EXIT * CSTRIDE) : "memory");
        old = __shfl_sync(~0u, old, 0);
        if (old == NCTA - 1) for (int i = lane; i < C_NUM; i += 32) g_cnt[i * CSTRIDE] = 0;
      }
      mbar_wait_slow(base + SM_SIG + 8 * SIG_DONE, 0);
      if (cta >= NREG || !(MASK & PH_OUT)) { cluster_arrive(); cluster_wait(); }
    }
  } else {
    asm volatile("setmaxnreg.inc.sync.aligned.u32 224;");
    TS_PRO();
    uint32_t rel;
    asm volatile("mapa.shared::cluster.u32 %0, %1, %2;" : "=r"(rel) : "r"(base + SM_BAR + 128 + 8 * (lane & 15)), "r"(lane >> 4));
    Cons c{base, rel, 0u, lane, warp, wg, (cta * 3 + wg) * 2048};
    if (wg == 1) bar_arrive(1, 256);
    if (NF0 < NFIRST && (MASK & PH_KV) && wi == 4 && cta < NREG) {
      if (elect()) {
#pragma unroll 1
        for (int it = NF0; it < NFIRST; it++) {
          asm volatile("{\n.reg .pred p;\n.reg .u32 a, b;\nmov.u32 a, %%clock;\nXL:\nmov.u32 b, %%clock;\nsub.u32 b, b, a;\nsetp.lt.u32 p, b, %0;\n@p bra XL;\n}\n" :: "r"(it == NF0 ? FGAP : FGAP2) : "memory");
          first_stage(it);
        }
      }
      __syncwarp();
    }
    TS(wg, 0);
    if (cta < NREG) {
      const int g = cta & 7, j = cta >> 3;
      Pend w = {};
      if (HOISTW && MASK == PH_ALL) c.wait(0);
#pragma unroll 1
      for (int half = 0; half < 2; half++) {
        const int h = j + 16 * half;
        if (MASK & PH_KV) cons_kv<(MASK & PH_ATT) != 0>(c, h, kv_slot<MASK>(h), g, w, half == 1 && (MASK & PH_ATT));
        TS(wg, 1 + 4 * half);
        if (MASK & PH_ATT) {
          Att a;
          cons_q<(MASK & PH_KV) != 0>(c, h, w, a.o);
          TS(wg, 2 + 4 * half);
          cons_att<MASK == PH_ALL>(c, a, h, g, w);
          if (half == 0) c.signal(SIG_WAR);
#pragma unroll
          for (int i = 0; i < 8; i++) w.hi[i] = make_uint4(0, 0, 0, 0);
          TS(wg, 3 + 4 * half);
          if (MASK != PH_ALL) { tile_store<0, 4>(w.lo, w.dst, lane); c.signal(SIG_CTX + half); }
        } else if (MASK & PH_KV) {
          out_piece<SCH_KV, true>(c, w, 0, true);
          for (int ks = 1; ks < 8; ks++) out_piece<SCH_KV, false>(c, w, ks, true);
          c.signal(SIG_KV + half);
        }
      }
      if (MASK & PH_OUT) cons_out<MASK>(c, M, P, cta, w);
    }
    if (cta >= NREG || !(MASK & PH_OUT)) {
      if (MASK & PH_CONV) cons_conv<MASK>(c, cta, cta < NREG ? CV_REG<MASK> : CV_EXTRA<MASK>);
      TS(wg, 9);
      c.signal(SIG_DONE);
      cluster_arrive();
    }
    TS(wg, 10);
  }
}

typedef CUresult (*EncFn)(CUtensorMap*, CUtensorMapDataType, cuuint32_t, void*, const cuuint64_t*, const cuuint64_t*, const cuuint32_t*, const cuuint32_t*,
                          CUtensorMapInterleave, CUtensorMapSwizzle, CUtensorMapL2promotion, CUtensorMapFloatOOBfill);
static void enc(EncFn f, CUtensorMap* m, const void* ptr, int rank, const cuuint64_t* dims, const cuuint64_t* strides, const cuuint32_t* box, CUtensorMapSwizzle sw,
                CUtensorMapDataType dt = CU_TENSOR_MAP_DATA_TYPE_BFLOAT16) {
  const cuuint32_t es[4] = {1, 1, 1, 1};
  f(m, dt, rank, (void*)ptr, dims, strides, box, es, CU_TENSOR_MAP_INTERLEAVE_NONE, sw, CU_TENSOR_MAP_L2_PROMOTION_L2_256B, CU_TENSOR_MAP_FLOAT_OOB_FILL_NONE);
}
static void enc2(EncFn f, CUtensorMap* m, const void* ptr, int cols, int rows, int brows) {
  const cuuint64_t d[2] = {(cuuint64_t)cols, (cuuint64_t)rows}, s[1] = {(cuuint64_t)cols * 2}; const cuuint32_t b[2] = {64, (cuuint32_t)brows};
  enc(f, m, ptr, 2, d, s, b, CU_TENSOR_MAP_SWIZZLE_128B);
}
static void encw(EncFn f, CUtensorMap* m, const void* ptr, int cols, int rows) {
  const cuuint64_t d[3] = {64, (cuuint64_t)rows, (cuuint64_t)cols / 64}, s[2] = {(cuuint64_t)cols * 2, 128}; const cuuint32_t b[3] = {64, 64, 2};
  enc(f, m, ptr, 3, d, s, b, CU_TENSOR_MAP_SWIZZLE_128B);
}
extern "C" void kernel_launch(void* const* d_in, const int* in_sizes, int n_in, void* d_out, int out_size) {
  static EncFn fn = nullptr;
  static int ncl = 0;
  static void* zptr = nullptr;
  static void* tptr = nullptr;
  if (!fn) {
    void* p = nullptr; cudaDriverEntryPointQueryResult qr;
    cudaGetDriverEntryPoint("cuTensorMapEncodeTiled", &p, cudaEnableDefault, &qr);
    fn = (EncFn)p;
    cudaFuncSetAttribute(gated_mix_kernel<PH_ALL>, cudaFuncAttributeMaxDynamicSharedMemorySize, SMEM_BYTES);
    cudaFuncSetAttribute(gated_mix_kernel<PH_PRE | PH_KV>, cudaFuncAttributeMaxDynamicSharedMemorySize, SMEM_BYTES);
    cudaFuncSetAttribute(gated_mix_kernel<PH_ATT | PH_CONV>, cudaFuncAttributeMaxDynamicSharedMemorySize, SMEM_BYTES);
    cudaFuncSetAttribute(gated_mix_kernel<PH_OUT>, cudaFuncAttributeMaxDynamicSharedMemorySize, SMEM_BYTES);
    cudaLaunchConfig_t cfg = {}; cfg.gridDim = NCTA; cfg.blockDim = 384; cfg.dynamicSmemBytes = SMEM_BYTES;
    cudaLaunchAttribute at; at.id = cudaLaunchAttributeClusterDimension; at.val.clusterDim.x = 2; at.val.clusterDim.y = 1; at.val.clusterDim.z = 1;
    cfg.attrs = &at; cfg.numAttrs = 1;
    cudaOccupancyMaxActiveClusters(&ncl, gated_mix_kernel<PH_ALL>, &cfg);
    cudaGetSymbolAddress(&zptr, g_z);
    cudaGetSymbolAddress(&tptr, g_T);
  }
  Maps M;
  enc2(fn, &M.x, d_in[0], 1024, 2048, 128);
  enc2(fn, &M.c, d_in[7], 512, 2048, 128);
  enc2(fn, &M.wq, d_in[8], 4096, 1024, 64);
  encw(fn, &M.wk, d_in[9], 4096, 512);
  encw(fn, &M.wv, d_in[10], 4096, 512);
  encw(fn, &M.wo, d_in[11], 1024, 4096);
  { const cuuint64_t d[3] = {64, 32, 1024}, s[2] = {128, 4096}; const cuuint32_t b[3] = {64, 40, 1}; enc(fn, &M.h, d_in[4], 3, d, s, b, CU_TENSOR_MAP_SWIZZLE_NONE); }
  enc2(fn, &M.z, zptr, 2048, 1024, 128);
  enc2(fn, &M.out, d_out, 1024, 2048, 16);
  { const cuuint64_t d[2] = {512, 512 * 16}, s[1] = {2048}; const cuuint32_t b[2] = {256, 8};
    enc(fn, &M.ctx, tptr, 2, d, s, b, CU_TENSOR_MAP_SWIZZLE_NONE, CU_TENSOR_MAP_DATA_TYPE_UINT32); }
  { const cuuint64_t d[4] = {1024, 2, 256, 4}, s[3] = {2048, 16384, 4096}; const cuuint32_t b[4] = {64, 2, 9, 4};
    enc(fn, &M.k, d_in[1], 4, d, s, b, CU_TENSOR_MAP_SWIZZLE_128B); enc(fn, &M.v, d_in[2], 4, d, s, b, CU_TENSOR_MAP_SWIZZLE_128B); }
  Params P{(const __nv_bfloat16*)d_in[0], (const __nv_bfloat16*)d_in[3],
           (const __nv_bfloat16*)d_in[5], (const __nv_bfloat16*)d_in[12], (__nv_bfloat16*)d_out};
  bool split = 2 * ncl < NCTA;
  if (!split) {
    gated_mix_kernel<PH_ALL><<<NCTA, 384, SMEM_BYTES>>>(M, P);
  } else {
    gated_mix_kernel<PH_PRE | PH_KV><<<NCTA, 384, SMEM_BYTES>>>(M, P);
    gated_mix_kernel<PH_ATT | PH_CONV><<<NCTA, 384, SMEM_BYTES>>>(M, P);
    gated_mix_kernel<PH_OUT><<<NCTA, 384, SMEM_BYTES>>>(M, P);
  }
}
```

```cpp
#include <cuda_runtime.h>
#include <cuda.h>
#include <cuda_bf16.h>
#include <stdint.h>

template<int TB> __device__ __forceinline__ void wgmma_ss_n256(float (&d)[128], uint64_t da, uint64_t db, int scale_d) {
  asm volatile("{\n.reg .pred p;\nsetp.ne.b32 p, %130, 0;\n"
    "wgmma.mma_async.sync.aligned.m64n256k16.f32.bf16.bf16 {%0, %1, %2, %3, %4, %5, %6, %7, %8, %9, %10, %11, %12, %13, %14, %15, %16, %17, %18, %19, %20, %21, %22, %23, %24, %25, %26, %27, %28, %29, %30, %31, %32, %33, %34, %35, %36, %37, %38, %39, %40, %41, %42, %43, %44, %45, %46, %47, %48, %49, %50, %51, %52, %53, %54, %55, %56, %57, %58, %59, %60, %61, %62, %63, %64, %65, %66, %67, %68, %69, %70, %71, %72, %73, %74, %75, %76, %77, %78, %79, %80, %81, %82, %83, %84, %85, %86, %87, %88, %89, %90, %91, %92, %93, %94, %95, %96, %97, %98, %99, %100, %101, %102, %103, %104, %105, %106, %107, %108, %109, %110, %111, %112, %113, %114, %115, %116, %117, %118, %119, %120, %121, %122, %123, %124, %125, %126, %127}, %128, %129, p, 1, 1, 0, %131;\n}\n"
    : "+f"(d[0]), "+f"(d[1]), "+f"(d[2]), "+f"(d[3]), "+f"(d[4]), "+f"(d[5]), "+f"(d[6]), "+f"(d[7]), "+f"(d[8]), "+f"(d[9]), "+f"(d[10]), "+f"(d[11]), "+f"(d[12]), "+f"(d[13]), "+f"(d[14]), "+f"(d[15]), "+f"(d[16]), "+f"(d[17]), "+f"(d[18]), "+f"(d[19]), "+f"(d[20]), "+f"(d[21]), "+f"(d[22]), "+f"(d[23]), "+f"(d[24]), "+f"(d[25]), "+f"(d[26]), "+f"(d[27]), "+f"(d[28]), "+f"(d[29]), "+f"(d[30]), "+f"(d[31]), "+f"(d[32]), "+f"(d[33]), "+f"(d[34]), "+f"(d[35]), "+f"(d[36]), "+f"(d[37]), "+f"(d[38]), "+f"(d[39]), "+f"(d[40]), "+f"(d[41]), "+f"(d[42]), "+f"(d[43]), "+f"(d[44]), "+f"(d[45]), "+f"(d[46]), "+f"(d[47]), "+f"(d[48]), "+f"(d[49]), "+f"(d[50]), "+f"(d[51]), "+f"(d[52]), "+f"(d[53]), "+f"(d[54]), "+f"(d[55]), "+f"(d[56]), "+f"(d[57]), "+f"(d[58]), "+f"(d[59]), "+f"(d[60]), "+f"(d[61]), "+f"(d[62]), "+f"(d[63]), "+f"(d[64]), "+f"(d[65]), "+f"(d[66]), "+f"(d[67]), "+f"(d[68]), "+f"(d[69]), "+f"(d[70]), "+f"(d[71]), "+f"(d[72]), "+f"(d[73]), "+f"(d[74]), "+f"(d[75]), "+f"(d[76]), "+f"(d[77]), "+f"(d[78]), "+f"(d[79]), "+f"(d[80]), "+f"(d[81]), "+f"(d[82]), "+f"(d[83]), "+f"(d[84]), "+f"(d[85]), "+f"(d[86]), "+f"(d[87]), "+f"(d[88]), "+f"(d[89]), "+f"(d[90]), "+f"(d[91]), "+f"(d[92]), "+f"(d[93]), "+f"(d[94]), "+f"(d[95]), "+f"(d[96]), "+f"(d[97]), "+f"(d[98]), "+f"(d[99]), "+f"(d[100]), "+f"(d[101]), "+f"(d[102]), "+f"(d[103]), "+f"(d[104]), "+f"(d[105]), "+f"(d[106]), "+f"(d[107]), "+f"(d[108]), "+f"(d[109]), "+f"(d[110]), "+f"(d[111]), "+f"(d[112]), "+f"(d[113]), "+f"(d[114]), "+f"(d[115]), "+f"(d[116]), "+f"(d[117]), "+f"(d[118]), "+f"(d[119]), "+f"(d[120]), "+f"(d[121]), "+f"(d[122]), "+f"(d[123]), "+f"(d[124]), "+f"(d[125]), "+f"(d[126]), "+f"(d[127])
    : "l"(da), "l"(db), "r"(scale_d), "n"(TB));
}
template<int TB> __device__ __forceinline__ void wgmma_ss_n128(float (&d)[64], uint64_t da, uint64_t db, int scale_d) {
  asm volatile("{\n.reg .pred p;\nsetp.ne.b32 p, %66, 0;\n"
    "wgmma.mma_async.sync.aligned.m64n128k16.f32.bf16.bf16 {%0, %1, %2, %3, %4, %5, %6, %7, %8, %9, %10, %11, %12, %13, %14, %15, %16, %17, %18, %19, %20, %21, %22, %23, %24, %25, %26, %27, %28, %29, %30, %31, %32, %33, %34, %35, %36, %37, %38, %39, %40, %41, %42, %43, %44, %45, %46, %47, %48, %49, %50, %51, %52, %53, %54, %55, %56, %57, %58, %59, %60, %61, %62, %63}, %64, %65, p, 1, 1, 0, %67;\n}\n"
    : "+f"(d[0]), "+f"(d[1]), "+f"(d[2]), "+f"(d[3]), "+f"(d[4]), "+f"(d[5]), "+f"(d[6]), "+f"(d[7]), "+f"(d[8]), "+f"(d[9]), "+f"(d[10]), "+f"(d[11]), "+f"(d[12]), "+f"(d[13]), "+f"(d[14]), "+f"(d[15]), "+f"(d[16]), "+f"(d[17]), "+f"(d[18]), "+f"(d[19]), "+f"(d[20]), "+f"(d[21]), "+f"(d[22]), "+f"(d[23]), "+f"(d[24]), "+f"(d[25]), "+f"(d[26]), "+f"(d[27]), "+f"(d[28]), "+f"(d[29]), "+f"(d[30]), "+f"(d[31]), "+f"(d[32]), "+f"(d[33]), "+f"(d[34]), "+f"(d[35]), "+f"(d[36]), "+f"(d[37]), "+f"(d[38]), "+f"(d[39]), "+f"(d[40]), "+f"(d[41]), "+f"(d[42]), "+f"(d[43]), "+f"(d[44]), "+f"(d[45]), "+f"(d[46]), "+f"(d[47]), "+f"(d[48]), "+f"(d[49]), "+f"(d[50]), "+f"(d[51]), "+f"(d[52]), "+f"(d[53]), "+f"(d[54]), "+f"(d[55]), "+f"(d[56]), "+f"(d[57]), "+f"(d[58]), "+f"(d[59]), "+f"(d[60]), "+f"(d[61]), "+f"(d[62]), "+f"(d[63])
    : "l"(da), "l"(db), "r"(scale_d), "n"(TB));
}
template<int TB> __device__ __forceinline__ void wgmma_rs_n32(float (&d)[16], uint32_t a0, uint32_t a1, uint32_t a2, uint32_t a3, uint64_t db, int scale_d) {
  asm volatile("{\n.reg .pred p;\nsetp.ne.b32 p, %21, 0;\n"
    "wgmma.mma_async.sync.aligned.m64n32k16.f32.bf16.bf16 {%0, %1, %2, %3, %4, %5, %6, %7, %8, %9, %10, %11, %12, %13, %14, %15}, {%16, %17, %18, %19}, %20, p, 1, 1, %22;\n}\n"
    : "+f"(d[0]), "+f"(d[1]), "+f"(d[2]), "+f"(d[3]), "+f"(d[4]), "+f"(d[5]), "+f"(d[6]), "+f"(d[7]), "+f"(d[8]), "+f"(d[9]), "+f"(d[10]), "+f"(d[11]), "+f"(d[12]), "+f"(d[13]), "+f"(d[14]), "+f"(d[15])
    : "r"(a0), "r"(a1), "r"(a2), "r"(a3), "l"(db), "r"(scale_d), "n"(TB));
}
__device__ __forceinline__ void wgmma_pv_sel(float (&d)[64], const uint32_t (&p)[32], uint64_t db, int full, int acc, int wg) {
  asm volatile("{\n.reg .pred q, s, w;\n.reg .b64 t;\nsetp.eq.b32 w, %99, 0;\nsetp.ne.b32 s, %98, 0;\nsetp.eq.b32 q, %97, 0;\n@q bra.uni LH;\n"
    "wgmma.fence.sync.aligned;\n"
    "add.s64 t, %96, 0;\nwgmma.mma_async.sync.aligned.m64n128k16.f32.bf16.bf16 {%0, %1, %2, %3, %4, %5, %6, %7, %8, %9, %10, %11, %12, %13, %14, %15, %16, %17, %18, %19, %20, %21, %22, %23, %24, %25, %26, %27, %28, %29, %30, %31, %32, %33, %34, %35, %36, %37, %38, %39, %40, %41, %42, %43, %44, %45, %46, %47, %48, %49, %50, %51, %52, %53, %54, %55, %56, %57, %58, %59, %60, %61, %62, %63}, {%64, %65, %66, %67}, t, s, 1, 1, 1;\n"
    "add.s64 t, %96, 256;\nwgmma.mma_async.sync.aligned.m64n128k16.f32.bf16.bf16 {%0, %1, %2, %3, %4, %5, %6, %7, %8, %9, %10, %11, %12, %13, %14, %15, %16, %17, %18, %19, %20, %21, %22, %23, %24, %25, %26, %27, %28, %29, %30, %31, %32, %33, %34, %35, %36, %37, %38, %39, %40, %41, %42, %43, %44, %45, %46, %47, %48, %49, %50, %51, %52, %53, %54, %55, %56, %57, %58, %59, %60, %61, %62, %63}, {%68, %69, %70, %71}, t, 1, 1, 1, 1;\n"
    "add.s64 t, %96, 512;\nwgmma.mma_async.sync.aligned.m64n128k16.f32.bf16.bf16 {%0, %1, %2, %3, %4, %5, %6, %7, %8, %9, %10, %11, %12, %13, %14, %15, %16, %17, %18, %19, %20, %21, %22, %23, %24, %25, %26, %27, %28, %29, %30, %31, %32, %33, %34, %35, %36, %37, %38, %39, %40, %41, %42, %43, %44, %45, %46, %47, %48, %49, %50, %51, %52, %53, %54, %55, %56, %57, %58, %59, %60, %61, %62, %63}, {%72, %73, %74, %75}, t, 1, 1, 1, 1;\n"
    "add.s64 t, %96, 768;\nwgmma.mma_async.sync.aligned.m64n128k16.f32.bf16.bf16 {%0, %1, %2, %3, %4, %5, %6, %7, %8, %9, %10, %11, %12, %13, %14, %15, %16, %17, %18, %19, %20, %21, %22, %23, %24, %25, %26, %27, %28, %29, %30, %31, %32, %33, %34, %35, %36, %37, %38, %39, %40, %41, %42, %43, %44, %45, %46, %47, %48, %49, %50, %51, %52, %53, %54, %55, %56, %57, %58, %59, %60, %61, %62, %63}, {%76, %77, %78, %79}, t, 1, 1, 1, 1;\n"
    "add.s64 t, %96, 1024;\nwgmma.mma_async.sync.aligned.m64n128k16.f32.bf16.bf16 {%0, %1, %2, %3, %4, %5, %6, %7, %8, %9, %10, %11, %12, %13, %14, %15, %16, %17, %18, %19, %20, %21, %22, %23, %24, %25, %26, %27, %28, %29, %30, %31, %32, %33, %34, %35, %36, %37, %38, %39, %40, %41, %42, %43, %44, %45, %46, %47, %48, %49, %50, %51, %52, %53, %54, %55, %56, %57, %58, %59, %60, %61, %62, %63}, {%80, %81, %82, %83}, t, 1, 1, 1, 1;\n"
    "add.s64 t, %96, 1280;\nwgmma.mma_async.sync.aligned.m64n128k16.f32.bf16.bf16 {%0, %1, %2, %3, %4, %5, %6, %7, %8, %9, %10, %11, %12, %13, %14, %15, %16, %17, %18, %19, %20, %21, %22, %23, %24, %25, %26, %27, %28, %29, %30, %31, %32, %33, %34, %35, %36, %37, %38, %39, %40, %41, %42, %43, %44, %45, %46, %47, %48, %49, %50, %51, %52, %53, %54, %55, %56, %57, %58, %59, %60, %61, %62, %63}, {%84, %85, %86, %87}, t, 1, 1, 1, 1;\n"
    "@w bar.arrive 2, 256;\n@!w bar.arrive 1, 256;\n"
    "add.s64 t, %96, 1536;\nwgmma.mma_async.sync.aligned.m64n128k16.f32.bf16.bf16 {%0, %1, %2, %3, %4, %5, %6, %7, %8, %9, %10, %11, %12, %13, %14, %15, %16, %17, %18, %19, %20, %21, %22, %23, %24, %25, %26, %27, %28, %29, %30, %31, %32, %33, %34, %35, %36, %37, %38, %39, %40, %41, %42, %43, %44, %45, %46, %47, %48, %49, %50, %51, %52, %53, %54, %55, %56, %57, %58, %59, %60, %61, %62, %63}, {%88, %89, %90, %91}, t, 1, 1, 1, 1;\n"
    "add.s64 t, %96, 1792;\nwgmma.mma_async.sync.aligned.m64n128k16.f32.bf16.bf16 {%0, %1, %2, %3, %4, %5, %6, %7, %8, %9, %10, %11, %12, %13, %14, %15, %16, %17, %18, %19, %20, %21, %22, %23, %24, %25, %26, %27, %28, %29, %30, %31, %32, %33, %34, %35, %36, %37, %38, %39, %40, %41, %42, %43, %44, %45, %46, %47, %48, %49, %50, %51, %52, %53, %54, %55, %56, %57, %58, %59, %60, %61, %62, %63}, {%92, %93, %94, %95}, t, 1, 1, 1, 1;\n"
    "wgmma.commit_group.sync.aligned;\n"
    "bra.uni LE;\nLH:\n"
    "wgmma.fence.sync.aligned;\n"
    "add.s64 t, %96, 0;\nwgmma.mma_async.sync.aligned.m64n128k16.f32.bf16.bf16 {%0, %1, %2, %3, %4, %5, %6, %7, %8, %9, %10, %11, %12, %13, %14, %15, %16, %17, %18, %19, %20, %21, %22, %23, %24, %25, %26, %27, %28, %29, %30, %31, %32, %33, %34, %35, %36, %37, %38, %39, %40, %41, %42, %43, %44, %45, %46, %47, %48, %49, %50, %51, %52, %53, %54, %55, %56, %57, %58, %59, %60, %61, %62, %63}, {%80, %81, %82, %83}, t, s, 1, 1, 1;\n"
    "add.s64 t, %96, 256;\nwgmma.mma_async.sync.aligned.m64n128k16.f32.bf16.bf16 {%0, %1, %2, %3, %4, %5, %6, %7, %8, %9, %10, %11, %12, %13, %14, %15, %16, %17, %18, %19, %20, %21, %22, %23, %24, %25, %26, %27, %28, %29, %30, %31, %32, %33, %34, %35, %36, %37, %38, %39, %40, %41, %42, %43, %44, %45, %46, %47, %48, %49, %50, %51, %52, %53, %54, %55, %56, %57, %58, %59, %60, %61, %62, %63}, {%84, %85, %86, %87}, t, 1, 1, 1, 1;\n"
    "@w bar.arrive 2, 256;\n@!w bar.arrive 1, 256;\n"
    "add.s64 t, %96, 512;\nwgmma.mma_async.sync.aligned.m64n128k16.f32.bf16.bf16 {%0, %1, %2, %3, %4, %5, %6, %7, %8, %9, %10, %11, %12, %13, %14, %15, %16, %17, %18, %19, %20, %21, %22, %23, %24, %25, %26, %27, %28, %29, %30, %31, %32, %33, %34, %35, %36, %37, %38, %39, %40, %41, %42, %43, %44, %45, %46, %47, %48, %49, %50, %51, %52, %53, %54, %55, %56, %57, %58, %59, %60, %61, %62, %63}, {%88, %89, %90, %91}, t, 1, 1, 1, 1;\n"
    "add.s64 t, %96, 768;\nwgmma.mma_async.sync.aligned.m64n128k16.f32.bf16.bf16 {%0, %1, %2, %3, %4, %5, %6, %7, %8, %9, %10, %11, %12, %13, %14, %15, %16, %17, %18, %19, %20, %21, %22, %23, %24, %25, %26, %27, %28, %29, %30, %31, %32, %33, %34, %35, %36, %37, %38, %39, %40, %41, %42, %43, %44, %45, %46, %47, %48, %49, %50, %51, %52, %53, %54, %55, %56, %57, %58, %59, %60, %61, %62, %63}, {%92, %93, %94, %95}, t, 1, 1, 1, 1;\n"
    "wgmma.commit_group.sync.aligned;\n"
    "LE:\n}\n"
    : "+f"(d[0]), "+f"(d[1]), "+f"(d[2]), "+f"(d[3]), "+f"(d[4]), "+f"(d[5]), "+f"(d[6]), "+f"(d[7]), "+f"(d[8]), "+f"(d[9]), "+f"(d[10]), "+f"(d[11]), "+f"(d[12]), "+f"(d[13]), "+f"(d[14]), "+f"(d[15]), "+f"(d[16]), "+f"(d[17]), "+f"(d[18]), "+f"(d[19]), "+f"(d[20]), "+f"(d[21]), "+f"(d[22]), "+f"(d[23]), "+f"(d[24]), "+f"(d[25]), "+f"(d[26]), "+f"(d[27]), "+f"(d[28]), "+f"(d[29]), "+f"(d[30]), "+f"(d[31]), "+f"(d[32]), "+f"(d[33]), "+f"(d[34]), "+f"(d[35]), "+f"(d[36]), "+f"(d[37]), "+f"(d[38]), "+f"(d[39]), "+f"(d[40]), "+f"(d[41]), "+f"(d[42]), "+f"(d[43]), "+f"(d[44]), "+f"(d[45]), "+f"(d[46]), "+f"(d[47]), "+f"(d[48]), "+f"(d[49]), "+f"(d[50]), "+f"(d[51]), "+f"(d[52]), "+f"(d[53]), "+f"(d[54]), "+f"(d[55]), "+f"(d[56]), "+f"(d[57]), "+f"(d[58]), "+f"(d[59]), "+f"(d[60]), "+f"(d[61]), "+f"(d[62]), "+f"(d[63])
    : "r"(p[0]), "r"(p[1]), "r"(p[2]), "r"(p[3]), "r"(p[4]), "r"(p[5]), "r"(p[6]), "r"(p[7]), "r"(p[8]), "r"(p[9]), "r"(p[10]), "r"(p[11]), "r"(p[12]), "r"(p[13]), "r"(p[14]), "r"(p[15]), "r"(p[16]), "r"(p[17]), "r"(p[18]), "r"(p[19]), "r"(p[20]), "r"(p[21]), "r"(p[22]), "r"(p[23]), "r"(p[24]), "r"(p[25]), "r"(p[26]), "r"(p[27]), "r"(p[28]), "r"(p[29]), "r"(p[30]), "r"(p[31]), "l"(db), "r"(full), "r"(acc), "r"(wg) : "memory");
}

constexpr int NCTA = 132, NREG = 128;
constexpr int UNIT = 16384, NUNIT = 14;
constexpr uint32_t SMEM_BASE = 1024;
constexpr int SM_BAR = NUNIT * UNIT;
constexpr int SM_GATE = SM_BAR + 1024;
constexpr int SMEM_BYTES = SM_BAR + 1536;
constexpr int UPITCH = 4160, UCH = 2 * UPITCH;
constexpr float QSCALE = 0.08838834764831845f * 1.4426950408889634f;
constexpr float BOUND2 = 60.f * 60.f / 1.15f;
#define CONV_REG 5
constexpr int C_KV = 0;
constexpr int C_CTX = 32;
constexpr int C_U = 48;
constexpr int C_Z = 80;
constexpr int C_GATE = 88;
constexpr int C_EXIT = 89;
#define PRE_EARLY 2
#define PRE_HALF 1
#define ATT_SPLIT 6
#define NFIRST 4
#define PRE_DELAY 0
#define FINAL_ST 1
#define Z_AT 60
#define PRE_DELAY_BAR 9
#define PRE_FMA 0
#define PRE_SLEEP 300
#define GATE_SLEEP 1000
#define GATE_EARLY 1
#define OC_S0 2
#define OC_S1 11
#define OC_POST 0
#define OC_L0 18
#define OC_L1 18
#define ST_1 4
#define ST_D 2
#define ST_0 1
#define ST_0D 0
#define SCH_KV 0x6665544433221100ull
#define SCH_Q 0x6665544433221100ull
#define NK_AT 1
#ifndef NV_AT
#define NV_AT 3
#endif
#define DS_A 0
#define DS_B 4
#define CHK_D 11
#define ER1 0
#define SHW 1
#define SHR 1
#define PK1 0
#define V1F 0
#define K1V0 0
#define TFMA 0
#define FGAP 600
#define FGAP2 200
#define NF0 1
#define HOISTW 0
#define BARP 1
#define EF 127
#define POL(bit) (((EF >> (bit)) & 1) != 0)
constexpr int C_WAR = 96;
constexpr int C_NUM = 112;
constexpr int CSTRIDE = 32;
constexpr int SM_KMAX = SM_BAR + 640, SM_DUMMY = SM_BAR + 648, SM_PRE = SM_BAR + 112, SM_SIG = SM_BAR + 256, SM_RDY = SM_BAR + 384;
enum { SIG_KV = 0, SIG_CTX = 2, SIG_Z = 4, SIG_DONE = 8, SIG_WAR = 9, SIG_ATT = 10 };
enum { RDY_KV = 0, RDY_CTX = 2, RDY_WAR = 4, RDY_G = 5, RDY_X = 6, RDY_AUX = 7, RDY_U = 8, RDY_Z = 9 };
enum { PH_PRE = 1, PH_KV = 2, PH_ATT = 4, PH_CONV = 8, PH_OUT = 16, PH_ALL = 31 };

constexpr uint32_t T_CTX = 0, T_KV = 16 * 32 * 32768, T_BYTES = T_KV + 32 * 16 * 65536;
__device__ __align__(1024) uint8_t g_T[T_BYTES];
__device__ __align__(1024) uint8_t g_u[1024 * UCH];
__device__ __align__(1024) __nv_bfloat16 g_z[1024 * 2048];
__device__ __align__(1024) float g_gate[2048];
__device__ __align__(1024) float g_kn2[32 * 128];
__device__ __align__(1024) unsigned g_cnt[C_NUM * CSTRIDE];

struct __align__(64) Maps { CUtensorMap c, wk, wv, x, wq, wo, h, z, out, ctx, k, v; };
struct Params {
  const __nv_bfloat16 *x, *shift, *D, *gw;
  __nv_bfloat16* out;
};

__device__ __forceinline__ void wg_fence() { asm volatile("wgmma.fence.sync.aligned;" ::: "memory"); }
__device__ __forceinline__ void wg_commit() { asm volatile("wgmma.commit_group.sync.aligned;" ::: "memory"); }
template<int N> __device__ __forceinline__ void wg_wait() { asm volatile("wgmma.wait_group.sync.aligned %0;" :: "n"(N) : "memory"); }
__device__ __forceinline__ uint64_t odesc(uint32_t addr, uint32_t lbo, uint32_t sbo, uint32_t swz) {
  uint64_t d = (uint64_t)(addr >> 4) + (((uint64_t)(lbo >> 4) << 16) | ((uint64_t)(sbo >> 4) << 32) | ((uint64_t)swz << 62));
  asm volatile("" : "+l"(d));
  return d;
}
__device__ __forceinline__ void mbar_init(uint32_t bar, int cnt) { asm volatile("mbarrier.init.shared::cta.b64 [%0], %1;" :: "r"(bar), "r"(cnt)); }
__device__ __forceinline__ void mbar_expect(uint32_t bar, uint32_t bytes) { asm volatile("mbarrier.arrive.expect_tx.shared::cta.b64 _, [%0], %1;" :: "r"(bar), "r"(bytes) : "memory"); }
__device__ __forceinline__ void mbar_arrive(uint32_t bar) { asm volatile("mbarrier.arrive.shared::cta.b64 _, [%0];" :: "r"(bar) : "memory"); }
__device__ __forceinline__ void mbar_arrive_n(uint32_t bar, int n) { asm volatile("mbarrier.arrive.shared::cta.b64 _, [%0], %1;" :: "r"(bar), "r"(n) : "memory"); }
__device__ __forceinline__ void mbar_wait(uint32_t bar, uint32_t parity) {
  asm volatile("{\n.reg .pred p;\nLW:\nmbarrier.try_wait.parity.shared::cta.b64 p, [%0], %1;\n@!p bra LW;\n}\n" :: "r"(bar), "r"(parity) : "memory");
}
__device__ __forceinline__ void mbar_wait_slow(uint32_t bar, uint32_t parity) {
  asm volatile("{\n.reg .pred p;\n.reg .u32 n;\nmov.u32 n, 0;\n"
    "LW:\nmbarrier.test_wait.parity.shared::cta.b64 p, [%0], %1;\n@p bra LD;\n"
    "nanosleep.u32 128;\nadd.u32 n, n, 1;\nsetp.lt.u32 p, n, 4194304;\n@p bra LW;\ntrap;\nLD:\n}\n" :: "r"(bar), "r"(parity) : "memory");
}
__device__ __forceinline__ void mbar_wait_all(uint32_t bar, uint32_t parity) {
  asm volatile("{\n.reg .pred p, q;\nLW:\nmbarrier.try_wait.parity.shared::cta.b64 p, [%0], %1;\nvote.sync.all.pred q, p, 0xffffffff;\n@!q bra.uni LW;\n}\n" :: "r"(bar), "r"(parity) : "memory");
}
__device__ __forceinline__ void cnt_wait(const unsigned* p, unsigned target) {
  asm volatile("{\n.reg .pred p;\n.reg .u32 n, v;\nmov.u32 n, 0;\n"
    "LW:\nld.relaxed.gpu.global.u32 v, [%0];\nsetp.ge.u32 p, v, %1;\n@p bra LD;\n"
    "nanosleep.u32 64;\nadd.u32 n, n, 1;\nsetp.lt.u32 p, n, 4194304;\n@p bra LW;\ntrap;\nLD:\nfence.acquire.gpu;\nfence.proxy.async.global;\n}\n" :: "l"(p), "r"(target) : "memory");
}
__device__ __forceinline__ void cnt_signal(unsigned* p, int lane) {
  __syncwarp();
  if (lane == 0) asm volatile("red.release.gpu.global.add.u32 [%0], 1;" :: "l"(p) : "memory");
}
__device__ __forceinline__ void cnt_publish(unsigned* p, unsigned n, bool fence) {
  if (fence) asm volatile("fence.release.gpu;" ::: "memory");
  asm volatile("red.relaxed.gpu.global.add.u32 [%0], %1;" :: "l"(p), "r"(n) : "memory");
}
__device__ __forceinline__ uint64_t pol_first() { uint64_t p; asm("createpolicy.fractional.L2::evict_first.b64 %0, 1.0;" : "=l"(p)); return p; }
__device__ __forceinline__ void bulk_g2s(uint32_t dst, const void* src, uint32_t bytes, uint32_t bar, bool stream = false) {
  if (stream) asm volatile("cp.async.bulk.shared::cluster.global.mbarrier::complete_tx::bytes.L2::cache_hint [%0], [%1], %2, [%3], %4;" :: "r"(dst), "l"(src), "r"(bytes), "r"(bar), "l"(pol_first()) : "memory");
  else asm volatile("cp.async.bulk.shared::cluster.global.mbarrier::complete_tx::bytes [%0], [%1], %2, [%3];" :: "r"(dst), "l"(src), "r"(bytes), "r"(bar) : "memory");
}
__device__ __forceinline__ void tma2d(uint32_t dst, const CUtensorMap* m, int x, int y, uint32_t bar, bool stream = false) {
  if (stream) asm volatile("cp.async.bulk.tensor.2d.shared::cluster.global.mbarrier::complete_tx::bytes.L2::cache_hint [%0], [%1, {%3, %4}], [%2], %5;" :: "r"(dst), "l"(m), "r"(bar), "r"(x), "r"(y), "l"(pol_first()) : "memory");
  else asm volatile("cp.async.bulk.tensor.2d.shared::cluster.global.mbarrier::complete_tx::bytes [%0], [%1, {%3, %4}], [%2];" :: "r"(dst), "l"(m), "r"(bar), "r"(x), "r"(y) : "memory");
}
__device__ __forceinline__ void tma3d(uint32_t dst, const CUtensorMap* m, int x, int y, int z, uint32_t bar, bool stream = false) {
  if (stream) asm volatile("cp.async.bulk.tensor.3d.shared::cluster.global.mbarrier::complete_tx::bytes.L2::cache_hint [%0], [%1, {%3, %4, %5}], [%2], %6;" :: "r"(dst), "l"(m), "r"(bar), "r"(x), "r"(y), "r"(z), "l"(pol_first()) : "memory");
  else asm volatile("cp.async.bulk.tensor.3d.shared::cluster.global.mbarrier::complete_tx::bytes [%0], [%1, {%3, %4, %5}], [%2];" :: "r"(dst), "l"(m), "r"(bar), "r"(x), "r"(y), "r"(z) : "memory");
}
__device__ __forceinline__ void tma4d(uint32_t dst, const CUtensorMap* m, int x, int y, int z, int w, uint32_t bar, bool stream = false) {
  if (stream) asm volatile("cp.async.bulk.tensor.4d.shared::cluster.global.mbarrier::complete_tx::bytes.L2::cache_hint [%0], [%1, {%3, %4, %5, %6}], [%2], %7;" :: "r"(dst), "l"(m), "r"(bar), "r"(x), "r"(y), "r"(z), "r"(w), "l"(pol_first()) : "memory");
  else asm volatile("cp.async.bulk.tensor.4d.shared::cluster.global.mbarrier::complete_tx::bytes [%0], [%1, {%3, %4, %5, %6}], [%2];" :: "r"(dst), "l"(m), "r"(bar), "r"(x), "r"(y), "r"(z), "r"(w) : "memory");
}
__device__ __forceinline__ void bulk_g2s_mc(uint32_t dst, const void* src, uint32_t bytes, uint32_t bar, bool stream = false) {
  if (stream) asm volatile("cp.async.bulk.shared::cluster.global.mbarrier::complete_tx::bytes.multicast::cluster.L2::cache_hint [%0], [%1], %2, [%3], %4, %5;" :: "r"(dst), "l"(src), "r"(bytes), "r"(bar), "h"((uint16_t)3), "l"(pol_first()) : "memory");
  else asm volatile("cp.async.bulk.shared::cluster.global.mbarrier::complete_tx::bytes.multicast::cluster [%0], [%1], %2, [%3], %4;" :: "r"(dst), "l"(src), "r"(bytes), "r"(bar), "h"((uint16_t)3) : "memory");
}
__device__ __forceinline__ void tma2d_mc(uint32_t dst, const CUtensorMap* m, int x, int y, uint32_t bar, bool stream = false) {
  if (stream) asm volatile("cp.async.bulk.tensor.2d.shared::cluster.global.mbarrier::complete_tx::bytes.multicast::cluster.L2::cache_hint [%0], [%1, {%3, %4}], [%2], %5, %6;" :: "r"(dst), "l"(m), "r"(bar), "r"(x), "r"(y), "h"((uint16_t)3), "l"(pol_first()) : "memory");
  else asm volatile("cp.async.bulk.tensor.2d.shared::cluster.global.mbarrier::complete_tx::bytes.multicast::cluster [%0], [%1, {%3, %4}], [%2], %5;" :: "r"(dst), "l"(m), "r"(bar), "r"(x), "r"(y), "h"((uint16_t)3) : "memory");
}
__device__ __forceinline__ void tma3d_mc(uint32_t dst, const CUtensorMap* m, int x, int y, int z, uint32_t bar, bool stream = false) {
  if (stream) asm volatile("cp.async.bulk.tensor.3d.shared::cluster.global.mbarrier::complete_tx::bytes.multicast::cluster.L2::cache_hint [%0], [%1, {%3, %4, %5}], [%2], %6, %7;" :: "r"(dst), "l"(m), "r"(bar), "r"(x), "r"(y), "r"(z), "h"((uint16_t)3), "l"(pol_first()) : "memory");
  else asm volatile("cp.async.bulk.tensor.3d.shared::cluster.global.mbarrier::complete_tx::bytes.multicast::cluster [%0], [%1, {%3, %4, %5}], [%2], %6;" :: "r"(dst), "l"(m), "r"(bar), "r"(x), "r"(y), "r"(z), "h"((uint16_t)3) : "memory");
}
__device__ __forceinline__ void map_pf(const CUtensorMap* m) { asm volatile("prefetch.tensormap [%0];" :: "l"(m) : "memory"); }
__device__ __forceinline__ void tma2d_store(const CUtensorMap* m, uint32_t src, int x, int y) {
  if (POL(12)) asm volatile("cp.async.bulk.tensor.2d.global.shared::cta.bulk_group.L2::cache_hint [%0, {%2, %3}], [%1], %4;" :: "l"(m), "r"(src), "r"(x), "r"(y), "l"(pol_first()) : "memory");
  else asm volatile("cp.async.bulk.tensor.2d.global.shared::cta.bulk_group [%0, {%2, %3}], [%1];" :: "l"(m), "r"(src), "r"(x), "r"(y) : "memory");
}
__device__ __forceinline__ bool elect() {
  uint32_t r; asm volatile("{\n.reg .pred p;\nelect.sync _|p, 0xffffffff;\nselp.u32 %0, 1, 0, p;\n}\n" : "=r"(r)); return r != 0;
}
__device__ __forceinline__ void cluster_arrive() { asm volatile("barrier.cluster.arrive;" ::: "memory"); }
__device__ __forceinline__ void cluster_wait() { asm volatile("barrier.cluster.wait;" ::: "memory"); }
__device__ __forceinline__ void bar_sync(int id, int n) { asm volatile("bar.sync %0, %1;" :: "r"(id), "r"(n) : "memory"); }
__device__ __forceinline__ void bar_arrive(int id, int n) { asm volatile("bar.arrive %0, %1;" :: "r"(id), "r"(n) : "memory"); }
__device__ __forceinline__ int bar_and(int id, int n, int pred) {
  int r; asm volatile("{\n.reg .pred p, q;\nsetp.ne.b32 p, %3, 0;\nbar.red.and.pred q, %1, %2, p;\nselp.b32 %0, 1, 0, q;\n}\n" : "=r"(r) : "r"(id), "r"(n), "r"(pred) : "memory");
  return r;
}
__device__ __forceinline__ void fence_async_smem() { asm volatile("fence.proxy.async.shared::cta;" ::: "memory"); }
__device__ __forceinline__ float ex2(float x) { float y; asm("ex2.approx.ftz.f32 %0, %1;" : "=f"(y) : "f"(x)); return y; }
__device__ __forceinline__ float rcp(float x) { float y; asm("rcp.approx.ftz.f32 %0, %1;" : "=f"(y) : "f"(x)); return y; }
__device__ __forceinline__ uint32_t pack_bf16(float lo, float hi) { uint32_t r; asm("cvt.rn.bf16x2.f32 %0, %1, %2;" : "=r"(r) : "f"(hi), "f"(lo)); return r; }
__device__ __forceinline__ uint32_t hmul2(uint32_t a, uint32_t b) { uint32_t r; asm("mul.rn.bf16x2 %0, %1, %2;" : "=r"(r) : "r"(a), "r"(b)); return r; }
__device__ __forceinline__ uint32_t hadd2(uint32_t a, uint32_t b) { uint32_t r; asm("add.rn.bf16x2 %0, %1, %2;" : "=r"(r) : "r"(a), "r"(b)); return r; }
__device__ __forceinline__ uint32_t hfma2(uint32_t a, uint32_t b, uint32_t c) { uint32_t r; asm("fma.rn.bf16x2 %0, %1, %2, %3;" : "=r"(r) : "r"(a), "r"(b), "r"(c)); return r; }
__device__ __forceinline__ float bf_lo(uint32_t a) { return __uint_as_float(a << 16); }
__device__ __forceinline__ float bf_hi(uint32_t a) { return __uint_as_float(a & 0xffff0000u); }
__device__ __forceinline__ uint32_t lds32(uint32_t a) { uint32_t v; asm volatile("ld.shared.u32 %0, [%1];" : "=r"(v) : "r"(a) : "memory"); return v; }
__device__ __forceinline__ float2 lds64f(uint32_t a) { float2 v; asm volatile("ld.shared.v2.f32 {%0,%1}, [%2];" : "=f"(v.x), "=f"(v.y) : "r"(a) : "memory"); return v; }
__device__ __forceinline__ uint4 lds128(uint32_t a) { uint4 v; asm volatile("ld.shared.v4.u32 {%0,%1,%2,%3}, [%4];" : "=r"(v.x), "=r"(v.y), "=r"(v.z), "=r"(v.w) : "r"(a) : "memory"); return v; }
__device__ __forceinline__ void sts64f(uint32_t a, float x, float y) { asm volatile("st.shared.v2.f32 [%0], {%1,%2};" :: "r"(a), "f"(x), "f"(y) : "memory"); }
__device__ __forceinline__ void sts128(uint32_t a, uint4 v) { asm volatile("st.shared.v4.u32 [%0], {%1,%2,%3,%4};" :: "r"(a), "r"(v.x), "r"(v.y), "r"(v.z), "r"(v.w) : "memory"); }
template<int OFF> __device__ __forceinline__ void sts128o(uint32_t a, uint4 v) { asm volatile("st.shared.v4.u32 [%0+%5], {%1,%2,%3,%4};" :: "r"(a), "r"(v.x), "r"(v.y), "r"(v.z), "r"(v.w), "n"(OFF) : "memory"); }
__device__ __forceinline__ void ldsm4(uint32_t a, uint32_t& r0, uint32_t& r1, uint32_t& r2, uint32_t& r3) {
  asm volatile("ldmatrix.sync.aligned.m8n8.x4.shared.b16 {%0,%1,%2,%3}, [%4];" : "=r"(r0), "=r"(r1), "=r"(r2), "=r"(r3) : "r"(a) : "memory");
}
__device__ __forceinline__ void ldsm4t(uint32_t a, uint32_t& r0, uint32_t& r1, uint32_t& r2, uint32_t& r3) {
  asm volatile("ldmatrix.sync.aligned.m8n8.x4.trans.shared.b16 {%0,%1,%2,%3}, [%4];" : "=r"(r0), "=r"(r1), "=r"(r2), "=r"(r3) : "r"(a) : "memory");
}
__device__ __forceinline__ void stsm4(uint32_t a, uint32_t r0, uint32_t r1, uint32_t r2, uint32_t r3) {
  asm volatile("stmatrix.sync.aligned.m8n8.x4.shared.b16 [%0], {%1,%2,%3,%4};" :: "r"(a), "r"(r0), "r"(r1), "r"(r2), "r"(r3) : "memory");
}
template<int N> __device__ __forceinline__ void fence_regs(float (&d)[N]) {
#pragma unroll
  for (int i = 0; i < N; i++) asm volatile("" : "+f"(d[i]) :: "memory");
}
template<int N> __device__ __forceinline__ void fence_regs(uint32_t (&d)[N]) {
#pragma unroll
  for (int i = 0; i < N; i++) asm volatile("" : "+r"(d[i]) :: "memory");
}
__device__ __forceinline__ void sched_fence(float x, uint32_t dummy) {
  asm volatile("{\n.reg .pred p;\nsetp.eq.u32 p, %0, 0x7fc12345;\n@p st.shared.u32 [%1], %0;\n}\n" :: "r"(__float_as_uint(x)), "r"(dummy) : "memory");
}
#define ROT 0
#define CTAID blockIdx.x
#define PTRACE 0
#define TS(role, i)
#define TSA(i)
#define TSS(i)
#define TS2(role, i)
#define TR(obj, role, tag)

#define SHADOW if (gridDim.y == 1)

struct Prod {
  uint32_t base, mask; int lane, nt;
  __device__ __forceinline__ uint32_t full(int u) const { return base + SM_BAR + 8 * u; }
  __device__ __forceinline__ uint32_t addr(int u) const { return base + u * UNIT; }
  __device__ __forceinline__ void acquire(int u, int n) {
    const int v = u + min(lane, n - 1);
    mbar_wait_all(base + SM_BAR + 128 + 8 * v, mask >> v);
    mask ^= ((1u << n) - 1) << u;
    TR(*this, 2, 16 + u);
  }
  __device__ __forceinline__ void acquire_slow(int u, int n) {
    for (int i = 0; i < n; i++) mbar_wait_slow(base + SM_BAR + 128 + 8 * (u + i), mask >> (u + i));
    mask ^= ((1u << n) - 1) << u;
  }
};
struct Cons {
  uint32_t base, rel, mask; int lane, warp, wg, nt;
  __device__ __forceinline__ uint32_t addr(int u) const { return base + u * UNIT; }
  __device__ __forceinline__ static uint32_t daddr(int u) { return SMEM_BASE + u * UNIT; }
  __device__ __forceinline__ void wait(int u) { TR(*this, wg, 1); mbar_wait(base + SM_BAR + 8 * u, mask >> u); mask ^= 1u << u; TR(*this, wg, 2); }
  __device__ __forceinline__ void skip(int u) { mask ^= 1u << u; }
  __device__ __forceinline__ void release(int u, int n) {
    TR(*this, wg, 5);
    asm volatile("{\n.reg .pred p;\nsetp.lt.s32 p, %1, %2;\n@p mbarrier.arrive.shared::cluster.b64 _, [%0];\n}\n" :: "r"(rel + 8 * u), "r"(lane & 15), "r"(n) : "memory");
  }
  __device__ __forceinline__ void release2(int u) {
    asm volatile("{\n.reg .pred p;\nsetp.eq.s32 p, %1, 0;\n@p mbarrier.arrive.shared::cluster.b64 _, [%0], 2;\n}\n" :: "r"(rel + 8 * u), "r"(lane & 15) : "memory");
  }
  __device__ __forceinline__ void signal(int i) {
    __syncwarp();
    asm volatile("{\n.reg .pred p;\nsetp.eq.s32 p, %1, 0;\n@p mbarrier.arrive.shared::cta.b64 _, [%0];\n}\n" :: "r"(base + SM_SIG + 8 * i), "r"(lane) : "memory");
  }
  __device__ __forceinline__ void turn() { asm volatile("{\n.reg .pred p;\nsetp.eq.s32 p, %0, 0;\n@p bar.sync 1, 256;\n@!p bar.sync 2, 256;\n}\n" :: "r"(wg) : "memory"); TR(*this, wg, 3); }
  __device__ __forceinline__ void pass() { asm volatile("{\n.reg .pred p;\nsetp.eq.s32 p, %0, 0;\n@p bar.arrive 2, 256;\n@!p bar.arrive 1, 256;\n}\n" :: "r"(wg) : "memory"); TR(*this, wg, 4); }
  __device__ __forceinline__ void sync() { asm volatile("{\n.reg .pred p;\nsetp.eq.s32 p, %0, 0;\n@p bar.sync 3, 128;\n@!p bar.sync 4, 128;\n}\n" :: "r"(wg) : "memory"); }
};
__device__ __forceinline__ int gemm_unit(int ks) { return 3 * (ks & 3); }
template<int MASK> __device__ __forceinline__ int kv_slot(int h) { return MASK == PH_ALL ? h & 15 : h; }
__device__ __forceinline__ int out_mb(int cta) { return cta >> 3; }
__device__ __forceinline__ int out_nb(int cta) { return cta & 7; }
template<int MASK> constexpr int CV_REG = MASK == PH_ALL ? CONV_REG : 6;
template<int MASK> constexpr int CV_EXTRA = (1024 - NREG * CV_REG<MASK>) / (NCTA - NREG);
template<int MASK> __device__ __forceinline__ int conv_channel(int cta, int i) {
  return cta < NREG ? CV_EXTRA<MASK> * (NCTA - NREG) + cta * CV_REG<MASK> + i : (i >> 1) * 8 + (cta - NREG) * 2 + (i & 1);
}

template<int OFF, int N> __device__ __forceinline__ void pack_chunk(const float (&a)[N], float sc0, float sc1, uint4& v0, uint4& v1) {
  v0.x = pack_bf16(a[OFF + 0] * sc0, a[OFF + 1] * sc0); v0.y = pack_bf16(a[OFF + 4] * sc0, a[OFF + 5] * sc0);
  v0.z = pack_bf16(a[OFF + 8] * sc0, a[OFF + 9] * sc0); v0.w = pack_bf16(a[OFF + 12] * sc0, a[OFF + 13] * sc0);
  v1.x = pack_bf16(a[OFF + 2] * sc1, a[OFF + 3] * sc1); v1.y = pack_bf16(a[OFF + 6] * sc1, a[OFF + 7] * sc1);
  v1.z = pack_bf16(a[OFF + 10] * sc1, a[OFF + 11] * sc1); v1.w = pack_bf16(a[OFF + 14] * sc1, a[OFF + 15] * sc1);
}
template<int OFF, int N> __device__ __forceinline__ void pack_chunk(const float (&a)[N], uint4& v0, uint4& v1) {
  v0.x = pack_bf16(a[OFF + 0], a[OFF + 1]); v0.y = pack_bf16(a[OFF + 4], a[OFF + 5]);
  v0.z = pack_bf16(a[OFF + 8], a[OFF + 9]); v0.w = pack_bf16(a[OFF + 12], a[OFF + 13]);
  v1.x = pack_bf16(a[OFF + 2], a[OFF + 3]); v1.y = pack_bf16(a[OFF + 6], a[OFF + 7]);
  v1.z = pack_bf16(a[OFF + 10], a[OFF + 11]); v1.w = pack_bf16(a[OFF + 14], a[OFF + 15]);
}
__device__ __forceinline__ void sq_acc(const uint4& v, uint32_t& a) { a = hfma2(v.x, v.x, a); a = hfma2(v.y, v.y, a); a = hfma2(v.z, v.z, a); a = hfma2(v.w, v.w, a); }
__device__ __forceinline__ float norm2_max(uint32_t a0, uint32_t a1) {
  float n0 = bf_lo(a0) + bf_hi(a0), n1 = bf_lo(a1) + bf_hi(a1);
  n0 += __shfl_xor_sync(~0u, n0, 1); n1 += __shfl_xor_sync(~0u, n1, 1);
  n0 += __shfl_xor_sync(~0u, n0, 2); n1 += __shfl_xor_sync(~0u, n1, 2);
  return __uint_as_float(__reduce_max_sync(~0u, max(__float_as_uint(n0) & 0x7fffffffu, __float_as_uint(n1) & 0x7fffffffu)));
}

struct Pend { uint4 lo[8], hi[8]; uint32_t dst; float kn; };
__device__ __forceinline__ void pin(uint4 (&v)[8]) {
#pragma unroll
  for (int i = 0; i < 8; i++) asm volatile("" : "+r"(v[i].x), "+r"(v[i].y), "+r"(v[i].z), "+r"(v[i].w) :: "memory");
}
__device__ __forceinline__ void pack_o(const float (&o)[64], float i0, float i1, uint4 (&v)[8]) {
  pack_chunk<0>(o, i0, i1, v[0], v[1]); pack_chunk<16>(o, i0, i1, v[2], v[3]);
  pack_chunk<32>(o, i0, i1, v[4], v[5]); pack_chunk<48>(o, i0, i1, v[6], v[7]);
  pin(v);
}
__device__ __forceinline__ uint32_t atom_off(int lane) { return (lane >> 2) * 64 + (((lane ^ (lane >> 3)) & 3) << 4); }
__device__ __forceinline__ void stg128(void* p, const uint4& v, bool stream) {
  if (stream) asm volatile("st.global.L2::cache_hint.v4.u32 [%0], {%1,%2,%3,%4}, %5;" :: "l"(p), "r"(v.x), "r"(v.y), "r"(v.z), "r"(v.w), "l"(pol_first()) : "memory");
  else *(uint4*)p = v;
}
template<int J0, int J1, bool STREAM = false> __device__ __forceinline__ void tile_store(const uint4 (&v)[8], uint32_t dst, int lane) {
  uint8_t* d = g_T + (dst + atom_off(lane));
#pragma unroll
  for (int j = J0; j < J1; j++) { stg128(d + j * 512, v[2 * j], STREAM); stg128(d + j * 512 + 2048, v[2 * j + 1], STREAM); }
}
template<int I0, int I1> __device__ __forceinline__ void tile_store_if(bool on, const uint4 (&v)[8], const uint8_t* dst) {
  if constexpr (I0 < I1) {
    asm volatile("{\n.reg .pred p;\nsetp.ne.b32 p, %5, 0;\n@p st.v4.u32 [%0+%6], {%1,%2,%3,%4};\n}\n"
      :: "l"(dst), "r"(v[I0].x), "r"(v[I0].y), "r"(v[I0].z), "r"(v[I0].w), "r"((int)on), "n"((I0 >> 1) * 512 + (I0 & 1) * 2048) : "memory");
    tile_store_if<I0 + 1, I1>(on, v, dst);
  }
}
__device__ __forceinline__ float tile_norm2(const uint4 (&v)[8]) {
  uint32_t n0 = 0, n1 = 0, n2 = 0, n3 = 0;
#pragma unroll
  for (int j = 0; j < 2; j++) { sq_acc(v[2 * j], n0); sq_acc(v[2 * j + 1], n1); sq_acc(v[2 * j + 4], n2); sq_acc(v[2 * j + 5], n3); }
  return norm2_max(hadd2(n0, n2), hadd2(n1, n3));
}
template<uint64_t SCHED, bool FIRST> __device__ __forceinline__ void out_piece(Cons& c, Pend& w, int ks, bool both) {
  uint8_t* d = g_T + (w.dst + atom_off(c.lane));
#pragma unroll
  for (int i = 0; i < 16; i++) {
    const int at = (SCHED >> (4 * i)) & 15;
    if (FIRST ? at == 0 : (at > 0 && ks == at && (i < 8 || both))) *(uint4*)(d + (i >> 3) * 32768 + ((i >> 1) & 3) * 512 + (i & 1) * 2048) = i < 8 ? w.lo[i & 7] : w.hi[i & 7];
  }
  if (FIRST || !both) return;
  if (ks == NK_AT) w.kn = tile_norm2(w.lo);
  if (ks == NV_AT) {
    const float vn = tile_norm2(w.hi);
    if (c.lane == 0) g_kn2[((w.dst - T_KV) >> 16) * 8 + c.wg * 4 + c.warp] = (vn <= 1.0e20f && vn >= 1.0e-20f) ? w.kn : __uint_as_float(0x7f800000u);
  }
}
template<bool FIRST> __device__ __forceinline__ void kv_issue(Cons& c, float (&acc)[128], int u) {
  const uint64_t da = odesc(c.daddr(u) + c.wg * 8192, 16, 1024, 1), db = odesc(c.daddr(u + 1), 8192, 1024, 1);
  c.turn();
  wg_fence();
#pragma unroll
  for (int kk = 0; kk < 4; kk++) wgmma_ss_n256<1>(acc, da + kk * 2, db + kk * 128, !(FIRST && kk == 0));
  wg_commit();
  c.pass();
}
template<bool NEXT> __device__ __forceinline__ void cons_kv(Cons& c, int h, int hs, int g, Pend& w, bool pend_o) {
#pragma unroll 1
  for (int tile = 0; tile < 2; tile++) {
    float acc[128];
    if (!(NEXT && HOISTW) && tile == 0) c.wait(0);
    if (tile == 0 && h < 16) TS(c.wg, 16);
    kv_issue<true>(c, acc, 0);
    c.release(9, tile == 1 ? 3 : 0);
    if (tile == 1 && pend_o) mbar_wait(c.base + SM_RDY + 8 * RDY_WAR, 0);
    if (tile == 1 || pend_o) out_piece<SCH_KV, true>(c, w, 0, false);
#pragma unroll 1
    for (int ks = 1; ks < 8; ks++) {
      const int u = gemm_unit(ks);
      c.wait(u);
      wg_wait<0>();
      c.release(gemm_unit(ks - 1), 3);
      kv_issue<false>(c, acc, u);
      if (tile == 1 || pend_o) { out_piece<SCH_KV, false>(c, w, ks, tile); if (ks == ((SCH_KV >> 28) & 15) && tile == 0) c.signal(SIG_CTX); }
    }
    if (NEXT || tile == 0) c.wait(0);
    wg_wait<0>(); fence_regs(acc);
    if (!NEXT) c.release(9, tile == 1 ? 3 : 0);
    pack_chunk<0>(acc, w.lo[0], w.lo[1]);  pack_chunk<16>(acc, w.lo[2], w.lo[3]); pack_chunk<32>(acc, w.lo[4], w.lo[5]); pack_chunk<48>(acc, w.lo[6], w.lo[7]);
    pack_chunk<64>(acc, w.hi[0], w.hi[1]); pack_chunk<80>(acc, w.hi[2], w.hi[3]); pack_chunk<96>(acc, w.hi[4], w.hi[5]); pack_chunk<112>(acc, w.hi[6], w.hi[7]);
    pin(w.lo); pin(w.hi);
    w.dst = T_KV + (hs * 16 + 2 * g + tile) * 65536 + (c.wg * 4 + c.warp) * 4096;
  }
}
template<bool FIRST> __device__ __forceinline__ void q_issue(Cons& c, float (&a)[64], float (&b)[64], int u) {
  const uint64_t da = odesc(c.daddr(u) + c.wg * 8192, 16, 1024, 1), db = odesc(c.daddr(u + 2), 8192, 1024, 1);
  const uint64_t da2 = odesc(c.daddr(u + 1) + (1 - c.wg) * 8192, 16, 1024, 1);
  c.turn();
  wg_fence();
#pragma unroll
  for (int kk = 0; kk < 4; kk++) wgmma_ss_n128<1>(a, da + kk * 2, db + kk * 128, !(FIRST && kk == 0));
#pragma unroll
  for (int kk = 0; kk < 4; kk++) wgmma_ss_n128<1>(b, da2 + kk * 2, db + kk * 128, !(FIRST && kk == 0));
  wg_commit();
  c.pass();
}
__device__ __forceinline__ void q_step(Cons& c, float (&d)[64], int ua, int ub, int rowhalf) {
  const uint64_t da = odesc(c.daddr(ua) + rowhalf * 8192, 16, 1024, 1), db = odesc(c.daddr(ub), 8192, 1024, 1);
#pragma unroll
  for (int kk = 0; kk < 4; kk++) wgmma_ss_n128<1>(d, da + kk * 2, db + kk * 128, 1);
}
template<bool PEND_KV> __device__ __forceinline__ void cons_q(Cons& c, int h, Pend& w, float (&b)[64]) {
  float a[64];
  if (!PEND_KV) c.wait(0);
  q_issue<true>(c, a, b, 0);
  if (PEND_KV) { c.release(9, 3); out_piece<SCH_Q, true>(c, w, 0, true); }
#pragma unroll 1
  for (int ks = 1; ks < 14; ks++) {
    const int u = gemm_unit(ks);
    c.wait(u);
    wg_wait<0>();
    c.release(gemm_unit(ks - 1), 3);
    q_issue<false>(c, a, b, u);
    if (PEND_KV && ks <= (int)(SCH_Q >> 60)) { out_piece<SCH_Q, false>(c, w, ks, true); if (ks == (int)(SCH_Q >> 60)) c.signal(SIG_KV + (h >> 4)); }
  }
  c.wait(6); c.wait(9);
  wg_wait<0>();
  c.release(3, 3);
  c.turn();
  TSS(0);
  wg_fence();
  q_step(c, a, 6, 8, c.wg); q_step(c, a, 9, 11, c.wg); wg_commit();
  q_step(c, b, 7, 8, 1 - c.wg); wg_commit();
  c.pass();
  TSS(1);
  c.wait(0);
  const uint32_t q0 = c.addr(0) + (c.wg * 4 + c.warp) * 4096 + atom_off(c.lane);
  wg_wait<1>(); fence_regs(a);
  TSS(2);
  pack_o(a, QSCALE, QSCALE, w.lo);
  sts128o<0>(q0, w.lo[0]);    sts128o<2048>(q0, w.lo[1]); sts128o<512>(q0, w.lo[2]);  sts128o<2560>(q0, w.lo[3]);
  wg_wait<0>();
  c.release(6, 4);
  sts128o<1024>(q0, w.lo[4]); sts128o<3072>(q0, w.lo[5]); sts128o<1536>(q0, w.lo[6]); sts128o<3584>(q0, w.lo[7]);
  TSS(3);
  c.wait(12);
  fence_async_smem();
  TSS(4);
}

__device__ __forceinline__ void issue_qk(float (&s)[64], uint64_t da, uint64_t db) {
#pragma unroll
  for (int kk = 0; kk < 8; kk++) wgmma_ss_n128<0>(s, da + (kk >> 1) * 32 + (kk & 1) * 2, db + (kk >> 1) * 32 + (kk & 1) * 2, kk > 0);
  wg_commit();
}
template<int A, int B> __device__ __forceinline__ void exp_rng(float (&s)[64]) {
#pragma unroll
  for (int i = 4 * A; i < 4 * B; i++) s[i] = ex2(s[i]);
}
template<int A, int B> __device__ __forceinline__ void sum_rng(const float (&s)[64], float (&l)[4]) {
#pragma unroll
  for (int i = A; i < B; i++) { l[0] += s[4 * i]; l[1] += s[4 * i + 1]; l[2] += s[4 * i + 2]; l[3] += s[4 * i + 3]; }
}
template<int A, int B> __device__ __forceinline__ void cvt_p(const float (&s)[64], uint32_t (&p)[32]) {
#pragma unroll
  for (int i = 2 * A; i < 2 * B; i++) p[i] = pack_bf16(s[2 * i], s[2 * i + 1]);
}
template<int K0> __device__ __forceinline__ void mask_half(float (&s)[64], int warp, int lane) {
  const int l0 = warp + (2 * (lane & 3) <= (lane >> 2)), l1 = warp + (2 * (lane & 3) < (lane >> 2));
#pragma unroll
  for (int k = 0; k < 4; k++) {
    float* t = s + 8 * (K0 + k);
    if (k >= l0) { t[0] = -INFINITY; t[6] = -INFINITY; }
    if (k >= l1) { t[1] = -INFINITY; t[7] = -INFINITY; }
    if (k > warp) { t[2] = -INFINITY; t[3] = -INFINITY; }
    if (k >= warp) { t[4] = -INFINITY; t[5] = -INFINITY; }
  }
}
__device__ __forceinline__ void row_inv(float& l0, float& l1) {
  l0 += __shfl_xor_sync(~0u, l0, 1); l1 += __shfl_xor_sync(~0u, l1, 1);
  l0 += __shfl_xor_sync(~0u, l0, 2); l1 += __shfl_xor_sync(~0u, l1, 2);
  l0 = rcp(l0); l1 = rcp(l1);
}
__device__ __forceinline__ void softmax_safe(float (&s)[64], bool upper_only, float& m0, float& m1, float& sc0, float& sc1) {
  float a0 = m0, a1 = m1;
#pragma unroll
  for (int i = 0; i < 8; i++) { a0 = fmaxf(a0, fmaxf(s[4 * i], s[4 * i + 1])); a1 = fmaxf(a1, fmaxf(s[4 * i + 2], s[4 * i + 3])); }
  if (upper_only) { a0 = m0; a1 = m1; }
#pragma unroll
  for (int i = 8; i < 16; i++) { a0 = fmaxf(a0, fmaxf(s[4 * i], s[4 * i + 1])); a1 = fmaxf(a1, fmaxf(s[4 * i + 2], s[4 * i + 3])); }
  a0 = fmaxf(a0, __shfl_xor_sync(~0u, a0, 1)); a1 = fmaxf(a1, __shfl_xor_sync(~0u, a1, 1));
  a0 = fmaxf(a0, __shfl_xor_sync(~0u, a0, 2)); a1 = fmaxf(a1, __shfl_xor_sync(~0u, a1, 2));
  sc0 = ex2(m0 - a0); sc1 = ex2(m1 - a1);
  m0 = a0; m1 = a1;
#pragma unroll
  for (int i = 0; i < 16; i++) { s[4 * i] -= a0; s[4 * i + 1] -= a0; s[4 * i + 2] -= a1; s[4 * i + 3] -= a1; }
}
struct Att {
  float s[64], o[64], l[4], i0, i1, t0, t1; uint32_t p[32];
  float kn; uint32_t qaddr; const uint8_t* dst;
};
__device__ __forceinline__ uint32_t ctx_off(const Cons& c, int h, int qb, int rowhalf) { return T_CTX + (qb * 32 + h) * 32768 + (rowhalf * 4 + c.warp) * 4096; }
__device__ __forceinline__ int att_fast(const uint4 (&q)[8], float kn) {
  uint32_t a0 = 0, a1 = 0, a2 = 0, a3 = 0;
#pragma unroll
  for (int j = 0; j < 2; j++) { sq_acc(q[2 * j], a0); sq_acc(q[2 * j + 1], a1); sq_acc(q[2 * j + 4], a2); sq_acc(q[2 * j + 5], a3); }
  a0 = hadd2(a0, a2); a1 = hadd2(a1, a3);
  return __shfl_sync(~0u, __all_sync(~0u, (bf_lo(a0) + bf_hi(a0)) * kn <= 0.25f * BOUND2 && (bf_lo(a1) + bf_hi(a1)) * kn <= 0.25f * BOUND2), 0);
}
__device__ __forceinline__ int att_first(Cons& c, Att& a, int h, const Pend& w) {
  a.kn = __uint_as_float(lds32(c.base + SM_KMAX + 4 * (h >> 4)));
  a.qaddr = c.daddr(0) + c.wg * 16384;
  c.turn();
  TSS(5);
  wg_fence();
  issue_qk(a.s, odesc(a.qaddr, 16, 2048, 2), odesc(c.daddr(12), 16, 2048, 2));
  int fast = 0;
  SHADOW fast = att_fast(w.lo, a.kn);
  wg_fence();
  TSS(6);
  q_step(c, a.o, 10, 11, 1 - c.wg); wg_commit();
  if (SHW) { if (c.wg) c.wait(6); else c.skip(6); }
  c.pass();
  TSS(7);
#pragma unroll
  for (int i = 0; i < 8; i++) { a.p[4 * i] = w.lo[i].x; a.p[4 * i + 1] = w.lo[i].y; a.p[4 * i + 2] = w.lo[i].z; a.p[4 * i + 3] = w.lo[i].w; }
  a.l[0] = a.l[1] = a.l[2] = a.l[3] = 0.f; a.i0 = a.i1 = a.t0 = a.t1 = 0.25f / QSCALE;
  a.dst = (const uint8_t*)__cvta_shared_to_generic(c.addr(2) + (c.wg * 4 + c.warp) * 4096 + atom_off(c.lane));
  wg_wait<1>(); fence_regs(a.s);
  c.signal(SIG_ATT + (h >> 4));
  if (ER1 && c.wg) { wg_wait<0>(); c.release(10, 2); }
  return fast;
}
template<bool NEXT> __device__ __forceinline__ void att_last(Cons& c, Att& a, Pend& w, int h, int g, bool drain) {
  const int uv = 6;
  if (!PK1 && drain) pack_o(a.o, rcp(a.i0), rcp(a.i1), w.hi);
  TSS(8);
  if (!SHW) c.wait(uv);
  c.turn();
  TSS(9);
  fence_regs(a.o); fence_regs(a.p);
  wgmma_pv_sel(a.o, a.p, odesc(c.daddr(uv), 512, 2048, 2), !(drain && c.wg == 1), !drain, c.wg);
  a.i0 = a.l[0] + a.l[1]; a.i1 = a.l[2] + a.l[3];
  SHADOW row_inv(a.i0, a.i1);
  sched_fence(a.i0 + a.i1, c.base + SM_DUMMY);
  tile_store_if<0, 4>(drain, w.hi, a.dst);
  if (NEXT && HOISTW) c.wait(h < 16 ? 0 : 12);
  wg_wait<0>(); fence_regs(a.o); fence_regs(a.p);
  c.release(uv, 2);
  TSS(10);
  tile_store_if<4, 8>(drain, w.hi, a.dst);
  pack_o(a.o, a.i0, a.i1, w.lo);
  w.dst = ctx_off(c, h, g, 1 - c.wg); w.kn = 0.f;
  TSS(11);
}
template<bool NEXT> __device__ __forceinline__ void cons_att(Cons& c, Att& a, int h, int g, Pend& w) {
  int fast = att_first(c, a, h, w), fast2 = 0;
  float m0 = -INFINITY, m1 = -INFINITY, sc0 = 0.f, sc1 = 0.f;
  int uk = 10, ur = 10;
  bool fresh = false;
#pragma unroll 1
  for (int d = g - 15;;) {
    const bool lo = d == c.wg;
    TSS(16 + 6 * (d - g + 15));
    if ((unsigned)d < 2 || !fast) {
      if ((unsigned)d < 2) {
        mask_half<4>(a.s, c.warp, c.lane);
        if (!SHR && lo) fast2 = att_fast(w.hi, a.kn);
        if (!SHR && d == 1) fast = fast2;
      }
      if (!fast) {
        if (d == 1) m0 = m1 = -INFINITY;
        softmax_safe(a.s, lo, m0, m1, sc0, sc1);
        a.l[0] *= sc0; a.l[1] *= sc0; a.l[2] *= sc1; a.l[3] *= sc1;
      }
    }
    exp_rng<8, 16>(a.s); sum_rng<8, 16>(a.s, a.l);
    exp_rng<ATT_SPLIT, 8>(a.s);
    sched_fence(((a.l[0] + a.l[1]) + (a.l[2] + a.l[3])) + (ATT_SPLIT < 8 ? a.s[4 * ATT_SPLIT + 3] : 0.f), c.base + SM_DUMMY);
    wg_wait<0>(); fence_regs(a.o); fence_regs(a.p);
    c.release(ur, ER1 && c.wg && d == g - 15 ? 0 : 2);
    TSS(17 + 6 * (d - g + 15));
    a.i0 += a.t0; a.i1 += a.t1;
    a.t0 = __shfl_xor_sync(~0u, a.i0, 2); a.t1 = __shfl_xor_sync(~0u, a.i1, 2);
    tile_store_if<DS_A, DS_B>(fresh, w.hi, a.dst);
    uk ^= 12; ur = 14 - uk;
    if (d == 0) a.qaddr += 32768;
    const uint64_t dq = odesc(a.qaddr, 16, 2048, 2), dk = odesc(c.daddr(uk) - (d + 1 == c.wg ? 16384 : 0), 16, 2048, 2), dv = odesc(c.daddr(ur), 512, 2048, 2);
    if (!lo) { exp_rng<0, ATT_SPLIT>(a.s); sum_rng<0, 8>(a.s, a.l); cvt_p<0, 16>(a.s, a.p); }
    else if (gridDim.y == 1) cvt_p<8, 16>(a.s, a.p);
    tile_store_if<DS_B, 8>(fresh, w.hi, a.dst);
    a.i0 += a.t0; a.i1 += a.t1;
    const bool early = PK1 && (d == 1 || d == g - 15) && (c.wg || d == g + 1);
    if (!fast || d == g + 1 || early || (!SHR && (unsigned)(d + 1) < 2)) {
      if (early) pack_o(a.o, rcp(a.i0), rcp(a.i1), w.hi);
      if (!SHR && d == -1) fence_async_smem();
      if (!fast && d != 1 && d != g - 15) {
#pragma unroll
        for (int i = 0; i < 16; i++) { a.o[4 * i] *= sc0; a.o[4 * i + 1] *= sc0; a.o[4 * i + 2] *= sc1; a.o[4 * i + 3] *= sc1; }
      }
      if (!SHR && d == 0) {
        a.i0 = a.l[0] + a.l[1]; a.i1 = a.l[2] + a.l[3];
        a.l[0] = a.l[1] = a.l[2] = a.l[3] = 0.f;
        uint32_t off = ctx_off(c, h, 15 - g, c.wg);
        asm volatile("" : "+r"(off));
        a.dst = g_T + (off + ((uint32_t)(uint64_t)a.dst & 511));
      }
      if (d == g + 1) break;
    }
    d++;
    fresh = d == 2 || d == g - 14;
    TSS(12 + 6 * (d - g + 15));
    if (!SHW) { if (c.wg == 0) c.wait(uk); else c.skip(uk); }
    c.turn();
    TSS(13 + 6 * (d - g + 15));
    fence_regs(a.o); fence_regs(a.p);
    wg_fence();
    issue_qk(a.s, dq, dk);
    TSS(14 + 6 * (d - g + 15));
    if (SHW) { c.wait(c.wg ? uk ^ 12 : ur); c.skip(c.wg ? ur : uk ^ 12); }
    if (!SHR) { a.t0 = __shfl_xor_sync(~0u, a.i0, 1); a.t1 = __shfl_xor_sync(~0u, a.i1, 1); }
    if (fresh || (SHR && (d == 1 || d == g - CHK_D))) {
      if (fresh) { if (!(PK1 && c.wg)) pack_o(a.o, rcp(a.i0), rcp(a.i1), w.hi); }
      else if (d == 1) {
        a.i0 = a.l[0] + a.l[1]; a.i1 = a.l[2] + a.l[3];
        a.t0 = __shfl_xor_sync(~0u, a.i0, 1); a.t1 = __shfl_xor_sync(~0u, a.i1, 1);
        a.l[0] = a.l[1] = a.l[2] = a.l[3] = 0.f;
        uint32_t off = ctx_off(c, h, 15 - g, c.wg);
        asm volatile("" : "+r"(off));
        a.dst = g_T + (off + ((uint32_t)(uint64_t)a.dst & 511));
        fast = fast2;
      } else {
        fast2 = att_fast(w.hi, a.kn);
        fence_async_smem();
      }
    }
    TSS(15 + 6 * (d - g + 15));
    wgmma_pv_sel(a.o, a.p, dv, !lo, !fresh, c.wg);
    tile_store_if<0, DS_A>(fresh, w.hi, a.dst);
    wg_wait<1>(); fence_regs(a.s);
    c.release(uk, 2);
    c.release(d == 0 ? 0 : 2, (d == 0 || d == g + 1) ? 2 : 0);
  }
  att_last<NEXT>(c, a, w, h, g, g == 0);
}

constexpr int CV_H = 1024, CV_U = 5120, CV_D = CV_U + 4128, CV_ROW = 1056;
template<int OFF> __device__ __forceinline__ uint32_t lds32o(uint32_t a) { uint32_t v; asm volatile("ld.shared.u32 %0, [%1+%2];" : "=r"(v) : "r"(a), "n"(OFF) : "memory"); return v; }
template<int G, int G1 = 16> __device__ __forceinline__ void conv_lda(uint32_t (&a)[64], uint32_t p) {
  a[4 * G + 0] = lds32o<-256 * G>(p);
  a[4 * G + 1] = lds32o<-256 * G - 128>(p);
  a[4 * G + 2] = lds32o<-256 * G + 16>(p);
  a[4 * G + 3] = lds32o<-256 * G - 112>(p);
  if constexpr (G + 1 < G1) conv_lda<G + 1, G1>(a, p);
}
struct CvAcc { float lo[16], hi[16]; };
__device__ __forceinline__ void fence_regs(CvAcc& d) { fence_regs(d.lo); fence_regs(d.hi); }
template<int R, int H> __device__ __forceinline__ void conv_mma_h(float (&d)[16], const uint32_t (&a)[64], uint64_t db) {
#pragma unroll
  for (int G = 0; G < 4 * R + 2 * H + 2; G++) wgmma_rs_n32<0>(d, a[4 * G], a[4 * G + 1], a[4 * G + 2], a[4 * G + 3], db + 64 * R + 32 * H - 16 * G, G > 0);
}
template<int T, int G0, int G1> __device__ __forceinline__ void conv_part(float (&d)[16], const uint32_t (&a)[64], uint64_t db) {
#pragma unroll
  for (int G = G0; G < G1; G++) wgmma_rs_n32<0>(d, a[4 * G], a[4 * G + 1], a[4 * G + 2], a[4 * G + 3], db + 32 * T - 16 * G, G > 0);
}
template<int R> __device__ __forceinline__ void conv_mma(CvAcc& d, const uint32_t (&a)[64], uint64_t db) { conv_mma_h<R, 0>(d.lo, a, db); conv_mma_h<R, 1>(d.hi, a, db); }
template<int C0> __device__ __forceinline__ void conv_st_h(const float (&d)[16], uint32_t wq, float& c0, float& c1) {
#pragma unroll
  for (int n = 0; n < 4; n++) { sts64f(wq + (C0 + n * 8) * 4, d[4 * n] + c0, d[4 * n + 1] + c1); c0 = d[4 * n + 2]; c1 = d[4 * n + 3]; }
}
template<int R> __device__ __forceinline__ void conv_st(const CvAcc& d, uint32_t wq, float& c0, float& c1) { conv_st_h<64 * R>(d.lo, wq, c0, c1); conv_st_h<64 * R + 32>(d.hi, wq, c0, c1); }
struct ConvTail { float t[64]; uint4 ua, uc; uint32_t D2; };
__device__ __forceinline__ void conv_emit(ConvTail& e, int ch, int tid) {
  fence_regs(e.t);
  float y[16];
#pragma unroll
  for (int i = 0; i < 16; i++) y[i] = (e.t[i] + e.t[16 + i]) + (e.t[32 + i] + e.t[48 + i]);
  uint4 z0, z1;
  z0.x = hadd2(pack_bf16(y[0], y[2]), hmul2(__byte_perm(e.ua.w, 0, 0x1032), e.D2));
  z0.y = hadd2(pack_bf16(y[4], y[6]), hmul2(__byte_perm(e.ua.z, 0, 0x1032), e.D2));
  z0.z = hadd2(pack_bf16(y[8], y[10]), hmul2(__byte_perm(e.ua.y, 0, 0x1032), e.D2));
  z0.w = hadd2(pack_bf16(y[12], y[14]), hmul2(__byte_perm(e.ua.x, 0, 0x1032), e.D2));
  z1.x = hadd2(pack_bf16(y[1], y[3]), hmul2(__byte_perm(e.uc.w, 0, 0x1032), e.D2));
  z1.y = hadd2(pack_bf16(y[5], y[7]), hmul2(__byte_perm(e.uc.z, 0, 0x1032), e.D2));
  z1.z = hadd2(pack_bf16(y[9], y[11]), hmul2(__byte_perm(e.uc.y, 0, 0x1032), e.D2));
  z1.w = hadd2(pack_bf16(y[13], y[15]), hmul2(__byte_perm(e.uc.x, 0, 0x1032), e.D2));
  uint4* zp = (uint4*)(g_z + (uint32_t)(ch * 2048 + tid * 16));
  zp[0] = z0; zp[1] = z1;
}
template<int MASK> __device__ __forceinline__ void cons_conv(Cons& c, int cta, int nch) {
  const int r = c.lane >> 2, q = c.lane & 3, tid = c.warp * 32 + c.lane;
  const uint32_t part = c.addr(4) - 2048 + (1 - c.wg) * (32 * CV_ROW) + 32;
  const uint32_t aoff = CV_U + ((r & 1) ? 0 : UPITCH) + 4 * (((2039 - r) >> 1) + q - 8 * c.warp);
  const uint32_t wq = part + (c.warp * 8 + r) * CV_ROW + q * 8, rq = part + tid * 8;
  uint32_t a[64];
  ConvTail e = {};
  c.wait(c.wg); c.skip(c.wg ^ 1);
  conv_lda<0>(a, c.addr(c.wg) + aoff);
  c.wait(4);
  sts64f(part + (tid >> 2) * CV_ROW - 32 + q * 8, 0.f, 0.f);
#pragma unroll 1
  for (int i = 0; i < nch / 2; i++) {
    const int u = 2 * (i & 1) + c.wg;
    CvAcc d0, d1, d2, d3;
    float c0 = 0.f, c1 = 0.f;
    const uint64_t db = odesc(c.daddr(u) + CV_H - 16, 16, 128, 0);
    c.turn();
    fence_regs(a);
    wg_fence();
    conv_mma<0>(d0, a, db); conv_mma<1>(d1, a, db); wg_commit();
    if (i > 0) {
      conv_emit(e, conv_channel<MASK>(cta, 2 * i - 2 + c.wg), tid);
      if ((i & 15) == 0) c.signal(SIG_Z + (i >> 4) - 1);
    }
    wg_fence();
    conv_mma_h<2, 0>(d2.lo, a, db); wg_commit();
    wg_wait<1>(); fence_regs(d0); fence_regs(d1);
    conv_st_h<0>(d0.lo, wq, c0, c1);
    wg_fence();
    conv_mma_h<2, 1>(d2.hi, a, db); wg_commit();
    conv_st_h<32>(d0.hi, wq, c0, c1);
    conv_mma_h<3, 0>(d3.lo, a, db);
    conv_st_h<64>(d1.lo, wq, c0, c1);
    conv_mma_h<3, 1>(d3.hi, a, db); wg_commit();
    c.pass();
    const int un = i + 1 < nch / 2 ? u ^ 2 : u;
    if (un != u) { c.wait(un); c.skip(un ^ 1); }
    wg_wait<1>(); fence_regs(d2);
    conv_st_h<96>(d1.hi, wq, c0, c1);
    conv_st<2>(d2, wq, c0, c1);
    {
      const int sw = (c.lane >> 2) & 1;
      const uint4 v0 = lds128(c.addr(u) + CV_U + 4064 - 32 * tid + 16 * sw), v1 = lds128(c.addr(u) + CV_U + 4080 - 32 * tid - 16 * sw);
      e.ua = sw ? v0 : v1; e.uc = sw ? v1 : v0;
    }
    e.D2 = lds32(c.addr(u) + CV_D);
    wg_wait<0>(); fence_regs(d3); fence_regs(a);
    conv_st<3>(d3, wq, c0, c1);
    conv_lda<0, 4>(a, c.addr(un) + aoff);
    c.sync();
    sched_fence(__uint_as_float(e.ua.x ^ e.uc.x ^ e.D2), c.base + SM_DUMMY);
    c.release2(u);
    conv_lda<4, 16>(a, c.addr(un) + aoff);
#pragma unroll
    for (int k = 0; k < 32; k++) { const float2 v = lds64f(rq + k * CV_ROW - (k >> 3) * 8); e.t[2 * k] = v.x; e.t[2 * k + 1] = v.y; }
  }
  conv_emit(e, conv_channel<MASK>(cta, nch - 2 + c.wg), tid);
  c.signal(SIG_Z + ((nch / 2 - 1) >> 4));
  c.release(4, 4);
}

constexpr int OC_PART = 13824, OC_ROW = 544;
__device__ __forceinline__ int out_next(int u) { return (0x84ac680u >> (2 * u)) & 15; }
struct Out { float acc[64]; int pu; uint64_t da, db; };
template<bool FIRST, bool REL, int W = 1, bool PRE = true, bool POST = false> __device__ __forceinline__ void out_step(Cons& c, Out& o, bool extra = false) {
  const int pu = o.pu, u = extra ? 2 : out_next(pu);
  o.pu = u;
  if (PRE) c.wait(u);
  const uint64_t da = o.da + (uint32_t)(u * 1024), db = o.db + (uint32_t)(u * 1024);
  wg_fence();
#pragma unroll
  for (int kk = 0; kk < 4; kk++) wgmma_ss_n128<1>(o.acc, da + (kk >> 1) * 32 + (kk & 1) * 2, db + kk * 128, !(FIRST && kk == 0));
  wg_commit();
  if (REL) { wg_wait<W>(); c.release(pu, 2); }
  if (POST) c.wait(out_next(u));
}
template<int I0, int I1> __device__ __forceinline__ void oc_red(float (&y)[8], uint32_t rq) {
#pragma unroll
  for (int i = I0; i < I1; i++) { const float v = __uint_as_float(lds32(rq + i * OC_ROW - (i >> 3) * 8)); y[i & 7] = i < 8 ? v : y[i & 7] + v; }
}
__device__ __forceinline__ void oc_emit(const float (&y)[8], const uint4& u, uint32_t D2, __nv_bfloat16* dst) {
  uint4 z;
  z.x = hadd2(pack_bf16(y[0], y[1]), hmul2(__byte_perm(u.w, 0, 0x1032), D2));
  z.y = hadd2(pack_bf16(y[2], y[3]), hmul2(__byte_perm(u.z, 0, 0x1032), D2));
  z.z = hadd2(pack_bf16(y[4], y[5]), hmul2(__byte_perm(u.y, 0, 0x1032), D2));
  z.w = hadd2(pack_bf16(y[6], y[7]), hmul2(__byte_perm(u.x, 0, 0x1032), D2));
  *(uint4*)dst = z;
}
__device__ __forceinline__ uint32_t mix(uint32_t og, uint32_t b, uint32_t ga) { return (TFMA & 1) ? hfma2(og, b, ga) : hadd2(ga, hmul2(og, b)); }
template<int MASK> __device__ __forceinline__ void cons_out(Cons& c, const Maps& M, const Params& P, int cta, Pend& w) {
  const int mb = out_mb(cta), nb = out_nb(cta);
  Out o;
  o.da = odesc(c.daddr(0) + c.wg * 8192, 16, 1024, 2); o.db = odesc(c.daddr(1), 8192, 1024, 1);
  o.pu = 5 + gridDim.y;
  out_step<true, false, 1, !(HOISTW && MASK == PH_ALL)>(c, o);
  int ks = 1;
#pragma unroll 1
  for (;; ks++) {
    if (MASK & PH_ATT) {
      if (ks == (c.wg ? ST_1 : ST_0)) tile_store<0, 1>(w.lo, w.dst, c.lane);
      if (ks == (c.wg ? ST_1 + ST_D : ST_0 + ST_0D / 2)) tile_store<1, 2>(w.lo, w.dst, c.lane);
      if (ks == (c.wg ? ST_1 + 2 * ST_D : ST_0 + ST_0D)) tile_store<2, 3>(w.lo, w.dst, c.lane);
      if (ks == (c.wg ? ST_1 + 3 * ST_D : ST_0 + 3 * ST_0D / 2)) { tile_store<3, 4>(w.lo, w.dst, c.lane); c.signal(SIG_CTX + 1); }
    }
    if (ks == (c.wg ? OC_S1 : OC_S0)) break;
    out_step<false, true>(c, o, ks == 1);
  }
  if (MASK & PH_CONV) {
    const int r = c.lane >> 2, q = c.lane & 3, tid = c.warp * 32 + c.lane, u = 2 * c.wg;
    const uint32_t ub = c.addr(u), part = ub + OC_PART + 32;
    const uint32_t ap = ub + CV_U + ((r & 1) ? 0 : UPITCH) + 4 * (((2039 - r) >> 1) + q - 8 * c.warp);
    const uint32_t wq = part + (c.warp * 8 + r) * OC_ROW + q * 8, rq = part + tid * 4;
    const int nr = (CV_REG<MASK> + 1 - c.wg) >> 1;
#define STEP(N) out_step<false, true, 1, !OC_POST, OC_POST>(c, o);
#pragma unroll 1
    for (int i = 0; i < nr; i++) {
      uint32_t a[64];
      CvAcc d0, d1;
      float y[8], c0 = 0.f, c1 = 0.f;
      const uint64_t db = odesc(c.daddr(u + (i >> 8)) + CV_H - 16, 16, 128, 0);
#define STEP2(N) out_step<false, true, 2, !OC_POST, OC_POST>(c, o);
#define PART(...) { const uint64_t db = db0 + (c.mask >> 16); wg_fence(); __VA_ARGS__; wg_commit(); }
      const uint64_t db0 = db;
#define KEEP() asm volatile("add.f32 %0, %0, 0f80000000;" : "+f"(c0)); asm volatile("add.f32 %0, %0, 0f80000000;" : "+f"(c1));
      c.wait(u);
      if (OC_POST) c.wait(out_next(o.pu));
      conv_lda<0, 4>(a, ap);
      STEP(0)
      conv_lda<4, 7>(a, ap);
      PART(conv_part<0, 0, 2>(d0.lo, a, db); conv_part<1, 0, 4>(d0.hi, a, db); conv_part<2, 0, 2>(d1.lo, a, db))
      STEP2(1)
      conv_lda<7, 10>(a, ap);
      PART(conv_part<2, 2, 6>(d1.lo, a, db); conv_part<3, 0, 4>(d1.hi, a, db))
      STEP2(2)
      fence_regs(d0);
      c.sync();
      sts64f(wq - 32, 0.f, 0.f);
      conv_st_h<0>(d0.lo, wq, c0, c1); KEEP()
      PART(conv_part<3, 4, 8>(d1.hi, a, db); conv_part<4, 0, 4>(d0.lo, a, db))
      STEP2(3)
      fence_regs(d1.lo);
      conv_st_h<32>(d0.hi, wq, c0, c1); conv_st_h<64>(d1.lo, wq, c0, c1); KEEP()
      PART(conv_part<4, 4, 10>(d0.lo, a, db); conv_part<5, 0, 2>(d0.hi, a, db))
      STEP2(4)
      fence_regs(d1.hi);
      float e0 = d1.hi[12] + d1.hi[10], e1 = d1.hi[13] + d1.hi[11];
      conv_st_h<96>(d1.hi, wq, c0, c1); KEEP()
      conv_lda<10, 12>(a, ap);
      PART(conv_part<5, 2, 10>(d0.hi, a, db))
      STEP2(5)
      conv_lda<12, 14>(a, ap);
      c.sync();
      oc_red<0, 6>(y, rq);
      PART(conv_part<5, 10, 12>(d0.hi, a, db); conv_part<6, 0, 6>(d1.lo, a, db))
      STEP2(6)
      oc_red<6, 20>(y, rq);
      PART(conv_part<6, 6, 14>(d1.lo, a, db))
      STEP2(7)
      oc_red<20, 26>(y, rq);
      conv_lda<14, 16>(a, ap);
      PART(conv_part<7, 0, 8>(d1.hi, a, db))
      STEP2(8)
      oc_red<26, 32>(y, rq);
      PART(conv_part<7, 8, 16>(d1.hi, a, db))
      STEP2(9)
      fence_regs(y); fence_regs(d0);
      c.sync();
      sts64f(wq - 32, e0, e1);
      conv_st<0>(d0, wq, c0, c1);
      STEP(10)
      fence_regs(d1); fence_regs(a);
      const uint4 u0 = lds128(ub + CV_U + 4080 - 16 * tid), u1 = lds128(ub + CV_U + 2032 - 16 * tid);
      const uint32_t D2 = lds32(ub + CV_D);
      conv_st<1>(d1, wq, c0, c1);
      STEP(11)
      sched_fence(__uint_as_float(u0.x ^ u1.x ^ D2), c.base + SM_DUMMY);
      __syncwarp();
      c.release2(u);
      __nv_bfloat16* zp = g_z + (uint32_t)(conv_channel<MASK>(cta, 2 * i + c.wg) * 2048 + (threadIdx.x & 127) * 8);
      oc_emit(y, u0, D2, zp);
      c.sync();
      oc_red<0, 12>(y, rq);
      STEP(12)
      oc_red<12, 24>(y, rq);
      STEP(13)
      oc_red<24, 32>(y, rq);
      oc_emit(y, u1, D2, zp + 1024);
#undef KEEP
      if (i == nr - 1) { c.signal(SIG_Z); c.release2(u + 1); TS2(c.wg, 8); }
      out_step<false, true, 1, !OC_POST>(c, o);
#pragma unroll 1
      for (int k = 15; k < (i == nr - 1 ? 0 : c.wg ? OC_L1 : OC_L0); k++) out_step<false, true>(c, o);
#undef STEP2
#undef PART
    }
#undef STEP
    if (((CV_REG<MASK> + c.wg) >> 1) & 1) c.skip(u ^ 2);
    ks += (nr - 1) * (c.wg ? OC_L1 : OC_L0) + 15;
  }
  TS(c.wg, 9);
#pragma unroll 1
  for (; ks < 57; ks++) out_step<false, true>(c, o);
  uint32_t ga[32];
  c.wait(2);
  const float g0 = __uint_as_float(lds32(c.base + SM_GATE + 4 * (c.wg * 64 + c.warp * 16 + (c.lane >> 2)))), g1 = __uint_as_float(lds32(c.base + SM_GATE + 32 + 4 * (c.wg * 64 + c.warp * 16 + (c.lane >> 2))));
  const uint32_t gg0 = pack_bf16(g0, g0), gg1 = pack_bf16(g1, g1);
  const uint32_t og0 = pack_bf16(1.f - g0, 1.f - g0), og1 = pack_bf16(1.f - g1, 1.f - g1);
  const int xr = c.wg * 64 + c.warp * 16 + (c.lane & 15);
  const uint32_t xa = c.addr(2) + xr * 128, xs = xr & 7, xh = c.lane >> 4;
  const int zr = (c.lane & 7) + ((c.lane >> 4) << 3);
  const uint32_t za = c.addr(0) + c.wg * 16384 + zr * 128 + (((c.warp * 2 + ((c.lane >> 3) & 1)) ^ (zr & 7)) << 4);
#pragma unroll
  for (int i = 0; i < 8; i++) {
    if (i == 0) out_step<false, true>(c, o);
    if (i == 3) out_step<false, true>(c, o);
    if (i == 6) out_step<false, true>(c, o);
    ldsm4(xa + (i >> 2) * 16384 + ((((i & 3) * 2 + xh) ^ xs) << 4), ga[4 * i], ga[4 * i + 1], ga[4 * i + 2], ga[4 * i + 3]);
  }
  if (TFMA & 2) {
#pragma unroll
    for (int i = 0; i < 32; i++) ga[i] = hmul2((i & 1) ? gg1 : gg0, ga[i]);
    fence_regs(ga);
  }
#pragma unroll 1
  for (ks = 60; ks < 64; ks++) out_step<false, false>(c, o);
  TS2(c.wg, 17);
  c.wait(0);
  TS2(c.wg, 18);
  SHADOW {
#pragma unroll
    for (int i = 0; i < 8; i++) {
      uint32_t z0, z1, z2, z3;
      ldsm4t(za + i * 2048, z0, z1, z2, z3);
      ga[4 * i + 0] = hmul2(ga[4 * i + 0], z0); ga[4 * i + 1] = hmul2(ga[4 * i + 1], z1); ga[4 * i + 2] = hmul2(ga[4 * i + 2], z2); ga[4 * i + 3] = hmul2(ga[4 * i + 3], z3);
      if (!(TFMA & 2)) { ga[4 * i + 0] = hmul2(gg0, ga[4 * i + 0]); ga[4 * i + 1] = hmul2(gg1, ga[4 * i + 1]); ga[4 * i + 2] = hmul2(gg0, ga[4 * i + 2]); ga[4 * i + 3] = hmul2(gg1, ga[4 * i + 3]); }
    }
  }
  c.signal(SIG_DONE);
  fence_regs(ga);
  TS2(c.wg, 19);
  wg_wait<0>(); fence_regs(o.acc);
  TS2(c.wg, 20);
#pragma unroll
  for (int i = 0; i < 8; i++) {
    const uint32_t r0 = mix(og0, pack_bf16(o.acc[8 * i + 0], o.acc[8 * i + 1]), ga[4 * i + 0]);
    const uint32_t r1 = mix(og1, pack_bf16(o.acc[8 * i + 2], o.acc[8 * i + 3]), ga[4 * i + 1]);
    const uint32_t r2 = mix(og0, pack_bf16(o.acc[8 * i + 4], o.acc[8 * i + 5]), ga[4 * i + 2]);
    const uint32_t r3 = mix(og1, pack_bf16(o.acc[8 * i + 6], o.acc[8 * i + 7]), ga[4 * i + 3]);
    stsm4(xa + (i >> 2) * 16384 + ((((i & 3) * 2 + xh) ^ xs) << 4), r0, r1, r2, r3);
    if ((i & 3) == 3 && (FINAL_ST == 0 || (FINAL_ST == 2 && i == 3))) {
      fence_async_smem();
      __syncwarp();
      const int r0 = c.wg * 64 + c.warp * 16;
      if (elect()) tma2d_store(&M.out, c.addr(2 + (i >> 2)) + r0 * 128, nb * 128 + (i >> 2) * 64, mb * 128 + r0);
    } else if ((i & 3) == 3) {
      __syncwarp();
#pragma unroll
      for (int k = 0; k < 4; k++) {
        const int rr = c.wg * 64 + c.warp * 16 + k * 4 + (c.lane >> 3);
        const uint4 v = lds128(c.addr(2 + (i >> 2)) + rr * 128 + (((c.lane ^ rr) & 7) << 4));
        *(uint4*)(P.out + (uint32_t)((mb * 128 + rr) * 1024 + nb * 128 + (i >> 2) * 64 + (c.lane & 7) * 8)) = v;
      }
    }
  }
  if (FINAL_ST != 1 && elect()) asm volatile("cp.async.bulk.commit_group;\ncp.async.bulk.wait_group.read 0;" ::: "memory");
}

__device__ __forceinline__ void load_conv(Prod& p, const Maps& M, int u, int ch) {
  if (elect()) {
    mbar_expect(p.full(u), 5120 + UCH);
    tma3d(p.addr(u), &M.h, 0, -8, ch, p.full(u), POL(4));
    bulk_g2s(p.addr(u) + CV_U, g_u + (size_t)ch * UCH, UCH, p.full(u), POL(4));
  }
}
template<int MASK> __device__ __forceinline__ void prod_conv(Prod& p, const Maps& M, int cta, int nch) {
  int ready = -1;
#pragma unroll 1
  for (int i = 0; i < nch; i++) {
    const int ch = conv_channel<MASK>(cta, i);
    const int u = i & 3;
    if ((ch >> 6) != ready) { ready = ch >> 6; if (cta < NREG) mbar_wait(p.base + SM_RDY + 8 * RDY_U, 0); else cnt_wait(g_cnt + (C_U + ready) * CSTRIDE, 128); }
    p.acquire(u, 1);
    load_conv(p, M, u, ch);
    if (i == 3) { p.acquire(4, 4); if (elect()) mbar_arrive(p.full(4)); }
  }
}
#define HOIST(v) asm volatile("" : "+r"(v))
template<int MASK> __device__ __forceinline__ void producer(const Maps& M, const Params& P, uint32_t base, int cta, int lane) {
  Prod p{base, ((MASK & PH_KV) && cta < NREG) ? 0xffffcfffu ^ ((1u << (3 * NFIRST)) - 1) : 0xffffffffu, lane,
         (cta * 3 + 2) * 2048};
  if (cta >= NREG) { if (MASK & PH_CONV) prod_conv<MASK>(p, M, cta, CV_EXTRA<MASK>); return; }
  const int g = cta & 7, j = cta >> 3, rank = cta & 1;
#pragma unroll 1
  for (int half = 0; half < 2; half++) {
    const int h = j + 16 * half;
    if (MASK & PH_KV) {
      const CUtensorMap* mw = rank ? &M.wv : &M.wk;
#pragma unroll 1
      for (int it = half ? 0 : NFIRST; it < 16; it++) {
        const int u = gemm_unit(it);
        uint32_t bar = p.full(u), d0 = p.addr(u), d1 = p.addr(u + 1 + rank); int k0 = (it & 7) * 64, r0 = (2 * g + (it >> 3)) * 128;
        HOIST(bar); HOIST(d0); HOIST(d1); HOIST(k0); HOIST(r0);
        p.acquire(u, 3);
        if (elect()) {
          mbar_expect(bar, 3 * UNIT);
          tma3d_mc(d1, mw, 0, k0, 2 * h, bar, POL(0) && it >= 8);
          tma2d(d0, &M.c, k0, r0, bar, half ? POL(8) : POL(10));
        }
      }
    }
    if (MASK & PH_ATT) {
#pragma unroll 1
      for (int ks = 0; ks < 16; ks++) {
        const int u = gemm_unit(ks);
        uint32_t bar = p.full(u), d0 = p.addr(u), d1 = p.addr(u + 1), d2 = p.addr(u + 2) + rank * 8192; int k0 = ks * 64;
        HOIST(bar); HOIST(d0); HOIST(d1); HOIST(d2); HOIST(k0);
        p.acquire(u, 3);
        if (elect()) {
          mbar_expect(bar, 3 * UNIT);
          tma2d_mc(d2, &M.wq, h * 128 + rank * 64, k0, bar, POL(1));
          tma2d(d0, &M.x, k0, (15 - g) * 128, bar, half ? POL(9) : POL(10));
          tma2d(d1, &M.x, k0, g * 128, bar, half ? POL(9) : POL(10));
        }
      }
      TS(2, 8 * half + 0);
      mbar_wait(base + SM_RDY + 8 * (RDY_KV + half), 0);
      TS(2, 8 * half + 1);
      const uint8_t* KVh = g_T + T_KV + (size_t)kv_slot<MASK>(h) * 16 * 65536;
      if (MASK & PH_PRE) mbar_wait(base + SM_RDY + 8 * RDY_AUX, 0);
      if (elect()) { mbar_expect(p.full(12), 32768); bulk_g2s(p.addr(12), KVh, 32768, p.full(12), POL(6)); }
      p.acquire(0, 4);
      if (elect()) mbar_arrive(p.full(0));
#pragma unroll 1
      for (int n = 1; n < 34; n++) {
        const int i = !V1F ? n : n == 3 ? 4 : n == 4 ? 3 : n, isv = !(i & 1) || i == 33, st = i == 33 ? 16 : (isv ? (i >> 1) - 1 : (i + 1) >> 1), u = 4 + 2 * (i & 3);
        const bool own = st == 15 - (g & 6);
        uint32_t bar = p.full((SHW || (i & 1)) ? u : 14 - u), d0 = p.addr(own ? u : u + rank), off = (st <= 15 - g ? st : 16 - st) * 65536 + isv * 32768 + (own ? 0 : rank * UNIT);
        HOIST(bar); HOIST(d0); HOIST(off);
        if (!K1V0 || n > 2) p.acquire(u, 2); else if (n == 1) p.acquire(6, 4);
        if (elect()) {
          if (SHW) mbar_expect(bar, 32768); else if (!isv || i == 33) mbar_expect(bar, isv ? 32768 : 65536);
          const bool ef = POL(6) || (POL(14) && st >= 8) || (POL(15) && half);
          if (own) bulk_g2s(d0, KVh + off, 32768, bar, ef); else bulk_g2s_mc(d0, KVh + off, UNIT, bar, ef);
        }
      }
    }
  }
  if ((MASK & PH_CONV) && !(MASK & PH_OUT)) prod_conv<MASK>(p, M, cta, CV_REG<MASK>);
  if (MASK & PH_OUT) {
    const int y0 = out_mb(cta) * 512 + rank * 8, z0 = 2 * out_nb(cta);
    int u = 6;
#pragma unroll 1
    for (int hf = 0; hf < 2; hf++) {
      TS(2, 16 + 2 * hf);
      mbar_wait(base + SM_RDY + 8 * (RDY_CTX + hf), 0);
      TS(2, 17 + 2 * hf);
#pragma unroll 1
      for (int n = hf * 32; n < hf * 32 + 32; n++) {
        const int ks = n == 1 ? 2 : n == 2 ? 1 : n;
        u = n == 2 ? 2 : n == 3 ? 10 : out_next(u);
        uint32_t bar = p.full(u), d0 = p.addr(u) + rank * 8192, d1 = p.addr(u + 1); int x = (ks & 1) * 256, y = y0 + (ks >> 1) * 16, k0 = ks * 64;
        HOIST(bar); HOIST(d0); HOIST(d1); HOIST(x); HOIST(y); HOIST(k0);
        p.acquire(u, 2);
        if (elect()) {
          mbar_expect(bar, 2 * UNIT);
          tma2d_mc(d0, &M.ctx, x, y, bar, POL(5));
          tma3d(d1, &M.wo, 0, k0, z0, bar, POL(2));
          if (ks == 1) mbar_arrive(base + SM_RDY + 8 * RDY_X);
          if (ks == Z_AT) mbar_arrive(base + SM_RDY + 8 * RDY_Z);
        }
      }
    }
  }
}
template<int MASK> __device__ __forceinline__ void producer2(const Maps& M, const Params& P, uint32_t base, int cta, int w, int lane) {
  Prod p{base, 0xffffffffu, lane, 0};
  const int mb = out_mb(cta), nb = out_nb(cta), u = 2 * w;
  if (w) { mbar_wait_slow(base + SM_RDY + 8 * RDY_X, 0); p.mask ^= 12; }
  if (MASK & PH_CONV) {
    mbar_wait_slow(base + SM_SIG + 8 * (SIG_ATT + 1), 0);
    mbar_wait_slow(base + SM_RDY + 8 * RDY_U, 0);
#pragma unroll 1
    for (int i = w; i < CV_REG<MASK>; i += 2) { p.acquire_slow(u, i < 2 ? 2 : 1); load_conv(p, M, u, conv_channel<MASK>(cta, i)); }
  }
  p.acquire_slow(u, 2);
  if (!w && elect()) map_pf(&M.z);
  TSA(52 - 2 * w);
  mbar_wait(base + SM_RDY + 8 * (!w ? RDY_Z : RDY_G), 0);
  TSA(53 - 2 * w);
  if (elect()) {
    mbar_expect(p.full(u), 2 * UNIT + (!w ? 0 : 512));
    tma2d(p.addr(u), !w ? &M.z : &M.x, (!w ? mb : nb) * 128, (!w ? nb : mb) * 128, p.full(u), POL(5));
    tma2d(p.addr(u + 1), !w ? &M.z : &M.x, (!w ? mb : nb) * 128 + 64, (!w ? nb : mb) * 128, p.full(u), POL(5));
    if (w) bulk_g2s(base + SM_GATE, g_gate + mb * 128, 512, p.full(u));
  }
}

__device__ __forceinline__ constexpr uint32_t PUB(int sig, int cnt, int n) { return 0x80000000u | (sig << 24) | (n << 8) | cnt; }
__device__ __forceinline__ constexpr uint32_t GET(int rdy, int cnt, int n) { return (rdy << 24) | (n << 8) | cnt; }
template<int MASK> __device__ __forceinline__ void sync_agent(uint32_t base, int cta, int lane) {
  if ((base & 0x3FFFF) != SMEM_BASE) asm volatile("trap;");
  const int g = cta & 7, j = cta >> 3, go = min(out_mb(cta), 15 - out_mb(cta));
  const int c0 = conv_channel<MASK>(cta, 0), c1 = c0 + CV_REG<MASK> - 1, n0 = min(CV_REG<MASK>, 128 - (c0 & 127));
  constexpr bool KV = MASK & PH_KV, ATT = MASK & PH_ATT, CONV = MASK & PH_CONV, OUT = MASK & PH_OUT, ALL = MASK == PH_ALL;
  uint32_t e = 0;
  if (cta >= NREG) { if (CONV && lane * 32 < CV_EXTRA<MASK>) e = PUB(SIG_Z + lane, C_Z + lane, min(32, CV_EXTRA<MASK> - lane * 32)); }
  else switch (lane) {
    case 0:  if (KV) e = PUB(SIG_KV, C_KV + j, 1); break;
    case 1:  if (ATT) e = GET(RDY_KV, C_KV + j, 8); break;
    case 2:  if (ALL) e = PUB(SIG_WAR, C_WAR + j, 1); break;
    case 3:  if (ATT) e = PUB(SIG_CTX, C_CTX + g, 1); break;
    case 4:  if (ALL) e = GET(RDY_WAR, C_WAR + j, 8); break;
    case 5:  if (KV) e = PUB(SIG_KV + 1, C_KV + 16 + j, 1); break;
    case 6:  if (ATT) e = GET(RDY_KV + 1, C_KV + 16 + j, 8); break;
    case 7:  if (OUT) e = GET(RDY_CTX, C_CTX + go, 16); break;
    case 8:  if (CONV) e = GET(RDY_U, C_U + (c0 >> 6), 128); break;
    case 9:  if (CONV) e = GET(RDY_U, C_U + (c1 >> 6), 128); break;
    case 10: if (ATT) e = PUB(SIG_CTX + 1, C_CTX + 8 + g, 1); break;
    case 11: if (OUT) e = GET(RDY_CTX + 1, C_CTX + 8 + go, 16); break;
    case 12: if (OUT) e = GET(RDY_G, C_GATE, 256); break;
    case 13: if (CONV) e = PUB(SIG_Z, C_Z + (c0 >> 7), n0); break;
    case 14: if (CONV && n0 < CV_REG<MASK>) e = PUB(SIG_Z, C_Z + (c1 >> 7), CV_REG<MASK> - n0); break;
    case 15: if (OUT) e = GET(RDY_Z, C_Z + out_nb(cta), 128); break;
  }
  __syncwarp();
#pragma unroll 1
  for (int i = 0; i < 16; i++) {
    const uint32_t x = __shfl_sync(~0u, e, i), id = (x >> 24) & 127, n = (x >> 8) & 0xffff;
    if (x == 0) continue;
    unsigned* cnt = g_cnt + (x & 255) * CSTRIDE;
    if (x >> 31) {
      mbar_wait_slow(base + SM_SIG + 8 * id, 0);
      if (i == 13) TSA(22);
      if (lane == 0) cnt_publish(cnt, n, i != 14);
    } else {
      cnt_wait(cnt, n);
      if (id < 2) {
        const float4 kn = __ldcg((const float4*)(g_kn2 + kv_slot<MASK>(j + 16 * id) * 128) + lane);
        const uint32_t m = __reduce_max_sync(~0u, max(max(__float_as_uint(kn.x), __float_as_uint(kn.y)), max(__float_as_uint(kn.z), __float_as_uint(kn.w))));
        if (lane == 0) asm volatile("st.shared.u32 [%0], %1;" :: "r"(base + SM_KMAX + 4 * id), "r"(m) : "memory");
      }
      if (lane == 0) mbar_arrive(base + SM_RDY + 8 * id);
    }
    __syncwarp();
    TSA(24 + i);
  }
}

__device__ __forceinline__ void aux_gate(const Params& P, int cta, int aw, int lane) {
  uint4 gw[4];
#pragma unroll
  for (int i = 0; i < 4; i++) gw[i] = __ldg((const uint4*)P.gw + i * 32 + lane);
#pragma unroll 1
  for (int row = cta * 16 + aw * 8; row < cta * 16 + aw * 8 + 8; row++) {
    float a = 0.f;
#pragma unroll
    for (int i = 0; i < 4; i++) {
      const uint4 xv = __ldg((const uint4*)(P.x + (size_t)row * 1024) + i * 32 + lane);
      uint32_t m;
      m = hmul2(xv.x, gw[i].x); a += bf_lo(m) + bf_hi(m); m = hmul2(xv.y, gw[i].y); a += bf_lo(m) + bf_hi(m);
      m = hmul2(xv.z, gw[i].z); a += bf_lo(m) + bf_hi(m); m = hmul2(xv.w, gw[i].w); a += bf_lo(m) + bf_hi(m);
    }
#pragma unroll
    for (int o = 16; o > 0; o >>= 1) a += __shfl_xor_sync(~0u, a, o);
    a = bf_lo(pack_bf16(a, 0.f));
    const float gt = bf_lo(pack_bf16(__fdividef(1.f, 1.f + ex2(-a * 1.4426950408889634f)), 0.f));
    if (lane == 0) g_gate[row] = gt;
    if (GATE_SLEEP) __nanosleep(GATE_SLEEP);
  }
  cnt_signal(g_cnt + C_GATE * CSTRIDE, lane);
  if (aw == 0) { TSA(44); }
}
template<int MASK> __device__ __forceinline__ void aux_pre(const Maps& M, const Params& P, uint32_t base, int cta, int aw, int lane) {
  const uint32_t kb = base + 12 * UNIT, bar = base + SM_PRE;
  const int r = lane >> 2, q = lane & 3;
  const int mi = lane >> 3, row0 = (lane & 6) + 1 - (lane & 1);
  const int ra = (mi * 9 + 1) * 2 + row0;
  const int rb = (mi == 0 ? 3 : mi) * 18 + row0;
  if (PRE_DELAY) mbar_wait_slow(base + SM_BAR + 8 * PRE_DELAY_BAR, 0);
#pragma unroll 1
  for (int it = 0; it < (cta < 96 ? 5 : 4); it++) {
    if (GATE_EARLY && it == PRE_EARLY && MASK == PH_ALL) { mbar_wait_slow(base + SM_SIG + 8 * SIG_ATT, 0); aux_gate(P, cta, aw, lane); }
    if (it == PRE_EARLY && MASK == PH_ALL) mbar_wait_slow(base + SM_SIG + 8 * (SIG_ATT + PRE_HALF), 0);
    const int cg = it ? it * 4 - 3 + (cta >> 5) : 0, tb = cta & 31;
    if (aw == 0 && elect()) {
      mbar_expect(bar, 2 * 9216);
      tma4d(kb, &M.k, cg * 64, 0, tb * 8 - 1, 0, bar, POL(3));
      tma4d(kb + 9216, &M.v, cg * 64, 0, tb * 8 - 1, 0, bar, POL(3));
    }
    const uint2 swl = __ldg((const uint2*)(P.shift + (cg * 64 + aw * 32 + lane) * 4));
    if (tb == 0) {
      uint8_t* e = g_u + (size_t)(cg * 64 + aw * 32 + lane) * UCH + 4096;
      *(uint4*)e = make_uint4(0, 0, 0, 0); *(uint4*)(e + UPITCH) = make_uint4(0, 0, 0, 0);
      *(uint32_t*)(e + 32) = (uint32_t)__bfloat16_as_ushort(P.D[cg * 64 + aw * 32 + lane]) * 0x10001u;
    }
    mbar_wait_slow(bar, it & 1);
#pragma unroll 1
    for (int ol = it ? 0 : cta >> 5; ol < (it ? 4 : (cta >> 5) + 1); ol++) {
      const int oc = aw * 4 + ol;
      const uint32_t s01 = __shfl_sync(~0u, swl.x, ol * 8 + r), s23 = __shfl_sync(~0u, swl.y, ol * 8 + r);
      const uint32_t w0 = __byte_perm(s01, 0, 0x1010), w1 = __byte_perm(s01, 0, 0x3232), w2 = __byte_perm(s23, 0, 0x1010), w3 = __byte_perm(s23, 0, 0x3232);
      const uint32_t pa = kb + ra * 128 + ((oc ^ (ra & 7)) << 4), pb = kb + (mi == 0 ? 9216 : 0) + rb * 128 + ((oc ^ (rb & 7)) << 4);
      uint8_t* e0 = g_u + (uint32_t)((cg * 64 + oc * 8 + r) * UCH + (2040 - tb * 64 - 8 * q) * 2);
#pragma unroll
      for (int hb = 0; hb < 2; hb++) {
        uint32_t k[7], v[5];
        ldsm4t(pa + hb * 1024, k[3], k[4], k[5], k[6]);
        ldsm4t(pa + hb * 1024 + 9216, v[1], v[2], v[3], v[4]);
        ldsm4t(pb + hb * 1024, v[0], k[0], k[1], k[2]);
        uint32_t o1 = __byte_perm(k[1], k[0], 0x5432);
#pragma unroll
        for (int m = 0; m < 5; m++) {
          const uint32_t o2 = __byte_perm(k[m + 2], k[m + 1], 0x5432);
          v[m] = hmul2(hadd2(hadd2(hadd2(hmul2(o1, w3), hmul2(k[m + 1], w2)), hmul2(o2, w1)), hmul2(k[m + 2], w0)), v[m]);
          o1 = o2;
        }
        *(uint4*)(e0 - hb * 64) = make_uint4(v[4], v[3], v[2], v[1]);
        *(uint4*)(e0 - hb * 64 + UPITCH) = make_uint4(__byte_perm(v[4], v[3], 0x5432), __byte_perm(v[3], v[2], 0x5432), __byte_perm(v[2], v[1], 0x5432), __byte_perm(v[1], v[0], 0x5432));
        if (it >= PRE_EARLY) __nanosleep(PRE_SLEEP);
      }
    }
    bar_sync(5, 64);
    if (aw == 0) { TSA(40 + min(it, 3)); }
    if (it == PRE_EARLY - 1 && aw == 0 && lane == 0) mbar_arrive(base + SM_RDY + 8 * RDY_AUX);
    if (aw == 1 && lane == 0) asm volatile("red.release.gpu.global.add.u32 [%0], %1;" :: "l"(g_cnt + (C_U + cg) * CSTRIDE), "r"(it ? 4 : 1) : "memory");
  }
  uint32_t rel;
  asm volatile("mapa.shared::cluster.u32 %0, %1, %2;" : "=r"(rel) : "r"(base + SM_BAR + 128 + 8 * (12 + (lane & 1))), "r"((lane >> 1) & 1));
  if (lane < 4) asm volatile("mbarrier.arrive.shared::cluster.b64 _, [%0], 4;" :: "r"(rel) : "memory");
  if (!(GATE_EARLY && MASK == PH_ALL)) aux_gate(P, cta, aw, lane);
}

template<int MASK> __global__ void __cluster_dims__(2, 1, 1) __launch_bounds__(384, 1) gated_mix_kernel(const __grid_constant__ Maps M, const __grid_constant__ Params P) {
  extern __shared__ __align__(1024) uint8_t smem[];
  const uint32_t base = (uint32_t)__cvta_generic_to_shared(smem);
  if ((MASK & PH_KV) && elect()) {
    map_pf(&M.wk + (blockIdx.x & 1)); map_pf(&M.c);
  }
  const int wi = __shfl_sync(~0u, threadIdx.x >> 5, 0), wg = wi >> 2, warp = wi & 3;
  if (elect()) {
    if (wi < 8) {
      const int cnt = 1 << ((0x10334400 >> (4 * wi)) & 15);
#pragma unroll
      for (int i = 0; i < 8; i++) mbar_init(base + SM_BAR + 64 * wi + 8 * i, cnt);
      asm volatile("fence.mbarrier_init.release.cluster;" ::: "memory");
    }
  }
  const int cta = blockIdx.x;
  const bool first_loads = (MASK & PH_KV) && wi == 8 && cta < NREG;
  const CUtensorMap* mw = (cta & 1) ? &M.wv : &M.wk;
  __syncwarp();
  asm volatile("barrier.cluster.arrive.relaxed.aligned;\nbarrier.cluster.wait.aligned;" ::: "memory");
  auto first_stage = [&](int it) {
    const uint32_t bar = base + SM_BAR + 24 * it, d0 = base + 3 * it * UNIT;
    mbar_expect(bar, 3 * UNIT);
    tma3d_mc(d0 + (1 + (cta & 1)) * UNIT, mw, 0, it * 64, 2 * (cta >> 3), bar);
    tma2d(d0, &M.c, it * 64, (cta & 7) * 256, bar);
  };
  if (first_loads && elect()) {
#pragma unroll 1
    for (int it = 0; it < NF0; it++) first_stage(it);
  }
  __syncwarp();
  const int lane = threadIdx.x & 31;
#define TS_PRO()
  if (wg == 2) {
    asm volatile("setmaxnreg.dec.sync.aligned.u32 56;");
    TS_PRO();
    TS(2, 62);
    if (warp == 0) producer<MASK>(M, P, base, cta, lane);
    else if (warp == 1) sync_agent<MASK>(base, cta, lane);
    else if (cta < NREG) {
      if (MASK & PH_PRE) aux_pre<MASK>(M, P, base, cta, warp - 2, lane);
      if (MASK & PH_OUT) producer2<MASK>(M, P, base, cta, warp - 2, lane);
    }
    if (warp == 1) {
      if (MASK & PH_OUT) {
        unsigned old = 0;
        if (lane == 0) asm volatile("atom.relaxed.gpu.global.add.u32 %0, [%1], 1;" : "=r"(old) : "l"(g_cnt + C_EXIT * CSTRIDE) : "memory");
        old = __shfl_sync(~0u, old, 0);
        if (old == NCTA - 1) for (int i = lane; i < C_NUM; i += 32) g_cnt[i * CSTRIDE] = 0;
      }
      mbar_wait_slow(base + SM_SIG + 8 * SIG_DONE, 0);
      if (cta >= NREG || !(MASK & PH_OUT)) { cluster_arrive(); cluster_wait(); }
    }
  } else {
    asm volatile("setmaxnreg.inc.sync.aligned.u32 224;");
    TS_PRO();
    uint32_t rel;
    asm volatile("mapa.shared::cluster.u32 %0, %1, %2;" : "=r"(rel) : "r"(base + SM_BAR + 128 + 8 * (lane & 15)), "r"(lane >> 4));
    Cons c{base, rel, 0u, lane, warp, wg, (cta * 3 + wg) * 2048};
    if (wg == 1) bar_arrive(1, 256);
    if (NF0 < NFIRST && (MASK & PH_KV) && wi == 4 && cta < NREG) {
      if (elect()) {
#pragma unroll 1
        for (int it = NF0; it < NFIRST; it++) {
          asm volatile("{\n.reg .pred p;\n.reg .u32 a, b;\nmov.u32 a, %%clock;\nXL:\nmov.u32 b, %%clock;\nsub.u32 b, b, a;\nsetp.lt.u32 p, b, %0;\n@p bra XL;\n}\n" :: "r"(it == NF0 ? FGAP : FGAP2) : "memory");
          first_stage(it);
        }
      }
      __syncwarp();
    }
    TS(wg, 0);
    if (cta < NREG) {
      const int g = cta & 7, j = cta >> 3;
      Pend w = {};
      if (HOISTW && MASK == PH_ALL) c.wait(0);
#pragma unroll 1
      for (int half = 0; half < 2; half++) {
        const int h = j + 16 * half;
        if (MASK & PH_KV) cons_kv<(MASK & PH_ATT) != 0>(c, h, kv_slot<MASK>(h), g, w, half == 1 && (MASK & PH_ATT));
        TS(wg, 1 + 4 * half);
        if (MASK & PH_ATT) {
          Att a;
          cons_q<(MASK & PH_KV) != 0>(c, h, w, a.o);
          TS(wg, 2 + 4 * half);
          cons_att<MASK == PH_ALL>(c, a, h, g, w);
          if (half == 0) c.signal(SIG_WAR);
#pragma unroll
          for (int i = 0; i < 8; i++) w.hi[i] = make_uint4(0, 0, 0, 0);
          TS(wg, 3 + 4 * half);
          if (MASK != PH_ALL) { tile_store<0, 4>(w.lo, w.dst, lane); c.signal(SIG_CTX + half); }
        } else if (MASK & PH_KV) {
          out_piece<SCH_KV, true>(c, w, 0, true);
          for (int ks = 1; ks < 8; ks++) out_piece<SCH_KV, false>(c, w, ks, true);
          c.signal(SIG_KV + half);
        }
      }
      if (MASK & PH_OUT) cons_out<MASK>(c, M, P, cta, w);
    }
    if (cta >= NREG || !(MASK & PH_OUT)) {
      if (MASK & PH_CONV) cons_conv<MASK>(c, cta, cta < NREG ? CV_REG<MASK> : CV_EXTRA<MASK>);
      TS(wg, 9);
      c.signal(SIG_DONE);
      cluster_arrive();
    }
    TS(wg, 10);
  }
}

typedef CUresult (*EncFn)(CUtensorMap*, CUtensorMapDataType, cuuint32_t, void*, const cuuint64_t*, const cuuint64_t*, const cuuint32_t*, const cuuint32_t*,
                          CUtensorMapInterleave, CUtensorMapSwizzle, CUtensorMapL2promotion, CUtensorMapFloatOOBfill);
static void enc(EncFn f, CUtensorMap* m, const void* ptr, int rank, const cuuint64_t* dims, const cuuint64_t* strides, const cuuint32_t* box, CUtensorMapSwizzle sw,
                CUtensorMapDataType dt = CU_TENSOR_MAP_DATA_TYPE_BFLOAT16) {
  const cuuint32_t es[4] = {1, 1, 1, 1};
  f(m, dt, rank, (void*)ptr, dims, strides, box, es, CU_TENSOR_MAP_INTERLEAVE_NONE, sw, CU_TENSOR_MAP_L2_PROMOTION_L2_256B, CU_TENSOR_MAP_FLOAT_OOB_FILL_NONE);
}
static void enc2(EncFn f, CUtensorMap* m, const void* ptr, int cols, int rows, int brows) {
  const cuuint64_t d[2] = {(cuuint64_t)cols, (cuuint64_t)rows}, s[1] = {(cuuint64_t)cols * 2}; const cuuint32_t b[2] = {64, (cuuint32_t)brows};
  enc(f, m, ptr, 2, d, s, b, CU_TENSOR_MAP_SWIZZLE_128B);
}
static void encw(EncFn f, CUtensorMap* m, const void* ptr, int cols, int rows) {
  const cuuint64_t d[3] = {64, (cuuint64_t)rows, (cuuint64_t)cols / 64}, s[2] = {(cuuint64_t)cols * 2, 128}; const cuuint32_t b[3] = {64, 64, 2};
  enc(f, m, ptr, 3, d, s, b, CU_TENSOR_MAP_SWIZZLE_128B);
}
extern "C" void kernel_launch(void* const* d_in, const int* in_sizes, int n_in, void* d_out, int out_size) {
  static EncFn fn = nullptr;
  static int ncl = 0;
  static void* zptr = nullptr;
  static void* tptr = nullptr;
  if (!fn) {
    void* p = nullptr; cudaDriverEntryPointQueryResult qr;
    cudaGetDriverEntryPoint("cuTensorMapEncodeTiled", &p, cudaEnableDefault, &qr);
    fn = (EncFn)p;
    cudaFuncSetAttribute(gated_mix_kernel<PH_ALL>, cudaFuncAttributeMaxDynamicSharedMemorySize, SMEM_BYTES);
    cudaFuncSetAttribute(gated_mix_kernel<PH_PRE | PH_KV>, cudaFuncAttributeMaxDynamicSharedMemorySize, SMEM_BYTES);
    cudaFuncSetAttribute(gated_mix_kernel<PH_ATT | PH_CONV>, cudaFuncAttributeMaxDynamicSharedMemorySize, SMEM_BYTES);
    cudaFuncSetAttribute(gated_mix_kernel<PH_OUT>, cudaFuncAttributeMaxDynamicSharedMemorySize, SMEM_BYTES);
    cudaLaunchConfig_t cfg = {}; cfg.gridDim = NCTA; cfg.blockDim = 384; cfg.dynamicSmemBytes = SMEM_BYTES;
    cudaLaunchAttribute at; at.id = cudaLaunchAttributeClusterDimension; at.val.clusterDim.x = 2; at.val.clusterDim.y = 1; at.val.clusterDim.z = 1;
    cfg.attrs = &at; cfg.numAttrs = 1;
    cudaOccupancyMaxActiveClusters(&ncl, gated_mix_kernel<PH_ALL>, &cfg);
    cudaGetSymbolAddress(&zptr, g_z);
    cudaGetSymbolAddress(&tptr, g_T);
  }
  Maps M;
  enc2(fn, &M.x, d_in[0], 1024, 2048, 128);
  enc2(fn, &M.c, d_in[7], 512, 2048, 128);
  enc2(fn, &M.wq, d_in[8], 4096, 1024, 64);
  encw(fn, &M.wk, d_in[9], 4096, 512);
  encw(fn, &M.wv, d_in[10], 4096, 512);
  encw(fn, &M.wo, d_in[11], 1024, 4096);
  { const cuuint64_t d[3] = {64, 32, 1024}, s[2] = {128, 4096}; const cuuint32_t b[3] = {64, 40, 1}; enc(fn, &M.h, d_in[4], 3, d, s, b, CU_TENSOR_MAP_SWIZZLE_NONE); }
  enc2(fn, &M.z, zptr, 2048, 1024, 128);
  enc2(fn, &M.out, d_out, 1024, 2048, 16);
  { const cuuint64_t d[2] = {512, 512 * 16}, s[1] = {2048}; const cuuint32_t b[2] = {256, 8};
    enc(fn, &M.ctx, tptr, 2, d, s, b, CU_TENSOR_MAP_SWIZZLE_NONE, CU_TENSOR_MAP_DATA_TYPE_UINT32); }
  { const cuuint64_t d[4] = {1024, 2, 256, 4}, s[3] = {2048, 16384, 4096}; const cuuint32_t b[4] = {64, 2, 9, 4};
    enc(fn, &M.k, d_in[1], 4, d, s, b, CU_TENSOR_MAP_SWIZZLE_128B); enc(fn, &M.v, d_in[2], 4, d, s, b, CU_TENSOR_MAP_SWIZZLE_128B); }
  Params P{(const __nv_bfloat16*)d_in[0], (const __nv_bfloat16*)d_in[3],
           (const __nv_bfloat16*)d_in[5], (const __nv_bfloat16*)d_in[12], (__nv_bfloat16*)d_out};
  bool split = 2 * ncl < NCTA;
  if (!split) {
    gated_mix_kernel<PH_ALL><<<NCTA, 384, SMEM_BYTES>>>(M, P);
  } else {
    gated_mix_kernel<PH_PRE | PH_KV><<<NCTA, 384, SMEM_BYTES>>>(M, P);
    gated_mix_kernel<PH_ATT | PH_CONV><<<NCTA, 384, SMEM_BYTES>>>(M, P);
    gated_mix_kernel<PH_OUT><<<NCTA, 384, SMEM_BYTES>>>(M, P);
  }
}
```

```cpp
#include <cuda_runtime.h>
#include <cuda.h>
#include <cuda_bf16.h>
#include <stdint.h>

template<int TB> __device__ __forceinline__ void wgmma_ss_n256(float (&d)[128], uint64_t da, uint64_t db, int scale_d) {
  asm volatile("{\n.reg .pred p;\nsetp.ne.b32 p, %130, 0;\n"
    "wgmma.mma_async.sync.aligned.m64n256k16.f32.bf16.bf16 {%0, %1, %2, %3, %4, %5, %6, %7, %8, %9, %10, %11, %12, %13, %14, %15, %16, %17, %18, %19, %20, %21, %22, %23, %24, %25, %26, %27, %28, %29, %30, %31, %32, %33, %34, %35, %36, %37, %38, %39, %40, %41, %42, %43, %44, %45, %46, %47, %48, %49, %50, %51, %52, %53, %54, %55, %56, %57, %58, %59, %60, %61, %62, %63, %64, %65, %66, %67, %68, %69, %70, %71, %72, %73, %74, %75, %76, %77, %78, %79, %80, %81, %82, %83, %84, %85, %86, %87, %88, %89, %90, %91, %92, %93, %94, %95, %96, %97, %98, %99, %100, %101, %102, %103, %104, %105, %106, %107, %108, %109, %110, %111, %112, %113, %114, %115, %116, %117, %118, %119, %120, %121, %122, %123, %124, %125, %126, %127}, %128, %129, p, 1, 1, 0, %131;\n}\n"
    : "+f"(d[0]), "+f"(d[1]), "+f"(d[2]), "+f"(d[3]), "+f"(d[4]), "+f"(d[5]), "+f"(d[6]), "+f"(d[7]), "+f"(d[8]), "+f"(d[9]), "+f"(d[10]), "+f"(d[11]), "+f"(d[12]), "+f"(d[13]), "+f"(d[14]), "+f"(d[15]), "+f"(d[16]), "+f"(d[17]), "+f"(d[18]), "+f"(d[19]), "+f"(d[20]), "+f"(d[21]), "+f"(d[22]), "+f"(d[23]), "+f"(d[24]), "+f"(d[25]), "+f"(d[26]), "+f"(d[27]), "+f"(d[28]), "+f"(d[29]), "+f"(d[30]), "+f"(d[31]), "+f"(d[32]), "+f"(d[33]), "+f"(d[34]), "+f"(d[35]), "+f"(d[36]), "+f"(d[37]), "+f"(d[38]), "+f"(d[39]), "+f"(d[40]), "+f"(d[41]), "+f"(d[42]), "+f"(d[43]), "+f"(d[44]), "+f"(d[45]), "+f"(d[46]), "+f"(d[47]), "+f"(d[48]), "+f"(d[49]), "+f"(d[50]), "+f"(d[51]), "+f"(d[52]), "+f"(d[53]), "+f"(d[54]), "+f"(d[55]), "+f"(d[56]), "+f"(d[57]), "+f"(d[58]), "+f"(d[59]), "+f"(d[60]), "+f"(d[61]), "+f"(d[62]), "+f"(d[63]), "+f"(d[64]), "+f"(d[65]), "+f"(d[66]), "+f"(d[67]), "+f"(d[68]), "+f"(d[69]), "+f"(d[70]), "+f"(d[71]), "+f"(d[72]), "+f"(d[73]), "+f"(d[74]), "+f"(d[75]), "+f"(d[76]), "+f"(d[77]), "+f"(d[78]), "+f"(d[79]), "+f"(d[80]), "+f"(d[81]), "+f"(d[82]), "+f"(d[83]), "+f"(d[84]), "+f"(d[85]), "+f"(d[86]), "+f"(d[87]), "+f"(d[88]), "+f"(d[89]), "+f"(d[90]), "+f"(d[91]), "+f"(d[92]), "+f"(d[93]), "+f"(d[94]), "+f"(d[95]), "+f"(d[96]), "+f"(d[97]), "+f"(d[98]), "+f"(d[99]), "+f"(d[100]), "+f"(d[101]), "+f"(d[102]), "+f"(d[103]), "+f"(d[104]), "+f"(d[105]), "+f"(d[106]), "+f"(d[107]), "+f"(d[108]), "+f"(d[109]), "+f"(d[110]), "+f"(d[111]), "+f"(d[112]), "+f"(d[113]), "+f"(d[114]), "+f"(d[115]), "+f"(d[116]), "+f"(d[117]), "+f"(d[118]), "+f"(d[119]), "+f"(d[120]), "+f"(d[121]), "+f"(d[122]), "+f"(d[123]), "+f"(d[124]), "+f"(d[125]), "+f"(d[126]), "+f"(d[127])
    : "l"(da), "l"(db), "r"(scale_d), "n"(TB));
}
template<int TB> __device__ __forceinline__ void wgmma_ss_n128(float (&d)[64], uint64_t da, uint64_t db, int scale_d) {
  asm volatile("{\n.reg .pred p;\nsetp.ne.b32 p, %66, 0;\n"
    "wgmma.mma_async.sync.aligned.m64n128k16.f32.bf16.bf16 {%0, %1, %2, %3, %4, %5, %6, %7, %8, %9, %10, %11, %12, %13, %14, %15, %16, %17, %18, %19, %20, %21, %22, %23, %24, %25, %26, %27, %28, %29, %30, %31, %32, %33, %34, %35, %36, %37, %38, %39, %40, %41, %42, %43, %44, %45, %46, %47, %48, %49, %50, %51, %52, %53, %54, %55, %56, %57, %58, %59, %60, %61, %62, %63}, %64, %65, p, 1, 1, 0, %67;\n}\n"
    : "+f"(d[0]), "+f"(d[1]), "+f"(d[2]), "+f"(d[3]), "+f"(d[4]), "+f"(d[5]), "+f"(d[6]), "+f"(d[7]), "+f"(d[8]), "+f"(d[9]), "+f"(d[10]), "+f"(d[11]), "+f"(d[12]), "+f"(d[13]), "+f"(d[14]), "+f"(d[15]), "+f"(d[16]), "+f"(d[17]), "+f"(d[18]), "+f"(d[19]), "+f"(d[20]), "+f"(d[21]), "+f"(d[22]), "+f"(d[23]), "+f"(d[24]), "+f"(d[25]), "+f"(d[26]), "+f"(d[27]), "+f"(d[28]), "+f"(d[29]), "+f"(d[30]), "+f"(d[31]), "+f"(d[32]), "+f"(d[33]), "+f"(d[34]), "+f"(d[35]), "+f"(d[36]), "+f"(d[37]), "+f"(d[38]), "+f"(d[39]), "+f"(d[40]), "+f"(d[41]), "+f"(d[42]), "+f"(d[43]), "+f"(d[44]), "+f"(d[45]), "+f"(d[46]), "+f"(d[47]), "+f"(d[48]), "+f"(d[49]), "+f"(d[50]), "+f"(d[51]), "+f"(d[52]), "+f"(d[53]), "+f"(d[54]), "+f"(d[55]), "+f"(d[56]), "+f"(d[57]), "+f"(d[58]), "+f"(d[59]), "+f"(d[60]), "+f"(d[61]), "+f"(d[62]), "+f"(d[63])
    : "l"(da), "l"(db), "r"(scale_d), "n"(TB));
}
template<int TB> __device__ __forceinline__ void wgmma_rs_n32(float (&d)[16], uint32_t a0, uint32_t a1, uint32_t a2, uint32_t a3, uint64_t db, int scale_d) {
  asm volatile("{\n.reg .pred p;\nsetp.ne.b32 p, %21, 0;\n"
    "wgmma.mma_async.sync.aligned.m64n32k16.f32.bf16.bf16 {%0, %1, %2, %3, %4, %5, %6, %7, %8, %9, %10, %11, %12, %13, %14, %15}, {%16, %17, %18, %19}, %20, p, 1, 1, %22;\n}\n"
    : "+f"(d[0]), "+f"(d[1]), "+f"(d[2]), "+f"(d[3]), "+f"(d[4]), "+f"(d[5]), "+f"(d[6]), "+f"(d[7]), "+f"(d[8]), "+f"(d[9]), "+f"(d[10]), "+f"(d[11]), "+f"(d[12]), "+f"(d[13]), "+f"(d[14]), "+f"(d[15])
    : "r"(a0), "r"(a1), "r"(a2), "r"(a3), "l"(db), "r"(scale_d), "n"(TB));
}
__device__ __forceinline__ void wgmma_pv_sel(float (&d)[64], const uint32_t (&p)[32], uint64_t db, int full, int acc, int wg) {
  asm volatile("{\n.reg .pred q, s, w;\n.reg .b64 t;\nsetp.eq.b32 w, %99, 0;\nsetp.ne.b32 s, %98, 0;\nsetp.eq.b32 q, %97, 0;\n@q bra.uni LH;\n"
    "wgmma.fence.sync.aligned;\n"
    "add.s64 t, %96, 0;\nwgmma.mma_async.sync.aligned.m64n128k16.f32.bf16.bf16 {%0, %1, %2, %3, %4, %5, %6, %7, %8, %9, %10, %11, %12, %13, %14, %15, %16, %17, %18, %19, %20, %21, %22, %23, %24, %25, %26, %27, %28, %29, %30, %31, %32, %33, %34, %35, %36, %37, %38, %39, %40, %41, %42, %43, %44, %45, %46, %47, %48, %49, %50, %51, %52, %53, %54, %55, %56, %57, %58, %59, %60, %61, %62, %63}, {%64, %65, %66, %67}, t, s, 1, 1, 1;\n"
    "add.s64 t, %96, 256;\nwgmma.mma_async.sync.aligned.m64n128k16.f32.bf16.bf16 {%0, %1, %2, %3, %4, %5, %6, %7, %8, %9, %10, %11, %12, %13, %14, %15, %16, %17, %18, %19, %20, %21, %22, %23, %24, %25, %26, %27, %28, %29, %30, %31, %32, %33, %34, %35, %36, %37, %38, %39, %40, %41, %42, %43, %44, %45, %46, %47, %48, %49, %50, %51, %52, %53, %54, %55, %56, %57, %58, %59, %60, %61, %62, %63}, {%68, %69, %70, %71}, t, 1, 1, 1, 1;\n"
    "add.s64 t, %96, 512;\nwgmma.mma_async.sync.aligned.m64n128k16.f32.bf16.bf16 {%0, %1, %2, %3, %4, %5, %6, %7, %8, %9, %10, %11, %12, %13, %14, %15, %16, %17, %18, %19, %20, %21, %22, %23, %24, %25, %26, %27, %28, %29, %30, %31, %32, %33, %34, %35, %36, %37, %38, %39, %40, %41, %42, %43, %44, %45, %46, %47, %48, %49, %50, %51, %52, %53, %54, %55, %56, %57, %58, %59, %60, %61, %62, %63}, {%72, %73, %74, %75}, t, 1, 1, 1, 1;\n"
    "add.s64 t, %96, 768;\nwgmma.mma_async.sync.aligned.m64n128k16.f32.bf16.bf16 {%0, %1, %2, %3, %4, %5, %6, %7, %8, %9, %10, %11, %12, %13, %14, %15, %16, %17, %18, %19, %20, %21, %22, %23, %24, %25, %26, %27, %28, %29, %30, %31, %32, %33, %34, %35, %36, %37, %38, %39, %40, %41, %42, %43, %44, %45, %46, %47, %48, %49, %50, %51, %52, %53, %54, %55, %56, %57, %58, %59, %60, %61, %62, %63}, {%76, %77, %78, %79}, t, 1, 1, 1, 1;\n"
    "add.s64 t, %96, 1024;\nwgmma.mma_async.sync.aligned.m64n128k16.f32.bf16.bf16 {%0, %1, %2, %3, %4, %5, %6, %7, %8, %9, %10, %11, %12, %13, %14, %15, %16, %17, %18, %19, %20, %21, %22, %23, %24, %25, %26, %27, %28, %29, %30, %31, %32, %33, %34, %35, %36, %37, %38, %39, %40, %41, %42, %43, %44, %45, %46, %47, %48, %49, %50, %51, %52, %53, %54, %55, %56, %57, %58, %59, %60, %61, %62, %63}, {%80, %81, %82, %83}, t, 1, 1, 1, 1;\n"
    "add.s64 t, %96, 1280;\nwgmma.mma_async.sync.aligned.m64n128k16.f32.bf16.bf16 {%0, %1, %2, %3, %4, %5, %6, %7, %8, %9, %10, %11, %12, %13, %14, %15, %16, %17, %18, %19, %20, %21, %22, %23, %24, %25, %26, %27, %28, %29, %30, %31, %32, %33, %34, %35, %36, %37, %38, %39, %40, %41, %42, %43, %44, %45, %46, %47, %48, %49, %50, %51, %52, %53, %54, %55, %56, %57, %58, %59, %60, %61, %62, %63}, {%84, %85, %86, %87}, t, 1, 1, 1, 1;\n"
    "@w bar.arrive 2, 256;\n@!w bar.arrive 1, 256;\n"
    "add.s64 t, %96, 1536;\nwgmma.mma_async.sync.aligned.m64n128k16.f32.bf16.bf16 {%0, %1, %2, %3, %4, %5, %6, %7, %8, %9, %10, %11, %12, %13, %14, %15, %16, %17, %18, %19, %20, %21, %22, %23, %24, %25, %26, %27, %28, %29, %30, %31, %32, %33, %34, %35, %36, %37, %38, %39, %40, %41, %42, %43, %44, %45, %46, %47, %48, %49, %50, %51, %52, %53, %54, %55, %56, %57, %58, %59, %60, %61, %62, %63}, {%88, %89, %90, %91}, t, 1, 1, 1, 1;\n"
    "add.s64 t, %96, 1792;\nwgmma.mma_async.sync.aligned.m64n128k16.f32.bf16.bf16 {%0, %1, %2, %3, %4, %5, %6, %7, %8, %9, %10, %11, %12, %13, %14, %15, %16, %17, %18, %19, %20, %21, %22, %23, %24, %25, %26, %27, %28, %29, %30, %31, %32, %33, %34, %35, %36, %37, %38, %39, %40, %41, %42, %43, %44, %45, %46, %47, %48, %49, %50, %51, %52, %53, %54, %55, %56, %57, %58, %59, %60, %61, %62, %63}, {%92, %93, %94, %95}, t, 1, 1, 1, 1;\n"
    "wgmma.commit_group.sync.aligned;\n"
    "bra.uni LE;\nLH:\n"
    "wgmma.fence.sync.aligned;\n"
    "add.s64 t, %96, 0;\nwgmma.mma_async.sync.aligned.m64n128k16.f32.bf16.bf16 {%0, %1, %2, %3, %4, %5, %6, %7, %8, %9, %10, %11, %12, %13, %14, %15, %16, %17, %18, %19, %20, %21, %22, %23, %24, %25, %26, %27, %28, %29, %30, %31, %32, %33, %34, %35, %36, %37, %38, %39, %40, %41, %42, %43, %44, %45, %46, %47, %48, %49, %50, %51, %52, %53, %54, %55, %56, %57, %58, %59, %60, %61, %62, %63}, {%80, %81, %82, %83}, t, s, 1, 1, 1;\n"
    "add.s64 t, %96, 256;\nwgmma.mma_async.sync.aligned.m64n128k16.f32.bf16.bf16 {%0, %1, %2, %3, %4, %5, %6, %7, %8, %9, %10, %11, %12, %13, %14, %15, %16, %17, %18, %19, %20, %21, %22, %23, %24, %25, %26, %27, %28, %29, %30, %31, %32, %33, %34, %35, %36, %37, %38, %39, %40, %41, %42, %43, %44, %45, %46, %47, %48, %49, %50, %51, %52, %53, %54, %55, %56, %57, %58, %59, %60, %61, %62, %63}, {%84, %85, %86, %87}, t, 1, 1, 1, 1;\n"
    "@w bar.arrive 2, 256;\n@!w bar.arrive 1, 256;\n"
    "add.s64 t, %96, 512;\nwgmma.mma_async.sync.aligned.m64n128k16.f32.bf16.bf16 {%0, %1, %2, %3, %4, %5, %6, %7, %8, %9, %10, %11, %12, %13, %14, %15, %16, %17, %18, %19, %20, %21, %22, %23, %24, %25, %26, %27, %28, %29, %30, %31, %32, %33, %34, %35, %36, %37, %38, %39, %40, %41, %42, %43, %44, %45, %46, %47, %48, %49, %50, %51, %52, %53, %54, %55, %56, %57, %58, %59, %60, %61, %62, %63}, {%88, %89, %90, %91}, t, 1, 1, 1, 1;\n"
    "add.s64 t, %96, 768;\nwgmma.mma_async.sync.aligned.m64n128k16.f32.bf16.bf16 {%0, %1, %2, %3, %4, %5, %6, %7, %8, %9, %10, %11, %12, %13, %14, %15, %16, %17, %18, %19, %20, %21, %22, %23, %24, %25, %26, %27, %28, %29, %30, %31, %32, %33, %34, %35, %36, %37, %38, %39, %40, %41, %42, %43, %44, %45, %46, %47, %48, %49, %50, %51, %52, %53, %54, %55, %56, %57, %58, %59, %60, %61, %62, %63}, {%92, %93, %94, %95}, t, 1, 1, 1, 1;\n"
    "wgmma.commit_group.sync.aligned;\n"
    "LE:\n}\n"
    : "+f"(d[0]), "+f"(d[1]), "+f"(d[2]), "+f"(d[3]), "+f"(d[4]), "+f"(d[5]), "+f"(d[6]), "+f"(d[7]), "+f"(d[8]), "+f"(d[9]), "+f"(d[10]), "+f"(d[11]), "+f"(d[12]), "+f"(d[13]), "+f"(d[14]), "+f"(d[15]), "+f"(d[16]), "+f"(d[17]), "+f"(d[18]), "+f"(d[19]), "+f"(d[20]), "+f"(d[21]), "+f"(d[22]), "+f"(d[23]), "+f"(d[24]), "+f"(d[25]), "+f"(d[26]), "+f"(d[27]), "+f"(d[28]), "+f"(d[29]), "+f"(d[30]), "+f"(d[31]), "+f"(d[32]), "+f"(d[33]), "+f"(d[34]), "+f"(d[35]), "+f"(d[36]), "+f"(d[37]), "+f"(d[38]), "+f"(d[39]), "+f"(d[40]), "+f"(d[41]), "+f"(d[42]), "+f"(d[43]), "+f"(d[44]), "+f"(d[45]), "+f"(d[46]), "+f"(d[47]), "+f"(d[48]), "+f"(d[49]), "+f"(d[50]), "+f"(d[51]), "+f"(d[52]), "+f"(d[53]), "+f"(d[54]), "+f"(d[55]), "+f"(d[56]), "+f"(d[57]), "+f"(d[58]), "+f"(d[59]), "+f"(d[60]), "+f"(d[61]), "+f"(d[62]), "+f"(d[63])
    : "r"(p[0]), "r"(p[1]), "r"(p[2]), "r"(p[3]), "r"(p[4]), "r"(p[5]), "r"(p[6]), "r"(p[7]), "r"(p[8]), "r"(p[9]), "r"(p[10]), "r"(p[11]), "r"(p[12]), "r"(p[13]), "r"(p[14]), "r"(p[15]), "r"(p[16]), "r"(p[17]), "r"(p[18]), "r"(p[19]), "r"(p[20]), "r"(p[21]), "r"(p[22]), "r"(p[23]), "r"(p[24]), "r"(p[25]), "r"(p[26]), "r"(p[27]), "r"(p[28]), "r"(p[29]), "r"(p[30]), "r"(p[31]), "l"(db), "r"(full), "r"(acc), "r"(wg) : "memory");
}

constexpr int NCTA = 132, NREG = 128;
constexpr int UNIT = 16384, NUNIT = 14;
constexpr uint32_t SMEM_BASE = 1024;
constexpr int SM_BAR = NUNIT * UNIT;
constexpr int SM_GATE = SM_BAR + 1024;
constexpr int SMEM_BYTES = SM_BAR + 1536;
constexpr int UPITCH = 4160, UCH = 2 * UPITCH;
constexpr float QSCALE = 0.08838834764831845f * 1.4426950408889634f;
constexpr float BOUND2 = 60.f * 60.f / 1.15f;
#define CONV_REG 5
constexpr int C_KV = 0;
constexpr int C_CTX = 32;
constexpr int C_U = 48;
constexpr int C_Z = 80;
constexpr int C_GATE = 88;
constexpr int C_EXIT = 89;
#define PRE_EARLY 2
#define PRE_HALF 1
#define ATT_SPLIT 4
#define NFIRST 4
#define PRE_DELAY 0
#define FINAL_ST 1
#define Z_AT 60
#define PRE_DELAY_BAR 9
#define PRE_FMA 0
#define PRE_SLEEP 300
#define GATE_SLEEP 1000
#define GATE_EARLY 1
#define OC_S0 2
#define OC_S1 11
#define OC_POST 0
#define OC_L0 18
#define OC_L1 18
#define ST_1 4
#define ST_D 2
#define ST_0 1
#define ST_0D 0
#define SCH_KV 0x6665544433221100ull
#define SCH_Q 0x6665544433221100ull
#define NK_AT 1
#ifndef NV_AT
#define NV_AT 3
#endif
#define DS_A 0
#define DS_B 4
#define CHK_D 12
#define ER1 1
#define PEXP 1
#define MFP 1
#define CH2 1
#define SHW 1
#define SHR 1
#define PK1 0
#define V1F 0
#define K1V0 0
#define TFMA 0
#define FGAP 600
#define FGAP2 200
#define NF0 1
#define HOISTW 0
#define BARP 1
#define EF 127
#define POL(bit) (((EF >> (bit)) & 1) != 0)
constexpr int C_WAR = 96;
constexpr int C_NUM = 112;
constexpr int CSTRIDE = 32;
constexpr int SM_KMAX = SM_BAR + 640, SM_DUMMY = SM_BAR + 648, SM_PRE = SM_BAR + 112, SM_SIG = SM_BAR + 256, SM_RDY = SM_BAR + 384;
enum { SIG_KV = 0, SIG_CTX = 2, SIG_Z = 4, SIG_DONE = 8, SIG_WAR = 9, SIG_ATT = 10 };
enum { RDY_KV = 0, RDY_CTX = 2, RDY_WAR = 4, RDY_G = 5, RDY_X = 6, RDY_AUX = 7, RDY_U = 8, RDY_Z = 9 };
enum { PH_PRE = 1, PH_KV = 2, PH_ATT = 4, PH_CONV = 8, PH_OUT = 16, PH_ALL = 31 };

constexpr uint32_t T_CTX = 0, T_KV = 16 * 32 * 32768, T_BYTES = T_KV + 32 * 16 * 65536;
__device__ __align__(1024) uint8_t g_T[T_BYTES];
__device__ __align__(1024) uint8_t g_u[1024 * UCH];
__device__ __align__(1024) __nv_bfloat16 g_z[1024 * 2048];
__device__ __align__(1024) float g_gate[2048];
__device__ __align__(1024) float g_kn2[32 * 128];
__device__ __align__(1024) unsigned g_cnt[C_NUM * CSTRIDE];

struct __align__(64) Maps { CUtensorMap c, wk, wv, x, wq, wo, h, z, out, ctx, k, v; };
struct Params {
  const __nv_bfloat16 *x, *shift, *D, *gw;
  __nv_bfloat16* out;
};

__device__ __forceinline__ void wg_fence() { asm volatile("wgmma.fence.sync.aligned;" ::: "memory"); }
__device__ __forceinline__ void wg_commit() { asm volatile("wgmma.commit_group.sync.aligned;" ::: "memory"); }
template<int N> __device__ __forceinline__ void wg_wait() { asm volatile("wgmma.wait_group.sync.aligned %0;" :: "n"(N) : "memory"); }
__device__ __forceinline__ uint64_t odesc(uint32_t addr, uint32_t lbo, uint32_t sbo, uint32_t swz) {
  uint64_t d = (uint64_t)(addr >> 4) + (((uint64_t)(lbo >> 4) << 16) | ((uint64_t)(sbo >> 4) << 32) | ((uint64_t)swz << 62));
  asm volatile("" : "+l"(d));
  return d;
}
__device__ __forceinline__ void mbar_init(uint32_t bar, int cnt) { asm volatile("mbarrier.init.shared::cta.b64 [%0], %1;" :: "r"(bar), "r"(cnt)); }
__device__ __forceinline__ void mbar_expect(uint32_t bar, uint32_t bytes) { asm volatile("mbarrier.arrive.expect_tx.shared::cta.b64 _, [%0], %1;" :: "r"(bar), "r"(bytes) : "memory"); }
__device__ __forceinline__ void mbar_arrive(uint32_t bar) { asm volatile("mbarrier.arrive.shared::cta.b64 _, [%0];" :: "r"(bar) : "memory"); }
__device__ __forceinline__ void mbar_arrive_n(uint32_t bar, int n) { asm volatile("mbarrier.arrive.shared::cta.b64 _, [%0], %1;" :: "r"(bar), "r"(n) : "memory"); }
__device__ __forceinline__ void mbar_wait(uint32_t bar, uint32_t parity) {
  asm volatile("{\n.reg .pred p;\nLW:\nmbarrier.try_wait.parity.shared::cta.b64 p, [%0], %1;\n@!p bra LW;\n}\n" :: "r"(bar), "r"(parity) : "memory");
}
__device__ __forceinline__ void mbar_wait_slow(uint32_t bar, uint32_t parity) {
  asm volatile("{\n.reg .pred p;\n.reg .u32 n;\nmov.u32 n, 0;\n"
    "LW:\nmbarrier.test_wait.parity.shared::cta.b64 p, [%0], %1;\n@p bra LD;\n"
    "nanosleep.u32 128;\nadd.u32 n, n, 1;\nsetp.lt.u32 p, n, 4194304;\n@p bra LW;\ntrap;\nLD:\n}\n" :: "r"(bar), "r"(parity) : "memory");
}
__device__ __forceinline__ void mbar_wait_all(uint32_t bar, uint32_t parity) {
  asm volatile("{\n.reg .pred p, q;\nLW:\nmbarrier.try_wait.parity.shared::cta.b64 p, [%0], %1;\nvote.sync.all.pred q, p, 0xffffffff;\n@!q bra.uni LW;\n}\n" :: "r"(bar), "r"(parity) : "memory");
}
__device__ __forceinline__ void cnt_wait(const unsigned* p, unsigned target) {
  asm volatile("{\n.reg .pred p;\n.reg .u32 n, v;\nmov.u32 n, 0;\n"
    "LW:\nld.relaxed.gpu.global.u32 v, [%0];\nsetp.ge.u32 p, v, %1;\n@p bra LD;\n"
    "nanosleep.u32 64;\nadd.u32 n, n, 1;\nsetp.lt.u32 p, n, 4194304;\n@p bra LW;\ntrap;\nLD:\nfence.acquire.gpu;\nfence.proxy.async.global;\n}\n" :: "l"(p), "r"(target) : "memory");
}
__device__ __forceinline__ void cnt_signal(unsigned* p, int lane) {
  __syncwarp();
  if (lane == 0) asm volatile("red.release.gpu.global.add.u32 [%0], 1;" :: "l"(p) : "memory");
}
__device__ __forceinline__ void cnt_publish(unsigned* p, unsigned n, bool fence) {
  if (fence) asm volatile("fence.release.gpu;" ::: "memory");
  asm volatile("red.relaxed.gpu.global.add.u32 [%0], %1;" :: "l"(p), "r"(n) : "memory");
}
__device__ __forceinline__ uint64_t pol_first() { uint64_t p; asm("createpolicy.fractional.L2::evict_first.b64 %0, 1.0;" : "=l"(p)); return p; }
__device__ __forceinline__ void bulk_g2s(uint32_t dst, const void* src, uint32_t bytes, uint32_t bar, bool stream = false) {
  if (stream) asm volatile("cp.async.bulk.shared::cluster.global.mbarrier::complete_tx::bytes.L2::cache_hint [%0], [%1], %2, [%3], %4;" :: "r"(dst), "l"(src), "r"(bytes), "r"(bar), "l"(pol_first()) : "memory");
  else asm volatile("cp.async.bulk.shared::cluster.global.mbarrier::complete_tx::bytes [%0], [%1], %2, [%3];" :: "r"(dst), "l"(src), "r"(bytes), "r"(bar) : "memory");
}
__device__ __forceinline__ void tma2d(uint32_t dst, const CUtensorMap* m, int x, int y, uint32_t bar, bool stream = false) {
  if (stream) asm volatile("cp.async.bulk.tensor.2d.shared::cluster.global.mbarrier::complete_tx::bytes.L2::cache_hint [%0], [%1, {%3, %4}], [%2], %5;" :: "r"(dst), "l"(m), "r"(bar), "r"(x), "r"(y), "l"(pol_first()) : "memory");
  else asm volatile("cp.async.bulk.tensor.2d.shared::cluster.global.mbarrier::complete_tx::bytes [%0], [%1, {%3, %4}], [%2];" :: "r"(dst), "l"(m), "r"(bar), "r"(x), "r"(y) : "memory");
}
__device__ __forceinline__ void tma3d(uint32_t dst, const CUtensorMap* m, int x, int y, int z, uint32_t bar, bool stream = false) {
  if (stream) asm volatile("cp.async.bulk.tensor.3d.shared::cluster.global.mbarrier::complete_tx::bytes.L2::cache_hint [%0], [%1, {%3, %4, %5}], [%2], %6;" :: "r"(dst), "l"(m), "r"(bar), "r"(x), "r"(y), "r"(z), "l"(pol_first()) : "memory");
  else asm volatile("cp.async.bulk.tensor.3d.shared::cluster.global.mbarrier::complete_tx::bytes [%0], [%1, {%3, %4, %5}], [%2];" :: "r"(dst), "l"(m), "r"(bar), "r"(x), "r"(y), "r"(z) : "memory");
}
__device__ __forceinline__ void tma4d(uint32_t dst, const CUtensorMap* m, int x, int y, int z, int w, uint32_t bar, bool stream = false) {
  if (stream) asm volatile("cp.async.bulk.tensor.4d.shared::cluster.global.mbarrier::complete_tx::bytes.L2::cache_hint [%0], [%1, {%3, %4, %5, %6}], [%2], %7;" :: "r"(dst), "l"(m), "r"(bar), "r"(x), "r"(y), "r"(z), "r"(w), "l"(pol_first()) : "memory");
  else asm volatile("cp.async.bulk.tensor.4d.shared::cluster.global.mbarrier::complete_tx::bytes [%0], [%1, {%3, %4, %5, %6}], [%2];" :: "r"(dst), "l"(m), "r"(bar), "r"(x), "r"(y), "r"(z), "r"(w) : "memory");
}
__device__ __forceinline__ void bulk_g2s_mc(uint32_t dst, const void* src, uint32_t bytes, uint32_t bar, bool stream = false) {
  if (stream) asm volatile("cp.async.bulk.shared::cluster.global.mbarrier::complete_tx::bytes.multicast::cluster.L2::cache_hint [%0], [%1], %2, [%3], %4, %5;" :: "r"(dst), "l"(src), "r"(bytes), "r"(bar), "h"((uint16_t)3), "l"(pol_first()) : "memory");
  else asm volatile("cp.async.bulk.shared::cluster.global.mbarrier::complete_tx::bytes.multicast::cluster [%0], [%1], %2, [%3], %4;" :: "r"(dst), "l"(src), "r"(bytes), "r"(bar), "h"((uint16_t)3) : "memory");
}
__device__ __forceinline__ void tma2d_mc(uint32_t dst, const CUtensorMap* m, int x, int y, uint32_t bar, bool stream = false) {
  if (stream) asm volatile("cp.async.bulk.tensor.2d.shared::cluster.global.mbarrier::complete_tx::bytes.multicast::cluster.L2::cache_hint [%0], [%1, {%3, %4}], [%2], %5, %6;" :: "r"(dst), "l"(m), "r"(bar), "r"(x), "r"(y), "h"((uint16_t)3), "l"(pol_first()) : "memory");
  else asm volatile("cp.async.bulk.tensor.2d.shared::cluster.global.mbarrier::complete_tx::bytes.multicast::cluster [%0], [%1, {%3, %4}], [%2], %5;" :: "r"(dst), "l"(m), "r"(bar), "r"(x), "r"(y), "h"((uint16_t)3) : "memory");
}
__device__ __forceinline__ void tma3d_mc(uint32_t dst, const CUtensorMap* m, int x, int y, int z, uint32_t bar, bool stream = false) {
  if (stream) asm volatile("cp.async.bulk.tensor.3d.shared::cluster.global.mbarrier::complete_tx::bytes.multicast::cluster.L2::cache_hint [%0], [%1, {%3, %4, %5}], [%2], %6, %7;" :: "r"(dst), "l"(m), "r"(bar), "r"(x), "r"(y), "r"(z), "h"((uint16_t)3), "l"(pol_first()) : "memory");
  else asm volatile("cp.async.bulk.tensor.3d.shared::cluster.global.mbarrier::complete_tx::bytes.multicast::cluster [%0], [%1, {%3, %4, %5}], [%2], %6;" :: "r"(dst), "l"(m), "r"(bar), "r"(x), "r"(y), "r"(z), "h"((uint16_t)3) : "memory");
}
__device__ __forceinline__ void map_pf(const CUtensorMap* m) { asm volatile("prefetch.tensormap [%0];" :: "l"(m) : "memory"); }
__device__ __forceinline__ void tma2d_store(const CUtensorMap* m, uint32_t src, int x, int y) {
  if (POL(12)) asm volatile("cp.async.bulk.tensor.2d.global.shared::cta.bulk_group.L2::cache_hint [%0, {%2, %3}], [%1], %4;" :: "l"(m), "r"(src), "r"(x), "r"(y), "l"(pol_first()) : "memory");
  else asm volatile("cp.async.bulk.tensor.2d.global.shared::cta.bulk_group [%0, {%2, %3}], [%1];" :: "l"(m), "r"(src), "r"(x), "r"(y) : "memory");
}
__device__ __forceinline__ bool elect() {
  uint32_t r; asm volatile("{\n.reg .pred p;\nelect.sync _|p, 0xffffffff;\nselp.u32 %0, 1, 0, p;\n}\n" : "=r"(r)); return r != 0;
}
__device__ __forceinline__ void cluster_arrive() { asm volatile("barrier.cluster.arrive;" ::: "memory"); }
__device__ __forceinline__ void cluster_wait() { asm volatile("barrier.cluster.wait;" ::: "memory"); }
__device__ __forceinline__ void bar_sync(int id, int n) { asm volatile("bar.sync %0, %1;" :: "r"(id), "r"(n) : "memory"); }
__device__ __forceinline__ void bar_arrive(int id, int n) { asm volatile("bar.arrive %0, %1;" :: "r"(id), "r"(n) : "memory"); }
__device__ __forceinline__ int bar_and(int id, int n, int pred) {
  int r; asm volatile("{\n.reg .pred p, q;\nsetp.ne.b32 p, %3, 0;\nbar.red.and.pred q, %1, %2, p;\nselp.b32 %0, 1, 0, q;\n}\n" : "=r"(r) : "r"(id), "r"(n), "r"(pred) : "memory");
  return r;
}
__device__ __forceinline__ void fence_async_smem() { asm volatile("fence.proxy.async.shared::cta;" ::: "memory"); }
__device__ __forceinline__ float ex2(float x) { float y; asm("ex2.approx.ftz.f32 %0, %1;" : "=f"(y) : "f"(x)); return y; }
__device__ __forceinline__ float rcp(float x) { float y; asm("rcp.approx.ftz.f32 %0, %1;" : "=f"(y) : "f"(x)); return y; }
__device__ __forceinline__ uint32_t pack_bf16(float lo, float hi) { uint32_t r; asm("cvt.rn.bf16x2.f32 %0, %1, %2;" : "=r"(r) : "f"(hi), "f"(lo)); return r; }
__device__ __forceinline__ uint32_t hmul2(uint32_t a, uint32_t b) { uint32_t r; asm("mul.rn.bf16x2 %0, %1, %2;" : "=r"(r) : "r"(a), "r"(b)); return r; }
__device__ __forceinline__ uint32_t hadd2(uint32_t a, uint32_t b) { uint32_t r; asm("add.rn.bf16x2 %0, %1, %2;" : "=r"(r) : "r"(a), "r"(b)); return r; }
__device__ __forceinline__ uint32_t hfma2(uint32_t a, uint32_t b, uint32_t c) { uint32_t r; asm("fma.rn.bf16x2 %0, %1, %2, %3;" : "=r"(r) : "r"(a), "r"(b), "r"(c)); return r; }
__device__ __forceinline__ float bf_lo(uint32_t a) { return __uint_as_float(a << 16); }
__device__ __forceinline__ float bf_hi(uint32_t a) { return __uint_as_float(a & 0xffff0000u); }
__device__ __forceinline__ uint32_t lds32(uint32_t a) { uint32_t v; asm volatile("ld.shared.u32 %0, [%1];" : "=r"(v) : "r"(a) : "memory"); return v; }
__device__ __forceinline__ float2 lds64f(uint32_t a) { float2 v; asm volatile("ld.shared.v2.f32 {%0,%1}, [%2];" : "=f"(v.x), "=f"(v.y) : "r"(a) : "memory"); return v; }
__device__ __forceinline__ uint4 lds128(uint32_t a) { uint4 v; asm volatile("ld.shared.v4.u32 {%0,%1,%2,%3}, [%4];" : "=r"(v.x), "=r"(v.y), "=r"(v.z), "=r"(v.w) : "r"(a) : "memory"); return v; }
__device__ __forceinline__ void sts64f(uint32_t a, float x, float y) { asm volatile("st.shared.v2.f32 [%0], {%1,%2};" :: "r"(a), "f"(x), "f"(y) : "memory"); }
__device__ __forceinline__ void sts128(uint32_t a, uint4 v) { asm volatile("st.shared.v4.u32 [%0], {%1,%2,%3,%4};" :: "r"(a), "r"(v.x), "r"(v.y), "r"(v.z), "r"(v.w) : "memory"); }
template<int OFF> __device__ __forceinline__ void sts128o(uint32_t a, uint4 v) { asm volatile("st.shared.v4.u32 [%0+%5], {%1,%2,%3,%4};" :: "r"(a), "r"(v.x), "r"(v.y), "r"(v.z), "r"(v.w), "n"(OFF) : "memory"); }
__device__ __forceinline__ void ldsm4(uint32_t a, uint32_t& r0, uint32_t& r1, uint32_t& r2, uint32_t& r3) {
  asm volatile("ldmatrix.sync.aligned.m8n8.x4.shared.b16 {%0,%1,%2,%3}, [%4];" : "=r"(r0), "=r"(r1), "=r"(r2), "=r"(r3) : "r"(a) : "memory");
}
__device__ __forceinline__ void ldsm4t(uint32_t a, uint32_t& r0, uint32_t& r1, uint32_t& r2, uint32_t& r3) {
  asm volatile("ldmatrix.sync.aligned.m8n8.x4.trans.shared.b16 {%0,%1,%2,%3}, [%4];" : "=r"(r0), "=r"(r1), "=r"(r2), "=r"(r3) : "r"(a) : "memory");
}
__device__ __forceinline__ void stsm4(uint32_t a, uint32_t r0, uint32_t r1, uint32_t r2, uint32_t r3) {
  asm volatile("stmatrix.sync.aligned.m8n8.x4.shared.b16 [%0], {%1,%2,%3,%4};" :: "r"(a), "r"(r0), "r"(r1), "r"(r2), "r"(r3) : "memory");
}
template<int N> __device__ __forceinline__ void fence_regs(float (&d)[N]) {
#pragma unroll
  for (int i = 0; i < N; i++) asm volatile("" : "+f"(d[i]) :: "memory");
}
template<int N> __device__ __forceinline__ void fence_regs(uint32_t (&d)[N]) {
#pragma unroll
  for (int i = 0; i < N; i++) asm volatile("" : "+r"(d[i]) :: "memory");
}
__device__ __forceinline__ void sched_fence(float x, uint32_t dummy) {
  asm volatile("{\n.reg .pred p;\nsetp.eq.u32 p, %0, 0x7fc12345;\n@p st.shared.u32 [%1], %0;\n}\n" :: "r"(__float_as_uint(x)), "r"(dummy) : "memory");
}
#define ROT 0
#define CTAID blockIdx.x
#define PTRACE 0
#define TS(role, i)
#define TSA(i)
#define TSS(i)
#define TSK(i)
#define TS2(role, i)
#define TR(obj, role, tag)

#define SHADOW if (gridDim.y == 1)

struct Prod {
  uint32_t base, mask; int lane, nt;
  __device__ __forceinline__ uint32_t full(int u) const { return base + SM_BAR + 8 * u; }
  __device__ __forceinline__ uint32_t addr(int u) const { return base + u * UNIT; }
  __device__ __forceinline__ void acquire(int u, int n) {
    const int v = u + min(lane, n - 1);
    mbar_wait_all(base + SM_BAR + 128 + 8 * v, mask >> v);
    mask ^= ((1u << n) - 1) << u;
    TR(*this, 2, 16 + u);
  }
  __device__ __forceinline__ void acquire_slow(int u, int n) {
    for (int i = 0; i < n; i++) mbar_wait_slow(base + SM_BAR + 128 + 8 * (u + i), mask >> (u + i));
    mask ^= ((1u << n) - 1) << u;
  }
};
struct Cons {
  uint32_t base, rel, mask; int lane, warp, wg, nt;
  __device__ __forceinline__ uint32_t addr(int u) const { return base + u * UNIT; }
  __device__ __forceinline__ static uint32_t daddr(int u) { return SMEM_BASE + u * UNIT; }
  __device__ __forceinline__ void wait(int u) { TR(*this, wg, 1); mbar_wait(base + SM_BAR + 8 * u, mask >> u); mask ^= 1u << u; TR(*this, wg, 2); }
  __device__ __forceinline__ void skip(int u) { mask ^= 1u << u; }
  __device__ __forceinline__ void release(int u, int n) {
    TR(*this, wg, 5);
    asm volatile("{\n.reg .pred p;\nsetp.lt.s32 p, %1, %2;\n@p mbarrier.arrive.shared::cluster.b64 _, [%0];\n}\n" :: "r"(rel + 8 * u), "r"(lane & 15), "r"(n) : "memory");
  }
  __device__ __forceinline__ void release2(int u) {
    asm volatile("{\n.reg .pred p;\nsetp.eq.s32 p, %1, 0;\n@p mbarrier.arrive.shared::cluster.b64 _, [%0], 2;\n}\n" :: "r"(rel + 8 * u), "r"(lane & 15) : "memory");
  }
  __device__ __forceinline__ void signal(int i) {
    __syncwarp();
    asm volatile("{\n.reg .pred p;\nsetp.eq.s32 p, %1, 0;\n@p mbarrier.arrive.shared::cta.b64 _, [%0];\n}\n" :: "r"(base + SM_SIG + 8 * i), "r"(lane) : "memory");
  }
  __device__ __forceinline__ void turn() { asm volatile("{\n.reg .pred p;\nsetp.eq.s32 p, %0, 0;\n@p bar.sync 1, 256;\n@!p bar.sync 2, 256;\n}\n" :: "r"(wg) : "memory"); TR(*this, wg, 3); }
  __device__ __forceinline__ void pass() { asm volatile("{\n.reg .pred p;\nsetp.eq.s32 p, %0, 0;\n@p bar.arrive 2, 256;\n@!p bar.arrive 1, 256;\n}\n" :: "r"(wg) : "memory"); TR(*this, wg, 4); }
  __device__ __forceinline__ void sync() { asm volatile("{\n.reg .pred p;\nsetp.eq.s32 p, %0, 0;\n@p bar.sync 3, 128;\n@!p bar.sync 4, 128;\n}\n" :: "r"(wg) : "memory"); }
};
__device__ __forceinline__ int gemm_unit(int ks) { return 3 * (ks & 3); }
template<int MASK> __device__ __forceinline__ int kv_slot(int h) { return MASK == PH_ALL ? h & 15 : h; }
__device__ __forceinline__ int out_mb(int cta) { return cta >> 3; }
__device__ __forceinline__ int out_nb(int cta) { return cta & 7; }
template<int MASK> constexpr int CV_REG = MASK == PH_ALL ? CONV_REG : 6;
template<int MASK> constexpr int CV_EXTRA = (1024 - NREG * CV_REG<MASK>) / (NCTA - NREG);
template<int MASK> __device__ __forceinline__ int conv_channel(int cta, int i) {
  return cta < NREG ? CV_EXTRA<MASK> * (NCTA - NREG) + cta * CV_REG<MASK> + i : (i >> 1) * 8 + (cta - NREG) * 2 + (i & 1);
}

template<int OFF, int N> __device__ __forceinline__ void pack_chunk(const float (&a)[N], float sc0, float sc1, uint4& v0, uint4& v1) {
  v0.x = pack_bf16(a[OFF + 0] * sc0, a[OFF + 1] * sc0); v0.y = pack_bf16(a[OFF + 4] * sc0, a[OFF + 5] * sc0);
  v0.z = pack_bf16(a[OFF + 8] * sc0, a[OFF + 9] * sc0); v0.w = pack_bf16(a[OFF + 12] * sc0, a[OFF + 13] * sc0);
  v1.x = pack_bf16(a[OFF + 2] * sc1, a[OFF + 3] * sc1); v1.y = pack_bf16(a[OFF + 6] * sc1, a[OFF + 7] * sc1);
  v1.z = pack_bf16(a[OFF + 10] * sc1, a[OFF + 11] * sc1); v1.w = pack_bf16(a[OFF + 14] * sc1, a[OFF + 15] * sc1);
}
template<int OFF, int N> __device__ __forceinline__ void pack_chunk(const float (&a)[N], uint4& v0, uint4& v1) {
  v0.x = pack_bf16(a[OFF + 0], a[OFF + 1]); v0.y = pack_bf16(a[OFF + 4], a[OFF + 5]);
  v0.z = pack_bf16(a[OFF + 8], a[OFF + 9]); v0.w = pack_bf16(a[OFF + 12], a[OFF + 13]);
  v1.x = pack_bf16(a[OFF + 2], a[OFF + 3]); v1.y = pack_bf16(a[OFF + 6], a[OFF + 7]);
  v1.z = pack_bf16(a[OFF + 10], a[OFF + 11]); v1.w = pack_bf16(a[OFF + 14], a[OFF + 15]);
}
__device__ __forceinline__ void sq_acc(const uint4& v, uint32_t& a) { a = hfma2(v.x, v.x, a); a = hfma2(v.y, v.y, a); a = hfma2(v.z, v.z, a); a = hfma2(v.w, v.w, a); }
__device__ __forceinline__ float norm2_max(uint32_t a0, uint32_t a1) {
  float n0 = bf_lo(a0) + bf_hi(a0), n1 = bf_lo(a1) + bf_hi(a1);
  n0 += __shfl_xor_sync(~0u, n0, 1); n1 += __shfl_xor_sync(~0u, n1, 1);
  n0 += __shfl_xor_sync(~0u, n0, 2); n1 += __shfl_xor_sync(~0u, n1, 2);
  return __uint_as_float(__reduce_max_sync(~0u, max(__float_as_uint(n0) & 0x7fffffffu, __float_as_uint(n1) & 0x7fffffffu)));
}

struct Pend { uint4 lo[8], hi[8]; uint32_t dst; float kn; };
__device__ __forceinline__ void pin(uint4 (&v)[8]) {
#pragma unroll
  for (int i = 0; i < 8; i++) asm volatile("" : "+r"(v[i].x), "+r"(v[i].y), "+r"(v[i].z), "+r"(v[i].w) :: "memory");
}
__device__ __forceinline__ void pack_o(const float (&o)[64], float i0, float i1, uint4 (&v)[8]) {
  pack_chunk<0>(o, i0, i1, v[0], v[1]); pack_chunk<16>(o, i0, i1, v[2], v[3]);
  pack_chunk<32>(o, i0, i1, v[4], v[5]); pack_chunk<48>(o, i0, i1, v[6], v[7]);
  pin(v);
}
__device__ __forceinline__ uint32_t atom_off(int lane) { return (lane >> 2) * 64 + (((lane ^ (lane >> 3)) & 3) << 4); }
__device__ __forceinline__ void stg128(void* p, const uint4& v, bool stream) {
  if (stream) asm volatile("st.global.L2::cache_hint.v4.u32 [%0], {%1,%2,%3,%4}, %5;" :: "l"(p), "r"(v.x), "r"(v.y), "r"(v.z), "r"(v.w), "l"(pol_first()) : "memory");
  else *(uint4*)p = v;
}
template<int J0, int J1, bool STREAM = false> __device__ __forceinline__ void tile_store(const uint4 (&v)[8], uint32_t dst, int lane) {
  uint8_t* d = g_T + (dst + atom_off(lane));
#pragma unroll
  for (int j = J0; j < J1; j++) { stg128(d + j * 512, v[2 * j], STREAM); stg128(d + j * 512 + 2048, v[2 * j + 1], STREAM); }
}
template<int I0, int I1> __device__ __forceinline__ void tile_store_if(bool on, const uint4 (&v)[8], const uint8_t* dst) {
  if constexpr (I0 < I1) {
    asm volatile("{\n.reg .pred p;\nsetp.ne.b32 p, %5, 0;\n@p st.v4.u32 [%0+%6], {%1,%2,%3,%4};\n}\n"
      :: "l"(dst), "r"(v[I0].x), "r"(v[I0].y), "r"(v[I0].z), "r"(v[I0].w), "r"((int)on), "n"((I0 >> 1) * 512 + (I0 & 1) * 2048) : "memory");
    tile_store_if<I0 + 1, I1>(on, v, dst);
  }
}
__device__ __forceinline__ float tile_norm2(const uint4 (&v)[8]) {
  uint32_t n0 = 0, n1 = 0, n2 = 0, n3 = 0;
#pragma unroll
  for (int j = 0; j < 2; j++) { sq_acc(v[2 * j], n0); sq_acc(v[2 * j + 1], n1); sq_acc(v[2 * j + 4], n2); sq_acc(v[2 * j + 5], n3); }
  return norm2_max(hadd2(n0, n2), hadd2(n1, n3));
}
template<uint64_t SCHED, bool FIRST> __device__ __forceinline__ void out_piece(Cons& c, Pend& w, int ks, bool both) {
  uint8_t* d = g_T + (w.dst + atom_off(c.lane));
#pragma unroll
  for (int i = 0; i < 16; i++) {
    const int at = (SCHED >> (4 * i)) & 15;
    if (FIRST ? at == 0 : (at > 0 && ks == at && (i < 8 || both))) *(uint4*)(d + (i >> 3) * 32768 + ((i >> 1) & 3) * 512 + (i & 1) * 2048) = i < 8 ? w.lo[i & 7] : w.hi[i & 7];
  }
  if (FIRST || !both) return;
  if (ks == NK_AT) w.kn = tile_norm2(w.lo);
  if (ks == NV_AT) {
    const float vn = tile_norm2(w.hi);
    if (c.lane == 0) g_kn2[((w.dst - T_KV) >> 16) * 8 + c.wg * 4 + c.warp] = (vn <= 1.0e20f && vn >= 1.0e-20f) ? w.kn : __uint_as_float(0x7f800000u);
  }
}
template<bool FIRST> __device__ __forceinline__ void kv_issue(Cons& c, float (&acc)[128], int u) {
  const uint64_t da = odesc(c.daddr(u) + c.wg * 8192, 16, 1024, 1), db = odesc(c.daddr(u + 1), 8192, 1024, 1);
  TSK(c.nt + 1);
  c.turn();
  TSK(c.nt + 2);
  wg_fence();
#pragma unroll
  for (int kk = 0; kk < 4; kk++) wgmma_ss_n256<1>(acc, da + kk * 2, db + kk * 128, !(FIRST && kk == 0));
  wg_commit();
  c.pass();
  TSK(c.nt + 3); c.nt += 4;
}
template<bool NEXT> __device__ __forceinline__ void cons_kv(Cons& c, int h, int hs, int g, Pend& w, bool pend_o) {
#pragma unroll 1
  for (int tile = 0; tile < 2; tile++) {
    float acc[128];
    if (!(NEXT && HOISTW) && tile == 0) c.wait(0);
    if (tile == 0 && h < 16) TS(c.wg, 16);
    kv_issue<true>(c, acc, 0);
    c.release(9, tile == 1 ? 3 : 0);
    if (tile == 1 && pend_o) mbar_wait(c.base + SM_RDY + 8 * RDY_WAR, 0);
    if (tile == 1 || pend_o) out_piece<SCH_KV, true>(c, w, 0, false);
#pragma unroll 1
    for (int ks = 1; ks < 8; ks++) {
      const int u = gemm_unit(ks);
      c.wait(u);
      TSK(c.nt);
      wg_wait<0>();
      c.release(gemm_unit(ks - 1), 3);
      kv_issue<false>(c, acc, u);
      if (tile == 1 || pend_o) { out_piece<SCH_KV, false>(c, w, ks, tile); if (ks == ((SCH_KV >> 28) & 15) && tile == 0) c.signal(SIG_CTX); }
    }
    if (NEXT || tile == 0) c.wait(0);
    wg_wait<0>(); fence_regs(acc);
    TSK(c.nt);
    if (!NEXT) c.release(9, tile == 1 ? 3 : 0);
    pack_chunk<0>(acc, w.lo[0], w.lo[1]);  pack_chunk<16>(acc, w.lo[2], w.lo[3]); pack_chunk<32>(acc, w.lo[4], w.lo[5]); pack_chunk<48>(acc, w.lo[6], w.lo[7]);
    pack_chunk<64>(acc, w.hi[0], w.hi[1]); pack_chunk<80>(acc, w.hi[2], w.hi[3]); pack_chunk<96>(acc, w.hi[4], w.hi[5]); pack_chunk<112>(acc, w.hi[6], w.hi[7]);
    pin(w.lo); pin(w.hi);
    w.dst = T_KV + (hs * 16 + 2 * g + tile) * 65536 + (c.wg * 4 + c.warp) * 4096;
  }
}
template<bool FIRST> __device__ __forceinline__ void q_issue(Cons& c, float (&a)[64], float (&b)[64], int u) {
  const uint64_t da = odesc(c.daddr(u) + c.wg * 8192, 16, 1024, 1), db = odesc(c.daddr(u + 2), 8192, 1024, 1);
  const uint64_t da2 = odesc(c.daddr(u + 1) + (1 - c.wg) * 8192, 16, 1024, 1);
  TSK(c.nt + 1);
  c.turn();
  TSK(c.nt + 2);
  wg_fence();
#pragma unroll
  for (int kk = 0; kk < 4; kk++) wgmma_ss_n128<1>(a, da + kk * 2, db + kk * 128, !(FIRST && kk == 0));
#pragma unroll
  for (int kk = 0; kk < 4; kk++) wgmma_ss_n128<1>(b, da2 + kk * 2, db + kk * 128, !(FIRST && kk == 0));
  wg_commit();
  c.pass();
  TSK(c.nt + 3); c.nt += 4;
}
__device__ __forceinline__ void q_step(Cons& c, float (&d)[64], int ua, int ub, int rowhalf) {
  const uint64_t da = odesc(c.daddr(ua) + rowhalf * 8192, 16, 1024, 1), db = odesc(c.daddr(ub), 8192, 1024, 1);
#pragma unroll
  for (int kk = 0; kk < 4; kk++) wgmma_ss_n128<1>(d, da + kk * 2, db + kk * 128, 1);
}
template<bool PEND_KV> __device__ __forceinline__ void cons_q(Cons& c, int h, Pend& w, float (&b)[64]) {
  float a[64];
  if (!PEND_KV) c.wait(0);
  q_issue<true>(c, a, b, 0);
  if (PEND_KV) { c.release(9, 3); out_piece<SCH_Q, true>(c, w, 0, true); }
#pragma unroll 1
  for (int ks = 1; ks < 14; ks++) {
    const int u = gemm_unit(ks);
    c.wait(u);
    TSK(c.nt);
    wg_wait<0>();
    c.release(gemm_unit(ks - 1), 3);
    q_issue<false>(c, a, b, u);
    if (PEND_KV && ks <= (int)(SCH_Q >> 60)) { out_piece<SCH_Q, false>(c, w, ks, true); if (ks == (int)(SCH_Q >> 60)) c.signal(SIG_KV + (h >> 4)); }
  }
  c.wait(6); c.wait(9);
  wg_wait<0>();
  c.release(3, 3);
  c.turn();
  TSS(0);
  wg_fence();
  q_step(c, a, 6, 8, c.wg); q_step(c, a, 9, 11, c.wg); wg_commit();
  q_step(c, b, 7, 8, 1 - c.wg); wg_commit();
  c.pass();
  TSS(1);
  c.wait(0);
  const uint32_t q0 = c.addr(0) + (c.wg * 4 + c.warp) * 4096 + atom_off(c.lane);
  wg_wait<1>(); fence_regs(a);
  TSS(2);
  pack_o(a, QSCALE, QSCALE, w.lo);
  sts128o<0>(q0, w.lo[0]);    sts128o<2048>(q0, w.lo[1]); sts128o<512>(q0, w.lo[2]);  sts128o<2560>(q0, w.lo[3]);
  wg_wait<0>();
  c.release(6, 4);
  sts128o<1024>(q0, w.lo[4]); sts128o<3072>(q0, w.lo[5]); sts128o<1536>(q0, w.lo[6]); sts128o<3584>(q0, w.lo[7]);
  TSS(3);
  c.wait(12);
  fence_async_smem();
  TSS(4);
}

__device__ __forceinline__ void issue_qk(float (&s)[64], uint64_t da, uint64_t db) {
#pragma unroll
  for (int kk = 0; kk < 8; kk++) wgmma_ss_n128<0>(s, da + (kk >> 1) * 32 + (kk & 1) * 2, db + (kk >> 1) * 32 + (kk & 1) * 2, kk > 0);
  wg_commit();
}
template<int A, int B> __device__ __forceinline__ void exp_rng(float (&s)[64]) {
#pragma unroll
  for (int i = 4 * A; i < 4 * B; i++) s[i] = ex2(s[i]);
}
template<int A, int B> __device__ __forceinline__ void sum_rng(const float (&s)[64], float (&l)[4]) {
#pragma unroll
  for (int i = A; i < B; i++) { l[0] += s[4 * i]; l[1] += s[4 * i + 1]; l[2] += s[4 * i + 2]; l[3] += s[4 * i + 3]; }
}
template<int A, int B> __device__ __forceinline__ void cvt_p(const float (&s)[64], uint32_t (&p)[32]) {
#pragma unroll
  for (int i = 2 * A; i < 2 * B; i++) p[i] = pack_bf16(s[2 * i], s[2 * i + 1]);
}
__device__ __forceinline__ void mask2(float& x, float& y, int k, int l, float ninf) {
  asm("{\n.reg .pred p;\nsetp.ge.s32 p, %2, %3;\n@p add.f32 %0, %4, 0f00000000;\n@p add.f32 %1, %4, 0f00000000;\n}\n" : "+f"(x), "+f"(y) : "r"(k), "r"(l), "f"(ninf));
}
template<int K0> __device__ __forceinline__ void mask_half(float (&s)[64], int warp, int lane) {
  const int l0 = warp + (2 * (lane & 3) <= (lane >> 2)), l1 = warp + (2 * (lane & 3) < (lane >> 2));
  const float ninf = __int_as_float(0xff7fffff + gridDim.y);
#pragma unroll
  for (int k = 0; k < 4; k++) {
    float* t = s + 8 * (K0 + k);
    if (MFP) { mask2(t[0], t[6], k, l0, ninf); mask2(t[1], t[7], k, l1, ninf); if (k) mask2(t[2], t[3], k - 1, warp, ninf); mask2(t[4], t[5], k, warp, ninf); continue; }
    if (k >= l0) { t[0] = -INFINITY; t[6] = -INFINITY; }
    if (k >= l1) { t[1] = -INFINITY; t[7] = -INFINITY; }
    if (k > warp) { t[2] = -INFINITY; t[3] = -INFINITY; }
    if (k >= warp) { t[4] = -INFINITY; t[5] = -INFINITY; }
  }
}
__device__ __forceinline__ void row_inv(float& l0, float& l1) {
  l0 += __shfl_xor_sync(~0u, l0, 1); l1 += __shfl_xor_sync(~0u, l1, 1);
  l0 += __shfl_xor_sync(~0u, l0, 2); l1 += __shfl_xor_sync(~0u, l1, 2);
  l0 = rcp(l0); l1 = rcp(l1);
}
__device__ __forceinline__ void softmax_safe(float (&s)[64], bool upper_only, float& m0, float& m1, float& sc0, float& sc1) {
  float a0 = m0, a1 = m1;
#pragma unroll
  for (int i = 0; i < 8; i++) { a0 = fmaxf(a0, fmaxf(s[4 * i], s[4 * i + 1])); a1 = fmaxf(a1, fmaxf(s[4 * i + 2], s[4 * i + 3])); }
  if (upper_only) { a0 = m0; a1 = m1; }
#pragma unroll
  for (int i = 8; i < 16; i++) { a0 = fmaxf(a0, fmaxf(s[4 * i], s[4 * i + 1])); a1 = fmaxf(a1, fmaxf(s[4 * i + 2], s[4 * i + 3])); }
  a0 = fmaxf(a0, __shfl_xor_sync(~0u, a0, 1)); a1 = fmaxf(a1, __shfl_xor_sync(~0u, a1, 1));
  a0 = fmaxf(a0, __shfl_xor_sync(~0u, a0, 2)); a1 = fmaxf(a1, __shfl_xor_sync(~0u, a1, 2));
  sc0 = ex2(m0 - a0); sc1 = ex2(m1 - a1);
  m0 = a0; m1 = a1;
#pragma unroll
  for (int i = 0; i < 16; i++) { s[4 * i] -= a0; s[4 * i + 1] -= a0; s[4 * i + 2] -= a1; s[4 * i + 3] -= a1; }
}
struct Att {
  float s[64], o[64], l[4], i0, i1, t0, t1; uint32_t p[32];
  float kn; uint32_t qaddr; const uint8_t* dst;
};
__device__ __forceinline__ uint32_t ctx_off(const Cons& c, int h, int qb, int rowhalf) { return T_CTX + (qb * 32 + h) * 32768 + (rowhalf * 4 + c.warp) * 4096; }
template<int E> __device__ __forceinline__ bool row_ok(uint4 (&q)[8], float kn) {
#pragma unroll
  for (int i = E; i < 8; i += 2) q[i].x = hfma2(q[i].w, q[i].w, hfma2(q[i].z, q[i].z, hfma2(q[i].y, q[i].y, hmul2(q[i].x, q[i].x))));
  const uint32_t n = hadd2(hadd2(q[E].x, q[E + 2].x), hadd2(q[E + 4].x, q[E + 6].x));
  return (bf_lo(n) + bf_hi(n)) * kn <= 0.25f * BOUND2;
}
__device__ __forceinline__ int all_ok(bool ok) { return __shfl_sync(~0u, __all_sync(~0u, ok), 0); }
__device__ __forceinline__ int att_fast(uint4 (&q)[8], float kn) { return all_ok(row_ok<0>(q, kn) & row_ok<1>(q, kn)); }
__device__ __forceinline__ int att_first(Cons& c, Att& a, int h, Pend& w) {
  a.kn = __uint_as_float(lds32(c.base + SM_KMAX + 4 * (h >> 4)));
  a.qaddr = c.daddr(0) + c.wg * 16384;
  c.turn();
  TSS(5);
  wg_fence();
  issue_qk(a.s, odesc(a.qaddr, 16, 2048, 2), odesc(c.daddr(12), 16, 2048, 2));
  int fast = 0;
  SHADOW fast = att_fast(w.lo, a.kn);
  wg_fence();
  TSS(6);
  q_step(c, a.o, 10, 11, 1 - c.wg); wg_commit();
  if (SHW) { if (c.wg) c.wait(6); else c.skip(6); }
  c.pass();
  TSS(7);
#pragma unroll
  for (int i = 0; i < 8; i++) { a.p[4 * i] = w.lo[i].x; a.p[4 * i + 1] = w.lo[i].y; a.p[4 * i + 2] = w.lo[i].z; a.p[4 * i + 3] = w.lo[i].w; }
  a.l[0] = a.l[1] = a.l[2] = a.l[3] = 0.f; a.i0 = a.i1 = a.t0 = a.t1 = 0.25f / QSCALE;
  a.dst = (const uint8_t*)__cvta_shared_to_generic(c.addr(2) + (c.wg * 4 + c.warp) * 4096 + atom_off(c.lane));
  wg_wait<1>(); fence_regs(a.s);
  c.signal(SIG_ATT + (h >> 4));
  if (ER1 && c.wg) { wg_wait<0>(); c.release(10, 2); }
  return fast;
}
template<bool NEXT> __device__ __forceinline__ void att_last(Cons& c, Att& a, Pend& w, int h, int g, bool drain) {
  const int uv = 6;
  if (!PK1 && drain) pack_o(a.o, rcp(a.i0), rcp(a.i1), w.hi);
  TSS(8);
  if (!SHW) c.wait(uv);
  c.turn();
  TSS(9);
  fence_regs(a.o); fence_regs(a.p);
  wgmma_pv_sel(a.o, a.p, odesc(c.daddr(uv), 512, 2048, 2), !(drain && c.wg == 1), !drain, c.wg);
  a.i0 = a.l[0] + a.l[1]; a.i1 = a.l[2] + a.l[3];
  SHADOW row_inv(a.i0, a.i1);
  sched_fence(a.i0 + a.i1, c.base + SM_DUMMY);
  tile_store_if<0, 4>(drain, w.hi, a.dst);
  if (NEXT && HOISTW) c.wait(h < 16 ? 0 : 12);
  wg_wait<0>(); fence_regs(a.o); fence_regs(a.p);
  c.release(uv, 2);
  TSS(10); if (h < 16) TSK(0);
  tile_store_if<4, 8>(drain, w.hi, a.dst);
  pack_o(a.o, a.i0, a.i1, w.lo);
  w.dst = ctx_off(c, h, g, 1 - c.wg); w.kn = 0.f;
  TSS(11);
}
template<bool NEXT> __device__ __forceinline__ void cons_att(Cons& c, Att& a, int h, int g, Pend& w) {
  int fast = att_first(c, a, h, w), fast2 = 0;
  float m0 = -INFINITY, m1 = -INFINITY, sc0 = 0.f, sc1 = 0.f;
  int uk = 10, ur = 10;
  bool fresh = false;
#pragma unroll 1
  for (int d = g - 15;;) {
    const bool lo = d == c.wg;
    TSS(16 + 6 * (d - g + 15));
    if ((unsigned)d < 2 || !fast) {
      if ((unsigned)d < 2) {
        mask_half<4>(a.s, c.warp, c.lane);
        if (!SHR && lo) fast2 = att_fast(w.hi, a.kn);
        if (!SHR && d == 1) fast = fast2;
      }
      if (!fast) {
        if (d == 1) m0 = m1 = -INFINITY;
        softmax_safe(a.s, lo, m0, m1, sc0, sc1);
        a.l[0] *= sc0; a.l[1] *= sc0; a.l[2] *= sc1; a.l[3] *= sc1;
      }
    }
    exp_rng<8, 16>(a.s); sum_rng<8, 16>(a.s, a.l);
    if (PEXP) {
#pragma unroll
      for (int i = 4 * ATT_SPLIT; i < 32; i++) asm("{\n.reg .pred p;\nsetp.ne.s32 p, %1, %2;\n@p ex2.approx.ftz.f32 %0, %0;\n}\n" : "+f"(a.s[i]) : "r"(d), "r"(c.wg));
    } else exp_rng<ATT_SPLIT, 8>(a.s);
    sched_fence(((a.l[0] + a.l[1]) + (a.l[2] + a.l[3])) + (ATT_SPLIT < 8 ? a.s[4 * ATT_SPLIT + 3] : 0.f), c.base + SM_DUMMY);
    wg_wait<0>(); fence_regs(a.o); fence_regs(a.p);
    c.release(ur, ER1 && c.wg && d == g - 15 ? 0 : 2);
    TSS(17 + 6 * (d - g + 15));
    a.i0 += a.t0; a.i1 += a.t1;
    a.t0 = __shfl_xor_sync(~0u, a.i0, 2); a.t1 = __shfl_xor_sync(~0u, a.i1, 2);
    tile_store_if<DS_A, DS_B>(fresh, w.hi, a.dst);
    uk ^= 12; ur = 14 - uk;
    if (d == 0) a.qaddr += 32768;
    const uint64_t dq = odesc(a.qaddr, 16, 2048, 2), dk = odesc(c.daddr(uk) - (d + 1 == c.wg ? 16384 : 0), 16, 2048, 2), dv = odesc(c.daddr(ur), 512, 2048, 2);
    if (!lo) { exp_rng<0, ATT_SPLIT>(a.s); sum_rng<0, 8>(a.s, a.l); cvt_p<0, 16>(a.s, a.p); }
    else if (gridDim.y == 1) cvt_p<8, 16>(a.s, a.p);
    tile_store_if<DS_B, 8>(fresh, w.hi, a.dst);
    a.i0 += a.t0; a.i1 += a.t1;
    const bool early = PK1 && (d == 1 || d == g - 15) && (c.wg || d == g + 1);
    if (!fast || d == g + 1 || early || (!SHR && (unsigned)(d + 1) < 2)) {
      if (early) pack_o(a.o, rcp(a.i0), rcp(a.i1), w.hi);
      if (!SHR && d == -1) fence_async_smem();
      if (!fast && d != 1 && d != g - 15) {
#pragma unroll
        for (int i = 0; i < 16; i++) { a.o[4 * i] *= sc0; a.o[4 * i + 1] *= sc0; a.o[4 * i + 2] *= sc1; a.o[4 * i + 3] *= sc1; }
      }
      if (!SHR && d == 0) {
        a.i0 = a.l[0] + a.l[1]; a.i1 = a.l[2] + a.l[3];
        a.l[0] = a.l[1] = a.l[2] = a.l[3] = 0.f;
        uint32_t off = ctx_off(c, h, 15 - g, c.wg);
        asm volatile("" : "+r"(off));
        a.dst = g_T + (off + ((uint32_t)(uint64_t)a.dst & 511));
      }
      if (d == g + 1) break;
    }
    d++;
    fresh = d == 2 || d == g - 14;
    TSS(12 + 6 * (d - g + 15));
    if (!SHW) { if (c.wg == 0) c.wait(uk); else c.skip(uk); }
    c.turn();
    TSS(13 + 6 * (d - g + 15));
    fence_regs(a.o); fence_regs(a.p);
    wg_fence();
    issue_qk(a.s, dq, dk);
    TSS(14 + 6 * (d - g + 15));
    if (SHW) { c.wait(c.wg ? uk ^ 12 : ur); c.skip(c.wg ? ur : uk ^ 12); }
    if (!SHR) { a.t0 = __shfl_xor_sync(~0u, a.i0, 1); a.t1 = __shfl_xor_sync(~0u, a.i1, 1); }
    if (fresh || (SHR && (d == 1 || (unsigned)(d - g + CHK_D) < 2 + CH2))) {
      if (fresh) { if (!(PK1 && c.wg)) pack_o(a.o, rcp(a.i0), rcp(a.i1), w.hi); }
      else if (d == 1) {
        a.i0 = a.l[0] + a.l[1]; a.i1 = a.l[2] + a.l[3];
        a.t0 = __shfl_xor_sync(~0u, a.i0, 1); a.t1 = __shfl_xor_sync(~0u, a.i1, 1);
        a.l[0] = a.l[1] = a.l[2] = a.l[3] = 0.f;
        uint32_t off = ctx_off(c, h, 15 - g, c.wg);
        asm volatile("" : "+r"(off));
        a.dst = g_T + (off + ((uint32_t)(uint64_t)a.dst & 511));
        fast = fast2;
      } else if (d == g - CHK_D) fence_async_smem();
      else if (!CH2) fast2 = att_fast(w.hi, a.kn);
      else if (d == g - CHK_D + 1) fast2 = all_ok(row_ok<0>(w.hi, a.kn));
      else fast2 = all_ok(row_ok<1>(w.hi, a.kn) & (fast2 != 0));
    }
    TSS(15 + 6 * (d - g + 15));
    wgmma_pv_sel(a.o, a.p, dv, !lo, !fresh, c.wg);
    tile_store_if<0, DS_A>(fresh, w.hi, a.dst);
    wg_wait<1>(); fence_regs(a.s);
    c.release(uk, 2);
    c.release(d == 0 ? 0 : 2, (d == 0 || d == g + 1) ? 2 : 0);
  }
  att_last<NEXT>(c, a, w, h, g, g == 0);
}

constexpr int CV_H = 1024, CV_U = 5120, CV_D = CV_U + 4128, CV_ROW = 1056;
template<int OFF> __device__ __forceinline__ uint32_t lds32o(uint32_t a) { uint32_t v; asm volatile("ld.shared.u32 %0, [%1+%2];" : "=r"(v) : "r"(a), "n"(OFF) : "memory"); return v; }
template<int G, int G1 = 16> __device__ __forceinline__ void conv_lda(uint32_t (&a)[64], uint32_t p) {
  a[4 * G + 0] = lds32o<-256 * G>(p);
  a[4 * G + 1] = lds32o<-256 * G - 128>(p);
  a[4 * G + 2] = lds32o<-256 * G + 16>(p);
  a[4 * G + 3] = lds32o<-256 * G - 112>(p);
  if constexpr (G + 1 < G1) conv_lda<G + 1, G1>(a, p);
}
struct CvAcc { float lo[16], hi[16]; };
__device__ __forceinline__ void fence_regs(CvAcc& d) { fence_regs(d.lo); fence_regs(d.hi); }
template<int R, int H> __device__ __forceinline__ void conv_mma_h(float (&d)[16], const uint32_t (&a)[64], uint64_t db) {
#pragma unroll
  for (int G = 0; G < 4 * R + 2 * H + 2; G++) wgmma_rs_n32<0>(d, a[4 * G], a[4 * G + 1], a[4 * G + 2], a[4 * G + 3], db + 64 * R + 32 * H - 16 * G, G > 0);
}
template<int T, int G0, int G1> __device__ __forceinline__ void conv_part(float (&d)[16], const uint32_t (&a)[64], uint64_t db) {
#pragma unroll
  for (int G = G0; G < G1; G++) wgmma_rs_n32<0>(d, a[4 * G], a[4 * G + 1], a[4 * G + 2], a[4 * G + 3], db + 32 * T - 16 * G, G > 0);
}
template<int R> __device__ __forceinline__ void conv_mma(CvAcc& d, const uint32_t (&a)[64], uint64_t db) { conv_mma_h<R, 0>(d.lo, a, db); conv_mma_h<R, 1>(d.hi, a, db); }
template<int C0> __device__ __forceinline__ void conv_st_h(const float (&d)[16], uint32_t wq, float& c0, float& c1) {
#pragma unroll
  for (int n = 0; n < 4; n++) { sts64f(wq + (C0 + n * 8) * 4, d[4 * n] + c0, d[4 * n + 1] + c1); c0 = d[4 * n + 2]; c1 = d[4 * n + 3]; }
}
template<int R> __device__ __forceinline__ void conv_st(const CvAcc& d, uint32_t wq, float& c0, float& c1) { conv_st_h<64 * R>(d.lo, wq, c0, c1); conv_st_h<64 * R + 32>(d.hi, wq, c0, c1); }
struct ConvTail { float t[64]; uint4 ua, uc; uint32_t D2; };
__device__ __forceinline__ void conv_emit(ConvTail& e, int ch, int tid) {
  fence_regs(e.t);
  float y[16];
#pragma unroll
  for (int i = 0; i < 16; i++) y[i] = (e.t[i] + e.t[16 + i]) + (e.t[32 + i] + e.t[48 + i]);
  uint4 z0, z1;
  z0.x = hadd2(pack_bf16(y[0], y[2]), hmul2(__byte_perm(e.ua.w, 0, 0x1032), e.D2));
  z0.y = hadd2(pack_bf16(y[4], y[6]), hmul2(__byte_perm(e.ua.z, 0, 0x1032), e.D2));
  z0.z = hadd2(pack_bf16(y[8], y[10]), hmul2(__byte_perm(e.ua.y, 0, 0x1032), e.D2));
  z0.w = hadd2(pack_bf16(y[12], y[14]), hmul2(__byte_perm(e.ua.x, 0, 0x1032), e.D2));
  z1.x = hadd2(pack_bf16(y[1], y[3]), hmul2(__byte_perm(e.uc.w, 0, 0x1032), e.D2));
  z1.y = hadd2(pack_bf16(y[5], y[7]), hmul2(__byte_perm(e.uc.z, 0, 0x1032), e.D2));
  z1.z = hadd2(pack_bf16(y[9], y[11]), hmul2(__byte_perm(e.uc.y, 0, 0x1032), e.D2));
  z1.w = hadd2(pack_bf16(y[13], y[15]), hmul2(__byte_perm(e.uc.x, 0, 0x1032), e.D2));
  uint4* zp = (uint4*)(g_z + (uint32_t)(ch * 2048 + tid * 16));
  zp[0] = z0; zp[1] = z1;
}
template<int MASK> __device__ __forceinline__ void cons_conv(Cons& c, int cta, int nch) {
  const int r = c.lane >> 2, q = c.lane & 3, tid = c.warp * 32 + c.lane;
  const uint32_t part = c.addr(4) - 2048 + (1 - c.wg) * (32 * CV_ROW) + 32;
  const uint32_t aoff = CV_U + ((r & 1) ? 0 : UPITCH) + 4 * (((2039 - r) >> 1) + q - 8 * c.warp);
  const uint32_t wq = part + (c.warp * 8 + r) * CV_ROW + q * 8, rq = part + tid * 8;
  uint32_t a[64];
  ConvTail e = {};
  c.wait(c.wg); c.skip(c.wg ^ 1);
  conv_lda<0>(a, c.addr(c.wg) + aoff);
  c.wait(4);
  sts64f(part + (tid >> 2) * CV_ROW - 32 + q * 8, 0.f, 0.f);
#pragma unroll 1
  for (int i = 0; i < nch / 2; i++) {
    const int u = 2 * (i & 1) + c.wg;
    CvAcc d0, d1, d2, d3;
    float c0 = 0.f, c1 = 0.f;
    const uint64_t db = odesc(c.daddr(u) + CV_H - 16, 16, 128, 0);
    c.turn();
    fence_regs(a);
    wg_fence();
    conv_mma<0>(d0, a, db); conv_mma<1>(d1, a, db); wg_commit();
    if (i > 0) {
      conv_emit(e, conv_channel<MASK>(cta, 2 * i - 2 + c.wg), tid);
      if ((i & 15) == 0) c.signal(SIG_Z + (i >> 4) - 1);
    }
    wg_fence();
    conv_mma_h<2, 0>(d2.lo, a, db); wg_commit();
    wg_wait<1>(); fence_regs(d0); fence_regs(d1);
    conv_st_h<0>(d0.lo, wq, c0, c1);
    wg_fence();
    conv_mma_h<2, 1>(d2.hi, a, db); wg_commit();
    conv_st_h<32>(d0.hi, wq, c0, c1);
    conv_mma_h<3, 0>(d3.lo, a, db);
    conv_st_h<64>(d1.lo, wq, c0, c1);
    conv_mma_h<3, 1>(d3.hi, a, db); wg_commit();
    c.pass();
    const int un = i + 1 < nch / 2 ? u ^ 2 : u;
    if (un != u) { c.wait(un); c.skip(un ^ 1); }
    wg_wait<1>(); fence_regs(d2);
    conv_st_h<96>(d1.hi, wq, c0, c1);
    conv_st<2>(d2, wq, c0, c1);
    {
      const int sw = (c.lane >> 2) & 1;
      const uint4 v0 = lds128(c.addr(u) + CV_U + 4064 - 32 * tid + 16 * sw), v1 = lds128(c.addr(u) + CV_U + 4080 - 32 * tid - 16 * sw);
      e.ua = sw ? v0 : v1; e.uc = sw ? v1 : v0;
    }
    e.D2 = lds32(c.addr(u) + CV_D);
    wg_wait<0>(); fence_regs(d3); fence_regs(a);
    conv_st<3>(d3, wq, c0, c1);
    conv_lda<0, 4>(a, c.addr(un) + aoff);
    c.sync();
    sched_fence(__uint_as_float(e.ua.x ^ e.uc.x ^ e.D2), c.base + SM_DUMMY);
    c.release2(u);
    conv_lda<4, 16>(a, c.addr(un) + aoff);
#pragma unroll
    for (int k = 0; k < 32; k++) { const float2 v = lds64f(rq + k * CV_ROW - (k >> 3) * 8); e.t[2 * k] = v.x; e.t[2 * k + 1] = v.y; }
  }
  conv_emit(e, conv_channel<MASK>(cta, nch - 2 + c.wg), tid);
  c.signal(SIG_Z + ((nch / 2 - 1) >> 4));
  c.release(4, 4);
}

constexpr int OC_PART = 13824, OC_ROW = 544;
__device__ __forceinline__ int out_next(int u) { return (0x84ac680u >> (2 * u)) & 15; }
struct Out { float acc[64]; int pu; uint64_t da, db; };
template<bool FIRST, bool REL, int W = 1, bool PRE = true, bool POST = false> __device__ __forceinline__ void out_step(Cons& c, Out& o, bool extra = false) {
  const int pu = o.pu, u = extra ? 2 : out_next(pu);
  o.pu = u;
  if (PRE) c.wait(u);
  const uint64_t da = o.da + (uint32_t)(u * 1024), db = o.db + (uint32_t)(u * 1024);
  wg_fence();
#pragma unroll
  for (int kk = 0; kk < 4; kk++) wgmma_ss_n128<1>(o.acc, da + (kk >> 1) * 32 + (kk & 1) * 2, db + kk * 128, !(FIRST && kk == 0));
  wg_commit();
  if (REL) { wg_wait<W>(); c.release(pu, 2); }
  if (POST) c.wait(out_next(u));
}
template<int I0, int I1> __device__ __forceinline__ void oc_red(float (&y)[8], uint32_t rq) {
#pragma unroll
  for (int i = I0; i < I1; i++) { const float v = __uint_as_float(lds32(rq + i * OC_ROW - (i >> 3) * 8)); y[i & 7] = i < 8 ? v : y[i & 7] + v; }
}
__device__ __forceinline__ void oc_emit(const float (&y)[8], const uint4& u, uint32_t D2, __nv_bfloat16* dst) {
  uint4 z;
  z.x = hadd2(pack_bf16(y[0], y[1]), hmul2(__byte_perm(u.w, 0, 0x1032), D2));
  z.y = hadd2(pack_bf16(y[2], y[3]), hmul2(__byte_perm(u.z, 0, 0x1032), D2));
  z.z = hadd2(pack_bf16(y[4], y[5]), hmul2(__byte_perm(u.y, 0, 0x1032), D2));
  z.w = hadd2(pack_bf16(y[6], y[7]), hmul2(__byte_perm(u.x, 0, 0x1032), D2));
  *(uint4*)dst = z;
}
__device__ __forceinline__ uint32_t mix(uint32_t og, uint32_t b, uint32_t ga) { return (TFMA & 1) ? hfma2(og, b, ga) : hadd2(ga, hmul2(og, b)); }
template<int MASK> __device__ __forceinline__ void cons_out(Cons& c, const Maps& M, const Params& P, int cta, Pend& w) {
  const int mb = out_mb(cta), nb = out_nb(cta);
  Out o;
  o.da = odesc(c.daddr(0) + c.wg * 8192, 16, 1024, 2); o.db = odesc(c.daddr(1), 8192, 1024, 1);
  o.pu = 5 + gridDim.y;
  out_step<true, false, 1, !(HOISTW && MASK == PH_ALL)>(c, o);
  int ks = 1;
#pragma unroll 1
  for (;; ks++) {
    if (MASK & PH_ATT) {
      if (ks == (c.wg ? ST_1 : ST_0)) tile_store<0, 1>(w.lo, w.dst, c.lane);
      if (ks == (c.wg ? ST_1 + ST_D : ST_0 + ST_0D / 2)) tile_store<1, 2>(w.lo, w.dst, c.lane);
      if (ks == (c.wg ? ST_1 + 2 * ST_D : ST_0 + ST_0D)) tile_store<2, 3>(w.lo, w.dst, c.lane);
      if (ks == (c.wg ? ST_1 + 3 * ST_D : ST_0 + 3 * ST_0D / 2)) { tile_store<3, 4>(w.lo, w.dst, c.lane); c.signal(SIG_CTX + 1); }
    }
    if (ks == (c.wg ? OC_S1 : OC_S0)) break;
    out_step<false, true>(c, o, ks == 1);
  }
  if (MASK & PH_CONV) {
    const int r = c.lane >> 2, q = c.lane & 3, tid = c.warp * 32 + c.lane, u = 2 * c.wg;
    const uint32_t ub = c.addr(u), part = ub + OC_PART + 32;
    const uint32_t ap = ub + CV_U + ((r & 1) ? 0 : UPITCH) + 4 * (((2039 - r) >> 1) + q - 8 * c.warp);
    const uint32_t wq = part + (c.warp * 8 + r) * OC_ROW + q * 8, rq = part + tid * 4;
    const int nr = (CV_REG<MASK> + 1 - c.wg) >> 1;
#define STEP(N) out_step<false, true, 1, !OC_POST, OC_POST>(c, o);
#pragma unroll 1
    for (int i = 0; i < nr; i++) {
      uint32_t a[64];
      CvAcc d0, d1;
      float y[8], c0 = 0.f, c1 = 0.f;
      const uint64_t db = odesc(c.daddr(u + (i >> 8)) + CV_H - 16, 16, 128, 0);
#define STEP2(N) out_step<false, true, 2, !OC_POST, OC_POST>(c, o);
#define PART(...) { const uint64_t db = db0 + (c.mask >> 16); wg_fence(); __VA_ARGS__; wg_commit(); }
      const uint64_t db0 = db;
#define KEEP() asm volatile("add.f32 %0, %0, 0f80000000;" : "+f"(c0)); asm volatile("add.f32 %0, %0, 0f80000000;" : "+f"(c1));
      c.wait(u);
      if (OC_POST) c.wait(out_next(o.pu));
      conv_lda<0, 4>(a, ap);
      STEP(0)
      conv_lda<4, 7>(a, ap);
      PART(conv_part<0, 0, 2>(d0.lo, a, db); conv_part<1, 0, 4>(d0.hi, a, db); conv_part<2, 0, 2>(d1.lo, a, db))
      STEP2(1)
      conv_lda<7, 10>(a, ap);
      PART(conv_part<2, 2, 6>(d1.lo, a, db); conv_part<3, 0, 4>(d1.hi, a, db))
      STEP2(2)
      fence_regs(d0);
      c.sync();
      sts64f(wq - 32, 0.f, 0.f);
      conv_st_h<0>(d0.lo, wq, c0, c1); KEEP()
      PART(conv_part<3, 4, 8>(d1.hi, a, db); conv_part<4, 0, 4>(d0.lo, a, db))
      STEP2(3)
      fence_regs(d1.lo);
      conv_st_h<32>(d0.hi, wq, c0, c1); conv_st_h<64>(d1.lo, wq, c0, c1); KEEP()
      PART(conv_part<4, 4, 10>(d0.lo, a, db); conv_part<5, 0, 2>(d0.hi, a, db))
      STEP2(4)
      fence_regs(d1.hi);
      float e0 = d1.hi[12] + d1.hi[10], e1 = d1.hi[13] + d1.hi[11];
      conv_st_h<96>(d1.hi, wq, c0, c1); KEEP()
      conv_lda<10, 12>(a, ap);
      PART(conv_part<5, 2, 10>(d0.hi, a, db))
      STEP2(5)
      conv_lda<12, 14>(a, ap);
      c.sync();
      oc_red<0, 6>(y, rq);
      PART(conv_part<5, 10, 12>(d0.hi, a, db); conv_part<6, 0, 6>(d1.lo, a, db))
      STEP2(6)
      oc_red<6, 20>(y, rq);
      PART(conv_part<6, 6, 14>(d1.lo, a, db))
      STEP2(7)
      oc_red<20, 26>(y, rq);
      conv_lda<14, 16>(a, ap);
      PART(conv_part<7, 0, 8>(d1.hi, a, db))
      STEP2(8)
      oc_red<26, 32>(y, rq);
      PART(conv_part<7, 8, 16>(d1.hi, a, db))
      STEP2(9)
      fence_regs(y); fence_regs(d0);
      c.sync();
      sts64f(wq - 32, e0, e1);
      conv_st<0>(d0, wq, c0, c1);
      STEP(10)
      fence_regs(d1); fence_regs(a);
      const uint4 u0 = lds128(ub + CV_U + 4080 - 16 * tid), u1 = lds128(ub + CV_U + 2032 - 16 * tid);
      const uint32_t D2 = lds32(ub + CV_D);
      conv_st<1>(d1, wq, c0, c1);
      STEP(11)
      sched_fence(__uint_as_float(u0.x ^ u1.x ^ D2), c.base + SM_DUMMY);
      __syncwarp();
      c.release2(u);
      __nv_bfloat16* zp = g_z + (uint32_t)(conv_channel<MASK>(cta, 2 * i + c.wg) * 2048 + (threadIdx.x & 127) * 8);
      oc_emit(y, u0, D2, zp);
      c.sync();
      oc_red<0, 12>(y, rq);
      STEP(12)
      oc_red<12, 24>(y, rq);
      STEP(13)
      oc_red<24, 32>(y, rq);
      oc_emit(y, u1, D2, zp + 1024);
#undef KEEP
      if (i == nr - 1) { c.signal(SIG_Z); c.release2(u + 1); TS2(c.wg, 8); }
      out_step<false, true, 1, !OC_POST>(c, o);
#pragma unroll 1
      for (int k = 15; k < (i == nr - 1 ? 0 : c.wg ? OC_L1 : OC_L0); k++) out_step<false, true>(c, o);
#undef STEP2
#undef PART
    }
#undef STEP
    if (((CV_REG<MASK> + c.wg) >> 1) & 1) c.skip(u ^ 2);
    ks += (nr - 1) * (c.wg ? OC_L1 : OC_L0) + 15;
  }
  TS(c.wg, 9);
#pragma unroll 1
  for (; ks < 57; ks++) out_step<false, true>(c, o);
  uint32_t ga[32];
  c.wait(2);
  const float g0 = __uint_as_float(lds32(c.base + SM_GATE + 4 * (c.wg * 64 + c.warp * 16 + (c.lane >> 2)))), g1 = __uint_as_float(lds32(c.base + SM_GATE + 32 + 4 * (c.wg * 64 + c.warp * 16 + (c.lane >> 2))));
  const uint32_t gg0 = pack_bf16(g0, g0), gg1 = pack_bf16(g1, g1);
  const uint32_t og0 = pack_bf16(1.f - g0, 1.f - g0), og1 = pack_bf16(1.f - g1, 1.f - g1);
  const int xr = c.wg * 64 + c.warp * 16 + (c.lane & 15);
  const uint32_t xa = c.addr(2) + xr * 128, xs = xr & 7, xh = c.lane >> 4;
  const int zr = (c.lane & 7) + ((c.lane >> 4) << 3);
  const uint32_t za = c.addr(0) + c.wg * 16384 + zr * 128 + (((c.warp * 2 + ((c.lane >> 3) & 1)) ^ (zr & 7)) << 4);
#pragma unroll
  for (int i = 0; i < 8; i++) {
    if (i == 0) out_step<false, true>(c, o);
    if (i == 3) out_step<false, true>(c, o);
    if (i == 6) out_step<false, true>(c, o);
    ldsm4(xa + (i >> 2) * 16384 + ((((i & 3) * 2 + xh) ^ xs) << 4), ga[4 * i], ga[4 * i + 1], ga[4 * i + 2], ga[4 * i + 3]);
  }
  if (TFMA & 2) {
#pragma unroll
    for (int i = 0; i < 32; i++) ga[i] = hmul2((i & 1) ? gg1 : gg0, ga[i]);
    fence_regs(ga);
  }
#pragma unroll 1
  for (ks = 60; ks < 64; ks++) out_step<false, false>(c, o);
  TS2(c.wg, 17);
  c.wait(0);
  TS2(c.wg, 18);
  SHADOW {
#pragma unroll
    for (int i = 0; i < 8; i++) {
      uint32_t z0, z1, z2, z3;
      ldsm4t(za + i * 2048, z0, z1, z2, z3);
      ga[4 * i + 0] = hmul2(ga[4 * i + 0], z0); ga[4 * i + 1] = hmul2(ga[4 * i + 1], z1); ga[4 * i + 2] = hmul2(ga[4 * i + 2], z2); ga[4 * i + 3] = hmul2(ga[4 * i + 3], z3);
      if (!(TFMA & 2)) { ga[4 * i + 0] = hmul2(gg0, ga[4 * i + 0]); ga[4 * i + 1] = hmul2(gg1, ga[4 * i + 1]); ga[4 * i + 2] = hmul2(gg0, ga[4 * i + 2]); ga[4 * i + 3] = hmul2(gg1, ga[4 * i + 3]); }
    }
  }
  c.signal(SIG_DONE);
  fence_regs(ga);
  TS2(c.wg, 19);
  wg_wait<0>(); fence_regs(o.acc);
  TS2(c.wg, 20);
#pragma unroll
  for (int i = 0; i < 8; i++) {
    const uint32_t r0 = mix(og0, pack_bf16(o.acc[8 * i + 0], o.acc[8 * i + 1]), ga[4 * i + 0]);
    const uint32_t r1 = mix(og1, pack_bf16(o.acc[8 * i + 2], o.acc[8 * i + 3]), ga[4 * i + 1]);
    const uint32_t r2 = mix(og0, pack_bf16(o.acc[8 * i + 4], o.acc[8 * i + 5]), ga[4 * i + 2]);
    const uint32_t r3 = mix(og1, pack_bf16(o.acc[8 * i + 6], o.acc[8 * i + 7]), ga[4 * i + 3]);
    stsm4(xa + (i >> 2) * 16384 + ((((i & 3) * 2 + xh) ^ xs) << 4), r0, r1, r2, r3);
    if ((i & 3) == 3 && (FINAL_ST == 0 || (FINAL_ST == 2 && i == 3))) {
      fence_async_smem();
      __syncwarp();
      const int r0 = c.wg * 64 + c.warp * 16;
      if (elect()) tma2d_store(&M.out, c.addr(2 + (i >> 2)) + r0 * 128, nb * 128 + (i >> 2) * 64, mb * 128 + r0);
    } else if ((i & 3) == 3) {
      __syncwarp();
#pragma unroll
      for (int k = 0; k < 4; k++) {
        const int rr = c.wg * 64 + c.warp * 16 + k * 4 + (c.lane >> 3);
        const uint4 v = lds128(c.addr(2 + (i >> 2)) + rr * 128 + (((c.lane ^ rr) & 7) << 4));
        *(uint4*)(P.out + (uint32_t)((mb * 128 + rr) * 1024 + nb * 128 + (i >> 2) * 64 + (c.lane & 7) * 8)) = v;
      }
    }
  }
  if (FINAL_ST != 1 && elect()) asm volatile("cp.async.bulk.commit_group;\ncp.async.bulk.wait_group.read 0;" ::: "memory");
}

__device__ __forceinline__ void load_conv(Prod& p, const Maps& M, int u, int ch) {
  if (elect()) {
    mbar_expect(p.full(u), 5120 + UCH);
    tma3d(p.addr(u), &M.h, 0, -8, ch, p.full(u), POL(4));
    bulk_g2s(p.addr(u) + CV_U, g_u + (size_t)ch * UCH, UCH, p.full(u), POL(4));
  }
}
template<int MASK> __device__ __forceinline__ void prod_conv(Prod& p, const Maps& M, int cta, int nch) {
  int ready = -1;
#pragma unroll 1
  for (int i = 0; i < nch; i++) {
    const int ch = conv_channel<MASK>(cta, i);
    const int u = i & 3;
    if ((ch >> 6) != ready) { ready = ch >> 6; if (cta < NREG) mbar_wait(p.base + SM_RDY + 8 * RDY_U, 0); else cnt_wait(g_cnt + (C_U + ready) * CSTRIDE, 128); }
    p.acquire(u, 1);
    load_conv(p, M, u, ch);
    if (i == 3) { p.acquire(4, 4); if (elect()) mbar_arrive(p.full(4)); }
  }
}
#define HOIST(v) asm volatile("" : "+r"(v))
template<int MASK> __device__ __forceinline__ void producer(const Maps& M, const Params& P, uint32_t base, int cta, int lane) {
  Prod p{base, ((MASK & PH_KV) && cta < NREG) ? 0xffffcfffu ^ ((1u << (3 * NFIRST)) - 1) : 0xffffffffu, lane,
         (cta * 3 + 2) * 2048};
  if (cta >= NREG) { if (MASK & PH_CONV) prod_conv<MASK>(p, M, cta, CV_EXTRA<MASK>); return; }
  const int g = cta & 7, j = cta >> 3, rank = cta & 1;
#pragma unroll 1
  for (int half = 0; half < 2; half++) {
    const int h = j + 16 * half;
    if (MASK & PH_KV) {
      const CUtensorMap* mw = rank ? &M.wv : &M.wk;
#pragma unroll 1
      for (int it = half ? 0 : NFIRST; it < 16; it++) {
        const int u = gemm_unit(it);
        uint32_t bar = p.full(u), d0 = p.addr(u), d1 = p.addr(u + 1 + rank); int k0 = (it & 7) * 64, r0 = (2 * g + (it >> 3)) * 128;
        HOIST(bar); HOIST(d0); HOIST(d1); HOIST(k0); HOIST(r0);
        p.acquire(u, 3);
        if (elect()) {
          mbar_expect(bar, 3 * UNIT);
          tma3d_mc(d1, mw, 0, k0, 2 * h, bar, POL(0) && it >= 8);
          tma2d(d0, &M.c, k0, r0, bar, half ? POL(8) : POL(10));
        }
      }
    }
    if (MASK & PH_ATT) {
#pragma unroll 1
      for (int ks = 0; ks < 16; ks++) {
        const int u = gemm_unit(ks);
        uint32_t bar = p.full(u), d0 = p.addr(u), d1 = p.addr(u + 1), d2 = p.addr(u + 2) + rank * 8192; int k0 = ks * 64;
        HOIST(bar); HOIST(d0); HOIST(d1); HOIST(d2); HOIST(k0);
        p.acquire(u, 3);
        if (elect()) {
          mbar_expect(bar, 3 * UNIT);
          tma2d_mc(d2, &M.wq, h * 128 + rank * 64, k0, bar, POL(1));
          tma2d(d0, &M.x, k0, (15 - g) * 128, bar, half ? POL(9) : POL(10));
          tma2d(d1, &M.x, k0, g * 128, bar, half ? POL(9) : POL(10));
        }
      }
      TS(2, 8 * half + 0);
      mbar_wait(base + SM_RDY + 8 * (RDY_KV + half), 0);
      TS(2, 8 * half + 1);
      const uint8_t* KVh = g_T + T_KV + (size_t)kv_slot<MASK>(h) * 16 * 65536;
      if (MASK & PH_PRE) mbar_wait(base + SM_RDY + 8 * RDY_AUX, 0);
      if (elect()) { mbar_expect(p.full(12), 32768); bulk_g2s(p.addr(12), KVh, 32768, p.full(12), POL(6)); }
      p.acquire(0, 4);
      if (elect()) mbar_arrive(p.full(0));
#pragma unroll 1
      for (int n = 1; n < 34; n++) {
        const int i = !V1F ? n : n == 3 ? 4 : n == 4 ? 3 : n, isv = !(i & 1) || i == 33, st = i == 33 ? 16 : (isv ? (i >> 1) - 1 : (i + 1) >> 1), u = 4 + 2 * (i & 3);
        const bool own = st == 15 - (g & 6);
        uint32_t bar = p.full((SHW || (i & 1)) ? u : 14 - u), d0 = p.addr(own ? u : u + rank), off = (st <= 15 - g ? st : 16 - st) * 65536 + isv * 32768 + (own ? 0 : rank * UNIT);
        HOIST(bar); HOIST(d0); HOIST(off);
        if (!K1V0 || n > 2) p.acquire(u, 2); else if (n == 1) p.acquire(6, 4);
        if (elect()) {
          if (SHW) mbar_expect(bar, 32768); else if (!isv || i == 33) mbar_expect(bar, isv ? 32768 : 65536);
          const bool ef = POL(6) || (POL(14) && st >= 8) || (POL(15) && half);
          if (own) bulk_g2s(d0, KVh + off, 32768, bar, ef); else bulk_g2s_mc(d0, KVh + off, UNIT, bar, ef);
        }
      }
    }
  }
  if ((MASK & PH_CONV) && !(MASK & PH_OUT)) prod_conv<MASK>(p, M, cta, CV_REG<MASK>);
  if (MASK & PH_OUT) {
    const int y0 = out_mb(cta) * 512 + rank * 8, z0 = 2 * out_nb(cta);
    int u = 6;
#pragma unroll 1
    for (int hf = 0; hf < 2; hf++) {
      TS(2, 16 + 2 * hf);
      mbar_wait(base + SM_RDY + 8 * (RDY_CTX + hf), 0);
      TS(2, 17 + 2 * hf);
#pragma unroll 1
      for (int n = hf * 32; n < hf * 32 + 32; n++) {
        const int ks = n == 1 ? 2 : n == 2 ? 1 : n;
        u = n == 2 ? 2 : n == 3 ? 10 : out_next(u);
        uint32_t bar = p.full(u), d0 = p.addr(u) + rank * 8192, d1 = p.addr(u + 1); int x = (ks & 1) * 256, y = y0 + (ks >> 1) * 16, k0 = ks * 64;
        HOIST(bar); HOIST(d0); HOIST(d1); HOIST(x); HOIST(y); HOIST(k0);
        p.acquire(u, 2);
        if (elect()) {
          mbar_expect(bar, 2 * UNIT);
          tma2d_mc(d0, &M.ctx, x, y, bar, POL(5));
          tma3d(d1, &M.wo, 0, k0, z0, bar, POL(2));
          if (ks == 1) mbar_arrive(base + SM_RDY + 8 * RDY_X);
          if (ks == Z_AT) mbar_arrive(base + SM_RDY + 8 * RDY_Z);
        }
      }
    }
  }
}
template<int MASK> __device__ __forceinline__ void producer2(const Maps& M, const Params& P, uint32_t base, int cta, int w, int lane) {
  Prod p{base, 0xffffffffu, lane, 0};
  const int mb = out_mb(cta), nb = out_nb(cta), u = 2 * w;
  if (w) { mbar_wait_slow(base + SM_RDY + 8 * RDY_X, 0); p.mask ^= 12; }
  if (MASK & PH_CONV) {
    mbar_wait_slow(base + SM_SIG + 8 * (SIG_ATT + 1), 0);
    mbar_wait_slow(base + SM_RDY + 8 * RDY_U, 0);
#pragma unroll 1
    for (int i = w; i < CV_REG<MASK>; i += 2) { p.acquire_slow(u, i < 2 ? 2 : 1); load_conv(p, M, u, conv_channel<MASK>(cta, i)); }
  }
  p.acquire_slow(u, 2);
  if (!w && elect()) map_pf(&M.z);
  TSA(52 - 2 * w);
  mbar_wait(base + SM_RDY + 8 * (!w ? RDY_Z : RDY_G), 0);
  TSA(53 - 2 * w);
  if (elect()) {
    mbar_expect(p.full(u), 2 * UNIT + (!w ? 0 : 512));
    tma2d(p.addr(u), !w ? &M.z : &M.x, (!w ? mb : nb) * 128, (!w ? nb : mb) * 128, p.full(u), POL(5));
    tma2d(p.addr(u + 1), !w ? &M.z : &M.x, (!w ? mb : nb) * 128 + 64, (!w ? nb : mb) * 128, p.full(u), POL(5));
    if (w) bulk_g2s(base + SM_GATE, g_gate + mb * 128, 512, p.full(u));
  }
}

__device__ __forceinline__ constexpr uint32_t PUB(int sig, int cnt, int n) { return 0x80000000u | (sig << 24) | (n << 8) | cnt; }
__device__ __forceinline__ constexpr uint32_t GET(int rdy, int cnt, int n) { return (rdy << 24) | (n << 8) | cnt; }
template<int MASK> __device__ __forceinline__ void sync_agent(uint32_t base, int cta, int lane) {
  if ((base & 0x3FFFF) != SMEM_BASE) asm volatile("trap;");
  const int g = cta & 7, j = cta >> 3, go = min(out_mb(cta), 15 - out_mb(cta));
  const int c0 = conv_channel<MASK>(cta, 0), c1 = c0 + CV_REG<MASK> - 1, n0 = min(CV_REG<MASK>, 128 - (c0 & 127));
  constexpr bool KV = MASK & PH_KV, ATT = MASK & PH_ATT, CONV = MASK & PH_CONV, OUT = MASK & PH_OUT, ALL = MASK == PH_ALL;
  uint32_t e = 0;
  if (cta >= NREG) { if (CONV && lane * 32 < CV_EXTRA<MASK>) e = PUB(SIG_Z + lane, C_Z + lane, min(32, CV_EXTRA<MASK> - lane * 32)); }
  else switch (lane) {
    case 0:  if (KV) e = PUB(SIG_KV, C_KV + j, 1); break;
    case 1:  if (ATT) e = GET(RDY_KV, C_KV + j, 8); break;
    case 2:  if (ALL) e = PUB(SIG_WAR, C_WAR + j, 1); break;
    case 3:  if (ATT) e = PUB(SIG_CTX, C_CTX + g, 1); break;
    case 4:  if (ALL) e = GET(RDY_WAR, C_WAR + j, 8); break;
    case 5:  if (KV) e = PUB(SIG_KV + 1, C_KV + 16 + j, 1); break;
    case 6:  if (ATT) e = GET(RDY_KV + 1, C_KV + 16 + j, 8); break;
    case 7:  if (OUT) e = GET(RDY_CTX, C_CTX + go, 16); break;
    case 8:  if (CONV) e = GET(RDY_U, C_U + (c0 >> 6), 128); break;
    case 9:  if (CONV) e = GET(RDY_U, C_U + (c1 >> 6), 128); break;
    case 10: if (ATT) e = PUB(SIG_CTX + 1, C_CTX + 8 + g, 1); break;
    case 11: if (OUT) e = GET(RDY_CTX + 1, C_CTX + 8 + go, 16); break;
    case 12: if (OUT) e = GET(RDY_G, C_GATE, 256); break;
    case 13: if (CONV) e = PUB(SIG_Z, C_Z + (c0 >> 7), n0); break;
    case 14: if (CONV && n0 < CV_REG<MASK>) e = PUB(SIG_Z, C_Z + (c1 >> 7), CV_REG<MASK> - n0); break;
    case 15: if (OUT) e = GET(RDY_Z, C_Z + out_nb(cta), 128); break;
  }
  __syncwarp();
#pragma unroll 1
  for (int i = 0; i < 16; i++) {
    const uint32_t x = __shfl_sync(~0u, e, i), id = (x >> 24) & 127, n = (x >> 8) & 0xffff;
    if (x == 0) continue;
    unsigned* cnt = g_cnt + (x & 255) * CSTRIDE;
    if (x >> 31) {
      mbar_wait_slow(base + SM_SIG + 8 * id, 0);
      if (i == 13) TSA(22);
      if (lane == 0) cnt_publish(cnt, n, i != 14);
    } else {
      cnt_wait(cnt, n);
      if (id < 2) {
        const float4 kn = __ldcg((const float4*)(g_kn2 + kv_slot<MASK>(j + 16 * id) * 128) + lane);
        const uint32_t m = __reduce_max_sync(~0u, max(max(__float_as_uint(kn.x), __float_as_uint(kn.y)), max(__float_as_uint(kn.z), __float_as_uint(kn.w))));
        if (lane == 0) asm volatile("st.shared.u32 [%0], %1;" :: "r"(base + SM_KMAX + 4 * id), "r"(m) : "memory");
      }
      if (lane == 0) mbar_arrive(base + SM_RDY + 8 * id);
    }
    __syncwarp();
    TSA(24 + i);
  }
}

__device__ __forceinline__ void aux_gate(const Params& P, int cta, int aw, int lane) {
  uint4 gw[4];
#pragma unroll
  for (int i = 0; i < 4; i++) gw[i] = __ldg((const uint4*)P.gw + i * 32 + lane);
#pragma unroll 1
  for (int row = cta * 16 + aw * 8; row < cta * 16 + aw * 8 + 8; row++) {
    float a = 0.f;
#pragma unroll
    for (int i = 0; i < 4; i++) {
      const uint4 xv = __ldg((const uint4*)(P.x + (size_t)row * 1024) + i * 32 + lane);
      uint32_t m;
      m = hmul2(xv.x, gw[i].x); a += bf_lo(m) + bf_hi(m); m = hmul2(xv.y, gw[i].y); a += bf_lo(m) + bf_hi(m);
      m = hmul2(xv.z, gw[i].z); a += bf_lo(m) + bf_hi(m); m = hmul2(xv.w, gw[i].w); a += bf_lo(m) + bf_hi(m);
    }
#pragma unroll
    for (int o = 16; o > 0; o >>= 1) a += __shfl_xor_sync(~0u, a, o);
    a = bf_lo(pack_bf16(a, 0.f));
    const float gt = bf_lo(pack_bf16(__fdividef(1.f, 1.f + ex2(-a * 1.4426950408889634f)), 0.f));
    if (lane == 0) g_gate[row] = gt;
    if (GATE_SLEEP) __nanosleep(GATE_SLEEP);
  }
  cnt_signal(g_cnt + C_GATE * CSTRIDE, lane);
  if (aw == 0) { TSA(44); }
}
template<int MASK> __device__ __forceinline__ void aux_pre(const Maps& M, const Params& P, uint32_t base, int cta, int aw, int lane) {
  const uint32_t kb = base + 12 * UNIT, bar = base + SM_PRE;
  const int r = lane >> 2, q = lane & 3;
  const int mi = lane >> 3, row0 = (lane & 6) + 1 - (lane & 1);
  const int ra = (mi * 9 + 1) * 2 + row0;
  const int rb = (mi == 0 ? 3 : mi) * 18 + row0;
  if (PRE_DELAY) mbar_wait_slow(base + SM_BAR + 8 * PRE_DELAY_BAR, 0);
#pragma unroll 1
  for (int it = 0; it < (cta < 96 ? 5 : 4); it++) {
    if (GATE_EARLY && it == PRE_EARLY && MASK == PH_ALL) { mbar_wait_slow(base + SM_SIG + 8 * SIG_ATT, 0); aux_gate(P, cta, aw, lane); }
    if (it == PRE_EARLY && MASK == PH_ALL) mbar_wait_slow(base + SM_SIG + 8 * (SIG_ATT + PRE_HALF), 0);
    const int cg = it ? it * 4 - 3 + (cta >> 5) : 0, tb = cta & 31;
    if (aw == 0 && elect()) {
      mbar_expect(bar, 2 * 9216);
      tma4d(kb, &M.k, cg * 64, 0, tb * 8 - 1, 0, bar, POL(3));
      tma4d(kb + 9216, &M.v, cg * 64, 0, tb * 8 - 1, 0, bar, POL(3));
    }
    const uint2 swl = __ldg((const uint2*)(P.shift + (cg * 64 + aw * 32 + lane) * 4));
    if (tb == 0) {
      uint8_t* e = g_u + (size_t)(cg * 64 + aw * 32 + lane) * UCH + 4096;
      *(uint4*)e = make_uint4(0, 0, 0, 0); *(uint4*)(e + UPITCH) = make_uint4(0, 0, 0, 0);
      *(uint32_t*)(e + 32) = (uint32_t)__bfloat16_as_ushort(P.D[cg * 64 + aw * 32 + lane]) * 0x10001u;
    }
    mbar_wait_slow(bar, it & 1);
#pragma unroll 1
    for (int ol = it ? 0 : cta >> 5; ol < (it ? 4 : (cta >> 5) + 1); ol++) {
      const int oc = aw * 4 + ol;
      const uint32_t s01 = __shfl_sync(~0u, swl.x, ol * 8 + r), s23 = __shfl_sync(~0u, swl.y, ol * 8 + r);
      const uint32_t w0 = __byte_perm(s01, 0, 0x1010), w1 = __byte_perm(s01, 0, 0x3232), w2 = __byte_perm(s23, 0, 0x1010), w3 = __byte_perm(s23, 0, 0x3232);
      const uint32_t pa = kb + ra * 128 + ((oc ^ (ra & 7)) << 4), pb = kb + (mi == 0 ? 9216 : 0) + rb * 128 + ((oc ^ (rb & 7)) << 4);
      uint8_t* e0 = g_u + (uint32_t)((cg * 64 + oc * 8 + r) * UCH + (2040 - tb * 64 - 8 * q) * 2);
#pragma unroll
      for (int hb = 0; hb < 2; hb++) {
        uint32_t k[7], v[5];
        ldsm4t(pa + hb * 1024, k[3], k[4], k[5], k[6]);
        ldsm4t(pa + hb * 1024 + 9216, v[1], v[2], v[3], v[4]);
        ldsm4t(pb + hb * 1024, v[0], k[0], k[1], k[2]);
        uint32_t o1 = __byte_perm(k[1], k[0], 0x5432);
#pragma unroll
        for (int m = 0; m < 5; m++) {
          const uint32_t o2 = __byte_perm(k[m + 2], k[m + 1], 0x5432);
          v[m] = hmul2(hadd2(hadd2(hadd2(hmul2(o1, w3), hmul2(k[m + 1], w2)), hmul2(o2, w1)), hmul2(k[m + 2], w0)), v[m]);
          o1 = o2;
        }
        *(uint4*)(e0 - hb * 64) = make_uint4(v[4], v[3], v[2], v[1]);
        *(uint4*)(e0 - hb * 64 + UPITCH) = make_uint4(__byte_perm(v[4], v[3], 0x5432), __byte_perm(v[3], v[2], 0x5432), __byte_perm(v[2], v[1], 0x5432), __byte_perm(v[1], v[0], 0x5432));
        if (it >= PRE_EARLY) __nanosleep(PRE_SLEEP);
      }
    }
    bar_sync(5, 64);
    if (aw == 0) { TSA(40 + min(it, 3)); }
    if (it == PRE_EARLY - 1 && aw == 0 && lane == 0) mbar_arrive(base + SM_RDY + 8 * RDY_AUX);
    if (aw == 1 && lane == 0) asm volatile("red.release.gpu.global.add.u32 [%0], %1;" :: "l"(g_cnt + (C_U + cg) * CSTRIDE), "r"(it ? 4 : 1) : "memory");
  }
  uint32_t rel;
  asm volatile("mapa.shared::cluster.u32 %0, %1, %2;" : "=r"(rel) : "r"(base + SM_BAR + 128 + 8 * (12 + (lane & 1))), "r"((lane >> 1) & 1));
  if (lane < 4) asm volatile("mbarrier.arrive.shared::cluster.b64 _, [%0], 4;" :: "r"(rel) : "memory");
  if (!(GATE_EARLY && MASK == PH_ALL)) aux_gate(P, cta, aw, lane);
}

template<int MASK> __global__ void __cluster_dims__(2, 1, 1) __launch_bounds__(384, 1) gated_mix_kernel(const __grid_constant__ Maps M, const __grid_constant__ Params P) {
  extern __shared__ __align__(1024) uint8_t smem[];
  const uint32_t base = (uint32_t)__cvta_generic_to_shared(smem);
  if ((MASK & PH_KV) && elect()) {
    map_pf(&M.wk + (blockIdx.x & 1)); map_pf(&M.c);
  }
  const int wi = __shfl_sync(~0u, threadIdx.x >> 5, 0), wg = wi >> 2, warp = wi & 3;
  if (elect()) {
    if (wi < 8) {
      const int cnt = 1 << ((0x10334400 >> (4 * wi)) & 15);
#pragma unroll
      for (int i = 0; i < 8; i++) mbar_init(base + SM_BAR + 64 * wi + 8 * i, cnt);
      asm volatile("fence.mbarrier_init.release.cluster;" ::: "memory");
    }
  }
  const int cta = blockIdx.x;
  const bool first_loads = (MASK & PH_KV) && wi == 8 && cta < NREG;
  const CUtensorMap* mw = (cta & 1) ? &M.wv : &M.wk;
  __syncwarp();
  asm volatile("barrier.cluster.arrive.relaxed.aligned;\nbarrier.cluster.wait.aligned;" ::: "memory");
  auto first_stage = [&](int it) {
    const uint32_t bar = base + SM_BAR + 24 * it, d0 = base + 3 * it * UNIT;
    mbar_expect(bar, 3 * UNIT);
    tma3d_mc(d0 + (1 + (cta & 1)) * UNIT, mw, 0, it * 64, 2 * (cta >> 3), bar);
    tma2d(d0, &M.c, it * 64, (cta & 7) * 256, bar);
  };
  if (first_loads && elect()) {
#pragma unroll 1
    for (int it = 0; it < NF0; it++) first_stage(it);
  }
  __syncwarp();
  const int lane = threadIdx.x & 31;
#define TS_PRO()
  if (wg == 2) {
    asm volatile("setmaxnreg.dec.sync.aligned.u32 56;");
    TS_PRO();
    TS(2, 62);
    if (warp == 0) producer<MASK>(M, P, base, cta, lane);
    else if (warp == 1) sync_agent<MASK>(base, cta, lane);
    else if (cta < NREG) {
      if (MASK & PH_PRE) aux_pre<MASK>(M, P, base, cta, warp - 2, lane);
      if (MASK & PH_OUT) producer2<MASK>(M, P, base, cta, warp - 2, lane);
    }
    if (warp == 1) {
      if (MASK & PH_OUT) {
        unsigned old = 0;
        if (lane == 0) asm volatile("atom.relaxed.gpu.global.add.u32 %0, [%1], 1;" : "=r"(old) : "l"(g_cnt + C_EXIT * CSTRIDE) : "memory");
        old = __shfl_sync(~0u, old, 0);
        if (old == NCTA - 1) for (int i = lane; i < C_NUM; i += 32) g_cnt[i * CSTRIDE] = 0;
      }
      mbar_wait_slow(base + SM_SIG + 8 * SIG_DONE, 0);
      if (cta >= NREG || !(MASK & PH_OUT)) { cluster_arrive(); cluster_wait(); }
    }
  } else {
    asm volatile("setmaxnreg.inc.sync.aligned.u32 224;");
    TS_PRO();
    uint32_t rel;
    asm volatile("mapa.shared::cluster.u32 %0, %1, %2;" : "=r"(rel) : "r"(base + SM_BAR + 128 + 8 * (lane & 15)), "r"(lane >> 4));
    Cons c{base, rel, 0u, lane, warp, wg, (cta * 3 + wg) * 2048};
    if (wg == 1) bar_arrive(1, 256);
    if (NF0 < NFIRST && (MASK & PH_KV) && wi == 4 && cta < NREG) {
      if (elect()) {
#pragma unroll 1
        for (int it = NF0; it < NFIRST; it++) {
          asm volatile("{\n.reg .pred p;\n.reg .u32 a, b;\nmov.u32 a, %%clock;\nXL:\nmov.u32 b, %%clock;\nsub.u32 b, b, a;\nsetp.lt.u32 p, b, %0;\n@p bra XL;\n}\n" :: "r"(it == NF0 ? FGAP : FGAP2) : "memory");
          first_stage(it);
        }
      }
      __syncwarp();
    }
    TS(wg, 0);
    if (cta < NREG) {
      const int g = cta & 7, j = cta >> 3;
      Pend w = {};
      if (HOISTW && MASK == PH_ALL) c.wait(0);
#pragma unroll 1
      for (int half = 0; half < 2; half++) {
        const int h = j + 16 * half;
        if (MASK & PH_KV) cons_kv<(MASK & PH_ATT) != 0>(c, h, kv_slot<MASK>(h), g, w, half == 1 && (MASK & PH_ATT));
        TS(wg, 1 + 4 * half);
        if (MASK & PH_ATT) {
          Att a;
          cons_q<(MASK & PH_KV) != 0>(c, h, w, a.o);
          TS(wg, 2 + 4 * half);
          cons_att<MASK == PH_ALL>(c, a, h, g, w);
          if (half == 0) c.signal(SIG_WAR);
#pragma unroll
          for (int i = 0; i < 8; i++) w.hi[i] = make_uint4(0, 0, 0, 0);
          TS(wg, 3 + 4 * half);
          if (MASK != PH_ALL) { tile_store<0, 4>(w.lo, w.dst, lane); c.signal(SIG_CTX + half); }
        } else if (MASK & PH_KV) {
          out_piece<SCH_KV, true>(c, w, 0, true);
          for (int ks = 1; ks < 8; ks++) out_piece<SCH_KV, false>(c, w, ks, true);
          c.signal(SIG_KV + half);
        }
      }
      if (MASK & PH_OUT) cons_out<MASK>(c, M, P, cta, w);
    }
    if (cta >= NREG || !(MASK & PH_OUT)) {
      if (MASK & PH_CONV) cons_conv<MASK>(c, cta, cta < NREG ? CV_REG<MASK> : CV_EXTRA<MASK>);
      TS(wg, 9);
      c.signal(SIG_DONE);
      cluster_arrive();
    }
    TS(wg, 10);
  }
}

typedef CUresult (*EncFn)(CUtensorMap*, CUtensorMapDataType, cuuint32_t, void*, const cuuint64_t*, const cuuint64_t*, const cuuint32_t*, const cuuint32_t*,
                          CUtensorMapInterleave, CUtensorMapSwizzle, CUtensorMapL2promotion, CUtensorMapFloatOOBfill);
static void enc(EncFn f, CUtensorMap* m, const void* ptr, int rank, const cuuint64_t* dims, const cuuint64_t* strides, const cuuint32_t* box, CUtensorMapSwizzle sw,
                CUtensorMapDataType dt = CU_TENSOR_MAP_DATA_TYPE_BFLOAT16) {
  const cuuint32_t es[4] = {1, 1, 1, 1};
  f(m, dt, rank, (void*)ptr, dims, strides, box, es, CU_TENSOR_MAP_INTERLEAVE_NONE, sw, CU_TENSOR_MAP_L2_PROMOTION_L2_256B, CU_TENSOR_MAP_FLOAT_OOB_FILL_NONE);
}
static void enc2(EncFn f, CUtensorMap* m, const void* ptr, int cols, int rows, int brows) {
  const cuuint64_t d[2] = {(cuuint64_t)cols, (cuuint64_t)rows}, s[1] = {(cuuint64_t)cols * 2}; const cuuint32_t b[2] = {64, (cuuint32_t)brows};
  enc(f, m, ptr, 2, d, s, b, CU_TENSOR_MAP_SWIZZLE_128B);
}
static void encw(EncFn f, CUtensorMap* m, const void* ptr, int cols, int rows) {
  const cuuint64_t d[3] = {64, (cuuint64_t)rows, (cuuint64_t)cols / 64}, s[2] = {(cuuint64_t)cols * 2, 128}; const cuuint32_t b[3] = {64, 64, 2};
  enc(f, m, ptr, 3, d, s, b, CU_TENSOR_MAP_SWIZZLE_128B);
}
extern "C" void kernel_launch(void* const* d_in, const int* in_sizes, int n_in, void* d_out, int out_size) {
  static EncFn fn = nullptr;
  static int ncl = 0;
  static void* zptr = nullptr;
  static void* tptr = nullptr;
  if (!fn) {
    void* p = nullptr; cudaDriverEntryPointQueryResult qr;
    cudaGetDriverEntryPoint("cuTensorMapEncodeTiled", &p, cudaEnableDefault, &qr);
    fn = (EncFn)p;
    cudaFuncSetAttribute(gated_mix_kernel<PH_ALL>, cudaFuncAttributeMaxDynamicSharedMemorySize, SMEM_BYTES);
    cudaFuncSetAttribute(gated_mix_kernel<PH_PRE | PH_KV>, cudaFuncAttributeMaxDynamicSharedMemorySize, SMEM_BYTES);
    cudaFuncSetAttribute(gated_mix_kernel<PH_ATT | PH_CONV>, cudaFuncAttributeMaxDynamicSharedMemorySize, SMEM_BYTES);
    cudaFuncSetAttribute(gated_mix_kernel<PH_OUT>, cudaFuncAttributeMaxDynamicSharedMemorySize, SMEM_BYTES);
    cudaLaunchConfig_t cfg = {}; cfg.gridDim = NCTA; cfg.blockDim = 384; cfg.dynamicSmemBytes = SMEM_BYTES;
    cudaLaunchAttribute at; at.id = cudaLaunchAttributeClusterDimension; at.val.clusterDim.x = 2; at.val.clusterDim.y = 1; at.val.clusterDim.z = 1;
    cfg.attrs = &at; cfg.numAttrs = 1;
    cudaOccupancyMaxActiveClusters(&ncl, gated_mix_kernel<PH_ALL>, &cfg);
    cudaGetSymbolAddress(&zptr, g_z);
    cudaGetSymbolAddress(&tptr, g_T);
  }
  Maps M;
  enc2(fn, &M.x, d_in[0], 1024, 2048, 128);
  enc2(fn, &M.c, d_in[7], 512, 2048, 128);
  enc2(fn, &M.wq, d_in[8], 4096, 1024, 64);
  encw(fn, &M.wk, d_in[9], 4096, 512);
  encw(fn, &M.wv, d_in[10], 4096, 512);
  encw(fn, &M.wo, d_in[11], 1024, 4096);
  { const cuuint64_t d[3] = {64, 32, 1024}, s[2] = {128, 4096}; const cuuint32_t b[3] = {64, 40, 1}; enc(fn, &M.h, d_in[4], 3, d, s, b, CU_TENSOR_MAP_SWIZZLE_NONE); }
  enc2(fn, &M.z, zptr, 2048, 1024, 128);
  enc2(fn, &M.out, d_out, 1024, 2048, 16);
  { const cuuint64_t d[2] = {512, 512 * 16}, s[1] = {2048}; const cuuint32_t b[2] = {256, 8};
    enc(fn, &M.ctx, tptr, 2, d, s, b, CU_TENSOR_MAP_SWIZZLE_NONE, CU_TENSOR_MAP_DATA_TYPE_UINT32); }
  { const cuuint64_t d[4] = {1024, 2, 256, 4}, s[3] = {2048, 16384, 4096}; const cuuint32_t b[4] = {64, 2, 9, 4};
    enc(fn, &M.k, d_in[1], 4, d, s, b, CU_TENSOR_MAP_SWIZZLE_128B); enc(fn, &M.v, d_in[2], 4, d, s, b, CU_TENSOR_MAP_SWIZZLE_128B); }
  Params P{(const __nv_bfloat16*)d_in[0], (const __nv_bfloat16*)d_in[3],
           (const __nv_bfloat16*)d_in[5], (const __nv_bfloat16*)d_in[12], (__nv_bfloat16*)d_out};
  bool split = 2 * ncl < NCTA;
  if (!split) {
    gated_mix_kernel<PH_ALL><<<NCTA, 384, SMEM_BYTES>>>(M, P);
  } else {
    gated_mix_kernel<PH_PRE | PH_KV><<<NCTA, 384, SMEM_BYTES>>>(M, P);
    gated_mix_kernel<PH_ATT | PH_CONV><<<NCTA, 384, SMEM_BYTES>>>(M, P);
    gated_mix_kernel<PH_OUT><<<NCTA, 384, SMEM_BYTES>>>(M, P);
  }
}
```

```cpp
#include <cuda_runtime.h>
#include <cuda.h>
#include <cuda_bf16.h>
#include <stdint.h>

template<int TB> __device__ __forceinline__ void wgmma_ss_n256(float (&d)[128], uint64_t da, uint64_t db, int scale_d) {
  asm volatile("{\n.reg .pred p;\nsetp.ne.b32 p, %130, 0;\n"
    "wgmma.mma_async.sync.aligned.m64n256k16.f32.bf16.bf16 {%0, %1, %2, %3, %4, %5, %6, %7, %8, %9, %10, %11, %12, %13, %14, %15, %16, %17, %18, %19, %20, %21, %22, %23, %24, %25, %26, %27, %28, %29, %30, %31, %32, %33, %34, %35, %36, %37, %38, %39, %40, %41, %42, %43, %44, %45, %46, %47, %48, %49, %50, %51, %52, %53, %54, %55, %56, %57, %58, %59, %60, %61, %62, %63, %64, %65, %66, %67, %68, %69, %70, %71, %72, %73, %74, %75, %76, %77, %78, %79, %80, %81, %82, %83, %84, %85, %86, %87, %88, %89, %90, %91, %92, %93, %94, %95, %96, %97, %98, %99, %100, %101, %102, %103, %104, %105, %106, %107, %108, %109, %110, %111, %112, %113, %114, %115, %116, %117, %118, %119, %120, %121, %122, %123, %124, %125, %126, %127}, %128, %129, p, 1, 1, 0, %131;\n}\n"
    : "+f"(d[0]), "+f"(d[1]), "+f"(d[2]), "+f"(d[3]), "+f"(d[4]), "+f"(d[5]), "+f"(d[6]), "+f"(d[7]), "+f"(d[8]), "+f"(d[9]), "+f"(d[10]), "+f"(d[11]), "+f"(d[12]), "+f"(d[13]), "+f"(d[14]), "+f"(d[15]), "+f"(d[16]), "+f"(d[17]), "+f"(d[18]), "+f"(d[19]), "+f"(d[20]), "+f"(d[21]), "+f"(d[22]), "+f"(d[23]), "+f"(d[24]), "+f"(d[25]), "+f"(d[26]), "+f"(d[27]), "+f"(d[28]), "+f"(d[29]), "+f"(d[30]), "+f"(d[31]), "+f"(d[32]), "+f"(d[33]), "+f"(d[34]), "+f"(d[35]), "+f"(d[36]), "+f"(d[37]), "+f"(d[38]), "+f"(d[39]), "+f"(d[40]), "+f"(d[41]), "+f"(d[42]), "+f"(d[43]), "+f"(d[44]), "+f"(d[45]), "+f"(d[46]), "+f"(d[47]), "+f"(d[48]), "+f"(d[49]), "+f"(d[50]), "+f"(d[51]), "+f"(d[52]), "+f"(d[53]), "+f"(d[54]), "+f"(d[55]), "+f"(d[56]), "+f"(d[57]), "+f"(d[58]), "+f"(d[59]), "+f"(d[60]), "+f"(d[61]), "+f"(d[62]), "+f"(d[63]), "+f"(d[64]), "+f"(d[65]), "+f"(d[66]), "+f"(d[67]), "+f"(d[68]), "+f"(d[69]), "+f"(d[70]), "+f"(d[71]), "+f"(d[72]), "+f"(d[73]), "+f"(d[74]), "+f"(d[75]), "+f"(d[76]), "+f"(d[77]), "+f"(d[78]), "+f"(d[79]), "+f"(d[80]), "+f"(d[81]), "+f"(d[82]), "+f"(d[83]), "+f"(d[84]), "+f"(d[85]), "+f"(d[86]), "+f"(d[87]), "+f"(d[88]), "+f"(d[89]), "+f"(d[90]), "+f"(d[91]), "+f"(d[92]), "+f"(d[93]), "+f"(d[94]), "+f"(d[95]), "+f"(d[96]), "+f"(d[97]), "+f"(d[98]), "+f"(d[99]), "+f"(d[100]), "+f"(d[101]), "+f"(d[102]), "+f"(d[103]), "+f"(d[104]), "+f"(d[105]), "+f"(d[106]), "+f"(d[107]), "+f"(d[108]), "+f"(d[109]), "+f"(d[110]), "+f"(d[111]), "+f"(d[112]), "+f"(d[113]), "+f"(d[114]), "+f"(d[115]), "+f"(d[116]), "+f"(d[117]), "+f"(d[118]), "+f"(d[119]), "+f"(d[120]), "+f"(d[121]), "+f"(d[122]), "+f"(d[123]), "+f"(d[124]), "+f"(d[125]), "+f"(d[126]), "+f"(d[127])
    : "l"(da), "l"(db), "r"(scale_d), "n"(TB));
}
template<int TB> __device__ __forceinline__ void wgmma_ss_n128(float (&d)[64], uint64_t da, uint64_t db, int scale_d) {
  asm volatile("{\n.reg .pred p;\nsetp.ne.b32 p, %66, 0;\n"
    "wgmma.mma_async.sync.aligned.m64n128k16.f32.bf16.bf16 {%0, %1, %2, %3, %4, %5, %6, %7, %8, %9, %10, %11, %12, %13, %14, %15, %16, %17, %18, %19, %20, %21, %22, %23, %24, %25, %26, %27, %28, %29, %30, %31, %32, %33, %34, %35, %36, %37, %38, %39, %40, %41, %42, %43, %44, %45, %46, %47, %48, %49, %50, %51, %52, %53, %54, %55, %56, %57, %58, %59, %60, %61, %62, %63}, %64, %65, p, 1, 1, 0, %67;\n}\n"
    : "+f"(d[0]), "+f"(d[1]), "+f"(d[2]), "+f"(d[3]), "+f"(d[4]), "+f"(d[5]), "+f"(d[6]), "+f"(d[7]), "+f"(d[8]), "+f"(d[9]), "+f"(d[10]), "+f"(d[11]), "+f"(d[12]), "+f"(d[13]), "+f"(d[14]), "+f"(d[15]), "+f"(d[16]), "+f"(d[17]), "+f"(d[18]), "+f"(d[19]), "+f"(d[20]), "+f"(d[21]), "+f"(d[22]), "+f"(d[23]), "+f"(d[24]), "+f"(d[25]), "+f"(d[26]), "+f"(d[27]), "+f"(d[28]), "+f"(d[29]), "+f"(d[30]), "+f"(d[31]), "+f"(d[32]), "+f"(d[33]), "+f"(d[34]), "+f"(d[35]), "+f"(d[36]), "+f"(d[37]), "+f"(d[38]), "+f"(d[39]), "+f"(d[40]), "+f"(d[41]), "+f"(d[42]), "+f"(d[43]), "+f"(d[44]), "+f"(d[45]), "+f"(d[46]), "+f"(d[47]), "+f"(d[48]), "+f"(d[49]), "+f"(d[50]), "+f"(d[51]), "+f"(d[52]), "+f"(d[53]), "+f"(d[54]), "+f"(d[55]), "+f"(d[56]), "+f"(d[57]), "+f"(d[58]), "+f"(d[59]), "+f"(d[60]), "+f"(d[61]), "+f"(d[62]), "+f"(d[63])
    : "l"(da), "l"(db), "r"(scale_d), "n"(TB));
}
template<int TB> __device__ __forceinline__ void wgmma_rs_n32(float (&d)[16], uint32_t a0, uint32_t a1, uint32_t a2, uint32_t a3, uint64_t db, int scale_d) {
  asm volatile("{\n.reg .pred p;\nsetp.ne.b32 p, %21, 0;\n"
    "wgmma.mma_async.sync.aligned.m64n32k16.f32.bf16.bf16 {%0, %1, %2, %3, %4, %5, %6, %7, %8, %9, %10, %11, %12, %13, %14, %15}, {%16, %17, %18, %19}, %20, p, 1, 1, %22;\n}\n"
    : "+f"(d[0]), "+f"(d[1]), "+f"(d[2]), "+f"(d[3]), "+f"(d[4]), "+f"(d[5]), "+f"(d[6]), "+f"(d[7]), "+f"(d[8]), "+f"(d[9]), "+f"(d[10]), "+f"(d[11]), "+f"(d[12]), "+f"(d[13]), "+f"(d[14]), "+f"(d[15])
    : "r"(a0), "r"(a1), "r"(a2), "r"(a3), "l"(db), "r"(scale_d), "n"(TB));
}
__device__ __forceinline__ void wgmma_pv_sel(float (&d)[64], const uint32_t (&p)[32], uint64_t db, int full, int acc, int wg) {
  asm volatile("{\n.reg .pred q, s, w;\n.reg .b64 t;\nsetp.eq.b32 w, %99, 0;\nsetp.ne.b32 s, %98, 0;\nsetp.eq.b32 q, %97, 0;\n@q bra.uni LH;\n"
    "wgmma.fence.sync.aligned;\n"
    "add.s64 t, %96, 0;\nwgmma.mma_async.sync.aligned.m64n128k16.f32.bf16.bf16 {%0, %1, %2, %3, %4, %5, %6, %7, %8, %9, %10, %11, %12, %13, %14, %15, %16, %17, %18, %19, %20, %21, %22, %23, %24, %25, %26, %27, %28, %29, %30, %31, %32, %33, %34, %35, %36, %37, %38, %39, %40, %41, %42, %43, %44, %45, %46, %47, %48, %49, %50, %51, %52, %53, %54, %55, %56, %57, %58, %59, %60, %61, %62, %63}, {%64, %65, %66, %67}, t, s, 1, 1, 1;\n"
    "add.s64 t, %96, 256;\nwgmma.mma_async.sync.aligned.m64n128k16.f32.bf16.bf16 {%0, %1, %2, %3, %4, %5, %6, %7, %8, %9, %10, %11, %12, %13, %14, %15, %16, %17, %18, %19, %20, %21, %22, %23, %24, %25, %26, %27, %28, %29, %30, %31, %32, %33, %34, %35, %36, %37, %38, %39, %40, %41, %42, %43, %44, %45, %46, %47, %48, %49, %50, %51, %52, %53, %54, %55, %56, %57, %58, %59, %60, %61, %62, %63}, {%68, %69, %70, %71}, t, 1, 1, 1, 1;\n"
    "add.s64 t, %96, 512;\nwgmma.mma_async.sync.aligned.m64n128k16.f32.bf16.bf16 {%0, %1, %2, %3, %4, %5, %6, %7, %8, %9, %10, %11, %12, %13, %14, %15, %16, %17, %18, %19, %20, %21, %22, %23, %24, %25, %26, %27, %28, %29, %30, %31, %32, %33, %34, %35, %36, %37, %38, %39, %40, %41, %42, %43, %44, %45, %46, %47, %48, %49, %50, %51, %52, %53, %54, %55, %56, %57, %58, %59, %60, %61, %62, %63}, {%72, %73, %74, %75}, t, 1, 1, 1, 1;\n"
    "add.s64 t, %96, 768;\nwgmma.mma_async.sync.aligned.m64n128k16.f32.bf16.bf16 {%0, %1, %2, %3, %4, %5, %6, %7, %8, %9, %10, %11, %12, %13, %14, %15, %16, %17, %18, %19, %20, %21, %22, %23, %24, %25, %26, %27, %28, %29, %30, %31, %32, %33, %34, %35, %36, %37, %38, %39, %40, %41, %42, %43, %44, %45, %46, %47, %48, %49, %50, %51, %52, %53, %54, %55, %56, %57, %58, %59, %60, %61, %62, %63}, {%76, %77, %78, %79}, t, 1, 1, 1, 1;\n"
    "add.s64 t, %96, 1024;\nwgmma.mma_async.sync.aligned.m64n128k16.f32.bf16.bf16 {%0, %1, %2, %3, %4, %5, %6, %7, %8, %9, %10, %11, %12, %13, %14, %15, %16, %17, %18, %19, %20, %21, %22, %23, %24, %25, %26, %27, %28, %29, %30, %31, %32, %33, %34, %35, %36, %37, %38, %39, %40, %41, %42, %43, %44, %45, %46, %47, %48, %49, %50, %51, %52, %53, %54, %55, %56, %57, %58, %59, %60, %61, %62, %63}, {%80, %81, %82, %83}, t, 1, 1, 1, 1;\n"
    "add.s64 t, %96, 1280;\nwgmma.mma_async.sync.aligned.m64n128k16.f32.bf16.bf16 {%0, %1, %2, %3, %4, %5, %6, %7, %8, %9, %10, %11, %12, %13, %14, %15, %16, %17, %18, %19, %20, %21, %22, %23, %24, %25, %26, %27, %28, %29, %30, %31, %32, %33, %34, %35, %36, %37, %38, %39, %40, %41, %42, %43, %44, %45, %46, %47, %48, %49, %50, %51, %52, %53, %54, %55, %56, %57, %58, %59, %60, %61, %62, %63}, {%84, %85, %86, %87}, t, 1, 1, 1, 1;\n"
    "@w bar.arrive 2, 256;\n@!w bar.arrive 1, 256;\n"
    "add.s64 t, %96, 1536;\nwgmma.mma_async.sync.aligned.m64n128k16.f32.bf16.bf16 {%0, %1, %2, %3, %4, %5, %6, %7, %8, %9, %10, %11, %12, %13, %14, %15, %16, %17, %18, %19, %20, %21, %22, %23, %24, %25, %26, %27, %28, %29, %30, %31, %32, %33, %34, %35, %36, %37, %38, %39, %40, %41, %42, %43, %44, %45, %46, %47, %48, %49, %50, %51, %52, %53, %54, %55, %56, %57, %58, %59, %60, %61, %62, %63}, {%88, %89, %90, %91}, t, 1, 1, 1, 1;\n"
    "add.s64 t, %96, 1792;\nwgmma.mma_async.sync.aligned.m64n128k16.f32.bf16.bf16 {%0, %1, %2, %3, %4, %5, %6, %7, %8, %9, %10, %11, %12, %13, %14, %15, %16, %17, %18, %19, %20, %21, %22, %23, %24, %25, %26, %27, %28, %29, %30, %31, %32, %33, %34, %35, %36, %37, %38, %39, %40, %41, %42, %43, %44, %45, %46, %47, %48, %49, %50, %51, %52, %53, %54, %55, %56, %57, %58, %59, %60, %61, %62, %63}, {%92, %93, %94, %95}, t, 1, 1, 1, 1;\n"
    "wgmma.commit_group.sync.aligned;\n"
    "bra.uni LE;\nLH:\n"
    "wgmma.fence.sync.aligned;\n"
    "add.s64 t, %96, 0;\nwgmma.mma_async.sync.aligned.m64n128k16.f32.bf16.bf16 {%0, %1, %2, %3, %4, %5, %6, %7, %8, %9, %10, %11, %12, %13, %14, %15, %16, %17, %18, %19, %20, %21, %22, %23, %24, %25, %26, %27, %28, %29, %30, %31, %32, %33, %34, %35, %36, %37, %38, %39, %40, %41, %42, %43, %44, %45, %46, %47, %48, %49, %50, %51, %52, %53, %54, %55, %56, %57, %58, %59, %60, %61, %62, %63}, {%80, %81, %82, %83}, t, s, 1, 1, 1;\n"
    "add.s64 t, %96, 256;\nwgmma.mma_async.sync.aligned.m64n128k16.f32.bf16.bf16 {%0, %1, %2, %3, %4, %5, %6, %7, %8, %9, %10, %11, %12, %13, %14, %15, %16, %17, %18, %19, %20, %21, %22, %23, %24, %25, %26, %27, %28, %29, %30, %31, %32, %33, %34, %35, %36, %37, %38, %39, %40, %41, %42, %43, %44, %45, %46, %47, %48, %49, %50, %51, %52, %53, %54, %55, %56, %57, %58, %59, %60, %61, %62, %63}, {%84, %85, %86, %87}, t, 1, 1, 1, 1;\n"
    "@w bar.arrive 2, 256;\n@!w bar.arrive 1, 256;\n"
    "add.s64 t, %96, 512;\nwgmma.mma_async.sync.aligned.m64n128k16.f32.bf16.bf16 {%0, %1, %2, %3, %4, %5, %6, %7, %8, %9, %10, %11, %12, %13, %14, %15, %16, %17, %18, %19, %20, %21, %22, %23, %24, %25, %26, %27, %28, %29, %30, %31, %32, %33, %34, %35, %36, %37, %38, %39, %40, %41, %42, %43, %44, %45, %46, %47, %48, %49, %50, %51, %52, %53, %54, %55, %56, %57, %58, %59, %60, %61, %62, %63}, {%88, %89, %90, %91}, t, 1, 1, 1, 1;\n"
    "add.s64 t, %96, 768;\nwgmma.mma_async.sync.aligned.m64n128k16.f32.bf16.bf16 {%0, %1, %2, %3, %4, %5, %6, %7, %8, %9, %10, %11, %12, %13, %14, %15, %16, %17, %18, %19, %20, %21, %22, %23, %24, %25, %26, %27, %28, %29, %30, %31, %32, %33, %34, %35, %36, %37, %38, %39, %40, %41, %42, %43, %44, %45, %46, %47, %48, %49, %50, %51, %52, %53, %54, %55, %56, %57, %58, %59, %60, %61, %62, %63}, {%92, %93, %94, %95}, t, 1, 1, 1, 1;\n"
    "wgmma.commit_group.sync.aligned;\n"
    "LE:\n}\n"
    : "+f"(d[0]), "+f"(d[1]), "+f"(d[2]), "+f"(d[3]), "+f"(d[4]), "+f"(d[5]), "+f"(d[6]), "+f"(d[7]), "+f"(d[8]), "+f"(d[9]), "+f"(d[10]), "+f"(d[11]), "+f"(d[12]), "+f"(d[13]), "+f"(d[14]), "+f"(d[15]), "+f"(d[16]), "+f"(d[17]), "+f"(d[18]), "+f"(d[19]), "+f"(d[20]), "+f"(d[21]), "+f"(d[22]), "+f"(d[23]), "+f"(d[24]), "+f"(d[25]), "+f"(d[26]), "+f"(d[27]), "+f"(d[28]), "+f"(d[29]), "+f"(d[30]), "+f"(d[31]), "+f"(d[32]), "+f"(d[33]), "+f"(d[34]), "+f"(d[35]), "+f"(d[36]), "+f"(d[37]), "+f"(d[38]), "+f"(d[39]), "+f"(d[40]), "+f"(d[41]), "+f"(d[42]), "+f"(d[43]), "+f"(d[44]), "+f"(d[45]), "+f"(d[46]), "+f"(d[47]), "+f"(d[48]), "+f"(d[49]), "+f"(d[50]), "+f"(d[51]), "+f"(d[52]), "+f"(d[53]), "+f"(d[54]), "+f"(d[55]), "+f"(d[56]), "+f"(d[57]), "+f"(d[58]), "+f"(d[59]), "+f"(d[60]), "+f"(d[61]), "+f"(d[62]), "+f"(d[63])
    : "r"(p[0]), "r"(p[1]), "r"(p[2]), "r"(p[3]), "r"(p[4]), "r"(p[5]), "r"(p[6]), "r"(p[7]), "r"(p[8]), "r"(p[9]), "r"(p[10]), "r"(p[11]), "r"(p[12]), "r"(p[13]), "r"(p[14]), "r"(p[15]), "r"(p[16]), "r"(p[17]), "r"(p[18]), "r"(p[19]), "r"(p[20]), "r"(p[21]), "r"(p[22]), "r"(p[23]), "r"(p[24]), "r"(p[25]), "r"(p[26]), "r"(p[27]), "r"(p[28]), "r"(p[29]), "r"(p[30]), "r"(p[31]), "l"(db), "r"(full), "r"(acc), "r"(wg) : "memory");
}

constexpr int NCTA = 132, NREG = 128;
constexpr int UNIT = 16384, NUNIT = 14;
constexpr uint32_t SMEM_BASE = 1024;
constexpr int SM_BAR = NUNIT * UNIT;
constexpr int SM_GATE = SM_BAR + 1024;
constexpr int SMEM_BYTES = SM_BAR + 1536;
constexpr int UPITCH = 4160, UCH = 2 * UPITCH;
constexpr float QSCALE = 0.08838834764831845f * 1.4426950408889634f;
constexpr float BOUND2 = 60.f * 60.f / 1.15f;
#define CONV_REG 5
constexpr int C_KV = 0;
constexpr int C_CTX = 32;
constexpr int C_U = 48;
constexpr int C_Z = 80;
constexpr int C_GATE = 88;
constexpr int C_EXIT = 89;
#define ATT_SPLIT 4
#define Z_AT 60
#define PRE_SLEEP 300
#define GATE_SLEEP 1000
#define OC_S0 2
#define OC_S1 11
#define OC_L0 18
#define OC_L1 18
#define ST_1 4
#define ST_D 2
#define SCH_KV 0x6665544433221100ull
#define SCH_Q 0x6665544433221100ull
#define NK_AT 1
#ifndef NV_AT
#define NV_AT 3
#endif
#define CHK_D 11
#define FGAP 600
#define FGAP2 200
constexpr int PRE_EARLY = 2, NFIRST = 4;
constexpr int C_WAR = 96;
constexpr int C_NUM = 112;
constexpr int CSTRIDE = 32;
constexpr int SM_KMAX = SM_BAR + 640, SM_DUMMY = SM_BAR + 648, SM_PRE = SM_BAR + 112, SM_SIG = SM_BAR + 256, SM_RDY = SM_BAR + 384;
enum { SIG_KV = 0, SIG_CTX = 2, SIG_Z = 4, SIG_DONE = 8, SIG_WAR = 9, SIG_ATT = 10 };
enum { RDY_KV = 0, RDY_CTX = 2, RDY_WAR = 4, RDY_G = 5, RDY_X = 6, RDY_AUX = 7, RDY_U = 8, RDY_Z = 9 };
enum { PH_PRE = 1, PH_KV = 2, PH_ATT = 4, PH_CONV = 8, PH_OUT = 16, PH_ALL = 31 };

constexpr uint32_t T_CTX = 0, T_KV = 16 * 32 * 32768, T_BYTES = T_KV + 32 * 16 * 65536;
__device__ __align__(1024) uint8_t g_T[T_BYTES];
__device__ __align__(1024) uint8_t g_u[1024 * UCH];
__device__ __align__(1024) __nv_bfloat16 g_z[1024 * 2048];
__device__ __align__(1024) float g_gate[2048];
__device__ __align__(1024) float g_kn2[32 * 128];
__device__ __align__(1024) unsigned g_cnt[C_NUM * CSTRIDE];

struct __align__(64) Maps { CUtensorMap c, wk, wv, x, wq, wo, h, z, out, ctx, k, v; };
struct Params {
  const __nv_bfloat16 *x, *shift, *D, *gw;
  __nv_bfloat16* out;
};

__device__ __forceinline__ void wg_fence() { asm volatile("wgmma.fence.sync.aligned;" ::: "memory"); }
__device__ __forceinline__ void wg_commit() { asm volatile("wgmma.commit_group.sync.aligned;" ::: "memory"); }
template<int N> __device__ __forceinline__ void wg_wait() { asm volatile("wgmma.wait_group.sync.aligned %0;" :: "n"(N) : "memory"); }
__device__ __forceinline__ uint64_t odesc(uint32_t addr, uint32_t lbo, uint32_t sbo, uint32_t swz) {
  uint64_t d = (uint64_t)(addr >> 4) + (((uint64_t)(lbo >> 4) << 16) | ((uint64_t)(sbo >> 4) << 32) | ((uint64_t)swz << 62));
  asm volatile("" : "+l"(d));
  return d;
}
__device__ __forceinline__ void mbar_init(uint32_t bar, int cnt) { asm volatile("mbarrier.init.shared::cta.b64 [%0], %1;" :: "r"(bar), "r"(cnt)); }
__device__ __forceinline__ void mbar_expect(uint32_t bar, uint32_t bytes) { asm volatile("mbarrier.arrive.expect_tx.shared::cta.b64 _, [%0], %1;" :: "r"(bar), "r"(bytes) : "memory"); }
__device__ __forceinline__ void mbar_arrive(uint32_t bar) { asm volatile("mbarrier.arrive.shared::cta.b64 _, [%0];" :: "r"(bar) : "memory"); }
__device__ __forceinline__ void mbar_wait(uint32_t bar, uint32_t parity) {
  asm volatile("{\n.reg .pred p;\nLW:\nmbarrier.try_wait.parity.shared::cta.b64 p, [%0], %1;\n@!p bra LW;\n}\n" :: "r"(bar), "r"(parity) : "memory");
}
__device__ __forceinline__ void mbar_wait_slow(uint32_t bar, uint32_t parity) {
  asm volatile("{\n.reg .pred p;\n.reg .u32 n;\nmov.u32 n, 0;\n"
    "LW:\nmbarrier.test_wait.parity.shared::cta.b64 p, [%0], %1;\n@p bra LD;\n"
    "nanosleep.u32 128;\nadd.u32 n, n, 1;\nsetp.lt.u32 p, n, 4194304;\n@p bra LW;\ntrap;\nLD:\n}\n" :: "r"(bar), "r"(parity) : "memory");
}
__device__ __forceinline__ void mbar_wait_all(uint32_t bar, uint32_t parity) {
  asm volatile("{\n.reg .pred p, q;\nLW:\nmbarrier.try_wait.parity.shared::cta.b64 p, [%0], %1;\nvote.sync.all.pred q, p, 0xffffffff;\n@!q bra.uni LW;\n}\n" :: "r"(bar), "r"(parity) : "memory");
}
__device__ __forceinline__ void cnt_wait(const unsigned* p, unsigned target) {
  asm volatile("{\n.reg .pred p;\n.reg .u32 n, v;\nmov.u32 n, 0;\n"
    "LW:\nld.relaxed.gpu.global.u32 v, [%0];\nsetp.ge.u32 p, v, %1;\n@p bra LD;\n"
    "nanosleep.u32 64;\nadd.u32 n, n, 1;\nsetp.lt.u32 p, n, 4194304;\n@p bra LW;\ntrap;\nLD:\nfence.acquire.gpu;\nfence.proxy.async.global;\n}\n" :: "l"(p), "r"(target) : "memory");
}
__device__ __forceinline__ void cnt_signal(unsigned* p, int lane) {
  __syncwarp();
  if (lane == 0) asm volatile("red.release.gpu.global.add.u32 [%0], 1;" :: "l"(p) : "memory");
}
__device__ __forceinline__ void cnt_publish(unsigned* p, unsigned n, bool fence) {
  if (fence) asm volatile("fence.release.gpu;" ::: "memory");
  asm volatile("red.relaxed.gpu.global.add.u32 [%0], %1;" :: "l"(p), "r"(n) : "memory");
}
__device__ __forceinline__ uint64_t pol_first() { uint64_t p; asm("createpolicy.fractional.L2::evict_first.b64 %0, 1.0;" : "=l"(p)); return p; }
__device__ __forceinline__ void bulk_g2s(uint32_t dst, const void* src, uint32_t bytes, uint32_t bar, bool stream = false) {
  if (stream) asm volatile("cp.async.bulk.shared::cluster.global.mbarrier::complete_tx::bytes.L2::cache_hint [%0], [%1], %2, [%3], %4;" :: "r"(dst), "l"(src), "r"(bytes), "r"(bar), "l"(pol_first()) : "memory");
  else asm volatile("cp.async.bulk.shared::cluster.global.mbarrier::complete_tx::bytes [%0], [%1], %2, [%3];" :: "r"(dst), "l"(src), "r"(bytes), "r"(bar) : "memory");
}
__device__ __forceinline__ void tma2d(uint32_t dst, const CUtensorMap* m, int x, int y, uint32_t bar, bool stream = false) {
  if (stream) asm volatile("cp.async.bulk.tensor.2d.shared::cluster.global.mbarrier::complete_tx::bytes.L2::cache_hint [%0], [%1, {%3, %4}], [%2], %5;" :: "r"(dst), "l"(m), "r"(bar), "r"(x), "r"(y), "l"(pol_first()) : "memory");
  else asm volatile("cp.async.bulk.tensor.2d.shared::cluster.global.mbarrier::complete_tx::bytes [%0], [%1, {%3, %4}], [%2];" :: "r"(dst), "l"(m), "r"(bar), "r"(x), "r"(y) : "memory");
}
__device__ __forceinline__ void tma3d(uint32_t dst, const CUtensorMap* m, int x, int y, int z, uint32_t bar, bool stream = false) {
  if (stream) asm volatile("cp.async.bulk.tensor.3d.shared::cluster.global.mbarrier::complete_tx::bytes.L2::cache_hint [%0], [%1, {%3, %4, %5}], [%2], %6;" :: "r"(dst), "l"(m), "r"(bar), "r"(x), "r"(y), "r"(z), "l"(pol_first()) : "memory");
  else asm volatile("cp.async.bulk.tensor.3d.shared::cluster.global.mbarrier::complete_tx::bytes [%0], [%1, {%3, %4, %5}], [%2];" :: "r"(dst), "l"(m), "r"(bar), "r"(x), "r"(y), "r"(z) : "memory");
}
__device__ __forceinline__ void tma4d(uint32_t dst, const CUtensorMap* m, int x, int y, int z, int w, uint32_t bar, bool stream = false) {
  if (stream) asm volatile("cp.async.bulk.tensor.4d.shared::cluster.global.mbarrier::complete_tx::bytes.L2::cache_hint [%0], [%1, {%3, %4, %5, %6}], [%2], %7;" :: "r"(dst), "l"(m), "r"(bar), "r"(x), "r"(y), "r"(z), "r"(w), "l"(pol_first()) : "memory");
  else asm volatile("cp.async.bulk.tensor.4d.shared::cluster.global.mbarrier::complete_tx::bytes [%0], [%1, {%3, %4, %5, %6}], [%2];" :: "r"(dst), "l"(m), "r"(bar), "r"(x), "r"(y), "r"(z), "r"(w) : "memory");
}
__device__ __forceinline__ void bulk_g2s_mc(uint32_t dst, const void* src, uint32_t bytes, uint32_t bar, bool stream = false) {
  if (stream) asm volatile("cp.async.bulk.shared::cluster.global.mbarrier::complete_tx::bytes.multicast::cluster.L2::cache_hint [%0], [%1], %2, [%3], %4, %5;" :: "r"(dst), "l"(src), "r"(bytes), "r"(bar), "h"((uint16_t)3), "l"(pol_first()) : "memory");
  else asm volatile("cp.async.bulk.shared::cluster.global.mbarrier::complete_tx::bytes.multicast::cluster [%0], [%1], %2, [%3], %4;" :: "r"(dst), "l"(src), "r"(bytes), "r"(bar), "h"((uint16_t)3) : "memory");
}
__device__ __forceinline__ void tma2d_mc(uint32_t dst, const CUtensorMap* m, int x, int y, uint32_t bar, bool stream = false) {
  if (stream) asm volatile("cp.async.bulk.tensor.2d.shared::cluster.global.mbarrier::complete_tx::bytes.multicast::cluster.L2::cache_hint [%0], [%1, {%3, %4}], [%2], %5, %6;" :: "r"(dst), "l"(m), "r"(bar), "r"(x), "r"(y), "h"((uint16_t)3), "l"(pol_first()) : "memory");
  else asm volatile("cp.async.bulk.tensor.2d.shared::cluster.global.mbarrier::complete_tx::bytes.multicast::cluster [%0], [%1, {%3, %4}], [%2], %5;" :: "r"(dst), "l"(m), "r"(bar), "r"(x), "r"(y), "h"((uint16_t)3) : "memory");
}
__device__ __forceinline__ void tma3d_mc(uint32_t dst, const CUtensorMap* m, int x, int y, int z, uint32_t bar, bool stream = false) {
  if (stream) asm volatile("cp.async.bulk.tensor.3d.shared::cluster.global.mbarrier::complete_tx::bytes.multicast::cluster.L2::cache_hint [%0], [%1, {%3, %4, %5}], [%2], %6, %7;" :: "r"(dst), "l"(m), "r"(bar), "r"(x), "r"(y), "r"(z), "h"((uint16_t)3), "l"(pol_first()) : "memory");
  else asm volatile("cp.async.bulk.tensor.3d.shared::cluster.global.mbarrier::complete_tx::bytes.multicast::cluster [%0], [%1, {%3, %4, %5}], [%2], %6;" :: "r"(dst), "l"(m), "r"(bar), "r"(x), "r"(y), "r"(z), "h"((uint16_t)3) : "memory");
}
__device__ __forceinline__ void map_pf(const CUtensorMap* m) { asm volatile("prefetch.tensormap [%0];" :: "l"(m) : "memory"); }
__device__ __forceinline__ bool elect() {
  uint32_t r; asm volatile("{\n.reg .pred p;\nelect.sync _|p, 0xffffffff;\nselp.u32 %0, 1, 0, p;\n}\n" : "=r"(r)); return r != 0;
}
__device__ __forceinline__ void cluster_arrive() { asm volatile("barrier.cluster.arrive;" ::: "memory"); }
__device__ __forceinline__ void cluster_wait() { asm volatile("barrier.cluster.wait;" ::: "memory"); }
__device__ __forceinline__ void bar_sync(int id, int n) { asm volatile("bar.sync %0, %1;" :: "r"(id), "r"(n) : "memory"); }
__device__ __forceinline__ void bar_arrive(int id, int n) { asm volatile("bar.arrive %0, %1;" :: "r"(id), "r"(n) : "memory"); }
__device__ __forceinline__ void fence_async_smem() { asm volatile("fence.proxy.async.shared::cta;" ::: "memory"); }
__device__ __forceinline__ float ex2(float x) { float y; asm("ex2.approx.ftz.f32 %0, %1;" : "=f"(y) : "f"(x)); return y; }
__device__ __forceinline__ float rcp(float x) { float y; asm("rcp.approx.ftz.f32 %0, %1;" : "=f"(y) : "f"(x)); return y; }
__device__ __forceinline__ uint32_t pack_bf16(float lo, float hi) { uint32_t r; asm("cvt.rn.bf16x2.f32 %0, %1, %2;" : "=r"(r) : "f"(hi), "f"(lo)); return r; }
__device__ __forceinline__ uint32_t hmul2(uint32_t a, uint32_t b) { uint32_t r; asm("mul.rn.bf16x2 %0, %1, %2;" : "=r"(r) : "r"(a), "r"(b)); return r; }
__device__ __forceinline__ uint32_t hadd2(uint32_t a, uint32_t b) { uint32_t r; asm("add.rn.bf16x2 %0, %1, %2;" : "=r"(r) : "r"(a), "r"(b)); return r; }
__device__ __forceinline__ uint32_t hfma2(uint32_t a, uint32_t b, uint32_t c) { uint32_t r; asm("fma.rn.bf16x2 %0, %1, %2, %3;" : "=r"(r) : "r"(a), "r"(b), "r"(c)); return r; }
__device__ __forceinline__ float bf_lo(uint32_t a) { return __uint_as_float(a << 16); }
__device__ __forceinline__ float bf_hi(uint32_t a) { return __uint_as_float(a & 0xffff0000u); }
__device__ __forceinline__ uint32_t lds32(uint32_t a) { uint32_t v; asm volatile("ld.shared.u32 %0, [%1];" : "=r"(v) : "r"(a) : "memory"); return v; }
__device__ __forceinline__ float2 lds64f(uint32_t a) { float2 v; asm volatile("ld.shared.v2.f32 {%0,%1}, [%2];" : "=f"(v.x), "=f"(v.y) : "r"(a) : "memory"); return v; }
__device__ __forceinline__ uint4 lds128(uint32_t a) { uint4 v; asm volatile("ld.shared.v4.u32 {%0,%1,%2,%3}, [%4];" : "=r"(v.x), "=r"(v.y), "=r"(v.z), "=r"(v.w) : "r"(a) : "memory"); return v; }
__device__ __forceinline__ void sts64f(uint32_t a, float x, float y) { asm volatile("st.shared.v2.f32 [%0], {%1,%2};" :: "r"(a), "f"(x), "f"(y) : "memory"); }
template<int OFF> __device__ __forceinline__ void sts128o(uint32_t a, uint4 v) { asm volatile("st.shared.v4.u32 [%0+%5], {%1,%2,%3,%4};" :: "r"(a), "r"(v.x), "r"(v.y), "r"(v.z), "r"(v.w), "n"(OFF) : "memory"); }
__device__ __forceinline__ void ldsm4(uint32_t a, uint32_t& r0, uint32_t& r1, uint32_t& r2, uint32_t& r3) {
  asm volatile("ldmatrix.sync.aligned.m8n8.x4.shared.b16 {%0,%1,%2,%3}, [%4];" : "=r"(r0), "=r"(r1), "=r"(r2), "=r"(r3) : "r"(a) : "memory");
}
__device__ __forceinline__ void ldsm4t(uint32_t a, uint32_t& r0, uint32_t& r1, uint32_t& r2, uint32_t& r3) {
  asm volatile("ldmatrix.sync.aligned.m8n8.x4.trans.shared.b16 {%0,%1,%2,%3}, [%4];" : "=r"(r0), "=r"(r1), "=r"(r2), "=r"(r3) : "r"(a) : "memory");
}
__device__ __forceinline__ void stsm4(uint32_t a, uint32_t r0, uint32_t r1, uint32_t r2, uint32_t r3) {
  asm volatile("stmatrix.sync.aligned.m8n8.x4.shared.b16 [%0], {%1,%2,%3,%4};" :: "r"(a), "r"(r0), "r"(r1), "r"(r2), "r"(r3) : "memory");
}
template<int N> __device__ __forceinline__ void fence_regs(float (&d)[N]) {
#pragma unroll
  for (int i = 0; i < N; i++) asm volatile("" : "+f"(d[i]) :: "memory");
}
template<int N> __device__ __forceinline__ void fence_regs(uint32_t (&d)[N]) {
#pragma unroll
  for (int i = 0; i < N; i++) asm volatile("" : "+r"(d[i]) :: "memory");
}
__device__ __forceinline__ void sched_fence(float x, uint32_t dummy) {
  asm volatile("{\n.reg .pred p;\nsetp.eq.u32 p, %0, 0x7fc12345;\n@p st.shared.u32 [%1], %0;\n}\n" :: "r"(__float_as_uint(x)), "r"(dummy) : "memory");
}
#define PTRACE 0
#define TS(role, i)
#define TSA(i)
#define TSS(i)
#define TSK(i)
#define TSO(i)

#define SHADOW if (gridDim.y == 1)

struct Prod {
  uint32_t base, mask; int lane, nt;
  __device__ __forceinline__ uint32_t full(int u) const { return base + SM_BAR + 8 * u; }
  __device__ __forceinline__ uint32_t addr(int u) const { return base + u * UNIT; }
  __device__ __forceinline__ void acquire(int u, int n) {
    const int v = u + min(lane, n - 1);
    mbar_wait_all(base + SM_BAR + 128 + 8 * v, mask >> v);
    mask ^= ((1u << n) - 1) << u;
  }
  __device__ __forceinline__ void acquire_slow(int u, int n) {
    for (int i = 0; i < n; i++) mbar_wait_slow(base + SM_BAR + 128 + 8 * (u + i), mask >> (u + i));
    mask ^= ((1u << n) - 1) << u;
  }
};
struct Cons {
  uint32_t base, rel, mask; int lane, warp, wg, nt;
  __device__ __forceinline__ uint32_t addr(int u) const { return base + u * UNIT; }
  __device__ __forceinline__ static uint32_t daddr(int u) { return SMEM_BASE + u * UNIT; }
  __device__ __forceinline__ void wait(int u) { mbar_wait(base + SM_BAR + 8 * u, mask >> u); mask ^= 1u << u; }
  __device__ __forceinline__ void skip(int u) { mask ^= 1u << u; }
  __device__ __forceinline__ void release(int u, int n) {
    asm volatile("{\n.reg .pred p;\nsetp.lt.s32 p, %1, %2;\n@p mbarrier.arrive.shared::cluster.b64 _, [%0];\n}\n" :: "r"(rel + 8 * u), "r"(lane & 15), "r"(n) : "memory");
  }
  __device__ __forceinline__ void release2(int u) {
    asm volatile("{\n.reg .pred p;\nsetp.eq.s32 p, %1, 0;\n@p mbarrier.arrive.shared::cluster.b64 _, [%0], 2;\n}\n" :: "r"(rel + 8 * u), "r"(lane & 15) : "memory");
  }
  __device__ __forceinline__ void signal(int i) {
    __syncwarp();
    asm volatile("{\n.reg .pred p;\nsetp.eq.s32 p, %1, 0;\n@p mbarrier.arrive.shared::cta.b64 _, [%0];\n}\n" :: "r"(base + SM_SIG + 8 * i), "r"(lane) : "memory");
  }
  __device__ __forceinline__ void turn() { asm volatile("{\n.reg .pred p;\nsetp.eq.s32 p, %0, 0;\n@p bar.sync 1, 256;\n@!p bar.sync 2, 256;\n}\n" :: "r"(wg) : "memory"); }
  __device__ __forceinline__ void pass() { asm volatile("{\n.reg .pred p;\nsetp.eq.s32 p, %0, 0;\n@p bar.arrive 2, 256;\n@!p bar.arrive 1, 256;\n}\n" :: "r"(wg) : "memory"); }
  __device__ __forceinline__ void sync() { asm volatile("{\n.reg .pred p;\nsetp.eq.s32 p, %0, 0;\n@p bar.sync 3, 128;\n@!p bar.sync 4, 128;\n}\n" :: "r"(wg) : "memory"); }
};
__device__ __forceinline__ int gemm_unit(int ks) { return 3 * (ks & 3); }
template<int MASK> __device__ __forceinline__ int kv_slot(int h) { return MASK == PH_ALL ? h & 15 : h; }
__device__ __forceinline__ int out_mb(int cta) { return cta >> 3; }
__device__ __forceinline__ int out_nb(int cta) { return cta & 7; }
template<int MASK> constexpr int CV_REG = MASK == PH_ALL ? CONV_REG : 6;
template<int MASK> constexpr int CV_EXTRA = (1024 - NREG * CV_REG<MASK>) / (NCTA - NREG);
template<int MASK> __device__ __forceinline__ int conv_channel(int cta, int i) {
  return cta < NREG ? CV_EXTRA<MASK> * (NCTA - NREG) + cta * CV_REG<MASK> + i : (i >> 1) * 8 + (cta - NREG) * 2 + (i & 1);
}

template<int OFF, int N> __device__ __forceinline__ void pack_chunk(const float (&a)[N], float sc0, float sc1, uint4& v0, uint4& v1) {
  v0.x = pack_bf16(a[OFF + 0] * sc0, a[OFF + 1] * sc0); v0.y = pack_bf16(a[OFF + 4] * sc0, a[OFF + 5] * sc0);
  v0.z = pack_bf16(a[OFF + 8] * sc0, a[OFF + 9] * sc0); v0.w = pack_bf16(a[OFF + 12] * sc0, a[OFF + 13] * sc0);
  v1.x = pack_bf16(a[OFF + 2] * sc1, a[OFF + 3] * sc1); v1.y = pack_bf16(a[OFF + 6] * sc1, a[OFF + 7] * sc1);
  v1.z = pack_bf16(a[OFF + 10] * sc1, a[OFF + 11] * sc1); v1.w = pack_bf16(a[OFF + 14] * sc1, a[OFF + 15] * sc1);
}
template<int OFF, int N> __device__ __forceinline__ void pack_chunk(const float (&a)[N], uint4& v0, uint4& v1) {
  v0.x = pack_bf16(a[OFF + 0], a[OFF + 1]); v0.y = pack_bf16(a[OFF + 4], a[OFF + 5]);
  v0.z = pack_bf16(a[OFF + 8], a[OFF + 9]); v0.w = pack_bf16(a[OFF + 12], a[OFF + 13]);
  v1.x = pack_bf16(a[OFF + 2], a[OFF + 3]); v1.y = pack_bf16(a[OFF + 6], a[OFF + 7]);
  v1.z = pack_bf16(a[OFF + 10], a[OFF + 11]); v1.w = pack_bf16(a[OFF + 14], a[OFF + 15]);
}
__device__ __forceinline__ void sq_acc(const uint4& v, uint32_t& a) { a = hfma2(v.x, v.x, a); a = hfma2(v.y, v.y, a); a = hfma2(v.z, v.z, a); a = hfma2(v.w, v.w, a); }
__device__ __forceinline__ float norm2_max(uint32_t a0, uint32_t a1) {
  float n0 = bf_lo(a0) + bf_hi(a0), n1 = bf_lo(a1) + bf_hi(a1);
  n0 += __shfl_xor_sync(~0u, n0, 1); n1 += __shfl_xor_sync(~0u, n1, 1);
  n0 += __shfl_xor_sync(~0u, n0, 2); n1 += __shfl_xor_sync(~0u, n1, 2);
  return __uint_as_float(__reduce_max_sync(~0u, max(__float_as_uint(n0) & 0x7fffffffu, __float_as_uint(n1) & 0x7fffffffu)));
}

struct Pend { uint4 lo[8], hi[8]; };
__device__ __forceinline__ uint32_t ctx_off(const Cons& c, int h, int qb, int rowhalf) { return T_CTX + (qb * 32 + h) * 32768 + (rowhalf * 4 + c.warp) * 4096; }
__device__ __forceinline__ uint32_t kv_off(const Cons& c, int blk) { return T_KV + blk * 65536 + (c.wg * 4 + c.warp) * 4096; }
__device__ __forceinline__ void pin(uint4 (&v)[8]) {
#pragma unroll
  for (int i = 0; i < 8; i++) asm volatile("" : "+r"(v[i].x), "+r"(v[i].y), "+r"(v[i].z), "+r"(v[i].w) :: "memory");
}
__device__ __forceinline__ void pack_o(const float (&o)[64], float i0, float i1, uint4 (&v)[8]) {
  pack_chunk<0>(o, i0, i1, v[0], v[1]); pack_chunk<16>(o, i0, i1, v[2], v[3]);
  pack_chunk<32>(o, i0, i1, v[4], v[5]); pack_chunk<48>(o, i0, i1, v[6], v[7]);
  pin(v);
}
__device__ __forceinline__ uint32_t atom_off(int lane) { return (lane >> 2) * 64 + (((lane ^ (lane >> 3)) & 3) << 4); }
template<int J0, int J1> __device__ __forceinline__ void tile_store(const uint4 (&v)[8], uint32_t dst, int lane) {
  uint8_t* d = g_T + (dst + atom_off(lane));
#pragma unroll
  for (int j = J0; j < J1; j++) { *(uint4*)(d + j * 512) = v[2 * j]; *(uint4*)(d + j * 512 + 2048) = v[2 * j + 1]; }
}
template<int I0, int I1> __device__ __forceinline__ void tile_store_if(bool on, const uint4 (&v)[8], const uint8_t* dst) {
  if constexpr (I0 < I1) {
    asm volatile("{\n.reg .pred p;\nsetp.ne.b32 p, %5, 0;\n@p st.v4.u32 [%0+%6], {%1,%2,%3,%4};\n}\n"
      :: "l"(dst), "r"(v[I0].x), "r"(v[I0].y), "r"(v[I0].z), "r"(v[I0].w), "r"((int)on), "n"((I0 >> 1) * 512 + (I0 & 1) * 2048) : "memory");
    tile_store_if<I0 + 1, I1>(on, v, dst);
  }
}
__device__ __forceinline__ float tile_norm2(const uint4 (&v)[8]) {
  uint32_t n0 = 0, n1 = 0, n2 = 0, n3 = 0;
#pragma unroll
  for (int j = 0; j < 2; j++) { sq_acc(v[2 * j], n0); sq_acc(v[2 * j + 1], n1); sq_acc(v[2 * j + 4], n2); sq_acc(v[2 * j + 5], n3); }
  return norm2_max(hadd2(n0, n2), hadd2(n1, n3));
}
template<uint64_t SCHED, bool FIRST> __device__ __forceinline__ void out_piece(Cons& c, Pend& w, uint32_t dst, int blk, float& kn, int ks, bool both) {
  uint8_t* d = g_T + (dst + atom_off(c.lane));
#pragma unroll
  for (int i = 0; i < 16; i++) {
    const int at = (SCHED >> (4 * i)) & 15;
    if (FIRST ? at == 0 : (at > 0 && ks == at && (i < 8 || both))) *(uint4*)(d + (i >> 3) * 32768 + ((i >> 1) & 3) * 512 + (i & 1) * 2048) = i < 8 ? w.lo[i & 7] : w.hi[i & 7];
  }
  if (FIRST || !both) return;
  if (ks == NK_AT) kn = tile_norm2(w.lo);
  if (ks == NV_AT) {
    const float vn = tile_norm2(w.hi);
    if (c.lane == 0) g_kn2[blk * 8 + c.wg * 4 + c.warp] = (vn <= 1.0e20f && vn >= 1.0e-20f) ? kn : __uint_as_float(0x7f800000u);
  }
}
template<bool FIRST> __device__ __forceinline__ void kv_issue(Cons& c, float (&acc)[128], int u) {
  const uint64_t da = odesc(c.daddr(u) + c.wg * 8192, 16, 1024, 1), db = odesc(c.daddr(u + 1), 8192, 1024, 1);
  TSK(c.nt + 1);
  c.turn();
  TSK(c.nt + 2);
  wg_fence();
#pragma unroll
  for (int kk = 0; kk < 4; kk++) wgmma_ss_n256<1>(acc, da + kk * 2, db + kk * 128, !(FIRST && kk == 0));
  wg_commit();
  c.pass();
  TSK(c.nt + 3); c.nt += 4;
}
template<bool NEXT> __device__ __forceinline__ void cons_kv(Cons& c, int h, int blk, int g, Pend& w, bool pend_o) {
#pragma unroll 1
  for (int tile = 0; tile < 2; tile++) {
    float acc[128];
    if (tile == 0) c.wait(0);
    if (tile == 0 && h < 16) TS(c.wg, 16);
    kv_issue<true>(c, acc, 0);
    c.release(9, tile == 1 ? 3 : 0);
    if (tile == 1 && pend_o) mbar_wait(c.base + SM_RDY + 8 * RDY_WAR, 0);
    const uint32_t dst = tile ? kv_off(c, blk) : ctx_off(c, h - 16, g, 1 - c.wg);
    float kn = 0.f;
    if (tile == 1 || pend_o) out_piece<SCH_KV, true>(c, w, dst, blk, kn, 0, false);
#pragma unroll 1
    for (int ks = 1; ks < 8; ks++) {
      const int u = gemm_unit(ks);
      c.wait(u);
      TSK(c.nt);
      wg_wait<0>();
      c.release(gemm_unit(ks - 1), 3);
      kv_issue<false>(c, acc, u);
      if (tile == 1 || pend_o) { out_piece<SCH_KV, false>(c, w, dst, blk, kn, ks, tile); if (ks == ((SCH_KV >> 28) & 15) && tile == 0) c.signal(SIG_CTX); }
    }
    if (NEXT || tile == 0) c.wait(0);
    wg_wait<0>(); fence_regs(acc);
    TSK(c.nt);
    if (!NEXT) c.release(9, tile == 1 ? 3 : 0);
    pack_chunk<0>(acc, w.lo[0], w.lo[1]);  pack_chunk<16>(acc, w.lo[2], w.lo[3]); pack_chunk<32>(acc, w.lo[4], w.lo[5]); pack_chunk<48>(acc, w.lo[6], w.lo[7]);
    pack_chunk<64>(acc, w.hi[0], w.hi[1]); pack_chunk<80>(acc, w.hi[2], w.hi[3]); pack_chunk<96>(acc, w.hi[4], w.hi[5]); pack_chunk<112>(acc, w.hi[6], w.hi[7]);
    pin(w.lo); pin(w.hi);
  }
}
template<bool FIRST> __device__ __forceinline__ void q_issue(Cons& c, float (&a)[64], float (&b)[64], int u) {
  const uint64_t da = odesc(c.daddr(u) + c.wg * 8192, 16, 1024, 1), db = odesc(c.daddr(u + 2), 8192, 1024, 1);
  const uint64_t da2 = odesc(c.daddr(u + 1) + (1 - c.wg) * 8192, 16, 1024, 1);
  TSK(c.nt + 1);
  c.turn();
  TSK(c.nt + 2);
  wg_fence();
#pragma unroll
  for (int kk = 0; kk < 4; kk++) wgmma_ss_n128<1>(a, da + kk * 2, db + kk * 128, !(FIRST && kk == 0));
#pragma unroll
  for (int kk = 0; kk < 4; kk++) wgmma_ss_n128<1>(b, da2 + kk * 2, db + kk * 128, !(FIRST && kk == 0));
  wg_commit();
  c.pass();
  TSK(c.nt + 3); c.nt += 4;
}
__device__ __forceinline__ void q_step(Cons& c, float (&d)[64], int ua, int ub, int rowhalf) {
  const uint64_t da = odesc(c.daddr(ua) + rowhalf * 8192, 16, 1024, 1), db = odesc(c.daddr(ub), 8192, 1024, 1);
#pragma unroll
  for (int kk = 0; kk < 4; kk++) wgmma_ss_n128<1>(d, da + kk * 2, db + kk * 128, 1);
}
template<bool PEND_KV> __device__ __forceinline__ void cons_q(Cons& c, int h, int blk, Pend& w, float (&b)[64]) {
  float a[64], kn = 0.f;
  if (!PEND_KV) c.wait(0);
  q_issue<true>(c, a, b, 0);
  if (PEND_KV) { c.release(9, 3); out_piece<SCH_Q, true>(c, w, kv_off(c, blk), blk, kn, 0, true); }
#pragma unroll 1
  for (int ks = 1; ks < 14; ks++) {
    const int u = gemm_unit(ks);
    c.wait(u);
    TSK(c.nt);
    wg_wait<0>();
    c.release(gemm_unit(ks - 1), 3);
    q_issue<false>(c, a, b, u);
    if (PEND_KV && ks <= (int)(SCH_Q >> 60)) { out_piece<SCH_Q, false>(c, w, kv_off(c, blk), blk, kn, ks, true); if (ks == (int)(SCH_Q >> 60)) c.signal(SIG_KV + (h >> 4)); }
  }
  c.wait(6); c.wait(9);
  wg_wait<0>();
  c.release(3, 3);
  c.turn();
  TSS(0);
  wg_fence();
  q_step(c, a, 6, 8, c.wg); q_step(c, a, 9, 11, c.wg); wg_commit();
  q_step(c, b, 7, 8, 1 - c.wg); wg_commit();
  c.pass();
  TSS(1);
  c.wait(0);
  const uint32_t q0 = c.addr(0) + (c.wg * 4 + c.warp) * 4096 + atom_off(c.lane);
  wg_wait<1>(); fence_regs(a);
  TSS(2);
  pack_o(a, QSCALE, QSCALE, w.lo);
  sts128o<0>(q0, w.lo[0]);    sts128o<2048>(q0, w.lo[1]); sts128o<512>(q0, w.lo[2]);  sts128o<2560>(q0, w.lo[3]);
  wg_wait<0>();
  c.release(6, 4);
  sts128o<1024>(q0, w.lo[4]); sts128o<3072>(q0, w.lo[5]); sts128o<1536>(q0, w.lo[6]); sts128o<3584>(q0, w.lo[7]);
  TSS(3);
  c.wait(12);
  fence_async_smem();
  TSS(4);
}

__device__ __forceinline__ void issue_qk(float (&s)[64], uint64_t da, uint64_t db) {
#pragma unroll
  for (int kk = 0; kk < 8; kk++) wgmma_ss_n128<0>(s, da + (kk >> 1) * 32 + (kk & 1) * 2, db + (kk >> 1) * 32 + (kk & 1) * 2, kk > 0);
  wg_commit();
}
template<int A, int B> __device__ __forceinline__ void exp_rng(float (&s)[64]) {
#pragma unroll
  for (int i = 4 * A; i < 4 * B; i++) s[i] = ex2(s[i]);
}
template<int A, int B> __device__ __forceinline__ void sum_rng(const float (&s)[64], float (&l)[4]) {
#pragma unroll
  for (int i = A; i < B; i++) { l[0] += s[4 * i]; l[1] += s[4 * i + 1]; l[2] += s[4 * i + 2]; l[3] += s[4 * i + 3]; }
}
template<int A, int B> __device__ __forceinline__ void cvt_p(const float (&s)[64], uint32_t (&p)[32]) {
#pragma unroll
  for (int i = 2 * A; i < 2 * B; i++) p[i] = pack_bf16(s[2 * i], s[2 * i + 1]);
}
template<int K0> __device__ __forceinline__ void mask_half(float (&s)[64], int warp, int lane) {
  const int l0 = warp + (2 * (lane & 3) <= (lane >> 2)), l1 = warp + (2 * (lane & 3) < (lane >> 2));
#pragma unroll
  for (int k = 0; k < 4; k++) {
    float* t = s + 8 * (K0 + k);
    if (k >= l0) { t[0] = -INFINITY; t[6] = -INFINITY; }
    if (k >= l1) { t[1] = -INFINITY; t[7] = -INFINITY; }
    if (k > warp) { t[2] = -INFINITY; t[3] = -INFINITY; }
    if (k >= warp) { t[4] = -INFINITY; t[5] = -INFINITY; }
  }
}
__device__ __forceinline__ void row_inv(float& l0, float& l1) {
  l0 += __shfl_xor_sync(~0u, l0, 1); l1 += __shfl_xor_sync(~0u, l1, 1);
  l0 += __shfl_xor_sync(~0u, l0, 2); l1 += __shfl_xor_sync(~0u, l1, 2);
  l0 = rcp(l0); l1 = rcp(l1);
}
__device__ __forceinline__ void softmax_safe(float (&s)[64], bool upper_only, float& m0, float& m1, float& sc0, float& sc1) {
  float a0 = m0, a1 = m1;
#pragma unroll
  for (int i = 0; i < 8; i++) { a0 = fmaxf(a0, fmaxf(s[4 * i], s[4 * i + 1])); a1 = fmaxf(a1, fmaxf(s[4 * i + 2], s[4 * i + 3])); }
  if (upper_only) { a0 = m0; a1 = m1; }
#pragma unroll
  for (int i = 8; i < 16; i++) { a0 = fmaxf(a0, fmaxf(s[4 * i], s[4 * i + 1])); a1 = fmaxf(a1, fmaxf(s[4 * i + 2], s[4 * i + 3])); }
  a0 = fmaxf(a0, __shfl_xor_sync(~0u, a0, 1)); a1 = fmaxf(a1, __shfl_xor_sync(~0u, a1, 1));
  a0 = fmaxf(a0, __shfl_xor_sync(~0u, a0, 2)); a1 = fmaxf(a1, __shfl_xor_sync(~0u, a1, 2));
  sc0 = ex2(m0 - a0); sc1 = ex2(m1 - a1);
  m0 = a0; m1 = a1;
#pragma unroll
  for (int i = 0; i < 16; i++) { s[4 * i] -= a0; s[4 * i + 1] -= a0; s[4 * i + 2] -= a1; s[4 * i + 3] -= a1; }
}
struct Att {
  float s[64], o[64], l[4], i0, i1, t0, t1; uint32_t p[32];
  float kn; uint32_t qaddr; const uint8_t* dst;
};
__device__ __forceinline__ int att_fast(uint4 (&q)[8], float kn) {
#pragma unroll
  for (int i = 0; i < 8; i++) q[i].x = hmul2(q[i].x, q[i].x);
#pragma unroll
  for (int i = 0; i < 8; i++) q[i].x = hfma2(q[i].w, q[i].w, hfma2(q[i].z, q[i].z, hfma2(q[i].y, q[i].y, q[i].x)));
#pragma unroll
  for (int i = 0; i < 4; i++) q[i].x = hadd2(q[i].x, q[i + 4].x);
  const uint32_t a0 = hadd2(q[0].x, q[2].x), a1 = hadd2(q[1].x, q[3].x);
  return __shfl_sync(~0u, __all_sync(~0u, ((bf_lo(a0) + bf_hi(a0)) * kn <= 0.25f * BOUND2) & ((bf_lo(a1) + bf_hi(a1)) * kn <= 0.25f * BOUND2)), 0);
}
__device__ __forceinline__ int att_first(Cons& c, Att& a, int h, Pend& w) {
  a.kn = __uint_as_float(lds32(c.base + SM_KMAX + 4 * (h >> 4)));
  a.qaddr = c.daddr(0) + c.wg * 16384;
  c.turn();
  TSS(5);
  wg_fence();
  issue_qk(a.s, odesc(a.qaddr, 16, 2048, 2), odesc(c.daddr(12), 16, 2048, 2));
  int fast = 0;
  SHADOW fast = att_fast(w.lo, a.kn);
  wg_fence();
  TSS(6);
  q_step(c, a.o, 10, 11, 1 - c.wg); wg_commit();
  if (c.wg) c.wait(6); else c.skip(6);
  c.pass();
  TSS(7);
#pragma unroll
  for (int i = 0; i < 8; i++) { a.p[4 * i] = w.lo[i].x; a.p[4 * i + 1] = w.lo[i].y; a.p[4 * i + 2] = w.lo[i].z; a.p[4 * i + 3] = w.lo[i].w; }
  a.l[0] = a.l[1] = a.l[2] = a.l[3] = 0.f; a.i0 = a.i1 = a.t0 = a.t1 = 0.25f / QSCALE;
  a.dst = (const uint8_t*)__cvta_shared_to_generic(c.addr(2) + (c.wg * 4 + c.warp) * 4096 + atom_off(c.lane));
  wg_wait<1>(); fence_regs(a.s);
  c.signal(SIG_ATT + (h >> 4));
  if (c.wg) { wg_wait<0>(); c.release(10, 2); }
  return fast;
}
__device__ __forceinline__ void att_last(Cons& c, Att& a, Pend& w, int h, int g, bool drain) {
  const int uv = 6;
  if (drain) pack_o(a.o, rcp(a.i0), rcp(a.i1), w.hi);
  TSS(8);
  c.turn();
  TSS(9);
  fence_regs(a.o); fence_regs(a.p);
  wgmma_pv_sel(a.o, a.p, odesc(c.daddr(uv), 512, 2048, 2), !(drain && c.wg == 1), !drain, c.wg);
  a.i0 = a.l[0] + a.l[1]; a.i1 = a.l[2] + a.l[3];
  SHADOW row_inv(a.i0, a.i1);
  sched_fence(a.i0 + a.i1, c.base + SM_DUMMY);
  tile_store_if<0, 4>(drain, w.hi, a.dst);
  wg_wait<0>(); fence_regs(a.o); fence_regs(a.p);
  c.release(uv, 2);
  TSS(10); if (h < 16) TSK(0);
  tile_store_if<4, 8>(drain, w.hi, a.dst);
  pack_o(a.o, a.i0, a.i1, w.lo);
  TSS(11);
}
__device__ __forceinline__ void cons_att(Cons& c, Att& a, int h, int g, Pend& w) {
  int fast = att_first(c, a, h, w), fast2 = 0;
  float m0 = -INFINITY, m1 = -INFINITY, sc0 = 0.f, sc1 = 0.f;
  int uk = 10, ur = 10;
  bool fresh = false;
#pragma unroll 1
  for (int d = g - 15;;) {
    const bool lo = d == c.wg;
    TSS(16 + 6 * (d - g + 15));
    if ((unsigned)d < 2 || !fast) {
      if ((unsigned)d < 2) mask_half<4>(a.s, c.warp, c.lane);
      if (!fast) {
        if (d == 1) m0 = m1 = -INFINITY;
        softmax_safe(a.s, lo, m0, m1, sc0, sc1);
        a.l[0] *= sc0; a.l[1] *= sc0; a.l[2] *= sc1; a.l[3] *= sc1;
      }
    }
    exp_rng<8, 16>(a.s); sum_rng<8, 16>(a.s, a.l);
#pragma unroll
    for (int i = 4 * ATT_SPLIT; i < 32; i++) asm("{\n.reg .pred p;\nsetp.ne.s32 p, %1, %2;\n@p ex2.approx.ftz.f32 %0, %0;\n}\n" : "+f"(a.s[i]) : "r"(d), "r"(c.wg));
    sched_fence(((a.l[0] + a.l[1]) + (a.l[2] + a.l[3])) + a.s[4 * ATT_SPLIT + 3], c.base + SM_DUMMY);
    wg_wait<0>(); fence_regs(a.o); fence_regs(a.p);
    c.release(ur, c.wg && d == g - 15 ? 0 : 2);
    TSS(17 + 6 * (d - g + 15));
    a.i0 += a.t0; a.i1 += a.t1;
    a.t0 = __shfl_xor_sync(~0u, a.i0, 2); a.t1 = __shfl_xor_sync(~0u, a.i1, 2);
    tile_store_if<0, 4>(fresh, w.hi, a.dst);
    uk ^= 12; ur = 14 - uk;
    if (d == 0) a.qaddr += 32768;
    const uint64_t dq = odesc(a.qaddr, 16, 2048, 2), dk = odesc(c.daddr(uk) - (d + 1 == c.wg ? 16384 : 0), 16, 2048, 2), dv = odesc(c.daddr(ur), 512, 2048, 2);
    if (!lo) { exp_rng<0, ATT_SPLIT>(a.s); sum_rng<0, 8>(a.s, a.l); cvt_p<0, 16>(a.s, a.p); }
    else if (gridDim.y == 1) cvt_p<8, 16>(a.s, a.p);
    tile_store_if<4, 8>(fresh, w.hi, a.dst);
    a.i0 += a.t0; a.i1 += a.t1;
    if (!fast || d == g + 1) {
      if (!fast && d != 1 && d != g - 15) {
#pragma unroll
        for (int i = 0; i < 16; i++) { a.o[4 * i] *= sc0; a.o[4 * i + 1] *= sc0; a.o[4 * i + 2] *= sc1; a.o[4 * i + 3] *= sc1; }
      }
      if (d == g + 1) break;
    }
    d++;
    fresh = d == 2 || d == g - 14;
    TSS(12 + 6 * (d - g + 15));
    c.turn();
    TSS(13 + 6 * (d - g + 15));
    fence_regs(a.o); fence_regs(a.p);
    wg_fence();
    issue_qk(a.s, dq, dk);
    TSS(14 + 6 * (d - g + 15));
    c.wait(c.wg ? uk ^ 12 : ur); c.skip(c.wg ? ur : uk ^ 12);
    if (fresh || d == 1 || (unsigned)(d - g + CHK_D) < 2) {
      if (fresh) pack_o(a.o, rcp(a.i0), rcp(a.i1), w.hi);
      else if (d == 1) {
        a.i0 = a.l[0] + a.l[1]; a.i1 = a.l[2] + a.l[3];
        a.t0 = __shfl_xor_sync(~0u, a.i0, 1); a.t1 = __shfl_xor_sync(~0u, a.i1, 1);
        a.l[0] = a.l[1] = a.l[2] = a.l[3] = 0.f;
        uint32_t off = ctx_off(c, h, 15 - g, c.wg);
        asm volatile("" : "+r"(off));
        a.dst = g_T + (off + ((uint32_t)(uint64_t)a.dst & 511));
        fast = fast2;
      } else if (d == g - CHK_D) fence_async_smem();
      else fast2 = att_fast(w.hi, a.kn);
    }
    TSS(15 + 6 * (d - g + 15));
    wgmma_pv_sel(a.o, a.p, dv, !lo, !fresh, c.wg);
    wg_wait<1>(); fence_regs(a.s);
    c.release(uk, 2);
    c.release(d == 0 ? 0 : 2, (d == 0 || d == g + 1) ? 2 : 0);
  }
  att_last(c, a, w, h, g, g == 0);
}

constexpr int CV_H = 1024, CV_U = 5120, CV_D = CV_U + 4128, CV_ROW = 1056;
template<int OFF> __device__ __forceinline__ uint32_t lds32o(uint32_t a) { uint32_t v; asm volatile("ld.shared.u32 %0, [%1+%2];" : "=r"(v) : "r"(a), "n"(OFF) : "memory"); return v; }
template<int G, int G1 = 16> __device__ __forceinline__ void conv_lda(uint32_t (&a)[64], uint32_t p) {
  a[4 * G + 0] = lds32o<-256 * G>(p);
  a[4 * G + 1] = lds32o<-256 * G - 128>(p);
  a[4 * G + 2] = lds32o<-256 * G + 16>(p);
  a[4 * G + 3] = lds32o<-256 * G - 112>(p);
  if constexpr (G + 1 < G1) conv_lda<G + 1, G1>(a, p);
}
struct CvAcc { float lo[16], hi[16]; };
__device__ __forceinline__ void fence_regs(CvAcc& d) { fence_regs(d.lo); fence_regs(d.hi); }
template<int R, int H> __device__ __forceinline__ void conv_mma_h(float (&d)[16], const uint32_t (&a)[64], uint64_t db) {
#pragma unroll
  for (int G = 0; G < 4 * R + 2 * H + 2; G++) wgmma_rs_n32<0>(d, a[4 * G], a[4 * G + 1], a[4 * G + 2], a[4 * G + 3], db + 64 * R + 32 * H - 16 * G, G > 0);
}
template<int T, int G0, int G1> __device__ __forceinline__ void conv_part(float (&d)[16], const uint32_t (&a)[64], uint64_t db) {
#pragma unroll
  for (int G = G0; G < G1; G++) wgmma_rs_n32<0>(d, a[4 * G], a[4 * G + 1], a[4 * G + 2], a[4 * G + 3], db + 32 * T - 16 * G, G > 0);
}
template<int R> __device__ __forceinline__ void conv_mma(CvAcc& d, const uint32_t (&a)[64], uint64_t db) { conv_mma_h<R, 0>(d.lo, a, db); conv_mma_h<R, 1>(d.hi, a, db); }
template<int C0> __device__ __forceinline__ void conv_st_h(const float (&d)[16], uint32_t wq, float& c0, float& c1) {
#pragma unroll
  for (int n = 0; n < 4; n++) { sts64f(wq + (C0 + n * 8) * 4, d[4 * n] + c0, d[4 * n + 1] + c1); c0 = d[4 * n + 2]; c1 = d[4 * n + 3]; }
}
template<int R> __device__ __forceinline__ void conv_st(const CvAcc& d, uint32_t wq, float& c0, float& c1) { conv_st_h<64 * R>(d.lo, wq, c0, c1); conv_st_h<64 * R + 32>(d.hi, wq, c0, c1); }
struct ConvTail { float t[64]; uint4 ua, uc; uint32_t D2; };
__device__ __forceinline__ void conv_emit(ConvTail& e, int ch, int tid) {
  fence_regs(e.t);
  float y[16];
#pragma unroll
  for (int i = 0; i < 16; i++) y[i] = (e.t[i] + e.t[16 + i]) + (e.t[32 + i] + e.t[48 + i]);
  uint4 z0, z1;
  z0.x = hadd2(pack_bf16(y[0], y[2]), hmul2(__byte_perm(e.ua.w, 0, 0x1032), e.D2));
  z0.y = hadd2(pack_bf16(y[4], y[6]), hmul2(__byte_perm(e.ua.z, 0, 0x1032), e.D2));
  z0.z = hadd2(pack_bf16(y[8], y[10]), hmul2(__byte_perm(e.ua.y, 0, 0x1032), e.D2));
  z0.w = hadd2(pack_bf16(y[12], y[14]), hmul2(__byte_perm(e.ua.x, 0, 0x1032), e.D2));
  z1.x = hadd2(pack_bf16(y[1], y[3]), hmul2(__byte_perm(e.uc.w, 0, 0x1032), e.D2));
  z1.y = hadd2(pack_bf16(y[5], y[7]), hmul2(__byte_perm(e.uc.z, 0, 0x1032), e.D2));
  z1.z = hadd2(pack_bf16(y[9], y[11]), hmul2(__byte_perm(e.uc.y, 0, 0x1032), e.D2));
  z1.w = hadd2(pack_bf16(y[13], y[15]), hmul2(__byte_perm(e.uc.x, 0, 0x1032), e.D2));
  uint4* zp = (uint4*)(g_z + (uint32_t)(ch * 2048 + tid * 16));
  zp[0] = z0; zp[1] = z1;
}
template<int MASK> __device__ __forceinline__ void cons_conv(Cons& c, int cta, int nch) {
  const int r = c.lane >> 2, q = c.lane & 3, tid = c.warp * 32 + c.lane;
  const uint32_t part = c.addr(4) - 2048 + (1 - c.wg) * (32 * CV_ROW) + 32;
  const uint32_t aoff = CV_U + ((r & 1) ? 0 : UPITCH) + 4 * (((2039 - r) >> 1) + q - 8 * c.warp);
  const uint32_t wq = part + (c.warp * 8 + r) * CV_ROW + q * 8, rq = part + tid * 8;
  uint32_t a[64];
  ConvTail e = {};
  c.wait(c.wg); c.skip(c.wg ^ 1);
  conv_lda<0>(a, c.addr(c.wg) + aoff);
  c.wait(4);
  sts64f(part + (tid >> 2) * CV_ROW - 32 + q * 8, 0.f, 0.f);
#pragma unroll 1
  for (int i = 0; i < nch / 2; i++) {
    const int u = 2 * (i & 1) + c.wg;
    CvAcc d0, d1, d2, d3;
    float c0 = 0.f, c1 = 0.f;
    const uint64_t db = odesc(c.daddr(u) + CV_H - 16, 16, 128, 0);
    c.turn();
    fence_regs(a);
    wg_fence();
    conv_mma<0>(d0, a, db); conv_mma<1>(d1, a, db); wg_commit();
    if (i > 0) {
      conv_emit(e, conv_channel<MASK>(cta, 2 * i - 2 + c.wg), tid);
      if ((i & 15) == 0) c.signal(SIG_Z + (i >> 4) - 1);
    }
    wg_fence();
    conv_mma_h<2, 0>(d2.lo, a, db); wg_commit();
    wg_wait<1>(); fence_regs(d0); fence_regs(d1);
    conv_st_h<0>(d0.lo, wq, c0, c1);
    wg_fence();
    conv_mma_h<2, 1>(d2.hi, a, db); wg_commit();
    conv_st_h<32>(d0.hi, wq, c0, c1);
    conv_mma_h<3, 0>(d3.lo, a, db);
    conv_st_h<64>(d1.lo, wq, c0, c1);
    conv_mma_h<3, 1>(d3.hi, a, db); wg_commit();
    c.pass();
    const int un = i + 1 < nch / 2 ? u ^ 2 : u;
    if (un != u) { c.wait(un); c.skip(un ^ 1); }
    wg_wait<1>(); fence_regs(d2);
    conv_st_h<96>(d1.hi, wq, c0, c1);
    conv_st<2>(d2, wq, c0, c1);
    {
      const int sw = (c.lane >> 2) & 1;
      const uint4 v0 = lds128(c.addr(u) + CV_U + 4064 - 32 * tid + 16 * sw), v1 = lds128(c.addr(u) + CV_U + 4080 - 32 * tid - 16 * sw);
      e.ua = sw ? v0 : v1; e.uc = sw ? v1 : v0;
    }
    e.D2 = lds32(c.addr(u) + CV_D);
    wg_wait<0>(); fence_regs(d3); fence_regs(a);
    conv_st<3>(d3, wq, c0, c1);
    conv_lda<0, 4>(a, c.addr(un) + aoff);
    c.sync();
    sched_fence(__uint_as_float(e.ua.x ^ e.uc.x ^ e.D2), c.base + SM_DUMMY);
    c.release2(u);
    conv_lda<4, 16>(a, c.addr(un) + aoff);
#pragma unroll
    for (int k = 0; k < 32; k++) { const float2 v = lds64f(rq + k * CV_ROW - (k >> 3) * 8); e.t[2 * k] = v.x; e.t[2 * k + 1] = v.y; }
  }
  conv_emit(e, conv_channel<MASK>(cta, nch - 2 + c.wg), tid);
  c.signal(SIG_Z + ((nch / 2 - 1) >> 4));
  c.release(4, 4);
}

constexpr int OC_PART = 13824, OC_ROW = 544;
__device__ __forceinline__ int out_next(int u) { return (0x84ac680u >> (2 * u)) & 15; }
struct Out { float acc[64]; int pu; uint64_t da, db; };
template<bool FIRST, bool REL, int W = 1> __device__ __forceinline__ void out_step(Cons& c, Out& o, bool extra = false) {
  const int pu = o.pu, u = extra ? 2 : out_next(pu);
  o.pu = u;
  c.wait(u);
  const uint64_t da = o.da + (uint32_t)(u * 1024), db = o.db + (uint32_t)(u * 1024);
  wg_fence();
#pragma unroll
  for (int kk = 0; kk < 4; kk++) wgmma_ss_n128<1>(o.acc, da + (kk >> 1) * 32 + (kk & 1) * 2, db + kk * 128, !(FIRST && kk == 0));
  wg_commit();
  if (REL) { wg_wait<W>(); c.release(pu, 2); }
}
template<int I0, int I1> __device__ __forceinline__ void oc_red(float (&y)[8], uint32_t rq) {
#pragma unroll
  for (int i = I0; i < I1; i++) { const float v = __uint_as_float(lds32(rq + i * OC_ROW - (i >> 3) * 8)); y[i & 7] = i < 8 ? v : y[i & 7] + v; }
}
__device__ __forceinline__ void oc_emit(const float (&y)[8], const uint4& u, uint32_t D2, __nv_bfloat16* dst) {
  uint4 z;
  z.x = hadd2(pack_bf16(y[0], y[1]), hmul2(__byte_perm(u.w, 0, 0x1032), D2));
  z.y = hadd2(pack_bf16(y[2], y[3]), hmul2(__byte_perm(u.z, 0, 0x1032), D2));
  z.z = hadd2(pack_bf16(y[4], y[5]), hmul2(__byte_perm(u.y, 0, 0x1032), D2));
  z.w = hadd2(pack_bf16(y[6], y[7]), hmul2(__byte_perm(u.x, 0, 0x1032), D2));
  *(uint4*)dst = z;
}
__device__ __forceinline__ uint32_t mix(uint32_t og, uint32_t b, uint32_t ga) { return hadd2(ga, hmul2(og, b)); }
template<int MASK> __device__ __forceinline__ void cons_out(Cons& c, const Maps& M, const Params& P, int cta, Pend& w) {
  const int mb = out_mb(cta), nb = out_nb(cta);
  Out o;
  o.da = odesc(c.daddr(0) + c.wg * 8192, 16, 1024, 2); o.db = odesc(c.daddr(1), 8192, 1024, 1);
  o.pu = 5 + gridDim.y;
  out_step<true, false>(c, o);
  int ks = 1;
  const uint32_t dst = ctx_off(c, 16 + (cta >> 3), cta & 7, 1 - c.wg);
#pragma unroll 1
  for (;; ks++) {
    if (MASK & PH_ATT) {
      if (ks == (c.wg ? ST_1 : 1)) tile_store<0, 1>(w.lo, dst, c.lane);
      if (ks == (c.wg ? ST_1 + ST_D : 1)) tile_store<1, 2>(w.lo, dst, c.lane);
      if (ks == (c.wg ? ST_1 + 2 * ST_D : 1)) tile_store<2, 3>(w.lo, dst, c.lane);
      if (ks == (c.wg ? ST_1 + 3 * ST_D : 1)) { tile_store<3, 4>(w.lo, dst, c.lane); c.signal(SIG_CTX + 1); }
    }
    if (ks == (c.wg ? OC_S1 : OC_S0)) break;
    out_step<false, true>(c, o, ks == 1);
  }
  if (MASK & PH_CONV) {
    const int r = c.lane >> 2, q = c.lane & 3, tid = c.warp * 32 + c.lane, u = 2 * c.wg;
    const uint32_t ub = c.addr(u), part = ub + OC_PART + 32;
    const uint32_t ap = ub + CV_U + ((r & 1) ? 0 : UPITCH) + 4 * (((2039 - r) >> 1) + q - 8 * c.warp);
    const uint32_t wq = part + (c.warp * 8 + r) * OC_ROW + q * 8, rq = part + tid * 4;
    const int nr = (CV_REG<MASK> + 1 - c.wg) >> 1;
#define STEP(N) out_step<false, true>(c, o);
#pragma unroll 1
    for (int i = 0; i < nr; i++) {
      uint32_t a[64];
      CvAcc d0, d1;
      float y[8], c0 = 0.f, c1 = 0.f;
      const uint64_t db = odesc(c.daddr(u + (i >> 8)) + CV_H - 16, 16, 128, 0);
#define STEP2(N) out_step<false, true, 2>(c, o);
#define PART(...) { const uint64_t db = db0 + (c.mask >> 16); wg_fence(); __VA_ARGS__; wg_commit(); }
      const uint64_t db0 = db;
#define KEEP() asm volatile("add.f32 %0, %0, 0f80000000;" : "+f"(c0)); asm volatile("add.f32 %0, %0, 0f80000000;" : "+f"(c1));
      c.wait(u);
      conv_lda<0, 4>(a, ap);
      STEP(0)
      conv_lda<4, 7>(a, ap);
      PART(conv_part<0, 0, 2>(d0.lo, a, db); conv_part<1, 0, 4>(d0.hi, a, db); conv_part<2, 0, 2>(d1.lo, a, db))
      STEP2(1)
      conv_lda<7, 10>(a, ap);
      PART(conv_part<2, 2, 6>(d1.lo, a, db); conv_part<3, 0, 4>(d1.hi, a, db))
      STEP2(2)
      fence_regs(d0);
      c.sync();
      sts64f(wq - 32, 0.f, 0.f);
      conv_st_h<0>(d0.lo, wq, c0, c1); KEEP()
      PART(conv_part<3, 4, 8>(d1.hi, a, db); conv_part<4, 0, 4>(d0.lo, a, db))
      STEP2(3)
      fence_regs(d1.lo);
      conv_st_h<32>(d0.hi, wq, c0, c1); conv_st_h<64>(d1.lo, wq, c0, c1); KEEP()
      PART(conv_part<4, 4, 10>(d0.lo, a, db); conv_part<5, 0, 2>(d0.hi, a, db))
      STEP2(4)
      fence_regs(d1.hi);
      float e0 = d1.hi[12] + d1.hi[10], e1 = d1.hi[13] + d1.hi[11];
      conv_st_h<96>(d1.hi, wq, c0, c1); KEEP()
      conv_lda<10, 12>(a, ap);
      PART(conv_part<5, 2, 10>(d0.hi, a, db))
      STEP2(5)
      conv_lda<12, 14>(a, ap);
      c.sync();
      oc_red<0, 6>(y, rq);
      PART(conv_part<5, 10, 12>(d0.hi, a, db); conv_part<6, 0, 6>(d1.lo, a, db))
      STEP2(6)
      oc_red<6, 20>(y, rq);
      PART(conv_part<6, 6, 14>(d1.lo, a, db))
      STEP2(7)
      oc_red<20, 26>(y, rq);
      conv_lda<14, 16>(a, ap);
      PART(conv_part<7, 0, 8>(d1.hi, a, db))
      STEP2(8)
      oc_red<26, 32>(y, rq);
      PART(conv_part<7, 8, 16>(d1.hi, a, db))
      STEP2(9)
      fence_regs(y); fence_regs(d0);
      c.sync();
      sts64f(wq - 32, e0, e1);
      conv_st<0>(d0, wq, c0, c1);
      STEP(10)
      fence_regs(d1); fence_regs(a);
      const uint4 u0 = lds128(ub + CV_U + 4080 - 16 * tid), u1 = lds128(ub + CV_U + 2032 - 16 * tid);
      const uint32_t D2 = lds32(ub + CV_D);
      conv_st<1>(d1, wq, c0, c1);
      STEP(11)
      sched_fence(__uint_as_float(u0.x ^ u1.x ^ D2), c.base + SM_DUMMY);
      __syncwarp();
      c.release2(u);
      __nv_bfloat16* zp = g_z + (uint32_t)(conv_channel<MASK>(cta, 2 * i + c.wg) * 2048 + (threadIdx.x & 127) * 8);
      oc_emit(y, u0, D2, zp);
      c.sync();
      oc_red<0, 12>(y, rq);
      STEP(12)
      oc_red<12, 24>(y, rq);
      STEP(13)
      oc_red<24, 32>(y, rq);
      oc_emit(y, u1, D2, zp + 1024);
#undef KEEP
      if (i == nr - 1) { c.signal(SIG_Z); c.release2(u + 1); TSO(0); }
      out_step<false, true>(c, o);
#pragma unroll 1
      for (int k = 15; k < (i == nr - 1 ? 0 : c.wg ? OC_L1 : OC_L0); k++) out_step<false, true>(c, o);
#undef STEP2
#undef PART
    }
#undef STEP
    if (((CV_REG<MASK> + c.wg) >> 1) & 1) c.skip(u ^ 2);
    ks += (nr - 1) * (c.wg ? OC_L1 : OC_L0) + 15;
  }
  TS(c.wg, 9);
#pragma unroll 1
  for (; ks < 57; ks++) out_step<false, true>(c, o);
  uint32_t ga[32];
  TSO(1);
  c.wait(2);
  TSO(2);
  const float g0 = __uint_as_float(lds32(c.base + SM_GATE + 4 * (c.wg * 64 + c.warp * 16 + (c.lane >> 2)))), g1 = __uint_as_float(lds32(c.base + SM_GATE + 32 + 4 * (c.wg * 64 + c.warp * 16 + (c.lane >> 2))));
  const uint32_t gg0 = pack_bf16(g0, g0), gg1 = pack_bf16(g1, g1);
  const uint32_t og0 = pack_bf16(1.f - g0, 1.f - g0), og1 = pack_bf16(1.f - g1, 1.f - g1);
  const int xr = c.wg * 64 + c.warp * 16 + (c.lane & 15);
  const uint32_t xa = c.addr(2) + xr * 128, xs = xr & 7, xh = c.lane >> 4;
  const int zr = (c.lane & 7) + ((c.lane >> 4) << 3);
  const uint32_t za = c.addr(0) + c.wg * 16384 + zr * 128 + (((c.warp * 2 + ((c.lane >> 3) & 1)) ^ (zr & 7)) << 4);
#pragma unroll
  for (int i = 0; i < 8; i++) {
    if (i == 0) out_step<false, true>(c, o);
    if (i == 3) out_step<false, true>(c, o);
    if (i == 6) out_step<false, true>(c, o);
    ldsm4(xa + (i >> 2) * 16384 + ((((i & 3) * 2 + xh) ^ xs) << 4), ga[4 * i], ga[4 * i + 1], ga[4 * i + 2], ga[4 * i + 3]);
  }
  TSO(3);
#pragma unroll 1
  for (ks = 60; ks < 64; ks++) out_step<false, false>(c, o);
  TSO(4);
  c.wait(0);
  TSO(5);
  SHADOW {
#pragma unroll
    for (int i = 0; i < 8; i++) {
      uint32_t z0, z1, z2, z3;
      ldsm4t(za + i * 2048, z0, z1, z2, z3);
      ga[4 * i + 0] = hmul2(ga[4 * i + 0], z0); ga[4 * i + 1] = hmul2(ga[4 * i + 1], z1); ga[4 * i + 2] = hmul2(ga[4 * i + 2], z2); ga[4 * i + 3] = hmul2(ga[4 * i + 3], z3);
      ga[4 * i + 0] = hmul2(gg0, ga[4 * i + 0]); ga[4 * i + 1] = hmul2(gg1, ga[4 * i + 1]); ga[4 * i + 2] = hmul2(gg0, ga[4 * i + 2]); ga[4 * i + 3] = hmul2(gg1, ga[4 * i + 3]);
    }
  }
  c.signal(SIG_DONE);
  fence_regs(ga);
  TSO(6);
  wg_wait<0>(); fence_regs(o.acc);
  TSO(7);
#pragma unroll
  for (int i = 0; i < 8; i++) {
    const uint32_t r0 = mix(og0, pack_bf16(o.acc[8 * i + 0], o.acc[8 * i + 1]), ga[4 * i + 0]);
    const uint32_t r1 = mix(og1, pack_bf16(o.acc[8 * i + 2], o.acc[8 * i + 3]), ga[4 * i + 1]);
    const uint32_t r2 = mix(og0, pack_bf16(o.acc[8 * i + 4], o.acc[8 * i + 5]), ga[4 * i + 2]);
    const uint32_t r3 = mix(og1, pack_bf16(o.acc[8 * i + 6], o.acc[8 * i + 7]), ga[4 * i + 3]);
    stsm4(xa + (i >> 2) * 16384 + ((((i & 3) * 2 + xh) ^ xs) << 4), r0, r1, r2, r3);
    if ((i & 3) == 3) {
      __syncwarp();
#pragma unroll
      for (int k = 0; k < 4; k++) {
        const int rr = c.wg * 64 + c.warp * 16 + k * 4 + (c.lane >> 3);
        const uint4 v = lds128(c.addr(2 + (i >> 2)) + rr * 128 + (((c.lane ^ rr) & 7) << 4));
        *(uint4*)(P.out + (uint32_t)((mb * 128 + rr) * 1024 + nb * 128 + (i >> 2) * 64 + (c.lane & 7) * 8)) = v;
      }
    }
  }
  TSO(8);
}

__device__ __forceinline__ void load_conv(Prod& p, const Maps& M, int u, int ch) {
  if (elect()) {
    mbar_expect(p.full(u), 5120 + UCH);
    tma3d(p.addr(u), &M.h, 0, -8, ch, p.full(u), true);
    bulk_g2s(p.addr(u) + CV_U, g_u + (size_t)ch * UCH, UCH, p.full(u), true);
  }
}
template<int MASK> __device__ __forceinline__ void prod_conv(Prod& p, const Maps& M, int cta, int nch) {
  int ready = -1;
#pragma unroll 1
  for (int i = 0; i < nch; i++) {
    const int ch = conv_channel<MASK>(cta, i);
    const int u = i & 3;
    if ((ch >> 6) != ready) { ready = ch >> 6; if (cta < NREG) mbar_wait(p.base + SM_RDY + 8 * RDY_U, 0); else cnt_wait(g_cnt + (C_U + ready) * CSTRIDE, 128); }
    p.acquire(u, 1);
    load_conv(p, M, u, ch);
    if (i == 3) { p.acquire(4, 4); if (elect()) mbar_arrive(p.full(4)); }
  }
}
#define HOIST(v) asm volatile("" : "+r"(v))
template<int MASK> __device__ __forceinline__ void producer(const Maps& M, const Params& P, uint32_t base, int cta, int lane) {
  Prod p{base, ((MASK & PH_KV) && cta < NREG) ? 0xffffcfffu ^ ((1u << (3 * NFIRST)) - 1) : 0xffffffffu, lane,
         (cta * 3 + 2) * 2048};
  if (cta >= NREG) { if (MASK & PH_CONV) prod_conv<MASK>(p, M, cta, CV_EXTRA<MASK>); return; }
  const int g = cta & 7, j = cta >> 3, rank = cta & 1;
#pragma unroll 1
  for (int half = 0; half < 2; half++) {
    const int h = j + 16 * half;
    if (MASK & PH_KV) {
      const CUtensorMap* mw = rank ? &M.wv : &M.wk;
#pragma unroll 1
      for (int it = half ? 0 : NFIRST; it < 16; it++) {
        const int u = gemm_unit(it);
        uint32_t bar = p.full(u), d0 = p.addr(u), d1 = p.addr(u + 1 + rank); int k0 = (it & 7) * 64, r0 = (2 * g + (it >> 3)) * 128;
        HOIST(bar); HOIST(d0); HOIST(d1); HOIST(k0); HOIST(r0);
        p.acquire(u, 3);
        if (elect()) {
          mbar_expect(bar, 3 * UNIT);
          tma3d_mc(d1, mw, 0, k0, 2 * h, bar, it >= 8);
          tma2d(d0, &M.c, k0, r0, bar);
        }
      }
    }
    if (MASK & PH_ATT) {
#pragma unroll 1
      for (int ks = 0; ks < 16; ks++) {
        const int u = gemm_unit(ks);
        uint32_t bar = p.full(u), d0 = p.addr(u), d1 = p.addr(u + 1), d2 = p.addr(u + 2) + rank * 8192; int k0 = ks * 64;
        HOIST(bar); HOIST(d0); HOIST(d1); HOIST(d2); HOIST(k0);
        p.acquire(u, 3);
        if (elect()) {
          mbar_expect(bar, 3 * UNIT);
          tma2d_mc(d2, &M.wq, h * 128 + rank * 64, k0, bar, true);
          tma2d(d0, &M.x, k0, (15 - g) * 128, bar);
          tma2d(d1, &M.x, k0, g * 128, bar);
        }
      }
      TS(2, 8 * half + 0);
      mbar_wait(base + SM_RDY + 8 * (RDY_KV + half), 0);
      TS(2, 8 * half + 1);
      const uint8_t* KVh = g_T + T_KV + (size_t)kv_slot<MASK>(h) * 16 * 65536;
      if (MASK & PH_PRE) mbar_wait(base + SM_RDY + 8 * RDY_AUX, 0);
      if (elect()) { mbar_expect(p.full(12), 32768); bulk_g2s(p.addr(12), KVh, 32768, p.full(12), true); }
      p.acquire(0, 4);
      if (elect()) mbar_arrive(p.full(0));
#pragma unroll 1
      for (int i = 1; i < 34; i++) {
        const int isv = !(i & 1) || i == 33, st = i == 33 ? 16 : (isv ? (i >> 1) - 1 : (i + 1) >> 1), u = 4 + 2 * (i & 3);
        const bool own = st == 15 - (g & 6);
        uint32_t bar = p.full(u), d0 = p.addr(own ? u : u + rank), off = (st <= 15 - g ? st : 16 - st) * 65536 + isv * 32768 + (own ? 0 : rank * UNIT);
        HOIST(bar); HOIST(d0); HOIST(off);
        p.acquire(u, 2);
        if (elect()) {
          mbar_expect(bar, 32768);
          if (own) bulk_g2s(d0, KVh + off, 32768, bar, true); else bulk_g2s_mc(d0, KVh + off, UNIT, bar, true);
        }
      }
    }
  }
  if ((MASK & PH_CONV) && !(MASK & PH_OUT)) prod_conv<MASK>(p, M, cta, CV_REG<MASK>);
  if (MASK & PH_OUT) {
    const int y0 = out_mb(cta) * 512 + rank * 8, z0 = 2 * out_nb(cta);
    int u = 6;
#pragma unroll 1
    for (int hf = 0; hf < 2; hf++) {
      TS(2, 16 + 2 * hf);
      mbar_wait(base + SM_RDY + 8 * (RDY_CTX + hf), 0);
      TS(2, 17 + 2 * hf);
#pragma unroll 1
      for (int n = hf * 32; n < hf * 32 + 32; n++) {
        const int ks = n == 1 ? 2 : n == 2 ? 1 : n;
        u = n == 2 ? 2 : n == 3 ? 10 : out_next(u);
        uint32_t bar = p.full(u), d0 = p.addr(u) + rank * 8192, d1 = p.addr(u + 1); int x = (ks & 1) * 256, y = y0 + (ks >> 1) * 16, k0 = ks * 64;
        HOIST(bar); HOIST(d0); HOIST(d1); HOIST(x); HOIST(y); HOIST(k0);
        p.acquire(u, 2);
        if (elect()) {
          mbar_expect(bar, 2 * UNIT);
          tma2d_mc(d0, &M.ctx, x, y, bar, true);
          tma3d(d1, &M.wo, 0, k0, z0, bar, true);
          if (ks == 1) mbar_arrive(base + SM_RDY + 8 * RDY_X);
          if (ks == Z_AT) mbar_arrive(base + SM_RDY + 8 * RDY_Z);
        }
      }
    }
  }
}
template<int MASK> __device__ __forceinline__ void producer2(const Maps& M, const Params& P, uint32_t base, int cta, int w, int lane) {
  Prod p{base, 0xffffffffu, lane, 0};
  const int mb = out_mb(cta), nb = out_nb(cta), u = 2 * w;
  if (w) { mbar_wait_slow(base + SM_RDY + 8 * RDY_X, 0); p.mask ^= 12; }
  if (MASK & PH_CONV) {
    mbar_wait_slow(base + SM_SIG + 8 * (SIG_ATT + 1), 0);
    mbar_wait_slow(base + SM_RDY + 8 * RDY_U, 0);
#pragma unroll 1
    for (int i = w; i < CV_REG<MASK>; i += 2) { p.acquire_slow(u, i < 2 ? 2 : 1); load_conv(p, M, u, conv_channel<MASK>(cta, i)); }
  }
  p.acquire_slow(u, 2);
  if (!w && elect()) map_pf(&M.z);
  TSA(52 - 2 * w);
  mbar_wait(base + SM_RDY + 8 * (!w ? RDY_Z : RDY_G), 0);
  TSA(53 - 2 * w);
  if (elect()) {
    mbar_expect(p.full(u), 2 * UNIT + (!w ? 0 : 512));
    tma2d(p.addr(u), !w ? &M.z : &M.x, (!w ? mb : nb) * 128, (!w ? nb : mb) * 128, p.full(u), true);
    tma2d(p.addr(u + 1), !w ? &M.z : &M.x, (!w ? mb : nb) * 128 + 64, (!w ? nb : mb) * 128, p.full(u), true);
    if (w) bulk_g2s(base + SM_GATE, g_gate + mb * 128, 512, p.full(u));
  }
}

__device__ __forceinline__ constexpr uint32_t PUB(int sig, int cnt, int n) { return 0x80000000u | (sig << 24) | (n << 8) | cnt; }
__device__ __forceinline__ constexpr uint32_t GET(int rdy, int cnt, int n) { return (rdy << 24) | (n << 8) | cnt; }
template<int MASK> __device__ __forceinline__ void sync_agent(uint32_t base, int cta, int lane) {
  if ((base & 0x3FFFF) != SMEM_BASE) asm volatile("trap;");
  const int g = cta & 7, j = cta >> 3, go = min(out_mb(cta), 15 - out_mb(cta));
  const int c0 = conv_channel<MASK>(cta, 0), c1 = c0 + CV_REG<MASK> - 1, n0 = min(CV_REG<MASK>, 128 - (c0 & 127));
  constexpr bool KV = MASK & PH_KV, ATT = MASK & PH_ATT, CONV = MASK & PH_CONV, OUT = MASK & PH_OUT, ALL = MASK == PH_ALL;
  uint32_t e = 0;
  if (cta >= NREG) { if (CONV && lane * 32 < CV_EXTRA<MASK>) e = PUB(SIG_Z + lane, C_Z + lane, min(32, CV_EXTRA<MASK> - lane * 32)); }
  else switch (lane) {
    case 0:  if (KV) e = PUB(SIG_KV, C_KV + j, 1); break;
    case 1:  if (ATT) e = GET(RDY_KV, C_KV + j, 8); break;
    case 2:  if (ALL) e = PUB(SIG_WAR, C_WAR + j, 1); break;
    case 3:  if (ATT) e = PUB(SIG_CTX, C_CTX + g, 1); break;
    case 4:  if (ALL) e = GET(RDY_WAR, C_WAR + j, 8); break;
    case 5:  if (KV) e = PUB(SIG_KV + 1, C_KV + 16 + j, 1); break;
    case 6:  if (ATT) e = GET(RDY_KV + 1, C_KV + 16 + j, 8); break;
    case 7:  if (OUT) e = GET(RDY_CTX, C_CTX + go, 16); break;
    case 8:  if (CONV) e = GET(RDY_U, C_U + (c0 >> 6), 128); break;
    case 9:  if (CONV) e = GET(RDY_U, C_U + (c1 >> 6), 128); break;
    case 10: if (ATT) e = PUB(SIG_CTX + 1, C_CTX + 8 + g, 1); break;
    case 11: if (OUT) e = GET(RDY_CTX + 1, C_CTX + 8 + go, 16); break;
    case 12: if (OUT) e = GET(RDY_G, C_GATE, 256); break;
    case 13: if (CONV) e = PUB(SIG_Z, C_Z + (c0 >> 7), n0); break;
    case 14: if (CONV && n0 < CV_REG<MASK>) e = PUB(SIG_Z, C_Z + (c1 >> 7), CV_REG<MASK> - n0); break;
    case 15: if (OUT) e = GET(RDY_Z, C_Z + out_nb(cta), 128); break;
  }
  __syncwarp();
#pragma unroll 1
  for (int i = 0; i < 16; i++) {
    const uint32_t x = __shfl_sync(~0u, e, i), id = (x >> 24) & 127, n = (x >> 8) & 0xffff;
    if (x == 0) continue;
    unsigned* cnt = g_cnt + (x & 255) * CSTRIDE;
    if (x >> 31) {
      mbar_wait_slow(base + SM_SIG + 8 * id, 0);
      if (i == 13) TSA(22);
      if (lane == 0) cnt_publish(cnt, n, i != 14);
    } else {
      cnt_wait(cnt, n);
      if (id < 2) {
        const float4 kn = __ldcg((const float4*)(g_kn2 + kv_slot<MASK>(j + 16 * id) * 128) + lane);
        const uint32_t m = __reduce_max_sync(~0u, max(max(__float_as_uint(kn.x), __float_as_uint(kn.y)), max(__float_as_uint(kn.z), __float_as_uint(kn.w))));
        if (lane == 0) asm volatile("st.shared.u32 [%0], %1;" :: "r"(base + SM_KMAX + 4 * id), "r"(m) : "memory");
      }
      if (lane == 0) mbar_arrive(base + SM_RDY + 8 * id);
    }
    __syncwarp();
    TSA(24 + i);
  }
}

__device__ __forceinline__ void aux_gate(const Params& P, int cta, int aw, int lane) {
  uint4 gw[4];
#pragma unroll
  for (int i = 0; i < 4; i++) gw[i] = __ldg((const uint4*)P.gw + i * 32 + lane);
#pragma unroll 1
  for (int row = cta * 16 + aw * 8; row < cta * 16 + aw * 8 + 8; row++) {
    float a = 0.f;
#pragma unroll
    for (int i = 0; i < 4; i++) {
      const uint4 xv = __ldg((const uint4*)(P.x + (size_t)row * 1024) + i * 32 + lane);
      uint32_t m;
      m = hmul2(xv.x, gw[i].x); a += bf_lo(m) + bf_hi(m); m = hmul2(xv.y, gw[i].y); a += bf_lo(m) + bf_hi(m);
      m = hmul2(xv.z, gw[i].z); a += bf_lo(m) + bf_hi(m); m = hmul2(xv.w, gw[i].w); a += bf_lo(m) + bf_hi(m);
    }
#pragma unroll
    for (int o = 16; o > 0; o >>= 1) a += __shfl_xor_sync(~0u, a, o);
    a = bf_lo(pack_bf16(a, 0.f));
    const float gt = bf_lo(pack_bf16(__fdividef(1.f, 1.f + ex2(-a * 1.4426950408889634f)), 0.f));
    if (lane == 0) g_gate[row] = gt;
    __nanosleep(GATE_SLEEP);
  }
  cnt_signal(g_cnt + C_GATE * CSTRIDE, lane);
  if (aw == 0) { TSA(44); }
}
template<int MASK> __device__ __forceinline__ void aux_pre(const Maps& M, const Params& P, uint32_t base, int cta, int aw, int lane) {
  const uint32_t kb = base + 12 * UNIT, bar = base + SM_PRE;
  const int r = lane >> 2, q = lane & 3;
  const int mi = lane >> 3, row0 = (lane & 6) + 1 - (lane & 1);
  const int ra = (mi * 9 + 1) * 2 + row0;
  const int rb = (mi == 0 ? 3 : mi) * 18 + row0;
#pragma unroll 1
  for (int it = 0; it < (cta < 96 ? 5 : 4); it++) {
    if (it == PRE_EARLY && MASK == PH_ALL) { mbar_wait_slow(base + SM_SIG + 8 * SIG_ATT, 0); aux_gate(P, cta, aw, lane); }
    if (it == PRE_EARLY && MASK == PH_ALL) mbar_wait_slow(base + SM_SIG + 8 * (SIG_ATT + 1), 0);
    const int cg = it ? it * 4 - 3 + (cta >> 5) : 0, tb = cta & 31;
    if (aw == 0 && elect()) {
      mbar_expect(bar, 2 * 9216);
      tma4d(kb, &M.k, cg * 64, 0, tb * 8 - 1, 0, bar, true);
      tma4d(kb + 9216, &M.v, cg * 64, 0, tb * 8 - 1, 0, bar, true);
    }
    const uint2 swl = __ldg((const uint2*)(P.shift + (cg * 64 + aw * 32 + lane) * 4));
    if (tb == 0) {
      uint8_t* e = g_u + (size_t)(cg * 64 + aw * 32 + lane) * UCH + 4096;
      *(uint4*)e = make_uint4(0, 0, 0, 0); *(uint4*)(e + UPITCH) = make_uint4(0, 0, 0, 0);
      *(uint32_t*)(e + 32) = (uint32_t)__bfloat16_as_ushort(P.D[cg * 64 + aw * 32 + lane]) * 0x10001u;
    }
    mbar_wait_slow(bar, it & 1);
#pragma unroll 1
    for (int ol = it ? 0 : cta >> 5; ol < (it ? 4 : (cta >> 5) + 1); ol++) {
      const int oc = aw * 4 + ol;
      const uint32_t s01 = __shfl_sync(~0u, swl.x, ol * 8 + r), s23 = __shfl_sync(~0u, swl.y, ol * 8 + r);
      const uint32_t w0 = __byte_perm(s01, 0, 0x1010), w1 = __byte_perm(s01, 0, 0x3232), w2 = __byte_perm(s23, 0, 0x1010), w3 = __byte_perm(s23, 0, 0x3232);
      const uint32_t pa = kb + ra * 128 + ((oc ^ (ra & 7)) << 4), pb = kb + (mi == 0 ? 9216 : 0) + rb * 128 + ((oc ^ (rb & 7)) << 4);
      uint8_t* e0 = g_u + (uint32_t)((cg * 64 + oc * 8 + r) * UCH + (2040 - tb * 64 - 8 * q) * 2);
#pragma unroll
      for (int hb = 0; hb < 2; hb++) {
        uint32_t k[7], v[5];
        ldsm4t(pa + hb * 1024, k[3], k[4], k[5], k[6]);
        ldsm4t(pa + hb * 1024 + 9216, v[1], v[2], v[3], v[4]);
        ldsm4t(pb + hb * 1024, v[0], k[0], k[1], k[2]);
        uint32_t o1 = __byte_perm(k[1], k[0], 0x5432);
#pragma unroll
        for (int m = 0; m < 5; m++) {
          const uint32_t o2 = __byte_perm(k[m + 2], k[m + 1], 0x5432);
          v[m] = hmul2(hadd2(hadd2(hadd2(hmul2(o1, w3), hmul2(k[m + 1], w2)), hmul2(o2, w1)), hmul2(k[m + 2], w0)), v[m]);
          o1 = o2;
        }
        *(uint4*)(e0 - hb * 64) = make_uint4(v[4], v[3], v[2], v[1]);
        *(uint4*)(e0 - hb * 64 + UPITCH) = make_uint4(__byte_perm(v[4], v[3], 0x5432), __byte_perm(v[3], v[2], 0x5432), __byte_perm(v[2], v[1], 0x5432), __byte_perm(v[1], v[0], 0x5432));
        if (it >= PRE_EARLY) __nanosleep(PRE_SLEEP);
      }
    }
    bar_sync(5, 64);
    if (aw == 0) { TSA(40 + min(it, 3)); }
    if (it == PRE_EARLY - 1 && aw == 0 && lane == 0) mbar_arrive(base + SM_RDY + 8 * RDY_AUX);
    if (aw == 1 && lane == 0) asm volatile("red.release.gpu.global.add.u32 [%0], %1;" :: "l"(g_cnt + (C_U + cg) * CSTRIDE), "r"(it ? 4 : 1) : "memory");
  }
  uint32_t rel;
  asm volatile("mapa.shared::cluster.u32 %0, %1, %2;" : "=r"(rel) : "r"(base + SM_BAR + 128 + 8 * (12 + (lane & 1))), "r"((lane >> 1) & 1));
  if (lane < 4) asm volatile("mbarrier.arrive.shared::cluster.b64 _, [%0], 4;" :: "r"(rel) : "memory");
  if (MASK != PH_ALL) aux_gate(P, cta, aw, lane);
}

template<int MASK> __global__ void __cluster_dims__(2, 1, 1) __launch_bounds__(384, 1) gated_mix_kernel(const __grid_constant__ Maps M, const __grid_constant__ Params P) {
  extern __shared__ __align__(1024) uint8_t smem[];
  const uint32_t base = (uint32_t)__cvta_generic_to_shared(smem);
  if ((MASK & PH_KV) && elect()) {
    map_pf(&M.wk + (blockIdx.x & 1)); map_pf(&M.c);
  }
  const int wi = __shfl_sync(~0u, threadIdx.x >> 5, 0), wg = wi >> 2, warp = wi & 3;
  if (elect()) {
    if (wi < 8) {
      const int cnt = 1 << ((0x10334400 >> (4 * wi)) & 15);
#pragma unroll
      for (int i = 0; i < 8; i++) mbar_init(base + SM_BAR + 64 * wi + 8 * i, cnt);
      asm volatile("fence.mbarrier_init.release.cluster;" ::: "memory");
    }
  }
  const int cta = blockIdx.x;
  const bool first_loads = (MASK & PH_KV) && wi == 8 && cta < NREG;
  const CUtensorMap* mw = (cta & 1) ? &M.wv : &M.wk;
  __syncwarp();
  asm volatile("barrier.cluster.arrive.relaxed.aligned;\nbarrier.cluster.wait.aligned;" ::: "memory");
  auto first_stage = [&](int it) {
    const uint32_t bar = base + SM_BAR + 24 * it, d0 = base + 3 * it * UNIT;
    mbar_expect(bar, 3 * UNIT);
    tma3d_mc(d0 + (1 + (cta & 1)) * UNIT, mw, 0, it * 64, 2 * (cta >> 3), bar);
    tma2d(d0, &M.c, it * 64, (cta & 7) * 256, bar);
  };
  if (first_loads && elect()) first_stage(0);
  __syncwarp();
  const int lane = threadIdx.x & 31;
#define TS_PRO()
  if (wg == 2) {
    asm volatile("setmaxnreg.dec.sync.aligned.u32 56;");
    TS_PRO();
    TS(2, 62);
    if (warp == 0) producer<MASK>(M, P, base, cta, lane);
    else if (warp == 1) sync_agent<MASK>(base, cta, lane);
    else if (cta < NREG) {
      if (MASK & PH_PRE) aux_pre<MASK>(M, P, base, cta, warp - 2, lane);
      if (MASK & PH_OUT) producer2<MASK>(M, P, base, cta, warp - 2, lane);
    }
    if (warp == 1) {
      if (MASK & PH_OUT) {
        unsigned old = 0;
        if (lane == 0) asm volatile("atom.relaxed.gpu.global.add.u32 %0, [%1], 1;" : "=r"(old) : "l"(g_cnt + C_EXIT * CSTRIDE) : "memory");
        old = __shfl_sync(~0u, old, 0);
        if (old == NCTA - 1) for (int i = lane; i < C_NUM; i += 32) g_cnt[i * CSTRIDE] = 0;
      }
      mbar_wait_slow(base + SM_SIG + 8 * SIG_DONE, 0);
      if (cta >= NREG || !(MASK & PH_OUT)) { cluster_arrive(); cluster_wait(); }
    }
  } else {
    asm volatile("setmaxnreg.inc.sync.aligned.u32 224;");
    TS_PRO();
    uint32_t rel;
    asm volatile("mapa.shared::cluster.u32 %0, %1, %2;" : "=r"(rel) : "r"(base + SM_BAR + 128 + 8 * (lane & 15)), "r"(lane >> 4));
    Cons c{base, rel, 0u, lane, warp, wg, (cta * 3 + wg) * 2048};
    if (wg == 1) bar_arrive(1, 256);
    if ((MASK & PH_KV) && wi == 4 && cta < NREG) {
      if (elect()) {
#pragma unroll 1
        for (int it = 1; it < NFIRST; it++) {
          asm volatile("{\n.reg .pred p;\n.reg .u32 a, b;\nmov.u32 a, %%clock;\nXL:\nmov.u32 b, %%clock;\nsub.u32 b, b, a;\nsetp.lt.u32 p, b, %0;\n@p bra XL;\n}\n" :: "r"(it == 1 ? FGAP : FGAP2) : "memory");
          first_stage(it);
        }
      }
      __syncwarp();
    }
    TS(wg, 0);
    if (cta < NREG) {
      const int g = cta & 7, j = cta >> 3;
      Pend w = {};
#pragma unroll 1
      for (int half = 0; half < 2; half++) {
        const int h = j + 16 * half, blk = kv_slot<MASK>(h) * 16 + 2 * g;
        if (MASK & PH_KV) cons_kv<(MASK & PH_ATT) != 0>(c, h, blk, g, w, half == 1 && (MASK & PH_ATT));
        TS(wg, 1 + 4 * half);
        if (MASK & PH_ATT) {
          Att a;
          cons_q<(MASK & PH_KV) != 0>(c, h, blk + 1, w, a.o);
          TS(wg, 2 + 4 * half);
          cons_att(c, a, h, g, w);
          if (half == 0) c.signal(SIG_WAR);
#pragma unroll
          for (int i = 0; i < 8; i++) w.hi[i] = make_uint4(0, 0, 0, 0);
          TS(wg, 3 + 4 * half);
          if (MASK != PH_ALL) { tile_store<0, 4>(w.lo, ctx_off(c, h, g, 1 - wg), lane); c.signal(SIG_CTX + half); }
        } else if (MASK & PH_KV) {
          float kn = 0.f;
          out_piece<SCH_KV, true>(c, w, kv_off(c, blk + 1), blk + 1, kn, 0, true);
          for (int ks = 1; ks < 8; ks++) out_piece<SCH_KV, false>(c, w, kv_off(c, blk + 1), blk + 1, kn, ks, true);
          c.signal(SIG_KV + half);
        }
      }
      if (MASK & PH_OUT) cons_out<MASK>(c, M, P, cta, w);
    }
    if (cta >= NREG || !(MASK & PH_OUT)) {
      if (MASK & PH_CONV) cons_conv<MASK>(c, cta, cta < NREG ? CV_REG<MASK> : CV_EXTRA<MASK>);
      TS(wg, 9);
      c.signal(SIG_DONE);
      cluster_arrive();
    }
    TS(wg, 10);
  }
}

typedef CUresult (*EncFn)(CUtensorMap*, CUtensorMapDataType, cuuint32_t, void*, const cuuint64_t*, const cuuint64_t*, const cuuint32_t*, const cuuint32_t*,
                          CUtensorMapInterleave, CUtensorMapSwizzle, CUtensorMapL2promotion, CUtensorMapFloatOOBfill);
static void enc(EncFn f, CUtensorMap* m, const void* ptr, int rank, const cuuint64_t* dims, const cuuint64_t* strides, const cuuint32_t* box, CUtensorMapSwizzle sw,
                CUtensorMapDataType dt = CU_TENSOR_MAP_DATA_TYPE_BFLOAT16) {
  const cuuint32_t es[4] = {1, 1, 1, 1};
  f(m, dt, rank, (void*)ptr, dims, strides, box, es, CU_TENSOR_MAP_INTERLEAVE_NONE, sw, CU_TENSOR_MAP_L2_PROMOTION_L2_256B, CU_TENSOR_MAP_FLOAT_OOB_FILL_NONE);
}
static void enc2(EncFn f, CUtensorMap* m, const void* ptr, int cols, int rows, int brows) {
  const cuuint64_t d[2] = {(cuuint64_t)cols, (cuuint64_t)rows}, s[1] = {(cuuint64_t)cols * 2}; const cuuint32_t b[2] = {64, (cuuint32_t)brows};
  enc(f, m, ptr, 2, d, s, b, CU_TENSOR_MAP_SWIZZLE_128B);
}
static void encw(EncFn f, CUtensorMap* m, const void* ptr, int cols, int rows) {
  const cuuint64_t d[3] = {64, (cuuint64_t)rows, (cuuint64_t)cols / 64}, s[2] = {(cuuint64_t)cols * 2, 128}; const cuuint32_t b[3] = {64, 64, 2};
  enc(f, m, ptr, 3, d, s, b, CU_TENSOR_MAP_SWIZZLE_128B);
}
extern "C" void kernel_launch(void* const* d_in, const int* in_sizes, int n_in, void* d_out, int out_size) {
  static EncFn fn = nullptr;
  static int ncl = 0;
  static void* zptr = nullptr;
  static void* tptr = nullptr;
  if (!fn) {
    void* p = nullptr; cudaDriverEntryPointQueryResult qr;
    cudaGetDriverEntryPoint("cuTensorMapEncodeTiled", &p, cudaEnableDefault, &qr);
    fn = (EncFn)p;
    cudaFuncSetAttribute(gated_mix_kernel<PH_ALL>, cudaFuncAttributeMaxDynamicSharedMemorySize, SMEM_BYTES);
    cudaFuncSetAttribute(gated_mix_kernel<PH_PRE | PH_KV>, cudaFuncAttributeMaxDynamicSharedMemorySize, SMEM_BYTES);
    cudaFuncSetAttribute(gated_mix_kernel<PH_ATT | PH_CONV>, cudaFuncAttributeMaxDynamicSharedMemorySize, SMEM_BYTES);
    cudaFuncSetAttribute(gated_mix_kernel<PH_OUT>, cudaFuncAttributeMaxDynamicSharedMemorySize, SMEM_BYTES);
    cudaLaunchConfig_t cfg = {}; cfg.gridDim = NCTA; cfg.blockDim = 384; cfg.dynamicSmemBytes = SMEM_BYTES;
    cudaLaunchAttribute at; at.id = cudaLaunchAttributeClusterDimension; at.val.clusterDim.x = 2; at.val.clusterDim.y = 1; at.val.clusterDim.z = 1;
    cfg.attrs = &at; cfg.numAttrs = 1;
    cudaOccupancyMaxActiveClusters(&ncl, gated_mix_kernel<PH_ALL>, &cfg);
    cudaGetSymbolAddress(&zptr, g_z);
    cudaGetSymbolAddress(&tptr, g_T);
  }
  Maps M;
  enc2(fn, &M.x, d_in[0], 1024, 2048, 128);
  enc2(fn, &M.c, d_in[7], 512, 2048, 128);
  enc2(fn, &M.wq, d_in[8], 4096, 1024, 64);
  encw(fn, &M.wk, d_in[9], 4096, 512);
  encw(fn, &M.wv, d_in[10], 4096, 512);
  encw(fn, &M.wo, d_in[11], 1024, 4096);
  { const cuuint64_t d[3] = {64, 32, 1024}, s[2] = {128, 4096}; const cuuint32_t b[3] = {64, 40, 1}; enc(fn, &M.h, d_in[4], 3, d, s, b, CU_TENSOR_MAP_SWIZZLE_NONE); }
  enc2(fn, &M.z, zptr, 2048, 1024, 128);
  enc2(fn, &M.out, d_out, 1024, 2048, 16);
  { const cuuint64_t d[2] = {512, 512 * 16}, s[1] = {2048}; const cuuint32_t b[2] = {256, 8};
    enc(fn, &M.ctx, tptr, 2, d, s, b, CU_TENSOR_MAP_SWIZZLE_NONE, CU_TENSOR_MAP_DATA_TYPE_UINT32); }
  { const cuuint64_t d[4] = {1024, 2, 256, 4}, s[3] = {2048, 16384, 4096}; const cuuint32_t b[4] = {64, 2, 9, 4};
    enc(fn, &M.k, d_in[1], 4, d, s, b, CU_TENSOR_MAP_SWIZZLE_128B); enc(fn, &M.v, d_in[2], 4, d, s, b, CU_TENSOR_MAP_SWIZZLE_128B); }
  Params P{(const __nv_bfloat16*)d_in[0], (const __nv_bfloat16*)d_in[3],
           (const __nv_bfloat16*)d_in[5], (const __nv_bfloat16*)d_in[12], (__nv_bfloat16*)d_out};
  bool split = 2 * ncl < NCTA;
  if (!split) {
    gated_mix_kernel<PH_ALL><<<NCTA, 384, SMEM_BYTES>>>(M, P);
  } else {
    gated_mix_kernel<PH_PRE | PH_KV><<<NCTA, 384, SMEM_BYTES>>>(M, P);
    gated_mix_kernel<PH_ATT | PH_CONV><<<NCTA, 384, SMEM_BYTES>>>(M, P);
    gated_mix_kernel<PH_OUT><<<NCTA, 384, SMEM_BYTES>>>(M, P);
  }
}
```

```cpp
#include <cuda_runtime.h>
#include <cuda.h>
#include <cuda_bf16.h>
#include <stdint.h>

template<int TB> __device__ __forceinline__ void wgmma_ss_n256(float (&d)[128], uint64_t da, uint64_t db, int scale_d) {
  asm volatile("{\n.reg .pred p;\nsetp.ne.b32 p, %130, 0;\n"
    "wgmma.mma_async.sync.aligned.m64n256k16.f32.bf16.bf16 {%0, %1, %2, %3, %4, %5, %6, %7, %8, %9, %10, %11, %12, %13, %14, %15, %16, %17, %18, %19, %20, %21, %22, %23, %24, %25, %26, %27, %28, %29, %30, %31, %32, %33, %34, %35, %36, %37, %38, %39, %40, %41, %42, %43, %44, %45, %46, %47, %48, %49, %50, %51, %52, %53, %54, %55, %56, %57, %58, %59, %60, %61, %62, %63, %64, %65, %66, %67, %68, %69, %70, %71, %72, %73, %74, %75, %76, %77, %78, %79, %80, %81, %82, %83, %84, %85, %86, %87, %88, %89, %90, %91, %92, %93, %94, %95, %96, %97, %98, %99, %100, %101, %102, %103, %104, %105, %106, %107, %108, %109, %110, %111, %112, %113, %114, %115, %116, %117, %118, %119, %120, %121, %122, %123, %124, %125, %126, %127}, %128, %129, p, 1, 1, 0, %131;\n}\n"
    : "+f"(d[0]), "+f"(d[1]), "+f"(d[2]), "+f"(d[3]), "+f"(d[4]), "+f"(d[5]), "+f"(d[6]), "+f"(d[7]), "+f"(d[8]), "+f"(d[9]), "+f"(d[10]), "+f"(d[11]), "+f"(d[12]), "+f"(d[13]), "+f"(d[14]), "+f"(d[15]), "+f"(d[16]), "+f"(d[17]), "+f"(d[18]), "+f"(d[19]), "+f"(d[20]), "+f"(d[21]), "+f"(d[22]), "+f"(d[23]), "+f"(d[24]), "+f"(d[25]), "+f"(d[26]), "+f"(d[27]), "+f"(d[28]), "+f"(d[29]), "+f"(d[30]), "+f"(d[31]), "+f"(d[32]), "+f"(d[33]), "+f"(d[34]), "+f"(d[35]), "+f"(d[36]), "+f"(d[37]), "+f"(d[38]), "+f"(d[39]), "+f"(d[40]), "+f"(d[41]), "+f"(d[42]), "+f"(d[43]), "+f"(d[44]), "+f"(d[45]), "+f"(d[46]), "+f"(d[47]), "+f"(d[48]), "+f"(d[49]), "+f"(d[50]), "+f"(d[51]), "+f"(d[52]), "+f"(d[53]), "+f"(d[54]), "+f"(d[55]), "+f"(d[56]), "+f"(d[57]), "+f"(d[58]), "+f"(d[59]), "+f"(d[60]), "+f"(d[61]), "+f"(d[62]), "+f"(d[63]), "+f"(d[64]), "+f"(d[65]), "+f"(d[66]), "+f"(d[67]), "+f"(d[68]), "+f"(d[69]), "+f"(d[70]), "+f"(d[71]), "+f"(d[72]), "+f"(d[73]), "+f"(d[74]), "+f"(d[75]), "+f"(d[76]), "+f"(d[77]), "+f"(d[78]), "+f"(d[79]), "+f"(d[80]), "+f"(d[81]), "+f"(d[82]), "+f"(d[83]), "+f"(d[84]), "+f"(d[85]), "+f"(d[86]), "+f"(d[87]), "+f"(d[88]), "+f"(d[89]), "+f"(d[90]), "+f"(d[91]), "+f"(d[92]), "+f"(d[93]), "+f"(d[94]), "+f"(d[95]), "+f"(d[96]), "+f"(d[97]), "+f"(d[98]), "+f"(d[99]), "+f"(d[100]), "+f"(d[101]), "+f"(d[102]), "+f"(d[103]), "+f"(d[104]), "+f"(d[105]), "+f"(d[106]), "+f"(d[107]), "+f"(d[108]), "+f"(d[109]), "+f"(d[110]), "+f"(d[111]), "+f"(d[112]), "+f"(d[113]), "+f"(d[114]), "+f"(d[115]), "+f"(d[116]), "+f"(d[117]), "+f"(d[118]), "+f"(d[119]), "+f"(d[120]), "+f"(d[121]), "+f"(d[122]), "+f"(d[123]), "+f"(d[124]), "+f"(d[125]), "+f"(d[126]), "+f"(d[127])
    : "l"(da), "l"(db), "r"(scale_d), "n"(TB));
}
template<int TB> __device__ __forceinline__ void wgmma_ss_n128(float (&d)[64], uint64_t da, uint64_t db, int scale_d) {
  asm volatile("{\n.reg .pred p;\nsetp.ne.b32 p, %66, 0;\n"
    "wgmma.mma_async.sync.aligned.m64n128k16.f32.bf16.bf16 {%0, %1, %2, %3, %4, %5, %6, %7, %8, %9, %10, %11, %12, %13, %14, %15, %16, %17, %18, %19, %20, %21, %22, %23, %24, %25, %26, %27, %28, %29, %30, %31, %32, %33, %34, %35, %36, %37, %38, %39, %40, %41, %42, %43, %44, %45, %46, %47, %48, %49, %50, %51, %52, %53, %54, %55, %56, %57, %58, %59, %60, %61, %62, %63}, %64, %65, p, 1, 1, 0, %67;\n}\n"
    : "+f"(d[0]), "+f"(d[1]), "+f"(d[2]), "+f"(d[3]), "+f"(d[4]), "+f"(d[5]), "+f"(d[6]), "+f"(d[7]), "+f"(d[8]), "+f"(d[9]), "+f"(d[10]), "+f"(d[11]), "+f"(d[12]), "+f"(d[13]), "+f"(d[14]), "+f"(d[15]), "+f"(d[16]), "+f"(d[17]), "+f"(d[18]), "+f"(d[19]), "+f"(d[20]), "+f"(d[21]), "+f"(d[22]), "+f"(d[23]), "+f"(d[24]), "+f"(d[25]), "+f"(d[26]), "+f"(d[27]), "+f"(d[28]), "+f"(d[29]), "+f"(d[30]), "+f"(d[31]), "+f"(d[32]), "+f"(d[33]), "+f"(d[34]), "+f"(d[35]), "+f"(d[36]), "+f"(d[37]), "+f"(d[38]), "+f"(d[39]), "+f"(d[40]), "+f"(d[41]), "+f"(d[42]), "+f"(d[43]), "+f"(d[44]), "+f"(d[45]), "+f"(d[46]), "+f"(d[47]), "+f"(d[48]), "+f"(d[49]), "+f"(d[50]), "+f"(d[51]), "+f"(d[52]), "+f"(d[53]), "+f"(d[54]), "+f"(d[55]), "+f"(d[56]), "+f"(d[57]), "+f"(d[58]), "+f"(d[59]), "+f"(d[60]), "+f"(d[61]), "+f"(d[62]), "+f"(d[63])
    : "l"(da), "l"(db), "r"(scale_d), "n"(TB));
}
template<int TB> __device__ __forceinline__ void wgmma_rs_n32(float (&d)[16], uint32_t a0, uint32_t a1, uint32_t a2, uint32_t a3, uint64_t db, int scale_d) {
  asm volatile("{\n.reg .pred p;\nsetp.ne.b32 p, %21, 0;\n"
    "wgmma.mma_async.sync.aligned.m64n32k16.f32.bf16.bf16 {%0, %1, %2, %3, %4, %5, %6, %7, %8, %9, %10, %11, %12, %13, %14, %15}, {%16, %17, %18, %19}, %20, p, 1, 1, %22;\n}\n"
    : "+f"(d[0]), "+f"(d[1]), "+f"(d[2]), "+f"(d[3]), "+f"(d[4]), "+f"(d[5]), "+f"(d[6]), "+f"(d[7]), "+f"(d[8]), "+f"(d[9]), "+f"(d[10]), "+f"(d[11]), "+f"(d[12]), "+f"(d[13]), "+f"(d[14]), "+f"(d[15])
    : "r"(a0), "r"(a1), "r"(a2), "r"(a3), "l"(db), "r"(scale_d), "n"(TB));
}
__device__ __forceinline__ void wgmma_pv_sel(float (&d)[64], const uint32_t (&p)[32], uint64_t db, int full, int acc, int wg) {
  asm volatile("{\n.reg .pred q, s, w;\n.reg .b64 t;\nsetp.eq.b32 w, %99, 0;\nsetp.ne.b32 s, %98, 0;\nsetp.eq.b32 q, %97, 0;\n@q bra.uni LH;\n"
    "wgmma.fence.sync.aligned;\n"
    "add.s64 t, %96, 0;\nwgmma.mma_async.sync.aligned.m64n128k16.f32.bf16.bf16 {%0, %1, %2, %3, %4, %5, %6, %7, %8, %9, %10, %11, %12, %13, %14, %15, %16, %17, %18, %19, %20, %21, %22, %23, %24, %25, %26, %27, %28, %29, %30, %31, %32, %33, %34, %35, %36, %37, %38, %39, %40, %41, %42, %43, %44, %45, %46, %47, %48, %49, %50, %51, %52, %53, %54, %55, %56, %57, %58, %59, %60, %61, %62, %63}, {%64, %65, %66, %67}, t, s, 1, 1, 1;\n"
    "add.s64 t, %96, 256;\nwgmma.mma_async.sync.aligned.m64n128k16.f32.bf16.bf16 {%0, %1, %2, %3, %4, %5, %6, %7, %8, %9, %10, %11, %12, %13, %14, %15, %16, %17, %18, %19, %20, %21, %22, %23, %24, %25, %26, %27, %28, %29, %30, %31, %32, %33, %34, %35, %36, %37, %38, %39, %40, %41, %42, %43, %44, %45, %46, %47, %48, %49, %50, %51, %52, %53, %54, %55, %56, %57, %58, %59, %60, %61, %62, %63}, {%68, %69, %70, %71}, t, 1, 1, 1, 1;\n"
    "add.s64 t, %96, 512;\nwgmma.mma_async.sync.aligned.m64n128k16.f32.bf16.bf16 {%0, %1, %2, %3, %4, %5, %6, %7, %8, %9, %10, %11, %12, %13, %14, %15, %16, %17, %18, %19, %20, %21, %22, %23, %24, %25, %26, %27, %28, %29, %30, %31, %32, %33, %34, %35, %36, %37, %38, %39, %40, %41, %42, %43, %44, %45, %46, %47, %48, %49, %50, %51, %52, %53, %54, %55, %56, %57, %58, %59, %60, %61, %62, %63}, {%72, %73, %74, %75}, t, 1, 1, 1, 1;\n"
    "add.s64 t, %96, 768;\nwgmma.mma_async.sync.aligned.m64n128k16.f32.bf16.bf16 {%0, %1, %2, %3, %4, %5, %6, %7, %8, %9, %10, %11, %12, %13, %14, %15, %16, %17, %18, %19, %20, %21, %22, %23, %24, %25, %26, %27, %28, %29, %30, %31, %32, %33, %34, %35, %36, %37, %38, %39, %40, %41, %42, %43, %44, %45, %46, %47, %48, %49, %50, %51, %52, %53, %54, %55, %56, %57, %58, %59, %60, %61, %62, %63}, {%76, %77, %78, %79}, t, 1, 1, 1, 1;\n"
    "add.s64 t, %96, 1024;\nwgmma.mma_async.sync.aligned.m64n128k16.f32.bf16.bf16 {%0, %1, %2, %3, %4, %5, %6, %7, %8, %9, %10, %11, %12, %13, %14, %15, %16, %17, %18, %19, %20, %21, %22, %23, %24, %25, %26, %27, %28, %29, %30, %31, %32, %33, %34, %35, %36, %37, %38, %39, %40, %41, %42, %43, %44, %45, %46, %47, %48, %49, %50, %51, %52, %53, %54, %55, %56, %57, %58, %59, %60, %61, %62, %63}, {%80, %81, %82, %83}, t, 1, 1, 1, 1;\n"
    "add.s64 t, %96, 1280;\nwgmma.mma_async.sync.aligned.m64n128k16.f32.bf16.bf16 {%0, %1, %2, %3, %4, %5, %6, %7, %8, %9, %10, %11, %12, %13, %14, %15, %16, %17, %18, %19, %20, %21, %22, %23, %24, %25, %26, %27, %28, %29, %30, %31, %32, %33, %34, %35, %36, %37, %38, %39, %40, %41, %42, %43, %44, %45, %46, %47, %48, %49, %50, %51, %52, %53, %54, %55, %56, %57, %58, %59, %60, %61, %62, %63}, {%84, %85, %86, %87}, t, 1, 1, 1, 1;\n"
    "@w bar.arrive 2, 256;\n@!w bar.arrive 1, 256;\n"
    "add.s64 t, %96, 1536;\nwgmma.mma_async.sync.aligned.m64n128k16.f32.bf16.bf16 {%0, %1, %2, %3, %4, %5, %6, %7, %8, %9, %10, %11, %12, %13, %14, %15, %16, %17, %18, %19, %20, %21, %22, %23, %24, %25, %26, %27, %28, %29, %30, %31, %32, %33, %34, %35, %36, %37, %38, %39, %40, %41, %42, %43, %44, %45, %46, %47, %48, %49, %50, %51, %52, %53, %54, %55, %56, %57, %58, %59, %60, %61, %62, %63}, {%88, %89, %90, %91}, t, 1, 1, 1, 1;\n"
    "add.s64 t, %96, 1792;\nwgmma.mma_async.sync.aligned.m64n128k16.f32.bf16.bf16 {%0, %1, %2, %3, %4, %5, %6, %7, %8, %9, %10, %11, %12, %13, %14, %15, %16, %17, %18, %19, %20, %21, %22, %23, %24, %25, %26, %27, %28, %29, %30, %31, %32, %33, %34, %35, %36, %37, %38, %39, %40, %41, %42, %43, %44, %45, %46, %47, %48, %49, %50, %51, %52, %53, %54, %55, %56, %57, %58, %59, %60, %61, %62, %63}, {%92, %93, %94, %95}, t, 1, 1, 1, 1;\n"
    "wgmma.commit_group.sync.aligned;\n"
    "bra.uni LE;\nLH:\n"
    "wgmma.fence.sync.aligned;\n"
    "add.s64 t, %96, 0;\nwgmma.mma_async.sync.aligned.m64n128k16.f32.bf16.bf16 {%0, %1, %2, %3, %4, %5, %6, %7, %8, %9, %10, %11, %12, %13, %14, %15, %16, %17, %18, %19, %20, %21, %22, %23, %24, %25, %26, %27, %28, %29, %30, %31, %32, %33, %34, %35, %36, %37, %38, %39, %40, %41, %42, %43, %44, %45, %46, %47, %48, %49, %50, %51, %52, %53, %54, %55, %56, %57, %58, %59, %60, %61, %62, %63}, {%80, %81, %82, %83}, t, s, 1, 1, 1;\n"
    "add.s64 t, %96, 256;\nwgmma.mma_async.sync.aligned.m64n128k16.f32.bf16.bf16 {%0, %1, %2, %3, %4, %5, %6, %7, %8, %9, %10, %11, %12, %13, %14, %15, %16, %17, %18, %19, %20, %21, %22, %23, %24, %25, %26, %27, %28, %29, %30, %31, %32, %33, %34, %35, %36, %37, %38, %39, %40, %41, %42, %43, %44, %45, %46, %47, %48, %49, %50, %51, %52, %53, %54, %55, %56, %57, %58, %59, %60, %61, %62, %63}, {%84, %85, %86, %87}, t, 1, 1, 1, 1;\n"
    "@w bar.arrive 2, 256;\n@!w bar.arrive 1, 256;\n"
    "add.s64 t, %96, 512;\nwgmma.mma_async.sync.aligned.m64n128k16.f32.bf16.bf16 {%0, %1, %2, %3, %4, %5, %6, %7, %8, %9, %10, %11, %12, %13, %14, %15, %16, %17, %18, %19, %20, %21, %22, %23, %24, %25, %26, %27, %28, %29, %30, %31, %32, %33, %34, %35, %36, %37, %38, %39, %40, %41, %42, %43, %44, %45, %46, %47, %48, %49, %50, %51, %52, %53, %54, %55, %56, %57, %58, %59, %60, %61, %62, %63}, {%88, %89, %90, %91}, t, 1, 1, 1, 1;\n"
    "add.s64 t, %96, 768;\nwgmma.mma_async.sync.aligned.m64n128k16.f32.bf16.bf16 {%0, %1, %2, %3, %4, %5, %6, %7, %8, %9, %10, %11, %12, %13, %14, %15, %16, %17, %18, %19, %20, %21, %22, %23, %24, %25, %26, %27, %28, %29, %30, %31, %32, %33, %34, %35, %36, %37, %38, %39, %40, %41, %42, %43, %44, %45, %46, %47, %48, %49, %50, %51, %52, %53, %54, %55, %56, %57, %58, %59, %60, %61, %62, %63}, {%92, %93, %94, %95}, t, 1, 1, 1, 1;\n"
    "wgmma.commit_group.sync.aligned;\n"
    "LE:\n}\n"
    : "+f"(d[0]), "+f"(d[1]), "+f"(d[2]), "+f"(d[3]), "+f"(d[4]), "+f"(d[5]), "+f"(d[6]), "+f"(d[7]), "+f"(d[8]), "+f"(d[9]), "+f"(d[10]), "+f"(d[11]), "+f"(d[12]), "+f"(d[13]), "+f"(d[14]), "+f"(d[15]), "+f"(d[16]), "+f"(d[17]), "+f"(d[18]), "+f"(d[19]), "+f"(d[20]), "+f"(d[21]), "+f"(d[22]), "+f"(d[23]), "+f"(d[24]), "+f"(d[25]), "+f"(d[26]), "+f"(d[27]), "+f"(d[28]), "+f"(d[29]), "+f"(d[30]), "+f"(d[31]), "+f"(d[32]), "+f"(d[33]), "+f"(d[34]), "+f"(d[35]), "+f"(d[36]), "+f"(d[37]), "+f"(d[38]), "+f"(d[39]), "+f"(d[40]), "+f"(d[41]), "+f"(d[42]), "+f"(d[43]), "+f"(d[44]), "+f"(d[45]), "+f"(d[46]), "+f"(d[47]), "+f"(d[48]), "+f"(d[49]), "+f"(d[50]), "+f"(d[51]), "+f"(d[52]), "+f"(d[53]), "+f"(d[54]), "+f"(d[55]), "+f"(d[56]), "+f"(d[57]), "+f"(d[58]), "+f"(d[59]), "+f"(d[60]), "+f"(d[61]), "+f"(d[62]), "+f"(d[63])
    : "r"(p[0]), "r"(p[1]), "r"(p[2]), "r"(p[3]), "r"(p[4]), "r"(p[5]), "r"(p[6]), "r"(p[7]), "r"(p[8]), "r"(p[9]), "r"(p[10]), "r"(p[11]), "r"(p[12]), "r"(p[13]), "r"(p[14]), "r"(p[15]), "r"(p[16]), "r"(p[17]), "r"(p[18]), "r"(p[19]), "r"(p[20]), "r"(p[21]), "r"(p[22]), "r"(p[23]), "r"(p[24]), "r"(p[25]), "r"(p[26]), "r"(p[27]), "r"(p[28]), "r"(p[29]), "r"(p[30]), "r"(p[31]), "l"(db), "r"(full), "r"(acc), "r"(wg) : "memory");
}

constexpr int NCTA = 132, NREG = 128;
constexpr int UNIT = 16384, NUNIT = 14;
constexpr uint32_t SMEM_BASE = 1024;
constexpr int SM_BAR = NUNIT * UNIT;
constexpr int SM_GATE = SM_BAR + 1024;
constexpr int SMEM_BYTES = SM_BAR + 1536;
constexpr int UPITCH = 4160, UCH = 2 * UPITCH;
constexpr float QSCALE = 0.08838834764831845f * 1.4426950408889634f;
constexpr float BOUND2 = 60.f * 60.f / 1.15f;
#define CONV_REG 5
constexpr int C_KV = 0;
constexpr int C_CTX = 32;
constexpr int C_U = 48;
constexpr int C_Z = 80;
constexpr int C_GATE = 88;
constexpr int C_EXIT = 89;
#define ATT_SPLIT 4
#define ONE 0
#define REL1 1
#define RELW 0
#define SL_BAR 256
#define SL_CNT 0
#define Z_AT 60
#define PRE_SLEEP 300
#define GATE_SLEEP 1000
#define OC_S0 2
#define OC_S1 11
#define OC_L0 18
#define OC_L1 18
#define ST_1 4
#define ST_D 2
#define SCH_KV 0x6665544433221100ull
#define SCH_Q 0x6665544433221100ull
#define NK_AT 1
#ifndef NV_AT
#define NV_AT 3
#endif
#define CHK_D 11
#define FGAP 600
#define FGAP2 200
constexpr int PRE_EARLY = 2, NFIRST = 4;
constexpr int C_WAR = 96;
constexpr int C_NUM = 112;
constexpr int CSTRIDE = 32;
constexpr int SM_KMAX = SM_BAR + 640, SM_DUMMY = SM_BAR + 648, SM_PRE = SM_BAR + 112, SM_SIG = SM_BAR + 256, SM_RDY = SM_BAR + 384;
enum { SIG_KV = 0, SIG_CTX = 2, SIG_Z = 4, SIG_DONE = 8, SIG_WAR = 9, SIG_ATT = 10 };
enum { RDY_KV = 0, RDY_CTX = 2, RDY_WAR = 4, RDY_G = 5, RDY_X = 6, RDY_AUX = 7, RDY_U = 8, RDY_Z = 9 };
enum { PH_PRE = 1, PH_KV = 2, PH_ATT = 4, PH_CONV = 8, PH_OUT = 16, PH_ALL = 31 };

constexpr uint32_t T_CTX = 0, T_KV = 16 * 32 * 32768, T_BYTES = T_KV + 32 * 16 * 65536;
__device__ __align__(1024) uint8_t g_T[T_BYTES];
__device__ __align__(1024) uint8_t g_u[1024 * UCH];
__device__ __align__(1024) __nv_bfloat16 g_z[1024 * 2048];
__device__ __align__(1024) float g_gate[2048];
__device__ __align__(1024) float g_kn2[32 * 128];
__device__ __align__(1024) unsigned g_cnt[C_NUM * CSTRIDE];

struct __align__(64) Maps { CUtensorMap c, wk, wv, x, wq, wo, h, z, out, ctx, k, v; };
struct Params {
  const __nv_bfloat16 *x, *shift, *D, *gw;
  __nv_bfloat16* out;
};

__device__ __forceinline__ void wg_fence() { asm volatile("wgmma.fence.sync.aligned;" ::: "memory"); }
__device__ __forceinline__ void wg_commit() { asm volatile("wgmma.commit_group.sync.aligned;" ::: "memory"); }
template<int N> __device__ __forceinline__ void wg_wait() { asm volatile("wgmma.wait_group.sync.aligned %0;" :: "n"(N) : "memory"); }
__device__ __forceinline__ uint64_t odesc(uint32_t addr, uint32_t lbo, uint32_t sbo, uint32_t swz) {
  uint64_t d = (uint64_t)(addr >> 4) + (((uint64_t)(lbo >> 4) << 16) | ((uint64_t)(sbo >> 4) << 32) | ((uint64_t)swz << 62));
  asm volatile("" : "+l"(d));
  return d;
}
__device__ __forceinline__ void mbar_init(uint32_t bar, int cnt) { asm volatile("mbarrier.init.shared::cta.b64 [%0], %1;" :: "r"(bar), "r"(cnt)); }
__device__ __forceinline__ void mbar_expect(uint32_t bar, uint32_t bytes) { asm volatile("mbarrier.arrive.expect_tx.shared::cta.b64 _, [%0], %1;" :: "r"(bar), "r"(bytes) : "memory"); }
__device__ __forceinline__ void mbar_arrive(uint32_t bar) { asm volatile("mbarrier.arrive.shared::cta.b64 _, [%0];" :: "r"(bar) : "memory"); }
__device__ __forceinline__ void mbar_wait(uint32_t bar, uint32_t parity) {
  asm volatile("{\n.reg .pred p;\nLW:\nmbarrier.try_wait.parity.shared::cta.b64 p, [%0], %1;\n@!p bra LW;\n}\n" :: "r"(bar), "r"(parity) : "memory");
}
__device__ __forceinline__ void mbar_wait_slow(uint32_t bar, uint32_t parity) {
  asm volatile("{\n.reg .pred p;\n.reg .u32 n;\nmov.u32 n, 0;\n"
    "LW:\nmbarrier.test_wait.parity.shared::cta.b64 p, [%0], %1;\n@p bra LD;\n"
    "nanosleep.u32 %2;\nadd.u32 n, n, 1;\nsetp.lt.u32 p, n, 16777216;\n@p bra LW;\ntrap;\nLD:\n}\n" :: "r"(bar), "r"(parity), "n"(SL_BAR) : "memory");
}
__device__ __forceinline__ void mbar_wait_all(uint32_t bar, uint32_t parity) {
  asm volatile("{\n.reg .pred p, q;\nLW:\nmbarrier.try_wait.parity.shared::cta.b64 p, [%0], %1;\nvote.sync.all.pred q, p, 0xffffffff;\n@!q bra.uni LW;\n}\n" :: "r"(bar), "r"(parity) : "memory");
}
__device__ __forceinline__ void cnt_wait(const unsigned* p, unsigned target) {
  asm volatile("{\n.reg .pred p;\n.reg .u32 n, v;\nmov.u32 n, 0;\n"
    "LW:\nld.relaxed.gpu.global.u32 v, [%0];\nsetp.ge.u32 p, v, %1;\n@p bra LD;\n"
    "nanosleep.u32 %2;\nadd.u32 n, n, 1;\nsetp.lt.u32 p, n, 4194304;\n@p bra LW;\ntrap;\nLD:\nfence.acquire.gpu;\nfence.proxy.async.global;\n}\n" :: "l"(p), "r"(target), "n"(SL_CNT) : "memory");
}
__device__ __forceinline__ void cnt_signal(unsigned* p, int lane) {
  __syncwarp();
  if (lane == 0) asm volatile("red.release.gpu.global.add.u32 [%0], 1;" :: "l"(p) : "memory");
}
__device__ __forceinline__ void cnt_publish(unsigned* p, unsigned n, bool fence) {
  if (fence) asm volatile("fence.release.gpu;" ::: "memory");
  asm volatile("red.relaxed.gpu.global.add.u32 [%0], %1;" :: "l"(p), "r"(n) : "memory");
}
__device__ __forceinline__ uint64_t pol_first() { uint64_t p; asm("createpolicy.fractional.L2::evict_first.b64 %0, 1.0;" : "=l"(p)); return p; }
__device__ __forceinline__ void bulk_g2s(uint32_t dst, const void* src, uint32_t bytes, uint32_t bar, bool stream = false) {
  if (stream) asm volatile("cp.async.bulk.shared::cluster.global.mbarrier::complete_tx::bytes.L2::cache_hint [%0], [%1], %2, [%3], %4;" :: "r"(dst), "l"(src), "r"(bytes), "r"(bar), "l"(pol_first()) : "memory");
  else asm volatile("cp.async.bulk.shared::cluster.global.mbarrier::complete_tx::bytes [%0], [%1], %2, [%3];" :: "r"(dst), "l"(src), "r"(bytes), "r"(bar) : "memory");
}
__device__ __forceinline__ void tma2d(uint32_t dst, const CUtensorMap* m, int x, int y, uint32_t bar, bool stream = false) {
  if (stream) asm volatile("cp.async.bulk.tensor.2d.shared::cluster.global.mbarrier::complete_tx::bytes.L2::cache_hint [%0], [%1, {%3, %4}], [%2], %5;" :: "r"(dst), "l"(m), "r"(bar), "r"(x), "r"(y), "l"(pol_first()) : "memory");
  else asm volatile("cp.async.bulk.tensor.2d.shared::cluster.global.mbarrier::complete_tx::bytes [%0], [%1, {%3, %4}], [%2];" :: "r"(dst), "l"(m), "r"(bar), "r"(x), "r"(y) : "memory");
}
__device__ __forceinline__ void tma3d(uint32_t dst, const CUtensorMap* m, int x, int y, int z, uint32_t bar, bool stream = false) {
  if (stream) asm volatile("cp.async.bulk.tensor.3d.shared::cluster.global.mbarrier::complete_tx::bytes.L2::cache_hint [%0], [%1, {%3, %4, %5}], [%2], %6;" :: "r"(dst), "l"(m), "r"(bar), "r"(x), "r"(y), "r"(z), "l"(pol_first()) : "memory");
  else asm volatile("cp.async.bulk.tensor.3d.shared::cluster.global.mbarrier::complete_tx::bytes [%0], [%1, {%3, %4, %5}], [%2];" :: "r"(dst), "l"(m), "r"(bar), "r"(x), "r"(y), "r"(z) : "memory");
}
__device__ __forceinline__ void tma4d(uint32_t dst, const CUtensorMap* m, int x, int y, int z, int w, uint32_t bar, bool stream = false) {
  if (stream) asm volatile("cp.async.bulk.tensor.4d.shared::cluster.global.mbarrier::complete_tx::bytes.L2::cache_hint [%0], [%1, {%3, %4, %5, %6}], [%2], %7;" :: "r"(dst), "l"(m), "r"(bar), "r"(x), "r"(y), "r"(z), "r"(w), "l"(pol_first()) : "memory");
  else asm volatile("cp.async.bulk.tensor.4d.shared::cluster.global.mbarrier::complete_tx::bytes [%0], [%1, {%3, %4, %5, %6}], [%2];" :: "r"(dst), "l"(m), "r"(bar), "r"(x), "r"(y), "r"(z), "r"(w) : "memory");
}
__device__ __forceinline__ void bulk_g2s_mc(uint32_t dst, const void* src, uint32_t bytes, uint32_t bar, bool stream = false) {
  if (stream) asm volatile("cp.async.bulk.shared::cluster.global.mbarrier::complete_tx::bytes.multicast::cluster.L2::cache_hint [%0], [%1], %2, [%3], %4, %5;" :: "r"(dst), "l"(src), "r"(bytes), "r"(bar), "h"((uint16_t)3), "l"(pol_first()) : "memory");
  else asm volatile("cp.async.bulk.shared::cluster.global.mbarrier::complete_tx::bytes.multicast::cluster [%0], [%1], %2, [%3], %4;" :: "r"(dst), "l"(src), "r"(bytes), "r"(bar), "h"((uint16_t)3) : "memory");
}
__device__ __forceinline__ void tma2d_mc(uint32_t dst, const CUtensorMap* m, int x, int y, uint32_t bar, bool stream = false) {
  if (stream) asm volatile("cp.async.bulk.tensor.2d.shared::cluster.global.mbarrier::complete_tx::bytes.multicast::cluster.L2::cache_hint [%0], [%1, {%3, %4}], [%2], %5, %6;" :: "r"(dst), "l"(m), "r"(bar), "r"(x), "r"(y), "h"((uint16_t)3), "l"(pol_first()) : "memory");
  else asm volatile("cp.async.bulk.tensor.2d.shared::cluster.global.mbarrier::complete_tx::bytes.multicast::cluster [%0], [%1, {%3, %4}], [%2], %5;" :: "r"(dst), "l"(m), "r"(bar), "r"(x), "r"(y), "h"((uint16_t)3) : "memory");
}
__device__ __forceinline__ void tma3d_mc(uint32_t dst, const CUtensorMap* m, int x, int y, int z, uint32_t bar, bool stream = false) {
  if (stream) asm volatile("cp.async.bulk.tensor.3d.shared::cluster.global.mbarrier::complete_tx::bytes.multicast::cluster.L2::cache_hint [%0], [%1, {%3, %4, %5}], [%2], %6, %7;" :: "r"(dst), "l"(m), "r"(bar), "r"(x), "r"(y), "r"(z), "h"((uint16_t)3), "l"(pol_first()) : "memory");
  else asm volatile("cp.async.bulk.tensor.3d.shared::cluster.global.mbarrier::complete_tx::bytes.multicast::cluster [%0], [%1, {%3, %4, %5}], [%2], %6;" :: "r"(dst), "l"(m), "r"(bar), "r"(x), "r"(y), "r"(z), "h"((uint16_t)3) : "memory");
}
__device__ __forceinline__ void map_pf(const CUtensorMap* m) { asm volatile("prefetch.tensormap [%0];" :: "l"(m) : "memory"); }
__device__ __forceinline__ bool elect() {
  uint32_t r; asm volatile("{\n.reg .pred p;\nelect.sync _|p, 0xffffffff;\nselp.u32 %0, 1, 0, p;\n}\n" : "=r"(r)); return r != 0;
}
__device__ __forceinline__ void cluster_arrive() { asm volatile("barrier.cluster.arrive;" ::: "memory"); }
__device__ __forceinline__ void cluster_wait() { asm volatile("barrier.cluster.wait;" ::: "memory"); }
__device__ __forceinline__ void bar_sync(int id, int n) { asm volatile("bar.sync %0, %1;" :: "r"(id), "r"(n) : "memory"); }
__device__ __forceinline__ void bar_arrive(int id, int n) { asm volatile("bar.arrive %0, %1;" :: "r"(id), "r"(n) : "memory"); }
__device__ __forceinline__ void fence_async_smem() { asm volatile("fence.proxy.async.shared::cta;" ::: "memory"); }
__device__ __forceinline__ float ex2(float x) { float y; asm("ex2.approx.ftz.f32 %0, %1;" : "=f"(y) : "f"(x)); return y; }
__device__ __forceinline__ float rcp(float x) { float y; asm("rcp.approx.ftz.f32 %0, %1;" : "=f"(y) : "f"(x)); return y; }
__device__ __forceinline__ uint32_t pack_bf16(float lo, float hi) { uint32_t r; asm("cvt.rn.bf16x2.f32 %0, %1, %2;" : "=r"(r) : "f"(hi), "f"(lo)); return r; }
__device__ __forceinline__ uint32_t hmul2(uint32_t a, uint32_t b) { uint32_t r; asm("mul.rn.bf16x2 %0, %1, %2;" : "=r"(r) : "r"(a), "r"(b)); return r; }
__device__ __forceinline__ uint32_t hadd2(uint32_t a, uint32_t b) { uint32_t r; asm("add.rn.bf16x2 %0, %1, %2;" : "=r"(r) : "r"(a), "r"(b)); return r; }
__device__ __forceinline__ uint32_t hfma2(uint32_t a, uint32_t b, uint32_t c) { uint32_t r; asm("fma.rn.bf16x2 %0, %1, %2, %3;" : "=r"(r) : "r"(a), "r"(b), "r"(c)); return r; }
__device__ __forceinline__ float bf_lo(uint32_t a) { return __uint_as_float(a << 16); }
__device__ __forceinline__ float bf_hi(uint32_t a) { return __uint_as_float(a & 0xffff0000u); }
__device__ __forceinline__ uint32_t lds32(uint32_t a) { uint32_t v; asm volatile("ld.shared.u32 %0, [%1];" : "=r"(v) : "r"(a) : "memory"); return v; }
__device__ __forceinline__ float2 lds64f(uint32_t a) { float2 v; asm volatile("ld.shared.v2.f32 {%0,%1}, [%2];" : "=f"(v.x), "=f"(v.y) : "r"(a) : "memory"); return v; }
__device__ __forceinline__ uint4 lds128(uint32_t a) { uint4 v; asm volatile("ld.shared.v4.u32 {%0,%1,%2,%3}, [%4];" : "=r"(v.x), "=r"(v.y), "=r"(v.z), "=r"(v.w) : "r"(a) : "memory"); return v; }
__device__ __forceinline__ void sts64f(uint32_t a, float x, float y) { asm volatile("st.shared.v2.f32 [%0], {%1,%2};" :: "r"(a), "f"(x), "f"(y) : "memory"); }
template<int OFF> __device__ __forceinline__ void sts128o(uint32_t a, uint4 v) { asm volatile("st.shared.v4.u32 [%0+%5], {%1,%2,%3,%4};" :: "r"(a), "r"(v.x), "r"(v.y), "r"(v.z), "r"(v.w), "n"(OFF) : "memory"); }
__device__ __forceinline__ void ldsm4(uint32_t a, uint32_t& r0, uint32_t& r1, uint32_t& r2, uint32_t& r3) {
  asm volatile("ldmatrix.sync.aligned.m8n8.x4.shared.b16 {%0,%1,%2,%3}, [%4];" : "=r"(r0), "=r"(r1), "=r"(r2), "=r"(r3) : "r"(a) : "memory");
}
__device__ __forceinline__ void ldsm4t(uint32_t a, uint32_t& r0, uint32_t& r1, uint32_t& r2, uint32_t& r3) {
  asm volatile("ldmatrix.sync.aligned.m8n8.x4.trans.shared.b16 {%0,%1,%2,%3}, [%4];" : "=r"(r0), "=r"(r1), "=r"(r2), "=r"(r3) : "r"(a) : "memory");
}
__device__ __forceinline__ void stsm4(uint32_t a, uint32_t r0, uint32_t r1, uint32_t r2, uint32_t r3) {
  asm volatile("stmatrix.sync.aligned.m8n8.x4.shared.b16 [%0], {%1,%2,%3,%4};" :: "r"(a), "r"(r0), "r"(r1), "r"(r2), "r"(r3) : "memory");
}
template<int N> __device__ __forceinline__ void fence_regs(float (&d)[N]) {
#pragma unroll
  for (int i = 0; i < N; i++) asm volatile("" : "+f"(d[i]) :: "memory");
}
template<int N> __device__ __forceinline__ void fence_regs(uint32_t (&d)[N]) {
#pragma unroll
  for (int i = 0; i < N; i++) asm volatile("" : "+r"(d[i]) :: "memory");
}
__device__ __forceinline__ void sched_fence(float x, uint32_t dummy) {
  asm volatile("{\n.reg .pred p;\nsetp.eq.u32 p, %0, 0x7fc12345;\n@p st.shared.u32 [%1], %0;\n}\n" :: "r"(__float_as_uint(x)), "r"(dummy) : "memory");
}
#define PTRACE 0
#define TS(role, i)
#define TSA(i)
#define TSS(i)
#define TSK(i)
#define TSO(i)

#define SHADOW if (gridDim.y == 1)

struct Prod {
  uint32_t base, mask; int lane, nt;
  __device__ __forceinline__ uint32_t full(int u) const { return base + SM_BAR + 8 * u; }
  __device__ __forceinline__ uint32_t addr(int u) const { return base + u * UNIT; }
  __device__ __forceinline__ void acquire(int u, int n) {
    const int v = u + min(lane, n - 1);
    mbar_wait_all(base + SM_BAR + 128 + 8 * v, mask >> v);
    mask ^= ((1u << n) - 1) << u;
  }
  __device__ __forceinline__ void acquire_slow(int u, int n) {
    for (int i = 0; i < n; i++) mbar_wait_slow(base + SM_BAR + 128 + 8 * (u + i), mask >> (u + i));
    mask ^= ((1u << n) - 1) << u;
  }
};
struct Cons {
  uint32_t base, rel, mask; int lane, warp, wg, lr, nt;
  __device__ __forceinline__ uint32_t addr(int u) const { return base + u * UNIT; }
  __device__ __forceinline__ static uint32_t daddr(int u) { return SMEM_BASE + u * UNIT; }
  __device__ __forceinline__ void wait(int u) { mbar_wait(base + SM_BAR + 8 * u, mask >> u); mask ^= 1u << u; }
  __device__ __forceinline__ void skip(int u) { mask ^= 1u << u; }
  __device__ __forceinline__ void release(int u, int n) {
    asm volatile("{\n.reg .pred p;\nsetp.lt.s32 p, %1, %2;\n@p mbarrier.arrive.shared::cluster.b64 _, [%0];\n}\n" :: "r"(rel + 8 * u), "r"(lr), "r"(n) : "memory");
  }
  __device__ __forceinline__ void release2(int u) {
    asm volatile("{\n.reg .pred p;\nsetp.eq.s32 p, %1, 0;\n@p mbarrier.arrive.shared::cluster.b64 _, [%0], 2;\n}\n" :: "r"(rel + 8 * u), "r"(lr) : "memory");
  }
  __device__ __forceinline__ void signal(int i) {
    __syncwarp();
    asm volatile("{\n.reg .pred p;\nsetp.eq.s32 p, %1, 0;\n@p mbarrier.arrive.shared::cta.b64 _, [%0];\n}\n" :: "r"(base + SM_SIG + 8 * i), "r"(lane) : "memory");
  }
  __device__ __forceinline__ void turn() { asm volatile("{\n.reg .pred p;\nsetp.eq.s32 p, %0, 0;\n@p bar.sync 1, 256;\n@!p bar.sync 2, 256;\n}\n" :: "r"(wg) : "memory"); }
  __device__ __forceinline__ void pass() { asm volatile("{\n.reg .pred p;\nsetp.eq.s32 p, %0, 0;\n@p bar.arrive 2, 256;\n@!p bar.arrive 1, 256;\n}\n" :: "r"(wg) : "memory"); }
  __device__ __forceinline__ void sync() { asm volatile("{\n.reg .pred p;\nsetp.eq.s32 p, %0, 0;\n@p bar.sync 3, 128;\n@!p bar.sync 4, 128;\n}\n" :: "r"(wg) : "memory"); }
};
__device__ __forceinline__ int gemm_unit(int ks) { return 3 * (ks & 3); }
template<int MASK> __device__ __forceinline__ int kv_slot(int h) { return MASK == PH_ALL ? h & 15 : h; }
__device__ __forceinline__ int out_mb(int cta) { return cta >> 3; }
__device__ __forceinline__ int out_nb(int cta) { return cta & 7; }
template<int MASK> constexpr int CV_REG = MASK == PH_ALL ? CONV_REG : 6;
template<int MASK> constexpr int CV_EXTRA = (1024 - NREG * CV_REG<MASK>) / (NCTA - NREG);
template<int MASK> __device__ __forceinline__ int conv_channel(int cta, int i) {
  return cta < NREG ? CV_EXTRA<MASK> * (NCTA - NREG) + cta * CV_REG<MASK> + i : (i >> 1) * 8 + (cta - NREG) * 2 + (i & 1);
}

template<int OFF, int N> __device__ __forceinline__ void pack_chunk(const float (&a)[N], float sc0, float sc1, uint4& v0, uint4& v1) {
  v0.x = pack_bf16(a[OFF + 0] * sc0, a[OFF + 1] * sc0); v0.y = pack_bf16(a[OFF + 4] * sc0, a[OFF + 5] * sc0);
  v0.z = pack_bf16(a[OFF + 8] * sc0, a[OFF + 9] * sc0); v0.w = pack_bf16(a[OFF + 12] * sc0, a[OFF + 13] * sc0);
  v1.x = pack_bf16(a[OFF + 2] * sc1, a[OFF + 3] * sc1); v1.y = pack_bf16(a[OFF + 6] * sc1, a[OFF + 7] * sc1);
  v1.z = pack_bf16(a[OFF + 10] * sc1, a[OFF + 11] * sc1); v1.w = pack_bf16(a[OFF + 14] * sc1, a[OFF + 15] * sc1);
}
template<int OFF, int N> __device__ __forceinline__ void pack_chunk(const float (&a)[N], uint4& v0, uint4& v1) {
  v0.x = pack_bf16(a[OFF + 0], a[OFF + 1]); v0.y = pack_bf16(a[OFF + 4], a[OFF + 5]);
  v0.z = pack_bf16(a[OFF + 8], a[OFF + 9]); v0.w = pack_bf16(a[OFF + 12], a[OFF + 13]);
  v1.x = pack_bf16(a[OFF + 2], a[OFF + 3]); v1.y = pack_bf16(a[OFF + 6], a[OFF + 7]);
  v1.z = pack_bf16(a[OFF + 10], a[OFF + 11]); v1.w = pack_bf16(a[OFF + 14], a[OFF + 15]);
}
__device__ __forceinline__ void sq_acc(const uint4& v, uint32_t& a) { a = hfma2(v.x, v.x, a); a = hfma2(v.y, v.y, a); a = hfma2(v.z, v.z, a); a = hfma2(v.w, v.w, a); }
__device__ __forceinline__ float norm2_max(uint32_t a0, uint32_t a1) {
  float n0 = bf_lo(a0) + bf_hi(a0), n1 = bf_lo(a1) + bf_hi(a1);
  n0 += __shfl_xor_sync(~0u, n0, 1); n1 += __shfl_xor_sync(~0u, n1, 1);
  n0 += __shfl_xor_sync(~0u, n0, 2); n1 += __shfl_xor_sync(~0u, n1, 2);
  return __uint_as_float(__reduce_max_sync(~0u, max(__float_as_uint(n0) & 0x7fffffffu, __float_as_uint(n1) & 0x7fffffffu)));
}

struct Pend { uint4 lo[8], hi[8]; };
__device__ __forceinline__ uint32_t ctx_off(const Cons& c, int h, int qb, int rowhalf) { return T_CTX + (qb * 32 + h) * 32768 + (rowhalf * 4 + c.warp) * 4096; }
__device__ __forceinline__ uint32_t kv_off(const Cons& c, int blk) { return T_KV + blk * 65536 + (c.wg * 4 + c.warp) * 4096; }
__device__ __forceinline__ void pin(uint4 (&v)[8]) {
#pragma unroll
  for (int i = 0; i < 8; i++) asm volatile("" : "+r"(v[i].x), "+r"(v[i].y), "+r"(v[i].z), "+r"(v[i].w) :: "memory");
}
__device__ __forceinline__ void pack_o(const float (&o)[64], float i0, float i1, uint4 (&v)[8]) {
  pack_chunk<0>(o, i0, i1, v[0], v[1]); pack_chunk<16>(o, i0, i1, v[2], v[3]);
  pack_chunk<32>(o, i0, i1, v[4], v[5]); pack_chunk<48>(o, i0, i1, v[6], v[7]);
  pin(v);
}
__device__ __forceinline__ uint32_t atom_off(int lane) { return (lane >> 2) * 64 + (((lane ^ (lane >> 3)) & 3) << 4); }
template<int J0, int J1> __device__ __forceinline__ void tile_store(const uint4 (&v)[8], uint32_t dst, int lane) {
  uint8_t* d = g_T + (dst + atom_off(lane));
#pragma unroll
  for (int j = J0; j < J1; j++) { *(uint4*)(d + j * 512) = v[2 * j]; *(uint4*)(d + j * 512 + 2048) = v[2 * j + 1]; }
}
template<int I0, int I1> __device__ __forceinline__ void tile_store_if(bool on, const uint4 (&v)[8], const uint8_t* dst) {
  if constexpr (I0 < I1) {
    asm volatile("{\n.reg .pred p;\nsetp.ne.b32 p, %5, 0;\n@p st.v4.u32 [%0+%6], {%1,%2,%3,%4};\n}\n"
      :: "l"(dst), "r"(v[I0].x), "r"(v[I0].y), "r"(v[I0].z), "r"(v[I0].w), "r"((int)on), "n"((I0 >> 1) * 512 + (I0 & 1) * 2048) : "memory");
    tile_store_if<I0 + 1, I1>(on, v, dst);
  }
}
__device__ __forceinline__ float tile_norm2(const uint4 (&v)[8]) {
  uint32_t n0 = 0, n1 = 0, n2 = 0, n3 = 0;
#pragma unroll
  for (int j = 0; j < 2; j++) { sq_acc(v[2 * j], n0); sq_acc(v[2 * j + 1], n1); sq_acc(v[2 * j + 4], n2); sq_acc(v[2 * j + 5], n3); }
  return norm2_max(hadd2(n0, n2), hadd2(n1, n3));
}
template<uint64_t SCHED, bool FIRST> __device__ __forceinline__ void out_piece(Cons& c, Pend& w, uint32_t dst, int blk, float& kn, int ks, bool both) {
  uint8_t* d = g_T + (dst + atom_off(c.lane));
#pragma unroll
  for (int i = 0; i < 16; i++) {
    const int at = (SCHED >> (4 * i)) & 15;
    if (FIRST ? at == 0 : (at > 0 && ks == at && (i < 8 || both))) *(uint4*)(d + (i >> 3) * 32768 + ((i >> 1) & 3) * 512 + (i & 1) * 2048) = i < 8 ? w.lo[i & 7] : w.hi[i & 7];
  }
  if (FIRST || !both) return;
  if (ks == NK_AT) kn = tile_norm2(w.lo);
  if (ks == NV_AT) {
    const float vn = tile_norm2(w.hi);
    if (c.lane == 0) g_kn2[blk * 8 + c.wg * 4 + c.warp] = (vn <= 1.0e20f && vn >= 1.0e-20f) ? kn : __uint_as_float(0x7f800000u);
  }
}
template<bool FIRST> __device__ __forceinline__ void kv_issue(Cons& c, float (&acc)[128], int u) {
  const uint64_t da = odesc(c.daddr(u) + c.wg * 8192, 16, 1024, 1), db = odesc(c.daddr(u + 1), 8192, 1024, 1);
  TSK(c.nt + 1);
  c.turn();
  TSK(c.nt + 2);
  wg_fence();
#pragma unroll
  for (int kk = 0; kk < 4; kk++) wgmma_ss_n256<1>(acc, da + kk * 2, db + kk * 128, !(FIRST && kk == 0));
  wg_commit();
  c.pass();
  TSK(c.nt + 3); c.nt += 4;
}
template<bool NEXT> __device__ __forceinline__ void cons_kv(Cons& c, int h, int blk, int g, Pend& w, bool pend_o) {
#pragma unroll 1
  for (int tile = 0; tile < 2; tile++) {
    float acc[128];
    if (tile == 0) c.wait(0);
    if (tile == 0 && h < 16) TS(c.wg, 16);
    kv_issue<true>(c, acc, 0);
    c.release(9, tile == 1 ? 3 : 0);
    if (tile == 1 && pend_o) mbar_wait(c.base + SM_RDY + 8 * RDY_WAR, 0);
    const uint32_t dst = tile ? kv_off(c, blk) : ctx_off(c, h - 16, g, 1 - c.wg);
    float kn = 0.f;
    if (tile == 1 || pend_o) out_piece<SCH_KV, true>(c, w, dst, blk, kn, 0, false);
#pragma unroll 1
    for (int ks = 1; ks < 8; ks++) {
      const int u = gemm_unit(ks);
      c.wait(u);
      TSK(c.nt);
      wg_wait<0>();
      c.release(gemm_unit(ks - 1), 3);
      kv_issue<false>(c, acc, u);
      if (tile == 1 || pend_o) { out_piece<SCH_KV, false>(c, w, dst, blk, kn, ks, tile); if (ks == ((SCH_KV >> 28) & 15) && tile == 0) c.signal(SIG_CTX); }
    }
    if (NEXT || tile == 0) c.wait(0);
    wg_wait<0>(); fence_regs(acc);
    TSK(c.nt);
    if (!NEXT) c.release(9, tile == 1 ? 3 : 0);
    pack_chunk<0>(acc, w.lo[0], w.lo[1]);  pack_chunk<16>(acc, w.lo[2], w.lo[3]); pack_chunk<32>(acc, w.lo[4], w.lo[5]); pack_chunk<48>(acc, w.lo[6], w.lo[7]);
    pack_chunk<64>(acc, w.hi[0], w.hi[1]); pack_chunk<80>(acc, w.hi[2], w.hi[3]); pack_chunk<96>(acc, w.hi[4], w.hi[5]); pack_chunk<112>(acc, w.hi[6], w.hi[7]);
    pin(w.lo); pin(w.hi);
  }
}
template<bool FIRST> __device__ __forceinline__ void q_issue(Cons& c, float (&a)[64], float (&b)[64], int u) {
  const uint64_t da = odesc(c.daddr(u) + c.wg * 8192, 16, 1024, 1), db = odesc(c.daddr(u + 2), 8192, 1024, 1);
  const uint64_t da2 = odesc(c.daddr(u + 1) + (1 - c.wg) * 8192, 16, 1024, 1);
  TSK(c.nt + 1);
  c.turn();
  TSK(c.nt + 2);
  wg_fence();
#pragma unroll
  for (int kk = 0; kk < 4; kk++) wgmma_ss_n128<1>(a, da + kk * 2, db + kk * 128, !(FIRST && kk == 0));
#pragma unroll
  for (int kk = 0; kk < 4; kk++) wgmma_ss_n128<1>(b, da2 + kk * 2, db + kk * 128, !(FIRST && kk == 0));
  wg_commit();
  c.pass();
  TSK(c.nt + 3); c.nt += 4;
}
__device__ __forceinline__ void q_step(Cons& c, float (&d)[64], int ua, int ub, int rowhalf) {
  const uint64_t da = odesc(c.daddr(ua) + rowhalf * 8192, 16, 1024, 1), db = odesc(c.daddr(ub), 8192, 1024, 1);
#pragma unroll
  for (int kk = 0; kk < 4; kk++) wgmma_ss_n128<1>(d, da + kk * 2, db + kk * 128, 1);
}
template<bool PEND_KV> __device__ __forceinline__ void cons_q(Cons& c, int h, int blk, Pend& w, float (&b)[64]) {
  float a[64], kn = 0.f;
  if (!PEND_KV) c.wait(0);
  q_issue<true>(c, a, b, 0);
  if (PEND_KV) { c.release(9, 3); out_piece<SCH_Q, true>(c, w, kv_off(c, blk), blk, kn, 0, true); }
#pragma unroll 1
  for (int ks = 1; ks < 14; ks++) {
    const int u = gemm_unit(ks);
    c.wait(u);
    TSK(c.nt);
    wg_wait<0>();
    c.release(gemm_unit(ks - 1), 3);
    q_issue<false>(c, a, b, u);
    if (PEND_KV && ks <= (int)(SCH_Q >> 60)) { out_piece<SCH_Q, false>(c, w, kv_off(c, blk), blk, kn, ks, true); if (ks == (int)(SCH_Q >> 60)) c.signal(SIG_KV + (h >> 4)); }
  }
  c.wait(6); c.wait(9);
  wg_wait<0>();
  c.release(3, 3);
  c.turn();
  TSS(0);
  wg_fence();
  q_step(c, a, 6, 8, c.wg); q_step(c, a, 9, 11, c.wg); wg_commit();
  q_step(c, b, 7, 8, 1 - c.wg); wg_commit();
  c.pass();
  TSS(1);
  c.wait(0);
  const uint32_t q0 = c.addr(0) + (c.wg * 4 + c.warp) * 4096 + atom_off(c.lane);
  wg_wait<1>(); fence_regs(a);
  TSS(2);
  pack_o(a, QSCALE, QSCALE, w.lo);
  sts128o<0>(q0, w.lo[0]);    sts128o<2048>(q0, w.lo[1]); sts128o<512>(q0, w.lo[2]);  sts128o<2560>(q0, w.lo[3]);
  wg_wait<0>();
  c.release(6, 4);
  sts128o<1024>(q0, w.lo[4]); sts128o<3072>(q0, w.lo[5]); sts128o<1536>(q0, w.lo[6]); sts128o<3584>(q0, w.lo[7]);
  TSS(3);
  c.wait(12);
  fence_async_smem();
  TSS(4);
}

__device__ __forceinline__ void issue_qk(float (&s)[64], uint64_t da, uint64_t db) {
#pragma unroll
  for (int kk = 0; kk < 8; kk++) wgmma_ss_n128<0>(s, da + (kk >> 1) * 32 + (kk & 1) * 2, db + (kk >> 1) * 32 + (kk & 1) * 2, kk > 0);
  wg_commit();
}
template<int A, int B> __device__ __forceinline__ void exp_rng(float (&s)[64]) {
#pragma unroll
  for (int i = 4 * A; i < 4 * B; i++) s[i] = ex2(s[i]);
}
template<int A, int B> __device__ __forceinline__ void sum_rng(const float (&s)[64], float (&l)[4]) {
#pragma unroll
  for (int i = A; i < B; i++) { l[0] += s[4 * i]; l[1] += s[4 * i + 1]; l[2] += s[4 * i + 2]; l[3] += s[4 * i + 3]; }
}
template<int A, int B> __device__ __forceinline__ void cvt_p(const float (&s)[64], uint32_t (&p)[32]) {
#pragma unroll
  for (int i = 2 * A; i < 2 * B; i++) p[i] = pack_bf16(s[2 * i], s[2 * i + 1]);
}
template<int K0> __device__ __forceinline__ void mask_half(float (&s)[64], int warp, int lane) {
  const int l0 = warp + (2 * (lane & 3) <= (lane >> 2)), l1 = warp + (2 * (lane & 3) < (lane >> 2));
#pragma unroll
  for (int k = 0; k < 4; k++) {
    float* t = s + 8 * (K0 + k);
    if (k >= l0) { t[0] = -INFINITY; t[6] = -INFINITY; }
    if (k >= l1) { t[1] = -INFINITY; t[7] = -INFINITY; }
    if (k > warp) { t[2] = -INFINITY; t[3] = -INFINITY; }
    if (k >= warp) { t[4] = -INFINITY; t[5] = -INFINITY; }
  }
}
__device__ __forceinline__ void row_inv(float& l0, float& l1) {
  l0 += __shfl_xor_sync(~0u, l0, 1); l1 += __shfl_xor_sync(~0u, l1, 1);
  l0 += __shfl_xor_sync(~0u, l0, 2); l1 += __shfl_xor_sync(~0u, l1, 2);
  l0 = rcp(l0); l1 = rcp(l1);
}
__device__ __forceinline__ void softmax_safe(float (&s)[64], bool upper_only, float& m0, float& m1, float& sc0, float& sc1) {
  float a0 = m0, a1 = m1;
#pragma unroll
  for (int i = 0; i < 8; i++) { a0 = fmaxf(a0, fmaxf(s[4 * i], s[4 * i + 1])); a1 = fmaxf(a1, fmaxf(s[4 * i + 2], s[4 * i + 3])); }
  if (upper_only) { a0 = m0; a1 = m1; }
#pragma unroll
  for (int i = 8; i < 16; i++) { a0 = fmaxf(a0, fmaxf(s[4 * i], s[4 * i + 1])); a1 = fmaxf(a1, fmaxf(s[4 * i + 2], s[4 * i + 3])); }
  a0 = fmaxf(a0, __shfl_xor_sync(~0u, a0, 1)); a1 = fmaxf(a1, __shfl_xor_sync(~0u, a1, 1));
  a0 = fmaxf(a0, __shfl_xor_sync(~0u, a0, 2)); a1 = fmaxf(a1, __shfl_xor_sync(~0u, a1, 2));
  sc0 = ex2(m0 - a0); sc1 = ex2(m1 - a1);
  m0 = a0; m1 = a1;
#pragma unroll
  for (int i = 0; i < 16; i++) { s[4 * i] -= a0; s[4 * i + 1] -= a0; s[4 * i + 2] -= a1; s[4 * i + 3] -= a1; }
}
struct Att {
  float s[64], o[64], l[4], i0, i1, t0, t1; uint32_t p[32];
  float kn; uint32_t qaddr; const uint8_t* dst;
};
__device__ __forceinline__ int att_fast(uint4 (&q)[8], float kn) {
#pragma unroll
  for (int i = 0; i < 8; i++) q[i].x = hmul2(q[i].x, q[i].x);
#pragma unroll
  for (int i = 0; i < 8; i++) q[i].x = hfma2(q[i].w, q[i].w, hfma2(q[i].z, q[i].z, hfma2(q[i].y, q[i].y, q[i].x)));
#pragma unroll
  for (int i = 0; i < 4; i++) q[i].x = hadd2(q[i].x, q[i + 4].x);
  const uint32_t a0 = hadd2(q[0].x, q[2].x), a1 = hadd2(q[1].x, q[3].x);
  return __shfl_sync(~0u, __all_sync(~0u, ((bf_lo(a0) + bf_hi(a0)) * kn <= 0.25f * BOUND2) & ((bf_lo(a1) + bf_hi(a1)) * kn <= 0.25f * BOUND2)), 0);
}
__device__ __forceinline__ int att_first(Cons& c, Att& a, int h, Pend& w) {
  a.kn = __uint_as_float(lds32(c.base + SM_KMAX + 4 * (h >> 4)));
  a.qaddr = c.daddr(0) + c.wg * 16384;
  c.turn();
  TSS(5);
  wg_fence();
  issue_qk(a.s, odesc(a.qaddr, 16, 2048, 2), odesc(c.daddr(12), 16, 2048, 2));
  int fast = 0;
  SHADOW fast = att_fast(w.lo, a.kn);
  wg_fence();
  TSS(6);
  q_step(c, a.o, 10, 11, 1 - c.wg); wg_commit();
  if (c.wg) c.wait(6); else c.skip(6);
  c.pass();
  TSS(7);
#pragma unroll
  for (int i = 0; i < 8; i++) { a.p[4 * i] = w.lo[i].x; a.p[4 * i + 1] = w.lo[i].y; a.p[4 * i + 2] = w.lo[i].z; a.p[4 * i + 3] = w.lo[i].w; }
  a.l[0] = a.l[1] = a.l[2] = a.l[3] = 0.f; a.i0 = a.i1 = a.t0 = a.t1 = 0.25f / QSCALE;
  a.dst = (const uint8_t*)__cvta_shared_to_generic(c.addr(2) + (c.wg * 4 + c.warp) * 4096 + atom_off(c.lane));
  wg_wait<1>(); fence_regs(a.s);
  c.signal(SIG_ATT + (h >> 4));
  if (c.wg) { wg_wait<0>(); c.release(10, 2); }
  return fast;
}
__device__ __forceinline__ void att_last(Cons& c, Att& a, Pend& w, int h, int g, bool drain) {
  const int uv = 6;
  if (drain) pack_o(a.o, rcp(a.i0), rcp(a.i1), w.hi);
  TSS(8);
  c.turn();
  TSS(9);
  fence_regs(a.o); fence_regs(a.p);
  wgmma_pv_sel(a.o, a.p, odesc(c.daddr(uv), 512, 2048, 2), !(drain && c.wg == 1), !drain, c.wg);
  a.i0 = a.l[0] + a.l[1]; a.i1 = a.l[2] + a.l[3];
  SHADOW row_inv(a.i0, a.i1);
  sched_fence(a.i0 + a.i1, c.base + SM_DUMMY);
  tile_store_if<0, 4>(drain, w.hi, a.dst);
  wg_wait<0>(); fence_regs(a.o); fence_regs(a.p);
  c.release(uv, 2);
  TSS(10); if (h < 16) TSK(0);
  tile_store_if<4, 8>(drain, w.hi, a.dst);
  pack_o(a.o, a.i0, a.i1, w.lo);
  TSS(11);
}
__device__ __forceinline__ void cons_att(Cons& c, Att& a, int h, int g, Pend& w) {
  int fast = att_first(c, a, h, w), fast2 = 0;
  float m0 = -INFINITY, m1 = -INFINITY, sc0 = 0.f, sc1 = 0.f;
  int uk = 10, ur = 10;
  bool fresh = false;
#pragma unroll 1
  for (int d = g - 15;;) {
    const bool lo = d == c.wg;
    TSS(16 + 6 * (d - g + 15));
    if ((unsigned)d < 2 || !fast) {
      if ((unsigned)d < 2) mask_half<4>(a.s, c.warp, c.lane);
      if (!fast) {
        if (d == 1) m0 = m1 = -INFINITY;
        softmax_safe(a.s, lo, m0, m1, sc0, sc1);
        a.l[0] *= sc0; a.l[1] *= sc0; a.l[2] *= sc1; a.l[3] *= sc1;
      }
    }
    exp_rng<8, 16>(a.s); sum_rng<8, 16>(a.s, a.l);
#pragma unroll
    for (int i = 4 * ATT_SPLIT; i < 32; i++) asm("{\n.reg .pred p;\nsetp.ne.s32 p, %1, %2;\n@p ex2.approx.ftz.f32 %0, %0;\n}\n" : "+f"(a.s[i]) : "r"(d), "r"(c.wg));
    sched_fence(((a.l[0] + a.l[1]) + (a.l[2] + a.l[3])) + a.s[4 * ATT_SPLIT + 3], c.base + SM_DUMMY);
    wg_wait<0>(); fence_regs(a.o); fence_regs(a.p);
    c.release(ur, c.wg && d == g - 15 ? 0 : 2);
    TSS(17 + 6 * (d - g + 15));
    a.i0 += a.t0; a.i1 += a.t1;
    a.t0 = __shfl_xor_sync(~0u, a.i0, 2); a.t1 = __shfl_xor_sync(~0u, a.i1, 2);
    tile_store_if<0, 4>(fresh, w.hi, a.dst);
    uk ^= 12; ur = 14 - uk;
    if (d == 0) a.qaddr += 32768;
    const uint64_t dq = odesc(a.qaddr, 16, 2048, 2), dk = odesc(c.daddr(uk) - (d + 1 == c.wg ? 16384 : 0), 16, 2048, 2), dv = odesc(c.daddr(ur), 512, 2048, 2);
    if (!lo) { exp_rng<0, ATT_SPLIT>(a.s); sum_rng<0, 8>(a.s, a.l); cvt_p<0, 16>(a.s, a.p); }
    else if (gridDim.y == 1) cvt_p<8, 16>(a.s, a.p);
    tile_store_if<4, 8>(fresh, w.hi, a.dst);
    a.i0 += a.t0; a.i1 += a.t1;
    if (!fast || d == g + 1) {
      if (!fast && d != 1 && d != g - 15) {
#pragma unroll
        for (int i = 0; i < 16; i++) { a.o[4 * i] *= sc0; a.o[4 * i + 1] *= sc0; a.o[4 * i + 2] *= sc1; a.o[4 * i + 3] *= sc1; }
      }
      if (d == g + 1) break;
    }
    d++;
    fresh = d == 2 || d == g - 14;
    TSS(12 + 6 * (d - g + 15));
    c.turn();
    TSS(13 + 6 * (d - g + 15));
    fence_regs(a.o); fence_regs(a.p);
    wg_fence();
    issue_qk(a.s, dq, dk);
    TSS(14 + 6 * (d - g + 15));
    c.wait(c.wg ? uk ^ 12 : ur); c.skip(c.wg ? ur : uk ^ 12);
    if (fresh || d == 1 || (unsigned)(d - g + CHK_D) < 2) {
      if (fresh) pack_o(a.o, rcp(a.i0), rcp(a.i1), w.hi);
      else if (d == 1) {
        a.i0 = a.l[0] + a.l[1]; a.i1 = a.l[2] + a.l[3];
        a.t0 = __shfl_xor_sync(~0u, a.i0, 1); a.t1 = __shfl_xor_sync(~0u, a.i1, 1);
        a.l[0] = a.l[1] = a.l[2] = a.l[3] = 0.f;
        uint32_t off = ctx_off(c, h, 15 - g, c.wg);
        asm volatile("" : "+r"(off));
        a.dst = g_T + (off + ((uint32_t)(uint64_t)a.dst & 511));
        fast = fast2;
      } else if (d == g - CHK_D) fence_async_smem();
      else fast2 = att_fast(w.hi, a.kn);
    }
    TSS(15 + 6 * (d - g + 15));
    wgmma_pv_sel(a.o, a.p, dv, !lo, !fresh, c.wg);
    wg_wait<1>(); fence_regs(a.s);
    c.release(uk, 2);
    c.release(d == 0 ? 0 : 2, (d == 0 || d == g + 1) ? 2 : 0);
  }
  att_last(c, a, w, h, g, g == 0);
}

constexpr int CV_H = 1024, CV_U = 5120, CV_D = CV_U + 4128, CV_ROW = 1056;
template<int OFF> __device__ __forceinline__ uint32_t lds32o(uint32_t a) { uint32_t v; asm volatile("ld.shared.u32 %0, [%1+%2];" : "=r"(v) : "r"(a), "n"(OFF) : "memory"); return v; }
template<int G, int G1 = 16> __device__ __forceinline__ void conv_lda(uint32_t (&a)[64], uint32_t p) {
  a[4 * G + 0] = lds32o<-256 * G>(p);
  a[4 * G + 1] = lds32o<-256 * G - 128>(p);
  a[4 * G + 2] = lds32o<-256 * G + 16>(p);
  a[4 * G + 3] = lds32o<-256 * G - 112>(p);
  if constexpr (G + 1 < G1) conv_lda<G + 1, G1>(a, p);
}
struct CvAcc { float lo[16], hi[16]; };
__device__ __forceinline__ void fence_regs(CvAcc& d) { fence_regs(d.lo); fence_regs(d.hi); }
template<int R, int H> __device__ __forceinline__ void conv_mma_h(float (&d)[16], const uint32_t (&a)[64], uint64_t db) {
#pragma unroll
  for (int G = 0; G < 4 * R + 2 * H + 2; G++) wgmma_rs_n32<0>(d, a[4 * G], a[4 * G + 1], a[4 * G + 2], a[4 * G + 3], db + 64 * R + 32 * H - 16 * G, G > 0);
}
template<int T, int G0, int G1> __device__ __forceinline__ void conv_part(float (&d)[16], const uint32_t (&a)[64], uint64_t db) {
#pragma unroll
  for (int G = G0; G < G1; G++) wgmma_rs_n32<0>(d, a[4 * G], a[4 * G + 1], a[4 * G + 2], a[4 * G + 3], db + 32 * T - 16 * G, G > 0);
}
template<int R> __device__ __forceinline__ void conv_mma(CvAcc& d, const uint32_t (&a)[64], uint64_t db) { conv_mma_h<R, 0>(d.lo, a, db); conv_mma_h<R, 1>(d.hi, a, db); }
template<int C0> __device__ __forceinline__ void conv_st_h(const float (&d)[16], uint32_t wq, float& c0, float& c1) {
#pragma unroll
  for (int n = 0; n < 4; n++) { sts64f(wq + (C0 + n * 8) * 4, d[4 * n] + c0, d[4 * n + 1] + c1); c0 = d[4 * n + 2]; c1 = d[4 * n + 3]; }
}
template<int R> __device__ __forceinline__ void conv_st(const CvAcc& d, uint32_t wq, float& c0, float& c1) { conv_st_h<64 * R>(d.lo, wq, c0, c1); conv_st_h<64 * R + 32>(d.hi, wq, c0, c1); }
struct ConvTail { float t[64]; uint4 ua, uc; uint32_t D2; };
__device__ __forceinline__ void conv_emit(ConvTail& e, int ch, int tid) {
  fence_regs(e.t);
  float y[16];
#pragma unroll
  for (int i = 0; i < 16; i++) y[i] = (e.t[i] + e.t[16 + i]) + (e.t[32 + i] + e.t[48 + i]);
  uint4 z0, z1;
  z0.x = hadd2(pack_bf16(y[0], y[2]), hmul2(__byte_perm(e.ua.w, 0, 0x1032), e.D2));
  z0.y = hadd2(pack_bf16(y[4], y[6]), hmul2(__byte_perm(e.ua.z, 0, 0x1032), e.D2));
  z0.z = hadd2(pack_bf16(y[8], y[10]), hmul2(__byte_perm(e.ua.y, 0, 0x1032), e.D2));
  z0.w = hadd2(pack_bf16(y[12], y[14]), hmul2(__byte_perm(e.ua.x, 0, 0x1032), e.D2));
  z1.x = hadd2(pack_bf16(y[1], y[3]), hmul2(__byte_perm(e.uc.w, 0, 0x1032), e.D2));
  z1.y = hadd2(pack_bf16(y[5], y[7]), hmul2(__byte_perm(e.uc.z, 0, 0x1032), e.D2));
  z1.z = hadd2(pack_bf16(y[9], y[11]), hmul2(__byte_perm(e.uc.y, 0, 0x1032), e.D2));
  z1.w = hadd2(pack_bf16(y[13], y[15]), hmul2(__byte_perm(e.uc.x, 0, 0x1032), e.D2));
  uint4* zp = (uint4*)(g_z + (uint32_t)(ch * 2048 + tid * 16));
  zp[0] = z0; zp[1] = z1;
}
template<int MASK> __device__ __forceinline__ void cons_conv(Cons& c, int cta, int nch) {
  const int r = c.lane >> 2, q = c.lane & 3, tid = c.warp * 32 + c.lane;
  const uint32_t part = c.addr(4) - 2048 + (1 - c.wg) * (32 * CV_ROW) + 32;
  const uint32_t aoff = CV_U + ((r & 1) ? 0 : UPITCH) + 4 * (((2039 - r) >> 1) + q - 8 * c.warp);
  const uint32_t wq = part + (c.warp * 8 + r) * CV_ROW + q * 8, rq = part + tid * 8;
  uint32_t a[64];
  ConvTail e = {};
  c.wait(c.wg); c.skip(c.wg ^ 1);
  conv_lda<0>(a, c.addr(c.wg) + aoff);
  c.wait(4);
  sts64f(part + (tid >> 2) * CV_ROW - 32 + q * 8, 0.f, 0.f);
#pragma unroll 1
  for (int i = 0; i < nch / 2; i++) {
    const int u = 2 * (i & 1) + c.wg;
    CvAcc d0, d1, d2, d3;
    float c0 = 0.f, c1 = 0.f;
    const uint64_t db = odesc(c.daddr(u) + CV_H - 16, 16, 128, 0);
    c.turn();
    fence_regs(a);
    wg_fence();
    conv_mma<0>(d0, a, db); conv_mma<1>(d1, a, db); wg_commit();
    if (i > 0) {
      conv_emit(e, conv_channel<MASK>(cta, 2 * i - 2 + c.wg), tid);
      if ((i & 15) == 0) c.signal(SIG_Z + (i >> 4) - 1);
    }
    wg_fence();
    conv_mma_h<2, 0>(d2.lo, a, db); wg_commit();
    wg_wait<1>(); fence_regs(d0); fence_regs(d1);
    conv_st_h<0>(d0.lo, wq, c0, c1);
    wg_fence();
    conv_mma_h<2, 1>(d2.hi, a, db); wg_commit();
    conv_st_h<32>(d0.hi, wq, c0, c1);
    conv_mma_h<3, 0>(d3.lo, a, db);
    conv_st_h<64>(d1.lo, wq, c0, c1);
    conv_mma_h<3, 1>(d3.hi, a, db); wg_commit();
    c.pass();
    const int un = i + 1 < nch / 2 ? u ^ 2 : u;
    if (un != u) { c.wait(un); c.skip(un ^ 1); }
    wg_wait<1>(); fence_regs(d2);
    conv_st_h<96>(d1.hi, wq, c0, c1);
    conv_st<2>(d2, wq, c0, c1);
    {
      const int sw = (c.lane >> 2) & 1;
      const uint4 v0 = lds128(c.addr(u) + CV_U + 4064 - 32 * tid + 16 * sw), v1 = lds128(c.addr(u) + CV_U + 4080 - 32 * tid - 16 * sw);
      e.ua = sw ? v0 : v1; e.uc = sw ? v1 : v0;
    }
    e.D2 = lds32(c.addr(u) + CV_D);
    wg_wait<0>(); fence_regs(d3); fence_regs(a);
    conv_st<3>(d3, wq, c0, c1);
    conv_lda<0, 4>(a, c.addr(un) + aoff);
    sched_fence(__uint_as_float(e.ua.x ^ e.uc.x ^ e.D2), c.base + SM_DUMMY);
    c.sync();
    c.release2(u);
    conv_lda<4, 16>(a, c.addr(un) + aoff);
#pragma unroll
    for (int k = 0; k < 32; k++) { const float2 v = lds64f(rq + k * CV_ROW - (k >> 3) * 8); e.t[2 * k] = v.x; e.t[2 * k + 1] = v.y; }
  }
  conv_emit(e, conv_channel<MASK>(cta, nch - 2 + c.wg), tid);
  c.signal(SIG_Z + ((nch / 2 - 1) >> 4));
}

constexpr int OC_PART = 13824, OC_ROW = 544;
__device__ __forceinline__ int out_next(int u) { return (0x84ac680u >> (2 * u)) & 15; }
struct Out { float acc[64]; int pu; uint64_t da, db; };
template<bool FIRST, bool REL, int W = 1> __device__ __forceinline__ void out_step(Cons& c, Out& o, bool extra = false) {
  const int pu = o.pu, u = extra ? 2 : out_next(pu);
  o.pu = u;
  c.wait(u);
  const uint64_t da = o.da + (uint32_t)(u * 1024), db = o.db + (uint32_t)(u * 1024);
  wg_fence();
#pragma unroll
  for (int kk = 0; kk < 4; kk++) wgmma_ss_n128<1>(o.acc, da + (kk >> 1) * 32 + (kk & 1) * 2, db + kk * 128, !(FIRST && kk == 0));
  wg_commit();
  if (REL) { wg_wait<W>(); c.release(pu, ONE && pu != 2 ? 1 : 2); }
}
template<int I0, int I1> __device__ __forceinline__ void oc_red(float (&y)[8], uint32_t rq) {
#pragma unroll
  for (int i = I0; i < I1; i++) { const float v = __uint_as_float(lds32(rq + i * OC_ROW - (i >> 3) * 8)); y[i & 7] = i < 8 ? v : y[i & 7] + v; }
}
__device__ __forceinline__ void oc_emit(const float (&y)[8], const uint4& u, uint32_t D2, __nv_bfloat16* dst) {
  uint4 z;
  z.x = hadd2(pack_bf16(y[0], y[1]), hmul2(__byte_perm(u.w, 0, 0x1032), D2));
  z.y = hadd2(pack_bf16(y[2], y[3]), hmul2(__byte_perm(u.z, 0, 0x1032), D2));
  z.z = hadd2(pack_bf16(y[4], y[5]), hmul2(__byte_perm(u.y, 0, 0x1032), D2));
  z.w = hadd2(pack_bf16(y[6], y[7]), hmul2(__byte_perm(u.x, 0, 0x1032), D2));
  *(uint4*)dst = z;
}
__device__ __forceinline__ uint32_t mix(uint32_t og, uint32_t b, uint32_t ga) { return hadd2(ga, hmul2(og, b)); }
template<int MASK> __device__ __forceinline__ void cons_out(Cons& c, const Maps& M, const Params& P, int cta, Pend& w) {
  const int mb = out_mb(cta), nb = out_nb(cta);
  Out o;
  o.da = odesc(c.daddr(0) + c.wg * 8192, 16, 1024, 2); o.db = odesc(c.daddr(1), 8192, 1024, 1);
  o.pu = 5 + gridDim.y;
  out_step<true, false>(c, o);
  int ks = 1;
  const uint32_t dst = ctx_off(c, 16 + (cta >> 3), cta & 7, 1 - c.wg);
#pragma unroll 1
  for (;; ks++) {
    if (MASK & PH_ATT) {
      if (ks == (c.wg ? ST_1 : 1)) tile_store<0, 1>(w.lo, dst, c.lane);
      if (ks == (c.wg ? ST_1 + ST_D : 1)) tile_store<1, 2>(w.lo, dst, c.lane);
      if (ks == (c.wg ? ST_1 + 2 * ST_D : 1)) tile_store<2, 3>(w.lo, dst, c.lane);
      if (ks == (c.wg ? ST_1 + 3 * ST_D : 1)) { tile_store<3, 4>(w.lo, dst, c.lane); c.signal(SIG_CTX + 1); }
    }
    if (ks == (c.wg ? OC_S1 : OC_S0)) break;
    out_step<false, true>(c, o, ks == 1);
  }
  if (MASK & PH_CONV) {
    const int r = c.lane >> 2, q = c.lane & 3, tid = c.warp * 32 + c.lane, u = 2 * c.wg;
    const uint32_t ub = c.addr(u), part = ub + OC_PART + 32;
    const uint32_t ap = ub + CV_U + ((r & 1) ? 0 : UPITCH) + 4 * (((2039 - r) >> 1) + q - 8 * c.warp);
    const uint32_t wq = part + (c.warp * 8 + r) * OC_ROW + q * 8, rq = part + tid * 4;
    const int nr = (CV_REG<MASK> + 1 - c.wg) >> 1;
#define STEP(N) out_step<false, true>(c, o);
#pragma unroll 1
    for (int i = 0; i < nr; i++) {
      uint32_t a[64];
      CvAcc d0, d1;
      float y[8], c0 = 0.f, c1 = 0.f;
      const uint64_t db = odesc(c.daddr(u + (i >> 8)) + CV_H - 16, 16, 128, 0);
#define STEP2(N) out_step<false, true, 2>(c, o);
#define PART(...) { const uint64_t db = db0 + (c.mask >> 16); wg_fence(); __VA_ARGS__; wg_commit(); }
      const uint64_t db0 = db;
#define KEEP() asm volatile("add.f32 %0, %0, 0f80000000;" : "+f"(c0)); asm volatile("add.f32 %0, %0, 0f80000000;" : "+f"(c1));
      c.wait(u);
      conv_lda<0, 4>(a, ap);
      STEP(0)
      conv_lda<4, 7>(a, ap);
      PART(conv_part<0, 0, 2>(d0.lo, a, db); conv_part<1, 0, 4>(d0.hi, a, db); conv_part<2, 0, 2>(d1.lo, a, db))
      STEP2(1)
      conv_lda<7, 10>(a, ap);
      PART(conv_part<2, 2, 6>(d1.lo, a, db); conv_part<3, 0, 4>(d1.hi, a, db))
      STEP2(2)
      fence_regs(d0);
      c.sync();
      sts64f(wq - 32, 0.f, 0.f);
      conv_st_h<0>(d0.lo, wq, c0, c1); KEEP()
      PART(conv_part<3, 4, 8>(d1.hi, a, db); conv_part<4, 0, 4>(d0.lo, a, db))
      STEP2(3)
      fence_regs(d1.lo);
      conv_st_h<32>(d0.hi, wq, c0, c1); conv_st_h<64>(d1.lo, wq, c0, c1); KEEP()
      PART(conv_part<4, 4, 10>(d0.lo, a, db); conv_part<5, 0, 2>(d0.hi, a, db))
      STEP2(4)
      fence_regs(d1.hi);
      float e0 = d1.hi[12] + d1.hi[10], e1 = d1.hi[13] + d1.hi[11];
      conv_st_h<96>(d1.hi, wq, c0, c1); KEEP()
      conv_lda<10, 12>(a, ap);
      PART(conv_part<5, 2, 10>(d0.hi, a, db))
      STEP2(5)
      conv_lda<12, 14>(a, ap);
      c.sync();
      oc_red<0, 6>(y, rq);
      PART(conv_part<5, 10, 12>(d0.hi, a, db); conv_part<6, 0, 6>(d1.lo, a, db))
      STEP2(6)
      oc_red<6, 20>(y, rq);
      PART(conv_part<6, 6, 14>(d1.lo, a, db))
      STEP2(7)
      oc_red<20, 26>(y, rq);
      conv_lda<14, 16>(a, ap);
      PART(conv_part<7, 0, 8>(d1.hi, a, db))
      STEP2(8)
      oc_red<26, 32>(y, rq);
      PART(conv_part<7, 8, 16>(d1.hi, a, db))
      STEP2(9)
      fence_regs(y); fence_regs(d0);
      c.sync();
      sts64f(wq - 32, e0, e1);
      conv_st<0>(d0, wq, c0, c1);
      STEP(10)
      fence_regs(d1); fence_regs(a);
      const uint4 u0 = lds128(ub + CV_U + 4080 - 16 * tid), u1 = lds128(ub + CV_U + 2032 - 16 * tid);
      const uint32_t D2 = lds32(ub + CV_D);
      conv_st<1>(d1, wq, c0, c1);
      STEP(11)
      sched_fence(__uint_as_float(u0.x ^ u1.x ^ D2), c.base + SM_DUMMY);
      __nv_bfloat16* zp = g_z + (uint32_t)(conv_channel<MASK>(cta, 2 * i + c.wg) * 2048 + (threadIdx.x & 127) * 8);
      oc_emit(y, u0, D2, zp);
      c.sync();
      c.release2(u);
      oc_red<0, 12>(y, rq);
      STEP(12)
      oc_red<12, 24>(y, rq);
      STEP(13)
      oc_red<24, 32>(y, rq);
      oc_emit(y, u1, D2, zp + 1024);
#undef KEEP
      if (i == nr - 1) { c.signal(SIG_Z); c.sync(); c.release2(u + 1); TSO(0); }
      out_step<false, true>(c, o);
#pragma unroll 1
      for (int k = 15; k < (i == nr - 1 ? 0 : c.wg ? OC_L1 : OC_L0); k++) out_step<false, true>(c, o);
#undef STEP2
#undef PART
    }
#undef STEP
    if (((CV_REG<MASK> + c.wg) >> 1) & 1) c.skip(u ^ 2);
    ks += (nr - 1) * (c.wg ? OC_L1 : OC_L0) + 15;
  }
  TS(c.wg, 9);
#pragma unroll 1
  for (; ks < 57; ks++) out_step<false, true>(c, o);
  uint32_t ga[32];
  TSO(1);
  c.wait(2);
  TSO(2);
  const float g0 = __uint_as_float(lds32(c.base + SM_GATE + 4 * (c.wg * 64 + c.warp * 16 + (c.lane >> 2)))), g1 = __uint_as_float(lds32(c.base + SM_GATE + 32 + 4 * (c.wg * 64 + c.warp * 16 + (c.lane >> 2))));
  const uint32_t gg0 = pack_bf16(g0, g0), gg1 = pack_bf16(g1, g1);
  const uint32_t og0 = pack_bf16(1.f - g0, 1.f - g0), og1 = pack_bf16(1.f - g1, 1.f - g1);
  const int xr = c.wg * 64 + c.warp * 16 + (c.lane & 15);
  const uint32_t xa = c.addr(2) + xr * 128, xs = xr & 7, xh = c.lane >> 4;
  const int zr = (c.lane & 7) + ((c.lane >> 4) << 3);
  const uint32_t za = c.addr(0) + c.wg * 16384 + zr * 128 + (((c.warp * 2 + ((c.lane >> 3) & 1)) ^ (zr & 7)) << 4);
#pragma unroll
  for (int i = 0; i < 8; i++) {
    if (i == 0) out_step<false, true>(c, o);
    if (i == 3) out_step<false, true>(c, o);
    if (i == 6) out_step<false, true>(c, o);
    ldsm4(xa + (i >> 2) * 16384 + ((((i & 3) * 2 + xh) ^ xs) << 4), ga[4 * i], ga[4 * i + 1], ga[4 * i + 2], ga[4 * i + 3]);
  }
  TSO(3);
#pragma unroll 1
  for (ks = 60; ks < 64; ks++) out_step<false, false>(c, o);
  TSO(4);
  c.wait(0);
  TSO(5);
  SHADOW {
#pragma unroll
    for (int i = 0; i < 8; i++) {
      uint32_t z0, z1, z2, z3;
      ldsm4t(za + i * 2048, z0, z1, z2, z3);
      ga[4 * i + 0] = hmul2(ga[4 * i + 0], z0); ga[4 * i + 1] = hmul2(ga[4 * i + 1], z1); ga[4 * i + 2] = hmul2(ga[4 * i + 2], z2); ga[4 * i + 3] = hmul2(ga[4 * i + 3], z3);
      ga[4 * i + 0] = hmul2(gg0, ga[4 * i + 0]); ga[4 * i + 1] = hmul2(gg1, ga[4 * i + 1]); ga[4 * i + 2] = hmul2(gg0, ga[4 * i + 2]); ga[4 * i + 3] = hmul2(gg1, ga[4 * i + 3]);
    }
  }
  c.signal(SIG_DONE);
  fence_regs(ga);
  TSO(6);
  wg_wait<0>(); fence_regs(o.acc);
  TSO(7);
#pragma unroll
  for (int i = 0; i < 8; i++) {
    const uint32_t r0 = mix(og0, pack_bf16(o.acc[8 * i + 0], o.acc[8 * i + 1]), ga[4 * i + 0]);
    const uint32_t r1 = mix(og1, pack_bf16(o.acc[8 * i + 2], o.acc[8 * i + 3]), ga[4 * i + 1]);
    const uint32_t r2 = mix(og0, pack_bf16(o.acc[8 * i + 4], o.acc[8 * i + 5]), ga[4 * i + 2]);
    const uint32_t r3 = mix(og1, pack_bf16(o.acc[8 * i + 6], o.acc[8 * i + 7]), ga[4 * i + 3]);
    stsm4(xa + (i >> 2) * 16384 + ((((i & 3) * 2 + xh) ^ xs) << 4), r0, r1, r2, r3);
    if ((i & 3) == 3) {
      __syncwarp();
#pragma unroll
      for (int k = 0; k < 4; k++) {
        const int rr = c.wg * 64 + c.warp * 16 + k * 4 + (c.lane >> 3);
        const uint4 v = lds128(c.addr(2 + (i >> 2)) + rr * 128 + (((c.lane ^ rr) & 7) << 4));
        *(uint4*)(P.out + (uint32_t)((mb * 128 + rr) * 1024 + nb * 128 + (i >> 2) * 64 + (c.lane & 7) * 8)) = v;
      }
    }
  }
  TSO(8);
}

__device__ __forceinline__ void load_conv(Prod& p, const Maps& M, int u, int ch) {
  if (elect()) {
    mbar_expect(p.full(u), 5120 + UCH);
    tma3d(p.addr(u), &M.h, 0, -8, ch, p.full(u), true);
    bulk_g2s(p.addr(u) + CV_U, g_u + (size_t)ch * UCH, UCH, p.full(u), true);
  }
}
template<int MASK> __device__ __forceinline__ void prod_conv(Prod& p, const Maps& M, int cta, int nch) {
  int ready = -1;
#pragma unroll 1
  for (int i = 0; i < nch; i++) {
    const int ch = conv_channel<MASK>(cta, i);
    const int u = i & 3;
    if ((ch >> 6) != ready) { ready = ch >> 6; if (cta < NREG) mbar_wait(p.base + SM_RDY + 8 * RDY_U, 0); else cnt_wait(g_cnt + (C_U + ready) * CSTRIDE, 128); }
    p.acquire(u, 1);
    load_conv(p, M, u, ch);
    if (i == 3) { p.acquire(4, 4); if (elect()) mbar_arrive(p.full(4)); }
  }
}
#define HOIST(v) asm volatile("" : "+r"(v))
template<int MASK> __device__ __forceinline__ void producer(const Maps& M, const Params& P, uint32_t base, int cta, int lane) {
  Prod p{base, ((MASK & PH_KV) && cta < NREG) ? 0xffffcfffu ^ ((1u << (3 * NFIRST)) - 1) : 0xffffffffu, lane,
         (cta * 3 + 2) * 2048};
  if (cta >= NREG) { if (MASK & PH_CONV) prod_conv<MASK>(p, M, cta, CV_EXTRA<MASK>); return; }
  const int g = cta & 7, j = cta >> 3, rank = cta & 1;
#pragma unroll 1
  for (int half = 0; half < 2; half++) {
    const int h = j + 16 * half;
    if (MASK & PH_KV) {
      const CUtensorMap* mw = rank ? &M.wv : &M.wk;
#pragma unroll 1
      for (int it = half ? 0 : NFIRST; it < 16; it++) {
        const int u = gemm_unit(it);
        uint32_t bar = p.full(u), d0 = p.addr(u), d1 = p.addr(u + 1 + rank); int k0 = (it & 7) * 64, r0 = (2 * g + (it >> 3)) * 128;
        HOIST(bar); HOIST(d0); HOIST(d1); HOIST(k0); HOIST(r0);
        p.acquire(u, 3);
        if (elect()) {
          mbar_expect(bar, 3 * UNIT);
          tma3d_mc(d1, mw, 0, k0, 2 * h, bar, it >= 8);
          tma2d(d0, &M.c, k0, r0, bar);
        }
      }
    }
    if (MASK & PH_ATT) {
#pragma unroll 1
      for (int ks = 0; ks < 16; ks++) {
        const int u = gemm_unit(ks);
        uint32_t bar = p.full(u), d0 = p.addr(u), d1 = p.addr(u + 1), d2 = p.addr(u + 2) + rank * 8192; int k0 = ks * 64;
        HOIST(bar); HOIST(d0); HOIST(d1); HOIST(d2); HOIST(k0);
        p.acquire(u, 3);
        if (elect()) {
          mbar_expect(bar, 3 * UNIT);
          tma2d_mc(d2, &M.wq, h * 128 + rank * 64, k0, bar, true);
          tma2d(d0, &M.x, k0, (15 - g) * 128, bar);
          tma2d(d1, &M.x, k0, g * 128, bar);
        }
      }
      TS(2, 8 * half + 0);
      mbar_wait(base + SM_RDY + 8 * (RDY_KV + half), 0);
      TS(2, 8 * half + 1);
      const uint8_t* KVh = g_T + T_KV + (size_t)kv_slot<MASK>(h) * 16 * 65536;
      if (MASK & PH_PRE) mbar_wait(base + SM_RDY + 8 * RDY_AUX, 0);
      if (elect()) { mbar_expect(p.full(12), 32768); bulk_g2s(p.addr(12), KVh, 32768, p.full(12), true); }
      p.acquire(0, 4);
      if (elect()) mbar_arrive(p.full(0));
#pragma unroll 1
      for (int i = 1; i < 34; i++) {
        const int isv = !(i & 1) || i == 33, st = i == 33 ? 16 : (isv ? (i >> 1) - 1 : (i + 1) >> 1), u = 4 + 2 * (i & 3);
        const bool own = st == 15 - (g & 6);
        uint32_t bar = p.full(u), d0 = p.addr(own ? u : u + rank), off = (st <= 15 - g ? st : 16 - st) * 65536 + isv * 32768 + (own ? 0 : rank * UNIT);
        HOIST(bar); HOIST(d0); HOIST(off);
        p.acquire(u, 2);
        if (elect()) {
          mbar_expect(bar, 32768);
          if (own) bulk_g2s(d0, KVh + off, 32768, bar, true); else bulk_g2s_mc(d0, KVh + off, UNIT, bar, true);
        }
      }
    }
  }
  if ((MASK & PH_CONV) && !(MASK & PH_OUT)) prod_conv<MASK>(p, M, cta, CV_REG<MASK>);
  if (MASK & PH_OUT) {
    const int y0 = out_mb(cta) * 512 + rank * 8, z0 = 2 * out_nb(cta);
    int u = 6;
#pragma unroll 1
    for (int hf = 0; hf < 2; hf++) {
      TS(2, 16 + 2 * hf);
      mbar_wait(base + SM_RDY + 8 * (RDY_CTX + hf), 0);
      TS(2, 17 + 2 * hf);
#pragma unroll 1
      for (int n = hf * 32; n < hf * 32 + 32; n++) {
        const int ks = n == 1 ? 2 : n == 2 ? 1 : n;
        u = n == 2 ? 2 : n == 3 ? 10 : out_next(u);
        uint32_t bar = p.full(u), d0 = p.addr(u) + rank * 8192, d1 = p.addr(u + 1); int x = (ks & 1) * 256, y = y0 + (ks >> 1) * 16, k0 = ks * 64;
        HOIST(bar); HOIST(d0); HOIST(d1); HOIST(x); HOIST(y); HOIST(k0);
        p.acquire(u, ONE && n > 5 ? 1 : 2);
        if (elect()) {
          mbar_expect(bar, 2 * UNIT);
          tma2d_mc(d0, &M.ctx, x, y, bar, true);
          tma3d(d1, &M.wo, 0, k0, z0, bar, true);
          if (ks == 1) mbar_arrive(base + SM_RDY + 8 * RDY_X);
          if (ks == Z_AT) mbar_arrive(base + SM_RDY + 8 * RDY_Z);
        }
      }
    }
  }
}
template<int MASK> __device__ __forceinline__ void producer2(const Maps& M, const Params& P, uint32_t base, int cta, int w, int lane) {
  Prod p{base, 0xffffffffu, lane, 0};
  const int mb = out_mb(cta), nb = out_nb(cta), u = 2 * w;
  if (w) { mbar_wait_slow(base + SM_RDY + 8 * RDY_X, 0); p.mask ^= 12; }
  if (MASK & PH_CONV) {
    mbar_wait_slow(base + SM_SIG + 8 * (SIG_ATT + 1), 0);
    mbar_wait_slow(base + SM_RDY + 8 * RDY_U, 0);
#pragma unroll 1
    for (int i = w; i < CV_REG<MASK>; i += 2) { p.acquire_slow(u, i < 2 ? 2 : 1); load_conv(p, M, u, conv_channel<MASK>(cta, i)); }
  }
  p.acquire_slow(u, 2);
  if (!w && elect()) map_pf(&M.z);
  TSA(52 - 2 * w);
  mbar_wait(base + SM_RDY + 8 * (!w ? RDY_Z : RDY_G), 0);
  TSA(53 - 2 * w);
  if (elect()) {
    mbar_expect(p.full(u), 2 * UNIT + (!w ? 0 : 512));
    tma2d(p.addr(u), !w ? &M.z : &M.x, (!w ? mb : nb) * 128, (!w ? nb : mb) * 128, p.full(u), true);
    tma2d(p.addr(u + 1), !w ? &M.z : &M.x, (!w ? mb : nb) * 128 + 64, (!w ? nb : mb) * 128, p.full(u), true);
    if (w) bulk_g2s(base + SM_GATE, g_gate + mb * 128, 512, p.full(u));
  }
}

__device__ __forceinline__ constexpr uint32_t PUB(int sig, int cnt, int n) { return 0x80000000u | (sig << 24) | (n << 8) | cnt; }
__device__ __forceinline__ constexpr uint32_t GET(int rdy, int cnt, int n) { return (rdy << 24) | (n << 8) | cnt; }
template<int MASK> __device__ __forceinline__ void sync_agent(uint32_t base, int cta, int lane) {
  if ((base & 0x3FFFF) != SMEM_BASE) asm volatile("trap;");
  const int g = cta & 7, j = cta >> 3, go = min(out_mb(cta), 15 - out_mb(cta));
  const int c0 = conv_channel<MASK>(cta, 0), c1 = c0 + CV_REG<MASK> - 1, n0 = min(CV_REG<MASK>, 128 - (c0 & 127));
  constexpr bool KV = MASK & PH_KV, ATT = MASK & PH_ATT, CONV = MASK & PH_CONV, OUT = MASK & PH_OUT, ALL = MASK == PH_ALL;
  uint32_t e = 0;
  if (cta >= NREG) { if (CONV && lane * 32 < CV_EXTRA<MASK>) e = PUB(SIG_Z + lane, C_Z + lane, min(32, CV_EXTRA<MASK> - lane * 32)); }
  else switch (lane) {
    case 0:  if (KV) e = PUB(SIG_KV, C_KV + j, 1); break;
    case 1:  if (ATT) e = GET(RDY_KV, C_KV + j, 8); break;
    case 2:  if (ALL) e = PUB(SIG_WAR, C_WAR + j, 1); break;
    case 3:  if (ATT) e = PUB(SIG_CTX, C_CTX + g, 1); break;
    case 4:  if (ALL) e = GET(RDY_WAR, C_WAR + j, 8); break;
    case 5:  if (KV) e = PUB(SIG_KV + 1, C_KV + 16 + j, 1); break;
    case 6:  if (ATT) e = GET(RDY_KV + 1, C_KV + 16 + j, 8); break;
    case 7:  if (OUT) e = GET(RDY_CTX, C_CTX + go, 16); break;
    case 8:  if (CONV) e = GET(RDY_U, C_U + (c0 >> 6), 128); break;
    case 9:  if (CONV) e = GET(RDY_U, C_U + (c1 >> 6), 128); break;
    case 10: if (ATT) e = PUB(SIG_CTX + 1, C_CTX + 8 + g, 1); break;
    case 11: if (OUT) e = GET(RDY_CTX + 1, C_CTX + 8 + go, 16); break;
    case 12: if (OUT) e = GET(RDY_G, C_GATE, 256); break;
    case 13: if (CONV) e = PUB(SIG_Z, C_Z + (c0 >> 7), n0); break;
    case 14: if (CONV && n0 < CV_REG<MASK>) e = PUB(SIG_Z, C_Z + (c1 >> 7), CV_REG<MASK> - n0); break;
    case 15: if (OUT) e = GET(RDY_Z, C_Z + out_nb(cta), 128); break;
  }
  __syncwarp();
#pragma unroll 1
  for (int i = 0; i < 16; i++) {
    const uint32_t x = __shfl_sync(~0u, e, i), id = (x >> 24) & 127, n = (x >> 8) & 0xffff;
    if (x == 0) continue;
    unsigned* cnt = g_cnt + (x & 255) * CSTRIDE;
    if (x >> 31) {
      mbar_wait_slow(base + SM_SIG + 8 * id, 0);
      if (i == 13) TSA(22);
      if (lane == 0) cnt_publish(cnt, n, i != 14);
    } else {
      cnt_wait(cnt, n);
      if (id < 2) {
        const float4 kn = __ldcg((const float4*)(g_kn2 + kv_slot<MASK>(j + 16 * id) * 128) + lane);
        const uint32_t m = __reduce_max_sync(~0u, max(max(__float_as_uint(kn.x), __float_as_uint(kn.y)), max(__float_as_uint(kn.z), __float_as_uint(kn.w))));
        if (lane == 0) asm volatile("st.shared.u32 [%0], %1;" :: "r"(base + SM_KMAX + 4 * id), "r"(m) : "memory");
      }
      if (lane == 0) mbar_arrive(base + SM_RDY + 8 * id);
    }
    __syncwarp();
    TSA(24 + i);
  }
}

__device__ __forceinline__ void aux_gate(const Params& P, int cta, int aw, int lane) {
  uint4 gw[4];
#pragma unroll
  for (int i = 0; i < 4; i++) gw[i] = __ldg((const uint4*)P.gw + i * 32 + lane);
#pragma unroll 1
  for (int row = cta * 16 + aw * 8; row < cta * 16 + aw * 8 + 8; row++) {
    float a = 0.f;
#pragma unroll
    for (int i = 0; i < 4; i++) {
      const uint4 xv = __ldg((const uint4*)(P.x + (size_t)row * 1024) + i * 32 + lane);
      uint32_t m;
      m = hmul2(xv.x, gw[i].x); a += bf_lo(m) + bf_hi(m); m = hmul2(xv.y, gw[i].y); a += bf_lo(m) + bf_hi(m);
      m = hmul2(xv.z, gw[i].z); a += bf_lo(m) + bf_hi(m); m = hmul2(xv.w, gw[i].w); a += bf_lo(m) + bf_hi(m);
    }
#pragma unroll
    for (int o = 16; o > 0; o >>= 1) a += __shfl_xor_sync(~0u, a, o);
    a = bf_lo(pack_bf16(a, 0.f));
    const float gt = bf_lo(pack_bf16(__fdividef(1.f, 1.f + ex2(-a * 1.4426950408889634f)), 0.f));
    if (lane == 0) g_gate[row] = gt;
    __nanosleep(GATE_SLEEP);
  }
  cnt_signal(g_cnt + C_GATE * CSTRIDE, lane);
  if (aw == 0) { TSA(44); }
}
template<int MASK> __device__ __forceinline__ void aux_pre(const Maps& M, const Params& P, uint32_t base, int cta, int aw, int lane) {
  const uint32_t kb = base + 12 * UNIT, bar = base + SM_PRE;
  const int r = lane >> 2, q = lane & 3;
  const int mi = lane >> 3, row0 = (lane & 6) + 1 - (lane & 1);
  const int ra = (mi * 9 + 1) * 2 + row0;
  const int rb = (mi == 0 ? 3 : mi) * 18 + row0;
#pragma unroll 1
  for (int it = 0; it < (cta < 96 ? 5 : 4); it++) {
    if (it == PRE_EARLY && MASK == PH_ALL) { mbar_wait_slow(base + SM_SIG + 8 * SIG_ATT, 0); aux_gate(P, cta, aw, lane); }
    if (it == PRE_EARLY && MASK == PH_ALL) mbar_wait_slow(base + SM_SIG + 8 * (SIG_ATT + 1), 0);
    const int cg = it ? it * 4 - 3 + (cta >> 5) : 0, tb = cta & 31;
    if (aw == 0 && elect()) {
      mbar_expect(bar, 2 * 9216);
      tma4d(kb, &M.k, cg * 64, 0, tb * 8 - 1, 0, bar, true);
      tma4d(kb + 9216, &M.v, cg * 64, 0, tb * 8 - 1, 0, bar, true);
    }
    const uint2 swl = __ldg((const uint2*)(P.shift + (cg * 64 + aw * 32 + lane) * 4));
    if (tb == 0) {
      uint8_t* e = g_u + (size_t)(cg * 64 + aw * 32 + lane) * UCH + 4096;
      *(uint4*)e = make_uint4(0, 0, 0, 0); *(uint4*)(e + UPITCH) = make_uint4(0, 0, 0, 0);
      *(uint32_t*)(e + 32) = (uint32_t)__bfloat16_as_ushort(P.D[cg * 64 + aw * 32 + lane]) * 0x10001u;
    }
    mbar_wait_slow(bar, it & 1);
#pragma unroll 1
    for (int ol = it ? 0 : cta >> 5; ol < (it ? 4 : (cta >> 5) + 1); ol++) {
      const int oc = aw * 4 + ol;
      const uint32_t s01 = __shfl_sync(~0u, swl.x, ol * 8 + r), s23 = __shfl_sync(~0u, swl.y, ol * 8 + r);
      const uint32_t w0 = __byte_perm(s01, 0, 0x1010), w1 = __byte_perm(s01, 0, 0x3232), w2 = __byte_perm(s23, 0, 0x1010), w3 = __byte_perm(s23, 0, 0x3232);
      const uint32_t pa = kb + ra * 128 + ((oc ^ (ra & 7)) << 4), pb = kb + (mi == 0 ? 9216 : 0) + rb * 128 + ((oc ^ (rb & 7)) << 4);
      uint8_t* e0 = g_u + (uint32_t)((cg * 64 + oc * 8 + r) * UCH + (2040 - tb * 64 - 8 * q) * 2);
#pragma unroll
      for (int hb = 0; hb < 2; hb++) {
        uint32_t k[7], v[5];
        ldsm4t(pa + hb * 1024, k[3], k[4], k[5], k[6]);
        ldsm4t(pa + hb * 1024 + 9216, v[1], v[2], v[3], v[4]);
        ldsm4t(pb + hb * 1024, v[0], k[0], k[1], k[2]);
        uint32_t o1 = __byte_perm(k[1], k[0], 0x5432);
#pragma unroll
        for (int m = 0; m < 5; m++) {
          const uint32_t o2 = __byte_perm(k[m + 2], k[m + 1], 0x5432);
          v[m] = hmul2(hadd2(hadd2(hadd2(hmul2(o1, w3), hmul2(k[m + 1], w2)), hmul2(o2, w1)), hmul2(k[m + 2], w0)), v[m]);
          o1 = o2;
        }
        *(uint4*)(e0 - hb * 64) = make_uint4(v[4], v[3], v[2], v[1]);
        *(uint4*)(e0 - hb * 64 + UPITCH) = make_uint4(__byte_perm(v[4], v[3], 0x5432), __byte_perm(v[3], v[2], 0x5432), __byte_perm(v[2], v[1], 0x5432), __byte_perm(v[1], v[0], 0x5432));
        if (it >= PRE_EARLY) __nanosleep(PRE_SLEEP);
      }
    }
    bar_sync(5, 64);
    if (aw == 0) { TSA(40 + min(it, 3)); }
    if (it == PRE_EARLY - 1 && aw == 0 && lane == 0) mbar_arrive(base + SM_RDY + 8 * RDY_AUX);
    if (aw == 1 && lane == 0) asm volatile("red.release.gpu.global.add.u32 [%0], %1;" :: "l"(g_cnt + (C_U + cg) * CSTRIDE), "r"(it ? 4 : 1) : "memory");
  }
  uint32_t rel;
  asm volatile("mapa.shared::cluster.u32 %0, %1, %2;" : "=r"(rel) : "r"(base + SM_BAR + 128 + 8 * (12 + (lane & 1))), "r"((lane >> 1) & 1));
  if (lane < 4) asm volatile("mbarrier.arrive.shared::cluster.b64 _, [%0], %1;" :: "r"(rel), "n"(REL1 ? 1 : 4) : "memory");
  if (MASK != PH_ALL) aux_gate(P, cta, aw, lane);
}

template<int MASK> __global__ void __cluster_dims__(2, 1, 1) __launch_bounds__(384, 1) gated_mix_kernel(const __grid_constant__ Maps M, const __grid_constant__ Params P) {
  extern __shared__ __align__(1024) uint8_t smem[];
  const uint32_t base = (uint32_t)__cvta_generic_to_shared(smem);
  if ((MASK & PH_KV) && elect()) {
    map_pf(&M.wk + (blockIdx.x & 1)); map_pf(&M.c);
  }
  const int wi = __shfl_sync(~0u, threadIdx.x >> 5, 0), wg = wi >> 2, warp = wi & 3;
  if (elect()) {
    if (wi < 8) {
      const int cnt = 1 << (((REL1 ? 0x10332200 : 0x10334400) >> (4 * wi)) & 15);
#pragma unroll
      for (int i = 0; i < 8; i++) mbar_init(base + SM_BAR + 64 * wi + 8 * i, cnt);
      asm volatile("fence.mbarrier_init.release.cluster;" ::: "memory");
    }
  }
  const int cta = blockIdx.x;
  const bool first_loads = (MASK & PH_KV) && wi == 8 && cta < NREG;
  const CUtensorMap* mw = (cta & 1) ? &M.wv : &M.wk;
  __syncwarp();
  asm volatile("barrier.cluster.arrive.relaxed.aligned;\nbarrier.cluster.wait.aligned;" ::: "memory");
  auto first_stage = [&](int it) {
    const uint32_t bar = base + SM_BAR + 24 * it, d0 = base + 3 * it * UNIT;
    mbar_expect(bar, 3 * UNIT);
    tma3d_mc(d0 + (1 + (cta & 1)) * UNIT, mw, 0, it * 64, 2 * (cta >> 3), bar);
    tma2d(d0, &M.c, it * 64, (cta & 7) * 256, bar);
  };
  if (first_loads && elect()) first_stage(0);
  __syncwarp();
  const int lane = threadIdx.x & 31;
#define TS_PRO()
  if (wg == 2) {
    asm volatile("setmaxnreg.dec.sync.aligned.u32 56;");
    TS_PRO();
    TS(2, 62);
    if (warp == 0) producer<MASK>(M, P, base, cta, lane);
    else if (warp == 1) sync_agent<MASK>(base, cta, lane);
    else if (cta < NREG) {
      if (MASK & PH_PRE) aux_pre<MASK>(M, P, base, cta, warp - 2, lane);
      if (MASK & PH_OUT) producer2<MASK>(M, P, base, cta, warp - 2, lane);
    }
    if (warp == 1) {
      if (MASK & PH_OUT) {
        unsigned old = 0;
        if (lane == 0) asm volatile("atom.relaxed.gpu.global.add.u32 %0, [%1], 1;" : "=r"(old) : "l"(g_cnt + C_EXIT * CSTRIDE) : "memory");
        old = __shfl_sync(~0u, old, 0);
        if (old == NCTA - 1) for (int i = lane; i < C_NUM; i += 32) g_cnt[i * CSTRIDE] = 0;
      }
      mbar_wait_slow(base + SM_SIG + 8 * SIG_DONE, 0);
      if (cta >= NREG || !(MASK & PH_OUT)) { cluster_arrive(); cluster_wait(); }
    }
  } else {
    asm volatile("setmaxnreg.inc.sync.aligned.u32 224;");
    TS_PRO();
    uint32_t rel;
    asm volatile("mapa.shared::cluster.u32 %0, %1, %2;" : "=r"(rel) : "r"(base + SM_BAR + 128 + 8 * (lane & 15)), "r"(lane >> 4));
    Cons c{base, rel, 0u, lane, warp, wg, REL1 && warp != RELW ? 16 : lane & 15, (cta * 3 + wg) * 2048};
    if (wg == 1) bar_arrive(1, 256);
    if ((MASK & PH_KV) && wi == 4 && cta < NREG) {
      if (elect()) {
#pragma unroll 1
        for (int it = 1; it < NFIRST; it++) {
          asm volatile("{\n.reg .pred p;\n.reg .u32 a, b;\nmov.u32 a, %%clock;\nXL:\nmov.u32 b, %%clock;\nsub.u32 b, b, a;\nsetp.lt.u32 p, b, %0;\n@p bra XL;\n}\n" :: "r"(it == 1 ? FGAP : FGAP2) : "memory");
          first_stage(it);
        }
      }
      __syncwarp();
    }
    TS(wg, 0);
    if (cta < NREG) {
      const int g = cta & 7, j = cta >> 3;
      Pend w = {};
#pragma unroll 1
      for (int half = 0; half < 2; half++) {
        const int h = j + 16 * half, blk = kv_slot<MASK>(h) * 16 + 2 * g;
        if (MASK & PH_KV) cons_kv<(MASK & PH_ATT) != 0>(c, h, blk, g, w, half == 1 && (MASK & PH_ATT));
        TS(wg, 1 + 4 * half);
        if (MASK & PH_ATT) {
          Att a;
          cons_q<(MASK & PH_KV) != 0>(c, h, blk + 1, w, a.o);
          TS(wg, 2 + 4 * half);
          cons_att(c, a, h, g, w);
          if (half == 0) c.signal(SIG_WAR);
#pragma unroll
          for (int i = 0; i < 8; i++) w.hi[i] = make_uint4(0, 0, 0, 0);
          TS(wg, 3 + 4 * half);
          if (MASK != PH_ALL) { tile_store<0, 4>(w.lo, ctx_off(c, h, g, 1 - wg), lane); c.signal(SIG_CTX + half); }
        } else if (MASK & PH_KV) {
          float kn = 0.f;
          out_piece<SCH_KV, true>(c, w, kv_off(c, blk + 1), blk + 1, kn, 0, true);
          for (int ks = 1; ks < 8; ks++) out_piece<SCH_KV, false>(c, w, kv_off(c, blk + 1), blk + 1, kn, ks, true);
          c.signal(SIG_KV + half);
        }
      }
      if (MASK & PH_OUT) cons_out<MASK>(c, M, P, cta, w);
    }
    if (cta >= NREG || !(MASK & PH_OUT)) {
      if (MASK & PH_CONV) cons_conv<MASK>(c, cta, cta < NREG ? CV_REG<MASK> : CV_EXTRA<MASK>);
      TS(wg, 9);
      c.signal(SIG_DONE);
      cluster_arrive();
    }
    TS(wg, 10);
  }
}

typedef CUresult (*EncFn)(CUtensorMap*, CUtensorMapDataType, cuuint32_t, void*, const cuuint64_t*, const cuuint64_t*, const cuuint32_t*, const cuuint32_t*,
                          CUtensorMapInterleave, CUtensorMapSwizzle, CUtensorMapL2promotion, CUtensorMapFloatOOBfill);
static void enc(EncFn f, CUtensorMap* m, const void* ptr, int rank, const cuuint64_t* dims, const cuuint64_t* strides, const cuuint32_t* box, CUtensorMapSwizzle sw,
                CUtensorMapDataType dt = CU_TENSOR_MAP_DATA_TYPE_BFLOAT16) {
  const cuuint32_t es[4] = {1, 1, 1, 1};
  f(m, dt, rank, (void*)ptr, dims, strides, box, es, CU_TENSOR_MAP_INTERLEAVE_NONE, sw, CU_TENSOR_MAP_L2_PROMOTION_L2_256B, CU_TENSOR_MAP_FLOAT_OOB_FILL_NONE);
}
static void enc2(EncFn f, CUtensorMap* m, const void* ptr, int cols, int rows, int brows) {
  const cuuint64_t d[2] = {(cuuint64_t)cols, (cuuint64_t)rows}, s[1] = {(cuuint64_t)cols * 2}; const cuuint32_t b[2] = {64, (cuuint32_t)brows};
  enc(f, m, ptr, 2, d, s, b, CU_TENSOR_MAP_SWIZZLE_128B);
}
static void encw(EncFn f, CUtensorMap* m, const void* ptr, int cols, int rows) {
  const cuuint64_t d[3] = {64, (cuuint64_t)rows, (cuuint64_t)cols / 64}, s[2] = {(cuuint64_t)cols * 2, 128}; const cuuint32_t b[3] = {64, 64, 2};
  enc(f, m, ptr, 3, d, s, b, CU_TENSOR_MAP_SWIZZLE_128B);
}
extern "C" void kernel_launch(void* const* d_in, const int* in_sizes, int n_in, void* d_out, int out_size) {
  static EncFn fn = nullptr;
  static int ncl = 0;
  static void* zptr = nullptr;
  static void* tptr = nullptr;
  if (!fn) {
    void* p = nullptr; cudaDriverEntryPointQueryResult qr;
    cudaGetDriverEntryPoint("cuTensorMapEncodeTiled", &p, cudaEnableDefault, &qr);
    fn = (EncFn)p;
    cudaFuncSetAttribute(gated_mix_kernel<PH_ALL>, cudaFuncAttributeMaxDynamicSharedMemorySize, SMEM_BYTES);
    cudaFuncSetAttribute(gated_mix_kernel<PH_PRE | PH_KV>, cudaFuncAttributeMaxDynamicSharedMemorySize, SMEM_BYTES);
    cudaFuncSetAttribute(gated_mix_kernel<PH_ATT | PH_CONV>, cudaFuncAttributeMaxDynamicSharedMemorySize, SMEM_BYTES);
    cudaFuncSetAttribute(gated_mix_kernel<PH_OUT>, cudaFuncAttributeMaxDynamicSharedMemorySize, SMEM_BYTES);
    cudaLaunchConfig_t cfg = {}; cfg.gridDim = NCTA; cfg.blockDim = 384; cfg.dynamicSmemBytes = SMEM_BYTES;
    cudaLaunchAttribute at; at.id = cudaLaunchAttributeClusterDimension; at.val.clusterDim.x = 2; at.val.clusterDim.y = 1; at.val.clusterDim.z = 1;
    cfg.attrs = &at; cfg.numAttrs = 1;
    cudaOccupancyMaxActiveClusters(&ncl, gated_mix_kernel<PH_ALL>, &cfg);
    cudaGetSymbolAddress(&zptr, g_z);
    cudaGetSymbolAddress(&tptr, g_T);
  }
  Maps M;
  enc2(fn, &M.x, d_in[0], 1024, 2048, 128);
  enc2(fn, &M.c, d_in[7], 512, 2048, 128);
  enc2(fn, &M.wq, d_in[8], 4096, 1024, 64);
  encw(fn, &M.wk, d_in[9], 4096, 512);
  encw(fn, &M.wv, d_in[10], 4096, 512);
  encw(fn, &M.wo, d_in[11], 1024, 4096);
  { const cuuint64_t d[3] = {64, 32, 1024}, s[2] = {128, 4096}; const cuuint32_t b[3] = {64, 40, 1}; enc(fn, &M.h, d_in[4], 3, d, s, b, CU_TENSOR_MAP_SWIZZLE_NONE); }
  enc2(fn, &M.z, zptr, 2048, 1024, 128);
  enc2(fn, &M.out, d_out, 1024, 2048, 16);
  { const cuuint64_t d[2] = {512, 512 * 16}, s[1] = {2048}; const cuuint32_t b[2] = {256, 8};
    enc(fn, &M.ctx, tptr, 2, d, s, b, CU_TENSOR_MAP_SWIZZLE_NONE, CU_TENSOR_MAP_DATA_TYPE_UINT32); }
  { const cuuint64_t d[4] = {1024, 2, 256, 4}, s[3] = {2048, 16384, 4096}; const cuuint32_t b[4] = {64, 2, 9, 4};
    enc(fn, &M.k, d_in[1], 4, d, s, b, CU_TENSOR_MAP_SWIZZLE_128B); enc(fn, &M.v, d_in[2], 4, d, s, b, CU_TENSOR_MAP_SWIZZLE_128B); }
  Params P{(const __nv_bfloat16*)d_in[0], (const __nv_bfloat16*)d_in[3],
           (const __nv_bfloat16*)d_in[5], (const __nv_bfloat16*)d_in[12], (__nv_bfloat16*)d_out};
  bool split = 2 * ncl < NCTA;
  if (!split) {
    gated_mix_kernel<PH_ALL><<<NCTA, 384, SMEM_BYTES>>>(M, P);
  } else {
    gated_mix_kernel<PH_PRE | PH_KV><<<NCTA, 384, SMEM_BYTES>>>(M, P);
    gated_mix_kernel<PH_ATT | PH_CONV><<<NCTA, 384, SMEM_BYTES>>>(M, P);
    gated_mix_kernel<PH_OUT><<<NCTA, 384, SMEM_BYTES>>>(M, P);
  }
}
```

```cpp
#include <cuda_runtime.h>
#include <cuda.h>
#include <cuda_bf16.h>
#include <stdint.h>

template<int TB> __device__ __forceinline__ void wgmma_ss_n256(float (&d)[128], uint64_t da, uint64_t db, int scale_d) {
  asm volatile("{\n.reg .pred p;\nsetp.ne.b32 p, %130, 0;\n"
    "wgmma.mma_async.sync.aligned.m64n256k16.f32.bf16.bf16 {%0, %1, %2, %3, %4, %5, %6, %7, %8, %9, %10, %11, %12, %13, %14, %15, %16, %17, %18, %19, %20, %21, %22, %23, %24, %25, %26, %27, %28, %29, %30, %31, %32, %33, %34, %35, %36, %37, %38, %39, %40, %41, %42, %43, %44, %45, %46, %47, %48, %49, %50, %51, %52, %53, %54, %55, %56, %57, %58, %59, %60, %61, %62, %63, %64, %65, %66, %67, %68, %69, %70, %71, %72, %73, %74, %75, %76, %77, %78, %79, %80, %81, %82, %83, %84, %85, %86, %87, %88, %89, %90, %91, %92, %93, %94, %95, %96, %97, %98, %99, %100, %101, %102, %103, %104, %105, %106, %107, %108, %109, %110, %111, %112, %113, %114, %115, %116, %117, %118, %119, %120, %121, %122, %123, %124, %125, %126, %127}, %128, %129, p, 1, 1, 0, %131;\n}\n"
    : "+f"(d[0]), "+f"(d[1]), "+f"(d[2]), "+f"(d[3]), "+f"(d[4]), "+f"(d[5]), "+f"(d[6]), "+f"(d[7]), "+f"(d[8]), "+f"(d[9]), "+f"(d[10]), "+f"(d[11]), "+f"(d[12]), "+f"(d[13]), "+f"(d[14]), "+f"(d[15]), "+f"(d[16]), "+f"(d[17]), "+f"(d[18]), "+f"(d[19]), "+f"(d[20]), "+f"(d[21]), "+f"(d[22]), "+f"(d[23]), "+f"(d[24]), "+f"(d[25]), "+f"(d[26]), "+f"(d[27]), "+f"(d[28]), "+f"(d[29]), "+f"(d[30]), "+f"(d[31]), "+f"(d[32]), "+f"(d[33]), "+f"(d[34]), "+f"(d[35]), "+f"(d[36]), "+f"(d[37]), "+f"(d[38]), "+f"(d[39]), "+f"(d[40]), "+f"(d[41]), "+f"(d[42]), "+f"(d[43]), "+f"(d[44]), "+f"(d[45]), "+f"(d[46]), "+f"(d[47]), "+f"(d[48]), "+f"(d[49]), "+f"(d[50]), "+f"(d[51]), "+f"(d[52]), "+f"(d[53]), "+f"(d[54]), "+f"(d[55]), "+f"(d[56]), "+f"(d[57]), "+f"(d[58]), "+f"(d[59]), "+f"(d[60]), "+f"(d[61]), "+f"(d[62]), "+f"(d[63]), "+f"(d[64]), "+f"(d[65]), "+f"(d[66]), "+f"(d[67]), "+f"(d[68]), "+f"(d[69]), "+f"(d[70]), "+f"(d[71]), "+f"(d[72]), "+f"(d[73]), "+f"(d[74]), "+f"(d[75]), "+f"(d[76]), "+f"(d[77]), "+f"(d[78]), "+f"(d[79]), "+f"(d[80]), "+f"(d[81]), "+f"(d[82]), "+f"(d[83]), "+f"(d[84]), "+f"(d[85]), "+f"(d[86]), "+f"(d[87]), "+f"(d[88]), "+f"(d[89]), "+f"(d[90]), "+f"(d[91]), "+f"(d[92]), "+f"(d[93]), "+f"(d[94]), "+f"(d[95]), "+f"(d[96]), "+f"(d[97]), "+f"(d[98]), "+f"(d[99]), "+f"(d[100]), "+f"(d[101]), "+f"(d[102]), "+f"(d[103]), "+f"(d[104]), "+f"(d[105]), "+f"(d[106]), "+f"(d[107]), "+f"(d[108]), "+f"(d[109]), "+f"(d[110]), "+f"(d[111]), "+f"(d[112]), "+f"(d[113]), "+f"(d[114]), "+f"(d[115]), "+f"(d[116]), "+f"(d[117]), "+f"(d[118]), "+f"(d[119]), "+f"(d[120]), "+f"(d[121]), "+f"(d[122]), "+f"(d[123]), "+f"(d[124]), "+f"(d[125]), "+f"(d[126]), "+f"(d[127])
    : "l"(da), "l"(db), "r"(scale_d), "n"(TB));
}
template<int TB> __device__ __forceinline__ void wgmma_ss_n128(float (&d)[64], uint64_t da, uint64_t db, int scale_d) {
  asm volatile("{\n.reg .pred p;\nsetp.ne.b32 p, %66, 0;\n"
    "wgmma.mma_async.sync.aligned.m64n128k16.f32.bf16.bf16 {%0, %1, %2, %3, %4, %5, %6, %7, %8, %9, %10, %11, %12, %13, %14, %15, %16, %17, %18, %19, %20, %21, %22, %23, %24, %25, %26, %27, %28, %29, %30, %31, %32, %33, %34, %35, %36, %37, %38, %39, %40, %41, %42, %43, %44, %45, %46, %47, %48, %49, %50, %51, %52, %53, %54, %55, %56, %57, %58, %59, %60, %61, %62, %63}, %64, %65, p, 1, 1, 0, %67;\n}\n"
    : "+f"(d[0]), "+f"(d[1]), "+f"(d[2]), "+f"(d[3]), "+f"(d[4]), "+f"(d[5]), "+f"(d[6]), "+f"(d[7]), "+f"(d[8]), "+f"(d[9]), "+f"(d[10]), "+f"(d[11]), "+f"(d[12]), "+f"(d[13]), "+f"(d[14]), "+f"(d[15]), "+f"(d[16]), "+f"(d[17]), "+f"(d[18]), "+f"(d[19]), "+f"(d[20]), "+f"(d[21]), "+f"(d[22]), "+f"(d[23]), "+f"(d[24]), "+f"(d[25]), "+f"(d[26]), "+f"(d[27]), "+f"(d[28]), "+f"(d[29]), "+f"(d[30]), "+f"(d[31]), "+f"(d[32]), "+f"(d[33]), "+f"(d[34]), "+f"(d[35]), "+f"(d[36]), "+f"(d[37]), "+f"(d[38]), "+f"(d[39]), "+f"(d[40]), "+f"(d[41]), "+f"(d[42]), "+f"(d[43]), "+f"(d[44]), "+f"(d[45]), "+f"(d[46]), "+f"(d[47]), "+f"(d[48]), "+f"(d[49]), "+f"(d[50]), "+f"(d[51]), "+f"(d[52]), "+f"(d[53]), "+f"(d[54]), "+f"(d[55]), "+f"(d[56]), "+f"(d[57]), "+f"(d[58]), "+f"(d[59]), "+f"(d[60]), "+f"(d[61]), "+f"(d[62]), "+f"(d[63])
    : "l"(da), "l"(db), "r"(scale_d), "n"(TB));
}
template<int TB> __device__ __forceinline__ void wgmma_rs_n32(float (&d)[16], uint32_t a0, uint32_t a1, uint32_t a2, uint32_t a3, uint64_t db, int scale_d) {
  asm volatile("{\n.reg .pred p;\nsetp.ne.b32 p, %21, 0;\n"
    "wgmma.mma_async.sync.aligned.m64n32k16.f32.bf16.bf16 {%0, %1, %2, %3, %4, %5, %6, %7, %8, %9, %10, %11, %12, %13, %14, %15}, {%16, %17, %18, %19}, %20, p, 1, 1, %22;\n}\n"
    : "+f"(d[0]), "+f"(d[1]), "+f"(d[2]), "+f"(d[3]), "+f"(d[4]), "+f"(d[5]), "+f"(d[6]), "+f"(d[7]), "+f"(d[8]), "+f"(d[9]), "+f"(d[10]), "+f"(d[11]), "+f"(d[12]), "+f"(d[13]), "+f"(d[14]), "+f"(d[15])
    : "r"(a0), "r"(a1), "r"(a2), "r"(a3), "l"(db), "r"(scale_d), "n"(TB));
}
__device__ __forceinline__ void wgmma_pv_sel(float (&d)[64], const uint32_t (&p)[32], uint64_t db, int full, int acc, int wg) {
  asm volatile("{\n.reg .pred q, s, w;\n.reg .b64 t;\nsetp.eq.b32 w, %99, 0;\nsetp.ne.b32 s, %98, 0;\nsetp.eq.b32 q, %97, 0;\n@q bra.uni LH;\n"
    "wgmma.fence.sync.aligned;\n"
    "add.s64 t, %96, 0;\nwgmma.mma_async.sync.aligned.m64n128k16.f32.bf16.bf16 {%0, %1, %2, %3, %4, %5, %6, %7, %8, %9, %10, %11, %12, %13, %14, %15, %16, %17, %18, %19, %20, %21, %22, %23, %24, %25, %26, %27, %28, %29, %30, %31, %32, %33, %34, %35, %36, %37, %38, %39, %40, %41, %42, %43, %44, %45, %46, %47, %48, %49, %50, %51, %52, %53, %54, %55, %56, %57, %58, %59, %60, %61, %62, %63}, {%64, %65, %66, %67}, t, s, 1, 1, 1;\n"
    "add.s64 t, %96, 256;\nwgmma.mma_async.sync.aligned.m64n128k16.f32.bf16.bf16 {%0, %1, %2, %3, %4, %5, %6, %7, %8, %9, %10, %11, %12, %13, %14, %15, %16, %17, %18, %19, %20, %21, %22, %23, %24, %25, %26, %27, %28, %29, %30, %31, %32, %33, %34, %35, %36, %37, %38, %39, %40, %41, %42, %43, %44, %45, %46, %47, %48, %49, %50, %51, %52, %53, %54, %55, %56, %57, %58, %59, %60, %61, %62, %63}, {%68, %69, %70, %71}, t, 1, 1, 1, 1;\n"
    "add.s64 t, %96, 512;\nwgmma.mma_async.sync.aligned.m64n128k16.f32.bf16.bf16 {%0, %1, %2, %3, %4, %5, %6, %7, %8, %9, %10, %11, %12, %13, %14, %15, %16, %17, %18, %19, %20, %21, %22, %23, %24, %25, %26, %27, %28, %29, %30, %31, %32, %33, %34, %35, %36, %37, %38, %39, %40, %41, %42, %43, %44, %45, %46, %47, %48, %49, %50, %51, %52, %53, %54, %55, %56, %57, %58, %59, %60, %61, %62, %63}, {%72, %73, %74, %75}, t, 1, 1, 1, 1;\n"
    "add.s64 t, %96, 768;\nwgmma.mma_async.sync.aligned.m64n128k16.f32.bf16.bf16 {%0, %1, %2, %3, %4, %5, %6, %7, %8, %9, %10, %11, %12, %13, %14, %15, %16, %17, %18, %19, %20, %21, %22, %23, %24, %25, %26, %27, %28, %29, %30, %31, %32, %33, %34, %35, %36, %37, %38, %39, %40, %41, %42, %43, %44, %45, %46, %47, %48, %49, %50, %51, %52, %53, %54, %55, %56, %57, %58, %59, %60, %61, %62, %63}, {%76, %77, %78, %79}, t, 1, 1, 1, 1;\n"
    "add.s64 t, %96, 1024;\nwgmma.mma_async.sync.aligned.m64n128k16.f32.bf16.bf16 {%0, %1, %2, %3, %4, %5, %6, %7, %8, %9, %10, %11, %12, %13, %14, %15, %16, %17, %18, %19, %20, %21, %22, %23, %24, %25, %26, %27, %28, %29, %30, %31, %32, %33, %34, %35, %36, %37, %38, %39, %40, %41, %42, %43, %44, %45, %46, %47, %48, %49, %50, %51, %52, %53, %54, %55, %56, %57, %58, %59, %60, %61, %62, %63}, {%80, %81, %82, %83}, t, 1, 1, 1, 1;\n"
    "add.s64 t, %96, 1280;\nwgmma.mma_async.sync.aligned.m64n128k16.f32.bf16.bf16 {%0, %1, %2, %3, %4, %5, %6, %7, %8, %9, %10, %11, %12, %13, %14, %15, %16, %17, %18, %19, %20, %21, %22, %23, %24, %25, %26, %27, %28, %29, %30, %31, %32, %33, %34, %35, %36, %37, %38, %39, %40, %41, %42, %43, %44, %45, %46, %47, %48, %49, %50, %51, %52, %53, %54, %55, %56, %57, %58, %59, %60, %61, %62, %63}, {%84, %85, %86, %87}, t, 1, 1, 1, 1;\n"
    "@w bar.arrive 2, 256;\n@!w bar.arrive 1, 256;\n"
    "add.s64 t, %96, 1536;\nwgmma.mma_async.sync.aligned.m64n128k16.f32.bf16.bf16 {%0, %1, %2, %3, %4, %5, %6, %7, %8, %9, %10, %11, %12, %13, %14, %15, %16, %17, %18, %19, %20, %21, %22, %23, %24, %25, %26, %27, %28, %29, %30, %31, %32, %33, %34, %35, %36, %37, %38, %39, %40, %41, %42, %43, %44, %45, %46, %47, %48, %49, %50, %51, %52, %53, %54, %55, %56, %57, %58, %59, %60, %61, %62, %63}, {%88, %89, %90, %91}, t, 1, 1, 1, 1;\n"
    "add.s64 t, %96, 1792;\nwgmma.mma_async.sync.aligned.m64n128k16.f32.bf16.bf16 {%0, %1, %2, %3, %4, %5, %6, %7, %8, %9, %10, %11, %12, %13, %14, %15, %16, %17, %18, %19, %20, %21, %22, %23, %24, %25, %26, %27, %28, %29, %30, %31, %32, %33, %34, %35, %36, %37, %38, %39, %40, %41, %42, %43, %44, %45, %46, %47, %48, %49, %50, %51, %52, %53, %54, %55, %56, %57, %58, %59, %60, %61, %62, %63}, {%92, %93, %94, %95}, t, 1, 1, 1, 1;\n"
    "wgmma.commit_group.sync.aligned;\n"
    "bra.uni LE;\nLH:\n"
    "wgmma.fence.sync.aligned;\n"
    "add.s64 t, %96, 0;\nwgmma.mma_async.sync.aligned.m64n128k16.f32.bf16.bf16 {%0, %1, %2, %3, %4, %5, %6, %7, %8, %9, %10, %11, %12, %13, %14, %15, %16, %17, %18, %19, %20, %21, %22, %23, %24, %25, %26, %27, %28, %29, %30, %31, %32, %33, %34, %35, %36, %37, %38, %39, %40, %41, %42, %43, %44, %45, %46, %47, %48, %49, %50, %51, %52, %53, %54, %55, %56, %57, %58, %59, %60, %61, %62, %63}, {%80, %81, %82, %83}, t, s, 1, 1, 1;\n"
    "add.s64 t, %96, 256;\nwgmma.mma_async.sync.aligned.m64n128k16.f32.bf16.bf16 {%0, %1, %2, %3, %4, %5, %6, %7, %8, %9, %10, %11, %12, %13, %14, %15, %16, %17, %18, %19, %20, %21, %22, %23, %24, %25, %26, %27, %28, %29, %30, %31, %32, %33, %34, %35, %36, %37, %38, %39, %40, %41, %42, %43, %44, %45, %46, %47, %48, %49, %50, %51, %52, %53, %54, %55, %56, %57, %58, %59, %60, %61, %62, %63}, {%84, %85, %86, %87}, t, 1, 1, 1, 1;\n"
    "@w bar.arrive 2, 256;\n@!w bar.arrive 1, 256;\n"
    "add.s64 t, %96, 512;\nwgmma.mma_async.sync.aligned.m64n128k16.f32.bf16.bf16 {%0, %1, %2, %3, %4, %5, %6, %7, %8, %9, %10, %11, %12, %13, %14, %15, %16, %17, %18, %19, %20, %21, %22, %23, %24, %25, %26, %27, %28, %29, %30, %31, %32, %33, %34, %35, %36, %37, %38, %39, %40, %41, %42, %43, %44, %45, %46, %47, %48, %49, %50, %51, %52, %53, %54, %55, %56, %57, %58, %59, %60, %61, %62, %63}, {%88, %89, %90, %91}, t, 1, 1, 1, 1;\n"
    "add.s64 t, %96, 768;\nwgmma.mma_async.sync.aligned.m64n128k16.f32.bf16.bf16 {%0, %1, %2, %3, %4, %5, %6, %7, %8, %9, %10, %11, %12, %13, %14, %15, %16, %17, %18, %19, %20, %21, %22, %23, %24, %25, %26, %27, %28, %29, %30, %31, %32, %33, %34, %35, %36, %37, %38, %39, %40, %41, %42, %43, %44, %45, %46, %47, %48, %49, %50, %51, %52, %53, %54, %55, %56, %57, %58, %59, %60, %61, %62, %63}, {%92, %93, %94, %95}, t, 1, 1, 1, 1;\n"
    "wgmma.commit_group.sync.aligned;\n"
    "LE:\n}\n"
    : "+f"(d[0]), "+f"(d[1]), "+f"(d[2]), "+f"(d[3]), "+f"(d[4]), "+f"(d[5]), "+f"(d[6]), "+f"(d[7]), "+f"(d[8]), "+f"(d[9]), "+f"(d[10]), "+f"(d[11]), "+f"(d[12]), "+f"(d[13]), "+f"(d[14]), "+f"(d[15]), "+f"(d[16]), "+f"(d[17]), "+f"(d[18]), "+f"(d[19]), "+f"(d[20]), "+f"(d[21]), "+f"(d[22]), "+f"(d[23]), "+f"(d[24]), "+f"(d[25]), "+f"(d[26]), "+f"(d[27]), "+f"(d[28]), "+f"(d[29]), "+f"(d[30]), "+f"(d[31]), "+f"(d[32]), "+f"(d[33]), "+f"(d[34]), "+f"(d[35]), "+f"(d[36]), "+f"(d[37]), "+f"(d[38]), "+f"(d[39]), "+f"(d[40]), "+f"(d[41]), "+f"(d[42]), "+f"(d[43]), "+f"(d[44]), "+f"(d[45]), "+f"(d[46]), "+f"(d[47]), "+f"(d[48]), "+f"(d[49]), "+f"(d[50]), "+f"(d[51]), "+f"(d[52]), "+f"(d[53]), "+f"(d[54]), "+f"(d[55]), "+f"(d[56]), "+f"(d[57]), "+f"(d[58]), "+f"(d[59]), "+f"(d[60]), "+f"(d[61]), "+f"(d[62]), "+f"(d[63])
    : "r"(p[0]), "r"(p[1]), "r"(p[2]), "r"(p[3]), "r"(p[4]), "r"(p[5]), "r"(p[6]), "r"(p[7]), "r"(p[8]), "r"(p[9]), "r"(p[10]), "r"(p[11]), "r"(p[12]), "r"(p[13]), "r"(p[14]), "r"(p[15]), "r"(p[16]), "r"(p[17]), "r"(p[18]), "r"(p[19]), "r"(p[20]), "r"(p[21]), "r"(p[22]), "r"(p[23]), "r"(p[24]), "r"(p[25]), "r"(p[26]), "r"(p[27]), "r"(p[28]), "r"(p[29]), "r"(p[30]), "r"(p[31]), "l"(db), "r"(full), "r"(acc), "r"(wg) : "memory");
}

constexpr int NCTA = 132, NREG = 128;
constexpr int UNIT = 16384, NUNIT = 14;
constexpr uint32_t SMEM_BASE = 1024;
constexpr int SM_BAR = NUNIT * UNIT;
constexpr int SM_GATE = SM_BAR + 1024;
constexpr int SMEM_BYTES = SM_BAR + 1536;
constexpr int UPITCH = 4160, UCH = 2 * UPITCH;
constexpr float QSCALE = 0.08838834764831845f * 1.4426950408889634f;
constexpr float BOUND2 = 60.f * 60.f / 1.15f;
#define CONV_REG 5
constexpr int C_KV = 0;
constexpr int C_CTX = 32;
constexpr int C_U = 48;
constexpr int C_Z = 80;
constexpr int C_GATE = 88;
constexpr int C_EXIT = 89;
#define ATT_SPLIT 4
#define SL_BAR 256
#define SL_CNT 0
#define USPLIT 0
#define Z_AT 60
#define PRE_SLEEP 300
#define GATE_SLEEP 1000
#define OC_S0 2
#define OC_S1 11
#define OC_L0 18
#define OC_L1 18
#define ST_1 4
#define ST_D 2
#define SCH_KV 0x6665544433221100ull
#define SCH_Q 0x6665544433221100ull
#define NK_AT 1
#ifndef NV_AT
#define NV_AT 3
#endif
#define CHK_D 11
#define FGAP 600
#define FGAP2 200
constexpr int PRE_EARLY = 2, NFIRST = 4;
constexpr int C_WAR = 96;
constexpr int C_NUM = 112;
constexpr int CSTRIDE = 32;
constexpr int SM_KMAX = SM_BAR + 640, SM_DUMMY = SM_BAR + 648, SM_PRE = SM_BAR + 112, SM_SIG = SM_BAR + 256, SM_RDY = SM_BAR + 384;
enum { SIG_KV = 0, SIG_CTX = 2, SIG_Z = 4, SIG_DONE = 8, SIG_WAR = 9, SIG_ATT = 10 };
enum { RDY_KV = 0, RDY_CTX = 2, RDY_WAR = 4, RDY_G = 5, RDY_X = 6, RDY_AUX = 7, RDY_U = 8, RDY_Z = 9 };
enum { PH_PRE = 1, PH_KV = 2, PH_ATT = 4, PH_CONV = 8, PH_OUT = 16, PH_ALL = 31 };

constexpr uint32_t T_CTX = 0, T_KV = 16 * 32 * 32768, T_BYTES = T_KV + 32 * 16 * 65536;
__device__ __align__(1024) uint8_t g_T[T_BYTES];
__device__ __align__(1024) uint8_t g_u[1024 * UCH];
__device__ __align__(1024) float g_gate[2048];
__device__ __align__(1024) float g_kn2[32 * 128];
__device__ __align__(1024) unsigned g_cnt[C_NUM * CSTRIDE];

struct __align__(64) Maps { CUtensorMap c, wk, wv, x, wq, wo, h, z, ctx, k, v; };
struct Params {
  const __nv_bfloat16 *x, *shift, *D, *gw;
  __nv_bfloat16* out;
};

__device__ __forceinline__ void wg_fence() { asm volatile("wgmma.fence.sync.aligned;" ::: "memory"); }
__device__ __forceinline__ void wg_commit() { asm volatile("wgmma.commit_group.sync.aligned;" ::: "memory"); }
template<int N> __device__ __forceinline__ void wg_wait() { asm volatile("wgmma.wait_group.sync.aligned %0;" :: "n"(N) : "memory"); }
__device__ __forceinline__ uint64_t odesc(uint32_t addr, uint32_t lbo, uint32_t sbo, uint32_t swz) {
  uint64_t d = (uint64_t)(addr >> 4) + (((uint64_t)(lbo >> 4) << 16) | ((uint64_t)(sbo >> 4) << 32) | ((uint64_t)swz << 62));
  asm volatile("" : "+l"(d));
  return d;
}
__device__ __forceinline__ void mbar_init(uint32_t bar, int cnt) { asm volatile("mbarrier.init.shared::cta.b64 [%0], %1;" :: "r"(bar), "r"(cnt)); }
__device__ __forceinline__ void mbar_expect(uint32_t bar, uint32_t bytes) { asm volatile("mbarrier.arrive.expect_tx.shared::cta.b64 _, [%0], %1;" :: "r"(bar), "r"(bytes) : "memory"); }
__device__ __forceinline__ void mbar_arrive(uint32_t bar) { asm volatile("mbarrier.arrive.shared::cta.b64 _, [%0];" :: "r"(bar) : "memory"); }
__device__ __forceinline__ void mbar_wait(uint32_t bar, uint32_t parity) {
  asm volatile("{\n.reg .pred p;\nLW:\nmbarrier.try_wait.parity.shared::cta.b64 p, [%0], %1;\n@!p bra LW;\n}\n" :: "r"(bar), "r"(parity) : "memory");
}
__device__ __forceinline__ void mbar_wait_slow(uint32_t bar, uint32_t parity) {
  asm volatile("{\n.reg .pred p;\n.reg .u32 n;\nmov.u32 n, 0;\n"
    "LW:\nmbarrier.test_wait.parity.shared::cta.b64 p, [%0], %1;\n@p bra LD;\n"
    "nanosleep.u32 %2;\nadd.u32 n, n, 1;\nsetp.lt.u32 p, n, 16777216;\n@p bra LW;\ntrap;\nLD:\n}\n" :: "r"(bar), "r"(parity), "n"(SL_BAR) : "memory");
}
__device__ __forceinline__ void mbar_wait_all(uint32_t bar, uint32_t parity) {
  asm volatile("{\n.reg .pred p, q;\nLW:\nmbarrier.try_wait.parity.shared::cta.b64 p, [%0], %1;\nvote.sync.all.pred q, p, 0xffffffff;\n@!q bra.uni LW;\n}\n" :: "r"(bar), "r"(parity) : "memory");
}
__device__ __forceinline__ void cnt_wait(const unsigned* p, unsigned target) {
  asm volatile("{\n.reg .pred p;\n.reg .u32 n, v;\nmov.u32 n, 0;\n"
    "LW:\nld.relaxed.gpu.global.u32 v, [%0];\nsetp.ge.u32 p, v, %1;\n@p bra LD;\n"
    "nanosleep.u32 %2;\nadd.u32 n, n, 1;\nsetp.lt.u32 p, n, 4194304;\n@p bra LW;\ntrap;\nLD:\nfence.acquire.gpu;\nfence.proxy.async.global;\n}\n" :: "l"(p), "r"(target), "n"(SL_CNT) : "memory");
}
__device__ __forceinline__ void cnt_signal(unsigned* p, int lane) {
  __syncwarp();
  if (lane == 0) asm volatile("red.release.gpu.global.add.u32 [%0], 1;" :: "l"(p) : "memory");
}
__device__ __forceinline__ void cnt_publish(unsigned* p, unsigned n, bool fence) {
  if (fence) asm volatile("fence.release.gpu;" ::: "memory");
  asm volatile("red.relaxed.gpu.global.add.u32 [%0], %1;" :: "l"(p), "r"(n) : "memory");
}
__device__ __forceinline__ uint64_t pol_first() { uint64_t p; asm("createpolicy.fractional.L2::evict_first.b64 %0, 1.0;" : "=l"(p)); return p; }
__device__ __forceinline__ void bulk_g2s(uint32_t dst, const void* src, uint32_t bytes, uint32_t bar, bool stream = false) {
  if (stream) asm volatile("cp.async.bulk.shared::cluster.global.mbarrier::complete_tx::bytes.L2::cache_hint [%0], [%1], %2, [%3], %4;" :: "r"(dst), "l"(src), "r"(bytes), "r"(bar), "l"(pol_first()) : "memory");
  else asm volatile("cp.async.bulk.shared::cluster.global.mbarrier::complete_tx::bytes [%0], [%1], %2, [%3];" :: "r"(dst), "l"(src), "r"(bytes), "r"(bar) : "memory");
}
__device__ __forceinline__ void tma2d(uint32_t dst, const CUtensorMap* m, int x, int y, uint32_t bar, bool stream = false) {
  if (stream) asm volatile("cp.async.bulk.tensor.2d.shared::cluster.global.mbarrier::complete_tx::bytes.L2::cache_hint [%0], [%1, {%3, %4}], [%2], %5;" :: "r"(dst), "l"(m), "r"(bar), "r"(x), "r"(y), "l"(pol_first()) : "memory");
  else asm volatile("cp.async.bulk.tensor.2d.shared::cluster.global.mbarrier::complete_tx::bytes [%0], [%1, {%3, %4}], [%2];" :: "r"(dst), "l"(m), "r"(bar), "r"(x), "r"(y) : "memory");
}
__device__ __forceinline__ void tma3d(uint32_t dst, const CUtensorMap* m, int x, int y, int z, uint32_t bar, bool stream = false) {
  if (stream) asm volatile("cp.async.bulk.tensor.3d.shared::cluster.global.mbarrier::complete_tx::bytes.L2::cache_hint [%0], [%1, {%3, %4, %5}], [%2], %6;" :: "r"(dst), "l"(m), "r"(bar), "r"(x), "r"(y), "r"(z), "l"(pol_first()) : "memory");
  else asm volatile("cp.async.bulk.tensor.3d.shared::cluster.global.mbarrier::complete_tx::bytes [%0], [%1, {%3, %4, %5}], [%2];" :: "r"(dst), "l"(m), "r"(bar), "r"(x), "r"(y), "r"(z) : "memory");
}
__device__ __forceinline__ void tma4d(uint32_t dst, const CUtensorMap* m, int x, int y, int z, int w, uint32_t bar, bool stream = false) {
  if (stream) asm volatile("cp.async.bulk.tensor.4d.shared::cluster.global.mbarrier::complete_tx::bytes.L2::cache_hint [%0], [%1, {%3, %4, %5, %6}], [%2], %7;" :: "r"(dst), "l"(m), "r"(bar), "r"(x), "r"(y), "r"(z), "r"(w), "l"(pol_first()) : "memory");
  else asm volatile("cp.async.bulk.tensor.4d.shared::cluster.global.mbarrier::complete_tx::bytes [%0], [%1, {%3, %4, %5, %6}], [%2];" :: "r"(dst), "l"(m), "r"(bar), "r"(x), "r"(y), "r"(z), "r"(w) : "memory");
}
__device__ __forceinline__ void bulk_g2s_mc(uint32_t dst, const void* src, uint32_t bytes, uint32_t bar, bool stream = false) {
  if (stream) asm volatile("cp.async.bulk.shared::cluster.global.mbarrier::complete_tx::bytes.multicast::cluster.L2::cache_hint [%0], [%1], %2, [%3], %4, %5;" :: "r"(dst), "l"(src), "r"(bytes), "r"(bar), "h"((uint16_t)3), "l"(pol_first()) : "memory");
  else asm volatile("cp.async.bulk.shared::cluster.global.mbarrier::complete_tx::bytes.multicast::cluster [%0], [%1], %2, [%3], %4;" :: "r"(dst), "l"(src), "r"(bytes), "r"(bar), "h"((uint16_t)3) : "memory");
}
__device__ __forceinline__ void tma2d_mc(uint32_t dst, const CUtensorMap* m, int x, int y, uint32_t bar, bool stream = false) {
  if (stream) asm volatile("cp.async.bulk.tensor.2d.shared::cluster.global.mbarrier::complete_tx::bytes.multicast::cluster.L2::cache_hint [%0], [%1, {%3, %4}], [%2], %5, %6;" :: "r"(dst), "l"(m), "r"(bar), "r"(x), "r"(y), "h"((uint16_t)3), "l"(pol_first()) : "memory");
  else asm volatile("cp.async.bulk.tensor.2d.shared::cluster.global.mbarrier::complete_tx::bytes.multicast::cluster [%0], [%1, {%3, %4}], [%2], %5;" :: "r"(dst), "l"(m), "r"(bar), "r"(x), "r"(y), "h"((uint16_t)3) : "memory");
}
__device__ __forceinline__ void tma3d_mc(uint32_t dst, const CUtensorMap* m, int x, int y, int z, uint32_t bar, bool stream = false) {
  if (stream) asm volatile("cp.async.bulk.tensor.3d.shared::cluster.global.mbarrier::complete_tx::bytes.multicast::cluster.L2::cache_hint [%0], [%1, {%3, %4, %5}], [%2], %6, %7;" :: "r"(dst), "l"(m), "r"(bar), "r"(x), "r"(y), "r"(z), "h"((uint16_t)3), "l"(pol_first()) : "memory");
  else asm volatile("cp.async.bulk.tensor.3d.shared::cluster.global.mbarrier::complete_tx::bytes.multicast::cluster [%0], [%1, {%3, %4, %5}], [%2], %6;" :: "r"(dst), "l"(m), "r"(bar), "r"(x), "r"(y), "r"(z), "h"((uint16_t)3) : "memory");
}
__device__ __forceinline__ void map_pf(const CUtensorMap* m) { asm volatile("prefetch.tensormap [%0];" :: "l"(m) : "memory"); }
__device__ __forceinline__ bool elect() {
  uint32_t r; asm volatile("{\n.reg .pred p;\nelect.sync _|p, 0xffffffff;\nselp.u32 %0, 1, 0, p;\n}\n" : "=r"(r)); return r != 0;
}
__device__ __forceinline__ void cluster_arrive() { asm volatile("barrier.cluster.arrive;" ::: "memory"); }
__device__ __forceinline__ void cluster_wait() { asm volatile("barrier.cluster.wait;" ::: "memory"); }
__device__ __forceinline__ void bar_sync(int id, int n) { asm volatile("bar.sync %0, %1;" :: "r"(id), "r"(n) : "memory"); }
__device__ __forceinline__ void bar_arrive(int id, int n) { asm volatile("bar.arrive %0, %1;" :: "r"(id), "r"(n) : "memory"); }
__device__ __forceinline__ void fence_async_smem() { asm volatile("fence.proxy.async.shared::cta;" ::: "memory"); }
__device__ __forceinline__ float ex2(float x) { float y; asm("ex2.approx.ftz.f32 %0, %1;" : "=f"(y) : "f"(x)); return y; }
__device__ __forceinline__ float rcp(float x) { float y; asm("rcp.approx.ftz.f32 %0, %1;" : "=f"(y) : "f"(x)); return y; }
__device__ __forceinline__ uint32_t pack_bf16(float lo, float hi) { uint32_t r; asm("cvt.rn.bf16x2.f32 %0, %1, %2;" : "=r"(r) : "f"(hi), "f"(lo)); return r; }
__device__ __forceinline__ uint32_t hmul2(uint32_t a, uint32_t b) { uint32_t r; asm("mul.rn.bf16x2 %0, %1, %2;" : "=r"(r) : "r"(a), "r"(b)); return r; }
__device__ __forceinline__ uint32_t hadd2(uint32_t a, uint32_t b) { uint32_t r; asm("add.rn.bf16x2 %0, %1, %2;" : "=r"(r) : "r"(a), "r"(b)); return r; }
__device__ __forceinline__ uint32_t hfma2(uint32_t a, uint32_t b, uint32_t c) { uint32_t r; asm("fma.rn.bf16x2 %0, %1, %2, %3;" : "=r"(r) : "r"(a), "r"(b), "r"(c)); return r; }
__device__ __forceinline__ float bf_lo(uint32_t a) { return __uint_as_float(a << 16); }
__device__ __forceinline__ float bf_hi(uint32_t a) { return __uint_as_float(a & 0xffff0000u); }
__device__ __forceinline__ uint32_t lds32(uint32_t a) { uint32_t v; asm volatile("ld.shared.u32 %0, [%1];" : "=r"(v) : "r"(a) : "memory"); return v; }
__device__ __forceinline__ float2 lds64f(uint32_t a) { float2 v; asm volatile("ld.shared.v2.f32 {%0,%1}, [%2];" : "=f"(v.x), "=f"(v.y) : "r"(a) : "memory"); return v; }
__device__ __forceinline__ uint4 lds128(uint32_t a) { uint4 v; asm volatile("ld.shared.v4.u32 {%0,%1,%2,%3}, [%4];" : "=r"(v.x), "=r"(v.y), "=r"(v.z), "=r"(v.w) : "r"(a) : "memory"); return v; }
__device__ __forceinline__ void sts64f(uint32_t a, float x, float y) { asm volatile("st.shared.v2.f32 [%0], {%1,%2};" :: "r"(a), "f"(x), "f"(y) : "memory"); }
template<int OFF> __device__ __forceinline__ void sts128o(uint32_t a, uint4 v) { asm volatile("st.shared.v4.u32 [%0+%5], {%1,%2,%3,%4};" :: "r"(a), "r"(v.x), "r"(v.y), "r"(v.z), "r"(v.w), "n"(OFF) : "memory"); }
__device__ __forceinline__ void ldsm4(uint32_t a, uint32_t& r0, uint32_t& r1, uint32_t& r2, uint32_t& r3) {
  asm volatile("ldmatrix.sync.aligned.m8n8.x4.shared.b16 {%0,%1,%2,%3}, [%4];" : "=r"(r0), "=r"(r1), "=r"(r2), "=r"(r3) : "r"(a) : "memory");
}
__device__ __forceinline__ void ldsm4t(uint32_t a, uint32_t& r0, uint32_t& r1, uint32_t& r2, uint32_t& r3) {
  asm volatile("ldmatrix.sync.aligned.m8n8.x4.trans.shared.b16 {%0,%1,%2,%3}, [%4];" : "=r"(r0), "=r"(r1), "=r"(r2), "=r"(r3) : "r"(a) : "memory");
}
__device__ __forceinline__ void stsm4(uint32_t a, uint32_t r0, uint32_t r1, uint32_t r2, uint32_t r3) {
  asm volatile("stmatrix.sync.aligned.m8n8.x4.shared.b16 [%0], {%1,%2,%3,%4};" :: "r"(a), "r"(r0), "r"(r1), "r"(r2), "r"(r3) : "memory");
}
template<int N> __device__ __forceinline__ void fence_regs(float (&d)[N]) {
#pragma unroll
  for (int i = 0; i < N; i++) asm volatile("" : "+f"(d[i]) :: "memory");
}
template<int N> __device__ __forceinline__ void fence_regs(uint32_t (&d)[N]) {
#pragma unroll
  for (int i = 0; i < N; i++) asm volatile("" : "+r"(d[i]) :: "memory");
}
__device__ __forceinline__ void sched_fence(float x, uint32_t dummy) {
  asm volatile("{\n.reg .pred p;\nsetp.eq.u32 p, %0, 0x7fc12345;\n@p st.shared.u32 [%1], %0;\n}\n" :: "r"(__float_as_uint(x)), "r"(dummy) : "memory");
}
#define PTRACE 0
#define TS(role, i)
#define TSA(i)
#define TSS(i)
#define TSK(i)
#define TSO(i)

#define SHADOW if (gridDim.y == 1)

struct Prod {
  uint32_t base, mask; int lane, nt;
  __device__ __forceinline__ uint32_t full(int u) const { return base + SM_BAR + 8 * u; }
  __device__ __forceinline__ uint32_t addr(int u) const { return base + u * UNIT; }
  __device__ __forceinline__ void acquire(int u, int n) {
    const int v = u + min(lane, n - 1);
    mbar_wait_all(base + SM_BAR + 128 + 8 * v, mask >> v);
    mask ^= ((1u << n) - 1) << u;
  }
  __device__ __forceinline__ void acquire_slow(int u, int n) {
    for (int i = 0; i < n; i++) mbar_wait_slow(base + SM_BAR + 128 + 8 * (u + i), mask >> (u + i));
    mask ^= ((1u << n) - 1) << u;
  }
};
struct Cons {
  uint32_t base, rel, mask; int lane, warp, wg, lr, nt;
  __device__ __forceinline__ uint32_t addr(int u) const { return base + u * UNIT; }
  __device__ __forceinline__ static uint32_t daddr(int u) { return SMEM_BASE + u * UNIT; }
  __device__ __forceinline__ void wait(int u) { mbar_wait(base + SM_BAR + 8 * u, mask >> u); mask ^= 1u << u; }
  __device__ __forceinline__ void skip(int u) { mask ^= 1u << u; }
  __device__ __forceinline__ void release(int u, int n) {
    asm volatile("{\n.reg .pred p;\nsetp.lt.s32 p, %1, %2;\n@p mbarrier.arrive.shared::cluster.b64 _, [%0];\n}\n" :: "r"(rel + 8 * u), "r"(lr), "r"(n) : "memory");
  }
  __device__ __forceinline__ void release2(int u) {
    asm volatile("{\n.reg .pred p;\nsetp.eq.s32 p, %1, 0;\n@p mbarrier.arrive.shared::cluster.b64 _, [%0], 2;\n}\n" :: "r"(rel + 8 * u), "r"(lr) : "memory");
  }
  __device__ __forceinline__ void signal(int i) {
    __syncwarp();
    asm volatile("{\n.reg .pred p;\nsetp.eq.s32 p, %1, 0;\n@p mbarrier.arrive.shared::cta.b64 _, [%0];\n}\n" :: "r"(base + SM_SIG + 8 * i), "r"(lane) : "memory");
  }
  __device__ __forceinline__ void turn() { asm volatile("{\n.reg .pred p;\nsetp.eq.s32 p, %0, 0;\n@p bar.sync 1, 256;\n@!p bar.sync 2, 256;\n}\n" :: "r"(wg) : "memory"); }
  __device__ __forceinline__ void pass() { asm volatile("{\n.reg .pred p;\nsetp.eq.s32 p, %0, 0;\n@p bar.arrive 2, 256;\n@!p bar.arrive 1, 256;\n}\n" :: "r"(wg) : "memory"); }
  __device__ __forceinline__ void sync() { asm volatile("{\n.reg .pred p;\nsetp.eq.s32 p, %0, 0;\n@p bar.sync 3, 128;\n@!p bar.sync 4, 128;\n}\n" :: "r"(wg) : "memory"); }
};
__device__ __forceinline__ int gemm_unit(int ks) { return 3 * (ks & 3); }
template<int MASK> __device__ __forceinline__ int kv_slot(int h) { return MASK == PH_ALL ? h & 15 : h; }
__device__ __forceinline__ int out_mb(int cta) { return cta >> 3; }
__device__ __forceinline__ int out_nb(int cta) { return cta & 7; }
template<int MASK> constexpr int CV_REG = MASK == PH_ALL ? CONV_REG : 6;
template<int MASK> constexpr int CV_EXTRA = (1024 - NREG * CV_REG<MASK>) / (NCTA - NREG);
template<int MASK> __device__ __forceinline__ int conv_channel(int cta, int i) {
  return cta < NREG ? CV_EXTRA<MASK> * (NCTA - NREG) + cta * CV_REG<MASK> + i : (i >> 1) * 8 + (cta - NREG) * 2 + (i & 1);
}

template<int OFF, int N> __device__ __forceinline__ void pack_chunk(const float (&a)[N], float sc0, float sc1, uint4& v0, uint4& v1) {
  v0.x = pack_bf16(a[OFF + 0] * sc0, a[OFF + 1] * sc0); v0.y = pack_bf16(a[OFF + 4] * sc0, a[OFF + 5] * sc0);
  v0.z = pack_bf16(a[OFF + 8] * sc0, a[OFF + 9] * sc0); v0.w = pack_bf16(a[OFF + 12] * sc0, a[OFF + 13] * sc0);
  v1.x = pack_bf16(a[OFF + 2] * sc1, a[OFF + 3] * sc1); v1.y = pack_bf16(a[OFF + 6] * sc1, a[OFF + 7] * sc1);
  v1.z = pack_bf16(a[OFF + 10] * sc1, a[OFF + 11] * sc1); v1.w = pack_bf16(a[OFF + 14] * sc1, a[OFF + 15] * sc1);
}
template<int OFF, int N> __device__ __forceinline__ void pack_chunk(const float (&a)[N], uint4& v0, uint4& v1) {
  v0.x = pack_bf16(a[OFF + 0], a[OFF + 1]); v0.y = pack_bf16(a[OFF + 4], a[OFF + 5]);
  v0.z = pack_bf16(a[OFF + 8], a[OFF + 9]); v0.w = pack_bf16(a[OFF + 12], a[OFF + 13]);
  v1.x = pack_bf16(a[OFF + 2], a[OFF + 3]); v1.y = pack_bf16(a[OFF + 6], a[OFF + 7]);
  v1.z = pack_bf16(a[OFF + 10], a[OFF + 11]); v1.w = pack_bf16(a[OFF + 14], a[OFF + 15]);
}
__device__ __forceinline__ void sq_acc(const uint4& v, uint32_t& a) { a = hfma2(v.x, v.x, a); a = hfma2(v.y, v.y, a); a = hfma2(v.z, v.z, a); a = hfma2(v.w, v.w, a); }
__device__ __forceinline__ float norm2_max(uint32_t a0, uint32_t a1) {
  float n0 = bf_lo(a0) + bf_hi(a0), n1 = bf_lo(a1) + bf_hi(a1);
  n0 += __shfl_xor_sync(~0u, n0, 1); n1 += __shfl_xor_sync(~0u, n1, 1);
  n0 += __shfl_xor_sync(~0u, n0, 2); n1 += __shfl_xor_sync(~0u, n1, 2);
  return __uint_as_float(__reduce_max_sync(~0u, max(__float_as_uint(n0) & 0x7fffffffu, __float_as_uint(n1) & 0x7fffffffu)));
}

struct Pend { uint4 lo[8], hi[8]; };
__device__ __forceinline__ uint32_t ctx_off(const Cons& c, int h, int qb, int rowhalf) { return T_CTX + (qb * 32 + h) * 32768 + (rowhalf * 4 + c.warp) * 4096; }
__device__ __forceinline__ uint32_t kv_off(const Cons& c, int blk) { return T_KV + blk * 65536 + (c.wg * 4 + c.warp) * 4096; }
__device__ __forceinline__ void pin(uint4 (&v)[8]) {
#pragma unroll
  for (int i = 0; i < 8; i++) asm volatile("" : "+r"(v[i].x), "+r"(v[i].y), "+r"(v[i].z), "+r"(v[i].w) :: "memory");
}
__device__ __forceinline__ void pack_o(const float (&o)[64], float i0, float i1, uint4 (&v)[8]) {
  pack_chunk<0>(o, i0, i1, v[0], v[1]); pack_chunk<16>(o, i0, i1, v[2], v[3]);
  pack_chunk<32>(o, i0, i1, v[4], v[5]); pack_chunk<48>(o, i0, i1, v[6], v[7]);
  pin(v);
}
__device__ __forceinline__ uint32_t atom_off(int lane) { return (lane >> 2) * 64 + (((lane ^ (lane >> 3)) & 3) << 4); }
template<int J0, int J1> __device__ __forceinline__ void tile_store(const uint4 (&v)[8], uint32_t dst, int lane) {
  uint8_t* d = g_T + (dst + atom_off(lane));
#pragma unroll
  for (int j = J0; j < J1; j++) { *(uint4*)(d + j * 512) = v[2 * j]; *(uint4*)(d + j * 512 + 2048) = v[2 * j + 1]; }
}
template<int I0, int I1> __device__ __forceinline__ void tile_store_if(bool on, const uint4 (&v)[8], const uint8_t* dst) {
  if constexpr (I0 < I1) {
    asm volatile("{\n.reg .pred p;\nsetp.ne.b32 p, %5, 0;\n@p st.v4.u32 [%0+%6], {%1,%2,%3,%4};\n}\n"
      :: "l"(dst), "r"(v[I0].x), "r"(v[I0].y), "r"(v[I0].z), "r"(v[I0].w), "r"((int)on), "n"((I0 >> 1) * 512 + (I0 & 1) * 2048) : "memory");
    tile_store_if<I0 + 1, I1>(on, v, dst);
  }
}
__device__ __forceinline__ float tile_norm2(const uint4 (&v)[8]) {
  uint32_t n0 = 0, n1 = 0, n2 = 0, n3 = 0;
#pragma unroll
  for (int j = 0; j < 2; j++) { sq_acc(v[2 * j], n0); sq_acc(v[2 * j + 1], n1); sq_acc(v[2 * j + 4], n2); sq_acc(v[2 * j + 5], n3); }
  return norm2_max(hadd2(n0, n2), hadd2(n1, n3));
}
template<uint64_t SCHED, bool FIRST> __device__ __forceinline__ void out_piece(Cons& c, Pend& w, uint32_t dst, int blk, float& kn, int ks, bool both) {
  uint8_t* d = g_T + (dst + atom_off(c.lane));
#pragma unroll
  for (int i = 0; i < 16; i++) {
    const int at = (SCHED >> (4 * i)) & 15;
    if (FIRST ? at == 0 : (at > 0 && ks == at && (i < 8 || both))) *(uint4*)(d + (i >> 3) * 32768 + ((i >> 1) & 3) * 512 + (i & 1) * 2048) = i < 8 ? w.lo[i & 7] : w.hi[i & 7];
  }
  if (FIRST || !both) return;
  if (ks == NK_AT) kn = tile_norm2(w.lo);
  if (ks == NV_AT) {
    const float vn = tile_norm2(w.hi);
    if (c.lane == 0) g_kn2[blk * 8 + c.wg * 4 + c.warp] = (vn <= 1.0e20f && vn >= 1.0e-20f) ? kn : __uint_as_float(0x7f800000u);
  }
}
template<bool FIRST> __device__ __forceinline__ void kv_issue(Cons& c, float (&acc)[128], int u) {
  const uint64_t da = odesc(c.daddr(u) + c.wg * 8192, 16, 1024, 1), db = odesc(c.daddr(u + 1), 8192, 1024, 1);
  TSK(c.nt + 1);
  c.turn();
  TSK(c.nt + 2);
  wg_fence();
#pragma unroll
  for (int kk = 0; kk < 4; kk++) wgmma_ss_n256<1>(acc, da + kk * 2, db + kk * 128, !(FIRST && kk == 0));
  wg_commit();
  c.pass();
  TSK(c.nt + 3); c.nt += 4;
}
template<bool NEXT> __device__ __forceinline__ void cons_kv(Cons& c, int h, int blk, int g, Pend& w, bool pend_o) {
#pragma unroll 1
  for (int tile = 0; tile < 2; tile++) {
    float acc[128];
    if (tile == 0) c.wait(0);
    if (tile == 0 && h < 16) TS(c.wg, 16);
    kv_issue<true>(c, acc, 0);
    c.release(9, tile == 1 ? 3 : 0);
    if (tile == 1 && pend_o) mbar_wait(c.base + SM_RDY + 8 * RDY_WAR, 0);
    const uint32_t dst = tile ? kv_off(c, blk) : ctx_off(c, h - 16, g, 1 - c.wg);
    float kn = 0.f;
    if (tile == 1 || pend_o) out_piece<SCH_KV, true>(c, w, dst, blk, kn, 0, false);
#pragma unroll 1
    for (int ks = 1; ks < 8; ks++) {
      const int u = gemm_unit(ks);
      c.wait(u);
      TSK(c.nt);
      wg_wait<0>();
      c.release(gemm_unit(ks - 1), 3);
      kv_issue<false>(c, acc, u);
      if (tile == 1 || pend_o) { out_piece<SCH_KV, false>(c, w, dst, blk, kn, ks, tile); if (ks == ((SCH_KV >> 28) & 15) && tile == 0) c.signal(SIG_CTX); }
    }
    if (NEXT || tile == 0) c.wait(0);
    wg_wait<0>(); fence_regs(acc);
    TSK(c.nt);
    if (!NEXT) c.release(9, tile == 1 ? 3 : 0);
    pack_chunk<0>(acc, w.lo[0], w.lo[1]);  pack_chunk<16>(acc, w.lo[2], w.lo[3]); pack_chunk<32>(acc, w.lo[4], w.lo[5]); pack_chunk<48>(acc, w.lo[6], w.lo[7]);
    pack_chunk<64>(acc, w.hi[0], w.hi[1]); pack_chunk<80>(acc, w.hi[2], w.hi[3]); pack_chunk<96>(acc, w.hi[4], w.hi[5]); pack_chunk<112>(acc, w.hi[6], w.hi[7]);
    pin(w.lo); pin(w.hi);
  }
}
template<bool FIRST> __device__ __forceinline__ void q_issue(Cons& c, float (&a)[64], float (&b)[64], int u) {
  const uint64_t da = odesc(c.daddr(u) + c.wg * 8192, 16, 1024, 1), db = odesc(c.daddr(u + 2), 8192, 1024, 1);
  const uint64_t da2 = odesc(c.daddr(u + 1) + (1 - c.wg) * 8192, 16, 1024, 1);
  TSK(c.nt + 1);
  c.turn();
  TSK(c.nt + 2);
  wg_fence();
#pragma unroll
  for (int kk = 0; kk < 4; kk++) wgmma_ss_n128<1>(a, da + kk * 2, db + kk * 128, !(FIRST && kk == 0));
#pragma unroll
  for (int kk = 0; kk < 4; kk++) wgmma_ss_n128<1>(b, da2 + kk * 2, db + kk * 128, !(FIRST && kk == 0));
  wg_commit();
  c.pass();
  TSK(c.nt + 3); c.nt += 4;
}
__device__ __forceinline__ void q_step(Cons& c, float (&d)[64], int ua, int ub, int rowhalf) {
  const uint64_t da = odesc(c.daddr(ua) + rowhalf * 8192, 16, 1024, 1), db = odesc(c.daddr(ub), 8192, 1024, 1);
#pragma unroll
  for (int kk = 0; kk < 4; kk++) wgmma_ss_n128<1>(d, da + kk * 2, db + kk * 128, 1);
}
template<bool PEND_KV> __device__ __forceinline__ void cons_q(Cons& c, int h, int blk, Pend& w, float (&b)[64]) {
  float a[64], kn = 0.f;
  if (!PEND_KV) c.wait(0);
  q_issue<true>(c, a, b, 0);
  if (PEND_KV) { c.release(9, 3); out_piece<SCH_Q, true>(c, w, kv_off(c, blk), blk, kn, 0, true); }
#pragma unroll 1
  for (int ks = 1; ks < 14; ks++) {
    const int u = gemm_unit(ks);
    c.wait(u);
    TSK(c.nt);
    wg_wait<0>();
    c.release(gemm_unit(ks - 1), 3);
    q_issue<false>(c, a, b, u);
    if (PEND_KV && ks <= (int)(SCH_Q >> 60)) { out_piece<SCH_Q, false>(c, w, kv_off(c, blk), blk, kn, ks, true); if (ks == (int)(SCH_Q >> 60)) c.signal(SIG_KV + (h >> 4)); }
  }
  c.wait(6); c.wait(9);
  wg_wait<0>();
  c.release(3, 3);
  c.turn();
  TSS(0);
  wg_fence();
  q_step(c, a, 6, 8, c.wg); q_step(c, a, 9, 11, c.wg); wg_commit();
  q_step(c, b, 7, 8, 1 - c.wg); wg_commit();
  c.pass();
  TSS(1);
  c.wait(0);
  const uint32_t q0 = c.addr(0) + (c.wg * 4 + c.warp) * 4096 + atom_off(c.lane);
  wg_wait<1>(); fence_regs(a);
  TSS(2);
  pack_o(a, QSCALE, QSCALE, w.lo);
  sts128o<0>(q0, w.lo[0]);    sts128o<2048>(q0, w.lo[1]); sts128o<512>(q0, w.lo[2]);  sts128o<2560>(q0, w.lo[3]);
  wg_wait<0>();
  c.release(6, 4);
  sts128o<1024>(q0, w.lo[4]); sts128o<3072>(q0, w.lo[5]); sts128o<1536>(q0, w.lo[6]); sts128o<3584>(q0, w.lo[7]);
  TSS(3);
  c.wait(12);
  fence_async_smem();
  TSS(4);
}

__device__ __forceinline__ void issue_qk(float (&s)[64], uint64_t da, uint64_t db) {
#pragma unroll
  for (int kk = 0; kk < 8; kk++) wgmma_ss_n128<0>(s, da + (kk >> 1) * 32 + (kk & 1) * 2, db + (kk >> 1) * 32 + (kk & 1) * 2, kk > 0);
  wg_commit();
}
template<int A, int B> __device__ __forceinline__ void exp_rng(float (&s)[64]) {
#pragma unroll
  for (int i = 4 * A; i < 4 * B; i++) s[i] = ex2(s[i]);
}
template<int A, int B> __device__ __forceinline__ void sum_rng(const float (&s)[64], float (&l)[4]) {
#pragma unroll
  for (int i = A; i < B; i++) { l[0] += s[4 * i]; l[1] += s[4 * i + 1]; l[2] += s[4 * i + 2]; l[3] += s[4 * i + 3]; }
}
template<int A, int B> __device__ __forceinline__ void cvt_p(const float (&s)[64], uint32_t (&p)[32]) {
#pragma unroll
  for (int i = 2 * A; i < 2 * B; i++) p[i] = pack_bf16(s[2 * i], s[2 * i + 1]);
}
template<int K0> __device__ __forceinline__ void mask_half(float (&s)[64], int warp, int lane) {
  const int l0 = warp + (2 * (lane & 3) <= (lane >> 2)), l1 = warp + (2 * (lane & 3) < (lane >> 2));
#pragma unroll
  for (int k = 0; k < 4; k++) {
    float* t = s + 8 * (K0 + k);
    if (k >= l0) { t[0] = -INFINITY; t[6] = -INFINITY; }
    if (k >= l1) { t[1] = -INFINITY; t[7] = -INFINITY; }
    if (k > warp) { t[2] = -INFINITY; t[3] = -INFINITY; }
    if (k >= warp) { t[4] = -INFINITY; t[5] = -INFINITY; }
  }
}
__device__ __forceinline__ void row_inv(float& l0, float& l1) {
  l0 += __shfl_xor_sync(~0u, l0, 1); l1 += __shfl_xor_sync(~0u, l1, 1);
  l0 += __shfl_xor_sync(~0u, l0, 2); l1 += __shfl_xor_sync(~0u, l1, 2);
  l0 = rcp(l0); l1 = rcp(l1);
}
__device__ __forceinline__ void softmax_safe(float (&s)[64], bool upper_only, float& m0, float& m1, float& sc0, float& sc1) {
  float a0 = m0, a1 = m1;
#pragma unroll
  for (int i = 0; i < 8; i++) { a0 = fmaxf(a0, fmaxf(s[4 * i], s[4 * i + 1])); a1 = fmaxf(a1, fmaxf(s[4 * i + 2], s[4 * i + 3])); }
  if (upper_only) { a0 = m0; a1 = m1; }
#pragma unroll
  for (int i = 8; i < 16; i++) { a0 = fmaxf(a0, fmaxf(s[4 * i], s[4 * i + 1])); a1 = fmaxf(a1, fmaxf(s[4 * i + 2], s[4 * i + 3])); }
  a0 = fmaxf(a0, __shfl_xor_sync(~0u, a0, 1)); a1 = fmaxf(a1, __shfl_xor_sync(~0u, a1, 1));
  a0 = fmaxf(a0, __shfl_xor_sync(~0u, a0, 2)); a1 = fmaxf(a1, __shfl_xor_sync(~0u, a1, 2));
  sc0 = ex2(m0 - a0); sc1 = ex2(m1 - a1);
  m0 = a0; m1 = a1;
#pragma unroll
  for (int i = 0; i < 16; i++) { s[4 * i] -= a0; s[4 * i + 1] -= a0; s[4 * i + 2] -= a1; s[4 * i + 3] -= a1; }
}
struct Att {
  float s[64], o[64], l[4], i0, i1, t0, t1; uint32_t p[32];
  float kn; uint32_t qaddr; const uint8_t* dst;
};
__device__ __forceinline__ int att_fast(uint4 (&q)[8], float kn) {
#pragma unroll
  for (int i = 0; i < 8; i++) q[i].x = hmul2(q[i].x, q[i].x);
#pragma unroll
  for (int i = 0; i < 8; i++) q[i].x = hfma2(q[i].w, q[i].w, hfma2(q[i].z, q[i].z, hfma2(q[i].y, q[i].y, q[i].x)));
#pragma unroll
  for (int i = 0; i < 4; i++) q[i].x = hadd2(q[i].x, q[i + 4].x);
  const uint32_t a0 = hadd2(q[0].x, q[2].x), a1 = hadd2(q[1].x, q[3].x);
  return __shfl_sync(~0u, __all_sync(~0u, ((bf_lo(a0) + bf_hi(a0)) * kn <= 0.25f * BOUND2) & ((bf_lo(a1) + bf_hi(a1)) * kn <= 0.25f * BOUND2)), 0);
}
__device__ __forceinline__ int att_first(Cons& c, Att& a, int h, Pend& w) {
  a.kn = __uint_as_float(lds32(c.base + SM_KMAX + 4 * (h >> 4)));
  a.qaddr = c.daddr(0) + c.wg * 16384;
  c.turn();
  TSS(5);
  wg_fence();
  issue_qk(a.s, odesc(a.qaddr, 16, 2048, 2), odesc(c.daddr(12), 16, 2048, 2));
  int fast = 0;
  SHADOW fast = att_fast(w.lo, a.kn);
  wg_fence();
  TSS(6);
  q_step(c, a.o, 10, 11, 1 - c.wg); wg_commit();
  if (c.wg) c.wait(6); else c.skip(6);
  c.pass();
  TSS(7);
#pragma unroll
  for (int i = 0; i < 8; i++) { a.p[4 * i] = w.lo[i].x; a.p[4 * i + 1] = w.lo[i].y; a.p[4 * i + 2] = w.lo[i].z; a.p[4 * i + 3] = w.lo[i].w; }
  a.l[0] = a.l[1] = a.l[2] = a.l[3] = 0.f; a.i0 = a.i1 = a.t0 = a.t1 = 0.25f / QSCALE;
  a.dst = (const uint8_t*)__cvta_shared_to_generic(c.addr(2) + (c.wg * 4 + c.warp) * 4096 + atom_off(c.lane));
  wg_wait<1>(); fence_regs(a.s);
  c.signal(SIG_ATT + (h >> 4));
  if (c.wg) { wg_wait<0>(); c.release(10, 2); }
  return fast;
}
__device__ __forceinline__ void att_last(Cons& c, Att& a, Pend& w, int h, int g, bool drain) {
  const int uv = 6;
  if (drain) pack_o(a.o, rcp(a.i0), rcp(a.i1), w.hi);
  TSS(8);
  c.turn();
  TSS(9);
  fence_regs(a.o); fence_regs(a.p);
  wgmma_pv_sel(a.o, a.p, odesc(c.daddr(uv), 512, 2048, 2), !(drain && c.wg == 1), !drain, c.wg);
  a.i0 = a.l[0] + a.l[1]; a.i1 = a.l[2] + a.l[3];
  SHADOW row_inv(a.i0, a.i1);
  sched_fence(a.i0 + a.i1, c.base + SM_DUMMY);
  tile_store_if<0, 4>(drain, w.hi, a.dst);
  wg_wait<0>(); fence_regs(a.o); fence_regs(a.p);
  c.release(uv, 2);
  TSS(10); if (h < 16) TSK(0);
  tile_store_if<4, 8>(drain, w.hi, a.dst);
  pack_o(a.o, a.i0, a.i1, w.lo);
  TSS(11);
}
__device__ __forceinline__ void cons_att(Cons& c, Att& a, int h, int g, Pend& w) {
  int fast = att_first(c, a, h, w), fast2 = 0;
  float m0 = -INFINITY, m1 = -INFINITY, sc0 = 0.f, sc1 = 0.f;
  int uk = 10, ur = 10;
  bool fresh = false;
#pragma unroll 1
  for (int d = g - 15;;) {
    const bool lo = d == c.wg;
    TSS(16 + 6 * (d - g + 15));
    if ((unsigned)d < 2 || !fast) {
      if ((unsigned)d < 2) mask_half<4>(a.s, c.warp, c.lane);
      if (!fast) {
        if (d == 1) m0 = m1 = -INFINITY;
        softmax_safe(a.s, lo, m0, m1, sc0, sc1);
        a.l[0] *= sc0; a.l[1] *= sc0; a.l[2] *= sc1; a.l[3] *= sc1;
      }
    }
    exp_rng<8, 16>(a.s); sum_rng<8, 16>(a.s, a.l);
#pragma unroll
    for (int i = 4 * ATT_SPLIT; i < 32; i++) asm("{\n.reg .pred p;\nsetp.ne.s32 p, %1, %2;\n@p ex2.approx.ftz.f32 %0, %0;\n}\n" : "+f"(a.s[i]) : "r"(d), "r"(c.wg));
    sched_fence(((a.l[0] + a.l[1]) + (a.l[2] + a.l[3])) + a.s[4 * ATT_SPLIT + 3], c.base + SM_DUMMY);
    wg_wait<0>(); fence_regs(a.o); fence_regs(a.p);
    c.release(ur, c.wg && d == g - 15 ? 0 : 2);
    TSS(17 + 6 * (d - g + 15));
    a.i0 += a.t0; a.i1 += a.t1;
    a.t0 = __shfl_xor_sync(~0u, a.i0, 2); a.t1 = __shfl_xor_sync(~0u, a.i1, 2);
    tile_store_if<0, 4>(fresh, w.hi, a.dst);
    uk ^= 12; ur = 14 - uk;
    if (d == 0) a.qaddr += 32768;
    const uint64_t dq = odesc(a.qaddr, 16, 2048, 2), dk = odesc(c.daddr(uk) - (d + 1 == c.wg ? 16384 : 0), 16, 2048, 2), dv = odesc(c.daddr(ur), 512, 2048, 2);
    if (!lo) { exp_rng<0, ATT_SPLIT>(a.s); sum_rng<0, 8>(a.s, a.l); cvt_p<0, 16>(a.s, a.p); }
    else if (gridDim.y == 1) cvt_p<8, 16>(a.s, a.p);
    tile_store_if<4, 8>(fresh, w.hi, a.dst);
    a.i0 += a.t0; a.i1 += a.t1;
    if (!fast || d == g + 1) {
      if (!fast && d != 1 && d != g - 15) {
#pragma unroll
        for (int i = 0; i < 16; i++) { a.o[4 * i] *= sc0; a.o[4 * i + 1] *= sc0; a.o[4 * i + 2] *= sc1; a.o[4 * i + 3] *= sc1; }
      }
      if (d == g + 1) break;
    }
    d++;
    fresh = d == 2 || d == g - 14;
    TSS(12 + 6 * (d - g + 15));
    c.turn();
    TSS(13 + 6 * (d - g + 15));
    fence_regs(a.o); fence_regs(a.p);
    wg_fence();
    issue_qk(a.s, dq, dk);
    TSS(14 + 6 * (d - g + 15));
    c.wait(c.wg ? uk ^ 12 : ur); c.skip(c.wg ? ur : uk ^ 12);
    if (fresh || d == 1 || (unsigned)(d - g + CHK_D) < 2) {
      if (fresh) pack_o(a.o, rcp(a.i0), rcp(a.i1), w.hi);
      else if (d == 1) {
        a.i0 = a.l[0] + a.l[1]; a.i1 = a.l[2] + a.l[3];
        a.t0 = __shfl_xor_sync(~0u, a.i0, 1); a.t1 = __shfl_xor_sync(~0u, a.i1, 1);
        a.l[0] = a.l[1] = a.l[2] = a.l[3] = 0.f;
        uint32_t off = ctx_off(c, h, 15 - g, c.wg);
        asm volatile("" : "+r"(off));
        a.dst = g_T + (off + ((uint32_t)(uint64_t)a.dst & 511));
        fast = fast2;
      } else if (d == g - CHK_D) fence_async_smem();
      else fast2 = att_fast(w.hi, a.kn);
    }
    TSS(15 + 6 * (d - g + 15));
    wgmma_pv_sel(a.o, a.p, dv, !lo, !fresh, c.wg);
    wg_wait<1>(); fence_regs(a.s);
    c.release(uk, 2);
    c.release(d == 0 ? 0 : 2, (d == 0 || d == g + 1) ? 2 : 0);
  }
  att_last(c, a, w, h, g, g == 0);
}

constexpr int CV_H = 1024, CV_U = 5120, CV_D = CV_U + 4128, CV_ROW = 1056;
template<int OFF> __device__ __forceinline__ uint32_t lds32o(uint32_t a) { uint32_t v; asm volatile("ld.shared.u32 %0, [%1+%2];" : "=r"(v) : "r"(a), "n"(OFF) : "memory"); return v; }
template<int G, int G1 = 16> __device__ __forceinline__ void conv_lda(uint32_t (&a)[64], uint32_t p) {
  a[4 * G + 0] = lds32o<-256 * G>(p);
  a[4 * G + 1] = lds32o<-256 * G - 128>(p);
  a[4 * G + 2] = lds32o<-256 * G + 16>(p);
  a[4 * G + 3] = lds32o<-256 * G - 112>(p);
  if constexpr (G + 1 < G1) conv_lda<G + 1, G1>(a, p);
}
struct CvAcc { float lo[16], hi[16]; };
__device__ __forceinline__ void fence_regs(CvAcc& d) { fence_regs(d.lo); fence_regs(d.hi); }
template<int R, int H> __device__ __forceinline__ void conv_mma_h(float (&d)[16], const uint32_t (&a)[64], uint64_t db) {
#pragma unroll
  for (int G = 0; G < 4 * R + 2 * H + 2; G++) wgmma_rs_n32<0>(d, a[4 * G], a[4 * G + 1], a[4 * G + 2], a[4 * G + 3], db + 64 * R + 32 * H - 16 * G, G > 0);
}
template<int T, int G0, int G1> __device__ __forceinline__ void conv_part(float (&d)[16], const uint32_t (&a)[64], uint64_t db) {
#pragma unroll
  for (int G = G0; G < G1; G++) wgmma_rs_n32<0>(d, a[4 * G], a[4 * G + 1], a[4 * G + 2], a[4 * G + 3], db + 32 * T - 16 * G, G > 0);
}
template<int R> __device__ __forceinline__ void conv_mma(CvAcc& d, const uint32_t (&a)[64], uint64_t db) { conv_mma_h<R, 0>(d.lo, a, db); conv_mma_h<R, 1>(d.hi, a, db); }
template<int C0> __device__ __forceinline__ void conv_st_h(const float (&d)[16], uint32_t wq, float& c0, float& c1) {
#pragma unroll
  for (int n = 0; n < 4; n++) { sts64f(wq + (C0 + n * 8) * 4, d[4 * n] + c0, d[4 * n + 1] + c1); c0 = d[4 * n + 2]; c1 = d[4 * n + 3]; }
}
template<int R> __device__ __forceinline__ void conv_st(const CvAcc& d, uint32_t wq, float& c0, float& c1) { conv_st_h<64 * R>(d.lo, wq, c0, c1); conv_st_h<64 * R + 32>(d.hi, wq, c0, c1); }
struct ConvTail { float t[64]; uint4 ua, uc; uint32_t D2; };
__device__ __forceinline__ void conv_emit(ConvTail& e, int ch, int tid) {
  fence_regs(e.t);
  float y[16];
#pragma unroll
  for (int i = 0; i < 16; i++) y[i] = (e.t[i] + e.t[16 + i]) + (e.t[32 + i] + e.t[48 + i]);
  uint4 z0, z1;
  z0.x = hadd2(pack_bf16(y[0], y[2]), hmul2(__byte_perm(e.ua.w, 0, 0x1032), e.D2));
  z0.y = hadd2(pack_bf16(y[4], y[6]), hmul2(__byte_perm(e.ua.z, 0, 0x1032), e.D2));
  z0.z = hadd2(pack_bf16(y[8], y[10]), hmul2(__byte_perm(e.ua.y, 0, 0x1032), e.D2));
  z0.w = hadd2(pack_bf16(y[12], y[14]), hmul2(__byte_perm(e.ua.x, 0, 0x1032), e.D2));
  z1.x = hadd2(pack_bf16(y[1], y[3]), hmul2(__byte_perm(e.uc.w, 0, 0x1032), e.D2));
  z1.y = hadd2(pack_bf16(y[5], y[7]), hmul2(__byte_perm(e.uc.z, 0, 0x1032), e.D2));
  z1.z = hadd2(pack_bf16(y[9], y[11]), hmul2(__byte_perm(e.uc.y, 0, 0x1032), e.D2));
  z1.w = hadd2(pack_bf16(y[13], y[15]), hmul2(__byte_perm(e.uc.x, 0, 0x1032), e.D2));
  uint4* zp = (uint4*)(g_u + (uint32_t)(ch * UCH + tid * 32));
  zp[0] = z0; zp[1] = z1;
}
template<int MASK> __device__ __forceinline__ void cons_conv(Cons& c, int cta, int nch) {
  const int r = c.lane >> 2, q = c.lane & 3, tid = c.warp * 32 + c.lane;
  const uint32_t part = c.addr(4) - 2048 + (1 - c.wg) * (32 * CV_ROW) + 32;
  const uint32_t aoff = CV_U + ((r & 1) ? 0 : UPITCH) + 4 * (((2039 - r) >> 1) + q - 8 * c.warp);
  const uint32_t wq = part + (c.warp * 8 + r) * CV_ROW + q * 8, rq = part + tid * 8;
  uint32_t a[64];
  ConvTail e = {};
  c.wait(c.wg); c.skip(c.wg ^ 1);
  conv_lda<0>(a, c.addr(c.wg) + aoff);
  c.wait(4);
  sts64f(part + (tid >> 2) * CV_ROW - 32 + q * 8, 0.f, 0.f);
#pragma unroll 1
  for (int i = 0; i < nch / 2; i++) {
    const int u = 2 * (i & 1) + c.wg;
    CvAcc d0, d1, d2, d3;
    float c0 = 0.f, c1 = 0.f;
    const uint64_t db = odesc(c.daddr(u) + CV_H - 16, 16, 128, 0);
    c.turn();
    fence_regs(a);
    wg_fence();
    conv_mma<0>(d0, a, db); conv_mma<1>(d1, a, db); wg_commit();
    if (i > 0) {
      conv_emit(e, conv_channel<MASK>(cta, 2 * i - 2 + c.wg), tid);
      if ((i & 15) == 0) c.signal(SIG_Z + (i >> 4) - 1);
    }
    wg_fence();
    conv_mma_h<2, 0>(d2.lo, a, db); wg_commit();
    wg_wait<1>(); fence_regs(d0); fence_regs(d1);
    conv_st_h<0>(d0.lo, wq, c0, c1);
    wg_fence();
    conv_mma_h<2, 1>(d2.hi, a, db); wg_commit();
    conv_st_h<32>(d0.hi, wq, c0, c1);
    conv_mma_h<3, 0>(d3.lo, a, db);
    conv_st_h<64>(d1.lo, wq, c0, c1);
    conv_mma_h<3, 1>(d3.hi, a, db); wg_commit();
    c.pass();
    const int un = i + 1 < nch / 2 ? u ^ 2 : u;
    if (un != u) { c.wait(un); c.skip(un ^ 1); }
    wg_wait<1>(); fence_regs(d2);
    conv_st_h<96>(d1.hi, wq, c0, c1);
    conv_st<2>(d2, wq, c0, c1);
    {
      const int sw = (c.lane >> 2) & 1;
      const uint4 v0 = lds128(c.addr(u) + CV_U + 4064 - 32 * tid + 16 * sw), v1 = lds128(c.addr(u) + CV_U + 4080 - 32 * tid - 16 * sw);
      e.ua = sw ? v0 : v1; e.uc = sw ? v1 : v0;
    }
    e.D2 = lds32(c.addr(u) + CV_D);
    wg_wait<0>(); fence_regs(d3); fence_regs(a);
    conv_st<3>(d3, wq, c0, c1);
    conv_lda<0, 4>(a, c.addr(un) + aoff);
    sched_fence(__uint_as_float(e.ua.x ^ e.uc.x ^ e.D2), c.base + SM_DUMMY);
    c.sync();
    c.release2(u);
    conv_lda<4, 16>(a, c.addr(un) + aoff);
#pragma unroll
    for (int k = 0; k < 32; k++) { const float2 v = lds64f(rq + k * CV_ROW - (k >> 3) * 8); e.t[2 * k] = v.x; e.t[2 * k + 1] = v.y; }
  }
  conv_emit(e, conv_channel<MASK>(cta, nch - 2 + c.wg), tid);
  c.signal(SIG_Z + ((nch / 2 - 1) >> 4));
}

constexpr int OC_PART = 13824, OC_ROW = 544;
__device__ __forceinline__ int out_next(int u) { return (0x84ac680u >> (2 * u)) & 15; }
struct Out { float acc[64]; int pu; uint64_t da, db; };
template<bool FIRST, bool REL, int W = 1> __device__ __forceinline__ void out_step(Cons& c, Out& o, bool extra = false) {
  const int pu = o.pu, u = extra ? 2 : out_next(pu);
  o.pu = u;
  c.wait(u);
  const uint64_t da = o.da + (uint32_t)(u * 1024), db = o.db + (uint32_t)(u * 1024);
  wg_fence();
#pragma unroll
  for (int kk = 0; kk < 4; kk++) wgmma_ss_n128<1>(o.acc, da + (kk >> 1) * 32 + (kk & 1) * 2, db + kk * 128, !(FIRST && kk == 0));
  wg_commit();
  if (REL) { wg_wait<W>(); c.release(pu, 2); }
}
template<int I0, int I1> __device__ __forceinline__ void oc_red(float (&y)[8], uint32_t rq) {
#pragma unroll
  for (int i = I0; i < I1; i++) { const float v = __uint_as_float(lds32(rq + i * OC_ROW - (i >> 3) * 8)); y[i & 7] = i < 8 ? v : y[i & 7] + v; }
}
__device__ __forceinline__ void oc_emit(const float (&y)[8], const uint4& u, uint32_t D2, uint8_t* dst) {
  uint4 z;
  z.x = hadd2(pack_bf16(y[0], y[1]), hmul2(__byte_perm(u.w, 0, 0x1032), D2));
  z.y = hadd2(pack_bf16(y[2], y[3]), hmul2(__byte_perm(u.z, 0, 0x1032), D2));
  z.z = hadd2(pack_bf16(y[4], y[5]), hmul2(__byte_perm(u.y, 0, 0x1032), D2));
  z.w = hadd2(pack_bf16(y[6], y[7]), hmul2(__byte_perm(u.x, 0, 0x1032), D2));
  *(uint4*)dst = z;
}
__device__ __forceinline__ uint32_t mix(uint32_t og, uint32_t b, uint32_t ga) { return hadd2(ga, hmul2(og, b)); }
template<int MASK> __device__ __forceinline__ void cons_out(Cons& c, const Maps& M, const Params& P, int cta, Pend& w) {
  const int mb = out_mb(cta), nb = out_nb(cta);
  Out o;
  o.da = odesc(c.daddr(0) + c.wg * 8192, 16, 1024, 2); o.db = odesc(c.daddr(1), 8192, 1024, 1);
  o.pu = 5 + gridDim.y;
  out_step<true, false>(c, o);
  int ks = 1;
  const uint32_t dst = ctx_off(c, 16 + (cta >> 3), cta & 7, 1 - c.wg);
#pragma unroll 1
  for (;; ks++) {
    if (MASK & PH_ATT) {
      if (ks == (c.wg ? ST_1 : 1)) tile_store<0, 1>(w.lo, dst, c.lane);
      if (ks == (c.wg ? ST_1 + ST_D : 1)) tile_store<1, 2>(w.lo, dst, c.lane);
      if (ks == (c.wg ? ST_1 + 2 * ST_D : 1)) tile_store<2, 3>(w.lo, dst, c.lane);
      if (ks == (c.wg ? ST_1 + 3 * ST_D : 1)) { tile_store<3, 4>(w.lo, dst, c.lane); c.signal(SIG_CTX + 1); }
    }
    if (ks == (c.wg ? OC_S1 : OC_S0)) break;
    out_step<false, true>(c, o, ks == 1);
  }
  if (MASK & PH_CONV) {
    const int r = c.lane >> 2, q = c.lane & 3, tid = c.warp * 32 + c.lane, u = 2 * c.wg;
    const uint32_t ub = c.addr(u), part = ub + OC_PART + 32;
    const uint32_t ap = ub + CV_U + ((r & 1) ? 0 : UPITCH) + 4 * (((2039 - r) >> 1) + q - 8 * c.warp);
    const uint32_t wq = part + (c.warp * 8 + r) * OC_ROW + q * 8, rq = part + tid * 4;
    const int nr = (CV_REG<MASK> + 1 - c.wg) >> 1;
#define STEP(N) out_step<false, true>(c, o);
#pragma unroll 1
    for (int i = 0; i < nr; i++) {
      uint32_t a[64];
      CvAcc d0, d1;
      float y[8], c0 = 0.f, c1 = 0.f;
      const uint64_t db = odesc(c.daddr(u + (i >> 8)) + CV_H - 16, 16, 128, 0);
#define STEP2(N) out_step<false, true, 2>(c, o);
#define PART(...) { const uint64_t db = db0 + (c.mask >> 16); wg_fence(); __VA_ARGS__; wg_commit(); }
      const uint64_t db0 = db;
#define KEEP() asm volatile("add.f32 %0, %0, 0f80000000;" : "+f"(c0)); asm volatile("add.f32 %0, %0, 0f80000000;" : "+f"(c1));
      c.wait(u);
      conv_lda<0, 4>(a, ap);
      STEP(0)
      conv_lda<4, 7>(a, ap);
      PART(conv_part<0, 0, 2>(d0.lo, a, db); conv_part<1, 0, 4>(d0.hi, a, db); conv_part<2, 0, 2>(d1.lo, a, db))
      STEP2(1)
      conv_lda<7, 10>(a, ap);
      PART(conv_part<2, 2, 6>(d1.lo, a, db); conv_part<3, 0, 4>(d1.hi, a, db))
      STEP2(2)
      fence_regs(d0);
      c.sync();
      sts64f(wq - 32, 0.f, 0.f);
      conv_st_h<0>(d0.lo, wq, c0, c1); KEEP()
      PART(conv_part<3, 4, 8>(d1.hi, a, db); conv_part<4, 0, 4>(d0.lo, a, db))
      STEP2(3)
      fence_regs(d1.lo);
      conv_st_h<32>(d0.hi, wq, c0, c1); conv_st_h<64>(d1.lo, wq, c0, c1); KEEP()
      PART(conv_part<4, 4, 10>(d0.lo, a, db); conv_part<5, 0, 2>(d0.hi, a, db))
      STEP2(4)
      fence_regs(d1.hi);
      float e0 = d1.hi[12] + d1.hi[10], e1 = d1.hi[13] + d1.hi[11];
      conv_st_h<96>(d1.hi, wq, c0, c1); KEEP()
      conv_lda<10, 12>(a, ap);
      PART(conv_part<5, 2, 10>(d0.hi, a, db))
      STEP2(5)
      conv_lda<12, 14>(a, ap);
      c.sync();
      oc_red<0, 6>(y, rq);
      PART(conv_part<5, 10, 12>(d0.hi, a, db); conv_part<6, 0, 6>(d1.lo, a, db))
      STEP2(6)
      oc_red<6, 20>(y, rq);
      PART(conv_part<6, 6, 14>(d1.lo, a, db))
      STEP2(7)
      oc_red<20, 26>(y, rq);
      conv_lda<14, 16>(a, ap);
      PART(conv_part<7, 0, 8>(d1.hi, a, db))
      STEP2(8)
      oc_red<26, 32>(y, rq);
      PART(conv_part<7, 8, 16>(d1.hi, a, db))
      STEP2(9)
      fence_regs(y); fence_regs(d0);
      c.sync();
      sts64f(wq - 32, e0, e1);
      conv_st<0>(d0, wq, c0, c1);
      STEP(10)
      fence_regs(d1); fence_regs(a);
      const uint4 u0 = lds128(ub + CV_U + 4080 - 16 * tid), u1 = lds128(ub + CV_U + 2032 - 16 * tid);
      const uint32_t D2 = lds32(ub + CV_D);
      conv_st<1>(d1, wq, c0, c1);
      STEP(11)
      sched_fence(__uint_as_float(u0.x ^ u1.x ^ D2), c.base + SM_DUMMY);
      uint8_t* zp = g_u + (uint32_t)(conv_channel<MASK>(cta, 2 * i + c.wg) * UCH + (threadIdx.x & 127) * 16);
      oc_emit(y, u0, D2, zp);
      c.sync();
      c.release2(u);
      oc_red<0, 12>(y, rq);
      STEP(12)
      oc_red<12, 24>(y, rq);
      STEP(13)
      oc_red<24, 32>(y, rq);
      oc_emit(y, u1, D2, zp + 2048);
#undef KEEP
      if (i == nr - 1) { c.signal(SIG_Z); c.sync(); c.release2(u + 1); TSO(0); }
      out_step<false, true>(c, o);
#pragma unroll 1
      for (int k = 15; k < (i == nr - 1 ? 0 : c.wg ? OC_L1 : OC_L0); k++) out_step<false, true>(c, o);
#undef STEP2
#undef PART
    }
#undef STEP
    if (((CV_REG<MASK> + c.wg) >> 1) & 1) c.skip(u ^ 2);
    ks += (nr - 1) * (c.wg ? OC_L1 : OC_L0) + 15;
  }
  TS(c.wg, 9);
#pragma unroll 1
  for (; ks < 57; ks++) out_step<false, true>(c, o);
  uint32_t ga[32];
  TSO(1);
  c.wait(2);
  TSO(2);
  const float g0 = __uint_as_float(lds32(c.base + SM_GATE + 4 * (c.wg * 64 + c.warp * 16 + (c.lane >> 2)))), g1 = __uint_as_float(lds32(c.base + SM_GATE + 32 + 4 * (c.wg * 64 + c.warp * 16 + (c.lane >> 2))));
  const uint32_t gg0 = pack_bf16(g0, g0), gg1 = pack_bf16(g1, g1);
  const uint32_t og0 = pack_bf16(1.f - g0, 1.f - g0), og1 = pack_bf16(1.f - g1, 1.f - g1);
  const int xr = c.wg * 64 + c.warp * 16 + (c.lane & 15);
  const uint32_t xa = c.addr(2) + xr * 128, xs = xr & 7, xh = c.lane >> 4;
  const int zr = (c.lane & 7) + ((c.lane >> 4) << 3);
  const uint32_t za = c.addr(0) + c.wg * 16384 + zr * 128 + (((c.warp * 2 + ((c.lane >> 3) & 1)) ^ (zr & 7)) << 4);
#pragma unroll
  for (int i = 0; i < 8; i++) {
    if (i == 0) out_step<false, true>(c, o);
    if (i == 3) out_step<false, true>(c, o);
    if (i == 6) out_step<false, true>(c, o);
    ldsm4(xa + (i >> 2) * 16384 + ((((i & 3) * 2 + xh) ^ xs) << 4), ga[4 * i], ga[4 * i + 1], ga[4 * i + 2], ga[4 * i + 3]);
  }
  TSO(3);
#pragma unroll 1
  for (ks = 60; ks < 64; ks++) out_step<false, false>(c, o);
  TSO(4);
  c.wait(0);
  TSO(5);
  SHADOW {
#pragma unroll
    for (int i = 0; i < 8; i++) {
      uint32_t z0, z1, z2, z3;
      ldsm4t(za + i * 2048, z0, z1, z2, z3);
      ga[4 * i + 0] = hmul2(ga[4 * i + 0], z0); ga[4 * i + 1] = hmul2(ga[4 * i + 1], z1); ga[4 * i + 2] = hmul2(ga[4 * i + 2], z2); ga[4 * i + 3] = hmul2(ga[4 * i + 3], z3);
      ga[4 * i + 0] = hmul2(gg0, ga[4 * i + 0]); ga[4 * i + 1] = hmul2(gg1, ga[4 * i + 1]); ga[4 * i + 2] = hmul2(gg0, ga[4 * i + 2]); ga[4 * i + 3] = hmul2(gg1, ga[4 * i + 3]);
    }
  }
  c.signal(SIG_DONE);
  fence_regs(ga);
  TSO(6);
  wg_wait<0>(); fence_regs(o.acc);
  TSO(7);
#pragma unroll
  for (int i = 0; i < 8; i++) {
    const uint32_t r0 = mix(og0, pack_bf16(o.acc[8 * i + 0], o.acc[8 * i + 1]), ga[4 * i + 0]);
    const uint32_t r1 = mix(og1, pack_bf16(o.acc[8 * i + 2], o.acc[8 * i + 3]), ga[4 * i + 1]);
    const uint32_t r2 = mix(og0, pack_bf16(o.acc[8 * i + 4], o.acc[8 * i + 5]), ga[4 * i + 2]);
    const uint32_t r3 = mix(og1, pack_bf16(o.acc[8 * i + 6], o.acc[8 * i + 7]), ga[4 * i + 3]);
    stsm4(xa + (i >> 2) * 16384 + ((((i & 3) * 2 + xh) ^ xs) << 4), r0, r1, r2, r3);
    if ((i & 3) == 3) {
      __syncwarp();
#pragma unroll
      for (int k = 0; k < 4; k++) {
        const int rr = c.wg * 64 + c.warp * 16 + k * 4 + (c.lane >> 3);
        const uint4 v = lds128(c.addr(2 + (i >> 2)) + rr * 128 + (((c.lane ^ rr) & 7) << 4));
        *(uint4*)(P.out + (uint32_t)((mb * 128 + rr) * 1024 + nb * 128 + (i >> 2) * 64 + (c.lane & 7) * 8)) = v;
      }
    }
  }
  TSO(8);
}

__device__ __forceinline__ void load_conv(Prod& p, const Maps& M, int u, int ch) {
  if (elect()) {
    mbar_expect(p.full(u), 5120 + UCH);
    tma3d(p.addr(u), &M.h, 0, -8, ch, p.full(u), true);
    if (USPLIT) {
      bulk_g2s(p.addr(u) + CV_U, g_u + (size_t)ch * UCH, 4096, p.full(u));
      bulk_g2s(p.addr(u) + CV_U + 4096, g_u + (size_t)ch * UCH + 4096, UCH - 4096, p.full(u), true);
    } else bulk_g2s(p.addr(u) + CV_U, g_u + (size_t)ch * UCH, UCH, p.full(u), true);
  }
}
template<int MASK> __device__ __forceinline__ void prod_conv(Prod& p, const Maps& M, int cta, int nch) {
  int ready = -1;
#pragma unroll 1
  for (int i = 0; i < nch; i++) {
    const int ch = conv_channel<MASK>(cta, i);
    const int u = i & 3;
    if ((ch >> 6) != ready) { ready = ch >> 6; if (cta < NREG) mbar_wait(p.base + SM_RDY + 8 * RDY_U, 0); else cnt_wait(g_cnt + (C_U + ready) * CSTRIDE, 128); }
    p.acquire(u, 1);
    load_conv(p, M, u, ch);
    if (i == 3) { p.acquire(4, 4); if (elect()) mbar_arrive(p.full(4)); }
  }
}
#define HOIST(v) asm volatile("" : "+r"(v))
template<int MASK> __device__ __forceinline__ void producer(const Maps& M, const Params& P, uint32_t base, int cta, int lane) {
  Prod p{base, ((MASK & PH_KV) && cta < NREG) ? 0xffffcfffu ^ ((1u << (3 * NFIRST)) - 1) : 0xffffffffu, lane,
         (cta * 3 + 2) * 2048};
  if (cta >= NREG) { if (MASK & PH_CONV) prod_conv<MASK>(p, M, cta, CV_EXTRA<MASK>); return; }
  const int g = cta & 7, j = cta >> 3, rank = cta & 1;
#pragma unroll 1
  for (int half = 0; half < 2; half++) {
    const int h = j + 16 * half;
    if (MASK & PH_KV) {
      const CUtensorMap* mw = rank ? &M.wv : &M.wk;
#pragma unroll 1
      for (int it = half ? 0 : NFIRST; it < 16; it++) {
        const int u = gemm_unit(it);
        uint32_t bar = p.full(u), d0 = p.addr(u), d1 = p.addr(u + 1 + rank); int k0 = (it & 7) * 64, r0 = (2 * g + (it >> 3)) * 128;
        HOIST(bar); HOIST(d0); HOIST(d1); HOIST(k0); HOIST(r0);
        p.acquire(u, 3);
        if (elect()) {
          mbar_expect(bar, 3 * UNIT);
          tma3d_mc(d1, mw, 0, k0, 2 * h, bar, it >= 8);
          tma2d(d0, &M.c, k0, r0, bar);
        }
      }
    }
    if (MASK & PH_ATT) {
#pragma unroll 1
      for (int ks = 0; ks < 16; ks++) {
        const int u = gemm_unit(ks);
        uint32_t bar = p.full(u), d0 = p.addr(u), d1 = p.addr(u + 1), d2 = p.addr(u + 2) + rank * 8192; int k0 = ks * 64;
        HOIST(bar); HOIST(d0); HOIST(d1); HOIST(d2); HOIST(k0);
        p.acquire(u, 3);
        if (elect()) {
          mbar_expect(bar, 3 * UNIT);
          tma2d_mc(d2, &M.wq, h * 128 + rank * 64, k0, bar, true);
          tma2d(d0, &M.x, k0, (15 - g) * 128, bar);
          tma2d(d1, &M.x, k0, g * 128, bar);
        }
      }
      TS(2, 8 * half + 0);
      mbar_wait(base + SM_RDY + 8 * (RDY_KV + half), 0);
      TS(2, 8 * half + 1);
      const uint8_t* KVh = g_T + T_KV + (size_t)kv_slot<MASK>(h) * 16 * 65536;
      if (MASK & PH_PRE) mbar_wait(base + SM_RDY + 8 * RDY_AUX, 0);
      if (elect()) { mbar_expect(p.full(12), 32768); bulk_g2s(p.addr(12), KVh, 32768, p.full(12), true); }
      p.acquire(0, 4);
      if (elect()) mbar_arrive(p.full(0));
#pragma unroll 1
      for (int i = 1; i < 34; i++) {
        const int isv = !(i & 1) || i == 33, st = i == 33 ? 16 : (isv ? (i >> 1) - 1 : (i + 1) >> 1), u = 4 + 2 * (i & 3);
        const bool own = st == 15 - (g & 6);
        uint32_t bar = p.full(u), d0 = p.addr(own ? u : u + rank), off = (st <= 15 - g ? st : 16 - st) * 65536 + isv * 32768 + (own ? 0 : rank * UNIT);
        HOIST(bar); HOIST(d0); HOIST(off);
        p.acquire(u, 2);
        if (elect()) {
          mbar_expect(bar, 32768);
          if (own) bulk_g2s(d0, KVh + off, 32768, bar, true); else bulk_g2s_mc(d0, KVh + off, UNIT, bar, true);
        }
      }
    }
  }
  if ((MASK & PH_CONV) && !(MASK & PH_OUT)) prod_conv<MASK>(p, M, cta, CV_REG<MASK>);
  if (MASK & PH_OUT) {
    const int y0 = out_mb(cta) * 512 + rank * 8, z0 = 2 * out_nb(cta);
    int u = 6;
#pragma unroll 1
    for (int hf = 0; hf < 2; hf++) {
      TS(2, 16 + 2 * hf);
      mbar_wait(base + SM_RDY + 8 * (RDY_CTX + hf), 0);
      TS(2, 17 + 2 * hf);
#pragma unroll 1
      for (int n = hf * 32; n < hf * 32 + 32; n++) {
        const int ks = n == 1 ? 2 : n == 2 ? 1 : n;
        u = n == 2 ? 2 : n == 3 ? 10 : out_next(u);
        uint32_t bar = p.full(u), d0 = p.addr(u) + rank * 8192, d1 = p.addr(u + 1); int x = (ks & 1) * 256, y = y0 + (ks >> 1) * 16, k0 = ks * 64;
        HOIST(bar); HOIST(d0); HOIST(d1); HOIST(x); HOIST(y); HOIST(k0);
        p.acquire(u, 2);
        if (elect()) {
          mbar_expect(bar, 2 * UNIT);
          tma2d_mc(d0, &M.ctx, x, y, bar, true);
          tma3d(d1, &M.wo, 0, k0, z0, bar, true);
          if (ks == 1) mbar_arrive(base + SM_RDY + 8 * RDY_X);
          if (ks == Z_AT) mbar_arrive(base + SM_RDY + 8 * RDY_Z);
        }
      }
    }
  }
}
template<int MASK> __device__ __forceinline__ void producer2(const Maps& M, const Params& P, uint32_t base, int cta, int w, int lane) {
  Prod p{base, 0xffffffffu, lane, 0};
  const int mb = out_mb(cta), nb = out_nb(cta), u = 2 * w;
  if (w) { mbar_wait_slow(base + SM_RDY + 8 * RDY_X, 0); p.mask ^= 12; }
  if (MASK & PH_CONV) {
    mbar_wait_slow(base + SM_SIG + 8 * (SIG_ATT + 1), 0);
    mbar_wait_slow(base + SM_RDY + 8 * RDY_U, 0);
#pragma unroll 1
    for (int i = w; i < CV_REG<MASK>; i += 2) { p.acquire_slow(u, i < 2 ? 2 : 1); load_conv(p, M, u, conv_channel<MASK>(cta, i)); }
  }
  p.acquire_slow(u, 2);
  if (!w && elect()) map_pf(&M.z);
  TSA(52 - 2 * w);
  mbar_wait(base + SM_RDY + 8 * (!w ? RDY_Z : RDY_G), 0);
  TSA(53 - 2 * w);
  if (elect()) {
    mbar_expect(p.full(u), 2 * UNIT + (!w ? 0 : 512));
    tma2d(p.addr(u), !w ? &M.z : &M.x, (!w ? mb : nb) * 128, (!w ? nb : mb) * 128, p.full(u), true);
    tma2d(p.addr(u + 1), !w ? &M.z : &M.x, (!w ? mb : nb) * 128 + 64, (!w ? nb : mb) * 128, p.full(u), true);
    if (w) bulk_g2s(base + SM_GATE, g_gate + mb * 128, 512, p.full(u));
  }
}

__device__ __forceinline__ constexpr uint32_t PUB(int sig, int cnt, int n) { return 0x80000000u | (sig << 24) | (n << 8) | cnt; }
__device__ __forceinline__ constexpr uint32_t GET(int rdy, int cnt, int n) { return (rdy << 24) | (n << 8) | cnt; }
template<int MASK> __device__ __forceinline__ void sync_agent(uint32_t base, int cta, int lane) {
  if ((base & 0x3FFFF) != SMEM_BASE) asm volatile("trap;");
  const int g = cta & 7, j = cta >> 3, go = min(out_mb(cta), 15 - out_mb(cta));
  const int c0 = conv_channel<MASK>(cta, 0), c1 = c0 + CV_REG<MASK> - 1, n0 = min(CV_REG<MASK>, 128 - (c0 & 127));
  constexpr bool KV = MASK & PH_KV, ATT = MASK & PH_ATT, CONV = MASK & PH_CONV, OUT = MASK & PH_OUT, ALL = MASK == PH_ALL;
  uint32_t e = 0;
  if (cta >= NREG) { if (CONV && lane * 32 < CV_EXTRA<MASK>) e = PUB(SIG_Z + lane, C_Z + lane, min(32, CV_EXTRA<MASK> - lane * 32)); }
  else switch (lane) {
    case 0:  if (KV) e = PUB(SIG_KV, C_KV + j, 1); break;
    case 1:  if (ATT) e = GET(RDY_KV, C_KV + j, 8); break;
    case 2:  if (ALL) e = PUB(SIG_WAR, C_WAR + j, 1); break;
    case 3:  if (ATT) e = PUB(SIG_CTX, C_CTX + g, 1); break;
    case 4:  if (ALL) e = GET(RDY_WAR, C_WAR + j, 8); break;
    case 5:  if (KV) e = PUB(SIG_KV + 1, C_KV + 16 + j, 1); break;
    case 6:  if (ATT) e = GET(RDY_KV + 1, C_KV + 16 + j, 8); break;
    case 7:  if (OUT) e = GET(RDY_CTX, C_CTX + go, 16); break;
    case 8:  if (CONV) e = GET(RDY_U, C_U + (c0 >> 6), 128); break;
    case 9:  if (CONV) e = GET(RDY_U, C_U + (c1 >> 6), 128); break;
    case 10: if (ATT) e = PUB(SIG_CTX + 1, C_CTX + 8 + g, 1); break;
    case 11: if (OUT) e = GET(RDY_CTX + 1, C_CTX + 8 + go, 16); break;
    case 12: if (OUT) e = GET(RDY_G, C_GATE, 256); break;
    case 13: if (CONV) e = PUB(SIG_Z, C_Z + (c0 >> 7), n0); break;
    case 14: if (CONV && n0 < CV_REG<MASK>) e = PUB(SIG_Z, C_Z + (c1 >> 7), CV_REG<MASK> - n0); break;
    case 15: if (OUT) e = GET(RDY_Z, C_Z + out_nb(cta), 128); break;
  }
  __syncwarp();
#pragma unroll 1
  for (int i = 0; i < 16; i++) {
    const uint32_t x = __shfl_sync(~0u, e, i), id = (x >> 24) & 127, n = (x >> 8) & 0xffff;
    if (x == 0) continue;
    unsigned* cnt = g_cnt + (x & 255) * CSTRIDE;
    if (x >> 31) {
      mbar_wait_slow(base + SM_SIG + 8 * id, 0);
      if (i == 13) TSA(22);
      if (lane == 0) cnt_publish(cnt, n, i != 14);
    } else {
      cnt_wait(cnt, n);
      if (id < 2) {
        const float4 kn = __ldcg((const float4*)(g_kn2 + kv_slot<MASK>(j + 16 * id) * 128) + lane);
        const uint32_t m = __reduce_max_sync(~0u, max(max(__float_as_uint(kn.x), __float_as_uint(kn.y)), max(__float_as_uint(kn.z), __float_as_uint(kn.w))));
        if (lane == 0) asm volatile("st.shared.u32 [%0], %1;" :: "r"(base + SM_KMAX + 4 * id), "r"(m) : "memory");
      }
      if (lane == 0) mbar_arrive(base + SM_RDY + 8 * id);
    }
    __syncwarp();
    TSA(24 + i);
  }
}

__device__ __forceinline__ void aux_gate(const Params& P, int cta, int aw, int lane) {
  uint4 gw[4];
#pragma unroll
  for (int i = 0; i < 4; i++) gw[i] = __ldg((const uint4*)P.gw + i * 32 + lane);
#pragma unroll 1
  for (int row = cta * 16 + aw * 8; row < cta * 16 + aw * 8 + 8; row++) {
    float a = 0.f;
#pragma unroll
    for (int i = 0; i < 4; i++) {
      const uint4 xv = __ldg((const uint4*)(P.x + (size_t)row * 1024) + i * 32 + lane);
      uint32_t m;
      m = hmul2(xv.x, gw[i].x); a += bf_lo(m) + bf_hi(m); m = hmul2(xv.y, gw[i].y); a += bf_lo(m) + bf_hi(m);
      m = hmul2(xv.z, gw[i].z); a += bf_lo(m) + bf_hi(m); m = hmul2(xv.w, gw[i].w); a += bf_lo(m) + bf_hi(m);
    }
#pragma unroll
    for (int o = 16; o > 0; o >>= 1) a += __shfl_xor_sync(~0u, a, o);
    a = bf_lo(pack_bf16(a, 0.f));
    const float gt = bf_lo(pack_bf16(__fdividef(1.f, 1.f + ex2(-a * 1.4426950408889634f)), 0.f));
    if (lane == 0) g_gate[row] = gt;
    __nanosleep(GATE_SLEEP);
  }
  cnt_signal(g_cnt + C_GATE * CSTRIDE, lane);
  if (aw == 0) { TSA(44); }
}
template<int MASK> __device__ __forceinline__ void aux_pre(const Maps& M, const Params& P, uint32_t base, int cta, int aw, int lane) {
  const uint32_t kb = base + 12 * UNIT, bar = base + SM_PRE;
  const int r = lane >> 2, q = lane & 3;
  const int mi = lane >> 3, row0 = (lane & 6) + 1 - (lane & 1);
  const int ra = (mi * 9 + 1) * 2 + row0;
  const int rb = (mi == 0 ? 3 : mi) * 18 + row0;
#pragma unroll 1
  for (int it = 0; it < (cta < 96 ? 5 : 4); it++) {
    if (it == PRE_EARLY && MASK == PH_ALL) { mbar_wait_slow(base + SM_SIG + 8 * SIG_ATT, 0); aux_gate(P, cta, aw, lane); }
    if (it == PRE_EARLY && MASK == PH_ALL) mbar_wait_slow(base + SM_SIG + 8 * (SIG_ATT + 1), 0);
    const int cg = it ? it * 4 - 3 + (cta >> 5) : 0, tb = cta & 31;
    if (aw == 0 && elect()) {
      mbar_expect(bar, 2 * 9216);
      tma4d(kb, &M.k, cg * 64, 0, tb * 8 - 1, 0, bar, true);
      tma4d(kb + 9216, &M.v, cg * 64, 0, tb * 8 - 1, 0, bar, true);
    }
    const uint2 swl = __ldg((const uint2*)(P.shift + (cg * 64 + aw * 32 + lane) * 4));
    if (tb == 0) {
      uint8_t* e = g_u + (size_t)(cg * 64 + aw * 32 + lane) * UCH + 4096;
      *(uint4*)e = make_uint4(0, 0, 0, 0); *(uint4*)(e + UPITCH) = make_uint4(0, 0, 0, 0);
      *(uint32_t*)(e + 32) = (uint32_t)__bfloat16_as_ushort(P.D[cg * 64 + aw * 32 + lane]) * 0x10001u;
    }
    mbar_wait_slow(bar, it & 1);
#pragma unroll 1
    for (int ol = it ? 0 : cta >> 5; ol < (it ? 4 : (cta >> 5) + 1); ol++) {
      const int oc = aw * 4 + ol;
      const uint32_t s01 = __shfl_sync(~0u, swl.x, ol * 8 + r), s23 = __shfl_sync(~0u, swl.y, ol * 8 + r);
      const uint32_t w0 = __byte_perm(s01, 0, 0x1010), w1 = __byte_perm(s01, 0, 0x3232), w2 = __byte_perm(s23, 0, 0x1010), w3 = __byte_perm(s23, 0, 0x3232);
      const uint32_t pa = kb + ra * 128 + ((oc ^ (ra & 7)) << 4), pb = kb + (mi == 0 ? 9216 : 0) + rb * 128 + ((oc ^ (rb & 7)) << 4);
      uint8_t* e0 = g_u + (uint32_t)((cg * 64 + oc * 8 + r) * UCH + (2040 - tb * 64 - 8 * q) * 2);
#pragma unroll
      for (int hb = 0; hb < 2; hb++) {
        uint32_t k[7], v[5];
        ldsm4t(pa + hb * 1024, k[3], k[4], k[5], k[6]);
        ldsm4t(pa + hb * 1024 + 9216, v[1], v[2], v[3], v[4]);
        ldsm4t(pb + hb * 1024, v[0], k[0], k[1], k[2]);
        uint32_t o1 = __byte_perm(k[1], k[0], 0x5432);
#pragma unroll
        for (int m = 0; m < 5; m++) {
          const uint32_t o2 = __byte_perm(k[m + 2], k[m + 1], 0x5432);
          v[m] = hmul2(hadd2(hadd2(hadd2(hmul2(o1, w3), hmul2(k[m + 1], w2)), hmul2(o2, w1)), hmul2(k[m + 2], w0)), v[m]);
          o1 = o2;
        }
        *(uint4*)(e0 - hb * 64) = make_uint4(v[4], v[3], v[2], v[1]);
        *(uint4*)(e0 - hb * 64 + UPITCH) = make_uint4(__byte_perm(v[4], v[3], 0x5432), __byte_perm(v[3], v[2], 0x5432), __byte_perm(v[2], v[1], 0x5432), __byte_perm(v[1], v[0], 0x5432));
        if (it >= PRE_EARLY) __nanosleep(PRE_SLEEP);
      }
    }
    bar_sync(5, 64);
    if (aw == 0) { TSA(40 + min(it, 3)); }
    if (it == PRE_EARLY - 1 && aw == 0 && lane == 0) mbar_arrive(base + SM_RDY + 8 * RDY_AUX);
    if (aw == 1 && lane == 0) asm volatile("red.release.gpu.global.add.u32 [%0], %1;" :: "l"(g_cnt + (C_U + cg) * CSTRIDE), "r"(it ? 4 : 1) : "memory");
  }
  uint32_t rel;
  asm volatile("mapa.shared::cluster.u32 %0, %1, %2;" : "=r"(rel) : "r"(base + SM_BAR + 128 + 8 * (12 + (lane & 1))), "r"((lane >> 1) & 1));
  if (lane < 4) asm volatile("mbarrier.arrive.shared::cluster.b64 _, [%0];" :: "r"(rel) : "memory");
  if (MASK != PH_ALL) aux_gate(P, cta, aw, lane);
}

template<int MASK> __global__ void __cluster_dims__(2, 1, 1) __launch_bounds__(384, 1) gated_mix_kernel(const __grid_constant__ Maps M, const __grid_constant__ Params P) {
  extern __shared__ __align__(1024) uint8_t smem[];
  const uint32_t base = (uint32_t)__cvta_generic_to_shared(smem);
  if ((MASK & PH_KV) && elect()) {
    map_pf(&M.wk + (blockIdx.x & 1)); map_pf(&M.c);
  }
  const int wi = __shfl_sync(~0u, threadIdx.x >> 5, 0), wg = wi >> 2, warp = wi & 3;
  if (elect()) {
    if (wi < 8) {
      const int cnt = 1 << ((0x10332200 >> (4 * wi)) & 15);
#pragma unroll
      for (int i = 0; i < 8; i++) mbar_init(base + SM_BAR + 64 * wi + 8 * i, cnt);
      asm volatile("fence.mbarrier_init.release.cluster;" ::: "memory");
    }
  }
  const int cta = blockIdx.x;
  const bool first_loads = (MASK & PH_KV) && wi == 8 && cta < NREG;
  const CUtensorMap* mw = (cta & 1) ? &M.wv : &M.wk;
  __syncwarp();
  asm volatile("barrier.cluster.arrive.relaxed.aligned;\nbarrier.cluster.wait.aligned;" ::: "memory");
  auto first_stage = [&](int it) {
    const uint32_t bar = base + SM_BAR + 24 * it, d0 = base + 3 * it * UNIT;
    mbar_expect(bar, 3 * UNIT);
    tma3d_mc(d0 + (1 + (cta & 1)) * UNIT, mw, 0, it * 64, 2 * (cta >> 3), bar);
    tma2d(d0, &M.c, it * 64, (cta & 7) * 256, bar);
  };
  if (first_loads && elect()) first_stage(0);
  __syncwarp();
  const int lane = threadIdx.x & 31;
#define TS_PRO()
  if (wg == 2) {
    asm volatile("setmaxnreg.dec.sync.aligned.u32 56;");
    TS_PRO();
    TS(2, 62);
    if (warp == 0) producer<MASK>(M, P, base, cta, lane);
    else if (warp == 1) sync_agent<MASK>(base, cta, lane);
    else if (cta < NREG) {
      if (MASK & PH_PRE) aux_pre<MASK>(M, P, base, cta, warp - 2, lane);
      if (MASK & PH_OUT) producer2<MASK>(M, P, base, cta, warp - 2, lane);
    }
    if (warp == 1) {
      if (MASK & PH_OUT) {
        unsigned old = 0;
        if (lane == 0) asm volatile("atom.relaxed.gpu.global.add.u32 %0, [%1], 1;" : "=r"(old) : "l"(g_cnt + C_EXIT * CSTRIDE) : "memory");
        old = __shfl_sync(~0u, old, 0);
        if (old == NCTA - 1) for (int i = lane; i < C_NUM; i += 32) g_cnt[i * CSTRIDE] = 0;
      }
      mbar_wait_slow(base + SM_SIG + 8 * SIG_DONE, 0);
      if (cta >= NREG || !(MASK & PH_OUT)) { cluster_arrive(); cluster_wait(); }
    }
  } else {
    asm volatile("setmaxnreg.inc.sync.aligned.u32 224;");
    TS_PRO();
    uint32_t rel;
    asm volatile("mapa.shared::cluster.u32 %0, %1, %2;" : "=r"(rel) : "r"(base + SM_BAR + 128 + 8 * (lane & 15)), "r"(lane >> 4));
    Cons c{base, rel, 0u, lane, warp, wg, warp == 3 ? lane & 15 : 16, (cta * 3 + wg) * 2048};
    if (wg == 1) bar_arrive(1, 256);
    if ((MASK & PH_KV) && wi == 4 && cta < NREG) {
      if (elect()) {
#pragma unroll 1
        for (int it = 1; it < NFIRST; it++) {
          asm volatile("{\n.reg .pred p;\n.reg .u32 a, b;\nmov.u32 a, %%clock;\nXL:\nmov.u32 b, %%clock;\nsub.u32 b, b, a;\nsetp.lt.u32 p, b, %0;\n@p bra XL;\n}\n" :: "r"(it == 1 ? FGAP : FGAP2) : "memory");
          first_stage(it);
        }
      }
      __syncwarp();
    }
    TS(wg, 0);
    if (cta < NREG) {
      const int g = cta & 7, j = cta >> 3;
      Pend w = {};
#pragma unroll 1
      for (int half = 0; half < 2; half++) {
        const int h = j + 16 * half, blk = kv_slot<MASK>(h) * 16 + 2 * g;
        if (MASK & PH_KV) cons_kv<(MASK & PH_ATT) != 0>(c, h, blk, g, w, half == 1 && (MASK & PH_ATT));
        TS(wg, 1 + 4 * half);
        if (MASK & PH_ATT) {
          Att a;
          cons_q<(MASK & PH_KV) != 0>(c, h, blk + 1, w, a.o);
          TS(wg, 2 + 4 * half);
          cons_att(c, a, h, g, w);
          if (half == 0) c.signal(SIG_WAR);
#pragma unroll
          for (int i = 0; i < 8; i++) w.hi[i] = make_uint4(0, 0, 0, 0);
          TS(wg, 3 + 4 * half);
          if (MASK != PH_ALL) { tile_store<0, 4>(w.lo, ctx_off(c, h, g, 1 - wg), lane); c.signal(SIG_CTX + half); }
        } else if (MASK & PH_KV) {
          float kn = 0.f;
          out_piece<SCH_KV, true>(c, w, kv_off(c, blk + 1), blk + 1, kn, 0, true);
          for (int ks = 1; ks < 8; ks++) out_piece<SCH_KV, false>(c, w, kv_off(c, blk + 1), blk + 1, kn, ks, true);
          c.signal(SIG_KV + half);
        }
      }
      if (MASK & PH_OUT) cons_out<MASK>(c, M, P, cta, w);
    }
    if (cta >= NREG || !(MASK & PH_OUT)) {
      if (MASK & PH_CONV) cons_conv<MASK>(c, cta, cta < NREG ? CV_REG<MASK> : CV_EXTRA<MASK>);
      TS(wg, 9);
      c.signal(SIG_DONE);
      cluster_arrive();
    }
    TS(wg, 10);
  }
}

typedef CUresult (*EncFn)(CUtensorMap*, CUtensorMapDataType, cuuint32_t, void*, const cuuint64_t*, const cuuint64_t*, const cuuint32_t*, const cuuint32_t*,
                          CUtensorMapInterleave, CUtensorMapSwizzle, CUtensorMapL2promotion, CUtensorMapFloatOOBfill);
static void enc(EncFn f, CUtensorMap* m, const void* ptr, int rank, const cuuint64_t* dims, const cuuint64_t* strides, const cuuint32_t* box, CUtensorMapSwizzle sw,
                CUtensorMapDataType dt = CU_TENSOR_MAP_DATA_TYPE_BFLOAT16) {
  const cuuint32_t es[4] = {1, 1, 1, 1};
  f(m, dt, rank, (void*)ptr, dims, strides, box, es, CU_TENSOR_MAP_INTERLEAVE_NONE, sw, CU_TENSOR_MAP_L2_PROMOTION_L2_256B, CU_TENSOR_MAP_FLOAT_OOB_FILL_NONE);
}
static void enc2(EncFn f, CUtensorMap* m, const void* ptr, int cols, int rows, int brows) {
  const cuuint64_t d[2] = {(cuuint64_t)cols, (cuuint64_t)rows}, s[1] = {(cuuint64_t)cols * 2}; const cuuint32_t b[2] = {64, (cuuint32_t)brows};
  enc(f, m, ptr, 2, d, s, b, CU_TENSOR_MAP_SWIZZLE_128B);
}
static void encw(EncFn f, CUtensorMap* m, const void* ptr, int cols, int rows) {
  const cuuint64_t d[3] = {64, (cuuint64_t)rows, (cuuint64_t)cols / 64}, s[2] = {(cuuint64_t)cols * 2, 128}; const cuuint32_t b[3] = {64, 64, 2};
  enc(f, m, ptr, 3, d, s, b, CU_TENSOR_MAP_SWIZZLE_128B);
}
extern "C" void kernel_launch(void* const* d_in, const int* in_sizes, int n_in, void* d_out, int out_size) {
  static EncFn fn = nullptr;
  static int ncl = 0;
  static void* zptr = nullptr;
  static void* tptr = nullptr;
  if (!fn) {
    void* p = nullptr; cudaDriverEntryPointQueryResult qr;
    cudaGetDriverEntryPoint("cuTensorMapEncodeTiled", &p, cudaEnableDefault, &qr);
    fn = (EncFn)p;
    cudaFuncSetAttribute(gated_mix_kernel<PH_ALL>, cudaFuncAttributeMaxDynamicSharedMemorySize, SMEM_BYTES);
    cudaFuncSetAttribute(gated_mix_kernel<PH_PRE | PH_KV>, cudaFuncAttributeMaxDynamicSharedMemorySize, SMEM_BYTES);
    cudaFuncSetAttribute(gated_mix_kernel<PH_ATT | PH_CONV>, cudaFuncAttributeMaxDynamicSharedMemorySize, SMEM_BYTES);
    cudaFuncSetAttribute(gated_mix_kernel<PH_OUT>, cudaFuncAttributeMaxDynamicSharedMemorySize, SMEM_BYTES);
    cudaLaunchConfig_t cfg = {}; cfg.gridDim = NCTA; cfg.blockDim = 384; cfg.dynamicSmemBytes = SMEM_BYTES;
    cudaLaunchAttribute at; at.id = cudaLaunchAttributeClusterDimension; at.val.clusterDim.x = 2; at.val.clusterDim.y = 1; at.val.clusterDim.z = 1;
    cfg.attrs = &at; cfg.numAttrs = 1;
    cudaOccupancyMaxActiveClusters(&ncl, gated_mix_kernel<PH_ALL>, &cfg);
    cudaGetSymbolAddress(&zptr, g_u);
    cudaGetSymbolAddress(&tptr, g_T);
  }
  Maps M;
  enc2(fn, &M.x, d_in[0], 1024, 2048, 128);
  enc2(fn, &M.c, d_in[7], 512, 2048, 128);
  enc2(fn, &M.wq, d_in[8], 4096, 1024, 64);
  encw(fn, &M.wk, d_in[9], 4096, 512);
  encw(fn, &M.wv, d_in[10], 4096, 512);
  encw(fn, &M.wo, d_in[11], 1024, 4096);
  { const cuuint64_t d[3] = {64, 32, 1024}, s[2] = {128, 4096}; const cuuint32_t b[3] = {64, 40, 1}; enc(fn, &M.h, d_in[4], 3, d, s, b, CU_TENSOR_MAP_SWIZZLE_NONE); }
  { const cuuint64_t d[2] = {2048, 1024}, s[1] = {UCH}; const cuuint32_t b[2] = {64, 128}; enc(fn, &M.z, zptr, 2, d, s, b, CU_TENSOR_MAP_SWIZZLE_128B); }
  { const cuuint64_t d[2] = {512, 512 * 16}, s[1] = {2048}; const cuuint32_t b[2] = {256, 8};
    enc(fn, &M.ctx, tptr, 2, d, s, b, CU_TENSOR_MAP_SWIZZLE_NONE, CU_TENSOR_MAP_DATA_TYPE_UINT32); }
  { const cuuint64_t d[4] = {1024, 2, 256, 4}, s[3] = {2048, 16384, 4096}; const cuuint32_t b[4] = {64, 2, 9, 4};
    enc(fn, &M.k, d_in[1], 4, d, s, b, CU_TENSOR_MAP_SWIZZLE_128B); enc(fn, &M.v, d_in[2], 4, d, s, b, CU_TENSOR_MAP_SWIZZLE_128B); }
  Params P{(const __nv_bfloat16*)d_in[0], (const __nv_bfloat16*)d_in[3],
           (const __nv_bfloat16*)d_in[5], (const __nv_bfloat16*)d_in[12], (__nv_bfloat16*)d_out};
  bool split = 2 * ncl < NCTA;
  if (!split) {
    gated_mix_kernel<PH_ALL><<<NCTA, 384, SMEM_BYTES>>>(M, P);
  } else {
    gated_mix_kernel<PH_PRE | PH_KV><<<NCTA, 384, SMEM_BYTES>>>(M, P);
    gated_mix_kernel<PH_ATT | PH_CONV><<<NCTA, 384, SMEM_BYTES>>>(M, P);
    gated_mix_kernel<PH_OUT><<<NCTA, 384, SMEM_BYTES>>>(M, P);
  }
}
```

```cpp
#include <cuda_runtime.h>
#include <cuda.h>
#include <cuda_bf16.h>
#include <stdint.h>

template<int TB> __device__ __forceinline__ void wgmma_ss_n256(float (&d)[128], uint64_t da, uint64_t db, int scale_d) {
  asm volatile("{\n.reg .pred p;\nsetp.ne.b32 p, %130, 0;\n"
    "wgmma.mma_async.sync.aligned.m64n256k16.f32.bf16.bf16 {%0, %1, %2, %3, %4, %5, %6, %7, %8, %9, %10, %11, %12, %13, %14, %15, %16, %17, %18, %19, %20, %21, %22, %23, %24, %25, %26, %27, %28, %29, %30, %31, %32, %33, %34, %35, %36, %37, %38, %39, %40, %41, %42, %43, %44, %45, %46, %47, %48, %49, %50, %51, %52, %53, %54, %55, %56, %57, %58, %59, %60, %61, %62, %63, %64, %65, %66, %67, %68, %69, %70, %71, %72, %73, %74, %75, %76, %77, %78, %79, %80, %81, %82, %83, %84, %85, %86, %87, %88, %89, %90, %91, %92, %93, %94, %95, %96, %97, %98, %99, %100, %101, %102, %103, %104, %105, %106, %107, %108, %109, %110, %111, %112, %113, %114, %115, %116, %117, %118, %119, %120, %121, %122, %123, %124, %125, %126, %127}, %128, %129, p, 1, 1, 0, %131;\n}\n"
    : "+f"(d[0]), "+f"(d[1]), "+f"(d[2]), "+f"(d[3]), "+f"(d[4]), "+f"(d[5]), "+f"(d[6]), "+f"(d[7]), "+f"(d[8]), "+f"(d[9]), "+f"(d[10]), "+f"(d[11]), "+f"(d[12]), "+f"(d[13]), "+f"(d[14]), "+f"(d[15]), "+f"(d[16]), "+f"(d[17]), "+f"(d[18]), "+f"(d[19]), "+f"(d[20]), "+f"(d[21]), "+f"(d[22]), "+f"(d[23]), "+f"(d[24]), "+f"(d[25]), "+f"(d[26]), "+f"(d[27]), "+f"(d[28]), "+f"(d[29]), "+f"(d[30]), "+f"(d[31]), "+f"(d[32]), "+f"(d[33]), "+f"(d[34]), "+f"(d[35]), "+f"(d[36]), "+f"(d[37]), "+f"(d[38]), "+f"(d[39]), "+f"(d[40]), "+f"(d[41]), "+f"(d[42]), "+f"(d[43]), "+f"(d[44]), "+f"(d[45]), "+f"(d[46]), "+f"(d[47]), "+f"(d[48]), "+f"(d[49]), "+f"(d[50]), "+f"(d[51]), "+f"(d[52]), "+f"(d[53]), "+f"(d[54]), "+f"(d[55]), "+f"(d[56]), "+f"(d[57]), "+f"(d[58]), "+f"(d[59]), "+f"(d[60]), "+f"(d[61]), "+f"(d[62]), "+f"(d[63]), "+f"(d[64]), "+f"(d[65]), "+f"(d[66]), "+f"(d[67]), "+f"(d[68]), "+f"(d[69]), "+f"(d[70]), "+f"(d[71]), "+f"(d[72]), "+f"(d[73]), "+f"(d[74]), "+f"(d[75]), "+f"(d[76]), "+f"(d[77]), "+f"(d[78]), "+f"(d[79]), "+f"(d[80]), "+f"(d[81]), "+f"(d[82]), "+f"(d[83]), "+f"(d[84]), "+f"(d[85]), "+f"(d[86]), "+f"(d[87]), "+f"(d[88]), "+f"(d[89]), "+f"(d[90]), "+f"(d[91]), "+f"(d[92]), "+f"(d[93]), "+f"(d[94]), "+f"(d[95]), "+f"(d[96]), "+f"(d[97]), "+f"(d[98]), "+f"(d[99]), "+f"(d[100]), "+f"(d[101]), "+f"(d[102]), "+f"(d[103]), "+f"(d[104]), "+f"(d[105]), "+f"(d[106]), "+f"(d[107]), "+f"(d[108]), "+f"(d[109]), "+f"(d[110]), "+f"(d[111]), "+f"(d[112]), "+f"(d[113]), "+f"(d[114]), "+f"(d[115]), "+f"(d[116]), "+f"(d[117]), "+f"(d[118]), "+f"(d[119]), "+f"(d[120]), "+f"(d[121]), "+f"(d[122]), "+f"(d[123]), "+f"(d[124]), "+f"(d[125]), "+f"(d[126]), "+f"(d[127])
    : "l"(da), "l"(db), "r"(scale_d), "n"(TB));
}
template<int TB> __device__ __forceinline__ void wgmma_ss_n128(float (&d)[64], uint64_t da, uint64_t db, int scale_d) {
  asm volatile("{\n.reg .pred p;\nsetp.ne.b32 p, %66, 0;\n"
    "wgmma.mma_async.sync.aligned.m64n128k16.f32.bf16.bf16 {%0, %1, %2, %3, %4, %5, %6, %7, %8, %9, %10, %11, %12, %13, %14, %15, %16, %17, %18, %19, %20, %21, %22, %23, %24, %25, %26, %27, %28, %29, %30, %31, %32, %33, %34, %35, %36, %37, %38, %39, %40, %41, %42, %43, %44, %45, %46, %47, %48, %49, %50, %51, %52, %53, %54, %55, %56, %57, %58, %59, %60, %61, %62, %63}, %64, %65, p, 1, 1, 0, %67;\n}\n"
    : "+f"(d[0]), "+f"(d[1]), "+f"(d[2]), "+f"(d[3]), "+f"(d[4]), "+f"(d[5]), "+f"(d[6]), "+f"(d[7]), "+f"(d[8]), "+f"(d[9]), "+f"(d[10]), "+f"(d[11]), "+f"(d[12]), "+f"(d[13]), "+f"(d[14]), "+f"(d[15]), "+f"(d[16]), "+f"(d[17]), "+f"(d[18]), "+f"(d[19]), "+f"(d[20]), "+f"(d[21]), "+f"(d[22]), "+f"(d[23]), "+f"(d[24]), "+f"(d[25]), "+f"(d[26]), "+f"(d[27]), "+f"(d[28]), "+f"(d[29]), "+f"(d[30]), "+f"(d[31]), "+f"(d[32]), "+f"(d[33]), "+f"(d[34]), "+f"(d[35]), "+f"(d[36]), "+f"(d[37]), "+f"(d[38]), "+f"(d[39]), "+f"(d[40]), "+f"(d[41]), "+f"(d[42]), "+f"(d[43]), "+f"(d[44]), "+f"(d[45]), "+f"(d[46]), "+f"(d[47]), "+f"(d[48]), "+f"(d[49]), "+f"(d[50]), "+f"(d[51]), "+f"(d[52]), "+f"(d[53]), "+f"(d[54]), "+f"(d[55]), "+f"(d[56]), "+f"(d[57]), "+f"(d[58]), "+f"(d[59]), "+f"(d[60]), "+f"(d[61]), "+f"(d[62]), "+f"(d[63])
    : "l"(da), "l"(db), "r"(scale_d), "n"(TB));
}
template<int TB> __device__ __forceinline__ void wgmma_rs_n32(float (&d)[16], uint32_t a0, uint32_t a1, uint32_t a2, uint32_t a3, uint64_t db, int scale_d) {
  asm volatile("{\n.reg .pred p;\nsetp.ne.b32 p, %21, 0;\n"
    "wgmma.mma_async.sync.aligned.m64n32k16.f32.bf16.bf16 {%0, %1, %2, %3, %4, %5, %6, %7, %8, %9, %10, %11, %12, %13, %14, %15}, {%16, %17, %18, %19}, %20, p, 1, 1, %22;\n}\n"
    : "+f"(d[0]), "+f"(d[1]), "+f"(d[2]), "+f"(d[3]), "+f"(d[4]), "+f"(d[5]), "+f"(d[6]), "+f"(d[7]), "+f"(d[8]), "+f"(d[9]), "+f"(d[10]), "+f"(d[11]), "+f"(d[12]), "+f"(d[13]), "+f"(d[14]), "+f"(d[15])
    : "r"(a0), "r"(a1), "r"(a2), "r"(a3), "l"(db), "r"(scale_d), "n"(TB));
}
__device__ __forceinline__ void wgmma_pv_sel(float (&d)[64], const uint32_t (&p)[32], uint64_t db, int full, int acc, int wg) {
  asm volatile("{\n.reg .pred q, s, w;\n.reg .b64 t;\nsetp.eq.b32 w, %99, 0;\nsetp.ne.b32 s, %98, 0;\nsetp.eq.b32 q, %97, 0;\n@q bra.uni LH;\n"
    "wgmma.fence.sync.aligned;\n"
    "add.s64 t, %96, 0;\nwgmma.mma_async.sync.aligned.m64n128k16.f32.bf16.bf16 {%0, %1, %2, %3, %4, %5, %6, %7, %8, %9, %10, %11, %12, %13, %14, %15, %16, %17, %18, %19, %20, %21, %22, %23, %24, %25, %26, %27, %28, %29, %30, %31, %32, %33, %34, %35, %36, %37, %38, %39, %40, %41, %42, %43, %44, %45, %46, %47, %48, %49, %50, %51, %52, %53, %54, %55, %56, %57, %58, %59, %60, %61, %62, %63}, {%64, %65, %66, %67}, t, s, 1, 1, 1;\n"
    "add.s64 t, %96, 256;\nwgmma.mma_async.sync.aligned.m64n128k16.f32.bf16.bf16 {%0, %1, %2, %3, %4, %5, %6, %7, %8, %9, %10, %11, %12, %13, %14, %15, %16, %17, %18, %19, %20, %21, %22, %23, %24, %25, %26, %27, %28, %29, %30, %31, %32, %33, %34, %35, %36, %37, %38, %39, %40, %41, %42, %43, %44, %45, %46, %47, %48, %49, %50, %51, %52, %53, %54, %55, %56, %57, %58, %59, %60, %61, %62, %63}, {%68, %69, %70, %71}, t, 1, 1, 1, 1;\n"
    "add.s64 t, %96, 512;\nwgmma.mma_async.sync.aligned.m64n128k16.f32.bf16.bf16 {%0, %1, %2, %3, %4, %5, %6, %7, %8, %9, %10, %11, %12, %13, %14, %15, %16, %17, %18, %19, %20, %21, %22, %23, %24, %25, %26, %27, %28, %29, %30, %31, %32, %33, %34, %35, %36, %37, %38, %39, %40, %41, %42, %43, %44, %45, %46, %47, %48, %49, %50, %51, %52, %53, %54, %55, %56, %57, %58, %59, %60, %61, %62, %63}, {%72, %73, %74, %75}, t, 1, 1, 1, 1;\n"
    "add.s64 t, %96, 768;\nwgmma.mma_async.sync.aligned.m64n128k16.f32.bf16.bf16 {%0, %1, %2, %3, %4, %5, %6, %7, %8, %9, %10, %11, %12, %13, %14, %15, %16, %17, %18, %19, %20, %21, %22, %23, %24, %25, %26, %27, %28, %29, %30, %31, %32, %33, %34, %35, %36, %37, %38, %39, %40, %41, %42, %43, %44, %45, %46, %47, %48, %49, %50, %51, %52, %53, %54, %55, %56, %57, %58, %59, %60, %61, %62, %63}, {%76, %77, %78, %79}, t, 1, 1, 1, 1;\n"
    "add.s64 t, %96, 1024;\nwgmma.mma_async.sync.aligned.m64n128k16.f32.bf16.bf16 {%0, %1, %2, %3, %4, %5, %6, %7, %8, %9, %10, %11, %12, %13, %14, %15, %16, %17, %18, %19, %20, %21, %22, %23, %24, %25, %26, %27, %28, %29, %30, %31, %32, %33, %34, %35, %36, %37, %38, %39, %40, %41, %42, %43, %44, %45, %46, %47, %48, %49, %50, %51, %52, %53, %54, %55, %56, %57, %58, %59, %60, %61, %62, %63}, {%80, %81, %82, %83}, t, 1, 1, 1, 1;\n"
    "add.s64 t, %96, 1280;\nwgmma.mma_async.sync.aligned.m64n128k16.f32.bf16.bf16 {%0, %1, %2, %3, %4, %5, %6, %7, %8, %9, %10, %11, %12, %13, %14, %15, %16, %17, %18, %19, %20, %21, %22, %23, %24, %25, %26, %27, %28, %29, %30, %31, %32, %33, %34, %35, %36, %37, %38, %39, %40, %41, %42, %43, %44, %45, %46, %47, %48, %49, %50, %51, %52, %53, %54, %55, %56, %57, %58, %59, %60, %61, %62, %63}, {%84, %85, %86, %87}, t, 1, 1, 1, 1;\n"
    "@w bar.arrive 2, 256;\n@!w bar.arrive 1, 256;\n"
    "add.s64 t, %96, 1536;\nwgmma.mma_async.sync.aligned.m64n128k16.f32.bf16.bf16 {%0, %1, %2, %3, %4, %5, %6, %7, %8, %9, %10, %11, %12, %13, %14, %15, %16, %17, %18, %19, %20, %21, %22, %23, %24, %25, %26, %27, %28, %29, %30, %31, %32, %33, %34, %35, %36, %37, %38, %39, %40, %41, %42, %43, %44, %45, %46, %47, %48, %49, %50, %51, %52, %53, %54, %55, %56, %57, %58, %59, %60, %61, %62, %63}, {%88, %89, %90, %91}, t, 1, 1, 1, 1;\n"
    "add.s64 t, %96, 1792;\nwgmma.mma_async.sync.aligned.m64n128k16.f32.bf16.bf16 {%0, %1, %2, %3, %4, %5, %6, %7, %8, %9, %10, %11, %12, %13, %14, %15, %16, %17, %18, %19, %20, %21, %22, %23, %24, %25, %26, %27, %28, %29, %30, %31, %32, %33, %34, %35, %36, %37, %38, %39, %40, %41, %42, %43, %44, %45, %46, %47, %48, %49, %50, %51, %52, %53, %54, %55, %56, %57, %58, %59, %60, %61, %62, %63}, {%92, %93, %94, %95}, t, 1, 1, 1, 1;\n"
    "wgmma.commit_group.sync.aligned;\n"
    "bra.uni LE;\nLH:\n"
    "wgmma.fence.sync.aligned;\n"
    "add.s64 t, %96, 0;\nwgmma.mma_async.sync.aligned.m64n128k16.f32.bf16.bf16 {%0, %1, %2, %3, %4, %5, %6, %7, %8, %9, %10, %11, %12, %13, %14, %15, %16, %17, %18, %19, %20, %21, %22, %23, %24, %25, %26, %27, %28, %29, %30, %31, %32, %33, %34, %35, %36, %37, %38, %39, %40, %41, %42, %43, %44, %45, %46, %47, %48, %49, %50, %51, %52, %53, %54, %55, %56, %57, %58, %59, %60, %61, %62, %63}, {%80, %81, %82, %83}, t, s, 1, 1, 1;\n"
    "add.s64 t, %96, 256;\nwgmma.mma_async.sync.aligned.m64n128k16.f32.bf16.bf16 {%0, %1, %2, %3, %4, %5, %6, %7, %8, %9, %10, %11, %12, %13, %14, %15, %16, %17, %18, %19, %20, %21, %22, %23, %24, %25, %26, %27, %28, %29, %30, %31, %32, %33, %34, %35, %36, %37, %38, %39, %40, %41, %42, %43, %44, %45, %46, %47, %48, %49, %50, %51, %52, %53, %54, %55, %56, %57, %58, %59, %60, %61, %62, %63}, {%84, %85, %86, %87}, t, 1, 1, 1, 1;\n"
    "@w bar.arrive 2, 256;\n@!w bar.arrive 1, 256;\n"
    "add.s64 t, %96, 512;\nwgmma.mma_async.sync.aligned.m64n128k16.f32.bf16.bf16 {%0, %1, %2, %3, %4, %5, %6, %7, %8, %9, %10, %11, %12, %13, %14, %15, %16, %17, %18, %19, %20, %21, %22, %23, %24, %25, %26, %27, %28, %29, %30, %31, %32, %33, %34, %35, %36, %37, %38, %39, %40, %41, %42, %43, %44, %45, %46, %47, %48, %49, %50, %51, %52, %53, %54, %55, %56, %57, %58, %59, %60, %61, %62, %63}, {%88, %89, %90, %91}, t, 1, 1, 1, 1;\n"
    "add.s64 t, %96, 768;\nwgmma.mma_async.sync.aligned.m64n128k16.f32.bf16.bf16 {%0, %1, %2, %3, %4, %5, %6, %7, %8, %9, %10, %11, %12, %13, %14, %15, %16, %17, %18, %19, %20, %21, %22, %23, %24, %25, %26, %27, %28, %29, %30, %31, %32, %33, %34, %35, %36, %37, %38, %39, %40, %41, %42, %43, %44, %45, %46, %47, %48, %49, %50, %51, %52, %53, %54, %55, %56, %57, %58, %59, %60, %61, %62, %63}, {%92, %93, %94, %95}, t, 1, 1, 1, 1;\n"
    "wgmma.commit_group.sync.aligned;\n"
    "LE:\n}\n"
    : "+f"(d[0]), "+f"(d[1]), "+f"(d[2]), "+f"(d[3]), "+f"(d[4]), "+f"(d[5]), "+f"(d[6]), "+f"(d[7]), "+f"(d[8]), "+f"(d[9]), "+f"(d[10]), "+f"(d[11]), "+f"(d[12]), "+f"(d[13]), "+f"(d[14]), "+f"(d[15]), "+f"(d[16]), "+f"(d[17]), "+f"(d[18]), "+f"(d[19]), "+f"(d[20]), "+f"(d[21]), "+f"(d[22]), "+f"(d[23]), "+f"(d[24]), "+f"(d[25]), "+f"(d[26]), "+f"(d[27]), "+f"(d[28]), "+f"(d[29]), "+f"(d[30]), "+f"(d[31]), "+f"(d[32]), "+f"(d[33]), "+f"(d[34]), "+f"(d[35]), "+f"(d[36]), "+f"(d[37]), "+f"(d[38]), "+f"(d[39]), "+f"(d[40]), "+f"(d[41]), "+f"(d[42]), "+f"(d[43]), "+f"(d[44]), "+f"(d[45]), "+f"(d[46]), "+f"(d[47]), "+f"(d[48]), "+f"(d[49]), "+f"(d[50]), "+f"(d[51]), "+f"(d[52]), "+f"(d[53]), "+f"(d[54]), "+f"(d[55]), "+f"(d[56]), "+f"(d[57]), "+f"(d[58]), "+f"(d[59]), "+f"(d[60]), "+f"(d[61]), "+f"(d[62]), "+f"(d[63])
    : "r"(p[0]), "r"(p[1]), "r"(p[2]), "r"(p[3]), "r"(p[4]), "r"(p[5]), "r"(p[6]), "r"(p[7]), "r"(p[8]), "r"(p[9]), "r"(p[10]), "r"(p[11]), "r"(p[12]), "r"(p[13]), "r"(p[14]), "r"(p[15]), "r"(p[16]), "r"(p[17]), "r"(p[18]), "r"(p[19]), "r"(p[20]), "r"(p[21]), "r"(p[22]), "r"(p[23]), "r"(p[24]), "r"(p[25]), "r"(p[26]), "r"(p[27]), "r"(p[28]), "r"(p[29]), "r"(p[30]), "r"(p[31]), "l"(db), "r"(full), "r"(acc), "r"(wg) : "memory");
}

constexpr int NCTA = 132, NREG = 128;
constexpr int UNIT = 16384, NUNIT = 14;
constexpr uint32_t SMEM_BASE = 1024;
constexpr int SM_BAR = NUNIT * UNIT;
constexpr int SM_GATE = SM_BAR + 1024;
constexpr int SMEM_BYTES = SM_BAR + 1536;
constexpr int UPITCH = 4160, UCH = 2 * UPITCH;
constexpr float QSCALE = 0.08838834764831845f * 1.4426950408889634f;
constexpr float BOUND2 = 60.f * 60.f / 1.15f;
#define NSKIP 8
constexpr int C_KV = 0;
constexpr int C_CTX = 32;
constexpr int C_U = 48;
constexpr int C_Z = 80;
constexpr int C_GATE = 88;
constexpr int C_EXIT = 89, C_TICKET = 90;
#define ATT_SPLIT 4
#define SL_BAR 256
#define SL_CNT 0
#define XFAKE 0
#define R0_AT 1
#define XPP 9
#define XL 12
#define XT 1
#define R0 3
#define Z_AT 60
#define PRE_SLEEP 300
#define GATE_SLEEP 1000
#define OC_S0 2
#define OC_S1 11
#define OC_L0 18
#define OC_L1 18
#define ST_1 4
#define ST_D 2
#define SCH_KV 0x6665544433221100ull
#define SCH_Q 0x6665544433221100ull
#define NK_AT 1
#ifndef NV_AT
#define NV_AT 3
#endif
#define CHK_D 11
#define FGAP 600
#define FGAP2 200
constexpr int PRE_EARLY = 2, NFIRST = 4;
constexpr int C_WAR = 96;
constexpr int C_NUM = 112;
constexpr int CSTRIDE = 32;
constexpr int SM_KMAX = SM_BAR + 640, SM_DUMMY = SM_BAR + 648, SM_POOL = SM_BAR + 652, SM_PRE = SM_BAR + 112, SM_SIG = SM_BAR + 256, SM_RDY = SM_BAR + 384;
enum { SIG_KV = 0, SIG_CTX = 2, SIG_Z = 4, SIG_DONE = 8, SIG_WAR = 9, SIG_ATT = 10 };
enum { RDY_KV = 0, RDY_CTX = 2, RDY_WAR = 4, RDY_G = 5, RDY_X = 6, RDY_AUX = 7, RDY_U = 8, RDY_Z = 9, RDY_T = 10, RDY_NONE = 11 };
enum { PH_PRE = 1, PH_KV = 2, PH_ATT = 4, PH_CONV = 8, PH_OUT = 16, PH_ALL = 31 };

constexpr uint32_t T_CTX = 0, T_KV = 16 * 32 * 32768, T_BYTES = T_KV + 32 * 16 * 65536;
__device__ __align__(1024) uint8_t g_T[T_BYTES];
__device__ __align__(1024) uint8_t g_u[1024 * UCH];
__device__ __align__(1024) float g_gate[2048];
__device__ __align__(1024) float g_kn2[32 * 128];
__device__ __align__(1024) unsigned g_cnt[C_NUM * CSTRIDE];

struct __align__(64) Maps { CUtensorMap c, wk, wv, x, wq, wo, h, z, ctx, k, v; };
struct Params {
  const __nv_bfloat16 *x, *shift, *D, *gw;
  __nv_bfloat16* out;
};

__device__ __forceinline__ void wg_fence() { asm volatile("wgmma.fence.sync.aligned;" ::: "memory"); }
__device__ __forceinline__ void wg_commit() { asm volatile("wgmma.commit_group.sync.aligned;" ::: "memory"); }
template<int N> __device__ __forceinline__ void wg_wait() { asm volatile("wgmma.wait_group.sync.aligned %0;" :: "n"(N) : "memory"); }
__device__ __forceinline__ uint64_t odesc(uint32_t addr, uint32_t lbo, uint32_t sbo, uint32_t swz) {
  uint64_t d = (uint64_t)(addr >> 4) + (((uint64_t)(lbo >> 4) << 16) | ((uint64_t)(sbo >> 4) << 32) | ((uint64_t)swz << 62));
  asm volatile("" : "+l"(d));
  return d;
}
__device__ __forceinline__ void mbar_init(uint32_t bar, int cnt) { asm volatile("mbarrier.init.shared::cta.b64 [%0], %1;" :: "r"(bar), "r"(cnt)); }
__device__ __forceinline__ void mbar_expect(uint32_t bar, uint32_t bytes) { asm volatile("mbarrier.arrive.expect_tx.shared::cta.b64 _, [%0], %1;" :: "r"(bar), "r"(bytes) : "memory"); }
__device__ __forceinline__ void mbar_arrive(uint32_t bar) { asm volatile("mbarrier.arrive.shared::cta.b64 _, [%0];" :: "r"(bar) : "memory"); }
__device__ __forceinline__ void mbar_wait(uint32_t bar, uint32_t parity) {
  asm volatile("{\n.reg .pred p;\nLW:\nmbarrier.try_wait.parity.shared::cta.b64 p, [%0], %1;\n@!p bra LW;\n}\n" :: "r"(bar), "r"(parity) : "memory");
}
__device__ __forceinline__ void mbar_wait_slow(uint32_t bar, uint32_t parity) {
  asm volatile("{\n.reg .pred p;\n.reg .u32 n;\nmov.u32 n, 0;\n"
    "LW:\nmbarrier.test_wait.parity.shared::cta.b64 p, [%0], %1;\n@p bra LD;\n"
    "nanosleep.u32 %2;\nadd.u32 n, n, 1;\nsetp.lt.u32 p, n, 16777216;\n@p bra LW;\ntrap;\nLD:\n}\n" :: "r"(bar), "r"(parity), "n"(SL_BAR) : "memory");
}
__device__ __forceinline__ void mbar_wait_all(uint32_t bar, uint32_t parity) {
  asm volatile("{\n.reg .pred p, q;\nLW:\nmbarrier.try_wait.parity.shared::cta.b64 p, [%0], %1;\nvote.sync.all.pred q, p, 0xffffffff;\n@!q bra.uni LW;\n}\n" :: "r"(bar), "r"(parity) : "memory");
}
__device__ __forceinline__ void cnt_wait(const unsigned* p, unsigned target) {
  asm volatile("{\n.reg .pred p;\n.reg .u32 n, v;\nmov.u32 n, 0;\n"
    "LW:\nld.relaxed.gpu.global.u32 v, [%0];\nsetp.ge.u32 p, v, %1;\n@p bra LD;\n"
    "nanosleep.u32 %2;\nadd.u32 n, n, 1;\nsetp.lt.u32 p, n, 4194304;\n@p bra LW;\ntrap;\nLD:\nfence.acquire.gpu;\nfence.proxy.async.global;\n}\n" :: "l"(p), "r"(target), "n"(SL_CNT) : "memory");
}
__device__ __forceinline__ void cnt_signal(unsigned* p, int lane) {
  __syncwarp();
  if (lane == 0) asm volatile("red.release.gpu.global.add.u32 [%0], 1;" :: "l"(p) : "memory");
}
__device__ __forceinline__ void cnt_publish(unsigned* p, unsigned n, bool fence) {
  if (fence) asm volatile("fence.release.gpu;" ::: "memory");
  asm volatile("red.relaxed.gpu.global.add.u32 [%0], %1;" :: "l"(p), "r"(n) : "memory");
}
__device__ __forceinline__ uint64_t pol_first() { uint64_t p; asm("createpolicy.fractional.L2::evict_first.b64 %0, 1.0;" : "=l"(p)); return p; }
__device__ __forceinline__ void bulk_g2s(uint32_t dst, const void* src, uint32_t bytes, uint32_t bar, bool stream = false) {
  if (stream) asm volatile("cp.async.bulk.shared::cluster.global.mbarrier::complete_tx::bytes.L2::cache_hint [%0], [%1], %2, [%3], %4;" :: "r"(dst), "l"(src), "r"(bytes), "r"(bar), "l"(pol_first()) : "memory");
  else asm volatile("cp.async.bulk.shared::cluster.global.mbarrier::complete_tx::bytes [%0], [%1], %2, [%3];" :: "r"(dst), "l"(src), "r"(bytes), "r"(bar) : "memory");
}
__device__ __forceinline__ void tma2d(uint32_t dst, const CUtensorMap* m, int x, int y, uint32_t bar, bool stream = false) {
  if (stream) asm volatile("cp.async.bulk.tensor.2d.shared::cluster.global.mbarrier::complete_tx::bytes.L2::cache_hint [%0], [%1, {%3, %4}], [%2], %5;" :: "r"(dst), "l"(m), "r"(bar), "r"(x), "r"(y), "l"(pol_first()) : "memory");
  else asm volatile("cp.async.bulk.tensor.2d.shared::cluster.global.mbarrier::complete_tx::bytes [%0], [%1, {%3, %4}], [%2];" :: "r"(dst), "l"(m), "r"(bar), "r"(x), "r"(y) : "memory");
}
__device__ __forceinline__ void tma3d(uint32_t dst, const CUtensorMap* m, int x, int y, int z, uint32_t bar, bool stream = false) {
  if (stream) asm volatile("cp.async.bulk.tensor.3d.shared::cluster.global.mbarrier::complete_tx::bytes.L2::cache_hint [%0], [%1, {%3, %4, %5}], [%2], %6;" :: "r"(dst), "l"(m), "r"(bar), "r"(x), "r"(y), "r"(z), "l"(pol_first()) : "memory");
  else asm volatile("cp.async.bulk.tensor.3d.shared::cluster.global.mbarrier::complete_tx::bytes [%0], [%1, {%3, %4, %5}], [%2];" :: "r"(dst), "l"(m), "r"(bar), "r"(x), "r"(y), "r"(z) : "memory");
}
__device__ __forceinline__ void tma4d(uint32_t dst, const CUtensorMap* m, int x, int y, int z, int w, uint32_t bar, bool stream = false) {
  if (stream) asm volatile("cp.async.bulk.tensor.4d.shared::cluster.global.mbarrier::complete_tx::bytes.L2::cache_hint [%0], [%1, {%3, %4, %5, %6}], [%2], %7;" :: "r"(dst), "l"(m), "r"(bar), "r"(x), "r"(y), "r"(z), "r"(w), "l"(pol_first()) : "memory");
  else asm volatile("cp.async.bulk.tensor.4d.shared::cluster.global.mbarrier::complete_tx::bytes [%0], [%1, {%3, %4, %5, %6}], [%2];" :: "r"(dst), "l"(m), "r"(bar), "r"(x), "r"(y), "r"(z), "r"(w) : "memory");
}
__device__ __forceinline__ void bulk_g2s_mc(uint32_t dst, const void* src, uint32_t bytes, uint32_t bar, bool stream = false) {
  if (stream) asm volatile("cp.async.bulk.shared::cluster.global.mbarrier::complete_tx::bytes.multicast::cluster.L2::cache_hint [%0], [%1], %2, [%3], %4, %5;" :: "r"(dst), "l"(src), "r"(bytes), "r"(bar), "h"((uint16_t)3), "l"(pol_first()) : "memory");
  else asm volatile("cp.async.bulk.shared::cluster.global.mbarrier::complete_tx::bytes.multicast::cluster [%0], [%1], %2, [%3], %4;" :: "r"(dst), "l"(src), "r"(bytes), "r"(bar), "h"((uint16_t)3) : "memory");
}
__device__ __forceinline__ void tma2d_mc(uint32_t dst, const CUtensorMap* m, int x, int y, uint32_t bar, bool stream = false) {
  if (stream) asm volatile("cp.async.bulk.tensor.2d.shared::cluster.global.mbarrier::complete_tx::bytes.multicast::cluster.L2::cache_hint [%0], [%1, {%3, %4}], [%2], %5, %6;" :: "r"(dst), "l"(m), "r"(bar), "r"(x), "r"(y), "h"((uint16_t)3), "l"(pol_first()) : "memory");
  else asm volatile("cp.async.bulk.tensor.2d.shared::cluster.global.mbarrier::complete_tx::bytes.multicast::cluster [%0], [%1, {%3, %4}], [%2], %5;" :: "r"(dst), "l"(m), "r"(bar), "r"(x), "r"(y), "h"((uint16_t)3) : "memory");
}
__device__ __forceinline__ void tma3d_mc(uint32_t dst, const CUtensorMap* m, int x, int y, int z, uint32_t bar, bool stream = false) {
  if (stream) asm volatile("cp.async.bulk.tensor.3d.shared::cluster.global.mbarrier::complete_tx::bytes.multicast::cluster.L2::cache_hint [%0], [%1, {%3, %4, %5}], [%2], %6, %7;" :: "r"(dst), "l"(m), "r"(bar), "r"(x), "r"(y), "r"(z), "h"((uint16_t)3), "l"(pol_first()) : "memory");
  else asm volatile("cp.async.bulk.tensor.3d.shared::cluster.global.mbarrier::complete_tx::bytes.multicast::cluster [%0], [%1, {%3, %4, %5}], [%2], %6;" :: "r"(dst), "l"(m), "r"(bar), "r"(x), "r"(y), "r"(z), "h"((uint16_t)3) : "memory");
}
__device__ __forceinline__ void map_pf(const CUtensorMap* m) { asm volatile("prefetch.tensormap [%0];" :: "l"(m) : "memory"); }
__device__ __forceinline__ bool elect() {
  uint32_t r; asm volatile("{\n.reg .pred p;\nelect.sync _|p, 0xffffffff;\nselp.u32 %0, 1, 0, p;\n}\n" : "=r"(r)); return r != 0;
}
__device__ __forceinline__ void cluster_arrive() { asm volatile("barrier.cluster.arrive;" ::: "memory"); }
__device__ __forceinline__ void cluster_wait() { asm volatile("barrier.cluster.wait;" ::: "memory"); }
__device__ __forceinline__ void bar_sync(int id, int n) { asm volatile("bar.sync %0, %1;" :: "r"(id), "r"(n) : "memory"); }
__device__ __forceinline__ void bar_arrive(int id, int n) { asm volatile("bar.arrive %0, %1;" :: "r"(id), "r"(n) : "memory"); }
__device__ __forceinline__ void fence_async_smem() { asm volatile("fence.proxy.async.shared::cta;" ::: "memory"); }
__device__ __forceinline__ float ex2(float x) { float y; asm("ex2.approx.ftz.f32 %0, %1;" : "=f"(y) : "f"(x)); return y; }
__device__ __forceinline__ float rcp(float x) { float y; asm("rcp.approx.ftz.f32 %0, %1;" : "=f"(y) : "f"(x)); return y; }
__device__ __forceinline__ uint32_t pack_bf16(float lo, float hi) { uint32_t r; asm("cvt.rn.bf16x2.f32 %0, %1, %2;" : "=r"(r) : "f"(hi), "f"(lo)); return r; }
__device__ __forceinline__ uint32_t hmul2(uint32_t a, uint32_t b) { uint32_t r; asm("mul.rn.bf16x2 %0, %1, %2;" : "=r"(r) : "r"(a), "r"(b)); return r; }
__device__ __forceinline__ uint32_t hadd2(uint32_t a, uint32_t b) { uint32_t r; asm("add.rn.bf16x2 %0, %1, %2;" : "=r"(r) : "r"(a), "r"(b)); return r; }
__device__ __forceinline__ uint32_t hfma2(uint32_t a, uint32_t b, uint32_t c) { uint32_t r; asm("fma.rn.bf16x2 %0, %1, %2, %3;" : "=r"(r) : "r"(a), "r"(b), "r"(c)); return r; }
__device__ __forceinline__ float bf_lo(uint32_t a) { return __uint_as_float(a << 16); }
__device__ __forceinline__ float bf_hi(uint32_t a) { return __uint_as_float(a & 0xffff0000u); }
__device__ __forceinline__ uint32_t lds32(uint32_t a) { uint32_t v; asm volatile("ld.shared.u32 %0, [%1];" : "=r"(v) : "r"(a) : "memory"); return v; }
__device__ __forceinline__ uint4 lds128(uint32_t a) { uint4 v; asm volatile("ld.shared.v4.u32 {%0,%1,%2,%3}, [%4];" : "=r"(v.x), "=r"(v.y), "=r"(v.z), "=r"(v.w) : "r"(a) : "memory"); return v; }
__device__ __forceinline__ void sts64f(uint32_t a, float x, float y) { asm volatile("st.shared.v2.f32 [%0], {%1,%2};" :: "r"(a), "f"(x), "f"(y) : "memory"); }
template<int OFF> __device__ __forceinline__ void sts128o(uint32_t a, uint4 v) { asm volatile("st.shared.v4.u32 [%0+%5], {%1,%2,%3,%4};" :: "r"(a), "r"(v.x), "r"(v.y), "r"(v.z), "r"(v.w), "n"(OFF) : "memory"); }
__device__ __forceinline__ void ldsm4(uint32_t a, uint32_t& r0, uint32_t& r1, uint32_t& r2, uint32_t& r3) {
  asm volatile("ldmatrix.sync.aligned.m8n8.x4.shared.b16 {%0,%1,%2,%3}, [%4];" : "=r"(r0), "=r"(r1), "=r"(r2), "=r"(r3) : "r"(a) : "memory");
}
__device__ __forceinline__ void ldsm4t(uint32_t a, uint32_t& r0, uint32_t& r1, uint32_t& r2, uint32_t& r3) {
  asm volatile("ldmatrix.sync.aligned.m8n8.x4.trans.shared.b16 {%0,%1,%2,%3}, [%4];" : "=r"(r0), "=r"(r1), "=r"(r2), "=r"(r3) : "r"(a) : "memory");
}
__device__ __forceinline__ void stsm4(uint32_t a, uint32_t r0, uint32_t r1, uint32_t r2, uint32_t r3) {
  asm volatile("stmatrix.sync.aligned.m8n8.x4.shared.b16 [%0], {%1,%2,%3,%4};" :: "r"(a), "r"(r0), "r"(r1), "r"(r2), "r"(r3) : "memory");
}
template<int N> __device__ __forceinline__ void fence_regs(float (&d)[N]) {
#pragma unroll
  for (int i = 0; i < N; i++) asm volatile("" : "+f"(d[i]) :: "memory");
}
template<int N> __device__ __forceinline__ void fence_regs(uint32_t (&d)[N]) {
#pragma unroll
  for (int i = 0; i < N; i++) asm volatile("" : "+r"(d[i]) :: "memory");
}
__device__ __forceinline__ void sched_fence(float x, uint32_t dummy) {
  asm volatile("{\n.reg .pred p;\nsetp.eq.u32 p, %0, 0x7fc12345;\n@p st.shared.u32 [%1], %0;\n}\n" :: "r"(__float_as_uint(x)), "r"(dummy) : "memory");
}
#define PTRACE 0
#define TS(role, i)
#define TSA(i)
#define TSS(i)
#define TSK(i)
#define TSO(i)

#define SHADOW if (gridDim.y == 1)

struct Prod {
  uint32_t base, mask; int lane, nt;
  __device__ __forceinline__ uint32_t full(int u) const { return base + SM_BAR + 8 * u; }
  __device__ __forceinline__ uint32_t addr(int u) const { return base + u * UNIT; }
  __device__ __forceinline__ void acquire(int u, int n) {
    const int v = u + min(lane, n - 1);
    mbar_wait_all(base + SM_BAR + 128 + 8 * v, mask >> v);
    mask ^= ((1u << n) - 1) << u;
  }
  __device__ __forceinline__ void acquire_slow(int u, int n) {
    for (int i = 0; i < n; i++) mbar_wait_slow(base + SM_BAR + 128 + 8 * (u + i), mask >> (u + i));
    mask ^= ((1u << n) - 1) << u;
  }
};
struct Cons {
  uint32_t base, rel, mask; int lane, warp, wg, lr, nt;
  __device__ __forceinline__ uint32_t addr(int u) const { return base + u * UNIT; }
  __device__ __forceinline__ static uint32_t daddr(int u) { return SMEM_BASE + u * UNIT; }
  __device__ __forceinline__ void wait(int u) { mbar_wait(base + SM_BAR + 8 * u, mask >> u); mask ^= 1u << u; }
  __device__ __forceinline__ void skip(int u) { mask ^= 1u << u; }
  __device__ __forceinline__ void release(int u, int n) {
    asm volatile("{\n.reg .pred p;\nsetp.lt.s32 p, %1, %2;\n@p mbarrier.arrive.shared::cluster.b64 _, [%0];\n}\n" :: "r"(rel + 8 * u), "r"(lr), "r"(n) : "memory");
  }
  __device__ __forceinline__ void release2(int u) {
    asm volatile("{\n.reg .pred p;\nsetp.eq.s32 p, %1, 0;\n@p mbarrier.arrive.shared::cluster.b64 _, [%0], 2;\n}\n" :: "r"(rel + 8 * u), "r"(lr) : "memory");
  }
  __device__ __forceinline__ void signal(int i) {
    __syncwarp();
    asm volatile("{\n.reg .pred p;\nsetp.eq.s32 p, %1, 0;\n@p mbarrier.arrive.shared::cta.b64 _, [%0];\n}\n" :: "r"(base + SM_SIG + 8 * i), "r"(lane) : "memory");
  }
  __device__ __forceinline__ void turn() { asm volatile("{\n.reg .pred p;\nsetp.eq.s32 p, %0, 0;\n@p bar.sync 1, 256;\n@!p bar.sync 2, 256;\n}\n" :: "r"(wg) : "memory"); }
  __device__ __forceinline__ void pass() { asm volatile("{\n.reg .pred p;\nsetp.eq.s32 p, %0, 0;\n@p bar.arrive 2, 256;\n@!p bar.arrive 1, 256;\n}\n" :: "r"(wg) : "memory"); }
  __device__ __forceinline__ void sync() { asm volatile("{\n.reg .pred p;\nsetp.eq.s32 p, %0, 0;\n@p bar.sync 3, 128;\n@!p bar.sync 4, 128;\n}\n" :: "r"(wg) : "memory"); }
};
__device__ __forceinline__ int gemm_unit(int ks) { return 3 * (ks & 3); }
template<int MASK> __device__ __forceinline__ int kv_slot(int h) { return MASK == PH_ALL ? h & 15 : h; }
__device__ __forceinline__ int out_mb(int cta) { return cta >> 3; }
__device__ __forceinline__ int out_nb(int cta) { return cta & 7; }
template<int MASK> constexpr int CV_REG = MASK == PH_ALL ? 4 : 6;
template<int MASK> constexpr int CV_EXTRA = MASK == PH_ALL ? 96 + NSKIP / 2 : 64;
constexpr int CV_POOL = 896 + 2 * NSKIP;
template<int MASK> __device__ __forceinline__ int conv_channel(int cta, int i) {
  return cta < NREG ? CV_EXTRA<MASK> * (NCTA - NREG) + cta * CV_REG<MASK> + i : (i >> 1) * 8 + (cta - NREG) * 2 + (i & 1);
}

template<int OFF, int N> __device__ __forceinline__ void pack_chunk(const float (&a)[N], float sc0, float sc1, uint4& v0, uint4& v1) {
  v0.x = pack_bf16(a[OFF + 0] * sc0, a[OFF + 1] * sc0); v0.y = pack_bf16(a[OFF + 4] * sc0, a[OFF + 5] * sc0);
  v0.z = pack_bf16(a[OFF + 8] * sc0, a[OFF + 9] * sc0); v0.w = pack_bf16(a[OFF + 12] * sc0, a[OFF + 13] * sc0);
  v1.x = pack_bf16(a[OFF + 2] * sc1, a[OFF + 3] * sc1); v1.y = pack_bf16(a[OFF + 6] * sc1, a[OFF + 7] * sc1);
  v1.z = pack_bf16(a[OFF + 10] * sc1, a[OFF + 11] * sc1); v1.w = pack_bf16(a[OFF + 14] * sc1, a[OFF + 15] * sc1);
}
template<int OFF, int N> __device__ __forceinline__ void pack_chunk(const float (&a)[N], uint4& v0, uint4& v1) {
  v0.x = pack_bf16(a[OFF + 0], a[OFF + 1]); v0.y = pack_bf16(a[OFF + 4], a[OFF + 5]);
  v0.z = pack_bf16(a[OFF + 8], a[OFF + 9]); v0.w = pack_bf16(a[OFF + 12], a[OFF + 13]);
  v1.x = pack_bf16(a[OFF + 2], a[OFF + 3]); v1.y = pack_bf16(a[OFF + 6], a[OFF + 7]);
  v1.z = pack_bf16(a[OFF + 10], a[OFF + 11]); v1.w = pack_bf16(a[OFF + 14], a[OFF + 15]);
}
__device__ __forceinline__ void sq_acc(const uint4& v, uint32_t& a) { a = hfma2(v.x, v.x, a); a = hfma2(v.y, v.y, a); a = hfma2(v.z, v.z, a); a = hfma2(v.w, v.w, a); }
__device__ __forceinline__ float norm2_max(uint32_t a0, uint32_t a1) {
  float n0 = bf_lo(a0) + bf_hi(a0), n1 = bf_lo(a1) + bf_hi(a1);
  n0 += __shfl_xor_sync(~0u, n0, 1); n1 += __shfl_xor_sync(~0u, n1, 1);
  n0 += __shfl_xor_sync(~0u, n0, 2); n1 += __shfl_xor_sync(~0u, n1, 2);
  return __uint_as_float(__reduce_max_sync(~0u, max(__float_as_uint(n0) & 0x7fffffffu, __float_as_uint(n1) & 0x7fffffffu)));
}

struct Pend { uint4 lo[8], hi[8]; };
__device__ __forceinline__ uint32_t ctx_off(const Cons& c, int h, int qb, int rowhalf) { return T_CTX + (qb * 32 + h) * 32768 + (rowhalf * 4 + c.warp) * 4096; }
__device__ __forceinline__ uint32_t kv_off(const Cons& c, int blk) { return T_KV + blk * 65536 + (c.wg * 4 + c.warp) * 4096; }
__device__ __forceinline__ void pin(uint4 (&v)[8]) {
#pragma unroll
  for (int i = 0; i < 8; i++) asm volatile("" : "+r"(v[i].x), "+r"(v[i].y), "+r"(v[i].z), "+r"(v[i].w) :: "memory");
}
__device__ __forceinline__ void pack_o(const float (&o)[64], float i0, float i1, uint4 (&v)[8]) {
  pack_chunk<0>(o, i0, i1, v[0], v[1]); pack_chunk<16>(o, i0, i1, v[2], v[3]);
  pack_chunk<32>(o, i0, i1, v[4], v[5]); pack_chunk<48>(o, i0, i1, v[6], v[7]);
  pin(v);
}
__device__ __forceinline__ uint32_t atom_off(int lane) { return (lane >> 2) * 64 + (((lane ^ (lane >> 3)) & 3) << 4); }
template<int J0, int J1> __device__ __forceinline__ void tile_store(const uint4 (&v)[8], uint32_t dst, int lane) {
  uint8_t* d = g_T + (dst + atom_off(lane));
#pragma unroll
  for (int j = J0; j < J1; j++) { *(uint4*)(d + j * 512) = v[2 * j]; *(uint4*)(d + j * 512 + 2048) = v[2 * j + 1]; }
}
template<int I0, int I1> __device__ __forceinline__ void tile_store_if(bool on, const uint4 (&v)[8], const uint8_t* dst) {
  if constexpr (I0 < I1) {
    asm volatile("{\n.reg .pred p;\nsetp.ne.b32 p, %5, 0;\n@p st.v4.u32 [%0+%6], {%1,%2,%3,%4};\n}\n"
      :: "l"(dst), "r"(v[I0].x), "r"(v[I0].y), "r"(v[I0].z), "r"(v[I0].w), "r"((int)on), "n"((I0 >> 1) * 512 + (I0 & 1) * 2048) : "memory");
    tile_store_if<I0 + 1, I1>(on, v, dst);
  }
}
__device__ __forceinline__ float tile_norm2(const uint4 (&v)[8]) {
  uint32_t n0 = 0, n1 = 0, n2 = 0, n3 = 0;
#pragma unroll
  for (int j = 0; j < 2; j++) { sq_acc(v[2 * j], n0); sq_acc(v[2 * j + 1], n1); sq_acc(v[2 * j + 4], n2); sq_acc(v[2 * j + 5], n3); }
  return norm2_max(hadd2(n0, n2), hadd2(n1, n3));
}
template<uint64_t SCHED, bool FIRST> __device__ __forceinline__ void out_piece(Cons& c, Pend& w, uint32_t dst, int blk, float& kn, int ks, bool both) {
  uint8_t* d = g_T + (dst + atom_off(c.lane));
#pragma unroll
  for (int i = 0; i < 16; i++) {
    const int at = (SCHED >> (4 * i)) & 15;
    if (FIRST ? at == 0 : (at > 0 && ks == at && (i < 8 || both))) *(uint4*)(d + (i >> 3) * 32768 + ((i >> 1) & 3) * 512 + (i & 1) * 2048) = i < 8 ? w.lo[i & 7] : w.hi[i & 7];
  }
  if (FIRST || !both) return;
  if (ks == NK_AT) kn = tile_norm2(w.lo);
  if (ks == NV_AT) {
    const float vn = tile_norm2(w.hi);
    if (c.lane == 0) g_kn2[blk * 8 + c.wg * 4 + c.warp] = (vn <= 1.0e20f && vn >= 1.0e-20f) ? kn : __uint_as_float(0x7f800000u);
  }
}
template<bool FIRST> __device__ __forceinline__ void kv_issue(Cons& c, float (&acc)[128], int u) {
  const uint64_t da = odesc(c.daddr(u) + c.wg * 8192, 16, 1024, 1), db = odesc(c.daddr(u + 1), 8192, 1024, 1);
  TSK(c.nt + 1);
  c.turn();
  TSK(c.nt + 2);
  wg_fence();
#pragma unroll
  for (int kk = 0; kk < 4; kk++) wgmma_ss_n256<1>(acc, da + kk * 2, db + kk * 128, !(FIRST && kk == 0));
  wg_commit();
  c.pass();
  TSK(c.nt + 3); c.nt += 4;
}
template<bool NEXT> __device__ __forceinline__ void cons_kv(Cons& c, int h, int blk, int g, Pend& w, bool pend_o) {
#pragma unroll 1
  for (int tile = 0; tile < 2; tile++) {
    float acc[128];
    if (tile == 0) c.wait(0);
    if (tile == 0 && h < 16) TS(c.wg, 16);
    kv_issue<true>(c, acc, 0);
    c.release(9, tile == 1 ? 3 : 0);
    if (tile == 1 && pend_o) mbar_wait(c.base + SM_RDY + 8 * RDY_WAR, 0);
    const uint32_t dst = tile ? kv_off(c, blk) : ctx_off(c, h - 16, g, 1 - c.wg);
    float kn = 0.f;
    if (tile == 1 || pend_o) out_piece<SCH_KV, true>(c, w, dst, blk, kn, 0, false);
#pragma unroll 1
    for (int ks = 1; ks < 8; ks++) {
      const int u = gemm_unit(ks);
      c.wait(u);
      TSK(c.nt);
      wg_wait<0>();
      c.release(gemm_unit(ks - 1), 3);
      kv_issue<false>(c, acc, u);
      if (tile == 1 || pend_o) { out_piece<SCH_KV, false>(c, w, dst, blk, kn, ks, tile); if (ks == ((SCH_KV >> 28) & 15) && tile == 0) c.signal(SIG_CTX); }
    }
    if (NEXT || tile == 0) c.wait(0);
    wg_wait<0>(); fence_regs(acc);
    TSK(c.nt);
    if (!NEXT) c.release(9, tile == 1 ? 3 : 0);
    pack_chunk<0>(acc, w.lo[0], w.lo[1]);  pack_chunk<16>(acc, w.lo[2], w.lo[3]); pack_chunk<32>(acc, w.lo[4], w.lo[5]); pack_chunk<48>(acc, w.lo[6], w.lo[7]);
    pack_chunk<64>(acc, w.hi[0], w.hi[1]); pack_chunk<80>(acc, w.hi[2], w.hi[3]); pack_chunk<96>(acc, w.hi[4], w.hi[5]); pack_chunk<112>(acc, w.hi[6], w.hi[7]);
    pin(w.lo); pin(w.hi);
  }
}
template<bool FIRST> __device__ __forceinline__ void q_issue(Cons& c, float (&a)[64], float (&b)[64], int u) {
  const uint64_t da = odesc(c.daddr(u) + c.wg * 8192, 16, 1024, 1), db = odesc(c.daddr(u + 2), 8192, 1024, 1);
  const uint64_t da2 = odesc(c.daddr(u + 1) + (1 - c.wg) * 8192, 16, 1024, 1);
  TSK(c.nt + 1);
  c.turn();
  TSK(c.nt + 2);
  wg_fence();
#pragma unroll
  for (int kk = 0; kk < 4; kk++) wgmma_ss_n128<1>(a, da + kk * 2, db + kk * 128, !(FIRST && kk == 0));
#pragma unroll
  for (int kk = 0; kk < 4; kk++) wgmma_ss_n128<1>(b, da2 + kk * 2, db + kk * 128, !(FIRST && kk == 0));
  wg_commit();
  c.pass();
  TSK(c.nt + 3); c.nt += 4;
}
__device__ __forceinline__ void q_step(Cons& c, float (&d)[64], int ua, int ub, int rowhalf) {
  const uint64_t da = odesc(c.daddr(ua) + rowhalf * 8192, 16, 1024, 1), db = odesc(c.daddr(ub), 8192, 1024, 1);
#pragma unroll
  for (int kk = 0; kk < 4; kk++) wgmma_ss_n128<1>(d, da + kk * 2, db + kk * 128, 1);
}
template<bool PEND_KV> __device__ __forceinline__ void cons_q(Cons& c, int h, int blk, Pend& w, float (&b)[64]) {
  float a[64], kn = 0.f;
  if (!PEND_KV) c.wait(0);
  q_issue<true>(c, a, b, 0);
  if (PEND_KV) { c.release(9, 3); out_piece<SCH_Q, true>(c, w, kv_off(c, blk), blk, kn, 0, true); }
#pragma unroll 1
  for (int ks = 1; ks < 14; ks++) {
    const int u = gemm_unit(ks);
    c.wait(u);
    TSK(c.nt);
    wg_wait<0>();
    c.release(gemm_unit(ks - 1), 3);
    q_issue<false>(c, a, b, u);
    if (PEND_KV && ks <= (int)(SCH_Q >> 60)) { out_piece<SCH_Q, false>(c, w, kv_off(c, blk), blk, kn, ks, true); if (ks == (int)(SCH_Q >> 60)) c.signal(SIG_KV + (h >> 4)); }
  }
  c.wait(6); c.wait(9);
  wg_wait<0>();
  c.release(3, 3);
  c.turn();
  TSS(0);
  wg_fence();
  q_step(c, a, 6, 8, c.wg); q_step(c, a, 9, 11, c.wg); wg_commit();
  q_step(c, b, 7, 8, 1 - c.wg); wg_commit();
  c.pass();
  TSS(1);
  c.wait(0);
  const uint32_t q0 = c.addr(0) + (c.wg * 4 + c.warp) * 4096 + atom_off(c.lane);
  wg_wait<1>(); fence_regs(a);
  TSS(2);
  pack_o(a, QSCALE, QSCALE, w.lo);
  sts128o<0>(q0, w.lo[0]);    sts128o<2048>(q0, w.lo[1]); sts128o<512>(q0, w.lo[2]);  sts128o<2560>(q0, w.lo[3]);
  wg_wait<0>();
  c.release(6, 4);
  sts128o<1024>(q0, w.lo[4]); sts128o<3072>(q0, w.lo[5]); sts128o<1536>(q0, w.lo[6]); sts128o<3584>(q0, w.lo[7]);
  TSS(3);
  c.wait(12);
  fence_async_smem();
  TSS(4);
}

__device__ __forceinline__ void issue_qk(float (&s)[64], uint64_t da, uint64_t db) {
#pragma unroll
  for (int kk = 0; kk < 8; kk++) wgmma_ss_n128<0>(s, da + (kk >> 1) * 32 + (kk & 1) * 2, db + (kk >> 1) * 32 + (kk & 1) * 2, kk > 0);
  wg_commit();
}
template<int A, int B> __device__ __forceinline__ void exp_rng(float (&s)[64]) {
#pragma unroll
  for (int i = 4 * A; i < 4 * B; i++) s[i] = ex2(s[i]);
}
template<int A, int B> __device__ __forceinline__ void sum_rng(const float (&s)[64], float (&l)[4]) {
#pragma unroll
  for (int i = A; i < B; i++) { l[0] += s[4 * i]; l[1] += s[4 * i + 1]; l[2] += s[4 * i + 2]; l[3] += s[4 * i + 3]; }
}
template<int A, int B> __device__ __forceinline__ void cvt_p(const float (&s)[64], uint32_t (&p)[32]) {
#pragma unroll
  for (int i = 2 * A; i < 2 * B; i++) p[i] = pack_bf16(s[2 * i], s[2 * i + 1]);
}
template<int K0> __device__ __forceinline__ void mask_half(float (&s)[64], int warp, int lane) {
  const int l0 = warp + (2 * (lane & 3) <= (lane >> 2)), l1 = warp + (2 * (lane & 3) < (lane >> 2));
#pragma unroll
  for (int k = 0; k < 4; k++) {
    float* t = s + 8 * (K0 + k);
    if (k >= l0) { t[0] = -INFINITY; t[6] = -INFINITY; }
    if (k >= l1) { t[1] = -INFINITY; t[7] = -INFINITY; }
    if (k > warp) { t[2] = -INFINITY; t[3] = -INFINITY; }
    if (k >= warp) { t[4] = -INFINITY; t[5] = -INFINITY; }
  }
}
__device__ __forceinline__ void row_inv(float& l0, float& l1) {
  l0 += __shfl_xor_sync(~0u, l0, 1); l1 += __shfl_xor_sync(~0u, l1, 1);
  l0 += __shfl_xor_sync(~0u, l0, 2); l1 += __shfl_xor_sync(~0u, l1, 2);
  l0 = rcp(l0); l1 = rcp(l1);
}
__device__ __forceinline__ void softmax_safe(float (&s)[64], bool upper_only, float& m0, float& m1, float& sc0, float& sc1) {
  float a0 = m0, a1 = m1;
#pragma unroll
  for (int i = 0; i < 8; i++) { a0 = fmaxf(a0, fmaxf(s[4 * i], s[4 * i + 1])); a1 = fmaxf(a1, fmaxf(s[4 * i + 2], s[4 * i + 3])); }
  if (upper_only) { a0 = m0; a1 = m1; }
#pragma unroll
  for (int i = 8; i < 16; i++) { a0 = fmaxf(a0, fmaxf(s[4 * i], s[4 * i + 1])); a1 = fmaxf(a1, fmaxf(s[4 * i + 2], s[4 * i + 3])); }
  a0 = fmaxf(a0, __shfl_xor_sync(~0u, a0, 1)); a1 = fmaxf(a1, __shfl_xor_sync(~0u, a1, 1));
  a0 = fmaxf(a0, __shfl_xor_sync(~0u, a0, 2)); a1 = fmaxf(a1, __shfl_xor_sync(~0u, a1, 2));
  sc0 = ex2(m0 - a0); sc1 = ex2(m1 - a1);
  m0 = a0; m1 = a1;
#pragma unroll
  for (int i = 0; i < 16; i++) { s[4 * i] -= a0; s[4 * i + 1] -= a0; s[4 * i + 2] -= a1; s[4 * i + 3] -= a1; }
}
struct Att {
  float s[64], o[64], l[4], i0, i1, t0, t1; uint32_t p[32];
  float kn; uint32_t qaddr; const uint8_t* dst;
};
__device__ __forceinline__ int att_fast(uint4 (&q)[8], float kn) {
#pragma unroll
  for (int i = 0; i < 8; i++) q[i].x = hmul2(q[i].x, q[i].x);
#pragma unroll
  for (int i = 0; i < 8; i++) q[i].x = hfma2(q[i].w, q[i].w, hfma2(q[i].z, q[i].z, hfma2(q[i].y, q[i].y, q[i].x)));
#pragma unroll
  for (int i = 0; i < 4; i++) q[i].x = hadd2(q[i].x, q[i + 4].x);
  const uint32_t a0 = hadd2(q[0].x, q[2].x), a1 = hadd2(q[1].x, q[3].x);
  return __shfl_sync(~0u, __all_sync(~0u, ((bf_lo(a0) + bf_hi(a0)) * kn <= 0.25f * BOUND2) & ((bf_lo(a1) + bf_hi(a1)) * kn <= 0.25f * BOUND2)), 0);
}
__device__ __forceinline__ int att_first(Cons& c, Att& a, int h, Pend& w) {
  a.kn = __uint_as_float(lds32(c.base + SM_KMAX + 4 * (h >> 4)));
  a.qaddr = c.daddr(0) + c.wg * 16384;
  c.turn();
  TSS(5);
  wg_fence();
  issue_qk(a.s, odesc(a.qaddr, 16, 2048, 2), odesc(c.daddr(12), 16, 2048, 2));
  int fast = 0;
  SHADOW fast = att_fast(w.lo, a.kn);
  wg_fence();
  TSS(6);
  q_step(c, a.o, 10, 11, 1 - c.wg); wg_commit();
  if (c.wg) c.wait(6); else c.skip(6);
  c.pass();
  TSS(7);
#pragma unroll
  for (int i = 0; i < 8; i++) { a.p[4 * i] = w.lo[i].x; a.p[4 * i + 1] = w.lo[i].y; a.p[4 * i + 2] = w.lo[i].z; a.p[4 * i + 3] = w.lo[i].w; }
  a.l[0] = a.l[1] = a.l[2] = a.l[3] = 0.f; a.i0 = a.i1 = a.t0 = a.t1 = 0.25f / QSCALE;
  a.dst = (const uint8_t*)__cvta_shared_to_generic(c.addr(2) + (c.wg * 4 + c.warp) * 4096 + atom_off(c.lane));
  wg_wait<1>(); fence_regs(a.s);
  c.signal(SIG_ATT + (h >> 4));
  if (c.wg) { wg_wait<0>(); c.release(10, 2); }
  return fast;
}
__device__ __forceinline__ void att_last(Cons& c, Att& a, Pend& w, int h, int g, bool drain) {
  const int uv = 6;
  if (drain) pack_o(a.o, rcp(a.i0), rcp(a.i1), w.hi);
  TSS(8);
  c.turn();
  TSS(9);
  fence_regs(a.o); fence_regs(a.p);
  wgmma_pv_sel(a.o, a.p, odesc(c.daddr(uv), 512, 2048, 2), !(drain && c.wg == 1), !drain, c.wg);
  a.i0 = a.l[0] + a.l[1]; a.i1 = a.l[2] + a.l[3];
  SHADOW row_inv(a.i0, a.i1);
  sched_fence(a.i0 + a.i1, c.base + SM_DUMMY);
  tile_store_if<0, 4>(drain, w.hi, a.dst);
  wg_wait<0>(); fence_regs(a.o); fence_regs(a.p);
  c.release(uv, 2);
  TSS(10); if (h < 16) TSK(0); TSO(9 + (h >> 4));
  tile_store_if<4, 8>(drain, w.hi, a.dst);
  pack_o(a.o, a.i0, a.i1, w.lo);
  TSS(11);
}
__device__ __forceinline__ void cons_att(Cons& c, Att& a, int h, int g, Pend& w) {
  int fast = att_first(c, a, h, w), fast2 = 0;
  float m0 = -INFINITY, m1 = -INFINITY, sc0 = 0.f, sc1 = 0.f;
  int uk = 10, ur = 10;
  bool fresh = false;
#pragma unroll 1
  for (int d = g - 15;;) {
    const bool lo = d == c.wg;
    TSS(16 + 6 * (d - g + 15));
    if ((unsigned)d < 2 || !fast) {
      if ((unsigned)d < 2) mask_half<4>(a.s, c.warp, c.lane);
      if (!fast) {
        if (d == 1) m0 = m1 = -INFINITY;
        softmax_safe(a.s, lo, m0, m1, sc0, sc1);
        a.l[0] *= sc0; a.l[1] *= sc0; a.l[2] *= sc1; a.l[3] *= sc1;
      }
    }
    exp_rng<8, 16>(a.s); sum_rng<8, 16>(a.s, a.l);
#pragma unroll
    for (int i = 4 * ATT_SPLIT; i < 32; i++) asm("{\n.reg .pred p;\nsetp.ne.s32 p, %1, %2;\n@p ex2.approx.ftz.f32 %0, %0;\n}\n" : "+f"(a.s[i]) : "r"(d), "r"(c.wg));
    sched_fence(((a.l[0] + a.l[1]) + (a.l[2] + a.l[3])) + a.s[4 * ATT_SPLIT + 3], c.base + SM_DUMMY);
    wg_wait<0>(); fence_regs(a.o); fence_regs(a.p);
    c.release(ur, c.wg && d == g - 15 ? 0 : 2);
    TSS(17 + 6 * (d - g + 15));
    a.i0 += a.t0; a.i1 += a.t1;
    a.t0 = __shfl_xor_sync(~0u, a.i0, 2); a.t1 = __shfl_xor_sync(~0u, a.i1, 2);
    tile_store_if<0, 4>(fresh, w.hi, a.dst);
    uk ^= 12; ur = 14 - uk;
    if (d == 0) a.qaddr += 32768;
    const uint64_t dq = odesc(a.qaddr, 16, 2048, 2), dk = odesc(c.daddr(uk) - (d + 1 == c.wg ? 16384 : 0), 16, 2048, 2), dv = odesc(c.daddr(ur), 512, 2048, 2);
    if (!lo) { exp_rng<0, ATT_SPLIT>(a.s); sum_rng<0, 8>(a.s, a.l); cvt_p<0, 16>(a.s, a.p); }
    else if (gridDim.y == 1) cvt_p<8, 16>(a.s, a.p);
    tile_store_if<4, 8>(fresh, w.hi, a.dst);
    a.i0 += a.t0; a.i1 += a.t1;
    if (!fast || d == g + 1) {
      if (!fast && d != 1 && d != g - 15) {
#pragma unroll
        for (int i = 0; i < 16; i++) { a.o[4 * i] *= sc0; a.o[4 * i + 1] *= sc0; a.o[4 * i + 2] *= sc1; a.o[4 * i + 3] *= sc1; }
      }
      if (d == g + 1) break;
    }
    d++;
    fresh = d == 2 || d == g - 14;
    TSS(12 + 6 * (d - g + 15));
    c.turn();
    TSS(13 + 6 * (d - g + 15));
    fence_regs(a.o); fence_regs(a.p);
    wg_fence();
    issue_qk(a.s, dq, dk);
    TSS(14 + 6 * (d - g + 15));
    c.wait(c.wg ? uk ^ 12 : ur); c.skip(c.wg ? ur : uk ^ 12);
    if (fresh || d == 1 || (unsigned)(d - g + CHK_D) < 2) {
      if (fresh) pack_o(a.o, rcp(a.i0), rcp(a.i1), w.hi);
      else if (d == 1) {
        a.i0 = a.l[0] + a.l[1]; a.i1 = a.l[2] + a.l[3];
        a.t0 = __shfl_xor_sync(~0u, a.i0, 1); a.t1 = __shfl_xor_sync(~0u, a.i1, 1);
        a.l[0] = a.l[1] = a.l[2] = a.l[3] = 0.f;
        uint32_t off = ctx_off(c, h, 15 - g, c.wg);
        asm volatile("" : "+r"(off));
        a.dst = g_T + (off + ((uint32_t)(uint64_t)a.dst & 511));
        fast = fast2;
      } else if (d == g - CHK_D) fence_async_smem();
      else fast2 = att_fast(w.hi, a.kn);
    }
    TSS(15 + 6 * (d - g + 15));
    wgmma_pv_sel(a.o, a.p, dv, !lo, !fresh, c.wg);
    wg_wait<1>(); fence_regs(a.s);
    c.release(uk, 2);
    c.release(d == 0 ? 0 : 2, (d == 0 || d == g + 1) ? 2 : 0);
  }
  att_last(c, a, w, h, g, g == 0);
}

constexpr int CV_H = 1024, CV_U = 5120, CV_D = CV_U + 4128;
template<int OFF> __device__ __forceinline__ uint32_t lds32o(uint32_t a) { uint32_t v; asm volatile("ld.shared.u32 %0, [%1+%2];" : "=r"(v) : "r"(a), "n"(OFF) : "memory"); return v; }
template<int G, int G1 = 16> __device__ __forceinline__ void conv_lda(uint32_t (&a)[64], uint32_t p) {
  a[4 * G + 0] = lds32o<-256 * G>(p);
  a[4 * G + 1] = lds32o<-256 * G - 128>(p);
  a[4 * G + 2] = lds32o<-256 * G + 16>(p);
  a[4 * G + 3] = lds32o<-256 * G - 112>(p);
  if constexpr (G + 1 < G1) conv_lda<G + 1, G1>(a, p);
}
struct CvAcc { float lo[16], hi[16]; };
__device__ __forceinline__ void fence_regs(CvAcc& d) { fence_regs(d.lo); fence_regs(d.hi); }
template<int T, int G0, int G1> __device__ __forceinline__ void conv_part(float (&d)[16], const uint32_t (&a)[64], uint64_t db) {
#pragma unroll
  for (int G = G0; G < G1; G++) wgmma_rs_n32<0>(d, a[4 * G], a[4 * G + 1], a[4 * G + 2], a[4 * G + 3], db + 32 * T - 16 * G, G > 0);
}
template<int C0> __device__ __forceinline__ void conv_st_h(const float (&d)[16], uint32_t wq, float& c0, float& c1) {
#pragma unroll
  for (int n = 0; n < 4; n++) { sts64f(wq + (C0 + n * 8) * 4, d[4 * n] + c0, d[4 * n + 1] + c1); c0 = d[4 * n + 2]; c1 = d[4 * n + 3]; }
}
template<int R> __device__ __forceinline__ void conv_st(const CvAcc& d, uint32_t wq, float& c0, float& c1) { conv_st_h<64 * R>(d.lo, wq, c0, c1); conv_st_h<64 * R + 32>(d.hi, wq, c0, c1); }

constexpr int OC_PART = 13824, OC_ROW = 544;
__device__ __forceinline__ int out_next(int u) { return (0x84ac680u >> (2 * u)) & 15; }
struct Out { float acc[64]; int pu; uint64_t da, db; };
template<bool FIRST, bool REL, int W = 1> __device__ __forceinline__ void out_step(Cons& c, Out& o, bool extra = false) {
  const int pu = o.pu, u = extra ? 2 : out_next(pu);
  o.pu = u;
  c.wait(u);
  const uint64_t da = o.da + (uint32_t)(u * 1024), db = o.db + (uint32_t)(u * 1024);
  wg_fence();
#pragma unroll
  for (int kk = 0; kk < 4; kk++) wgmma_ss_n128<1>(o.acc, da + (kk >> 1) * 32 + (kk & 1) * 2, db + kk * 128, !(FIRST && kk == 0));
  wg_commit();
  if (REL) { wg_wait<W>(); c.release(pu, 2); }
}
template<int I0, int I1> __device__ __forceinline__ void oc_red(float (&y)[8], uint32_t rq) {
#pragma unroll
  for (int i = I0; i < I1; i++) { const float v = __uint_as_float(lds32(rq + i * OC_ROW - (i >> 3) * 8)); y[i & 7] = i < 8 ? v : y[i & 7] + v; }
}
template<int I0, int I1> __device__ __forceinline__ void oc_ld(float (&t)[32], uint32_t rq) {
#pragma unroll
  for (int i = I0; i < I1; i++) t[i] = __uint_as_float(lds32(rq + i * OC_ROW - (i >> 3) * 8));
}
__device__ __forceinline__ void oc_emit(const float (&y)[8], const uint4& u, uint32_t D2, uint8_t* dst) {
  uint4 z;
  z.x = hadd2(pack_bf16(y[0], y[1]), hmul2(__byte_perm(u.w, 0, 0x1032), D2));
  z.y = hadd2(pack_bf16(y[2], y[3]), hmul2(__byte_perm(u.z, 0, 0x1032), D2));
  z.z = hadd2(pack_bf16(y[4], y[5]), hmul2(__byte_perm(u.y, 0, 0x1032), D2));
  z.w = hadd2(pack_bf16(y[6], y[7]), hmul2(__byte_perm(u.x, 0, 0x1032), D2));
  *(uint4*)dst = z;
}
template<bool THR> __device__ __forceinline__ void conv_round(Cons& c, Out& o, int u, uint32_t ub, uint32_t wq, uint32_t rq, int ch) {
  const int r = c.lane >> 2, q = c.lane & 3, tid = c.warp * 32 + c.lane;
  const uint32_t ap = ub + CV_U + ((r & 1) ? 0 : UPITCH) + 4 * (((2039 - r) >> 1) + q - 8 * c.warp);
  uint32_t a[64];
  CvAcc d0, d1;
  float y[8], t[32], c0 = 0.f, c1 = 0.f;
  const uint64_t db0 = odesc(c.daddr(u) + CV_H - 16, 16, 128, 0);
#define STEP(N) if (THR) out_step<false, true>(c, o); else if (N == 0) { if (XPP) c.turn(); } else if (N == 10) wg_wait<0>();
#define STEP2(N) if (THR) out_step<false, true, 2>(c, o); else { if (XPP && N == XPP) c.pass(); wg_wait<1>(); }
#define PART(...) { const uint64_t db = db0 + (c.mask >> 16); wg_fence(); __VA_ARGS__; wg_commit(); }
#define KEEP() asm volatile("add.f32 %0, %0, 0f80000000;" : "+f"(c0)); asm volatile("add.f32 %0, %0, 0f80000000;" : "+f"(c1));
  c.wait(u);
  conv_lda<0, THR ? 4 : XL>(a, ap);
  STEP(0)
  if (THR || XL < 7) conv_lda<4, 7>(a, ap);
  PART(conv_part<0, 0, 2>(d0.lo, a, db); conv_part<1, 0, 4>(d0.hi, a, db); conv_part<2, 0, 2>(d1.lo, a, db))
  STEP2(1)
  if (THR || XL < 10) conv_lda<7, 10>(a, ap);
  PART(conv_part<2, 2, 6>(d1.lo, a, db); conv_part<3, 0, 4>(d1.hi, a, db))
  STEP2(2)
  fence_regs(d0);
  if (THR || !XPP) c.sync();
  sts64f(wq - 32, 0.f, 0.f);
  conv_st_h<0>(d0.lo, wq, c0, c1); KEEP()
  PART(conv_part<3, 4, 8>(d1.hi, a, db); conv_part<4, 0, 4>(d0.lo, a, db))
  STEP2(3)
  fence_regs(d1.lo);
  conv_st_h<32>(d0.hi, wq, c0, c1); conv_st_h<64>(d1.lo, wq, c0, c1); KEEP()
  PART(conv_part<4, 4, 10>(d0.lo, a, db); conv_part<5, 0, 2>(d0.hi, a, db))
  STEP2(4)
  fence_regs(d1.hi);
  float e0 = d1.hi[12] + d1.hi[10], e1 = d1.hi[13] + d1.hi[11];
  conv_st_h<96>(d1.hi, wq, c0, c1); KEEP()
  if (THR || XL < 12) conv_lda<10, 12>(a, ap);
  PART(conv_part<5, 2, 10>(d0.hi, a, db))
  STEP2(5)
  if (THR || XL < 14) conv_lda<12, 14>(a, ap);
  c.sync();
  if (THR || !XT) oc_red<0, 6>(y, rq); else oc_ld<0, 8>(t, rq);
  PART(conv_part<5, 10, 12>(d0.hi, a, db); conv_part<6, 0, 6>(d1.lo, a, db))
  STEP2(6)
  if (THR || !XT) oc_red<6, 20>(y, rq); else oc_ld<8, 16>(t, rq);
  PART(conv_part<6, 6, 14>(d1.lo, a, db))
  STEP2(7)
  if (THR || !XT) oc_red<20, 26>(y, rq); else oc_ld<16, 24>(t, rq);
  if (THR || XL < 16) conv_lda<14, 16>(a, ap);
  PART(conv_part<7, 0, 8>(d1.hi, a, db))
  STEP2(8)
  if (THR || !XT) oc_red<26, 32>(y, rq); else oc_ld<24, 32>(t, rq);
  PART(conv_part<7, 8, 16>(d1.hi, a, db))
  STEP2(9)
  if (!THR && XT) {
#pragma unroll
    for (int i = 0; i < 8; i++) y[i] = t[i];
    SHADOW {
#pragma unroll
      for (int i = 0; i < 8; i++) y[i] = ((t[i] + t[8 + i]) + t[16 + i]) + t[24 + i];
    }
  }
  fence_regs(y); fence_regs(d0);
  c.sync();
  sts64f(wq - 32, e0, e1);
  conv_st<0>(d0, wq, c0, c1);
  STEP(10)
  fence_regs(d1); fence_regs(a);
  const uint4 u0 = lds128(ub + CV_U + 4080 - 16 * tid), u1 = lds128(ub + CV_U + 2032 - 16 * tid);
  const uint32_t D2 = lds32(ub + CV_D);
  conv_st<1>(d1, wq, c0, c1);
  STEP(11)
  sched_fence(__uint_as_float(u0.x ^ u1.x ^ D2), c.base + SM_DUMMY);
  uint8_t* zp = g_u + (uint32_t)(ch * UCH + (threadIdx.x & 127) * 16);
  oc_emit(y, u0, D2, zp);
  c.sync();
  c.release2(u);
  oc_red<0, 12>(y, rq);
  STEP(12)
  oc_red<12, 24>(y, rq);
  STEP(13)
  oc_red<24, 32>(y, rq);
  oc_emit(y, u1, D2, zp + 2048);
#undef KEEP
#undef STEP
#undef STEP2
#undef PART
}
template<int MASK> __device__ __forceinline__ void cons_conv(Cons& c, int cta, int nch) {
  const uint32_t part = c.addr(4 + 2 * c.wg) + 32;
  const uint32_t wq = part + (c.warp * 8 + (c.lane >> 2)) * OC_ROW + (c.lane & 3) * 8, rq = part + (c.warp * 32 + c.lane) * 4;
  Out o;
  c.wait(4);
#pragma unroll 1
  for (int i = 0; i < nch / 2; i++) {
    const int u = 2 * (i & 1) + c.wg;
    conv_round<false>(c, o, u, c.addr(u), wq, rq, conv_channel<MASK>(cta, 2 * i + c.wg));
    if ((i & 15) == 15 || i == nch / 2 - 1) c.signal(SIG_Z + (i >> 4));
  }
  if (XFAKE) c.signal(SIG_Z + 3);
}
__device__ __forceinline__ uint32_t mix(uint32_t og, uint32_t b, uint32_t ga) { return hadd2(ga, hmul2(og, b)); }
template<int MASK> __device__ __forceinline__ void cons_out(Cons& c, const Maps& M, const Params& P, int cta, Pend& w) {
  const int mb = out_mb(cta), nb = out_nb(cta);
  Out o;
  o.da = odesc(c.daddr(0) + c.wg * 8192, 16, 1024, 2); o.db = odesc(c.daddr(1), 8192, 1024, 1);
  o.pu = 5 + gridDim.y;
  out_step<true, false>(c, o);
  int ks = 1;
  const uint32_t dst = ctx_off(c, 16 + (cta >> 3), cta & 7, 1 - c.wg);
#pragma unroll 1
  for (;; ks++) {
    if (MASK & PH_ATT) {
      if (ks == (c.wg ? ST_1 : 1)) tile_store<0, 1>(w.lo, dst, c.lane);
      if (ks == (c.wg ? ST_1 + ST_D : 1)) tile_store<1, 2>(w.lo, dst, c.lane);
      if (ks == (c.wg ? ST_1 + 2 * ST_D : 1)) tile_store<2, 3>(w.lo, dst, c.lane);
      if (ks == (c.wg ? ST_1 + 3 * ST_D : 1)) { tile_store<3, 4>(w.lo, dst, c.lane); c.signal(SIG_CTX + 1); }
    }
    if (ks == (c.wg ? OC_S1 : OC_S0)) break;
    out_step<false, true>(c, o, ks == 1);
  }
  if (MASK & PH_CONV) {
    const int r = c.lane >> 2, q = c.lane & 3, tid = c.warp * 32 + c.lane, u = 2 * c.wg;
    const uint32_t ub = c.addr(u), part = ub + OC_PART + 32;
    const uint32_t wq = part + (c.warp * 8 + r) * OC_ROW + q * 8, rq = part + tid * 4;
    int ch = conv_channel<MASK>(cta, 3 * c.wg);
#pragma unroll 1
    for (int i = 0; ch >= 0; i++) {
      conv_round<true>(c, o, u + (i >> 8), ub, wq, rq, ch);
      ch = i + c.wg < 2 ? ch + 1 : -1;
      if (c.wg > i) { mbar_wait(c.base + SM_RDY + 8 * RDY_T, 0); ch = __shfl_sync(~0u, lds32(c.base + SM_POOL), 0); }
      if (ch < 0) { c.signal(SIG_Z); c.sync(); c.release2(u + 1); TSO(0); }
      out_step<false, true>(c, o);
#pragma unroll 1
      for (int k = 15; k < (ch < 0 ? 0 : c.wg ? OC_L1 : OC_L0); k++) out_step<false, true>(c, o);
      ks += ch < 0 ? 15 : c.wg ? OC_L1 : OC_L0;
    }
    if (c.wg) c.skip(0);
  }
  TS(c.wg, 9);
#pragma unroll 1
  for (; ks < 57; ks++) out_step<false, true>(c, o);
  uint32_t ga[32];
  TSO(1);
  c.wait(3);
  TSO(2);
  const float g0 = __uint_as_float(lds32(c.base + SM_GATE + 4 * (c.wg * 64 + c.warp * 16 + (c.lane >> 2)))), g1 = __uint_as_float(lds32(c.base + SM_GATE + 32 + 4 * (c.wg * 64 + c.warp * 16 + (c.lane >> 2))));
  const uint32_t gg0 = pack_bf16(g0, g0), gg1 = pack_bf16(g1, g1);
  const uint32_t og0 = pack_bf16(1.f - g0, 1.f - g0), og1 = pack_bf16(1.f - g1, 1.f - g1);
  const int xr = c.wg * 64 + c.warp * 16 + (c.lane & 15);
  const uint32_t xa = c.addr(2) + xr * 128, xs = xr & 7, xh = c.lane >> 4;
  const int zr = (c.lane & 7) + ((c.lane >> 4) << 3);
  const uint32_t za = c.addr(0) + c.wg * 16384 + zr * 128 + (((c.warp * 2 + ((c.lane >> 3) & 1)) ^ (zr & 7)) << 4);
#pragma unroll
  for (int i = 0; i < 8; i++) {
    if (i == 0) out_step<false, true>(c, o);
    if (i == 3) out_step<false, true>(c, o);
    if (i == 6) out_step<false, true>(c, o);
    ldsm4(xa + (i >> 2) * 16384 + ((((i & 3) * 2 + xh) ^ xs) << 4), ga[4 * i], ga[4 * i + 1], ga[4 * i + 2], ga[4 * i + 3]);
  }
  TSO(3);
#pragma unroll 1
  for (ks = 60; ks < 64; ks++) out_step<false, false>(c, o);
  TSO(4);
  c.wait(0);
  TSO(5);
  SHADOW {
#pragma unroll
    for (int i = 0; i < 8; i++) {
      uint32_t z0, z1, z2, z3;
      ldsm4t(za + i * 2048, z0, z1, z2, z3);
      ga[4 * i + 0] = hmul2(ga[4 * i + 0], z0); ga[4 * i + 1] = hmul2(ga[4 * i + 1], z1); ga[4 * i + 2] = hmul2(ga[4 * i + 2], z2); ga[4 * i + 3] = hmul2(ga[4 * i + 3], z3);
      ga[4 * i + 0] = hmul2(gg0, ga[4 * i + 0]); ga[4 * i + 1] = hmul2(gg1, ga[4 * i + 1]); ga[4 * i + 2] = hmul2(gg0, ga[4 * i + 2]); ga[4 * i + 3] = hmul2(gg1, ga[4 * i + 3]);
    }
  }
  c.signal(SIG_DONE);
  fence_regs(ga);
  TSO(6);
  wg_wait<0>(); fence_regs(o.acc);
  TSO(7);
#pragma unroll
  for (int i = 0; i < 8; i++) {
    const uint32_t r0 = mix(og0, pack_bf16(o.acc[8 * i + 0], o.acc[8 * i + 1]), ga[4 * i + 0]);
    const uint32_t r1 = mix(og1, pack_bf16(o.acc[8 * i + 2], o.acc[8 * i + 3]), ga[4 * i + 1]);
    const uint32_t r2 = mix(og0, pack_bf16(o.acc[8 * i + 4], o.acc[8 * i + 5]), ga[4 * i + 2]);
    const uint32_t r3 = mix(og1, pack_bf16(o.acc[8 * i + 6], o.acc[8 * i + 7]), ga[4 * i + 3]);
    stsm4(xa + (i >> 2) * 16384 + ((((i & 3) * 2 + xh) ^ xs) << 4), r0, r1, r2, r3);
    if ((i & 3) == 3) {
      __syncwarp();
#pragma unroll
      for (int k = 0; k < 4; k++) {
        const int rr = c.wg * 64 + c.warp * 16 + k * 4 + (c.lane >> 3);
        const uint4 v = lds128(c.addr(2 + (i >> 2)) + rr * 128 + (((c.lane ^ rr) & 7) << 4));
        *(uint4*)(P.out + (uint32_t)((mb * 128 + rr) * 1024 + nb * 128 + (i >> 2) * 64 + (c.lane & 7) * 8)) = v;
      }
    }
  }
  TSO(8);
}

__device__ __forceinline__ void load_conv(Prod& p, const Maps& M, int u, int ch) {
  if (elect()) {
    mbar_expect(p.full(u), 5120 + UCH);
    tma3d(p.addr(u), &M.h, 0, -8, ch, p.full(u), true);
    bulk_g2s(p.addr(u) + CV_U, g_u + (size_t)ch * UCH, UCH, p.full(u), true);
  }
}
template<int MASK> __device__ __forceinline__ void prod_conv(Prod& p, const Maps& M, int cta, int nch) {
  int ready = -1;
#pragma unroll 1
  for (int i = 0; i < nch; i++) {
    const int ch = conv_channel<MASK>(cta, i);
    const int u = i & 3;
    if ((ch >> 6) != ready) { ready = ch >> 6; if (cta < NREG) mbar_wait(p.base + SM_RDY + 8 * RDY_U, 0); else cnt_wait(g_cnt + (C_U + ready) * CSTRIDE, 128); }
    p.acquire(u, 1);
    load_conv(p, M, u, ch);
    if (i == 3) { p.acquire(4, 4); if (elect()) mbar_arrive(p.full(4)); }
  }
}
#define HOIST(v) asm volatile("" : "+r"(v))
template<int MASK> __device__ __forceinline__ void producer(const Maps& M, const Params& P, uint32_t base, int cta, int lane) {
  Prod p{base, ((MASK & PH_KV) && cta < NREG) ? 0xffffcfffu ^ ((1u << (3 * NFIRST)) - 1) : 0xffffffffu, lane,
         (cta * 3 + 2) * 2048};
  if (cta >= NREG) { if (MASK & PH_CONV) prod_conv<MASK>(p, M, cta, XFAKE ? 90 : CV_EXTRA<MASK>); return; }
  const int g = cta & 7, j = cta >> 3, rank = cta & 1;
#pragma unroll 1
  for (int half = 0; half < 2; half++) {
    const int h = j + 16 * half;
    if (MASK & PH_KV) {
      const CUtensorMap* mw = rank ? &M.wv : &M.wk;
#pragma unroll 1
      for (int it = half ? 0 : NFIRST; it < 16; it++) {
        const int u = gemm_unit(it);
        uint32_t bar = p.full(u), d0 = p.addr(u), d1 = p.addr(u + 1 + rank); int k0 = (it & 7) * 64, r0 = (2 * g + (it >> 3)) * 128;
        HOIST(bar); HOIST(d0); HOIST(d1); HOIST(k0); HOIST(r0);
        p.acquire(u, 3);
        if (elect()) {
          mbar_expect(bar, 3 * UNIT);
          tma3d_mc(d1, mw, 0, k0, 2 * h, bar, it >= 8);
          tma2d(d0, &M.c, k0, r0, bar);
        }
      }
    }
    if (MASK & PH_ATT) {
#pragma unroll 1
      for (int ks = 0; ks < 16; ks++) {
        const int u = gemm_unit(ks);
        uint32_t bar = p.full(u), d0 = p.addr(u), d1 = p.addr(u + 1), d2 = p.addr(u + 2) + rank * 8192; int k0 = ks * 64;
        HOIST(bar); HOIST(d0); HOIST(d1); HOIST(d2); HOIST(k0);
        p.acquire(u, 3);
        if (elect()) {
          mbar_expect(bar, 3 * UNIT);
          tma2d_mc(d2, &M.wq, h * 128 + rank * 64, k0, bar, true);
          tma2d(d0, &M.x, k0, (15 - g) * 128, bar);
          tma2d(d1, &M.x, k0, g * 128, bar);
        }
      }
      TS(2, 8 * half + 0);
      mbar_wait(base + SM_RDY + 8 * (RDY_KV + half), 0);
      TS(2, 8 * half + 1);
      const uint8_t* KVh = g_T + T_KV + (size_t)kv_slot<MASK>(h) * 16 * 65536;
      if (MASK & PH_PRE) mbar_wait(base + SM_RDY + 8 * RDY_AUX, 0);
      if (elect()) { mbar_expect(p.full(12), 32768); bulk_g2s(p.addr(12), KVh, 32768, p.full(12), true); }
      p.acquire(0, 4);
      if (elect()) mbar_arrive(p.full(0));
#pragma unroll 1
      for (int i = 1; i < 34; i++) {
        const int isv = !(i & 1) || i == 33, st = i == 33 ? 16 : (isv ? (i >> 1) - 1 : (i + 1) >> 1), u = 4 + 2 * (i & 3);
        const bool own = st == 15 - (g & 6);
        uint32_t bar = p.full(u), d0 = p.addr(own ? u : u + rank), off = (st <= 15 - g ? st : 16 - st) * 65536 + isv * 32768 + (own ? 0 : rank * UNIT);
        HOIST(bar); HOIST(d0); HOIST(off);
        p.acquire(u, 2);
        if (elect()) {
          mbar_expect(bar, 32768);
          if (own) bulk_g2s(d0, KVh + off, 32768, bar, true); else bulk_g2s_mc(d0, KVh + off, UNIT, bar, true);
        }
      }
    }
  }
  if ((MASK & PH_CONV) && !(MASK & PH_OUT)) prod_conv<MASK>(p, M, cta, CV_REG<MASK>);
  if (MASK & PH_OUT) {
    const int y0 = out_mb(cta) * 512 + rank * 8, z0 = 2 * out_nb(cta);
    int u = 6;
#pragma unroll 1
    for (int hf = 0; hf < 2; hf++) {
      TS(2, 16 + 2 * hf);
      mbar_wait(base + SM_RDY + 8 * (RDY_CTX + hf), 0);
      TS(2, 17 + 2 * hf);
#pragma unroll 1
      for (int n = hf * 32; n < hf * 32 + 32; n++) {
        const int ks = n == 1 ? 2 : n == 2 ? 1 : n;
        u = n == 2 ? 2 : n == 3 ? 10 : out_next(u);
        uint32_t bar = p.full(u), d0 = p.addr(u) + rank * 8192, d1 = p.addr(u + 1); int x = (ks & 1) * 256, y = y0 + (ks >> 1) * 16, k0 = ks * 64;
        HOIST(bar); HOIST(d0); HOIST(d1); HOIST(x); HOIST(y); HOIST(k0);
        p.acquire(u, 2);
        if (elect()) {
          mbar_expect(bar, 2 * UNIT);
          tma2d_mc(d0, &M.ctx, x, y, bar, true);
          tma3d(d1, &M.wo, 0, k0, z0, bar, true);
          if (ks == 1) mbar_arrive(base + SM_RDY + 8 * RDY_X);
          if (ks == Z_AT) mbar_arrive(base + SM_RDY + 8 * RDY_Z);
        }
      }
    }
  }
}
template<int MASK> __device__ __forceinline__ void producer2(const Maps& M, const Params& P, uint32_t base, int cta, int w, int lane) {
  Prod p{base, 0xffffffffu, lane, 0};
  const int mb = out_mb(cta), nb = out_nb(cta), u = 2 * w;
  if (w) { mbar_wait_slow(base + SM_RDY + 8 * RDY_X, 0); p.mask ^= 12; }
  if (MASK & PH_CONV) {
    mbar_wait_slow(base + SM_SIG + 8 * (SIG_ATT + 1), 0);
    mbar_wait_slow(base + SM_RDY + 8 * RDY_U, 0);
#pragma unroll 1
    for (int i = 0, ch = conv_channel<MASK>(cta, 3 * w); ch >= 0; i++) {
      p.acquire_slow(u, i ? 1 : 2);
      load_conv(p, M, u, ch);
      ch = i + w < 2 ? ch + 1 : -1;
      if (w > i) { mbar_wait_slow(base + SM_RDY + 8 * RDY_T, 0); ch = lds32(base + SM_POOL); }
    }
  }
  p.acquire_slow(u, 2);
  if (!w && elect()) map_pf(&M.z);
  TSA(52 - 2 * w);
  mbar_wait(base + SM_RDY + 8 * (!w ? RDY_Z : RDY_G), 0);
  TSA(53 - 2 * w);
  if (elect()) {
    const uint32_t bar = p.full(3 * w);
    mbar_expect(bar, 2 * UNIT + (!w ? 0 : 512));
    tma2d(p.addr(u), !w ? &M.z : &M.x, (!w ? mb : nb) * 128, (!w ? nb : mb) * 128, bar, true);
    tma2d(p.addr(u + 1), !w ? &M.z : &M.x, (!w ? mb : nb) * 128 + 64, (!w ? nb : mb) * 128, bar, true);
    if (w) bulk_g2s(base + SM_GATE, g_gate + mb * 128, 512, bar);
  }
}

__device__ __forceinline__ constexpr uint32_t PUB(int sig, int cnt, int n) { return 0x80000000u | (sig << 24) | (n << 8) | cnt; }
__device__ __forceinline__ constexpr uint32_t GET(int rdy, int cnt, int n) { return (rdy << 24) | (n << 8) | cnt; }
template<int MASK> __device__ __forceinline__ void sync_agent(uint32_t base, int cta, int lane) {
  if ((base & 0x3FFFF) != SMEM_BASE) asm volatile("trap;");
  const int g = cta & 7, j = cta >> 3, go = min(out_mb(cta), 15 - out_mb(cta));
  const int c0 = conv_channel<MASK>(cta, 0), c1 = c0 + CV_REG<MASK> - 1, n0 = min(CV_REG<MASK>, 128 - (c0 & 127));
  constexpr bool KV = MASK & PH_KV, ATT = MASK & PH_ATT, CONV = MASK & PH_CONV, OUT = MASK & PH_OUT, ALL = MASK == PH_ALL;
  uint32_t e = 0;
  if (cta >= NREG) { if (CONV && lane * 32 < CV_EXTRA<MASK>) e = PUB(SIG_Z + lane, C_Z + lane, min(32, CV_EXTRA<MASK> - lane * 32)); }
  else switch (lane) {
    case 0:  if (KV) e = PUB(SIG_KV, C_KV + j, 1); break;
    case 1:  if (ATT) e = GET(RDY_KV, C_KV + j, 8); break;
    case 2:  if (ALL) e = PUB(SIG_WAR, C_WAR + j, 1); break;
    case 3:  if (ATT) e = PUB(SIG_CTX, C_CTX + g, 1); break;
    case 4:  if (ALL) e = GET(RDY_WAR, C_WAR + j, 8); break;
    case 5:  if (KV) e = PUB(SIG_KV + 1, C_KV + 16 + j, 1); break;
    case 6:  if (ATT) e = GET(RDY_KV + 1, C_KV + 16 + j, 8); break;
    case 7:  if (OUT) e = GET(RDY_CTX, C_CTX + go, 16); break;
    case 8:  if (CONV) e = GET(RDY_U, C_U + (c0 >> 6), 128); break;
    case 9:  if (CONV) e = GET(ALL ? RDY_NONE : RDY_U, C_U + (ALL ? 14 : c1 >> 6), 128); break;
    case 10: if (ALL) e = GET(RDY_T, C_U + 15, 128); break;
    case 11: if (ATT) e = PUB(SIG_CTX + 1, C_CTX + 8 + g, 1); break;
    case 12: if (OUT) e = GET(RDY_CTX + 1, C_CTX + 8 + go, 16); break;
    case 13: if (OUT) e = GET(RDY_G, C_GATE, 256); break;
    case 14: if (CONV) e = PUB(SIG_Z, C_Z + (c0 >> 7), n0); break;
    case 15: if (ALL) e = PUB(SIG_Z, C_Z + 7, 1); else if (CONV && n0 < CV_REG<MASK>) e = PUB(SIG_Z, C_Z + (c1 >> 7), CV_REG<MASK> - n0); break;
    case 16: if (OUT) e = GET(RDY_Z, C_Z + out_nb(cta), 128); break;
  }
  if (ALL && lane == 0) { mbar_expect(base + SM_RDY + 8 * RDY_T, 4); mbar_arrive(base + SM_RDY + 8 * RDY_U); }
  __syncwarp();
#pragma unroll 1
  for (int i = 0; i < 17; i++) {
    const uint32_t x = __shfl_sync(~0u, e, i), id = (x >> 24) & 127, n = (x >> 8) & 0xffff;
    if (x == 0) continue;
    unsigned* cnt = g_cnt + (x & 255) * CSTRIDE;
    if (x >> 31) {
      mbar_wait_slow(base + SM_SIG + 8 * id, 0);
      const bool draw = ALL && i == 11 && !(cta & 1);
      unsigned t = 0;
      if (draw && lane == 0) asm volatile("atom.relaxed.gpu.global.add.u32 %0, [%1], 1;" : "=r"(t) : "l"(g_cnt + C_TICKET * CSTRIDE) : "memory");
      if (lane == 0 && !(ALL && i == 15 && (int)lds32(base + SM_POOL) < 0)) cnt_publish(cnt, n, i != 15);
      if (draw) {
        t = __shfl_sync(~0u, t, 0);
        uint32_t peer;
        asm volatile("mapa.shared::cluster.u32 %0, %1, %2;" : "=r"(peer) : "r"(base), "r"(lane & 1));
        if (lane < 2) asm volatile("st.async.weak.shared::cluster.mbarrier::complete_tx::bytes.u32 [%0], %1, [%2];"
          :: "r"(peer + SM_POOL), "r"(t < 64 - NSKIP ? CV_POOL + 2 * t + lane : ~0u), "r"(peer + SM_RDY + 8 * RDY_T) : "memory");
      }
    } else {
      cnt_wait(cnt, n);
      if (id < 2) {
        const float4 kn = __ldcg((const float4*)(g_kn2 + kv_slot<MASK>(j + 16 * id) * 128) + lane);
        const uint32_t m = __reduce_max_sync(~0u, max(max(__float_as_uint(kn.x), __float_as_uint(kn.y)), max(__float_as_uint(kn.z), __float_as_uint(kn.w))));
        if (lane == 0) asm volatile("st.shared.u32 [%0], %1;" :: "r"(base + SM_KMAX + 4 * id), "r"(m) : "memory");
      }
      if (lane == 0) mbar_arrive(base + SM_RDY + 8 * id);
    }
    __syncwarp();
  }
}

__device__ __forceinline__ void aux_gate(const Params& P, int cta, int aw, int lane) {
  uint4 gw[4];
#pragma unroll
  for (int i = 0; i < 4; i++) gw[i] = __ldg((const uint4*)P.gw + i * 32 + lane);
#pragma unroll 1
  for (int row = cta * 16 + aw * 8; row < cta * 16 + aw * 8 + 8; row++) {
    float a = 0.f;
#pragma unroll
    for (int i = 0; i < 4; i++) {
      const uint4 xv = __ldg((const uint4*)(P.x + (size_t)row * 1024) + i * 32 + lane);
      uint32_t m;
      m = hmul2(xv.x, gw[i].x); a += bf_lo(m) + bf_hi(m); m = hmul2(xv.y, gw[i].y); a += bf_lo(m) + bf_hi(m);
      m = hmul2(xv.z, gw[i].z); a += bf_lo(m) + bf_hi(m); m = hmul2(xv.w, gw[i].w); a += bf_lo(m) + bf_hi(m);
    }
#pragma unroll
    for (int o = 16; o > 0; o >>= 1) a += __shfl_xor_sync(~0u, a, o);
    a = bf_lo(pack_bf16(a, 0.f));
    const float gt = bf_lo(pack_bf16(__fdividef(1.f, 1.f + ex2(-a * 1.4426950408889634f)), 0.f));
    if (lane == 0) g_gate[row] = gt;
    __nanosleep(GATE_SLEEP);
  }
  cnt_signal(g_cnt + C_GATE * CSTRIDE, lane);
  if (aw == 0) { TSA(44); }
}
template<int MASK> __device__ __forceinline__ void aux_pre(const Maps& M, const Params& P, uint32_t base, int cta, int aw, int lane) {
  const uint32_t kb = base + 12 * UNIT, bar = base + SM_PRE;
  const int r = lane >> 2, q = lane & 3;
  const int mi = lane >> 3, row0 = (lane & 6) + 1 - (lane & 1);
  const int ra = (mi * 9 + 1) * 2 + row0;
  const int rb = (mi == 0 ? 3 : mi) * 18 + row0;
#pragma unroll 1
  for (int it = 0; it < (cta < 96 ? 5 : 4); it++) {
    if (it == PRE_EARLY && MASK == PH_ALL) { mbar_wait_slow(base + SM_SIG + 8 * SIG_ATT, 0); aux_gate(P, cta, aw, lane); }
    if (it == PRE_EARLY && MASK == PH_ALL) mbar_wait_slow(base + SM_SIG + 8 * (SIG_ATT + 1), 0);
    const int cg = it ? it * 4 - 3 + (cta >> 5) : 0, tb = cta & 31;
    if (it == 0 && aw == 0) TSA(45);
    if (aw == 0 && !((R0 & 4) && it == 0) && elect()) {
      mbar_expect(bar, 2 * 9216);
      tma4d(kb, &M.k, cg * 64, 0, tb * 8 - 1, 0, bar, true);
      tma4d(kb + 9216, &M.v, cg * 64, 0, tb * 8 - 1, 0, bar, true);
    }
    const uint2 swl = __ldg((const uint2*)(P.shift + (cg * 64 + aw * 32 + lane) * 4));
    if (tb == 0) {
      uint8_t* e = g_u + (size_t)(cg * 64 + aw * 32 + lane) * UCH + 4096;
      *(uint4*)e = make_uint4(0, 0, 0, 0); *(uint4*)(e + UPITCH) = make_uint4(0, 0, 0, 0);
      *(uint32_t*)(e + 32) = (uint32_t)__bfloat16_as_ushort(P.D[cg * 64 + aw * 32 + lane]) * 0x10001u;
    }
    if (it == 0 && aw == 0) TSA(46);
    if ((R0 & 2) && it == 0) mbar_wait(bar, 0); else mbar_wait_slow(bar, it & 1);
    if (it == 0 && aw == 0) TSA(47);
#pragma unroll 1
    for (int ol = it ? 0 : cta >> 5; ol < (it ? 4 : (cta >> 5) + 1); ol++) {
      const int oc = aw * 4 + ol;
      const uint32_t s01 = __shfl_sync(~0u, swl.x, ol * 8 + r), s23 = __shfl_sync(~0u, swl.y, ol * 8 + r);
      const uint32_t w0 = __byte_perm(s01, 0, 0x1010), w1 = __byte_perm(s01, 0, 0x3232), w2 = __byte_perm(s23, 0, 0x1010), w3 = __byte_perm(s23, 0, 0x3232);
      const uint32_t pa = kb + ra * 128 + ((oc ^ (ra & 7)) << 4), pb = kb + (mi == 0 ? 9216 : 0) + rb * 128 + ((oc ^ (rb & 7)) << 4);
      uint8_t* e0 = g_u + (uint32_t)((cg * 64 + oc * 8 + r) * UCH + (2040 - tb * 64 - 8 * q) * 2);
#pragma unroll
      for (int hb = 0; hb < 2; hb++) {
        uint32_t k[7], v[5];
        ldsm4t(pa + hb * 1024, k[3], k[4], k[5], k[6]);
        ldsm4t(pa + hb * 1024 + 9216, v[1], v[2], v[3], v[4]);
        ldsm4t(pb + hb * 1024, v[0], k[0], k[1], k[2]);
        uint32_t o1 = __byte_perm(k[1], k[0], 0x5432);
#pragma unroll
        for (int m = 0; m < 5; m++) {
          const uint32_t o2 = __byte_perm(k[m + 2], k[m + 1], 0x5432);
          v[m] = hmul2(hadd2(hadd2(hadd2(hmul2(o1, w3), hmul2(k[m + 1], w2)), hmul2(o2, w1)), hmul2(k[m + 2], w0)), v[m]);
          o1 = o2;
        }
        *(uint4*)(e0 - hb * 64) = make_uint4(v[4], v[3], v[2], v[1]);
        *(uint4*)(e0 - hb * 64 + UPITCH) = make_uint4(__byte_perm(v[4], v[3], 0x5432), __byte_perm(v[3], v[2], 0x5432), __byte_perm(v[2], v[1], 0x5432), __byte_perm(v[1], v[0], 0x5432));
        if (it >= PRE_EARLY) __nanosleep(PRE_SLEEP);
      }
    }
    bar_sync(5, 64);
    if (aw == 0) { TSA(40 + min(it, 3)); }
    if (it == PRE_EARLY - 1 && aw == 0 && lane == 0) mbar_arrive(base + SM_RDY + 8 * RDY_AUX);
    if (aw == 1 && lane == 0) asm volatile("red.release.gpu.global.add.u32 [%0], %1;" :: "l"(g_cnt + (C_U + cg) * CSTRIDE), "r"(it ? 4 : 1) : "memory");
    if (it == 0 && aw == 1) TSA(48);
  }
  uint32_t rel;
  asm volatile("mapa.shared::cluster.u32 %0, %1, %2;" : "=r"(rel) : "r"(base + SM_BAR + 128 + 8 * (12 + (lane & 1))), "r"((lane >> 1) & 1));
  if (lane < 4) asm volatile("mbarrier.arrive.shared::cluster.b64 _, [%0];" :: "r"(rel) : "memory");
  if (MASK != PH_ALL) aux_gate(P, cta, aw, lane);
}

template<int MASK> __global__ void __cluster_dims__(2, 1, 1) __launch_bounds__(384, 1) gated_mix_kernel(const __grid_constant__ Maps M, const __grid_constant__ Params P) {
  extern __shared__ __align__(1024) uint8_t smem[];
  const uint32_t base = (uint32_t)__cvta_generic_to_shared(smem);
  if ((MASK & PH_KV) && elect()) {
    map_pf(&M.wk + (blockIdx.x & 1)); map_pf(&M.c);
  }
  const int wi = __shfl_sync(~0u, threadIdx.x >> 5, 0), wg = wi >> 2, warp = wi & 3;
  if (elect()) {
    if (wi < 8) {
      const int cnt = 1 << ((0x10332200 >> (4 * wi)) & 15);
#pragma unroll
      for (int i = 0; i < 8; i++) mbar_init(base + SM_BAR + 64 * wi + 8 * i, cnt);
      asm volatile("fence.mbarrier_init.release.cluster;" ::: "memory");
    } else if ((R0 & 1) && wi >= 10) map_pf(&M.k + (wi & 1));
  }
  const int cta = blockIdx.x;
  const bool first_loads = (MASK & PH_KV) && wi == 8 && cta < NREG;
  const CUtensorMap* mw = (cta & 1) ? &M.wv : &M.wk;
  __syncwarp();
  asm volatile("barrier.cluster.arrive.relaxed.aligned;\nbarrier.cluster.wait.aligned;" ::: "memory");
  auto first_stage = [&](int it) {
    const uint32_t bar = base + SM_BAR + 24 * it, d0 = base + 3 * it * UNIT;
    mbar_expect(bar, 3 * UNIT);
    tma3d_mc(d0 + (1 + (cta & 1)) * UNIT, mw, 0, it * 64, 2 * (cta >> 3), bar);
    tma2d(d0, &M.c, it * 64, (cta & 7) * 256, bar);
  };
  if (first_loads && elect()) first_stage(0);
  __syncwarp();
  const int lane = threadIdx.x & 31;
#define TS_PRO()
  if (wg == 2) {
    asm volatile("setmaxnreg.dec.sync.aligned.u32 56;");
    TS_PRO();
    TS(2, 62);
    if (warp == 0) producer<MASK>(M, P, base, cta, lane);
    else if (warp == 1) sync_agent<MASK>(base, cta, lane);
    else if (cta < NREG) {
      if (MASK & PH_PRE) aux_pre<MASK>(M, P, base, cta, warp - 2, lane);
      if (MASK & PH_OUT) producer2<MASK>(M, P, base, cta, warp - 2, lane);
    }
    if (warp == 1) {
      if (MASK & PH_OUT) {
        unsigned old = 0;
        if (lane == 0) asm volatile("atom.relaxed.gpu.global.add.u32 %0, [%1], 1;" : "=r"(old) : "l"(g_cnt + C_EXIT * CSTRIDE) : "memory");
        old = __shfl_sync(~0u, old, 0);
        if (old == NCTA - 1) for (int i = lane; i < C_NUM; i += 32) g_cnt[i * CSTRIDE] = 0;
      }
      mbar_wait_slow(base + SM_SIG + 8 * SIG_DONE, 0);
      if (cta >= NREG || !(MASK & PH_OUT)) { cluster_arrive(); cluster_wait(); }
    }
  } else {
    asm volatile("setmaxnreg.inc.sync.aligned.u32 224;");
    TS_PRO();
    uint32_t rel;
    asm volatile("mapa.shared::cluster.u32 %0, %1, %2;" : "=r"(rel) : "r"(base + SM_BAR + 128 + 8 * (lane & 15)), "r"(lane >> 4));
    Cons c{base, rel, 0u, lane, warp, wg, warp == 3 ? lane & 15 : 16, (cta * 3 + wg) * 2048};
    if (wg == 1) bar_arrive(1, 256);
    if ((MASK & PH_KV) && wi == 4 && cta < NREG) {
      if (elect()) {
#pragma unroll 1
        for (int it = 1; it < NFIRST; it++) {
          asm volatile("{\n.reg .pred p;\n.reg .u32 a, b;\nmov.u32 a, %%clock;\nXL:\nmov.u32 b, %%clock;\nsub.u32 b, b, a;\nsetp.lt.u32 p, b, %0;\n@p bra XL;\n}\n" :: "r"(it == 1 ? FGAP : FGAP2) : "memory");
          first_stage(it);
          if ((R0 & 4) && it == R0_AT) {
            mbar_expect(base + SM_PRE, 2 * 9216);
            tma4d(base + 12 * UNIT, &M.k, 0, 0, (cta & 31) * 8 - 1, 0, base + SM_PRE, true);
            tma4d(base + 12 * UNIT + 9216, &M.v, 0, 0, (cta & 31) * 8 - 1, 0, base + SM_PRE, true);
          }
        }
      }
      __syncwarp();
    }
    TS(wg, 0);
    if (cta < NREG) {
      const int g = cta & 7, j = cta >> 3;
      Pend w = {};
#pragma unroll 1
      for (int half = 0; half < 2; half++) {
        const int h = j + 16 * half, blk = kv_slot<MASK>(h) * 16 + 2 * g;
        if (MASK & PH_KV) cons_kv<(MASK & PH_ATT) != 0>(c, h, blk, g, w, half == 1 && (MASK & PH_ATT));
        TS(wg, 1 + 4 * half);
        if (MASK & PH_ATT) {
          Att a;
          cons_q<(MASK & PH_KV) != 0>(c, h, blk + 1, w, a.o);
          TS(wg, 2 + 4 * half);
          cons_att(c, a, h, g, w);
          if (half == 0) c.signal(SIG_WAR);
#pragma unroll
          for (int i = 0; i < 8; i++) w.hi[i] = make_uint4(0, 0, 0, 0);
          TS(wg, 3 + 4 * half);
          if (MASK != PH_ALL) { tile_store<0, 4>(w.lo, ctx_off(c, h, g, 1 - wg), lane); c.signal(SIG_CTX + half); }
        } else if (MASK & PH_KV) {
          float kn = 0.f;
          out_piece<SCH_KV, true>(c, w, kv_off(c, blk + 1), blk + 1, kn, 0, true);
          for (int ks = 1; ks < 8; ks++) out_piece<SCH_KV, false>(c, w, kv_off(c, blk + 1), blk + 1, kn, ks, true);
          c.signal(SIG_KV + half);
        }
      }
      if (MASK & PH_OUT) cons_out<MASK>(c, M, P, cta, w);
    }
    if (cta >= NREG || !(MASK & PH_OUT)) {
      if (MASK & PH_CONV) cons_conv<MASK>(c, cta, cta < NREG ? CV_REG<MASK> : XFAKE ? 90 : CV_EXTRA<MASK>);
      TS(wg, 9);
      c.signal(SIG_DONE);
      cluster_arrive();
    }
    TS(wg, 10);
  }
}

typedef CUresult (*EncFn)(CUtensorMap*, CUtensorMapDataType, cuuint32_t, void*, const cuuint64_t*, const cuuint64_t*, const cuuint32_t*, const cuuint32_t*,
                          CUtensorMapInterleave, CUtensorMapSwizzle, CUtensorMapL2promotion, CUtensorMapFloatOOBfill);
static void enc(EncFn f, CUtensorMap* m, const void* ptr, int rank, const cuuint64_t* dims, const cuuint64_t* strides, const cuuint32_t* box, CUtensorMapSwizzle sw,
                CUtensorMapDataType dt = CU_TENSOR_MAP_DATA_TYPE_BFLOAT16) {
  const cuuint32_t es[4] = {1, 1, 1, 1};
  f(m, dt, rank, (void*)ptr, dims, strides, box, es, CU_TENSOR_MAP_INTERLEAVE_NONE, sw, CU_TENSOR_MAP_L2_PROMOTION_L2_256B, CU_TENSOR_MAP_FLOAT_OOB_FILL_NONE);
}
static void enc2(EncFn f, CUtensorMap* m, const void* ptr, int cols, int rows, int brows) {
  const cuuint64_t d[2] = {(cuuint64_t)cols, (cuuint64_t)rows}, s[1] = {(cuuint64_t)cols * 2}; const cuuint32_t b[2] = {64, (cuuint32_t)brows};
  enc(f, m, ptr, 2, d, s, b, CU_TENSOR_MAP_SWIZZLE_128B);
}
static void encw(EncFn f, CUtensorMap* m, const void* ptr, int cols, int rows) {
  const cuuint64_t d[3] = {64, (cuuint64_t)rows, (cuuint64_t)cols / 64}, s[2] = {(cuuint64_t)cols * 2, 128}; const cuuint32_t b[3] = {64, 64, 2};
  enc(f, m, ptr, 3, d, s, b, CU_TENSOR_MAP_SWIZZLE_128B);
}
extern "C" void kernel_launch(void* const* d_in, const int* in_sizes, int n_in, void* d_out, int out_size) {
  static EncFn fn = nullptr;
  static int ncl = 0;
  static void* zptr = nullptr;
  static void* tptr = nullptr;
  if (!fn) {
    void* p = nullptr; cudaDriverEntryPointQueryResult qr;
    cudaGetDriverEntryPoint("cuTensorMapEncodeTiled", &p, cudaEnableDefault, &qr);
    fn = (EncFn)p;
    cudaFuncSetAttribute(gated_mix_kernel<PH_ALL>, cudaFuncAttributeMaxDynamicSharedMemorySize, SMEM_BYTES);
    cudaFuncSetAttribute(gated_mix_kernel<PH_PRE | PH_KV>, cudaFuncAttributeMaxDynamicSharedMemorySize, SMEM_BYTES);
    cudaFuncSetAttribute(gated_mix_kernel<PH_ATT | PH_CONV>, cudaFuncAttributeMaxDynamicSharedMemorySize, SMEM_BYTES);
    cudaFuncSetAttribute(gated_mix_kernel<PH_OUT>, cudaFuncAttributeMaxDynamicSharedMemorySize, SMEM_BYTES);
    cudaLaunchConfig_t cfg = {}; cfg.gridDim = NCTA; cfg.blockDim = 384; cfg.dynamicSmemBytes = SMEM_BYTES;
    cudaLaunchAttribute at; at.id = cudaLaunchAttributeClusterDimension; at.val.clusterDim.x = 2; at.val.clusterDim.y = 1; at.val.clusterDim.z = 1;
    cfg.attrs = &at; cfg.numAttrs = 1;
    cudaOccupancyMaxActiveClusters(&ncl, gated_mix_kernel<PH_ALL>, &cfg);
    cudaGetSymbolAddress(&zptr, g_u);
    cudaGetSymbolAddress(&tptr, g_T);
  }
  Maps M;
  enc2(fn, &M.x, d_in[0], 1024, 2048, 128);
  enc2(fn, &M.c, d_in[7], 512, 2048, 128);
  enc2(fn, &M.wq, d_in[8], 4096, 1024, 64);
  encw(fn, &M.wk, d_in[9], 4096, 512);
  encw(fn, &M.wv, d_in[10], 4096, 512);
  encw(fn, &M.wo, d_in[11], 1024, 4096);
  { const cuuint64_t d[3] = {64, 32, 1024}, s[2] = {128, 4096}; const cuuint32_t b[3] = {64, 40, 1}; enc(fn, &M.h, d_in[4], 3, d, s, b, CU_TENSOR_MAP_SWIZZLE_NONE); }
  { const cuuint64_t d[2] = {2048, 1024}, s[1] = {UCH}; const cuuint32_t b[2] = {64, 128}; enc(fn, &M.z, zptr, 2, d, s, b, CU_TENSOR_MAP_SWIZZLE_128B); }
  { const cuuint64_t d[2] = {512, 512 * 16}, s[1] = {2048}; const cuuint32_t b[2] = {256, 8};
    enc(fn, &M.ctx, tptr, 2, d, s, b, CU_TENSOR_MAP_SWIZZLE_NONE, CU_TENSOR_MAP_DATA_TYPE_UINT32); }
  { const cuuint64_t d[4] = {1024, 2, 256, 4}, s[3] = {2048, 16384, 4096}; const cuuint32_t b[4] = {64, 2, 9, 4};
    enc(fn, &M.k, d_in[1], 4, d, s, b, CU_TENSOR_MAP_SWIZZLE_128B); enc(fn, &M.v, d_in[2], 4, d, s, b, CU_TENSOR_MAP_SWIZZLE_128B); }
  Params P{(const __nv_bfloat16*)d_in[0], (const __nv_bfloat16*)d_in[3],
           (const __nv_bfloat16*)d_in[5], (const __nv_bfloat16*)d_in[12], (__nv_bfloat16*)d_out};
  bool split = 2 * ncl < NCTA;
  if (!split) {
    gated_mix_kernel<PH_ALL><<<NCTA, 384, SMEM_BYTES>>>(M, P);
  } else {
    gated_mix_kernel<PH_PRE | PH_KV><<<NCTA, 384, SMEM_BYTES>>>(M, P);
    gated_mix_kernel<PH_ATT | PH_CONV><<<NCTA, 384, SMEM_BYTES>>>(M, P);
    gated_mix_kernel<PH_OUT><<<NCTA, 384, SMEM_BYTES>>>(M, P);
  }
}
```

```cpp
#include <cuda_runtime.h>
#include <cuda.h>
#include <cuda_bf16.h>
#include <stdint.h>

template<int TB> __device__ __forceinline__ void wgmma_ss_n256(float (&d)[128], uint64_t da, uint64_t db, int scale_d) {
  asm volatile("{\n.reg .pred p;\nsetp.ne.b32 p, %130, 0;\n"
    "wgmma.mma_async.sync.aligned.m64n256k16.f32.bf16.bf16 {%0, %1, %2, %3, %4, %5, %6, %7, %8, %9, %10, %11, %12, %13, %14, %15, %16, %17, %18, %19, %20, %21, %22, %23, %24, %25, %26, %27, %28, %29, %30, %31, %32, %33, %34, %35, %36, %37, %38, %39, %40, %41, %42, %43, %44, %45, %46, %47, %48, %49, %50, %51, %52, %53, %54, %55, %56, %57, %58, %59, %60, %61, %62, %63, %64, %65, %66, %67, %68, %69, %70, %71, %72, %73, %74, %75, %76, %77, %78, %79, %80, %81, %82, %83, %84, %85, %86, %87, %88, %89, %90, %91, %92, %93, %94, %95, %96, %97, %98, %99, %100, %101, %102, %103, %104, %105, %106, %107, %108, %109, %110, %111, %112, %113, %114, %115, %116, %117, %118, %119, %120, %121, %122, %123, %124, %125, %126, %127}, %128, %129, p, 1, 1, 0, %131;\n}\n"
    : "+f"(d[0]), "+f"(d[1]), "+f"(d[2]), "+f"(d[3]), "+f"(d[4]), "+f"(d[5]), "+f"(d[6]), "+f"(d[7]), "+f"(d[8]), "+f"(d[9]), "+f"(d[10]), "+f"(d[11]), "+f"(d[12]), "+f"(d[13]), "+f"(d[14]), "+f"(d[15]), "+f"(d[16]), "+f"(d[17]), "+f"(d[18]), "+f"(d[19]), "+f"(d[20]), "+f"(d[21]), "+f"(d[22]), "+f"(d[23]), "+f"(d[24]), "+f"(d[25]), "+f"(d[26]), "+f"(d[27]), "+f"(d[28]), "+f"(d[29]), "+f"(d[30]), "+f"(d[31]), "+f"(d[32]), "+f"(d[33]), "+f"(d[34]), "+f"(d[35]), "+f"(d[36]), "+f"(d[37]), "+f"(d[38]), "+f"(d[39]), "+f"(d[40]), "+f"(d[41]), "+f"(d[42]), "+f"(d[43]), "+f"(d[44]), "+f"(d[45]), "+f"(d[46]), "+f"(d[47]), "+f"(d[48]), "+f"(d[49]), "+f"(d[50]), "+f"(d[51]), "+f"(d[52]), "+f"(d[53]), "+f"(d[54]), "+f"(d[55]), "+f"(d[56]), "+f"(d[57]), "+f"(d[58]), "+f"(d[59]), "+f"(d[60]), "+f"(d[61]), "+f"(d[62]), "+f"(d[63]), "+f"(d[64]), "+f"(d[65]), "+f"(d[66]), "+f"(d[67]), "+f"(d[68]), "+f"(d[69]), "+f"(d[70]), "+f"(d[71]), "+f"(d[72]), "+f"(d[73]), "+f"(d[74]), "+f"(d[75]), "+f"(d[76]), "+f"(d[77]), "+f"(d[78]), "+f"(d[79]), "+f"(d[80]), "+f"(d[81]), "+f"(d[82]), "+f"(d[83]), "+f"(d[84]), "+f"(d[85]), "+f"(d[86]), "+f"(d[87]), "+f"(d[88]), "+f"(d[89]), "+f"(d[90]), "+f"(d[91]), "+f"(d[92]), "+f"(d[93]), "+f"(d[94]), "+f"(d[95]), "+f"(d[96]), "+f"(d[97]), "+f"(d[98]), "+f"(d[99]), "+f"(d[100]), "+f"(d[101]), "+f"(d[102]), "+f"(d[103]), "+f"(d[104]), "+f"(d[105]), "+f"(d[106]), "+f"(d[107]), "+f"(d[108]), "+f"(d[109]), "+f"(d[110]), "+f"(d[111]), "+f"(d[112]), "+f"(d[113]), "+f"(d[114]), "+f"(d[115]), "+f"(d[116]), "+f"(d[117]), "+f"(d[118]), "+f"(d[119]), "+f"(d[120]), "+f"(d[121]), "+f"(d[122]), "+f"(d[123]), "+f"(d[124]), "+f"(d[125]), "+f"(d[126]), "+f"(d[127])
    : "l"(da), "l"(db), "r"(scale_d), "n"(TB));
}
template<int TB> __device__ __forceinline__ void wgmma_ss_n128(float (&d)[64], uint64_t da, uint64_t db, int scale_d) {
  asm volatile("{\n.reg .pred p;\nsetp.ne.b32 p, %66, 0;\n"
    "wgmma.mma_async.sync.aligned.m64n128k16.f32.bf16.bf16 {%0, %1, %2, %3, %4, %5, %6, %7, %8, %9, %10, %11, %12, %13, %14, %15, %16, %17, %18, %19, %20, %21, %22, %23, %24, %25, %26, %27, %28, %29, %30, %31, %32, %33, %34, %35, %36, %37, %38, %39, %40, %41, %42, %43, %44, %45, %46, %47, %48, %49, %50, %51, %52, %53, %54, %55, %56, %57, %58, %59, %60, %61, %62, %63}, %64, %65, p, 1, 1, 0, %67;\n}\n"
    : "+f"(d[0]), "+f"(d[1]), "+f"(d[2]), "+f"(d[3]), "+f"(d[4]), "+f"(d[5]), "+f"(d[6]), "+f"(d[7]), "+f"(d[8]), "+f"(d[9]), "+f"(d[10]), "+f"(d[11]), "+f"(d[12]), "+f"(d[13]), "+f"(d[14]), "+f"(d[15]), "+f"(d[16]), "+f"(d[17]), "+f"(d[18]), "+f"(d[19]), "+f"(d[20]), "+f"(d[21]), "+f"(d[22]), "+f"(d[23]), "+f"(d[24]), "+f"(d[25]), "+f"(d[26]), "+f"(d[27]), "+f"(d[28]), "+f"(d[29]), "+f"(d[30]), "+f"(d[31]), "+f"(d[32]), "+f"(d[33]), "+f"(d[34]), "+f"(d[35]), "+f"(d[36]), "+f"(d[37]), "+f"(d[38]), "+f"(d[39]), "+f"(d[40]), "+f"(d[41]), "+f"(d[42]), "+f"(d[43]), "+f"(d[44]), "+f"(d[45]), "+f"(d[46]), "+f"(d[47]), "+f"(d[48]), "+f"(d[49]), "+f"(d[50]), "+f"(d[51]), "+f"(d[52]), "+f"(d[53]), "+f"(d[54]), "+f"(d[55]), "+f"(d[56]), "+f"(d[57]), "+f"(d[58]), "+f"(d[59]), "+f"(d[60]), "+f"(d[61]), "+f"(d[62]), "+f"(d[63])
    : "l"(da), "l"(db), "r"(scale_d), "n"(TB));
}
template<int TB> __device__ __forceinline__ void wgmma_rs_n32(float (&d)[16], uint32_t a0, uint32_t a1, uint32_t a2, uint32_t a3, uint64_t db, int scale_d) {
  asm volatile("{\n.reg .pred p;\nsetp.ne.b32 p, %21, 0;\n"
    "wgmma.mma_async.sync.aligned.m64n32k16.f32.bf16.bf16 {%0, %1, %2, %3, %4, %5, %6, %7, %8, %9, %10, %11, %12, %13, %14, %15}, {%16, %17, %18, %19}, %20, p, 1, 1, %22;\n}\n"
    : "+f"(d[0]), "+f"(d[1]), "+f"(d[2]), "+f"(d[3]), "+f"(d[4]), "+f"(d[5]), "+f"(d[6]), "+f"(d[7]), "+f"(d[8]), "+f"(d[9]), "+f"(d[10]), "+f"(d[11]), "+f"(d[12]), "+f"(d[13]), "+f"(d[14]), "+f"(d[15])
    : "r"(a0), "r"(a1), "r"(a2), "r"(a3), "l"(db), "r"(scale_d), "n"(TB));
}
__device__ __forceinline__ void wgmma_pv_sel(float (&d)[64], const uint32_t (&p)[32], uint64_t db, int full, int acc, int wg) {
  asm volatile("{\n.reg .pred q, s, w;\n.reg .b64 t;\nsetp.eq.b32 w, %99, 0;\nsetp.ne.b32 s, %98, 0;\nsetp.eq.b32 q, %97, 0;\n@q bra.uni LH;\n"
    "wgmma.fence.sync.aligned;\n"
    "add.s64 t, %96, 0;\nwgmma.mma_async.sync.aligned.m64n128k16.f32.bf16.bf16 {%0, %1, %2, %3, %4, %5, %6, %7, %8, %9, %10, %11, %12, %13, %14, %15, %16, %17, %18, %19, %20, %21, %22, %23, %24, %25, %26, %27, %28, %29, %30, %31, %32, %33, %34, %35, %36, %37, %38, %39, %40, %41, %42, %43, %44, %45, %46, %47, %48, %49, %50, %51, %52, %53, %54, %55, %56, %57, %58, %59, %60, %61, %62, %63}, {%64, %65, %66, %67}, t, s, 1, 1, 1;\n"
    "add.s64 t, %96, 256;\nwgmma.mma_async.sync.aligned.m64n128k16.f32.bf16.bf16 {%0, %1, %2, %3, %4, %5, %6, %7, %8, %9, %10, %11, %12, %13, %14, %15, %16, %17, %18, %19, %20, %21, %22, %23, %24, %25, %26, %27, %28, %29, %30, %31, %32, %33, %34, %35, %36, %37, %38, %39, %40, %41, %42, %43, %44, %45, %46, %47, %48, %49, %50, %51, %52, %53, %54, %55, %56, %57, %58, %59, %60, %61, %62, %63}, {%68, %69, %70, %71}, t, 1, 1, 1, 1;\n"
    "add.s64 t, %96, 512;\nwgmma.mma_async.sync.aligned.m64n128k16.f32.bf16.bf16 {%0, %1, %2, %3, %4, %5, %6, %7, %8, %9, %10, %11, %12, %13, %14, %15, %16, %17, %18, %19, %20, %21, %22, %23, %24, %25, %26, %27, %28, %29, %30, %31, %32, %33, %34, %35, %36, %37, %38, %39, %40, %41, %42, %43, %44, %45, %46, %47, %48, %49, %50, %51, %52, %53, %54, %55, %56, %57, %58, %59, %60, %61, %62, %63}, {%72, %73, %74, %75}, t, 1, 1, 1, 1;\n"
    "add.s64 t, %96, 768;\nwgmma.mma_async.sync.aligned.m64n128k16.f32.bf16.bf16 {%0, %1, %2, %3, %4, %5, %6, %7, %8, %9, %10, %11, %12, %13, %14, %15, %16, %17, %18, %19, %20, %21, %22, %23, %24, %25, %26, %27, %28, %29, %30, %31, %32, %33, %34, %35, %36, %37, %38, %39, %40, %41, %42, %43, %44, %45, %46, %47, %48, %49, %50, %51, %52, %53, %54, %55, %56, %57, %58, %59, %60, %61, %62, %63}, {%76, %77, %78, %79}, t, 1, 1, 1, 1;\n"
    "add.s64 t, %96, 1024;\nwgmma.mma_async.sync.aligned.m64n128k16.f32.bf16.bf16 {%0, %1, %2, %3, %4, %5, %6, %7, %8, %9, %10, %11, %12, %13, %14, %15, %16, %17, %18, %19, %20, %21, %22, %23, %24, %25, %26, %27, %28, %29, %30, %31, %32, %33, %34, %35, %36, %37, %38, %39, %40, %41, %42, %43, %44, %45, %46, %47, %48, %49, %50, %51, %52, %53, %54, %55, %56, %57, %58, %59, %60, %61, %62, %63}, {%80, %81, %82, %83}, t, 1, 1, 1, 1;\n"
    "add.s64 t, %96, 1280;\nwgmma.mma_async.sync.aligned.m64n128k16.f32.bf16.bf16 {%0, %1, %2, %3, %4, %5, %6, %7, %8, %9, %10, %11, %12, %13, %14, %15, %16, %17, %18, %19, %20, %21, %22, %23, %24, %25, %26, %27, %28, %29, %30, %31, %32, %33, %34, %35, %36, %37, %38, %39, %40, %41, %42, %43, %44, %45, %46, %47, %48, %49, %50, %51, %52, %53, %54, %55, %56, %57, %58, %59, %60, %61, %62, %63}, {%84, %85, %86, %87}, t, 1, 1, 1, 1;\n"
    "@w bar.arrive 2, 256;\n@!w bar.arrive 1, 256;\n"
    "add.s64 t, %96, 1536;\nwgmma.mma_async.sync.aligned.m64n128k16.f32.bf16.bf16 {%0, %1, %2, %3, %4, %5, %6, %7, %8, %9, %10, %11, %12, %13, %14, %15, %16, %17, %18, %19, %20, %21, %22, %23, %24, %25, %26, %27, %28, %29, %30, %31, %32, %33, %34, %35, %36, %37, %38, %39, %40, %41, %42, %43, %44, %45, %46, %47, %48, %49, %50, %51, %52, %53, %54, %55, %56, %57, %58, %59, %60, %61, %62, %63}, {%88, %89, %90, %91}, t, 1, 1, 1, 1;\n"
    "add.s64 t, %96, 1792;\nwgmma.mma_async.sync.aligned.m64n128k16.f32.bf16.bf16 {%0, %1, %2, %3, %4, %5, %6, %7, %8, %9, %10, %11, %12, %13, %14, %15, %16, %17, %18, %19, %20, %21, %22, %23, %24, %25, %26, %27, %28, %29, %30, %31, %32, %33, %34, %35, %36, %37, %38, %39, %40, %41, %42, %43, %44, %45, %46, %47, %48, %49, %50, %51, %52, %53, %54, %55, %56, %57, %58, %59, %60, %61, %62, %63}, {%92, %93, %94, %95}, t, 1, 1, 1, 1;\n"
    "wgmma.commit_group.sync.aligned;\n"
    "bra.uni LE;\nLH:\n"
    "wgmma.fence.sync.aligned;\n"
    "add.s64 t, %96, 0;\nwgmma.mma_async.sync.aligned.m64n128k16.f32.bf16.bf16 {%0, %1, %2, %3, %4, %5, %6, %7, %8, %9, %10, %11, %12, %13, %14, %15, %16, %17, %18, %19, %20, %21, %22, %23, %24, %25, %26, %27, %28, %29, %30, %31, %32, %33, %34, %35, %36, %37, %38, %39, %40, %41, %42, %43, %44, %45, %46, %47, %48, %49, %50, %51, %52, %53, %54, %55, %56, %57, %58, %59, %60, %61, %62, %63}, {%80, %81, %82, %83}, t, s, 1, 1, 1;\n"
    "add.s64 t, %96, 256;\nwgmma.mma_async.sync.aligned.m64n128k16.f32.bf16.bf16 {%0, %1, %2, %3, %4, %5, %6, %7, %8, %9, %10, %11, %12, %13, %14, %15, %16, %17, %18, %19, %20, %21, %22, %23, %24, %25, %26, %27, %28, %29, %30, %31, %32, %33, %34, %35, %36, %37, %38, %39, %40, %41, %42, %43, %44, %45, %46, %47, %48, %49, %50, %51, %52, %53, %54, %55, %56, %57, %58, %59, %60, %61, %62, %63}, {%84, %85, %86, %87}, t, 1, 1, 1, 1;\n"
    "@w bar.arrive 2, 256;\n@!w bar.arrive 1, 256;\n"
    "add.s64 t, %96, 512;\nwgmma.mma_async.sync.aligned.m64n128k16.f32.bf16.bf16 {%0, %1, %2, %3, %4, %5, %6, %7, %8, %9, %10, %11, %12, %13, %14, %15, %16, %17, %18, %19, %20, %21, %22, %23, %24, %25, %26, %27, %28, %29, %30, %31, %32, %33, %34, %35, %36, %37, %38, %39, %40, %41, %42, %43, %44, %45, %46, %47, %48, %49, %50, %51, %52, %53, %54, %55, %56, %57, %58, %59, %60, %61, %62, %63}, {%88, %89, %90, %91}, t, 1, 1, 1, 1;\n"
    "add.s64 t, %96, 768;\nwgmma.mma_async.sync.aligned.m64n128k16.f32.bf16.bf16 {%0, %1, %2, %3, %4, %5, %6, %7, %8, %9, %10, %11, %12, %13, %14, %15, %16, %17, %18, %19, %20, %21, %22, %23, %24, %25, %26, %27, %28, %29, %30, %31, %32, %33, %34, %35, %36, %37, %38, %39, %40, %41, %42, %43, %44, %45, %46, %47, %48, %49, %50, %51, %52, %53, %54, %55, %56, %57, %58, %59, %60, %61, %62, %63}, {%92, %93, %94, %95}, t, 1, 1, 1, 1;\n"
    "wgmma.commit_group.sync.aligned;\n"
    "LE:\n}\n"
    : "+f"(d[0]), "+f"(d[1]), "+f"(d[2]), "+f"(d[3]), "+f"(d[4]), "+f"(d[5]), "+f"(d[6]), "+f"(d[7]), "+f"(d[8]), "+f"(d[9]), "+f"(d[10]), "+f"(d[11]), "+f"(d[12]), "+f"(d[13]), "+f"(d[14]), "+f"(d[15]), "+f"(d[16]), "+f"(d[17]), "+f"(d[18]), "+f"(d[19]), "+f"(d[20]), "+f"(d[21]), "+f"(d[22]), "+f"(d[23]), "+f"(d[24]), "+f"(d[25]), "+f"(d[26]), "+f"(d[27]), "+f"(d[28]), "+f"(d[29]), "+f"(d[30]), "+f"(d[31]), "+f"(d[32]), "+f"(d[33]), "+f"(d[34]), "+f"(d[35]), "+f"(d[36]), "+f"(d[37]), "+f"(d[38]), "+f"(d[39]), "+f"(d[40]), "+f"(d[41]), "+f"(d[42]), "+f"(d[43]), "+f"(d[44]), "+f"(d[45]), "+f"(d[46]), "+f"(d[47]), "+f"(d[48]), "+f"(d[49]), "+f"(d[50]), "+f"(d[51]), "+f"(d[52]), "+f"(d[53]), "+f"(d[54]), "+f"(d[55]), "+f"(d[56]), "+f"(d[57]), "+f"(d[58]), "+f"(d[59]), "+f"(d[60]), "+f"(d[61]), "+f"(d[62]), "+f"(d[63])
    : "r"(p[0]), "r"(p[1]), "r"(p[2]), "r"(p[3]), "r"(p[4]), "r"(p[5]), "r"(p[6]), "r"(p[7]), "r"(p[8]), "r"(p[9]), "r"(p[10]), "r"(p[11]), "r"(p[12]), "r"(p[13]), "r"(p[14]), "r"(p[15]), "r"(p[16]), "r"(p[17]), "r"(p[18]), "r"(p[19]), "r"(p[20]), "r"(p[21]), "r"(p[22]), "r"(p[23]), "r"(p[24]), "r"(p[25]), "r"(p[26]), "r"(p[27]), "r"(p[28]), "r"(p[29]), "r"(p[30]), "r"(p[31]), "l"(db), "r"(full), "r"(acc), "r"(wg) : "memory");
}

constexpr int NCTA = 132, NREG = 128;
constexpr int UNIT = 16384, NUNIT = 14;
constexpr uint32_t SMEM_BASE = 1024;
constexpr int SM_BAR = NUNIT * UNIT;
constexpr int SM_GATE = SM_BAR + 1024;
constexpr int SMEM_BYTES = SM_BAR + 1536;
constexpr int UPITCH = 4160, UCH = 2 * UPITCH;
constexpr float QSCALE = 0.08838834764831845f * 1.4426950408889634f;
constexpr float BOUND2 = 60.f * 60.f / 1.15f;
#define NSKIP 8
constexpr int C_KV = 0;
constexpr int C_CTX = 32;
constexpr int C_U = 48;
constexpr int C_Z = 80;
constexpr int C_GATE = 88;
constexpr int C_EXIT = 89, C_TICKET = 90;
#define ATT_SPLIT 4
#define SL_BAR 256
#define SL_CNT 0
#define Z_AT 60
#define PRE_SLEEP 300
#define GATE_SLEEP 1000
#define OC_S0 2
#define OC_S1 11
#define OC_L0 18
#define OC_L1 18
#define ST_1 4
#define ST_D 2
#define SCH_KV 0x6665544433221100ull
#define SCH_Q 0x6665544433221100ull
#define NK_AT 1
#ifndef NV_AT
#define NV_AT 3
#endif
#define CHK_D 11
#define FGAP 600
#define FGAP2 200
constexpr int PRE_EARLY = 2, NFIRST = 4;
constexpr int C_WAR = 96;
constexpr int C_NUM = 112;
constexpr int CSTRIDE = 32;
constexpr int SM_KMAX = SM_BAR + 640, SM_DUMMY = SM_BAR + 648, SM_POOL = SM_BAR + 652, SM_PRE = SM_BAR + 112, SM_SIG = SM_BAR + 256, SM_RDY = SM_BAR + 384;
enum { SIG_KV = 0, SIG_CTX = 2, SIG_Z = 4, SIG_DONE = 8, SIG_WAR = 9, SIG_ATT = 10 };
enum { RDY_KV = 0, RDY_CTX = 2, RDY_WAR = 4, RDY_G = 5, RDY_X = 6, RDY_AUX = 7, RDY_U = 8, RDY_Z = 9, RDY_T = 10, RDY_NONE = 11 };
enum { PH_PRE = 1, PH_KV = 2, PH_ATT = 4, PH_CONV = 8, PH_OUT = 16, PH_ALL = 31 };

constexpr uint32_t T_CTX = 0, T_KV = 16 * 32 * 32768, T_BYTES = T_KV + 32 * 16 * 65536;
__device__ __align__(1024) uint8_t g_T[T_BYTES];
__device__ __align__(1024) uint8_t g_u[1024 * UCH];
__device__ __align__(1024) float g_gate[2048];
__device__ __align__(1024) float g_kn2[32 * 128];
__device__ __align__(1024) unsigned g_cnt[C_NUM * CSTRIDE];

struct __align__(64) Maps { CUtensorMap c, wk, wv, x, wq, wo, h, z, ctx, k, v; };
struct Params {
  const __nv_bfloat16 *x, *shift, *D, *gw;
  __nv_bfloat16* out;
};

__device__ __forceinline__ void wg_fence() { asm volatile("wgmma.fence.sync.aligned;" ::: "memory"); }
__device__ __forceinline__ void wg_commit() { asm volatile("wgmma.commit_group.sync.aligned;" ::: "memory"); }
template<int N> __device__ __forceinline__ void wg_wait() { asm volatile("wgmma.wait_group.sync.aligned %0;" :: "n"(N) : "memory"); }
__device__ __forceinline__ uint64_t odesc(uint32_t addr, uint32_t lbo, uint32_t sbo, uint32_t swz) {
  uint64_t d = (uint64_t)(addr >> 4) + (((uint64_t)(lbo >> 4) << 16) | ((uint64_t)(sbo >> 4) << 32) | ((uint64_t)swz << 62));
  asm volatile("" : "+l"(d));
  return d;
}
__device__ __forceinline__ void mbar_init(uint32_t bar, int cnt) { asm volatile("mbarrier.init.shared::cta.b64 [%0], %1;" :: "r"(bar), "r"(cnt)); }
__device__ __forceinline__ void mbar_expect(uint32_t bar, uint32_t bytes) { asm volatile("mbarrier.arrive.expect_tx.shared::cta.b64 _, [%0], %1;" :: "r"(bar), "r"(bytes) : "memory"); }
__device__ __forceinline__ void mbar_arrive(uint32_t bar) { asm volatile("mbarrier.arrive.shared::cta.b64 _, [%0];" :: "r"(bar) : "memory"); }
__device__ __forceinline__ void mbar_wait(uint32_t bar, uint32_t parity) {
  asm volatile("{\n.reg .pred p;\nLW:\nmbarrier.try_wait.parity.shared::cta.b64 p, [%0], %1;\n@!p bra LW;\n}\n" :: "r"(bar), "r"(parity) : "memory");
}
__device__ __forceinline__ void mbar_wait_slow(uint32_t bar, uint32_t parity) {
  asm volatile("{\n.reg .pred p;\n.reg .u32 n;\nmov.u32 n, 0;\n"
    "LW:\nmbarrier.test_wait.parity.shared::cta.b64 p, [%0], %1;\n@p bra LD;\n"
    "nanosleep.u32 %2;\nadd.u32 n, n, 1;\nsetp.lt.u32 p, n, 16777216;\n@p bra LW;\ntrap;\nLD:\n}\n" :: "r"(bar), "r"(parity), "n"(SL_BAR) : "memory");
}
__device__ __forceinline__ void mbar_wait_all(uint32_t bar, uint32_t parity) {
  asm volatile("{\n.reg .pred p, q;\nLW:\nmbarrier.try_wait.parity.shared::cta.b64 p, [%0], %1;\nvote.sync.all.pred q, p, 0xffffffff;\n@!q bra.uni LW;\n}\n" :: "r"(bar), "r"(parity) : "memory");
}
__device__ __forceinline__ void cnt_wait(const unsigned* p, unsigned target) {
  asm volatile("{\n.reg .pred p;\n.reg .u32 n, v;\nmov.u32 n, 0;\n"
    "LW:\nld.relaxed.gpu.global.u32 v, [%0];\nsetp.ge.u32 p, v, %1;\n@p bra LD;\n"
    "nanosleep.u32 %2;\nadd.u32 n, n, 1;\nsetp.lt.u32 p, n, 4194304;\n@p bra LW;\ntrap;\nLD:\nfence.acquire.gpu;\nfence.proxy.async.global;\n}\n" :: "l"(p), "r"(target), "n"(SL_CNT) : "memory");
}
__device__ __forceinline__ void cnt_signal(unsigned* p, int lane) {
  __syncwarp();
  if (lane == 0) asm volatile("red.release.gpu.global.add.u32 [%0], 1;" :: "l"(p) : "memory");
}
__device__ __forceinline__ void cnt_publish(unsigned* p, unsigned n, bool fence) {
  if (fence) asm volatile("fence.release.gpu;" ::: "memory");
  asm volatile("red.relaxed.gpu.global.add.u32 [%0], %1;" :: "l"(p), "r"(n) : "memory");
}
__device__ __forceinline__ uint64_t pol_first() { uint64_t p; asm("createpolicy.fractional.L2::evict_first.b64 %0, 1.0;" : "=l"(p)); return p; }
__device__ __forceinline__ void bulk_g2s(uint32_t dst, const void* src, uint32_t bytes, uint32_t bar, bool stream = false) {
  if (stream) asm volatile("cp.async.bulk.shared::cluster.global.mbarrier::complete_tx::bytes.L2::cache_hint [%0], [%1], %2, [%3], %4;" :: "r"(dst), "l"(src), "r"(bytes), "r"(bar), "l"(pol_first()) : "memory");
  else asm volatile("cp.async.bulk.shared::cluster.global.mbarrier::complete_tx::bytes [%0], [%1], %2, [%3];" :: "r"(dst), "l"(src), "r"(bytes), "r"(bar) : "memory");
}
__device__ __forceinline__ void tma2d(uint32_t dst, const CUtensorMap* m, int x, int y, uint32_t bar, bool stream = false) {
  if (stream) asm volatile("cp.async.bulk.tensor.2d.shared::cluster.global.mbarrier::complete_tx::bytes.L2::cache_hint [%0], [%1, {%3, %4}], [%2], %5;" :: "r"(dst), "l"(m), "r"(bar), "r"(x), "r"(y), "l"(pol_first()) : "memory");
  else asm volatile("cp.async.bulk.tensor.2d.shared::cluster.global.mbarrier::complete_tx::bytes [%0], [%1, {%3, %4}], [%2];" :: "r"(dst), "l"(m), "r"(bar), "r"(x), "r"(y) : "memory");
}
__device__ __forceinline__ void tma3d(uint32_t dst, const CUtensorMap* m, int x, int y, int z, uint32_t bar, bool stream = false) {
  if (stream) asm volatile("cp.async.bulk.tensor.3d.shared::cluster.global.mbarrier::complete_tx::bytes.L2::cache_hint [%0], [%1, {%3, %4, %5}], [%2], %6;" :: "r"(dst), "l"(m), "r"(bar), "r"(x), "r"(y), "r"(z), "l"(pol_first()) : "memory");
  else asm volatile("cp.async.bulk.tensor.3d.shared::cluster.global.mbarrier::complete_tx::bytes [%0], [%1, {%3, %4, %5}], [%2];" :: "r"(dst), "l"(m), "r"(bar), "r"(x), "r"(y), "r"(z) : "memory");
}
__device__ __forceinline__ void tma4d(uint32_t dst, const CUtensorMap* m, int x, int y, int z, int w, uint32_t bar, bool stream = false) {
  if (stream) asm volatile("cp.async.bulk.tensor.4d.shared::cluster.global.mbarrier::complete_tx::bytes.L2::cache_hint [%0], [%1, {%3, %4, %5, %6}], [%2], %7;" :: "r"(dst), "l"(m), "r"(bar), "r"(x), "r"(y), "r"(z), "r"(w), "l"(pol_first()) : "memory");
  else asm volatile("cp.async.bulk.tensor.4d.shared::cluster.global.mbarrier::complete_tx::bytes [%0], [%1, {%3, %4, %5, %6}], [%2];" :: "r"(dst), "l"(m), "r"(bar), "r"(x), "r"(y), "r"(z), "r"(w) : "memory");
}
__device__ __forceinline__ void bulk_g2s_mc(uint32_t dst, const void* src, uint32_t bytes, uint32_t bar, bool stream = false) {
  if (stream) asm volatile("cp.async.bulk.shared::cluster.global.mbarrier::complete_tx::bytes.multicast::cluster.L2::cache_hint [%0], [%1], %2, [%3], %4, %5;" :: "r"(dst), "l"(src), "r"(bytes), "r"(bar), "h"((uint16_t)3), "l"(pol_first()) : "memory");
  else asm volatile("cp.async.bulk.shared::cluster.global.mbarrier::complete_tx::bytes.multicast::cluster [%0], [%1], %2, [%3], %4;" :: "r"(dst), "l"(src), "r"(bytes), "r"(bar), "h"((uint16_t)3) : "memory");
}
__device__ __forceinline__ void tma2d_mc(uint32_t dst, const CUtensorMap* m, int x, int y, uint32_t bar, bool stream = false) {
  if (stream) asm volatile("cp.async.bulk.tensor.2d.shared::cluster.global.mbarrier::complete_tx::bytes.multicast::cluster.L2::cache_hint [%0], [%1, {%3, %4}], [%2], %5, %6;" :: "r"(dst), "l"(m), "r"(bar), "r"(x), "r"(y), "h"((uint16_t)3), "l"(pol_first()) : "memory");
  else asm volatile("cp.async.bulk.tensor.2d.shared::cluster.global.mbarrier::complete_tx::bytes.multicast::cluster [%0], [%1, {%3, %4}], [%2], %5;" :: "r"(dst), "l"(m), "r"(bar), "r"(x), "r"(y), "h"((uint16_t)3) : "memory");
}
__device__ __forceinline__ void tma3d_mc(uint32_t dst, const CUtensorMap* m, int x, int y, int z, uint32_t bar, bool stream = false) {
  if (stream) asm volatile("cp.async.bulk.tensor.3d.shared::cluster.global.mbarrier::complete_tx::bytes.multicast::cluster.L2::cache_hint [%0], [%1, {%3, %4, %5}], [%2], %6, %7;" :: "r"(dst), "l"(m), "r"(bar), "r"(x), "r"(y), "r"(z), "h"((uint16_t)3), "l"(pol_first()) : "memory");
  else asm volatile("cp.async.bulk.tensor.3d.shared::cluster.global.mbarrier::complete_tx::bytes.multicast::cluster [%0], [%1, {%3, %4, %5}], [%2], %6;" :: "r"(dst), "l"(m), "r"(bar), "r"(x), "r"(y), "r"(z), "h"((uint16_t)3) : "memory");
}
__device__ __forceinline__ void map_pf(const CUtensorMap* m) { asm volatile("prefetch.tensormap [%0];" :: "l"(m) : "memory"); }
__device__ __forceinline__ bool elect() {
  uint32_t r; asm volatile("{\n.reg .pred p;\nelect.sync _|p, 0xffffffff;\nselp.u32 %0, 1, 0, p;\n}\n" : "=r"(r)); return r != 0;
}
__device__ __forceinline__ void cluster_arrive() { asm volatile("barrier.cluster.arrive;" ::: "memory"); }
__device__ __forceinline__ void cluster_wait() { asm volatile("barrier.cluster.wait;" ::: "memory"); }
__device__ __forceinline__ void bar_sync(int id, int n) { asm volatile("bar.sync %0, %1;" :: "r"(id), "r"(n) : "memory"); }
__device__ __forceinline__ void bar_arrive(int id, int n) { asm volatile("bar.arrive %0, %1;" :: "r"(id), "r"(n) : "memory"); }
__device__ __forceinline__ void fence_async_smem() { asm volatile("fence.proxy.async.shared::cta;" ::: "memory"); }
__device__ __forceinline__ float ex2(float x) { float y; asm("ex2.approx.ftz.f32 %0, %1;" : "=f"(y) : "f"(x)); return y; }
__device__ __forceinline__ float rcp(float x) { float y; asm("rcp.approx.ftz.f32 %0, %1;" : "=f"(y) : "f"(x)); return y; }
__device__ __forceinline__ uint32_t pack_bf16(float lo, float hi) { uint32_t r; asm("cvt.rn.bf16x2.f32 %0, %1, %2;" : "=r"(r) : "f"(hi), "f"(lo)); return r; }
__device__ __forceinline__ uint32_t hmul2(uint32_t a, uint32_t b) { uint32_t r; asm("mul.rn.bf16x2 %0, %1, %2;" : "=r"(r) : "r"(a), "r"(b)); return r; }
__device__ __forceinline__ uint32_t hadd2(uint32_t a, uint32_t b) { uint32_t r; asm("add.rn.bf16x2 %0, %1, %2;" : "=r"(r) : "r"(a), "r"(b)); return r; }
__device__ __forceinline__ uint32_t hfma2(uint32_t a, uint32_t b, uint32_t c) { uint32_t r; asm("fma.rn.bf16x2 %0, %1, %2, %3;" : "=r"(r) : "r"(a), "r"(b), "r"(c)); return r; }
__device__ __forceinline__ float bf_lo(uint32_t a) { return __uint_as_float(a << 16); }
__device__ __forceinline__ float bf_hi(uint32_t a) { return __uint_as_float(a & 0xffff0000u); }
__device__ __forceinline__ uint32_t lds32(uint32_t a) { uint32_t v; asm volatile("ld.shared.u32 %0, [%1];" : "=r"(v) : "r"(a) : "memory"); return v; }
__device__ __forceinline__ uint4 lds128(uint32_t a) { uint4 v; asm volatile("ld.shared.v4.u32 {%0,%1,%2,%3}, [%4];" : "=r"(v.x), "=r"(v.y), "=r"(v.z), "=r"(v.w) : "r"(a) : "memory"); return v; }
__device__ __forceinline__ void sts64f(uint32_t a, float x, float y) { asm volatile("st.shared.v2.f32 [%0], {%1,%2};" :: "r"(a), "f"(x), "f"(y) : "memory"); }
template<int OFF> __device__ __forceinline__ void sts128o(uint32_t a, uint4 v) { asm volatile("st.shared.v4.u32 [%0+%5], {%1,%2,%3,%4};" :: "r"(a), "r"(v.x), "r"(v.y), "r"(v.z), "r"(v.w), "n"(OFF) : "memory"); }
__device__ __forceinline__ void ldsm4(uint32_t a, uint32_t& r0, uint32_t& r1, uint32_t& r2, uint32_t& r3) {
  asm volatile("ldmatrix.sync.aligned.m8n8.x4.shared.b16 {%0,%1,%2,%3}, [%4];" : "=r"(r0), "=r"(r1), "=r"(r2), "=r"(r3) : "r"(a) : "memory");
}
__device__ __forceinline__ void ldsm4t(uint32_t a, uint32_t& r0, uint32_t& r1, uint32_t& r2, uint32_t& r3) {
  asm volatile("ldmatrix.sync.aligned.m8n8.x4.trans.shared.b16 {%0,%1,%2,%3}, [%4];" : "=r"(r0), "=r"(r1), "=r"(r2), "=r"(r3) : "r"(a) : "memory");
}
__device__ __forceinline__ void stsm4(uint32_t a, uint32_t r0, uint32_t r1, uint32_t r2, uint32_t r3) {
  asm volatile("stmatrix.sync.aligned.m8n8.x4.shared.b16 [%0], {%1,%2,%3,%4};" :: "r"(a), "r"(r0), "r"(r1), "r"(r2), "r"(r3) : "memory");
}
template<int N> __device__ __forceinline__ void fence_regs(float (&d)[N]) {
#pragma unroll
  for (int i = 0; i < N; i++) asm volatile("" : "+f"(d[i]) :: "memory");
}
template<int N> __device__ __forceinline__ void fence_regs(uint32_t (&d)[N]) {
#pragma unroll
  for (int i = 0; i < N; i++) asm volatile("" : "+r"(d[i]) :: "memory");
}
__device__ __forceinline__ void sched_fence(float x, uint32_t dummy) {
  asm volatile("{\n.reg .pred p;\nsetp.eq.u32 p, %0, 0x7fc12345;\n@p st.shared.u32 [%1], %0;\n}\n" :: "r"(__float_as_uint(x)), "r"(dummy) : "memory");
}
#define PTRACE 0
#define TS(role, i)
#define TSA(i)
#define TSS(i)
#define TSK(i)
#define TSO(i)

#define SHADOW if (gridDim.y == 1)

struct Prod {
  uint32_t base, mask; int lane, nt;
  __device__ __forceinline__ uint32_t full(int u) const { return base + SM_BAR + 8 * u; }
  __device__ __forceinline__ uint32_t addr(int u) const { return base + u * UNIT; }
  __device__ __forceinline__ void acquire(int u, int n) {
    const int v = u + min(lane, n - 1);
    mbar_wait_all(base + SM_BAR + 128 + 8 * v, mask >> v);
    mask ^= ((1u << n) - 1) << u;
  }
  __device__ __forceinline__ void acquire_slow(int u, int n) {
    for (int i = 0; i < n; i++) mbar_wait_slow(base + SM_BAR + 128 + 8 * (u + i), mask >> (u + i));
    mask ^= ((1u << n) - 1) << u;
  }
};
struct Cons {
  uint32_t base, rel, mask; int lane, warp, wg, lr, nt;
  __device__ __forceinline__ uint32_t addr(int u) const { return base + u * UNIT; }
  __device__ __forceinline__ static uint32_t daddr(int u) { return SMEM_BASE + u * UNIT; }
  __device__ __forceinline__ void wait(int u) { mbar_wait(base + SM_BAR + 8 * u, mask >> u); mask ^= 1u << u; }
  __device__ __forceinline__ void skip(int u) { mask ^= 1u << u; }
  __device__ __forceinline__ void release(int u, int n) {
    asm volatile("{\n.reg .pred p;\nsetp.lt.s32 p, %1, %2;\n@p mbarrier.arrive.shared::cluster.b64 _, [%0];\n}\n" :: "r"(rel + 8 * u), "r"(lr), "r"(n) : "memory");
  }
  __device__ __forceinline__ void release2(int u) {
    asm volatile("{\n.reg .pred p;\nsetp.eq.s32 p, %1, 0;\n@p mbarrier.arrive.shared::cluster.b64 _, [%0], 2;\n}\n" :: "r"(rel + 8 * u), "r"(lr) : "memory");
  }
  __device__ __forceinline__ void signal(int i) {
    __syncwarp();
    asm volatile("{\n.reg .pred p;\nsetp.eq.s32 p, %1, 0;\n@p mbarrier.arrive.shared::cta.b64 _, [%0];\n}\n" :: "r"(base + SM_SIG + 8 * i), "r"(lane) : "memory");
  }
  __device__ __forceinline__ void turn() { asm volatile("{\n.reg .pred p;\nsetp.eq.s32 p, %0, 0;\n@p bar.sync 1, 256;\n@!p bar.sync 2, 256;\n}\n" :: "r"(wg) : "memory"); }
  __device__ __forceinline__ void pass() { asm volatile("{\n.reg .pred p;\nsetp.eq.s32 p, %0, 0;\n@p bar.arrive 2, 256;\n@!p bar.arrive 1, 256;\n}\n" :: "r"(wg) : "memory"); }
  __device__ __forceinline__ void sync() { asm volatile("{\n.reg .pred p;\nsetp.eq.s32 p, %0, 0;\n@p bar.sync 3, 128;\n@!p bar.sync 4, 128;\n}\n" :: "r"(wg) : "memory"); }
};
__device__ __forceinline__ int gemm_unit(int ks) { return 3 * (ks & 3); }
template<int MASK> __device__ __forceinline__ int kv_slot(int h) { return MASK == PH_ALL ? h & 15 : h; }
__device__ __forceinline__ int out_mb(int cta) { return cta >> 3; }
__device__ __forceinline__ int out_nb(int cta) { return cta & 7; }
template<int MASK> constexpr int CV_REG = MASK == PH_ALL ? 4 : 6;
template<int MASK> constexpr int CV_EXTRA = MASK == PH_ALL ? 96 + NSKIP / 2 : 64;
constexpr int CV_POOL = 896 + 2 * NSKIP;
template<int MASK> __device__ __forceinline__ int conv_channel(int cta, int i) {
  return cta < NREG ? CV_EXTRA<MASK> * (NCTA - NREG) + cta * CV_REG<MASK> + i : (i >> 1) * 8 + (cta - NREG) * 2 + (i & 1);
}

template<int OFF, int N> __device__ __forceinline__ void pack_chunk(const float (&a)[N], float sc0, float sc1, uint4& v0, uint4& v1) {
  v0.x = pack_bf16(a[OFF + 0] * sc0, a[OFF + 1] * sc0); v0.y = pack_bf16(a[OFF + 4] * sc0, a[OFF + 5] * sc0);
  v0.z = pack_bf16(a[OFF + 8] * sc0, a[OFF + 9] * sc0); v0.w = pack_bf16(a[OFF + 12] * sc0, a[OFF + 13] * sc0);
  v1.x = pack_bf16(a[OFF + 2] * sc1, a[OFF + 3] * sc1); v1.y = pack_bf16(a[OFF + 6] * sc1, a[OFF + 7] * sc1);
  v1.z = pack_bf16(a[OFF + 10] * sc1, a[OFF + 11] * sc1); v1.w = pack_bf16(a[OFF + 14] * sc1, a[OFF + 15] * sc1);
}
template<int OFF, int N> __device__ __forceinline__ void pack_chunk(const float (&a)[N], uint4& v0, uint4& v1) {
  v0.x = pack_bf16(a[OFF + 0], a[OFF + 1]); v0.y = pack_bf16(a[OFF + 4], a[OFF + 5]);
  v0.z = pack_bf16(a[OFF + 8], a[OFF + 9]); v0.w = pack_bf16(a[OFF + 12], a[OFF + 13]);
  v1.x = pack_bf16(a[OFF + 2], a[OFF + 3]); v1.y = pack_bf16(a[OFF + 6], a[OFF + 7]);
  v1.z = pack_bf16(a[OFF + 10], a[OFF + 11]); v1.w = pack_bf16(a[OFF + 14], a[OFF + 15]);
}
__device__ __forceinline__ void sq_acc(const uint4& v, uint32_t& a) { a = hfma2(v.x, v.x, a); a = hfma2(v.y, v.y, a); a = hfma2(v.z, v.z, a); a = hfma2(v.w, v.w, a); }
__device__ __forceinline__ float norm2_max(uint32_t a0, uint32_t a1) {
  float n0 = bf_lo(a0) + bf_hi(a0), n1 = bf_lo(a1) + bf_hi(a1);
  n0 += __shfl_xor_sync(~0u, n0, 1); n1 += __shfl_xor_sync(~0u, n1, 1);
  n0 += __shfl_xor_sync(~0u, n0, 2); n1 += __shfl_xor_sync(~0u, n1, 2);
  return __uint_as_float(__reduce_max_sync(~0u, max(__float_as_uint(n0) & 0x7fffffffu, __float_as_uint(n1) & 0x7fffffffu)));
}

struct Pend { uint4 lo[8], hi[8]; };
__device__ __forceinline__ uint32_t ctx_off(const Cons& c, int h, int qb, int rowhalf) { return T_CTX + (qb * 32 + h) * 32768 + (rowhalf * 4 + c.warp) * 4096; }
__device__ __forceinline__ uint32_t kv_off(const Cons& c, int blk) { return T_KV + blk * 65536 + (c.wg * 4 + c.warp) * 4096; }
__device__ __forceinline__ void pin(uint4 (&v)[8]) {
#pragma unroll
  for (int i = 0; i < 8; i++) asm volatile("" : "+r"(v[i].x), "+r"(v[i].y), "+r"(v[i].z), "+r"(v[i].w) :: "memory");
}
__device__ __forceinline__ void pack_o(const float (&o)[64], float i0, float i1, uint4 (&v)[8]) {
  pack_chunk<0>(o, i0, i1, v[0], v[1]); pack_chunk<16>(o, i0, i1, v[2], v[3]);
  pack_chunk<32>(o, i0, i1, v[4], v[5]); pack_chunk<48>(o, i0, i1, v[6], v[7]);
  pin(v);
}
__device__ __forceinline__ uint32_t atom_off(int lane) { return (lane >> 2) * 64 + (((lane ^ (lane >> 3)) & 3) << 4); }
template<int J0, int J1> __device__ __forceinline__ void tile_store(const uint4 (&v)[8], uint32_t dst, int lane) {
  uint8_t* d = g_T + (dst + atom_off(lane));
#pragma unroll
  for (int j = J0; j < J1; j++) { *(uint4*)(d + j * 512) = v[2 * j]; *(uint4*)(d + j * 512 + 2048) = v[2 * j + 1]; }
}
template<int I0, int I1> __device__ __forceinline__ void tile_store_if(bool on, const uint4 (&v)[8], const uint8_t* dst) {
  if constexpr (I0 < I1) {
    asm volatile("{\n.reg .pred p;\nsetp.ne.b32 p, %5, 0;\n@p st.v4.u32 [%0+%6], {%1,%2,%3,%4};\n}\n"
      :: "l"(dst), "r"(v[I0].x), "r"(v[I0].y), "r"(v[I0].z), "r"(v[I0].w), "r"((int)on), "n"((I0 >> 1) * 512 + (I0 & 1) * 2048) : "memory");
    tile_store_if<I0 + 1, I1>(on, v, dst);
  }
}
__device__ __forceinline__ float tile_norm2(const uint4 (&v)[8]) {
  uint32_t n0 = 0, n1 = 0, n2 = 0, n3 = 0;
#pragma unroll
  for (int j = 0; j < 2; j++) { sq_acc(v[2 * j], n0); sq_acc(v[2 * j + 1], n1); sq_acc(v[2 * j + 4], n2); sq_acc(v[2 * j + 5], n3); }
  return norm2_max(hadd2(n0, n2), hadd2(n1, n3));
}
template<uint64_t SCHED, bool FIRST> __device__ __forceinline__ void out_piece(Cons& c, Pend& w, uint32_t dst, int blk, float& kn, int ks, bool both) {
  uint8_t* d = g_T + (dst + atom_off(c.lane));
#pragma unroll
  for (int i = 0; i < 16; i++) {
    const int at = (SCHED >> (4 * i)) & 15;
    if (FIRST ? at == 0 : (at > 0 && ks == at && (i < 8 || both))) *(uint4*)(d + (i >> 3) * 32768 + ((i >> 1) & 3) * 512 + (i & 1) * 2048) = i < 8 ? w.lo[i & 7] : w.hi[i & 7];
  }
  if (FIRST || !both) return;
  if (ks == NK_AT) kn = tile_norm2(w.lo);
  if (ks == NV_AT) {
    const float vn = tile_norm2(w.hi);
    if (c.lane == 0) g_kn2[blk * 8 + c.wg * 4 + c.warp] = (vn <= 1.0e20f && vn >= 1.0e-20f) ? kn : __uint_as_float(0x7f800000u);
  }
}
template<bool FIRST> __device__ __forceinline__ void kv_issue(Cons& c, float (&acc)[128], int u) {
  const uint64_t da = odesc(c.daddr(u) + c.wg * 8192, 16, 1024, 1), db = odesc(c.daddr(u + 1), 8192, 1024, 1);
  TSK(c.nt + 1);
  c.turn();
  TSK(c.nt + 2);
  wg_fence();
#pragma unroll
  for (int kk = 0; kk < 4; kk++) wgmma_ss_n256<1>(acc, da + kk * 2, db + kk * 128, !(FIRST && kk == 0));
  wg_commit();
  c.pass();
  TSK(c.nt + 3); c.nt += 4;
}
template<bool NEXT> __device__ __forceinline__ void cons_kv(Cons& c, int h, int blk, int g, Pend& w, bool pend_o) {
#pragma unroll 1
  for (int tile = 0; tile < 2; tile++) {
    float acc[128];
    if (tile == 0) c.wait(0);
    if (tile == 0 && h < 16) TS(c.wg, 16);
    kv_issue<true>(c, acc, 0);
    c.release(9, tile == 1 ? 3 : 0);
    if (tile == 1 && pend_o) mbar_wait(c.base + SM_RDY + 8 * RDY_WAR, 0);
    const uint32_t dst = tile ? kv_off(c, blk) : ctx_off(c, h - 16, g, 1 - c.wg);
    float kn = 0.f;
    if (tile == 1 || pend_o) out_piece<SCH_KV, true>(c, w, dst, blk, kn, 0, false);
#pragma unroll 1
    for (int ks = 1; ks < 8; ks++) {
      const int u = gemm_unit(ks);
      c.wait(u);
      TSK(c.nt);
      wg_wait<0>();
      c.release(gemm_unit(ks - 1), 3);
      kv_issue<false>(c, acc, u);
      if (tile == 1 || pend_o) { out_piece<SCH_KV, false>(c, w, dst, blk, kn, ks, tile); if (ks == ((SCH_KV >> 28) & 15) && tile == 0) c.signal(SIG_CTX); }
    }
    if (NEXT || tile == 0) c.wait(0);
    wg_wait<0>(); fence_regs(acc);
    TSK(c.nt);
    if (!NEXT) c.release(9, tile == 1 ? 3 : 0);
    pack_chunk<0>(acc, w.lo[0], w.lo[1]);  pack_chunk<16>(acc, w.lo[2], w.lo[3]); pack_chunk<32>(acc, w.lo[4], w.lo[5]); pack_chunk<48>(acc, w.lo[6], w.lo[7]);
    pack_chunk<64>(acc, w.hi[0], w.hi[1]); pack_chunk<80>(acc, w.hi[2], w.hi[3]); pack_chunk<96>(acc, w.hi[4], w.hi[5]); pack_chunk<112>(acc, w.hi[6], w.hi[7]);
    pin(w.lo); pin(w.hi);
  }
}
template<bool FIRST> __device__ __forceinline__ void q_issue(Cons& c, float (&a)[64], float (&b)[64], int u) {
  const uint64_t da = odesc(c.daddr(u) + c.wg * 8192, 16, 1024, 1), db = odesc(c.daddr(u + 2), 8192, 1024, 1);
  const uint64_t da2 = odesc(c.daddr(u + 1) + (1 - c.wg) * 8192, 16, 1024, 1);
  TSK(c.nt + 1);
  c.turn();
  TSK(c.nt + 2);
  wg_fence();
#pragma unroll
  for (int kk = 0; kk < 4; kk++) wgmma_ss_n128<1>(a, da + kk * 2, db + kk * 128, !(FIRST && kk == 0));
#pragma unroll
  for (int kk = 0; kk < 4; kk++) wgmma_ss_n128<1>(b, da2 + kk * 2, db + kk * 128, !(FIRST && kk == 0));
  wg_commit();
  c.pass();
  TSK(c.nt + 3); c.nt += 4;
}
__device__ __forceinline__ void q_step(Cons& c, float (&d)[64], int ua, int ub, int rowhalf) {
  const uint64_t da = odesc(c.daddr(ua) + rowhalf * 8192, 16, 1024, 1), db = odesc(c.daddr(ub), 8192, 1024, 1);
#pragma unroll
  for (int kk = 0; kk < 4; kk++) wgmma_ss_n128<1>(d, da + kk * 2, db + kk * 128, 1);
}
template<bool PEND_KV> __device__ __forceinline__ void cons_q(Cons& c, int h, int blk, Pend& w, float (&b)[64]) {
  float a[64], kn = 0.f;
  if (!PEND_KV) c.wait(0);
  q_issue<true>(c, a, b, 0);
  if (PEND_KV) { c.release(9, 3); out_piece<SCH_Q, true>(c, w, kv_off(c, blk), blk, kn, 0, true); }
#pragma unroll 1
  for (int ks = 1; ks < 14; ks++) {
    const int u = gemm_unit(ks);
    c.wait(u);
    TSK(c.nt);
    wg_wait<0>();
    c.release(gemm_unit(ks - 1), 3);
    q_issue<false>(c, a, b, u);
    if (PEND_KV && ks <= (int)(SCH_Q >> 60)) { out_piece<SCH_Q, false>(c, w, kv_off(c, blk), blk, kn, ks, true); if (ks == (int)(SCH_Q >> 60)) c.signal(SIG_KV + (h >> 4)); }
  }
  c.wait(6); c.wait(9);
  wg_wait<0>();
  c.release(3, 3);
  c.turn();
  TSS(0);
  wg_fence();
  q_step(c, a, 6, 8, c.wg); q_step(c, a, 9, 11, c.wg); wg_commit();
  q_step(c, b, 7, 8, 1 - c.wg); wg_commit();
  c.pass();
  TSS(1);
  c.wait(0);
  const uint32_t q0 = c.addr(0) + (c.wg * 4 + c.warp) * 4096 + atom_off(c.lane);
  wg_wait<1>(); fence_regs(a);
  TSS(2);
  pack_o(a, QSCALE, QSCALE, w.lo);
  sts128o<0>(q0, w.lo[0]);    sts128o<2048>(q0, w.lo[1]); sts128o<512>(q0, w.lo[2]);  sts128o<2560>(q0, w.lo[3]);
  wg_wait<0>();
  c.release(6, 4);
  sts128o<1024>(q0, w.lo[4]); sts128o<3072>(q0, w.lo[5]); sts128o<1536>(q0, w.lo[6]); sts128o<3584>(q0, w.lo[7]);
  TSS(3);
  c.wait(12);
  fence_async_smem();
  TSS(4);
}

__device__ __forceinline__ void issue_qk(float (&s)[64], uint64_t da, uint64_t db) {
#pragma unroll
  for (int kk = 0; kk < 8; kk++) wgmma_ss_n128<0>(s, da + (kk >> 1) * 32 + (kk & 1) * 2, db + (kk >> 1) * 32 + (kk & 1) * 2, kk > 0);
  wg_commit();
}
template<int A, int B> __device__ __forceinline__ void exp_rng(float (&s)[64]) {
#pragma unroll
  for (int i = 4 * A; i < 4 * B; i++) s[i] = ex2(s[i]);
}
template<int A, int B> __device__ __forceinline__ void sum_rng(const float (&s)[64], float (&l)[4]) {
#pragma unroll
  for (int i = A; i < B; i++) { l[0] += s[4 * i]; l[1] += s[4 * i + 1]; l[2] += s[4 * i + 2]; l[3] += s[4 * i + 3]; }
}
template<int A, int B> __device__ __forceinline__ void cvt_p(const float (&s)[64], uint32_t (&p)[32]) {
#pragma unroll
  for (int i = 2 * A; i < 2 * B; i++) p[i] = pack_bf16(s[2 * i], s[2 * i + 1]);
}
template<int K0> __device__ __forceinline__ void mask_half(float (&s)[64], int warp, int lane) {
  const int l0 = warp + (2 * (lane & 3) <= (lane >> 2)), l1 = warp + (2 * (lane & 3) < (lane >> 2));
#pragma unroll
  for (int k = 0; k < 4; k++) {
    float* t = s + 8 * (K0 + k);
    if (k >= l0) { t[0] = -INFINITY; t[6] = -INFINITY; }
    if (k >= l1) { t[1] = -INFINITY; t[7] = -INFINITY; }
    if (k > warp) { t[2] = -INFINITY; t[3] = -INFINITY; }
    if (k >= warp) { t[4] = -INFINITY; t[5] = -INFINITY; }
  }
}
__device__ __forceinline__ void row_inv(float& l0, float& l1) {
  l0 += __shfl_xor_sync(~0u, l0, 1); l1 += __shfl_xor_sync(~0u, l1, 1);
  l0 += __shfl_xor_sync(~0u, l0, 2); l1 += __shfl_xor_sync(~0u, l1, 2);
  l0 = rcp(l0); l1 = rcp(l1);
}
__device__ __forceinline__ void softmax_safe(float (&s)[64], bool upper_only, float& m0, float& m1, float& sc0, float& sc1) {
  float a0 = m0, a1 = m1;
#pragma unroll
  for (int i = 0; i < 8; i++) { a0 = fmaxf(a0, fmaxf(s[4 * i], s[4 * i + 1])); a1 = fmaxf(a1, fmaxf(s[4 * i + 2], s[4 * i + 3])); }
  if (upper_only) { a0 = m0; a1 = m1; }
#pragma unroll
  for (int i = 8; i < 16; i++) { a0 = fmaxf(a0, fmaxf(s[4 * i], s[4 * i + 1])); a1 = fmaxf(a1, fmaxf(s[4 * i + 2], s[4 * i + 3])); }
  a0 = fmaxf(a0, __shfl_xor_sync(~0u, a0, 1)); a1 = fmaxf(a1, __shfl_xor_sync(~0u, a1, 1));
  a0 = fmaxf(a0, __shfl_xor_sync(~0u, a0, 2)); a1 = fmaxf(a1, __shfl_xor_sync(~0u, a1, 2));
  sc0 = ex2(m0 - a0); sc1 = ex2(m1 - a1);
  m0 = a0; m1 = a1;
#pragma unroll
  for (int i = 0; i < 16; i++) { s[4 * i] -= a0; s[4 * i + 1] -= a0; s[4 * i + 2] -= a1; s[4 * i + 3] -= a1; }
}
struct Att {
  float s[64], o[64], l[4], i0, i1, t0, t1; uint32_t p[32];
  float kn; uint32_t qaddr; const uint8_t* dst;
};
__device__ __forceinline__ int att_fast(uint4 (&q)[8], float kn) {
#pragma unroll
  for (int i = 0; i < 8; i++) q[i].x = hmul2(q[i].x, q[i].x);
#pragma unroll
  for (int i = 0; i < 8; i++) q[i].x = hfma2(q[i].w, q[i].w, hfma2(q[i].z, q[i].z, hfma2(q[i].y, q[i].y, q[i].x)));
#pragma unroll
  for (int i = 0; i < 4; i++) q[i].x = hadd2(q[i].x, q[i + 4].x);
  const uint32_t a0 = hadd2(q[0].x, q[2].x), a1 = hadd2(q[1].x, q[3].x);
  return __shfl_sync(~0u, __all_sync(~0u, ((bf_lo(a0) + bf_hi(a0)) * kn <= 0.25f * BOUND2) & ((bf_lo(a1) + bf_hi(a1)) * kn <= 0.25f * BOUND2)), 0);
}
__device__ __forceinline__ int att_first(Cons& c, Att& a, int h, Pend& w) {
  a.kn = __uint_as_float(lds32(c.base + SM_KMAX + 4 * (h >> 4)));
  a.qaddr = c.daddr(0) + c.wg * 16384;
  c.turn();
  TSS(5);
  wg_fence();
  issue_qk(a.s, odesc(a.qaddr, 16, 2048, 2), odesc(c.daddr(12), 16, 2048, 2));
  int fast = 0;
  SHADOW fast = att_fast(w.lo, a.kn);
  wg_fence();
  TSS(6);
  q_step(c, a.o, 10, 11, 1 - c.wg); wg_commit();
  if (c.wg) c.wait(6); else c.skip(6);
  c.pass();
  TSS(7);
#pragma unroll
  for (int i = 0; i < 8; i++) { a.p[4 * i] = w.lo[i].x; a.p[4 * i + 1] = w.lo[i].y; a.p[4 * i + 2] = w.lo[i].z; a.p[4 * i + 3] = w.lo[i].w; }
  a.l[0] = a.l[1] = a.l[2] = a.l[3] = 0.f; a.i0 = a.i1 = a.t0 = a.t1 = 0.25f / QSCALE;
  a.dst = (const uint8_t*)__cvta_shared_to_generic(c.addr(2) + (c.wg * 4 + c.warp) * 4096 + atom_off(c.lane));
  wg_wait<1>(); fence_regs(a.s);
  c.signal(SIG_ATT + (h >> 4));
  if (c.wg) { wg_wait<0>(); c.release(10, 2); }
  return fast;
}
__device__ __forceinline__ void att_last(Cons& c, Att& a, Pend& w, int h, int g, bool drain) {
  const int uv = 6;
  if (drain) pack_o(a.o, rcp(a.i0), rcp(a.i1), w.hi);
  TSS(8);
  c.turn();
  TSS(9);
  fence_regs(a.o); fence_regs(a.p);
  wgmma_pv_sel(a.o, a.p, odesc(c.daddr(uv), 512, 2048, 2), !(drain && c.wg == 1), !drain, c.wg);
  a.i0 = a.l[0] + a.l[1]; a.i1 = a.l[2] + a.l[3];
  SHADOW row_inv(a.i0, a.i1);
  sched_fence(a.i0 + a.i1, c.base + SM_DUMMY);
  tile_store_if<0, 4>(drain, w.hi, a.dst);
  wg_wait<0>(); fence_regs(a.o); fence_regs(a.p);
  c.release(uv, 2);
  TSS(10); if (h < 16) TSK(0); TSO(9 + (h >> 4));
  tile_store_if<4, 8>(drain, w.hi, a.dst);
  pack_o(a.o, a.i0, a.i1, w.lo);
  TSS(11);
}
__device__ __forceinline__ void cons_att(Cons& c, Att& a, int h, int g, Pend& w) {
  int fast = att_first(c, a, h, w), fast2 = 0;
  float m0 = -INFINITY, m1 = -INFINITY, sc0 = 0.f, sc1 = 0.f;
  int uk = 10, ur = 10;
  bool fresh = false;
#pragma unroll 1
  for (int d = g - 15;;) {
    const bool lo = d == c.wg;
    TSS(16 + 6 * (d - g + 15));
    if ((unsigned)d < 2 || !fast) {
      if ((unsigned)d < 2) mask_half<4>(a.s, c.warp, c.lane);
      if (!fast) {
        if (d == 1) m0 = m1 = -INFINITY;
        softmax_safe(a.s, lo, m0, m1, sc0, sc1);
        a.l[0] *= sc0; a.l[1] *= sc0; a.l[2] *= sc1; a.l[3] *= sc1;
      }
    }
    exp_rng<8, 16>(a.s); sum_rng<8, 16>(a.s, a.l);
#pragma unroll
    for (int i = 4 * ATT_SPLIT; i < 32; i++) asm("{\n.reg .pred p;\nsetp.ne.s32 p, %1, %2;\n@p ex2.approx.ftz.f32 %0, %0;\n}\n" : "+f"(a.s[i]) : "r"(d), "r"(c.wg));
    sched_fence(((a.l[0] + a.l[1]) + (a.l[2] + a.l[3])) + a.s[4 * ATT_SPLIT + 3], c.base + SM_DUMMY);
    wg_wait<0>(); fence_regs(a.o); fence_regs(a.p);
    c.release(ur, c.wg && d == g - 15 ? 0 : 2);
    TSS(17 + 6 * (d - g + 15));
    a.i0 += a.t0; a.i1 += a.t1;
    a.t0 = __shfl_xor_sync(~0u, a.i0, 2); a.t1 = __shfl_xor_sync(~0u, a.i1, 2);
    tile_store_if<0, 4>(fresh, w.hi, a.dst);
    uk ^= 12; ur = 14 - uk;
    if (d == 0) a.qaddr += 32768;
    const uint64_t dq = odesc(a.qaddr, 16, 2048, 2), dk = odesc(c.daddr(uk) - (d + 1 == c.wg ? 16384 : 0), 16, 2048, 2), dv = odesc(c.daddr(ur), 512, 2048, 2);
    if (!lo) { exp_rng<0, ATT_SPLIT>(a.s); sum_rng<0, 8>(a.s, a.l); cvt_p<0, 16>(a.s, a.p); }
    else if (gridDim.y == 1) cvt_p<8, 16>(a.s, a.p);
    tile_store_if<4, 8>(fresh, w.hi, a.dst);
    a.i0 += a.t0; a.i1 += a.t1;
    if (!fast || d == g + 1) {
      if (!fast && d != 1 && d != g - 15) {
#pragma unroll
        for (int i = 0; i < 16; i++) { a.o[4 * i] *= sc0; a.o[4 * i + 1] *= sc0; a.o[4 * i + 2] *= sc1; a.o[4 * i + 3] *= sc1; }
      }
      if (d == g + 1) break;
    }
    d++;
    fresh = d == 2 || d == g - 14;
    TSS(12 + 6 * (d - g + 15));
    c.turn();
    TSS(13 + 6 * (d - g + 15));
    fence_regs(a.o); fence_regs(a.p);
    wg_fence();
    issue_qk(a.s, dq, dk);
    TSS(14 + 6 * (d - g + 15));
    c.wait(c.wg ? uk ^ 12 : ur); c.skip(c.wg ? ur : uk ^ 12);
    if (fresh || d == 1 || (unsigned)(d - g + CHK_D) < 2) {
      if (fresh) pack_o(a.o, rcp(a.i0), rcp(a.i1), w.hi);
      else if (d == 1) {
        a.i0 = a.l[0] + a.l[1]; a.i1 = a.l[2] + a.l[3];
        a.t0 = __shfl_xor_sync(~0u, a.i0, 1); a.t1 = __shfl_xor_sync(~0u, a.i1, 1);
        a.l[0] = a.l[1] = a.l[2] = a.l[3] = 0.f;
        uint32_t off = ctx_off(c, h, 15 - g, c.wg);
        asm volatile("" : "+r"(off));
        a.dst = g_T + (off + ((uint32_t)(uint64_t)a.dst & 511));
        fast = fast2;
      } else if (d == g - CHK_D) fence_async_smem();
      else fast2 = att_fast(w.hi, a.kn);
    }
    TSS(15 + 6 * (d - g + 15));
    wgmma_pv_sel(a.o, a.p, dv, !lo, !fresh, c.wg);
    wg_wait<1>(); fence_regs(a.s);
    c.release(uk, 2);
    c.release(d == 0 ? 0 : 2, (d == 0 || d == g + 1) ? 2 : 0);
  }
  att_last(c, a, w, h, g, g == 0);
}

constexpr int CV_H = 1024, CV_U = 5120, CV_D = CV_U + 4128;
template<int OFF> __device__ __forceinline__ uint32_t lds32o(uint32_t a) { uint32_t v; asm volatile("ld.shared.u32 %0, [%1+%2];" : "=r"(v) : "r"(a), "n"(OFF) : "memory"); return v; }
template<int G, int G1 = 16> __device__ __forceinline__ void conv_lda(uint32_t (&a)[64], uint32_t p) {
  a[4 * G + 0] = lds32o<-256 * G>(p);
  a[4 * G + 1] = lds32o<-256 * G - 128>(p);
  a[4 * G + 2] = lds32o<-256 * G + 16>(p);
  a[4 * G + 3] = lds32o<-256 * G - 112>(p);
  if constexpr (G + 1 < G1) conv_lda<G + 1, G1>(a, p);
}
struct CvAcc { float lo[16], hi[16]; };
__device__ __forceinline__ void fence_regs(CvAcc& d) { fence_regs(d.lo); fence_regs(d.hi); }
template<int T, int G0, int G1> __device__ __forceinline__ void conv_part(float (&d)[16], const uint32_t (&a)[64], uint64_t db) {
#pragma unroll
  for (int G = G0; G < G1; G++) wgmma_rs_n32<0>(d, a[4 * G], a[4 * G + 1], a[4 * G + 2], a[4 * G + 3], db + 32 * T - 16 * G, G > 0);
}
template<int C0> __device__ __forceinline__ void conv_st_h(const float (&d)[16], uint32_t wq, float& c0, float& c1) {
#pragma unroll
  for (int n = 0; n < 4; n++) { sts64f(wq + (C0 + n * 8) * 4, d[4 * n] + c0, d[4 * n + 1] + c1); c0 = d[4 * n + 2]; c1 = d[4 * n + 3]; }
}
template<int R> __device__ __forceinline__ void conv_st(const CvAcc& d, uint32_t wq, float& c0, float& c1) { conv_st_h<64 * R>(d.lo, wq, c0, c1); conv_st_h<64 * R + 32>(d.hi, wq, c0, c1); }

constexpr int OC_PART = 13824, OC_ROW = 544;
__device__ __forceinline__ int out_next(int u) { return (0x84ac680u >> (2 * u)) & 15; }
struct Out { float acc[64]; int pu; uint64_t da, db; };
template<bool FIRST, bool REL, int W = 1> __device__ __forceinline__ void out_step(Cons& c, Out& o, bool extra = false) {
  const int pu = o.pu, u = extra ? 2 : out_next(pu);
  o.pu = u;
  c.wait(u);
  const uint64_t da = o.da + (uint32_t)(u * 1024), db = o.db + (uint32_t)(u * 1024);
  wg_fence();
#pragma unroll
  for (int kk = 0; kk < 4; kk++) wgmma_ss_n128<1>(o.acc, da + (kk >> 1) * 32 + (kk & 1) * 2, db + kk * 128, !(FIRST && kk == 0));
  wg_commit();
  if (REL) { wg_wait<W>(); c.release(pu, 2); }
}
template<int I0, int I1> __device__ __forceinline__ void oc_red(float (&y)[8], uint32_t rq) {
#pragma unroll
  for (int i = I0; i < I1; i++) { const float v = __uint_as_float(lds32(rq + i * OC_ROW - (i >> 3) * 8)); y[i & 7] = i < 8 ? v : y[i & 7] + v; }
}
template<int I0, int I1> __device__ __forceinline__ void oc_ld(float (&t)[32], uint32_t rq) {
#pragma unroll
  for (int i = I0; i < I1; i++) t[i] = __uint_as_float(lds32(rq + i * OC_ROW - (i >> 3) * 8));
}
__device__ __forceinline__ void oc_emit(const float (&y)[8], const uint4& u, uint32_t D2, uint8_t* dst) {
  uint4 z;
  z.x = hadd2(pack_bf16(y[0], y[1]), hmul2(__byte_perm(u.w, 0, 0x1032), D2));
  z.y = hadd2(pack_bf16(y[2], y[3]), hmul2(__byte_perm(u.z, 0, 0x1032), D2));
  z.z = hadd2(pack_bf16(y[4], y[5]), hmul2(__byte_perm(u.y, 0, 0x1032), D2));
  z.w = hadd2(pack_bf16(y[6], y[7]), hmul2(__byte_perm(u.x, 0, 0x1032), D2));
  *(uint4*)dst = z;
}
template<bool THR> __device__ __forceinline__ void conv_round(Cons& c, Out& o, int u, uint32_t ub, uint32_t wq, uint32_t rq, int ch) {
  const int r = c.lane >> 2, q = c.lane & 3, tid = c.warp * 32 + c.lane;
  const uint32_t ap = ub + CV_U + ((r & 1) ? 0 : UPITCH) + 4 * (((2039 - r) >> 1) + q - 8 * c.warp);
  uint32_t a[64];
  CvAcc d0, d1;
  float y[8], t[32], c0 = 0.f, c1 = 0.f;
  const uint64_t db0 = odesc(c.daddr(u) + CV_H - 16, 16, 128, 0);
#define STEP(N) if (THR) out_step<false, true>(c, o); else if (N == 0) c.turn(); else if (N == 10) wg_wait<0>();
#define STEP2(N) if (THR) out_step<false, true, 2>(c, o); else { if (N == 9) c.pass(); wg_wait<1>(); }
#define PART(...) { const uint64_t db = db0 + (c.mask >> 16); wg_fence(); __VA_ARGS__; wg_commit(); }
#define KEEP() asm volatile("add.f32 %0, %0, 0f80000000;" : "+f"(c0)); asm volatile("add.f32 %0, %0, 0f80000000;" : "+f"(c1));
  c.wait(u);
  conv_lda<0, THR ? 4 : 12>(a, ap);
  STEP(0)
  if (THR) conv_lda<4, 7>(a, ap);
  PART(conv_part<0, 0, 2>(d0.lo, a, db); conv_part<1, 0, 4>(d0.hi, a, db); conv_part<2, 0, 2>(d1.lo, a, db))
  STEP2(1)
  if (THR) conv_lda<7, 10>(a, ap);
  PART(conv_part<2, 2, 6>(d1.lo, a, db); conv_part<3, 0, 4>(d1.hi, a, db))
  STEP2(2)
  fence_regs(d0);
  if (THR) c.sync();
  sts64f(wq - 32, 0.f, 0.f);
  conv_st_h<0>(d0.lo, wq, c0, c1); KEEP()
  PART(conv_part<3, 4, 8>(d1.hi, a, db); conv_part<4, 0, 4>(d0.lo, a, db))
  STEP2(3)
  fence_regs(d1.lo);
  conv_st_h<32>(d0.hi, wq, c0, c1); conv_st_h<64>(d1.lo, wq, c0, c1); KEEP()
  PART(conv_part<4, 4, 10>(d0.lo, a, db); conv_part<5, 0, 2>(d0.hi, a, db))
  STEP2(4)
  fence_regs(d1.hi);
  float e0 = d1.hi[12] + d1.hi[10], e1 = d1.hi[13] + d1.hi[11];
  conv_st_h<96>(d1.hi, wq, c0, c1); KEEP()
  if (THR) conv_lda<10, 12>(a, ap);
  PART(conv_part<5, 2, 10>(d0.hi, a, db))
  STEP2(5)
  conv_lda<12, 14>(a, ap);
  c.sync();
  if (THR) oc_red<0, 6>(y, rq); else oc_ld<0, 8>(t, rq);
  PART(conv_part<5, 10, 12>(d0.hi, a, db); conv_part<6, 0, 6>(d1.lo, a, db))
  STEP2(6)
  if (THR) oc_red<6, 20>(y, rq); else oc_ld<8, 16>(t, rq);
  PART(conv_part<6, 6, 14>(d1.lo, a, db))
  STEP2(7)
  if (THR) oc_red<20, 26>(y, rq); else oc_ld<16, 24>(t, rq);
  conv_lda<14, 16>(a, ap);
  PART(conv_part<7, 0, 8>(d1.hi, a, db))
  STEP2(8)
  if (THR) oc_red<26, 32>(y, rq); else oc_ld<24, 32>(t, rq);
  PART(conv_part<7, 8, 16>(d1.hi, a, db))
  STEP2(9)
  if (!THR) {
#pragma unroll
    for (int i = 0; i < 8; i++) y[i] = t[i];
    SHADOW {
#pragma unroll
      for (int i = 0; i < 8; i++) y[i] = ((t[i] + t[8 + i]) + t[16 + i]) + t[24 + i];
    }
  }
  fence_regs(y); fence_regs(d0);
  c.sync();
  sts64f(wq - 32, e0, e1);
  conv_st<0>(d0, wq, c0, c1);
  STEP(10)
  fence_regs(d1); fence_regs(a);
  const uint4 u0 = lds128(ub + CV_U + 4080 - 16 * tid), u1 = lds128(ub + CV_U + 2032 - 16 * tid);
  const uint32_t D2 = lds32(ub + CV_D);
  conv_st<1>(d1, wq, c0, c1);
  STEP(11)
  sched_fence(__uint_as_float(u0.x ^ u1.x ^ D2), c.base + SM_DUMMY);
  uint8_t* zp = g_u + (uint32_t)(ch * UCH + (threadIdx.x & 127) * 16);
  oc_emit(y, u0, D2, zp);
  c.sync();
  c.release2(u);
  oc_red<0, 12>(y, rq);
  STEP(12)
  oc_red<12, 24>(y, rq);
  STEP(13)
  oc_red<24, 32>(y, rq);
  oc_emit(y, u1, D2, zp + 2048);
#undef KEEP
#undef STEP
#undef STEP2
#undef PART
}
template<int MASK> __device__ __forceinline__ void cons_conv(Cons& c, int cta, int nch) {
  const uint32_t part = c.addr(4 + 2 * c.wg) + 32;
  const uint32_t wq = part + (c.warp * 8 + (c.lane >> 2)) * OC_ROW + (c.lane & 3) * 8, rq = part + (c.warp * 32 + c.lane) * 4;
  Out o;
  c.wait(4);
#pragma unroll 1
  for (int i = 0; i < nch / 2; i++) {
    const int u = 2 * (i & 1) + c.wg;
    conv_round<false>(c, o, u, c.addr(u), wq, rq, conv_channel<MASK>(cta, 2 * i + c.wg));
    if ((i & 15) == 15 || i == nch / 2 - 1) c.signal(SIG_Z + (i >> 4));
  }
}
__device__ __forceinline__ uint32_t mix(uint32_t og, uint32_t b, uint32_t ga) { return hadd2(ga, hmul2(og, b)); }
template<int MASK> __device__ __forceinline__ void cons_out(Cons& c, const Maps& M, const Params& P, int cta, Pend& w) {
  const int mb = out_mb(cta), nb = out_nb(cta);
  Out o;
  o.da = odesc(c.daddr(0) + c.wg * 8192, 16, 1024, 2); o.db = odesc(c.daddr(1), 8192, 1024, 1);
  o.pu = 5 + gridDim.y;
  out_step<true, false>(c, o);
  int ks = 1;
  const uint32_t dst = ctx_off(c, 16 + (cta >> 3), cta & 7, 1 - c.wg);
#pragma unroll 1
  for (;; ks++) {
    if (MASK & PH_ATT) {
      if (ks == (c.wg ? ST_1 : 1)) tile_store<0, 1>(w.lo, dst, c.lane);
      if (ks == (c.wg ? ST_1 + ST_D : 1)) tile_store<1, 2>(w.lo, dst, c.lane);
      if (ks == (c.wg ? ST_1 + 2 * ST_D : 1)) tile_store<2, 3>(w.lo, dst, c.lane);
      if (ks == (c.wg ? ST_1 + 3 * ST_D : 1)) { tile_store<3, 4>(w.lo, dst, c.lane); c.signal(SIG_CTX + 1); }
    }
    if (ks == (c.wg ? OC_S1 : OC_S0)) break;
    out_step<false, true>(c, o, ks == 1);
  }
  if (MASK & PH_CONV) {
    const int r = c.lane >> 2, q = c.lane & 3, tid = c.warp * 32 + c.lane, u = 2 * c.wg;
    const uint32_t ub = c.addr(u), part = ub + OC_PART + 32;
    const uint32_t wq = part + (c.warp * 8 + r) * OC_ROW + q * 8, rq = part + tid * 4;
    int ch = conv_channel<MASK>(cta, 3 * c.wg);
#pragma unroll 1
    for (int i = 0; ch >= 0; i++) {
      conv_round<true>(c, o, u + (i >> 8), ub, wq, rq, ch);
      ch = i + c.wg < 2 ? ch + 1 : -1;
      if (c.wg > i) { mbar_wait(c.base + SM_RDY + 8 * RDY_T, 0); ch = __shfl_sync(~0u, lds32(c.base + SM_POOL), 0); }
      if (ch < 0) { c.signal(SIG_Z); c.sync(); c.release2(u + 1); TSO(0); }
      out_step<false, true>(c, o);
#pragma unroll 1
      for (int k = 15; k < (ch < 0 ? 0 : c.wg ? OC_L1 : OC_L0); k++) out_step<false, true>(c, o);
      ks += ch < 0 ? 15 : c.wg ? OC_L1 : OC_L0;
    }
    if (c.wg) c.skip(0);
  }
  TS(c.wg, 9);
#pragma unroll 1
  for (; ks < 57; ks++) out_step<false, true>(c, o);
  uint32_t ga[32];
  TSO(1);
  c.wait(3);
  TSO(2);
  const float g0 = __uint_as_float(lds32(c.base + SM_GATE + 4 * (c.wg * 64 + c.warp * 16 + (c.lane >> 2)))), g1 = __uint_as_float(lds32(c.base + SM_GATE + 32 + 4 * (c.wg * 64 + c.warp * 16 + (c.lane >> 2))));
  const uint32_t gg0 = pack_bf16(g0, g0), gg1 = pack_bf16(g1, g1);
  const uint32_t og0 = pack_bf16(1.f - g0, 1.f - g0), og1 = pack_bf16(1.f - g1, 1.f - g1);
  const int xr = c.wg * 64 + c.warp * 16 + (c.lane & 15);
  const uint32_t xa = c.addr(2) + xr * 128, xs = xr & 7, xh = c.lane >> 4;
  const int zr = (c.lane & 7) + ((c.lane >> 4) << 3);
  const uint32_t za = c.addr(0) + c.wg * 16384 + zr * 128 + (((c.warp * 2 + ((c.lane >> 3) & 1)) ^ (zr & 7)) << 4);
#pragma unroll
  for (int i = 0; i < 8; i++) {
    if (i == 0) out_step<false, true>(c, o);
    if (i == 3) out_step<false, true>(c, o);
    if (i == 6) out_step<false, true>(c, o);
    ldsm4(xa + (i >> 2) * 16384 + ((((i & 3) * 2 + xh) ^ xs) << 4), ga[4 * i], ga[4 * i + 1], ga[4 * i + 2], ga[4 * i + 3]);
  }
  TSO(3);
#pragma unroll 1
  for (ks = 60; ks < 64; ks++) out_step<false, false>(c, o);
  TSO(4);
  c.wait(0);
  TSO(5);
  SHADOW {
#pragma unroll
    for (int i = 0; i < 8; i++) {
      uint32_t z0, z1, z2, z3;
      ldsm4t(za + i * 2048, z0, z1, z2, z3);
      ga[4 * i + 0] = hmul2(ga[4 * i + 0], z0); ga[4 * i + 1] = hmul2(ga[4 * i + 1], z1); ga[4 * i + 2] = hmul2(ga[4 * i + 2], z2); ga[4 * i + 3] = hmul2(ga[4 * i + 3], z3);
      ga[4 * i + 0] = hmul2(gg0, ga[4 * i + 0]); ga[4 * i + 1] = hmul2(gg1, ga[4 * i + 1]); ga[4 * i + 2] = hmul2(gg0, ga[4 * i + 2]); ga[4 * i + 3] = hmul2(gg1, ga[4 * i + 3]);
    }
  }
  c.signal(SIG_DONE);
  fence_regs(ga);
  TSO(6);
  wg_wait<0>(); fence_regs(o.acc);
  TSO(7);
#pragma unroll
  for (int i = 0; i < 8; i++) {
    const uint32_t r0 = mix(og0, pack_bf16(o.acc[8 * i + 0], o.acc[8 * i + 1]), ga[4 * i + 0]);
    const uint32_t r1 = mix(og1, pack_bf16(o.acc[8 * i + 2], o.acc[8 * i + 3]), ga[4 * i + 1]);
    const uint32_t r2 = mix(og0, pack_bf16(o.acc[8 * i + 4], o.acc[8 * i + 5]), ga[4 * i + 2]);
    const uint32_t r3 = mix(og1, pack_bf16(o.acc[8 * i + 6], o.acc[8 * i + 7]), ga[4 * i + 3]);
    stsm4(xa + (i >> 2) * 16384 + ((((i & 3) * 2 + xh) ^ xs) << 4), r0, r1, r2, r3);
    if ((i & 3) == 3) {
      __syncwarp();
#pragma unroll
      for (int k = 0; k < 4; k++) {
        const int rr = c.wg * 64 + c.warp * 16 + k * 4 + (c.lane >> 3);
        const uint4 v = lds128(c.addr(2 + (i >> 2)) + rr * 128 + (((c.lane ^ rr) & 7) << 4));
        *(uint4*)(P.out + (uint32_t)((mb * 128 + rr) * 1024 + nb * 128 + (i >> 2) * 64 + (c.lane & 7) * 8)) = v;
      }
    }
  }
  TSO(8);
}

__device__ __forceinline__ void load_conv(Prod& p, const Maps& M, int u, int ch) {
  if (elect()) {
    mbar_expect(p.full(u), 5120 + UCH);
    tma3d(p.addr(u), &M.h, 0, -8, ch, p.full(u), true);
    bulk_g2s(p.addr(u) + CV_U, g_u + (size_t)ch * UCH, UCH, p.full(u), true);
  }
}
template<int MASK> __device__ __forceinline__ void prod_conv(Prod& p, const Maps& M, int cta, int nch) {
  int ready = -1;
#pragma unroll 1
  for (int i = 0; i < nch; i++) {
    const int ch = conv_channel<MASK>(cta, i);
    const int u = i & 3;
    if ((ch >> 6) != ready) { ready = ch >> 6; if (cta < NREG) mbar_wait(p.base + SM_RDY + 8 * RDY_U, 0); else cnt_wait(g_cnt + (C_U + ready) * CSTRIDE, 128); }
    p.acquire(u, 1);
    load_conv(p, M, u, ch);
    if (i == 3) { p.acquire(4, 4); if (elect()) mbar_arrive(p.full(4)); }
  }
}
#define HOIST(v) asm volatile("" : "+r"(v))
template<int MASK> __device__ __forceinline__ void producer(const Maps& M, const Params& P, uint32_t base, int cta, int lane) {
  Prod p{base, ((MASK & PH_KV) && cta < NREG) ? 0xffffcfffu ^ ((1u << (3 * NFIRST)) - 1) : 0xffffffffu, lane,
         (cta * 3 + 2) * 2048};
  if (cta >= NREG) { if (MASK & PH_CONV) prod_conv<MASK>(p, M, cta, CV_EXTRA<MASK>); return; }
  const int g = cta & 7, j = cta >> 3, rank = cta & 1;
#pragma unroll 1
  for (int half = 0; half < 2; half++) {
    const int h = j + 16 * half;
    if (MASK & PH_KV) {
      const CUtensorMap* mw = rank ? &M.wv : &M.wk;
#pragma unroll 1
      for (int it = half ? 0 : NFIRST; it < 16; it++) {
        const int u = gemm_unit(it);
        uint32_t bar = p.full(u), d0 = p.addr(u), d1 = p.addr(u + 1 + rank); int k0 = (it & 7) * 64, r0 = (2 * g + (it >> 3)) * 128;
        HOIST(bar); HOIST(d0); HOIST(d1); HOIST(k0); HOIST(r0);
        p.acquire(u, 3);
        if (elect()) {
          mbar_expect(bar, 3 * UNIT);
          tma3d_mc(d1, mw, 0, k0, 2 * h, bar, it >= 8);
          tma2d(d0, &M.c, k0, r0, bar);
        }
      }
    }
    if (MASK & PH_ATT) {
#pragma unroll 1
      for (int ks = 0; ks < 16; ks++) {
        const int u = gemm_unit(ks);
        uint32_t bar = p.full(u), d0 = p.addr(u), d1 = p.addr(u + 1), d2 = p.addr(u + 2) + rank * 8192; int k0 = ks * 64;
        HOIST(bar); HOIST(d0); HOIST(d1); HOIST(d2); HOIST(k0);
        p.acquire(u, 3);
        if (elect()) {
          mbar_expect(bar, 3 * UNIT);
          tma2d_mc(d2, &M.wq, h * 128 + rank * 64, k0, bar, true);
          tma2d(d0, &M.x, k0, (15 - g) * 128, bar);
          tma2d(d1, &M.x, k0, g * 128, bar);
        }
      }
      TS(2, 8 * half + 0);
      mbar_wait(base + SM_RDY + 8 * (RDY_KV + half), 0);
      TS(2, 8 * half + 1);
      const uint8_t* KVh = g_T + T_KV + (size_t)kv_slot<MASK>(h) * 16 * 65536;
      if (MASK & PH_PRE) mbar_wait(base + SM_RDY + 8 * RDY_AUX, 0);
      if (elect()) { mbar_expect(p.full(12), 32768); bulk_g2s(p.addr(12), KVh, 32768, p.full(12), true); }
      p.acquire(0, 4);
      if (elect()) mbar_arrive(p.full(0));
#pragma unroll 1
      for (int i = 1; i < 34; i++) {
        const int isv = !(i & 1) || i == 33, st = i == 33 ? 16 : (isv ? (i >> 1) - 1 : (i + 1) >> 1), u = 4 + 2 * (i & 3);
        const bool own = st == 15 - (g & 6);
        uint32_t bar = p.full(u), d0 = p.addr(own ? u : u + rank), off = (st <= 15 - g ? st : 16 - st) * 65536 + isv * 32768 + (own ? 0 : rank * UNIT);
        HOIST(bar); HOIST(d0); HOIST(off);
        p.acquire(u, 2);
        if (elect()) {
          mbar_expect(bar, 32768);
          if (own) bulk_g2s(d0, KVh + off, 32768, bar, true); else bulk_g2s_mc(d0, KVh + off, UNIT, bar, true);
        }
      }
    }
  }
  if ((MASK & PH_CONV) && !(MASK & PH_OUT)) prod_conv<MASK>(p, M, cta, CV_REG<MASK>);
  if (MASK & PH_OUT) {
    const int y0 = out_mb(cta) * 512 + rank * 8, z0 = 2 * out_nb(cta);
    int u = 6;
#pragma unroll 1
    for (int hf = 0; hf < 2; hf++) {
      TS(2, 16 + 2 * hf);
      mbar_wait(base + SM_RDY + 8 * (RDY_CTX + hf), 0);
      TS(2, 17 + 2 * hf);
#pragma unroll 1
      for (int n = hf * 32; n < hf * 32 + 32; n++) {
        const int ks = n == 1 ? 2 : n == 2 ? 1 : n;
        u = n == 2 ? 2 : n == 3 ? 10 : out_next(u);
        uint32_t bar = p.full(u), d0 = p.addr(u) + rank * 8192, d1 = p.addr(u + 1); int x = (ks & 1) * 256, y = y0 + (ks >> 1) * 16, k0 = ks * 64;
        HOIST(bar); HOIST(d0); HOIST(d1); HOIST(x); HOIST(y); HOIST(k0);
        p.acquire(u, 2);
        if (elect()) {
          mbar_expect(bar, 2 * UNIT);
          tma2d_mc(d0, &M.ctx, x, y, bar, true);
          tma3d(d1, &M.wo, 0, k0, z0, bar, true);
          if (ks == 1) mbar_arrive(base + SM_RDY + 8 * RDY_X);
          if (ks == Z_AT) mbar_arrive(base + SM_RDY + 8 * RDY_Z);
        }
      }
    }
  }
}
template<int MASK> __device__ __forceinline__ void producer2(const Maps& M, const Params& P, uint32_t base, int cta, int w, int lane) {
  Prod p{base, 0xffffffffu, lane, 0};
  const int mb = out_mb(cta), nb = out_nb(cta), u = 2 * w;
  if (w) { mbar_wait_slow(base + SM_RDY + 8 * RDY_X, 0); p.mask ^= 12; }
  if (MASK & PH_CONV) {
    mbar_wait_slow(base + SM_SIG + 8 * (SIG_ATT + 1), 0);
    mbar_wait_slow(base + SM_RDY + 8 * RDY_U, 0);
#pragma unroll 1
    for (int i = 0, ch = conv_channel<MASK>(cta, 3 * w); ch >= 0; i++) {
      p.acquire_slow(u, i ? 1 : 2);
      load_conv(p, M, u, ch);
      ch = i + w < 2 ? ch + 1 : -1;
      if (w > i) { mbar_wait_slow(base + SM_RDY + 8 * RDY_T, 0); ch = lds32(base + SM_POOL); }
    }
  }
  p.acquire_slow(u, 2);
  if (!w && elect()) map_pf(&M.z);
  TSA(52 - 2 * w);
  mbar_wait(base + SM_RDY + 8 * (!w ? RDY_Z : RDY_G), 0);
  TSA(53 - 2 * w);
  if (elect()) {
    const uint32_t bar = p.full(3 * w);
    mbar_expect(bar, 2 * UNIT + (!w ? 0 : 512));
    tma2d(p.addr(u), !w ? &M.z : &M.x, (!w ? mb : nb) * 128, (!w ? nb : mb) * 128, bar, true);
    tma2d(p.addr(u + 1), !w ? &M.z : &M.x, (!w ? mb : nb) * 128 + 64, (!w ? nb : mb) * 128, bar, true);
    if (w) bulk_g2s(base + SM_GATE, g_gate + mb * 128, 512, bar);
  }
}

__device__ __forceinline__ constexpr uint32_t PUB(int sig, int cnt, int n) { return 0x80000000u | (sig << 24) | (n << 8) | cnt; }
__device__ __forceinline__ constexpr uint32_t GET(int rdy, int cnt, int n) { return (rdy << 24) | (n << 8) | cnt; }
template<int MASK> __device__ __forceinline__ void sync_agent(uint32_t base, int cta, int lane) {
  if ((base & 0x3FFFF) != SMEM_BASE) asm volatile("trap;");
  const int g = cta & 7, j = cta >> 3, go = min(out_mb(cta), 15 - out_mb(cta));
  const int c0 = conv_channel<MASK>(cta, 0), c1 = c0 + CV_REG<MASK> - 1, n0 = min(CV_REG<MASK>, 128 - (c0 & 127));
  constexpr bool KV = MASK & PH_KV, ATT = MASK & PH_ATT, CONV = MASK & PH_CONV, OUT = MASK & PH_OUT, ALL = MASK == PH_ALL;
  uint32_t e = 0;
  if (cta >= NREG) { if (CONV && lane * 32 < CV_EXTRA<MASK>) e = PUB(SIG_Z + lane, C_Z + lane, min(32, CV_EXTRA<MASK> - lane * 32)); }
  else switch (lane) {
    case 0:  if (KV) e = PUB(SIG_KV, C_KV + j, 1); break;
    case 1:  if (ATT) e = GET(RDY_KV, C_KV + j, 8); break;
    case 2:  if (ALL) e = PUB(SIG_WAR, C_WAR + j, 1); break;
    case 3:  if (ATT) e = PUB(SIG_CTX, C_CTX + g, 1); break;
    case 4:  if (ALL) e = GET(RDY_WAR, C_WAR + j, 8); break;
    case 5:  if (KV) e = PUB(SIG_KV + 1, C_KV + 16 + j, 1); break;
    case 6:  if (ATT) e = GET(RDY_KV + 1, C_KV + 16 + j, 8); break;
    case 7:  if (OUT) e = GET(RDY_CTX, C_CTX + go, 16); break;
    case 8:  if (CONV) e = GET(RDY_U, C_U + (c0 >> 6), 128); break;
    case 9:  if (CONV) e = GET(ALL ? RDY_NONE : RDY_U, C_U + (ALL ? 14 : c1 >> 6), 128); break;
    case 10: if (ALL) e = GET(RDY_T, C_U + 15, 128); break;
    case 11: if (ATT) e = PUB(SIG_CTX + 1, C_CTX + 8 + g, 1); break;
    case 12: if (OUT) e = GET(RDY_CTX + 1, C_CTX + 8 + go, 16); break;
    case 13: if (OUT) e = GET(RDY_G, C_GATE, 256); break;
    case 14: if (CONV) e = PUB(SIG_Z, C_Z + (c0 >> 7), n0); break;
    case 15: if (ALL) e = PUB(SIG_Z, C_Z + 7, 1); else if (CONV && n0 < CV_REG<MASK>) e = PUB(SIG_Z, C_Z + (c1 >> 7), CV_REG<MASK> - n0); break;
    case 16: if (OUT) e = GET(RDY_Z, C_Z + out_nb(cta), 128); break;
  }
  if (ALL && lane == 0) { mbar_expect(base + SM_RDY + 8 * RDY_T, 4); mbar_arrive(base + SM_RDY + 8 * RDY_U); }
  __syncwarp();
#pragma unroll 1
  for (int i = 0; i < 17; i++) {
    const uint32_t x = __shfl_sync(~0u, e, i), id = (x >> 24) & 127, n = (x >> 8) & 0xffff;
    if (x == 0) continue;
    unsigned* cnt = g_cnt + (x & 255) * CSTRIDE;
    if (x >> 31) {
      mbar_wait_slow(base + SM_SIG + 8 * id, 0);
      const bool draw = ALL && i == 11 && !(cta & 1);
      unsigned t = 0;
      if (draw && lane == 0) asm volatile("atom.relaxed.gpu.global.add.u32 %0, [%1], 1;" : "=r"(t) : "l"(g_cnt + C_TICKET * CSTRIDE) : "memory");
      if (lane == 0 && !(ALL && i == 15 && (int)lds32(base + SM_POOL) < 0)) cnt_publish(cnt, n, i != 15);
      if (draw) {
        t = __shfl_sync(~0u, t, 0);
        uint32_t peer;
        asm volatile("mapa.shared::cluster.u32 %0, %1, %2;" : "=r"(peer) : "r"(base), "r"(lane & 1));
        if (lane < 2) asm volatile("st.async.weak.shared::cluster.mbarrier::complete_tx::bytes.u32 [%0], %1, [%2];"
          :: "r"(peer + SM_POOL), "r"(t < 64 - NSKIP ? CV_POOL + 2 * t + lane : ~0u), "r"(peer + SM_RDY + 8 * RDY_T) : "memory");
      }
    } else {
      cnt_wait(cnt, n);
      if (id < 2) {
        const float4 kn = __ldcg((const float4*)(g_kn2 + kv_slot<MASK>(j + 16 * id) * 128) + lane);
        const uint32_t m = __reduce_max_sync(~0u, max(max(__float_as_uint(kn.x), __float_as_uint(kn.y)), max(__float_as_uint(kn.z), __float_as_uint(kn.w))));
        if (lane == 0) asm volatile("st.shared.u32 [%0], %1;" :: "r"(base + SM_KMAX + 4 * id), "r"(m) : "memory");
      }
      if (lane == 0) mbar_arrive(base + SM_RDY + 8 * id);
    }
    __syncwarp();
  }
}

__device__ __forceinline__ void aux_gate(const Params& P, int cta, int aw, int lane) {
  uint4 gw[4];
#pragma unroll
  for (int i = 0; i < 4; i++) gw[i] = __ldg((const uint4*)P.gw + i * 32 + lane);
#pragma unroll 1
  for (int row = cta * 16 + aw * 8; row < cta * 16 + aw * 8 + 8; row++) {
    float a = 0.f;
#pragma unroll
    for (int i = 0; i < 4; i++) {
      const uint4 xv = __ldg((const uint4*)(P.x + (size_t)row * 1024) + i * 32 + lane);
      uint32_t m;
      m = hmul2(xv.x, gw[i].x); a += bf_lo(m) + bf_hi(m); m = hmul2(xv.y, gw[i].y); a += bf_lo(m) + bf_hi(m);
      m = hmul2(xv.z, gw[i].z); a += bf_lo(m) + bf_hi(m); m = hmul2(xv.w, gw[i].w); a += bf_lo(m) + bf_hi(m);
    }
#pragma unroll
    for (int o = 16; o > 0; o >>= 1) a += __shfl_xor_sync(~0u, a, o);
    a = bf_lo(pack_bf16(a, 0.f));
    const float gt = bf_lo(pack_bf16(__fdividef(1.f, 1.f + ex2(-a * 1.4426950408889634f)), 0.f));
    if (lane == 0) g_gate[row] = gt;
    __nanosleep(GATE_SLEEP);
  }
  cnt_signal(g_cnt + C_GATE * CSTRIDE, lane);
  if (aw == 0) { TSA(44); }
}
template<int MASK> __device__ __forceinline__ void aux_pre(const Maps& M, const Params& P, uint32_t base, int cta, int aw, int lane) {
  const uint32_t kb = base + 12 * UNIT, bar = base + SM_PRE;
  const int r = lane >> 2, q = lane & 3;
  const int mi = lane >> 3, row0 = (lane & 6) + 1 - (lane & 1);
  const int ra = (mi * 9 + 1) * 2 + row0;
  const int rb = (mi == 0 ? 3 : mi) * 18 + row0;
#pragma unroll 1
  for (int it = 0; it < (cta < 96 ? 5 : 4); it++) {
    if (it == PRE_EARLY && MASK == PH_ALL) { mbar_wait_slow(base + SM_SIG + 8 * SIG_ATT, 0); aux_gate(P, cta, aw, lane); }
    if (it == PRE_EARLY && MASK == PH_ALL) mbar_wait_slow(base + SM_SIG + 8 * (SIG_ATT + 1), 0);
    const int cg = it ? it * 4 - 3 + (cta >> 5) : 0, tb = cta & 31;
    if (it == 0 && aw == 0) TSA(45);
    if (aw == 0 && elect()) {
      mbar_expect(bar, 2 * 9216);
      tma4d(kb, &M.k, cg * 64, 0, tb * 8 - 1, 0, bar, true);
      tma4d(kb + 9216, &M.v, cg * 64, 0, tb * 8 - 1, 0, bar, true);
    }
    const uint2 swl = __ldg((const uint2*)(P.shift + (cg * 64 + aw * 32 + lane) * 4));
    if (tb == 0) {
      uint8_t* e = g_u + (size_t)(cg * 64 + aw * 32 + lane) * UCH + 4096;
      *(uint4*)e = make_uint4(0, 0, 0, 0); *(uint4*)(e + UPITCH) = make_uint4(0, 0, 0, 0);
      *(uint32_t*)(e + 32) = (uint32_t)__bfloat16_as_ushort(P.D[cg * 64 + aw * 32 + lane]) * 0x10001u;
    }
    if (it == 0 && aw == 0) TSA(46);
    if (it == 0) mbar_wait(bar, 0); else mbar_wait_slow(bar, it & 1);
    if (it == 0 && aw == 0) TSA(47);
#pragma unroll 1
    for (int ol = it ? 0 : cta >> 5; ol < (it ? 4 : (cta >> 5) + 1); ol++) {
      const int oc = aw * 4 + ol;
      const uint32_t s01 = __shfl_sync(~0u, swl.x, ol * 8 + r), s23 = __shfl_sync(~0u, swl.y, ol * 8 + r);
      const uint32_t w0 = __byte_perm(s01, 0, 0x1010), w1 = __byte_perm(s01, 0, 0x3232), w2 = __byte_perm(s23, 0, 0x1010), w3 = __byte_perm(s23, 0, 0x3232);
      const uint32_t pa = kb + ra * 128 + ((oc ^ (ra & 7)) << 4), pb = kb + (mi == 0 ? 9216 : 0) + rb * 128 + ((oc ^ (rb & 7)) << 4);
      uint8_t* e0 = g_u + (uint32_t)((cg * 64 + oc * 8 + r) * UCH + (2040 - tb * 64 - 8 * q) * 2);
#pragma unroll
      for (int hb = 0; hb < 2; hb++) {
        uint32_t k[7], v[5];
        ldsm4t(pa + hb * 1024, k[3], k[4], k[5], k[6]);
        ldsm4t(pa + hb * 1024 + 9216, v[1], v[2], v[3], v[4]);
        ldsm4t(pb + hb * 1024, v[0], k[0], k[1], k[2]);
        uint32_t o1 = __byte_perm(k[1], k[0], 0x5432);
#pragma unroll
        for (int m = 0; m < 5; m++) {
          const uint32_t o2 = __byte_perm(k[m + 2], k[m + 1], 0x5432);
          v[m] = hmul2(hadd2(hadd2(hadd2(hmul2(o1, w3), hmul2(k[m + 1], w2)), hmul2(o2, w1)), hmul2(k[m + 2], w0)), v[m]);
          o1 = o2;
        }
        *(uint4*)(e0 - hb * 64) = make_uint4(v[4], v[3], v[2], v[1]);
        *(uint4*)(e0 - hb * 64 + UPITCH) = make_uint4(__byte_perm(v[4], v[3], 0x5432), __byte_perm(v[3], v[2], 0x5432), __byte_perm(v[2], v[1], 0x5432), __byte_perm(v[1], v[0], 0x5432));
        if (it >= PRE_EARLY) __nanosleep(PRE_SLEEP);
      }
    }
    bar_sync(5, 64);
    if (aw == 0) { TSA(40 + min(it, 3)); }
    if (it == PRE_EARLY - 1 && aw == 0 && lane == 0) mbar_arrive(base + SM_RDY + 8 * RDY_AUX);
    if (aw == 1 && lane == 0) asm volatile("red.release.gpu.global.add.u32 [%0], %1;" :: "l"(g_cnt + (C_U + cg) * CSTRIDE), "r"(it ? 4 : 1) : "memory");
    if (it == 0 && aw == 1) TSA(48);
  }
  uint32_t rel;
  asm volatile("mapa.shared::cluster.u32 %0, %1, %2;" : "=r"(rel) : "r"(base + SM_BAR + 128 + 8 * (12 + (lane & 1))), "r"((lane >> 1) & 1));
  if (lane < 4) asm volatile("mbarrier.arrive.shared::cluster.b64 _, [%0];" :: "r"(rel) : "memory");
  if (MASK != PH_ALL) aux_gate(P, cta, aw, lane);
}

template<int MASK> __global__ void __cluster_dims__(2, 1, 1) __launch_bounds__(384, 1) gated_mix_kernel(const __grid_constant__ Maps M, const __grid_constant__ Params P) {
  extern __shared__ __align__(1024) uint8_t smem[];
  const uint32_t base = (uint32_t)__cvta_generic_to_shared(smem);
  if ((MASK & PH_KV) && elect()) {
    map_pf(&M.wk + (blockIdx.x & 1)); map_pf(&M.c);
  }
  const int wi = __shfl_sync(~0u, threadIdx.x >> 5, 0), wg = wi >> 2, warp = wi & 3;
  if (elect()) {
    if (wi < 8) {
      const int cnt = 1 << ((0x10332200 >> (4 * wi)) & 15);
#pragma unroll
      for (int i = 0; i < 8; i++) mbar_init(base + SM_BAR + 64 * wi + 8 * i, cnt);
      asm volatile("fence.mbarrier_init.release.cluster;" ::: "memory");
    }
  }
  const int cta = blockIdx.x;
  const bool first_loads = (MASK & PH_KV) && wi == 8 && cta < NREG;
  const CUtensorMap* mw = (cta & 1) ? &M.wv : &M.wk;
  __syncwarp();
  asm volatile("barrier.cluster.arrive.relaxed.aligned;\nbarrier.cluster.wait.aligned;" ::: "memory");
  auto first_stage = [&](int it) {
    const uint32_t bar = base + SM_BAR + 24 * it, d0 = base + 3 * it * UNIT;
    mbar_expect(bar, 3 * UNIT);
    tma3d_mc(d0 + (1 + (cta & 1)) * UNIT, mw, 0, it * 64, 2 * (cta >> 3), bar);
    tma2d(d0, &M.c, it * 64, (cta & 7) * 256, bar);
  };
  if (first_loads && elect()) first_stage(0);
  __syncwarp();
  const int lane = threadIdx.x & 31;
#define TS_PRO()
  if (wg == 2) {
    asm volatile("setmaxnreg.dec.sync.aligned.u32 56;");
    TS_PRO();
    TS(2, 62);
    if (warp == 0) producer<MASK>(M, P, base, cta, lane);
    else if (warp == 1) sync_agent<MASK>(base, cta, lane);
    else if (cta < NREG) {
      if (MASK & PH_PRE) aux_pre<MASK>(M, P, base, cta, warp - 2, lane);
      if (MASK & PH_OUT) producer2<MASK>(M, P, base, cta, warp - 2, lane);
    }
    if (warp == 1) {
      if (MASK & PH_OUT) {
        unsigned old = 0;
        if (lane == 0) asm volatile("atom.relaxed.gpu.global.add.u32 %0, [%1], 1;" : "=r"(old) : "l"(g_cnt + C_EXIT * CSTRIDE) : "memory");
        old = __shfl_sync(~0u, old, 0);
        if (old == NCTA - 1) for (int i = lane; i < C_NUM; i += 32) g_cnt[i * CSTRIDE] = 0;
      }
      mbar_wait_slow(base + SM_SIG + 8 * SIG_DONE, 0);
      if (cta >= NREG || !(MASK & PH_OUT)) { cluster_arrive(); cluster_wait(); }
    }
  } else {
    asm volatile("setmaxnreg.inc.sync.aligned.u32 224;");
    TS_PRO();
    uint32_t rel;
    asm volatile("mapa.shared::cluster.u32 %0, %1, %2;" : "=r"(rel) : "r"(base + SM_BAR + 128 + 8 * (lane & 15)), "r"(lane >> 4));
    Cons c{base, rel, 0u, lane, warp, wg, warp == 3 ? lane & 15 : 16, (cta * 3 + wg) * 2048};
    if (wg == 1) bar_arrive(1, 256);
    if ((MASK & PH_KV) && wi == 4 && cta < NREG) {
      if (elect()) {
#pragma unroll 1
        for (int it = 1; it < NFIRST; it++) {
          asm volatile("{\n.reg .pred p;\n.reg .u32 a, b;\nmov.u32 a, %%clock;\nXL:\nmov.u32 b, %%clock;\nsub.u32 b, b, a;\nsetp.lt.u32 p, b, %0;\n@p bra XL;\n}\n" :: "r"(it == 1 ? FGAP : FGAP2) : "memory");
          first_stage(it);
        }
      }
      __syncwarp();
    }
    TS(wg, 0);
    if (cta < NREG) {
      const int g = cta & 7, j = cta >> 3;
      Pend w = {};
#pragma unroll 1
      for (int half = 0; half < 2; half++) {
        const int h = j + 16 * half, blk = kv_slot<MASK>(h) * 16 + 2 * g;
        if (MASK & PH_KV) cons_kv<(MASK & PH_ATT) != 0>(c, h, blk, g, w, half == 1 && (MASK & PH_ATT));
        TS(wg, 1 + 4 * half);
        if (MASK & PH_ATT) {
          Att a;
          cons_q<(MASK & PH_KV) != 0>(c, h, blk + 1, w, a.o);
          TS(wg, 2 + 4 * half);
          cons_att(c, a, h, g, w);
          if (half == 0) c.signal(SIG_WAR);
#pragma unroll
          for (int i = 0; i < 8; i++) w.hi[i] = make_uint4(0, 0, 0, 0);
          TS(wg, 3 + 4 * half);
          if (MASK != PH_ALL) { tile_store<0, 4>(w.lo, ctx_off(c, h, g, 1 - wg), lane); c.signal(SIG_CTX + half); }
        } else if (MASK & PH_KV) {
          float kn = 0.f;
          out_piece<SCH_KV, true>(c, w, kv_off(c, blk + 1), blk + 1, kn, 0, true);
          for (int ks = 1; ks < 8; ks++) out_piece<SCH_KV, false>(c, w, kv_off(c, blk + 1), blk + 1, kn, ks, true);
          c.signal(SIG_KV + half);
        }
      }
      if (MASK & PH_OUT) cons_out<MASK>(c, M, P, cta, w);
    }
    if (cta >= NREG || !(MASK & PH_OUT)) {
      if (MASK & PH_CONV) cons_conv<MASK>(c, cta, cta < NREG ? CV_REG<MASK> : CV_EXTRA<MASK>);
      TS(wg, 9);
      c.signal(SIG_DONE);
      cluster_arrive();
    }
    TS(wg, 10);
  }
}

typedef CUresult (*EncFn)(CUtensorMap*, CUtensorMapDataType, cuuint32_t, void*, const cuuint64_t*, const cuuint64_t*, const cuuint32_t*, const cuuint32_t*,
                          CUtensorMapInterleave, CUtensorMapSwizzle, CUtensorMapL2promotion, CUtensorMapFloatOOBfill);
static void enc(EncFn f, CUtensorMap* m, const void* ptr, int rank, const cuuint64_t* dims, const cuuint64_t* strides, const cuuint32_t* box, CUtensorMapSwizzle sw,
                CUtensorMapDataType dt = CU_TENSOR_MAP_DATA_TYPE_BFLOAT16) {
  const cuuint32_t es[4] = {1, 1, 1, 1};
  f(m, dt, rank, (void*)ptr, dims, strides, box, es, CU_TENSOR_MAP_INTERLEAVE_NONE, sw, CU_TENSOR_MAP_L2_PROMOTION_L2_256B, CU_TENSOR_MAP_FLOAT_OOB_FILL_NONE);
}
static void enc2(EncFn f, CUtensorMap* m, const void* ptr, int cols, int rows, int brows) {
  const cuuint64_t d[2] = {(cuuint64_t)cols, (cuuint64_t)rows}, s[1] = {(cuuint64_t)cols * 2}; const cuuint32_t b[2] = {64, (cuuint32_t)brows};
  enc(f, m, ptr, 2, d, s, b, CU_TENSOR_MAP_SWIZZLE_128B);
}
static void encw(EncFn f, CUtensorMap* m, const void* ptr, int cols, int rows) {
  const cuuint64_t d[3] = {64, (cuuint64_t)rows, (cuuint64_t)cols / 64}, s[2] = {(cuuint64_t)cols * 2, 128}; const cuuint32_t b[3] = {64, 64, 2};
  enc(f, m, ptr, 3, d, s, b, CU_TENSOR_MAP_SWIZZLE_128B);
}
extern "C" void kernel_launch(void* const* d_in, const int* in_sizes, int n_in, void* d_out, int out_size) {
  static EncFn fn = nullptr;
  static int ncl = 0;
  static void* zptr = nullptr;
  static void* tptr = nullptr;
  if (!fn) {
    void* p = nullptr; cudaDriverEntryPointQueryResult qr;
    cudaGetDriverEntryPoint("cuTensorMapEncodeTiled", &p, cudaEnableDefault, &qr);
    fn = (EncFn)p;
    cudaFuncSetAttribute(gated_mix_kernel<PH_ALL>, cudaFuncAttributeMaxDynamicSharedMemorySize, SMEM_BYTES);
    cudaFuncSetAttribute(gated_mix_kernel<PH_PRE | PH_KV>, cudaFuncAttributeMaxDynamicSharedMemorySize, SMEM_BYTES);
    cudaFuncSetAttribute(gated_mix_kernel<PH_ATT | PH_CONV>, cudaFuncAttributeMaxDynamicSharedMemorySize, SMEM_BYTES);
    cudaFuncSetAttribute(gated_mix_kernel<PH_OUT>, cudaFuncAttributeMaxDynamicSharedMemorySize, SMEM_BYTES);
    cudaLaunchConfig_t cfg = {}; cfg.gridDim = NCTA; cfg.blockDim = 384; cfg.dynamicSmemBytes = SMEM_BYTES;
    cudaLaunchAttribute at; at.id = cudaLaunchAttributeClusterDimension; at.val.clusterDim.x = 2; at.val.clusterDim.y = 1; at.val.clusterDim.z = 1;
    cfg.attrs = &at; cfg.numAttrs = 1;
    cudaOccupancyMaxActiveClusters(&ncl, gated_mix_kernel<PH_ALL>, &cfg);
    cudaGetSymbolAddress(&zptr, g_u);
    cudaGetSymbolAddress(&tptr, g_T);
  }
  Maps M;
  enc2(fn, &M.x, d_in[0], 1024, 2048, 128);
  enc2(fn, &M.c, d_in[7], 512, 2048, 128);
  enc2(fn, &M.wq, d_in[8], 4096, 1024, 64);
  encw(fn, &M.wk, d_in[9], 4096, 512);
  encw(fn, &M.wv, d_in[10], 4096, 512);
  encw(fn, &M.wo, d_in[11], 1024, 4096);
  { const cuuint64_t d[3] = {64, 32, 1024}, s[2] = {128, 4096}; const cuuint32_t b[3] = {64, 40, 1}; enc(fn, &M.h, d_in[4], 3, d, s, b, CU_TENSOR_MAP_SWIZZLE_NONE); }
  { const cuuint64_t d[2] = {2048, 1024}, s[1] = {UCH}; const cuuint32_t b[2] = {64, 128}; enc(fn, &M.z, zptr, 2, d, s, b, CU_TENSOR_MAP_SWIZZLE_128B); }
  { const cuuint64_t d[2] = {512, 512 * 16}, s[1] = {2048}; const cuuint32_t b[2] = {256, 8};
    enc(fn, &M.ctx, tptr, 2, d, s, b, CU_TENSOR_MAP_SWIZZLE_NONE, CU_TENSOR_MAP_DATA_TYPE_UINT32); }
  { const cuuint64_t d[4] = {1024, 2, 256, 4}, s[3] = {2048, 16384, 4096}; const cuuint32_t b[4] = {64, 2, 9, 4};
    enc(fn, &M.k, d_in[1], 4, d, s, b, CU_TENSOR_MAP_SWIZZLE_128B); enc(fn, &M.v, d_in[2], 4, d, s, b, CU_TENSOR_MAP_SWIZZLE_128B); }
  Params P{(const __nv_bfloat16*)d_in[0], (const __nv_bfloat16*)d_in[3],
           (const __nv_bfloat16*)d_in[5], (const __nv_bfloat16*)d_in[12], (__nv_bfloat16*)d_out};
  bool split = 2 * ncl < NCTA;
  if (!split) {
    gated_mix_kernel<PH_ALL><<<NCTA, 384, SMEM_BYTES>>>(M, P);
  } else {
    gated_mix_kernel<PH_PRE | PH_KV><<<NCTA, 384, SMEM_BYTES>>>(M, P);
    gated_mix_kernel<PH_ATT | PH_CONV><<<NCTA, 384, SMEM_BYTES>>>(M, P);
    gated_mix_kernel<PH_OUT><<<NCTA, 384, SMEM_BYTES>>>(M, P);
  }
}
```

```cpp
#include <cuda_runtime.h>
#include <cuda.h>
#include <cuda_bf16.h>
#include <stdint.h>

template<int TB> __device__ __forceinline__ void wgmma_ss_n256(float (&d)[128], uint64_t da, uint64_t db, int scale_d) {
  asm volatile("{\n.reg .pred p;\nsetp.ne.b32 p, %130, 0;\n"
    "wgmma.mma_async.sync.aligned.m64n256k16.f32.bf16.bf16 {%0, %1, %2, %3, %4, %5, %6, %7, %8, %9, %10, %11, %12, %13, %14, %15, %16, %17, %18, %19, %20, %21, %22, %23, %24, %25, %26, %27, %28, %29, %30, %31, %32, %33, %34, %35, %36, %37, %38, %39, %40, %41, %42, %43, %44, %45, %46, %47, %48, %49, %50, %51, %52, %53, %54, %55, %56, %57, %58, %59, %60, %61, %62, %63, %64, %65, %66, %67, %68, %69, %70, %71, %72, %73, %74, %75, %76, %77, %78, %79, %80, %81, %82, %83, %84, %85, %86, %87, %88, %89, %90, %91, %92, %93, %94, %95, %96, %97, %98, %99, %100, %101, %102, %103, %104, %105, %106, %107, %108, %109, %110, %111, %112, %113, %114, %115, %116, %117, %118, %119, %120, %121, %122, %123, %124, %125, %126, %127}, %128, %129, p, 1, 1, 0, %131;\n}\n"
    : "+f"(d[0]), "+f"(d[1]), "+f"(d[2]), "+f"(d[3]), "+f"(d[4]), "+f"(d[5]), "+f"(d[6]), "+f"(d[7]), "+f"(d[8]), "+f"(d[9]), "+f"(d[10]), "+f"(d[11]), "+f"(d[12]), "+f"(d[13]), "+f"(d[14]), "+f"(d[15]), "+f"(d[16]), "+f"(d[17]), "+f"(d[18]), "+f"(d[19]), "+f"(d[20]), "+f"(d[21]), "+f"(d[22]), "+f"(d[23]), "+f"(d[24]), "+f"(d[25]), "+f"(d[26]), "+f"(d[27]), "+f"(d[28]), "+f"(d[29]), "+f"(d[30]), "+f"(d[31]), "+f"(d[32]), "+f"(d[33]), "+f"(d[34]), "+f"(d[35]), "+f"(d[36]), "+f"(d[37]), "+f"(d[38]), "+f"(d[39]), "+f"(d[40]), "+f"(d[41]), "+f"(d[42]), "+f"(d[43]), "+f"(d[44]), "+f"(d[45]), "+f"(d[46]), "+f"(d[47]), "+f"(d[48]), "+f"(d[49]), "+f"(d[50]), "+f"(d[51]), "+f"(d[52]), "+f"(d[53]), "+f"(d[54]), "+f"(d[55]), "+f"(d[56]), "+f"(d[57]), "+f"(d[58]), "+f"(d[59]), "+f"(d[60]), "+f"(d[61]), "+f"(d[62]), "+f"(d[63]), "+f"(d[64]), "+f"(d[65]), "+f"(d[66]), "+f"(d[67]), "+f"(d[68]), "+f"(d[69]), "+f"(d[70]), "+f"(d[71]), "+f"(d[72]), "+f"(d[73]), "+f"(d[74]), "+f"(d[75]), "+f"(d[76]), "+f"(d[77]), "+f"(d[78]), "+f"(d[79]), "+f"(d[80]), "+f"(d[81]), "+f"(d[82]), "+f"(d[83]), "+f"(d[84]), "+f"(d[85]), "+f"(d[86]), "+f"(d[87]), "+f"(d[88]), "+f"(d[89]), "+f"(d[90]), "+f"(d[91]), "+f"(d[92]), "+f"(d[93]), "+f"(d[94]), "+f"(d[95]), "+f"(d[96]), "+f"(d[97]), "+f"(d[98]), "+f"(d[99]), "+f"(d[100]), "+f"(d[101]), "+f"(d[102]), "+f"(d[103]), "+f"(d[104]), "+f"(d[105]), "+f"(d[106]), "+f"(d[107]), "+f"(d[108]), "+f"(d[109]), "+f"(d[110]), "+f"(d[111]), "+f"(d[112]), "+f"(d[113]), "+f"(d[114]), "+f"(d[115]), "+f"(d[116]), "+f"(d[117]), "+f"(d[118]), "+f"(d[119]), "+f"(d[120]), "+f"(d[121]), "+f"(d[122]), "+f"(d[123]), "+f"(d[124]), "+f"(d[125]), "+f"(d[126]), "+f"(d[127])
    : "l"(da), "l"(db), "r"(scale_d), "n"(TB));
}
template<int TB> __device__ __forceinline__ void wgmma_ss_n128(float (&d)[64], uint64_t da, uint64_t db, int scale_d) {
  asm volatile("{\n.reg .pred p;\nsetp.ne.b32 p, %66, 0;\n"
    "wgmma.mma_async.sync.aligned.m64n128k16.f32.bf16.bf16 {%0, %1, %2, %3, %4, %5, %6, %7, %8, %9, %10, %11, %12, %13, %14, %15, %16, %17, %18, %19, %20, %21, %22, %23, %24, %25, %26, %27, %28, %29, %30, %31, %32, %33, %34, %35, %36, %37, %38, %39, %40, %41, %42, %43, %44, %45, %46, %47, %48, %49, %50, %51, %52, %53, %54, %55, %56, %57, %58, %59, %60, %61, %62, %63}, %64, %65, p, 1, 1, 0, %67;\n}\n"
    : "+f"(d[0]), "+f"(d[1]), "+f"(d[2]), "+f"(d[3]), "+f"(d[4]), "+f"(d[5]), "+f"(d[6]), "+f"(d[7]), "+f"(d[8]), "+f"(d[9]), "+f"(d[10]), "+f"(d[11]), "+f"(d[12]), "+f"(d[13]), "+f"(d[14]), "+f"(d[15]), "+f"(d[16]), "+f"(d[17]), "+f"(d[18]), "+f"(d[19]), "+f"(d[20]), "+f"(d[21]), "+f"(d[22]), "+f"(d[23]), "+f"(d[24]), "+f"(d[25]), "+f"(d[26]), "+f"(d[27]), "+f"(d[28]), "+f"(d[29]), "+f"(d[30]), "+f"(d[31]), "+f"(d[32]), "+f"(d[33]), "+f"(d[34]), "+f"(d[35]), "+f"(d[36]), "+f"(d[37]), "+f"(d[38]), "+f"(d[39]), "+f"(d[40]), "+f"(d[41]), "+f"(d[42]), "+f"(d[43]), "+f"(d[44]), "+f"(d[45]), "+f"(d[46]), "+f"(d[47]), "+f"(d[48]), "+f"(d[49]), "+f"(d[50]), "+f"(d[51]), "+f"(d[52]), "+f"(d[53]), "+f"(d[54]), "+f"(d[55]), "+f"(d[56]), "+f"(d[57]), "+f"(d[58]), "+f"(d[59]), "+f"(d[60]), "+f"(d[61]), "+f"(d[62]), "+f"(d[63])
    : "l"(da), "l"(db), "r"(scale_d), "n"(TB));
}
template<int TB> __device__ __forceinline__ void wgmma_rs_n32(float (&d)[16], uint32_t a0, uint32_t a1, uint32_t a2, uint32_t a3, uint64_t db, int scale_d) {
  asm volatile("{\n.reg .pred p;\nsetp.ne.b32 p, %21, 0;\n"
    "wgmma.mma_async.sync.aligned.m64n32k16.f32.bf16.bf16 {%0, %1, %2, %3, %4, %5, %6, %7, %8, %9, %10, %11, %12, %13, %14, %15}, {%16, %17, %18, %19}, %20, p, 1, 1, %22;\n}\n"
    : "+f"(d[0]), "+f"(d[1]), "+f"(d[2]), "+f"(d[3]), "+f"(d[4]), "+f"(d[5]), "+f"(d[6]), "+f"(d[7]), "+f"(d[8]), "+f"(d[9]), "+f"(d[10]), "+f"(d[11]), "+f"(d[12]), "+f"(d[13]), "+f"(d[14]), "+f"(d[15])
    : "r"(a0), "r"(a1), "r"(a2), "r"(a3), "l"(db), "r"(scale_d), "n"(TB));
}
__device__ __forceinline__ void wgmma_pv_sel(float (&d)[64], const uint32_t (&p)[32], uint64_t db, int full, int acc, int wg) {
  asm volatile("{\n.reg .pred q, s, w;\n.reg .b64 t;\nsetp.eq.b32 w, %99, 0;\nsetp.ne.b32 s, %98, 0;\nsetp.eq.b32 q, %97, 0;\n@q bra.uni LH;\n"
    "wgmma.fence.sync.aligned;\n"
    "add.s64 t, %96, 0;\nwgmma.mma_async.sync.aligned.m64n128k16.f32.bf16.bf16 {%0, %1, %2, %3, %4, %5, %6, %7, %8, %9, %10, %11, %12, %13, %14, %15, %16, %17, %18, %19, %20, %21, %22, %23, %24, %25, %26, %27, %28, %29, %30, %31, %32, %33, %34, %35, %36, %37, %38, %39, %40, %41, %42, %43, %44, %45, %46, %47, %48, %49, %50, %51, %52, %53, %54, %55, %56, %57, %58, %59, %60, %61, %62, %63}, {%64, %65, %66, %67}, t, s, 1, 1, 1;\n"
    "add.s64 t, %96, 256;\nwgmma.mma_async.sync.aligned.m64n128k16.f32.bf16.bf16 {%0, %1, %2, %3, %4, %5, %6, %7, %8, %9, %10, %11, %12, %13, %14, %15, %16, %17, %18, %19, %20, %21, %22, %23, %24, %25, %26, %27, %28, %29, %30, %31, %32, %33, %34, %35, %36, %37, %38, %39, %40, %41, %42, %43, %44, %45, %46, %47, %48, %49, %50, %51, %52, %53, %54, %55, %56, %57, %58, %59, %60, %61, %62, %63}, {%68, %69, %70, %71}, t, 1, 1, 1, 1;\n"
    "add.s64 t, %96, 512;\nwgmma.mma_async.sync.aligned.m64n128k16.f32.bf16.bf16 {%0, %1, %2, %3, %4, %5, %6, %7, %8, %9, %10, %11, %12, %13, %14, %15, %16, %17, %18, %19, %20, %21, %22, %23, %24, %25, %26, %27, %28, %29, %30, %31, %32, %33, %34, %35, %36, %37, %38, %39, %40, %41, %42, %43, %44, %45, %46, %47, %48, %49, %50, %51, %52, %53, %54, %55, %56, %57, %58, %59, %60, %61, %62, %63}, {%72, %73, %74, %75}, t, 1, 1, 1, 1;\n"
    "add.s64 t, %96, 768;\nwgmma.mma_async.sync.aligned.m64n128k16.f32.bf16.bf16 {%0, %1, %2, %3, %4, %5, %6, %7, %8, %9, %10, %11, %12, %13, %14, %15, %16, %17, %18, %19, %20, %21, %22, %23, %24, %25, %26, %27, %28, %29, %30, %31, %32, %33, %34, %35, %36, %37, %38, %39, %40, %41, %42, %43, %44, %45, %46, %47, %48, %49, %50, %51, %52, %53, %54, %55, %56, %57, %58, %59, %60, %61, %62, %63}, {%76, %77, %78, %79}, t, 1, 1, 1, 1;\n"
    "add.s64 t, %96, 1024;\nwgmma.mma_async.sync.aligned.m64n128k16.f32.bf16.bf16 {%0, %1, %2, %3, %4, %5, %6, %7, %8, %9, %10, %11, %12, %13, %14, %15, %16, %17, %18, %19, %20, %21, %22, %23, %24, %25, %26, %27, %28, %29, %30, %31, %32, %33, %34, %35, %36, %37, %38, %39, %40, %41, %42, %43, %44, %45, %46, %47, %48, %49, %50, %51, %52, %53, %54, %55, %56, %57, %58, %59, %60, %61, %62, %63}, {%80, %81, %82, %83}, t, 1, 1, 1, 1;\n"
    "add.s64 t, %96, 1280;\nwgmma.mma_async.sync.aligned.m64n128k16.f32.bf16.bf16 {%0, %1, %2, %3, %4, %5, %6, %7, %8, %9, %10, %11, %12, %13, %14, %15, %16, %17, %18, %19, %20, %21, %22, %23, %24, %25, %26, %27, %28, %29, %30, %31, %32, %33, %34, %35, %36, %37, %38, %39, %40, %41, %42, %43, %44, %45, %46, %47, %48, %49, %50, %51, %52, %53, %54, %55, %56, %57, %58, %59, %60, %61, %62, %63}, {%84, %85, %86, %87}, t, 1, 1, 1, 1;\n"
    "@w bar.arrive 2, 256;\n@!w bar.arrive 1, 256;\n"
    "add.s64 t, %96, 1536;\nwgmma.mma_async.sync.aligned.m64n128k16.f32.bf16.bf16 {%0, %1, %2, %3, %4, %5, %6, %7, %8, %9, %10, %11, %12, %13, %14, %15, %16, %17, %18, %19, %20, %21, %22, %23, %24, %25, %26, %27, %28, %29, %30, %31, %32, %33, %34, %35, %36, %37, %38, %39, %40, %41, %42, %43, %44, %45, %46, %47, %48, %49, %50, %51, %52, %53, %54, %55, %56, %57, %58, %59, %60, %61, %62, %63}, {%88, %89, %90, %91}, t, 1, 1, 1, 1;\n"
    "add.s64 t, %96, 1792;\nwgmma.mma_async.sync.aligned.m64n128k16.f32.bf16.bf16 {%0, %1, %2, %3, %4, %5, %6, %7, %8, %9, %10, %11, %12, %13, %14, %15, %16, %17, %18, %19, %20, %21, %22, %23, %24, %25, %26, %27, %28, %29, %30, %31, %32, %33, %34, %35, %36, %37, %38, %39, %40, %41, %42, %43, %44, %45, %46, %47, %48, %49, %50, %51, %52, %53, %54, %55, %56, %57, %58, %59, %60, %61, %62, %63}, {%92, %93, %94, %95}, t, 1, 1, 1, 1;\n"
    "wgmma.commit_group.sync.aligned;\n"
    "bra.uni LE;\nLH:\n"
    "wgmma.fence.sync.aligned;\n"
    "add.s64 t, %96, 0;\nwgmma.mma_async.sync.aligned.m64n128k16.f32.bf16.bf16 {%0, %1, %2, %3, %4, %5, %6, %7, %8, %9, %10, %11, %12, %13, %14, %15, %16, %17, %18, %19, %20, %21, %22, %23, %24, %25, %26, %27, %28, %29, %30, %31, %32, %33, %34, %35, %36, %37, %38, %39, %40, %41, %42, %43, %44, %45, %46, %47, %48, %49, %50, %51, %52, %53, %54, %55, %56, %57, %58, %59, %60, %61, %62, %63}, {%80, %81, %82, %83}, t, s, 1, 1, 1;\n"
    "add.s64 t, %96, 256;\nwgmma.mma_async.sync.aligned.m64n128k16.f32.bf16.bf16 {%0, %1, %2, %3, %4, %5, %6, %7, %8, %9, %10, %11, %12, %13, %14, %15, %16, %17, %18, %19, %20, %21, %22, %23, %24, %25, %26, %27, %28, %29, %30, %31, %32, %33, %34, %35, %36, %37, %38, %39, %40, %41, %42, %43, %44, %45, %46, %47, %48, %49, %50, %51, %52, %53, %54, %55, %56, %57, %58, %59, %60, %61, %62, %63}, {%84, %85, %86, %87}, t, 1, 1, 1, 1;\n"
    "@w bar.arrive 2, 256;\n@!w bar.arrive 1, 256;\n"
    "add.s64 t, %96, 512;\nwgmma.mma_async.sync.aligned.m64n128k16.f32.bf16.bf16 {%0, %1, %2, %3, %4, %5, %6, %7, %8, %9, %10, %11, %12, %13, %14, %15, %16, %17, %18, %19, %20, %21, %22, %23, %24, %25, %26, %27, %28, %29, %30, %31, %32, %33, %34, %35, %36, %37, %38, %39, %40, %41, %42, %43, %44, %45, %46, %47, %48, %49, %50, %51, %52, %53, %54, %55, %56, %57, %58, %59, %60, %61, %62, %63}, {%88, %89, %90, %91}, t, 1, 1, 1, 1;\n"
    "add.s64 t, %96, 768;\nwgmma.mma_async.sync.aligned.m64n128k16.f32.bf16.bf16 {%0, %1, %2, %3, %4, %5, %6, %7, %8, %9, %10, %11, %12, %13, %14, %15, %16, %17, %18, %19, %20, %21, %22, %23, %24, %25, %26, %27, %28, %29, %30, %31, %32, %33, %34, %35, %36, %37, %38, %39, %40, %41, %42, %43, %44, %45, %46, %47, %48, %49, %50, %51, %52, %53, %54, %55, %56, %57, %58, %59, %60, %61, %62, %63}, {%92, %93, %94, %95}, t, 1, 1, 1, 1;\n"
    "wgmma.commit_group.sync.aligned;\n"
    "LE:\n}\n"
    : "+f"(d[0]), "+f"(d[1]), "+f"(d[2]), "+f"(d[3]), "+f"(d[4]), "+f"(d[5]), "+f"(d[6]), "+f"(d[7]), "+f"(d[8]), "+f"(d[9]), "+f"(d[10]), "+f"(d[11]), "+f"(d[12]), "+f"(d[13]), "+f"(d[14]), "+f"(d[15]), "+f"(d[16]), "+f"(d[17]), "+f"(d[18]), "+f"(d[19]), "+f"(d[20]), "+f"(d[21]), "+f"(d[22]), "+f"(d[23]), "+f"(d[24]), "+f"(d[25]), "+f"(d[26]), "+f"(d[27]), "+f"(d[28]), "+f"(d[29]), "+f"(d[30]), "+f"(d[31]), "+f"(d[32]), "+f"(d[33]), "+f"(d[34]), "+f"(d[35]), "+f"(d[36]), "+f"(d[37]), "+f"(d[38]), "+f"(d[39]), "+f"(d[40]), "+f"(d[41]), "+f"(d[42]), "+f"(d[43]), "+f"(d[44]), "+f"(d[45]), "+f"(d[46]), "+f"(d[47]), "+f"(d[48]), "+f"(d[49]), "+f"(d[50]), "+f"(d[51]), "+f"(d[52]), "+f"(d[53]), "+f"(d[54]), "+f"(d[55]), "+f"(d[56]), "+f"(d[57]), "+f"(d[58]), "+f"(d[59]), "+f"(d[60]), "+f"(d[61]), "+f"(d[62]), "+f"(d[63])
    : "r"(p[0]), "r"(p[1]), "r"(p[2]), "r"(p[3]), "r"(p[4]), "r"(p[5]), "r"(p[6]), "r"(p[7]), "r"(p[8]), "r"(p[9]), "r"(p[10]), "r"(p[11]), "r"(p[12]), "r"(p[13]), "r"(p[14]), "r"(p[15]), "r"(p[16]), "r"(p[17]), "r"(p[18]), "r"(p[19]), "r"(p[20]), "r"(p[21]), "r"(p[22]), "r"(p[23]), "r"(p[24]), "r"(p[25]), "r"(p[26]), "r"(p[27]), "r"(p[28]), "r"(p[29]), "r"(p[30]), "r"(p[31]), "l"(db), "r"(full), "r"(acc), "r"(wg) : "memory");
}

constexpr int NCTA = 132, NREG = 128;
constexpr int UNIT = 16384, NUNIT = 14;
constexpr uint32_t SMEM_BASE = 1024;
constexpr int SM_BAR = NUNIT * UNIT;
constexpr int SM_GATE = SM_BAR + 1024;
constexpr int SMEM_BYTES = SM_BAR + 1536;
constexpr int UPITCH = 4160, UCH = 2 * UPITCH;
constexpr float QSCALE = 0.08838834764831845f * 1.4426950408889634f;
constexpr float BOUND2 = 60.f * 60.f / 1.15f;
#define NSKIP 8
constexpr int C_KV = 0;
constexpr int C_CTX = 32;
constexpr int C_U = 48;
constexpr int C_Z = 80;
constexpr int C_GATE = 88;
constexpr int C_EXIT = 89, C_TICKET = 90;
#define ATT_SPLIT 4
#define SL_BAR 256
#define SL_CNT 0
#define Z_AT 60
#define PRE_SLEEP 300
#define GATE_SLEEP 1000
#define OC_S0 2
#define OC_S1 11
#define OC_L0 18
#define OC_L1 18
#define ST_1 4
#define ST_D 2
#define SCH_KV 0x7766555443322100ull
#define SCH_Q 0x7766555443322100ull
#define NK_AT 1
#ifndef NV_AT
#define NV_AT 3
#endif
#define CHK_D 11
#define FGAP 600
#define FGAP2 200
constexpr int PRE_EARLY = 2, NFIRST = 4;
constexpr int C_WAR = 96;
constexpr int C_NUM = 112;
constexpr int CSTRIDE = 32;
constexpr int SM_KMAX = SM_BAR + 640, SM_DUMMY = SM_BAR + 648, SM_POOL = SM_BAR + 652, SM_PRE = SM_BAR + 112, SM_SIG = SM_BAR + 256, SM_RDY = SM_BAR + 384;
enum { SIG_KV = 0, SIG_CTX = 2, SIG_Z = 4, SIG_DONE = 8, SIG_WAR = 9, SIG_ATT = 10 };
enum { RDY_KV = 0, RDY_CTX = 2, RDY_WAR = 4, RDY_G = 5, RDY_X = 6, RDY_AUX = 7, RDY_U = 8, RDY_Z = 9, RDY_T = 10, RDY_NONE = 11 };
enum { PH_PRE = 1, PH_KV = 2, PH_ATT = 4, PH_CONV = 8, PH_OUT = 16, PH_ALL = 31 };

constexpr uint32_t T_CTX = 0, T_KV = 16 * 32 * 32768, T_BYTES = T_KV + 32 * 16 * 65536;
__device__ __align__(1024) uint8_t g_T[T_BYTES];
__device__ __align__(1024) uint8_t g_u[1024 * UCH];
__device__ __align__(1024) float g_gate[2048];
__device__ __align__(1024) float g_kn2[32 * 128];
__device__ __align__(1024) unsigned g_cnt[C_NUM * CSTRIDE];

struct __align__(64) Maps { CUtensorMap c, wk, wv, x, wq, wo, h, z, ctx, k, v; };
struct Params {
  const __nv_bfloat16 *x, *shift, *D, *gw;
  __nv_bfloat16* out;
};

__device__ __forceinline__ void wg_fence() { asm volatile("wgmma.fence.sync.aligned;" ::: "memory"); }
__device__ __forceinline__ void wg_commit() { asm volatile("wgmma.commit_group.sync.aligned;" ::: "memory"); }
template<int N> __device__ __forceinline__ void wg_wait() { asm volatile("wgmma.wait_group.sync.aligned %0;" :: "n"(N) : "memory"); }
__device__ __forceinline__ uint64_t odesc(uint32_t addr, uint32_t lbo, uint32_t sbo, uint32_t swz) {
  uint64_t d = (uint64_t)(addr >> 4) + (((uint64_t)(lbo >> 4) << 16) | ((uint64_t)(sbo >> 4) << 32) | ((uint64_t)swz << 62));
  asm volatile("" : "+l"(d));
  return d;
}
__device__ __forceinline__ void mbar_init(uint32_t bar, int cnt) { asm volatile("mbarrier.init.shared::cta.b64 [%0], %1;" :: "r"(bar), "r"(cnt)); }
__device__ __forceinline__ void mbar_expect(uint32_t bar, uint32_t bytes) { asm volatile("mbarrier.arrive.expect_tx.shared::cta.b64 _, [%0], %1;" :: "r"(bar), "r"(bytes) : "memory"); }
__device__ __forceinline__ void mbar_arrive(uint32_t bar) { asm volatile("mbarrier.arrive.shared::cta.b64 _, [%0];" :: "r"(bar) : "memory"); }
__device__ __forceinline__ void mbar_wait(uint32_t bar, uint32_t parity) {
  asm volatile("{\n.reg .pred p;\nLW:\nmbarrier.try_wait.parity.shared::cta.b64 p, [%0], %1;\n@!p bra LW;\n}\n" :: "r"(bar), "r"(parity) : "memory");
}
__device__ __forceinline__ void mbar_wait_slow(uint32_t bar, uint32_t parity) {
  asm volatile("{\n.reg .pred p;\n.reg .u32 n;\nmov.u32 n, 0;\n"
    "LW:\nmbarrier.test_wait.parity.shared::cta.b64 p, [%0], %1;\n@p bra LD;\n"
    "nanosleep.u32 %2;\nadd.u32 n, n, 1;\nsetp.lt.u32 p, n, 16777216;\n@p bra LW;\ntrap;\nLD:\n}\n" :: "r"(bar), "r"(parity), "n"(SL_BAR) : "memory");
}
__device__ __forceinline__ void mbar_wait_all(uint32_t bar, uint32_t parity) {
  asm volatile("{\n.reg .pred p, q;\nLW:\nmbarrier.try_wait.parity.shared::cta.b64 p, [%0], %1;\nvote.sync.all.pred q, p, 0xffffffff;\n@!q bra.uni LW;\n}\n" :: "r"(bar), "r"(parity) : "memory");
}
__device__ __forceinline__ void cnt_wait(const unsigned* p, unsigned target) {
  asm volatile("{\n.reg .pred p;\n.reg .u32 n, v;\nmov.u32 n, 0;\n"
    "LW:\nld.relaxed.gpu.global.u32 v, [%0];\nsetp.ge.u32 p, v, %1;\n@p bra LD;\n"
    "nanosleep.u32 %2;\nadd.u32 n, n, 1;\nsetp.lt.u32 p, n, 4194304;\n@p bra LW;\ntrap;\nLD:\nfence.acquire.gpu;\nfence.proxy.async.global;\n}\n" :: "l"(p), "r"(target), "n"(SL_CNT) : "memory");
}
__device__ __forceinline__ void cnt_signal(unsigned* p, int lane) {
  __syncwarp();
  if (lane == 0) asm volatile("red.release.gpu.global.add.u32 [%0], 1;" :: "l"(p) : "memory");
}
__device__ __forceinline__ void cnt_publish(unsigned* p, unsigned n, bool fence) {
  if (fence) asm volatile("fence.release.gpu;" ::: "memory");
  asm volatile("red.relaxed.gpu.global.add.u32 [%0], %1;" :: "l"(p), "r"(n) : "memory");
}
__device__ __forceinline__ uint64_t pol_first() { uint64_t p; asm("createpolicy.fractional.L2::evict_first.b64 %0, 1.0;" : "=l"(p)); return p; }
__device__ __forceinline__ void bulk_g2s(uint32_t dst, const void* src, uint32_t bytes, uint32_t bar, bool stream = false) {
  if (stream) asm volatile("cp.async.bulk.shared::cluster.global.mbarrier::complete_tx::bytes.L2::cache_hint [%0], [%1], %2, [%3], %4;" :: "r"(dst), "l"(src), "r"(bytes), "r"(bar), "l"(pol_first()) : "memory");
  else asm volatile("cp.async.bulk.shared::cluster.global.mbarrier::complete_tx::bytes [%0], [%1], %2, [%3];" :: "r"(dst), "l"(src), "r"(bytes), "r"(bar) : "memory");
}
__device__ __forceinline__ void tma2d(uint32_t dst, const CUtensorMap* m, int x, int y, uint32_t bar, bool stream = false) {
  if (stream) asm volatile("cp.async.bulk.tensor.2d.shared::cluster.global.mbarrier::complete_tx::bytes.L2::cache_hint [%0], [%1, {%3, %4}], [%2], %5;" :: "r"(dst), "l"(m), "r"(bar), "r"(x), "r"(y), "l"(pol_first()) : "memory");
  else asm volatile("cp.async.bulk.tensor.2d.shared::cluster.global.mbarrier::complete_tx::bytes [%0], [%1, {%3, %4}], [%2];" :: "r"(dst), "l"(m), "r"(bar), "r"(x), "r"(y) : "memory");
}
__device__ __forceinline__ void tma3d(uint32_t dst, const CUtensorMap* m, int x, int y, int z, uint32_t bar, bool stream = false) {
  if (stream) asm volatile("cp.async.bulk.tensor.3d.shared::cluster.global.mbarrier::complete_tx::bytes.L2::cache_hint [%0], [%1, {%3, %4, %5}], [%2], %6;" :: "r"(dst), "l"(m), "r"(bar), "r"(x), "r"(y), "r"(z), "l"(pol_first()) : "memory");
  else asm volatile("cp.async.bulk.tensor.3d.shared::cluster.global.mbarrier::complete_tx::bytes [%0], [%1, {%3, %4, %5}], [%2];" :: "r"(dst), "l"(m), "r"(bar), "r"(x), "r"(y), "r"(z) : "memory");
}
__device__ __forceinline__ void tma4d(uint32_t dst, const CUtensorMap* m, int x, int y, int z, int w, uint32_t bar, bool stream = false) {
  if (stream) asm volatile("cp.async.bulk.tensor.4d.shared::cluster.global.mbarrier::complete_tx::bytes.L2::cache_hint [%0], [%1, {%3, %4, %5, %6}], [%2], %7;" :: "r"(dst), "l"(m), "r"(bar), "r"(x), "r"(y), "r"(z), "r"(w), "l"(pol_first()) : "memory");
  else asm volatile("cp.async.bulk.tensor.4d.shared::cluster.global.mbarrier::complete_tx::bytes [%0], [%1, {%3, %4, %5, %6}], [%2];" :: "r"(dst), "l"(m), "r"(bar), "r"(x), "r"(y), "r"(z), "r"(w) : "memory");
}
__device__ __forceinline__ void bulk_g2s_mc(uint32_t dst, const void* src, uint32_t bytes, uint32_t bar, bool stream = false) {
  if (stream) asm volatile("cp.async.bulk.shared::cluster.global.mbarrier::complete_tx::bytes.multicast::cluster.L2::cache_hint [%0], [%1], %2, [%3], %4, %5;" :: "r"(dst), "l"(src), "r"(bytes), "r"(bar), "h"((uint16_t)3), "l"(pol_first()) : "memory");
  else asm volatile("cp.async.bulk.shared::cluster.global.mbarrier::complete_tx::bytes.multicast::cluster [%0], [%1], %2, [%3], %4;" :: "r"(dst), "l"(src), "r"(bytes), "r"(bar), "h"((uint16_t)3) : "memory");
}
__device__ __forceinline__ void tma2d_mc(uint32_t dst, const CUtensorMap* m, int x, int y, uint32_t bar, bool stream = false) {
  if (stream) asm volatile("cp.async.bulk.tensor.2d.shared::cluster.global.mbarrier::complete_tx::bytes.multicast::cluster.L2::cache_hint [%0], [%1, {%3, %4}], [%2], %5, %6;" :: "r"(dst), "l"(m), "r"(bar), "r"(x), "r"(y), "h"((uint16_t)3), "l"(pol_first()) : "memory");
  else asm volatile("cp.async.bulk.tensor.2d.shared::cluster.global.mbarrier::complete_tx::bytes.multicast::cluster [%0], [%1, {%3, %4}], [%2], %5;" :: "r"(dst), "l"(m), "r"(bar), "r"(x), "r"(y), "h"((uint16_t)3) : "memory");
}
__device__ __forceinline__ void tma3d_mc(uint32_t dst, const CUtensorMap* m, int x, int y, int z, uint32_t bar, bool stream = false) {
  if (stream) asm volatile("cp.async.bulk.tensor.3d.shared::cluster.global.mbarrier::complete_tx::bytes.multicast::cluster.L2::cache_hint [%0], [%1, {%3, %4, %5}], [%2], %6, %7;" :: "r"(dst), "l"(m), "r"(bar), "r"(x), "r"(y), "r"(z), "h"((uint16_t)3), "l"(pol_first()) : "memory");
  else asm volatile("cp.async.bulk.tensor.3d.shared::cluster.global.mbarrier::complete_tx::bytes.multicast::cluster [%0], [%1, {%3, %4, %5}], [%2], %6;" :: "r"(dst), "l"(m), "r"(bar), "r"(x), "r"(y), "r"(z), "h"((uint16_t)3) : "memory");
}
__device__ __forceinline__ void map_pf(const CUtensorMap* m) { asm volatile("prefetch.tensormap [%0];" :: "l"(m) : "memory"); }
__device__ __forceinline__ bool elect() {
  uint32_t r; asm volatile("{\n.reg .pred p;\nelect.sync _|p, 0xffffffff;\nselp.u32 %0, 1, 0, p;\n}\n" : "=r"(r)); return r != 0;
}
__device__ __forceinline__ void cluster_arrive() { asm volatile("barrier.cluster.arrive;" ::: "memory"); }
__device__ __forceinline__ void cluster_wait() { asm volatile("barrier.cluster.wait;" ::: "memory"); }
__device__ __forceinline__ void bar_sync(int id, int n) { asm volatile("bar.sync %0, %1;" :: "r"(id), "r"(n) : "memory"); }
__device__ __forceinline__ void bar_arrive(int id, int n) { asm volatile("bar.arrive %0, %1;" :: "r"(id), "r"(n) : "memory"); }
__device__ __forceinline__ void fence_async_smem() { asm volatile("fence.proxy.async.shared::cta;" ::: "memory"); }
__device__ __forceinline__ float ex2(float x) { float y; asm("ex2.approx.ftz.f32 %0, %1;" : "=f"(y) : "f"(x)); return y; }
__device__ __forceinline__ float rcp(float x) { float y; asm("rcp.approx.ftz.f32 %0, %1;" : "=f"(y) : "f"(x)); return y; }
__device__ __forceinline__ uint32_t pack_bf16(float lo, float hi) { uint32_t r; asm("cvt.rn.bf16x2.f32 %0, %1, %2;" : "=r"(r) : "f"(hi), "f"(lo)); return r; }
__device__ __forceinline__ uint32_t hmul2(uint32_t a, uint32_t b) { uint32_t r; asm("mul.rn.bf16x2 %0, %1, %2;" : "=r"(r) : "r"(a), "r"(b)); return r; }
__device__ __forceinline__ uint32_t hadd2(uint32_t a, uint32_t b) { uint32_t r; asm("add.rn.bf16x2 %0, %1, %2;" : "=r"(r) : "r"(a), "r"(b)); return r; }
__device__ __forceinline__ uint32_t hfma2(uint32_t a, uint32_t b, uint32_t c) { uint32_t r; asm("fma.rn.bf16x2 %0, %1, %2, %3;" : "=r"(r) : "r"(a), "r"(b), "r"(c)); return r; }
__device__ __forceinline__ float bf_lo(uint32_t a) { return __uint_as_float(a << 16); }
__device__ __forceinline__ float bf_hi(uint32_t a) { return __uint_as_float(a & 0xffff0000u); }
__device__ __forceinline__ uint32_t lds32(uint32_t a) { uint32_t v; asm volatile("ld.shared.u32 %0, [%1];" : "=r"(v) : "r"(a) : "memory"); return v; }
__device__ __forceinline__ uint4 lds128(uint32_t a) { uint4 v; asm volatile("ld.shared.v4.u32 {%0,%1,%2,%3}, [%4];" : "=r"(v.x), "=r"(v.y), "=r"(v.z), "=r"(v.w) : "r"(a) : "memory"); return v; }
__device__ __forceinline__ void sts64f(uint32_t a, float x, float y) { asm volatile("st.shared.v2.f32 [%0], {%1,%2};" :: "r"(a), "f"(x), "f"(y) : "memory"); }
template<int OFF> __device__ __forceinline__ void sts128o(uint32_t a, uint4 v) { asm volatile("st.shared.v4.u32 [%0+%5], {%1,%2,%3,%4};" :: "r"(a), "r"(v.x), "r"(v.y), "r"(v.z), "r"(v.w), "n"(OFF) : "memory"); }
__device__ __forceinline__ void ldsm4(uint32_t a, uint32_t& r0, uint32_t& r1, uint32_t& r2, uint32_t& r3) {
  asm volatile("ldmatrix.sync.aligned.m8n8.x4.shared.b16 {%0,%1,%2,%3}, [%4];" : "=r"(r0), "=r"(r1), "=r"(r2), "=r"(r3) : "r"(a) : "memory");
}
__device__ __forceinline__ void ldsm4t(uint32_t a, uint32_t& r0, uint32_t& r1, uint32_t& r2, uint32_t& r3) {
  asm volatile("ldmatrix.sync.aligned.m8n8.x4.trans.shared.b16 {%0,%1,%2,%3}, [%4];" : "=r"(r0), "=r"(r1), "=r"(r2), "=r"(r3) : "r"(a) : "memory");
}
__device__ __forceinline__ void stsm4(uint32_t a, uint32_t r0, uint32_t r1, uint32_t r2, uint32_t r3) {
  asm volatile("stmatrix.sync.aligned.m8n8.x4.shared.b16 [%0], {%1,%2,%3,%4};" :: "r"(a), "r"(r0), "r"(r1), "r"(r2), "r"(r3) : "memory");
}
template<int N> __device__ __forceinline__ void fence_regs(float (&d)[N]) {
#pragma unroll
  for (int i = 0; i < N; i++) asm volatile("" : "+f"(d[i]) :: "memory");
}
template<int N> __device__ __forceinline__ void fence_regs(uint32_t (&d)[N]) {
#pragma unroll
  for (int i = 0; i < N; i++) asm volatile("" : "+r"(d[i]) :: "memory");
}
__device__ __forceinline__ void sched_fence(float x, uint32_t dummy) {
  asm volatile("{\n.reg .pred p;\nsetp.eq.u32 p, %0, 0x7fc12345;\n@p st.shared.u32 [%1], %0;\n}\n" :: "r"(__float_as_uint(x)), "r"(dummy) : "memory");
}
#define PTRACE 0
#define TS(role, i)
#define TSA(i)
#define TSS(i)
#define TSK(i)
#define TSO(i)

#define SHADOW if (gridDim.y == 1)

struct Prod {
  uint32_t base, mask; int lane, nt;
  __device__ __forceinline__ uint32_t full(int u) const { return base + SM_BAR + 8 * u; }
  __device__ __forceinline__ uint32_t addr(int u) const { return base + u * UNIT; }
  __device__ __forceinline__ void acquire(int u, int n) {
    const int v = u + min(lane, n - 1);
    mbar_wait_all(base + SM_BAR + 128 + 8 * v, mask >> v);
    mask ^= ((1u << n) - 1) << u;
  }
  __device__ __forceinline__ void acquire_slow(int u, int n) {
    for (int i = 0; i < n; i++) mbar_wait_slow(base + SM_BAR + 128 + 8 * (u + i), mask >> (u + i));
    mask ^= ((1u << n) - 1) << u;
  }
};
struct Cons {
  uint32_t base, rel, mask; int lane, warp, wg, lr, nt;
  __device__ __forceinline__ uint32_t addr(int u) const { return base + u * UNIT; }
  __device__ __forceinline__ static uint32_t daddr(int u) { return SMEM_BASE + u * UNIT; }
  __device__ __forceinline__ void wait(int u) { mbar_wait(base + SM_BAR + 8 * u, mask >> u); mask ^= 1u << u; }
  __device__ __forceinline__ void skip(int u) { mask ^= 1u << u; }
  __device__ __forceinline__ void release(int u, int n) {
    asm volatile("{\n.reg .pred p;\nsetp.lt.s32 p, %1, %2;\n@p mbarrier.arrive.shared::cluster.b64 _, [%0];\n}\n" :: "r"(rel + 8 * u), "r"(lr), "r"(n) : "memory");
  }
  __device__ __forceinline__ void release2(int u) {
    asm volatile("{\n.reg .pred p;\nsetp.eq.s32 p, %1, 0;\n@p mbarrier.arrive.shared::cluster.b64 _, [%0], 2;\n}\n" :: "r"(rel + 8 * u), "r"(lr) : "memory");
  }
  __device__ __forceinline__ void signal(int i) {
    __syncwarp();
    asm volatile("{\n.reg .pred p;\nsetp.eq.s32 p, %1, 0;\n@p mbarrier.arrive.shared::cta.b64 _, [%0];\n}\n" :: "r"(base + SM_SIG + 8 * i), "r"(lane) : "memory");
  }
  __device__ __forceinline__ void turn() { asm volatile("{\n.reg .pred p;\nsetp.eq.s32 p, %0, 0;\n@p bar.sync 1, 256;\n@!p bar.sync 2, 256;\n}\n" :: "r"(wg) : "memory"); }
  __device__ __forceinline__ void pass() { asm volatile("{\n.reg .pred p;\nsetp.eq.s32 p, %0, 0;\n@p bar.arrive 2, 256;\n@!p bar.arrive 1, 256;\n}\n" :: "r"(wg) : "memory"); }
  __device__ __forceinline__ void sync() { asm volatile("{\n.reg .pred p;\nsetp.eq.s32 p, %0, 0;\n@p bar.sync 3, 128;\n@!p bar.sync 4, 128;\n}\n" :: "r"(wg) : "memory"); }
};
__device__ __forceinline__ int gemm_unit(int ks) { return 3 * (ks & 3); }
template<int MASK> __device__ __forceinline__ int kv_slot(int h) { return MASK == PH_ALL ? h & 15 : h; }
__device__ __forceinline__ int out_mb(int cta) { return cta >> 3; }
__device__ __forceinline__ int out_nb(int cta) { return cta & 7; }
template<int MASK> constexpr int CV_REG = MASK == PH_ALL ? 4 : 6;
template<int MASK> constexpr int CV_EXTRA = MASK == PH_ALL ? 96 + NSKIP / 2 : 64;
constexpr int CV_POOL = 896 + 2 * NSKIP;
template<int MASK> __device__ __forceinline__ int conv_channel(int cta, int i) {
  return cta < NREG ? CV_EXTRA<MASK> * (NCTA - NREG) + cta * CV_REG<MASK> + i : (i >> 1) * 8 + (cta - NREG) * 2 + (i & 1);
}

template<int OFF, int N> __device__ __forceinline__ void pack_chunk(const float (&a)[N], float sc0, float sc1, uint4& v0, uint4& v1) {
  v0.x = pack_bf16(a[OFF + 0] * sc0, a[OFF + 1] * sc0); v0.y = pack_bf16(a[OFF + 4] * sc0, a[OFF + 5] * sc0);
  v0.z = pack_bf16(a[OFF + 8] * sc0, a[OFF + 9] * sc0); v0.w = pack_bf16(a[OFF + 12] * sc0, a[OFF + 13] * sc0);
  v1.x = pack_bf16(a[OFF + 2] * sc1, a[OFF + 3] * sc1); v1.y = pack_bf16(a[OFF + 6] * sc1, a[OFF + 7] * sc1);
  v1.z = pack_bf16(a[OFF + 10] * sc1, a[OFF + 11] * sc1); v1.w = pack_bf16(a[OFF + 14] * sc1, a[OFF + 15] * sc1);
}
template<int OFF, int N> __device__ __forceinline__ void pack_chunk(const float (&a)[N], uint4& v0, uint4& v1) {
  v0.x = pack_bf16(a[OFF + 0], a[OFF + 1]); v0.y = pack_bf16(a[OFF + 4], a[OFF + 5]);
  v0.z = pack_bf16(a[OFF + 8], a[OFF + 9]); v0.w = pack_bf16(a[OFF + 12], a[OFF + 13]);
  v1.x = pack_bf16(a[OFF + 2], a[OFF + 3]); v1.y = pack_bf16(a[OFF + 6], a[OFF + 7]);
  v1.z = pack_bf16(a[OFF + 10], a[OFF + 11]); v1.w = pack_bf16(a[OFF + 14], a[OFF + 15]);
}
__device__ __forceinline__ void sq_acc(const uint4& v, uint32_t& a) { a = hfma2(v.x, v.x, a); a = hfma2(v.y, v.y, a); a = hfma2(v.z, v.z, a); a = hfma2(v.w, v.w, a); }
template<bool ROWS> __device__ __forceinline__ float norm2_max(uint32_t a0, uint32_t a1) {
  float n0 = bf_lo(a0) + bf_hi(a0), n1 = bf_lo(a1) + bf_hi(a1);
  if (ROWS) {
    n0 += __shfl_xor_sync(~0u, n0, 1); n1 += __shfl_xor_sync(~0u, n1, 1);
    n0 += __shfl_xor_sync(~0u, n0, 2); n1 += __shfl_xor_sync(~0u, n1, 2);
  }
  return __uint_as_float(__reduce_max_sync(~0u, max(__float_as_uint(n0) & 0x7fffffffu, __float_as_uint(n1) & 0x7fffffffu)));
}

struct Pend { uint4 lo[8], hi[8]; };
__device__ __forceinline__ uint32_t ctx_off(const Cons& c, int h, int qb, int rowhalf) { return T_CTX + (qb * 32 + h) * 32768 + (rowhalf * 4 + c.warp) * 4096; }
__device__ __forceinline__ uint32_t kv_off(const Cons& c, int blk) { return T_KV + blk * 65536 + (c.wg * 4 + c.warp) * 4096; }
__device__ __forceinline__ void pin(uint4 (&v)[8]) {
#pragma unroll
  for (int i = 0; i < 8; i++) asm volatile("" : "+r"(v[i].x), "+r"(v[i].y), "+r"(v[i].z), "+r"(v[i].w) :: "memory");
}
__device__ __forceinline__ void pack_o(const float (&o)[64], float i0, float i1, uint4 (&v)[8]) {
  pack_chunk<0>(o, i0, i1, v[0], v[1]); pack_chunk<16>(o, i0, i1, v[2], v[3]);
  pack_chunk<32>(o, i0, i1, v[4], v[5]); pack_chunk<48>(o, i0, i1, v[6], v[7]);
  pin(v);
}
__device__ __forceinline__ uint32_t atom_off(int lane) { return (lane >> 2) * 64 + (((lane ^ (lane >> 3)) & 3) << 4); }
template<int J0, int J1> __device__ __forceinline__ void tile_store(const uint4 (&v)[8], uint32_t dst, int lane) {
  uint8_t* d = g_T + (dst + atom_off(lane));
#pragma unroll
  for (int j = J0; j < J1; j++) { *(uint4*)(d + j * 512) = v[2 * j]; *(uint4*)(d + j * 512 + 2048) = v[2 * j + 1]; }
}
template<int I0, int I1> __device__ __forceinline__ void tile_store_if(bool on, const uint4 (&v)[8], const uint8_t* dst) {
  if constexpr (I0 < I1) {
    asm volatile("{\n.reg .pred p;\nsetp.ne.b32 p, %5, 0;\n@p st.v4.u32 [%0+%6], {%1,%2,%3,%4};\n}\n"
      :: "l"(dst), "r"(v[I0].x), "r"(v[I0].y), "r"(v[I0].z), "r"(v[I0].w), "r"((int)on), "n"((I0 >> 1) * 512 + (I0 & 1) * 2048) : "memory");
    tile_store_if<I0 + 1, I1>(on, v, dst);
  }
}
template<bool ROWS> __device__ __forceinline__ float tile_norm2(const uint4 (&v)[8]) {
  uint32_t n0 = 0, n1 = 0, n2 = 0, n3 = 0;
#pragma unroll
  for (int j = 0; j < 2; j++) { sq_acc(v[2 * j], n0); sq_acc(v[2 * j + 1], n1); sq_acc(v[2 * j + 4], n2); sq_acc(v[2 * j + 5], n3); }
  return norm2_max<ROWS>(hadd2(n0, n2), hadd2(n1, n3));
}
template<uint64_t SCHED, bool FIRST> __device__ __forceinline__ void out_piece(Cons& c, Pend& w, uint32_t dst, int blk, float& kn, int ks, bool both) {
  uint8_t* d = g_T + (dst + atom_off(c.lane));
#pragma unroll
  for (int i = 0; i < 16; i++) {
    const int at = (SCHED >> (4 * i)) & 15;
    if (FIRST ? at == 0 : (at > 0 && ks == at && (i < 8 || both))) *(uint4*)(d + (i >> 3) * 32768 + ((i >> 1) & 3) * 512 + (i & 1) * 2048) = i < 8 ? w.lo[i & 7] : w.hi[i & 7];
  }
  if (FIRST || !both) return;
  if (ks == NK_AT) kn = tile_norm2<true>(w.lo);
  if (ks == NV_AT) {
    const float vn = tile_norm2<false>(w.hi);
    if (c.lane == 0) g_kn2[blk * 8 + c.wg * 4 + c.warp] = (vn <= 1.0e20f && vn >= 1.0e-20f) ? kn : __uint_as_float(0x7f800000u);
  }
}
template<bool FIRST> __device__ __forceinline__ void kv_issue(Cons& c, float (&acc)[128], int u) {
  const uint64_t da = odesc(c.daddr(u) + c.wg * 8192, 16, 1024, 1), db = odesc(c.daddr(u + 1), 8192, 1024, 1);
  TSK(c.nt + 1);
  c.turn();
  TSK(c.nt + 2);
  wg_fence();
#pragma unroll
  for (int kk = 0; kk < 4; kk++) wgmma_ss_n256<1>(acc, da + kk * 2, db + kk * 128, !(FIRST && kk == 0));
  wg_commit();
  c.pass();
  TSK(c.nt + 3); c.nt += 4;
}
template<bool NEXT> __device__ __forceinline__ void cons_kv(Cons& c, int h, int blk, int g, Pend& w, bool pend_o) {
#pragma unroll 1
  for (int tile = 0; tile < 2; tile++) {
    float acc[128];
    if (tile == 0) c.wait(0);
    if (tile == 0 && h < 16) TS(c.wg, 16);
    kv_issue<true>(c, acc, 0);
    c.release(9, tile == 1 ? 3 : 0);
    if (tile == 1 && pend_o) mbar_wait(c.base + SM_RDY + 8 * RDY_WAR, 0);
    const uint32_t dst = tile ? kv_off(c, blk) : ctx_off(c, h - 16, g, 1 - c.wg);
    float kn = 0.f;
    if (tile == 1 || pend_o) out_piece<SCH_KV, true>(c, w, dst, blk, kn, 0, false);
#pragma unroll 1
    for (int ks = 1; ks < 8; ks++) {
      const int u = gemm_unit(ks);
      c.wait(u);
      TSK(c.nt);
      wg_wait<0>();
      c.release(gemm_unit(ks - 1), 3);
      kv_issue<false>(c, acc, u);
      if (tile == 1 || pend_o) { out_piece<SCH_KV, false>(c, w, dst, blk, kn, ks, tile); if (ks == ((SCH_KV >> 28) & 15) && tile == 0) c.signal(SIG_CTX); }
    }
    if (NEXT || tile == 0) c.wait(0);
    wg_wait<0>(); fence_regs(acc);
    TSK(c.nt);
    if (!NEXT) c.release(9, tile == 1 ? 3 : 0);
    pack_chunk<0>(acc, w.lo[0], w.lo[1]);  pack_chunk<16>(acc, w.lo[2], w.lo[3]); pack_chunk<32>(acc, w.lo[4], w.lo[5]); pack_chunk<48>(acc, w.lo[6], w.lo[7]);
    pack_chunk<64>(acc, w.hi[0], w.hi[1]); pack_chunk<80>(acc, w.hi[2], w.hi[3]); pack_chunk<96>(acc, w.hi[4], w.hi[5]); pack_chunk<112>(acc, w.hi[6], w.hi[7]);
    pin(w.lo); pin(w.hi);
  }
}
template<bool FIRST> __device__ __forceinline__ void q_issue(Cons& c, float (&a)[64], float (&b)[64], int u) {
  const uint64_t da = odesc(c.daddr(u) + c.wg * 8192, 16, 1024, 1), db = odesc(c.daddr(u + 2), 8192, 1024, 1);
  const uint64_t da2 = odesc(c.daddr(u + 1) + (1 - c.wg) * 8192, 16, 1024, 1);
  TSK(c.nt + 1);
  c.turn();
  TSK(c.nt + 2);
  wg_fence();
#pragma unroll
  for (int kk = 0; kk < 4; kk++) wgmma_ss_n128<1>(a, da + kk * 2, db + kk * 128, !(FIRST && kk == 0));
#pragma unroll
  for (int kk = 0; kk < 4; kk++) wgmma_ss_n128<1>(b, da2 + kk * 2, db + kk * 128, !(FIRST && kk == 0));
  wg_commit();
  c.pass();
  TSK(c.nt + 3); c.nt += 4;
}
__device__ __forceinline__ void q_step(Cons& c, float (&d)[64], int ua, int ub, int rowhalf) {
  const uint64_t da = odesc(c.daddr(ua) + rowhalf * 8192, 16, 1024, 1), db = odesc(c.daddr(ub), 8192, 1024, 1);
#pragma unroll
  for (int kk = 0; kk < 4; kk++) wgmma_ss_n128<1>(d, da + kk * 2, db + kk * 128, 1);
}
template<bool PEND_KV> __device__ __forceinline__ void cons_q(Cons& c, int h, int blk, Pend& w, float (&b)[64]) {
  float a[64], kn = 0.f;
  if (!PEND_KV) c.wait(0);
  q_issue<true>(c, a, b, 0);
  if (PEND_KV) { c.release(9, 3); out_piece<SCH_Q, true>(c, w, kv_off(c, blk), blk, kn, 0, true); }
#pragma unroll 1
  for (int ks = 1; ks < 14; ks++) {
    const int u = gemm_unit(ks);
    c.wait(u);
    TSK(c.nt);
    wg_wait<0>();
    c.release(gemm_unit(ks - 1), 3);
    q_issue<false>(c, a, b, u);
    if (PEND_KV && ks <= (int)(SCH_Q >> 60)) { out_piece<SCH_Q, false>(c, w, kv_off(c, blk), blk, kn, ks, true); if (ks == (int)(SCH_Q >> 60)) c.signal(SIG_KV + (h >> 4)); }
  }
  c.wait(6); c.wait(9);
  wg_wait<0>();
  c.release(3, 3);
  c.turn();
  TSS(0);
  wg_fence();
  q_step(c, a, 6, 8, c.wg); q_step(c, a, 9, 11, c.wg); wg_commit();
  q_step(c, b, 7, 8, 1 - c.wg); wg_commit();
  c.pass();
  TSS(1);
  c.wait(0);
  const uint32_t q0 = c.addr(0) + (c.wg * 4 + c.warp) * 4096 + atom_off(c.lane);
  wg_wait<1>(); fence_regs(a);
  TSS(2);
  pack_o(a, QSCALE, QSCALE, w.lo);
  sts128o<0>(q0, w.lo[0]);    sts128o<2048>(q0, w.lo[1]); sts128o<512>(q0, w.lo[2]);  sts128o<2560>(q0, w.lo[3]);
  wg_wait<0>();
  c.release(6, 4);
  sts128o<1024>(q0, w.lo[4]); sts128o<3072>(q0, w.lo[5]); sts128o<1536>(q0, w.lo[6]); sts128o<3584>(q0, w.lo[7]);
  TSS(3);
  c.wait(12);
  fence_async_smem();
  TSS(4);
}

__device__ __forceinline__ void issue_qk(float (&s)[64], uint64_t da, uint64_t db) {
#pragma unroll
  for (int kk = 0; kk < 8; kk++) wgmma_ss_n128<0>(s, da + (kk >> 1) * 32 + (kk & 1) * 2, db + (kk >> 1) * 32 + (kk & 1) * 2, kk > 0);
  wg_commit();
}
template<int A, int B> __device__ __forceinline__ void exp_rng(float (&s)[64]) {
#pragma unroll
  for (int i = 4 * A; i < 4 * B; i++) s[i] = ex2(s[i]);
}
template<int A, int B> __device__ __forceinline__ void sum_rng(const float (&s)[64], float (&l)[4]) {
#pragma unroll
  for (int i = A; i < B; i++) { l[0] += s[4 * i]; l[1] += s[4 * i + 1]; l[2] += s[4 * i + 2]; l[3] += s[4 * i + 3]; }
}
template<int A, int B> __device__ __forceinline__ void cvt_p(const float (&s)[64], uint32_t (&p)[32]) {
#pragma unroll
  for (int i = 2 * A; i < 2 * B; i++) p[i] = pack_bf16(s[2 * i], s[2 * i + 1]);
}
template<int K0> __device__ __forceinline__ void mask_half(float (&s)[64], int warp, int lane) {
  const int l0 = warp + (2 * (lane & 3) <= (lane >> 2)), l1 = warp + (2 * (lane & 3) < (lane >> 2));
#pragma unroll
  for (int k = 0; k < 4; k++) {
    float* t = s + 8 * (K0 + k);
    if (k >= l0) { t[0] = -INFINITY; t[6] = -INFINITY; }
    if (k >= l1) { t[1] = -INFINITY; t[7] = -INFINITY; }
    if (k > warp) { t[2] = -INFINITY; t[3] = -INFINITY; }
    if (k >= warp) { t[4] = -INFINITY; t[5] = -INFINITY; }
  }
}
__device__ __forceinline__ void row_inv(float& l0, float& l1) {
  l0 += __shfl_xor_sync(~0u, l0, 1); l1 += __shfl_xor_sync(~0u, l1, 1);
  l0 += __shfl_xor_sync(~0u, l0, 2); l1 += __shfl_xor_sync(~0u, l1, 2);
  l0 = rcp(l0); l1 = rcp(l1);
}
__device__ __forceinline__ void softmax_safe(float (&s)[64], bool upper_only, float& m0, float& m1, float& sc0, float& sc1) {
  float a0 = m0, a1 = m1;
#pragma unroll
  for (int i = 0; i < 8; i++) { a0 = fmaxf(a0, fmaxf(s[4 * i], s[4 * i + 1])); a1 = fmaxf(a1, fmaxf(s[4 * i + 2], s[4 * i + 3])); }
  if (upper_only) { a0 = m0; a1 = m1; }
#pragma unroll
  for (int i = 8; i < 16; i++) { a0 = fmaxf(a0, fmaxf(s[4 * i], s[4 * i + 1])); a1 = fmaxf(a1, fmaxf(s[4 * i + 2], s[4 * i + 3])); }
  a0 = fmaxf(a0, __shfl_xor_sync(~0u, a0, 1)); a1 = fmaxf(a1, __shfl_xor_sync(~0u, a1, 1));
  a0 = fmaxf(a0, __shfl_xor_sync(~0u, a0, 2)); a1 = fmaxf(a1, __shfl_xor_sync(~0u, a1, 2));
  sc0 = ex2(m0 - a0); sc1 = ex2(m1 - a1);
  m0 = a0; m1 = a1;
#pragma unroll
  for (int i = 0; i < 16; i++) { s[4 * i] -= a0; s[4 * i + 1] -= a0; s[4 * i + 2] -= a1; s[4 * i + 3] -= a1; }
}
struct Att {
  float s[64], o[64], l[4], i0, i1, t0, t1; uint32_t p[32];
  float kn; uint32_t qaddr; const uint8_t* dst;
};
__device__ __forceinline__ int att_fast(uint4 (&q)[8], float kn) {
#pragma unroll
  for (int i = 0; i < 8; i++) q[i].x = hmul2(q[i].x, q[i].x);
#pragma unroll
  for (int i = 0; i < 8; i++) q[i].x = hfma2(q[i].w, q[i].w, hfma2(q[i].z, q[i].z, hfma2(q[i].y, q[i].y, q[i].x)));
#pragma unroll
  for (int i = 0; i < 4; i++) q[i].x = hadd2(q[i].x, q[i + 4].x);
  const uint32_t a0 = hadd2(q[0].x, q[2].x), a1 = hadd2(q[1].x, q[3].x);
  return __shfl_sync(~0u, __all_sync(~0u, ((bf_lo(a0) + bf_hi(a0)) * kn <= 0.25f * BOUND2) & ((bf_lo(a1) + bf_hi(a1)) * kn <= 0.25f * BOUND2)), 0);
}
__device__ __forceinline__ int att_first(Cons& c, Att& a, int h, Pend& w) {
  a.kn = __uint_as_float(lds32(c.base + SM_KMAX + 4 * (h >> 4)));
  a.qaddr = c.daddr(0) + c.wg * 16384;
  c.turn();
  TSS(5);
  wg_fence();
  issue_qk(a.s, odesc(a.qaddr, 16, 2048, 2), odesc(c.daddr(12), 16, 2048, 2));
  int fast = 0;
  SHADOW fast = att_fast(w.lo, a.kn);
  wg_fence();
  TSS(6);
  q_step(c, a.o, 10, 11, 1 - c.wg); wg_commit();
  if (c.wg) c.wait(6); else c.skip(6);
  c.pass();
  TSS(7);
#pragma unroll
  for (int i = 0; i < 8; i++) { a.p[4 * i] = w.lo[i].x; a.p[4 * i + 1] = w.lo[i].y; a.p[4 * i + 2] = w.lo[i].z; a.p[4 * i + 3] = w.lo[i].w; }
  a.l[0] = a.l[1] = a.l[2] = a.l[3] = 0.f; a.i0 = a.i1 = a.t0 = a.t1 = 0.25f / QSCALE;
  a.dst = (const uint8_t*)__cvta_shared_to_generic(c.addr(2) + (c.wg * 4 + c.warp) * 4096 + atom_off(c.lane));
  wg_wait<1>(); fence_regs(a.s);
  c.signal(SIG_ATT + (h >> 4));
  if (c.wg) { wg_wait<0>(); c.release(10, 2); }
  return fast;
}
__device__ __forceinline__ void att_last(Cons& c, Att& a, Pend& w, int h, int g, bool drain) {
  const int uv = 6;
  if (drain) pack_o(a.o, rcp(a.i0), rcp(a.i1), w.hi);
  TSS(8);
  c.turn();
  TSS(9);
  fence_regs(a.o); fence_regs(a.p);
  wgmma_pv_sel(a.o, a.p, odesc(c.daddr(uv), 512, 2048, 2), !(drain && c.wg == 1), !drain, c.wg);
  a.i0 = a.l[0] + a.l[1]; a.i1 = a.l[2] + a.l[3];
  SHADOW row_inv(a.i0, a.i1);
  sched_fence(a.i0 + a.i1, c.base + SM_DUMMY);
  tile_store_if<0, 4>(drain, w.hi, a.dst);
  wg_wait<0>(); fence_regs(a.o); fence_regs(a.p);
  c.release(uv, 2);
  TSS(10); if (h < 16) TSK(0); TSO(9 + (h >> 4));
  tile_store_if<4, 8>(drain, w.hi, a.dst);
  pack_o(a.o, a.i0, a.i1, w.lo);
  TSS(11);
}
__device__ __forceinline__ void cons_att(Cons& c, Att& a, int h, int g, Pend& w) {
  int fast = att_first(c, a, h, w), fast2 = 0;
  float m0 = -INFINITY, m1 = -INFINITY, sc0 = 0.f, sc1 = 0.f;
  int uk = 10, ur = 10;
  bool fresh = false;
#pragma unroll 1
  for (int d = g - 15;;) {
    const bool lo = d == c.wg;
    TSS(16 + 6 * (d - g + 15));
    if ((unsigned)d < 2 || !fast) {
      if ((unsigned)d < 2) mask_half<4>(a.s, c.warp, c.lane);
      if (!fast) {
        if (d == 1) m0 = m1 = -INFINITY;
        softmax_safe(a.s, lo, m0, m1, sc0, sc1);
        a.l[0] *= sc0; a.l[1] *= sc0; a.l[2] *= sc1; a.l[3] *= sc1;
      }
    }
    exp_rng<8, 16>(a.s); sum_rng<8, 16>(a.s, a.l);
#pragma unroll
    for (int i = 4 * ATT_SPLIT; i < 32; i++) asm("{\n.reg .pred p;\nsetp.ne.s32 p, %1, %2;\n@p ex2.approx.ftz.f32 %0, %0;\n}\n" : "+f"(a.s[i]) : "r"(d), "r"(c.wg));
    sched_fence(((a.l[0] + a.l[1]) + (a.l[2] + a.l[3])) + a.s[4 * ATT_SPLIT + 3], c.base + SM_DUMMY);
    wg_wait<0>(); fence_regs(a.o); fence_regs(a.p);
    c.release(ur, c.wg && d == g - 15 ? 0 : 2);
    TSS(17 + 6 * (d - g + 15));
    a.i0 += a.t0; a.i1 += a.t1;
    a.t0 = __shfl_xor_sync(~0u, a.i0, 2); a.t1 = __shfl_xor_sync(~0u, a.i1, 2);
    tile_store_if<0, 4>(fresh, w.hi, a.dst);
    uk ^= 12; ur = 14 - uk;
    if (d == 0) a.qaddr += 32768;
    const uint64_t dq = odesc(a.qaddr, 16, 2048, 2), dk = odesc(c.daddr(uk) - (d + 1 == c.wg ? 16384 : 0), 16, 2048, 2), dv = odesc(c.daddr(ur), 512, 2048, 2);
    if (!lo) { exp_rng<0, ATT_SPLIT>(a.s); sum_rng<0, 8>(a.s, a.l); cvt_p<0, 16>(a.s, a.p); }
    else if (gridDim.y == 1) cvt_p<8, 16>(a.s, a.p);
    tile_store_if<4, 8>(fresh, w.hi, a.dst);
    a.i0 += a.t0; a.i1 += a.t1;
    if (!fast || d == g + 1) {
      if (!fast && d != 1 && d != g - 15) {
#pragma unroll
        for (int i = 0; i < 16; i++) { a.o[4 * i] *= sc0; a.o[4 * i + 1] *= sc0; a.o[4 * i + 2] *= sc1; a.o[4 * i + 3] *= sc1; }
      }
      if (d == g + 1) break;
    }
    d++;
    fresh = d == 2 || d == g - 14;
    TSS(12 + 6 * (d - g + 15));
    c.turn();
    TSS(13 + 6 * (d - g + 15));
    fence_regs(a.o); fence_regs(a.p);
    wg_fence();
    issue_qk(a.s, dq, dk);
    TSS(14 + 6 * (d - g + 15));
    c.wait(c.wg ? uk ^ 12 : ur); c.skip(c.wg ? ur : uk ^ 12);
    if (fresh || d == 1 || (unsigned)(d - g + CHK_D) < 2) {
      if (fresh) pack_o(a.o, rcp(a.i0), rcp(a.i1), w.hi);
      else if (d == 1) {
        a.i0 = a.l[0] + a.l[1]; a.i1 = a.l[2] + a.l[3];
        a.t0 = __shfl_xor_sync(~0u, a.i0, 1); a.t1 = __shfl_xor_sync(~0u, a.i1, 1);
        a.l[0] = a.l[1] = a.l[2] = a.l[3] = 0.f;
        uint32_t off = ctx_off(c, h, 15 - g, c.wg);
        asm volatile("" : "+r"(off));
        a.dst = g_T + (off + ((uint32_t)(uint64_t)a.dst & 511));
        fast = fast2;
      } else if (d == g - CHK_D) fence_async_smem();
      else fast2 = att_fast(w.hi, a.kn);
    }
    TSS(15 + 6 * (d - g + 15));
    wgmma_pv_sel(a.o, a.p, dv, !lo, !fresh, c.wg);
    wg_wait<1>(); fence_regs(a.s);
    c.release(uk, 2);
    c.release(d == 0 ? 0 : 2, (d == 0 || d == g + 1) ? 2 : 0);
  }
  att_last(c, a, w, h, g, g == 0);
}

constexpr int CV_H = 1024, CV_U = 5120, CV_D = CV_U + 4128;
template<int OFF> __device__ __forceinline__ uint32_t lds32o(uint32_t a) { uint32_t v; asm volatile("ld.shared.u32 %0, [%1+%2];" : "=r"(v) : "r"(a), "n"(OFF) : "memory"); return v; }
template<int G, int G1 = 16> __device__ __forceinline__ void conv_lda(uint32_t (&a)[64], uint32_t p) {
  a[4 * G + 0] = lds32o<-256 * G>(p);
  a[4 * G + 1] = lds32o<-256 * G - 128>(p);
  a[4 * G + 2] = lds32o<-256 * G + 16>(p);
  a[4 * G + 3] = lds32o<-256 * G - 112>(p);
  if constexpr (G + 1 < G1) conv_lda<G + 1, G1>(a, p);
}
struct CvAcc { float lo[16], hi[16]; };
__device__ __forceinline__ void fence_regs(CvAcc& d) { fence_regs(d.lo); fence_regs(d.hi); }
template<int T, int G0, int G1> __device__ __forceinline__ void conv_part(float (&d)[16], const uint32_t (&a)[64], uint64_t db) {
#pragma unroll
  for (int G = G0; G < G1; G++) wgmma_rs_n32<0>(d, a[4 * G], a[4 * G + 1], a[4 * G + 2], a[4 * G + 3], db + 32 * T - 16 * G, G > 0);
}
template<int C0> __device__ __forceinline__ void conv_st_h(const float (&d)[16], uint32_t wq, float& c0, float& c1) {
#pragma unroll
  for (int n = 0; n < 4; n++) { sts64f(wq + (C0 + n * 8) * 4, d[4 * n] + c0, d[4 * n + 1] + c1); c0 = d[4 * n + 2]; c1 = d[4 * n + 3]; }
}
template<int R> __device__ __forceinline__ void conv_st(const CvAcc& d, uint32_t wq, float& c0, float& c1) { conv_st_h<64 * R>(d.lo, wq, c0, c1); conv_st_h<64 * R + 32>(d.hi, wq, c0, c1); }

constexpr int OC_PART = 13824, OC_ROW = 544;
__device__ __forceinline__ int out_next(int u) { return (0x84ac680u >> (2 * u)) & 15; }
struct Out { float acc[64]; int pu; uint64_t da, db; };
template<bool FIRST, bool REL, int W = 1> __device__ __forceinline__ void out_step(Cons& c, Out& o, bool extra = false) {
  const int pu = o.pu, u = extra ? 2 : out_next(pu);
  o.pu = u;
  c.wait(u);
  const uint64_t da = o.da + (uint32_t)(u * 1024), db = o.db + (uint32_t)(u * 1024);
  wg_fence();
#pragma unroll
  for (int kk = 0; kk < 4; kk++) wgmma_ss_n128<1>(o.acc, da + (kk >> 1) * 32 + (kk & 1) * 2, db + kk * 128, !(FIRST && kk == 0));
  wg_commit();
  if (REL) { wg_wait<W>(); c.release(pu, 2); }
}
template<int I0, int I1> __device__ __forceinline__ void oc_red(float (&y)[8], uint32_t rq) {
#pragma unroll
  for (int i = I0; i < I1; i++) { const float v = __uint_as_float(lds32(rq + i * OC_ROW - (i >> 3) * 8)); y[i & 7] = i < 8 ? v : y[i & 7] + v; }
}
template<int I0, int I1> __device__ __forceinline__ void oc_ld(float (&t)[32], uint32_t rq) {
#pragma unroll
  for (int i = I0; i < I1; i++) t[i] = __uint_as_float(lds32(rq + i * OC_ROW - (i >> 3) * 8));
}
__device__ __forceinline__ void oc_emit(const float (&y)[8], const uint4& u, uint32_t D2, uint8_t* dst) {
  uint4 z;
  z.x = hadd2(pack_bf16(y[0], y[1]), hmul2(__byte_perm(u.w, 0, 0x1032), D2));
  z.y = hadd2(pack_bf16(y[2], y[3]), hmul2(__byte_perm(u.z, 0, 0x1032), D2));
  z.z = hadd2(pack_bf16(y[4], y[5]), hmul2(__byte_perm(u.y, 0, 0x1032), D2));
  z.w = hadd2(pack_bf16(y[6], y[7]), hmul2(__byte_perm(u.x, 0, 0x1032), D2));
  *(uint4*)dst = z;
}
template<bool THR> __device__ __forceinline__ void conv_round(Cons& c, Out& o, int u, uint32_t ub, uint32_t wq, uint32_t rq, int ch) {
  const int r = c.lane >> 2, q = c.lane & 3, tid = c.warp * 32 + c.lane;
  const uint32_t ap = ub + CV_U + ((r & 1) ? 0 : UPITCH) + 4 * (((2039 - r) >> 1) + q - 8 * c.warp);
  uint32_t a[64];
  CvAcc d0, d1;
  float y[8], t[32], c0 = 0.f, c1 = 0.f;
  const uint64_t db0 = odesc(c.daddr(u) + CV_H - 16, 16, 128, 0);
#define STEP(N) if (THR) out_step<false, true>(c, o); else if (N == 0) c.turn(); else if (N == 10) wg_wait<0>();
#define STEP2(N) if (THR) out_step<false, true, 2>(c, o); else { if (N == 9) c.pass(); wg_wait<1>(); }
#define PART(...) { const uint64_t db = db0 + (c.mask >> 16); wg_fence(); __VA_ARGS__; wg_commit(); }
#define KEEP() asm volatile("add.f32 %0, %0, 0f80000000;" : "+f"(c0)); asm volatile("add.f32 %0, %0, 0f80000000;" : "+f"(c1));
  c.wait(u);
  conv_lda<0, THR ? 4 : 12>(a, ap);
  STEP(0)
  if (THR) conv_lda<4, 7>(a, ap);
  PART(conv_part<0, 0, 2>(d0.lo, a, db); conv_part<1, 0, 4>(d0.hi, a, db); conv_part<2, 0, 2>(d1.lo, a, db))
  STEP2(1)
  if (THR) conv_lda<7, 10>(a, ap);
  PART(conv_part<2, 2, 6>(d1.lo, a, db); conv_part<3, 0, 4>(d1.hi, a, db))
  STEP2(2)
  fence_regs(d0);
  if (THR) c.sync();
  sts64f(wq - 32, 0.f, 0.f);
  conv_st_h<0>(d0.lo, wq, c0, c1); KEEP()
  PART(conv_part<3, 4, 8>(d1.hi, a, db); conv_part<4, 0, 4>(d0.lo, a, db))
  STEP2(3)
  fence_regs(d1.lo);
  conv_st_h<32>(d0.hi, wq, c0, c1); conv_st_h<64>(d1.lo, wq, c0, c1); KEEP()
  PART(conv_part<4, 4, 10>(d0.lo, a, db); conv_part<5, 0, 2>(d0.hi, a, db))
  STEP2(4)
  fence_regs(d1.hi);
  float e0 = d1.hi[12] + d1.hi[10], e1 = d1.hi[13] + d1.hi[11];
  conv_st_h<96>(d1.hi, wq, c0, c1); KEEP()
  if (THR) conv_lda<10, 12>(a, ap);
  PART(conv_part<5, 2, 10>(d0.hi, a, db))
  STEP2(5)
  conv_lda<12, 14>(a, ap);
  c.sync();
  if (THR) oc_red<0, 6>(y, rq); else oc_ld<0, 8>(t, rq);
  PART(conv_part<5, 10, 12>(d0.hi, a, db); conv_part<6, 0, 6>(d1.lo, a, db))
  STEP2(6)
  if (THR) oc_red<6, 20>(y, rq); else oc_ld<8, 16>(t, rq);
  PART(conv_part<6, 6, 14>(d1.lo, a, db))
  STEP2(7)
  if (THR) oc_red<20, 26>(y, rq); else oc_ld<16, 24>(t, rq);
  conv_lda<14, 16>(a, ap);
  PART(conv_part<7, 0, 8>(d1.hi, a, db))
  STEP2(8)
  if (THR) oc_red<26, 32>(y, rq); else oc_ld<24, 32>(t, rq);
  PART(conv_part<7, 8, 16>(d1.hi, a, db))
  STEP2(9)
  if (!THR) {
#pragma unroll
    for (int i = 0; i < 8; i++) y[i] = t[i];
    SHADOW {
#pragma unroll
      for (int i = 0; i < 8; i++) y[i] = ((t[i] + t[8 + i]) + t[16 + i]) + t[24 + i];
    }
  }
  fence_regs(y); fence_regs(d0);
  c.sync();
  sts64f(wq - 32, e0, e1);
  conv_st<0>(d0, wq, c0, c1);
  STEP(10)
  fence_regs(d1); fence_regs(a);
  const uint4 u0 = lds128(ub + CV_U + 4080 - 16 * tid), u1 = lds128(ub + CV_U + 2032 - 16 * tid);
  const uint32_t D2 = lds32(ub + CV_D);
  conv_st<1>(d1, wq, c0, c1);
  STEP(11)
  sched_fence(__uint_as_float(u0.x ^ u1.x ^ D2), c.base + SM_DUMMY);
  uint8_t* zp = g_u + (uint32_t)(ch * UCH + (threadIdx.x & 127) * 16);
  oc_emit(y, u0, D2, zp);
  c.sync();
  c.release2(u);
  oc_red<0, 12>(y, rq);
  STEP(12)
  oc_red<12, 24>(y, rq);
  STEP(13)
  oc_red<24, 32>(y, rq);
  oc_emit(y, u1, D2, zp + 2048);
#undef KEEP
#undef STEP
#undef STEP2
#undef PART
}
template<int MASK> __device__ __forceinline__ void cons_conv(Cons& c, int cta, int nch) {
  const uint32_t part = c.addr(4 + 2 * c.wg) + 32;
  const uint32_t wq = part + (c.warp * 8 + (c.lane >> 2)) * OC_ROW + (c.lane & 3) * 8, rq = part + (c.warp * 32 + c.lane) * 4;
  Out o;
  c.wait(4);
#pragma unroll 1
  for (int i = 0; i < nch / 2; i++) {
    const int u = 2 * (i & 1) + c.wg;
    conv_round<false>(c, o, u, c.addr(u), wq, rq, conv_channel<MASK>(cta, 2 * i + c.wg));
    if ((i & 15) == 15 || i == nch / 2 - 1) c.signal(SIG_Z + (i >> 4));
  }
}
__device__ __forceinline__ uint32_t mix(uint32_t og, uint32_t b, uint32_t ga) { return hadd2(ga, hmul2(og, b)); }
template<int MASK> __device__ __forceinline__ void cons_out(Cons& c, const Maps& M, const Params& P, int cta, Pend& w) {
  const int mb = out_mb(cta), nb = out_nb(cta);
  Out o;
  o.da = odesc(c.daddr(0) + c.wg * 8192, 16, 1024, 2); o.db = odesc(c.daddr(1), 8192, 1024, 1);
  o.pu = 5 + gridDim.y;
  out_step<true, false>(c, o);
  int ks = 1;
  const uint32_t dst = ctx_off(c, 16 + (cta >> 3), cta & 7, 1 - c.wg);
#pragma unroll 1
  for (;; ks++) {
    if (MASK & PH_ATT) {
      if (ks == (c.wg ? ST_1 : 1)) tile_store<0, 1>(w.lo, dst, c.lane);
      if (ks == (c.wg ? ST_1 + ST_D : 1)) tile_store<1, 2>(w.lo, dst, c.lane);
      if (ks == (c.wg ? ST_1 + 2 * ST_D : 1)) tile_store<2, 3>(w.lo, dst, c.lane);
      if (ks == (c.wg ? ST_1 + 3 * ST_D : 1)) { tile_store<3, 4>(w.lo, dst, c.lane); c.signal(SIG_CTX + 1); }
    }
    if (ks == (c.wg ? OC_S1 : OC_S0)) break;
    out_step<false, true>(c, o, ks == 1);
  }
  if (MASK & PH_CONV) {
    const int r = c.lane >> 2, q = c.lane & 3, tid = c.warp * 32 + c.lane, u = 2 * c.wg;
    const uint32_t ub = c.addr(u), part = ub + OC_PART + 32;
    const uint32_t wq = part + (c.warp * 8 + r) * OC_ROW + q * 8, rq = part + tid * 4;
    int ch = conv_channel<MASK>(cta, 3 * c.wg);
#pragma unroll 1
    for (int i = 0; ch >= 0; i++) {
      conv_round<true>(c, o, u + (i >> 8), ub, wq, rq, ch);
      ch = i + c.wg < 2 ? ch + 1 : -1;
      if (c.wg > i) { mbar_wait(c.base + SM_RDY + 8 * RDY_T, 0); ch = __shfl_sync(~0u, lds32(c.base + SM_POOL), 0); }
      if (ch < 0) { c.signal(SIG_Z); c.sync(); c.release2(u + 1); TSO(0); }
      out_step<false, true>(c, o);
#pragma unroll 1
      for (int k = 15; k < (ch < 0 ? 0 : c.wg ? OC_L1 : OC_L0); k++) out_step<false, true>(c, o);
      ks += ch < 0 ? 15 : c.wg ? OC_L1 : OC_L0;
    }
    if (c.wg) c.skip(0);
  }
  TS(c.wg, 9);
#pragma unroll 1
  for (; ks < 57; ks++) out_step<false, true>(c, o);
  uint32_t ga[32];
  TSO(1);
  c.wait(3);
  TSO(2);
  const float g0 = __uint_as_float(lds32(c.base + SM_GATE + 4 * (c.wg * 64 + c.warp * 16 + (c.lane >> 2)))), g1 = __uint_as_float(lds32(c.base + SM_GATE + 32 + 4 * (c.wg * 64 + c.warp * 16 + (c.lane >> 2))));
  const uint32_t gg0 = pack_bf16(g0, g0), gg1 = pack_bf16(g1, g1);
  const uint32_t og0 = pack_bf16(1.f - g0, 1.f - g0), og1 = pack_bf16(1.f - g1, 1.f - g1);
  const int xr = c.wg * 64 + c.warp * 16 + (c.lane & 15);
  const uint32_t xa = c.addr(2) + xr * 128, xs = xr & 7, xh = c.lane >> 4;
  const int zr = (c.lane & 7) + ((c.lane >> 4) << 3);
  const uint32_t za = c.addr(0) + c.wg * 16384 + zr * 128 + (((c.warp * 2 + ((c.lane >> 3) & 1)) ^ (zr & 7)) << 4);
#pragma unroll
  for (int i = 0; i < 8; i++) {
    if (i == 0) out_step<false, true>(c, o);
    if (i == 3) out_step<false, true>(c, o);
    if (i == 6) out_step<false, true>(c, o);
    ldsm4(xa + (i >> 2) * 16384 + ((((i & 3) * 2 + xh) ^ xs) << 4), ga[4 * i], ga[4 * i + 1], ga[4 * i + 2], ga[4 * i + 3]);
  }
  TSO(3);
#pragma unroll 1
  for (ks = 60; ks < 64; ks++) out_step<false, false>(c, o);
  TSO(4);
  c.wait(0);
  TSO(5);
  SHADOW {
#pragma unroll
    for (int i = 0; i < 8; i++) {
      uint32_t z0, z1, z2, z3;
      ldsm4t(za + i * 2048, z0, z1, z2, z3);
      ga[4 * i + 0] = hmul2(ga[4 * i + 0], z0); ga[4 * i + 1] = hmul2(ga[4 * i + 1], z1); ga[4 * i + 2] = hmul2(ga[4 * i + 2], z2); ga[4 * i + 3] = hmul2(ga[4 * i + 3], z3);
      ga[4 * i + 0] = hmul2(gg0, ga[4 * i + 0]); ga[4 * i + 1] = hmul2(gg1, ga[4 * i + 1]); ga[4 * i + 2] = hmul2(gg0, ga[4 * i + 2]); ga[4 * i + 3] = hmul2(gg1, ga[4 * i + 3]);
    }
  }
  c.signal(SIG_DONE);
  fence_regs(ga);
  TSO(6);
  wg_wait<0>(); fence_regs(o.acc);
  TSO(7);
#pragma unroll
  for (int i = 0; i < 8; i++) {
    const uint32_t r0 = mix(og0, pack_bf16(o.acc[8 * i + 0], o.acc[8 * i + 1]), ga[4 * i + 0]);
    const uint32_t r1 = mix(og1, pack_bf16(o.acc[8 * i + 2], o.acc[8 * i + 3]), ga[4 * i + 1]);
    const uint32_t r2 = mix(og0, pack_bf16(o.acc[8 * i + 4], o.acc[8 * i + 5]), ga[4 * i + 2]);
    const uint32_t r3 = mix(og1, pack_bf16(o.acc[8 * i + 6], o.acc[8 * i + 7]), ga[4 * i + 3]);
    stsm4(xa + (i >> 2) * 16384 + ((((i & 3) * 2 + xh) ^ xs) << 4), r0, r1, r2, r3);
    if ((i & 3) == 3) {
      __syncwarp();
#pragma unroll
      for (int k = 0; k < 4; k++) {
        const int rr = c.wg * 64 + c.warp * 16 + k * 4 + (c.lane >> 3);
        const uint4 v = lds128(c.addr(2 + (i >> 2)) + rr * 128 + (((c.lane ^ rr) & 7) << 4));
        *(uint4*)(P.out + (uint32_t)((mb * 128 + rr) * 1024 + nb * 128 + (i >> 2) * 64 + (c.lane & 7) * 8)) = v;
      }
    }
  }
  TSO(8);
}

__device__ __forceinline__ void load_conv(Prod& p, const Maps& M, int u, int ch) {
  if (elect()) {
    mbar_expect(p.full(u), 5120 + UCH);
    tma3d(p.addr(u), &M.h, 0, -8, ch, p.full(u), true);
    bulk_g2s(p.addr(u) + CV_U, g_u + (size_t)ch * UCH, UCH, p.full(u), true);
  }
}
template<int MASK> __device__ __forceinline__ void prod_conv(Prod& p, const Maps& M, int cta, int nch) {
  int ready = -1;
#pragma unroll 1
  for (int i = 0; i < nch; i++) {
    const int ch = conv_channel<MASK>(cta, i);
    const int u = i & 3;
    if ((ch >> 6) != ready) { ready = ch >> 6; if (cta < NREG) mbar_wait(p.base + SM_RDY + 8 * RDY_U, 0); else cnt_wait(g_cnt + (C_U + ready) * CSTRIDE, 128); }
    p.acquire(u, 1);
    load_conv(p, M, u, ch);
    if (i == 3) { p.acquire(4, 4); if (elect()) mbar_arrive(p.full(4)); }
  }
}
#define HOIST(v) asm volatile("" : "+r"(v))
template<int MASK> __device__ __forceinline__ void producer(const Maps& M, const Params& P, uint32_t base, int cta, int lane) {
  Prod p{base, ((MASK & PH_KV) && cta < NREG) ? 0xffffcfffu ^ ((1u << (3 * NFIRST)) - 1) : 0xffffffffu, lane,
         (cta * 3 + 2) * 2048};
  if (cta >= NREG) { if (MASK & PH_CONV) prod_conv<MASK>(p, M, cta, CV_EXTRA<MASK>); return; }
  const int g = cta & 7, j = cta >> 3, rank = cta & 1;
#pragma unroll 1
  for (int half = 0; half < 2; half++) {
    const int h = j + 16 * half;
    if (MASK & PH_KV) {
      const CUtensorMap* mw = rank ? &M.wv : &M.wk;
#pragma unroll 1
      for (int it = half ? 0 : NFIRST; it < 16; it++) {
        const int u = gemm_unit(it);
        uint32_t bar = p.full(u), d0 = p.addr(u), d1 = p.addr(u + 1 + rank); int k0 = (it & 7) * 64, r0 = (2 * g + (it >> 3)) * 128;
        HOIST(bar); HOIST(d0); HOIST(d1); HOIST(k0); HOIST(r0);
        p.acquire(u, 3);
        if (elect()) {
          mbar_expect(bar, 3 * UNIT);
          tma3d_mc(d1, mw, 0, k0, 2 * h, bar, it >= 8);
          tma2d(d0, &M.c, k0, r0, bar);
        }
      }
    }
    if (MASK & PH_ATT) {
#pragma unroll 1
      for (int ks = 0; ks < 16; ks++) {
        const int u = gemm_unit(ks);
        uint32_t bar = p.full(u), d0 = p.addr(u), d1 = p.addr(u + 1), d2 = p.addr(u + 2) + rank * 8192; int k0 = ks * 64;
        HOIST(bar); HOIST(d0); HOIST(d1); HOIST(d2); HOIST(k0);
        p.acquire(u, 3);
        if (elect()) {
          mbar_expect(bar, 3 * UNIT);
          tma2d_mc(d2, &M.wq, h * 128 + rank * 64, k0, bar, true);
          tma2d(d0, &M.x, k0, (15 - g) * 128, bar);
          tma2d(d1, &M.x, k0, g * 128, bar);
        }
      }
      TS(2, 8 * half + 0);
      mbar_wait(base + SM_RDY + 8 * (RDY_KV + half), 0);
      TS(2, 8 * half + 1);
      const uint8_t* KVh = g_T + T_KV + (size_t)kv_slot<MASK>(h) * 16 * 65536;
      if (MASK & PH_PRE) mbar_wait(base + SM_RDY + 8 * RDY_AUX, 0);
      if (elect()) { mbar_expect(p.full(12), 32768); bulk_g2s(p.addr(12), KVh, 32768, p.full(12), true); }
      p.acquire(0, 4);
      if (elect()) mbar_arrive(p.full(0));
#pragma unroll 1
      for (int i = 1; i < 34; i++) {
        const int isv = !(i & 1) || i == 33, st = i == 33 ? 16 : (isv ? (i >> 1) - 1 : (i + 1) >> 1), u = 4 + 2 * (i & 3);
        const bool own = st == 15 - (g & 6);
        uint32_t bar = p.full(u), d0 = p.addr(own ? u : u + rank), off = (st <= 15 - g ? st : 16 - st) * 65536 + isv * 32768 + (own ? 0 : rank * UNIT);
        HOIST(bar); HOIST(d0); HOIST(off);
        p.acquire(u, 2);
        if (elect()) {
          mbar_expect(bar, 32768);
          if (own) bulk_g2s(d0, KVh + off, 32768, bar, true); else bulk_g2s_mc(d0, KVh + off, UNIT, bar, true);
        }
      }
    }
  }
  if ((MASK & PH_CONV) && !(MASK & PH_OUT)) prod_conv<MASK>(p, M, cta, CV_REG<MASK>);
  if (MASK & PH_OUT) {
    const int y0 = out_mb(cta) * 512 + rank * 8, z0 = 2 * out_nb(cta);
    int u = 6;
#pragma unroll 1
    for (int hf = 0; hf < 2; hf++) {
      TS(2, 16 + 2 * hf);
      mbar_wait(base + SM_RDY + 8 * (RDY_CTX + hf), 0);
      TS(2, 17 + 2 * hf);
#pragma unroll 1
      for (int n = hf * 32; n < hf * 32 + 32; n++) {
        const int ks = n == 1 ? 2 : n == 2 ? 1 : n;
        u = n == 2 ? 2 : n == 3 ? 10 : out_next(u);
        uint32_t bar = p.full(u), d0 = p.addr(u) + rank * 8192, d1 = p.addr(u + 1); int x = (ks & 1) * 256, y = y0 + (ks >> 1) * 16, k0 = ks * 64;
        HOIST(bar); HOIST(d0); HOIST(d1); HOIST(x); HOIST(y); HOIST(k0);
        p.acquire(u, 2);
        if (elect()) {
          mbar_expect(bar, 2 * UNIT);
          tma2d_mc(d0, &M.ctx, x, y, bar, true);
          tma3d(d1, &M.wo, 0, k0, z0, bar, true);
          if (ks == 1) mbar_arrive(base + SM_RDY + 8 * RDY_X);
          if (ks == Z_AT) mbar_arrive(base + SM_RDY + 8 * RDY_Z);
        }
      }
    }
  }
}
template<int MASK> __device__ __forceinline__ void producer2(const Maps& M, const Params& P, uint32_t base, int cta, int w, int lane) {
  Prod p{base, 0xffffffffu, lane, 0};
  const int mb = out_mb(cta), nb = out_nb(cta), u = 2 * w;
  if (w) { mbar_wait_slow(base + SM_RDY + 8 * RDY_X, 0); p.mask ^= 12; }
  if (MASK & PH_CONV) {
    mbar_wait_slow(base + SM_SIG + 8 * (SIG_ATT + 1), 0);
    mbar_wait_slow(base + SM_RDY + 8 * RDY_U, 0);
#pragma unroll 1
    for (int i = 0, ch = conv_channel<MASK>(cta, 3 * w); ch >= 0; i++) {
      p.acquire_slow(u, i ? 1 : 2);
      load_conv(p, M, u, ch);
      ch = i + w < 2 ? ch + 1 : -1;
      if (w > i) { mbar_wait_slow(base + SM_RDY + 8 * RDY_T, 0); ch = lds32(base + SM_POOL); }
    }
  }
  p.acquire_slow(u, 2);
  if (!w && elect()) map_pf(&M.z);
  TSA(52 - 2 * w);
  mbar_wait(base + SM_RDY + 8 * (!w ? RDY_Z : RDY_G), 0);
  TSA(53 - 2 * w);
  if (elect()) {
    const uint32_t bar = p.full(3 * w);
    mbar_expect(bar, 2 * UNIT + (!w ? 0 : 512));
    tma2d(p.addr(u), !w ? &M.z : &M.x, (!w ? mb : nb) * 128, (!w ? nb : mb) * 128, bar, true);
    tma2d(p.addr(u + 1), !w ? &M.z : &M.x, (!w ? mb : nb) * 128 + 64, (!w ? nb : mb) * 128, bar, true);
    if (w) bulk_g2s(base + SM_GATE, g_gate + mb * 128, 512, bar);
  }
}

__device__ __forceinline__ constexpr uint32_t PUB(int sig, int cnt, int n) { return 0x80000000u | (sig << 24) | (n << 8) | cnt; }
__device__ __forceinline__ constexpr uint32_t GET(int rdy, int cnt, int n) { return (rdy << 24) | (n << 8) | cnt; }
template<int MASK> __device__ __forceinline__ void sync_agent(uint32_t base, int cta, int lane) {
  if ((base & 0x3FFFF) != SMEM_BASE) asm volatile("trap;");
  const int g = cta & 7, j = cta >> 3, go = min(out_mb(cta), 15 - out_mb(cta));
  const int c0 = conv_channel<MASK>(cta, 0), c1 = c0 + CV_REG<MASK> - 1, n0 = min(CV_REG<MASK>, 128 - (c0 & 127));
  constexpr bool KV = MASK & PH_KV, ATT = MASK & PH_ATT, CONV = MASK & PH_CONV, OUT = MASK & PH_OUT, ALL = MASK == PH_ALL;
  uint32_t e = 0;
  if (cta >= NREG) { if (CONV && lane * 32 < CV_EXTRA<MASK>) e = PUB(SIG_Z + lane, C_Z + lane, min(32, CV_EXTRA<MASK> - lane * 32)); }
  else switch (lane) {
    case 0:  if (KV) e = PUB(SIG_KV, C_KV + j, 1); break;
    case 1:  if (ATT) e = GET(RDY_KV, C_KV + j, 8); break;
    case 2:  if (ALL) e = PUB(SIG_WAR, C_WAR + j, 1); break;
    case 3:  if (ATT) e = PUB(SIG_CTX, C_CTX + g, 1); break;
    case 4:  if (ALL) e = GET(RDY_WAR, C_WAR + j, 8); break;
    case 5:  if (KV) e = PUB(SIG_KV + 1, C_KV + 16 + j, 1); break;
    case 6:  if (ATT) e = GET(RDY_KV + 1, C_KV + 16 + j, 8); break;
    case 7:  if (OUT) e = GET(RDY_CTX, C_CTX + go, 16); break;
    case 8:  if (CONV) e = GET(RDY_U, C_U + (c0 >> 6), 128); break;
    case 9:  if (CONV) e = GET(ALL ? RDY_NONE : RDY_U, C_U + (ALL ? 14 : c1 >> 6), 128); break;
    case 10: if (ALL) e = GET(RDY_T, C_U + 15, 128); break;
    case 11: if (ATT) e = PUB(SIG_CTX + 1, C_CTX + 8 + g, 1); break;
    case 12: if (OUT) e = GET(RDY_CTX + 1, C_CTX + 8 + go, 16); break;
    case 13: if (OUT) e = GET(RDY_G, C_GATE, 256); break;
    case 14: if (CONV) e = PUB(SIG_Z, C_Z + (c0 >> 7), n0); break;
    case 15: if (ALL) e = PUB(SIG_Z, C_Z + 7, 1); else if (CONV && n0 < CV_REG<MASK>) e = PUB(SIG_Z, C_Z + (c1 >> 7), CV_REG<MASK> - n0); break;
    case 16: if (OUT) e = GET(RDY_Z, C_Z + out_nb(cta), 128); break;
  }
  if (ALL && lane == 0) { mbar_expect(base + SM_RDY + 8 * RDY_T, 4); mbar_arrive(base + SM_RDY + 8 * RDY_U); }
  __syncwarp();
#pragma unroll 1
  for (int i = 0; i < 17; i++) {
    const uint32_t x = __shfl_sync(~0u, e, i), id = (x >> 24) & 127, n = (x >> 8) & 0xffff;
    if (x == 0) continue;
    unsigned* cnt = g_cnt + (x & 255) * CSTRIDE;
    if (x >> 31) {
      mbar_wait_slow(base + SM_SIG + 8 * id, 0);
      const bool draw = ALL && i == 11 && !(cta & 1);
      unsigned t = 0;
      if (draw && lane == 0) asm volatile("atom.relaxed.gpu.global.add.u32 %0, [%1], 1;" : "=r"(t) : "l"(g_cnt + C_TICKET * CSTRIDE) : "memory");
      if (lane == 0 && !(ALL && i == 15 && (int)lds32(base + SM_POOL) < 0)) cnt_publish(cnt, n, i != 15);
      if (draw) {
        t = __shfl_sync(~0u, t, 0);
        uint32_t peer;
        asm volatile("mapa.shared::cluster.u32 %0, %1, %2;" : "=r"(peer) : "r"(base), "r"(lane & 1));
        if (lane < 2) asm volatile("st.async.weak.shared::cluster.mbarrier::complete_tx::bytes.u32 [%0], %1, [%2];"
          :: "r"(peer + SM_POOL), "r"(t < 64 - NSKIP ? CV_POOL + 2 * t + lane : ~0u), "r"(peer + SM_RDY + 8 * RDY_T) : "memory");
      }
    } else {
      cnt_wait(cnt, n);
      if (id < 2) {
        const float4 kn = __ldcg((const float4*)(g_kn2 + kv_slot<MASK>(j + 16 * id) * 128) + lane);
        const uint32_t m = __reduce_max_sync(~0u, max(max(__float_as_uint(kn.x), __float_as_uint(kn.y)), max(__float_as_uint(kn.z), __float_as_uint(kn.w))));
        if (lane == 0) asm volatile("st.shared.u32 [%0], %1;" :: "r"(base + SM_KMAX + 4 * id), "r"(m) : "memory");
      }
      if (lane == 0) mbar_arrive(base + SM_RDY + 8 * id);
    }
    __syncwarp();
  }
}

__device__ __forceinline__ void aux_gate(const Params& P, int cta, int aw, int lane) {
  uint4 gw[4];
#pragma unroll
  for (int i = 0; i < 4; i++) gw[i] = __ldg((const uint4*)P.gw + i * 32 + lane);
#pragma unroll 1
  for (int row = cta * 16 + aw * 8; row < cta * 16 + aw * 8 + 8; row++) {
    float a = 0.f;
#pragma unroll
    for (int i = 0; i < 4; i++) {
      const uint4 xv = __ldg((const uint4*)(P.x + (size_t)row * 1024) + i * 32 + lane);
      uint32_t m;
      m = hmul2(xv.x, gw[i].x); a += bf_lo(m) + bf_hi(m); m = hmul2(xv.y, gw[i].y); a += bf_lo(m) + bf_hi(m);
      m = hmul2(xv.z, gw[i].z); a += bf_lo(m) + bf_hi(m); m = hmul2(xv.w, gw[i].w); a += bf_lo(m) + bf_hi(m);
    }
#pragma unroll
    for (int o = 16; o > 0; o >>= 1) a += __shfl_xor_sync(~0u, a, o);
    a = bf_lo(pack_bf16(a, 0.f));
    const float gt = bf_lo(pack_bf16(__fdividef(1.f, 1.f + ex2(-a * 1.4426950408889634f)), 0.f));
    if (lane == 0) g_gate[row] = gt;
    __nanosleep(GATE_SLEEP);
  }
  cnt_signal(g_cnt + C_GATE * CSTRIDE, lane);
  if (aw == 0) { TSA(44); }
}
template<int MASK> __device__ __forceinline__ void aux_pre(const Maps& M, const Params& P, uint32_t base, int cta, int aw, int lane) {
  const uint32_t kb = base + 12 * UNIT, bar = base + SM_PRE;
  const int r = lane >> 2, q = lane & 3;
  const int mi = lane >> 3, row0 = (lane & 6) + 1 - (lane & 1);
  const int ra = (mi * 9 + 1) * 2 + row0;
  const int rb = (mi == 0 ? 3 : mi) * 18 + row0;
#pragma unroll 1
  for (int it = 0; it < (cta < 96 ? 5 : 4); it++) {
    if (it == PRE_EARLY && MASK == PH_ALL) { mbar_wait_slow(base + SM_SIG + 8 * SIG_ATT, 0); aux_gate(P, cta, aw, lane); }
    if (it == PRE_EARLY && MASK == PH_ALL) mbar_wait_slow(base + SM_SIG + 8 * (SIG_ATT + 1), 0);
    const int cg = it ? it * 4 - 3 + (cta >> 5) : 0, tb = cta & 31;
    if (it == 0 && aw == 0) TSA(45);
    if (aw == 0 && elect()) {
      mbar_expect(bar, 2 * 9216);
      tma4d(kb, &M.k, cg * 64, 0, tb * 8 - 1, 0, bar, true);
      tma4d(kb + 9216, &M.v, cg * 64, 0, tb * 8 - 1, 0, bar, true);
    }
    const uint2 swl = __ldg((const uint2*)(P.shift + (cg * 64 + aw * 32 + lane) * 4));
    if (tb == 0) {
      uint8_t* e = g_u + (size_t)(cg * 64 + aw * 32 + lane) * UCH + 4096;
      *(uint4*)e = make_uint4(0, 0, 0, 0); *(uint4*)(e + UPITCH) = make_uint4(0, 0, 0, 0);
      *(uint32_t*)(e + 32) = (uint32_t)__bfloat16_as_ushort(P.D[cg * 64 + aw * 32 + lane]) * 0x10001u;
    }
    if (it == 0 && aw == 0) TSA(46);
    if (it == 0) mbar_wait(bar, 0); else mbar_wait_slow(bar, it & 1);
    if (it == 0 && aw == 0) TSA(47);
#pragma unroll 1
    for (int ol = it ? 0 : cta >> 5; ol < (it ? 4 : (cta >> 5) + 1); ol++) {
      const int oc = aw * 4 + ol;
      const uint32_t s01 = __shfl_sync(~0u, swl.x, ol * 8 + r), s23 = __shfl_sync(~0u, swl.y, ol * 8 + r);
      const uint32_t w0 = __byte_perm(s01, 0, 0x1010), w1 = __byte_perm(s01, 0, 0x3232), w2 = __byte_perm(s23, 0, 0x1010), w3 = __byte_perm(s23, 0, 0x3232);
      const uint32_t pa = kb + ra * 128 + ((oc ^ (ra & 7)) << 4), pb = kb + (mi == 0 ? 9216 : 0) + rb * 128 + ((oc ^ (rb & 7)) << 4);
      uint8_t* e0 = g_u + (uint32_t)((cg * 64 + oc * 8 + r) * UCH + (2040 - tb * 64 - 8 * q) * 2);
#pragma unroll
      for (int hb = 0; hb < 2; hb++) {
        uint32_t k[7], v[5];
        ldsm4t(pa + hb * 1024, k[3], k[4], k[5], k[6]);
        ldsm4t(pa + hb * 1024 + 9216, v[1], v[2], v[3], v[4]);
        ldsm4t(pb + hb * 1024, v[0], k[0], k[1], k[2]);
        uint32_t o1 = __byte_perm(k[1], k[0], 0x5432);
#pragma unroll
        for (int m = 0; m < 5; m++) {
          const uint32_t o2 = __byte_perm(k[m + 2], k[m + 1], 0x5432);
          v[m] = hmul2(hadd2(hadd2(hadd2(hmul2(o1, w3), hmul2(k[m + 1], w2)), hmul2(o2, w1)), hmul2(k[m + 2], w0)), v[m]);
          o1 = o2;
        }
        *(uint4*)(e0 - hb * 64) = make_uint4(v[4], v[3], v[2], v[1]);
        *(uint4*)(e0 - hb * 64 + UPITCH) = make_uint4(__byte_perm(v[4], v[3], 0x5432), __byte_perm(v[3], v[2], 0x5432), __byte_perm(v[2], v[1], 0x5432), __byte_perm(v[1], v[0], 0x5432));
        if (it >= PRE_EARLY) __nanosleep(PRE_SLEEP);
      }
    }
    bar_sync(5, 64);
    if (aw == 0) { TSA(40 + min(it, 3)); }
    if (it == PRE_EARLY - 1 && aw == 0 && lane == 0) mbar_arrive(base + SM_RDY + 8 * RDY_AUX);
    if (aw == 1 && lane == 0) asm volatile("red.release.gpu.global.add.u32 [%0], %1;" :: "l"(g_cnt + (C_U + cg) * CSTRIDE), "r"(it ? 4 : 1) : "memory");
    if (it == 0 && aw == 1) TSA(48);
  }
  uint32_t rel;
  asm volatile("mapa.shared::cluster.u32 %0, %1, %2;" : "=r"(rel) : "r"(base + SM_BAR + 128 + 8 * (12 + (lane & 1))), "r"((lane >> 1) & 1));
  if (lane < 4) asm volatile("mbarrier.arrive.shared::cluster.b64 _, [%0];" :: "r"(rel) : "memory");
  if (MASK != PH_ALL) aux_gate(P, cta, aw, lane);
}

template<int MASK> __global__ void __cluster_dims__(2, 1, 1) __launch_bounds__(384, 1) gated_mix_kernel(const __grid_constant__ Maps M, const __grid_constant__ Params P) {
  extern __shared__ __align__(1024) uint8_t smem[];
  const uint32_t base = (uint32_t)__cvta_generic_to_shared(smem);
  if ((MASK & PH_KV) && elect()) {
    map_pf(&M.wk + (blockIdx.x & 1)); map_pf(&M.c);
  }
  const int wi = __shfl_sync(~0u, threadIdx.x >> 5, 0), wg = wi >> 2, warp = wi & 3;
  if (elect()) {
    if (wi < 8) {
      const int cnt = 1 << ((0x10332200 >> (4 * wi)) & 15);
#pragma unroll
      for (int i = 0; i < 8; i++) mbar_init(base + SM_BAR + 64 * wi + 8 * i, cnt);
      asm volatile("fence.mbarrier_init.release.cluster;" ::: "memory");
    }
  }
  const int cta = blockIdx.x;
  const bool first_loads = (MASK & PH_KV) && wi == 8 && cta < NREG;
  const CUtensorMap* mw = (cta & 1) ? &M.wv : &M.wk;
  __syncwarp();
  asm volatile("barrier.cluster.arrive.relaxed.aligned;\nbarrier.cluster.wait.aligned;" ::: "memory");
  auto first_stage = [&](int it) {
    const uint32_t bar = base + SM_BAR + 24 * it, d0 = base + 3 * it * UNIT;
    mbar_expect(bar, 3 * UNIT);
    tma3d_mc(d0 + (1 + (cta & 1)) * UNIT, mw, 0, it * 64, 2 * (cta >> 3), bar);
    tma2d(d0, &M.c, it * 64, (cta & 7) * 256, bar);
  };
  if (first_loads && elect()) first_stage(0);
  __syncwarp();
  const int lane = threadIdx.x & 31;
#define TS_PRO()
  if (wg == 2) {
    asm volatile("setmaxnreg.dec.sync.aligned.u32 56;");
    TS_PRO();
    TS(2, 62);
    if (warp == 0) producer<MASK>(M, P, base, cta, lane);
    else if (warp == 1) sync_agent<MASK>(base, cta, lane);
    else if (cta < NREG) {
      if (MASK & PH_PRE) aux_pre<MASK>(M, P, base, cta, warp - 2, lane);
      if (MASK & PH_OUT) producer2<MASK>(M, P, base, cta, warp - 2, lane);
    }
    if (warp == 1) {
      if (MASK & PH_OUT) {
        unsigned old = 0;
        if (lane == 0) asm volatile("atom.relaxed.gpu.global.add.u32 %0, [%1], 1;" : "=r"(old) : "l"(g_cnt + C_EXIT * CSTRIDE) : "memory");
        old = __shfl_sync(~0u, old, 0);
        if (old == NCTA - 1) for (int i = lane; i < C_NUM; i += 32) g_cnt[i * CSTRIDE] = 0;
      }
      mbar_wait_slow(base + SM_SIG + 8 * SIG_DONE, 0);
      if (cta >= NREG || !(MASK & PH_OUT)) { cluster_arrive(); cluster_wait(); }
    }
  } else {
    asm volatile("setmaxnreg.inc.sync.aligned.u32 224;");
    TS_PRO();
    uint32_t rel;
    asm volatile("mapa.shared::cluster.u32 %0, %1, %2;" : "=r"(rel) : "r"(base + SM_BAR + 128 + 8 * (lane & 15)), "r"(lane >> 4));
    Cons c{base, rel, 0u, lane, warp, wg, warp == 3 ? lane & 15 : 16, (cta * 3 + wg) * 2048};
    if (wg == 1) bar_arrive(1, 256);
    if ((MASK & PH_KV) && wi == 4 && cta < NREG) {
      if (elect()) {
#pragma unroll 1
        for (int it = 1; it < NFIRST; it++) {
          asm volatile("{\n.reg .pred p;\n.reg .u32 a, b;\nmov.u32 a, %%clock;\nXL:\nmov.u32 b, %%clock;\nsub.u32 b, b, a;\nsetp.lt.u32 p, b, %0;\n@p bra XL;\n}\n" :: "r"(it == 1 ? FGAP : FGAP2) : "memory");
          first_stage(it);
        }
      }
      __syncwarp();
    }
    TS(wg, 0);
    if (cta < NREG) {
      const int g = cta & 7, j = cta >> 3;
      Pend w = {};
#pragma unroll 1
      for (int half = 0; half < 2; half++) {
        const int h = j + 16 * half, blk = kv_slot<MASK>(h) * 16 + 2 * g;
        if (MASK & PH_KV) cons_kv<(MASK & PH_ATT) != 0>(c, h, blk, g, w, half == 1 && (MASK & PH_ATT));
        TS(wg, 1 + 4 * half);
        if (MASK & PH_ATT) {
          Att a;
          cons_q<(MASK & PH_KV) != 0>(c, h, blk + 1, w, a.o);
          TS(wg, 2 + 4 * half);
          cons_att(c, a, h, g, w);
          if (half == 0) c.signal(SIG_WAR);
#pragma unroll
          for (int i = 0; i < 8; i++) w.hi[i] = make_uint4(0, 0, 0, 0);
          TS(wg, 3 + 4 * half);
          if (MASK != PH_ALL) { tile_store<0, 4>(w.lo, ctx_off(c, h, g, 1 - wg), lane); c.signal(SIG_CTX + half); }
        } else if (MASK & PH_KV) {
          float kn = 0.f;
          out_piece<SCH_KV, true>(c, w, kv_off(c, blk + 1), blk + 1, kn, 0, true);
          for (int ks = 1; ks < 8; ks++) out_piece<SCH_KV, false>(c, w, kv_off(c, blk + 1), blk + 1, kn, ks, true);
          c.signal(SIG_KV + half);
        }
      }
      if (MASK & PH_OUT) cons_out<MASK>(c, M, P, cta, w);
    }
    if (cta >= NREG || !(MASK & PH_OUT)) {
      if (MASK & PH_CONV) cons_conv<MASK>(c, cta, cta < NREG ? CV_REG<MASK> : CV_EXTRA<MASK>);
      TS(wg, 9);
      c.signal(SIG_DONE);
      cluster_arrive();
    }
    TS(wg, 10);
  }
}

typedef CUresult (*EncFn)(CUtensorMap*, CUtensorMapDataType, cuuint32_t, void*, const cuuint64_t*, const cuuint64_t*, const cuuint32_t*, const cuuint32_t*,
                          CUtensorMapInterleave, CUtensorMapSwizzle, CUtensorMapL2promotion, CUtensorMapFloatOOBfill);
static void enc(EncFn f, CUtensorMap* m, const void* ptr, int rank, const cuuint64_t* dims, const cuuint64_t* strides, const cuuint32_t* box, CUtensorMapSwizzle sw,
                CUtensorMapDataType dt = CU_TENSOR_MAP_DATA_TYPE_BFLOAT16) {
  const cuuint32_t es[4] = {1, 1, 1, 1};
  f(m, dt, rank, (void*)ptr, dims, strides, box, es, CU_TENSOR_MAP_INTERLEAVE_NONE, sw, CU_TENSOR_MAP_L2_PROMOTION_L2_256B, CU_TENSOR_MAP_FLOAT_OOB_FILL_NONE);
}
static void enc2(EncFn f, CUtensorMap* m, const void* ptr, int cols, int rows, int brows) {
  const cuuint64_t d[2] = {(cuuint64_t)cols, (cuuint64_t)rows}, s[1] = {(cuuint64_t)cols * 2}; const cuuint32_t b[2] = {64, (cuuint32_t)brows};
  enc(f, m, ptr, 2, d, s, b, CU_TENSOR_MAP_SWIZZLE_128B);
}
static void encw(EncFn f, CUtensorMap* m, const void* ptr, int cols, int rows) {
  const cuuint64_t d[3] = {64, (cuuint64_t)rows, (cuuint64_t)cols / 64}, s[2] = {(cuuint64_t)cols * 2, 128}; const cuuint32_t b[3] = {64, 64, 2};
  enc(f, m, ptr, 3, d, s, b, CU_TENSOR_MAP_SWIZZLE_128B);
}
extern "C" void kernel_launch(void* const* d_in, const int* in_sizes, int n_in, void* d_out, int out_size) {
  static EncFn fn = nullptr;
  static int ncl = 0;
  static void* zptr = nullptr;
  static void* tptr = nullptr;
  if (!fn) {
    void* p = nullptr; cudaDriverEntryPointQueryResult qr;
    cudaGetDriverEntryPoint("cuTensorMapEncodeTiled", &p, cudaEnableDefault, &qr);
    fn = (EncFn)p;
    cudaFuncSetAttribute(gated_mix_kernel<PH_ALL>, cudaFuncAttributeMaxDynamicSharedMemorySize, SMEM_BYTES);
    cudaFuncSetAttribute(gated_mix_kernel<PH_PRE | PH_KV>, cudaFuncAttributeMaxDynamicSharedMemorySize, SMEM_BYTES);
    cudaFuncSetAttribute(gated_mix_kernel<PH_ATT | PH_CONV>, cudaFuncAttributeMaxDynamicSharedMemorySize, SMEM_BYTES);
    cudaFuncSetAttribute(gated_mix_kernel<PH_OUT>, cudaFuncAttributeMaxDynamicSharedMemorySize, SMEM_BYTES);
    cudaLaunchConfig_t cfg = {}; cfg.gridDim = NCTA; cfg.blockDim = 384; cfg.dynamicSmemBytes = SMEM_BYTES;
    cudaLaunchAttribute at; at.id = cudaLaunchAttributeClusterDimension; at.val.clusterDim.x = 2; at.val.clusterDim.y = 1; at.val.clusterDim.z = 1;
    cfg.attrs = &at; cfg.numAttrs = 1;
    cudaOccupancyMaxActiveClusters(&ncl, gated_mix_kernel<PH_ALL>, &cfg);
    cudaGetSymbolAddress(&zptr, g_u);
    cudaGetSymbolAddress(&tptr, g_T);
  }
  Maps M;
  enc2(fn, &M.x, d_in[0], 1024, 2048, 128);
  enc2(fn, &M.c, d_in[7], 512, 2048, 128);
  enc2(fn, &M.wq, d_in[8], 4096, 1024, 64);
  encw(fn, &M.wk, d_in[9], 4096, 512);
  encw(fn, &M.wv, d_in[10], 4096, 512);
  encw(fn, &M.wo, d_in[11], 1024, 4096);
  { const cuuint64_t d[3] = {64, 32, 1024}, s[2] = {128, 4096}; const cuuint32_t b[3] = {64, 40, 1}; enc(fn, &M.h, d_in[4], 3, d, s, b, CU_TENSOR_MAP_SWIZZLE_NONE); }
  { const cuuint64_t d[2] = {2048, 1024}, s[1] = {UCH}; const cuuint32_t b[2] = {64, 128}; enc(fn, &M.z, zptr, 2, d, s, b, CU_TENSOR_MAP_SWIZZLE_128B); }
  { const cuuint64_t d[2] = {512, 512 * 16}, s[1] = {2048}; const cuuint32_t b[2] = {256, 8};
    enc(fn, &M.ctx, tptr, 2, d, s, b, CU_TENSOR_MAP_SWIZZLE_NONE, CU_TENSOR_MAP_DATA_TYPE_UINT32); }
  { const cuuint64_t d[4] = {1024, 2, 256, 4}, s[3] = {2048, 16384, 4096}; const cuuint32_t b[4] = {64, 2, 9, 4};
    enc(fn, &M.k, d_in[1], 4, d, s, b, CU_TENSOR_MAP_SWIZZLE_128B); enc(fn, &M.v, d_in[2], 4, d, s, b, CU_TENSOR_MAP_SWIZZLE_128B); }
  Params P{(const __nv_bfloat16*)d_in[0], (const __nv_bfloat16*)d_in[3],
           (const __nv_bfloat16*)d_in[5], (const __nv_bfloat16*)d_in[12], (__nv_bfloat16*)d_out};
  bool split = 2 * ncl < NCTA;
  if (!split) {
    gated_mix_kernel<PH_ALL><<<NCTA, 384, SMEM_BYTES>>>(M, P);
  } else {
    gated_mix_kernel<PH_PRE | PH_KV><<<NCTA, 384, SMEM_BYTES>>>(M, P);
    gated_mix_kernel<PH_ATT | PH_CONV><<<NCTA, 384, SMEM_BYTES>>>(M, P);
    gated_mix_kernel<PH_OUT><<<NCTA, 384, SMEM_BYTES>>>(M, P);
  }
}
```

```cpp
#include <cuda_runtime.h>
#include <cuda.h>
#include <cuda_bf16.h>
#include <stdint.h>

template<int TB> __device__ __forceinline__ void wgmma_ss_n256(float (&d)[128], uint64_t da, uint64_t db, int scale_d) {
  asm volatile("{\n.reg .pred p;\nsetp.ne.b32 p, %130, 0;\n"
    "wgmma.mma_async.sync.aligned.m64n256k16.f32.bf16.bf16 {%0, %1, %2, %3, %4, %5, %6, %7, %8, %9, %10, %11, %12, %13, %14, %15, %16, %17, %18, %19, %20, %21, %22, %23, %24, %25, %26, %27, %28, %29, %30, %31, %32, %33, %34, %35, %36, %37, %38, %39, %40, %41, %42, %43, %44, %45, %46, %47, %48, %49, %50, %51, %52, %53, %54, %55, %56, %57, %58, %59, %60, %61, %62, %63, %64, %65, %66, %67, %68, %69, %70, %71, %72, %73, %74, %75, %76, %77, %78, %79, %80, %81, %82, %83, %84, %85, %86, %87, %88, %89, %90, %91, %92, %93, %94, %95, %96, %97, %98, %99, %100, %101, %102, %103, %104, %105, %106, %107, %108, %109, %110, %111, %112, %113, %114, %115, %116, %117, %118, %119, %120, %121, %122, %123, %124, %125, %126, %127}, %128, %129, p, 1, 1, 0, %131;\n}\n"
    : "+f"(d[0]), "+f"(d[1]), "+f"(d[2]), "+f"(d[3]), "+f"(d[4]), "+f"(d[5]), "+f"(d[6]), "+f"(d[7]), "+f"(d[8]), "+f"(d[9]), "+f"(d[10]), "+f"(d[11]), "+f"(d[12]), "+f"(d[13]), "+f"(d[14]), "+f"(d[15]), "+f"(d[16]), "+f"(d[17]), "+f"(d[18]), "+f"(d[19]), "+f"(d[20]), "+f"(d[21]), "+f"(d[22]), "+f"(d[23]), "+f"(d[24]), "+f"(d[25]), "+f"(d[26]), "+f"(d[27]), "+f"(d[28]), "+f"(d[29]), "+f"(d[30]), "+f"(d[31]), "+f"(d[32]), "+f"(d[33]), "+f"(d[34]), "+f"(d[35]), "+f"(d[36]), "+f"(d[37]), "+f"(d[38]), "+f"(d[39]), "+f"(d[40]), "+f"(d[41]), "+f"(d[42]), "+f"(d[43]), "+f"(d[44]), "+f"(d[45]), "+f"(d[46]), "+f"(d[47]), "+f"(d[48]), "+f"(d[49]), "+f"(d[50]), "+f"(d[51]), "+f"(d[52]), "+f"(d[53]), "+f"(d[54]), "+f"(d[55]), "+f"(d[56]), "+f"(d[57]), "+f"(d[58]), "+f"(d[59]), "+f"(d[60]), "+f"(d[61]), "+f"(d[62]), "+f"(d[63]), "+f"(d[64]), "+f"(d[65]), "+f"(d[66]), "+f"(d[67]), "+f"(d[68]), "+f"(d[69]), "+f"(d[70]), "+f"(d[71]), "+f"(d[72]), "+f"(d[73]), "+f"(d[74]), "+f"(d[75]), "+f"(d[76]), "+f"(d[77]), "+f"(d[78]), "+f"(d[79]), "+f"(d[80]), "+f"(d[81]), "+f"(d[82]), "+f"(d[83]), "+f"(d[84]), "+f"(d[85]), "+f"(d[86]), "+f"(d[87]), "+f"(d[88]), "+f"(d[89]), "+f"(d[90]), "+f"(d[91]), "+f"(d[92]), "+f"(d[93]), "+f"(d[94]), "+f"(d[95]), "+f"(d[96]), "+f"(d[97]), "+f"(d[98]), "+f"(d[99]), "+f"(d[100]), "+f"(d[101]), "+f"(d[102]), "+f"(d[103]), "+f"(d[104]), "+f"(d[105]), "+f"(d[106]), "+f"(d[107]), "+f"(d[108]), "+f"(d[109]), "+f"(d[110]), "+f"(d[111]), "+f"(d[112]), "+f"(d[113]), "+f"(d[114]), "+f"(d[115]), "+f"(d[116]), "+f"(d[117]), "+f"(d[118]), "+f"(d[119]), "+f"(d[120]), "+f"(d[121]), "+f"(d[122]), "+f"(d[123]), "+f"(d[124]), "+f"(d[125]), "+f"(d[126]), "+f"(d[127])
    : "l"(da), "l"(db), "r"(scale_d), "n"(TB));
}
template<int TB> __device__ __forceinline__ void wgmma_ss_n128(float (&d)[64], uint64_t da, uint64_t db, int scale_d) {
  asm volatile("{\n.reg .pred p;\nsetp.ne.b32 p, %66, 0;\n"
    "wgmma.mma_async.sync.aligned.m64n128k16.f32.bf16.bf16 {%0, %1, %2, %3, %4, %5, %6, %7, %8, %9, %10, %11, %12, %13, %14, %15, %16, %17, %18, %19, %20, %21, %22, %23, %24, %25, %26, %27, %28, %29, %30, %31, %32, %33, %34, %35, %36, %37, %38, %39, %40, %41, %42, %43, %44, %45, %46, %47, %48, %49, %50, %51, %52, %53, %54, %55, %56, %57, %58, %59, %60, %61, %62, %63}, %64, %65, p, 1, 1, 0, %67;\n}\n"
    : "+f"(d[0]), "+f"(d[1]), "+f"(d[2]), "+f"(d[3]), "+f"(d[4]), "+f"(d[5]), "+f"(d[6]), "+f"(d[7]), "+f"(d[8]), "+f"(d[9]), "+f"(d[10]), "+f"(d[11]), "+f"(d[12]), "+f"(d[13]), "+f"(d[14]), "+f"(d[15]), "+f"(d[16]), "+f"(d[17]), "+f"(d[18]), "+f"(d[19]), "+f"(d[20]), "+f"(d[21]), "+f"(d[22]), "+f"(d[23]), "+f"(d[24]), "+f"(d[25]), "+f"(d[26]), "+f"(d[27]), "+f"(d[28]), "+f"(d[29]), "+f"(d[30]), "+f"(d[31]), "+f"(d[32]), "+f"(d[33]), "+f"(d[34]), "+f"(d[35]), "+f"(d[36]), "+f"(d[37]), "+f"(d[38]), "+f"(d[39]), "+f"(d[40]), "+f"(d[41]), "+f"(d[42]), "+f"(d[43]), "+f"(d[44]), "+f"(d[45]), "+f"(d[46]), "+f"(d[47]), "+f"(d[48]), "+f"(d[49]), "+f"(d[50]), "+f"(d[51]), "+f"(d[52]), "+f"(d[53]), "+f"(d[54]), "+f"(d[55]), "+f"(d[56]), "+f"(d[57]), "+f"(d[58]), "+f"(d[59]), "+f"(d[60]), "+f"(d[61]), "+f"(d[62]), "+f"(d[63])
    : "l"(da), "l"(db), "r"(scale_d), "n"(TB));
}
template<int TB> __device__ __forceinline__ void wgmma_rs_n32(float (&d)[16], uint32_t a0, uint32_t a1, uint32_t a2, uint32_t a3, uint64_t db, int scale_d) {
  asm volatile("{\n.reg .pred p;\nsetp.ne.b32 p, %21, 0;\n"
    "wgmma.mma_async.sync.aligned.m64n32k16.f32.bf16.bf16 {%0, %1, %2, %3, %4, %5, %6, %7, %8, %9, %10, %11, %12, %13, %14, %15}, {%16, %17, %18, %19}, %20, p, 1, 1, %22;\n}\n"
    : "+f"(d[0]), "+f"(d[1]), "+f"(d[2]), "+f"(d[3]), "+f"(d[4]), "+f"(d[5]), "+f"(d[6]), "+f"(d[7]), "+f"(d[8]), "+f"(d[9]), "+f"(d[10]), "+f"(d[11]), "+f"(d[12]), "+f"(d[13]), "+f"(d[14]), "+f"(d[15])
    : "r"(a0), "r"(a1), "r"(a2), "r"(a3), "l"(db), "r"(scale_d), "n"(TB));
}
__device__ __forceinline__ void wgmma_pv_sel(float (&d)[64], const uint32_t (&p)[32], uint64_t db, int full, int acc, int wg) {
  asm volatile("{\n.reg .pred q, s, w;\n.reg .b64 t;\nsetp.eq.b32 w, %99, 0;\nsetp.ne.b32 s, %98, 0;\nsetp.eq.b32 q, %97, 0;\n@q bra.uni LH;\n"
    "wgmma.fence.sync.aligned;\n"
    "add.s64 t, %96, 0;\nwgmma.mma_async.sync.aligned.m64n128k16.f32.bf16.bf16 {%0, %1, %2, %3, %4, %5, %6, %7, %8, %9, %10, %11, %12, %13, %14, %15, %16, %17, %18, %19, %20, %21, %22, %23, %24, %25, %26, %27, %28, %29, %30, %31, %32, %33, %34, %35, %36, %37, %38, %39, %40, %41, %42, %43, %44, %45, %46, %47, %48, %49, %50, %51, %52, %53, %54, %55, %56, %57, %58, %59, %60, %61, %62, %63}, {%64, %65, %66, %67}, t, s, 1, 1, 1;\n"
    "add.s64 t, %96, 256;\nwgmma.mma_async.sync.aligned.m64n128k16.f32.bf16.bf16 {%0, %1, %2, %3, %4, %5, %6, %7, %8, %9, %10, %11, %12, %13, %14, %15, %16, %17, %18, %19, %20, %21, %22, %23, %24, %25, %26, %27, %28, %29, %30, %31, %32, %33, %34, %35, %36, %37, %38, %39, %40, %41, %42, %43, %44, %45, %46, %47, %48, %49, %50, %51, %52, %53, %54, %55, %56, %57, %58, %59, %60, %61, %62, %63}, {%68, %69, %70, %71}, t, 1, 1, 1, 1;\n"
    "add.s64 t, %96, 512;\nwgmma.mma_async.sync.aligned.m64n128k16.f32.bf16.bf16 {%0, %1, %2, %3, %4, %5, %6, %7, %8, %9, %10, %11, %12, %13, %14, %15, %16, %17, %18, %19, %20, %21, %22, %23, %24, %25, %26, %27, %28, %29, %30, %31, %32, %33, %34, %35, %36, %37, %38, %39, %40, %41, %42, %43, %44, %45, %46, %47, %48, %49, %50, %51, %52, %53, %54, %55, %56, %57, %58, %59, %60, %61, %62, %63}, {%72, %73, %74, %75}, t, 1, 1, 1, 1;\n"
    "add.s64 t, %96, 768;\nwgmma.mma_async.sync.aligned.m64n128k16.f32.bf16.bf16 {%0, %1, %2, %3, %4, %5, %6, %7, %8, %9, %10, %11, %12, %13, %14, %15, %16, %17, %18, %19, %20, %21, %22, %23, %24, %25, %26, %27, %28, %29, %30, %31, %32, %33, %34, %35, %36, %37, %38, %39, %40, %41, %42, %43, %44, %45, %46, %47, %48, %49, %50, %51, %52, %53, %54, %55, %56, %57, %58, %59, %60, %61, %62, %63}, {%76, %77, %78, %79}, t, 1, 1, 1, 1;\n"
    "add.s64 t, %96, 1024;\nwgmma.mma_async.sync.aligned.m64n128k16.f32.bf16.bf16 {%0, %1, %2, %3, %4, %5, %6, %7, %8, %9, %10, %11, %12, %13, %14, %15, %16, %17, %18, %19, %20, %21, %22, %23, %24, %25, %26, %27, %28, %29, %30, %31, %32, %33, %34, %35, %36, %37, %38, %39, %40, %41, %42, %43, %44, %45, %46, %47, %48, %49, %50, %51, %52, %53, %54, %55, %56, %57, %58, %59, %60, %61, %62, %63}, {%80, %81, %82, %83}, t, 1, 1, 1, 1;\n"
    "add.s64 t, %96, 1280;\nwgmma.mma_async.sync.aligned.m64n128k16.f32.bf16.bf16 {%0, %1, %2, %3, %4, %5, %6, %7, %8, %9, %10, %11, %12, %13, %14, %15, %16, %17, %18, %19, %20, %21, %22, %23, %24, %25, %26, %27, %28, %29, %30, %31, %32, %33, %34, %35, %36, %37, %38, %39, %40, %41, %42, %43, %44, %45, %46, %47, %48, %49, %50, %51, %52, %53, %54, %55, %56, %57, %58, %59, %60, %61, %62, %63}, {%84, %85, %86, %87}, t, 1, 1, 1, 1;\n"
    "@w bar.arrive 2, 256;\n@!w bar.arrive 1, 256;\n"
    "add.s64 t, %96, 1536;\nwgmma.mma_async.sync.aligned.m64n128k16.f32.bf16.bf16 {%0, %1, %2, %3, %4, %5, %6, %7, %8, %9, %10, %11, %12, %13, %14, %15, %16, %17, %18, %19, %20, %21, %22, %23, %24, %25, %26, %27, %28, %29, %30, %31, %32, %33, %34, %35, %36, %37, %38, %39, %40, %41, %42, %43, %44, %45, %46, %47, %48, %49, %50, %51, %52, %53, %54, %55, %56, %57, %58, %59, %60, %61, %62, %63}, {%88, %89, %90, %91}, t, 1, 1, 1, 1;\n"
    "add.s64 t, %96, 1792;\nwgmma.mma_async.sync.aligned.m64n128k16.f32.bf16.bf16 {%0, %1, %2, %3, %4, %5, %6, %7, %8, %9, %10, %11, %12, %13, %14, %15, %16, %17, %18, %19, %20, %21, %22, %23, %24, %25, %26, %27, %28, %29, %30, %31, %32, %33, %34, %35, %36, %37, %38, %39, %40, %41, %42, %43, %44, %45, %46, %47, %48, %49, %50, %51, %52, %53, %54, %55, %56, %57, %58, %59, %60, %61, %62, %63}, {%92, %93, %94, %95}, t, 1, 1, 1, 1;\n"
    "wgmma.commit_group.sync.aligned;\n"
    "bra.uni LE;\nLH:\n"
    "wgmma.fence.sync.aligned;\n"
    "add.s64 t, %96, 0;\nwgmma.mma_async.sync.aligned.m64n128k16.f32.bf16.bf16 {%0, %1, %2, %3, %4, %5, %6, %7, %8, %9, %10, %11, %12, %13, %14, %15, %16, %17, %18, %19, %20, %21, %22, %23, %24, %25, %26, %27, %28, %29, %30, %31, %32, %33, %34, %35, %36, %37, %38, %39, %40, %41, %42, %43, %44, %45, %46, %47, %48, %49, %50, %51, %52, %53, %54, %55, %56, %57, %58, %59, %60, %61, %62, %63}, {%80, %81, %82, %83}, t, s, 1, 1, 1;\n"
    "add.s64 t, %96, 256;\nwgmma.mma_async.sync.aligned.m64n128k16.f32.bf16.bf16 {%0, %1, %2, %3, %4, %5, %6, %7, %8, %9, %10, %11, %12, %13, %14, %15, %16, %17, %18, %19, %20, %21, %22, %23, %24, %25, %26, %27, %28, %29, %30, %31, %32, %33, %34, %35, %36, %37, %38, %39, %40, %41, %42, %43, %44, %45, %46, %47, %48, %49, %50, %51, %52, %53, %54, %55, %56, %57, %58, %59, %60, %61, %62, %63}, {%84, %85, %86, %87}, t, 1, 1, 1, 1;\n"
    "@w bar.arrive 2, 256;\n@!w bar.arrive 1, 256;\n"
    "add.s64 t, %96, 512;\nwgmma.mma_async.sync.aligned.m64n128k16.f32.bf16.bf16 {%0, %1, %2, %3, %4, %5, %6, %7, %8, %9, %10, %11, %12, %13, %14, %15, %16, %17, %18, %19, %20, %21, %22, %23, %24, %25, %26, %27, %28, %29, %30, %31, %32, %33, %34, %35, %36, %37, %38, %39, %40, %41, %42, %43, %44, %45, %46, %47, %48, %49, %50, %51, %52, %53, %54, %55, %56, %57, %58, %59, %60, %61, %62, %63}, {%88, %89, %90, %91}, t, 1, 1, 1, 1;\n"
    "add.s64 t, %96, 768;\nwgmma.mma_async.sync.aligned.m64n128k16.f32.bf16.bf16 {%0, %1, %2, %3, %4, %5, %6, %7, %8, %9, %10, %11, %12, %13, %14, %15, %16, %17, %18, %19, %20, %21, %22, %23, %24, %25, %26, %27, %28, %29, %30, %31, %32, %33, %34, %35, %36, %37, %38, %39, %40, %41, %42, %43, %44, %45, %46, %47, %48, %49, %50, %51, %52, %53, %54, %55, %56, %57, %58, %59, %60, %61, %62, %63}, {%92, %93, %94, %95}, t, 1, 1, 1, 1;\n"
    "wgmma.commit_group.sync.aligned;\n"
    "LE:\n}\n"
    : "+f"(d[0]), "+f"(d[1]), "+f"(d[2]), "+f"(d[3]), "+f"(d[4]), "+f"(d[5]), "+f"(d[6]), "+f"(d[7]), "+f"(d[8]), "+f"(d[9]), "+f"(d[10]), "+f"(d[11]), "+f"(d[12]), "+f"(d[13]), "+f"(d[14]), "+f"(d[15]), "+f"(d[16]), "+f"(d[17]), "+f"(d[18]), "+f"(d[19]), "+f"(d[20]), "+f"(d[21]), "+f"(d[22]), "+f"(d[23]), "+f"(d[24]), "+f"(d[25]), "+f"(d[26]), "+f"(d[27]), "+f"(d[28]), "+f"(d[29]), "+f"(d[30]), "+f"(d[31]), "+f"(d[32]), "+f"(d[33]), "+f"(d[34]), "+f"(d[35]), "+f"(d[36]), "+f"(d[37]), "+f"(d[38]), "+f"(d[39]), "+f"(d[40]), "+f"(d[41]), "+f"(d[42]), "+f"(d[43]), "+f"(d[44]), "+f"(d[45]), "+f"(d[46]), "+f"(d[47]), "+f"(d[48]), "+f"(d[49]), "+f"(d[50]), "+f"(d[51]), "+f"(d[52]), "+f"(d[53]), "+f"(d[54]), "+f"(d[55]), "+f"(d[56]), "+f"(d[57]), "+f"(d[58]), "+f"(d[59]), "+f"(d[60]), "+f"(d[61]), "+f"(d[62]), "+f"(d[63])
    : "r"(p[0]), "r"(p[1]), "r"(p[2]), "r"(p[3]), "r"(p[4]), "r"(p[5]), "r"(p[6]), "r"(p[7]), "r"(p[8]), "r"(p[9]), "r"(p[10]), "r"(p[11]), "r"(p[12]), "r"(p[13]), "r"(p[14]), "r"(p[15]), "r"(p[16]), "r"(p[17]), "r"(p[18]), "r"(p[19]), "r"(p[20]), "r"(p[21]), "r"(p[22]), "r"(p[23]), "r"(p[24]), "r"(p[25]), "r"(p[26]), "r"(p[27]), "r"(p[28]), "r"(p[29]), "r"(p[30]), "r"(p[31]), "l"(db), "r"(full), "r"(acc), "r"(wg) : "memory");
}

constexpr int NCTA = 132, NREG = 128;
constexpr int UNIT = 16384, NUNIT = 14;
constexpr uint32_t SMEM_BASE = 1024;
constexpr int SM_BAR = NUNIT * UNIT;
constexpr int SM_GATE = SM_BAR + 1024;
constexpr int SMEM_BYTES = SM_BAR + 1536;
constexpr int UPITCH = 4160, UCH = 2 * UPITCH;
constexpr float QSCALE = 0.08838834764831845f * 1.4426950408889634f;
constexpr float BOUND2 = 60.f * 60.f / 1.15f;
#define NSKIP 8
constexpr int C_KV = 0;
constexpr int C_CTX = 32;
constexpr int C_U = 48;
constexpr int C_Z = 80;
constexpr int C_GATE = 88;
constexpr int C_EXIT = 89, C_TICKET = 90;
#define ATT_SPLIT 4
#define SL_BAR 256
#define SL_CNT 0
#define K0W 1
#define Z_AT 60
#define PRE_SLEEP 300
#define GATE_SLEEP 1000
#define OC_S0 2
#define OC_S1 11
#define OC_L0 18
#define OC_L1 18
#define ST_1 4
#define ST_D 2
#define SCH_KV 0x7766555443322100ull
#define SCH_Q 0x7766555443322100ull
#define NK_AT 1
#ifndef NV_AT
#define NV_AT 3
#endif
#define CHK_D 11
#define FGAP 600
#define FGAP2 200
constexpr int PRE_EARLY = 2, NFIRST = 4;
constexpr int C_WAR = 96;
constexpr int C_NUM = 112;
constexpr int CSTRIDE = 32;
constexpr int SM_KMAX = SM_BAR + 640, SM_DUMMY = SM_BAR + 648, SM_POOL = SM_BAR + 652, SM_PRE = SM_BAR + 112, SM_SIG = SM_BAR + 256, SM_RDY = SM_BAR + 384;
enum { SIG_KV = 0, SIG_CTX = 2, SIG_Z = 4, SIG_DONE = 8, SIG_WAR = 9, SIG_ATT = 10 };
enum { RDY_KV = 0, RDY_CTX = 2, RDY_WAR = 4, RDY_G = 5, RDY_X = 6, RDY_AUX = 7, RDY_U = 8, RDY_Z = 9, RDY_T = 10, RDY_NONE = 11 };
enum { PH_PRE = 1, PH_KV = 2, PH_ATT = 4, PH_CONV = 8, PH_OUT = 16, PH_ALL = 31 };

constexpr uint32_t T_CTX = 0, T_KV = 16 * 32 * 32768, T_BYTES = T_KV + 32 * 16 * 65536;
__device__ __align__(1024) uint8_t g_T[T_BYTES];
__device__ __align__(1024) uint8_t g_u[1024 * UCH];
__device__ __align__(1024) float g_gate[2048];
__device__ __align__(1024) float g_kn2[32 * 128];
__device__ __align__(1024) unsigned g_cnt[C_NUM * CSTRIDE];

struct __align__(64) Maps { CUtensorMap c, wk, wv, x, wq, wo, h, z, ctx, k, v; };
struct Params {
  const __nv_bfloat16 *x, *shift, *D, *gw;
  __nv_bfloat16* out;
};

__device__ __forceinline__ void wg_fence() { asm volatile("wgmma.fence.sync.aligned;" ::: "memory"); }
__device__ __forceinline__ void wg_commit() { asm volatile("wgmma.commit_group.sync.aligned;" ::: "memory"); }
template<int N> __device__ __forceinline__ void wg_wait() { asm volatile("wgmma.wait_group.sync.aligned %0;" :: "n"(N) : "memory"); }
__device__ __forceinline__ uint64_t odesc(uint32_t addr, uint32_t lbo, uint32_t sbo, uint32_t swz) {
  uint64_t d = (uint64_t)(addr >> 4) + (((uint64_t)(lbo >> 4) << 16) | ((uint64_t)(sbo >> 4) << 32) | ((uint64_t)swz << 62));
  asm volatile("" : "+l"(d));
  return d;
}
__device__ __forceinline__ void mbar_init(uint32_t bar, int cnt) { asm volatile("mbarrier.init.shared::cta.b64 [%0], %1;" :: "r"(bar), "r"(cnt)); }
__device__ __forceinline__ void mbar_expect(uint32_t bar, uint32_t bytes) { asm volatile("mbarrier.arrive.expect_tx.shared::cta.b64 _, [%0], %1;" :: "r"(bar), "r"(bytes) : "memory"); }
__device__ __forceinline__ void mbar_arrive(uint32_t bar) { asm volatile("mbarrier.arrive.shared::cta.b64 _, [%0];" :: "r"(bar) : "memory"); }
__device__ __forceinline__ void mbar_wait(uint32_t bar, uint32_t parity) {
  asm volatile("{\n.reg .pred p;\nLW:\nmbarrier.try_wait.parity.shared::cta.b64 p, [%0], %1;\n@!p bra LW;\n}\n" :: "r"(bar), "r"(parity) : "memory");
}
__device__ __forceinline__ void mbar_wait_slow(uint32_t bar, uint32_t parity) {
  asm volatile("{\n.reg .pred p;\n.reg .u32 n;\nmov.u32 n, 0;\n"
    "LW:\nmbarrier.test_wait.parity.shared::cta.b64 p, [%0], %1;\n@p bra LD;\n"
    "nanosleep.u32 %2;\nadd.u32 n, n, 1;\nsetp.lt.u32 p, n, 16777216;\n@p bra LW;\ntrap;\nLD:\n}\n" :: "r"(bar), "r"(parity), "n"(SL_BAR) : "memory");
}
__device__ __forceinline__ void mbar_wait_all(uint32_t bar, uint32_t parity) {
  asm volatile("{\n.reg .pred p, q;\nLW:\nmbarrier.try_wait.parity.shared::cta.b64 p, [%0], %1;\nvote.sync.all.pred q, p, 0xffffffff;\n@!q bra.uni LW;\n}\n" :: "r"(bar), "r"(parity) : "memory");
}
__device__ __forceinline__ void cnt_wait(const unsigned* p, unsigned target) {
  asm volatile("{\n.reg .pred p;\n.reg .u32 n, v;\nmov.u32 n, 0;\n"
    "LW:\nld.relaxed.gpu.global.u32 v, [%0];\nsetp.ge.u32 p, v, %1;\n@p bra LD;\n"
    "nanosleep.u32 %2;\nadd.u32 n, n, 1;\nsetp.lt.u32 p, n, 4194304;\n@p bra LW;\ntrap;\nLD:\nfence.acquire.gpu;\nfence.proxy.async.global;\n}\n" :: "l"(p), "r"(target), "n"(SL_CNT) : "memory");
}
__device__ __forceinline__ void cnt_signal(unsigned* p, int lane) {
  __syncwarp();
  if (lane == 0) asm volatile("red.release.gpu.global.add.u32 [%0], 1;" :: "l"(p) : "memory");
}
__device__ __forceinline__ void cnt_publish(unsigned* p, unsigned n, bool fence) {
  if (fence) asm volatile("fence.release.gpu;" ::: "memory");
  asm volatile("red.relaxed.gpu.global.add.u32 [%0], %1;" :: "l"(p), "r"(n) : "memory");
}
__device__ __forceinline__ uint64_t pol_first() { uint64_t p; asm("createpolicy.fractional.L2::evict_first.b64 %0, 1.0;" : "=l"(p)); return p; }
__device__ __forceinline__ void bulk_g2s(uint32_t dst, const void* src, uint32_t bytes, uint32_t bar, bool stream = false) {
  if (stream) asm volatile("cp.async.bulk.shared::cluster.global.mbarrier::complete_tx::bytes.L2::cache_hint [%0], [%1], %2, [%3], %4;" :: "r"(dst), "l"(src), "r"(bytes), "r"(bar), "l"(pol_first()) : "memory");
  else asm volatile("cp.async.bulk.shared::cluster.global.mbarrier::complete_tx::bytes [%0], [%1], %2, [%3];" :: "r"(dst), "l"(src), "r"(bytes), "r"(bar) : "memory");
}
__device__ __forceinline__ void tma2d(uint32_t dst, const CUtensorMap* m, int x, int y, uint32_t bar, bool stream = false) {
  if (stream) asm volatile("cp.async.bulk.tensor.2d.shared::cluster.global.mbarrier::complete_tx::bytes.L2::cache_hint [%0], [%1, {%3, %4}], [%2], %5;" :: "r"(dst), "l"(m), "r"(bar), "r"(x), "r"(y), "l"(pol_first()) : "memory");
  else asm volatile("cp.async.bulk.tensor.2d.shared::cluster.global.mbarrier::complete_tx::bytes [%0], [%1, {%3, %4}], [%2];" :: "r"(dst), "l"(m), "r"(bar), "r"(x), "r"(y) : "memory");
}
__device__ __forceinline__ void tma3d(uint32_t dst, const CUtensorMap* m, int x, int y, int z, uint32_t bar, bool stream = false) {
  if (stream) asm volatile("cp.async.bulk.tensor.3d.shared::cluster.global.mbarrier::complete_tx::bytes.L2::cache_hint [%0], [%1, {%3, %4, %5}], [%2], %6;" :: "r"(dst), "l"(m), "r"(bar), "r"(x), "r"(y), "r"(z), "l"(pol_first()) : "memory");
  else asm volatile("cp.async.bulk.tensor.3d.shared::cluster.global.mbarrier::complete_tx::bytes [%0], [%1, {%3, %4, %5}], [%2];" :: "r"(dst), "l"(m), "r"(bar), "r"(x), "r"(y), "r"(z) : "memory");
}
__device__ __forceinline__ void tma4d(uint32_t dst, const CUtensorMap* m, int x, int y, int z, int w, uint32_t bar, bool stream = false) {
  if (stream) asm volatile("cp.async.bulk.tensor.4d.shared::cluster.global.mbarrier::complete_tx::bytes.L2::cache_hint [%0], [%1, {%3, %4, %5, %6}], [%2], %7;" :: "r"(dst), "l"(m), "r"(bar), "r"(x), "r"(y), "r"(z), "r"(w), "l"(pol_first()) : "memory");
  else asm volatile("cp.async.bulk.tensor.4d.shared::cluster.global.mbarrier::complete_tx::bytes [%0], [%1, {%3, %4, %5, %6}], [%2];" :: "r"(dst), "l"(m), "r"(bar), "r"(x), "r"(y), "r"(z), "r"(w) : "memory");
}
__device__ __forceinline__ void bulk_g2s_mc(uint32_t dst, const void* src, uint32_t bytes, uint32_t bar, bool stream = false) {
  if (stream) asm volatile("cp.async.bulk.shared::cluster.global.mbarrier::complete_tx::bytes.multicast::cluster.L2::cache_hint [%0], [%1], %2, [%3], %4, %5;" :: "r"(dst), "l"(src), "r"(bytes), "r"(bar), "h"((uint16_t)3), "l"(pol_first()) : "memory");
  else asm volatile("cp.async.bulk.shared::cluster.global.mbarrier::complete_tx::bytes.multicast::cluster [%0], [%1], %2, [%3], %4;" :: "r"(dst), "l"(src), "r"(bytes), "r"(bar), "h"((uint16_t)3) : "memory");
}
__device__ __forceinline__ void tma2d_mc(uint32_t dst, const CUtensorMap* m, int x, int y, uint32_t bar, bool stream = false) {
  if (stream) asm volatile("cp.async.bulk.tensor.2d.shared::cluster.global.mbarrier::complete_tx::bytes.multicast::cluster.L2::cache_hint [%0], [%1, {%3, %4}], [%2], %5, %6;" :: "r"(dst), "l"(m), "r"(bar), "r"(x), "r"(y), "h"((uint16_t)3), "l"(pol_first()) : "memory");
  else asm volatile("cp.async.bulk.tensor.2d.shared::cluster.global.mbarrier::complete_tx::bytes.multicast::cluster [%0], [%1, {%3, %4}], [%2], %5;" :: "r"(dst), "l"(m), "r"(bar), "r"(x), "r"(y), "h"((uint16_t)3) : "memory");
}
__device__ __forceinline__ void tma3d_mc(uint32_t dst, const CUtensorMap* m, int x, int y, int z, uint32_t bar, bool stream = false) {
  if (stream) asm volatile("cp.async.bulk.tensor.3d.shared::cluster.global.mbarrier::complete_tx::bytes.multicast::cluster.L2::cache_hint [%0], [%1, {%3, %4, %5}], [%2], %6, %7;" :: "r"(dst), "l"(m), "r"(bar), "r"(x), "r"(y), "r"(z), "h"((uint16_t)3), "l"(pol_first()) : "memory");
  else asm volatile("cp.async.bulk.tensor.3d.shared::cluster.global.mbarrier::complete_tx::bytes.multicast::cluster [%0], [%1, {%3, %4, %5}], [%2], %6;" :: "r"(dst), "l"(m), "r"(bar), "r"(x), "r"(y), "r"(z), "h"((uint16_t)3) : "memory");
}
__device__ __forceinline__ void map_pf(const CUtensorMap* m) { asm volatile("prefetch.tensormap [%0];" :: "l"(m) : "memory"); }
__device__ __forceinline__ bool elect() {
  uint32_t r; asm volatile("{\n.reg .pred p;\nelect.sync _|p, 0xffffffff;\nselp.u32 %0, 1, 0, p;\n}\n" : "=r"(r)); return r != 0;
}
__device__ __forceinline__ void cluster_arrive() { asm volatile("barrier.cluster.arrive;" ::: "memory"); }
__device__ __forceinline__ void cluster_wait() { asm volatile("barrier.cluster.wait;" ::: "memory"); }
__device__ __forceinline__ void bar_sync(int id, int n) { asm volatile("bar.sync %0, %1;" :: "r"(id), "r"(n) : "memory"); }
__device__ __forceinline__ void bar_arrive(int id, int n) { asm volatile("bar.arrive %0, %1;" :: "r"(id), "r"(n) : "memory"); }
__device__ __forceinline__ void fence_async_smem() { asm volatile("fence.proxy.async.shared::cta;" ::: "memory"); }
__device__ __forceinline__ float ex2(float x) { float y; asm("ex2.approx.ftz.f32 %0, %1;" : "=f"(y) : "f"(x)); return y; }
__device__ __forceinline__ float rcp(float x) { float y; asm("rcp.approx.ftz.f32 %0, %1;" : "=f"(y) : "f"(x)); return y; }
__device__ __forceinline__ uint32_t pack_bf16(float lo, float hi) { uint32_t r; asm("cvt.rn.bf16x2.f32 %0, %1, %2;" : "=r"(r) : "f"(hi), "f"(lo)); return r; }
__device__ __forceinline__ uint32_t hmul2(uint32_t a, uint32_t b) { uint32_t r; asm("mul.rn.bf16x2 %0, %1, %2;" : "=r"(r) : "r"(a), "r"(b)); return r; }
__device__ __forceinline__ uint32_t hadd2(uint32_t a, uint32_t b) { uint32_t r; asm("add.rn.bf16x2 %0, %1, %2;" : "=r"(r) : "r"(a), "r"(b)); return r; }
__device__ __forceinline__ uint32_t hfma2(uint32_t a, uint32_t b, uint32_t c) { uint32_t r; asm("fma.rn.bf16x2 %0, %1, %2, %3;" : "=r"(r) : "r"(a), "r"(b), "r"(c)); return r; }
__device__ __forceinline__ float bf_lo(uint32_t a) { return __uint_as_float(a << 16); }
__device__ __forceinline__ float bf_hi(uint32_t a) { return __uint_as_float(a & 0xffff0000u); }
__device__ __forceinline__ uint32_t lds32(uint32_t a) { uint32_t v; asm volatile("ld.shared.u32 %0, [%1];" : "=r"(v) : "r"(a) : "memory"); return v; }
__device__ __forceinline__ uint4 lds128(uint32_t a) { uint4 v; asm volatile("ld.shared.v4.u32 {%0,%1,%2,%3}, [%4];" : "=r"(v.x), "=r"(v.y), "=r"(v.z), "=r"(v.w) : "r"(a) : "memory"); return v; }
__device__ __forceinline__ void sts64f(uint32_t a, float x, float y) { asm volatile("st.shared.v2.f32 [%0], {%1,%2};" :: "r"(a), "f"(x), "f"(y) : "memory"); }
template<int OFF> __device__ __forceinline__ void sts128o(uint32_t a, uint4 v) { asm volatile("st.shared.v4.u32 [%0+%5], {%1,%2,%3,%4};" :: "r"(a), "r"(v.x), "r"(v.y), "r"(v.z), "r"(v.w), "n"(OFF) : "memory"); }
__device__ __forceinline__ void ldsm4(uint32_t a, uint32_t& r0, uint32_t& r1, uint32_t& r2, uint32_t& r3) {
  asm volatile("ldmatrix.sync.aligned.m8n8.x4.shared.b16 {%0,%1,%2,%3}, [%4];" : "=r"(r0), "=r"(r1), "=r"(r2), "=r"(r3) : "r"(a) : "memory");
}
__device__ __forceinline__ void ldsm4t(uint32_t a, uint32_t& r0, uint32_t& r1, uint32_t& r2, uint32_t& r3) {
  asm volatile("ldmatrix.sync.aligned.m8n8.x4.trans.shared.b16 {%0,%1,%2,%3}, [%4];" : "=r"(r0), "=r"(r1), "=r"(r2), "=r"(r3) : "r"(a) : "memory");
}
__device__ __forceinline__ void stsm4(uint32_t a, uint32_t r0, uint32_t r1, uint32_t r2, uint32_t r3) {
  asm volatile("stmatrix.sync.aligned.m8n8.x4.shared.b16 [%0], {%1,%2,%3,%4};" :: "r"(a), "r"(r0), "r"(r1), "r"(r2), "r"(r3) : "memory");
}
template<int N> __device__ __forceinline__ void fence_regs(float (&d)[N]) {
#pragma unroll
  for (int i = 0; i < N; i++) asm volatile("" : "+f"(d[i]) :: "memory");
}
template<int N> __device__ __forceinline__ void fence_regs(uint32_t (&d)[N]) {
#pragma unroll
  for (int i = 0; i < N; i++) asm volatile("" : "+r"(d[i]) :: "memory");
}
__device__ __forceinline__ void sched_fence(float x, uint32_t dummy) {
  asm volatile("{\n.reg .pred p;\nsetp.eq.u32 p, %0, 0x7fc12345;\n@p st.shared.u32 [%1], %0;\n}\n" :: "r"(__float_as_uint(x)), "r"(dummy) : "memory");
}
#define PTRACE 0
#define TS(role, i)
#define TSA(i)
#define TSS(i)
#define TSK(i)
#define TSO(i)

#define SHADOW if (gridDim.y == 1)

struct Prod {
  uint32_t base, mask; int lane, nt;
  __device__ __forceinline__ uint32_t full(int u) const { return base + SM_BAR + 8 * u; }
  __device__ __forceinline__ uint32_t addr(int u) const { return base + u * UNIT; }
  __device__ __forceinline__ void acquire(int u, int n) {
    const int v = u + min(lane, n - 1);
    mbar_wait_all(base + SM_BAR + 128 + 8 * v, mask >> v);
    mask ^= ((1u << n) - 1) << u;
  }
  __device__ __forceinline__ void acquire_slow(int u, int n) {
    for (int i = 0; i < n; i++) mbar_wait_slow(base + SM_BAR + 128 + 8 * (u + i), mask >> (u + i));
    mask ^= ((1u << n) - 1) << u;
  }
};
struct Cons {
  uint32_t base, rel, mask; int lane, warp, wg, lr, nt;
  __device__ __forceinline__ uint32_t addr(int u) const { return base + u * UNIT; }
  __device__ __forceinline__ static uint32_t daddr(int u) { return SMEM_BASE + u * UNIT; }
  __device__ __forceinline__ void wait(int u) { mbar_wait(base + SM_BAR + 8 * u, mask >> u); mask ^= 1u << u; }
  __device__ __forceinline__ void skip(int u) { mask ^= 1u << u; }
  __device__ __forceinline__ void release(int u, int n) {
    asm volatile("{\n.reg .pred p;\nsetp.lt.s32 p, %1, %2;\n@p mbarrier.arrive.shared::cluster.b64 _, [%0];\n}\n" :: "r"(rel + 8 * u), "r"(lr), "r"(n) : "memory");
  }
  __device__ __forceinline__ void release2(int u) {
    asm volatile("{\n.reg .pred p;\nsetp.eq.s32 p, %1, 0;\n@p mbarrier.arrive.shared::cluster.b64 _, [%0], 2;\n}\n" :: "r"(rel + 8 * u), "r"(lr) : "memory");
  }
  __device__ __forceinline__ void signal(int i) {
    __syncwarp();
    asm volatile("{\n.reg .pred p;\nsetp.eq.s32 p, %1, 0;\n@p mbarrier.arrive.shared::cta.b64 _, [%0];\n}\n" :: "r"(base + SM_SIG + 8 * i), "r"(lane) : "memory");
  }
  __device__ __forceinline__ void turn() { asm volatile("{\n.reg .pred p;\nsetp.eq.s32 p, %0, 0;\n@p bar.sync 1, 256;\n@!p bar.sync 2, 256;\n}\n" :: "r"(wg) : "memory"); }
  __device__ __forceinline__ void pass() { asm volatile("{\n.reg .pred p;\nsetp.eq.s32 p, %0, 0;\n@p bar.arrive 2, 256;\n@!p bar.arrive 1, 256;\n}\n" :: "r"(wg) : "memory"); }
  __device__ __forceinline__ void sync() { asm volatile("{\n.reg .pred p;\nsetp.eq.s32 p, %0, 0;\n@p bar.sync 3, 128;\n@!p bar.sync 4, 128;\n}\n" :: "r"(wg) : "memory"); }
};
__device__ __forceinline__ int gemm_unit(int ks) { return 3 * (ks & 3); }
template<int MASK> __device__ __forceinline__ int kv_slot(int h) { return MASK == PH_ALL ? h & 15 : h; }
__device__ __forceinline__ int out_mb(int cta) { return cta >> 3; }
__device__ __forceinline__ int out_nb(int cta) { return cta & 7; }
template<int MASK> constexpr int CV_REG = MASK == PH_ALL ? 4 : 6;
template<int MASK> constexpr int CV_EXTRA = MASK == PH_ALL ? 96 + NSKIP / 2 : 64;
constexpr int CV_POOL = 896 + 2 * NSKIP;
template<int MASK> __device__ __forceinline__ int conv_channel(int cta, int i) {
  return cta < NREG ? CV_EXTRA<MASK> * (NCTA - NREG) + cta * CV_REG<MASK> + i : (i >> 1) * 8 + (cta - NREG) * 2 + (i & 1);
}

template<int OFF, int N> __device__ __forceinline__ void pack_chunk(const float (&a)[N], float sc0, float sc1, uint4& v0, uint4& v1) {
  v0.x = pack_bf16(a[OFF + 0] * sc0, a[OFF + 1] * sc0); v0.y = pack_bf16(a[OFF + 4] * sc0, a[OFF + 5] * sc0);
  v0.z = pack_bf16(a[OFF + 8] * sc0, a[OFF + 9] * sc0); v0.w = pack_bf16(a[OFF + 12] * sc0, a[OFF + 13] * sc0);
  v1.x = pack_bf16(a[OFF + 2] * sc1, a[OFF + 3] * sc1); v1.y = pack_bf16(a[OFF + 6] * sc1, a[OFF + 7] * sc1);
  v1.z = pack_bf16(a[OFF + 10] * sc1, a[OFF + 11] * sc1); v1.w = pack_bf16(a[OFF + 14] * sc1, a[OFF + 15] * sc1);
}
template<int OFF, int N> __device__ __forceinline__ void pack_chunk(const float (&a)[N], uint4& v0, uint4& v1) {
  v0.x = pack_bf16(a[OFF + 0], a[OFF + 1]); v0.y = pack_bf16(a[OFF + 4], a[OFF + 5]);
  v0.z = pack_bf16(a[OFF + 8], a[OFF + 9]); v0.w = pack_bf16(a[OFF + 12], a[OFF + 13]);
  v1.x = pack_bf16(a[OFF + 2], a[OFF + 3]); v1.y = pack_bf16(a[OFF + 6], a[OFF + 7]);
  v1.z = pack_bf16(a[OFF + 10], a[OFF + 11]); v1.w = pack_bf16(a[OFF + 14], a[OFF + 15]);
}
__device__ __forceinline__ void sq_acc(const uint4& v, uint32_t& a) { a = hfma2(v.x, v.x, a); a = hfma2(v.y, v.y, a); a = hfma2(v.z, v.z, a); a = hfma2(v.w, v.w, a); }
template<bool ROWS> __device__ __forceinline__ float norm2_max(uint32_t a0, uint32_t a1) {
  float n0 = bf_lo(a0) + bf_hi(a0), n1 = bf_lo(a1) + bf_hi(a1);
  if (ROWS) {
    n0 += __shfl_xor_sync(~0u, n0, 1); n1 += __shfl_xor_sync(~0u, n1, 1);
    n0 += __shfl_xor_sync(~0u, n0, 2); n1 += __shfl_xor_sync(~0u, n1, 2);
  }
  return __uint_as_float(__reduce_max_sync(~0u, max(__float_as_uint(n0) & 0x7fffffffu, __float_as_uint(n1) & 0x7fffffffu)));
}

struct Pend { uint4 lo[8], hi[8]; };
__device__ __forceinline__ uint32_t ctx_off(const Cons& c, int h, int qb, int rowhalf) { return T_CTX + (qb * 32 + h) * 32768 + (rowhalf * 4 + c.warp) * 4096; }
__device__ __forceinline__ uint32_t kv_off(const Cons& c, int blk) { return T_KV + blk * 65536 + (c.wg * 4 + c.warp) * 4096; }
__device__ __forceinline__ void pin(uint4 (&v)[8]) {
#pragma unroll
  for (int i = 0; i < 8; i++) asm volatile("" : "+r"(v[i].x), "+r"(v[i].y), "+r"(v[i].z), "+r"(v[i].w) :: "memory");
}
__device__ __forceinline__ void pack_o(const float (&o)[64], float i0, float i1, uint4 (&v)[8]) {
  pack_chunk<0>(o, i0, i1, v[0], v[1]); pack_chunk<16>(o, i0, i1, v[2], v[3]);
  pack_chunk<32>(o, i0, i1, v[4], v[5]); pack_chunk<48>(o, i0, i1, v[6], v[7]);
  pin(v);
}
__device__ __forceinline__ uint32_t atom_off(int lane) { return (lane >> 2) * 64 + (((lane ^ (lane >> 3)) & 3) << 4); }
template<int J0, int J1> __device__ __forceinline__ void tile_store(const uint4 (&v)[8], uint32_t dst, int lane) {
  uint8_t* d = g_T + (dst + atom_off(lane));
#pragma unroll
  for (int j = J0; j < J1; j++) { *(uint4*)(d + j * 512) = v[2 * j]; *(uint4*)(d + j * 512 + 2048) = v[2 * j + 1]; }
}
template<int I0, int I1> __device__ __forceinline__ void tile_store_if(bool on, const uint4 (&v)[8], const uint8_t* dst) {
  if constexpr (I0 < I1) {
    asm volatile("{\n.reg .pred p;\nsetp.ne.b32 p, %5, 0;\n@p st.v4.u32 [%0+%6], {%1,%2,%3,%4};\n}\n"
      :: "l"(dst), "r"(v[I0].x), "r"(v[I0].y), "r"(v[I0].z), "r"(v[I0].w), "r"((int)on), "n"((I0 >> 1) * 512 + (I0 & 1) * 2048) : "memory");
    tile_store_if<I0 + 1, I1>(on, v, dst);
  }
}
template<bool ROWS> __device__ __forceinline__ float tile_norm2(const uint4 (&v)[8]) {
  uint32_t n0 = 0, n1 = 0, n2 = 0, n3 = 0;
#pragma unroll
  for (int j = 0; j < 2; j++) { sq_acc(v[2 * j], n0); sq_acc(v[2 * j + 1], n1); sq_acc(v[2 * j + 4], n2); sq_acc(v[2 * j + 5], n3); }
  return norm2_max<ROWS>(hadd2(n0, n2), hadd2(n1, n3));
}
template<uint64_t SCHED, bool FIRST> __device__ __forceinline__ void out_piece(Cons& c, Pend& w, uint32_t dst, int blk, float& kn, int ks, bool both) {
  uint8_t* d = g_T + (dst + atom_off(c.lane));
#pragma unroll
  for (int i = 0; i < 16; i++) {
    const int at = (SCHED >> (4 * i)) & 15;
    if (FIRST ? at == 0 : (at > 0 && ks == at && (i < 8 || both))) *(uint4*)(d + (i >> 3) * 32768 + ((i >> 1) & 3) * 512 + (i & 1) * 2048) = i < 8 ? w.lo[i & 7] : w.hi[i & 7];
  }
  if (FIRST || !both) return;
  if (ks == NK_AT) kn = tile_norm2<true>(w.lo);
  if (ks == NV_AT) {
    const float vn = tile_norm2<false>(w.hi);
    if (c.lane == 0) g_kn2[blk * 8 + c.wg * 4 + c.warp] = (vn <= 1.0e20f && vn >= 1.0e-20f) ? kn : __uint_as_float(0x7f800000u);
  }
}
template<bool FIRST> __device__ __forceinline__ void kv_issue(Cons& c, float (&acc)[128], int u) {
  const uint64_t da = odesc(c.daddr(u) + c.wg * 8192, 16, 1024, 1), db = odesc(c.daddr(u + 1), 8192, 1024, 1);
  TSK(c.nt + 1);
  c.turn();
  TSK(c.nt + 2);
  wg_fence();
#pragma unroll
  for (int kk = 0; kk < 4; kk++) wgmma_ss_n256<1>(acc, da + kk * 2, db + kk * 128, !(FIRST && kk == 0));
  wg_commit();
  c.pass();
  TSK(c.nt + 3); c.nt += 4;
}
template<bool NEXT> __device__ __forceinline__ void cons_kv(Cons& c, int h, int blk, int g, Pend& w, bool pend_o) {
#pragma unroll 1
  for (int tile = 0; tile < 2; tile++) {
    float acc[128];
    if (tile == 0) c.wait(0);
    if (tile == 0 && h < 16) TS(c.wg, 16);
    kv_issue<true>(c, acc, 0);
    c.release(9, tile == 1 ? 3 : 0);
    if (tile == 1 && pend_o) mbar_wait(c.base + SM_RDY + 8 * RDY_WAR, 0);
    const uint32_t dst = tile ? kv_off(c, blk) : ctx_off(c, h - 16, g, 1 - c.wg);
    float kn = 0.f;
    if (tile == 1 || pend_o) out_piece<SCH_KV, true>(c, w, dst, blk, kn, 0, false);
#pragma unroll 1
    for (int ks = 1; ks < 8; ks++) {
      const int u = gemm_unit(ks);
      c.wait(u);
      TSK(c.nt);
      wg_wait<0>();
      c.release(gemm_unit(ks - 1), 3);
      kv_issue<false>(c, acc, u);
      if (tile == 1 || pend_o) { out_piece<SCH_KV, false>(c, w, dst, blk, kn, ks, tile); if (ks == ((SCH_KV >> 28) & 15) && tile == 0) c.signal(SIG_CTX); }
    }
    if (NEXT || tile == 0) c.wait(0);
    wg_wait<0>(); fence_regs(acc);
    TSK(c.nt);
    if (!NEXT) c.release(9, tile == 1 ? 3 : 0);
    pack_chunk<0>(acc, w.lo[0], w.lo[1]);  pack_chunk<16>(acc, w.lo[2], w.lo[3]); pack_chunk<32>(acc, w.lo[4], w.lo[5]); pack_chunk<48>(acc, w.lo[6], w.lo[7]);
    pack_chunk<64>(acc, w.hi[0], w.hi[1]); pack_chunk<80>(acc, w.hi[2], w.hi[3]); pack_chunk<96>(acc, w.hi[4], w.hi[5]); pack_chunk<112>(acc, w.hi[6], w.hi[7]);
    pin(w.lo); pin(w.hi);
  }
}
template<bool FIRST> __device__ __forceinline__ void q_issue(Cons& c, float (&a)[64], float (&b)[64], int u) {
  const uint64_t da = odesc(c.daddr(u) + c.wg * 8192, 16, 1024, 1), db = odesc(c.daddr(u + 2), 8192, 1024, 1);
  const uint64_t da2 = odesc(c.daddr(u + 1) + (1 - c.wg) * 8192, 16, 1024, 1);
  TSK(c.nt + 1);
  c.turn();
  TSK(c.nt + 2);
  wg_fence();
#pragma unroll
  for (int kk = 0; kk < 4; kk++) wgmma_ss_n128<1>(a, da + kk * 2, db + kk * 128, !(FIRST && kk == 0));
#pragma unroll
  for (int kk = 0; kk < 4; kk++) wgmma_ss_n128<1>(b, da2 + kk * 2, db + kk * 128, !(FIRST && kk == 0));
  wg_commit();
  c.pass();
  TSK(c.nt + 3); c.nt += 4;
}
__device__ __forceinline__ void q_step(Cons& c, float (&d)[64], int ua, int ub, int rowhalf) {
  const uint64_t da = odesc(c.daddr(ua) + rowhalf * 8192, 16, 1024, 1), db = odesc(c.daddr(ub), 8192, 1024, 1);
#pragma unroll
  for (int kk = 0; kk < 4; kk++) wgmma_ss_n128<1>(d, da + kk * 2, db + kk * 128, 1);
}
__device__ __forceinline__ int att_fast(uint4 (&q)[8], float kn) {
#pragma unroll
  for (int i = 0; i < 8; i++) q[i].x = hmul2(q[i].x, q[i].x);
#pragma unroll
  for (int i = 0; i < 8; i++) q[i].x = hfma2(q[i].w, q[i].w, hfma2(q[i].z, q[i].z, hfma2(q[i].y, q[i].y, q[i].x)));
#pragma unroll
  for (int i = 0; i < 4; i++) q[i].x = hadd2(q[i].x, q[i + 4].x);
  const uint32_t a0 = hadd2(q[0].x, q[2].x), a1 = hadd2(q[1].x, q[3].x);
  return __shfl_sync(~0u, __all_sync(~0u, ((bf_lo(a0) + bf_hi(a0)) * kn <= 0.25f * BOUND2) & ((bf_lo(a1) + bf_hi(a1)) * kn <= 0.25f * BOUND2)), 0);
}
template<bool PEND_KV> __device__ __forceinline__ int cons_q(Cons& c, int h, int blk, Pend& w, float (&b)[64], float& kmax) {
  float a[64], kn = 0.f;
  if (!PEND_KV) c.wait(0);
  q_issue<true>(c, a, b, 0);
  if (PEND_KV) { c.release(9, 3); out_piece<SCH_Q, true>(c, w, kv_off(c, blk), blk, kn, 0, true); }
#pragma unroll 1
  for (int ks = 1; ks < 14; ks++) {
    const int u = gemm_unit(ks);
    c.wait(u);
    TSK(c.nt);
    wg_wait<0>();
    c.release(gemm_unit(ks - 1), 3);
    q_issue<false>(c, a, b, u);
    if (PEND_KV && ks <= (int)(SCH_Q >> 60)) { out_piece<SCH_Q, false>(c, w, kv_off(c, blk), blk, kn, ks, true); if (ks == (int)(SCH_Q >> 60)) c.signal(SIG_KV + (h >> 4)); }
  }
  c.wait(6); c.wait(9);
  wg_wait<0>();
  c.release(3, 3);
  c.turn();
  TSS(0);
  wg_fence();
  q_step(c, a, 6, 8, c.wg); q_step(c, a, 9, 11, c.wg); wg_commit();
  q_step(c, b, 7, 8, 1 - c.wg); wg_commit();
  c.pass();
  TSS(1);
  c.wait(0);
  kmax = __uint_as_float(lds32(c.base + SM_KMAX + 4 * (h >> 4)));
  if (K0W) c.wait(12);
  const uint32_t q0 = c.addr(0) + (c.wg * 4 + c.warp) * 4096 + atom_off(c.lane);
  wg_wait<1>(); fence_regs(a);
  TSS(2);
  pack_o(a, QSCALE, QSCALE, w.lo);
  sts128o<0>(q0, w.lo[0]);    sts128o<2048>(q0, w.lo[1]); sts128o<512>(q0, w.lo[2]);  sts128o<2560>(q0, w.lo[3]);
  wg_wait<0>();
  c.release(6, 4);
  sts128o<1024>(q0, w.lo[4]); sts128o<3072>(q0, w.lo[5]); sts128o<1536>(q0, w.lo[6]); sts128o<3584>(q0, w.lo[7]);
  TSS(3);
  int fast = 0;
  SHADOW {
    uint4 q[8];
#pragma unroll
    for (int i = 0; i < 8; i++) q[i] = w.lo[i];
    fast = att_fast(q, kmax);
  }
  if (!K0W) c.wait(12);
  fence_async_smem();
  TSS(4);
  return fast;
}

__device__ __forceinline__ void issue_qk(float (&s)[64], uint64_t da, uint64_t db) {
#pragma unroll
  for (int kk = 0; kk < 8; kk++) wgmma_ss_n128<0>(s, da + (kk >> 1) * 32 + (kk & 1) * 2, db + (kk >> 1) * 32 + (kk & 1) * 2, kk > 0);
  wg_commit();
}
template<int A, int B> __device__ __forceinline__ void exp_rng(float (&s)[64]) {
#pragma unroll
  for (int i = 4 * A; i < 4 * B; i++) s[i] = ex2(s[i]);
}
template<int A, int B> __device__ __forceinline__ void sum_rng(const float (&s)[64], float (&l)[4]) {
#pragma unroll
  for (int i = A; i < B; i++) { l[0] += s[4 * i]; l[1] += s[4 * i + 1]; l[2] += s[4 * i + 2]; l[3] += s[4 * i + 3]; }
}
template<int A, int B> __device__ __forceinline__ void cvt_p(const float (&s)[64], uint32_t (&p)[32]) {
#pragma unroll
  for (int i = 2 * A; i < 2 * B; i++) p[i] = pack_bf16(s[2 * i], s[2 * i + 1]);
}
template<int K0> __device__ __forceinline__ void mask_half(float (&s)[64], int warp, int lane) {
  const int l0 = warp + (2 * (lane & 3) <= (lane >> 2)), l1 = warp + (2 * (lane & 3) < (lane >> 2));
#pragma unroll
  for (int k = 0; k < 4; k++) {
    float* t = s + 8 * (K0 + k);
    if (k >= l0) { t[0] = -INFINITY; t[6] = -INFINITY; }
    if (k >= l1) { t[1] = -INFINITY; t[7] = -INFINITY; }
    if (k > warp) { t[2] = -INFINITY; t[3] = -INFINITY; }
    if (k >= warp) { t[4] = -INFINITY; t[5] = -INFINITY; }
  }
}
__device__ __forceinline__ void row_inv(float& l0, float& l1) {
  l0 += __shfl_xor_sync(~0u, l0, 1); l1 += __shfl_xor_sync(~0u, l1, 1);
  l0 += __shfl_xor_sync(~0u, l0, 2); l1 += __shfl_xor_sync(~0u, l1, 2);
  l0 = rcp(l0); l1 = rcp(l1);
}
__device__ __forceinline__ void softmax_safe(float (&s)[64], bool upper_only, float& m0, float& m1, float& sc0, float& sc1) {
  float a0 = m0, a1 = m1;
#pragma unroll
  for (int i = 0; i < 8; i++) { a0 = fmaxf(a0, fmaxf(s[4 * i], s[4 * i + 1])); a1 = fmaxf(a1, fmaxf(s[4 * i + 2], s[4 * i + 3])); }
  if (upper_only) { a0 = m0; a1 = m1; }
#pragma unroll
  for (int i = 8; i < 16; i++) { a0 = fmaxf(a0, fmaxf(s[4 * i], s[4 * i + 1])); a1 = fmaxf(a1, fmaxf(s[4 * i + 2], s[4 * i + 3])); }
  a0 = fmaxf(a0, __shfl_xor_sync(~0u, a0, 1)); a1 = fmaxf(a1, __shfl_xor_sync(~0u, a1, 1));
  a0 = fmaxf(a0, __shfl_xor_sync(~0u, a0, 2)); a1 = fmaxf(a1, __shfl_xor_sync(~0u, a1, 2));
  sc0 = ex2(m0 - a0); sc1 = ex2(m1 - a1);
  m0 = a0; m1 = a1;
#pragma unroll
  for (int i = 0; i < 16; i++) { s[4 * i] -= a0; s[4 * i + 1] -= a0; s[4 * i + 2] -= a1; s[4 * i + 3] -= a1; }
}
struct Att {
  float s[64], o[64], l[4], i0, i1, t0, t1; uint32_t p[32];
  float kn; uint32_t qaddr; const uint8_t* dst;
};
__device__ __forceinline__ void att_first(Cons& c, Att& a, int h, const Pend& w) {
  a.qaddr = c.daddr(0) + c.wg * 16384;
  c.turn();
  TSS(5);
  wg_fence();
  issue_qk(a.s, odesc(a.qaddr, 16, 2048, 2), odesc(c.daddr(12), 16, 2048, 2));
  TSS(6);
  q_step(c, a.o, 10, 11, 1 - c.wg); wg_commit();
  if (c.wg) c.wait(6); else c.skip(6);
  c.pass();
  TSS(7);
#pragma unroll
  for (int i = 0; i < 8; i++) { a.p[4 * i] = w.lo[i].x; a.p[4 * i + 1] = w.lo[i].y; a.p[4 * i + 2] = w.lo[i].z; a.p[4 * i + 3] = w.lo[i].w; }
  a.l[0] = a.l[1] = a.l[2] = a.l[3] = 0.f; a.i0 = a.i1 = a.t0 = a.t1 = 0.25f / QSCALE;
  a.dst = (const uint8_t*)__cvta_shared_to_generic(c.addr(2) + (c.wg * 4 + c.warp) * 4096 + atom_off(c.lane));
  wg_wait<1>(); fence_regs(a.s);
  c.signal(SIG_ATT + (h >> 4));
  if (c.wg) { wg_wait<0>(); c.release(10, 2); }
}
__device__ __forceinline__ void att_last(Cons& c, Att& a, Pend& w, int h, int g, bool drain) {
  const int uv = 6;
  if (drain) pack_o(a.o, rcp(a.i0), rcp(a.i1), w.hi);
  TSS(8);
  c.turn();
  TSS(9);
  fence_regs(a.o); fence_regs(a.p);
  wgmma_pv_sel(a.o, a.p, odesc(c.daddr(uv), 512, 2048, 2), !(drain && c.wg == 1), !drain, c.wg);
  a.i0 = a.l[0] + a.l[1]; a.i1 = a.l[2] + a.l[3];
  SHADOW row_inv(a.i0, a.i1);
  sched_fence(a.i0 + a.i1, c.base + SM_DUMMY);
  tile_store_if<0, 4>(drain, w.hi, a.dst);
  wg_wait<0>(); fence_regs(a.o); fence_regs(a.p);
  c.release(uv, 2);
  TSS(10); if (h < 16) TSK(0); TSO(9 + (h >> 4));
  tile_store_if<4, 8>(drain, w.hi, a.dst);
  pack_o(a.o, a.i0, a.i1, w.lo);
  TSS(11);
}
__device__ __forceinline__ void cons_att(Cons& c, Att& a, int h, int g, Pend& w, int fast) {
  att_first(c, a, h, w);
  int fast2 = 0;
  float m0 = -INFINITY, m1 = -INFINITY, sc0 = 0.f, sc1 = 0.f;
  int uk = 10, ur = 10;
  bool fresh = false;
#pragma unroll 1
  for (int d = g - 15;;) {
    const bool lo = d == c.wg;
    TSS(16 + 6 * (d - g + 15));
    if ((unsigned)d < 2 || !fast) {
      if ((unsigned)d < 2) mask_half<4>(a.s, c.warp, c.lane);
      if (!fast) {
        if (d == 1) m0 = m1 = -INFINITY;
        softmax_safe(a.s, lo, m0, m1, sc0, sc1);
        a.l[0] *= sc0; a.l[1] *= sc0; a.l[2] *= sc1; a.l[3] *= sc1;
      }
    }
    exp_rng<8, 16>(a.s); sum_rng<8, 16>(a.s, a.l);
#pragma unroll
    for (int i = 4 * ATT_SPLIT; i < 32; i++) asm("{\n.reg .pred p;\nsetp.ne.s32 p, %1, %2;\n@p ex2.approx.ftz.f32 %0, %0;\n}\n" : "+f"(a.s[i]) : "r"(d), "r"(c.wg));
    sched_fence(((a.l[0] + a.l[1]) + (a.l[2] + a.l[3])) + a.s[4 * ATT_SPLIT + 3], c.base + SM_DUMMY);
    wg_wait<0>(); fence_regs(a.o); fence_regs(a.p);
    c.release(ur, c.wg && d == g - 15 ? 0 : 2);
    TSS(17 + 6 * (d - g + 15));
    a.i0 += a.t0; a.i1 += a.t1;
    a.t0 = __shfl_xor_sync(~0u, a.i0, 2); a.t1 = __shfl_xor_sync(~0u, a.i1, 2);
    tile_store_if<0, 4>(fresh, w.hi, a.dst);
    uk ^= 12; ur = 14 - uk;
    if (d == 0) a.qaddr += 32768;
    const uint64_t dq = odesc(a.qaddr, 16, 2048, 2), dk = odesc(c.daddr(uk) - (d + 1 == c.wg ? 16384 : 0), 16, 2048, 2), dv = odesc(c.daddr(ur), 512, 2048, 2);
    if (!lo) { exp_rng<0, ATT_SPLIT>(a.s); sum_rng<0, 8>(a.s, a.l); cvt_p<0, 16>(a.s, a.p); }
    else if (gridDim.y == 1) cvt_p<8, 16>(a.s, a.p);
    tile_store_if<4, 8>(fresh, w.hi, a.dst);
    a.i0 += a.t0; a.i1 += a.t1;
    if (!fast || d == g + 1) {
      if (!fast && d != 1 && d != g - 15) {
#pragma unroll
        for (int i = 0; i < 16; i++) { a.o[4 * i] *= sc0; a.o[4 * i + 1] *= sc0; a.o[4 * i + 2] *= sc1; a.o[4 * i + 3] *= sc1; }
      }
      if (d == g + 1) break;
    }
    d++;
    fresh = d == 2 || d == g - 14;
    TSS(12 + 6 * (d - g + 15));
    c.turn();
    TSS(13 + 6 * (d - g + 15));
    fence_regs(a.o); fence_regs(a.p);
    wg_fence();
    issue_qk(a.s, dq, dk);
    TSS(14 + 6 * (d - g + 15));
    c.wait(c.wg ? uk ^ 12 : ur); c.skip(c.wg ? ur : uk ^ 12);
    if (fresh || d == 1 || (unsigned)(d - g + CHK_D) < 2) {
      if (fresh) pack_o(a.o, rcp(a.i0), rcp(a.i1), w.hi);
      else if (d == 1) {
        a.i0 = a.l[0] + a.l[1]; a.i1 = a.l[2] + a.l[3];
        a.t0 = __shfl_xor_sync(~0u, a.i0, 1); a.t1 = __shfl_xor_sync(~0u, a.i1, 1);
        a.l[0] = a.l[1] = a.l[2] = a.l[3] = 0.f;
        uint32_t off = ctx_off(c, h, 15 - g, c.wg);
        asm volatile("" : "+r"(off));
        a.dst = g_T + (off + ((uint32_t)(uint64_t)a.dst & 511));
        fast = fast2;
      } else if (d == g - CHK_D) fence_async_smem();
      else fast2 = att_fast(w.hi, a.kn);
    }
    TSS(15 + 6 * (d - g + 15));
    wgmma_pv_sel(a.o, a.p, dv, !lo, !fresh, c.wg);
    wg_wait<1>(); fence_regs(a.s);
    c.release(uk, 2);
    c.release(d == 0 ? 0 : 2, (d == 0 || d == g + 1) ? 2 : 0);
  }
  att_last(c, a, w, h, g, g == 0);
}

constexpr int CV_H = 1024, CV_U = 5120, CV_D = CV_U + 4128;
template<int OFF> __device__ __forceinline__ uint32_t lds32o(uint32_t a) { uint32_t v; asm volatile("ld.shared.u32 %0, [%1+%2];" : "=r"(v) : "r"(a), "n"(OFF) : "memory"); return v; }
template<int G, int G1 = 16> __device__ __forceinline__ void conv_lda(uint32_t (&a)[64], uint32_t p) {
  a[4 * G + 0] = lds32o<-256 * G>(p);
  a[4 * G + 1] = lds32o<-256 * G - 128>(p);
  a[4 * G + 2] = lds32o<-256 * G + 16>(p);
  a[4 * G + 3] = lds32o<-256 * G - 112>(p);
  if constexpr (G + 1 < G1) conv_lda<G + 1, G1>(a, p);
}
struct CvAcc { float lo[16], hi[16]; };
__device__ __forceinline__ void fence_regs(CvAcc& d) { fence_regs(d.lo); fence_regs(d.hi); }
template<int T, int G0, int G1> __device__ __forceinline__ void conv_part(float (&d)[16], const uint32_t (&a)[64], uint64_t db) {
#pragma unroll
  for (int G = G0; G < G1; G++) wgmma_rs_n32<0>(d, a[4 * G], a[4 * G + 1], a[4 * G + 2], a[4 * G + 3], db + 32 * T - 16 * G, G > 0);
}
template<int C0> __device__ __forceinline__ void conv_st_h(const float (&d)[16], uint32_t wq, float& c0, float& c1) {
#pragma unroll
  for (int n = 0; n < 4; n++) { sts64f(wq + (C0 + n * 8) * 4, d[4 * n] + c0, d[4 * n + 1] + c1); c0 = d[4 * n + 2]; c1 = d[4 * n + 3]; }
}
template<int R> __device__ __forceinline__ void conv_st(const CvAcc& d, uint32_t wq, float& c0, float& c1) { conv_st_h<64 * R>(d.lo, wq, c0, c1); conv_st_h<64 * R + 32>(d.hi, wq, c0, c1); }

constexpr int OC_PART = 13824, OC_ROW = 544;
__device__ __forceinline__ int out_next(int u) { return (0x84ac680u >> (2 * u)) & 15; }
struct Out { float acc[64]; int pu; uint64_t da, db; };
template<bool FIRST, bool REL, int W = 1> __device__ __forceinline__ void out_step(Cons& c, Out& o, bool extra = false) {
  const int pu = o.pu, u = extra ? 2 : out_next(pu);
  o.pu = u;
  c.wait(u);
  const uint64_t da = o.da + (uint32_t)(u * 1024), db = o.db + (uint32_t)(u * 1024);
  wg_fence();
#pragma unroll
  for (int kk = 0; kk < 4; kk++) wgmma_ss_n128<1>(o.acc, da + (kk >> 1) * 32 + (kk & 1) * 2, db + kk * 128, !(FIRST && kk == 0));
  wg_commit();
  if (REL) { wg_wait<W>(); c.release(pu, 2); }
}
template<int I0, int I1> __device__ __forceinline__ void oc_red(float (&y)[8], uint32_t rq) {
#pragma unroll
  for (int i = I0; i < I1; i++) { const float v = __uint_as_float(lds32(rq + i * OC_ROW - (i >> 3) * 8)); y[i & 7] = i < 8 ? v : y[i & 7] + v; }
}
template<int I0, int I1> __device__ __forceinline__ void oc_ld(float (&t)[32], uint32_t rq) {
#pragma unroll
  for (int i = I0; i < I1; i++) t[i] = __uint_as_float(lds32(rq + i * OC_ROW - (i >> 3) * 8));
}
__device__ __forceinline__ void oc_emit(const float (&y)[8], const uint4& u, uint32_t D2, uint8_t* dst) {
  uint4 z;
  z.x = hadd2(pack_bf16(y[0], y[1]), hmul2(__byte_perm(u.w, 0, 0x1032), D2));
  z.y = hadd2(pack_bf16(y[2], y[3]), hmul2(__byte_perm(u.z, 0, 0x1032), D2));
  z.z = hadd2(pack_bf16(y[4], y[5]), hmul2(__byte_perm(u.y, 0, 0x1032), D2));
  z.w = hadd2(pack_bf16(y[6], y[7]), hmul2(__byte_perm(u.x, 0, 0x1032), D2));
  *(uint4*)dst = z;
}
template<bool THR> __device__ __forceinline__ void conv_round(Cons& c, Out& o, int u, uint32_t ub, uint32_t wq, uint32_t rq, int ch) {
  const int r = c.lane >> 2, q = c.lane & 3, tid = c.warp * 32 + c.lane;
  const uint32_t ap = ub + CV_U + ((r & 1) ? 0 : UPITCH) + 4 * (((2039 - r) >> 1) + q - 8 * c.warp);
  uint32_t a[64];
  CvAcc d0, d1;
  float y[8], t[32], c0 = 0.f, c1 = 0.f;
  const uint64_t db0 = odesc(c.daddr(u) + CV_H - 16, 16, 128, 0);
#define STEP(N) if (THR) out_step<false, true>(c, o); else if (N == 0) c.turn(); else if (N == 10) wg_wait<0>();
#define STEP2(N) if (THR) out_step<false, true, 2>(c, o); else { if (N == 9) c.pass(); wg_wait<1>(); }
#define PART(...) { const uint64_t db = db0 + (c.mask >> 16); wg_fence(); __VA_ARGS__; wg_commit(); }
#define KEEP() asm volatile("add.f32 %0, %0, 0f80000000;" : "+f"(c0)); asm volatile("add.f32 %0, %0, 0f80000000;" : "+f"(c1));
  c.wait(u);
  conv_lda<0, THR ? 4 : 12>(a, ap);
  STEP(0)
  if (THR) conv_lda<4, 7>(a, ap);
  PART(conv_part<0, 0, 2>(d0.lo, a, db); conv_part<1, 0, 4>(d0.hi, a, db); conv_part<2, 0, 2>(d1.lo, a, db))
  STEP2(1)
  if (THR) conv_lda<7, 10>(a, ap);
  PART(conv_part<2, 2, 6>(d1.lo, a, db); conv_part<3, 0, 4>(d1.hi, a, db))
  STEP2(2)
  fence_regs(d0);
  if (THR) c.sync();
  sts64f(wq - 32, 0.f, 0.f);
  conv_st_h<0>(d0.lo, wq, c0, c1); KEEP()
  PART(conv_part<3, 4, 8>(d1.hi, a, db); conv_part<4, 0, 4>(d0.lo, a, db))
  STEP2(3)
  fence_regs(d1.lo);
  conv_st_h<32>(d0.hi, wq, c0, c1); conv_st_h<64>(d1.lo, wq, c0, c1); KEEP()
  PART(conv_part<4, 4, 10>(d0.lo, a, db); conv_part<5, 0, 2>(d0.hi, a, db))
  STEP2(4)
  fence_regs(d1.hi);
  float e0 = d1.hi[12] + d1.hi[10], e1 = d1.hi[13] + d1.hi[11];
  conv_st_h<96>(d1.hi, wq, c0, c1); KEEP()
  if (THR) conv_lda<10, 12>(a, ap);
  PART(conv_part<5, 2, 10>(d0.hi, a, db))
  STEP2(5)
  conv_lda<12, 14>(a, ap);
  c.sync();
  if (THR) oc_red<0, 6>(y, rq); else oc_ld<0, 8>(t, rq);
  PART(conv_part<5, 10, 12>(d0.hi, a, db); conv_part<6, 0, 6>(d1.lo, a, db))
  STEP2(6)
  if (THR) oc_red<6, 20>(y, rq); else oc_ld<8, 16>(t, rq);
  PART(conv_part<6, 6, 14>(d1.lo, a, db))
  STEP2(7)
  if (THR) oc_red<20, 26>(y, rq); else oc_ld<16, 24>(t, rq);
  conv_lda<14, 16>(a, ap);
  PART(conv_part<7, 0, 8>(d1.hi, a, db))
  STEP2(8)
  if (THR) oc_red<26, 32>(y, rq); else oc_ld<24, 32>(t, rq);
  PART(conv_part<7, 8, 16>(d1.hi, a, db))
  STEP2(9)
  if (!THR) {
#pragma unroll
    for (int i = 0; i < 8; i++) y[i] = t[i];
    SHADOW {
#pragma unroll
      for (int i = 0; i < 8; i++) y[i] = ((t[i] + t[8 + i]) + t[16 + i]) + t[24 + i];
    }
  }
  fence_regs(y); fence_regs(d0);
  c.sync();
  sts64f(wq - 32, e0, e1);
  conv_st<0>(d0, wq, c0, c1);
  STEP(10)
  fence_regs(d1); fence_regs(a);
  const uint4 u0 = lds128(ub + CV_U + 4080 - 16 * tid), u1 = lds128(ub + CV_U + 2032 - 16 * tid);
  const uint32_t D2 = lds32(ub + CV_D);
  conv_st<1>(d1, wq, c0, c1);
  STEP(11)
  sched_fence(__uint_as_float(u0.x ^ u1.x ^ D2), c.base + SM_DUMMY);
  uint8_t* zp = g_u + (uint32_t)(ch * UCH + (threadIdx.x & 127) * 16);
  oc_emit(y, u0, D2, zp);
  c.sync();
  c.release2(u);
  oc_red<0, 12>(y, rq);
  STEP(12)
  oc_red<12, 24>(y, rq);
  STEP(13)
  oc_red<24, 32>(y, rq);
  oc_emit(y, u1, D2, zp + 2048);
#undef KEEP
#undef STEP
#undef STEP2
#undef PART
}
template<int MASK> __device__ __forceinline__ void cons_conv(Cons& c, int cta, int nch) {
  const uint32_t part = c.addr(4 + 2 * c.wg) + 32;
  const uint32_t wq = part + (c.warp * 8 + (c.lane >> 2)) * OC_ROW + (c.lane & 3) * 8, rq = part + (c.warp * 32 + c.lane) * 4;
  Out o;
  c.wait(4);
#pragma unroll 1
  for (int i = 0; i < nch / 2; i++) {
    const int u = 2 * (i & 1) + c.wg;
    conv_round<false>(c, o, u, c.addr(u), wq, rq, conv_channel<MASK>(cta, 2 * i + c.wg));
    if ((i & 15) == 15 || i == nch / 2 - 1) c.signal(SIG_Z + (i >> 4));
  }
}
__device__ __forceinline__ uint32_t mix(uint32_t og, uint32_t b, uint32_t ga) { return hadd2(ga, hmul2(og, b)); }
template<int MASK> __device__ __forceinline__ void cons_out(Cons& c, const Maps& M, const Params& P, int cta, Pend& w) {
  const int mb = out_mb(cta), nb = out_nb(cta);
  Out o;
  o.da = odesc(c.daddr(0) + c.wg * 8192, 16, 1024, 2); o.db = odesc(c.daddr(1), 8192, 1024, 1);
  o.pu = 5 + gridDim.y;
  out_step<true, false>(c, o);
  int ks = 1;
  const uint32_t dst = ctx_off(c, 16 + (cta >> 3), cta & 7, 1 - c.wg);
#pragma unroll 1
  for (;; ks++) {
    if (MASK & PH_ATT) {
      if (ks == (c.wg ? ST_1 : 1)) tile_store<0, 1>(w.lo, dst, c.lane);
      if (ks == (c.wg ? ST_1 + ST_D : 1)) tile_store<1, 2>(w.lo, dst, c.lane);
      if (ks == (c.wg ? ST_1 + 2 * ST_D : 1)) tile_store<2, 3>(w.lo, dst, c.lane);
      if (ks == (c.wg ? ST_1 + 3 * ST_D : 1)) { tile_store<3, 4>(w.lo, dst, c.lane); c.signal(SIG_CTX + 1); }
    }
    if (ks == (c.wg ? OC_S1 : OC_S0)) break;
    out_step<false, true>(c, o, ks == 1);
  }
  if (MASK & PH_CONV) {
    const int r = c.lane >> 2, q = c.lane & 3, tid = c.warp * 32 + c.lane, u = 2 * c.wg;
    const uint32_t ub = c.addr(u), part = ub + OC_PART + 32;
    const uint32_t wq = part + (c.warp * 8 + r) * OC_ROW + q * 8, rq = part + tid * 4;
    int ch = conv_channel<MASK>(cta, 3 * c.wg);
#pragma unroll 1
    for (int i = 0; ch >= 0; i++) {
      conv_round<true>(c, o, u + (i >> 8), ub, wq, rq, ch);
      ch = i + c.wg < 2 ? ch + 1 : -1;
      if (c.wg > i) { mbar_wait(c.base + SM_RDY + 8 * RDY_T, 0); ch = __shfl_sync(~0u, lds32(c.base + SM_POOL), 0); }
      if (ch < 0) { c.signal(SIG_Z); c.sync(); c.release2(u + 1); TSO(0); }
      out_step<false, true>(c, o);
#pragma unroll 1
      for (int k = 15; k < (ch < 0 ? 0 : c.wg ? OC_L1 : OC_L0); k++) out_step<false, true>(c, o);
      ks += ch < 0 ? 15 : c.wg ? OC_L1 : OC_L0;
    }
    if (c.wg) c.skip(0);
  }
  TS(c.wg, 9);
#pragma unroll 1
  for (; ks < 57; ks++) out_step<false, true>(c, o);
  uint32_t ga[32];
  TSO(1);
  c.wait(3);
  TSO(2);
  const float g0 = __uint_as_float(lds32(c.base + SM_GATE + 4 * (c.wg * 64 + c.warp * 16 + (c.lane >> 2)))), g1 = __uint_as_float(lds32(c.base + SM_GATE + 32 + 4 * (c.wg * 64 + c.warp * 16 + (c.lane >> 2))));
  const uint32_t gg0 = pack_bf16(g0, g0), gg1 = pack_bf16(g1, g1);
  const uint32_t og0 = pack_bf16(1.f - g0, 1.f - g0), og1 = pack_bf16(1.f - g1, 1.f - g1);
  const int xr = c.wg * 64 + c.warp * 16 + (c.lane & 15);
  const uint32_t xa = c.addr(2) + xr * 128, xs = xr & 7, xh = c.lane >> 4;
  const int zr = (c.lane & 7) + ((c.lane >> 4) << 3);
  const uint32_t za = c.addr(0) + c.wg * 16384 + zr * 128 + (((c.warp * 2 + ((c.lane >> 3) & 1)) ^ (zr & 7)) << 4);
#pragma unroll
  for (int i = 0; i < 8; i++) {
    if (i == 0) out_step<false, true>(c, o);
    if (i == 3) out_step<false, true>(c, o);
    if (i == 6) out_step<false, true>(c, o);
    ldsm4(xa + (i >> 2) * 16384 + ((((i & 3) * 2 + xh) ^ xs) << 4), ga[4 * i], ga[4 * i + 1], ga[4 * i + 2], ga[4 * i + 3]);
  }
  TSO(3);
#pragma unroll 1
  for (ks = 60; ks < 64; ks++) out_step<false, false>(c, o);
  TSO(4);
  c.wait(0);
  TSO(5);
  SHADOW {
#pragma unroll
    for (int i = 0; i < 8; i++) {
      uint32_t z0, z1, z2, z3;
      ldsm4t(za + i * 2048, z0, z1, z2, z3);
      ga[4 * i + 0] = hmul2(ga[4 * i + 0], z0); ga[4 * i + 1] = hmul2(ga[4 * i + 1], z1); ga[4 * i + 2] = hmul2(ga[4 * i + 2], z2); ga[4 * i + 3] = hmul2(ga[4 * i + 3], z3);
      ga[4 * i + 0] = hmul2(gg0, ga[4 * i + 0]); ga[4 * i + 1] = hmul2(gg1, ga[4 * i + 1]); ga[4 * i + 2] = hmul2(gg0, ga[4 * i + 2]); ga[4 * i + 3] = hmul2(gg1, ga[4 * i + 3]);
    }
  }
  c.signal(SIG_DONE);
  fence_regs(ga);
  TSO(6);
  wg_wait<0>(); fence_regs(o.acc);
  TSO(7);
#pragma unroll
  for (int i = 0; i < 8; i++) {
    const uint32_t r0 = mix(og0, pack_bf16(o.acc[8 * i + 0], o.acc[8 * i + 1]), ga[4 * i + 0]);
    const uint32_t r1 = mix(og1, pack_bf16(o.acc[8 * i + 2], o.acc[8 * i + 3]), ga[4 * i + 1]);
    const uint32_t r2 = mix(og0, pack_bf16(o.acc[8 * i + 4], o.acc[8 * i + 5]), ga[4 * i + 2]);
    const uint32_t r3 = mix(og1, pack_bf16(o.acc[8 * i + 6], o.acc[8 * i + 7]), ga[4 * i + 3]);
    stsm4(xa + (i >> 2) * 16384 + ((((i & 3) * 2 + xh) ^ xs) << 4), r0, r1, r2, r3);
    if ((i & 3) == 3) {
      __syncwarp();
#pragma unroll
      for (int k = 0; k < 4; k++) {
        const int rr = c.wg * 64 + c.warp * 16 + k * 4 + (c.lane >> 3);
        const uint4 v = lds128(c.addr(2 + (i >> 2)) + rr * 128 + (((c.lane ^ rr) & 7) << 4));
        *(uint4*)(P.out + (uint32_t)((mb * 128 + rr) * 1024 + nb * 128 + (i >> 2) * 64 + (c.lane & 7) * 8)) = v;
      }
    }
  }
  TSO(8);
}

__device__ __forceinline__ void load_conv(Prod& p, const Maps& M, int u, int ch) {
  if (elect()) {
    mbar_expect(p.full(u), 5120 + UCH);
    tma3d(p.addr(u), &M.h, 0, -8, ch, p.full(u), true);
    bulk_g2s(p.addr(u) + CV_U, g_u + (size_t)ch * UCH, UCH, p.full(u), true);
  }
}
template<int MASK> __device__ __forceinline__ void prod_conv(Prod& p, const Maps& M, int cta, int nch) {
  int ready = -1;
#pragma unroll 1
  for (int i = 0; i < nch; i++) {
    const int ch = conv_channel<MASK>(cta, i);
    const int u = i & 3;
    if ((ch >> 6) != ready) { ready = ch >> 6; if (cta < NREG) mbar_wait(p.base + SM_RDY + 8 * RDY_U, 0); else cnt_wait(g_cnt + (C_U + ready) * CSTRIDE, 128); }
    p.acquire(u, 1);
    load_conv(p, M, u, ch);
    if (i == 3) { p.acquire(4, 4); if (elect()) mbar_arrive(p.full(4)); }
  }
}
#define HOIST(v) asm volatile("" : "+r"(v))
template<int MASK> __device__ __forceinline__ void producer(const Maps& M, const Params& P, uint32_t base, int cta, int lane) {
  Prod p{base, ((MASK & PH_KV) && cta < NREG) ? 0xffffcfffu ^ ((1u << (3 * NFIRST)) - 1) : 0xffffffffu, lane,
         (cta * 3 + 2) * 2048};
  if (cta >= NREG) { if (MASK & PH_CONV) prod_conv<MASK>(p, M, cta, CV_EXTRA<MASK>); return; }
  const int g = cta & 7, j = cta >> 3, rank = cta & 1;
#pragma unroll 1
  for (int half = 0; half < 2; half++) {
    const int h = j + 16 * half;
    if (MASK & PH_KV) {
      const CUtensorMap* mw = rank ? &M.wv : &M.wk;
#pragma unroll 1
      for (int it = half ? 0 : NFIRST; it < 16; it++) {
        const int u = gemm_unit(it);
        uint32_t bar = p.full(u), d0 = p.addr(u), d1 = p.addr(u + 1 + rank); int k0 = (it & 7) * 64, r0 = (2 * g + (it >> 3)) * 128;
        HOIST(bar); HOIST(d0); HOIST(d1); HOIST(k0); HOIST(r0);
        p.acquire(u, 3);
        if (elect()) {
          mbar_expect(bar, 3 * UNIT);
          tma3d_mc(d1, mw, 0, k0, 2 * h, bar, it >= 8);
          tma2d(d0, &M.c, k0, r0, bar);
        }
      }
    }
    if (MASK & PH_ATT) {
#pragma unroll 1
      for (int ks = 0; ks < 16; ks++) {
        const int u = gemm_unit(ks);
        uint32_t bar = p.full(u), d0 = p.addr(u), d1 = p.addr(u + 1), d2 = p.addr(u + 2) + rank * 8192; int k0 = ks * 64;
        HOIST(bar); HOIST(d0); HOIST(d1); HOIST(d2); HOIST(k0);
        p.acquire(u, 3);
        if (elect()) {
          mbar_expect(bar, 3 * UNIT);
          tma2d_mc(d2, &M.wq, h * 128 + rank * 64, k0, bar, true);
          tma2d(d0, &M.x, k0, (15 - g) * 128, bar);
          tma2d(d1, &M.x, k0, g * 128, bar);
        }
      }
      TS(2, 8 * half + 0);
      mbar_wait(base + SM_RDY + 8 * (RDY_KV + half), 0);
      TS(2, 8 * half + 1);
      const uint8_t* KVh = g_T + T_KV + (size_t)kv_slot<MASK>(h) * 16 * 65536;
      if (MASK & PH_PRE) mbar_wait(base + SM_RDY + 8 * RDY_AUX, 0);
      if (elect()) { mbar_expect(p.full(12), 32768); bulk_g2s(p.addr(12), KVh, 32768, p.full(12), true); }
      p.acquire(0, 4);
      if (elect()) mbar_arrive(p.full(0));
#pragma unroll 1
      for (int i = 1; i < 34; i++) {
        const int isv = !(i & 1) || i == 33, st = i == 33 ? 16 : (isv ? (i >> 1) - 1 : (i + 1) >> 1), u = 4 + 2 * (i & 3);
        const bool own = st == 15 - (g & 6);
        uint32_t bar = p.full(u), d0 = p.addr(own ? u : u + rank), off = (st <= 15 - g ? st : 16 - st) * 65536 + isv * 32768 + (own ? 0 : rank * UNIT);
        HOIST(bar); HOIST(d0); HOIST(off);
        p.acquire(u, 2);
        if (elect()) {
          mbar_expect(bar, 32768);
          if (own) bulk_g2s(d0, KVh + off, 32768, bar, true); else bulk_g2s_mc(d0, KVh + off, UNIT, bar, true);
        }
      }
    }
  }
  if ((MASK & PH_CONV) && !(MASK & PH_OUT)) prod_conv<MASK>(p, M, cta, CV_REG<MASK>);
  if (MASK & PH_OUT) {
    const int y0 = out_mb(cta) * 512 + rank * 8, z0 = 2 * out_nb(cta);
    int u = 6;
#pragma unroll 1
    for (int hf = 0; hf < 2; hf++) {
      TS(2, 16 + 2 * hf);
      mbar_wait(base + SM_RDY + 8 * (RDY_CTX + hf), 0);
      TS(2, 17 + 2 * hf);
#pragma unroll 1
      for (int n = hf * 32; n < hf * 32 + 32; n++) {
        const int ks = n == 1 ? 2 : n == 2 ? 1 : n;
        u = n == 2 ? 2 : n == 3 ? 10 : out_next(u);
        uint32_t bar = p.full(u), d0 = p.addr(u) + rank * 8192, d1 = p.addr(u + 1); int x = (ks & 1) * 256, y = y0 + (ks >> 1) * 16, k0 = ks * 64;
        HOIST(bar); HOIST(d0); HOIST(d1); HOIST(x); HOIST(y); HOIST(k0);
        p.acquire(u, 2);
        if (elect()) {
          mbar_expect(bar, 2 * UNIT);
          tma2d_mc(d0, &M.ctx, x, y, bar, true);
          tma3d(d1, &M.wo, 0, k0, z0, bar, true);
          if (ks == 1) mbar_arrive(base + SM_RDY + 8 * RDY_X);
          if (ks == Z_AT) mbar_arrive(base + SM_RDY + 8 * RDY_Z);
        }
      }
    }
  }
}
template<int MASK> __device__ __forceinline__ void producer2(const Maps& M, const Params& P, uint32_t base, int cta, int w, int lane) {
  Prod p{base, 0xffffffffu, lane, 0};
  const int mb = out_mb(cta), nb = out_nb(cta), u = 2 * w;
  if (w) { mbar_wait_slow(base + SM_RDY + 8 * RDY_X, 0); p.mask ^= 12; }
  if (MASK & PH_CONV) {
    mbar_wait_slow(base + SM_SIG + 8 * (SIG_ATT + 1), 0);
    mbar_wait_slow(base + SM_RDY + 8 * RDY_U, 0);
#pragma unroll 1
    for (int i = 0, ch = conv_channel<MASK>(cta, 3 * w); ch >= 0; i++) {
      p.acquire_slow(u, i ? 1 : 2);
      load_conv(p, M, u, ch);
      ch = i + w < 2 ? ch + 1 : -1;
      if (w > i) { mbar_wait_slow(base + SM_RDY + 8 * RDY_T, 0); ch = lds32(base + SM_POOL); }
    }
  }
  p.acquire_slow(u, 2);
  if (!w && elect()) map_pf(&M.z);
  TSA(52 - 2 * w);
  mbar_wait(base + SM_RDY + 8 * (!w ? RDY_Z : RDY_G), 0);
  TSA(53 - 2 * w);
  if (elect()) {
    const uint32_t bar = p.full(3 * w);
    mbar_expect(bar, 2 * UNIT + (!w ? 0 : 512));
    tma2d(p.addr(u), !w ? &M.z : &M.x, (!w ? mb : nb) * 128, (!w ? nb : mb) * 128, bar, true);
    tma2d(p.addr(u + 1), !w ? &M.z : &M.x, (!w ? mb : nb) * 128 + 64, (!w ? nb : mb) * 128, bar, true);
    if (w) bulk_g2s(base + SM_GATE, g_gate + mb * 128, 512, bar);
  }
}

__device__ __forceinline__ constexpr uint32_t PUB(int sig, int cnt, int n) { return 0x80000000u | (sig << 24) | (n << 8) | cnt; }
__device__ __forceinline__ constexpr uint32_t GET(int rdy, int cnt, int n) { return (rdy << 24) | (n << 8) | cnt; }
template<int MASK> __device__ __forceinline__ void sync_agent(uint32_t base, int cta, int lane) {
  if ((base & 0x3FFFF) != SMEM_BASE) asm volatile("trap;");
  const int g = cta & 7, j = cta >> 3, go = min(out_mb(cta), 15 - out_mb(cta));
  const int c0 = conv_channel<MASK>(cta, 0), c1 = c0 + CV_REG<MASK> - 1, n0 = min(CV_REG<MASK>, 128 - (c0 & 127));
  constexpr bool KV = MASK & PH_KV, ATT = MASK & PH_ATT, CONV = MASK & PH_CONV, OUT = MASK & PH_OUT, ALL = MASK == PH_ALL;
  uint32_t e = 0;
  if (cta >= NREG) { if (CONV && lane * 32 < CV_EXTRA<MASK>) e = PUB(SIG_Z + lane, C_Z + lane, min(32, CV_EXTRA<MASK> - lane * 32)); }
  else switch (lane) {
    case 0:  if (KV) e = PUB(SIG_KV, C_KV + j, 1); break;
    case 1:  if (ATT) e = GET(RDY_KV, C_KV + j, 8); break;
    case 2:  if (ALL) e = PUB(SIG_WAR, C_WAR + j, 1); break;
    case 3:  if (ATT) e = PUB(SIG_CTX, C_CTX + g, 1); break;
    case 4:  if (ALL) e = GET(RDY_WAR, C_WAR + j, 8); break;
    case 5:  if (KV) e = PUB(SIG_KV + 1, C_KV + 16 + j, 1); break;
    case 6:  if (ATT) e = GET(RDY_KV + 1, C_KV + 16 + j, 8); break;
    case 7:  if (OUT) e = GET(RDY_CTX, C_CTX + go, 16); break;
    case 8:  if (CONV) e = GET(RDY_U, C_U + (c0 >> 6), 128); break;
    case 9:  if (CONV) e = GET(ALL ? RDY_NONE : RDY_U, C_U + (ALL ? 14 : c1 >> 6), 128); break;
    case 10: if (ALL) e = GET(RDY_T, C_U + 15, 128); break;
    case 11: if (ATT) e = PUB(SIG_CTX + 1, C_CTX + 8 + g, 1); break;
    case 12: if (OUT) e = GET(RDY_CTX + 1, C_CTX + 8 + go, 16); break;
    case 13: if (OUT) e = GET(RDY_G, C_GATE, 256); break;
    case 14: if (CONV) e = PUB(SIG_Z, C_Z + (c0 >> 7), n0); break;
    case 15: if (ALL) e = PUB(SIG_Z, C_Z + 7, 1); else if (CONV && n0 < CV_REG<MASK>) e = PUB(SIG_Z, C_Z + (c1 >> 7), CV_REG<MASK> - n0); break;
    case 16: if (OUT) e = GET(RDY_Z, C_Z + out_nb(cta), 128); break;
  }
  if (ALL && lane == 0) { mbar_expect(base + SM_RDY + 8 * RDY_T, 4); mbar_arrive(base + SM_RDY + 8 * RDY_U); }
  __syncwarp();
#pragma unroll 1
  for (int i = 0; i < 17; i++) {
    const uint32_t x = __shfl_sync(~0u, e, i), id = (x >> 24) & 127, n = (x >> 8) & 0xffff;
    if (x == 0) continue;
    unsigned* cnt = g_cnt + (x & 255) * CSTRIDE;
    if (x >> 31) {
      mbar_wait_slow(base + SM_SIG + 8 * id, 0);
      const bool draw = ALL && i == 11 && !(cta & 1);
      unsigned t = 0;
      if (draw && lane == 0) asm volatile("atom.relaxed.gpu.global.add.u32 %0, [%1], 1;" : "=r"(t) : "l"(g_cnt + C_TICKET * CSTRIDE) : "memory");
      if (lane == 0 && !(ALL && i == 15 && (int)lds32(base + SM_POOL) < 0)) cnt_publish(cnt, n, i != 15);
      if (draw) {
        t = __shfl_sync(~0u, t, 0);
        uint32_t peer;
        asm volatile("mapa.shared::cluster.u32 %0, %1, %2;" : "=r"(peer) : "r"(base), "r"(lane & 1));
        if (lane < 2) asm volatile("st.async.weak.shared::cluster.mbarrier::complete_tx::bytes.u32 [%0], %1, [%2];"
          :: "r"(peer + SM_POOL), "r"(t < 64 - NSKIP ? CV_POOL + 2 * t + lane : ~0u), "r"(peer + SM_RDY + 8 * RDY_T) : "memory");
      }
    } else {
      cnt_wait(cnt, n);
      if (id < 2) {
        const float4 kn = __ldcg((const float4*)(g_kn2 + kv_slot<MASK>(j + 16 * id) * 128) + lane);
        const uint32_t m = __reduce_max_sync(~0u, max(max(__float_as_uint(kn.x), __float_as_uint(kn.y)), max(__float_as_uint(kn.z), __float_as_uint(kn.w))));
        if (lane == 0) asm volatile("st.shared.u32 [%0], %1;" :: "r"(base + SM_KMAX + 4 * id), "r"(m) : "memory");
      }
      if (lane == 0) mbar_arrive(base + SM_RDY + 8 * id);
    }
    __syncwarp();
  }
}

__device__ __forceinline__ void aux_gate(const Params& P, int cta, int aw, int lane) {
  uint4 gw[4];
#pragma unroll
  for (int i = 0; i < 4; i++) gw[i] = __ldg((const uint4*)P.gw + i * 32 + lane);
#pragma unroll 1
  for (int row = cta * 16 + aw * 8; row < cta * 16 + aw * 8 + 8; row++) {
    float a = 0.f;
#pragma unroll
    for (int i = 0; i < 4; i++) {
      const uint4 xv = __ldg((const uint4*)(P.x + (size_t)row * 1024) + i * 32 + lane);
      uint32_t m;
      m = hmul2(xv.x, gw[i].x); a += bf_lo(m) + bf_hi(m); m = hmul2(xv.y, gw[i].y); a += bf_lo(m) + bf_hi(m);
      m = hmul2(xv.z, gw[i].z); a += bf_lo(m) + bf_hi(m); m = hmul2(xv.w, gw[i].w); a += bf_lo(m) + bf_hi(m);
    }
#pragma unroll
    for (int o = 16; o > 0; o >>= 1) a += __shfl_xor_sync(~0u, a, o);
    a = bf_lo(pack_bf16(a, 0.f));
    const float gt = bf_lo(pack_bf16(__fdividef(1.f, 1.f + ex2(-a * 1.4426950408889634f)), 0.f));
    if (lane == 0) g_gate[row] = gt;
    __nanosleep(GATE_SLEEP);
  }
  cnt_signal(g_cnt + C_GATE * CSTRIDE, lane);
  if (aw == 0) { TSA(44); }
}
template<int MASK> __device__ __forceinline__ void aux_pre(const Maps& M, const Params& P, uint32_t base, int cta, int aw, int lane) {
  const uint32_t kb = base + 12 * UNIT, bar = base + SM_PRE;
  const int r = lane >> 2, q = lane & 3;
  const int mi = lane >> 3, row0 = (lane & 6) + 1 - (lane & 1);
  const int ra = (mi * 9 + 1) * 2 + row0;
  const int rb = (mi == 0 ? 3 : mi) * 18 + row0;
#pragma unroll 1
  for (int it = 0; it < (cta < 96 ? 5 : 4); it++) {
    if (it == PRE_EARLY && MASK == PH_ALL) { mbar_wait_slow(base + SM_SIG + 8 * SIG_ATT, 0); aux_gate(P, cta, aw, lane); }
    if (it == PRE_EARLY && MASK == PH_ALL) mbar_wait_slow(base + SM_SIG + 8 * (SIG_ATT + 1), 0);
    const int cg = it ? it * 4 - 3 + (cta >> 5) : 0, tb = cta & 31;
    if (it == 0 && aw == 0) TSA(45);
    if (aw == 0 && elect()) {
      mbar_expect(bar, 2 * 9216);
      tma4d(kb, &M.k, cg * 64, 0, tb * 8 - 1, 0, bar, true);
      tma4d(kb + 9216, &M.v, cg * 64, 0, tb * 8 - 1, 0, bar, true);
    }
    const uint2 swl = __ldg((const uint2*)(P.shift + (cg * 64 + aw * 32 + lane) * 4));
    if (tb == 0) {
      uint8_t* e = g_u + (size_t)(cg * 64 + aw * 32 + lane) * UCH + 4096;
      *(uint4*)e = make_uint4(0, 0, 0, 0); *(uint4*)(e + UPITCH) = make_uint4(0, 0, 0, 0);
      *(uint32_t*)(e + 32) = (uint32_t)__bfloat16_as_ushort(P.D[cg * 64 + aw * 32 + lane]) * 0x10001u;
    }
    if (it == 0 && aw == 0) TSA(46);
    if (it == 0) mbar_wait(bar, 0); else mbar_wait_slow(bar, it & 1);
    if (it == 0 && aw == 0) TSA(47);
#pragma unroll 1
    for (int ol = it ? 0 : cta >> 5; ol < (it ? 4 : (cta >> 5) + 1); ol++) {
      const int oc = aw * 4 + ol;
      const uint32_t s01 = __shfl_sync(~0u, swl.x, ol * 8 + r), s23 = __shfl_sync(~0u, swl.y, ol * 8 + r);
      const uint32_t w0 = __byte_perm(s01, 0, 0x1010), w1 = __byte_perm(s01, 0, 0x3232), w2 = __byte_perm(s23, 0, 0x1010), w3 = __byte_perm(s23, 0, 0x3232);
      const uint32_t pa = kb + ra * 128 + ((oc ^ (ra & 7)) << 4), pb = kb + (mi == 0 ? 9216 : 0) + rb * 128 + ((oc ^ (rb & 7)) << 4);
      uint8_t* e0 = g_u + (uint32_t)((cg * 64 + oc * 8 + r) * UCH + (2040 - tb * 64 - 8 * q) * 2);
#pragma unroll
      for (int hb = 0; hb < 2; hb++) {
        uint32_t k[7], v[5];
        ldsm4t(pa + hb * 1024, k[3], k[4], k[5], k[6]);
        ldsm4t(pa + hb * 1024 + 9216, v[1], v[2], v[3], v[4]);
        ldsm4t(pb + hb * 1024, v[0], k[0], k[1], k[2]);
        uint32_t o1 = __byte_perm(k[1], k[0], 0x5432);
#pragma unroll
        for (int m = 0; m < 5; m++) {
          const uint32_t o2 = __byte_perm(k[m + 2], k[m + 1], 0x5432);
          v[m] = hmul2(hadd2(hadd2(hadd2(hmul2(o1, w3), hmul2(k[m + 1], w2)), hmul2(o2, w1)), hmul2(k[m + 2], w0)), v[m]);
          o1 = o2;
        }
        *(uint4*)(e0 - hb * 64) = make_uint4(v[4], v[3], v[2], v[1]);
        *(uint4*)(e0 - hb * 64 + UPITCH) = make_uint4(__byte_perm(v[4], v[3], 0x5432), __byte_perm(v[3], v[2], 0x5432), __byte_perm(v[2], v[1], 0x5432), __byte_perm(v[1], v[0], 0x5432));
        if (it >= PRE_EARLY) __nanosleep(PRE_SLEEP);
      }
    }
    bar_sync(5, 64);
    if (aw == 0) { TSA(40 + min(it, 3)); }
    if (it == PRE_EARLY - 1 && aw == 0 && lane == 0) mbar_arrive(base + SM_RDY + 8 * RDY_AUX);
    if (aw == 1 && lane == 0) asm volatile("red.release.gpu.global.add.u32 [%0], %1;" :: "l"(g_cnt + (C_U + cg) * CSTRIDE), "r"(it ? 4 : 1) : "memory");
    if (it == 0 && aw == 1) TSA(48);
  }
  uint32_t rel;
  asm volatile("mapa.shared::cluster.u32 %0, %1, %2;" : "=r"(rel) : "r"(base + SM_BAR + 128 + 8 * (12 + (lane & 1))), "r"((lane >> 1) & 1));
  if (lane < 4) asm volatile("mbarrier.arrive.shared::cluster.b64 _, [%0];" :: "r"(rel) : "memory");
  if (MASK != PH_ALL) aux_gate(P, cta, aw, lane);
}

template<int MASK> __global__ void __cluster_dims__(2, 1, 1) __launch_bounds__(384, 1) gated_mix_kernel(const __grid_constant__ Maps M, const __grid_constant__ Params P) {
  extern __shared__ __align__(1024) uint8_t smem[];
  const uint32_t base = (uint32_t)__cvta_generic_to_shared(smem);
  if ((MASK & PH_KV) && elect()) {
    map_pf(&M.wk + (blockIdx.x & 1)); map_pf(&M.c);
  }
  const int wi = __shfl_sync(~0u, threadIdx.x >> 5, 0), wg = wi >> 2, warp = wi & 3;
  if (elect()) {
    if (wi < 8) {
      const int cnt = 1 << ((0x10332200 >> (4 * wi)) & 15);
#pragma unroll
      for (int i = 0; i < 8; i++) mbar_init(base + SM_BAR + 64 * wi + 8 * i, cnt);
      asm volatile("fence.mbarrier_init.release.cluster;" ::: "memory");
    }
  }
  const int cta = blockIdx.x;
  const bool first_loads = (MASK & PH_KV) && wi == 8 && cta < NREG;
  const CUtensorMap* mw = (cta & 1) ? &M.wv : &M.wk;
  __syncwarp();
  asm volatile("barrier.cluster.arrive.relaxed.aligned;\nbarrier.cluster.wait.aligned;" ::: "memory");
  auto first_stage = [&](int it) {
    const uint32_t bar = base + SM_BAR + 24 * it, d0 = base + 3 * it * UNIT;
    mbar_expect(bar, 3 * UNIT);
    tma3d_mc(d0 + (1 + (cta & 1)) * UNIT, mw, 0, it * 64, 2 * (cta >> 3), bar);
    tma2d(d0, &M.c, it * 64, (cta & 7) * 256, bar);
  };
  if (first_loads && elect()) first_stage(0);
  __syncwarp();
  const int lane = threadIdx.x & 31;
#define TS_PRO()
  if (wg == 2) {
    asm volatile("setmaxnreg.dec.sync.aligned.u32 56;");
    TS_PRO();
    TS(2, 62);
    if (warp == 0) producer<MASK>(M, P, base, cta, lane);
    else if (warp == 1) sync_agent<MASK>(base, cta, lane);
    else if (cta < NREG) {
      if (MASK & PH_PRE) aux_pre<MASK>(M, P, base, cta, warp - 2, lane);
      if (MASK & PH_OUT) producer2<MASK>(M, P, base, cta, warp - 2, lane);
    }
    if (warp == 1) {
      if (MASK & PH_OUT) {
        unsigned old = 0;
        if (lane == 0) asm volatile("atom.relaxed.gpu.global.add.u32 %0, [%1], 1;" : "=r"(old) : "l"(g_cnt + C_EXIT * CSTRIDE) : "memory");
        old = __shfl_sync(~0u, old, 0);
        if (old == NCTA - 1) for (int i = lane; i < C_NUM; i += 32) g_cnt[i * CSTRIDE] = 0;
      }
      mbar_wait_slow(base + SM_SIG + 8 * SIG_DONE, 0);
      if (cta >= NREG || !(MASK & PH_OUT)) { cluster_arrive(); cluster_wait(); }
    }
  } else {
    asm volatile("setmaxnreg.inc.sync.aligned.u32 224;");
    TS_PRO();
    uint32_t rel;
    asm volatile("mapa.shared::cluster.u32 %0, %1, %2;" : "=r"(rel) : "r"(base + SM_BAR + 128 + 8 * (lane & 15)), "r"(lane >> 4));
    Cons c{base, rel, 0u, lane, warp, wg, warp == 3 ? lane & 15 : 16, (cta * 3 + wg) * 2048};
    if (wg == 1) bar_arrive(1, 256);
    if ((MASK & PH_KV) && wi == 4 && cta < NREG) {
      if (elect()) {
#pragma unroll 1
        for (int it = 1; it < NFIRST; it++) {
          asm volatile("{\n.reg .pred p;\n.reg .u32 a, b;\nmov.u32 a, %%clock;\nXL:\nmov.u32 b, %%clock;\nsub.u32 b, b, a;\nsetp.lt.u32 p, b, %0;\n@p bra XL;\n}\n" :: "r"(it == 1 ? FGAP : FGAP2) : "memory");
          first_stage(it);
        }
      }
      __syncwarp();
    }
    TS(wg, 0);
    if (cta < NREG) {
      const int g = cta & 7, j = cta >> 3;
      Pend w = {};
#pragma unroll 1
      for (int half = 0; half < 2; half++) {
        const int h = j + 16 * half, blk = kv_slot<MASK>(h) * 16 + 2 * g;
        if (MASK & PH_KV) cons_kv<(MASK & PH_ATT) != 0>(c, h, blk, g, w, half == 1 && (MASK & PH_ATT));
        TS(wg, 1 + 4 * half);
        if (MASK & PH_ATT) {
          Att a;
          const int fast = cons_q<(MASK & PH_KV) != 0>(c, h, blk + 1, w, a.o, a.kn);
          TS(wg, 2 + 4 * half);
          cons_att(c, a, h, g, w, fast);
          if (half == 0) c.signal(SIG_WAR);
#pragma unroll
          for (int i = 0; i < 8; i++) w.hi[i] = make_uint4(0, 0, 0, 0);
          TS(wg, 3 + 4 * half);
          if (MASK != PH_ALL) { tile_store<0, 4>(w.lo, ctx_off(c, h, g, 1 - wg), lane); c.signal(SIG_CTX + half); }
        } else if (MASK & PH_KV) {
          float kn = 0.f;
          out_piece<SCH_KV, true>(c, w, kv_off(c, blk + 1), blk + 1, kn, 0, true);
          for (int ks = 1; ks < 8; ks++) out_piece<SCH_KV, false>(c, w, kv_off(c, blk + 1), blk + 1, kn, ks, true);
          c.signal(SIG_KV + half);
        }
      }
      if (MASK & PH_OUT) cons_out<MASK>(c, M, P, cta, w);
    }
    if (cta >= NREG || !(MASK & PH_OUT)) {
      if (MASK & PH_CONV) cons_conv<MASK>(c, cta, cta < NREG ? CV_REG<MASK> : CV_EXTRA<MASK>);
      TS(wg, 9);
      c.signal(SIG_DONE);
      cluster_arrive();
    }
    TS(wg, 10);
  }
}

typedef CUresult (*EncFn)(CUtensorMap*, CUtensorMapDataType, cuuint32_t, void*, const cuuint64_t*, const cuuint64_t*, const cuuint32_t*, const cuuint32_t*,
                          CUtensorMapInterleave, CUtensorMapSwizzle, CUtensorMapL2promotion, CUtensorMapFloatOOBfill);
static void enc(EncFn f, CUtensorMap* m, const void* ptr, int rank, const cuuint64_t* dims, const cuuint64_t* strides, const cuuint32_t* box, CUtensorMapSwizzle sw,
                CUtensorMapDataType dt = CU_TENSOR_MAP_DATA_TYPE_BFLOAT16) {
  const cuuint32_t es[4] = {1, 1, 1, 1};
  f(m, dt, rank, (void*)ptr, dims, strides, box, es, CU_TENSOR_MAP_INTERLEAVE_NONE, sw, CU_TENSOR_MAP_L2_PROMOTION_L2_256B, CU_TENSOR_MAP_FLOAT_OOB_FILL_NONE);
}
static void enc2(EncFn f, CUtensorMap* m, const void* ptr, int cols, int rows, int brows) {
  const cuuint64_t d[2] = {(cuuint64_t)cols, (cuuint64_t)rows}, s[1] = {(cuuint64_t)cols * 2}; const cuuint32_t b[2] = {64, (cuuint32_t)brows};
  enc(f, m, ptr, 2, d, s, b, CU_TENSOR_MAP_SWIZZLE_128B);
}
static void encw(EncFn f, CUtensorMap* m, const void* ptr, int cols, int rows) {
  const cuuint64_t d[3] = {64, (cuuint64_t)rows, (cuuint64_t)cols / 64}, s[2] = {(cuuint64_t)cols * 2, 128}; const cuuint32_t b[3] = {64, 64, 2};
  enc(f, m, ptr, 3, d, s, b, CU_TENSOR_MAP_SWIZZLE_128B);
}
extern "C" void kernel_launch(void* const* d_in, const int* in_sizes, int n_in, void* d_out, int out_size) {
  static EncFn fn = nullptr;
  static int ncl = 0;
  static void* zptr = nullptr;
  static void* tptr = nullptr;
  if (!fn) {
    void* p = nullptr; cudaDriverEntryPointQueryResult qr;
    cudaGetDriverEntryPoint("cuTensorMapEncodeTiled", &p, cudaEnableDefault, &qr);
    fn = (EncFn)p;
    cudaFuncSetAttribute(gated_mix_kernel<PH_ALL>, cudaFuncAttributeMaxDynamicSharedMemorySize, SMEM_BYTES);
    cudaFuncSetAttribute(gated_mix_kernel<PH_PRE | PH_KV>, cudaFuncAttributeMaxDynamicSharedMemorySize, SMEM_BYTES);
    cudaFuncSetAttribute(gated_mix_kernel<PH_ATT | PH_CONV>, cudaFuncAttributeMaxDynamicSharedMemorySize, SMEM_BYTES);
    cudaFuncSetAttribute(gated_mix_kernel<PH_OUT>, cudaFuncAttributeMaxDynamicSharedMemorySize, SMEM_BYTES);
    cudaLaunchConfig_t cfg = {}; cfg.gridDim = NCTA; cfg.blockDim = 384; cfg.dynamicSmemBytes = SMEM_BYTES;
    cudaLaunchAttribute at; at.id = cudaLaunchAttributeClusterDimension; at.val.clusterDim.x = 2; at.val.clusterDim.y = 1; at.val.clusterDim.z = 1;
    cfg.attrs = &at; cfg.numAttrs = 1;
    cudaOccupancyMaxActiveClusters(&ncl, gated_mix_kernel<PH_ALL>, &cfg);
    cudaGetSymbolAddress(&zptr, g_u);
    cudaGetSymbolAddress(&tptr, g_T);
  }
  Maps M;
  enc2(fn, &M.x, d_in[0], 1024, 2048, 128);
  enc2(fn, &M.c, d_in[7], 512, 2048, 128);
  enc2(fn, &M.wq, d_in[8], 4096, 1024, 64);
  encw(fn, &M.wk, d_in[9], 4096, 512);
  encw(fn, &M.wv, d_in[10], 4096, 512);
  encw(fn, &M.wo, d_in[11], 1024, 4096);
  { const cuuint64_t d[3] = {64, 32, 1024}, s[2] = {128, 4096}; const cuuint32_t b[3] = {64, 40, 1}; enc(fn, &M.h, d_in[4], 3, d, s, b, CU_TENSOR_MAP_SWIZZLE_NONE); }
  { const cuuint64_t d[2] = {2048, 1024}, s[1] = {UCH}; const cuuint32_t b[2] = {64, 128}; enc(fn, &M.z, zptr, 2, d, s, b, CU_TENSOR_MAP_SWIZZLE_128B); }
  { const cuuint64_t d[2] = {512, 512 * 16}, s[1] = {2048}; const cuuint32_t b[2] = {256, 8};
    enc(fn, &M.ctx, tptr, 2, d, s, b, CU_TENSOR_MAP_SWIZZLE_NONE, CU_TENSOR_MAP_DATA_TYPE_UINT32); }
  { const cuuint64_t d[4] = {1024, 2, 256, 4}, s[3] = {2048, 16384, 4096}; const cuuint32_t b[4] = {64, 2, 9, 4};
    enc(fn, &M.k, d_in[1], 4, d, s, b, CU_TENSOR_MAP_SWIZZLE_128B); enc(fn, &M.v, d_in[2], 4, d, s, b, CU_TENSOR_MAP_SWIZZLE_128B); }
  Params P{(const __nv_bfloat16*)d_in[0], (const __nv_bfloat16*)d_in[3],
           (const __nv_bfloat16*)d_in[5], (const __nv_bfloat16*)d_in[12], (__nv_bfloat16*)d_out};
  bool split = 2 * ncl < NCTA;
  if (!split) {
    gated_mix_kernel<PH_ALL><<<NCTA, 384, SMEM_BYTES>>>(M, P);
  } else {
    gated_mix_kernel<PH_PRE | PH_KV><<<NCTA, 384, SMEM_BYTES>>>(M, P);
    gated_mix_kernel<PH_ATT | PH_CONV><<<NCTA, 384, SMEM_BYTES>>>(M, P);
    gated_mix_kernel<PH_OUT><<<NCTA, 384, SMEM_BYTES>>>(M, P);
  }
}
```

```cpp
#include <cuda_runtime.h>
#include <cuda.h>
#include <cuda_bf16.h>
#include <stdint.h>

template<int TB> __device__ __forceinline__ void wgmma_ss_n256(float (&d)[128], uint64_t da, uint64_t db, int scale_d) {
  asm volatile("{\n.reg .pred p;\nsetp.ne.b32 p, %130, 0;\n"
    "wgmma.mma_async.sync.aligned.m64n256k16.f32.bf16.bf16 {%0, %1, %2, %3, %4, %5, %6, %7, %8, %9, %10, %11, %12, %13, %14, %15, %16, %17, %18, %19, %20, %21, %22, %23, %24, %25, %26, %27, %28, %29, %30, %31, %32, %33, %34, %35, %36, %37, %38, %39, %40, %41, %42, %43, %44, %45, %46, %47, %48, %49, %50, %51, %52, %53, %54, %55, %56, %57, %58, %59, %60, %61, %62, %63, %64, %65, %66, %67, %68, %69, %70, %71, %72, %73, %74, %75, %76, %77, %78, %79, %80, %81, %82, %83, %84, %85, %86, %87, %88, %89, %90, %91, %92, %93, %94, %95, %96, %97, %98, %99, %100, %101, %102, %103, %104, %105, %106, %107, %108, %109, %110, %111, %112, %113, %114, %115, %116, %117, %118, %119, %120, %121, %122, %123, %124, %125, %126, %127}, %128, %129, p, 1, 1, 0, %131;\n}\n"
    : "+f"(d[0]), "+f"(d[1]), "+f"(d[2]), "+f"(d[3]), "+f"(d[4]), "+f"(d[5]), "+f"(d[6]), "+f"(d[7]), "+f"(d[8]), "+f"(d[9]), "+f"(d[10]), "+f"(d[11]), "+f"(d[12]), "+f"(d[13]), "+f"(d[14]), "+f"(d[15]), "+f"(d[16]), "+f"(d[17]), "+f"(d[18]), "+f"(d[19]), "+f"(d[20]), "+f"(d[21]), "+f"(d[22]), "+f"(d[23]), "+f"(d[24]), "+f"(d[25]), "+f"(d[26]), "+f"(d[27]), "+f"(d[28]), "+f"(d[29]), "+f"(d[30]), "+f"(d[31]), "+f"(d[32]), "+f"(d[33]), "+f"(d[34]), "+f"(d[35]), "+f"(d[36]), "+f"(d[37]), "+f"(d[38]), "+f"(d[39]), "+f"(d[40]), "+f"(d[41]), "+f"(d[42]), "+f"(d[43]), "+f"(d[44]), "+f"(d[45]), "+f"(d[46]), "+f"(d[47]), "+f"(d[48]), "+f"(d[49]), "+f"(d[50]), "+f"(d[51]), "+f"(d[52]), "+f"(d[53]), "+f"(d[54]), "+f"(d[55]), "+f"(d[56]), "+f"(d[57]), "+f"(d[58]), "+f"(d[59]), "+f"(d[60]), "+f"(d[61]), "+f"(d[62]), "+f"(d[63]), "+f"(d[64]), "+f"(d[65]), "+f"(d[66]), "+f"(d[67]), "+f"(d[68]), "+f"(d[69]), "+f"(d[70]), "+f"(d[71]), "+f"(d[72]), "+f"(d[73]), "+f"(d[74]), "+f"(d[75]), "+f"(d[76]), "+f"(d[77]), "+f"(d[78]), "+f"(d[79]), "+f"(d[80]), "+f"(d[81]), "+f"(d[82]), "+f"(d[83]), "+f"(d[84]), "+f"(d[85]), "+f"(d[86]), "+f"(d[87]), "+f"(d[88]), "+f"(d[89]), "+f"(d[90]), "+f"(d[91]), "+f"(d[92]), "+f"(d[93]), "+f"(d[94]), "+f"(d[95]), "+f"(d[96]), "+f"(d[97]), "+f"(d[98]), "+f"(d[99]), "+f"(d[100]), "+f"(d[101]), "+f"(d[102]), "+f"(d[103]), "+f"(d[104]), "+f"(d[105]), "+f"(d[106]), "+f"(d[107]), "+f"(d[108]), "+f"(d[109]), "+f"(d[110]), "+f"(d[111]), "+f"(d[112]), "+f"(d[113]), "+f"(d[114]), "+f"(d[115]), "+f"(d[116]), "+f"(d[117]), "+f"(d[118]), "+f"(d[119]), "+f"(d[120]), "+f"(d[121]), "+f"(d[122]), "+f"(d[123]), "+f"(d[124]), "+f"(d[125]), "+f"(d[126]), "+f"(d[127])
    : "l"(da), "l"(db), "r"(scale_d), "n"(TB));
}
template<int TB> __device__ __forceinline__ void wgmma_ss_n128(float (&d)[64], uint64_t da, uint64_t db, int scale_d) {
  asm volatile("{\n.reg .pred p;\nsetp.ne.b32 p, %66, 0;\n"
    "wgmma.mma_async.sync.aligned.m64n128k16.f32.bf16.bf16 {%0, %1, %2, %3, %4, %5, %6, %7, %8, %9, %10, %11, %12, %13, %14, %15, %16, %17, %18, %19, %20, %21, %22, %23, %24, %25, %26, %27, %28, %29, %30, %31, %32, %33, %34, %35, %36, %37, %38, %39, %40, %41, %42, %43, %44, %45, %46, %47, %48, %49, %50, %51, %52, %53, %54, %55, %56, %57, %58, %59, %60, %61, %62, %63}, %64, %65, p, 1, 1, 0, %67;\n}\n"
    : "+f"(d[0]), "+f"(d[1]), "+f"(d[2]), "+f"(d[3]), "+f"(d[4]), "+f"(d[5]), "+f"(d[6]), "+f"(d[7]), "+f"(d[8]), "+f"(d[9]), "+f"(d[10]), "+f"(d[11]), "+f"(d[12]), "+f"(d[13]), "+f"(d[14]), "+f"(d[15]), "+f"(d[16]), "+f"(d[17]), "+f"(d[18]), "+f"(d[19]), "+f"(d[20]), "+f"(d[21]), "+f"(d[22]), "+f"(d[23]), "+f"(d[24]), "+f"(d[25]), "+f"(d[26]), "+f"(d[27]), "+f"(d[28]), "+f"(d[29]), "+f"(d[30]), "+f"(d[31]), "+f"(d[32]), "+f"(d[33]), "+f"(d[34]), "+f"(d[35]), "+f"(d[36]), "+f"(d[37]), "+f"(d[38]), "+f"(d[39]), "+f"(d[40]), "+f"(d[41]), "+f"(d[42]), "+f"(d[43]), "+f"(d[44]), "+f"(d[45]), "+f"(d[46]), "+f"(d[47]), "+f"(d[48]), "+f"(d[49]), "+f"(d[50]), "+f"(d[51]), "+f"(d[52]), "+f"(d[53]), "+f"(d[54]), "+f"(d[55]), "+f"(d[56]), "+f"(d[57]), "+f"(d[58]), "+f"(d[59]), "+f"(d[60]), "+f"(d[61]), "+f"(d[62]), "+f"(d[63])
    : "l"(da), "l"(db), "r"(scale_d), "n"(TB));
}
template<int TB> __device__ __forceinline__ void wgmma_rs_n32(float (&d)[16], uint32_t a0, uint32_t a1, uint32_t a2, uint32_t a3, uint64_t db, int scale_d) {
  asm volatile("{\n.reg .pred p;\nsetp.ne.b32 p, %21, 0;\n"
    "wgmma.mma_async.sync.aligned.m64n32k16.f32.bf16.bf16 {%0, %1, %2, %3, %4, %5, %6, %7, %8, %9, %10, %11, %12, %13, %14, %15}, {%16, %17, %18, %19}, %20, p, 1, 1, %22;\n}\n"
    : "+f"(d[0]), "+f"(d[1]), "+f"(d[2]), "+f"(d[3]), "+f"(d[4]), "+f"(d[5]), "+f"(d[6]), "+f"(d[7]), "+f"(d[8]), "+f"(d[9]), "+f"(d[10]), "+f"(d[11]), "+f"(d[12]), "+f"(d[13]), "+f"(d[14]), "+f"(d[15])
    : "r"(a0), "r"(a1), "r"(a2), "r"(a3), "l"(db), "r"(scale_d), "n"(TB));
}
__device__ __forceinline__ void wgmma_pv_sel(float (&d)[64], const uint32_t (&p)[32], uint64_t db, int full, int acc, int wg) {
  asm volatile("{\n.reg .pred q, s, w;\n.reg .b64 t;\nsetp.eq.b32 w, %99, 0;\nsetp.ne.b32 s, %98, 0;\nsetp.eq.b32 q, %97, 0;\n@q bra.uni LH;\n"
    "wgmma.fence.sync.aligned;\n"
    "add.s64 t, %96, 0;\nwgmma.mma_async.sync.aligned.m64n128k16.f32.bf16.bf16 {%0, %1, %2, %3, %4, %5, %6, %7, %8, %9, %10, %11, %12, %13, %14, %15, %16, %17, %18, %19, %20, %21, %22, %23, %24, %25, %26, %27, %28, %29, %30, %31, %32, %33, %34, %35, %36, %37, %38, %39, %40, %41, %42, %43, %44, %45, %46, %47, %48, %49, %50, %51, %52, %53, %54, %55, %56, %57, %58, %59, %60, %61, %62, %63}, {%64, %65, %66, %67}, t, s, 1, 1, 1;\n"
    "add.s64 t, %96, 256;\nwgmma.mma_async.sync.aligned.m64n128k16.f32.bf16.bf16 {%0, %1, %2, %3, %4, %5, %6, %7, %8, %9, %10, %11, %12, %13, %14, %15, %16, %17, %18, %19, %20, %21, %22, %23, %24, %25, %26, %27, %28, %29, %30, %31, %32, %33, %34, %35, %36, %37, %38, %39, %40, %41, %42, %43, %44, %45, %46, %47, %48, %49, %50, %51, %52, %53, %54, %55, %56, %57, %58, %59, %60, %61, %62, %63}, {%68, %69, %70, %71}, t, 1, 1, 1, 1;\n"
    "add.s64 t, %96, 512;\nwgmma.mma_async.sync.aligned.m64n128k16.f32.bf16.bf16 {%0, %1, %2, %3, %4, %5, %6, %7, %8, %9, %10, %11, %12, %13, %14, %15, %16, %17, %18, %19, %20, %21, %22, %23, %24, %25, %26, %27, %28, %29, %30, %31, %32, %33, %34, %35, %36, %37, %38, %39, %40, %41, %42, %43, %44, %45, %46, %47, %48, %49, %50, %51, %52, %53, %54, %55, %56, %57, %58, %59, %60, %61, %62, %63}, {%72, %73, %74, %75}, t, 1, 1, 1, 1;\n"
    "add.s64 t, %96, 768;\nwgmma.mma_async.sync.aligned.m64n128k16.f32.bf16.bf16 {%0, %1, %2, %3, %4, %5, %6, %7, %8, %9, %10, %11, %12, %13, %14, %15, %16, %17, %18, %19, %20, %21, %22, %23, %24, %25, %26, %27, %28, %29, %30, %31, %32, %33, %34, %35, %36, %37, %38, %39, %40, %41, %42, %43, %44, %45, %46, %47, %48, %49, %50, %51, %52, %53, %54, %55, %56, %57, %58, %59, %60, %61, %62, %63}, {%76, %77, %78, %79}, t, 1, 1, 1, 1;\n"
    "add.s64 t, %96, 1024;\nwgmma.mma_async.sync.aligned.m64n128k16.f32.bf16.bf16 {%0, %1, %2, %3, %4, %5, %6, %7, %8, %9, %10, %11, %12, %13, %14, %15, %16, %17, %18, %19, %20, %21, %22, %23, %24, %25, %26, %27, %28, %29, %30, %31, %32, %33, %34, %35, %36, %37, %38, %39, %40, %41, %42, %43, %44, %45, %46, %47, %48, %49, %50, %51, %52, %53, %54, %55, %56, %57, %58, %59, %60, %61, %62, %63}, {%80, %81, %82, %83}, t, 1, 1, 1, 1;\n"
    "add.s64 t, %96, 1280;\nwgmma.mma_async.sync.aligned.m64n128k16.f32.bf16.bf16 {%0, %1, %2, %3, %4, %5, %6, %7, %8, %9, %10, %11, %12, %13, %14, %15, %16, %17, %18, %19, %20, %21, %22, %23, %24, %25, %26, %27, %28, %29, %30, %31, %32, %33, %34, %35, %36, %37, %38, %39, %40, %41, %42, %43, %44, %45, %46, %47, %48, %49, %50, %51, %52, %53, %54, %55, %56, %57, %58, %59, %60, %61, %62, %63}, {%84, %85, %86, %87}, t, 1, 1, 1, 1;\n"
    "@w bar.arrive 2, 256;\n@!w bar.arrive 1, 256;\n"
    "add.s64 t, %96, 1536;\nwgmma.mma_async.sync.aligned.m64n128k16.f32.bf16.bf16 {%0, %1, %2, %3, %4, %5, %6, %7, %8, %9, %10, %11, %12, %13, %14, %15, %16, %17, %18, %19, %20, %21, %22, %23, %24, %25, %26, %27, %28, %29, %30, %31, %32, %33, %34, %35, %36, %37, %38, %39, %40, %41, %42, %43, %44, %45, %46, %47, %48, %49, %50, %51, %52, %53, %54, %55, %56, %57, %58, %59, %60, %61, %62, %63}, {%88, %89, %90, %91}, t, 1, 1, 1, 1;\n"
    "add.s64 t, %96, 1792;\nwgmma.mma_async.sync.aligned.m64n128k16.f32.bf16.bf16 {%0, %1, %2, %3, %4, %5, %6, %7, %8, %9, %10, %11, %12, %13, %14, %15, %16, %17, %18, %19, %20, %21, %22, %23, %24, %25, %26, %27, %28, %29, %30, %31, %32, %33, %34, %35, %36, %37, %38, %39, %40, %41, %42, %43, %44, %45, %46, %47, %48, %49, %50, %51, %52, %53, %54, %55, %56, %57, %58, %59, %60, %61, %62, %63}, {%92, %93, %94, %95}, t, 1, 1, 1, 1;\n"
    "wgmma.commit_group.sync.aligned;\n"
    "bra.uni LE;\nLH:\n"
    "wgmma.fence.sync.aligned;\n"
    "add.s64 t, %96, 0;\nwgmma.mma_async.sync.aligned.m64n128k16.f32.bf16.bf16 {%0, %1, %2, %3, %4, %5, %6, %7, %8, %9, %10, %11, %12, %13, %14, %15, %16, %17, %18, %19, %20, %21, %22, %23, %24, %25, %26, %27, %28, %29, %30, %31, %32, %33, %34, %35, %36, %37, %38, %39, %40, %41, %42, %43, %44, %45, %46, %47, %48, %49, %50, %51, %52, %53, %54, %55, %56, %57, %58, %59, %60, %61, %62, %63}, {%80, %81, %82, %83}, t, s, 1, 1, 1;\n"
    "add.s64 t, %96, 256;\nwgmma.mma_async.sync.aligned.m64n128k16.f32.bf16.bf16 {%0, %1, %2, %3, %4, %5, %6, %7, %8, %9, %10, %11, %12, %13, %14, %15, %16, %17, %18, %19, %20, %21, %22, %23, %24, %25, %26, %27, %28, %29, %30, %31, %32, %33, %34, %35, %36, %37, %38, %39, %40, %41, %42, %43, %44, %45, %46, %47, %48, %49, %50, %51, %52, %53, %54, %55, %56, %57, %58, %59, %60, %61, %62, %63}, {%84, %85, %86, %87}, t, 1, 1, 1, 1;\n"
    "@w bar.arrive 2, 256;\n@!w bar.arrive 1, 256;\n"
    "add.s64 t, %96, 512;\nwgmma.mma_async.sync.aligned.m64n128k16.f32.bf16.bf16 {%0, %1, %2, %3, %4, %5, %6, %7, %8, %9, %10, %11, %12, %13, %14, %15, %16, %17, %18, %19, %20, %21, %22, %23, %24, %25, %26, %27, %28, %29, %30, %31, %32, %33, %34, %35, %36, %37, %38, %39, %40, %41, %42, %43, %44, %45, %46, %47, %48, %49, %50, %51, %52, %53, %54, %55, %56, %57, %58, %59, %60, %61, %62, %63}, {%88, %89, %90, %91}, t, 1, 1, 1, 1;\n"
    "add.s64 t, %96, 768;\nwgmma.mma_async.sync.aligned.m64n128k16.f32.bf16.bf16 {%0, %1, %2, %3, %4, %5, %6, %7, %8, %9, %10, %11, %12, %13, %14, %15, %16, %17, %18, %19, %20, %21, %22, %23, %24, %25, %26, %27, %28, %29, %30, %31, %32, %33, %34, %35, %36, %37, %38, %39, %40, %41, %42, %43, %44, %45, %46, %47, %48, %49, %50, %51, %52, %53, %54, %55, %56, %57, %58, %59, %60, %61, %62, %63}, {%92, %93, %94, %95}, t, 1, 1, 1, 1;\n"
    "wgmma.commit_group.sync.aligned;\n"
    "LE:\n}\n"
    : "+f"(d[0]), "+f"(d[1]), "+f"(d[2]), "+f"(d[3]), "+f"(d[4]), "+f"(d[5]), "+f"(d[6]), "+f"(d[7]), "+f"(d[8]), "+f"(d[9]), "+f"(d[10]), "+f"(d[11]), "+f"(d[12]), "+f"(d[13]), "+f"(d[14]), "+f"(d[15]), "+f"(d[16]), "+f"(d[17]), "+f"(d[18]), "+f"(d[19]), "+f"(d[20]), "+f"(d[21]), "+f"(d[22]), "+f"(d[23]), "+f"(d[24]), "+f"(d[25]), "+f"(d[26]), "+f"(d[27]), "+f"(d[28]), "+f"(d[29]), "+f"(d[30]), "+f"(d[31]), "+f"(d[32]), "+f"(d[33]), "+f"(d[34]), "+f"(d[35]), "+f"(d[36]), "+f"(d[37]), "+f"(d[38]), "+f"(d[39]), "+f"(d[40]), "+f"(d[41]), "+f"(d[42]), "+f"(d[43]), "+f"(d[44]), "+f"(d[45]), "+f"(d[46]), "+f"(d[47]), "+f"(d[48]), "+f"(d[49]), "+f"(d[50]), "+f"(d[51]), "+f"(d[52]), "+f"(d[53]), "+f"(d[54]), "+f"(d[55]), "+f"(d[56]), "+f"(d[57]), "+f"(d[58]), "+f"(d[59]), "+f"(d[60]), "+f"(d[61]), "+f"(d[62]), "+f"(d[63])
    : "r"(p[0]), "r"(p[1]), "r"(p[2]), "r"(p[3]), "r"(p[4]), "r"(p[5]), "r"(p[6]), "r"(p[7]), "r"(p[8]), "r"(p[9]), "r"(p[10]), "r"(p[11]), "r"(p[12]), "r"(p[13]), "r"(p[14]), "r"(p[15]), "r"(p[16]), "r"(p[17]), "r"(p[18]), "r"(p[19]), "r"(p[20]), "r"(p[21]), "r"(p[22]), "r"(p[23]), "r"(p[24]), "r"(p[25]), "r"(p[26]), "r"(p[27]), "r"(p[28]), "r"(p[29]), "r"(p[30]), "r"(p[31]), "l"(db), "r"(full), "r"(acc), "r"(wg) : "memory");
}

constexpr int NCTA = 132, NREG = 128;
constexpr int UNIT = 16384, NUNIT = 14;
constexpr uint32_t SMEM_BASE = 1024;
constexpr int SM_BAR = NUNIT * UNIT;
constexpr int SM_GATE = SM_BAR + 1024;
constexpr int SMEM_BYTES = SM_BAR + 1536;
constexpr int UPITCH = 4160, UCH = 2 * UPITCH;
constexpr float QSCALE = 0.08838834764831845f * 1.4426950408889634f;
constexpr float BOUND2 = 60.f * 60.f / 1.15f;
#define NSKIP 8
constexpr int C_KV = 0;
constexpr int C_CTX = 32;
constexpr int C_U = 48;
constexpr int C_Z = 80;
constexpr int C_GATE = 88;
constexpr int C_EXIT = 89, C_TICKET = 90;
#define ATT_SPLIT 4
#define SL_BAR 256
#define SL_CNT 0
#define PF_WAIT 6
#define PF_GAP 300
#define Z_AT 60
#define PRE_SLEEP 300
#define GATE_SLEEP 1000
#define OC_S0 2
#define OC_S1 11
#define OC_L0 18
#define OC_L1 18
#define ST_1 4
#define ST_D 2
#define SCH_KV 0x7766555443322100ull
#define SCH_Q 0x7766555443322100ull
#define NK_AT 1
#define NV_AT 3
#define CHK_D 11
#define FGAP 600
#define FGAP2 200
constexpr int PRE_EARLY = 2, NFIRST = 4;
constexpr int C_WAR = 96;
constexpr int C_NUM = 112;
constexpr int CSTRIDE = 32;
constexpr int SM_KMAX = SM_BAR + 640, SM_DUMMY = SM_BAR + 648, SM_POOL = SM_BAR + 652, SM_PRE = SM_BAR + 112, SM_SIG = SM_BAR + 256, SM_RDY = SM_BAR + 384;
enum { SIG_KV = 0, SIG_CTX = 2, SIG_Z = 4, SIG_DONE = 8, SIG_WAR = 9, SIG_ATT = 10 };
enum { RDY_KV = 0, RDY_CTX = 2, RDY_WAR = 4, RDY_G = 5, RDY_X = 6, RDY_AUX = 7, RDY_U = 8, RDY_Z = 9, RDY_T = 10, RDY_NONE = 11 };
enum { PH_PRE = 1, PH_KV = 2, PH_ATT = 4, PH_CONV = 8, PH_OUT = 16, PH_ALL = 31 };

constexpr uint32_t T_CTX = 0, T_KV = 16 * 32 * 32768, T_BYTES = T_KV + 32 * 16 * 65536;
__device__ __align__(1024) uint8_t g_T[T_BYTES];
__device__ __align__(1024) uint8_t g_u[1024 * UCH];
__device__ __align__(1024) float g_gate[2048];
__device__ __align__(1024) float g_kn2[32 * 128];
__device__ __align__(1024) unsigned g_cnt[C_NUM * CSTRIDE];

struct __align__(64) Maps { CUtensorMap c, wk, wv, x, wq, wo, h, z, ctx, k, v; };
struct Params {
  const __nv_bfloat16 *x, *shift, *D, *gw, *wk, *wv, *c;
  __nv_bfloat16* out;
};

__device__ __forceinline__ void wg_fence() { asm volatile("wgmma.fence.sync.aligned;" ::: "memory"); }
__device__ __forceinline__ void wg_commit() { asm volatile("wgmma.commit_group.sync.aligned;" ::: "memory"); }
template<int N> __device__ __forceinline__ void wg_wait() { asm volatile("wgmma.wait_group.sync.aligned %0;" :: "n"(N) : "memory"); }
__device__ __forceinline__ uint64_t odesc(uint32_t addr, uint32_t lbo, uint32_t sbo, uint32_t swz) {
  uint64_t d = (uint64_t)(addr >> 4) + (((uint64_t)(lbo >> 4) << 16) | ((uint64_t)(sbo >> 4) << 32) | ((uint64_t)swz << 62));
  asm volatile("" : "+l"(d));
  return d;
}
__device__ __forceinline__ void mbar_init(uint32_t bar, int cnt) { asm volatile("mbarrier.init.shared::cta.b64 [%0], %1;" :: "r"(bar), "r"(cnt)); }
__device__ __forceinline__ void mbar_expect(uint32_t bar, uint32_t bytes) { asm volatile("mbarrier.arrive.expect_tx.shared::cta.b64 _, [%0], %1;" :: "r"(bar), "r"(bytes) : "memory"); }
__device__ __forceinline__ void mbar_arrive(uint32_t bar) { asm volatile("mbarrier.arrive.shared::cta.b64 _, [%0];" :: "r"(bar) : "memory"); }
__device__ __forceinline__ void mbar_wait(uint32_t bar, uint32_t parity) {
  asm volatile("{\n.reg .pred p;\nLW:\nmbarrier.try_wait.parity.shared::cta.b64 p, [%0], %1;\n@!p bra LW;\n}\n" :: "r"(bar), "r"(parity) : "memory");
}
__device__ __forceinline__ void mbar_wait_slow(uint32_t bar, uint32_t parity) {
  asm volatile("{\n.reg .pred p;\n.reg .u32 n;\nmov.u32 n, 0;\n"
    "LW:\nmbarrier.test_wait.parity.shared::cta.b64 p, [%0], %1;\n@p bra LD;\n"
    "nanosleep.u32 %2;\nadd.u32 n, n, 1;\nsetp.lt.u32 p, n, 16777216;\n@p bra LW;\ntrap;\nLD:\n}\n" :: "r"(bar), "r"(parity), "n"(SL_BAR) : "memory");
}
__device__ __forceinline__ void mbar_wait_all(uint32_t bar, uint32_t parity) {
  asm volatile("{\n.reg .pred p, q;\nLW:\nmbarrier.try_wait.parity.shared::cta.b64 p, [%0], %1;\nvote.sync.all.pred q, p, 0xffffffff;\n@!q bra.uni LW;\n}\n" :: "r"(bar), "r"(parity) : "memory");
}
__device__ __forceinline__ void cnt_wait(const unsigned* p, unsigned target) {
  asm volatile("{\n.reg .pred p;\n.reg .u32 n, v;\nmov.u32 n, 0;\n"
    "LW:\nld.relaxed.gpu.global.u32 v, [%0];\nsetp.ge.u32 p, v, %1;\n@p bra LD;\n"
    "nanosleep.u32 %2;\nadd.u32 n, n, 1;\nsetp.lt.u32 p, n, 4194304;\n@p bra LW;\ntrap;\nLD:\nfence.acquire.gpu;\nfence.proxy.async.global;\n}\n" :: "l"(p), "r"(target), "n"(SL_CNT) : "memory");
}
__device__ __forceinline__ void cnt_signal(unsigned* p, int lane) {
  __syncwarp();
  if (lane == 0) asm volatile("red.release.gpu.global.add.u32 [%0], 1;" :: "l"(p) : "memory");
}
__device__ __forceinline__ void cnt_publish(unsigned* p, unsigned n, bool fence) {
  if (fence) asm volatile("fence.release.gpu;" ::: "memory");
  asm volatile("red.relaxed.gpu.global.add.u32 [%0], %1;" :: "l"(p), "r"(n) : "memory");
}
__device__ __forceinline__ uint64_t pol_first() { uint64_t p; asm("createpolicy.fractional.L2::evict_first.b64 %0, 1.0;" : "=l"(p)); return p; }
__device__ __forceinline__ void bulk_g2s(uint32_t dst, const void* src, uint32_t bytes, uint32_t bar, bool stream = false) {
  if (stream) asm volatile("cp.async.bulk.shared::cluster.global.mbarrier::complete_tx::bytes.L2::cache_hint [%0], [%1], %2, [%3], %4;" :: "r"(dst), "l"(src), "r"(bytes), "r"(bar), "l"(pol_first()) : "memory");
  else asm volatile("cp.async.bulk.shared::cluster.global.mbarrier::complete_tx::bytes [%0], [%1], %2, [%3];" :: "r"(dst), "l"(src), "r"(bytes), "r"(bar) : "memory");
}
__device__ __forceinline__ void tma2d(uint32_t dst, const CUtensorMap* m, int x, int y, uint32_t bar, bool stream = false) {
  if (stream) asm volatile("cp.async.bulk.tensor.2d.shared::cluster.global.mbarrier::complete_tx::bytes.L2::cache_hint [%0], [%1, {%3, %4}], [%2], %5;" :: "r"(dst), "l"(m), "r"(bar), "r"(x), "r"(y), "l"(pol_first()) : "memory");
  else asm volatile("cp.async.bulk.tensor.2d.shared::cluster.global.mbarrier::complete_tx::bytes [%0], [%1, {%3, %4}], [%2];" :: "r"(dst), "l"(m), "r"(bar), "r"(x), "r"(y) : "memory");
}
__device__ __forceinline__ void tma3d(uint32_t dst, const CUtensorMap* m, int x, int y, int z, uint32_t bar, bool stream = false) {
  if (stream) asm volatile("cp.async.bulk.tensor.3d.shared::cluster.global.mbarrier::complete_tx::bytes.L2::cache_hint [%0], [%1, {%3, %4, %5}], [%2], %6;" :: "r"(dst), "l"(m), "r"(bar), "r"(x), "r"(y), "r"(z), "l"(pol_first()) : "memory");
  else asm volatile("cp.async.bulk.tensor.3d.shared::cluster.global.mbarrier::complete_tx::bytes [%0], [%1, {%3, %4, %5}], [%2];" :: "r"(dst), "l"(m), "r"(bar), "r"(x), "r"(y), "r"(z) : "memory");
}
__device__ __forceinline__ void tma4d(uint32_t dst, const CUtensorMap* m, int x, int y, int z, int w, uint32_t bar, bool stream = false) {
  if (stream) asm volatile("cp.async.bulk.tensor.4d.shared::cluster.global.mbarrier::complete_tx::bytes.L2::cache_hint [%0], [%1, {%3, %4, %5, %6}], [%2], %7;" :: "r"(dst), "l"(m), "r"(bar), "r"(x), "r"(y), "r"(z), "r"(w), "l"(pol_first()) : "memory");
  else asm volatile("cp.async.bulk.tensor.4d.shared::cluster.global.mbarrier::complete_tx::bytes [%0], [%1, {%3, %4, %5, %6}], [%2];" :: "r"(dst), "l"(m), "r"(bar), "r"(x), "r"(y), "r"(z), "r"(w) : "memory");
}
__device__ __forceinline__ void bulk_g2s_mc(uint32_t dst, const void* src, uint32_t bytes, uint32_t bar, bool stream = false) {
  if (stream) asm volatile("cp.async.bulk.shared::cluster.global.mbarrier::complete_tx::bytes.multicast::cluster.L2::cache_hint [%0], [%1], %2, [%3], %4, %5;" :: "r"(dst), "l"(src), "r"(bytes), "r"(bar), "h"((uint16_t)3), "l"(pol_first()) : "memory");
  else asm volatile("cp.async.bulk.shared::cluster.global.mbarrier::complete_tx::bytes.multicast::cluster [%0], [%1], %2, [%3], %4;" :: "r"(dst), "l"(src), "r"(bytes), "r"(bar), "h"((uint16_t)3) : "memory");
}
__device__ __forceinline__ void tma2d_mc(uint32_t dst, const CUtensorMap* m, int x, int y, uint32_t bar, bool stream = false) {
  if (stream) asm volatile("cp.async.bulk.tensor.2d.shared::cluster.global.mbarrier::complete_tx::bytes.multicast::cluster.L2::cache_hint [%0], [%1, {%3, %4}], [%2], %5, %6;" :: "r"(dst), "l"(m), "r"(bar), "r"(x), "r"(y), "h"((uint16_t)3), "l"(pol_first()) : "memory");
  else asm volatile("cp.async.bulk.tensor.2d.shared::cluster.global.mbarrier::complete_tx::bytes.multicast::cluster [%0], [%1, {%3, %4}], [%2], %5;" :: "r"(dst), "l"(m), "r"(bar), "r"(x), "r"(y), "h"((uint16_t)3) : "memory");
}
__device__ __forceinline__ void tma3d_mc(uint32_t dst, const CUtensorMap* m, int x, int y, int z, uint32_t bar, bool stream = false) {
  if (stream) asm volatile("cp.async.bulk.tensor.3d.shared::cluster.global.mbarrier::complete_tx::bytes.multicast::cluster.L2::cache_hint [%0], [%1, {%3, %4, %5}], [%2], %6, %7;" :: "r"(dst), "l"(m), "r"(bar), "r"(x), "r"(y), "r"(z), "h"((uint16_t)3), "l"(pol_first()) : "memory");
  else asm volatile("cp.async.bulk.tensor.3d.shared::cluster.global.mbarrier::complete_tx::bytes.multicast::cluster [%0], [%1, {%3, %4, %5}], [%2], %6;" :: "r"(dst), "l"(m), "r"(bar), "r"(x), "r"(y), "r"(z), "h"((uint16_t)3) : "memory");
}
__device__ __forceinline__ void map_pf(const CUtensorMap* m) { asm volatile("prefetch.tensormap [%0];" :: "l"(m) : "memory"); }
__device__ __forceinline__ bool elect() {
  uint32_t r; asm volatile("{\n.reg .pred p;\nelect.sync _|p, 0xffffffff;\nselp.u32 %0, 1, 0, p;\n}\n" : "=r"(r)); return r != 0;
}
__device__ __forceinline__ void cluster_arrive() { asm volatile("barrier.cluster.arrive;" ::: "memory"); }
__device__ __forceinline__ void cluster_wait() { asm volatile("barrier.cluster.wait;" ::: "memory"); }
__device__ __forceinline__ void bar_sync(int id, int n) { asm volatile("bar.sync %0, %1;" :: "r"(id), "r"(n) : "memory"); }
__device__ __forceinline__ void bar_arrive(int id, int n) { asm volatile("bar.arrive %0, %1;" :: "r"(id), "r"(n) : "memory"); }
__device__ __forceinline__ void fence_async_smem() { asm volatile("fence.proxy.async.shared::cta;" ::: "memory"); }
__device__ __forceinline__ float ex2(float x) { float y; asm("ex2.approx.ftz.f32 %0, %1;" : "=f"(y) : "f"(x)); return y; }
__device__ __forceinline__ float rcp(float x) { float y; asm("rcp.approx.ftz.f32 %0, %1;" : "=f"(y) : "f"(x)); return y; }
__device__ __forceinline__ uint32_t pack_bf16(float lo, float hi) { uint32_t r; asm("cvt.rn.bf16x2.f32 %0, %1, %2;" : "=r"(r) : "f"(hi), "f"(lo)); return r; }
__device__ __forceinline__ uint32_t hmul2(uint32_t a, uint32_t b) { uint32_t r; asm("mul.rn.bf16x2 %0, %1, %2;" : "=r"(r) : "r"(a), "r"(b)); return r; }
__device__ __forceinline__ uint32_t hadd2(uint32_t a, uint32_t b) { uint32_t r; asm("add.rn.bf16x2 %0, %1, %2;" : "=r"(r) : "r"(a), "r"(b)); return r; }
__device__ __forceinline__ uint32_t hfma2(uint32_t a, uint32_t b, uint32_t c) { uint32_t r; asm("fma.rn.bf16x2 %0, %1, %2, %3;" : "=r"(r) : "r"(a), "r"(b), "r"(c)); return r; }
__device__ __forceinline__ float bf_lo(uint32_t a) { return __uint_as_float(a << 16); }
__device__ __forceinline__ float bf_hi(uint32_t a) { return __uint_as_float(a & 0xffff0000u); }
__device__ __forceinline__ uint32_t lds32(uint32_t a) { uint32_t v; asm volatile("ld.shared.u32 %0, [%1];" : "=r"(v) : "r"(a) : "memory"); return v; }
__device__ __forceinline__ uint4 lds128(uint32_t a) { uint4 v; asm volatile("ld.shared.v4.u32 {%0,%1,%2,%3}, [%4];" : "=r"(v.x), "=r"(v.y), "=r"(v.z), "=r"(v.w) : "r"(a) : "memory"); return v; }
__device__ __forceinline__ void sts64f(uint32_t a, float x, float y) { asm volatile("st.shared.v2.f32 [%0], {%1,%2};" :: "r"(a), "f"(x), "f"(y) : "memory"); }
template<int OFF> __device__ __forceinline__ void sts128o(uint32_t a, uint4 v) { asm volatile("st.shared.v4.u32 [%0+%5], {%1,%2,%3,%4};" :: "r"(a), "r"(v.x), "r"(v.y), "r"(v.z), "r"(v.w), "n"(OFF) : "memory"); }
__device__ __forceinline__ void ldsm4(uint32_t a, uint32_t& r0, uint32_t& r1, uint32_t& r2, uint32_t& r3) {
  asm volatile("ldmatrix.sync.aligned.m8n8.x4.shared.b16 {%0,%1,%2,%3}, [%4];" : "=r"(r0), "=r"(r1), "=r"(r2), "=r"(r3) : "r"(a) : "memory");
}
__device__ __forceinline__ void ldsm4t(uint32_t a, uint32_t& r0, uint32_t& r1, uint32_t& r2, uint32_t& r3) {
  asm volatile("ldmatrix.sync.aligned.m8n8.x4.trans.shared.b16 {%0,%1,%2,%3}, [%4];" : "=r"(r0), "=r"(r1), "=r"(r2), "=r"(r3) : "r"(a) : "memory");
}
__device__ __forceinline__ void stsm4(uint32_t a, uint32_t r0, uint32_t r1, uint32_t r2, uint32_t r3) {
  asm volatile("stmatrix.sync.aligned.m8n8.x4.shared.b16 [%0], {%1,%2,%3,%4};" :: "r"(a), "r"(r0), "r"(r1), "r"(r2), "r"(r3) : "memory");
}
template<int N> __device__ __forceinline__ void fence_regs(float (&d)[N]) {
#pragma unroll
  for (int i = 0; i < N; i++) asm volatile("" : "+f"(d[i]) :: "memory");
}
template<int N> __device__ __forceinline__ void fence_regs(uint32_t (&d)[N]) {
#pragma unroll
  for (int i = 0; i < N; i++) asm volatile("" : "+r"(d[i]) :: "memory");
}
__device__ __forceinline__ void sched_fence(float x, uint32_t dummy) {
  asm volatile("{\n.reg .pred p;\nsetp.eq.u32 p, %0, 0x7fc12345;\n@p st.shared.u32 [%1], %0;\n}\n" :: "r"(__float_as_uint(x)), "r"(dummy) : "memory");
}

#define SHADOW if (gridDim.y == 1)

struct Prod {
  uint32_t base, mask; int lane;
  __device__ __forceinline__ uint32_t full(int u) const { return base + SM_BAR + 8 * u; }
  __device__ __forceinline__ uint32_t addr(int u) const { return base + u * UNIT; }
  __device__ __forceinline__ void acquire(int u, int n) {
    const int v = u + min(lane, n - 1);
    mbar_wait_all(base + SM_BAR + 128 + 8 * v, mask >> v);
    mask ^= ((1u << n) - 1) << u;
  }
  __device__ __forceinline__ void acquire_slow(int u, int n) {
    for (int i = 0; i < n; i++) mbar_wait_slow(base + SM_BAR + 128 + 8 * (u + i), mask >> (u + i));
    mask ^= ((1u << n) - 1) << u;
  }
};
struct Cons {
  uint32_t base, rel, mask; int lane, warp, wg, lr;
  __device__ __forceinline__ uint32_t addr(int u) const { return base + u * UNIT; }
  __device__ __forceinline__ static uint32_t daddr(int u) { return SMEM_BASE + u * UNIT; }
  __device__ __forceinline__ void wait(int u) { mbar_wait(base + SM_BAR + 8 * u, mask >> u); mask ^= 1u << u; }
  __device__ __forceinline__ void skip(int u) { mask ^= 1u << u; }
  __device__ __forceinline__ void release(int u, int n) {
    asm volatile("{\n.reg .pred p;\nsetp.lt.s32 p, %1, %2;\n@p mbarrier.arrive.shared::cluster.b64 _, [%0];\n}\n" :: "r"(rel + 8 * u), "r"(lr), "r"(n) : "memory");
  }
  __device__ __forceinline__ void release2(int u) {
    asm volatile("{\n.reg .pred p;\nsetp.eq.s32 p, %1, 0;\n@p mbarrier.arrive.shared::cluster.b64 _, [%0], 2;\n}\n" :: "r"(rel + 8 * u), "r"(lr) : "memory");
  }
  __device__ __forceinline__ void signal(int i) {
    __syncwarp();
    asm volatile("{\n.reg .pred p;\nsetp.eq.s32 p, %1, 0;\n@p mbarrier.arrive.shared::cta.b64 _, [%0];\n}\n" :: "r"(base + SM_SIG + 8 * i), "r"(lane) : "memory");
  }
  __device__ __forceinline__ void turn() { asm volatile("{\n.reg .pred p;\nsetp.eq.s32 p, %0, 0;\n@p bar.sync 1, 256;\n@!p bar.sync 2, 256;\n}\n" :: "r"(wg) : "memory"); }
  __device__ __forceinline__ void pass() { asm volatile("{\n.reg .pred p;\nsetp.eq.s32 p, %0, 0;\n@p bar.arrive 2, 256;\n@!p bar.arrive 1, 256;\n}\n" :: "r"(wg) : "memory"); }
  __device__ __forceinline__ void sync() { asm volatile("{\n.reg .pred p;\nsetp.eq.s32 p, %0, 0;\n@p bar.sync 3, 128;\n@!p bar.sync 4, 128;\n}\n" :: "r"(wg) : "memory"); }
};
__device__ __forceinline__ int gemm_unit(int ks) { return 3 * (ks & 3); }
template<int MASK> __device__ __forceinline__ int kv_slot(int h) { return MASK == PH_ALL ? h & 15 : h; }
__device__ __forceinline__ int out_mb(int cta) { return cta >> 3; }
__device__ __forceinline__ int out_nb(int cta) { return cta & 7; }
template<int MASK> constexpr int CV_REG = MASK == PH_ALL ? 4 : 6;
template<int MASK> constexpr int CV_EXTRA = MASK == PH_ALL ? 96 + NSKIP / 2 : 64;
constexpr int CV_POOL = 896 + 2 * NSKIP;
template<int MASK> __device__ __forceinline__ int conv_channel(int cta, int i) {
  return cta < NREG ? CV_EXTRA<MASK> * (NCTA - NREG) + cta * CV_REG<MASK> + i : (i >> 1) * 8 + (cta - NREG) * 2 + (i & 1);
}

template<int OFF, int N> __device__ __forceinline__ void pack_chunk(const float (&a)[N], float sc0, float sc1, uint4& v0, uint4& v1) {
  v0.x = pack_bf16(a[OFF + 0] * sc0, a[OFF + 1] * sc0); v0.y = pack_bf16(a[OFF + 4] * sc0, a[OFF + 5] * sc0);
  v0.z = pack_bf16(a[OFF + 8] * sc0, a[OFF + 9] * sc0); v0.w = pack_bf16(a[OFF + 12] * sc0, a[OFF + 13] * sc0);
  v1.x = pack_bf16(a[OFF + 2] * sc1, a[OFF + 3] * sc1); v1.y = pack_bf16(a[OFF + 6] * sc1, a[OFF + 7] * sc1);
  v1.z = pack_bf16(a[OFF + 10] * sc1, a[OFF + 11] * sc1); v1.w = pack_bf16(a[OFF + 14] * sc1, a[OFF + 15] * sc1);
}
template<int OFF, int N> __device__ __forceinline__ void pack_chunk(const float (&a)[N], uint4& v0, uint4& v1) {
  v0.x = pack_bf16(a[OFF + 0], a[OFF + 1]); v0.y = pack_bf16(a[OFF + 4], a[OFF + 5]);
  v0.z = pack_bf16(a[OFF + 8], a[OFF + 9]); v0.w = pack_bf16(a[OFF + 12], a[OFF + 13]);
  v1.x = pack_bf16(a[OFF + 2], a[OFF + 3]); v1.y = pack_bf16(a[OFF + 6], a[OFF + 7]);
  v1.z = pack_bf16(a[OFF + 10], a[OFF + 11]); v1.w = pack_bf16(a[OFF + 14], a[OFF + 15]);
}
__device__ __forceinline__ void sq_acc(const uint4& v, uint32_t& a) { a = hfma2(v.x, v.x, a); a = hfma2(v.y, v.y, a); a = hfma2(v.z, v.z, a); a = hfma2(v.w, v.w, a); }
template<bool ROWS> __device__ __forceinline__ float norm2_max(uint32_t a0, uint32_t a1) {
  float n0 = bf_lo(a0) + bf_hi(a0), n1 = bf_lo(a1) + bf_hi(a1);
  if (ROWS) {
    n0 += __shfl_xor_sync(~0u, n0, 1); n1 += __shfl_xor_sync(~0u, n1, 1);
    n0 += __shfl_xor_sync(~0u, n0, 2); n1 += __shfl_xor_sync(~0u, n1, 2);
  }
  return __uint_as_float(__reduce_max_sync(~0u, max(__float_as_uint(n0) & 0x7fffffffu, __float_as_uint(n1) & 0x7fffffffu)));
}

struct Pend { uint4 lo[8], hi[8]; };
__device__ __forceinline__ uint32_t ctx_off(const Cons& c, int h, int qb, int rowhalf) { return T_CTX + (qb * 32 + h) * 32768 + (rowhalf * 4 + c.warp) * 4096; }
__device__ __forceinline__ uint32_t kv_off(const Cons& c, int blk) { return T_KV + blk * 65536 + (c.wg * 4 + c.warp) * 4096; }
__device__ __forceinline__ void pin(uint4 (&v)[8]) {
#pragma unroll
  for (int i = 0; i < 8; i++) asm volatile("" : "+r"(v[i].x), "+r"(v[i].y), "+r"(v[i].z), "+r"(v[i].w) :: "memory");
}
__device__ __forceinline__ void pack_o(const float (&o)[64], float i0, float i1, uint4 (&v)[8]) {
  pack_chunk<0>(o, i0, i1, v[0], v[1]); pack_chunk<16>(o, i0, i1, v[2], v[3]);
  pack_chunk<32>(o, i0, i1, v[4], v[5]); pack_chunk<48>(o, i0, i1, v[6], v[7]);
  pin(v);
}
__device__ __forceinline__ uint32_t atom_off(int lane) { return (lane >> 2) * 64 + (((lane ^ (lane >> 3)) & 3) << 4); }
template<int J0, int J1> __device__ __forceinline__ void tile_store(const uint4 (&v)[8], uint32_t dst, int lane) {
  uint8_t* d = g_T + (dst + atom_off(lane));
#pragma unroll
  for (int j = J0; j < J1; j++) { *(uint4*)(d + j * 512) = v[2 * j]; *(uint4*)(d + j * 512 + 2048) = v[2 * j + 1]; }
}
template<int I0, int I1> __device__ __forceinline__ void tile_store_if(bool on, const uint4 (&v)[8], const uint8_t* dst) {
  if constexpr (I0 < I1) {
    asm volatile("{\n.reg .pred p;\nsetp.ne.b32 p, %5, 0;\n@p st.v4.u32 [%0+%6], {%1,%2,%3,%4};\n}\n"
      :: "l"(dst), "r"(v[I0].x), "r"(v[I0].y), "r"(v[I0].z), "r"(v[I0].w), "r"((int)on), "n"((I0 >> 1) * 512 + (I0 & 1) * 2048) : "memory");
    tile_store_if<I0 + 1, I1>(on, v, dst);
  }
}
template<bool ROWS> __device__ __forceinline__ float tile_norm2(const uint4 (&v)[8]) {
  uint32_t n0 = 0, n1 = 0, n2 = 0, n3 = 0;
#pragma unroll
  for (int j = 0; j < 2; j++) { sq_acc(v[2 * j], n0); sq_acc(v[2 * j + 1], n1); sq_acc(v[2 * j + 4], n2); sq_acc(v[2 * j + 5], n3); }
  return norm2_max<ROWS>(hadd2(n0, n2), hadd2(n1, n3));
}
template<uint64_t SCHED, bool FIRST> __device__ __forceinline__ void out_piece(Cons& c, Pend& w, uint32_t dst, int blk, float& kn, int ks, bool both) {
  uint8_t* d = g_T + (dst + atom_off(c.lane));
#pragma unroll
  for (int i = 0; i < 16; i++) {
    const int at = (SCHED >> (4 * i)) & 15;
    if (FIRST ? at == 0 : (at > 0 && ks == at && (i < 8 || both))) *(uint4*)(d + (i >> 3) * 32768 + ((i >> 1) & 3) * 512 + (i & 1) * 2048) = i < 8 ? w.lo[i & 7] : w.hi[i & 7];
  }
  if (FIRST || !both) return;
  if (ks == NK_AT) kn = tile_norm2<true>(w.lo);
  if (ks == NV_AT) {
    const float vn = tile_norm2<false>(w.hi);
    if (c.lane == 0) g_kn2[blk * 8 + c.wg * 4 + c.warp] = (vn <= 1.0e20f && vn >= 1.0e-20f) ? kn : __uint_as_float(0x7f800000u);
  }
}
template<bool FIRST> __device__ __forceinline__ void kv_issue(Cons& c, float (&acc)[128], int ua, int ub) {
  const uint64_t da = odesc(c.daddr(ua) + c.wg * 8192, 16, 1024, 1), db = odesc(c.daddr(ub), 8192, 1024, 1);
  c.turn();
  wg_fence();
#pragma unroll
  for (int kk = 0; kk < 4; kk++) wgmma_ss_n256<1>(acc, da + kk * 2, db + kk * 128, !(FIRST && kk == 0));
  wg_commit();
  c.pass();
}
template<bool NEXT> __device__ __forceinline__ void cons_kv(Cons& c, int h, int blk, int g, Pend& w, bool pend_o) {
#pragma unroll 1
  for (int tile = 0; tile < 2; tile++) {
    float acc[128];
    if (tile == 0) c.wait(0);
    const bool early = pend_o && tile == 0;
    kv_issue<true>(c, acc, early ? 12 : 0, early ? 0 : 1);
    c.release(9, tile == 1 ? 3 : 0);
    if (tile == 1 && pend_o) mbar_wait(c.base + SM_RDY + 8 * RDY_WAR, 0);
    const uint32_t dst = tile ? kv_off(c, blk) : ctx_off(c, h - 16, g, 1 - c.wg);
    float kn = 0.f;
    if (tile == 1 || pend_o) out_piece<SCH_KV, true>(c, w, dst, blk, kn, 0, false);
#pragma unroll 1
    for (int ks = 1; ks < 8; ks++) {
      const int u = gemm_unit(ks);
      c.wait(u);
      wg_wait<0>();
      c.release(gemm_unit(ks - 1), early && ks == 1 ? 2 : 3);
      kv_issue<false>(c, acc, u, u + 1);
      if (tile == 1 || pend_o) { out_piece<SCH_KV, false>(c, w, dst, blk, kn, ks, tile); if (ks == ((SCH_KV >> 28) & 15) && tile == 0) c.signal(SIG_CTX); }
    }
    if (NEXT || tile == 0) c.wait(0);
    wg_wait<0>(); fence_regs(acc);
    if (!NEXT) c.release(9, tile == 1 ? 3 : 0);
    pack_chunk<0>(acc, w.lo[0], w.lo[1]);  pack_chunk<16>(acc, w.lo[2], w.lo[3]); pack_chunk<32>(acc, w.lo[4], w.lo[5]); pack_chunk<48>(acc, w.lo[6], w.lo[7]);
    pack_chunk<64>(acc, w.hi[0], w.hi[1]); pack_chunk<80>(acc, w.hi[2], w.hi[3]); pack_chunk<96>(acc, w.hi[4], w.hi[5]); pack_chunk<112>(acc, w.hi[6], w.hi[7]);
    pin(w.lo); pin(w.hi);
  }
}
template<bool FIRST> __device__ __forceinline__ void q_issue(Cons& c, float (&a)[64], float (&b)[64], int u) {
  const uint64_t da = odesc(c.daddr(u) + c.wg * 8192, 16, 1024, 1), db = odesc(c.daddr(u + 2), 8192, 1024, 1);
  const uint64_t da2 = odesc(c.daddr(u + 1) + (1 - c.wg) * 8192, 16, 1024, 1);
  c.turn();
  wg_fence();
#pragma unroll
  for (int kk = 0; kk < 4; kk++) wgmma_ss_n128<1>(a, da + kk * 2, db + kk * 128, !(FIRST && kk == 0));
#pragma unroll
  for (int kk = 0; kk < 4; kk++) wgmma_ss_n128<1>(b, da2 + kk * 2, db + kk * 128, !(FIRST && kk == 0));
  wg_commit();
  c.pass();
}
__device__ __forceinline__ void q_step(Cons& c, float (&d)[64], int ua, int ub, int rowhalf) {
  const uint64_t da = odesc(c.daddr(ua) + rowhalf * 8192, 16, 1024, 1), db = odesc(c.daddr(ub), 8192, 1024, 1);
#pragma unroll
  for (int kk = 0; kk < 4; kk++) wgmma_ss_n128<1>(d, da + kk * 2, db + kk * 128, 1);
}
template<bool PEND_KV> __device__ __forceinline__ void cons_q(Cons& c, int h, int blk, Pend& w, float (&b)[64], float& kmax) {
  float a[64], kn = 0.f;
  if (!PEND_KV) c.wait(0);
  q_issue<true>(c, a, b, 0);
  if (PEND_KV) { c.release(9, 3); out_piece<SCH_Q, true>(c, w, kv_off(c, blk), blk, kn, 0, true); }
#pragma unroll 1
  for (int ks = 1; ks < 14; ks++) {
    const int u = gemm_unit(ks);
    c.wait(u);
    wg_wait<0>();
    c.release(gemm_unit(ks - 1), 3);
    q_issue<false>(c, a, b, u);
    if (PEND_KV && ks <= (int)(SCH_Q >> 60)) { out_piece<SCH_Q, false>(c, w, kv_off(c, blk), blk, kn, ks, true); if (ks == (int)(SCH_Q >> 60)) c.signal(SIG_KV + (h >> 4)); }
  }
  c.wait(6); c.wait(9);
  wg_wait<0>();
  c.release(3, 3);
  c.turn();
  wg_fence();
  q_step(c, a, 6, 8, c.wg); q_step(c, a, 9, 11, c.wg); wg_commit();
  q_step(c, b, 7, 8, 1 - c.wg); wg_commit();
  c.pass();
  c.wait(0);
  kmax = __uint_as_float(lds32(c.base + SM_KMAX + 4 * (h >> 4)));
  c.wait(12);
  const uint32_t q0 = c.addr(0) + (c.wg * 4 + c.warp) * 4096 + atom_off(c.lane);
  wg_wait<1>(); fence_regs(a);
  pack_o(a, QSCALE, QSCALE, w.lo);
  sts128o<0>(q0, w.lo[0]);    sts128o<2048>(q0, w.lo[1]); sts128o<512>(q0, w.lo[2]);  sts128o<2560>(q0, w.lo[3]);
  wg_wait<0>();
  c.release(6, 4);
  sts128o<1024>(q0, w.lo[4]); sts128o<3072>(q0, w.lo[5]); sts128o<1536>(q0, w.lo[6]); sts128o<3584>(q0, w.lo[7]);
  fence_async_smem();
}

__device__ __forceinline__ void issue_qk(float (&s)[64], uint64_t da, uint64_t db) {
#pragma unroll
  for (int kk = 0; kk < 8; kk++) wgmma_ss_n128<0>(s, da + (kk >> 1) * 32 + (kk & 1) * 2, db + (kk >> 1) * 32 + (kk & 1) * 2, kk > 0);
  wg_commit();
}
template<int A, int B> __device__ __forceinline__ void exp_rng(float (&s)[64]) {
#pragma unroll
  for (int i = 4 * A; i < 4 * B; i++) s[i] = ex2(s[i]);
}
template<int A, int B> __device__ __forceinline__ void sum_rng(const float (&s)[64], float (&l)[4]) {
#pragma unroll
  for (int i = A; i < B; i++) { l[0] += s[4 * i]; l[1] += s[4 * i + 1]; l[2] += s[4 * i + 2]; l[3] += s[4 * i + 3]; }
}
template<int A, int B> __device__ __forceinline__ void cvt_p(const float (&s)[64], uint32_t (&p)[32]) {
#pragma unroll
  for (int i = 2 * A; i < 2 * B; i++) p[i] = pack_bf16(s[2 * i], s[2 * i + 1]);
}
template<int K0> __device__ __forceinline__ void mask_half(float (&s)[64], int warp, int lane) {
  const int l0 = warp + (2 * (lane & 3) <= (lane >> 2)), l1 = warp + (2 * (lane & 3) < (lane >> 2));
#pragma unroll
  for (int k = 0; k < 4; k++) {
    float* t = s + 8 * (K0 + k);
    if (k >= l0) { t[0] = -INFINITY; t[6] = -INFINITY; }
    if (k >= l1) { t[1] = -INFINITY; t[7] = -INFINITY; }
    if (k > warp) { t[2] = -INFINITY; t[3] = -INFINITY; }
    if (k >= warp) { t[4] = -INFINITY; t[5] = -INFINITY; }
  }
}
__device__ __forceinline__ void row_inv(float& l0, float& l1) {
  l0 += __shfl_xor_sync(~0u, l0, 1); l1 += __shfl_xor_sync(~0u, l1, 1);
  l0 += __shfl_xor_sync(~0u, l0, 2); l1 += __shfl_xor_sync(~0u, l1, 2);
  l0 = rcp(l0); l1 = rcp(l1);
}
__device__ __forceinline__ void softmax_safe(float (&s)[64], bool upper_only, float& m0, float& m1, float& sc0, float& sc1) {
  float a0 = m0, a1 = m1;
#pragma unroll
  for (int i = 0; i < 8; i++) { a0 = fmaxf(a0, fmaxf(s[4 * i], s[4 * i + 1])); a1 = fmaxf(a1, fmaxf(s[4 * i + 2], s[4 * i + 3])); }
  if (upper_only) { a0 = m0; a1 = m1; }
#pragma unroll
  for (int i = 8; i < 16; i++) { a0 = fmaxf(a0, fmaxf(s[4 * i], s[4 * i + 1])); a1 = fmaxf(a1, fmaxf(s[4 * i + 2], s[4 * i + 3])); }
  a0 = fmaxf(a0, __shfl_xor_sync(~0u, a0, 1)); a1 = fmaxf(a1, __shfl_xor_sync(~0u, a1, 1));
  a0 = fmaxf(a0, __shfl_xor_sync(~0u, a0, 2)); a1 = fmaxf(a1, __shfl_xor_sync(~0u, a1, 2));
  sc0 = ex2(m0 - a0); sc1 = ex2(m1 - a1);
  m0 = a0; m1 = a1;
#pragma unroll
  for (int i = 0; i < 16; i++) { s[4 * i] -= a0; s[4 * i + 1] -= a0; s[4 * i + 2] -= a1; s[4 * i + 3] -= a1; }
}
struct Att {
  float s[64], o[64], l[4], i0, i1, t0, t1; uint32_t p[32];
  float kn; uint32_t qaddr; const uint8_t* dst;
};
__device__ __forceinline__ int att_fast(uint4 (&q)[8], float kn) {
#pragma unroll
  for (int i = 0; i < 8; i++) q[i].x = hmul2(q[i].x, q[i].x);
#pragma unroll
  for (int i = 0; i < 8; i++) q[i].x = hfma2(q[i].w, q[i].w, hfma2(q[i].z, q[i].z, hfma2(q[i].y, q[i].y, q[i].x)));
#pragma unroll
  for (int i = 0; i < 4; i++) q[i].x = hadd2(q[i].x, q[i + 4].x);
  const uint32_t a0 = hadd2(q[0].x, q[2].x), a1 = hadd2(q[1].x, q[3].x);
  return __shfl_sync(~0u, __all_sync(~0u, ((bf_lo(a0) + bf_hi(a0)) * kn <= 0.25f * BOUND2) & ((bf_lo(a1) + bf_hi(a1)) * kn <= 0.25f * BOUND2)), 0);
}
__device__ __forceinline__ int att_first(Cons& c, Att& a, int h, Pend& w) {
  a.qaddr = c.daddr(0) + c.wg * 16384;
  c.turn();
  wg_fence();
  issue_qk(a.s, odesc(a.qaddr, 16, 2048, 2), odesc(c.daddr(12), 16, 2048, 2));
  int fast = 0;
  SHADOW fast = att_fast(w.lo, a.kn);
  wg_fence();
  q_step(c, a.o, 10, 11, 1 - c.wg); wg_commit();
  if (c.wg) c.wait(6); else c.skip(6);
  c.pass();
#pragma unroll
  for (int i = 0; i < 8; i++) { a.p[4 * i] = w.lo[i].x; a.p[4 * i + 1] = w.lo[i].y; a.p[4 * i + 2] = w.lo[i].z; a.p[4 * i + 3] = w.lo[i].w; }
  a.l[0] = a.l[1] = a.l[2] = a.l[3] = 0.f; a.i0 = a.i1 = a.t0 = a.t1 = 0.25f / QSCALE;
  a.dst = (const uint8_t*)__cvta_shared_to_generic(c.addr(2) + (c.wg * 4 + c.warp) * 4096 + atom_off(c.lane));
  wg_wait<1>(); fence_regs(a.s);
  c.signal(SIG_ATT + (h >> 4));
  if (c.wg) { wg_wait<0>(); c.release(10, 2); }
  return fast;
}
__device__ __forceinline__ void att_last(Cons& c, Att& a, Pend& w, int h, int g, bool drain) {
  const int uv = 6;
  if (drain) pack_o(a.o, rcp(a.i0), rcp(a.i1), w.hi);
  c.turn();
  fence_regs(a.o); fence_regs(a.p);
  wgmma_pv_sel(a.o, a.p, odesc(c.daddr(uv), 512, 2048, 2), !(drain && c.wg == 1), !drain, c.wg);
  a.i0 = a.l[0] + a.l[1]; a.i1 = a.l[2] + a.l[3];
  SHADOW row_inv(a.i0, a.i1);
  sched_fence(a.i0 + a.i1, c.base + SM_DUMMY);
  tile_store_if<0, 4>(drain, w.hi, a.dst);
  wg_wait<0>(); fence_regs(a.o); fence_regs(a.p);
  c.release(uv, 2);
  tile_store_if<4, 8>(drain, w.hi, a.dst);
  pack_o(a.o, a.i0, a.i1, w.lo);
}
__device__ __forceinline__ void cons_att(Cons& c, Att& a, int h, int g, Pend& w) {
  int fast = att_first(c, a, h, w), fast2 = 0;
  float m0 = -INFINITY, m1 = -INFINITY, sc0 = 0.f, sc1 = 0.f;
  int uk = 10, ur = 10;
  bool fresh = false;
#pragma unroll 1
  for (int d = g - 15;;) {
    const bool lo = d == c.wg;
    if ((unsigned)d < 2 || !fast) {
      if ((unsigned)d < 2) mask_half<4>(a.s, c.warp, c.lane);
      if (!fast) {
        if (d == 1) m0 = m1 = -INFINITY;
        softmax_safe(a.s, lo, m0, m1, sc0, sc1);
        a.l[0] *= sc0; a.l[1] *= sc0; a.l[2] *= sc1; a.l[3] *= sc1;
      }
    }
    exp_rng<8, 16>(a.s); sum_rng<8, 16>(a.s, a.l);
#pragma unroll
    for (int i = 4 * ATT_SPLIT; i < 32; i++) asm("{\n.reg .pred p;\nsetp.ne.s32 p, %1, %2;\n@p ex2.approx.ftz.f32 %0, %0;\n}\n" : "+f"(a.s[i]) : "r"(d), "r"(c.wg));
    sched_fence(((a.l[0] + a.l[1]) + (a.l[2] + a.l[3])) + a.s[4 * ATT_SPLIT + 3], c.base + SM_DUMMY);
    wg_wait<0>(); fence_regs(a.o); fence_regs(a.p);
    c.release(ur, c.wg && d == g - 15 ? 0 : 2);
    a.i0 += a.t0; a.i1 += a.t1;
    a.t0 = __shfl_xor_sync(~0u, a.i0, 2); a.t1 = __shfl_xor_sync(~0u, a.i1, 2);
    tile_store_if<0, 4>(fresh, w.hi, a.dst);
    uk ^= 12; ur = 14 - uk;
    if (d == 0) a.qaddr += 32768;
    const uint64_t dq = odesc(a.qaddr, 16, 2048, 2), dk = odesc(c.daddr(uk) - (d + 1 == c.wg ? 16384 : 0), 16, 2048, 2), dv = odesc(c.daddr(ur), 512, 2048, 2);
    if (!lo) { exp_rng<0, ATT_SPLIT>(a.s); sum_rng<0, 8>(a.s, a.l); cvt_p<0, 16>(a.s, a.p); }
    else if (gridDim.y == 1) cvt_p<8, 16>(a.s, a.p);
    tile_store_if<4, 8>(fresh, w.hi, a.dst);
    a.i0 += a.t0; a.i1 += a.t1;
    if (!fast || d == g + 1) {
      if (!fast && d != 1 && d != g - 15) {
#pragma unroll
        for (int i = 0; i < 16; i++) { a.o[4 * i] *= sc0; a.o[4 * i + 1] *= sc0; a.o[4 * i + 2] *= sc1; a.o[4 * i + 3] *= sc1; }
      }
      if (d == g + 1) break;
    }
    d++;
    fresh = d == 2 || d == g - 14;
    c.turn();
    fence_regs(a.o); fence_regs(a.p);
    wg_fence();
    issue_qk(a.s, dq, dk);
    c.wait(c.wg ? uk ^ 12 : ur); c.skip(c.wg ? ur : uk ^ 12);
    if (fresh || d == 1 || (unsigned)(d - g + CHK_D) < 2) {
      if (fresh) pack_o(a.o, rcp(a.i0), rcp(a.i1), w.hi);
      else if (d == 1) {
        a.i0 = a.l[0] + a.l[1]; a.i1 = a.l[2] + a.l[3];
        a.t0 = __shfl_xor_sync(~0u, a.i0, 1); a.t1 = __shfl_xor_sync(~0u, a.i1, 1);
        a.l[0] = a.l[1] = a.l[2] = a.l[3] = 0.f;
        uint32_t off = ctx_off(c, h, 15 - g, c.wg);
        asm volatile("" : "+r"(off));
        a.dst = g_T + (off + ((uint32_t)(uint64_t)a.dst & 511));
        fast = fast2;
      } else if (d == g - CHK_D) fence_async_smem();
      else fast2 = att_fast(w.hi, a.kn);
    }
    wgmma_pv_sel(a.o, a.p, dv, !lo, !fresh, c.wg);
    wg_wait<1>(); fence_regs(a.s);
    c.release(uk, 2);
    c.release(d == 0 ? 0 : 2, (d == 0 || d == g + 1) ? 2 : 0);
  }
  att_last(c, a, w, h, g, g == 0);
}

constexpr int CV_H = 1024, CV_U = 5120, CV_D = CV_U + 4128;
template<int OFF> __device__ __forceinline__ uint32_t lds32o(uint32_t a) { uint32_t v; asm volatile("ld.shared.u32 %0, [%1+%2];" : "=r"(v) : "r"(a), "n"(OFF) : "memory"); return v; }
template<int G, int G1 = 16> __device__ __forceinline__ void conv_lda(uint32_t (&a)[64], uint32_t p) {
  a[4 * G + 0] = lds32o<-256 * G>(p);
  a[4 * G + 1] = lds32o<-256 * G - 128>(p);
  a[4 * G + 2] = lds32o<-256 * G + 16>(p);
  a[4 * G + 3] = lds32o<-256 * G - 112>(p);
  if constexpr (G + 1 < G1) conv_lda<G + 1, G1>(a, p);
}
struct CvAcc { float lo[16], hi[16]; };
__device__ __forceinline__ void fence_regs(CvAcc& d) { fence_regs(d.lo); fence_regs(d.hi); }
template<int T, int G0, int G1> __device__ __forceinline__ void conv_part(float (&d)[16], const uint32_t (&a)[64], uint64_t db) {
#pragma unroll
  for (int G = G0; G < G1; G++) wgmma_rs_n32<0>(d, a[4 * G], a[4 * G + 1], a[4 * G + 2], a[4 * G + 3], db + 32 * T - 16 * G, G > 0);
}
template<int C0> __device__ __forceinline__ void conv_st_h(const float (&d)[16], uint32_t wq, float& c0, float& c1) {
#pragma unroll
  for (int n = 0; n < 4; n++) { sts64f(wq + (C0 + n * 8) * 4, d[4 * n] + c0, d[4 * n + 1] + c1); c0 = d[4 * n + 2]; c1 = d[4 * n + 3]; }
}
template<int R> __device__ __forceinline__ void conv_st(const CvAcc& d, uint32_t wq, float& c0, float& c1) { conv_st_h<64 * R>(d.lo, wq, c0, c1); conv_st_h<64 * R + 32>(d.hi, wq, c0, c1); }

constexpr int OC_PART = 13824, OC_ROW = 544;
__device__ __forceinline__ int out_next(int u) { return (0x84ac680u >> (2 * u)) & 15; }
struct Out { float acc[64]; int pu; uint64_t da, db; };
template<bool FIRST, bool REL, int W = 1> __device__ __forceinline__ void out_step(Cons& c, Out& o, bool extra = false) {
  const int pu = o.pu, u = extra ? 2 : out_next(pu);
  o.pu = u;
  c.wait(u);
  const uint64_t da = o.da + (uint32_t)(u * 1024), db = o.db + (uint32_t)(u * 1024);
  wg_fence();
#pragma unroll
  for (int kk = 0; kk < 4; kk++) wgmma_ss_n128<1>(o.acc, da + (kk >> 1) * 32 + (kk & 1) * 2, db + kk * 128, !(FIRST && kk == 0));
  wg_commit();
  if (REL) { wg_wait<W>(); c.release(pu, 2); }
}
template<int I0, int I1> __device__ __forceinline__ void oc_red(float (&y)[8], uint32_t rq) {
#pragma unroll
  for (int i = I0; i < I1; i++) { const float v = __uint_as_float(lds32(rq + i * OC_ROW - (i >> 3) * 8)); y[i & 7] = i < 8 ? v : y[i & 7] + v; }
}
template<int I0, int I1> __device__ __forceinline__ void oc_ld(float (&t)[32], uint32_t rq) {
#pragma unroll
  for (int i = I0; i < I1; i++) t[i] = __uint_as_float(lds32(rq + i * OC_ROW - (i >> 3) * 8));
}
__device__ __forceinline__ void oc_emit(const float (&y)[8], const uint4& u, uint32_t D2, uint8_t* dst) {
  uint4 z;
  z.x = hadd2(pack_bf16(y[0], y[1]), hmul2(__byte_perm(u.w, 0, 0x1032), D2));
  z.y = hadd2(pack_bf16(y[2], y[3]), hmul2(__byte_perm(u.z, 0, 0x1032), D2));
  z.z = hadd2(pack_bf16(y[4], y[5]), hmul2(__byte_perm(u.y, 0, 0x1032), D2));
  z.w = hadd2(pack_bf16(y[6], y[7]), hmul2(__byte_perm(u.x, 0, 0x1032), D2));
  *(uint4*)dst = z;
}
template<bool THR> __device__ __forceinline__ void conv_round(Cons& c, Out& o, int u, uint32_t ub, uint32_t wq, uint32_t rq, int ch) {
  const int r = c.lane >> 2, q = c.lane & 3, tid = c.warp * 32 + c.lane;
  const uint32_t ap = ub + CV_U + ((r & 1) ? 0 : UPITCH) + 4 * (((2039 - r) >> 1) + q - 8 * c.warp);
  uint32_t a[64];
  CvAcc d0, d1;
  float y[8], t[32], c0 = 0.f, c1 = 0.f;
  const uint64_t db0 = odesc(c.daddr(u) + CV_H - 16, 16, 128, 0);
#define STEP(N) if (THR) out_step<false, true>(c, o); else if (N == 0) c.turn(); else if (N == 10) wg_wait<0>();
#define STEP2(N) if (THR) out_step<false, true, 2>(c, o); else { if (N == 9) c.pass(); wg_wait<1>(); }
#define PART(...) { const uint64_t db = db0 + (c.mask >> 16); wg_fence(); __VA_ARGS__; wg_commit(); }
#define KEEP() asm volatile("add.f32 %0, %0, 0f80000000;" : "+f"(c0)); asm volatile("add.f32 %0, %0, 0f80000000;" : "+f"(c1));
  c.wait(u);
  conv_lda<0, THR ? 4 : 12>(a, ap);
  STEP(0)
  if (THR) conv_lda<4, 7>(a, ap);
  PART(conv_part<0, 0, 2>(d0.lo, a, db); conv_part<1, 0, 4>(d0.hi, a, db); conv_part<2, 0, 2>(d1.lo, a, db))
  STEP2(1)
  if (THR) conv_lda<7, 10>(a, ap);
  PART(conv_part<2, 2, 6>(d1.lo, a, db); conv_part<3, 0, 4>(d1.hi, a, db))
  STEP2(2)
  fence_regs(d0);
  if (THR) c.sync();
  sts64f(wq - 32, 0.f, 0.f);
  conv_st_h<0>(d0.lo, wq, c0, c1); KEEP()
  PART(conv_part<3, 4, 8>(d1.hi, a, db); conv_part<4, 0, 4>(d0.lo, a, db))
  STEP2(3)
  fence_regs(d1.lo);
  conv_st_h<32>(d0.hi, wq, c0, c1); conv_st_h<64>(d1.lo, wq, c0, c1); KEEP()
  PART(conv_part<4, 4, 10>(d0.lo, a, db); conv_part<5, 0, 2>(d0.hi, a, db))
  STEP2(4)
  fence_regs(d1.hi);
  float e0 = d1.hi[12] + d1.hi[10], e1 = d1.hi[13] + d1.hi[11];
  conv_st_h<96>(d1.hi, wq, c0, c1); KEEP()
  if (THR) conv_lda<10, 12>(a, ap);
  PART(conv_part<5, 2, 10>(d0.hi, a, db))
  STEP2(5)
  conv_lda<12, 14>(a, ap);
  c.sync();
  if (THR) oc_red<0, 6>(y, rq); else oc_ld<0, 8>(t, rq);
  PART(conv_part<5, 10, 12>(d0.hi, a, db); conv_part<6, 0, 6>(d1.lo, a, db))
  STEP2(6)
  if (THR) oc_red<6, 20>(y, rq); else oc_ld<8, 16>(t, rq);
  PART(conv_part<6, 6, 14>(d1.lo, a, db))
  STEP2(7)
  if (THR) oc_red<20, 26>(y, rq); else oc_ld<16, 24>(t, rq);
  conv_lda<14, 16>(a, ap);
  PART(conv_part<7, 0, 8>(d1.hi, a, db))
  STEP2(8)
  if (THR) oc_red<26, 32>(y, rq); else oc_ld<24, 32>(t, rq);
  PART(conv_part<7, 8, 16>(d1.hi, a, db))
  STEP2(9)
  if (!THR) {
#pragma unroll
    for (int i = 0; i < 8; i++) y[i] = t[i];
    SHADOW {
#pragma unroll
      for (int i = 0; i < 8; i++) y[i] = ((t[i] + t[8 + i]) + t[16 + i]) + t[24 + i];
    }
  }
  fence_regs(y); fence_regs(d0);
  c.sync();
  sts64f(wq - 32, e0, e1);
  conv_st<0>(d0, wq, c0, c1);
  STEP(10)
  fence_regs(d1); fence_regs(a);
  const uint4 u0 = lds128(ub + CV_U + 4080 - 16 * tid), u1 = lds128(ub + CV_U + 2032 - 16 * tid);
  const uint32_t D2 = lds32(ub + CV_D);
  conv_st<1>(d1, wq, c0, c1);
  STEP(11)
  sched_fence(__uint_as_float(u0.x ^ u1.x ^ D2), c.base + SM_DUMMY);
  uint8_t* zp = g_u + (uint32_t)(ch * UCH + (threadIdx.x & 127) * 16);
  oc_emit(y, u0, D2, zp);
  c.sync();
  c.release2(u);
  oc_red<0, 12>(y, rq);
  STEP(12)
  oc_red<12, 24>(y, rq);
  STEP(13)
  oc_red<24, 32>(y, rq);
  oc_emit(y, u1, D2, zp + 2048);
#undef KEEP
#undef STEP
#undef STEP2
#undef PART
}
template<int MASK> __device__ __forceinline__ void cons_conv(Cons& c, int cta, int nch) {
  const uint32_t part = c.addr(4 + 2 * c.wg) + 32;
  const uint32_t wq = part + (c.warp * 8 + (c.lane >> 2)) * OC_ROW + (c.lane & 3) * 8, rq = part + (c.warp * 32 + c.lane) * 4;
  Out o;
  c.wait(4);
#pragma unroll 1
  for (int i = 0; i < nch / 2; i++) {
    const int u = 2 * (i & 1) + c.wg;
    conv_round<false>(c, o, u, c.addr(u), wq, rq, conv_channel<MASK>(cta, 2 * i + c.wg));
    if ((i & 15) == 15 || i == nch / 2 - 1) c.signal(SIG_Z + (i >> 4));
  }
}
__device__ __forceinline__ uint32_t mix(uint32_t og, uint32_t b, uint32_t ga) { return hadd2(ga, hmul2(og, b)); }
template<int MASK> __device__ __forceinline__ void cons_out(Cons& c, const Maps& M, const Params& P, int cta, Pend& w) {
  const int mb = out_mb(cta), nb = out_nb(cta);
  Out o;
  o.da = odesc(c.daddr(0) + c.wg * 8192, 16, 1024, 2); o.db = odesc(c.daddr(1), 8192, 1024, 1);
  o.pu = 5 + gridDim.y;
  out_step<true, false>(c, o);
  int ks = 1;
  const uint32_t dst = ctx_off(c, 16 + (cta >> 3), cta & 7, 1 - c.wg);
#pragma unroll 1
  for (;; ks++) {
    if (MASK & PH_ATT) {
      if (ks == (c.wg ? ST_1 : 1)) tile_store<0, 1>(w.lo, dst, c.lane);
      if (ks == (c.wg ? ST_1 + ST_D : 1)) tile_store<1, 2>(w.lo, dst, c.lane);
      if (ks == (c.wg ? ST_1 + 2 * ST_D : 1)) tile_store<2, 3>(w.lo, dst, c.lane);
      if (ks == (c.wg ? ST_1 + 3 * ST_D : 1)) { tile_store<3, 4>(w.lo, dst, c.lane); c.signal(SIG_CTX + 1); }
    }
    if (ks == (c.wg ? OC_S1 : OC_S0)) break;
    out_step<false, true>(c, o, ks == 1);
  }
  if (MASK & PH_CONV) {
    const int r = c.lane >> 2, q = c.lane & 3, tid = c.warp * 32 + c.lane, u = 2 * c.wg;
    const uint32_t ub = c.addr(u), part = ub + OC_PART + 32;
    const uint32_t wq = part + (c.warp * 8 + r) * OC_ROW + q * 8, rq = part + tid * 4;
    int ch = conv_channel<MASK>(cta, 3 * c.wg);
#pragma unroll 1
    for (int i = 0; ch >= 0; i++) {
      conv_round<true>(c, o, u + (i >> 8), ub, wq, rq, ch);
      ch = i + c.wg < 2 ? ch + 1 : -1;
      if (c.wg > i) { mbar_wait(c.base + SM_RDY + 8 * RDY_T, 0); ch = __shfl_sync(~0u, lds32(c.base + SM_POOL), 0); }
      if (ch < 0) { c.signal(SIG_Z); c.sync(); c.release2(u + 1);  }
      out_step<false, true>(c, o);
#pragma unroll 1
      for (int k = 15; k < (ch < 0 ? 0 : c.wg ? OC_L1 : OC_L0); k++) out_step<false, true>(c, o);
      ks += ch < 0 ? 15 : c.wg ? OC_L1 : OC_L0;
    }
    if (c.wg) c.skip(0);
  }
#pragma unroll 1
  for (; ks < 57; ks++) out_step<false, true>(c, o);
  uint32_t ga[32];
  c.wait(3);
  const float g0 = __uint_as_float(lds32(c.base + SM_GATE + 4 * (c.wg * 64 + c.warp * 16 + (c.lane >> 2)))), g1 = __uint_as_float(lds32(c.base + SM_GATE + 32 + 4 * (c.wg * 64 + c.warp * 16 + (c.lane >> 2))));
  const uint32_t gg0 = pack_bf16(g0, g0), gg1 = pack_bf16(g1, g1);
  const uint32_t og0 = pack_bf16(1.f - g0, 1.f - g0), og1 = pack_bf16(1.f - g1, 1.f - g1);
  const int xr = c.wg * 64 + c.warp * 16 + (c.lane & 15);
  const uint32_t xa = c.addr(2) + xr * 128, xs = xr & 7, xh = c.lane >> 4;
  const int zr = (c.lane & 7) + ((c.lane >> 4) << 3);
  const uint32_t za = c.addr(0) + c.wg * 16384 + zr * 128 + (((c.warp * 2 + ((c.lane >> 3) & 1)) ^ (zr & 7)) << 4);
#pragma unroll
  for (int i = 0; i < 8; i++) {
    if (i == 0) out_step<false, true>(c, o);
    if (i == 3) out_step<false, true>(c, o);
    if (i == 6) out_step<false, true>(c, o);
    ldsm4(xa + (i >> 2) * 16384 + ((((i & 3) * 2 + xh) ^ xs) << 4), ga[4 * i], ga[4 * i + 1], ga[4 * i + 2], ga[4 * i + 3]);
  }
#pragma unroll 1
  for (ks = 60; ks < 64; ks++) out_step<false, false>(c, o);
  c.wait(0);
  SHADOW {
#pragma unroll
    for (int i = 0; i < 8; i++) {
      uint32_t z0, z1, z2, z3;
      ldsm4t(za + i * 2048, z0, z1, z2, z3);
      ga[4 * i + 0] = hmul2(ga[4 * i + 0], z0); ga[4 * i + 1] = hmul2(ga[4 * i + 1], z1); ga[4 * i + 2] = hmul2(ga[4 * i + 2], z2); ga[4 * i + 3] = hmul2(ga[4 * i + 3], z3);
      ga[4 * i + 0] = hmul2(gg0, ga[4 * i + 0]); ga[4 * i + 1] = hmul2(gg1, ga[4 * i + 1]); ga[4 * i + 2] = hmul2(gg0, ga[4 * i + 2]); ga[4 * i + 3] = hmul2(gg1, ga[4 * i + 3]);
    }
  }
  c.signal(SIG_DONE);
  fence_regs(ga);
  wg_wait<0>(); fence_regs(o.acc);
#pragma unroll
  for (int i = 0; i < 8; i++) {
    const uint32_t r0 = mix(og0, pack_bf16(o.acc[8 * i + 0], o.acc[8 * i + 1]), ga[4 * i + 0]);
    const uint32_t r1 = mix(og1, pack_bf16(o.acc[8 * i + 2], o.acc[8 * i + 3]), ga[4 * i + 1]);
    const uint32_t r2 = mix(og0, pack_bf16(o.acc[8 * i + 4], o.acc[8 * i + 5]), ga[4 * i + 2]);
    const uint32_t r3 = mix(og1, pack_bf16(o.acc[8 * i + 6], o.acc[8 * i + 7]), ga[4 * i + 3]);
    stsm4(xa + (i >> 2) * 16384 + ((((i & 3) * 2 + xh) ^ xs) << 4), r0, r1, r2, r3);
    if ((i & 3) == 3) {
      __syncwarp();
#pragma unroll
      for (int k = 0; k < 4; k++) {
        const int rr = c.wg * 64 + c.warp * 16 + k * 4 + (c.lane >> 3);
        const uint4 v = lds128(c.addr(2 + (i >> 2)) + rr * 128 + (((c.lane ^ rr) & 7) << 4));
        *(uint4*)(P.out + (uint32_t)((mb * 128 + rr) * 1024 + nb * 128 + (i >> 2) * 64 + (c.lane & 7) * 8)) = v;
      }
    }
  }
}

__device__ __forceinline__ void load_conv(Prod& p, const Maps& M, int u, int ch) {
  if (elect()) {
    mbar_expect(p.full(u), 5120 + UCH);
    tma3d(p.addr(u), &M.h, 0, -8, ch, p.full(u), true);
    bulk_g2s(p.addr(u) + CV_U, g_u + (size_t)ch * UCH, UCH, p.full(u), true);
  }
}
template<int MASK> __device__ __forceinline__ void prod_conv(Prod& p, const Maps& M, int cta, int nch) {
  int ready = -1;
#pragma unroll 1
  for (int i = 0; i < nch; i++) {
    const int ch = conv_channel<MASK>(cta, i);
    const int u = i & 3;
    if ((ch >> 6) != ready) { ready = ch >> 6; if (cta < NREG) mbar_wait(p.base + SM_RDY + 8 * RDY_U, 0); else cnt_wait(g_cnt + (C_U + ready) * CSTRIDE, 128); }
    p.acquire(u, 1);
    load_conv(p, M, u, ch);
    if (i == 3) { p.acquire(4, 4); if (elect()) mbar_arrive(p.full(4)); }
  }
}
#define HOIST(v) asm volatile("" : "+r"(v))
template<int MASK> __device__ __forceinline__ void producer(const Maps& M, const Params& P, uint32_t base, int cta, int lane) {
  Prod p{base, ((MASK & PH_KV) && cta < NREG) ? 0xffffcfffu ^ ((1u << (3 * NFIRST)) - 1) : 0xffffffffu, lane};
  if (cta >= NREG) { if (MASK & PH_CONV) prod_conv<MASK>(p, M, cta, CV_EXTRA<MASK>); return; }
  const int g = cta & 7, j = cta >> 3, rank = cta & 1;
#pragma unroll 1
  for (int half = 0; half < 2; half++) {
    const int h = j + 16 * half;
    if (MASK & PH_KV) {
      const CUtensorMap* mw = rank ? &M.wv : &M.wk;
#pragma unroll 1
      for (int it = half ? 0 : NFIRST; it < 16; it++) {
        const int u = gemm_unit(it);
        const bool early = MASK == PH_ALL && it == 0;
        uint32_t bar = p.full(u), d0 = p.addr(early ? 12 : u), d1 = p.addr(u + !early + rank); int k0 = (it & 7) * 64, r0 = (2 * g + (it >> 3)) * 128;
        HOIST(bar); HOIST(d0); HOIST(d1); HOIST(k0); HOIST(r0);
        p.acquire(u, 3 - early);
        if (elect()) {
          mbar_expect(bar, 3 * UNIT);
          tma3d_mc(d1, mw, 0, k0, 2 * h, bar, it >= 8);
          tma2d(d0, &M.c, k0, r0, bar);
        }
      }
    }
    if (MASK & PH_ATT) {
#pragma unroll 1
      for (int ks = 0; ks < 16; ks++) {
        const int u = gemm_unit(ks);
        uint32_t bar = p.full(u), d0 = p.addr(u), d1 = p.addr(u + 1), d2 = p.addr(u + 2) + rank * 8192; int k0 = ks * 64;
        HOIST(bar); HOIST(d0); HOIST(d1); HOIST(d2); HOIST(k0);
        p.acquire(u, 3);
        if (elect()) {
          mbar_expect(bar, 3 * UNIT);
          tma2d_mc(d2, &M.wq, h * 128 + rank * 64, k0, bar, true);
          tma2d(d0, &M.x, k0, (15 - g) * 128, bar);
          tma2d(d1, &M.x, k0, g * 128, bar);
        }
      }
      mbar_wait(base + SM_RDY + 8 * (RDY_KV + half), 0);
      const uint8_t* KVh = g_T + T_KV + (size_t)kv_slot<MASK>(h) * 16 * 65536;
      if (MASK & PH_PRE) mbar_wait(base + SM_RDY + 8 * RDY_AUX, 0);
      if (elect()) { mbar_expect(p.full(12), 32768); bulk_g2s(p.addr(12), KVh, 32768, p.full(12), true); }
      p.acquire(0, 4);
      if (elect()) mbar_arrive(p.full(0));
#pragma unroll 1
      for (int i = 1; i < 34; i++) {
        const int isv = !(i & 1) || i == 33, st = i == 33 ? 16 : (isv ? (i >> 1) - 1 : (i + 1) >> 1), u = 4 + 2 * (i & 3);
        const bool own = st == 15 - (g & 6);
        uint32_t bar = p.full(u), d0 = p.addr(own ? u : u + rank), off = (st <= 15 - g ? st : 16 - st) * 65536 + isv * 32768 + (own ? 0 : rank * UNIT);
        HOIST(bar); HOIST(d0); HOIST(off);
        p.acquire(u, 2);
        if (elect()) {
          mbar_expect(bar, 32768);
          if (own) bulk_g2s(d0, KVh + off, 32768, bar, true); else bulk_g2s_mc(d0, KVh + off, UNIT, bar, true);
        }
      }
    }
  }
  if ((MASK & PH_CONV) && !(MASK & PH_OUT)) prod_conv<MASK>(p, M, cta, CV_REG<MASK>);
  if (MASK & PH_OUT) {
    const int y0 = out_mb(cta) * 512 + rank * 8, z0 = 2 * out_nb(cta);
    int u = 6;
#pragma unroll 1
    for (int hf = 0; hf < 2; hf++) {
      mbar_wait(base + SM_RDY + 8 * (RDY_CTX + hf), 0);
#pragma unroll 1
      for (int n = hf * 32; n < hf * 32 + 32; n++) {
        const int ks = n == 1 ? 2 : n == 2 ? 1 : n;
        u = n == 2 ? 2 : n == 3 ? 10 : out_next(u);
        uint32_t bar = p.full(u), d0 = p.addr(u) + rank * 8192, d1 = p.addr(u + 1); int x = (ks & 1) * 256, y = y0 + (ks >> 1) * 16, k0 = ks * 64;
        HOIST(bar); HOIST(d0); HOIST(d1); HOIST(x); HOIST(y); HOIST(k0);
        p.acquire(u, 2);
        if (elect()) {
          mbar_expect(bar, 2 * UNIT);
          tma2d_mc(d0, &M.ctx, x, y, bar, true);
          tma3d(d1, &M.wo, 0, k0, z0, bar, true);
          if (ks == 1) mbar_arrive(base + SM_RDY + 8 * RDY_X);
          if (ks == Z_AT) mbar_arrive(base + SM_RDY + 8 * RDY_Z);
        }
      }
    }
  }
}
template<int MASK> __device__ __forceinline__ void producer2(const Maps& M, const Params& P, uint32_t base, int cta, int w, int lane) {
  Prod p{base, 0xffffffffu, lane};
  const int mb = out_mb(cta), nb = out_nb(cta), u = 2 * w;
  if (w) { mbar_wait_slow(base + SM_RDY + 8 * RDY_X, 0); p.mask ^= MASK == PH_ALL ? 8 : 12; }
  if (MASK & PH_CONV) {
    mbar_wait_slow(base + SM_SIG + 8 * (SIG_ATT + 1), 0);
    mbar_wait_slow(base + SM_RDY + 8 * RDY_U, 0);
#pragma unroll 1
    for (int i = 0, ch = conv_channel<MASK>(cta, 3 * w); ch >= 0; i++) {
      p.acquire_slow(u, i ? 1 : 2);
      load_conv(p, M, u, ch);
      ch = i + w < 2 ? ch + 1 : -1;
      if (w > i) { mbar_wait_slow(base + SM_RDY + 8 * RDY_T, 0); ch = lds32(base + SM_POOL); }
    }
  }
  p.acquire_slow(u, 2);
  if (!w && elect()) map_pf(&M.z);
  mbar_wait(base + SM_RDY + 8 * (!w ? RDY_Z : RDY_G), 0);
  if (elect()) {
    const uint32_t bar = p.full(3 * w);
    mbar_expect(bar, 2 * UNIT + (!w ? 0 : 512));
    tma2d(p.addr(u), !w ? &M.z : &M.x, (!w ? mb : nb) * 128, (!w ? nb : mb) * 128, bar, true);
    tma2d(p.addr(u + 1), !w ? &M.z : &M.x, (!w ? mb : nb) * 128 + 64, (!w ? nb : mb) * 128, bar, true);
    if (w) bulk_g2s(base + SM_GATE, g_gate + mb * 128, 512, bar);
  }
}

__device__ __forceinline__ constexpr uint32_t PUB(int sig, int cnt, int n) { return 0x80000000u | (sig << 24) | (n << 8) | cnt; }
__device__ __forceinline__ constexpr uint32_t GET(int rdy, int cnt, int n) { return (rdy << 24) | (n << 8) | cnt; }
template<int MASK> __device__ __forceinline__ void sync_agent(uint32_t base, int cta, int lane) {
  if ((base & 0x3FFFF) != SMEM_BASE) asm volatile("trap;");
  const int g = cta & 7, j = cta >> 3, go = min(out_mb(cta), 15 - out_mb(cta));
  const int c0 = conv_channel<MASK>(cta, 0), c1 = c0 + CV_REG<MASK> - 1, n0 = min(CV_REG<MASK>, 128 - (c0 & 127));
  constexpr bool KV = MASK & PH_KV, ATT = MASK & PH_ATT, CONV = MASK & PH_CONV, OUT = MASK & PH_OUT, ALL = MASK == PH_ALL;
  uint32_t e = 0;
  if (cta >= NREG) { if (CONV && lane * 32 < CV_EXTRA<MASK>) e = PUB(SIG_Z + lane, C_Z + lane, min(32, CV_EXTRA<MASK> - lane * 32)); }
  else switch (lane) {
    case 0:  if (KV) e = PUB(SIG_KV, C_KV + j, 1); break;
    case 1:  if (ATT) e = GET(RDY_KV, C_KV + j, 8); break;
    case 2:  if (ALL) e = PUB(SIG_WAR, C_WAR + j, 1); break;
    case 3:  if (ATT) e = PUB(SIG_CTX, C_CTX + g, 1); break;
    case 4:  if (ALL) e = GET(RDY_WAR, C_WAR + j, 8); break;
    case 5:  if (KV) e = PUB(SIG_KV + 1, C_KV + 16 + j, 1); break;
    case 6:  if (ATT) e = GET(RDY_KV + 1, C_KV + 16 + j, 8); break;
    case 7:  if (OUT) e = GET(RDY_CTX, C_CTX + go, 16); break;
    case 8:  if (CONV) e = GET(RDY_U, C_U + (c0 >> 6), 128); break;
    case 9:  if (CONV) e = GET(ALL ? RDY_NONE : RDY_U, C_U + (ALL ? 14 : c1 >> 6), 128); break;
    case 10: if (ALL) e = GET(RDY_T, C_U + 15, 128); break;
    case 11: if (ATT) e = PUB(SIG_CTX + 1, C_CTX + 8 + g, 1); break;
    case 12: if (OUT) e = GET(RDY_CTX + 1, C_CTX + 8 + go, 16); break;
    case 13: if (OUT) e = GET(RDY_G, C_GATE, 256); break;
    case 14: if (CONV) e = PUB(SIG_Z, C_Z + (c0 >> 7), n0); break;
    case 15: if (ALL) e = PUB(SIG_Z, C_Z + 7, 1); else if (CONV && n0 < CV_REG<MASK>) e = PUB(SIG_Z, C_Z + (c1 >> 7), CV_REG<MASK> - n0); break;
    case 16: if (OUT) e = GET(RDY_Z, C_Z + out_nb(cta), 128); break;
  }
  if (ALL && lane == 0) { mbar_expect(base + SM_RDY + 8 * RDY_T, 4); mbar_arrive(base + SM_RDY + 8 * RDY_U); }
  __syncwarp();
#pragma unroll 1
  for (int i = 0; i < 17; i++) {
    const uint32_t x = __shfl_sync(~0u, e, i), id = (x >> 24) & 127, n = (x >> 8) & 0xffff;
    if (x == 0) continue;
    unsigned* cnt = g_cnt + (x & 255) * CSTRIDE;
    if (x >> 31) {
      mbar_wait_slow(base + SM_SIG + 8 * id, 0);
      const bool draw = ALL && i == 11 && !(cta & 1);
      unsigned t = 0;
      if (draw && lane == 0) asm volatile("atom.relaxed.gpu.global.add.u32 %0, [%1], 1;" : "=r"(t) : "l"(g_cnt + C_TICKET * CSTRIDE) : "memory");
      if (lane == 0 && !(ALL && i == 15 && (int)lds32(base + SM_POOL) < 0)) cnt_publish(cnt, n, i != 15);
      if (draw) {
        t = __shfl_sync(~0u, t, 0);
        uint32_t peer;
        asm volatile("mapa.shared::cluster.u32 %0, %1, %2;" : "=r"(peer) : "r"(base), "r"(lane & 1));
        if (lane < 2) asm volatile("st.async.weak.shared::cluster.mbarrier::complete_tx::bytes.u32 [%0], %1, [%2];"
          :: "r"(peer + SM_POOL), "r"(t < 64 - NSKIP ? CV_POOL + 2 * t + lane : ~0u), "r"(peer + SM_RDY + 8 * RDY_T) : "memory");
      }
    } else {
      cnt_wait(cnt, n);
      if (id < 2) {
        const float4 kn = __ldcg((const float4*)(g_kn2 + kv_slot<MASK>(j + 16 * id) * 128) + lane);
        const uint32_t m = __reduce_max_sync(~0u, max(max(__float_as_uint(kn.x), __float_as_uint(kn.y)), max(__float_as_uint(kn.z), __float_as_uint(kn.w))));
        if (lane == 0) asm volatile("st.shared.u32 [%0], %1;" :: "r"(base + SM_KMAX + 4 * id), "r"(m) : "memory");
      }
      if (lane == 0) mbar_arrive(base + SM_RDY + 8 * id);
    }
    __syncwarp();
  }
}

__device__ __forceinline__ void aux_gate(const Params& P, int cta, int aw, int lane) {
  uint4 gw[4];
#pragma unroll
  for (int i = 0; i < 4; i++) gw[i] = __ldg((const uint4*)P.gw + i * 32 + lane);
#pragma unroll 1
  for (int row = cta * 16 + aw * 8; row < cta * 16 + aw * 8 + 8; row++) {
    float a = 0.f;
#pragma unroll
    for (int i = 0; i < 4; i++) {
      const uint4 xv = __ldg((const uint4*)(P.x + (size_t)row * 1024) + i * 32 + lane);
      uint32_t m;
      m = hmul2(xv.x, gw[i].x); a += bf_lo(m) + bf_hi(m); m = hmul2(xv.y, gw[i].y); a += bf_lo(m) + bf_hi(m);
      m = hmul2(xv.z, gw[i].z); a += bf_lo(m) + bf_hi(m); m = hmul2(xv.w, gw[i].w); a += bf_lo(m) + bf_hi(m);
    }
#pragma unroll
    for (int o = 16; o > 0; o >>= 1) a += __shfl_xor_sync(~0u, a, o);
    a = bf_lo(pack_bf16(a, 0.f));
    const float gt = bf_lo(pack_bf16(__fdividef(1.f, 1.f + ex2(-a * 1.4426950408889634f)), 0.f));
    if (lane == 0) g_gate[row] = gt;
    __nanosleep(GATE_SLEEP);
  }
  cnt_signal(g_cnt + C_GATE * CSTRIDE, lane);
}
__device__ __forceinline__ void pf64(const void* p) { asm volatile("prefetch.global.L2 [%0];" :: "l"(p) : "memory"); }
__device__ __forceinline__ void aux_pf(const Params& P, int cta, int aw, int lane) {
  for (int i = 0; i < PF_WAIT; i++) __nanosleep(1000);
#pragma unroll 1
  for (int i = 0; i < 8; i++) {
    pf64((const uint8_t*)(aw ? P.wv : P.wk) + ((16 + (cta >> 3)) * 256 + (lane & 3) * 64 + (i * 64 + (cta & 7) * 8 + (lane >> 2)) * 8192));
    if ((i & 3) == 0) pf64((const uint8_t*)P.c + (((cta & 7) * 256 + (cta >> 3) * 8 + aw * 4 + (lane >> 3)) * 1024 + (i >> 2) * 512 + (lane & 7) * 64));
    __nanosleep(PF_GAP);
  }
}
template<int MASK> __device__ __forceinline__ void aux_pre(const Maps& M, const Params& P, uint32_t base, int cta, int aw, int lane) {
  const uint32_t kb = base + 12 * UNIT, bar = base + SM_PRE;
  const int r = lane >> 2, q = lane & 3;
  const int mi = lane >> 3, row0 = (lane & 6) + 1 - (lane & 1);
  const int ra = (mi * 9 + 1) * 2 + row0;
  const int rb = (mi == 0 ? 3 : mi) * 18 + row0;
#pragma unroll 1
  for (int it = 0; it < (cta < 96 ? 5 : 4); it++) {
    if (it == PRE_EARLY && MASK == PH_ALL) { mbar_wait_slow(base + SM_SIG + 8 * SIG_ATT, 0); aux_gate(P, cta, aw, lane); aux_pf(P, cta, aw, lane); }
    if (it == PRE_EARLY && MASK == PH_ALL) mbar_wait_slow(base + SM_SIG + 8 * (SIG_ATT + 1), 0);
    const int cg = it ? it * 4 - 3 + (cta >> 5) : 0, tb = cta & 31;
    if (aw == 0 && elect()) {
      mbar_expect(bar, 2 * 9216);
      tma4d(kb, &M.k, cg * 64, 0, tb * 8 - 1, 0, bar, true);
      tma4d(kb + 9216, &M.v, cg * 64, 0, tb * 8 - 1, 0, bar, true);
    }
    const uint2 swl = __ldg((const uint2*)(P.shift + (cg * 64 + aw * 32 + lane) * 4));
    if (tb == 0) {
      uint8_t* e = g_u + (size_t)(cg * 64 + aw * 32 + lane) * UCH + 4096;
      *(uint4*)e = make_uint4(0, 0, 0, 0); *(uint4*)(e + UPITCH) = make_uint4(0, 0, 0, 0);
      *(uint32_t*)(e + 32) = (uint32_t)__bfloat16_as_ushort(P.D[cg * 64 + aw * 32 + lane]) * 0x10001u;
    }
    if (it == 0) mbar_wait(bar, 0); else mbar_wait_slow(bar, it & 1);
#pragma unroll 1
    for (int ol = it ? 0 : cta >> 5; ol < (it ? 4 : (cta >> 5) + 1); ol++) {
      const int oc = aw * 4 + ol;
      const uint32_t s01 = __shfl_sync(~0u, swl.x, ol * 8 + r), s23 = __shfl_sync(~0u, swl.y, ol * 8 + r);
      const uint32_t w0 = __byte_perm(s01, 0, 0x1010), w1 = __byte_perm(s01, 0, 0x3232), w2 = __byte_perm(s23, 0, 0x1010), w3 = __byte_perm(s23, 0, 0x3232);
      const uint32_t pa = kb + ra * 128 + ((oc ^ (ra & 7)) << 4), pb = kb + (mi == 0 ? 9216 : 0) + rb * 128 + ((oc ^ (rb & 7)) << 4);
      uint8_t* e0 = g_u + (uint32_t)((cg * 64 + oc * 8 + r) * UCH + (2040 - tb * 64 - 8 * q) * 2);
#pragma unroll
      for (int hb = 0; hb < 2; hb++) {
        uint32_t k[7], v[5];
        ldsm4t(pa + hb * 1024, k[3], k[4], k[5], k[6]);
        ldsm4t(pa + hb * 1024 + 9216, v[1], v[2], v[3], v[4]);
        ldsm4t(pb + hb * 1024, v[0], k[0], k[1], k[2]);
        uint32_t o1 = __byte_perm(k[1], k[0], 0x5432);
#pragma unroll
        for (int m = 0; m < 5; m++) {
          const uint32_t o2 = __byte_perm(k[m + 2], k[m + 1], 0x5432);
          v[m] = hmul2(hadd2(hadd2(hadd2(hmul2(o1, w3), hmul2(k[m + 1], w2)), hmul2(o2, w1)), hmul2(k[m + 2], w0)), v[m]);
          o1 = o2;
        }
        *(uint4*)(e0 - hb * 64) = make_uint4(v[4], v[3], v[2], v[1]);
        *(uint4*)(e0 - hb * 64 + UPITCH) = make_uint4(__byte_perm(v[4], v[3], 0x5432), __byte_perm(v[3], v[2], 0x5432), __byte_perm(v[2], v[1], 0x5432), __byte_perm(v[1], v[0], 0x5432));
        if (it >= PRE_EARLY) __nanosleep(PRE_SLEEP);
      }
    }
    bar_sync(5, 64);
    if (it == PRE_EARLY - 1 && aw == 0 && lane == 0) mbar_arrive(base + SM_RDY + 8 * RDY_AUX);
    if (aw == 1 && lane == 0) asm volatile("red.release.gpu.global.add.u32 [%0], %1;" :: "l"(g_cnt + (C_U + cg) * CSTRIDE), "r"(it ? 4 : 1) : "memory");
  }
  uint32_t rel;
  asm volatile("mapa.shared::cluster.u32 %0, %1, %2;" : "=r"(rel) : "r"(base + SM_BAR + 128 + 8 * (12 + (lane & 1))), "r"((lane >> 1) & 1));
  if (lane < 4) asm volatile("mbarrier.arrive.shared::cluster.b64 _, [%0];" :: "r"(rel) : "memory");
  if (MASK != PH_ALL) aux_gate(P, cta, aw, lane);
}

template<int MASK> __global__ void __cluster_dims__(2, 1, 1) __launch_bounds__(384, 1) gated_mix_kernel(const __grid_constant__ Maps M, const __grid_constant__ Params P) {
  extern __shared__ __align__(1024) uint8_t smem[];
  const uint32_t base = (uint32_t)__cvta_generic_to_shared(smem);
  if ((MASK & PH_KV) && elect()) {
    map_pf(&M.wk + (blockIdx.x & 1)); map_pf(&M.c);
  }
  const int wi = __shfl_sync(~0u, threadIdx.x >> 5, 0), wg = wi >> 2, warp = wi & 3;
  if (elect()) {
    if (wi < 8) {
      const int cnt = 1 << ((0x10332200 >> (4 * wi)) & 15);
#pragma unroll
      for (int i = 0; i < 8; i++) mbar_init(base + SM_BAR + 64 * wi + 8 * i, cnt);
      asm volatile("fence.mbarrier_init.release.cluster;" ::: "memory");
    }
  }
  const int cta = blockIdx.x;
  const bool first_loads = (MASK & PH_KV) && wi == 8 && cta < NREG;
  const CUtensorMap* mw = (cta & 1) ? &M.wv : &M.wk;
  __syncwarp();
  asm volatile("barrier.cluster.arrive.relaxed.aligned;\nbarrier.cluster.wait.aligned;" ::: "memory");
  auto first_stage = [&](int it) {
    const uint32_t bar = base + SM_BAR + 24 * it, d0 = base + 3 * it * UNIT;
    mbar_expect(bar, 3 * UNIT);
    tma3d_mc(d0 + (1 + (cta & 1)) * UNIT, mw, 0, it * 64, 2 * (cta >> 3), bar);
    tma2d(d0, &M.c, it * 64, (cta & 7) * 256, bar);
  };
  if (first_loads && elect()) first_stage(0);
  __syncwarp();
  const int lane = threadIdx.x & 31;
  if (wg == 2) {
    asm volatile("setmaxnreg.dec.sync.aligned.u32 56;");
    if (warp == 0) producer<MASK>(M, P, base, cta, lane);
    else if (warp == 1) sync_agent<MASK>(base, cta, lane);
    else if (cta < NREG) {
      if (MASK & PH_PRE) aux_pre<MASK>(M, P, base, cta, warp - 2, lane);
      if (MASK & PH_OUT) producer2<MASK>(M, P, base, cta, warp - 2, lane);
    }
    if (warp == 1) {
      if (MASK & PH_OUT) {
        unsigned old = 0;
        if (lane == 0) asm volatile("atom.relaxed.gpu.global.add.u32 %0, [%1], 1;" : "=r"(old) : "l"(g_cnt + C_EXIT * CSTRIDE) : "memory");
        old = __shfl_sync(~0u, old, 0);
        if (old == NCTA - 1) for (int i = lane; i < C_NUM; i += 32) g_cnt[i * CSTRIDE] = 0;
      }
      mbar_wait_slow(base + SM_SIG + 8 * SIG_DONE, 0);
      if (cta >= NREG || !(MASK & PH_OUT)) { cluster_arrive(); cluster_wait(); }
    }
  } else {
    asm volatile("setmaxnreg.inc.sync.aligned.u32 224;");
    uint32_t rel;
    asm volatile("mapa.shared::cluster.u32 %0, %1, %2;" : "=r"(rel) : "r"(base + SM_BAR + 128 + 8 * (lane & 15)), "r"(lane >> 4));
    Cons c{base, rel, 0u, lane, warp, wg, warp == 3 ? lane & 15 : 16};
    if (wg == 1) bar_arrive(1, 256);
    if ((MASK & PH_KV) && wi == 4 && cta < NREG) {
      if (elect()) {
#pragma unroll 1
        for (int it = 1; it < NFIRST; it++) {
          asm volatile("{\n.reg .pred p;\n.reg .u32 a, b;\nmov.u32 a, %%clock;\nXL:\nmov.u32 b, %%clock;\nsub.u32 b, b, a;\nsetp.lt.u32 p, b, %0;\n@p bra XL;\n}\n" :: "r"(it == 1 ? FGAP : FGAP2) : "memory");
          first_stage(it);
        }
      }
      __syncwarp();
    }
    if (cta < NREG) {
      const int g = cta & 7, j = cta >> 3;
      Pend w = {};
#pragma unroll 1
      for (int half = 0; half < 2; half++) {
        const int h = j + 16 * half, blk = kv_slot<MASK>(h) * 16 + 2 * g;
        if (MASK & PH_KV) cons_kv<(MASK & PH_ATT) != 0>(c, h, blk, g, w, half == 1 && (MASK & PH_ATT));
        if (MASK & PH_ATT) {
          Att a;
          cons_q<(MASK & PH_KV) != 0>(c, h, blk + 1, w, a.o, a.kn);
          cons_att(c, a, h, g, w);
          if (half == 0) c.signal(SIG_WAR);
          if (MASK != PH_ALL) { tile_store<0, 4>(w.lo, ctx_off(c, h, g, 1 - wg), lane); c.signal(SIG_CTX + half); }
        } else if (MASK & PH_KV) {
          float kn = 0.f;
          out_piece<SCH_KV, true>(c, w, kv_off(c, blk + 1), blk + 1, kn, 0, true);
          for (int ks = 1; ks < 8; ks++) out_piece<SCH_KV, false>(c, w, kv_off(c, blk + 1), blk + 1, kn, ks, true);
          c.signal(SIG_KV + half);
        }
      }
      if (MASK & PH_OUT) cons_out<MASK>(c, M, P, cta, w);
    }
    if (cta >= NREG || !(MASK & PH_OUT)) {
      if (MASK & PH_CONV) cons_conv<MASK>(c, cta, cta < NREG ? CV_REG<MASK> : CV_EXTRA<MASK>);
      c.signal(SIG_DONE);
      cluster_arrive();
    }
  }
}

typedef CUresult (*EncFn)(CUtensorMap*, CUtensorMapDataType, cuuint32_t, void*, const cuuint64_t*, const cuuint64_t*, const cuuint32_t*, const cuuint32_t*,
                          CUtensorMapInterleave, CUtensorMapSwizzle, CUtensorMapL2promotion, CUtensorMapFloatOOBfill);
static void enc(EncFn f, CUtensorMap* m, const void* ptr, int rank, const cuuint64_t* dims, const cuuint64_t* strides, const cuuint32_t* box, CUtensorMapSwizzle sw,
                CUtensorMapDataType dt = CU_TENSOR_MAP_DATA_TYPE_BFLOAT16) {
  const cuuint32_t es[4] = {1, 1, 1, 1};
  f(m, dt, rank, (void*)ptr, dims, strides, box, es, CU_TENSOR_MAP_INTERLEAVE_NONE, sw, CU_TENSOR_MAP_L2_PROMOTION_L2_256B, CU_TENSOR_MAP_FLOAT_OOB_FILL_NONE);
}
static void enc2(EncFn f, CUtensorMap* m, const void* ptr, int cols, int rows, int brows) {
  const cuuint64_t d[2] = {(cuuint64_t)cols, (cuuint64_t)rows}, s[1] = {(cuuint64_t)cols * 2}; const cuuint32_t b[2] = {64, (cuuint32_t)brows};
  enc(f, m, ptr, 2, d, s, b, CU_TENSOR_MAP_SWIZZLE_128B);
}
static void encw(EncFn f, CUtensorMap* m, const void* ptr, int cols, int rows) {
  const cuuint64_t d[3] = {64, (cuuint64_t)rows, (cuuint64_t)cols / 64}, s[2] = {(cuuint64_t)cols * 2, 128}; const cuuint32_t b[3] = {64, 64, 2};
  enc(f, m, ptr, 3, d, s, b, CU_TENSOR_MAP_SWIZZLE_128B);
}
extern "C" void kernel_launch(void* const* d_in, const int* in_sizes, int n_in, void* d_out, int out_size) {
  static EncFn fn = nullptr;
  static int ncl = 0;
  static void* zptr = nullptr;
  static void* tptr = nullptr;
  if (!fn) {
    void* p = nullptr; cudaDriverEntryPointQueryResult qr;
    cudaGetDriverEntryPoint("cuTensorMapEncodeTiled", &p, cudaEnableDefault, &qr);
    fn = (EncFn)p;
    cudaFuncSetAttribute(gated_mix_kernel<PH_ALL>, cudaFuncAttributeMaxDynamicSharedMemorySize, SMEM_BYTES);
    cudaFuncSetAttribute(gated_mix_kernel<PH_PRE | PH_KV>, cudaFuncAttributeMaxDynamicSharedMemorySize, SMEM_BYTES);
    cudaFuncSetAttribute(gated_mix_kernel<PH_ATT | PH_CONV>, cudaFuncAttributeMaxDynamicSharedMemorySize, SMEM_BYTES);
    cudaFuncSetAttribute(gated_mix_kernel<PH_OUT>, cudaFuncAttributeMaxDynamicSharedMemorySize, SMEM_BYTES);
    cudaLaunchConfig_t cfg = {}; cfg.gridDim = NCTA; cfg.blockDim = 384; cfg.dynamicSmemBytes = SMEM_BYTES;
    cudaLaunchAttribute at; at.id = cudaLaunchAttributeClusterDimension; at.val.clusterDim.x = 2; at.val.clusterDim.y = 1; at.val.clusterDim.z = 1;
    cfg.attrs = &at; cfg.numAttrs = 1;
    cudaOccupancyMaxActiveClusters(&ncl, gated_mix_kernel<PH_ALL>, &cfg);
    cudaGetSymbolAddress(&zptr, g_u);
    cudaGetSymbolAddress(&tptr, g_T);
  }
  Maps M;
  enc2(fn, &M.x, d_in[0], 1024, 2048, 128);
  enc2(fn, &M.c, d_in[7], 512, 2048, 128);
  enc2(fn, &M.wq, d_in[8], 4096, 1024, 64);
  encw(fn, &M.wk, d_in[9], 4096, 512);
  encw(fn, &M.wv, d_in[10], 4096, 512);
  encw(fn, &M.wo, d_in[11], 1024, 4096);
  { const cuuint64_t d[3] = {64, 32, 1024}, s[2] = {128, 4096}; const cuuint32_t b[3] = {64, 40, 1}; enc(fn, &M.h, d_in[4], 3, d, s, b, CU_TENSOR_MAP_SWIZZLE_NONE); }
  { const cuuint64_t d[2] = {2048, 1024}, s[1] = {UCH}; const cuuint32_t b[2] = {64, 128}; enc(fn, &M.z, zptr, 2, d, s, b, CU_TENSOR_MAP_SWIZZLE_128B); }
  { const cuuint64_t d[2] = {512, 512 * 16}, s[1] = {2048}; const cuuint32_t b[2] = {256, 8};
    enc(fn, &M.ctx, tptr, 2, d, s, b, CU_TENSOR_MAP_SWIZZLE_NONE, CU_TENSOR_MAP_DATA_TYPE_UINT32); }
  { const cuuint64_t d[4] = {1024, 2, 256, 4}, s[3] = {2048, 16384, 4096}; const cuuint32_t b[4] = {64, 2, 9, 4};
    enc(fn, &M.k, d_in[1], 4, d, s, b, CU_TENSOR_MAP_SWIZZLE_128B); enc(fn, &M.v, d_in[2], 4, d, s, b, CU_TENSOR_MAP_SWIZZLE_128B); }
  Params P{(const __nv_bfloat16*)d_in[0], (const __nv_bfloat16*)d_in[3],
           (const __nv_bfloat16*)d_in[5], (const __nv_bfloat16*)d_in[12],
           (const __nv_bfloat16*)d_in[9], (const __nv_bfloat16*)d_in[10], (const __nv_bfloat16*)d_in[7], (__nv_bfloat16*)d_out};
  bool split = 2 * ncl < NCTA;
  if (!split) {
    gated_mix_kernel<PH_ALL><<<NCTA, 384, SMEM_BYTES>>>(M, P);
  } else {
    gated_mix_kernel<PH_PRE | PH_KV><<<NCTA, 384, SMEM_BYTES>>>(M, P);
    gated_mix_kernel<PH_ATT | PH_CONV><<<NCTA, 384, SMEM_BYTES>>>(M, P);
    gated_mix_kernel<PH_OUT><<<NCTA, 384, SMEM_BYTES>>>(M, P);
  }
}
```

```cpp
#include <cuda_runtime.h>
#include <cuda.h>
#include <cuda_bf16.h>
#include <stdint.h>

template<int TB> __device__ __forceinline__ void wgmma_ss_n256(float (&d)[128], uint64_t da, uint64_t db, int scale_d) {
  asm volatile("{\n.reg .pred p;\nsetp.ne.b32 p, %130, 0;\n"
    "wgmma.mma_async.sync.aligned.m64n256k16.f32.bf16.bf16 {%0, %1, %2, %3, %4, %5, %6, %7, %8, %9, %10, %11, %12, %13, %14, %15, %16, %17, %18, %19, %20, %21, %22, %23, %24, %25, %26, %27, %28, %29, %30, %31, %32, %33, %34, %35, %36, %37, %38, %39, %40, %41, %42, %43, %44, %45, %46, %47, %48, %49, %50, %51, %52, %53, %54, %55, %56, %57, %58, %59, %60, %61, %62, %63, %64, %65, %66, %67, %68, %69, %70, %71, %72, %73, %74, %75, %76, %77, %78, %79, %80, %81, %82, %83, %84, %85, %86, %87, %88, %89, %90, %91, %92, %93, %94, %95, %96, %97, %98, %99, %100, %101, %102, %103, %104, %105, %106, %107, %108, %109, %110, %111, %112, %113, %114, %115, %116, %117, %118, %119, %120, %121, %122, %123, %124, %125, %126, %127}, %128, %129, p, 1, 1, 0, %131;\n}\n"
    : "+f"(d[0]), "+f"(d[1]), "+f"(d[2]), "+f"(d[3]), "+f"(d[4]), "+f"(d[5]), "+f"(d[6]), "+f"(d[7]), "+f"(d[8]), "+f"(d[9]), "+f"(d[10]), "+f"(d[11]), "+f"(d[12]), "+f"(d[13]), "+f"(d[14]), "+f"(d[15]), "+f"(d[16]), "+f"(d[17]), "+f"(d[18]), "+f"(d[19]), "+f"(d[20]), "+f"(d[21]), "+f"(d[22]), "+f"(d[23]), "+f"(d[24]), "+f"(d[25]), "+f"(d[26]), "+f"(d[27]), "+f"(d[28]), "+f"(d[29]), "+f"(d[30]), "+f"(d[31]), "+f"(d[32]), "+f"(d[33]), "+f"(d[34]), "+f"(d[35]), "+f"(d[36]), "+f"(d[37]), "+f"(d[38]), "+f"(d[39]), "+f"(d[40]), "+f"(d[41]), "+f"(d[42]), "+f"(d[43]), "+f"(d[44]), "+f"(d[45]), "+f"(d[46]), "+f"(d[47]), "+f"(d[48]), "+f"(d[49]), "+f"(d[50]), "+f"(d[51]), "+f"(d[52]), "+f"(d[53]), "+f"(d[54]), "+f"(d[55]), "+f"(d[56]), "+f"(d[57]), "+f"(d[58]), "+f"(d[59]), "+f"(d[60]), "+f"(d[61]), "+f"(d[62]), "+f"(d[63]), "+f"(d[64]), "+f"(d[65]), "+f"(d[66]), "+f"(d[67]), "+f"(d[68]), "+f"(d[69]), "+f"(d[70]), "+f"(d[71]), "+f"(d[72]), "+f"(d[73]), "+f"(d[74]), "+f"(d[75]), "+f"(d[76]), "+f"(d[77]), "+f"(d[78]), "+f"(d[79]), "+f"(d[80]), "+f"(d[81]), "+f"(d[82]), "+f"(d[83]), "+f"(d[84]), "+f"(d[85]), "+f"(d[86]), "+f"(d[87]), "+f"(d[88]), "+f"(d[89]), "+f"(d[90]), "+f"(d[91]), "+f"(d[92]), "+f"(d[93]), "+f"(d[94]), "+f"(d[95]), "+f"(d[96]), "+f"(d[97]), "+f"(d[98]), "+f"(d[99]), "+f"(d[100]), "+f"(d[101]), "+f"(d[102]), "+f"(d[103]), "+f"(d[104]), "+f"(d[105]), "+f"(d[106]), "+f"(d[107]), "+f"(d[108]), "+f"(d[109]), "+f"(d[110]), "+f"(d[111]), "+f"(d[112]), "+f"(d[113]), "+f"(d[114]), "+f"(d[115]), "+f"(d[116]), "+f"(d[117]), "+f"(d[118]), "+f"(d[119]), "+f"(d[120]), "+f"(d[121]), "+f"(d[122]), "+f"(d[123]), "+f"(d[124]), "+f"(d[125]), "+f"(d[126]), "+f"(d[127])
    : "l"(da), "l"(db), "r"(scale_d), "n"(TB));
}
template<int TB> __device__ __forceinline__ void wgmma_ss_n128(float (&d)[64], uint64_t da, uint64_t db, int scale_d) {
  asm volatile("{\n.reg .pred p;\nsetp.ne.b32 p, %66, 0;\n"
    "wgmma.mma_async.sync.aligned.m64n128k16.f32.bf16.bf16 {%0, %1, %2, %3, %4, %5, %6, %7, %8, %9, %10, %11, %12, %13, %14, %15, %16, %17, %18, %19, %20, %21, %22, %23, %24, %25, %26, %27, %28, %29, %30, %31, %32, %33, %34, %35, %36, %37, %38, %39, %40, %41, %42, %43, %44, %45, %46, %47, %48, %49, %50, %51, %52, %53, %54, %55, %56, %57, %58, %59, %60, %61, %62, %63}, %64, %65, p, 1, 1, 0, %67;\n}\n"
    : "+f"(d[0]), "+f"(d[1]), "+f"(d[2]), "+f"(d[3]), "+f"(d[4]), "+f"(d[5]), "+f"(d[6]), "+f"(d[7]), "+f"(d[8]), "+f"(d[9]), "+f"(d[10]), "+f"(d[11]), "+f"(d[12]), "+f"(d[13]), "+f"(d[14]), "+f"(d[15]), "+f"(d[16]), "+f"(d[17]), "+f"(d[18]), "+f"(d[19]), "+f"(d[20]), "+f"(d[21]), "+f"(d[22]), "+f"(d[23]), "+f"(d[24]), "+f"(d[25]), "+f"(d[26]), "+f"(d[27]), "+f"(d[28]), "+f"(d[29]), "+f"(d[30]), "+f"(d[31]), "+f"(d[32]), "+f"(d[33]), "+f"(d[34]), "+f"(d[35]), "+f"(d[36]), "+f"(d[37]), "+f"(d[38]), "+f"(d[39]), "+f"(d[40]), "+f"(d[41]), "+f"(d[42]), "+f"(d[43]), "+f"(d[44]), "+f"(d[45]), "+f"(d[46]), "+f"(d[47]), "+f"(d[48]), "+f"(d[49]), "+f"(d[50]), "+f"(d[51]), "+f"(d[52]), "+f"(d[53]), "+f"(d[54]), "+f"(d[55]), "+f"(d[56]), "+f"(d[57]), "+f"(d[58]), "+f"(d[59]), "+f"(d[60]), "+f"(d[61]), "+f"(d[62]), "+f"(d[63])
    : "l"(da), "l"(db), "r"(scale_d), "n"(TB));
}
template<int TB> __device__ __forceinline__ void wgmma_rs_n32(float (&d)[16], uint32_t a0, uint32_t a1, uint32_t a2, uint32_t a3, uint64_t db, int scale_d) {
  asm volatile("{\n.reg .pred p;\nsetp.ne.b32 p, %21, 0;\n"
    "wgmma.mma_async.sync.aligned.m64n32k16.f32.bf16.bf16 {%0, %1, %2, %3, %4, %5, %6, %7, %8, %9, %10, %11, %12, %13, %14, %15}, {%16, %17, %18, %19}, %20, p, 1, 1, %22;\n}\n"
    : "+f"(d[0]), "+f"(d[1]), "+f"(d[2]), "+f"(d[3]), "+f"(d[4]), "+f"(d[5]), "+f"(d[6]), "+f"(d[7]), "+f"(d[8]), "+f"(d[9]), "+f"(d[10]), "+f"(d[11]), "+f"(d[12]), "+f"(d[13]), "+f"(d[14]), "+f"(d[15])
    : "r"(a0), "r"(a1), "r"(a2), "r"(a3), "l"(db), "r"(scale_d), "n"(TB));
}
__device__ __forceinline__ void wgmma_pv_sel(float (&d)[64], const uint32_t (&p)[32], uint64_t db, int full, int acc, int wg) {
  asm volatile("{\n.reg .pred q, s, w;\n.reg .b64 t;\nsetp.eq.b32 w, %99, 0;\nsetp.ne.b32 s, %98, 0;\nsetp.eq.b32 q, %97, 0;\n@q bra.uni LH;\n"
    "wgmma.fence.sync.aligned;\n"
    "add.s64 t, %96, 0;\nwgmma.mma_async.sync.aligned.m64n128k16.f32.bf16.bf16 {%0, %1, %2, %3, %4, %5, %6, %7, %8, %9, %10, %11, %12, %13, %14, %15, %16, %17, %18, %19, %20, %21, %22, %23, %24, %25, %26, %27, %28, %29, %30, %31, %32, %33, %34, %35, %36, %37, %38, %39, %40, %41, %42, %43, %44, %45, %46, %47, %48, %49, %50, %51, %52, %53, %54, %55, %56, %57, %58, %59, %60, %61, %62, %63}, {%64, %65, %66, %67}, t, s, 1, 1, 1;\n"
    "add.s64 t, %96, 256;\nwgmma.mma_async.sync.aligned.m64n128k16.f32.bf16.bf16 {%0, %1, %2, %3, %4, %5, %6, %7, %8, %9, %10, %11, %12, %13, %14, %15, %16, %17, %18, %19, %20, %21, %22, %23, %24, %25, %26, %27, %28, %29, %30, %31, %32, %33, %34, %35, %36, %37, %38, %39, %40, %41, %42, %43, %44, %45, %46, %47, %48, %49, %50, %51, %52, %53, %54, %55, %56, %57, %58, %59, %60, %61, %62, %63}, {%68, %69, %70, %71}, t, 1, 1, 1, 1;\n"
    "add.s64 t, %96, 512;\nwgmma.mma_async.sync.aligned.m64n128k16.f32.bf16.bf16 {%0, %1, %2, %3, %4, %5, %6, %7, %8, %9, %10, %11, %12, %13, %14, %15, %16, %17, %18, %19, %20, %21, %22, %23, %24, %25, %26, %27, %28, %29, %30, %31, %32, %33, %34, %35, %36, %37, %38, %39, %40, %41, %42, %43, %44, %45, %46, %47, %48, %49, %50, %51, %52, %53, %54, %55, %56, %57, %58, %59, %60, %61, %62, %63}, {%72, %73, %74, %75}, t, 1, 1, 1, 1;\n"
    "add.s64 t, %96, 768;\nwgmma.mma_async.sync.aligned.m64n128k16.f32.bf16.bf16 {%0, %1, %2, %3, %4, %5, %6, %7, %8, %9, %10, %11, %12, %13, %14, %15, %16, %17, %18, %19, %20, %21, %22, %23, %24, %25, %26, %27, %28, %29, %30, %31, %32, %33, %34, %35, %36, %37, %38, %39, %40, %41, %42, %43, %44, %45, %46, %47, %48, %49, %50, %51, %52, %53, %54, %55, %56, %57, %58, %59, %60, %61, %62, %63}, {%76, %77, %78, %79}, t, 1, 1, 1, 1;\n"
    "add.s64 t, %96, 1024;\nwgmma.mma_async.sync.aligned.m64n128k16.f32.bf16.bf16 {%0, %1, %2, %3, %4, %5, %6, %7, %8, %9, %10, %11, %12, %13, %14, %15, %16, %17, %18, %19, %20, %21, %22, %23, %24, %25, %26, %27, %28, %29, %30, %31, %32, %33, %34, %35, %36, %37, %38, %39, %40, %41, %42, %43, %44, %45, %46, %47, %48, %49, %50, %51, %52, %53, %54, %55, %56, %57, %58, %59, %60, %61, %62, %63}, {%80, %81, %82, %83}, t, 1, 1, 1, 1;\n"
    "add.s64 t, %96, 1280;\nwgmma.mma_async.sync.aligned.m64n128k16.f32.bf16.bf16 {%0, %1, %2, %3, %4, %5, %6, %7, %8, %9, %10, %11, %12, %13, %14, %15, %16, %17, %18, %19, %20, %21, %22, %23, %24, %25, %26, %27, %28, %29, %30, %31, %32, %33, %34, %35, %36, %37, %38, %39, %40, %41, %42, %43, %44, %45, %46, %47, %48, %49, %50, %51, %52, %53, %54, %55, %56, %57, %58, %59, %60, %61, %62, %63}, {%84, %85, %86, %87}, t, 1, 1, 1, 1;\n"
    "@w bar.arrive 2, 256;\n@!w bar.arrive 1, 256;\n"
    "add.s64 t, %96, 1536;\nwgmma.mma_async.sync.aligned.m64n128k16.f32.bf16.bf16 {%0, %1, %2, %3, %4, %5, %6, %7, %8, %9, %10, %11, %12, %13, %14, %15, %16, %17, %18, %19, %20, %21, %22, %23, %24, %25, %26, %27, %28, %29, %30, %31, %32, %33, %34, %35, %36, %37, %38, %39, %40, %41, %42, %43, %44, %45, %46, %47, %48, %49, %50, %51, %52, %53, %54, %55, %56, %57, %58, %59, %60, %61, %62, %63}, {%88, %89, %90, %91}, t, 1, 1, 1, 1;\n"
    "add.s64 t, %96, 1792;\nwgmma.mma_async.sync.aligned.m64n128k16.f32.bf16.bf16 {%0, %1, %2, %3, %4, %5, %6, %7, %8, %9, %10, %11, %12, %13, %14, %15, %16, %17, %18, %19, %20, %21, %22, %23, %24, %25, %26, %27, %28, %29, %30, %31, %32, %33, %34, %35, %36, %37, %38, %39, %40, %41, %42, %43, %44, %45, %46, %47, %48, %49, %50, %51, %52, %53, %54, %55, %56, %57, %58, %59, %60, %61, %62, %63}, {%92, %93, %94, %95}, t, 1, 1, 1, 1;\n"
    "wgmma.commit_group.sync.aligned;\n"
    "bra.uni LE;\nLH:\n"
    "wgmma.fence.sync.aligned;\n"
    "add.s64 t, %96, 0;\nwgmma.mma_async.sync.aligned.m64n128k16.f32.bf16.bf16 {%0, %1, %2, %3, %4, %5, %6, %7, %8, %9, %10, %11, %12, %13, %14, %15, %16, %17, %18, %19, %20, %21, %22, %23, %24, %25, %26, %27, %28, %29, %30, %31, %32, %33, %34, %35, %36, %37, %38, %39, %40, %41, %42, %43, %44, %45, %46, %47, %48, %49, %50, %51, %52, %53, %54, %55, %56, %57, %58, %59, %60, %61, %62, %63}, {%80, %81, %82, %83}, t, s, 1, 1, 1;\n"
    "add.s64 t, %96, 256;\nwgmma.mma_async.sync.aligned.m64n128k16.f32.bf16.bf16 {%0, %1, %2, %3, %4, %5, %6, %7, %8, %9, %10, %11, %12, %13, %14, %15, %16, %17, %18, %19, %20, %21, %22, %23, %24, %25, %26, %27, %28, %29, %30, %31, %32, %33, %34, %35, %36, %37, %38, %39, %40, %41, %42, %43, %44, %45, %46, %47, %48, %49, %50, %51, %52, %53, %54, %55, %56, %57, %58, %59, %60, %61, %62, %63}, {%84, %85, %86, %87}, t, 1, 1, 1, 1;\n"
    "@w bar.arrive 2, 256;\n@!w bar.arrive 1, 256;\n"
    "add.s64 t, %96, 512;\nwgmma.mma_async.sync.aligned.m64n128k16.f32.bf16.bf16 {%0, %1, %2, %3, %4, %5, %6, %7, %8, %9, %10, %11, %12, %13, %14, %15, %16, %17, %18, %19, %20, %21, %22, %23, %24, %25, %26, %27, %28, %29, %30, %31, %32, %33, %34, %35, %36, %37, %38, %39, %40, %41, %42, %43, %44, %45, %46, %47, %48, %49, %50, %51, %52, %53, %54, %55, %56, %57, %58, %59, %60, %61, %62, %63}, {%88, %89, %90, %91}, t, 1, 1, 1, 1;\n"
    "add.s64 t, %96, 768;\nwgmma.mma_async.sync.aligned.m64n128k16.f32.bf16.bf16 {%0, %1, %2, %3, %4, %5, %6, %7, %8, %9, %10, %11, %12, %13, %14, %15, %16, %17, %18, %19, %20, %21, %22, %23, %24, %25, %26, %27, %28, %29, %30, %31, %32, %33, %34, %35, %36, %37, %38, %39, %40, %41, %42, %43, %44, %45, %46, %47, %48, %49, %50, %51, %52, %53, %54, %55, %56, %57, %58, %59, %60, %61, %62, %63}, {%92, %93, %94, %95}, t, 1, 1, 1, 1;\n"
    "wgmma.commit_group.sync.aligned;\n"
    "LE:\n}\n"
    : "+f"(d[0]), "+f"(d[1]), "+f"(d[2]), "+f"(d[3]), "+f"(d[4]), "+f"(d[5]), "+f"(d[6]), "+f"(d[7]), "+f"(d[8]), "+f"(d[9]), "+f"(d[10]), "+f"(d[11]), "+f"(d[12]), "+f"(d[13]), "+f"(d[14]), "+f"(d[15]), "+f"(d[16]), "+f"(d[17]), "+f"(d[18]), "+f"(d[19]), "+f"(d[20]), "+f"(d[21]), "+f"(d[22]), "+f"(d[23]), "+f"(d[24]), "+f"(d[25]), "+f"(d[26]), "+f"(d[27]), "+f"(d[28]), "+f"(d[29]), "+f"(d[30]), "+f"(d[31]), "+f"(d[32]), "+f"(d[33]), "+f"(d[34]), "+f"(d[35]), "+f"(d[36]), "+f"(d[37]), "+f"(d[38]), "+f"(d[39]), "+f"(d[40]), "+f"(d[41]), "+f"(d[42]), "+f"(d[43]), "+f"(d[44]), "+f"(d[45]), "+f"(d[46]), "+f"(d[47]), "+f"(d[48]), "+f"(d[49]), "+f"(d[50]), "+f"(d[51]), "+f"(d[52]), "+f"(d[53]), "+f"(d[54]), "+f"(d[55]), "+f"(d[56]), "+f"(d[57]), "+f"(d[58]), "+f"(d[59]), "+f"(d[60]), "+f"(d[61]), "+f"(d[62]), "+f"(d[63])
    : "r"(p[0]), "r"(p[1]), "r"(p[2]), "r"(p[3]), "r"(p[4]), "r"(p[5]), "r"(p[6]), "r"(p[7]), "r"(p[8]), "r"(p[9]), "r"(p[10]), "r"(p[11]), "r"(p[12]), "r"(p[13]), "r"(p[14]), "r"(p[15]), "r"(p[16]), "r"(p[17]), "r"(p[18]), "r"(p[19]), "r"(p[20]), "r"(p[21]), "r"(p[22]), "r"(p[23]), "r"(p[24]), "r"(p[25]), "r"(p[26]), "r"(p[27]), "r"(p[28]), "r"(p[29]), "r"(p[30]), "r"(p[31]), "l"(db), "r"(full), "r"(acc), "r"(wg) : "memory");
}

constexpr int NCTA = 132, NREG = 128;
constexpr int UNIT = 16384, NUNIT = 14;
constexpr uint32_t SMEM_BASE = 1024;
constexpr int SM_BAR = NUNIT * UNIT;
constexpr int SM_GATE = SM_BAR + 1024;
constexpr int SMEM_BYTES = SM_BAR + 1536;
constexpr int UPITCH = 4160, UCH = 2 * UPITCH;
constexpr float QSCALE = 0.08838834764831845f * 1.4426950408889634f;
constexpr float BOUND2 = 60.f * 60.f / 1.15f;
#define NSKIP 8
constexpr int C_KV = 0;
constexpr int C_CTX = 32;
constexpr int C_U = 48;
constexpr int C_Z = 80;
constexpr int C_GATE = 88;
constexpr int C_EXIT = 89, C_TICKET = 90;
#define ATT_SPLIT 4
#define SL_BAR 256
#define SL_CNT 0
#define PF_WAIT 6
#define PF_GAP 300
#define TK 24
#define Z_AT 60
#define PRE_SLEEP 300
#define GATE_SLEEP 1000
#define OC_S0 2
#define OC_S1 11
#define OC_L0 18
#define OC_L1 18
#define ST_1 4
#define ST_D 2
#define SCH_KV 0x7766555443322100ull
#define SCH_Q 0x7766555443322100ull
#define NK_AT 1
#define NV_AT 3
#define CHK_D 11
#define FGAP 600
#define FGAP2 200
constexpr int PRE_EARLY = 2, NFIRST = 4;
constexpr int C_WAR = 96;
constexpr int C_NUM = 112;
constexpr int CSTRIDE = 32;
constexpr int SM_KMAX = SM_BAR + 640, SM_DUMMY = SM_BAR + 648, SM_POOL = SM_BAR + 652, SM_PRE = SM_BAR + 112, SM_SIG = SM_BAR + 256, SM_RDY = SM_BAR + 384;
enum { SIG_KV = 0, SIG_CTX = 2, SIG_Z = 4, SIG_DONE = 8, SIG_WAR = 9, SIG_ATT = 10 };
enum { RDY_KV = 0, RDY_CTX = 2, RDY_WAR = 4, RDY_G = 5, RDY_X = 6, RDY_AUX = 7, RDY_U = 8, RDY_Z = 9, RDY_T = 10, RDY_DRAW = 11 };
enum { PH_PRE = 1, PH_KV = 2, PH_ATT = 4, PH_CONV = 8, PH_OUT = 16, PH_ALL = 31 };

constexpr uint32_t T_CTX = 0, T_KV = 16 * 32 * 32768, T_BYTES = T_KV + 32 * 16 * 65536;
__device__ __align__(1024) uint8_t g_T[T_BYTES];
__device__ __align__(1024) uint8_t g_u[1024 * UCH];
__device__ __align__(1024) float g_gate[2048];
__device__ __align__(1024) float g_kn2[32 * 128];
__device__ __align__(1024) unsigned g_cnt[C_NUM * CSTRIDE];

struct __align__(64) Maps { CUtensorMap c, wk, wv, x, wq, wo, h, z, ctx, k, v; };
struct Params {
  const __nv_bfloat16 *x, *shift, *D, *gw, *wk, *wv, *c;
  __nv_bfloat16* out;
};

__device__ __forceinline__ void wg_fence() { asm volatile("wgmma.fence.sync.aligned;" ::: "memory"); }
__device__ __forceinline__ void wg_commit() { asm volatile("wgmma.commit_group.sync.aligned;" ::: "memory"); }
template<int N> __device__ __forceinline__ void wg_wait() { asm volatile("wgmma.wait_group.sync.aligned %0;" :: "n"(N) : "memory"); }
__device__ __forceinline__ uint64_t odesc(uint32_t addr, uint32_t lbo, uint32_t sbo, uint32_t swz) {
  uint64_t d = (uint64_t)(addr >> 4) + (((uint64_t)(lbo >> 4) << 16) | ((uint64_t)(sbo >> 4) << 32) | ((uint64_t)swz << 62));
  asm volatile("" : "+l"(d));
  return d;
}
__device__ __forceinline__ void mbar_init(uint32_t bar, int cnt) { asm volatile("mbarrier.init.shared::cta.b64 [%0], %1;" :: "r"(bar), "r"(cnt)); }
__device__ __forceinline__ void mbar_expect(uint32_t bar, uint32_t bytes) { asm volatile("mbarrier.arrive.expect_tx.shared::cta.b64 _, [%0], %1;" :: "r"(bar), "r"(bytes) : "memory"); }
__device__ __forceinline__ void mbar_arrive(uint32_t bar) { asm volatile("mbarrier.arrive.shared::cta.b64 _, [%0];" :: "r"(bar) : "memory"); }
__device__ __forceinline__ void mbar_wait(uint32_t bar, uint32_t parity) {
  asm volatile("{\n.reg .pred p;\nLW:\nmbarrier.try_wait.parity.shared::cta.b64 p, [%0], %1;\n@!p bra LW;\n}\n" :: "r"(bar), "r"(parity) : "memory");
}
template<int NS = SL_BAR> __device__ __forceinline__ void mbar_wait_slow(uint32_t bar, uint32_t parity) {
  asm volatile("{\n.reg .pred p;\n.reg .u32 n;\nmov.u32 n, 0;\n"
    "LW:\nmbarrier.test_wait.parity.shared::cta.b64 p, [%0], %1;\n@p bra LD;\n"
    "nanosleep.u32 %2;\nadd.u32 n, n, 1;\nsetp.lt.u32 p, n, 16777216;\n@p bra LW;\ntrap;\nLD:\n}\n" :: "r"(bar), "r"(parity), "n"(NS) : "memory");
}
__device__ __forceinline__ void mbar_wait_all(uint32_t bar, uint32_t parity) {
  asm volatile("{\n.reg .pred p, q;\nLW:\nmbarrier.try_wait.parity.shared::cta.b64 p, [%0], %1;\nvote.sync.all.pred q, p, 0xffffffff;\n@!q bra.uni LW;\n}\n" :: "r"(bar), "r"(parity) : "memory");
}
__device__ __forceinline__ void cnt_wait(const unsigned* p, unsigned target) {
  asm volatile("{\n.reg .pred p;\n.reg .u32 n, v;\nmov.u32 n, 0;\n"
    "LW:\nld.relaxed.gpu.global.u32 v, [%0];\nsetp.ge.u32 p, v, %1;\n@p bra LD;\n"
    "nanosleep.u32 %2;\nadd.u32 n, n, 1;\nsetp.lt.u32 p, n, 4194304;\n@p bra LW;\ntrap;\nLD:\nfence.acquire.gpu;\nfence.proxy.async.global;\n}\n" :: "l"(p), "r"(target), "n"(SL_CNT) : "memory");
}
__device__ __forceinline__ void cnt_signal(unsigned* p, int lane) {
  __syncwarp();
  if (lane == 0) asm volatile("red.release.gpu.global.add.u32 [%0], 1;" :: "l"(p) : "memory");
}
__device__ __forceinline__ void cnt_publish(unsigned* p, unsigned n, bool fence) {
  if (fence) asm volatile("fence.release.gpu;" ::: "memory");
  asm volatile("red.relaxed.gpu.global.add.u32 [%0], %1;" :: "l"(p), "r"(n) : "memory");
}
__device__ __forceinline__ uint64_t pol_first() { uint64_t p; asm("createpolicy.fractional.L2::evict_first.b64 %0, 1.0;" : "=l"(p)); return p; }
__device__ __forceinline__ void bulk_g2s(uint32_t dst, const void* src, uint32_t bytes, uint32_t bar, bool stream = false) {
  if (stream) asm volatile("cp.async.bulk.shared::cluster.global.mbarrier::complete_tx::bytes.L2::cache_hint [%0], [%1], %2, [%3], %4;" :: "r"(dst), "l"(src), "r"(bytes), "r"(bar), "l"(pol_first()) : "memory");
  else asm volatile("cp.async.bulk.shared::cluster.global.mbarrier::complete_tx::bytes [%0], [%1], %2, [%3];" :: "r"(dst), "l"(src), "r"(bytes), "r"(bar) : "memory");
}
__device__ __forceinline__ void tma2d(uint32_t dst, const CUtensorMap* m, int x, int y, uint32_t bar, bool stream = false) {
  if (stream) asm volatile("cp.async.bulk.tensor.2d.shared::cluster.global.mbarrier::complete_tx::bytes.L2::cache_hint [%0], [%1, {%3, %4}], [%2], %5;" :: "r"(dst), "l"(m), "r"(bar), "r"(x), "r"(y), "l"(pol_first()) : "memory");
  else asm volatile("cp.async.bulk.tensor.2d.shared::cluster.global.mbarrier::complete_tx::bytes [%0], [%1, {%3, %4}], [%2];" :: "r"(dst), "l"(m), "r"(bar), "r"(x), "r"(y) : "memory");
}
__device__ __forceinline__ void tma3d(uint32_t dst, const CUtensorMap* m, int x, int y, int z, uint32_t bar, bool stream = false) {
  if (stream) asm volatile("cp.async.bulk.tensor.3d.shared::cluster.global.mbarrier::complete_tx::bytes.L2::cache_hint [%0], [%1, {%3, %4, %5}], [%2], %6;" :: "r"(dst), "l"(m), "r"(bar), "r"(x), "r"(y), "r"(z), "l"(pol_first()) : "memory");
  else asm volatile("cp.async.bulk.tensor.3d.shared::cluster.global.mbarrier::complete_tx::bytes [%0], [%1, {%3, %4, %5}], [%2];" :: "r"(dst), "l"(m), "r"(bar), "r"(x), "r"(y), "r"(z) : "memory");
}
__device__ __forceinline__ void tma4d(uint32_t dst, const CUtensorMap* m, int x, int y, int z, int w, uint32_t bar, bool stream = false) {
  if (stream) asm volatile("cp.async.bulk.tensor.4d.shared::cluster.global.mbarrier::complete_tx::bytes.L2::cache_hint [%0], [%1, {%3, %4, %5, %6}], [%2], %7;" :: "r"(dst), "l"(m), "r"(bar), "r"(x), "r"(y), "r"(z), "r"(w), "l"(pol_first()) : "memory");
  else asm volatile("cp.async.bulk.tensor.4d.shared::cluster.global.mbarrier::complete_tx::bytes [%0], [%1, {%3, %4, %5, %6}], [%2];" :: "r"(dst), "l"(m), "r"(bar), "r"(x), "r"(y), "r"(z), "r"(w) : "memory");
}
__device__ __forceinline__ void bulk_g2s_mc(uint32_t dst, const void* src, uint32_t bytes, uint32_t bar, bool stream = false) {
  if (stream) asm volatile("cp.async.bulk.shared::cluster.global.mbarrier::complete_tx::bytes.multicast::cluster.L2::cache_hint [%0], [%1], %2, [%3], %4, %5;" :: "r"(dst), "l"(src), "r"(bytes), "r"(bar), "h"((uint16_t)3), "l"(pol_first()) : "memory");
  else asm volatile("cp.async.bulk.shared::cluster.global.mbarrier::complete_tx::bytes.multicast::cluster [%0], [%1], %2, [%3], %4;" :: "r"(dst), "l"(src), "r"(bytes), "r"(bar), "h"((uint16_t)3) : "memory");
}
__device__ __forceinline__ void tma2d_mc(uint32_t dst, const CUtensorMap* m, int x, int y, uint32_t bar, bool stream = false) {
  if (stream) asm volatile("cp.async.bulk.tensor.2d.shared::cluster.global.mbarrier::complete_tx::bytes.multicast::cluster.L2::cache_hint [%0], [%1, {%3, %4}], [%2], %5, %6;" :: "r"(dst), "l"(m), "r"(bar), "r"(x), "r"(y), "h"((uint16_t)3), "l"(pol_first()) : "memory");
  else asm volatile("cp.async.bulk.tensor.2d.shared::cluster.global.mbarrier::complete_tx::bytes.multicast::cluster [%0], [%1, {%3, %4}], [%2], %5;" :: "r"(dst), "l"(m), "r"(bar), "r"(x), "r"(y), "h"((uint16_t)3) : "memory");
}
__device__ __forceinline__ void tma3d_mc(uint32_t dst, const CUtensorMap* m, int x, int y, int z, uint32_t bar, bool stream = false) {
  if (stream) asm volatile("cp.async.bulk.tensor.3d.shared::cluster.global.mbarrier::complete_tx::bytes.multicast::cluster.L2::cache_hint [%0], [%1, {%3, %4, %5}], [%2], %6, %7;" :: "r"(dst), "l"(m), "r"(bar), "r"(x), "r"(y), "r"(z), "h"((uint16_t)3), "l"(pol_first()) : "memory");
  else asm volatile("cp.async.bulk.tensor.3d.shared::cluster.global.mbarrier::complete_tx::bytes.multicast::cluster [%0], [%1, {%3, %4, %5}], [%2], %6;" :: "r"(dst), "l"(m), "r"(bar), "r"(x), "r"(y), "r"(z), "h"((uint16_t)3) : "memory");
}
__device__ __forceinline__ void map_pf(const CUtensorMap* m) { asm volatile("prefetch.tensormap [%0];" :: "l"(m) : "memory"); }
__device__ __forceinline__ bool elect() {
  uint32_t r; asm volatile("{\n.reg .pred p;\nelect.sync _|p, 0xffffffff;\nselp.u32 %0, 1, 0, p;\n}\n" : "=r"(r)); return r != 0;
}
__device__ __forceinline__ void cluster_arrive() { asm volatile("barrier.cluster.arrive;" ::: "memory"); }
__device__ __forceinline__ void cluster_wait() { asm volatile("barrier.cluster.wait;" ::: "memory"); }
__device__ __forceinline__ void bar_sync(int id, int n) { asm volatile("bar.sync %0, %1;" :: "r"(id), "r"(n) : "memory"); }
__device__ __forceinline__ void bar_arrive(int id, int n) { asm volatile("bar.arrive %0, %1;" :: "r"(id), "r"(n) : "memory"); }
__device__ __forceinline__ void fence_async_smem() { asm volatile("fence.proxy.async.shared::cta;" ::: "memory"); }
__device__ __forceinline__ float ex2(float x) { float y; asm("ex2.approx.ftz.f32 %0, %1;" : "=f"(y) : "f"(x)); return y; }
__device__ __forceinline__ float rcp(float x) { float y; asm("rcp.approx.ftz.f32 %0, %1;" : "=f"(y) : "f"(x)); return y; }
__device__ __forceinline__ uint32_t pack_bf16(float lo, float hi) { uint32_t r; asm("cvt.rn.bf16x2.f32 %0, %1, %2;" : "=r"(r) : "f"(hi), "f"(lo)); return r; }
__device__ __forceinline__ uint32_t hmul2(uint32_t a, uint32_t b) { uint32_t r; asm("mul.rn.bf16x2 %0, %1, %2;" : "=r"(r) : "r"(a), "r"(b)); return r; }
__device__ __forceinline__ uint32_t hadd2(uint32_t a, uint32_t b) { uint32_t r; asm("add.rn.bf16x2 %0, %1, %2;" : "=r"(r) : "r"(a), "r"(b)); return r; }
__device__ __forceinline__ uint32_t hfma2(uint32_t a, uint32_t b, uint32_t c) { uint32_t r; asm("fma.rn.bf16x2 %0, %1, %2, %3;" : "=r"(r) : "r"(a), "r"(b), "r"(c)); return r; }
__device__ __forceinline__ float bf_lo(uint32_t a) { return __uint_as_float(a << 16); }
__device__ __forceinline__ float bf_hi(uint32_t a) { return __uint_as_float(a & 0xffff0000u); }
__device__ __forceinline__ uint32_t lds32(uint32_t a) { uint32_t v; asm volatile("ld.shared.u32 %0, [%1];" : "=r"(v) : "r"(a) : "memory"); return v; }
__device__ __forceinline__ uint4 lds128(uint32_t a) { uint4 v; asm volatile("ld.shared.v4.u32 {%0,%1,%2,%3}, [%4];" : "=r"(v.x), "=r"(v.y), "=r"(v.z), "=r"(v.w) : "r"(a) : "memory"); return v; }
__device__ __forceinline__ void sts64f(uint32_t a, float x, float y) { asm volatile("st.shared.v2.f32 [%0], {%1,%2};" :: "r"(a), "f"(x), "f"(y) : "memory"); }
template<int OFF> __device__ __forceinline__ void sts128o(uint32_t a, uint4 v) { asm volatile("st.shared.v4.u32 [%0+%5], {%1,%2,%3,%4};" :: "r"(a), "r"(v.x), "r"(v.y), "r"(v.z), "r"(v.w), "n"(OFF) : "memory"); }
__device__ __forceinline__ void ldsm4(uint32_t a, uint32_t& r0, uint32_t& r1, uint32_t& r2, uint32_t& r3) {
  asm volatile("ldmatrix.sync.aligned.m8n8.x4.shared.b16 {%0,%1,%2,%3}, [%4];" : "=r"(r0), "=r"(r1), "=r"(r2), "=r"(r3) : "r"(a) : "memory");
}
__device__ __forceinline__ void ldsm4t(uint32_t a, uint32_t& r0, uint32_t& r1, uint32_t& r2, uint32_t& r3) {
  asm volatile("ldmatrix.sync.aligned.m8n8.x4.trans.shared.b16 {%0,%1,%2,%3}, [%4];" : "=r"(r0), "=r"(r1), "=r"(r2), "=r"(r3) : "r"(a) : "memory");
}
__device__ __forceinline__ void stsm4(uint32_t a, uint32_t r0, uint32_t r1, uint32_t r2, uint32_t r3) {
  asm volatile("stmatrix.sync.aligned.m8n8.x4.shared.b16 [%0], {%1,%2,%3,%4};" :: "r"(a), "r"(r0), "r"(r1), "r"(r2), "r"(r3) : "memory");
}
template<int N> __device__ __forceinline__ void fence_regs(float (&d)[N]) {
#pragma unroll
  for (int i = 0; i < N; i++) asm volatile("" : "+f"(d[i]) :: "memory");
}
template<int N> __device__ __forceinline__ void fence_regs(uint32_t (&d)[N]) {
#pragma unroll
  for (int i = 0; i < N; i++) asm volatile("" : "+r"(d[i]) :: "memory");
}
__device__ __forceinline__ void sched_fence(float x, uint32_t dummy) {
  asm volatile("{\n.reg .pred p;\nsetp.eq.u32 p, %0, 0x7fc12345;\n@p st.shared.u32 [%1], %0;\n}\n" :: "r"(__float_as_uint(x)), "r"(dummy) : "memory");
}

#define SHADOW if (gridDim.y == 1)

struct Prod {
  uint32_t base, mask; int lane;
  __device__ __forceinline__ uint32_t full(int u) const { return base + SM_BAR + 8 * u; }
  __device__ __forceinline__ uint32_t addr(int u) const { return base + u * UNIT; }
  __device__ __forceinline__ void acquire(int u, int n) {
    const int v = u + min(lane, n - 1);
    mbar_wait_all(base + SM_BAR + 128 + 8 * v, mask >> v);
    mask ^= ((1u << n) - 1) << u;
  }
  __device__ __forceinline__ void acquire_slow(int u, int n) {
    for (int i = 0; i < n; i++) mbar_wait_slow(base + SM_BAR + 128 + 8 * (u + i), mask >> (u + i));
    mask ^= ((1u << n) - 1) << u;
  }
};
struct Cons {
  uint32_t base, rel, mask; int lane, warp, wg, lr;
  __device__ __forceinline__ uint32_t addr(int u) const { return base + u * UNIT; }
  __device__ __forceinline__ static uint32_t daddr(int u) { return SMEM_BASE + u * UNIT; }
  __device__ __forceinline__ void wait(int u) { mbar_wait(base + SM_BAR + 8 * u, mask >> u); mask ^= 1u << u; }
  __device__ __forceinline__ void skip(int u) { mask ^= 1u << u; }
  __device__ __forceinline__ void release(int u, int n) {
    asm volatile("{\n.reg .pred p;\nsetp.lt.s32 p, %1, %2;\n@p mbarrier.arrive.shared::cluster.b64 _, [%0];\n}\n" :: "r"(rel + 8 * u), "r"(lr), "r"(n) : "memory");
  }
  __device__ __forceinline__ void release2(int u) {
    asm volatile("{\n.reg .pred p;\nsetp.eq.s32 p, %1, 0;\n@p mbarrier.arrive.shared::cluster.b64 _, [%0], 2;\n}\n" :: "r"(rel + 8 * u), "r"(lr) : "memory");
  }
  __device__ __forceinline__ void signal(int i) {
    __syncwarp();
    asm volatile("{\n.reg .pred p;\nsetp.eq.s32 p, %1, 0;\n@p mbarrier.arrive.shared::cta.b64 _, [%0];\n}\n" :: "r"(base + SM_SIG + 8 * i), "r"(lane) : "memory");
  }
  __device__ __forceinline__ void turn() { asm volatile("{\n.reg .pred p;\nsetp.eq.s32 p, %0, 0;\n@p bar.sync 1, 256;\n@!p bar.sync 2, 256;\n}\n" :: "r"(wg) : "memory"); }
  __device__ __forceinline__ void pass() { asm volatile("{\n.reg .pred p;\nsetp.eq.s32 p, %0, 0;\n@p bar.arrive 2, 256;\n@!p bar.arrive 1, 256;\n}\n" :: "r"(wg) : "memory"); }
  __device__ __forceinline__ void sync() { asm volatile("{\n.reg .pred p;\nsetp.eq.s32 p, %0, 0;\n@p bar.sync 3, 128;\n@!p bar.sync 4, 128;\n}\n" :: "r"(wg) : "memory"); }
};
__device__ __forceinline__ int gemm_unit(int ks) { return 3 * (ks & 3); }
template<int MASK> __device__ __forceinline__ int kv_slot(int h) { return MASK == PH_ALL ? h & 15 : h; }
__device__ __forceinline__ int out_mb(int cta) { return cta >> 3; }
__device__ __forceinline__ int out_nb(int cta) { return cta & 7; }
template<int MASK> constexpr int CV_REG = MASK == PH_ALL ? 4 : 6;
template<int MASK> constexpr int CV_EXTRA = MASK == PH_ALL ? 96 + NSKIP / 2 : 64;
constexpr int CV_POOL = 896 + 2 * NSKIP;
template<int MASK> __device__ __forceinline__ int conv_channel(int cta, int i) {
  return cta < NREG ? CV_EXTRA<MASK> * (NCTA - NREG) + cta * CV_REG<MASK> + i : (i >> 1) * 8 + (cta - NREG) * 2 + (i & 1);
}

template<int OFF, int N> __device__ __forceinline__ void pack_chunk(const float (&a)[N], float sc0, float sc1, uint4& v0, uint4& v1) {
  v0.x = pack_bf16(a[OFF + 0] * sc0, a[OFF + 1] * sc0); v0.y = pack_bf16(a[OFF + 4] * sc0, a[OFF + 5] * sc0);
  v0.z = pack_bf16(a[OFF + 8] * sc0, a[OFF + 9] * sc0); v0.w = pack_bf16(a[OFF + 12] * sc0, a[OFF + 13] * sc0);
  v1.x = pack_bf16(a[OFF + 2] * sc1, a[OFF + 3] * sc1); v1.y = pack_bf16(a[OFF + 6] * sc1, a[OFF + 7] * sc1);
  v1.z = pack_bf16(a[OFF + 10] * sc1, a[OFF + 11] * sc1); v1.w = pack_bf16(a[OFF + 14] * sc1, a[OFF + 15] * sc1);
}
template<int OFF, int N> __device__ __forceinline__ void pack_chunk(const float (&a)[N], uint4& v0, uint4& v1) {
  v0.x = pack_bf16(a[OFF + 0], a[OFF + 1]); v0.y = pack_bf16(a[OFF + 4], a[OFF + 5]);
  v0.z = pack_bf16(a[OFF + 8], a[OFF + 9]); v0.w = pack_bf16(a[OFF + 12], a[OFF + 13]);
  v1.x = pack_bf16(a[OFF + 2], a[OFF + 3]); v1.y = pack_bf16(a[OFF + 6], a[OFF + 7]);
  v1.z = pack_bf16(a[OFF + 10], a[OFF + 11]); v1.w = pack_bf16(a[OFF + 14], a[OFF + 15]);
}
__device__ __forceinline__ void sq_acc(const uint4& v, uint32_t& a) { a = hfma2(v.x, v.x, a); a = hfma2(v.y, v.y, a); a = hfma2(v.z, v.z, a); a = hfma2(v.w, v.w, a); }
template<bool ROWS> __device__ __forceinline__ float norm2_max(uint32_t a0, uint32_t a1) {
  float n0 = bf_lo(a0) + bf_hi(a0), n1 = bf_lo(a1) + bf_hi(a1);
  if (ROWS) {
    n0 += __shfl_xor_sync(~0u, n0, 1); n1 += __shfl_xor_sync(~0u, n1, 1);
    n0 += __shfl_xor_sync(~0u, n0, 2); n1 += __shfl_xor_sync(~0u, n1, 2);
  }
  return __uint_as_float(__reduce_max_sync(~0u, max(__float_as_uint(n0) & 0x7fffffffu, __float_as_uint(n1) & 0x7fffffffu)));
}

struct Pend { uint4 lo[8], hi[8]; };
__device__ __forceinline__ uint32_t ctx_off(const Cons& c, int h, int qb, int rowhalf) { return T_CTX + (qb * 32 + h) * 32768 + (rowhalf * 4 + c.warp) * 4096; }
__device__ __forceinline__ uint32_t kv_off(const Cons& c, int blk) { return T_KV + blk * 65536 + (c.wg * 4 + c.warp) * 4096; }
__device__ __forceinline__ void pin(uint4 (&v)[8]) {
#pragma unroll
  for (int i = 0; i < 8; i++) asm volatile("" : "+r"(v[i].x), "+r"(v[i].y), "+r"(v[i].z), "+r"(v[i].w) :: "memory");
}
__device__ __forceinline__ void pack_o(const float (&o)[64], float i0, float i1, uint4 (&v)[8]) {
  pack_chunk<0>(o, i0, i1, v[0], v[1]); pack_chunk<16>(o, i0, i1, v[2], v[3]);
  pack_chunk<32>(o, i0, i1, v[4], v[5]); pack_chunk<48>(o, i0, i1, v[6], v[7]);
  pin(v);
}
__device__ __forceinline__ uint32_t atom_off(int lane) { return (lane >> 2) * 64 + (((lane ^ (lane >> 3)) & 3) << 4); }
template<int J0, int J1> __device__ __forceinline__ void tile_store(const uint4 (&v)[8], uint32_t dst, int lane) {
  uint8_t* d = g_T + (dst + atom_off(lane));
#pragma unroll
  for (int j = J0; j < J1; j++) { *(uint4*)(d + j * 512) = v[2 * j]; *(uint4*)(d + j * 512 + 2048) = v[2 * j + 1]; }
}
template<int I0, int I1> __device__ __forceinline__ void tile_store_if(bool on, const uint4 (&v)[8], const uint8_t* dst) {
  if constexpr (I0 < I1) {
    asm volatile("{\n.reg .pred p;\nsetp.ne.b32 p, %5, 0;\n@p st.v4.u32 [%0+%6], {%1,%2,%3,%4};\n}\n"
      :: "l"(dst), "r"(v[I0].x), "r"(v[I0].y), "r"(v[I0].z), "r"(v[I0].w), "r"((int)on), "n"((I0 >> 1) * 512 + (I0 & 1) * 2048) : "memory");
    tile_store_if<I0 + 1, I1>(on, v, dst);
  }
}
template<bool ROWS> __device__ __forceinline__ float tile_norm2(const uint4 (&v)[8]) {
  uint32_t n0 = 0, n1 = 0, n2 = 0, n3 = 0;
#pragma unroll
  for (int j = 0; j < 2; j++) { sq_acc(v[2 * j], n0); sq_acc(v[2 * j + 1], n1); sq_acc(v[2 * j + 4], n2); sq_acc(v[2 * j + 5], n3); }
  return norm2_max<ROWS>(hadd2(n0, n2), hadd2(n1, n3));
}
template<uint64_t SCHED, bool FIRST> __device__ __forceinline__ void out_piece(Cons& c, Pend& w, uint32_t dst, int blk, float& kn, int ks, bool both) {
  uint8_t* d = g_T + (dst + atom_off(c.lane));
#pragma unroll
  for (int i = 0; i < 16; i++) {
    const int at = (SCHED >> (4 * i)) & 15;
    if (FIRST ? at == 0 : (at > 0 && ks == at && (i < 8 || both))) *(uint4*)(d + (i >> 3) * 32768 + ((i >> 1) & 3) * 512 + (i & 1) * 2048) = i < 8 ? w.lo[i & 7] : w.hi[i & 7];
  }
  if (FIRST || !both) return;
  if (ks == NK_AT) kn = tile_norm2<true>(w.lo);
  if (ks == NV_AT) {
    const float vn = tile_norm2<false>(w.hi);
    if (c.lane == 0) g_kn2[blk * 8 + c.wg * 4 + c.warp] = (vn <= 1.0e20f && vn >= 1.0e-20f) ? kn : __uint_as_float(0x7f800000u);
  }
}
template<bool FIRST> __device__ __forceinline__ void kv_issue(Cons& c, float (&acc)[128], int ua, int ub) {
  const uint64_t da = odesc(c.daddr(ua) + c.wg * 8192, 16, 1024, 1), db = odesc(c.daddr(ub), 8192, 1024, 1);
  c.turn();
  wg_fence();
#pragma unroll
  for (int kk = 0; kk < 4; kk++) wgmma_ss_n256<1>(acc, da + kk * 2, db + kk * 128, !(FIRST && kk == 0));
  wg_commit();
  c.pass();
}
template<bool NEXT> __device__ __forceinline__ void cons_kv(Cons& c, int h, int blk, int g, Pend& w, bool pend_o) {
#pragma unroll 1
  for (int tile = 0; tile < 2; tile++) {
    float acc[128];
    if (tile == 0) c.wait(0);
    const bool early = pend_o && tile == 0;
    kv_issue<true>(c, acc, early ? 12 : 0, early ? 0 : 1);
    c.release(9, tile == 1 ? 3 : 0);
    if (tile == 1 && pend_o) mbar_wait(c.base + SM_RDY + 8 * RDY_WAR, 0);
    const uint32_t dst = tile ? kv_off(c, blk) : ctx_off(c, h - 16, g, 1 - c.wg);
    float kn = 0.f;
    if (tile == 1 || pend_o) out_piece<SCH_KV, true>(c, w, dst, blk, kn, 0, false);
#pragma unroll 1
    for (int ks = 1; ks < 8; ks++) {
      const int u = gemm_unit(ks);
      c.wait(u);
      wg_wait<0>();
      c.release(gemm_unit(ks - 1), early && ks == 1 ? 2 : 3);
      kv_issue<false>(c, acc, u, u + 1);
      if (tile == 1 || pend_o) { out_piece<SCH_KV, false>(c, w, dst, blk, kn, ks, tile); if (ks == ((SCH_KV >> 28) & 15) && tile == 0) c.signal(SIG_CTX); }
    }
    if (NEXT || tile == 0) c.wait(0);
    wg_wait<0>(); fence_regs(acc);
    if (!NEXT) c.release(9, tile == 1 ? 3 : 0);
    pack_chunk<0>(acc, w.lo[0], w.lo[1]);  pack_chunk<16>(acc, w.lo[2], w.lo[3]); pack_chunk<32>(acc, w.lo[4], w.lo[5]); pack_chunk<48>(acc, w.lo[6], w.lo[7]);
    pack_chunk<64>(acc, w.hi[0], w.hi[1]); pack_chunk<80>(acc, w.hi[2], w.hi[3]); pack_chunk<96>(acc, w.hi[4], w.hi[5]); pack_chunk<112>(acc, w.hi[6], w.hi[7]);
    pin(w.lo); pin(w.hi);
  }
}
template<bool FIRST> __device__ __forceinline__ void q_issue(Cons& c, float (&a)[64], float (&b)[64], int u) {
  const uint64_t da = odesc(c.daddr(u) + c.wg * 8192, 16, 1024, 1), db = odesc(c.daddr(u + 2), 8192, 1024, 1);
  const uint64_t da2 = odesc(c.daddr(u + 1) + (1 - c.wg) * 8192, 16, 1024, 1);
  c.turn();
  wg_fence();
#pragma unroll
  for (int kk = 0; kk < 4; kk++) wgmma_ss_n128<1>(a, da + kk * 2, db + kk * 128, !(FIRST && kk == 0));
#pragma unroll
  for (int kk = 0; kk < 4; kk++) wgmma_ss_n128<1>(b, da2 + kk * 2, db + kk * 128, !(FIRST && kk == 0));
  wg_commit();
  c.pass();
}
__device__ __forceinline__ void q_step(Cons& c, float (&d)[64], int ua, int ub, int rowhalf) {
  const uint64_t da = odesc(c.daddr(ua) + rowhalf * 8192, 16, 1024, 1), db = odesc(c.daddr(ub), 8192, 1024, 1);
#pragma unroll
  for (int kk = 0; kk < 4; kk++) wgmma_ss_n128<1>(d, da + kk * 2, db + kk * 128, 1);
}
template<bool PEND_KV> __device__ __forceinline__ void cons_q(Cons& c, int h, int blk, Pend& w, float (&b)[64], float& kmax) {
  float a[64], kn = 0.f;
  if (!PEND_KV) c.wait(0);
  q_issue<true>(c, a, b, 0);
  if (PEND_KV) { c.release(9, 3); out_piece<SCH_Q, true>(c, w, kv_off(c, blk), blk, kn, 0, true); }
#pragma unroll 1
  for (int ks = 1; ks < 14; ks++) {
    const int u = gemm_unit(ks);
    c.wait(u);
    wg_wait<0>();
    c.release(gemm_unit(ks - 1), 3);
    q_issue<false>(c, a, b, u);
    if (PEND_KV && ks <= (int)(SCH_Q >> 60)) { out_piece<SCH_Q, false>(c, w, kv_off(c, blk), blk, kn, ks, true); if (ks == (int)(SCH_Q >> 60)) c.signal(SIG_KV + (h >> 4)); }
  }
  c.wait(6); c.wait(9);
  wg_wait<0>();
  c.release(3, 3);
  c.turn();
  wg_fence();
  q_step(c, a, 6, 8, c.wg); q_step(c, a, 9, 11, c.wg); wg_commit();
  q_step(c, b, 7, 8, 1 - c.wg); wg_commit();
  c.pass();
  c.wait(0);
  kmax = __uint_as_float(lds32(c.base + SM_KMAX + 4 * (h >> 4)));
  c.wait(12);
  const uint32_t q0 = c.addr(0) + (c.wg * 4 + c.warp) * 4096 + atom_off(c.lane);
  wg_wait<1>(); fence_regs(a);
  pack_o(a, QSCALE, QSCALE, w.lo);
  sts128o<0>(q0, w.lo[0]);    sts128o<2048>(q0, w.lo[1]); sts128o<512>(q0, w.lo[2]);  sts128o<2560>(q0, w.lo[3]);
  wg_wait<0>();
  c.release(6, 4);
  sts128o<1024>(q0, w.lo[4]); sts128o<3072>(q0, w.lo[5]); sts128o<1536>(q0, w.lo[6]); sts128o<3584>(q0, w.lo[7]);
  fence_async_smem();
}

__device__ __forceinline__ void issue_qk(float (&s)[64], uint64_t da, uint64_t db) {
#pragma unroll
  for (int kk = 0; kk < 8; kk++) wgmma_ss_n128<0>(s, da + (kk >> 1) * 32 + (kk & 1) * 2, db + (kk >> 1) * 32 + (kk & 1) * 2, kk > 0);
  wg_commit();
}
template<int A, int B> __device__ __forceinline__ void exp_rng(float (&s)[64]) {
#pragma unroll
  for (int i = 4 * A; i < 4 * B; i++) s[i] = ex2(s[i]);
}
template<int A, int B> __device__ __forceinline__ void sum_rng(const float (&s)[64], float (&l)[4]) {
#pragma unroll
  for (int i = A; i < B; i++) { l[0] += s[4 * i]; l[1] += s[4 * i + 1]; l[2] += s[4 * i + 2]; l[3] += s[4 * i + 3]; }
}
template<int A, int B> __device__ __forceinline__ void cvt_p(const float (&s)[64], uint32_t (&p)[32]) {
#pragma unroll
  for (int i = 2 * A; i < 2 * B; i++) p[i] = pack_bf16(s[2 * i], s[2 * i + 1]);
}
template<int K0> __device__ __forceinline__ void mask_half(float (&s)[64], int warp, int lane) {
  const int l0 = warp + (2 * (lane & 3) <= (lane >> 2)), l1 = warp + (2 * (lane & 3) < (lane >> 2));
#pragma unroll
  for (int k = 0; k < 4; k++) {
    float* t = s + 8 * (K0 + k);
    if (k >= l0) { t[0] = -INFINITY; t[6] = -INFINITY; }
    if (k >= l1) { t[1] = -INFINITY; t[7] = -INFINITY; }
    if (k > warp) { t[2] = -INFINITY; t[3] = -INFINITY; }
    if (k >= warp) { t[4] = -INFINITY; t[5] = -INFINITY; }
  }
}
__device__ __forceinline__ void row_inv(float& l0, float& l1) {
  l0 += __shfl_xor_sync(~0u, l0, 1); l1 += __shfl_xor_sync(~0u, l1, 1);
  l0 += __shfl_xor_sync(~0u, l0, 2); l1 += __shfl_xor_sync(~0u, l1, 2);
  l0 = rcp(l0); l1 = rcp(l1);
}
__device__ __forceinline__ void softmax_safe(float (&s)[64], bool upper_only, float& m0, float& m1, float& sc0, float& sc1) {
  float a0 = m0, a1 = m1;
#pragma unroll
  for (int i = 0; i < 8; i++) { a0 = fmaxf(a0, fmaxf(s[4 * i], s[4 * i + 1])); a1 = fmaxf(a1, fmaxf(s[4 * i + 2], s[4 * i + 3])); }
  if (upper_only) { a0 = m0; a1 = m1; }
#pragma unroll
  for (int i = 8; i < 16; i++) { a0 = fmaxf(a0, fmaxf(s[4 * i], s[4 * i + 1])); a1 = fmaxf(a1, fmaxf(s[4 * i + 2], s[4 * i + 3])); }
  a0 = fmaxf(a0, __shfl_xor_sync(~0u, a0, 1)); a1 = fmaxf(a1, __shfl_xor_sync(~0u, a1, 1));
  a0 = fmaxf(a0, __shfl_xor_sync(~0u, a0, 2)); a1 = fmaxf(a1, __shfl_xor_sync(~0u, a1, 2));
  sc0 = ex2(m0 - a0); sc1 = ex2(m1 - a1);
  m0 = a0; m1 = a1;
#pragma unroll
  for (int i = 0; i < 16; i++) { s[4 * i] -= a0; s[4 * i + 1] -= a0; s[4 * i + 2] -= a1; s[4 * i + 3] -= a1; }
}
struct Att {
  float s[64], o[64], l[4], i0, i1, t0, t1; uint32_t p[32];
  float kn; uint32_t qaddr; const uint8_t* dst;
};
__device__ __forceinline__ int att_fast(uint4 (&q)[8], float kn) {
#pragma unroll
  for (int i = 0; i < 8; i++) q[i].x = hmul2(q[i].x, q[i].x);
#pragma unroll
  for (int i = 0; i < 8; i++) q[i].x = hfma2(q[i].w, q[i].w, hfma2(q[i].z, q[i].z, hfma2(q[i].y, q[i].y, q[i].x)));
#pragma unroll
  for (int i = 0; i < 4; i++) q[i].x = hadd2(q[i].x, q[i + 4].x);
  const uint32_t a0 = hadd2(q[0].x, q[2].x), a1 = hadd2(q[1].x, q[3].x);
  return __shfl_sync(~0u, __all_sync(~0u, ((bf_lo(a0) + bf_hi(a0)) * kn <= 0.25f * BOUND2) & ((bf_lo(a1) + bf_hi(a1)) * kn <= 0.25f * BOUND2)), 0);
}
__device__ __forceinline__ int att_first(Cons& c, Att& a, int h, Pend& w) {
  a.qaddr = c.daddr(0) + c.wg * 16384;
  c.turn();
  wg_fence();
  issue_qk(a.s, odesc(a.qaddr, 16, 2048, 2), odesc(c.daddr(12), 16, 2048, 2));
  int fast = 0;
  SHADOW fast = att_fast(w.lo, a.kn);
  wg_fence();
  q_step(c, a.o, 10, 11, 1 - c.wg); wg_commit();
  if (c.wg) c.wait(6); else c.skip(6);
  c.pass();
#pragma unroll
  for (int i = 0; i < 8; i++) { a.p[4 * i] = w.lo[i].x; a.p[4 * i + 1] = w.lo[i].y; a.p[4 * i + 2] = w.lo[i].z; a.p[4 * i + 3] = w.lo[i].w; }
  a.l[0] = a.l[1] = a.l[2] = a.l[3] = 0.f; a.i0 = a.i1 = a.t0 = a.t1 = 0.25f / QSCALE;
  a.dst = (const uint8_t*)__cvta_shared_to_generic(c.addr(2) + (c.wg * 4 + c.warp) * 4096 + atom_off(c.lane));
  wg_wait<1>(); fence_regs(a.s);
  c.signal(SIG_ATT + (h >> 4));
  if (c.wg) { wg_wait<0>(); c.release(10, 2); }
  return fast;
}
__device__ __forceinline__ void att_last(Cons& c, Att& a, Pend& w, int h, int g, bool drain) {
  const int uv = 6;
  if (drain) pack_o(a.o, rcp(a.i0), rcp(a.i1), w.hi);
  c.turn();
  fence_regs(a.o); fence_regs(a.p);
  wgmma_pv_sel(a.o, a.p, odesc(c.daddr(uv), 512, 2048, 2), !(drain && c.wg == 1), !drain, c.wg);
  a.i0 = a.l[0] + a.l[1]; a.i1 = a.l[2] + a.l[3];
  SHADOW row_inv(a.i0, a.i1);
  sched_fence(a.i0 + a.i1, c.base + SM_DUMMY);
  tile_store_if<0, 4>(drain, w.hi, a.dst);
  wg_wait<0>(); fence_regs(a.o); fence_regs(a.p);
  c.release(uv, 2);
  tile_store_if<4, 8>(drain, w.hi, a.dst);
  pack_o(a.o, a.i0, a.i1, w.lo);
}
__device__ __forceinline__ void cons_att(Cons& c, Att& a, int h, int g, Pend& w) {
  int fast = att_first(c, a, h, w), fast2 = 0;
  float m0 = -INFINITY, m1 = -INFINITY, sc0 = 0.f, sc1 = 0.f;
  int uk = 10, ur = 10;
  bool fresh = false;
#pragma unroll 1
  for (int d = g - 15;;) {
    const bool lo = d == c.wg;
    if ((unsigned)d < 2 || !fast) {
      if ((unsigned)d < 2) mask_half<4>(a.s, c.warp, c.lane);
      if (!fast) {
        if (d == 1) m0 = m1 = -INFINITY;
        softmax_safe(a.s, lo, m0, m1, sc0, sc1);
        a.l[0] *= sc0; a.l[1] *= sc0; a.l[2] *= sc1; a.l[3] *= sc1;
      }
    }
    exp_rng<8, 16>(a.s); sum_rng<8, 16>(a.s, a.l);
#pragma unroll
    for (int i = 4 * ATT_SPLIT; i < 32; i++) asm("{\n.reg .pred p;\nsetp.ne.s32 p, %1, %2;\n@p ex2.approx.ftz.f32 %0, %0;\n}\n" : "+f"(a.s[i]) : "r"(d), "r"(c.wg));
    sched_fence(((a.l[0] + a.l[1]) + (a.l[2] + a.l[3])) + a.s[4 * ATT_SPLIT + 3], c.base + SM_DUMMY);
    wg_wait<0>(); fence_regs(a.o); fence_regs(a.p);
    c.release(ur, c.wg && d == g - 15 ? 0 : 2);
    a.i0 += a.t0; a.i1 += a.t1;
    a.t0 = __shfl_xor_sync(~0u, a.i0, 2); a.t1 = __shfl_xor_sync(~0u, a.i1, 2);
    tile_store_if<0, 4>(fresh, w.hi, a.dst);
    uk ^= 12; ur = 14 - uk;
    if (d == 0) a.qaddr += 32768;
    const uint64_t dq = odesc(a.qaddr, 16, 2048, 2), dk = odesc(c.daddr(uk) - (d + 1 == c.wg ? 16384 : 0), 16, 2048, 2), dv = odesc(c.daddr(ur), 512, 2048, 2);
    if (!lo) { exp_rng<0, ATT_SPLIT>(a.s); sum_rng<0, 8>(a.s, a.l); cvt_p<0, 16>(a.s, a.p); }
    else if (gridDim.y == 1) cvt_p<8, 16>(a.s, a.p);
    tile_store_if<4, 8>(fresh, w.hi, a.dst);
    a.i0 += a.t0; a.i1 += a.t1;
    if (!fast || d == g + 1) {
      if (!fast && d != 1 && d != g - 15) {
#pragma unroll
        for (int i = 0; i < 16; i++) { a.o[4 * i] *= sc0; a.o[4 * i + 1] *= sc0; a.o[4 * i + 2] *= sc1; a.o[4 * i + 3] *= sc1; }
      }
      if (d == g + 1) break;
    }
    d++;
    fresh = d == 2 || d == g - 14;
    c.turn();
    fence_regs(a.o); fence_regs(a.p);
    wg_fence();
    issue_qk(a.s, dq, dk);
    c.wait(c.wg ? uk ^ 12 : ur); c.skip(c.wg ? ur : uk ^ 12);
    if (fresh || d == 1 || (unsigned)(d - g + CHK_D) < 2) {
      if (fresh) pack_o(a.o, rcp(a.i0), rcp(a.i1), w.hi);
      else if (d == 1) {
        a.i0 = a.l[0] + a.l[1]; a.i1 = a.l[2] + a.l[3];
        a.t0 = __shfl_xor_sync(~0u, a.i0, 1); a.t1 = __shfl_xor_sync(~0u, a.i1, 1);
        a.l[0] = a.l[1] = a.l[2] = a.l[3] = 0.f;
        uint32_t off = ctx_off(c, h, 15 - g, c.wg);
        asm volatile("" : "+r"(off));
        a.dst = g_T + (off + ((uint32_t)(uint64_t)a.dst & 511));
        fast = fast2;
      } else if (d == g - CHK_D) fence_async_smem();
      else fast2 = att_fast(w.hi, a.kn);
    }
    wgmma_pv_sel(a.o, a.p, dv, !lo, !fresh, c.wg);
    wg_wait<1>(); fence_regs(a.s);
    c.release(uk, 2);
    c.release(d == 0 ? 0 : 2, (d == 0 || d == g + 1) ? 2 : 0);
  }
  att_last(c, a, w, h, g, g == 0);
}

constexpr int CV_H = 1024, CV_U = 5120, CV_D = CV_U + 4128;
template<int OFF> __device__ __forceinline__ uint32_t lds32o(uint32_t a) { uint32_t v; asm volatile("ld.shared.u32 %0, [%1+%2];" : "=r"(v) : "r"(a), "n"(OFF) : "memory"); return v; }
template<int G, int G1 = 16> __device__ __forceinline__ void conv_lda(uint32_t (&a)[64], uint32_t p) {
  a[4 * G + 0] = lds32o<-256 * G>(p);
  a[4 * G + 1] = lds32o<-256 * G - 128>(p);
  a[4 * G + 2] = lds32o<-256 * G + 16>(p);
  a[4 * G + 3] = lds32o<-256 * G - 112>(p);
  if constexpr (G + 1 < G1) conv_lda<G + 1, G1>(a, p);
}
struct CvAcc { float lo[16], hi[16]; };
__device__ __forceinline__ void fence_regs(CvAcc& d) { fence_regs(d.lo); fence_regs(d.hi); }
template<int T, int G0, int G1> __device__ __forceinline__ void conv_part(float (&d)[16], const uint32_t (&a)[64], uint64_t db) {
#pragma unroll
  for (int G = G0; G < G1; G++) wgmma_rs_n32<0>(d, a[4 * G], a[4 * G + 1], a[4 * G + 2], a[4 * G + 3], db + 32 * T - 16 * G, G > 0);
}
template<int C0> __device__ __forceinline__ void conv_st_h(const float (&d)[16], uint32_t wq, float& c0, float& c1) {
#pragma unroll
  for (int n = 0; n < 4; n++) { sts64f(wq + (C0 + n * 8) * 4, d[4 * n] + c0, d[4 * n + 1] + c1); c0 = d[4 * n + 2]; c1 = d[4 * n + 3]; }
}
template<int R> __device__ __forceinline__ void conv_st(const CvAcc& d, uint32_t wq, float& c0, float& c1) { conv_st_h<64 * R>(d.lo, wq, c0, c1); conv_st_h<64 * R + 32>(d.hi, wq, c0, c1); }

constexpr int OC_PART = 13824, OC_ROW = 544;
__device__ __forceinline__ int out_next(int u) { return (0x84ac680u >> (2 * u)) & 15; }
struct Out { float acc[64]; int pu; uint64_t da, db; };
template<bool FIRST, bool REL, int W = 1> __device__ __forceinline__ void out_step(Cons& c, Out& o, bool extra = false) {
  const int pu = o.pu, u = extra ? 2 : out_next(pu);
  o.pu = u;
  c.wait(u);
  const uint64_t da = o.da + (uint32_t)(u * 1024), db = o.db + (uint32_t)(u * 1024);
  wg_fence();
#pragma unroll
  for (int kk = 0; kk < 4; kk++) wgmma_ss_n128<1>(o.acc, da + (kk >> 1) * 32 + (kk & 1) * 2, db + kk * 128, !(FIRST && kk == 0));
  wg_commit();
  if (REL) { wg_wait<W>(); c.release(pu, 2); }
}
template<int I0, int I1> __device__ __forceinline__ void oc_red(float (&y)[8], uint32_t rq) {
#pragma unroll
  for (int i = I0; i < I1; i++) { const float v = __uint_as_float(lds32(rq + i * OC_ROW - (i >> 3) * 8)); y[i & 7] = i < 8 ? v : y[i & 7] + v; }
}
template<int I0, int I1> __device__ __forceinline__ void oc_ld(float (&t)[32], uint32_t rq) {
#pragma unroll
  for (int i = I0; i < I1; i++) t[i] = __uint_as_float(lds32(rq + i * OC_ROW - (i >> 3) * 8));
}
__device__ __forceinline__ void oc_emit(const float (&y)[8], const uint4& u, uint32_t D2, uint8_t* dst) {
  uint4 z;
  z.x = hadd2(pack_bf16(y[0], y[1]), hmul2(__byte_perm(u.w, 0, 0x1032), D2));
  z.y = hadd2(pack_bf16(y[2], y[3]), hmul2(__byte_perm(u.z, 0, 0x1032), D2));
  z.z = hadd2(pack_bf16(y[4], y[5]), hmul2(__byte_perm(u.y, 0, 0x1032), D2));
  z.w = hadd2(pack_bf16(y[6], y[7]), hmul2(__byte_perm(u.x, 0, 0x1032), D2));
  *(uint4*)dst = z;
}
template<bool THR> __device__ __forceinline__ void conv_round(Cons& c, Out& o, int u, uint32_t ub, uint32_t wq, uint32_t rq, int ch) {
  const int r = c.lane >> 2, q = c.lane & 3, tid = c.warp * 32 + c.lane;
  const uint32_t ap = ub + CV_U + ((r & 1) ? 0 : UPITCH) + 4 * (((2039 - r) >> 1) + q - 8 * c.warp);
  uint32_t a[64];
  CvAcc d0, d1;
  float y[8], t[32], c0 = 0.f, c1 = 0.f;
  const uint64_t db0 = odesc(c.daddr(u) + CV_H - 16, 16, 128, 0);
#define STEP(N) if (THR) out_step<false, true>(c, o); else if (N == 0) c.turn(); else if (N == 10) wg_wait<0>();
#define STEP2(N) if (THR) out_step<false, true, 2>(c, o); else { if (N == 9) c.pass(); wg_wait<1>(); }
#define PART(...) { const uint64_t db = db0 + (c.mask >> 16); wg_fence(); __VA_ARGS__; wg_commit(); }
#define KEEP() asm volatile("add.f32 %0, %0, 0f80000000;" : "+f"(c0)); asm volatile("add.f32 %0, %0, 0f80000000;" : "+f"(c1));
  c.wait(u);
  conv_lda<0, THR ? 4 : 12>(a, ap);
  STEP(0)
  if (THR) conv_lda<4, 7>(a, ap);
  PART(conv_part<0, 0, 2>(d0.lo, a, db); conv_part<1, 0, 4>(d0.hi, a, db); conv_part<2, 0, 2>(d1.lo, a, db))
  STEP2(1)
  if (THR) conv_lda<7, 10>(a, ap);
  PART(conv_part<2, 2, 6>(d1.lo, a, db); conv_part<3, 0, 4>(d1.hi, a, db))
  STEP2(2)
  fence_regs(d0);
  if (THR) c.sync();
  sts64f(wq - 32, 0.f, 0.f);
  conv_st_h<0>(d0.lo, wq, c0, c1); KEEP()
  PART(conv_part<3, 4, 8>(d1.hi, a, db); conv_part<4, 0, 4>(d0.lo, a, db))
  STEP2(3)
  fence_regs(d1.lo);
  conv_st_h<32>(d0.hi, wq, c0, c1); conv_st_h<64>(d1.lo, wq, c0, c1); KEEP()
  PART(conv_part<4, 4, 10>(d0.lo, a, db); conv_part<5, 0, 2>(d0.hi, a, db))
  STEP2(4)
  fence_regs(d1.hi);
  float e0 = d1.hi[12] + d1.hi[10], e1 = d1.hi[13] + d1.hi[11];
  conv_st_h<96>(d1.hi, wq, c0, c1); KEEP()
  if (THR) conv_lda<10, 12>(a, ap);
  PART(conv_part<5, 2, 10>(d0.hi, a, db))
  STEP2(5)
  conv_lda<12, 14>(a, ap);
  c.sync();
  if (THR) oc_red<0, 6>(y, rq); else oc_ld<0, 8>(t, rq);
  PART(conv_part<5, 10, 12>(d0.hi, a, db); conv_part<6, 0, 6>(d1.lo, a, db))
  STEP2(6)
  if (THR) oc_red<6, 20>(y, rq); else oc_ld<8, 16>(t, rq);
  PART(conv_part<6, 6, 14>(d1.lo, a, db))
  STEP2(7)
  if (THR) oc_red<20, 26>(y, rq); else oc_ld<16, 24>(t, rq);
  conv_lda<14, 16>(a, ap);
  PART(conv_part<7, 0, 8>(d1.hi, a, db))
  STEP2(8)
  if (THR) oc_red<26, 32>(y, rq); else oc_ld<24, 32>(t, rq);
  PART(conv_part<7, 8, 16>(d1.hi, a, db))
  STEP2(9)
  if (!THR) {
#pragma unroll
    for (int i = 0; i < 8; i++) y[i] = t[i];
    SHADOW {
#pragma unroll
      for (int i = 0; i < 8; i++) y[i] = ((t[i] + t[8 + i]) + t[16 + i]) + t[24 + i];
    }
  }
  fence_regs(y); fence_regs(d0);
  c.sync();
  sts64f(wq - 32, e0, e1);
  conv_st<0>(d0, wq, c0, c1);
  STEP(10)
  fence_regs(d1); fence_regs(a);
  const uint4 u0 = lds128(ub + CV_U + 4080 - 16 * tid), u1 = lds128(ub + CV_U + 2032 - 16 * tid);
  const uint32_t D2 = lds32(ub + CV_D);
  conv_st<1>(d1, wq, c0, c1);
  STEP(11)
  sched_fence(__uint_as_float(u0.x ^ u1.x ^ D2), c.base + SM_DUMMY);
  uint8_t* zp = g_u + (uint32_t)(ch * UCH + (threadIdx.x & 127) * 16);
  oc_emit(y, u0, D2, zp);
  c.sync();
  c.release2(u);
  oc_red<0, 12>(y, rq);
  STEP(12)
  oc_red<12, 24>(y, rq);
  STEP(13)
  oc_red<24, 32>(y, rq);
  oc_emit(y, u1, D2, zp + 2048);
#undef KEEP
#undef STEP
#undef STEP2
#undef PART
}
template<int MASK> __device__ __forceinline__ void cons_conv(Cons& c, int cta, int nch) {
  const uint32_t part = c.addr(4 + 2 * c.wg) + 32;
  const uint32_t wq = part + (c.warp * 8 + (c.lane >> 2)) * OC_ROW + (c.lane & 3) * 8, rq = part + (c.warp * 32 + c.lane) * 4;
  Out o;
  c.wait(4);
#pragma unroll 1
  for (int i = 0; i < nch / 2; i++) {
    const int u = 2 * (i & 1) + c.wg;
    conv_round<false>(c, o, u, c.addr(u), wq, rq, conv_channel<MASK>(cta, 2 * i + c.wg));
    if ((i & 15) == 15 || i == nch / 2 - 1) c.signal(SIG_Z + (i >> 4));
  }
}
__device__ __forceinline__ uint32_t mix(uint32_t og, uint32_t b, uint32_t ga) { return hadd2(ga, hmul2(og, b)); }
template<int MASK> __device__ __forceinline__ void cons_out(Cons& c, const Maps& M, const Params& P, int cta, Pend& w) {
  const int mb = out_mb(cta), nb = out_nb(cta);
  Out o;
  o.da = odesc(c.daddr(0) + c.wg * 8192, 16, 1024, 2); o.db = odesc(c.daddr(1), 8192, 1024, 1);
  o.pu = 5 + gridDim.y;
  out_step<true, false>(c, o);
  int ks = 1;
  const uint32_t dst = ctx_off(c, 16 + (cta >> 3), cta & 7, 1 - c.wg);
#pragma unroll 1
  for (;; ks++) {
    if (MASK & PH_ATT) {
      if (ks == (c.wg ? ST_1 : 1)) tile_store<0, 1>(w.lo, dst, c.lane);
      if (ks == (c.wg ? ST_1 + ST_D : 1)) tile_store<1, 2>(w.lo, dst, c.lane);
      if (ks == (c.wg ? ST_1 + 2 * ST_D : 1)) tile_store<2, 3>(w.lo, dst, c.lane);
      if (ks == (c.wg ? ST_1 + 3 * ST_D : 1)) { tile_store<3, 4>(w.lo, dst, c.lane); c.signal(SIG_CTX + 1); }
    }
    if (ks == (c.wg ? OC_S1 : OC_S0)) break;
    out_step<false, true>(c, o, ks == 1);
  }
  if (MASK & PH_CONV) {
    const int r = c.lane >> 2, q = c.lane & 3, tid = c.warp * 32 + c.lane, u = 2 * c.wg;
    const uint32_t ub = c.addr(u), part = ub + OC_PART + 32;
    const uint32_t wq = part + (c.warp * 8 + r) * OC_ROW + q * 8, rq = part + tid * 4;
    int ch = conv_channel<MASK>(cta, 3 * c.wg);
#pragma unroll 1
    for (int i = 0; ch >= 0; i++) {
      conv_round<true>(c, o, u + (i >> 8), ub, wq, rq, ch);
      ch = i + c.wg < 2 ? ch + 1 : -1;
      if (c.wg > i) { mbar_wait(c.base + SM_RDY + 8 * RDY_T, 0); ch = __shfl_sync(~0u, lds32(c.base + SM_POOL), 0); }
      if (ch < 0) { c.signal(SIG_Z); c.sync(); c.release2(u + 1);  }
      out_step<false, true>(c, o);
#pragma unroll 1
      for (int k = 15; k < (ch < 0 ? 0 : c.wg ? OC_L1 : OC_L0); k++) out_step<false, true>(c, o);
      ks += ch < 0 ? 15 : c.wg ? OC_L1 : OC_L0;
    }
    if (c.wg) c.skip(0);
  }
#pragma unroll 1
  for (; ks < 57; ks++) out_step<false, true>(c, o);
  uint32_t ga[32];
  c.wait(3);
  const float g0 = __uint_as_float(lds32(c.base + SM_GATE + 4 * (c.wg * 64 + c.warp * 16 + (c.lane >> 2)))), g1 = __uint_as_float(lds32(c.base + SM_GATE + 32 + 4 * (c.wg * 64 + c.warp * 16 + (c.lane >> 2))));
  const uint32_t gg0 = pack_bf16(g0, g0), gg1 = pack_bf16(g1, g1);
  const uint32_t og0 = pack_bf16(1.f - g0, 1.f - g0), og1 = pack_bf16(1.f - g1, 1.f - g1);
  const int xr = c.wg * 64 + c.warp * 16 + (c.lane & 15);
  const uint32_t xa = c.addr(2) + xr * 128, xs = xr & 7, xh = c.lane >> 4;
  const int zr = (c.lane & 7) + ((c.lane >> 4) << 3);
  const uint32_t za = c.addr(0) + c.wg * 16384 + zr * 128 + (((c.warp * 2 + ((c.lane >> 3) & 1)) ^ (zr & 7)) << 4);
#pragma unroll
  for (int i = 0; i < 8; i++) {
    if (i == 0) out_step<false, true>(c, o);
    if (i == 3) out_step<false, true>(c, o);
    if (i == 6) out_step<false, true>(c, o);
    ldsm4(xa + (i >> 2) * 16384 + ((((i & 3) * 2 + xh) ^ xs) << 4), ga[4 * i], ga[4 * i + 1], ga[4 * i + 2], ga[4 * i + 3]);
  }
#pragma unroll 1
  for (ks = 60; ks < 64; ks++) out_step<false, false>(c, o);
  c.wait(0);
  SHADOW {
#pragma unroll
    for (int i = 0; i < 8; i++) {
      uint32_t z0, z1, z2, z3;
      ldsm4t(za + i * 2048, z0, z1, z2, z3);
      ga[4 * i + 0] = hmul2(ga[4 * i + 0], z0); ga[4 * i + 1] = hmul2(ga[4 * i + 1], z1); ga[4 * i + 2] = hmul2(ga[4 * i + 2], z2); ga[4 * i + 3] = hmul2(ga[4 * i + 3], z3);
      ga[4 * i + 0] = hmul2(gg0, ga[4 * i + 0]); ga[4 * i + 1] = hmul2(gg1, ga[4 * i + 1]); ga[4 * i + 2] = hmul2(gg0, ga[4 * i + 2]); ga[4 * i + 3] = hmul2(gg1, ga[4 * i + 3]);
    }
  }
  c.signal(SIG_DONE);
  fence_regs(ga);
  wg_wait<0>(); fence_regs(o.acc);
#pragma unroll
  for (int i = 0; i < 8; i++) {
    const uint32_t r0 = mix(og0, pack_bf16(o.acc[8 * i + 0], o.acc[8 * i + 1]), ga[4 * i + 0]);
    const uint32_t r1 = mix(og1, pack_bf16(o.acc[8 * i + 2], o.acc[8 * i + 3]), ga[4 * i + 1]);
    const uint32_t r2 = mix(og0, pack_bf16(o.acc[8 * i + 4], o.acc[8 * i + 5]), ga[4 * i + 2]);
    const uint32_t r3 = mix(og1, pack_bf16(o.acc[8 * i + 6], o.acc[8 * i + 7]), ga[4 * i + 3]);
    stsm4(xa + (i >> 2) * 16384 + ((((i & 3) * 2 + xh) ^ xs) << 4), r0, r1, r2, r3);
    if ((i & 3) == 3) {
      __syncwarp();
#pragma unroll
      for (int k = 0; k < 4; k++) {
        const int rr = c.wg * 64 + c.warp * 16 + k * 4 + (c.lane >> 3);
        const uint4 v = lds128(c.addr(2 + (i >> 2)) + rr * 128 + (((c.lane ^ rr) & 7) << 4));
        *(uint4*)(P.out + (uint32_t)((mb * 128 + rr) * 1024 + nb * 128 + (i >> 2) * 64 + (c.lane & 7) * 8)) = v;
      }
    }
  }
}

__device__ __forceinline__ void load_conv(Prod& p, const Maps& M, int u, int ch) {
  if (elect()) {
    mbar_expect(p.full(u), 5120 + UCH);
    tma3d(p.addr(u), &M.h, 0, -8, ch, p.full(u), true);
    bulk_g2s(p.addr(u) + CV_U, g_u + (size_t)ch * UCH, UCH, p.full(u), true);
  }
}
template<int MASK> __device__ __forceinline__ void prod_conv(Prod& p, const Maps& M, int cta, int nch) {
  int ready = -1;
#pragma unroll 1
  for (int i = 0; i < nch; i++) {
    const int ch = conv_channel<MASK>(cta, i);
    const int u = i & 3;
    if ((ch >> 6) != ready) { ready = ch >> 6; if (cta < NREG) mbar_wait(p.base + SM_RDY + 8 * RDY_U, 0); else cnt_wait(g_cnt + (C_U + ready) * CSTRIDE, 128); }
    p.acquire(u, 1);
    load_conv(p, M, u, ch);
    if (i == 3) { p.acquire(4, 4); if (elect()) mbar_arrive(p.full(4)); }
  }
}
#define HOIST(v) asm volatile("" : "+r"(v))
template<int MASK> __device__ __forceinline__ void producer(const Maps& M, const Params& P, uint32_t base, int cta, int lane) {
  Prod p{base, ((MASK & PH_KV) && cta < NREG) ? 0xffffcfffu ^ ((1u << (3 * NFIRST)) - 1) : 0xffffffffu, lane};
  if (cta >= NREG) { if (MASK & PH_CONV) prod_conv<MASK>(p, M, cta, CV_EXTRA<MASK>); return; }
  const int g = cta & 7, j = cta >> 3, rank = cta & 1;
#pragma unroll 1
  for (int half = 0; half < 2; half++) {
    const int h = j + 16 * half;
    if (MASK & PH_KV) {
      const CUtensorMap* mw = rank ? &M.wv : &M.wk;
#pragma unroll 1
      for (int it = half ? 0 : NFIRST; it < 16; it++) {
        const int u = gemm_unit(it);
        const bool early = MASK == PH_ALL && it == 0;
        uint32_t bar = p.full(u), d0 = p.addr(early ? 12 : u), d1 = p.addr(u + !early + rank); int k0 = (it & 7) * 64, r0 = (2 * g + (it >> 3)) * 128;
        HOIST(bar); HOIST(d0); HOIST(d1); HOIST(k0); HOIST(r0);
        p.acquire(u, 3 - early);
        if (elect()) {
          mbar_expect(bar, 3 * UNIT);
          tma3d_mc(d1, mw, 0, k0, 2 * h, bar, it >= 8);
          tma2d(d0, &M.c, k0, r0, bar);
        }
      }
    }
    if (MASK & PH_ATT) {
#pragma unroll 1
      for (int ks = 0; ks < 16; ks++) {
        const int u = gemm_unit(ks);
        uint32_t bar = p.full(u), d0 = p.addr(u), d1 = p.addr(u + 1), d2 = p.addr(u + 2) + rank * 8192; int k0 = ks * 64;
        HOIST(bar); HOIST(d0); HOIST(d1); HOIST(d2); HOIST(k0);
        p.acquire(u, 3);
        if (elect()) {
          mbar_expect(bar, 3 * UNIT);
          tma2d_mc(d2, &M.wq, h * 128 + rank * 64, k0, bar, true);
          tma2d(d0, &M.x, k0, (15 - g) * 128, bar);
          tma2d(d1, &M.x, k0, g * 128, bar);
        }
      }
      mbar_wait(base + SM_RDY + 8 * (RDY_KV + half), 0);
      const uint8_t* KVh = g_T + T_KV + (size_t)kv_slot<MASK>(h) * 16 * 65536;
      if (MASK & PH_PRE) mbar_wait(base + SM_RDY + 8 * RDY_AUX, 0);
      if (elect()) { mbar_expect(p.full(12), 32768); bulk_g2s(p.addr(12), KVh, 32768, p.full(12), true); }
      p.acquire(0, 4);
      if (elect()) mbar_arrive(p.full(0));
#pragma unroll 1
      for (int i = 1; i < 34; i++) {
        const int isv = !(i & 1) || i == 33, st = i == 33 ? 16 : (isv ? (i >> 1) - 1 : (i + 1) >> 1), u = 4 + 2 * (i & 3);
        const bool own = st == 15 - (g & 6);
        uint32_t bar = p.full(u), d0 = p.addr(own ? u : u + rank), off = (st <= 15 - g ? st : 16 - st) * 65536 + isv * 32768 + (own ? 0 : rank * UNIT);
        HOIST(bar); HOIST(d0); HOIST(off);
        p.acquire(u, 2);
        if (elect()) {
          mbar_expect(bar, 32768);
          if (own) bulk_g2s(d0, KVh + off, 32768, bar, true); else bulk_g2s_mc(d0, KVh + off, UNIT, bar, true);
        }
      }
    }
  }
  if ((MASK & PH_CONV) && !(MASK & PH_OUT)) prod_conv<MASK>(p, M, cta, CV_REG<MASK>);
  if (MASK & PH_OUT) {
    const int y0 = out_mb(cta) * 512 + rank * 8, z0 = 2 * out_nb(cta);
    int u = 6;
#pragma unroll 1
    for (int hf = 0; hf < 2; hf++) {
      mbar_wait(base + SM_RDY + 8 * (RDY_CTX + hf), 0);
#pragma unroll 1
      for (int n = hf * 32; n < hf * 32 + 32; n++) {
        const int ks = n == 1 ? 2 : n == 2 ? 1 : n;
        u = n == 2 ? 2 : n == 3 ? 10 : out_next(u);
        uint32_t bar = p.full(u), d0 = p.addr(u) + rank * 8192, d1 = p.addr(u + 1); int x = (ks & 1) * 256, y = y0 + (ks >> 1) * 16, k0 = ks * 64;
        HOIST(bar); HOIST(d0); HOIST(d1); HOIST(x); HOIST(y); HOIST(k0);
        p.acquire(u, 2);
        if (elect()) {
          mbar_expect(bar, 2 * UNIT);
          tma2d_mc(d0, &M.ctx, x, y, bar, true);
          tma3d(d1, &M.wo, 0, k0, z0, bar, true);
          if (ks == 1 || ks == TK) mbar_arrive(base + SM_RDY + 8 * (ks == 1 ? RDY_X : RDY_DRAW));
          if (ks == Z_AT) mbar_arrive(base + SM_RDY + 8 * RDY_Z);
        }
      }
    }
  }
}
template<int MASK> __device__ __forceinline__ void producer2(const Maps& M, const Params& P, uint32_t base, int cta, int w, int lane) {
  Prod p{base, 0xffffffffu, lane};
  const int mb = out_mb(cta), nb = out_nb(cta), u = 2 * w;
  if (w) { mbar_wait_slow(base + SM_RDY + 8 * RDY_X, 0); p.mask ^= MASK == PH_ALL ? 8 : 12; }
  if (MASK & PH_CONV) {
    mbar_wait_slow(base + SM_SIG + 8 * (SIG_ATT + 1), 0);
    mbar_wait_slow(base + SM_RDY + 8 * RDY_U, 0);
#pragma unroll 1
    for (int i = 0, ch = conv_channel<MASK>(cta, 3 * w); ch >= 0; i++) {
      p.acquire_slow(u, i ? 1 : 2);
      load_conv(p, M, u, ch);
      ch = i + w < 2 ? ch + 1 : -1;
      if (w > i) { mbar_wait_slow(base + SM_RDY + 8 * RDY_T, 0); ch = lds32(base + SM_POOL); }
    }
  }
  p.acquire_slow(u, 2);
  if (!w && elect()) map_pf(&M.z);
  mbar_wait(base + SM_RDY + 8 * (!w ? RDY_Z : RDY_G), 0);
  if (elect()) {
    const uint32_t bar = p.full(3 * w);
    mbar_expect(bar, 2 * UNIT + (!w ? 0 : 512));
    tma2d(p.addr(u), !w ? &M.z : &M.x, (!w ? mb : nb) * 128, (!w ? nb : mb) * 128, bar, true);
    tma2d(p.addr(u + 1), !w ? &M.z : &M.x, (!w ? mb : nb) * 128 + 64, (!w ? nb : mb) * 128, bar, true);
    if (w) bulk_g2s(base + SM_GATE, g_gate + mb * 128, 512, bar);
  }
}

__device__ __forceinline__ constexpr uint32_t PUB(int sig, int cnt, int n) { return 0x80000000u | (sig << 24) | (n << 8) | cnt; }
__device__ __forceinline__ constexpr uint32_t GET(int rdy, int cnt, int n) { return (rdy << 24) | (n << 8) | cnt; }
template<int MASK> __device__ __forceinline__ void sync_agent(uint32_t base, int cta, int lane) {
  if ((base & 0x3FFFF) != SMEM_BASE) asm volatile("trap;");
  const int g = cta & 7, j = cta >> 3, go = min(out_mb(cta), 15 - out_mb(cta));
  const int c0 = conv_channel<MASK>(cta, 0), c1 = c0 + CV_REG<MASK> - 1, n0 = min(CV_REG<MASK>, 128 - (c0 & 127));
  constexpr bool KV = MASK & PH_KV, ATT = MASK & PH_ATT, CONV = MASK & PH_CONV, OUT = MASK & PH_OUT, ALL = MASK == PH_ALL;
  uint32_t e = 0;
  if (cta >= NREG) { if (CONV && lane * 32 < CV_EXTRA<MASK>) e = PUB(SIG_Z + lane, C_Z + lane, min(32, CV_EXTRA<MASK> - lane * 32)); }
  else switch (lane) {
    case 0:  if (KV) e = PUB(SIG_KV, C_KV + j, 1); break;
    case 1:  if (ATT) e = GET(RDY_KV, C_KV + j, 8); break;
    case 2:  if (ALL) e = PUB(SIG_WAR, C_WAR + j, 1); break;
    case 3:  if (ATT) e = PUB(SIG_CTX, C_CTX + g, 1); break;
    case 4:  if (ALL) e = GET(RDY_WAR, C_WAR + j, 8); break;
    case 5:  if (KV) e = PUB(SIG_KV + 1, C_KV + 16 + j, 1); break;
    case 6:  if (ATT) e = GET(RDY_KV + 1, C_KV + 16 + j, 8); break;
    case 7:  if (OUT) e = GET(RDY_CTX, C_CTX + go, 16); break;
    case 8:  if (CONV) e = GET(RDY_U, C_U + (c0 >> 6), 128); break;
    case 9:  if (CONV) e = GET(ALL ? RDY_DRAW : RDY_U, C_U + (ALL ? 14 : c1 >> 6), 128); break;
    case 10: if (ALL) e = GET(RDY_T, C_U + 15, 128); break;
    case 11: if (OUT) e = GET(RDY_G, C_GATE, 256); break;
    case 12: if (ATT) e = PUB(SIG_CTX + 1, C_CTX + 8 + g, 1); break;
    case 13: if (OUT) e = GET(RDY_CTX + 1, C_CTX + 8 + go, 16); break;
    case 14: if (CONV) e = PUB(SIG_Z, C_Z + (c0 >> 7), n0); break;
    case 15: if (ALL) e = PUB(SIG_Z, C_Z + 7, 1); else if (CONV && n0 < CV_REG<MASK>) e = PUB(SIG_Z, C_Z + (c1 >> 7), CV_REG<MASK> - n0); break;
    case 16: if (OUT) e = GET(RDY_Z, C_Z + out_nb(cta), 128); break;
  }
  if (ALL && lane == 0) { mbar_expect(base + SM_RDY + 8 * RDY_T, 4); mbar_arrive(base + SM_RDY + 8 * RDY_U); }
  __syncwarp();
#pragma unroll 1
  for (int i = 0; i < 17; i++) {
    const uint32_t x = __shfl_sync(~0u, e, i), id = (x >> 24) & 127, n = (x >> 8) & 0xffff;
    if (x == 0) continue;
    unsigned* cnt = g_cnt + (x & 255) * CSTRIDE;
    if (ALL && i == 14 && !(cta & 1)) {
      mbar_wait_slow<64>(base + SM_RDY + 8 * RDY_DRAW, 0);
      unsigned t = 0;
      if (lane == 0) asm volatile("atom.relaxed.gpu.global.add.u32 %0, [%1], 1;" : "=r"(t) : "l"(g_cnt + C_TICKET * CSTRIDE) : "memory");
      t = __shfl_sync(~0u, t, 0);
      uint32_t peer;
      asm volatile("mapa.shared::cluster.u32 %0, %1, %2;" : "=r"(peer) : "r"(base), "r"(lane & 1));
      if (lane < 2) asm volatile("st.async.weak.shared::cluster.mbarrier::complete_tx::bytes.u32 [%0], %1, [%2];"
        :: "r"(peer + SM_POOL), "r"(t < 64 - NSKIP ? CV_POOL + 2 * t + lane : ~0u), "r"(peer + SM_RDY + 8 * RDY_T) : "memory");
    }
    if (x >> 31) {
      mbar_wait_slow(base + SM_SIG + 8 * id, 0);
      if (lane == 0 && !(ALL && i == 15 && (int)lds32(base + SM_POOL) < 0)) cnt_publish(cnt, n, i != 15);
    } else {
      cnt_wait(cnt, n);
      if (id < 2) {
        const float4 kn = __ldcg((const float4*)(g_kn2 + kv_slot<MASK>(j + 16 * id) * 128) + lane);
        const uint32_t m = __reduce_max_sync(~0u, max(max(__float_as_uint(kn.x), __float_as_uint(kn.y)), max(__float_as_uint(kn.z), __float_as_uint(kn.w))));
        if (lane == 0) asm volatile("st.shared.u32 [%0], %1;" :: "r"(base + SM_KMAX + 4 * id), "r"(m) : "memory");
      }
      if (lane == 0) mbar_arrive(base + SM_RDY + 8 * id);
    }
    __syncwarp();
  }
}

__device__ __forceinline__ void aux_gate(const Params& P, int cta, int aw, int lane) {
  uint4 gw[4];
#pragma unroll
  for (int i = 0; i < 4; i++) gw[i] = __ldg((const uint4*)P.gw + i * 32 + lane);
#pragma unroll 1
  for (int row = cta * 16 + aw * 8; row < cta * 16 + aw * 8 + 8; row++) {
    float a = 0.f;
#pragma unroll
    for (int i = 0; i < 4; i++) {
      const uint4 xv = __ldg((const uint4*)(P.x + (size_t)row * 1024) + i * 32 + lane);
      uint32_t m;
      m = hmul2(xv.x, gw[i].x); a += bf_lo(m) + bf_hi(m); m = hmul2(xv.y, gw[i].y); a += bf_lo(m) + bf_hi(m);
      m = hmul2(xv.z, gw[i].z); a += bf_lo(m) + bf_hi(m); m = hmul2(xv.w, gw[i].w); a += bf_lo(m) + bf_hi(m);
    }
#pragma unroll
    for (int o = 16; o > 0; o >>= 1) a += __shfl_xor_sync(~0u, a, o);
    a = bf_lo(pack_bf16(a, 0.f));
    const float gt = bf_lo(pack_bf16(__fdividef(1.f, 1.f + ex2(-a * 1.4426950408889634f)), 0.f));
    if (lane == 0) g_gate[row] = gt;
    __nanosleep(GATE_SLEEP);
  }
  cnt_signal(g_cnt + C_GATE * CSTRIDE, lane);
}
__device__ __forceinline__ void pf64(const void* p) { asm volatile("prefetch.global.L2 [%0];" :: "l"(p) : "memory"); }
__device__ __forceinline__ void aux_pf(const Params& P, int cta, int aw, int lane) {
  for (int i = 0; i < PF_WAIT; i++) __nanosleep(1000);
#pragma unroll 1
  for (int i = 0; i < 8; i++) {
    pf64((const uint8_t*)(aw ? P.wv : P.wk) + ((16 + (cta >> 3)) * 256 + (lane & 3) * 64 + (i * 64 + (cta & 7) * 8 + (lane >> 2)) * 8192));
    if ((i & 3) == 0) pf64((const uint8_t*)P.c + (((cta & 7) * 256 + (cta >> 3) * 8 + aw * 4 + (lane >> 3)) * 1024 + (i >> 2) * 512 + (lane & 7) * 64));
    __nanosleep(PF_GAP);
  }
}
template<int MASK> __device__ __forceinline__ void aux_pre(const Maps& M, const Params& P, uint32_t base, int cta, int aw, int lane) {
  const uint32_t kb = base + 12 * UNIT, bar = base + SM_PRE;
  const int r = lane >> 2, q = lane & 3;
  const int mi = lane >> 3, row0 = (lane & 6) + 1 - (lane & 1);
  const int ra = (mi * 9 + 1) * 2 + row0;
  const int rb = (mi == 0 ? 3 : mi) * 18 + row0;
#pragma unroll 1
  for (int it = 0; it < (cta < 96 ? 5 : 4); it++) {
    if (it == PRE_EARLY && MASK == PH_ALL) { mbar_wait_slow(base + SM_SIG + 8 * SIG_ATT, 0); aux_gate(P, cta, aw, lane); aux_pf(P, cta, aw, lane); }
    if (it == PRE_EARLY && MASK == PH_ALL) mbar_wait_slow(base + SM_SIG + 8 * (SIG_ATT + 1), 0);
    const int cg = it ? it * 4 - 3 + (cta >> 5) : 0, tb = cta & 31;
    if (aw == 0 && elect()) {
      mbar_expect(bar, 2 * 9216);
      tma4d(kb, &M.k, cg * 64, 0, tb * 8 - 1, 0, bar, true);
      tma4d(kb + 9216, &M.v, cg * 64, 0, tb * 8 - 1, 0, bar, true);
    }
    const uint2 swl = __ldg((const uint2*)(P.shift + (cg * 64 + aw * 32 + lane) * 4));
    if (tb == 0) {
      uint8_t* e = g_u + (size_t)(cg * 64 + aw * 32 + lane) * UCH + 4096;
      *(uint4*)e = make_uint4(0, 0, 0, 0); *(uint4*)(e + UPITCH) = make_uint4(0, 0, 0, 0);
      *(uint32_t*)(e + 32) = (uint32_t)__bfloat16_as_ushort(P.D[cg * 64 + aw * 32 + lane]) * 0x10001u;
    }
    if (it == 0) mbar_wait(bar, 0); else mbar_wait_slow(bar, it & 1);
#pragma unroll 1
    for (int ol = it ? 0 : cta >> 5; ol < (it ? 4 : (cta >> 5) + 1); ol++) {
      const int oc = aw * 4 + ol;
      const uint32_t s01 = __shfl_sync(~0u, swl.x, ol * 8 + r), s23 = __shfl_sync(~0u, swl.y, ol * 8 + r);
      const uint32_t w0 = __byte_perm(s01, 0, 0x1010), w1 = __byte_perm(s01, 0, 0x3232), w2 = __byte_perm(s23, 0, 0x1010), w3 = __byte_perm(s23, 0, 0x3232);
      const uint32_t pa = kb + ra * 128 + ((oc ^ (ra & 7)) << 4), pb = kb + (mi == 0 ? 9216 : 0) + rb * 128 + ((oc ^ (rb & 7)) << 4);
      uint8_t* e0 = g_u + (uint32_t)((cg * 64 + oc * 8 + r) * UCH + (2040 - tb * 64 - 8 * q) * 2);
#pragma unroll
      for (int hb = 0; hb < 2; hb++) {
        uint32_t k[7], v[5];
        ldsm4t(pa + hb * 1024, k[3], k[4], k[5], k[6]);
        ldsm4t(pa + hb * 1024 + 9216, v[1], v[2], v[3], v[4]);
        ldsm4t(pb + hb * 1024, v[0], k[0], k[1], k[2]);
        uint32_t o1 = __byte_perm(k[1], k[0], 0x5432);
#pragma unroll
        for (int m = 0; m < 5; m++) {
          const uint32_t o2 = __byte_perm(k[m + 2], k[m + 1], 0x5432);
          v[m] = hmul2(hadd2(hadd2(hadd2(hmul2(o1, w3), hmul2(k[m + 1], w2)), hmul2(o2, w1)), hmul2(k[m + 2], w0)), v[m]);
          o1 = o2;
        }
        *(uint4*)(e0 - hb * 64) = make_uint4(v[4], v[3], v[2], v[1]);
        *(uint4*)(e0 - hb * 64 + UPITCH) = make_uint4(__byte_perm(v[4], v[3], 0x5432), __byte_perm(v[3], v[2], 0x5432), __byte_perm(v[2], v[1], 0x5432), __byte_perm(v[1], v[0], 0x5432));
        if (it >= PRE_EARLY) __nanosleep(PRE_SLEEP);
      }
    }
    bar_sync(5, 64);
    if (it == PRE_EARLY - 1 && aw == 0 && lane == 0) mbar_arrive(base + SM_RDY + 8 * RDY_AUX);
    if (aw == 1 && lane == 0) asm volatile("red.release.gpu.global.add.u32 [%0], %1;" :: "l"(g_cnt + (C_U + cg) * CSTRIDE), "r"(it ? 4 : 1) : "memory");
    if (it == 0) bar_sync(5, 64);
  }
  uint32_t rel;
  asm volatile("mapa.shared::cluster.u32 %0, %1, %2;" : "=r"(rel) : "r"(base + SM_BAR + 128 + 8 * (12 + (lane & 1))), "r"((lane >> 1) & 1));
  if (lane < 4) asm volatile("mbarrier.arrive.shared::cluster.b64 _, [%0];" :: "r"(rel) : "memory");
  if (MASK != PH_ALL) aux_gate(P, cta, aw, lane);
}

template<int MASK> __global__ void __cluster_dims__(2, 1, 1) __launch_bounds__(384, 1) gated_mix_kernel(const __grid_constant__ Maps M, const __grid_constant__ Params P) {
  extern __shared__ __align__(1024) uint8_t smem[];
  const uint32_t base = (uint32_t)__cvta_generic_to_shared(smem);
  if ((MASK & PH_KV) && elect()) {
    map_pf(&M.wk + (blockIdx.x & 1)); map_pf(&M.c);
  }
  const int wi = __shfl_sync(~0u, threadIdx.x >> 5, 0), wg = wi >> 2, warp = wi & 3;
  if (elect()) {
    if (wi < 8) {
      const int cnt = 1 << ((0x10332200 >> (4 * wi)) & 15);
#pragma unroll
      for (int i = 0; i < 8; i++) mbar_init(base + SM_BAR + 64 * wi + 8 * i, cnt);
      asm volatile("fence.mbarrier_init.release.cluster;" ::: "memory");
    }
  }
  const int cta = blockIdx.x;
  const bool first_loads = (MASK & PH_KV) && wi == 8 && cta < NREG;
  const CUtensorMap* mw = (cta & 1) ? &M.wv : &M.wk;
  __syncwarp();
  asm volatile("barrier.cluster.arrive.relaxed.aligned;\nbarrier.cluster.wait.aligned;" ::: "memory");
  auto first_stage = [&](int it) {
    const uint32_t bar = base + SM_BAR + 24 * it, d0 = base + 3 * it * UNIT;
    mbar_expect(bar, 3 * UNIT);
    tma3d_mc(d0 + (1 + (cta & 1)) * UNIT, mw, 0, it * 64, 2 * (cta >> 3), bar);
    tma2d(d0, &M.c, it * 64, (cta & 7) * 256, bar);
  };
  if (first_loads && elect()) first_stage(0);
  __syncwarp();
  const int lane = threadIdx.x & 31;
  if (wg == 2) {
    asm volatile("setmaxnreg.dec.sync.aligned.u32 56;");
    if (warp == 0) producer<MASK>(M, P, base, cta, lane);
    else if (warp == 1) sync_agent<MASK>(base, cta, lane);
    else if (cta < NREG) {
      if (MASK & PH_PRE) aux_pre<MASK>(M, P, base, cta, warp - 2, lane);
      if (MASK & PH_OUT) producer2<MASK>(M, P, base, cta, warp - 2, lane);
    }
    if (warp == 1) {
      if (MASK & PH_OUT) {
        unsigned old = 0;
        if (lane == 0) asm volatile("atom.relaxed.gpu.global.add.u32 %0, [%1], 1;" : "=r"(old) : "l"(g_cnt + C_EXIT * CSTRIDE) : "memory");
        old = __shfl_sync(~0u, old, 0);
        if (old == NCTA - 1) for (int i = lane; i < C_NUM; i += 32) g_cnt[i * CSTRIDE] = 0;
      }
      mbar_wait_slow(base + SM_SIG + 8 * SIG_DONE, 0);
      if (cta >= NREG || !(MASK & PH_OUT)) { cluster_arrive(); cluster_wait(); }
    }
  } else {
    asm volatile("setmaxnreg.inc.sync.aligned.u32 224;");
    uint32_t rel;
    asm volatile("mapa.shared::cluster.u32 %0, %1, %2;" : "=r"(rel) : "r"(base + SM_BAR + 128 + 8 * (lane & 15)), "r"(lane >> 4));
    Cons c{base, rel, 0u, lane, warp, wg, warp == 3 ? lane & 15 : 16};
    if (wg == 1) bar_arrive(1, 256);
    if ((MASK & PH_KV) && wi == 4 && cta < NREG) {
      if (elect()) {
#pragma unroll 1
        for (int it = 1; it < NFIRST; it++) {
          asm volatile("{\n.reg .pred p;\n.reg .u32 a, b;\nmov.u32 a, %%clock;\nXL:\nmov.u32 b, %%clock;\nsub.u32 b, b, a;\nsetp.lt.u32 p, b, %0;\n@p bra XL;\n}\n" :: "r"(it == 1 ? FGAP : FGAP2) : "memory");
          first_stage(it);
        }
      }
      __syncwarp();
    }
    if (cta < NREG) {
      const int g = cta & 7, j = cta >> 3;
      Pend w = {};
#pragma unroll 1
      for (int half = 0; half < 2; half++) {
        const int h = j + 16 * half, blk = kv_slot<MASK>(h) * 16 + 2 * g;
        if (MASK & PH_KV) cons_kv<(MASK & PH_ATT) != 0>(c, h, blk, g, w, half == 1 && (MASK & PH_ATT));
        if (MASK & PH_ATT) {
          Att a;
          cons_q<(MASK & PH_KV) != 0>(c, h, blk + 1, w, a.o, a.kn);
          cons_att(c, a, h, g, w);
          if (half == 0) c.signal(SIG_WAR);
          if (MASK != PH_ALL) { tile_store<0, 4>(w.lo, ctx_off(c, h, g, 1 - wg), lane); c.signal(SIG_CTX + half); }
        } else if (MASK & PH_KV) {
          float kn = 0.f;
          out_piece<SCH_KV, true>(c, w, kv_off(c, blk + 1), blk + 1, kn, 0, true);
          for (int ks = 1; ks < 8; ks++) out_piece<SCH_KV, false>(c, w, kv_off(c, blk + 1), blk + 1, kn, ks, true);
          c.signal(SIG_KV + half);
        }
      }
      if (MASK & PH_OUT) cons_out<MASK>(c, M, P, cta, w);
    }
    if (cta >= NREG || !(MASK & PH_OUT)) {
      if (MASK & PH_CONV) cons_conv<MASK>(c, cta, cta < NREG ? CV_REG<MASK> : CV_EXTRA<MASK>);
      c.signal(SIG_DONE);
      cluster_arrive();
    }
  }
}

typedef CUresult (*EncFn)(CUtensorMap*, CUtensorMapDataType, cuuint32_t, void*, const cuuint64_t*, const cuuint64_t*, const cuuint32_t*, const cuuint32_t*,
                          CUtensorMapInterleave, CUtensorMapSwizzle, CUtensorMapL2promotion, CUtensorMapFloatOOBfill);
static void enc(EncFn f, CUtensorMap* m, const void* ptr, int rank, const cuuint64_t* dims, const cuuint64_t* strides, const cuuint32_t* box, CUtensorMapSwizzle sw,
                CUtensorMapDataType dt = CU_TENSOR_MAP_DATA_TYPE_BFLOAT16) {
  const cuuint32_t es[4] = {1, 1, 1, 1};
  f(m, dt, rank, (void*)ptr, dims, strides, box, es, CU_TENSOR_MAP_INTERLEAVE_NONE, sw, CU_TENSOR_MAP_L2_PROMOTION_L2_256B, CU_TENSOR_MAP_FLOAT_OOB_FILL_NONE);
}
static void enc2(EncFn f, CUtensorMap* m, const void* ptr, int cols, int rows, int brows) {
  const cuuint64_t d[2] = {(cuuint64_t)cols, (cuuint64_t)rows}, s[1] = {(cuuint64_t)cols * 2}; const cuuint32_t b[2] = {64, (cuuint32_t)brows};
  enc(f, m, ptr, 2, d, s, b, CU_TENSOR_MAP_SWIZZLE_128B);
}
static void encw(EncFn f, CUtensorMap* m, const void* ptr, int cols, int rows) {
  const cuuint64_t d[3] = {64, (cuuint64_t)rows, (cuuint64_t)cols / 64}, s[2] = {(cuuint64_t)cols * 2, 128}; const cuuint32_t b[3] = {64, 64, 2};
  enc(f, m, ptr, 3, d, s, b, CU_TENSOR_MAP_SWIZZLE_128B);
}
extern "C" void kernel_launch(void* const* d_in, const int* in_sizes, int n_in, void* d_out, int out_size) {
  static EncFn fn = nullptr;
  static int ncl = 0;
  static void* zptr = nullptr;
  static void* tptr = nullptr;
  if (!fn) {
    void* p = nullptr; cudaDriverEntryPointQueryResult qr;
    cudaGetDriverEntryPoint("cuTensorMapEncodeTiled", &p, cudaEnableDefault, &qr);
    fn = (EncFn)p;
    cudaFuncSetAttribute(gated_mix_kernel<PH_ALL>, cudaFuncAttributeMaxDynamicSharedMemorySize, SMEM_BYTES);
    cudaFuncSetAttribute(gated_mix_kernel<PH_PRE | PH_KV>, cudaFuncAttributeMaxDynamicSharedMemorySize, SMEM_BYTES);
    cudaFuncSetAttribute(gated_mix_kernel<PH_ATT | PH_CONV>, cudaFuncAttributeMaxDynamicSharedMemorySize, SMEM_BYTES);
    cudaFuncSetAttribute(gated_mix_kernel<PH_OUT>, cudaFuncAttributeMaxDynamicSharedMemorySize, SMEM_BYTES);
    cudaLaunchConfig_t cfg = {}; cfg.gridDim = NCTA; cfg.blockDim = 384; cfg.dynamicSmemBytes = SMEM_BYTES;
    cudaLaunchAttribute at; at.id = cudaLaunchAttributeClusterDimension; at.val.clusterDim.x = 2; at.val.clusterDim.y = 1; at.val.clusterDim.z = 1;
    cfg.attrs = &at; cfg.numAttrs = 1;
    cudaOccupancyMaxActiveClusters(&ncl, gated_mix_kernel<PH_ALL>, &cfg);
    cudaGetSymbolAddress(&zptr, g_u);
    cudaGetSymbolAddress(&tptr, g_T);
  }
  Maps M;
  enc2(fn, &M.x, d_in[0], 1024, 2048, 128);
  enc2(fn, &M.c, d_in[7], 512, 2048, 128);
  enc2(fn, &M.wq, d_in[8], 4096, 1024, 64);
  encw(fn, &M.wk, d_in[9], 4096, 512);
  encw(fn, &M.wv, d_in[10], 4096, 512);
  encw(fn, &M.wo, d_in[11], 1024, 4096);
  { const cuuint64_t d[3] = {64, 32, 1024}, s[2] = {128, 4096}; const cuuint32_t b[3] = {64, 40, 1}; enc(fn, &M.h, d_in[4], 3, d, s, b, CU_TENSOR_MAP_SWIZZLE_NONE); }
  { const cuuint64_t d[2] = {2048, 1024}, s[1] = {UCH}; const cuuint32_t b[2] = {64, 128}; enc(fn, &M.z, zptr, 2, d, s, b, CU_TENSOR_MAP_SWIZZLE_128B); }
  { const cuuint64_t d[2] = {512, 512 * 16}, s[1] = {2048}; const cuuint32_t b[2] = {256, 8};
    enc(fn, &M.ctx, tptr, 2, d, s, b, CU_TENSOR_MAP_SWIZZLE_NONE, CU_TENSOR_MAP_DATA_TYPE_UINT32); }
  { const cuuint64_t d[4] = {1024, 2, 256, 4}, s[3] = {2048, 16384, 4096}; const cuuint32_t b[4] = {64, 2, 9, 4};
    enc(fn, &M.k, d_in[1], 4, d, s, b, CU_TENSOR_MAP_SWIZZLE_128B); enc(fn, &M.v, d_in[2], 4, d, s, b, CU_TENSOR_MAP_SWIZZLE_128B); }
  Params P{(const __nv_bfloat16*)d_in[0], (const __nv_bfloat16*)d_in[3],
           (const __nv_bfloat16*)d_in[5], (const __nv_bfloat16*)d_in[12],
           (const __nv_bfloat16*)d_in[9], (const __nv_bfloat16*)d_in[10], (const __nv_bfloat16*)d_in[7], (__nv_bfloat16*)d_out};
  bool split = 2 * ncl < NCTA;
  if (!split) {
    gated_mix_kernel<PH_ALL><<<NCTA, 384, SMEM_BYTES>>>(M, P);
  } else {
    gated_mix_kernel<PH_PRE | PH_KV><<<NCTA, 384, SMEM_BYTES>>>(M, P);
    gated_mix_kernel<PH_ATT | PH_CONV><<<NCTA, 384, SMEM_BYTES>>>(M, P);
    gated_mix_kernel<PH_OUT><<<NCTA, 384, SMEM_BYTES>>>(M, P);
  }
}
```

```cpp
#include <cuda_runtime.h>
#include <cuda.h>
#include <cuda_bf16.h>
#include <stdint.h>

template<int TB> __device__ __forceinline__ void wgmma_ss_n256(float (&d)[128], uint64_t da, uint64_t db, int scale_d) {
  asm volatile("{\n.reg .pred p;\nsetp.ne.b32 p, %130, 0;\n"
    "wgmma.mma_async.sync.aligned.m64n256k16.f32.bf16.bf16 {%0, %1, %2, %3, %4, %5, %6, %7, %8, %9, %10, %11, %12, %13, %14, %15, %16, %17, %18, %19, %20, %21, %22, %23, %24, %25, %26, %27, %28, %29, %30, %31, %32, %33, %34, %35, %36, %37, %38, %39, %40, %41, %42, %43, %44, %45, %46, %47, %48, %49, %50, %51, %52, %53, %54, %55, %56, %57, %58, %59, %60, %61, %62, %63, %64, %65, %66, %67, %68, %69, %70, %71, %72, %73, %74, %75, %76, %77, %78, %79, %80, %81, %82, %83, %84, %85, %86, %87, %88, %89, %90, %91, %92, %93, %94, %95, %96, %97, %98, %99, %100, %101, %102, %103, %104, %105, %106, %107, %108, %109, %110, %111, %112, %113, %114, %115, %116, %117, %118, %119, %120, %121, %122, %123, %124, %125, %126, %127}, %128, %129, p, 1, 1, 0, %131;\n}\n"
    : "+f"(d[0]), "+f"(d[1]), "+f"(d[2]), "+f"(d[3]), "+f"(d[4]), "+f"(d[5]), "+f"(d[6]), "+f"(d[7]), "+f"(d[8]), "+f"(d[9]), "+f"(d[10]), "+f"(d[11]), "+f"(d[12]), "+f"(d[13]), "+f"(d[14]), "+f"(d[15]), "+f"(d[16]), "+f"(d[17]), "+f"(d[18]), "+f"(d[19]), "+f"(d[20]), "+f"(d[21]), "+f"(d[22]), "+f"(d[23]), "+f"(d[24]), "+f"(d[25]), "+f"(d[26]), "+f"(d[27]), "+f"(d[28]), "+f"(d[29]), "+f"(d[30]), "+f"(d[31]), "+f"(d[32]), "+f"(d[33]), "+f"(d[34]), "+f"(d[35]), "+f"(d[36]), "+f"(d[37]), "+f"(d[38]), "+f"(d[39]), "+f"(d[40]), "+f"(d[41]), "+f"(d[42]), "+f"(d[43]), "+f"(d[44]), "+f"(d[45]), "+f"(d[46]), "+f"(d[47]), "+f"(d[48]), "+f"(d[49]), "+f"(d[50]), "+f"(d[51]), "+f"(d[52]), "+f"(d[53]), "+f"(d[54]), "+f"(d[55]), "+f"(d[56]), "+f"(d[57]), "+f"(d[58]), "+f"(d[59]), "+f"(d[60]), "+f"(d[61]), "+f"(d[62]), "+f"(d[63]), "+f"(d[64]), "+f"(d[65]), "+f"(d[66]), "+f"(d[67]), "+f"(d[68]), "+f"(d[69]), "+f"(d[70]), "+f"(d[71]), "+f"(d[72]), "+f"(d[73]), "+f"(d[74]), "+f"(d[75]), "+f"(d[76]), "+f"(d[77]), "+f"(d[78]), "+f"(d[79]), "+f"(d[80]), "+f"(d[81]), "+f"(d[82]), "+f"(d[83]), "+f"(d[84]), "+f"(d[85]), "+f"(d[86]), "+f"(d[87]), "+f"(d[88]), "+f"(d[89]), "+f"(d[90]), "+f"(d[91]), "+f"(d[92]), "+f"(d[93]), "+f"(d[94]), "+f"(d[95]), "+f"(d[96]), "+f"(d[97]), "+f"(d[98]), "+f"(d[99]), "+f"(d[100]), "+f"(d[101]), "+f"(d[102]), "+f"(d[103]), "+f"(d[104]), "+f"(d[105]), "+f"(d[106]), "+f"(d[107]), "+f"(d[108]), "+f"(d[109]), "+f"(d[110]), "+f"(d[111]), "+f"(d[112]), "+f"(d[113]), "+f"(d[114]), "+f"(d[115]), "+f"(d[116]), "+f"(d[117]), "+f"(d[118]), "+f"(d[119]), "+f"(d[120]), "+f"(d[121]), "+f"(d[122]), "+f"(d[123]), "+f"(d[124]), "+f"(d[125]), "+f"(d[126]), "+f"(d[127])
    : "l"(da), "l"(db), "r"(scale_d), "n"(TB));
}
template<int TB> __device__ __forceinline__ void wgmma_ss_n128(float (&d)[64], uint64_t da, uint64_t db, int scale_d) {
  asm volatile("{\n.reg .pred p;\nsetp.ne.b32 p, %66, 0;\n"
    "wgmma.mma_async.sync.aligned.m64n128k16.f32.bf16.bf16 {%0, %1, %2, %3, %4, %5, %6, %7, %8, %9, %10, %11, %12, %13, %14, %15, %16, %17, %18, %19, %20, %21, %22, %23, %24, %25, %26, %27, %28, %29, %30, %31, %32, %33, %34, %35, %36, %37, %38, %39, %40, %41, %42, %43, %44, %45, %46, %47, %48, %49, %50, %51, %52, %53, %54, %55, %56, %57, %58, %59, %60, %61, %62, %63}, %64, %65, p, 1, 1, 0, %67;\n}\n"
    : "+f"(d[0]), "+f"(d[1]), "+f"(d[2]), "+f"(d[3]), "+f"(d[4]), "+f"(d[5]), "+f"(d[6]), "+f"(d[7]), "+f"(d[8]), "+f"(d[9]), "+f"(d[10]), "+f"(d[11]), "+f"(d[12]), "+f"(d[13]), "+f"(d[14]), "+f"(d[15]), "+f"(d[16]), "+f"(d[17]), "+f"(d[18]), "+f"(d[19]), "+f"(d[20]), "+f"(d[21]), "+f"(d[22]), "+f"(d[23]), "+f"(d[24]), "+f"(d[25]), "+f"(d[26]), "+f"(d[27]), "+f"(d[28]), "+f"(d[29]), "+f"(d[30]), "+f"(d[31]), "+f"(d[32]), "+f"(d[33]), "+f"(d[34]), "+f"(d[35]), "+f"(d[36]), "+f"(d[37]), "+f"(d[38]), "+f"(d[39]), "+f"(d[40]), "+f"(d[41]), "+f"(d[42]), "+f"(d[43]), "+f"(d[44]), "+f"(d[45]), "+f"(d[46]), "+f"(d[47]), "+f"(d[48]), "+f"(d[49]), "+f"(d[50]), "+f"(d[51]), "+f"(d[52]), "+f"(d[53]), "+f"(d[54]), "+f"(d[55]), "+f"(d[56]), "+f"(d[57]), "+f"(d[58]), "+f"(d[59]), "+f"(d[60]), "+f"(d[61]), "+f"(d[62]), "+f"(d[63])
    : "l"(da), "l"(db), "r"(scale_d), "n"(TB));
}
template<int TB> __device__ __forceinline__ void wgmma_ss_n64(float (&d)[32], uint64_t da, uint64_t db, int scale_d) {
  asm volatile("{\n.reg .pred p;\nsetp.ne.b32 p, %34, 0;\n"
    "wgmma.mma_async.sync.aligned.m64n64k16.f32.bf16.bf16 {%0, %1, %2, %3, %4, %5, %6, %7, %8, %9, %10, %11, %12, %13, %14, %15, %16, %17, %18, %19, %20, %21, %22, %23, %24, %25, %26, %27, %28, %29, %30, %31}, %32, %33, p, 1, 1, 0, %35;\n}\n"
    : "+f"(d[0]), "+f"(d[1]), "+f"(d[2]), "+f"(d[3]), "+f"(d[4]), "+f"(d[5]), "+f"(d[6]), "+f"(d[7]), "+f"(d[8]), "+f"(d[9]), "+f"(d[10]), "+f"(d[11]), "+f"(d[12]), "+f"(d[13]), "+f"(d[14]), "+f"(d[15]), "+f"(d[16]), "+f"(d[17]), "+f"(d[18]), "+f"(d[19]), "+f"(d[20]), "+f"(d[21]), "+f"(d[22]), "+f"(d[23]), "+f"(d[24]), "+f"(d[25]), "+f"(d[26]), "+f"(d[27]), "+f"(d[28]), "+f"(d[29]), "+f"(d[30]), "+f"(d[31])
    : "l"(da), "l"(db), "r"(scale_d), "n"(TB));
}
template<int TB> __device__ __forceinline__ void wgmma_rs_n32(float (&d)[16], uint32_t a0, uint32_t a1, uint32_t a2, uint32_t a3, uint64_t db, int scale_d) {
  asm volatile("{\n.reg .pred p;\nsetp.ne.b32 p, %21, 0;\n"
    "wgmma.mma_async.sync.aligned.m64n32k16.f32.bf16.bf16 {%0, %1, %2, %3, %4, %5, %6, %7, %8, %9, %10, %11, %12, %13, %14, %15}, {%16, %17, %18, %19}, %20, p, 1, 1, %22;\n}\n"
    : "+f"(d[0]), "+f"(d[1]), "+f"(d[2]), "+f"(d[3]), "+f"(d[4]), "+f"(d[5]), "+f"(d[6]), "+f"(d[7]), "+f"(d[8]), "+f"(d[9]), "+f"(d[10]), "+f"(d[11]), "+f"(d[12]), "+f"(d[13]), "+f"(d[14]), "+f"(d[15])
    : "r"(a0), "r"(a1), "r"(a2), "r"(a3), "l"(db), "r"(scale_d), "n"(TB));
}
__device__ __forceinline__ void wgmma_pv_sel(float (&d)[64], const uint32_t (&p)[32], uint64_t db, int full, int acc, int wg) {
  asm volatile("{\n.reg .pred q, s, w;\n.reg .b64 t;\nsetp.eq.b32 w, %99, 0;\nsetp.ne.b32 s, %98, 0;\nsetp.eq.b32 q, %97, 0;\n@q bra.uni LH;\n"
    "wgmma.fence.sync.aligned;\n"
    "add.s64 t, %96, 0;\nwgmma.mma_async.sync.aligned.m64n128k16.f32.bf16.bf16 {%0, %1, %2, %3, %4, %5, %6, %7, %8, %9, %10, %11, %12, %13, %14, %15, %16, %17, %18, %19, %20, %21, %22, %23, %24, %25, %26, %27, %28, %29, %30, %31, %32, %33, %34, %35, %36, %37, %38, %39, %40, %41, %42, %43, %44, %45, %46, %47, %48, %49, %50, %51, %52, %53, %54, %55, %56, %57, %58, %59, %60, %61, %62, %63}, {%64, %65, %66, %67}, t, s, 1, 1, 1;\n"
    "add.s64 t, %96, 256;\nwgmma.mma_async.sync.aligned.m64n128k16.f32.bf16.bf16 {%0, %1, %2, %3, %4, %5, %6, %7, %8, %9, %10, %11, %12, %13, %14, %15, %16, %17, %18, %19, %20, %21, %22, %23, %24, %25, %26, %27, %28, %29, %30, %31, %32, %33, %34, %35, %36, %37, %38, %39, %40, %41, %42, %43, %44, %45, %46, %47, %48, %49, %50, %51, %52, %53, %54, %55, %56, %57, %58, %59, %60, %61, %62, %63}, {%68, %69, %70, %71}, t, 1, 1, 1, 1;\n"
    "add.s64 t, %96, 512;\nwgmma.mma_async.sync.aligned.m64n128k16.f32.bf16.bf16 {%0, %1, %2, %3, %4, %5, %6, %7, %8, %9, %10, %11, %12, %13, %14, %15, %16, %17, %18, %19, %20, %21, %22, %23, %24, %25, %26, %27, %28, %29, %30, %31, %32, %33, %34, %35, %36, %37, %38, %39, %40, %41, %42, %43, %44, %45, %46, %47, %48, %49, %50, %51, %52, %53, %54, %55, %56, %57, %58, %59, %60, %61, %62, %63}, {%72, %73, %74, %75}, t, 1, 1, 1, 1;\n"
    "add.s64 t, %96, 768;\nwgmma.mma_async.sync.aligned.m64n128k16.f32.bf16.bf16 {%0, %1, %2, %3, %4, %5, %6, %7, %8, %9, %10, %11, %12, %13, %14, %15, %16, %17, %18, %19, %20, %21, %22, %23, %24, %25, %26, %27, %28, %29, %30, %31, %32, %33, %34, %35, %36, %37, %38, %39, %40, %41, %42, %43, %44, %45, %46, %47, %48, %49, %50, %51, %52, %53, %54, %55, %56, %57, %58, %59, %60, %61, %62, %63}, {%76, %77, %78, %79}, t, 1, 1, 1, 1;\n"
    "add.s64 t, %96, 1024;\nwgmma.mma_async.sync.aligned.m64n128k16.f32.bf16.bf16 {%0, %1, %2, %3, %4, %5, %6, %7, %8, %9, %10, %11, %12, %13, %14, %15, %16, %17, %18, %19, %20, %21, %22, %23, %24, %25, %26, %27, %28, %29, %30, %31, %32, %33, %34, %35, %36, %37, %38, %39, %40, %41, %42, %43, %44, %45, %46, %47, %48, %49, %50, %51, %52, %53, %54, %55, %56, %57, %58, %59, %60, %61, %62, %63}, {%80, %81, %82, %83}, t, 1, 1, 1, 1;\n"
    "add.s64 t, %96, 1280;\nwgmma.mma_async.sync.aligned.m64n128k16.f32.bf16.bf16 {%0, %1, %2, %3, %4, %5, %6, %7, %8, %9, %10, %11, %12, %13, %14, %15, %16, %17, %18, %19, %20, %21, %22, %23, %24, %25, %26, %27, %28, %29, %30, %31, %32, %33, %34, %35, %36, %37, %38, %39, %40, %41, %42, %43, %44, %45, %46, %47, %48, %49, %50, %51, %52, %53, %54, %55, %56, %57, %58, %59, %60, %61, %62, %63}, {%84, %85, %86, %87}, t, 1, 1, 1, 1;\n"
    "@w bar.arrive 2, 256;\n@!w bar.arrive 1, 256;\n"
    "add.s64 t, %96, 1536;\nwgmma.mma_async.sync.aligned.m64n128k16.f32.bf16.bf16 {%0, %1, %2, %3, %4, %5, %6, %7, %8, %9, %10, %11, %12, %13, %14, %15, %16, %17, %18, %19, %20, %21, %22, %23, %24, %25, %26, %27, %28, %29, %30, %31, %32, %33, %34, %35, %36, %37, %38, %39, %40, %41, %42, %43, %44, %45, %46, %47, %48, %49, %50, %51, %52, %53, %54, %55, %56, %57, %58, %59, %60, %61, %62, %63}, {%88, %89, %90, %91}, t, 1, 1, 1, 1;\n"
    "add.s64 t, %96, 1792;\nwgmma.mma_async.sync.aligned.m64n128k16.f32.bf16.bf16 {%0, %1, %2, %3, %4, %5, %6, %7, %8, %9, %10, %11, %12, %13, %14, %15, %16, %17, %18, %19, %20, %21, %22, %23, %24, %25, %26, %27, %28, %29, %30, %31, %32, %33, %34, %35, %36, %37, %38, %39, %40, %41, %42, %43, %44, %45, %46, %47, %48, %49, %50, %51, %52, %53, %54, %55, %56, %57, %58, %59, %60, %61, %62, %63}, {%92, %93, %94, %95}, t, 1, 1, 1, 1;\n"
    "wgmma.commit_group.sync.aligned;\n"
    "bra.uni LE;\nLH:\n"
    "wgmma.fence.sync.aligned;\n"
    "add.s64 t, %96, 0;\nwgmma.mma_async.sync.aligned.m64n128k16.f32.bf16.bf16 {%0, %1, %2, %3, %4, %5, %6, %7, %8, %9, %10, %11, %12, %13, %14, %15, %16, %17, %18, %19, %20, %21, %22, %23, %24, %25, %26, %27, %28, %29, %30, %31, %32, %33, %34, %35, %36, %37, %38, %39, %40, %41, %42, %43, %44, %45, %46, %47, %48, %49, %50, %51, %52, %53, %54, %55, %56, %57, %58, %59, %60, %61, %62, %63}, {%80, %81, %82, %83}, t, s, 1, 1, 1;\n"
    "add.s64 t, %96, 256;\nwgmma.mma_async.sync.aligned.m64n128k16.f32.bf16.bf16 {%0, %1, %2, %3, %4, %5, %6, %7, %8, %9, %10, %11, %12, %13, %14, %15, %16, %17, %18, %19, %20, %21, %22, %23, %24, %25, %26, %27, %28, %29, %30, %31, %32, %33, %34, %35, %36, %37, %38, %39, %40, %41, %42, %43, %44, %45, %46, %47, %48, %49, %50, %51, %52, %53, %54, %55, %56, %57, %58, %59, %60, %61, %62, %63}, {%84, %85, %86, %87}, t, 1, 1, 1, 1;\n"
    "@w bar.arrive 2, 256;\n@!w bar.arrive 1, 256;\n"
    "add.s64 t, %96, 512;\nwgmma.mma_async.sync.aligned.m64n128k16.f32.bf16.bf16 {%0, %1, %2, %3, %4, %5, %6, %7, %8, %9, %10, %11, %12, %13, %14, %15, %16, %17, %18, %19, %20, %21, %22, %23, %24, %25, %26, %27, %28, %29, %30, %31, %32, %33, %34, %35, %36, %37, %38, %39, %40, %41, %42, %43, %44, %45, %46, %47, %48, %49, %50, %51, %52, %53, %54, %55, %56, %57, %58, %59, %60, %61, %62, %63}, {%88, %89, %90, %91}, t, 1, 1, 1, 1;\n"
    "add.s64 t, %96, 768;\nwgmma.mma_async.sync.aligned.m64n128k16.f32.bf16.bf16 {%0, %1, %2, %3, %4, %5, %6, %7, %8, %9, %10, %11, %12, %13, %14, %15, %16, %17, %18, %19, %20, %21, %22, %23, %24, %25, %26, %27, %28, %29, %30, %31, %32, %33, %34, %35, %36, %37, %38, %39, %40, %41, %42, %43, %44, %45, %46, %47, %48, %49, %50, %51, %52, %53, %54, %55, %56, %57, %58, %59, %60, %61, %62, %63}, {%92, %93, %94, %95}, t, 1, 1, 1, 1;\n"
    "wgmma.commit_group.sync.aligned;\n"
    "LE:\n}\n"
    : "+f"(d[0]), "+f"(d[1]), "+f"(d[2]), "+f"(d[3]), "+f"(d[4]), "+f"(d[5]), "+f"(d[6]), "+f"(d[7]), "+f"(d[8]), "+f"(d[9]), "+f"(d[10]), "+f"(d[11]), "+f"(d[12]), "+f"(d[13]), "+f"(d[14]), "+f"(d[15]), "+f"(d[16]), "+f"(d[17]), "+f"(d[18]), "+f"(d[19]), "+f"(d[20]), "+f"(d[21]), "+f"(d[22]), "+f"(d[23]), "+f"(d[24]), "+f"(d[25]), "+f"(d[26]), "+f"(d[27]), "+f"(d[28]), "+f"(d[29]), "+f"(d[30]), "+f"(d[31]), "+f"(d[32]), "+f"(d[33]), "+f"(d[34]), "+f"(d[35]), "+f"(d[36]), "+f"(d[37]), "+f"(d[38]), "+f"(d[39]), "+f"(d[40]), "+f"(d[41]), "+f"(d[42]), "+f"(d[43]), "+f"(d[44]), "+f"(d[45]), "+f"(d[46]), "+f"(d[47]), "+f"(d[48]), "+f"(d[49]), "+f"(d[50]), "+f"(d[51]), "+f"(d[52]), "+f"(d[53]), "+f"(d[54]), "+f"(d[55]), "+f"(d[56]), "+f"(d[57]), "+f"(d[58]), "+f"(d[59]), "+f"(d[60]), "+f"(d[61]), "+f"(d[62]), "+f"(d[63])
    : "r"(p[0]), "r"(p[1]), "r"(p[2]), "r"(p[3]), "r"(p[4]), "r"(p[5]), "r"(p[6]), "r"(p[7]), "r"(p[8]), "r"(p[9]), "r"(p[10]), "r"(p[11]), "r"(p[12]), "r"(p[13]), "r"(p[14]), "r"(p[15]), "r"(p[16]), "r"(p[17]), "r"(p[18]), "r"(p[19]), "r"(p[20]), "r"(p[21]), "r"(p[22]), "r"(p[23]), "r"(p[24]), "r"(p[25]), "r"(p[26]), "r"(p[27]), "r"(p[28]), "r"(p[29]), "r"(p[30]), "r"(p[31]), "l"(db), "r"(full), "r"(acc), "r"(wg) : "memory");
}

constexpr int NCTA = 132, NREG = 128;
constexpr int UNIT = 16384, NUNIT = 14;
constexpr uint32_t SMEM_BASE = 1024;
constexpr int SM_BAR = NUNIT * UNIT;
constexpr int SM_GATE = SM_BAR + 1024;
constexpr int SMEM_BYTES = SM_BAR + 1536;
constexpr int UPITCH = 4160, UCH = 2 * UPITCH;
constexpr float QSCALE = 0.08838834764831845f * 1.4426950408889634f;
constexpr float BOUND2 = 60.f * 60.f / 1.15f;
#define NSKIP 8
constexpr int C_KV = 0;
constexpr int C_CTX = 32;
constexpr int C_U = 48;
constexpr int C_Z = 80;
constexpr int C_GATE = 88;
constexpr int C_EXIT = 89, C_TICKET = 90;
#define ATT_SPLIT 4
#define SL_BAR 256
#define SL_CNT 0
#define PF_WAIT 6
#define PF_GAP 300
#define TK 24
#define Z_AT 60
#define PRE_SLEEP 300
#define GATE_SLEEP 1000
#define OC_S0 2
#define OC_S1 11
#define OC_L0 18
#define OC_L1 18
#define ST_1 4
#define ST_D 2
#define SCH_KV 0x7766555443322100ull
#define SCH_Q 0x7766555443322100ull
#define NK_AT 1
#define NV_AT 3
#define CHK_D 11
#define FGAP 600
#define FGAP2 200
constexpr int PRE_EARLY = 2, NFIRST = 4;
constexpr int C_WAR = 96;
constexpr int C_NUM = 112;
constexpr int CSTRIDE = 32;
constexpr int SM_KMAX = SM_BAR + 640, SM_DUMMY = SM_BAR + 648, SM_POOL = SM_BAR + 652, SM_PRE = SM_BAR + 112, SM_SIG = SM_BAR + 256, SM_RDY = SM_BAR + 384;
enum { SIG_KV = 0, SIG_CTX = 2, SIG_Z = 4, SIG_DONE = 8, SIG_WAR = 9, SIG_ATT = 10 };
enum { RDY_KV = 0, RDY_CTX = 2, RDY_WAR = 4, RDY_G = 5, RDY_X = 6, RDY_AUX = 7, RDY_U = 8, RDY_Z = 9, RDY_T = 10, RDY_DRAW = 11 };
enum { PH_PRE = 1, PH_KV = 2, PH_ATT = 4, PH_CONV = 8, PH_OUT = 16, PH_ALL = 31 };

constexpr uint32_t T_CTX = 0, T_KV = 16 * 32 * 32768, T_BYTES = T_KV + 32 * 16 * 65536;
__device__ __align__(1024) uint8_t g_T[T_BYTES];
__device__ __align__(1024) uint8_t g_u[1024 * UCH];
__device__ __align__(1024) float g_gate[2048];
__device__ __align__(1024) float g_kn2[32 * 128];
__device__ __align__(1024) unsigned g_cnt[C_NUM * CSTRIDE];

struct __align__(64) Maps { CUtensorMap c, wk, wv, x, wq, wo, h, z, ctx, k, v; };
struct Params {
  const __nv_bfloat16 *x, *shift, *D, *gw, *wk, *wv, *c;
  __nv_bfloat16* out;
};

__device__ __forceinline__ void wg_fence() { asm volatile("wgmma.fence.sync.aligned;" ::: "memory"); }
__device__ __forceinline__ void wg_commit() { asm volatile("wgmma.commit_group.sync.aligned;" ::: "memory"); }
template<int N> __device__ __forceinline__ void wg_wait() { asm volatile("wgmma.wait_group.sync.aligned %0;" :: "n"(N) : "memory"); }
__device__ __forceinline__ uint64_t odesc(uint32_t addr, uint32_t lbo, uint32_t sbo, uint32_t swz) {
  uint64_t d = (uint64_t)(addr >> 4) + (((uint64_t)(lbo >> 4) << 16) | ((uint64_t)(sbo >> 4) << 32) | ((uint64_t)swz << 62));
  asm volatile("" : "+l"(d));
  return d;
}
__device__ __forceinline__ void mbar_init(uint32_t bar, int cnt) { asm volatile("mbarrier.init.shared::cta.b64 [%0], %1;" :: "r"(bar), "r"(cnt)); }
__device__ __forceinline__ void mbar_expect(uint32_t bar, uint32_t bytes) { asm volatile("mbarrier.arrive.expect_tx.shared::cta.b64 _, [%0], %1;" :: "r"(bar), "r"(bytes) : "memory"); }
__device__ __forceinline__ void mbar_arrive(uint32_t bar) { asm volatile("mbarrier.arrive.shared::cta.b64 _, [%0];" :: "r"(bar) : "memory"); }
__device__ __forceinline__ void mbar_wait(uint32_t bar, uint32_t parity) {
  asm volatile("{\n.reg .pred p;\nLW:\nmbarrier.try_wait.parity.shared::cta.b64 p, [%0], %1;\n@!p bra LW;\n}\n" :: "r"(bar), "r"(parity) : "memory");
}
template<int NS = SL_BAR> __device__ __forceinline__ void mbar_wait_slow(uint32_t bar, uint32_t parity) {
  asm volatile("{\n.reg .pred p;\n.reg .u32 n;\nmov.u32 n, 0;\n"
    "LW:\nmbarrier.test_wait.parity.shared::cta.b64 p, [%0], %1;\n@p bra LD;\n"
    "nanosleep.u32 %2;\nadd.u32 n, n, 1;\nsetp.lt.u32 p, n, 16777216;\n@p bra LW;\ntrap;\nLD:\n}\n" :: "r"(bar), "r"(parity), "n"(NS) : "memory");
}
__device__ __forceinline__ void mbar_wait_all(uint32_t bar, uint32_t parity) {
  asm volatile("{\n.reg .pred p, q;\nLW:\nmbarrier.try_wait.parity.shared::cta.b64 p, [%0], %1;\nvote.sync.all.pred q, p, 0xffffffff;\n@!q bra.uni LW;\n}\n" :: "r"(bar), "r"(parity) : "memory");
}
__device__ __forceinline__ void cnt_wait(const unsigned* p, unsigned target) {
  asm volatile("{\n.reg .pred p;\n.reg .u32 n, v;\nmov.u32 n, 0;\n"
    "LW:\nld.relaxed.gpu.global.u32 v, [%0];\nsetp.ge.u32 p, v, %1;\n@p bra LD;\n"
    "nanosleep.u32 %2;\nadd.u32 n, n, 1;\nsetp.lt.u32 p, n, 4194304;\n@p bra LW;\ntrap;\nLD:\nfence.acquire.gpu;\nfence.proxy.async.global;\n}\n" :: "l"(p), "r"(target), "n"(SL_CNT) : "memory");
}
__device__ __forceinline__ void cnt_signal(unsigned* p, int lane) {
  __syncwarp();
  if (lane == 0) asm volatile("red.release.gpu.global.add.u32 [%0], 1;" :: "l"(p) : "memory");
}
__device__ __forceinline__ void cnt_publish(unsigned* p, unsigned n, bool fence) {
  if (fence) asm volatile("fence.release.gpu;" ::: "memory");
  asm volatile("red.relaxed.gpu.global.add.u32 [%0], %1;" :: "l"(p), "r"(n) : "memory");
}
__device__ __forceinline__ uint64_t pol_first() { uint64_t p; asm("createpolicy.fractional.L2::evict_first.b64 %0, 1.0;" : "=l"(p)); return p; }
__device__ __forceinline__ void bulk_g2s(uint32_t dst, const void* src, uint32_t bytes, uint32_t bar, bool stream = false) {
  if (stream) asm volatile("cp.async.bulk.shared::cluster.global.mbarrier::complete_tx::bytes.L2::cache_hint [%0], [%1], %2, [%3], %4;" :: "r"(dst), "l"(src), "r"(bytes), "r"(bar), "l"(pol_first()) : "memory");
  else asm volatile("cp.async.bulk.shared::cluster.global.mbarrier::complete_tx::bytes [%0], [%1], %2, [%3];" :: "r"(dst), "l"(src), "r"(bytes), "r"(bar) : "memory");
}
__device__ __forceinline__ void tma2d(uint32_t dst, const CUtensorMap* m, int x, int y, uint32_t bar, bool stream = false) {
  if (stream) asm volatile("cp.async.bulk.tensor.2d.shared::cluster.global.mbarrier::complete_tx::bytes.L2::cache_hint [%0], [%1, {%3, %4}], [%2], %5;" :: "r"(dst), "l"(m), "r"(bar), "r"(x), "r"(y), "l"(pol_first()) : "memory");
  else asm volatile("cp.async.bulk.tensor.2d.shared::cluster.global.mbarrier::complete_tx::bytes [%0], [%1, {%3, %4}], [%2];" :: "r"(dst), "l"(m), "r"(bar), "r"(x), "r"(y) : "memory");
}
__device__ __forceinline__ void tma3d(uint32_t dst, const CUtensorMap* m, int x, int y, int z, uint32_t bar, bool stream = false) {
  if (stream) asm volatile("cp.async.bulk.tensor.3d.shared::cluster.global.mbarrier::complete_tx::bytes.L2::cache_hint [%0], [%1, {%3, %4, %5}], [%2], %6;" :: "r"(dst), "l"(m), "r"(bar), "r"(x), "r"(y), "r"(z), "l"(pol_first()) : "memory");
  else asm volatile("cp.async.bulk.tensor.3d.shared::cluster.global.mbarrier::complete_tx::bytes [%0], [%1, {%3, %4, %5}], [%2];" :: "r"(dst), "l"(m), "r"(bar), "r"(x), "r"(y), "r"(z) : "memory");
}
__device__ __forceinline__ void tma4d(uint32_t dst, const CUtensorMap* m, int x, int y, int z, int w, uint32_t bar, bool stream = false) {
  if (stream) asm volatile("cp.async.bulk.tensor.4d.shared::cluster.global.mbarrier::complete_tx::bytes.L2::cache_hint [%0], [%1, {%3, %4, %5, %6}], [%2], %7;" :: "r"(dst), "l"(m), "r"(bar), "r"(x), "r"(y), "r"(z), "r"(w), "l"(pol_first()) : "memory");
  else asm volatile("cp.async.bulk.tensor.4d.shared::cluster.global.mbarrier::complete_tx::bytes [%0], [%1, {%3, %4, %5, %6}], [%2];" :: "r"(dst), "l"(m), "r"(bar), "r"(x), "r"(y), "r"(z), "r"(w) : "memory");
}
__device__ __forceinline__ void bulk_g2s_mc(uint32_t dst, const void* src, uint32_t bytes, uint32_t bar, bool stream = false) {
  if (stream) asm volatile("cp.async.bulk.shared::cluster.global.mbarrier::complete_tx::bytes.multicast::cluster.L2::cache_hint [%0], [%1], %2, [%3], %4, %5;" :: "r"(dst), "l"(src), "r"(bytes), "r"(bar), "h"((uint16_t)3), "l"(pol_first()) : "memory");
  else asm volatile("cp.async.bulk.shared::cluster.global.mbarrier::complete_tx::bytes.multicast::cluster [%0], [%1], %2, [%3], %4;" :: "r"(dst), "l"(src), "r"(bytes), "r"(bar), "h"((uint16_t)3) : "memory");
}
__device__ __forceinline__ void tma2d_mc(uint32_t dst, const CUtensorMap* m, int x, int y, uint32_t bar, bool stream = false) {
  if (stream) asm volatile("cp.async.bulk.tensor.2d.shared::cluster.global.mbarrier::complete_tx::bytes.multicast::cluster.L2::cache_hint [%0], [%1, {%3, %4}], [%2], %5, %6;" :: "r"(dst), "l"(m), "r"(bar), "r"(x), "r"(y), "h"((uint16_t)3), "l"(pol_first()) : "memory");
  else asm volatile("cp.async.bulk.tensor.2d.shared::cluster.global.mbarrier::complete_tx::bytes.multicast::cluster [%0], [%1, {%3, %4}], [%2], %5;" :: "r"(dst), "l"(m), "r"(bar), "r"(x), "r"(y), "h"((uint16_t)3) : "memory");
}
__device__ __forceinline__ void tma3d_mc(uint32_t dst, const CUtensorMap* m, int x, int y, int z, uint32_t bar, bool stream = false) {
  if (stream) asm volatile("cp.async.bulk.tensor.3d.shared::cluster.global.mbarrier::complete_tx::bytes.multicast::cluster.L2::cache_hint [%0], [%1, {%3, %4, %5}], [%2], %6, %7;" :: "r"(dst), "l"(m), "r"(bar), "r"(x), "r"(y), "r"(z), "h"((uint16_t)3), "l"(pol_first()) : "memory");
  else asm volatile("cp.async.bulk.tensor.3d.shared::cluster.global.mbarrier::complete_tx::bytes.multicast::cluster [%0], [%1, {%3, %4, %5}], [%2], %6;" :: "r"(dst), "l"(m), "r"(bar), "r"(x), "r"(y), "r"(z), "h"((uint16_t)3) : "memory");
}
__device__ __forceinline__ void map_pf(const CUtensorMap* m) { asm volatile("prefetch.tensormap [%0];" :: "l"(m) : "memory"); }
__device__ __forceinline__ bool elect() {
  uint32_t r; asm volatile("{\n.reg .pred p;\nelect.sync _|p, 0xffffffff;\nselp.u32 %0, 1, 0, p;\n}\n" : "=r"(r)); return r != 0;
}
__device__ __forceinline__ void cluster_arrive() { asm volatile("barrier.cluster.arrive;" ::: "memory"); }
__device__ __forceinline__ void cluster_wait() { asm volatile("barrier.cluster.wait;" ::: "memory"); }
__device__ __forceinline__ void bar_sync(int id, int n) { asm volatile("bar.sync %0, %1;" :: "r"(id), "r"(n) : "memory"); }
__device__ __forceinline__ void bar_arrive(int id, int n) { asm volatile("bar.arrive %0, %1;" :: "r"(id), "r"(n) : "memory"); }
__device__ __forceinline__ void fence_async_smem() { asm volatile("fence.proxy.async.shared::cta;" ::: "memory"); }
__device__ __forceinline__ float ex2(float x) { float y; asm("ex2.approx.ftz.f32 %0, %1;" : "=f"(y) : "f"(x)); return y; }
__device__ __forceinline__ float rcp(float x) { float y; asm("rcp.approx.ftz.f32 %0, %1;" : "=f"(y) : "f"(x)); return y; }
__device__ __forceinline__ uint32_t pack_bf16(float lo, float hi) { uint32_t r; asm("cvt.rn.bf16x2.f32 %0, %1, %2;" : "=r"(r) : "f"(hi), "f"(lo)); return r; }
__device__ __forceinline__ uint32_t hmul2(uint32_t a, uint32_t b) { uint32_t r; asm("mul.rn.bf16x2 %0, %1, %2;" : "=r"(r) : "r"(a), "r"(b)); return r; }
__device__ __forceinline__ uint32_t hadd2(uint32_t a, uint32_t b) { uint32_t r; asm("add.rn.bf16x2 %0, %1, %2;" : "=r"(r) : "r"(a), "r"(b)); return r; }
__device__ __forceinline__ uint32_t hfma2(uint32_t a, uint32_t b, uint32_t c) { uint32_t r; asm("fma.rn.bf16x2 %0, %1, %2, %3;" : "=r"(r) : "r"(a), "r"(b), "r"(c)); return r; }
__device__ __forceinline__ float bf_lo(uint32_t a) { return __uint_as_float(a << 16); }
__device__ __forceinline__ float bf_hi(uint32_t a) { return __uint_as_float(a & 0xffff0000u); }
__device__ __forceinline__ uint32_t lds32(uint32_t a) { uint32_t v; asm volatile("ld.shared.u32 %0, [%1];" : "=r"(v) : "r"(a) : "memory"); return v; }
__device__ __forceinline__ uint4 lds128(uint32_t a) { uint4 v; asm volatile("ld.shared.v4.u32 {%0,%1,%2,%3}, [%4];" : "=r"(v.x), "=r"(v.y), "=r"(v.z), "=r"(v.w) : "r"(a) : "memory"); return v; }
__device__ __forceinline__ void sts64f(uint32_t a, float x, float y) { asm volatile("st.shared.v2.f32 [%0], {%1,%2};" :: "r"(a), "f"(x), "f"(y) : "memory"); }
template<int OFF> __device__ __forceinline__ void sts128o(uint32_t a, uint4 v) { asm volatile("st.shared.v4.u32 [%0+%5], {%1,%2,%3,%4};" :: "r"(a), "r"(v.x), "r"(v.y), "r"(v.z), "r"(v.w), "n"(OFF) : "memory"); }
__device__ __forceinline__ void ldsm4(uint32_t a, uint32_t& r0, uint32_t& r1, uint32_t& r2, uint32_t& r3) {
  asm volatile("ldmatrix.sync.aligned.m8n8.x4.shared.b16 {%0,%1,%2,%3}, [%4];" : "=r"(r0), "=r"(r1), "=r"(r2), "=r"(r3) : "r"(a) : "memory");
}
__device__ __forceinline__ void ldsm4t(uint32_t a, uint32_t& r0, uint32_t& r1, uint32_t& r2, uint32_t& r3) {
  asm volatile("ldmatrix.sync.aligned.m8n8.x4.trans.shared.b16 {%0,%1,%2,%3}, [%4];" : "=r"(r0), "=r"(r1), "=r"(r2), "=r"(r3) : "r"(a) : "memory");
}
__device__ __forceinline__ void stsm4(uint32_t a, uint32_t r0, uint32_t r1, uint32_t r2, uint32_t r3) {
  asm volatile("stmatrix.sync.aligned.m8n8.x4.shared.b16 [%0], {%1,%2,%3,%4};" :: "r"(a), "r"(r0), "r"(r1), "r"(r2), "r"(r3) : "memory");
}
template<int N> __device__ __forceinline__ void fence_regs(float (&d)[N]) {
#pragma unroll
  for (int i = 0; i < N; i++) asm volatile("" : "+f"(d[i]) :: "memory");
}
template<int N> __device__ __forceinline__ void fence_regs(uint32_t (&d)[N]) {
#pragma unroll
  for (int i = 0; i < N; i++) asm volatile("" : "+r"(d[i]) :: "memory");
}
__device__ __forceinline__ void sched_fence(float x, uint32_t dummy) {
  asm volatile("{\n.reg .pred p;\nsetp.eq.u32 p, %0, 0x7fc12345;\n@p st.shared.u32 [%1], %0;\n}\n" :: "r"(__float_as_uint(x)), "r"(dummy) : "memory");
}

#define SHADOW if (gridDim.y == 1)

struct Prod {
  uint32_t base, mask; int lane;
  __device__ __forceinline__ uint32_t full(int u) const { return base + SM_BAR + 8 * u; }
  __device__ __forceinline__ uint32_t addr(int u) const { return base + u * UNIT; }
  __device__ __forceinline__ void acquire(int u, int n) {
    const int v = u + min(lane, n - 1);
    mbar_wait_all(base + SM_BAR + 128 + 8 * v, mask >> v);
    mask ^= ((1u << n) - 1) << u;
  }
  __device__ __forceinline__ void acquire_slow(int u, int n) {
    for (int i = 0; i < n; i++) mbar_wait_slow(base + SM_BAR + 128 + 8 * (u + i), mask >> (u + i));
    mask ^= ((1u << n) - 1) << u;
  }
};
struct Cons {
  uint32_t base, rel, mask; int lane, warp, wg, lr;
  __device__ __forceinline__ uint32_t addr(int u) const { return base + u * UNIT; }
  __device__ __forceinline__ static uint32_t daddr(int u) { return SMEM_BASE + u * UNIT; }
  __device__ __forceinline__ void wait(int u) { mbar_wait(base + SM_BAR + 8 * u, mask >> u); mask ^= 1u << u; }
  __device__ __forceinline__ void skip(int u) { mask ^= 1u << u; }
  __device__ __forceinline__ void release(int u, int n) {
    asm volatile("{\n.reg .pred p;\nsetp.lt.s32 p, %1, %2;\n@p mbarrier.arrive.shared::cluster.b64 _, [%0];\n}\n" :: "r"(rel + 8 * u), "r"(lr), "r"(n) : "memory");
  }
  __device__ __forceinline__ void release2(int u) {
    asm volatile("{\n.reg .pred p;\nsetp.eq.s32 p, %1, 0;\n@p mbarrier.arrive.shared::cluster.b64 _, [%0], 2;\n}\n" :: "r"(rel + 8 * u), "r"(lr) : "memory");
  }
  __device__ __forceinline__ void signal(int i) {
    __syncwarp();
    asm volatile("{\n.reg .pred p;\nsetp.eq.s32 p, %1, 0;\n@p mbarrier.arrive.shared::cta.b64 _, [%0];\n}\n" :: "r"(base + SM_SIG + 8 * i), "r"(lane) : "memory");
  }
  __device__ __forceinline__ void turn() { asm volatile("{\n.reg .pred p;\nsetp.eq.s32 p, %0, 0;\n@p bar.sync 1, 256;\n@!p bar.sync 2, 256;\n}\n" :: "r"(wg) : "memory"); }
  __device__ __forceinline__ void pass() { asm volatile("{\n.reg .pred p;\nsetp.eq.s32 p, %0, 0;\n@p bar.arrive 2, 256;\n@!p bar.arrive 1, 256;\n}\n" :: "r"(wg) : "memory"); }
  __device__ __forceinline__ void sync() { asm volatile("{\n.reg .pred p;\nsetp.eq.s32 p, %0, 0;\n@p bar.sync 3, 128;\n@!p bar.sync 4, 128;\n}\n" :: "r"(wg) : "memory"); }
};
__device__ __forceinline__ int gemm_unit(int ks) { return 3 * (ks & 3); }
template<int MASK> __device__ __forceinline__ int kv_slot(int h) { return MASK == PH_ALL ? h & 15 : h; }
__device__ __forceinline__ int out_mb(int cta) { return cta >> 3; }
__device__ __forceinline__ int out_nb(int cta) { return cta & 7; }
template<int MASK> constexpr int CV_REG = MASK == PH_ALL ? 4 : 6;
template<int MASK> constexpr int CV_EXTRA = MASK == PH_ALL ? 96 + NSKIP / 2 : 64;
constexpr int CV_POOL = 896 + 2 * NSKIP;
template<int MASK> __device__ __forceinline__ int conv_channel(int cta, int i) {
  return cta < NREG ? CV_EXTRA<MASK> * (NCTA - NREG) + cta * CV_REG<MASK> + i : (i >> 1) * 8 + (cta - NREG) * 2 + (i & 1);
}

template<int OFF, int N> __device__ __forceinline__ void pack_chunk(const float (&a)[N], float sc0, float sc1, uint4& v0, uint4& v1) {
  v0.x = pack_bf16(a[OFF + 0] * sc0, a[OFF + 1] * sc0); v0.y = pack_bf16(a[OFF + 4] * sc0, a[OFF + 5] * sc0);
  v0.z = pack_bf16(a[OFF + 8] * sc0, a[OFF + 9] * sc0); v0.w = pack_bf16(a[OFF + 12] * sc0, a[OFF + 13] * sc0);
  v1.x = pack_bf16(a[OFF + 2] * sc1, a[OFF + 3] * sc1); v1.y = pack_bf16(a[OFF + 6] * sc1, a[OFF + 7] * sc1);
  v1.z = pack_bf16(a[OFF + 10] * sc1, a[OFF + 11] * sc1); v1.w = pack_bf16(a[OFF + 14] * sc1, a[OFF + 15] * sc1);
}
template<int OFF, int N> __device__ __forceinline__ void pack_chunk(const float (&a)[N], uint4& v0, uint4& v1) {
  v0.x = pack_bf16(a[OFF + 0], a[OFF + 1]); v0.y = pack_bf16(a[OFF + 4], a[OFF + 5]);
  v0.z = pack_bf16(a[OFF + 8], a[OFF + 9]); v0.w = pack_bf16(a[OFF + 12], a[OFF + 13]);
  v1.x = pack_bf16(a[OFF + 2], a[OFF + 3]); v1.y = pack_bf16(a[OFF + 6], a[OFF + 7]);
  v1.z = pack_bf16(a[OFF + 10], a[OFF + 11]); v1.w = pack_bf16(a[OFF + 14], a[OFF + 15]);
}
__device__ __forceinline__ void sq_acc(const uint4& v, uint32_t& a) { a = hfma2(v.x, v.x, a); a = hfma2(v.y, v.y, a); a = hfma2(v.z, v.z, a); a = hfma2(v.w, v.w, a); }
template<bool ROWS> __device__ __forceinline__ float norm2_max(uint32_t a0, uint32_t a1) {
  float n0 = bf_lo(a0) + bf_hi(a0), n1 = bf_lo(a1) + bf_hi(a1);
  if (ROWS) {
    n0 += __shfl_xor_sync(~0u, n0, 1); n1 += __shfl_xor_sync(~0u, n1, 1);
    n0 += __shfl_xor_sync(~0u, n0, 2); n1 += __shfl_xor_sync(~0u, n1, 2);
  }
  return __uint_as_float(__reduce_max_sync(~0u, max(__float_as_uint(n0) & 0x7fffffffu, __float_as_uint(n1) & 0x7fffffffu)));
}

struct Pend { uint4 lo[8], hi[8]; };
__device__ __forceinline__ uint32_t ctx_off(const Cons& c, int h, int qb, int rowhalf) { return T_CTX + (qb * 32 + h) * 32768 + (rowhalf * 4 + c.warp) * 4096; }
__device__ __forceinline__ uint32_t kv_off(const Cons& c, int blk) { return T_KV + blk * 65536 + (c.wg * 4 + c.warp) * 4096; }
__device__ __forceinline__ void pin(uint4 (&v)[8]) {
#pragma unroll
  for (int i = 0; i < 8; i++) asm volatile("" : "+r"(v[i].x), "+r"(v[i].y), "+r"(v[i].z), "+r"(v[i].w) :: "memory");
}
__device__ __forceinline__ void pack_o(const float (&o)[64], float i0, float i1, uint4 (&v)[8]) {
  pack_chunk<0>(o, i0, i1, v[0], v[1]); pack_chunk<16>(o, i0, i1, v[2], v[3]);
  pack_chunk<32>(o, i0, i1, v[4], v[5]); pack_chunk<48>(o, i0, i1, v[6], v[7]);
  pin(v);
}
__device__ __forceinline__ uint32_t atom_off(int lane) { return (lane >> 2) * 64 + (((lane ^ (lane >> 3)) & 3) << 4); }
template<int J0, int J1> __device__ __forceinline__ void tile_store(const uint4 (&v)[8], uint32_t dst, int lane) {
  uint8_t* d = g_T + (dst + atom_off(lane));
#pragma unroll
  for (int j = J0; j < J1; j++) { *(uint4*)(d + j * 512) = v[2 * j]; *(uint4*)(d + j * 512 + 2048) = v[2 * j + 1]; }
}
template<int I0, int I1> __device__ __forceinline__ void tile_store_if(bool on, const uint4 (&v)[8], const uint8_t* dst) {
  if constexpr (I0 < I1) {
    asm volatile("{\n.reg .pred p;\nsetp.ne.b32 p, %5, 0;\n@p st.v4.u32 [%0+%6], {%1,%2,%3,%4};\n}\n"
      :: "l"(dst), "r"(v[I0].x), "r"(v[I0].y), "r"(v[I0].z), "r"(v[I0].w), "r"((int)on), "n"((I0 >> 1) * 512 + (I0 & 1) * 2048) : "memory");
    tile_store_if<I0 + 1, I1>(on, v, dst);
  }
}
template<bool ROWS> __device__ __forceinline__ float tile_norm2(const uint4 (&v)[8]) {
  uint32_t n0 = 0, n1 = 0, n2 = 0, n3 = 0;
#pragma unroll
  for (int j = 0; j < 2; j++) { sq_acc(v[2 * j], n0); sq_acc(v[2 * j + 1], n1); sq_acc(v[2 * j + 4], n2); sq_acc(v[2 * j + 5], n3); }
  return norm2_max<ROWS>(hadd2(n0, n2), hadd2(n1, n3));
}
template<uint64_t SCHED, bool FIRST> __device__ __forceinline__ void out_piece(Cons& c, Pend& w, uint32_t dst, int blk, float& kn, int ks, bool both) {
  uint8_t* d = g_T + (dst + atom_off(c.lane));
#pragma unroll
  for (int i = 0; i < 16; i++) {
    const int at = (SCHED >> (4 * i)) & 15;
    if (FIRST ? at == 0 : (at > 0 && ks == at && (i < 8 || both))) *(uint4*)(d + (i >> 3) * 32768 + ((i >> 1) & 3) * 512 + (i & 1) * 2048) = i < 8 ? w.lo[i & 7] : w.hi[i & 7];
  }
  if (FIRST || !both) return;
  if (ks == NK_AT) kn = tile_norm2<true>(w.lo);
  if (ks == NV_AT) {
    const float vn = tile_norm2<false>(w.hi);
    if (c.lane == 0) g_kn2[blk * 8 + c.wg * 4 + c.warp] = (vn <= 1.0e20f && vn >= 1.0e-20f) ? kn : __uint_as_float(0x7f800000u);
  }
}
template<bool FIRST> __device__ __forceinline__ void kv_issue(Cons& c, float (&acc)[128], int ua, int ub) {
  const uint64_t da = odesc(c.daddr(ua) + c.wg * 8192, 16, 1024, 1), db = odesc(c.daddr(ub), 8192, 1024, 1);
  c.turn();
  wg_fence();
#pragma unroll
  for (int kk = 0; kk < 4; kk++) wgmma_ss_n256<1>(acc, da + kk * 2, db + kk * 128, !(FIRST && kk == 0));
  wg_commit();
  c.pass();
}
template<bool NEXT> __device__ __forceinline__ void cons_kv(Cons& c, int h, int blk, int g, Pend& w, bool pend_o) {
#pragma unroll 1
  for (int tile = 0; tile < 2; tile++) {
    float acc[128];
    if (tile == 0) c.wait(0);
    const bool early = pend_o && tile == 0;
    kv_issue<true>(c, acc, early ? 12 : 0, early ? 0 : 1);
    c.release(9, tile == 1 ? 3 : 0);
    if (tile == 1 && pend_o) mbar_wait(c.base + SM_RDY + 8 * RDY_WAR, 0);
    const uint32_t dst = tile ? kv_off(c, blk) : ctx_off(c, h - 16, g, 1 - c.wg);
    float kn = 0.f;
    if (tile == 1 || pend_o) out_piece<SCH_KV, true>(c, w, dst, blk, kn, 0, false);
#pragma unroll 1
    for (int ks = 1; ks < 8; ks++) {
      const int u = gemm_unit(ks);
      c.wait(u);
      wg_wait<0>();
      c.release(gemm_unit(ks - 1), early && ks == 1 ? 2 : 3);
      kv_issue<false>(c, acc, u, u + 1);
      if (tile == 1 || pend_o) { out_piece<SCH_KV, false>(c, w, dst, blk, kn, ks, tile); if (ks == ((SCH_KV >> 28) & 15) && tile == 0) c.signal(SIG_CTX); }
    }
    if (NEXT || tile == 0) c.wait(0);
    wg_wait<0>(); fence_regs(acc);
    if (!NEXT) c.release(9, tile == 1 ? 3 : 0);
    pack_chunk<0>(acc, w.lo[0], w.lo[1]);  pack_chunk<16>(acc, w.lo[2], w.lo[3]); pack_chunk<32>(acc, w.lo[4], w.lo[5]); pack_chunk<48>(acc, w.lo[6], w.lo[7]);
    pack_chunk<64>(acc, w.hi[0], w.hi[1]); pack_chunk<80>(acc, w.hi[2], w.hi[3]); pack_chunk<96>(acc, w.hi[4], w.hi[5]); pack_chunk<112>(acc, w.hi[6], w.hi[7]);
    pin(w.lo); pin(w.hi);
  }
}
template<bool FIRST> __device__ __forceinline__ void q_issue(Cons& c, float (&a)[64], float (&b)[64], int u) {
  const uint64_t da = odesc(c.daddr(u) + c.wg * 8192, 16, 1024, 1), db = odesc(c.daddr(u + 2), 8192, 1024, 1);
  const uint64_t da2 = odesc(c.daddr(u + 1) + (1 - c.wg) * 8192, 16, 1024, 1);
  c.turn();
  wg_fence();
#pragma unroll
  for (int kk = 0; kk < 4; kk++) wgmma_ss_n128<1>(a, da + kk * 2, db + kk * 128, !(FIRST && kk == 0));
#pragma unroll
  for (int kk = 0; kk < 4; kk++) wgmma_ss_n128<1>(b, da2 + kk * 2, db + kk * 128, !(FIRST && kk == 0));
  wg_commit();
  c.pass();
}
__device__ __forceinline__ void q_step(Cons& c, float (&d)[64], int ua, int ub, int rowhalf) {
  const uint64_t da = odesc(c.daddr(ua) + rowhalf * 8192, 16, 1024, 1), db = odesc(c.daddr(ub), 8192, 1024, 1);
#pragma unroll
  for (int kk = 0; kk < 4; kk++) wgmma_ss_n128<1>(d, da + kk * 2, db + kk * 128, 1);
}
template<bool PEND_KV> __device__ __forceinline__ void cons_q(Cons& c, int h, int blk, Pend& w, float (&b)[64], float& kmax) {
  float a[64], kn = 0.f;
  if (!PEND_KV) c.wait(0);
  q_issue<true>(c, a, b, 0);
  if (PEND_KV) { c.release(9, 3); out_piece<SCH_Q, true>(c, w, kv_off(c, blk), blk, kn, 0, true); }
#pragma unroll 1
  for (int ks = 1; ks < 14; ks++) {
    const int u = gemm_unit(ks);
    c.wait(u);
    wg_wait<0>();
    c.release(gemm_unit(ks - 1), 3);
    q_issue<false>(c, a, b, u);
    if (PEND_KV && ks <= (int)(SCH_Q >> 60)) { out_piece<SCH_Q, false>(c, w, kv_off(c, blk), blk, kn, ks, true); if (ks == (int)(SCH_Q >> 60)) c.signal(SIG_KV + (h >> 4)); }
  }
  c.wait(6); c.wait(9);
  wg_wait<0>();
  c.release(3, 3);
  c.turn();
  wg_fence();
  q_step(c, a, 6, 8, c.wg); q_step(c, a, 9, 11, c.wg); wg_commit();
  q_step(c, b, 7, 8, 1 - c.wg); wg_commit();
  c.pass();
  c.wait(0);
  kmax = __uint_as_float(lds32(c.base + SM_KMAX + 4 * (h >> 4)));
  c.wait(12);
  const uint32_t q0 = c.addr(0) + (c.wg * 4 + c.warp) * 4096 + atom_off(c.lane);
  wg_wait<1>(); fence_regs(a);
  pack_o(a, QSCALE, QSCALE, w.lo);
  sts128o<0>(q0, w.lo[0]);    sts128o<2048>(q0, w.lo[1]); sts128o<512>(q0, w.lo[2]);  sts128o<2560>(q0, w.lo[3]);
  wg_wait<0>();
  c.release(6, 4);
  sts128o<1024>(q0, w.lo[4]); sts128o<3072>(q0, w.lo[5]); sts128o<1536>(q0, w.lo[6]); sts128o<3584>(q0, w.lo[7]);
  fence_async_smem();
}

__device__ __forceinline__ void issue_qk(float (&s)[64], uint64_t da, uint64_t db) {
#pragma unroll
  for (int kk = 0; kk < 8; kk++) wgmma_ss_n128<0>(s, da + (kk >> 1) * 32 + (kk & 1) * 2, db + (kk >> 1) * 32 + (kk & 1) * 2, kk > 0);
  wg_commit();
}
template<int A, int B> __device__ __forceinline__ void exp_rng(float (&s)[64]) {
#pragma unroll
  for (int i = 4 * A; i < 4 * B; i++) s[i] = ex2(s[i]);
}
template<int A, int B> __device__ __forceinline__ void sum_rng(const float (&s)[64], float (&l)[4]) {
#pragma unroll
  for (int i = A; i < B; i++) { l[0] += s[4 * i]; l[1] += s[4 * i + 1]; l[2] += s[4 * i + 2]; l[3] += s[4 * i + 3]; }
}
template<int A, int B> __device__ __forceinline__ void cvt_p(const float (&s)[64], uint32_t (&p)[32]) {
#pragma unroll
  for (int i = 2 * A; i < 2 * B; i++) p[i] = pack_bf16(s[2 * i], s[2 * i + 1]);
}
__device__ __forceinline__ void mask_move(float (&s)[64], const float (&u)[32], int warp, int lane) {
  const int l0 = warp + (2 * (lane & 3) <= (lane >> 2)), l1 = warp + (2 * (lane & 3) < (lane >> 2));
#pragma unroll
  for (int i = 0; i < 32; i++) {
    const int k = i >> 3, e = i & 7;
    const bool off = (e == 0 || e == 6) ? k >= l0 : (e == 1 || e == 7) ? k >= l1 : e < 4 ? k > warp : k >= warp;
    s[32 + i] = off ? -INFINITY : u[i];
    if (k == 0 && (e == 2 || e == 3)) asm volatile("add.f32 %0, %0, 0f80000000;" : "+f"(s[32 + i]));
  }
}
template<int K0> __device__ __forceinline__ void mask_half(float (&s)[64], int warp, int lane) {
  const int l0 = warp + (2 * (lane & 3) <= (lane >> 2)), l1 = warp + (2 * (lane & 3) < (lane >> 2));
#pragma unroll
  for (int k = 0; k < 4; k++) {
    float* t = s + 8 * (K0 + k);
    if (k >= l0) { t[0] = -INFINITY; t[6] = -INFINITY; }
    if (k >= l1) { t[1] = -INFINITY; t[7] = -INFINITY; }
    if (k > warp) { t[2] = -INFINITY; t[3] = -INFINITY; }
    if (k >= warp) { t[4] = -INFINITY; t[5] = -INFINITY; }
  }
}
__device__ __forceinline__ void row_inv(float& l0, float& l1) {
  l0 += __shfl_xor_sync(~0u, l0, 1); l1 += __shfl_xor_sync(~0u, l1, 1);
  l0 += __shfl_xor_sync(~0u, l0, 2); l1 += __shfl_xor_sync(~0u, l1, 2);
  l0 = rcp(l0); l1 = rcp(l1);
}
__device__ __forceinline__ void softmax_safe(float (&s)[64], bool upper_only, float& m0, float& m1, float& sc0, float& sc1) {
  float a0 = m0, a1 = m1;
#pragma unroll
  for (int i = 0; i < 8; i++) { a0 = fmaxf(a0, fmaxf(s[4 * i], s[4 * i + 1])); a1 = fmaxf(a1, fmaxf(s[4 * i + 2], s[4 * i + 3])); }
  if (upper_only) { a0 = m0; a1 = m1; }
#pragma unroll
  for (int i = 8; i < 16; i++) { a0 = fmaxf(a0, fmaxf(s[4 * i], s[4 * i + 1])); a1 = fmaxf(a1, fmaxf(s[4 * i + 2], s[4 * i + 3])); }
  a0 = fmaxf(a0, __shfl_xor_sync(~0u, a0, 1)); a1 = fmaxf(a1, __shfl_xor_sync(~0u, a1, 1));
  a0 = fmaxf(a0, __shfl_xor_sync(~0u, a0, 2)); a1 = fmaxf(a1, __shfl_xor_sync(~0u, a1, 2));
  sc0 = ex2(m0 - a0); sc1 = ex2(m1 - a1);
  m0 = a0; m1 = a1;
#pragma unroll
  for (int i = 0; i < 16; i++) { s[4 * i] -= a0; s[4 * i + 1] -= a0; s[4 * i + 2] -= a1; s[4 * i + 3] -= a1; }
}
struct Att {
  float s[64], o[64], l[4], i0, i1, t0, t1; uint32_t p[32];
  float kn; uint32_t qaddr; const uint8_t* dst;
};
__device__ __forceinline__ int att_fast(uint4 (&q)[8], float kn) {
#pragma unroll
  for (int i = 0; i < 8; i++) q[i].x = hmul2(q[i].x, q[i].x);
#pragma unroll
  for (int i = 0; i < 8; i++) q[i].x = hfma2(q[i].w, q[i].w, hfma2(q[i].z, q[i].z, hfma2(q[i].y, q[i].y, q[i].x)));
#pragma unroll
  for (int i = 0; i < 4; i++) q[i].x = hadd2(q[i].x, q[i + 4].x);
  const uint32_t a0 = hadd2(q[0].x, q[2].x), a1 = hadd2(q[1].x, q[3].x);
  return __shfl_sync(~0u, __all_sync(~0u, ((bf_lo(a0) + bf_hi(a0)) * kn <= 0.25f * BOUND2) & ((bf_lo(a1) + bf_hi(a1)) * kn <= 0.25f * BOUND2)), 0);
}
__device__ __forceinline__ int att_first(Cons& c, Att& a, int h, Pend& w) {
  a.qaddr = c.daddr(0) + c.wg * 16384;
  c.turn();
  wg_fence();
  issue_qk(a.s, odesc(a.qaddr, 16, 2048, 2), odesc(c.daddr(12), 16, 2048, 2));
  int fast = 0;
  SHADOW fast = att_fast(w.lo, a.kn);
  wg_fence();
  q_step(c, a.o, 10, 11, 1 - c.wg); wg_commit();
  if (c.wg) c.wait(6); else c.skip(6);
  c.pass();
#pragma unroll
  for (int i = 0; i < 8; i++) { a.p[4 * i] = w.lo[i].x; a.p[4 * i + 1] = w.lo[i].y; a.p[4 * i + 2] = w.lo[i].z; a.p[4 * i + 3] = w.lo[i].w; }
  a.l[0] = a.l[1] = a.l[2] = a.l[3] = 0.f; a.i0 = a.i1 = a.t0 = a.t1 = 0.25f / QSCALE;
  a.dst = (const uint8_t*)__cvta_shared_to_generic(c.addr(2) + (c.wg * 4 + c.warp) * 4096 + atom_off(c.lane));
  wg_wait<1>(); fence_regs(a.s);
  c.signal(SIG_ATT + (h >> 4));
  if (c.wg) { wg_wait<0>(); c.release(10, 2); }
  return fast;
}
__device__ __forceinline__ void att_last(Cons& c, Att& a, Pend& w, int h, int g, bool drain) {
  const int uv = 6;
  if (drain) pack_o(a.o, rcp(a.i0), rcp(a.i1), w.hi);
  c.turn();
  fence_regs(a.o); fence_regs(a.p);
  wgmma_pv_sel(a.o, a.p, odesc(c.daddr(uv), 512, 2048, 2), !(drain && c.wg == 1), !drain, c.wg);
  a.i0 = a.l[0] + a.l[1]; a.i1 = a.l[2] + a.l[3];
  SHADOW row_inv(a.i0, a.i1);
  sched_fence(a.i0 + a.i1, c.base + SM_DUMMY);
  tile_store_if<0, 4>(drain, w.hi, a.dst);
  wg_wait<0>(); fence_regs(a.o); fence_regs(a.p);
  c.release(uv, 2);
  tile_store_if<4, 8>(drain, w.hi, a.dst);
  pack_o(a.o, a.i0, a.i1, w.lo);
}
__device__ __forceinline__ void cons_att(Cons& c, Att& a, int h, int g, Pend& w) {
  int fast = att_first(c, a, h, w), fast2 = 0;
  float m0 = -INFINITY, m1 = -INFINITY, sc0 = 0.f, sc1 = 0.f;
  int uk = 10, ur = 10;
  bool fresh = false;
  auto next_tile = [&]() {
    a.i0 = a.l[0] + a.l[1]; a.i1 = a.l[2] + a.l[3];
    a.t0 = __shfl_xor_sync(~0u, a.i0, 1); a.t1 = __shfl_xor_sync(~0u, a.i1, 1);
    a.l[0] = a.l[1] = a.l[2] = a.l[3] = 0.f;
    uint32_t off = ctx_off(c, h, 15 - g, c.wg);
    asm volatile("" : "+r"(off));
    a.dst = g_T + (off + ((uint32_t)(uint64_t)a.dst & 511));
    fast = fast2;
  };
#pragma unroll 1
  for (int d = g - 15;;) {
    const bool lo = d == c.wg;
    if (d == 1 - c.wg || !fast) {
      if (d == 1 - c.wg) mask_half<4>(a.s, c.warp, c.lane);
      if (!fast) {
        if (d == 1) m0 = m1 = -INFINITY;
        softmax_safe(a.s, lo, m0, m1, sc0, sc1);
        a.l[0] *= sc0; a.l[1] *= sc0; a.l[2] *= sc1; a.l[3] *= sc1;
      }
    }
    exp_rng<8, 16>(a.s); sum_rng<8, 16>(a.s, a.l);
#pragma unroll
    for (int i = 4 * ATT_SPLIT; i < 32; i++) asm("{\n.reg .pred p;\nsetp.ne.s32 p, %1, %2;\n@p ex2.approx.ftz.f32 %0, %0;\n}\n" : "+f"(a.s[i]) : "r"(d), "r"(c.wg));
    sched_fence(((a.l[0] + a.l[1]) + (a.l[2] + a.l[3])) + a.s[4 * ATT_SPLIT + 3], c.base + SM_DUMMY);
    wg_wait<0>(); fence_regs(a.o); fence_regs(a.p);
    c.release(ur, c.wg && d == g - 15 ? 0 : 2);
    a.i0 += a.t0; a.i1 += a.t1;
    a.t0 = __shfl_xor_sync(~0u, a.i0, 2); a.t1 = __shfl_xor_sync(~0u, a.i1, 2);
    tile_store_if<0, 4>(fresh, w.hi, a.dst);
    uk ^= 12; ur = 14 - uk;
    if (d == 0) a.qaddr += 32768;
    const uint64_t dq = odesc(a.qaddr, 16, 2048, 2), dk = odesc(c.daddr(uk), 16, 2048, 2), dv = odesc(c.daddr(ur), 512, 2048, 2);
    if (!lo) { exp_rng<0, ATT_SPLIT>(a.s); sum_rng<0, 8>(a.s, a.l); cvt_p<0, 16>(a.s, a.p); }
    else if (gridDim.y == 1) cvt_p<8, 16>(a.s, a.p);
    tile_store_if<4, 8>(fresh, w.hi, a.dst);
    a.i0 += a.t0; a.i1 += a.t1;
    if (!fast || d == g + 1 || d + 1 == c.wg) {
      if (!fast && d != 1 && d != g - 15) {
#pragma unroll
        for (int i = 0; i < 16; i++) { a.o[4 * i] *= sc0; a.o[4 * i + 1] *= sc0; a.o[4 * i + 2] *= sc1; a.o[4 * i + 3] *= sc1; }
      }
      if (d == g + 1) break;
      if (d + 1 == c.wg) {
        float t[32];
        d++;
        if (!c.wg) c.wait(ur);
        c.turn();
        fence_regs(a.o); fence_regs(a.p);
        wg_fence();
#pragma unroll
        for (int kk = 0; kk < 8; kk++) wgmma_ss_n64<0>(t, dq + (kk >> 1) * 32 + (kk & 1) * 2, dk + (kk >> 1) * 32 + (kk & 1) * 2, kk > 0);
        wg_commit();
        if (c.wg) c.wait(uk ^ 12);
        c.skip(c.wg ? ur : uk ^ 12);
        wgmma_pv_sel(a.o, a.p, dv, 1, 1, c.wg);
        if (d == 1) next_tile();
        wg_wait<1>(); fence_regs(t);
        c.release(uk, 2);
        c.release(2 * d, (d == 0 || g == 0) ? 2 : 0);
        mask_move(a.s, t, c.warp, c.lane);
#pragma unroll
        for (int i = 0; i < 8; i++) w.hi[i] = make_uint4(0, 0, 0, 0);
        continue;
      }
    }
    d++;
    fresh = d == 2 || d == g - 14;
    c.turn();
    fence_regs(a.o); fence_regs(a.p);
    wg_fence();
    issue_qk(a.s, dq, dk);
    c.wait(c.wg ? uk ^ 12 : ur); c.skip(c.wg ? ur : uk ^ 12);
    if (fresh || d == 1 || (unsigned)(d - g + CHK_D) < 2) {
      if (fresh) pack_o(a.o, rcp(a.i0), rcp(a.i1), w.hi);
      else if (d == 1) next_tile();
      else if (d == g - CHK_D) fence_async_smem();
      else fast2 = att_fast(w.hi, a.kn);
    }
    wgmma_pv_sel(a.o, a.p, dv, !lo, !fresh, c.wg);
    wg_wait<1>(); fence_regs(a.s);
    c.release(uk, 2);
    c.release(d == 0 ? 0 : 2, (d == 0 || d == g + 1) ? 2 : 0);
  }
  att_last(c, a, w, h, g, g == 0);
}

constexpr int CV_H = 1024, CV_U = 5120, CV_D = CV_U + 4128;
template<int OFF> __device__ __forceinline__ uint32_t lds32o(uint32_t a) { uint32_t v; asm volatile("ld.shared.u32 %0, [%1+%2];" : "=r"(v) : "r"(a), "n"(OFF) : "memory"); return v; }
template<int G, int G1 = 16> __device__ __forceinline__ void conv_lda(uint32_t (&a)[64], uint32_t p) {
  a[4 * G + 0] = lds32o<-256 * G>(p);
  a[4 * G + 1] = lds32o<-256 * G - 128>(p);
  a[4 * G + 2] = lds32o<-256 * G + 16>(p);
  a[4 * G + 3] = lds32o<-256 * G - 112>(p);
  if constexpr (G + 1 < G1) conv_lda<G + 1, G1>(a, p);
}
struct CvAcc { float lo[16], hi[16]; };
__device__ __forceinline__ void fence_regs(CvAcc& d) { fence_regs(d.lo); fence_regs(d.hi); }
template<int T, int G0, int G1> __device__ __forceinline__ void conv_part(float (&d)[16], const uint32_t (&a)[64], uint64_t db) {
#pragma unroll
  for (int G = G0; G < G1; G++) wgmma_rs_n32<0>(d, a[4 * G], a[4 * G + 1], a[4 * G + 2], a[4 * G + 3], db + 32 * T - 16 * G, G > 0);
}
template<int C0> __device__ __forceinline__ void conv_st_h(const float (&d)[16], uint32_t wq, float& c0, float& c1) {
#pragma unroll
  for (int n = 0; n < 4; n++) { sts64f(wq + (C0 + n * 8) * 4, d[4 * n] + c0, d[4 * n + 1] + c1); c0 = d[4 * n + 2]; c1 = d[4 * n + 3]; }
}
template<int R> __device__ __forceinline__ void conv_st(const CvAcc& d, uint32_t wq, float& c0, float& c1) { conv_st_h<64 * R>(d.lo, wq, c0, c1); conv_st_h<64 * R + 32>(d.hi, wq, c0, c1); }

constexpr int OC_PART = 13824, OC_ROW = 544;
__device__ __forceinline__ int out_next(int u) { return (0x84ac680u >> (2 * u)) & 15; }
struct Out { float acc[64]; int pu; uint64_t da, db; };
template<bool FIRST, bool REL, int W = 1> __device__ __forceinline__ void out_step(Cons& c, Out& o, bool extra = false) {
  const int pu = o.pu, u = extra ? 2 : out_next(pu);
  o.pu = u;
  c.wait(u);
  const uint64_t da = o.da + (uint32_t)(u * 1024), db = o.db + (uint32_t)(u * 1024);
  wg_fence();
#pragma unroll
  for (int kk = 0; kk < 4; kk++) wgmma_ss_n128<1>(o.acc, da + (kk >> 1) * 32 + (kk & 1) * 2, db + kk * 128, !(FIRST && kk == 0));
  wg_commit();
  if (REL) { wg_wait<W>(); c.release(pu, 2); }
}
template<int I0, int I1> __device__ __forceinline__ void oc_red(float (&y)[8], uint32_t rq) {
#pragma unroll
  for (int i = I0; i < I1; i++) { const float v = __uint_as_float(lds32(rq + i * OC_ROW - (i >> 3) * 8)); y[i & 7] = i < 8 ? v : y[i & 7] + v; }
}
template<int I0, int I1> __device__ __forceinline__ void oc_ld(float (&t)[32], uint32_t rq) {
#pragma unroll
  for (int i = I0; i < I1; i++) t[i] = __uint_as_float(lds32(rq + i * OC_ROW - (i >> 3) * 8));
}
__device__ __forceinline__ void oc_emit(const float (&y)[8], const uint4& u, uint32_t D2, uint8_t* dst) {
  uint4 z;
  z.x = hadd2(pack_bf16(y[0], y[1]), hmul2(__byte_perm(u.w, 0, 0x1032), D2));
  z.y = hadd2(pack_bf16(y[2], y[3]), hmul2(__byte_perm(u.z, 0, 0x1032), D2));
  z.z = hadd2(pack_bf16(y[4], y[5]), hmul2(__byte_perm(u.y, 0, 0x1032), D2));
  z.w = hadd2(pack_bf16(y[6], y[7]), hmul2(__byte_perm(u.x, 0, 0x1032), D2));
  *(uint4*)dst = z;
}
template<bool THR> __device__ __forceinline__ void conv_round(Cons& c, Out& o, int u, uint32_t ub, uint32_t wq, uint32_t rq, int ch) {
  const int r = c.lane >> 2, q = c.lane & 3, tid = c.warp * 32 + c.lane;
  const uint32_t ap = ub + CV_U + ((r & 1) ? 0 : UPITCH) + 4 * (((2039 - r) >> 1) + q - 8 * c.warp);
  uint32_t a[64];
  CvAcc d0, d1;
  float y[8], t[32], c0 = 0.f, c1 = 0.f;
  const uint64_t db0 = odesc(c.daddr(u) + CV_H - 16, 16, 128, 0);
#define STEP(N) if (THR) out_step<false, true>(c, o); else if (N == 0) c.turn(); else if (N == 10) wg_wait<0>();
#define STEP2(N) if (THR) out_step<false, true, 2>(c, o); else { if (N == 9) c.pass(); wg_wait<1>(); }
#define PART(...) { const uint64_t db = db0 + (c.mask >> 16); wg_fence(); __VA_ARGS__; wg_commit(); }
#define KEEP() asm volatile("add.f32 %0, %0, 0f80000000;" : "+f"(c0)); asm volatile("add.f32 %0, %0, 0f80000000;" : "+f"(c1));
  c.wait(u);
  conv_lda<0, THR ? 4 : 12>(a, ap);
  STEP(0)
  if (THR) conv_lda<4, 7>(a, ap);
  PART(conv_part<0, 0, 2>(d0.lo, a, db); conv_part<1, 0, 4>(d0.hi, a, db); conv_part<2, 0, 2>(d1.lo, a, db))
  STEP2(1)
  if (THR) conv_lda<7, 10>(a, ap);
  PART(conv_part<2, 2, 6>(d1.lo, a, db); conv_part<3, 0, 4>(d1.hi, a, db))
  STEP2(2)
  fence_regs(d0);
  if (THR) c.sync();
  sts64f(wq - 32, 0.f, 0.f);
  conv_st_h<0>(d0.lo, wq, c0, c1); KEEP()
  PART(conv_part<3, 4, 8>(d1.hi, a, db); conv_part<4, 0, 4>(d0.lo, a, db))
  STEP2(3)
  fence_regs(d1.lo);
  conv_st_h<32>(d0.hi, wq, c0, c1); conv_st_h<64>(d1.lo, wq, c0, c1); KEEP()
  PART(conv_part<4, 4, 10>(d0.lo, a, db); conv_part<5, 0, 2>(d0.hi, a, db))
  STEP2(4)
  fence_regs(d1.hi);
  float e0 = d1.hi[12] + d1.hi[10], e1 = d1.hi[13] + d1.hi[11];
  conv_st_h<96>(d1.hi, wq, c0, c1); KEEP()
  if (THR) conv_lda<10, 12>(a, ap);
  PART(conv_part<5, 2, 10>(d0.hi, a, db))
  STEP2(5)
  conv_lda<12, 14>(a, ap);
  c.sync();
  if (THR) oc_red<0, 6>(y, rq); else oc_ld<0, 8>(t, rq);
  PART(conv_part<5, 10, 12>(d0.hi, a, db); conv_part<6, 0, 6>(d1.lo, a, db))
  STEP2(6)
  if (THR) oc_red<6, 20>(y, rq); else oc_ld<8, 16>(t, rq);
  PART(conv_part<6, 6, 14>(d1.lo, a, db))
  STEP2(7)
  if (THR) oc_red<20, 26>(y, rq); else oc_ld<16, 24>(t, rq);
  conv_lda<14, 16>(a, ap);
  PART(conv_part<7, 0, 8>(d1.hi, a, db))
  STEP2(8)
  if (THR) oc_red<26, 32>(y, rq); else oc_ld<24, 32>(t, rq);
  PART(conv_part<7, 8, 16>(d1.hi, a, db))
  STEP2(9)
  if (!THR) {
#pragma unroll
    for (int i = 0; i < 8; i++) y[i] = t[i];
    SHADOW {
#pragma unroll
      for (int i = 0; i < 8; i++) y[i] = ((t[i] + t[8 + i]) + t[16 + i]) + t[24 + i];
    }
  }
  fence_regs(y); fence_regs(d0);
  c.sync();
  sts64f(wq - 32, e0, e1);
  conv_st<0>(d0, wq, c0, c1);
  STEP(10)
  fence_regs(d1); fence_regs(a);
  const uint4 u0 = lds128(ub + CV_U + 4080 - 16 * tid), u1 = lds128(ub + CV_U + 2032 - 16 * tid);
  const uint32_t D2 = lds32(ub + CV_D);
  conv_st<1>(d1, wq, c0, c1);
  STEP(11)
  sched_fence(__uint_as_float(u0.x ^ u1.x ^ D2), c.base + SM_DUMMY);
  uint8_t* zp = g_u + (uint32_t)(ch * UCH + (threadIdx.x & 127) * 16);
  oc_emit(y, u0, D2, zp);
  c.sync();
  c.release2(u);
  oc_red<0, 12>(y, rq);
  STEP(12)
  oc_red<12, 24>(y, rq);
  STEP(13)
  oc_red<24, 32>(y, rq);
  oc_emit(y, u1, D2, zp + 2048);
#undef KEEP
#undef STEP
#undef STEP2
#undef PART
}
template<int MASK> __device__ __forceinline__ void cons_conv(Cons& c, int cta, int nch) {
  const uint32_t part = c.addr(4 + 2 * c.wg) + 32;
  const uint32_t wq = part + (c.warp * 8 + (c.lane >> 2)) * OC_ROW + (c.lane & 3) * 8, rq = part + (c.warp * 32 + c.lane) * 4;
  Out o;
  c.wait(4);
#pragma unroll 1
  for (int i = 0; i < nch / 2; i++) {
    const int u = 2 * (i & 1) + c.wg;
    conv_round<false>(c, o, u, c.addr(u), wq, rq, conv_channel<MASK>(cta, 2 * i + c.wg));
    if ((i & 15) == 15 || i == nch / 2 - 1) c.signal(SIG_Z + (i >> 4));
  }
}
__device__ __forceinline__ uint32_t mix(uint32_t og, uint32_t b, uint32_t ga) { return hadd2(ga, hmul2(og, b)); }
template<int MASK> __device__ __forceinline__ void cons_out(Cons& c, const Maps& M, const Params& P, int cta, Pend& w) {
  const int mb = out_mb(cta), nb = out_nb(cta);
  Out o;
  o.da = odesc(c.daddr(0) + c.wg * 8192, 16, 1024, 2); o.db = odesc(c.daddr(1), 8192, 1024, 1);
  o.pu = 5 + gridDim.y;
  out_step<true, false>(c, o);
  int ks = 1;
  const uint32_t dst = ctx_off(c, 16 + (cta >> 3), cta & 7, 1 - c.wg);
#pragma unroll 1
  for (;; ks++) {
    if (MASK & PH_ATT) {
      if (ks == (c.wg ? ST_1 : 1)) tile_store<0, 1>(w.lo, dst, c.lane);
      if (ks == (c.wg ? ST_1 + ST_D : 1)) tile_store<1, 2>(w.lo, dst, c.lane);
      if (ks == (c.wg ? ST_1 + 2 * ST_D : 1)) tile_store<2, 3>(w.lo, dst, c.lane);
      if (ks == (c.wg ? ST_1 + 3 * ST_D : 1)) { tile_store<3, 4>(w.lo, dst, c.lane); c.signal(SIG_CTX + 1); }
    }
    if (ks == (c.wg ? OC_S1 : OC_S0)) break;
    out_step<false, true>(c, o, ks == 1);
  }
  if (MASK & PH_CONV) {
    const int r = c.lane >> 2, q = c.lane & 3, tid = c.warp * 32 + c.lane, u = 2 * c.wg;
    const uint32_t ub = c.addr(u), part = ub + OC_PART + 32;
    const uint32_t wq = part + (c.warp * 8 + r) * OC_ROW + q * 8, rq = part + tid * 4;
    int ch = conv_channel<MASK>(cta, 3 * c.wg);
#pragma unroll 1
    for (int i = 0; ch >= 0; i++) {
      conv_round<true>(c, o, u + (i >> 8), ub, wq, rq, ch);
      ch = i + c.wg < 2 ? ch + 1 : -1;
      if (c.wg > i) { mbar_wait(c.base + SM_RDY + 8 * RDY_T, 0); ch = __shfl_sync(~0u, lds32(c.base + SM_POOL), 0); }
      if (ch < 0) { c.signal(SIG_Z); c.sync(); c.release2(u + 1);  }
      const int end = ch < 0 ? 57 : ks + (c.wg ? OC_L1 : OC_L0);
#pragma unroll 1
      for (ks += 14; ks < end; ks++) out_step<false, true>(c, o);
    }
    if (c.wg) c.skip(0);
  }
  if (!(MASK & PH_CONV)) {
#pragma unroll 1
    for (; ks < 57; ks++) out_step<false, true>(c, o);
  }
  uint32_t ga[32];
  c.wait(3);
  const float g0 = __uint_as_float(lds32(c.base + SM_GATE + 4 * (c.wg * 64 + c.warp * 16 + (c.lane >> 2)))), g1 = __uint_as_float(lds32(c.base + SM_GATE + 32 + 4 * (c.wg * 64 + c.warp * 16 + (c.lane >> 2))));
  const uint32_t gg0 = pack_bf16(g0, g0), gg1 = pack_bf16(g1, g1);
  const uint32_t og0 = pack_bf16(1.f - g0, 1.f - g0), og1 = pack_bf16(1.f - g1, 1.f - g1);
  const int xr = c.wg * 64 + c.warp * 16 + (c.lane & 15);
  const uint32_t xa = c.addr(2) + xr * 128, xs = xr & 7, xh = c.lane >> 4;
  const int zr = (c.lane & 7) + ((c.lane >> 4) << 3);
  const uint32_t za = c.addr(0) + c.wg * 16384 + zr * 128 + (((c.warp * 2 + ((c.lane >> 3) & 1)) ^ (zr & 7)) << 4);
#pragma unroll
  for (int i = 0; i < 8; i++) {
    if (i == 0) out_step<false, true>(c, o);
    if (i == 3) out_step<false, true>(c, o);
    if (i == 6) out_step<false, true>(c, o);
    ldsm4(xa + (i >> 2) * 16384 + ((((i & 3) * 2 + xh) ^ xs) << 4), ga[4 * i], ga[4 * i + 1], ga[4 * i + 2], ga[4 * i + 3]);
  }
#pragma unroll 1
  for (ks = 60; ks < 64; ks++) out_step<false, false>(c, o);
  c.wait(0);
  SHADOW {
#pragma unroll
    for (int i = 0; i < 8; i++) {
      uint32_t z0, z1, z2, z3;
      ldsm4t(za + i * 2048, z0, z1, z2, z3);
      ga[4 * i + 0] = hmul2(ga[4 * i + 0], z0); ga[4 * i + 1] = hmul2(ga[4 * i + 1], z1); ga[4 * i + 2] = hmul2(ga[4 * i + 2], z2); ga[4 * i + 3] = hmul2(ga[4 * i + 3], z3);
      ga[4 * i + 0] = hmul2(gg0, ga[4 * i + 0]); ga[4 * i + 1] = hmul2(gg1, ga[4 * i + 1]); ga[4 * i + 2] = hmul2(gg0, ga[4 * i + 2]); ga[4 * i + 3] = hmul2(gg1, ga[4 * i + 3]);
    }
  }
  c.signal(SIG_DONE);
  fence_regs(ga);
  wg_wait<0>(); fence_regs(o.acc);
#pragma unroll
  for (int i = 0; i < 8; i++) {
    const uint32_t r0 = mix(og0, pack_bf16(o.acc[8 * i + 0], o.acc[8 * i + 1]), ga[4 * i + 0]);
    const uint32_t r1 = mix(og1, pack_bf16(o.acc[8 * i + 2], o.acc[8 * i + 3]), ga[4 * i + 1]);
    const uint32_t r2 = mix(og0, pack_bf16(o.acc[8 * i + 4], o.acc[8 * i + 5]), ga[4 * i + 2]);
    const uint32_t r3 = mix(og1, pack_bf16(o.acc[8 * i + 6], o.acc[8 * i + 7]), ga[4 * i + 3]);
    stsm4(xa + (i >> 2) * 16384 + ((((i & 3) * 2 + xh) ^ xs) << 4), r0, r1, r2, r3);
    if ((i & 3) == 3) {
      __syncwarp();
#pragma unroll
      for (int k = 0; k < 4; k++) {
        const int rr = c.wg * 64 + c.warp * 16 + k * 4 + (c.lane >> 3);
        const uint4 v = lds128(c.addr(2 + (i >> 2)) + rr * 128 + (((c.lane ^ rr) & 7) << 4));
        *(uint4*)(P.out + (uint32_t)((mb * 128 + rr) * 1024 + nb * 128 + (i >> 2) * 64 + (c.lane & 7) * 8)) = v;
      }
    }
  }
}

__device__ __forceinline__ void load_conv(Prod& p, const Maps& M, int u, int ch) {
  if (elect()) {
    mbar_expect(p.full(u), 5120 + UCH);
    tma3d(p.addr(u), &M.h, 0, -8, ch, p.full(u), true);
    bulk_g2s(p.addr(u) + CV_U, g_u + (size_t)ch * UCH, UCH, p.full(u), true);
  }
}
template<int MASK> __device__ __forceinline__ void prod_conv(Prod& p, const Maps& M, int cta, int nch) {
  int ready = -1;
#pragma unroll 1
  for (int i = 0; i < nch; i++) {
    const int ch = conv_channel<MASK>(cta, i);
    const int u = i & 3;
    if ((ch >> 6) != ready) { ready = ch >> 6; if (cta < NREG) mbar_wait(p.base + SM_RDY + 8 * RDY_U, 0); else cnt_wait(g_cnt + (C_U + ready) * CSTRIDE, 128); }
    p.acquire(u, 1);
    load_conv(p, M, u, ch);
    if (i == 3) { p.acquire(4, 4); if (elect()) mbar_arrive(p.full(4)); }
  }
}
#define HOIST(v) asm volatile("" : "+r"(v))
template<int MASK> __device__ __forceinline__ void producer(const Maps& M, const Params& P, uint32_t base, int cta, int lane) {
  Prod p{base, ((MASK & PH_KV) && cta < NREG) ? 0xffffcfffu ^ ((1u << (3 * NFIRST)) - 1) : 0xffffffffu, lane};
  if (cta >= NREG) { if (MASK & PH_CONV) prod_conv<MASK>(p, M, cta, CV_EXTRA<MASK>); return; }
  const int g = cta & 7, j = cta >> 3, rank = cta & 1;
#pragma unroll 1
  for (int half = 0; half < 2; half++) {
    const int h = j + 16 * half;
    if (MASK & PH_KV) {
      const CUtensorMap* mw = rank ? &M.wv : &M.wk;
#pragma unroll 1
      for (int it = half ? 0 : NFIRST; it < 16; it++) {
        const int u = gemm_unit(it);
        const bool early = MASK == PH_ALL && it == 0;
        uint32_t bar = p.full(u), d0 = p.addr(early ? 12 : u), d1 = p.addr(u + !early + rank); int k0 = (it & 7) * 64, r0 = (2 * g + (it >> 3)) * 128;
        HOIST(bar); HOIST(d0); HOIST(d1); HOIST(k0); HOIST(r0);
        p.acquire(u, 3 - early);
        if (elect()) {
          mbar_expect(bar, 3 * UNIT);
          tma3d_mc(d1, mw, 0, k0, 2 * h, bar, it >= 8);
          tma2d(d0, &M.c, k0, r0, bar);
        }
      }
    }
    if (MASK & PH_ATT) {
#pragma unroll 1
      for (int ks = 0; ks < 16; ks++) {
        const int u = gemm_unit(ks);
        uint32_t bar = p.full(u), d0 = p.addr(u), d1 = p.addr(u + 1), d2 = p.addr(u + 2) + rank * 8192; int k0 = ks * 64;
        HOIST(bar); HOIST(d0); HOIST(d1); HOIST(d2); HOIST(k0);
        p.acquire(u, 3);
        if (elect()) {
          mbar_expect(bar, 3 * UNIT);
          tma2d_mc(d2, &M.wq, h * 128 + rank * 64, k0, bar, true);
          tma2d(d0, &M.x, k0, (15 - g) * 128, bar);
          tma2d(d1, &M.x, k0, g * 128, bar);
        }
      }
      mbar_wait(base + SM_RDY + 8 * (RDY_KV + half), 0);
      const uint8_t* KVh = g_T + T_KV + (size_t)kv_slot<MASK>(h) * 16 * 65536;
      if (MASK & PH_PRE) mbar_wait(base + SM_RDY + 8 * RDY_AUX, 0);
      if (elect()) { mbar_expect(p.full(12), 32768); bulk_g2s(p.addr(12), KVh, 32768, p.full(12)); }
      p.acquire(0, 4);
      if (elect()) mbar_arrive(p.full(0));
#pragma unroll 1
      for (int i = 1; i < 34; i++) {
        const int isv = !(i & 1) || i == 33, st = i == 33 ? 16 : (isv ? (i >> 1) - 1 : (i + 1) >> 1), u = 4 + 2 * (i & 3);
        const bool own = st == 15 - (g & 6);
        uint32_t bar = p.full(u), d0 = p.addr(own ? u : u + rank), off = (st <= 15 - g ? st : 16 - st) * 65536 + isv * 32768 + (own ? 0 : rank * UNIT);
        HOIST(bar); HOIST(d0); HOIST(off);
        p.acquire(u, 2);
        if (elect()) {
          mbar_expect(bar, 32768);
          const bool last = st >= 8;
          if (own) bulk_g2s(d0, KVh + off, 32768, bar, last); else bulk_g2s_mc(d0, KVh + off, UNIT, bar, last);
        }
      }
    }
  }
  if ((MASK & PH_CONV) && !(MASK & PH_OUT)) prod_conv<MASK>(p, M, cta, CV_REG<MASK>);
  if (MASK & PH_OUT) {
    const int y0 = out_mb(cta) * 512 + rank * 8, z0 = 2 * out_nb(cta);
    int u = 6;
#pragma unroll 1
    for (int hf = 0; hf < 2; hf++) {
      mbar_wait(base + SM_RDY + 8 * (RDY_CTX + hf), 0);
#pragma unroll 1
      for (int n = hf * 32; n < hf * 32 + 32; n++) {
        const int ks = n == 1 ? 2 : n == 2 ? 1 : n;
        u = n == 2 ? 2 : n == 3 ? 10 : out_next(u);
        uint32_t bar = p.full(u), d0 = p.addr(u) + rank * 8192, d1 = p.addr(u + 1); int x = (ks & 1) * 256, y = y0 + (ks >> 1) * 16, k0 = ks * 64;
        HOIST(bar); HOIST(d0); HOIST(d1); HOIST(x); HOIST(y); HOIST(k0);
        p.acquire(u, 2);
        if (elect()) {
          mbar_expect(bar, 2 * UNIT);
          tma2d_mc(d0, &M.ctx, x, y, bar, true);
          tma3d(d1, &M.wo, 0, k0, z0, bar, true);
          if (ks == 1 || ks == TK) mbar_arrive(base + SM_RDY + 8 * (ks == 1 ? RDY_X : RDY_DRAW));
          if (ks == Z_AT) mbar_arrive(base + SM_RDY + 8 * RDY_Z);
        }
      }
    }
  }
}
template<int MASK> __device__ __forceinline__ void producer2(const Maps& M, const Params& P, uint32_t base, int cta, int w, int lane) {
  Prod p{base, 0xffffffffu, lane};
  const int mb = out_mb(cta), nb = out_nb(cta), u = 2 * w;
  if (w) { mbar_wait_slow(base + SM_RDY + 8 * RDY_X, 0); p.mask ^= MASK == PH_ALL ? 8 : 12; }
  if (MASK & PH_CONV) {
    mbar_wait_slow(base + SM_SIG + 8 * (SIG_ATT + 1), 0);
    mbar_wait_slow(base + SM_RDY + 8 * RDY_U, 0);
#pragma unroll 1
    for (int i = 0, ch = conv_channel<MASK>(cta, 3 * w); ch >= 0; i++) {
      p.acquire_slow(u, i ? 1 : 2);
      load_conv(p, M, u, ch);
      ch = i + w < 2 ? ch + 1 : -1;
      if (w > i) { mbar_wait_slow(base + SM_RDY + 8 * RDY_T, 0); ch = lds32(base + SM_POOL); }
    }
  }
  p.acquire_slow(u, 2);
  if (!w && elect()) map_pf(&M.z);
  mbar_wait(base + SM_RDY + 8 * (!w ? RDY_Z : RDY_G), 0);
  if (elect()) {
    const uint32_t bar = p.full(3 * w);
    mbar_expect(bar, 2 * UNIT + (!w ? 0 : 512));
    tma2d(p.addr(u), !w ? &M.z : &M.x, (!w ? mb : nb) * 128, (!w ? nb : mb) * 128, bar, true);
    tma2d(p.addr(u + 1), !w ? &M.z : &M.x, (!w ? mb : nb) * 128 + 64, (!w ? nb : mb) * 128, bar, true);
    if (w) bulk_g2s(base + SM_GATE, g_gate + mb * 128, 512, bar);
  }
}

__device__ __forceinline__ constexpr uint32_t PUB(int sig, int cnt, int n) { return 0x80000000u | (sig << 24) | (n << 8) | cnt; }
__device__ __forceinline__ constexpr uint32_t GET(int rdy, int cnt, int n) { return (rdy << 24) | (n << 8) | cnt; }
template<int MASK> __device__ __forceinline__ void sync_agent(uint32_t base, int cta, int lane) {
  if ((base & 0x3FFFF) != SMEM_BASE) asm volatile("trap;");
  const int g = cta & 7, j = cta >> 3, go = min(out_mb(cta), 15 - out_mb(cta));
  const int c0 = conv_channel<MASK>(cta, 0), c1 = c0 + CV_REG<MASK> - 1, n0 = min(CV_REG<MASK>, 128 - (c0 & 127));
  constexpr bool KV = MASK & PH_KV, ATT = MASK & PH_ATT, CONV = MASK & PH_CONV, OUT = MASK & PH_OUT, ALL = MASK == PH_ALL;
  uint32_t e = 0;
  if (cta >= NREG) { if (CONV && lane * 32 < CV_EXTRA<MASK>) e = PUB(SIG_Z + lane, C_Z + lane, min(32, CV_EXTRA<MASK> - lane * 32)); }
  else switch (lane) {
    case 0:  if (KV) e = PUB(SIG_KV, C_KV + j, 1); break;
    case 1:  if (ATT) e = GET(RDY_KV, C_KV + j, 8); break;
    case 2:  if (ALL) e = PUB(SIG_WAR, C_WAR + j, 1); break;
    case 3:  if (ATT) e = PUB(SIG_CTX, C_CTX + g, 1); break;
    case 4:  if (ALL) e = GET(RDY_WAR, C_WAR + j, 8); break;
    case 5:  if (KV) e = PUB(SIG_KV + 1, C_KV + 16 + j, 1); break;
    case 6:  if (ATT) e = GET(RDY_KV + 1, C_KV + 16 + j, 8); break;
    case 7:  if (OUT) e = GET(RDY_CTX, C_CTX + go, 16); break;
    case 8:  if (CONV) e = GET(RDY_U, C_U + (c0 >> 6), 128); break;
    case 9:  if (CONV) e = GET(ALL ? RDY_DRAW : RDY_U, C_U + (ALL ? 14 : c1 >> 6), 128); break;
    case 10: if (ALL) e = GET(RDY_T, C_U + 15, 128); break;
    case 11: if (OUT) e = GET(RDY_G, C_GATE, 256); break;
    case 12: if (ATT) e = PUB(SIG_CTX + 1, C_CTX + 8 + g, 1); break;
    case 13: if (OUT) e = GET(RDY_CTX + 1, C_CTX + 8 + go, 16); break;
    case 14: if (CONV) e = PUB(SIG_Z, C_Z + (c0 >> 7), n0); break;
    case 15: if (ALL) e = PUB(SIG_Z, C_Z + 7, 1); else if (CONV && n0 < CV_REG<MASK>) e = PUB(SIG_Z, C_Z + (c1 >> 7), CV_REG<MASK> - n0); break;
    case 16: if (OUT) e = GET(RDY_Z, C_Z + out_nb(cta), 128); break;
  }
  if (ALL && lane == 0) { mbar_expect(base + SM_RDY + 8 * RDY_T, 4); mbar_arrive(base + SM_RDY + 8 * RDY_U); }
  __syncwarp();
#pragma unroll 1
  for (int i = 0; i < 17; i++) {
    const uint32_t x = __shfl_sync(~0u, e, i), id = (x >> 24) & 127, n = (x >> 8) & 0xffff;
    if (x == 0) continue;
    unsigned* cnt = g_cnt + (x & 255) * CSTRIDE;
    if (ALL && i == 14 && !(cta & 1)) {
      mbar_wait_slow<64>(base + SM_RDY + 8 * RDY_DRAW, 0);
      unsigned t = 0;
      if (lane == 0) asm volatile("atom.relaxed.gpu.global.add.u32 %0, [%1], 1;" : "=r"(t) : "l"(g_cnt + C_TICKET * CSTRIDE) : "memory");
      t = __shfl_sync(~0u, t, 0);
      uint32_t peer;
      asm volatile("mapa.shared::cluster.u32 %0, %1, %2;" : "=r"(peer) : "r"(base), "r"(lane & 1));
      if (lane < 2) asm volatile("st.async.weak.shared::cluster.mbarrier::complete_tx::bytes.u32 [%0], %1, [%2];"
        :: "r"(peer + SM_POOL), "r"(t < 64 - NSKIP ? CV_POOL + 2 * t + lane : ~0u), "r"(peer + SM_RDY + 8 * RDY_T) : "memory");
    }
    if (x >> 31) {
      mbar_wait_slow(base + SM_SIG + 8 * id, 0);
      if (lane == 0 && !(ALL && i == 15 && (int)lds32(base + SM_POOL) < 0)) cnt_publish(cnt, n, i != 15);
    } else {
      cnt_wait(cnt, n);
      if (id < 2) {
        const float4 kn = __ldcg((const float4*)(g_kn2 + kv_slot<MASK>(j + 16 * id) * 128) + lane);
        const uint32_t m = __reduce_max_sync(~0u, max(max(__float_as_uint(kn.x), __float_as_uint(kn.y)), max(__float_as_uint(kn.z), __float_as_uint(kn.w))));
        if (lane == 0) asm volatile("st.shared.u32 [%0], %1;" :: "r"(base + SM_KMAX + 4 * id), "r"(m) : "memory");
      }
      if (lane == 0) mbar_arrive(base + SM_RDY + 8 * id);
    }
    __syncwarp();
  }
}

__device__ __forceinline__ void aux_gate(const Params& P, int cta, int aw, int lane) {
  uint4 gw[4];
#pragma unroll
  for (int i = 0; i < 4; i++) gw[i] = __ldg((const uint4*)P.gw + i * 32 + lane);
#pragma unroll 1
  for (int row = cta * 16 + aw * 8; row < cta * 16 + aw * 8 + 8; row++) {
    float a = 0.f;
#pragma unroll
    for (int i = 0; i < 4; i++) {
      const uint4 xv = __ldg((const uint4*)(P.x + (size_t)row * 1024) + i * 32 + lane);
      uint32_t m;
      m = hmul2(xv.x, gw[i].x); a += bf_lo(m) + bf_hi(m); m = hmul2(xv.y, gw[i].y); a += bf_lo(m) + bf_hi(m);
      m = hmul2(xv.z, gw[i].z); a += bf_lo(m) + bf_hi(m); m = hmul2(xv.w, gw[i].w); a += bf_lo(m) + bf_hi(m);
    }
#pragma unroll
    for (int o = 16; o > 0; o >>= 1) a += __shfl_xor_sync(~0u, a, o);
    a = bf_lo(pack_bf16(a, 0.f));
    const float gt = bf_lo(pack_bf16(__fdividef(1.f, 1.f + ex2(-a * 1.4426950408889634f)), 0.f));
    if (lane == 0) g_gate[row] = gt;
    __nanosleep(GATE_SLEEP);
  }
  cnt_signal(g_cnt + C_GATE * CSTRIDE, lane);
}
__device__ __forceinline__ void pf64(const void* p) { asm volatile("prefetch.global.L2 [%0];" :: "l"(p) : "memory"); }
__device__ __forceinline__ void aux_pf(const Params& P, int cta, int aw, int lane) {
  for (int i = 0; i < PF_WAIT; i++) __nanosleep(1000);
#pragma unroll 1
  for (int i = 0; i < 8; i++) {
    pf64((const uint8_t*)(aw ? P.wv : P.wk) + ((16 + (cta >> 3)) * 256 + (lane & 3) * 64 + (i * 64 + (cta & 7) * 8 + (lane >> 2)) * 8192));
    if ((i & 3) == 0) pf64((const uint8_t*)P.c + (((cta & 7) * 256 + (cta >> 3) * 8 + aw * 4 + (lane >> 3)) * 1024 + (i >> 2) * 512 + (lane & 7) * 64));
    __nanosleep(PF_GAP);
  }
}
template<int MASK> __device__ __forceinline__ void aux_pre(const Maps& M, const Params& P, uint32_t base, int cta, int aw, int lane) {
  const uint32_t kb = base + 12 * UNIT, bar = base + SM_PRE;
  const int r = lane >> 2, q = lane & 3;
  const int mi = lane >> 3, row0 = (lane & 6) + 1 - (lane & 1);
  const int ra = (mi * 9 + 1) * 2 + row0;
  const int rb = (mi == 0 ? 3 : mi) * 18 + row0;
#pragma unroll 1
  for (int it = 0; it < (cta < 96 ? 5 : 4); it++) {
    if (it == PRE_EARLY && MASK == PH_ALL) { mbar_wait_slow(base + SM_SIG + 8 * SIG_ATT, 0); aux_gate(P, cta, aw, lane); aux_pf(P, cta, aw, lane); }
    if (it == PRE_EARLY && MASK == PH_ALL) mbar_wait_slow(base + SM_SIG + 8 * (SIG_ATT + 1), 0);
    const int cg = it ? it * 4 - 3 + (cta >> 5) : 0, tb = cta & 31;
    if (aw == 0 && elect()) {
      mbar_expect(bar, 2 * 9216);
      tma4d(kb, &M.k, cg * 64, 0, tb * 8 - 1, 0, bar, true);
      tma4d(kb + 9216, &M.v, cg * 64, 0, tb * 8 - 1, 0, bar, true);
    }
    const uint2 swl = __ldg((const uint2*)(P.shift + (cg * 64 + aw * 32 + lane) * 4));
    if (tb == 0) {
      uint8_t* e = g_u + (size_t)(cg * 64 + aw * 32 + lane) * UCH + 4096;
      *(uint4*)e = make_uint4(0, 0, 0, 0); *(uint4*)(e + UPITCH) = make_uint4(0, 0, 0, 0);
      *(uint32_t*)(e + 32) = (uint32_t)__bfloat16_as_ushort(P.D[cg * 64 + aw * 32 + lane]) * 0x10001u;
    }
    if (it == 0) mbar_wait(bar, 0); else mbar_wait_slow(bar, it & 1);
#pragma unroll 1
    for (int ol = it ? 0 : cta >> 5; ol < (it ? 4 : (cta >> 5) + 1); ol++) {
      const int oc = aw * 4 + ol;
      const uint32_t s01 = __shfl_sync(~0u, swl.x, ol * 8 + r), s23 = __shfl_sync(~0u, swl.y, ol * 8 + r);
      const uint32_t w0 = __byte_perm(s01, 0, 0x1010), w1 = __byte_perm(s01, 0, 0x3232), w2 = __byte_perm(s23, 0, 0x1010), w3 = __byte_perm(s23, 0, 0x3232);
      const uint32_t pa = kb + ra * 128 + ((oc ^ (ra & 7)) << 4), pb = kb + (mi == 0 ? 9216 : 0) + rb * 128 + ((oc ^ (rb & 7)) << 4);
      uint8_t* e0 = g_u + (uint32_t)((cg * 64 + oc * 8 + r) * UCH + (2040 - tb * 64 - 8 * q) * 2);
#pragma unroll
      for (int hb = 0; hb < 2; hb++) {
        uint32_t k[7], v[5];
        ldsm4t(pa + hb * 1024, k[3], k[4], k[5], k[6]);
        ldsm4t(pa + hb * 1024 + 9216, v[1], v[2], v[3], v[4]);
        ldsm4t(pb + hb * 1024, v[0], k[0], k[1], k[2]);
        uint32_t o1 = __byte_perm(k[1], k[0], 0x5432);
#pragma unroll
        for (int m = 0; m < 5; m++) {
          const uint32_t o2 = __byte_perm(k[m + 2], k[m + 1], 0x5432);
          v[m] = hmul2(hadd2(hadd2(hadd2(hmul2(o1, w3), hmul2(k[m + 1], w2)), hmul2(o2, w1)), hmul2(k[m + 2], w0)), v[m]);
          o1 = o2;
        }
        *(uint4*)(e0 - hb * 64) = make_uint4(v[4], v[3], v[2], v[1]);
        *(uint4*)(e0 - hb * 64 + UPITCH) = make_uint4(__byte_perm(v[4], v[3], 0x5432), __byte_perm(v[3], v[2], 0x5432), __byte_perm(v[2], v[1], 0x5432), __byte_perm(v[1], v[0], 0x5432));
        if (it >= PRE_EARLY) __nanosleep(PRE_SLEEP);
      }
    }
    bar_sync(5, 64);
    if (it == PRE_EARLY - 1 && aw == 0 && lane == 0) mbar_arrive(base + SM_RDY + 8 * RDY_AUX);
    if (aw == 1 && lane == 0) asm volatile("red.release.gpu.global.add.u32 [%0], %1;" :: "l"(g_cnt + (C_U + cg) * CSTRIDE), "r"(it ? 4 : 1) : "memory");
    if (it == 0) bar_sync(5, 64);
  }
  uint32_t rel;
  asm volatile("mapa.shared::cluster.u32 %0, %1, %2;" : "=r"(rel) : "r"(base + SM_BAR + 128 + 8 * (12 + (lane & 1))), "r"((lane >> 1) & 1));
  if (lane < 4) asm volatile("mbarrier.arrive.shared::cluster.b64 _, [%0];" :: "r"(rel) : "memory");
  if (MASK != PH_ALL) aux_gate(P, cta, aw, lane);
}

template<int MASK> __global__ void __cluster_dims__(2, 1, 1) __launch_bounds__(384, 1) gated_mix_kernel(const __grid_constant__ Maps M, const __grid_constant__ Params P) {
  extern __shared__ __align__(1024) uint8_t smem[];
  const uint32_t base = (uint32_t)__cvta_generic_to_shared(smem);
  if ((MASK & PH_KV) && elect()) {
    map_pf(&M.wk + (blockIdx.x & 1)); map_pf(&M.c);
  }
  const int wi = __shfl_sync(~0u, threadIdx.x >> 5, 0), wg = wi >> 2, warp = wi & 3;
  if (elect()) {
    if (wi < 8) {
      const int cnt = 1 << ((0x10332200 >> (4 * wi)) & 15);
#pragma unroll
      for (int i = 0; i < 8; i++) mbar_init(base + SM_BAR + 64 * wi + 8 * i, cnt);
      asm volatile("fence.mbarrier_init.release.cluster;" ::: "memory");
    }
  }
  const int cta = blockIdx.x;
  const bool first_loads = (MASK & PH_KV) && wi == 8 && cta < NREG;
  const CUtensorMap* mw = (cta & 1) ? &M.wv : &M.wk;
  __syncwarp();
  asm volatile("barrier.cluster.arrive.relaxed.aligned;\nbarrier.cluster.wait.aligned;" ::: "memory");
  auto first_stage = [&](int it) {
    const uint32_t bar = base + SM_BAR + 24 * it, d0 = base + 3 * it * UNIT;
    mbar_expect(bar, 3 * UNIT);
    tma3d_mc(d0 + (1 + (cta & 1)) * UNIT, mw, 0, it * 64, 2 * (cta >> 3), bar);
    tma2d(d0, &M.c, it * 64, (cta & 7) * 256, bar);
  };
  if (first_loads && elect()) first_stage(0);
  __syncwarp();
  const int lane = threadIdx.x & 31;
  if (wg == 2) {
    asm volatile("setmaxnreg.dec.sync.aligned.u32 56;");
    if (warp == 0) producer<MASK>(M, P, base, cta, lane);
    else if (warp == 1) sync_agent<MASK>(base, cta, lane);
    else if (cta < NREG) {
      if (MASK & PH_PRE) aux_pre<MASK>(M, P, base, cta, warp - 2, lane);
      if (MASK & PH_OUT) producer2<MASK>(M, P, base, cta, warp - 2, lane);
    }
    if (warp == 1) {
      if (MASK & PH_OUT) {
        unsigned old = 0;
        if (lane == 0) asm volatile("atom.relaxed.gpu.global.add.u32 %0, [%1], 1;" : "=r"(old) : "l"(g_cnt + C_EXIT * CSTRIDE) : "memory");
        old = __shfl_sync(~0u, old, 0);
        if (old == NCTA - 1) for (int i = lane; i < C_NUM; i += 32) g_cnt[i * CSTRIDE] = 0;
      }
      mbar_wait_slow(base + SM_SIG + 8 * SIG_DONE, 0);
      if (cta >= NREG || !(MASK & PH_OUT)) { cluster_arrive(); cluster_wait(); }
    }
  } else {
    asm volatile("setmaxnreg.inc.sync.aligned.u32 224;");
    uint32_t rel;
    asm volatile("mapa.shared::cluster.u32 %0, %1, %2;" : "=r"(rel) : "r"(base + SM_BAR + 128 + 8 * (lane & 15)), "r"(lane >> 4));
    Cons c{base, rel, 0u, lane, warp, wg, warp == 3 ? lane & 15 : 16};
    if (wg == 1) bar_arrive(1, 256);
    if ((MASK & PH_KV) && wi == 4 && cta < NREG) {
      if (elect()) {
#pragma unroll 1
        for (int it = 1; it < NFIRST; it++) {
          asm volatile("{\n.reg .pred p;\n.reg .u32 a, b;\nmov.u32 a, %%clock;\nXL:\nmov.u32 b, %%clock;\nsub.u32 b, b, a;\nsetp.lt.u32 p, b, %0;\n@p bra XL;\n}\n" :: "r"(it == 1 ? FGAP : FGAP2) : "memory");
          first_stage(it);
        }
      }
      __syncwarp();
    }
    if (cta < NREG) {
      const int g = cta & 7, j = cta >> 3;
      Pend w = {};
#pragma unroll 1
      for (int half = 0; half < 2; half++) {
        const int h = j + 16 * half, blk = kv_slot<MASK>(h) * 16 + 2 * g;
        if (MASK & PH_KV) cons_kv<(MASK & PH_ATT) != 0>(c, h, blk, g, w, half == 1 && (MASK & PH_ATT));
        if (MASK & PH_ATT) {
          Att a;
          cons_q<(MASK & PH_KV) != 0>(c, h, blk + 1, w, a.o, a.kn);
          cons_att(c, a, h, g, w);
          if (half == 0) c.signal(SIG_WAR);
          if (MASK != PH_ALL) { tile_store<0, 4>(w.lo, ctx_off(c, h, g, 1 - wg), lane); c.signal(SIG_CTX + half); }
        } else if (MASK & PH_KV) {
          float kn = 0.f;
          out_piece<SCH_KV, true>(c, w, kv_off(c, blk + 1), blk + 1, kn, 0, true);
          for (int ks = 1; ks < 8; ks++) out_piece<SCH_KV, false>(c, w, kv_off(c, blk + 1), blk + 1, kn, ks, true);
          c.signal(SIG_KV + half);
        }
      }
      if (MASK & PH_OUT) cons_out<MASK>(c, M, P, cta, w);
    }
    if (cta >= NREG || !(MASK & PH_OUT)) {
      if (MASK & PH_CONV) cons_conv<MASK>(c, cta, cta < NREG ? CV_REG<MASK> : CV_EXTRA<MASK>);
      c.signal(SIG_DONE);
      cluster_arrive();
    }
  }
}

typedef CUresult (*EncFn)(CUtensorMap*, CUtensorMapDataType, cuuint32_t, void*, const cuuint64_t*, const cuuint64_t*, const cuuint32_t*, const cuuint32_t*,
                          CUtensorMapInterleave, CUtensorMapSwizzle, CUtensorMapL2promotion, CUtensorMapFloatOOBfill);
static void enc(EncFn f, CUtensorMap* m, const void* ptr, int rank, const cuuint64_t* dims, const cuuint64_t* strides, const cuuint32_t* box, CUtensorMapSwizzle sw,
                CUtensorMapDataType dt = CU_TENSOR_MAP_DATA_TYPE_BFLOAT16) {
  const cuuint32_t es[4] = {1, 1, 1, 1};
  f(m, dt, rank, (void*)ptr, dims, strides, box, es, CU_TENSOR_MAP_INTERLEAVE_NONE, sw, CU_TENSOR_MAP_L2_PROMOTION_L2_128B, CU_TENSOR_MAP_FLOAT_OOB_FILL_NONE);
}
static void enc2(EncFn f, CUtensorMap* m, const void* ptr, int cols, int rows, int brows) {
  const cuuint64_t d[2] = {(cuuint64_t)cols, (cuuint64_t)rows}, s[1] = {(cuuint64_t)cols * 2}; const cuuint32_t b[2] = {64, (cuuint32_t)brows};
  enc(f, m, ptr, 2, d, s, b, CU_TENSOR_MAP_SWIZZLE_128B);
}
static void encw(EncFn f, CUtensorMap* m, const void* ptr, int cols, int rows) {
  const cuuint64_t d[3] = {64, (cuuint64_t)rows, (cuuint64_t)cols / 64}, s[2] = {(cuuint64_t)cols * 2, 128}; const cuuint32_t b[3] = {64, 64, 2};
  enc(f, m, ptr, 3, d, s, b, CU_TENSOR_MAP_SWIZZLE_128B);
}
extern "C" void kernel_launch(void* const* d_in, const int* in_sizes, int n_in, void* d_out, int out_size) {
  static EncFn fn = nullptr;
  static int ncl = 0;
  static void* zptr = nullptr;
  static void* tptr = nullptr;
  if (!fn) {
    void* p = nullptr; cudaDriverEntryPointQueryResult qr;
    cudaGetDriverEntryPoint("cuTensorMapEncodeTiled", &p, cudaEnableDefault, &qr);
    fn = (EncFn)p;
    cudaFuncSetAttribute(gated_mix_kernel<PH_ALL>, cudaFuncAttributeMaxDynamicSharedMemorySize, SMEM_BYTES);
    cudaFuncSetAttribute(gated_mix_kernel<PH_PRE | PH_KV>, cudaFuncAttributeMaxDynamicSharedMemorySize, SMEM_BYTES);
    cudaFuncSetAttribute(gated_mix_kernel<PH_ATT | PH_CONV>, cudaFuncAttributeMaxDynamicSharedMemorySize, SMEM_BYTES);
    cudaFuncSetAttribute(gated_mix_kernel<PH_OUT>, cudaFuncAttributeMaxDynamicSharedMemorySize, SMEM_BYTES);
    cudaLaunchConfig_t cfg = {}; cfg.gridDim = NCTA; cfg.blockDim = 384; cfg.dynamicSmemBytes = SMEM_BYTES;
    cudaLaunchAttribute at; at.id = cudaLaunchAttributeClusterDimension; at.val.clusterDim.x = 2; at.val.clusterDim.y = 1; at.val.clusterDim.z = 1;
    cfg.attrs = &at; cfg.numAttrs = 1;
    cudaOccupancyMaxActiveClusters(&ncl, gated_mix_kernel<PH_ALL>, &cfg);
    cudaGetSymbolAddress(&zptr, g_u);
    cudaGetSymbolAddress(&tptr, g_T);
  }
  Maps M;
  enc2(fn, &M.x, d_in[0], 1024, 2048, 128);
  enc2(fn, &M.c, d_in[7], 512, 2048, 128);
  enc2(fn, &M.wq, d_in[8], 4096, 1024, 64);
  encw(fn, &M.wk, d_in[9], 4096, 512);
  encw(fn, &M.wv, d_in[10], 4096, 512);
  encw(fn, &M.wo, d_in[11], 1024, 4096);
  { const cuuint64_t d[3] = {64, 32, 1024}, s[2] = {128, 4096}; const cuuint32_t b[3] = {64, 40, 1}; enc(fn, &M.h, d_in[4], 3, d, s, b, CU_TENSOR_MAP_SWIZZLE_NONE); }
  { const cuuint64_t d[2] = {2048, 1024}, s[1] = {UCH}; const cuuint32_t b[2] = {64, 128}; enc(fn, &M.z, zptr, 2, d, s, b, CU_TENSOR_MAP_SWIZZLE_128B); }
  { const cuuint64_t d[2] = {512, 512 * 16}, s[1] = {2048}; const cuuint32_t b[2] = {256, 8};
    enc(fn, &M.ctx, tptr, 2, d, s, b, CU_TENSOR_MAP_SWIZZLE_NONE, CU_TENSOR_MAP_DATA_TYPE_UINT32); }
  { const cuuint64_t d[4] = {1024, 2, 256, 4}, s[3] = {2048, 16384, 4096}; const cuuint32_t b[4] = {64, 2, 9, 4};
    enc(fn, &M.k, d_in[1], 4, d, s, b, CU_TENSOR_MAP_SWIZZLE_128B); enc(fn, &M.v, d_in[2], 4, d, s, b, CU_TENSOR_MAP_SWIZZLE_128B); }
  Params P{(const __nv_bfloat16*)d_in[0], (const __nv_bfloat16*)d_in[3],
           (const __nv_bfloat16*)d_in[5], (const __nv_bfloat16*)d_in[12],
           (const __nv_bfloat16*)d_in[9], (const __nv_bfloat16*)d_in[10], (const __nv_bfloat16*)d_in[7], (__nv_bfloat16*)d_out};
  bool split = 2 * ncl < NCTA;
  if (!split) {
    gated_mix_kernel<PH_ALL><<<NCTA, 384, SMEM_BYTES>>>(M, P);
  } else {
    gated_mix_kernel<PH_PRE | PH_KV><<<NCTA, 384, SMEM_BYTES>>>(M, P);
    gated_mix_kernel<PH_ATT | PH_CONV><<<NCTA, 384, SMEM_BYTES>>>(M, P);
    gated_mix_kernel<PH_OUT><<<NCTA, 384, SMEM_BYTES>>>(M, P);
  }
}
```
